```python
import torch

def _softmax(x, axis=-1):
    return torch.softmax(x, dim=axis)

def _gelu(x):
    return torch.nn.functional.gelu(x, approximate='tanh')

def _silu(x):
    return torch.nn.functional.silu(x)

def _sigmoid(x):
    return torch.sigmoid(x)

def _layernorm(x, axis=-1, eps=1e-05):
    m = x.mean(dim=axis, keepdim=True)
    v = x.var(dim=axis, keepdim=True, unbiased=False)
    return (x - m) / torch.sqrt(v + eps)

def _scatter_add(tgt, idx, src, axis=0):
    return tgt.clone().index_add_(axis, idx, src)

def _segment_sum(src, seg, n):
    out = torch.zeros((n,) + src.shape[1:], dtype=src.dtype)
    return out.index_add_(0, seg, src)

def _pad(x, pw):
    flat = tuple((v for pair in reversed(pw) for v in pair))
    return torch.nn.functional.pad(x, flat)
kernel_name = 'standalone__conformer_family_zipformer__speech'

def setup_inputs():

    _w = lambda a: (lambda t: t.to(torch.bfloat16) if t.is_floating_point() else t)(torch.as_tensor(a))
    B, T, D, K, H = (2, 1000, 256, 15, 4)
    sc = 0.1
    return {'x': _w((lambda *s: torch.randn(*s, dtype=torch.bfloat16) * 0.8)(B, T, D)), 'w_ff1a': _w((lambda *s: torch.randn(*s, dtype=torch.bfloat16) * 0.8)(D, 4 * D) * sc), 'w_ff1b': _w((lambda *s: torch.randn(*s, dtype=torch.bfloat16) * 0.8)(4 * D, D) * sc), 'w_qkv': _w((lambda *s: torch.randn(*s, dtype=torch.bfloat16) * 0.8)(D, 3 * D) * sc), 'w_o': _w((lambda *s: torch.randn(*s, dtype=torch.bfloat16) * 1.6)(D, D) * sc), 'w_pw1': _w((lambda *s: torch.randn(*s, dtype=torch.bfloat16) * 1.6)(D, 2 * D) * sc), 'dw': _w((lambda *s: torch.randn(*s, dtype=torch.bfloat16) * 0.4)(K, D)), 'w_pw2': _w((lambda *s: torch.randn(*s, dtype=torch.bfloat16) * 0.4)(D, D) * sc), 'w_ff2a': _w((lambda *s: torch.randn(*s, dtype=torch.bfloat16) * 0.8)(D, 4 * D) * sc), 'w_ff2b': _w((lambda *s: torch.randn(*s, dtype=torch.bfloat16) * 0.8)(4 * D, D) * sc)}

def reference(x, w_ff1a, w_ff1b, w_qkv, w_o, w_pw1, dw, w_pw2, w_ff2a, w_ff2b):
    B, T, D = x.shape
    K = dw.shape[0]
    H = 4
    Dh = D // H
    h = _layernorm(x, axis=-1)
    h = _silu(h @ w_ff1a) @ w_ff1b
    x = x + 0.5 * h
    h = _layernorm(x, axis=-1)
    qkv = h @ w_qkv
    q = (lambda x, *d: x.permute(*d))(qkv[..., :D].reshape(B, T, H, Dh), 0, 2, 1, 3)
    k = (lambda x, *d: x.permute(*d))(qkv[..., D:2 * D].reshape(B, T, H, Dh), 0, 2, 1, 3)
    v = (lambda x, *d: x.permute(*d))(qkv[..., 2 * D:].reshape(B, T, H, Dh), 0, 2, 1, 3)
    scale = Dh ** (-0.5)
    scores = torch.einsum('bhqd,bhkd->bhqk', q, k) * scale
    p = _softmax(scores, axis=-1)
    att = torch.einsum('bhqk,bhkd->bhqd', p, v)
    att = (lambda x, *d: x.permute(*d))(att, 0, 2, 1, 3).reshape(B, T, D)
    x = x + att @ w_o
    h = _layernorm(x, axis=-1)
    h = h @ w_pw1
    a, b = (h[..., :D].clone(), h[..., D:].clone())
    h = a * _sigmoid(b)
    pad = K // 2
    hp = _pad(h, ((0, 0), (pad, pad), (0, 0)))
    c = torch.zeros_like(h)
    for i in range(K):
        c = c + hp[:, i:i + T, :] * dw[i][None, None, :]
    x = x + _silu(c) @ w_pw2
    h = _layernorm(x, axis=-1)
    h = _silu(h @ w_ff2a) @ w_ff2b
    x = x + 0.5 * h
    return _layernorm(x, axis=-1)
```

```cpp
#include <cuda_runtime.h>
#include <cuda_bf16.h>
#include <cuda.h>
#include <stdint.h>

namespace {

constexpr int T_ = 1000;
constexpr int NCTA = 128;
constexpr int NTHREADS = 384;
constexpr int NSLOT = 5;
constexpr int SLOT = 16384;
constexpr int NLOADS = 54;

constexpr uint32_t OFF_RING = 0;
constexpr uint32_t OFF_P = 163840;
constexpr uint32_t OFF_H = 188416;
constexpr uint32_t OFF_INBOX = 221184;
constexpr uint32_t OFF_STATS = 229376;
constexpr uint32_t OFF_BARS = 229888;
constexpr uint32_t SMEM_BYTES = 230400;
constexpr uint32_t XCH = 6144;
constexpr uint32_t HCH = 4096;

constexpr int B_FULL = 0, B_EMPTY = 10, B_XF = 20, B_HF = 28, B_INB = 32, B_QIN = 34, B_X1IN = 35, B_ATT = 36, NBARS = 37;

constexpr int PADROWS = 1040;
constexpr int FS = 8;

struct Params {
    CUtensorMap tm[9];
    const char* w[8];
    const __nv_bfloat16* dw;
    __nv_bfloat16* out;
};

__device__ __align__(1024) unsigned char g_q[8 * 1024 * 128];
__device__ __align__(1024) unsigned char g_k[8 * 1024 * 128];
__device__ __align__(1024) unsigned char g_v[8 * 1024 * 128];
__device__ __align__(1024) unsigned char g_o[8 * PADROWS * 128];
__device__ __align__(1024) unsigned char g_x1[8 * PADROWS * 128];
__device__ uint32_t g_flag_qk[8 * 32 * FS];
__device__ uint32_t g_flag_v[8 * 32 * FS];
__device__ uint32_t g_flag_o[2 * 16 * 4 * FS];
__device__ uint32_t g_epoch[NCTA * FS];

#define TS(i) do { } while (0)

__device__ __forceinline__ long long gtime() { return clock64(); }

__device__ __forceinline__ uint32_t smem_u32(const void* p) { return (uint32_t)__cvta_generic_to_shared(p); }
__device__ __forceinline__ void mbar_init(uint32_t b, uint32_t c) { asm volatile("mbarrier.init.shared::cta.b64 [%0], %1;" ::"r"(b), "r"(c) : "memory"); }
__device__ __forceinline__ void mbar_arrive(uint32_t b) { asm volatile("mbarrier.arrive.shared::cta.b64 _, [%0];" ::"r"(b) : "memory"); }
__device__ __forceinline__ void mbar_arrive_n(uint32_t b, uint32_t n) { asm volatile("mbarrier.arrive.shared::cta.b64 _, [%0], %1;" ::"r"(b), "r"(n) : "memory"); }
__device__ __forceinline__ void mbar_arrive_tx(uint32_t b, uint32_t tx) { asm volatile("mbarrier.arrive.expect_tx.shared::cta.b64 _, [%0], %1;" ::"r"(b), "r"(tx) : "memory"); }
__device__ __forceinline__ void mbar_expect_tx(uint32_t b, uint32_t tx) { asm volatile("mbarrier.expect_tx.relaxed.cta.shared::cta.b64 [%0], %1;" ::"r"(b), "r"(tx) : "memory"); }
__device__ __forceinline__ bool mbar_try(uint32_t b, uint32_t ph) {
    uint32_t ok;
    asm volatile("{.reg .pred p; mbarrier.try_wait.parity.acquire.cluster.shared::cta.b64 p, [%1], %2; selp.u32 %0, 1, 0, p;}" : "=r"(ok) : "r"(b), "r"(ph) : "memory");
    return ok;
}
__device__ __forceinline__ void mbar_wait(uint32_t b, uint32_t ph) {
    if (mbar_try(b, ph)) return;
    for (int i = 0; i < (1 << 20); i++)
        if (mbar_try(b, ph)) return;
    __trap();
}
__device__ __forceinline__ uint32_t mapa(uint32_t a, uint32_t r) { uint32_t o; asm("mapa.shared::cluster.u32 %0, %1, %2;" : "=r"(o) : "r"(a), "r"(r)); return o; }
__device__ __forceinline__ void fence_async_smem() { asm volatile("fence.proxy.async.shared::cta;" ::: "memory"); }
__device__ __forceinline__ void fence_async_global() { asm volatile("fence.proxy.async.global;" ::: "memory"); }
__device__ __forceinline__ void bar_sync(int id, int n) { asm volatile("bar.sync %0, %1;" ::"r"(id), "r"(n) : "memory"); }
__device__ __forceinline__ void cluster_arrive() { asm volatile("barrier.cluster.arrive.aligned;" ::: "memory"); }
__device__ __forceinline__ void cluster_wait() { asm volatile("barrier.cluster.wait.aligned;" ::: "memory"); }

__device__ __forceinline__ void tma2d(uint32_t dst, const CUtensorMap* tm, int c0, int c1, uint32_t bar) {
    asm volatile("cp.async.bulk.tensor.2d.shared::cluster.global.mbarrier::complete_tx::bytes [%0], [%1, {%3, %4}], [%2];"
                 ::"r"(dst), "l"(tm), "r"(bar), "r"(c0), "r"(c1) : "memory");
}
__device__ __forceinline__ void tma3d(uint32_t dst, const CUtensorMap* tm, int c0, int c1, int c2, uint32_t bar) {
    asm volatile("cp.async.bulk.tensor.3d.shared::cluster.global.mbarrier::complete_tx::bytes [%0], [%1, {%3, %4, %5}], [%2];"
                 ::"r"(dst), "l"(tm), "r"(bar), "r"(c0), "r"(c1), "r"(c2) : "memory");
}
__device__ __forceinline__ void bulk_g2s(uint32_t dst, const void* src, uint32_t bytes, uint32_t bar) {
    asm volatile("cp.async.bulk.shared::cluster.global.mbarrier::complete_tx::bytes [%0], [%1], %2, [%3];" ::"r"(dst), "l"(src), "r"(bytes), "r"(bar) : "memory");
}
__device__ __forceinline__ void bulk_s2s(uint32_t dst, uint32_t src, uint32_t bytes, uint32_t bar) {
    asm volatile("cp.async.bulk.shared::cluster.shared::cta.mbarrier::complete_tx::bytes [%0], [%1], %2, [%3];" ::"r"(dst), "r"(src), "r"(bytes), "r"(bar) : "memory");
}
__device__ __forceinline__ void bulk_s2g(void* dst, uint32_t src, uint32_t bytes) {
    asm volatile("cp.async.bulk.global.shared::cta.bulk_group [%0], [%1], %2;" ::"l"(dst), "r"(src), "r"(bytes) : "memory");
    asm volatile("cp.async.bulk.commit_group;" ::: "memory");
}
__device__ __forceinline__ void st_async4(uint32_t dst, uint32_t a, uint32_t b, uint32_t c, uint32_t d, uint32_t bar) {
    asm volatile("st.async.shared::cluster.mbarrier::complete_tx::bytes.v4.b32 [%0], {%1,%2,%3,%4}, [%5];" ::"r"(dst), "r"(a), "r"(b), "r"(c), "r"(d), "r"(bar) : "memory");
}
__device__ __forceinline__ void stsm4t(uint32_t a, uint32_t r0, uint32_t r1, uint32_t r2, uint32_t r3) {
    asm volatile("stmatrix.sync.aligned.m8n8.x4.trans.shared.b16 [%0], {%1,%2,%3,%4};" ::"r"(a), "r"(r0), "r"(r1), "r"(r2), "r"(r3) : "memory");
}
__device__ __forceinline__ void stsm4(uint32_t a, uint32_t r0, uint32_t r1, uint32_t r2, uint32_t r3) {
    asm volatile("stmatrix.sync.aligned.m8n8.x4.shared.b16 [%0], {%1,%2,%3,%4};" ::"r"(a), "r"(r0), "r"(r1), "r"(r2), "r"(r3) : "memory");
}
__device__ __forceinline__ void ldsm4t(uint32_t a, uint32_t& r0, uint32_t& r1, uint32_t& r2, uint32_t& r3) {
    asm volatile("ldmatrix.sync.aligned.m8n8.x4.trans.shared.b16 {%0,%1,%2,%3}, [%4];" : "=r"(r0), "=r"(r1), "=r"(r2), "=r"(r3) : "r"(a) : "memory");
}
__device__ __forceinline__ uint4 lds128(uint32_t a) { uint4 v; asm volatile("ld.shared.v4.b32 {%0,%1,%2,%3}, [%4];" : "=r"(v.x), "=r"(v.y), "=r"(v.z), "=r"(v.w) : "r"(a) : "memory"); return v; }
__device__ __forceinline__ float4 lds128f(uint32_t a) { float4 v; asm volatile("ld.shared.v4.f32 {%0,%1,%2,%3}, [%4];" : "=f"(v.x), "=f"(v.y), "=f"(v.z), "=f"(v.w) : "r"(a) : "memory"); return v; }
__device__ __forceinline__ float2 lds64f(uint32_t a) { float2 v; asm volatile("ld.shared.v2.f32 {%0,%1}, [%2];" : "=f"(v.x), "=f"(v.y) : "r"(a) : "memory"); return v; }
__device__ __forceinline__ uint32_t lds32(uint32_t a) { uint32_t v; asm volatile("ld.shared.b32 %0, [%1];" : "=r"(v) : "r"(a) : "memory"); return v; }
__device__ __forceinline__ void sts128(uint32_t a, uint32_t x, uint32_t y, uint32_t z, uint32_t w) { asm volatile("st.shared.v4.b32 [%0], {%1,%2,%3,%4};" ::"r"(a), "r"(x), "r"(y), "r"(z), "r"(w) : "memory"); }
__device__ __forceinline__ void sts128f(uint32_t a, float x, float y, float z, float w) { asm volatile("st.shared.v4.f32 [%0], {%1,%2,%3,%4};" ::"r"(a), "f"(x), "f"(y), "f"(z), "f"(w) : "memory"); }
__device__ __forceinline__ void sts64f(uint32_t a, float x, float y) { asm volatile("st.shared.v2.f32 [%0], {%1,%2};" ::"r"(a), "f"(x), "f"(y) : "memory"); }
__device__ __forceinline__ void sts32(uint32_t a, uint32_t x) { asm volatile("st.shared.b32 [%0], %1;" ::"r"(a), "r"(x) : "memory"); }
__device__ __forceinline__ void stg128(void* p, uint4 v) { asm volatile("st.global.v4.b32 [%0], {%1,%2,%3,%4};" ::"l"(p), "r"(v.x), "r"(v.y), "r"(v.z), "r"(v.w) : "memory"); }

__device__ __forceinline__ uint32_t pack2(float lo, float hi) { uint32_t r; asm("cvt.rn.bf16x2.f32 %0, %1, %2;" : "=r"(r) : "f"(hi), "f"(lo)); return r; }
__device__ __forceinline__ float blo(uint32_t v) { return __uint_as_float(v << 16); }
__device__ __forceinline__ float bhi(uint32_t v) { return __uint_as_float(v & 0xffff0000u); }
__device__ __forceinline__ float tanh_fast(float x) { float r; asm("tanh.approx.f32 %0, %1;" : "=f"(r) : "f"(x)); return r; }
__device__ __forceinline__ float ex2(float x) { float r; asm("ex2.approx.ftz.f32 %0, %1;" : "=f"(r) : "f"(x)); return r; }

__device__ __forceinline__ void flag_wait(const uint32_t* p, uint32_t e) {
    for (int i = 0; i < (1 << 22); i++) {
        uint32_t v;
        asm volatile("ld.acquire.gpu.global.u32 %0, [%1];" : "=r"(v) : "l"(p) : "memory");
        if (v == e) return;
    }
    __trap();
}
__device__ __forceinline__ void flag_set(uint32_t* p, uint32_t e) { asm volatile("st.release.gpu.global.u32 [%0], %1;" ::"l"(p), "r"(e) : "memory"); }

__device__ __forceinline__ uint64_t mkdesc(uint32_t addr) { return (uint64_t)(((addr & 0x3FFFF) >> 4) | 0x10000u) | (0x40000040ull << 32); }
__device__ __forceinline__ void wg_fence() { asm volatile("wgmma.fence.sync.aligned;" ::: "memory"); }
__device__ __forceinline__ void wg_commit() { asm volatile("wgmma.commit_group.sync.aligned;" ::: "memory"); }
template <int N> __device__ __forceinline__ void wg_wait() { asm volatile("wgmma.wait_group.sync.aligned %0;" ::"n"(N) : "memory"); }
template <int N> __device__ __forceinline__ void pin(float (&d)[N]) {
#pragma unroll
    for (int i = 0; i < N; i++) asm volatile("" : "+f"(d[i])::"memory");
}
template <int N> __device__ __forceinline__ void pin(uint32_t (&d)[N]) {
#pragma unroll
    for (int i = 0; i < N; i++) asm volatile("" : "+r"(d[i])::"memory");
}

#define F4(d, i) "+f"(d[i]), "+f"(d[i + 1]), "+f"(d[i + 2]), "+f"(d[i + 3])
#define F16(d, i) F4(d, i), F4(d, i + 4), F4(d, i + 8), F4(d, i + 12)

__device__ __forceinline__ void mma_t(float (&d)[16], uint64_t a, uint64_t b, int acc) {
    asm volatile("{.reg .pred p; setp.ne.b32 p, %18, 0;\n"
                 "wgmma.mma_async.sync.aligned.m64n32k16.f32.bf16.bf16 {%0,%1,%2,%3,%4,%5,%6,%7,%8,%9,%10,%11,%12,%13,%14,%15}, %16, %17, p, 1, 1, 1, 0;}\n"
                 : F16(d, 0) : "l"(a), "l"(b), "r"(acc));
}
__device__ __forceinline__ void mma_t(float (&d)[20], uint64_t a, uint64_t b, int acc) {
    asm volatile("{.reg .pred p; setp.ne.b32 p, %22, 0;\n"
                 "wgmma.mma_async.sync.aligned.m64n40k16.f32.bf16.bf16 {%0,%1,%2,%3,%4,%5,%6,%7,%8,%9,%10,%11,%12,%13,%14,%15,%16,%17,%18,%19}, %20, %21, p, 1, 1, 1, 0;}\n"
                 : F16(d, 0), F4(d, 16) : "l"(a), "l"(b), "r"(acc));
}
__device__ __forceinline__ void mma_t(float (&d)[24], uint64_t a, uint64_t b, int acc) {
    asm volatile("{.reg .pred p; setp.ne.b32 p, %26, 0;\n"
                 "wgmma.mma_async.sync.aligned.m64n48k16.f32.bf16.bf16 {%0,%1,%2,%3,%4,%5,%6,%7,%8,%9,%10,%11,%12,%13,%14,%15,%16,%17,%18,%19,%20,%21,%22,%23}, %24, %25, p, 1, 1, 1, 0;}\n"
                 : F16(d, 0), F4(d, 16), F4(d, 20) : "l"(a), "l"(b), "r"(acc));
}
__device__ __forceinline__ void mma_qk(float (&d)[64], uint64_t a, uint64_t b, int acc) {
    asm volatile("{.reg .pred p; setp.ne.b32 p, %66, 0;\n"
                 "wgmma.mma_async.sync.aligned.m64n128k16.f32.bf16.bf16 {%0,%1,%2,%3,%4,%5,%6,%7,%8,%9,%10,%11,%12,%13,%14,%15,%16,%17,%18,%19,%20,%21,%22,%23,%24,%25,%26,%27,%28,%29,%30,%31,"
                 "%32,%33,%34,%35,%36,%37,%38,%39,%40,%41,%42,%43,%44,%45,%46,%47,%48,%49,%50,%51,%52,%53,%54,%55,%56,%57,%58,%59,%60,%61,%62,%63}, %64, %65, p, 1, 1, 0, 0;}\n"
                 : F16(d, 0), F16(d, 16), F16(d, 32), F16(d, 48) : "l"(a), "l"(b), "r"(acc));
}
__device__ __forceinline__ void mma_pv(float (&d)[32], uint32_t a0, uint32_t a1, uint32_t a2, uint32_t a3, uint64_t b) {
    asm volatile("wgmma.mma_async.sync.aligned.m64n64k16.f32.bf16.bf16 {%0,%1,%2,%3,%4,%5,%6,%7,%8,%9,%10,%11,%12,%13,%14,%15,%16,%17,%18,%19,%20,%21,%22,%23,%24,%25,%26,%27,%28,%29,%30,%31}, "
                 "{%32,%33,%34,%35}, %36, 1, 1, 1, 1;\n"
                 : F16(d, 0), F16(d, 16) : "r"(a0), "r"(a1), "r"(a2), "r"(a3), "l"(b));
}

template <int N>
__device__ __forceinline__ void issue_half(float (&d)[N], uint32_t slot, uint32_t c0, uint32_t cstride, bool first) {
    const uint64_t a = mkdesc(slot), b0 = mkdesc(c0), b1 = mkdesc(c0 + cstride);
    wg_fence();
#pragma unroll
    for (int k = 0; k < 8; k++) mma_t(d, a + k * 128, (k < 4 ? b0 : b1) + (k & 3) * 2, !(first && k == 0));
    wg_commit();
}

struct Ring {
    uint32_t base, full, empty;
    uint32_t s, ph, rs;
    __device__ __forceinline__ uint32_t acquire() {
        mbar_wait(full + s * 8, ph);
        uint32_t a = base + s * SLOT;
        if (++s == NSLOT) { s = 0; ph ^= 1; }
        return a;
    }
    __device__ __forceinline__ void release(int lane) {
        if (lane == 0) mbar_arrive(empty + rs * 8);
        if (++rs == NSLOT) rs = 0;
    }
};

template <int RPW>
__device__ __forceinline__ void row_stats(uint32_t buf, uint32_t stats, int warp, int lane, float alpha) {
    float s[RPW], q[RPW];
#pragma unroll
    for (int i = 0; i < RPW; i++) {
        uint4 v = lds128(buf + (lane >> 3) * XCH + (warp * RPW + i) * 128 + (lane & 7) * 16);
        float a0 = blo(v.x), a1 = bhi(v.x), a2 = blo(v.y), a3 = bhi(v.y), a4 = blo(v.z), a5 = bhi(v.z), a6 = blo(v.w), a7 = bhi(v.w);
        s[i] = ((a0 + a1) + (a2 + a3)) + ((a4 + a5) + (a6 + a7));
        q[i] = fmaf(a0, a0, fmaf(a1, a1, fmaf(a2, a2, a3 * a3))) + fmaf(a4, a4, fmaf(a5, a5, fmaf(a6, a6, a7 * a7)));
    }
#pragma unroll
    for (int o = 16; o > 0; o >>= 1) {
#pragma unroll
        for (int i = 0; i < RPW; i++) {
            s[i] += __shfl_xor_sync(~0u, s[i], o);
            q[i] += __shfl_xor_sync(~0u, q[i], o);
        }
    }
    float ms = s[0], mq = q[0];
#pragma unroll
    for (int i = 1; i < RPW; i++)
        if (lane == i) { ms = s[i]; mq = q[i]; }
    const float mean = ms * (1.f / 256.f);
    const float var = fmaxf(fmaf(-mean, mean, mq * (1.f / 256.f)), 0.f);
    const float rstd = rsqrtf(var + 1e-5f) * alpha;
    if (lane < RPW) sts64f(stats + (warp * RPW + lane) * 8, mean * rstd, rstd);
    bar_sync(1, 256);
}

__global__ void __cluster_dims__(2, 1, 1) __launch_bounds__(NTHREADS, 1)
conformer_kernel(const __grid_constant__ Params p) {
    extern __shared__ __align__(1024) unsigned char smem_raw[];
    const uint32_t sb = smem_u32(smem_raw);
    const uint32_t bars = sb + OFF_BARS;
    const int tid = threadIdx.x;
    const int lane = tid & 31;
    const int warp = __shfl_sync(~0u, tid >> 5, 0);
    const int r = blockIdx.x & 1;
    const int pair = blockIdx.x >> 1;
    const int b = pair >> 5, pt = pair & 31;
    const int ah = pt >> 3, qt = (pt & 7) * 2 + r;
    const int abh = b * 4 + ah;

    TS(0);
    if (tid == 0) {
        for (int i = 0; i < NBARS; i++) {
            uint32_t c = 1;
            if (i >= B_EMPTY && i < B_XF) c = 4;
            else if (i >= B_XF && i < B_HF) c = ((((i - B_XF) & 3) >> 1) == r) ? 4 : 1;
            else if (i >= B_HF && i < B_INB) c = 8;
            mbar_init(bars + i * 8, c);
        }
        asm volatile("fence.mbarrier_init.release.cluster;" ::: "memory");
    }
    if (tid < 256) {
        sts128(sb + OFF_P + (tid >> 6) * XCH + 4096 + (tid & 63) * 16, 0x3F803F80u, 0x3F803F80u, 0x3F803F80u, 0x3F803F80u);
        fence_async_smem();
    }
    const uint32_t epoch = g_epoch[blockIdx.x * FS] + 1;
    __syncthreads();
    cluster_arrive();

    if (warp >= 8) {
        if (warp < 10) {
            const int w = warp - 8;
            const int tile = 2 * r + w;
            const uint32_t ring = sb + OFF_RING + w * NSLOT * SLOT;
            const uint32_t full = bars + (B_FULL + w * NSLOT) * 8, empty = bars + (B_EMPTY + w * NSLOT) * 8;
            uint32_t s = 0, ph = 1;
            for (int n = 0; n < NLOADS; n++) {
                if (n == 22) { flag_wait(&g_flag_qk[(abh * 32 + lane) * FS], epoch); __syncwarp(); fence_async_global(); }
                if (n == 24) { flag_wait(&g_flag_v[(abh * 32 + lane) * FS], epoch); __syncwarp(); fence_async_global(); }
                if (n >= NSLOT) mbar_wait(empty + s * 8, ph);
                if (lane == 0) {
                    mbar_arrive_tx(full + s * 8, SLOT);
                    if (n >= 22 && n < 30) {
                        const int k = n - 22;
                        const bool isv = (k == 7) || (k >= 2 && !(k & 1));
                        const int i = isv ? (k == 7 ? 3 : (k >> 1) - 1) : ((k + 1) >> 1);
                        bulk_g2s(ring + s * SLOT, (isv ? g_v : g_k) + (size_t)(abh * 1024 + (2 * i + w) * 128) * 128, SLOT, full + s * 8);
                    } else {
                        int m, col, row;
                        if (n < 16 || n >= 38) {
                            const int k = n < 16 ? n : n - 38;
                            m = n < 16 ? 1 : 7;
                            if (k < 8) { col = 64 * (8 * r + (k & 6) + w); row = 128 * ((k & 1) ^ r); }
                            else { m++; col = 64 * (k < 12 ? (tile ^ 2) : tile); row = 512 * r + 128 * (k & 3); }
                        } else if (n < 22) {
                            const int k = n - 16;
                            m = 3;
                            if (k < 4) { col = 64 * tile + ((k & 1) ? 0 : 256); row = 128 * ((k >> 1) ^ r); }
                            else { col = 512 + 64 * tile; row = 128 * ((k & 1) ^ r); }
                        } else if (n < 32) { m = 4; col = 64 * tile; row = 128 * (n - 30); }
                        else if (n < 36) { const int k = n - 32; m = 5; col = 64 * tile + 256 * (k & 1); row = 128 * ((k >> 1) ^ r); }
                        else { m = 6; col = 64 * tile; row = 128 * ((n & 1) ^ r); }
                        tma2d(ring + s * SLOT, &p.tm[m], col, row, full + s * 8);
                    }
                }
                __syncwarp();
                if (++s == NSLOT) { s = 0; ph ^= 1; }
            }
        } else if (warp == 10) {
            if (lane < 4) {
                const uint32_t bar = bars + (B_XF + lane) * 8;
                mbar_expect_tx(bar, 4096);
                mbar_arrive_n(bar, (lane >> 1) == r ? 4 : 1);
                tma3d(sb + OFF_P + lane * XCH, &p.tm[0], lane * 64, pt * 32, b, bar);
            }
            __syncwarp();
            if (lane < 2) flag_wait(&g_flag_qk[(abh * 32 + 2 * qt + lane) * FS], epoch);
            __syncwarp();
            if (lane == 0) {
                fence_async_global();
                mbar_arrive_tx(bars + B_QIN * 8, 8192);
                bulk_g2s(sb + OFF_H + 24576, g_q + (size_t)(abh * 1024 + qt * 64) * 128, 8192, bars + B_QIN * 8);
            }
            if (lane < 12) {
                const int np = pt - 1 + (lane >> 2);
                if (np >= 0 && np < 32) flag_wait(&g_flag_v[((b * 4 + (lane & 3)) * 32 + np) * FS], epoch);
            }
            __syncwarp();
            if (lane == 0) {
                fence_async_global();
                mbar_arrive_tx(bars + B_X1IN * 8, 2 * XCH);
                for (int w = 0; w < 2; w++)
                    bulk_g2s(sb + OFF_P + (2 * r + w) * XCH, g_x1 + (size_t)((b * 4 + 2 * r + w) * PADROWS + pt * 32) * 128, XCH, bars + B_X1IN * 8);
            }
            if (lane < 8) {
                const int q = (pt >> 1) + (lane < 4 ? 0 : ((pt & 1) ? 1 : -1));
                if (q >= 0 && q < 16) flag_wait(&g_flag_o[((b * 16 + q) * 4 + (lane & 3)) * FS], epoch);
            }
            __syncwarp();
            mbar_wait(bars + B_ATT * 8, 0);
            if (lane < 4) {
                fence_async_global();
                const uint32_t bar = bars + (B_XF + lane) * 8;
                mbar_expect_tx(bar, XCH);
                mbar_arrive_n(bar, (lane >> 1) == r ? 4 : 1);
                bulk_g2s(sb + OFF_H + lane * XCH, g_o + (size_t)((b * 4 + lane) * PADROWS + pt * 32) * 128, XCH, bar);
            }
            __syncwarp();
        } else {
            if (lane < 8) {
                const uint32_t kb = (lane < 2 || lane > 5) ? 4096 : (lane == 2 ? 3072 : (lane == 4 ? 2048 : 1024));
                asm volatile("cp.async.bulk.prefetch.L2.global [%0], %1;" ::"l"(p.w[lane] + (size_t)blockIdx.x * kb), "r"(kb) : "memory");
            }
            __syncwarp();
        }
        cluster_wait();
        return;
    }

    const int w = warp >> 2, wq = warp & 3;
    const int tile = 2 * r + w;
    const int wt = tid & 127;
    const int c4 = lane & 3;
    Ring ring{sb + OFF_RING + w * NSLOT * SLOT, bars + (B_FULL + w * NSLOT) * 8, bars + (B_EMPTY + w * NSLOT) * 8, 0, 0, 0};
    const uint32_t P = sb + OFF_P, H = sb + OFF_H;
    const uint32_t toff = ((lane >> 4) * 8 + (lane & 7)) * 128 + (((2 * wq + ((lane >> 3) & 1)) ^ (lane & 7)) << 4);

    auto xwait = [&](int stage, int half) {
        const uint32_t bar = bars + (B_XF + (stage & 1) * 4 + 2 * half) * 8;
        mbar_wait(bar, (stage >> 1) & 1);
        mbar_wait(bar + 8, (stage >> 1) & 1);
    };
    auto publish = [&](int stage, uint32_t chunk, uint32_t off, uint32_t bytes) {
        const uint32_t bar = bars + (B_XF + (stage & 1) * 4 + tile) * 8;
        fence_async_smem();
        __syncwarp();
        if (lane == 0) mbar_arrive(bar);
        if (wq == 0) {
            mbar_wait(bar, (stage >> 1) & 1);
            if (lane == 0) {
                mbar_arrive_tx(bar ^ 16, bytes);
                bulk_s2s(mapa(chunk + off, r ^ 1), chunk + off, bytes, mapa(bar, r ^ 1));
            }
            __syncwarp();
        }
    };

#pragma unroll 1
    for (int ffi = 0; ffi < 2; ffi++) {
        {
            const int sin = ffi ? 5 : 0;
            float st[16];
            float a0[20], a1[20], rem[16], own[16];
            if (wt == 0) mbar_arrive_tx(bars + (B_INB + w) * 8, 4096);
            uint32_t sl = ring.acquire();
            xwait(sin, r);
            TS(1 + ffi * 20);
            issue_half(a0, sl, P + 2 * r * XCH, XCH, true);
            sl = ring.acquire();
            xwait(sin, r ^ 1);
            issue_half(a0, sl, P + 2 * (r ^ 1) * XCH, XCH, false);
            row_stats<4>(P, sb + OFF_STATS, warp, lane, 0.5f);
#pragma unroll
            for (int j = 0; j < 4; j++) {
                float4 v = lds128f(sb + OFF_STATS + (8 * j + 2 * c4) * 8);
                st[4 * j] = v.x; st[4 * j + 1] = v.y; st[4 * j + 2] = v.z; st[4 * j + 3] = v.w;
            }
            auto g1_issue = [&](float (&d)[20]) {
                uint32_t s0 = ring.acquire();
                issue_half(d, s0, P + 2 * r * XCH, XCH, true);
                s0 = ring.acquire();
                issue_half(d, s0, P + 2 * (r ^ 1) * XCH, XCH, false);
            };
            auto g1_epi = [&](float (&d)[20], int i) {
                pin(d);
                ring.release(lane);
                ring.release(lane);
                uint32_t pk[8];
#pragma unroll
                for (int j = 0; j < 4; j++)
#pragma unroll
                    for (int hh = 0; hh < 2; hh++) {
                        const float cs = d[16 + 2 * hh];
                        const float v0 = fmaf(-st[4 * j], cs, d[4 * j + 2 * hh] * st[4 * j + 1]);
                        const float v1 = fmaf(-st[4 * j + 2], cs, d[4 * j + 2 * hh + 1] * st[4 * j + 3]);
                        pk[2 * j + hh] = pack2(fmaf(v0, tanh_fast(v0), v0), fmaf(v1, tanh_fast(v1), v1));
                    }
                const uint32_t dst = H + (2 * i + w) * HCH + toff;
                stsm4t(dst, pk[0], pk[1], pk[2], pk[3]);
                stsm4t(dst + 2048, pk[4], pk[5], pk[6], pk[7]);
                fence_async_smem();
                __syncwarp();
                if (lane == 0) mbar_arrive(bars + (B_HF + i) * 8);
            };
            auto g2_issue = [&](float (&d)[16], int q, bool hwait) {
                const uint32_t s0 = ring.acquire();
                if (hwait) mbar_wait(bars + (B_HF + q) * 8, ffi);
                issue_half(d, s0, H + 2 * q * HCH, HCH, q == 0);
            };
            g1_issue(a1); wg_wait<2>(); g1_epi(a0, 0);
            g1_issue(a0); wg_wait<2>(); g1_epi(a1, 1);
            g1_issue(a1); wg_wait<2>(); g1_epi(a0, 2);
            g2_issue(rem, 0, true); g2_issue(rem, 1, true); wg_wait<2>(); g1_epi(a1, 3);
            TS(2 + ffi * 20);
            g2_issue(rem, 2, true); wg_wait<1>(); ring.release(lane); ring.release(lane);
            g2_issue(rem, 3, true); wg_wait<1>(); ring.release(lane);
            g2_issue(own, 0, false); wg_wait<1>(); ring.release(lane);
            pin(rem);
            if (ffi == 0) cluster_wait();
            {
                const uint32_t dst = mapa(sb + OFF_INBOX + w * 4096 + wt * 16, r ^ 1), bar = mapa(bars + (B_INB + w) * 8, r ^ 1);
                st_async4(dst, pack2(rem[0], rem[1]), pack2(rem[2], rem[3]), pack2(rem[4], rem[5]), pack2(rem[6], rem[7]), bar);
                st_async4(dst + 2048, pack2(rem[8], rem[9]), pack2(rem[10], rem[11]), pack2(rem[12], rem[13]), pack2(rem[14], rem[15]), bar);
            }
            g2_issue(own, 1, false); wg_wait<1>(); ring.release(lane);
            g2_issue(own, 2, false); wg_wait<1>(); ring.release(lane);
            g2_issue(own, 3, false); wg_wait<1>(); ring.release(lane);
            uint32_t xr[8], pr[8];
            const uint32_t xa = P + tile * XCH + toff;
            ldsm4t(xa, xr[0], xr[1], xr[2], xr[3]);
            ldsm4t(xa + 2048, xr[4], xr[5], xr[6], xr[7]);
            mbar_wait(bars + (B_INB + w) * 8, ffi);
            {
                uint4 u = lds128(sb + OFF_INBOX + w * 4096 + wt * 16), v = lds128(sb + OFF_INBOX + w * 4096 + 2048 + wt * 16);
                pr[0] = u.x; pr[1] = u.y; pr[2] = u.z; pr[3] = u.w; pr[4] = v.x; pr[5] = v.y; pr[6] = v.z; pr[7] = v.w;
            }
            wg_wait<0>();
            pin(own);
            ring.release(lane);
            TS(3 + ffi * 20);
#pragma unroll
            for (int i = 0; i < 8; i++)
                xr[i] = pack2(fmaf(0.5f, own[2 * i] + blo(pr[i]), blo(xr[i])), fmaf(0.5f, own[2 * i + 1] + bhi(pr[i]), bhi(xr[i])));
            stsm4t(xa, xr[0], xr[1], xr[2], xr[3]);
            stsm4t(xa + 2048, xr[4], xr[5], xr[6], xr[7]);
        }
        if (ffi == 1) break;
        publish(1, P + tile * XCH, 0, 4096);
        if (wt == 0) bulk_s2g(g_x1 + (size_t)((b * 4 + tile) * PADROWS + 8 + pt * 32) * 128, P + tile * XCH, 4096);

        {
            float ak[20], aq[20], av[20], st[16];
            uint32_t sl = ring.acquire();
            xwait(1, r);
            issue_half(ak, sl, P + 2 * r * XCH, XCH, true);
            sl = ring.acquire();
            issue_half(aq, sl, P + 2 * r * XCH, XCH, true);
            sl = ring.acquire();
            xwait(1, r ^ 1);
            issue_half(ak, sl, P + 2 * (r ^ 1) * XCH, XCH, false);
            sl = ring.acquire();
            issue_half(aq, sl, P + 2 * (r ^ 1) * XCH, XCH, false);
            row_stats<4>(P, sb + OFF_STATS, warp, lane, 1.f);
#pragma unroll
            for (int j = 0; j < 4; j++) {
                float4 v = lds128f(sb + OFF_STATS + (8 * j + 2 * c4) * 8);
                st[4 * j] = v.x; st[4 * j + 1] = v.y; st[4 * j + 2] = v.z; st[4 * j + 3] = v.w;
            }
            wg_wait<2>();
            ring.release(lane); ring.release(lane);
            sl = ring.acquire();
            issue_half(av, sl, P + 2 * r * XCH, XCH, true);
            sl = ring.acquire();
            issue_half(av, sl, P + 2 * (r ^ 1) * XCH, XCH, false);
            auto stage_out = [&](float (&d)[20], uint32_t dst) {
                uint32_t pk[8];
#pragma unroll
                for (int j = 0; j < 4; j++)
#pragma unroll
                    for (int hh = 0; hh < 2; hh++) {
                        const float cs = d[16 + 2 * hh];
                        pk[2 * j + hh] = pack2(fmaf(-st[4 * j], cs, d[4 * j + 2 * hh] * st[4 * j + 1]),
                                               fmaf(-st[4 * j + 2], cs, d[4 * j + 2 * hh + 1] * st[4 * j + 3]));
                    }
                stsm4t(dst + toff, pk[0], pk[1], pk[2], pk[3]);
                stsm4t(dst + toff + 2048, pk[4], pk[5], pk[6], pk[7]);
            };
            const uint32_t stg = H + w * 12288;
            const size_t goff = (size_t)((b * 4 + tile) * 1024 + pt * 32) * 128 + wt * 16;
            wg_wait<2>();
            pin(ak); pin(aq);
            ring.release(lane); ring.release(lane);
            TS(4);
            stage_out(ak, stg);
            stage_out(aq, stg + 4096);
            bar_sync(2 + w, 128);
            {
                uint4 k0 = lds128(stg + wt * 16), k1 = lds128(stg + 2048 + wt * 16), q0 = lds128(stg + 4096 + wt * 16), q1 = lds128(stg + 6144 + wt * 16);
                stg128(g_k + goff, k0); stg128(g_k + goff + 2048, k1);
                stg128(g_q + goff, q0); stg128(g_q + goff + 2048, q1);
            }
            bar_sync(2 + w, 128);
            if (wt == 32) flag_set(&g_flag_qk[((b * 4 + tile) * 32 + pt) * FS], epoch);
            __syncwarp();
            wg_wait<0>();
            pin(av);
            ring.release(lane); ring.release(lane);
            stage_out(av, stg + 8192);
            bar_sync(2 + w, 128);
            {
                uint4 v0 = lds128(stg + 8192 + wt * 16), v1 = lds128(stg + 10240 + wt * 16);
                stg128(g_v + goff, v0); stg128(g_v + goff + 2048, v1);
            }
            bar_sync(2 + w, 128);
            if (wt == 0) {
                asm volatile("cp.async.bulk.wait_group 0;" ::: "memory");
                fence_async_global();
                flag_set(&g_flag_v[((b * 4 + tile) * 32 + pt) * FS], epoch);
            }
            __syncwarp();
            TS(5);
        }

        {
            constexpr float CS = 0.125f * 1.4426950408889634f;
            float s[64], o[32];
            uint32_t pp[32];
            float m0 = -INFINITY, m1 = -INFINITY, l0 = 0.f, l1 = 0.f;
#pragma unroll
            for (int i = 0; i < 32; i++) o[i] = 0.f;
            const uint64_t qd = mkdesc(H + 24576);
            auto qk_issue = [&]() {
                const uint64_t kd = mkdesc(ring.acquire());
                wg_fence();
#pragma unroll
                for (int k = 0; k < 4; k++) mma_qk(s, qd + 2 * k, kd + 2 * k, k != 0);
                wg_commit();
            };
            auto pv_issue = [&]() {
                const uint64_t vd = mkdesc(ring.acquire());
                wg_fence();
#pragma unroll
                for (int k = 0; k < 8; k++) mma_pv(o, pp[4 * k], pp[4 * k + 1], pp[4 * k + 2], pp[4 * k + 3], vd + k * 128);
                wg_commit();
            };
            float sc0, sc1;
            auto softmax = [&](bool mask) {
                if (mask) {
#pragma unroll
                    for (int i = 52; i < 64; i++) s[i] = -INFINITY;
                }
                float x0 = m0, x1 = m1;
#pragma unroll
                for (int j = 0; j < 16; j++) {
                    x0 = fmaxf(x0, fmaxf(s[4 * j], s[4 * j + 1]));
                    x1 = fmaxf(x1, fmaxf(s[4 * j + 2], s[4 * j + 3]));
                }
                x0 = fmaxf(x0, __shfl_xor_sync(~0u, x0, 1)); x1 = fmaxf(x1, __shfl_xor_sync(~0u, x1, 1));
                x0 = fmaxf(x0, __shfl_xor_sync(~0u, x0, 2)); x1 = fmaxf(x1, __shfl_xor_sync(~0u, x1, 2));
                sc0 = ex2((m0 - x0) * CS); sc1 = ex2((m1 - x1) * CS);
                m0 = x0; m1 = x1;
                const float n0 = -x0 * CS, n1 = -x1 * CS;
                float r0 = 0.f, r1 = 0.f;
#pragma unroll
                for (int j = 0; j < 16; j++) {
                    s[4 * j] = ex2(fmaf(s[4 * j], CS, n0)); s[4 * j + 1] = ex2(fmaf(s[4 * j + 1], CS, n0));
                    s[4 * j + 2] = ex2(fmaf(s[4 * j + 2], CS, n1)); s[4 * j + 3] = ex2(fmaf(s[4 * j + 3], CS, n1));
                    r0 += s[4 * j] + s[4 * j + 1]; r1 += s[4 * j + 2] + s[4 * j + 3];
                }
                l0 = fmaf(l0, sc0, r0); l1 = fmaf(l1, sc1, r1);
            };
            auto to_p = [&]() {
#pragma unroll
                for (int i = 0; i < 32; i++) pp[i] = pack2(s[2 * i], s[2 * i + 1]);
#pragma unroll
                for (int j = 0; j < 8; j++) { o[4 * j] *= sc0; o[4 * j + 1] *= sc0; o[4 * j + 2] *= sc1; o[4 * j + 3] *= sc1; }
            };
            mbar_wait(bars + B_QIN * 8, 0);
            qk_issue();
            wg_wait<0>();
            pin(s);
            TS(6);
            ring.release(lane);
            softmax(false);
            to_p();
#pragma unroll 1
            for (int it = 1; it < 4; it++) {
                pin(s); pin(o); pin(pp);
                qk_issue();
                pv_issue();
                wg_wait<1>();
                pin(s);
                ring.release(lane);
                softmax(it == 3 && w == 1);
                wg_wait<0>();
                pin(o); pin(pp);
                ring.release(lane);
                to_p();
            }
            pin(o); pin(pp);
            pv_issue();
            l0 += __shfl_xor_sync(~0u, l0, 1); l1 += __shfl_xor_sync(~0u, l1, 1);
            l0 += __shfl_xor_sync(~0u, l0, 2); l1 += __shfl_xor_sync(~0u, l1, 2);
            const int row = wq * 16 + (lane >> 2);
            const uint32_t ml = sb + OFF_INBOX;
            if (c4 == 0) { sts64f(ml + w * 512 + row * 8, m0, l0); sts64f(ml + w * 512 + row * 8 + 64, m1, l1); }
            wg_wait<0>();
            pin(o); pin(pp);
            ring.release(lane);
            TS(7);
            float mine[16];
#pragma unroll
            for (int j = 0; j < 4; j++) {
                if (w == 0) sts128f(H + j * 2048 + wt * 16, o[16 + 4 * j], o[17 + 4 * j], o[18 + 4 * j], o[19 + 4 * j]);
                else sts128f(H + 8192 + j * 2048 + wt * 16, o[4 * j], o[4 * j + 1], o[4 * j + 2], o[4 * j + 3]);
            }
#pragma unroll
            for (int i = 0; i < 16; i++) mine[i] = w == 0 ? o[i] : o[16 + i];
            bar_sync(1, 256);
            const float2 u0 = lds64f(ml + (w ^ 1) * 512 + row * 8), u1 = lds64f(ml + (w ^ 1) * 512 + row * 8 + 64);
            const float x0 = fmaxf(m0, u0.x), x1 = fmaxf(m1, u1.x);
            float a0 = ex2((m0 - x0) * CS), b0 = ex2((u0.x - x0) * CS), a1 = ex2((m1 - x1) * CS), b1 = ex2((u1.x - x1) * CS);
            const float i0 = __fdividef(1.f, fmaf(a0, l0, b0 * u0.y)), i1 = __fdividef(1.f, fmaf(a1, l1, b1 * u1.y));
            a0 *= i0; b0 *= i0; a1 *= i1; b1 *= i1;
            uint32_t pk[8];
#pragma unroll
            for (int j = 0; j < 4; j++) {
                const float4 v = lds128f(H + (w ^ 1) * 8192 + j * 2048 + wt * 16);
                pk[2 * j] = pack2(fmaf(a0, mine[4 * j], b0 * v.x), fmaf(a0, mine[4 * j + 1], b0 * v.y));
                pk[2 * j + 1] = pack2(fmaf(a1, mine[4 * j + 2], b1 * v.z), fmaf(a1, mine[4 * j + 3], b1 * v.w));
            }
            const uint32_t og = H + 16384 + wq * 2048;
            {
                const uint32_t ra = og + (((lane >> 3) & 1) * 8 + (lane & 7)) * 128;
                stsm4(ra + (((4 * w + (lane >> 4)) ^ (lane & 7)) << 4), pk[0], pk[1], pk[2], pk[3]);
                stsm4(ra + (((4 * w + 2 + (lane >> 4)) ^ (lane & 7)) << 4), pk[4], pk[5], pk[6], pk[7]);
            }
            __syncwarp();
            {
                const uint32_t off = (lane >> 2) * 128 + (((4 * w + c4) ^ (lane >> 2)) << 4);
                const uint4 v0 = lds128(og + off), v1 = lds128(og + off + 1024);
                unsigned char* dst = g_o + (size_t)(abh * PADROWS + 8 + qt * 64 + wq * 16) * 128 + off;
                stg128(dst, v0); stg128(dst + 1024, v1);
            }
            bar_sync(1, 256);
            if (tid == 0) {
                mbar_arrive(bars + B_ATT * 8);
                flag_set(&g_flag_o[((b * 16 + qt) * 4 + ah) * FS], epoch);
            }
            __syncwarp();
            TS(8);
        }

        uint32_t x2r[8];
        uint32_t dwr[15];
        {
#pragma unroll
            for (int i = 0; i < 15; i++) dwr[i] = __ldg(reinterpret_cast<const uint32_t*>(p.dw + i * 256 + tile * 64) + lane);
            float d[24];
            uint32_t xr[12];
            const uint32_t xa = P + tile * XCH + toff;
            mbar_wait(bars + B_X1IN * 8, 0);
#pragma unroll
            for (int j = 0; j < 3; j++) ldsm4t(xa + j * 2048, xr[4 * j], xr[4 * j + 1], xr[4 * j + 2], xr[4 * j + 3]);
            uint32_t sl = ring.acquire();
            xwait(2, 0);
            TS(9);
            issue_half(d, sl, H, XCH, true);
            sl = ring.acquire();
            xwait(2, 1);
            issue_half(d, sl, H + 2 * XCH, XCH, false);
            wg_wait<0>();
            pin(d);
            ring.release(lane); ring.release(lane);
#pragma unroll
            for (int i = 0; i < 12; i++) xr[i] = pack2(d[2 * i] + blo(xr[i]), d[2 * i + 1] + bhi(xr[i]));
            if (c4 == 0) { xr[0] = (xr[0] & 0xffff0000u) | 0x3F80u; xr[1] = (xr[1] & 0xffff0000u) | 0x3F80u; }
#pragma unroll
            for (int j = 0; j < 3; j++) stsm4t(xa + j * 2048, xr[4 * j], xr[4 * j + 1], xr[4 * j + 2], xr[4 * j + 3]);
#pragma unroll
            for (int i = 0; i < 8; i++) x2r[i] = xr[2 + i];
            publish(3, P + tile * XCH, 0, XCH);
            TS(10);
        }
        {
            float da[24], db[24];
            uint32_t sl = ring.acquire();
            xwait(3, r);
            issue_half(da, sl, P + 2 * r * XCH, XCH, true);
            sl = ring.acquire();
            issue_half(db, sl, P + 2 * r * XCH, XCH, true);
            sl = ring.acquire();
            xwait(3, r ^ 1);
            issue_half(da, sl, P + 2 * (r ^ 1) * XCH, XCH, false);
            sl = ring.acquire();
            issue_half(db, sl, P + 2 * (r ^ 1) * XCH, XCH, false);
            row_stats<6>(P, sb + OFF_STATS, warp, lane, 0.5f);
            float st[24];
#pragma unroll
            for (int j = 0; j < 6; j++) {
                float4 v = lds128f(sb + OFF_STATS + (8 * j + 2 * c4) * 8);
                st[4 * j] = v.x; st[4 * j + 1] = v.y; st[4 * j + 2] = v.z; st[4 * j + 3] = v.w;
            }
            wg_wait<2>();
            ring.release(lane); ring.release(lane);
            wg_wait<0>();
            pin(da); pin(db);
            ring.release(lane); ring.release(lane);
            TS(11);
            uint32_t pk[12];
#pragma unroll
            for (int hh = 0; hh < 2; hh++) {
                const float ca = __shfl_sync(~0u, da[2 * hh], lane & 28), cb = __shfl_sync(~0u, db[2 * hh], lane & 28);
#pragma unroll
                for (int j = 0; j < 6; j++) {
                    const float u0 = fmaf(-st[4 * j], ca, da[4 * j + 2 * hh] * st[4 * j + 1]);
                    const float u1 = fmaf(-st[4 * j + 2], ca, da[4 * j + 2 * hh + 1] * st[4 * j + 3]);
                    const float v0 = fmaf(-st[4 * j], cb, db[4 * j + 2 * hh] * st[4 * j + 1]);
                    const float v1 = fmaf(-st[4 * j + 2], cb, db[4 * j + 2 * hh + 1] * st[4 * j + 3]);
                    const uint32_t g = pack2(fmaf(u0, tanh_fast(v0), u0), fmaf(u1, tanh_fast(v1), u1));
                    const int t0 = pt * 32 - 8 + 8 * j;
                    pk[2 * j + hh] = (t0 >= 0 && t0 < T_) ? g : 0u;
                }
            }
            const uint32_t gs = H + 16384 + w * XCH;
#pragma unroll
            for (int j = 0; j < 3; j++) stsm4t(gs + toff + j * 2048, pk[4 * j], pk[4 * j + 1], pk[4 * j + 2], pk[4 * j + 3]);
            bar_sync(2 + w, 128);
            float c0[8], c1[8];
#pragma unroll
            for (int i = 0; i < 8; i++) { c0[i] = 0.f; c1[i] = 0.f; }
#pragma unroll
            for (int k = 0; k < 22; k++) {
                const uint32_t v = lds32(gs + (8 * wq + 1 + k) * 128 + (((lane >> 2) ^ ((1 + k) & 7)) << 4) + c4 * 4);
                const float v0 = blo(v), v1 = bhi(v);
#pragma unroll
                for (int i = 0; i < 8; i++)
                    if (k - i >= 0 && k - i < 15) { c0[i] = fmaf(v0, blo(dwr[k - i]), c0[i]); c1[i] = fmaf(v1, bhi(dwr[k - i]), c1[i]); }
            }
#pragma unroll
            for (int i = 0; i < 8; i++) {
                const float h0 = 0.5f * c0[i], h1 = 0.5f * c1[i];
                sts32(H + tile * HCH + (8 * wq + i) * 128 + (((lane >> 2) ^ i) << 4) + c4 * 4,
                      pack2(fmaf(h0, tanh_fast(h0), h0), fmaf(h1, tanh_fast(h1), h1)));
            }
            publish(4, H + tile * HCH, 0, HCH);
            TS(12);
        }
        {
            float d[16];
            uint32_t sl = ring.acquire();
            xwait(4, r);
            issue_half(d, sl, H + 2 * r * HCH, HCH, true);
            sl = ring.acquire();
            xwait(4, r ^ 1);
            issue_half(d, sl, H + 2 * (r ^ 1) * HCH, HCH, false);
            sts128(P + (wt >> 6 ? (tile ^ 2) : tile) * XCH + 4096 + (wt & 63) * 16, 0x3F803F80u, 0x3F803F80u, 0x3F803F80u, 0x3F803F80u);
            wg_wait<0>();
            pin(d);
            ring.release(lane); ring.release(lane);
#pragma unroll
            for (int i = 0; i < 8; i++) x2r[i] = pack2(d[2 * i] + blo(x2r[i]), d[2 * i + 1] + bhi(x2r[i]));
            const uint32_t xa = P + tile * XCH + toff;
            stsm4t(xa, x2r[0], x2r[1], x2r[2], x2r[3]);
            stsm4t(xa + 2048, x2r[4], x2r[5], x2r[6], x2r[7]);
            publish(5, P + tile * XCH, 0, HCH);
            TS(13);
        }
    }

    publish(6, P + tile * XCH, (r ^ 1) * 2048, 2048);
    xwait(6, r);
    xwait(6, r ^ 1);
    cluster_arrive();
    TS(24);
    {
        float a[2][8], s[2], q[2];
        const int row0 = 16 * r + 2 * warp;
#pragma unroll
        for (int i = 0; i < 2; i++) {
            const uint4 v = lds128(P + (lane >> 3) * XCH + (row0 + i) * 128 + (((lane & 7) ^ ((row0 + i) & 7)) << 4));
            a[i][0] = blo(v.x); a[i][1] = bhi(v.x); a[i][2] = blo(v.y); a[i][3] = bhi(v.y);
            a[i][4] = blo(v.z); a[i][5] = bhi(v.z); a[i][6] = blo(v.w); a[i][7] = bhi(v.w);
            s[i] = ((a[i][0] + a[i][1]) + (a[i][2] + a[i][3])) + ((a[i][4] + a[i][5]) + (a[i][6] + a[i][7]));
            q[i] = 0.f;
#pragma unroll
            for (int k = 0; k < 8; k++) q[i] = fmaf(a[i][k], a[i][k], q[i]);
        }
#pragma unroll
        for (int o = 16; o > 0; o >>= 1) {
#pragma unroll
            for (int i = 0; i < 2; i++) { s[i] += __shfl_xor_sync(~0u, s[i], o); q[i] += __shfl_xor_sync(~0u, q[i], o); }
        }
#pragma unroll
        for (int i = 0; i < 2; i++) {
            const float mean = s[i] * (1.f / 256.f);
            const float rstd = rsqrtf(fmaxf(fmaf(-mean, mean, q[i] * (1.f / 256.f)), 0.f) + 1e-5f);
            const float nb = -mean * rstd;
            uint4 v;
            v.x = pack2(fmaf(a[i][0], rstd, nb), fmaf(a[i][1], rstd, nb)); v.y = pack2(fmaf(a[i][2], rstd, nb), fmaf(a[i][3], rstd, nb));
            v.z = pack2(fmaf(a[i][4], rstd, nb), fmaf(a[i][5], rstd, nb)); v.w = pack2(fmaf(a[i][6], rstd, nb), fmaf(a[i][7], rstd, nb));
            const int t = pt * 32 + row0 + i;
            if (t < T_) stg128(p.out + (size_t)(b * T_ + t) * 256 + lane * 8, v);
        }
    }
    if (tid == 0) g_epoch[blockIdx.x * FS] = epoch;
    TS(25);
    cluster_wait();
}

typedef CUresult (*EncodeFn)(CUtensorMap*, CUtensorMapDataType, cuuint32_t, void*, const cuuint64_t*, const cuuint64_t*,
                             const cuuint32_t*, const cuuint32_t*, CUtensorMapInterleave, CUtensorMapSwizzle,
                             CUtensorMapL2promotion, CUtensorMapFloatOOBfill);

}

extern "C" void kernel_launch(void* const* d_in, const int* in_sizes, int n_in, void* d_out, int out_size) {
    static EncodeFn encode = nullptr;
    if (!encode) {
        void* fn = nullptr;
        cudaDriverEntryPointQueryResult qr;
        cudaGetDriverEntryPoint("cuTensorMapEncodeTiled", &fn, cudaEnableDefault, &qr);
        encode = (EncodeFn)fn;
        cudaFuncSetAttribute(conformer_kernel, cudaFuncAttributeMaxDynamicSharedMemorySize, SMEM_BYTES);
    }
    Params p;
    const cuuint32_t ones[3] = {1, 1, 1};
    {
        const cuuint64_t dims[3] = {256, T_, 2};
        const cuuint64_t strides[2] = {512, 512ull * T_};
        const cuuint32_t box[3] = {64, 32, 1};
        encode(&p.tm[0], CU_TENSOR_MAP_DATA_TYPE_BFLOAT16, 3, d_in[0], dims, strides, box, ones, CU_TENSOR_MAP_INTERLEAVE_NONE,
               CU_TENSOR_MAP_SWIZZLE_128B, CU_TENSOR_MAP_L2_PROMOTION_L2_256B, CU_TENSOR_MAP_FLOAT_OOB_FILL_NONE);
    }
    const int idx[8] = {1, 2, 3, 4, 5, 7, 8, 9};
    const int rows[8] = {256, 1024, 256, 256, 256, 256, 256, 1024};
    const int cols[8] = {1024, 256, 768, 256, 512, 256, 1024, 256};
    for (int i = 0; i < 8; i++) {
        const cuuint64_t dims[2] = {(cuuint64_t)cols[i], (cuuint64_t)rows[i]};
        const cuuint64_t strides[1] = {(cuuint64_t)cols[i] * 2};
        const cuuint32_t box[2] = {64, 128};
        encode(&p.tm[1 + i], CU_TENSOR_MAP_DATA_TYPE_BFLOAT16, 2, d_in[idx[i]], dims, strides, box, ones, CU_TENSOR_MAP_INTERLEAVE_NONE,
               CU_TENSOR_MAP_SWIZZLE_128B, CU_TENSOR_MAP_L2_PROMOTION_L2_128B, CU_TENSOR_MAP_FLOAT_OOB_FILL_NONE);
        p.w[i] = (const char*)d_in[idx[i]];
    }
    p.dw = (const __nv_bfloat16*)d_in[6];
    p.out = (__nv_bfloat16*)d_out;
    conformer_kernel<<<NCTA, NTHREADS, SMEM_BYTES>>>(p);
}
```

```cpp
#include <cuda_runtime.h>
#include <cuda_bf16.h>
#include <cuda.h>
#include <stdint.h>

namespace {

constexpr int T_ = 1000;
constexpr int NCTA = 128;
constexpr int NTHREADS = 512;
constexpr int NSLOT = 5;
constexpr int SLOT = 16384;
constexpr int NLOADS = 54;

constexpr uint32_t OFF_RING = 0;
constexpr uint32_t OFF_P = 163840;
constexpr uint32_t OFF_H = 188416;
constexpr uint32_t OFF_INBOX = 221184;
constexpr uint32_t OFF_STATS = 229376;
constexpr uint32_t OFF_BARS = 229888;
constexpr uint32_t SMEM_BYTES = 230400;
constexpr uint32_t XCH = 6144;
constexpr uint32_t HCH = 4096;

constexpr int B_FULL = 0, B_EMPTY = 10, B_XF = 20, B_HF = 28, B_INB = 32, B_QIN = 34, B_X1IN = 35, B_ST = 36;

constexpr int PADROWS = 1040;
constexpr int FS = 8;

struct Params {
    CUtensorMap tm[10];
    const char* w[9];
    const __nv_bfloat16* dw;
    __nv_bfloat16* out;
};

__device__ __align__(1024) unsigned char g_kqv[3 * 8 * 1024 * 128];
__device__ __align__(1024) unsigned char g_o[8 * PADROWS * 128];
__device__ __align__(1024) unsigned char g_x1[8 * PADROWS * 128];
__device__ uint32_t g_flag_qk[8 * 32 * FS];
__device__ uint32_t g_flag_v[8 * 32 * FS];
__device__ uint32_t g_flag_o[2 * 16 * 4 * FS];
__device__ uint32_t g_epoch[NCTA * FS];

#define TS(i) do { } while (0)
#define TG(i) do { } while (0)
#define TSINIT() do { } while (0)
#define TSDUMP() do { } while (0)
constexpr uint32_t SMEM_LAUNCH = SMEM_BYTES;

__device__ __forceinline__ uint32_t smem_u32(const void* p) { return (uint32_t)__cvta_generic_to_shared(p); }
__device__ __forceinline__ void mbar_init(uint32_t b, uint32_t c) { asm volatile("mbarrier.init.shared::cta.b64 [%0], %1;" ::"r"(b), "r"(c) : "memory"); }
__device__ __forceinline__ void mbar_arrive(uint32_t b) { asm volatile("mbarrier.arrive.shared::cta.b64 _, [%0];" ::"r"(b) : "memory"); }
__device__ __forceinline__ void mbar_arrive_n(uint32_t b, uint32_t n) { asm volatile("mbarrier.arrive.shared::cta.b64 _, [%0], %1;" ::"r"(b), "r"(n) : "memory"); }
__device__ __forceinline__ void mbar_arrive_tx(uint32_t b, uint32_t tx) { asm volatile("mbarrier.arrive.expect_tx.shared::cta.b64 _, [%0], %1;" ::"r"(b), "r"(tx) : "memory"); }
__device__ __forceinline__ void mbar_expect_tx(uint32_t b, uint32_t tx) { asm volatile("mbarrier.expect_tx.relaxed.cta.shared::cta.b64 [%0], %1;" ::"r"(b), "r"(tx) : "memory"); }
__device__ __forceinline__ void mbar_wait(uint32_t b, uint32_t ph) {
    asm volatile("{\n.reg .pred p;\n.reg .u32 c;\nmov.u32 c, 0;\n"
                 "MW_LOOP:\n.pragma \"nounroll\";\n"
                 "mbarrier.try_wait.parity.shared::cta.b64 p, [%0], %1;\n@p bra MW_DONE;\n"
                 "add.u32 c, c, 1;\nsetp.lt.u32 p, c, 1048576;\n@p bra MW_LOOP;\ntrap;\n"
                 "MW_DONE:\n}" ::"r"(b), "r"(ph) : "memory");
}
__device__ __forceinline__ uint32_t mapa(uint32_t a, uint32_t r) { uint32_t o; asm("mapa.shared::cluster.u32 %0, %1, %2;" : "=r"(o) : "r"(a), "r"(r)); return o; }
__device__ __forceinline__ void fence_async_smem() { asm volatile("fence.proxy.async.shared::cta;" ::: "memory"); }
__device__ __forceinline__ void fence_async_global() { asm volatile("fence.proxy.async.global;" ::: "memory"); }
__device__ __forceinline__ void bar_sync(int id, int n) { asm volatile("bar.sync %0, %1;" ::"r"(id), "r"(n) : "memory"); }
__device__ __forceinline__ void bar_arrive(int id, int n) { asm volatile("bar.arrive %0, %1;" ::"r"(id), "r"(n) : "memory"); }
__device__ __forceinline__ void cluster_arrive() { asm volatile("barrier.cluster.arrive.relaxed.aligned;" ::: "memory"); }
__device__ __forceinline__ void cluster_wait() { asm volatile("barrier.cluster.wait.aligned;" ::: "memory"); }

__device__ __forceinline__ void ring_load(uint32_t dst, const CUtensorMap* tm, int c0, int c1, uint32_t bar) {
    asm volatile("{\n.reg .pred p;\nelect.sync _|p, 0xffffffff;\n"
                 "@p mbarrier.arrive.expect_tx.shared::cta.b64 _, [%2], 16384;\n"
                 "@p cp.async.bulk.tensor.2d.shared::cluster.global.mbarrier::complete_tx::bytes [%0], [%1, {%3, %4}], [%2];\n}"
                 ::"r"(dst), "l"(tm), "r"(bar), "r"(c0), "r"(c1) : "memory");
}
__device__ __forceinline__ void tma3d(uint32_t dst, const CUtensorMap* tm, int c0, int c1, int c2, uint32_t bar) {
    asm volatile("cp.async.bulk.tensor.3d.shared::cluster.global.mbarrier::complete_tx::bytes [%0], [%1, {%3, %4, %5}], [%2];"
                 ::"r"(dst), "l"(tm), "r"(bar), "r"(c0), "r"(c1), "r"(c2) : "memory");
}
__device__ __forceinline__ void bulk_g2s(uint32_t dst, const void* src, uint32_t bytes, uint32_t bar) {
    asm volatile("cp.async.bulk.shared::cluster.global.mbarrier::complete_tx::bytes [%0], [%1], %2, [%3];" ::"r"(dst), "l"(src), "r"(bytes), "r"(bar) : "memory");
}
__device__ __forceinline__ void peer_copy(uint32_t dst, uint32_t src, uint32_t bytes, uint32_t rbar, uint32_t lbar) {
    asm volatile("{\n.reg .pred p;\nelect.sync _|p, 0xffffffff;\n"
                 "@p cp.async.bulk.shared::cluster.shared::cta.mbarrier::complete_tx::bytes [%0], [%1], %2, [%3];\n"
                 "@p mbarrier.arrive.expect_tx.shared::cta.b64 _, [%4], %2;\n}"
                 ::"r"(dst), "r"(src), "r"(bytes), "r"(rbar), "r"(lbar) : "memory");
}
__device__ __forceinline__ void st_async4(uint32_t dst, uint32_t a, uint32_t b, uint32_t c, uint32_t d, uint32_t bar) {
    asm volatile("st.async.shared::cluster.mbarrier::complete_tx::bytes.v4.b32 [%0], {%1,%2,%3,%4}, [%5];" ::"r"(dst), "r"(a), "r"(b), "r"(c), "r"(d), "r"(bar) : "memory");
}
__device__ __forceinline__ void stsm4t(uint32_t a, uint32_t r0, uint32_t r1, uint32_t r2, uint32_t r3) {
    asm volatile("stmatrix.sync.aligned.m8n8.x4.trans.shared.b16 [%0], {%1,%2,%3,%4};" ::"r"(a), "r"(r0), "r"(r1), "r"(r2), "r"(r3) : "memory");
}
__device__ __forceinline__ void stsm4(uint32_t a, uint32_t r0, uint32_t r1, uint32_t r2, uint32_t r3) {
    asm volatile("stmatrix.sync.aligned.m8n8.x4.shared.b16 [%0], {%1,%2,%3,%4};" ::"r"(a), "r"(r0), "r"(r1), "r"(r2), "r"(r3) : "memory");
}
__device__ __forceinline__ void ldsm4t(uint32_t a, uint32_t& r0, uint32_t& r1, uint32_t& r2, uint32_t& r3) {
    asm volatile("ldmatrix.sync.aligned.m8n8.x4.trans.shared.b16 {%0,%1,%2,%3}, [%4];" : "=r"(r0), "=r"(r1), "=r"(r2), "=r"(r3) : "r"(a) : "memory");
}
__device__ __forceinline__ uint4 lds128(uint32_t a) { uint4 v; asm volatile("ld.shared.v4.b32 {%0,%1,%2,%3}, [%4];" : "=r"(v.x), "=r"(v.y), "=r"(v.z), "=r"(v.w) : "r"(a) : "memory"); return v; }
__device__ __forceinline__ float4 lds128f(uint32_t a) { float4 v; asm volatile("ld.shared.v4.f32 {%0,%1,%2,%3}, [%4];" : "=f"(v.x), "=f"(v.y), "=f"(v.z), "=f"(v.w) : "r"(a) : "memory"); return v; }
__device__ __forceinline__ float2 lds64f(uint32_t a) { float2 v; asm volatile("ld.shared.v2.f32 {%0,%1}, [%2];" : "=f"(v.x), "=f"(v.y) : "r"(a) : "memory"); return v; }
__device__ __forceinline__ uint32_t lds32(uint32_t a) { uint32_t v; asm volatile("ld.shared.b32 %0, [%1];" : "=r"(v) : "r"(a) : "memory"); return v; }
__device__ __forceinline__ void sts128(uint32_t a, uint32_t x, uint32_t y, uint32_t z, uint32_t w) { asm volatile("st.shared.v4.b32 [%0], {%1,%2,%3,%4};" ::"r"(a), "r"(x), "r"(y), "r"(z), "r"(w) : "memory"); }
__device__ __forceinline__ void sts128f(uint32_t a, float x, float y, float z, float w) { asm volatile("st.shared.v4.f32 [%0], {%1,%2,%3,%4};" ::"r"(a), "f"(x), "f"(y), "f"(z), "f"(w) : "memory"); }
__device__ __forceinline__ void sts64f(uint32_t a, float x, float y) { asm volatile("st.shared.v2.f32 [%0], {%1,%2};" ::"r"(a), "f"(x), "f"(y) : "memory"); }
__device__ __forceinline__ void sts32(uint32_t a, uint32_t x) { asm volatile("st.shared.b32 [%0], %1;" ::"r"(a), "r"(x) : "memory"); }
__device__ __forceinline__ void stg128(void* p, uint4 v) { asm volatile("st.global.v4.b32 [%0], {%1,%2,%3,%4};" ::"l"(p), "r"(v.x), "r"(v.y), "r"(v.z), "r"(v.w) : "memory"); }

__device__ __forceinline__ uint32_t pack2(float lo, float hi) { uint32_t r; asm("cvt.rn.bf16x2.f32 %0, %1, %2;" : "=r"(r) : "f"(hi), "f"(lo)); return r; }
__device__ __forceinline__ float blo(uint32_t v) { return __uint_as_float(v << 16); }
__device__ __forceinline__ float bhi(uint32_t v) { return __uint_as_float(v & 0xffff0000u); }
__device__ __forceinline__ float tanh_fast(float x) { float r; asm("tanh.approx.f32 %0, %1;" : "=f"(r) : "f"(x)); return r; }
__device__ __forceinline__ float ex2(float x) { float r; asm("ex2.approx.ftz.f32 %0, %1;" : "=f"(r) : "f"(x)); return r; }

__device__ __forceinline__ void flag_wait(const uint32_t* p, uint32_t e) {
#pragma unroll 1
    for (int i = 0; i < (1 << 22); i++) {
        uint32_t v;
        asm volatile("ld.acquire.gpu.global.u32 %0, [%1];" : "=r"(v) : "l"(p) : "memory");
        if (v == e) return;
    }
    __trap();
}
__device__ __forceinline__ uint32_t ld_epoch() {
    uint32_t v;
    asm volatile("ld.relaxed.gpu.global.u32 %0, [%1];" : "=r"(v) : "l"(&g_epoch[blockIdx.x * FS]) : "memory");
    return v + 1;
}
__device__ __forceinline__ void flag_set(uint32_t* p, uint32_t e) { asm volatile("st.release.gpu.global.u32 [%0], %1;" ::"l"(p), "r"(e) : "memory"); }

__device__ __forceinline__ uint64_t mkdesc(uint32_t addr) { return (uint64_t)(((addr & 0x3FFFF) >> 4) | 0x10000u) | (0x40000040ull << 32); }
__device__ __forceinline__ void wg_fence() { asm volatile("wgmma.fence.sync.aligned;" ::: "memory"); }
__device__ __forceinline__ void wg_commit() { asm volatile("wgmma.commit_group.sync.aligned;" ::: "memory"); }
template <int N> __device__ __forceinline__ void wg_wait() { asm volatile("wgmma.wait_group.sync.aligned %0;" ::"n"(N) : "memory"); }
template <int N> __device__ __forceinline__ void pin(float (&d)[N]) {
#pragma unroll
    for (int i = 0; i < N; i++) asm volatile("" : "+f"(d[i])::"memory");
}
template <int N> __device__ __forceinline__ void pin(uint32_t (&d)[N]) {
#pragma unroll
    for (int i = 0; i < N; i++) asm volatile("" : "+r"(d[i])::"memory");
}

template <typename Tp, int N> __device__ __forceinline__ void zero(Tp (&d)[N]) {
#pragma unroll
    for (int i = 0; i < N; i++) d[i] = 0;
    pin(d);
}

#define F4(d, i) "+f"(d[i]), "+f"(d[i + 1]), "+f"(d[i + 2]), "+f"(d[i + 3])
#define F16(d, i) F4(d, i), F4(d, i + 4), F4(d, i + 8), F4(d, i + 12)

__device__ __forceinline__ void mma_t(float (&d)[16], uint64_t a, uint64_t b, int acc) {
    asm volatile("{.reg .pred p; setp.ne.b32 p, %18, 0;\n"
                 "wgmma.mma_async.sync.aligned.m64n32k16.f32.bf16.bf16 {%0,%1,%2,%3,%4,%5,%6,%7,%8,%9,%10,%11,%12,%13,%14,%15}, %16, %17, p, 1, 1, 1, 0;}\n"
                 : F16(d, 0) : "l"(a), "l"(b), "r"(acc));
}
__device__ __forceinline__ void mma_t(float (&d)[20], uint64_t a, uint64_t b, int acc) {
    asm volatile("{.reg .pred p; setp.ne.b32 p, %22, 0;\n"
                 "wgmma.mma_async.sync.aligned.m64n40k16.f32.bf16.bf16 {%0,%1,%2,%3,%4,%5,%6,%7,%8,%9,%10,%11,%12,%13,%14,%15,%16,%17,%18,%19}, %20, %21, p, 1, 1, 1, 0;}\n"
                 : F16(d, 0), F4(d, 16) : "l"(a), "l"(b), "r"(acc));
}
__device__ __forceinline__ void mma_t(float (&d)[24], uint64_t a, uint64_t b, int acc) {
    asm volatile("{.reg .pred p; setp.ne.b32 p, %26, 0;\n"
                 "wgmma.mma_async.sync.aligned.m64n48k16.f32.bf16.bf16 {%0,%1,%2,%3,%4,%5,%6,%7,%8,%9,%10,%11,%12,%13,%14,%15,%16,%17,%18,%19,%20,%21,%22,%23}, %24, %25, p, 1, 1, 1, 0;}\n"
                 : F16(d, 0), F4(d, 16), F4(d, 20) : "l"(a), "l"(b), "r"(acc));
}
__device__ __forceinline__ void mma_qk(float (&d)[64], uint64_t a, uint64_t b, int acc) {
    asm volatile("{.reg .pred p; setp.ne.b32 p, %66, 0;\n"
                 "wgmma.mma_async.sync.aligned.m64n128k16.f32.bf16.bf16 {%0,%1,%2,%3,%4,%5,%6,%7,%8,%9,%10,%11,%12,%13,%14,%15,%16,%17,%18,%19,%20,%21,%22,%23,%24,%25,%26,%27,%28,%29,%30,%31,"
                 "%32,%33,%34,%35,%36,%37,%38,%39,%40,%41,%42,%43,%44,%45,%46,%47,%48,%49,%50,%51,%52,%53,%54,%55,%56,%57,%58,%59,%60,%61,%62,%63}, %64, %65, p, 1, 1, 0, 0;}\n"
                 : F16(d, 0), F16(d, 16), F16(d, 32), F16(d, 48) : "l"(a), "l"(b), "r"(acc));
}
__device__ __forceinline__ void mma_pv(float (&d)[32], uint32_t a0, uint32_t a1, uint32_t a2, uint32_t a3, uint64_t b) {
    asm volatile("wgmma.mma_async.sync.aligned.m64n64k16.f32.bf16.bf16 {%0,%1,%2,%3,%4,%5,%6,%7,%8,%9,%10,%11,%12,%13,%14,%15,%16,%17,%18,%19,%20,%21,%22,%23,%24,%25,%26,%27,%28,%29,%30,%31}, "
                 "{%32,%33,%34,%35}, %36, 1, 1, 1, 1;\n"
                 : F16(d, 0), F16(d, 16) : "r"(a0), "r"(a1), "r"(a2), "r"(a3), "l"(b));
}

template <uint32_t CSTRIDE, int N>
__device__ __forceinline__ void issue_half(float (&d)[N], uint32_t slot, uint32_t c0, int acc) {
    const uint64_t a = mkdesc(slot), b = mkdesc(c0);
    wg_fence();
#pragma unroll
    for (int k = 0; k < 8; k++) mma_t(d, a + k * 128, b + (k >> 2) * (CSTRIDE >> 4) + (k & 3) * 2, k == 0 ? acc : 1);
    wg_commit();
}

__device__ __forceinline__ uint32_t load_code(int n, int r, int w, int abh) {
    const int tile = 2 * r + w;
    int m, col, row;
    if (n < 16 || n >= 38) {
        const int k = n < 16 ? n : n - 38;
        m = n < 16 ? 1 : 7;
        if (k < 8) { col = 8 * r + (k & 6) + w; row = (k & 1) ^ r; }
        else { m++; col = k < 12 ? (tile ^ 2) : tile; row = 4 * r + (k & 3); }
    } else if (n < 22) {
        const int k = n - 16;
        m = 3;
        col = tile + (k < 2 ? 4 : (k < 4 ? 0 : 8)); row = (k & 1) ^ r;
    } else if (n < 30) {
        const int k = n - 22;
        const bool isv = (k == 7) || (k >= 2 && !(k & 1));
        const int i = isv ? (k == 7 ? 3 : (k >> 1) - 1) : ((k + 1) >> 1);
        m = 9; col = 0; row = (isv ? 128 : 0) + abh * 8 + 2 * i + w;
    } else if (n < 32) { m = 4; col = tile; row = n - 30; }
    else if (n < 36) { const int k = n - 32; m = 5; col = tile + 4 * (k & 1); row = (k >> 1) ^ r; }
    else { m = 6; col = tile; row = (n & 1) ^ r; }
    return m | (col << 4) | (row << 8);
}

struct Ring {
    uint32_t base, full, empty;
    uint32_t s, ph, rs;
    __device__ __forceinline__ uint32_t acquire() {
        mbar_wait(full + s * 8, ph);
        uint32_t a = base + s * SLOT;
        if (++s == NSLOT) { s = 0; ph ^= 1; }
        return a;
    }
    __device__ __forceinline__ void release(int lane) {
        if (lane == 0) mbar_arrive(empty + rs * 8);
        if (++rs == NSLOT) rs = 0;
    }
};

__global__ void __cluster_dims__(2, 1, 1) __launch_bounds__(NTHREADS, 1)
conformer_kernel(const __grid_constant__ Params p) {
    extern __shared__ __align__(1024) unsigned char smem_raw[];
    const uint32_t sb = smem_u32(smem_raw);
    const uint32_t bars = sb + OFF_BARS;
    const int tid = threadIdx.x;
    const int lane = tid & 31;
    const int warp = __shfl_sync(~0u, tid >> 5, 0);
    const int r = blockIdx.x & 1;
    const int pair = blockIdx.x >> 1;
    const int b = pair >> 5, pt = pair & 31;
    const int ah = pt >> 3, qt = (pt & 7) * 2 + r;
    const int abh = b * 4 + ah;

    TG(30);
    TSINIT();
    TS(0);
    if (warp >= 8 && warp < 10) {
        const int w = warp - 8;
        const uint32_t full = bars + (B_FULL + w * NSLOT) * 8;
        if (lane == 0) {
#pragma unroll
            for (int i = 0; i < NSLOT; i++) mbar_init(full + i * 8, 1);
            asm volatile("fence.mbarrier_init.release.cluster;" ::: "memory");
            fence_async_smem();
        }
        __syncwarp();
#pragma unroll
        for (int n = 0; n < NSLOT; n++)
            ring_load(sb + OFF_RING + (w * NSLOT + n) * SLOT, &p.tm[1], 64 * (8 * r + (n & 6) + w), 128 * ((n & 1) ^ r), full + n * 8);
    } else if (warp == 10) {
        if (lane == 0) {
#pragma unroll
            for (int i = 0; i < 4; i++) mbar_init(bars + (B_XF + i) * 8, (i >> 1) == r ? 4 : 1);
            asm volatile("fence.mbarrier_init.release.cluster;" ::: "memory");
            fence_async_smem();
#pragma unroll
            for (int i = 0; i < 4; i++) {
                const uint32_t bar = bars + (B_XF + i) * 8;
                mbar_expect_tx(bar, 4096);
                mbar_arrive_n(bar, (i >> 1) == r ? 4 : 1);
                tma3d(sb + OFF_P + i * XCH, &p.tm[0], i * 64, pt * 32, b, bar);
            }
        }
    } else if (warp == 11) {
        if (lane < 9) {
            uint32_t kb = (lane < 2 || lane > 5) ? 4096 : (lane == 2 ? 3072 : (lane == 4 ? 2048 : 1024));
            size_t off = (size_t)blockIdx.x * kb;
            if (lane == 8) { kb = 8192; off = (size_t)min(b * T_ + pt * 32 + r * 16, 2 * T_ - 16) * 512; }
            asm volatile("cp.async.bulk.prefetch.L2.global [%0], %1;" ::"l"(p.w[lane] + off), "r"(kb) : "memory");
        }
    } else if (warp == 12) {
        if (lane >= 2 && lane < 10) asm volatile("prefetch.tensormap [%0];" ::"l"(&p.tm[lane]) : "memory");
    } else if (warp < 8) {
        if (lane == 0) {
            mbar_init(bars + (B_EMPTY + warp) * 8, 4);
            mbar_init(bars + (B_HF + warp) * 8, warp < 4 ? 8 : 1);
            if (warp < 4) mbar_init(bars + (B_XF + 4 + warp) * 8, (warp >> 1) == r ? 4 : 1);
            else if (warp < 7) mbar_init(bars + (warp == 6 ? B_ST : B_EMPTY + 4 + warp) * 8, 4);
            asm volatile("fence.mbarrier_init.release.cluster;" ::: "memory");
        }
        sts128(sb + OFF_P + (tid >> 6) * XCH + 4096 + (tid & 63) * 16, 0x3F803F80u, 0x3F803F80u, 0x3F803F80u, 0x3F803F80u);
        fence_async_smem();
    }
    __syncthreads();
    cluster_arrive();
    const uint32_t P = sb + OFF_P, H = sb + OFF_H;
    auto xwait = [&](int stage, int half) {
        const uint32_t bar = bars + (B_XF + (stage & 1) * 4 + 2 * half) * 8;
        mbar_wait(bar, (stage >> 1) & 1);
        mbar_wait(bar + 8, (stage >> 1) & 1);
    };

    if (warp >= 8) {
        asm volatile("setmaxnreg.dec.sync.aligned.u32 40;");
        TS(1);
        if (warp >= 12) {
            const int ut = tid & 127, part = lane & 3;
#pragma unroll 1
            for (int k = 0; k < 4; k++) {
                const int stage = k == 0 ? 0 : 2 * k - 1;
#pragma unroll 1
                for (int row = ut >> 2; row < (k == 2 ? 48 : 32); row += 32) {
                    float s = 0.f, q = 0.f;
#pragma unroll
                    for (int h = 0; h < 2; h++) {
                        xwait(stage, r ^ h);
#pragma unroll
                        for (int i = 0; i < 4; i++) {
                            const uint4 v = lds128(P + (2 * (r ^ h) + (i >> 1)) * XCH + row * 128 + (2 * part + ((i ^ row) & 1)) * 16);
                            const float a0 = blo(v.x), a1 = bhi(v.x), a2 = blo(v.y), a3 = bhi(v.y), a4 = blo(v.z), a5 = bhi(v.z), a6 = blo(v.w), a7 = bhi(v.w);
                            s += ((a0 + a1) + (a2 + a3)) + ((a4 + a5) + (a6 + a7));
                            q += fmaf(a0, a0, fmaf(a1, a1, fmaf(a2, a2, a3 * a3))) + fmaf(a4, a4, fmaf(a5, a5, fmaf(a6, a6, a7 * a7)));
                        }
                    }
                    s += __shfl_xor_sync(~0u, s, 1); q += __shfl_xor_sync(~0u, q, 1);
                    s += __shfl_xor_sync(~0u, s, 2); q += __shfl_xor_sync(~0u, q, 2);
                    const float mean = s * (1.f / 256.f);
                    const float rstd = 0.5f * rsqrtf(fmaxf(fmaf(-mean, mean, q * (1.f / 256.f)), 0.f) + 1e-5f);
                    if (part == 0) sts64f(sb + OFF_STATS + row * 8, mean * rstd, rstd);
                }
                __syncwarp();
                if (lane == 0) mbar_arrive(bars + B_ST * 8);
                TS(2 + k);
                if (k == 1) {
#pragma unroll 1
                    for (int i = -1; i < 3; i++) {
                        uint32_t src = P + 2 * r * XCH, ss = XCH, ds = PADROWS * 128;
                        unsigned char* dst = g_x1 + 1024;
                        if (i >= 0) {
                            src = H + 2 * i * HCH; ss = HCH; ds = 1024 * 128; dst = g_kqv + i * 1048576;
                            mbar_wait(bars + (B_HF + i) * 8, 1);
                        }
                        src += ut * 16;
                        dst += (size_t)(b * 4 + 2 * r) * ds + pt * 4096 + ut * 16;
                        const uint4 v0 = lds128(src), v1 = lds128(src + 2048), v2 = lds128(src + ss), v3 = lds128(src + ss + 2048);
                        stg128(dst, v0); stg128(dst + 2048, v1); stg128(dst + ds, v2); stg128(dst + ds + 2048, v3);
                        if (i >= 1) bar_arrive(3 + i, 160);
                        TS(10 + i);
                    }
                }
            }
        } else if (warp < 10) {
            const int w = warp - 8;
            const uint32_t code = load_code(lane, r, w, abh) | (load_code(lane + 32, r, w, abh) << 16);
            const uint32_t ring = sb + OFF_RING + w * NSLOT * SLOT;
            const uint32_t full = bars + (B_FULL + w * NSLOT) * 8;
            uint32_t s = 0, ph = 0;
            int n = NSLOT;
#pragma unroll 1
            for (int seg = 0; seg < 3; seg++) {
                const int end = seg == 0 ? 22 : (seg == 1 ? 24 : NLOADS);
#pragma unroll 1
                for (; n < end; n++) {
                    const uint32_t c = __shfl_sync(~0u, code, n) >> (n & 32 ? 16 : 0);
                    mbar_wait(full + (B_EMPTY - B_FULL) * 8 + s * 8, ph);
                    ring_load(ring + s * SLOT, &p.tm[c & 15], (c & 0xf0) * 4, (c & 0xff00) >> 1, full + s * 8);
                    if (++s == NSLOT) { s = 0; ph ^= 1; }
                }
                if (seg < 2) {
                    flag_wait((seg == 0 ? g_flag_qk : g_flag_v) + (abh * 32 + lane) * FS, ld_epoch());
                    __syncwarp();
                    fence_async_global();
                    TS(5 + seg);
                }
            }
        } else if (warp == 10) {
            const uint32_t epoch = ld_epoch();
            if (lane < 2) flag_wait(&g_flag_qk[(abh * 32 + 2 * qt + lane) * FS], epoch);
            __syncwarp();
            if (lane == 0) {
                fence_async_global();
                mbar_arrive_tx(bars + B_QIN * 8, 8192);
                bulk_g2s(H + 24576, g_kqv + 1048576 + (size_t)(abh * 1024 + qt * 64) * 128, 8192, bars + B_QIN * 8);
            }
            if (lane < 12) {
                const int np = pt - 1 + (lane >> 2);
                if (np >= 0 && np < 32) flag_wait(&g_flag_v[((b * 4 + (lane & 3)) * 32 + np) * FS], epoch);
            }
            __syncwarp();
            if (lane == 0) {
                fence_async_global();
                mbar_arrive_tx(bars + B_X1IN * 8, 2 * XCH);
                for (int w = 0; w < 2; w++)
                    bulk_g2s(P + (2 * r + w) * XCH, g_x1 + (size_t)((b * 4 + 2 * r + w) * PADROWS + pt * 32) * 128, XCH, bars + B_X1IN * 8);
            }
            if (lane < 4) {
                const uint32_t bar = bars + (B_XF + lane) * 8;
                mbar_expect_tx(bar, XCH);
                mbar_arrive_n(bar, (lane >> 1) == r ? 4 : 1);
            }
            __syncwarp();
            bar_sync(9, 64);
            if (lane < 8) {
                const int q = (pt >> 1) + (lane < 4 ? 0 : ((pt & 1) ? 1 : -1));
                if (q >= 0 && q < 16) flag_wait(&g_flag_o[((b * 16 + q) * 4 + (lane & 3)) * FS], epoch);
            }
            __syncwarp();
            if (lane == 0) {
                fence_async_global();
#pragma unroll
                for (int i = 0; i < 4; i++)
                    bulk_g2s(H + i * XCH, g_o + (size_t)((b * 4 + i) * PADROWS + pt * 32) * 128, XCH, bars + (B_XF + i) * 8);
            }
            __syncwarp();
        } else {
            const uint32_t epoch = ld_epoch();
            bar_sync(4, 160);
            if (lane < 2) flag_set(&g_flag_qk[((b * 4 + 2 * r + lane) * 32 + pt) * FS], epoch);
            __syncwarp();
            bar_sync(5, 160);
            if (lane < 2) flag_set(&g_flag_v[((b * 4 + 2 * r + lane) * 32 + pt) * FS], epoch);
            __syncwarp();
            bar_sync(6, 288);
            bar_arrive(9, 64);
            if (lane == 0) {
                flag_set(&g_flag_o[((b * 16 + qt) * 4 + ah) * FS], epoch);
                g_epoch[blockIdx.x * FS] = epoch;
            }
            __syncwarp();
        }
        TSDUMP();
        cluster_wait();
        return;
    }

    asm volatile("setmaxnreg.inc.sync.aligned.u32 216;");
    const int w = warp >> 2, wq = warp & 3;
    const int tile = 2 * r + w;
    const int wt = tid & 127;
    const int c4 = lane & 3;
    Ring ring{sb + OFF_RING + w * NSLOT * SLOT, bars + (B_FULL + w * NSLOT) * 8, bars + (B_EMPTY + w * NSLOT) * 8, 0, 0, 0};
    const uint32_t toff = ((lane >> 4) * 8 + (lane & 7)) * 128 + (((2 * wq + ((lane >> 3) & 1)) ^ (lane & 7)) << 4);
    const uint32_t xa = P + tile * XCH + toff;
    auto turn_wait = [&]() { bar_sync(7 + w, 256); };
    auto turn_pass = [&]() { bar_arrive(8 - w, 256); };
    if (w == 1) turn_pass();

    auto publish = [&](int stage, uint32_t chunk, uint32_t off, uint32_t bytes) {
        const uint32_t bar = bars + (B_XF + (stage & 1) * 4 + tile) * 8;
        fence_async_smem();
        __syncwarp();
        if (lane == 0) mbar_arrive(bar);
        if (wq == 0) {
            mbar_wait(bar, (stage >> 1) & 1);
            peer_copy(mapa(chunk + off, r ^ 1), chunk + off, bytes, mapa(bar, r ^ 1), bar ^ 16);
        }
    };

#pragma unroll 1
    for (int ph = 0; ph < 3; ph++) {
        {
            const int stage = ph == 2 ? 5 : ph;
            float st[16], d[20];
            zero(st); zero(d);
#pragma unroll 1
            for (int i = 0; i < (ph == 1 ? 3 : 4); i++) {
                uint32_t sl = ring.acquire();
                if (i == 0) { xwait(stage, r); TS(1 + ph * 10); } else turn_wait();
                issue_half<XCH>(d, sl, P + 2 * r * XCH, 0);
                sl = ring.acquire();
                if (i == 0) { xwait(stage, r ^ 1); turn_wait(); }
                issue_half<XCH>(d, sl, P + 2 * (r ^ 1) * XCH, 1);
                turn_pass();
                if (i == 0) {
                    mbar_wait(bars + B_ST * 8, ph != 0);
#pragma unroll
                    for (int j = 0; j < 4; j++) {
                        const float4 v = lds128f(sb + OFF_STATS + (8 * j + 2 * c4) * 8);
                        st[4 * j] = v.x; st[4 * j + 1] = v.y; st[4 * j + 2] = v.z; st[4 * j + 3] = v.w;
                    }
                }
                wg_wait<1>();
                ring.release(lane);
                wg_wait<0>();
                pin(d);
                ring.release(lane);
                float t[16];
#pragma unroll
                for (int k = 0; k < 16; k++) {
                    d[k] = fmaf(-st[(k & 12) + 2 * (k & 1)], d[16 + (k & 2)], d[k] * st[(k & 12) + 2 * (k & 1) + 1]);
                    t[k] = 1.f;
                }
                if (ph != 1) {
#pragma unroll
                    for (int k = 0; k < 16; k++) t[k] = tanh_fast(d[k]);
                }
                uint32_t pk[8];
#pragma unroll
                for (int k = 0; k < 8; k++) pk[k] = pack2(fmaf(d[2 * k], t[2 * k], d[2 * k]), fmaf(d[2 * k + 1], t[2 * k + 1], d[2 * k + 1]));
                const uint32_t dst = H + (2 * i + w) * HCH + toff;
                stsm4t(dst, pk[0], pk[1], pk[2], pk[3]);
                stsm4t(dst + 2048, pk[4], pk[5], pk[6], pk[7]);
                fence_async_smem();
                __syncwarp();
                if (lane == 0) mbar_arrive(bars + (B_HF + i) * 8);
            }
            TS(2 + ph * 10);
        }
        if (ph != 1) {
            const uint32_t inb = bars + (B_INB + w) * 8, box = sb + OFF_INBOX + w * 4096 + wt * 16;
            float d[16];
            uint32_t xr[8], pr[8];
            zero(d); zero(xr); zero(pr);
            if (wt == 0) mbar_arrive_tx(inb, 4096);
            if (ph == 0) cluster_wait();
#pragma unroll 1
            for (int t = 0; t < 2; t++) {
#pragma unroll 1
                for (int q = 0; q < 4; q++) {
                    const uint32_t sl = ring.acquire();
                    if (t == 0) mbar_wait(bars + (B_HF + q) * 8, 0);
                    issue_half<HCH>(d, sl, H + 2 * q * HCH, q);
                    wg_wait<1>();
                    if (q) ring.release(lane);
                }
                if (t == 1) {
                    ldsm4t(xa, xr[0], xr[1], xr[2], xr[3]);
                    ldsm4t(xa + 2048, xr[4], xr[5], xr[6], xr[7]);
                    mbar_wait(inb, ph >> 1);
                    const uint4 u = lds128(box), v = lds128(box + 2048);
                    pr[0] = u.x; pr[1] = u.y; pr[2] = u.z; pr[3] = u.w; pr[4] = v.x; pr[5] = v.y; pr[6] = v.z; pr[7] = v.w;
                }
                wg_wait<0>();
                pin(d);
                ring.release(lane);
                if (t == 0) {
                    const uint32_t dst = mapa(box, r ^ 1), bar = mapa(inb, r ^ 1);
                    st_async4(dst, pack2(d[0], d[1]), pack2(d[2], d[3]), pack2(d[4], d[5]), pack2(d[6], d[7]), bar);
                    st_async4(dst + 2048, pack2(d[8], d[9]), pack2(d[10], d[11]), pack2(d[12], d[13]), pack2(d[14], d[15]), bar);
                }
            }
            TS(3 + ph * 10);
#pragma unroll
            for (int i = 0; i < 8; i++)
                xr[i] = pack2(fmaf(0.5f, d[2 * i] + blo(pr[i]), blo(xr[i])), fmaf(0.5f, d[2 * i + 1] + bhi(pr[i]), bhi(xr[i])));
            stsm4t(xa, xr[0], xr[1], xr[2], xr[3]);
            stsm4t(xa + 2048, xr[4], xr[5], xr[6], xr[7]);
            publish(ph ? 6 : 1, P + tile * XCH, ph ? (r ^ 1) * 2048 : 0, ph ? 2048 : 4096);
            continue;
        }
        if (lane == 0) mbar_arrive(bars + (B_HF + 3) * 8);

        {
            constexpr float CS = 0.125f * 1.4426950408889634f;
            float s[64], o[32];
            uint32_t pp[32];
            float m0 = -INFINITY, m1 = -INFINITY, l0 = 0.f, l1 = 0.f;
            zero(o); zero(pp);
            const uint64_t qd = mkdesc(H + 24576);
            auto qk_issue = [&](uint32_t slot) {
                const uint64_t kd = mkdesc(slot);
                wg_fence();
#pragma unroll
                for (int k = 0; k < 4; k++) mma_qk(s, qd + 2 * k, kd + 2 * k, k != 0);
                wg_commit();
            };
            auto pv_issue = [&](uint32_t slot) {
                const uint64_t vd = mkdesc(slot);
                wg_fence();
#pragma unroll
                for (int k = 0; k < 8; k++) mma_pv(o, pp[4 * k], pp[4 * k + 1], pp[4 * k + 2], pp[4 * k + 3], vd + k * 128);
                wg_commit();
            };
            float sc0, sc1;
            auto softmax = [&](bool mask) {
                if (mask) {
#pragma unroll
                    for (int i = 52; i < 64; i++) s[i] = -INFINITY;
                }
                float x0 = m0, x1 = m1;
#pragma unroll
                for (int j = 0; j < 16; j++) {
                    x0 = fmaxf(x0, fmaxf(s[4 * j], s[4 * j + 1]));
                    x1 = fmaxf(x1, fmaxf(s[4 * j + 2], s[4 * j + 3]));
                }
                x0 = fmaxf(x0, __shfl_xor_sync(~0u, x0, 1)); x1 = fmaxf(x1, __shfl_xor_sync(~0u, x1, 1));
                x0 = fmaxf(x0, __shfl_xor_sync(~0u, x0, 2)); x1 = fmaxf(x1, __shfl_xor_sync(~0u, x1, 2));
                sc0 = ex2((m0 - x0) * CS); sc1 = ex2((m1 - x1) * CS);
                m0 = x0; m1 = x1;
                const float n0 = -x0 * CS, n1 = -x1 * CS;
                float r0 = 0.f, r1 = 0.f;
#pragma unroll
                for (int j = 0; j < 16; j++) {
                    s[4 * j] = ex2(fmaf(s[4 * j], CS, n0)); s[4 * j + 1] = ex2(fmaf(s[4 * j + 1], CS, n0));
                    s[4 * j + 2] = ex2(fmaf(s[4 * j + 2], CS, n1)); s[4 * j + 3] = ex2(fmaf(s[4 * j + 3], CS, n1));
                    r0 += s[4 * j] + s[4 * j + 1]; r1 += s[4 * j + 2] + s[4 * j + 3];
                }
                l0 = fmaf(l0, sc0, r0); l1 = fmaf(l1, sc1, r1);
            };
            auto to_p = [&]() {
#pragma unroll
                for (int i = 0; i < 32; i++) pp[i] = pack2(s[2 * i], s[2 * i + 1]);
#pragma unroll
                for (int j = 0; j < 8; j++) { o[4 * j] *= sc0; o[4 * j + 1] *= sc0; o[4 * j + 2] *= sc1; o[4 * j + 3] *= sc1; }
            };
            mbar_wait(bars + B_QIN * 8, 0);
            {
                const uint32_t sl = ring.acquire();
                TS(13);
                turn_wait();
                qk_issue(sl);
                turn_pass();
                wg_commit();
            }
#pragma unroll 1
            for (int it = 0;; it++) {
                wg_wait<1>();
                pin(s);
                ring.release(lane);
                softmax(it == 3 && w == 1);
                pin(s);
                wg_wait<0>();
                pin(o); pin(pp);
                if (it) ring.release(lane);
                to_p();
                pin(s); pin(o); pin(pp);
                if (it == 3) break;
                const uint32_t sl = ring.acquire();
                turn_wait();
                qk_issue(sl);
                pv_issue(ring.acquire());
                turn_pass();
            }
            pv_issue(ring.acquire());
            l0 += __shfl_xor_sync(~0u, l0, 1); l1 += __shfl_xor_sync(~0u, l1, 1);
            l0 += __shfl_xor_sync(~0u, l0, 2); l1 += __shfl_xor_sync(~0u, l1, 2);
            const int row = wq * 16 + (lane >> 2);
            const uint32_t ml = sb + OFF_INBOX;
            if (c4 == 0) { sts64f(ml + w * 512 + row * 8, m0, l0); sts64f(ml + w * 512 + row * 8 + 64, m1, l1); }
            wg_wait<0>();
            pin(o); pin(pp);
            ring.release(lane);
            TS(14);
            float mine[16];
#pragma unroll
            for (int j = 0; j < 4; j++) {
                if (w == 0) sts128f(H + j * 2048 + wt * 16, o[16 + 4 * j], o[17 + 4 * j], o[18 + 4 * j], o[19 + 4 * j]);
                else sts128f(H + 8192 + j * 2048 + wt * 16, o[4 * j], o[4 * j + 1], o[4 * j + 2], o[4 * j + 3]);
            }
#pragma unroll
            for (int i = 0; i < 16; i++) mine[i] = w == 0 ? o[i] : o[16 + i];
            bar_sync(1, 256);
            const float2 u0 = lds64f(ml + (w ^ 1) * 512 + row * 8), u1 = lds64f(ml + (w ^ 1) * 512 + row * 8 + 64);
            const float x0 = fmaxf(m0, u0.x), x1 = fmaxf(m1, u1.x);
            float a0 = ex2((m0 - x0) * CS), b0 = ex2((u0.x - x0) * CS), a1 = ex2((m1 - x1) * CS), b1 = ex2((u1.x - x1) * CS);
            const float i0 = __fdividef(1.f, fmaf(a0, l0, b0 * u0.y)), i1 = __fdividef(1.f, fmaf(a1, l1, b1 * u1.y));
            a0 *= i0; b0 *= i0; a1 *= i1; b1 *= i1;
            uint32_t pk[8];
#pragma unroll
            for (int j = 0; j < 4; j++) {
                const float4 v = lds128f(H + (w ^ 1) * 8192 + j * 2048 + wt * 16);
                pk[2 * j] = pack2(fmaf(a0, mine[4 * j], b0 * v.x), fmaf(a0, mine[4 * j + 1], b0 * v.y));
                pk[2 * j + 1] = pack2(fmaf(a1, mine[4 * j + 2], b1 * v.z), fmaf(a1, mine[4 * j + 3], b1 * v.w));
            }
            const uint32_t og = H + 16384 + wq * 2048;
            {
                const uint32_t ra = og + (((lane >> 3) & 1) * 8 + (lane & 7)) * 128;
                stsm4(ra + (((4 * w + (lane >> 4)) ^ (lane & 7)) << 4), pk[0], pk[1], pk[2], pk[3]);
                stsm4(ra + (((4 * w + 2 + (lane >> 4)) ^ (lane & 7)) << 4), pk[4], pk[5], pk[6], pk[7]);
            }
            __syncwarp();
            {
                const uint32_t off = (lane >> 2) * 128 + (((4 * w + c4) ^ (lane >> 2)) << 4);
                const uint4 v0 = lds128(og + off), v1 = lds128(og + off + 1024);
                unsigned char* dst = g_o + (size_t)(abh * PADROWS + 8 + qt * 64 + wq * 16) * 128 + off;
                stg128(dst, v0); stg128(dst + 1024, v1);
            }
            bar_arrive(6, 288);
            TS(15);
        }

        uint32_t x2r[8];
        uint32_t dwr[15];
        {
#pragma unroll
            for (int i = 0; i < 15; i++) dwr[i] = __ldg(reinterpret_cast<const uint32_t*>(p.dw + i * 256 + tile * 64) + lane);
            float d[24];
            uint32_t xr[12];
            zero(d);
            mbar_wait(bars + B_X1IN * 8, 0);
#pragma unroll
            for (int j = 0; j < 3; j++) ldsm4t(xa + j * 2048, xr[4 * j], xr[4 * j + 1], xr[4 * j + 2], xr[4 * j + 3]);
#pragma unroll 1
            for (int h = 0; h < 2; h++) {
                const uint32_t sl = ring.acquire();
                xwait(2, h);
                if (h == 0) TS(16);
                issue_half<XCH>(d, sl, H + 2 * h * XCH, 1);
            }
            wg_wait<0>();
            pin(d);
            ring.release(lane); ring.release(lane);
#pragma unroll
            for (int i = 0; i < 12; i++) xr[i] = pack2(d[2 * i] + blo(xr[i]), d[2 * i + 1] + bhi(xr[i]));
            if (c4 == 0) { xr[0] = (xr[0] & 0xffff0000u) | 0x3F80u; xr[1] = (xr[1] & 0xffff0000u) | 0x3F80u; }
#pragma unroll
            for (int j = 0; j < 3; j++) stsm4t(xa + j * 2048, xr[4 * j], xr[4 * j + 1], xr[4 * j + 2], xr[4 * j + 3]);
#pragma unroll
            for (int i = 0; i < 8; i++) x2r[i] = xr[2 + i];
            publish(3, P + tile * XCH, 0, XCH);
            TS(17);
        }
        {
            float da[24], db[24];
            zero(da); zero(db);
#pragma unroll 1
            for (int h = 0; h < 2; h++) {
                uint32_t sl = ring.acquire();
                xwait(3, r ^ h);
                issue_half<XCH>(da, sl, P + 2 * (r ^ h) * XCH, 1);
                sl = ring.acquire();
                issue_half<XCH>(db, sl, P + 2 * (r ^ h) * XCH, 1);
            }
            mbar_wait(bars + B_ST * 8, 0);
            float st[24];
#pragma unroll
            for (int j = 0; j < 6; j++) {
                float4 v = lds128f(sb + OFF_STATS + (8 * j + 2 * c4) * 8);
                st[4 * j] = v.x; st[4 * j + 1] = v.y; st[4 * j + 2] = v.z; st[4 * j + 3] = v.w;
            }
            wg_wait<2>();
            ring.release(lane); ring.release(lane);
            wg_wait<0>();
            pin(da); pin(db);
            ring.release(lane); ring.release(lane);
            TS(18);
            uint32_t pk[12];
#pragma unroll
            for (int hh = 0; hh < 2; hh++) {
                const float ca = __shfl_sync(~0u, da[2 * hh], lane & 28), cb = __shfl_sync(~0u, db[2 * hh], lane & 28);
#pragma unroll
                for (int j = 0; j < 6; j++) {
                    const float u0 = fmaf(-st[4 * j], ca, da[4 * j + 2 * hh] * st[4 * j + 1]);
                    const float u1 = fmaf(-st[4 * j + 2], ca, da[4 * j + 2 * hh + 1] * st[4 * j + 3]);
                    const float v0 = fmaf(-st[4 * j], cb, db[4 * j + 2 * hh] * st[4 * j + 1]);
                    const float v1 = fmaf(-st[4 * j + 2], cb, db[4 * j + 2 * hh + 1] * st[4 * j + 3]);
                    const uint32_t g = pack2(fmaf(u0, tanh_fast(v0), u0), fmaf(u1, tanh_fast(v1), u1));
                    const int t0 = pt * 32 - 8 + 8 * j;
                    pk[2 * j + hh] = (t0 >= 0 && t0 < T_) ? g : 0u;
                }
            }
            const uint32_t gs = H + 16384 + w * XCH;
#pragma unroll
            for (int j = 0; j < 3; j++) stsm4t(gs + toff + j * 2048, pk[4 * j], pk[4 * j + 1], pk[4 * j + 2], pk[4 * j + 3]);
            bar_sync(2 + w, 128);
            float c0[8], c1[8];
#pragma unroll
            for (int i = 0; i < 8; i++) { c0[i] = 0.f; c1[i] = 0.f; }
#pragma unroll
            for (int k = 0; k < 22; k++) {
                const uint32_t v = lds32(gs + (8 * wq + 1 + k) * 128 + (((lane >> 2) ^ ((1 + k) & 7)) << 4) + c4 * 4);
                const float v0 = blo(v), v1 = bhi(v);
#pragma unroll
                for (int i = 0; i < 8; i++)
                    if (k - i >= 0 && k - i < 15) { c0[i] = fmaf(v0, blo(dwr[k - i]), c0[i]); c1[i] = fmaf(v1, bhi(dwr[k - i]), c1[i]); }
            }
#pragma unroll
            for (int i = 0; i < 8; i++) {
                const float h0 = 0.5f * c0[i], h1 = 0.5f * c1[i];
                sts32(H + tile * HCH + (8 * wq + i) * 128 + (((lane >> 2) ^ i) << 4) + c4 * 4,
                      pack2(fmaf(h0, tanh_fast(h0), h0), fmaf(h1, tanh_fast(h1), h1)));
            }
            publish(4, H + tile * HCH, 0, HCH);
            TS(19);
        }
        {
            float d[16];
            zero(d);
#pragma unroll 1
            for (int h = 0; h < 2; h++) {
                const uint32_t sl = ring.acquire();
                xwait(4, r ^ h);
                issue_half<HCH>(d, sl, H + 2 * (r ^ h) * HCH, 1);
            }
            sts128(P + (wt >> 6 ? (tile ^ 2) : tile) * XCH + 4096 + (wt & 63) * 16, 0x3F803F80u, 0x3F803F80u, 0x3F803F80u, 0x3F803F80u);
            wg_wait<0>();
            pin(d);
            ring.release(lane); ring.release(lane);
#pragma unroll
            for (int i = 0; i < 8; i++) x2r[i] = pack2(d[2 * i] + blo(x2r[i]), d[2 * i + 1] + bhi(x2r[i]));
            stsm4t(xa, x2r[0], x2r[1], x2r[2], x2r[3]);
            stsm4t(xa + 2048, x2r[4], x2r[5], x2r[6], x2r[7]);
            publish(5, P + tile * XCH, 0, HCH);
            TS(20);
        }
    }

    if (w == 0) turn_wait();
    xwait(6, r);
    xwait(6, r ^ 1);
    cluster_arrive();
    TS(24);
    {
        float a[2][8], s[2], q[2];
        const int row0 = 16 * r + 2 * warp;
#pragma unroll
        for (int i = 0; i < 2; i++) {
            const uint4 v = lds128(P + (lane >> 3) * XCH + (row0 + i) * 128 + (((lane & 7) ^ ((row0 + i) & 7)) << 4));
            a[i][0] = blo(v.x); a[i][1] = bhi(v.x); a[i][2] = blo(v.y); a[i][3] = bhi(v.y);
            a[i][4] = blo(v.z); a[i][5] = bhi(v.z); a[i][6] = blo(v.w); a[i][7] = bhi(v.w);
            s[i] = ((a[i][0] + a[i][1]) + (a[i][2] + a[i][3])) + ((a[i][4] + a[i][5]) + (a[i][6] + a[i][7]));
            q[i] = 0.f;
#pragma unroll
            for (int k = 0; k < 8; k++) q[i] = fmaf(a[i][k], a[i][k], q[i]);
        }
#pragma unroll
        for (int o = 16; o > 0; o >>= 1) {
#pragma unroll
            for (int i = 0; i < 2; i++) { s[i] += __shfl_xor_sync(~0u, s[i], o); q[i] += __shfl_xor_sync(~0u, q[i], o); }
        }
#pragma unroll
        for (int i = 0; i < 2; i++) {
            const float mean = s[i] * (1.f / 256.f);
            const float rstd = rsqrtf(fmaxf(fmaf(-mean, mean, q[i] * (1.f / 256.f)), 0.f) + 1e-5f);
            const float nb = -mean * rstd;
            uint4 v;
            v.x = pack2(fmaf(a[i][0], rstd, nb), fmaf(a[i][1], rstd, nb)); v.y = pack2(fmaf(a[i][2], rstd, nb), fmaf(a[i][3], rstd, nb));
            v.z = pack2(fmaf(a[i][4], rstd, nb), fmaf(a[i][5], rstd, nb)); v.w = pack2(fmaf(a[i][6], rstd, nb), fmaf(a[i][7], rstd, nb));
            const int t = pt * 32 + row0 + i;
            if (t < T_) stg128(p.out + (size_t)(b * T_ + t) * 256 + lane * 8, v);
        }
    }
    TS(25);
    TG(31);
    TSDUMP();
    cluster_wait();
}

typedef CUresult (*EncodeFn)(CUtensorMap*, CUtensorMapDataType, cuuint32_t, void*, const cuuint64_t*, const cuuint64_t*,
                             const cuuint32_t*, const cuuint32_t*, CUtensorMapInterleave, CUtensorMapSwizzle,
                             CUtensorMapL2promotion, CUtensorMapFloatOOBfill);

}

extern "C" void kernel_launch(void* const* d_in, const int* in_sizes, int n_in, void* d_out, int out_size) {
    static EncodeFn encode = nullptr;
    if (!encode) {
        void* fn = nullptr;
        cudaDriverEntryPointQueryResult qr;
        cudaGetDriverEntryPoint("cuTensorMapEncodeTiled", &fn, cudaEnableDefault, &qr);
        encode = (EncodeFn)fn;
        cudaFuncSetAttribute(conformer_kernel, cudaFuncAttributeMaxDynamicSharedMemorySize, SMEM_LAUNCH);
    }
    Params p;
    const cuuint32_t ones[3] = {1, 1, 1};
    {
        const cuuint64_t dims[3] = {256, T_, 2};
        const cuuint64_t strides[2] = {512, 512ull * T_};
        const cuuint32_t box[3] = {64, 32, 1};
        encode(&p.tm[0], CU_TENSOR_MAP_DATA_TYPE_BFLOAT16, 3, d_in[0], dims, strides, box, ones, CU_TENSOR_MAP_INTERLEAVE_NONE,
               CU_TENSOR_MAP_SWIZZLE_128B, CU_TENSOR_MAP_L2_PROMOTION_L2_256B, CU_TENSOR_MAP_FLOAT_OOB_FILL_NONE);
    }
    const int idx[8] = {1, 2, 3, 4, 5, 7, 8, 9};
    const int rows[8] = {256, 1024, 256, 256, 256, 256, 256, 1024};
    const int cols[8] = {1024, 256, 768, 256, 512, 256, 1024, 256};
    for (int i = 0; i < 8; i++) {
        const cuuint64_t dims[2] = {(cuuint64_t)cols[i], (cuuint64_t)rows[i]};
        const cuuint64_t strides[1] = {(cuuint64_t)cols[i] * 2};
        const cuuint32_t box[2] = {64, 128};
        encode(&p.tm[1 + i], CU_TENSOR_MAP_DATA_TYPE_BFLOAT16, 2, d_in[idx[i]], dims, strides, box, ones, CU_TENSOR_MAP_INTERLEAVE_NONE,
               CU_TENSOR_MAP_SWIZZLE_128B, CU_TENSOR_MAP_L2_PROMOTION_L2_128B, CU_TENSOR_MAP_FLOAT_OOB_FILL_NONE);
        p.w[i] = (const char*)d_in[idx[i]];
    }
    {
        void* kv = nullptr;
        cudaGetSymbolAddress(&kv, g_kqv);
        const cuuint64_t dims[2] = {64, 24576};
        const cuuint64_t strides[1] = {128};
        const cuuint32_t box[2] = {64, 128};
        encode(&p.tm[9], CU_TENSOR_MAP_DATA_TYPE_BFLOAT16, 2, kv, dims, strides, box, ones, CU_TENSOR_MAP_INTERLEAVE_NONE,
               CU_TENSOR_MAP_SWIZZLE_NONE, CU_TENSOR_MAP_L2_PROMOTION_L2_128B, CU_TENSOR_MAP_FLOAT_OOB_FILL_NONE);
    }
    p.w[8] = (const char*)d_in[0];
    p.dw = (const __nv_bfloat16*)d_in[6];
    p.out = (__nv_bfloat16*)d_out;
    conformer_kernel<<<NCTA, NTHREADS, SMEM_LAUNCH>>>(p);
}
```

```cpp
#include <cuda_runtime.h>
#include <cuda_bf16.h>
#include <cuda.h>
#include <stdint.h>

namespace {

constexpr int T_ = 1000;
constexpr int NCTA = 128;
constexpr int NTHREADS = 512;
constexpr int NSLOT = 5;
constexpr int SLOT = 16384;
constexpr int NLOADS = 54;

constexpr uint32_t OFF_RING = 0;
constexpr uint32_t OFF_P = 163840;
constexpr uint32_t OFF_H = 188416;
constexpr uint32_t OFF_INBOX = 221184;
constexpr uint32_t OFF_STATS = 229376;
constexpr uint32_t OFF_BARS = 229888;
constexpr uint32_t SMEM_BYTES = 230400;
constexpr uint32_t XCH = 6144;
constexpr uint32_t HCH = 4096;

constexpr int B_FULL = 0, B_EMPTY = 10, B_XR = 20, B_OIN = 22, B_HF = 24, B_INB = 28, B_QIN = 30, B_X1IN = 31, B_ST = 32, B_RDY = 33;

constexpr int PADROWS = 1040;
constexpr int FS = 8;

struct Params {
    CUtensorMap tm[10];
    const char* w[9];
    const __nv_bfloat16* dw;
    __nv_bfloat16* out;
};

__device__ __align__(1024) unsigned char g_kqv[3 * 8 * 1024 * 128];
__device__ __align__(1024) unsigned char g_o[8 * PADROWS * 128];
__device__ __align__(1024) unsigned char g_x1[8 * PADROWS * 128];
__device__ uint32_t g_flag_qk[8 * 32 * FS];
__device__ uint32_t g_flag_v[8 * 32 * FS];
__device__ uint32_t g_flag_o[2 * 16 * 4 * FS];
__device__ uint32_t g_epoch[NCTA * FS];

#define TS(i) do { } while (0)
#define TG(i) do { } while (0)
#define TSINIT() do { } while (0)
#define TSDUMP() do { } while (0)
constexpr uint32_t SMEM_LAUNCH = SMEM_BYTES;

__device__ __forceinline__ uint32_t smem_u32(const void* p) { return (uint32_t)__cvta_generic_to_shared(p); }
__device__ __forceinline__ void mbar_init(uint32_t b, uint32_t c) { asm volatile("mbarrier.init.shared::cta.b64 [%0], %1;" ::"r"(b), "r"(c) : "memory"); }
__device__ __forceinline__ void mbar_arrive(uint32_t b) { asm volatile("mbarrier.arrive.shared::cta.b64 _, [%0];" ::"r"(b) : "memory"); }
__device__ __forceinline__ void mbar_arrive_tx(uint32_t b, uint32_t tx) { asm volatile("mbarrier.arrive.expect_tx.shared::cta.b64 _, [%0], %1;" ::"r"(b), "r"(tx) : "memory"); }
__device__ __forceinline__ void mbar_wait(uint32_t b, uint32_t ph) {
    asm volatile("{\n.reg .pred p;\n.reg .u32 c;\nmov.u32 c, 0;\n"
                 "MW_LOOP:\n.pragma \"nounroll\";\n"
                 "mbarrier.try_wait.parity.shared::cta.b64 p, [%0], %1;\n@p bra MW_DONE;\n"
                 "add.u32 c, c, 1;\nsetp.lt.u32 p, c, 1048576;\n@p bra MW_LOOP;\ntrap;\n"
                 "MW_DONE:\n}" ::"r"(b), "r"(ph) : "memory");
}
__device__ __forceinline__ void mbar_wait2(uint32_t b0, uint32_t ph0, uint32_t b1, uint32_t ph1) {
    asm volatile("{\n.reg .pred p, q;\n.reg .u32 c;\nmov.u32 c, 0;\n"
                 "MW_LOOP:\n.pragma \"nounroll\";\n"
                 "mbarrier.try_wait.parity.shared::cta.b64 p, [%0], %1;\n"
                 "mbarrier.try_wait.parity.shared::cta.b64 q, [%2], %3;\n"
                 "and.pred p, p, q;\n@p bra MW_DONE;\n"
                 "add.u32 c, c, 1;\nsetp.lt.u32 p, c, 1048576;\n@p bra MW_LOOP;\ntrap;\n"
                 "MW_DONE:\n}" ::"r"(b0), "r"(ph0), "r"(b1), "r"(ph1) : "memory");
}
__device__ __forceinline__ uint32_t mapa(uint32_t a, uint32_t r) { uint32_t o; asm("mapa.shared::cluster.u32 %0, %1, %2;" : "=r"(o) : "r"(a), "r"(r)); return o; }
__device__ __forceinline__ void fence_async_smem() { asm volatile("fence.proxy.async.shared::cta;" ::: "memory"); }
__device__ __forceinline__ void fence_async_global() { asm volatile("fence.proxy.async.global;" ::: "memory"); }
__device__ __forceinline__ void bar_sync(int id, int n) { asm volatile("bar.sync %0, %1;" ::"r"(id), "r"(n) : "memory"); }
__device__ __forceinline__ void bar_arrive(int id, int n) { asm volatile("bar.arrive %0, %1;" ::"r"(id), "r"(n) : "memory"); }
__device__ __forceinline__ void cluster_arrive() { asm volatile("barrier.cluster.arrive.relaxed.aligned;" ::: "memory"); }
__device__ __forceinline__ void cluster_wait() { asm volatile("barrier.cluster.wait.aligned;" ::: "memory"); }

__device__ __forceinline__ void ring_load(uint32_t dst, const CUtensorMap* tm, int c0, int c1, uint32_t bar) {
    asm volatile("{\n.reg .pred p;\nelect.sync _|p, 0xffffffff;\n"
                 "@p mbarrier.arrive.expect_tx.shared::cta.b64 _, [%2], 16384;\n"
                 "@p cp.async.bulk.tensor.2d.shared::cluster.global.mbarrier::complete_tx::bytes [%0], [%1, {%3, %4}], [%2];\n}"
                 ::"r"(dst), "l"(tm), "r"(bar), "r"(c0), "r"(c1) : "memory");
}
__device__ __forceinline__ void ring_load_both(uint32_t dst, const CUtensorMap* tm, int c1, uint32_t bar) {
    asm volatile("{\n.reg .pred p;\nelect.sync _|p, 0xffffffff;\n"
                 "@p mbarrier.arrive.expect_tx.shared::cta.b64 _, [%2], 16384;\n"
                 "@p cp.async.bulk.tensor.2d.shared::cluster.global.mbarrier::complete_tx::bytes.multicast::cluster [%0], [%1, {0, %3}], [%2], %4;\n}"
                 ::"r"(dst), "l"(tm), "r"(bar), "r"(c1), "h"((uint16_t)3) : "memory");
}
__device__ __forceinline__ void ring_arm_signal(uint32_t bar, uint32_t peer_rdy) {
    asm volatile("{\n.reg .pred p;\nelect.sync _|p, 0xffffffff;\n"
                 "@p mbarrier.arrive.expect_tx.shared::cta.b64 _, [%0], 16384;\n"
                 "@p mbarrier.arrive.relaxed.cluster.shared::cluster.b64 _, [%1];\n}"
                 ::"r"(bar), "r"(peer_rdy) : "memory");
}
__device__ __forceinline__ void tma3d(uint32_t dst, const CUtensorMap* tm, int c0, int c1, int c2, uint32_t bar) {
    asm volatile("cp.async.bulk.tensor.3d.shared::cluster.global.mbarrier::complete_tx::bytes [%0], [%1, {%3, %4, %5}], [%2];"
                 ::"r"(dst), "l"(tm), "r"(bar), "r"(c0), "r"(c1), "r"(c2) : "memory");
}
__device__ __forceinline__ void bulk_g2s(uint32_t dst, const void* src, uint32_t bytes, uint32_t bar) {
    asm volatile("cp.async.bulk.shared::cluster.global.mbarrier::complete_tx::bytes [%0], [%1], %2, [%3];" ::"r"(dst), "l"(src), "r"(bytes), "r"(bar) : "memory");
}
__device__ __forceinline__ void peer_copy(uint32_t dst, uint32_t src, uint32_t bytes, uint32_t rbar) {
    asm volatile("{\n.reg .pred p;\nelect.sync _|p, 0xffffffff;\n"
                 "@p cp.async.bulk.shared::cluster.shared::cta.mbarrier::complete_tx::bytes [%0], [%1], %2, [%3];\n}"
                 ::"r"(dst), "r"(src), "r"(bytes), "r"(rbar) : "memory");
}
__device__ __forceinline__ void st_async4(uint32_t dst, uint32_t a, uint32_t b, uint32_t c, uint32_t d, uint32_t bar) {
    asm volatile("st.async.shared::cluster.mbarrier::complete_tx::bytes.v4.b32 [%0], {%1,%2,%3,%4}, [%5];" ::"r"(dst), "r"(a), "r"(b), "r"(c), "r"(d), "r"(bar) : "memory");
}
__device__ __forceinline__ void stsm4t(uint32_t a, uint32_t r0, uint32_t r1, uint32_t r2, uint32_t r3) {
    asm volatile("stmatrix.sync.aligned.m8n8.x4.trans.shared.b16 [%0], {%1,%2,%3,%4};" ::"r"(a), "r"(r0), "r"(r1), "r"(r2), "r"(r3) : "memory");
}
__device__ __forceinline__ void stsm4(uint32_t a, uint32_t r0, uint32_t r1, uint32_t r2, uint32_t r3) {
    asm volatile("stmatrix.sync.aligned.m8n8.x4.shared.b16 [%0], {%1,%2,%3,%4};" ::"r"(a), "r"(r0), "r"(r1), "r"(r2), "r"(r3) : "memory");
}
__device__ __forceinline__ void ldsm4t(uint32_t a, uint32_t& r0, uint32_t& r1, uint32_t& r2, uint32_t& r3) {
    asm volatile("ldmatrix.sync.aligned.m8n8.x4.trans.shared.b16 {%0,%1,%2,%3}, [%4];" : "=r"(r0), "=r"(r1), "=r"(r2), "=r"(r3) : "r"(a) : "memory");
}
__device__ __forceinline__ uint4 lds128(uint32_t a) { uint4 v; asm volatile("ld.shared.v4.b32 {%0,%1,%2,%3}, [%4];" : "=r"(v.x), "=r"(v.y), "=r"(v.z), "=r"(v.w) : "r"(a) : "memory"); return v; }
__device__ __forceinline__ float4 lds128f(uint32_t a) { float4 v; asm volatile("ld.shared.v4.f32 {%0,%1,%2,%3}, [%4];" : "=f"(v.x), "=f"(v.y), "=f"(v.z), "=f"(v.w) : "r"(a) : "memory"); return v; }
__device__ __forceinline__ float2 lds64f(uint32_t a) { float2 v; asm volatile("ld.shared.v2.f32 {%0,%1}, [%2];" : "=f"(v.x), "=f"(v.y) : "r"(a) : "memory"); return v; }
__device__ __forceinline__ uint32_t lds32(uint32_t a) { uint32_t v; asm volatile("ld.shared.b32 %0, [%1];" : "=r"(v) : "r"(a) : "memory"); return v; }
__device__ __forceinline__ void sts128(uint32_t a, uint32_t x, uint32_t y, uint32_t z, uint32_t w) { asm volatile("st.shared.v4.b32 [%0], {%1,%2,%3,%4};" ::"r"(a), "r"(x), "r"(y), "r"(z), "r"(w) : "memory"); }
__device__ __forceinline__ void sts128f(uint32_t a, float x, float y, float z, float w) { asm volatile("st.shared.v4.f32 [%0], {%1,%2,%3,%4};" ::"r"(a), "f"(x), "f"(y), "f"(z), "f"(w) : "memory"); }
__device__ __forceinline__ void sts64f(uint32_t a, float x, float y) { asm volatile("st.shared.v2.f32 [%0], {%1,%2};" ::"r"(a), "f"(x), "f"(y) : "memory"); }
__device__ __forceinline__ void sts32(uint32_t a, uint32_t x) { asm volatile("st.shared.b32 [%0], %1;" ::"r"(a), "r"(x) : "memory"); }
__device__ __forceinline__ void stg128(void* p, uint4 v) { asm volatile("st.global.v4.b32 [%0], {%1,%2,%3,%4};" ::"l"(p), "r"(v.x), "r"(v.y), "r"(v.z), "r"(v.w) : "memory"); }

__device__ __forceinline__ uint32_t pack2(float lo, float hi) { uint32_t r; asm("cvt.rn.bf16x2.f32 %0, %1, %2;" : "=r"(r) : "f"(hi), "f"(lo)); return r; }
__device__ __forceinline__ float blo(uint32_t v) { return __uint_as_float(v << 16); }
__device__ __forceinline__ float bhi(uint32_t v) { return __uint_as_float(v & 0xffff0000u); }
__device__ __forceinline__ float tanh_fast(float x) { float r; asm("tanh.approx.f32 %0, %1;" : "=f"(r) : "f"(x)); return r; }
__device__ __forceinline__ float ex2(float x) { float r; asm("ex2.approx.ftz.f32 %0, %1;" : "=f"(r) : "f"(x)); return r; }

__device__ __forceinline__ void flag_wait(const uint32_t* p, uint32_t e) {
#pragma unroll 1
    for (int i = 0; i < (1 << 22); i++) {
        uint32_t v;
        asm volatile("ld.acquire.gpu.global.u32 %0, [%1];" : "=r"(v) : "l"(p) : "memory");
        if (v == e) return;
    }
    __trap();
}
__device__ __forceinline__ uint32_t ld_epoch() {
    uint32_t v;
    asm volatile("ld.relaxed.gpu.global.u32 %0, [%1];" : "=r"(v) : "l"(&g_epoch[blockIdx.x * FS]) : "memory");
    return v + 1;
}
__device__ __forceinline__ void flag_set(uint32_t* p, uint32_t e) { asm volatile("st.release.gpu.global.u32 [%0], %1;" ::"l"(p), "r"(e) : "memory"); }

__device__ __forceinline__ uint64_t mkdesc(uint32_t addr) { return (uint64_t)(((addr & 0x3FFFF) >> 4) | 0x10000u) | (0x40000040ull << 32); }
__device__ __forceinline__ void wg_fence() { asm volatile("wgmma.fence.sync.aligned;" ::: "memory"); }
__device__ __forceinline__ void wg_commit() { asm volatile("wgmma.commit_group.sync.aligned;" ::: "memory"); }
template <int N> __device__ __forceinline__ void wg_wait() { asm volatile("wgmma.wait_group.sync.aligned %0;" ::"n"(N) : "memory"); }
template <int N> __device__ __forceinline__ void pin(float (&d)[N]) {
#pragma unroll
    for (int i = 0; i < N; i++) asm volatile("" : "+f"(d[i])::"memory");
}
template <int N> __device__ __forceinline__ void pin(uint32_t (&d)[N]) {
#pragma unroll
    for (int i = 0; i < N; i++) asm volatile("" : "+r"(d[i])::"memory");
}

template <typename Tp, int N> __device__ __forceinline__ void zero(Tp (&d)[N]) {
#pragma unroll
    for (int i = 0; i < N; i++) d[i] = 0;
    pin(d);
}

#define F4(d, i) "+f"(d[i]), "+f"(d[i + 1]), "+f"(d[i + 2]), "+f"(d[i + 3])
#define F16(d, i) F4(d, i), F4(d, i + 4), F4(d, i + 8), F4(d, i + 12)

__device__ __forceinline__ void mma_t(float (&d)[16], uint64_t a, uint64_t b, int acc) {
    asm volatile("{.reg .pred p; setp.ne.b32 p, %18, 0;\n"
                 "wgmma.mma_async.sync.aligned.m64n32k16.f32.bf16.bf16 {%0,%1,%2,%3,%4,%5,%6,%7,%8,%9,%10,%11,%12,%13,%14,%15}, %16, %17, p, 1, 1, 1, 0;}\n"
                 : F16(d, 0) : "l"(a), "l"(b), "r"(acc));
}
__device__ __forceinline__ void mma_t(float (&d)[20], uint64_t a, uint64_t b, int acc) {
    asm volatile("{.reg .pred p; setp.ne.b32 p, %22, 0;\n"
                 "wgmma.mma_async.sync.aligned.m64n40k16.f32.bf16.bf16 {%0,%1,%2,%3,%4,%5,%6,%7,%8,%9,%10,%11,%12,%13,%14,%15,%16,%17,%18,%19}, %20, %21, p, 1, 1, 1, 0;}\n"
                 : F16(d, 0), F4(d, 16) : "l"(a), "l"(b), "r"(acc));
}
__device__ __forceinline__ void mma_t(float (&d)[24], uint64_t a, uint64_t b, int acc) {
    asm volatile("{.reg .pred p; setp.ne.b32 p, %26, 0;\n"
                 "wgmma.mma_async.sync.aligned.m64n48k16.f32.bf16.bf16 {%0,%1,%2,%3,%4,%5,%6,%7,%8,%9,%10,%11,%12,%13,%14,%15,%16,%17,%18,%19,%20,%21,%22,%23}, %24, %25, p, 1, 1, 1, 0;}\n"
                 : F16(d, 0), F4(d, 16), F4(d, 20) : "l"(a), "l"(b), "r"(acc));
}
__device__ __forceinline__ void mma_qk(float (&d)[64], uint64_t a, uint64_t b, int acc) {
    asm volatile("{.reg .pred p; setp.ne.b32 p, %66, 0;\n"
                 "wgmma.mma_async.sync.aligned.m64n128k16.f32.bf16.bf16 {%0,%1,%2,%3,%4,%5,%6,%7,%8,%9,%10,%11,%12,%13,%14,%15,%16,%17,%18,%19,%20,%21,%22,%23,%24,%25,%26,%27,%28,%29,%30,%31,"
                 "%32,%33,%34,%35,%36,%37,%38,%39,%40,%41,%42,%43,%44,%45,%46,%47,%48,%49,%50,%51,%52,%53,%54,%55,%56,%57,%58,%59,%60,%61,%62,%63}, %64, %65, p, 1, 1, 0, 0;}\n"
                 : F16(d, 0), F16(d, 16), F16(d, 32), F16(d, 48) : "l"(a), "l"(b), "r"(acc));
}
__device__ __forceinline__ void mma_pv(float (&d)[32], uint32_t a0, uint32_t a1, uint32_t a2, uint32_t a3, uint64_t b) {
    asm volatile("wgmma.mma_async.sync.aligned.m64n64k16.f32.bf16.bf16 {%0,%1,%2,%3,%4,%5,%6,%7,%8,%9,%10,%11,%12,%13,%14,%15,%16,%17,%18,%19,%20,%21,%22,%23,%24,%25,%26,%27,%28,%29,%30,%31}, "
                 "{%32,%33,%34,%35}, %36, 1, 1, 1, 1;\n"
                 : F16(d, 0), F16(d, 16) : "r"(a0), "r"(a1), "r"(a2), "r"(a3), "l"(b));
}

template <uint32_t CSTRIDE, int N>
__device__ __forceinline__ void issue_half(float (&d)[N], uint32_t slot, uint32_t c0, int acc) {
    const uint64_t a = mkdesc(slot), b = mkdesc(c0);
    wg_fence();
#pragma unroll
    for (int k = 0; k < 8; k++) mma_t(d, a + k * 128, b + (k >> 2) * (CSTRIDE >> 4) + (k & 3) * 2, k == 0 ? acc : 1);
    wg_commit();
}

__device__ __forceinline__ uint32_t load_code(int n, int r, int w, int abh) {
    const int tile = 2 * r + w;
    int m, col, row;
    if (n < 16 || n >= 38) {
        const int k = n < 16 ? n : n - 38;
        m = n < 16 ? 1 : 7;
        if (k < 8) { col = 8 * r + (k & 6) + w; row = (k & 1) ^ r; }
        else { m++; col = k < 12 ? (tile ^ 2) : tile; row = 4 * r + (k & 3); }
    } else if (n < 22) {
        const int k = n - 16;
        m = 3;
        col = tile + (k < 2 ? 4 : (k < 4 ? 0 : 8)); row = (k & 1) ^ r;
    } else if (n < 30) {
        const int k = n - 22;
        const bool isv = (k == 7) || (k >= 2 && !(k & 1));
        const int i = isv ? (k == 7 ? 3 : (k >> 1) - 1) : ((k + 1) >> 1);
        m = 9; col = 0; row = (isv ? 128 : 0) + abh * 8 + 2 * i + w;
    } else if (n < 32) { m = 4; col = tile; row = n - 30; }
    else if (n < 36) { const int k = n - 32; m = 5; col = tile + 4 * (k & 1); row = (k >> 1) ^ r; }
    else { m = 6; col = tile; row = (n & 1) ^ r; }
    return m | (col << 4) | (row << 8);
}

struct Ring {
    uint32_t base, full, empty;
    uint32_t s, ph, rs;
    __device__ __forceinline__ uint32_t acquire() {
        mbar_wait(full + s * 8, ph);
        uint32_t a = base + s * SLOT;
        if (++s == NSLOT) { s = 0; ph ^= 1; }
        return a;
    }
    __device__ __forceinline__ void acquire2(uint32_t& a0, uint32_t& a1) {
        uint32_t s1 = s + 1, ph1 = ph;
        if (s1 == NSLOT) { s1 = 0; ph1 ^= 1; }
        mbar_wait2(full + s * 8, ph, full + s1 * 8, ph1);
        a0 = base + s * SLOT; a1 = base + s1 * SLOT;
        s = s1 + 1; ph = ph1;
        if (s == NSLOT) { s = 0; ph ^= 1; }
    }
    __device__ __forceinline__ void release(int lane) {
        if (lane == 0) mbar_arrive(empty + rs * 8);
        if (++rs == NSLOT) rs = 0;
    }
};

__global__ void __cluster_dims__(2, 1, 1) __launch_bounds__(NTHREADS, 1)
conformer_kernel(const __grid_constant__ Params p) {
    extern __shared__ __align__(1024) unsigned char smem_raw[];
    const uint32_t sb = smem_u32(smem_raw);
    const uint32_t bars = sb + OFF_BARS;
    const int tid = threadIdx.x;
    const int lane = tid & 31;
    const int warp = __shfl_sync(~0u, tid >> 5, 0);
    const int r = blockIdx.x & 1;
    const int pair = blockIdx.x >> 1;
    const int b = pair >> 5, pt = pair & 31;
    const int ah = pt >> 3, qt = (pt & 7) * 2 + r;
    const int abh = b * 4 + ah;

    TG(30);
    TSINIT();
    TS(0);
    const uint32_t P = sb + OFF_P, H = sb + OFF_H;
    auto xwait = [&](int j) { mbar_wait(bars + (B_XR + (j & 1)) * 8, (j >> 1) & 1); };

    if (warp >= 8) {
        asm volatile("setmaxnreg.dec.sync.aligned.u32 40;");
        if (warp >= 12) {
            if (warp == 12 && lane >= 2 && lane < 10) asm volatile("prefetch.tensormap [%0];" ::"l"(&p.tm[lane]) : "memory");
            cluster_arrive();
            cluster_wait();
            const int ut = tid & 127;
            const uint32_t a4 = P + (ut >> 2) * 128 + (2 * (ut & 3) + ((ut >> 2) & 1)) * 16;
            const uint32_t a8 = P + (32 + (ut >> 3)) * 128 + (ut & 7) * 16;
            auto accum = [](uint32_t a, float& s, float& q) {
                const uint4 v = lds128(a);
                const float a0 = blo(v.x), a1 = bhi(v.x), a2 = blo(v.y), a3 = bhi(v.y), a4 = blo(v.z), a5 = bhi(v.z), a6 = blo(v.w), a7 = bhi(v.w);
                s += ((a0 + a1) + (a2 + a3)) + ((a4 + a5) + (a6 + a7));
                q += fmaf(a0, a0, fmaf(a1, a1, fmaf(a2, a2, a3 * a3))) + fmaf(a4, a4, fmaf(a5, a5, fmaf(a6, a6, a7 * a7)));
            };
#pragma unroll 1
            for (int k = 0; k < 4; k++) {
                float s = 0.f, q = 0.f, s2 = 0.f, q2 = 0.f;
#pragma unroll 1
                for (int h = 0; h < 2; h++) {
                    if (h == 0 && k != 0) bar_sync(1, 384);
                    else xwait(k == 3 ? 4 : k);
                    const uint32_t off = 2 * (r ^ h) * XCH;
                    accum(a4 + off, s, q); accum((a4 ^ 16) + off, s, q); accum(a4 + off + XCH, s, q); accum((a4 ^ 16) + off + XCH, s, q);
                    if (k == 2) { accum(a8 + off, s2, q2); accum(a8 + off + XCH, s2, q2); }
                }
#pragma unroll
                for (int o = 1; o < 8; o <<= 1) {
                    if (o < 4) { s += __shfl_xor_sync(~0u, s, o); q += __shfl_xor_sync(~0u, q, o); }
                    if (k == 2) { s2 += __shfl_xor_sync(~0u, s2, o); q2 += __shfl_xor_sync(~0u, q2, o); }
                }
                const bool second = (ut & 7) == 1;
                if (second) { s = s2; q = q2; }
                const float mean = s * (1.f / 256.f);
                const float rstd = 0.5f * rsqrtf(fmaxf(fmaf(-mean, mean, q * (1.f / 256.f)), 0.f) + 1e-5f);
                if ((ut & 3) == 0 || second) sts64f(sb + OFF_STATS + (second ? 32 + (ut >> 3) : ut >> 2) * 8, mean * rstd, rstd);
                __syncwarp();
                if (lane == 0) mbar_arrive(bars + B_ST * 8);
                TS(2 + k);
                if (k == 1) {
                    const uint32_t epoch = ld_epoch();
#pragma unroll 1
                    for (int i = -1; i < 3; i++) {
                        uint32_t src = P + 2 * r * XCH, ss = XCH, ds = PADROWS * 128;
                        unsigned char* dst = g_x1 + 1024;
                        if (i >= 0) { src = H + 2 * i * HCH; ss = HCH; ds = 1024 * 128; dst = g_kqv + i * 1048576; }
                        src += ut * 16;
                        dst += (size_t)(b * 4 + 2 * r) * ds + pt * 4096 + ut * 16;
                        if (i >= 0) mbar_wait(bars + (B_HF + i) * 8, 1);
                        const uint4 v0 = lds128(src), v1 = lds128(src + 2048), v2 = lds128(src + ss), v3 = lds128(src + ss + 2048);
                        stg128(dst, v0); stg128(dst + 2048, v1); stg128(dst + ds, v2); stg128(dst + ds + 2048, v3);
                        if (i == 1) bar_arrive(4, 160);
                        TS(10 + i);
                    }
                    bar_sync(5, 128);
                    if (ut < 2) flag_set(&g_flag_v[((b * 4 + 2 * r + ut) * 32 + pt) * FS], epoch);
                    __syncwarp();
                    TS(13);
                }
            }
        } else if (warp < 10) {
            const int w = warp - 8;
            const uint32_t ring = sb + OFF_RING + w * NSLOT * SLOT;
            const uint32_t full = bars + (B_FULL + w * NSLOT) * 8;
            if (lane == 0) {
#pragma unroll
                for (int i = 0; i < NSLOT; i++) mbar_init(full + i * 8, 1);
                asm volatile("fence.mbarrier_init.release.cluster;" ::: "memory");
                fence_async_smem();
            }
            __syncwarp();
            cluster_arrive();
            TS(1);
#pragma unroll
            for (int n = 0; n < NSLOT; n++)
                ring_load(ring + n * SLOT, &p.tm[1], 64 * (8 * r + (n & 6) + w), 128 * ((n & 1) ^ r), full + n * 8);
            TS(2);
            const uint32_t code = load_code(lane, r, w, abh) | (load_code(lane + 32, r, w, abh) << 16);
            cluster_wait();
            uint32_t s = 0, ph = 0;
            int n = NSLOT;
#pragma unroll 1
            for (int seg = 0; seg < 2; seg++) {
#pragma unroll 1
                for (; n < (seg == 0 ? 22 : NLOADS); n++) {
                    const uint32_t c = __shfl_sync(~0u, code, n) >> (n & 32 ? 16 : 0);
                    mbar_wait(full + (B_EMPTY - B_FULL) * 8 + s * 8, ph);
                    ring_load(ring + s * SLOT, &p.tm[c & 15], (c & 0xf0) * 4, (c & 0xff00) >> 1, full + s * 8);
                    if (++s == NSLOT) { s = 0; ph ^= 1; }
                }
                if (seg == 1) break;
                const uint32_t epoch = ld_epoch();
                const uint32_t rdy = bars + (B_RDY + w) * 8;
#pragma unroll 1
                for (; n < 30; n++) {
                    const uint32_t c = __shfl_sync(~0u, code, n);
                    mbar_wait(full + (B_EMPTY - B_FULL) * 8 + s * 8, ph);
                    if ((n & 1) == r) {
                        mbar_wait(rdy, ((n - 22) >> 1) & 1);
                        if (n < 25 || n == 29) {
                            flag_wait((n < 24 ? g_flag_qk : g_flag_v) + (abh * 32 + lane) * FS, epoch);
                            __syncwarp();
                            fence_async_global();
                            TS(n < 24 ? 5 : (n == 24 ? 6 : 7));
                        }
                        ring_load_both(ring + s * SLOT, &p.tm[9], (c & 0xff00) >> 1, full + s * 8);
                    } else {
                        ring_arm_signal(full + s * 8, mapa(rdy, r ^ 1));
                    }
                    if (++s == NSLOT) { s = 0; ph ^= 1; }
                }
            }
        } else if (warp == 10) {
            if (lane == 0) {
                mbar_init(bars + B_XR * 8, 1);
                asm volatile("fence.mbarrier_init.release.cluster;" ::: "memory");
                fence_async_smem();
            }
            __syncwarp();
            cluster_arrive();
            if (lane == 0) {
                mbar_arrive_tx(bars + B_XR * 8, 16384);
#pragma unroll
                for (int i = 0; i < 4; i++) tma3d(P + i * XCH, &p.tm[0], i * 64, pt * 32, b, bars + B_XR * 8);
            }
            __syncwarp();
            cluster_wait();
            const uint32_t epoch = ld_epoch();
            if (lane == 0) {
                mbar_arrive_tx(bars + B_QIN * 8, 8192);
                mbar_arrive_tx(bars + B_X1IN * 8, 2 * XCH);
                mbar_arrive_tx(bars + B_OIN * 8, 2 * XCH);
                mbar_arrive_tx(bars + B_OIN * 8 + 8, 2 * XCH);
            }
            if (lane < 2) flag_wait(&g_flag_qk[(abh * 32 + 2 * qt + lane) * FS], epoch);
            __syncwarp();
            if (lane == 0) {
                fence_async_global();
                bulk_g2s(H + 24576, g_kqv + 1048576 + (size_t)(abh * 1024 + qt * 64) * 128, 8192, bars + B_QIN * 8);
            }
            if (lane < 12) {
                const int np = pt - 1 + (lane >> 2);
                if (np >= 0 && np < 32) flag_wait(&g_flag_v[((b * 4 + (lane & 3)) * 32 + np) * FS], epoch);
            }
            __syncwarp();
            if (lane == 0) {
                fence_async_global();
#pragma unroll
                for (int w = 0; w < 2; w++)
                    bulk_g2s(P + (2 * r + w) * XCH, g_x1 + (size_t)((b * 4 + 2 * r + w) * PADROWS + pt * 32) * 128, XCH, bars + B_X1IN * 8);
            }
            __syncwarp();
            bar_sync(9, 64);
            if (lane < 8) {
                const int q = (pt >> 1) + (lane < 4 ? 0 : ((pt & 1) ? 1 : -1));
                if (q >= 0 && q < 16) flag_wait(&g_flag_o[((b * 16 + q) * 4 + (lane & 3)) * FS], epoch);
            }
            __syncwarp();
            if (lane == 0) {
                fence_async_global();
#pragma unroll
                for (int i = 0; i < 4; i++)
                    bulk_g2s(H + i * XCH, g_o + (size_t)((b * 4 + i) * PADROWS + pt * 32) * 128, XCH, bars + (B_OIN + (i >> 1)) * 8);
            }
            __syncwarp();
        } else {
            if (lane < 9) {
                uint32_t kb = (lane < 2 || lane > 5) ? 4096 : (lane == 2 ? 3072 : (lane == 4 ? 2048 : 1024));
                size_t off = (size_t)blockIdx.x * kb;
                if (lane == 8) { kb = 8192; off = (size_t)min(b * T_ + pt * 32 + r * 16, 2 * T_ - 16) * 512; }
                asm volatile("cp.async.bulk.prefetch.L2.global [%0], %1;" ::"l"(p.w[lane] + off), "r"(kb) : "memory");
            }
            __syncwarp();
            cluster_arrive();
            cluster_wait();
            const uint32_t epoch = ld_epoch();
            bar_sync(4, 160);
            if (lane < 2) flag_set(&g_flag_qk[((b * 4 + 2 * r + lane) * 32 + pt) * FS], epoch);
            __syncwarp();
            bar_sync(6, 288);
            bar_arrive(9, 64);
            if (lane == 0) {
                flag_set(&g_flag_o[((b * 16 + qt) * 4 + ah) * FS], epoch);
                g_epoch[blockIdx.x * FS] = epoch;
            }
            __syncwarp();
        }
        TSDUMP();
        return;
    }

    if (lane == 0) {
        mbar_init(bars + (B_EMPTY + warp) * 8, 4);
        mbar_init(bars + (B_HF + warp) * 8, warp < 4 ? 8 : 1);
        if (warp < 3) mbar_init(bars + (warp == 2 ? B_ST : B_EMPTY + 8 + warp) * 8, 4);
        else mbar_init(bars + (warp < 6 ? B_XR - 2 + warp : B_RDY - 6 + warp) * 8, 1);
        asm volatile("fence.mbarrier_init.release.cluster;" ::: "memory");
    }
    sts128(P + (tid >> 6) * XCH + 4096 + (tid & 63) * 16, 0x3F803F80u, 0x3F803F80u, 0x3F803F80u, 0x3F803F80u);
    fence_async_smem();
    __syncwarp();
    cluster_arrive();
    asm volatile("setmaxnreg.inc.sync.aligned.u32 216;");
    const int w = warp >> 2, wq = warp & 3;
    const int tile = 2 * r + w;
    const int wt = tid & 127;
    const int c4 = lane & 3;
    Ring ring{sb + OFF_RING + w * NSLOT * SLOT, bars + (B_FULL + w * NSLOT) * 8, bars + (B_EMPTY + w * NSLOT) * 8, 0, 0, 0};
    const uint32_t toff = ((lane >> 4) * 8 + (lane & 7)) * 128 + (((2 * wq + ((lane >> 3) & 1)) ^ (lane & 7)) << 4);
    const uint32_t xa = P + tile * XCH + toff;
    auto turn_wait = [&]() { bar_sync(7 + w, 256); };
    auto turn_pass = [&]() { bar_arrive(8 - w, 256); };
    if (w == 1) turn_pass();

    auto publish = [&](int j, uint32_t src, uint32_t bytes, int nsync) {
        const uint32_t bar = bars + (B_XR + (j & 1)) * 8;
        fence_async_smem();
        bar_sync(2 + w, 128);
        if (wq == 0) peer_copy(mapa(src, r ^ 1), src, bytes, mapa(bar, r ^ 1));
        if (tid == 32) mbar_arrive_tx(bar, 2 * bytes);
        bar_sync(nsync == 384 ? 1 : 10, nsync);
    };
    bar_sync(10, 256);
    cluster_wait();
    uint32_t s0, s1;
    ring.acquire2(s0, s1);
    xwait(0);

#pragma unroll 1
    for (int ph = 0; ph < 3; ph++) {
        {
            float st[16], d[20], e[18];
            zero(st); zero(d); zero(e);
            const uint32_t issue_mask = ph == 1 ? 0x0b : 0x0f, epi_mask = ph == 1 ? 0x16 : 0x1e;
            uint32_t dst = H + w * HCH + toff, hf = bars + B_HF * 8;
            TS(1 + ph * 10);
#pragma unroll 1
            for (int it = 0; it < 5; it++) {
                const bool di = (issue_mask >> it) & 1;
                if (di) {
                    if (it) turn_wait();
                    TS(32 + it * 6);
                    issue_half<XCH>(d, s0, P + 2 * r * XCH, 0);
                    if (it == 0) { turn_wait(); xwait(ph == 2 ? 4 : ph); }
                    issue_half<XCH>(d, s1, P + 2 * (r ^ 1) * XCH, 1);
                    turn_pass();
                    TS(33 + it * 6);
                    wg_wait<1>();
                    ring.release(lane);
                }
                if ((epi_mask >> it) & 1) {
                    if (it == 1) {
                        mbar_wait(bars + B_ST * 8, ph != 0);
#pragma unroll
                        for (int j = 0; j < 4; j++) {
                            const float4 v = lds128f(sb + OFF_STATS + (8 * j + 2 * c4) * 8);
                            st[4 * j] = v.x; st[4 * j + 1] = v.y; st[4 * j + 2] = v.z; st[4 * j + 3] = v.w;
                        }
                    }
                    TS(34 + it * 6);
                    uint32_t pk[8];
                    if (ph != 1) {
#pragma unroll
                        for (int k = 0; k < 8; k++) {
                            const float v0 = fmaf(-st[(k >> 1) * 4], e[16 + (k & 1)], e[2 * k] * st[(k >> 1) * 4 + 1]);
                            const float v1 = fmaf(-st[(k >> 1) * 4 + 2], e[16 + (k & 1)], e[2 * k + 1] * st[(k >> 1) * 4 + 3]);
                            pk[k] = pack2(fmaf(v0, tanh_fast(v0), v0), fmaf(v1, tanh_fast(v1), v1));
                        }
                    } else {
#pragma unroll
                        for (int k = 0; k < 8; k++) {
                            const float v0 = fmaf(-st[(k >> 1) * 4], e[16 + (k & 1)], e[2 * k] * st[(k >> 1) * 4 + 1]);
                            const float v1 = fmaf(-st[(k >> 1) * 4 + 2], e[16 + (k & 1)], e[2 * k + 1] * st[(k >> 1) * 4 + 3]);
                            pk[k] = pack2(v0 + v0, v1 + v1);
                        }
                    }
                    stsm4t(dst, pk[0], pk[1], pk[2], pk[3]);
                    stsm4t(dst + 2048, pk[4], pk[5], pk[6], pk[7]);
                    TS(35 + it * 6);
                    fence_async_smem();
                    __syncwarp();
                    if (lane == 0) mbar_arrive(hf);
                    dst += 2 * HCH; hf += 8;
                }
                wg_wait<0>();
                pin(d);
                TS(36 + it * 6);
                if (di) {
                    ring.release(lane);
                    if (ph != 1 || it != 3) ring.acquire2(s0, s1);
                }
#pragma unroll
                for (int k = 0; k < 16; k++) e[k] = d[k];
                e[16] = d[16]; e[17] = d[18];
                pin(e);
                TS(37 + it * 6);
            }
            TS(2 + ph * 10);
        }
        if (ph != 1) {
            const uint32_t inb = bars + (B_INB + w) * 8, box = sb + OFF_INBOX + w * 4096 + wt * 16;
            float d[16];
            uint32_t xr[8], pr[8];
            zero(d); zero(xr); zero(pr);
            if (wt == 0) mbar_arrive_tx(inb, 4096);
#pragma unroll 1
            for (int k = 0; k < 4; k++) {
                if (k < 2) mbar_wait(bars + (B_HF + 2 * k + 1) * 8, 0);
                turn_wait();
                issue_half<HCH>(d, s0, H + 4 * (k & 1) * HCH, k & 1);
                issue_half<HCH>(d, s1, H + (4 * (k & 1) + 2) * HCH, 1);
                turn_pass();
                wg_wait<1>();
                ring.release(lane);
                if (k == 3) {
                    ldsm4t(xa, xr[0], xr[1], xr[2], xr[3]);
                    ldsm4t(xa + 2048, xr[4], xr[5], xr[6], xr[7]);
                    const uint4 u = lds128(box), v = lds128(box + 2048);
                    pr[0] = u.x; pr[1] = u.y; pr[2] = u.z; pr[3] = u.w; pr[4] = v.x; pr[5] = v.y; pr[6] = v.z; pr[7] = v.w;
                }
                if (ph == 0 || k != 3) ring.acquire2(s0, s1);
                wg_wait<0>();
                pin(d);
                ring.release(lane);
                if (k == 1) {
                    const uint32_t dst = mapa(box, r ^ 1), bar = mapa(inb, r ^ 1);
                    st_async4(dst, pack2(d[0], d[1]), pack2(d[2], d[3]), pack2(d[4], d[5]), pack2(d[6], d[7]), bar);
                    st_async4(dst + 2048, pack2(d[8], d[9]), pack2(d[10], d[11]), pack2(d[12], d[13]), pack2(d[14], d[15]), bar);
                }
                if (k == 2) mbar_wait(inb, ph >> 1);
            }
            TS(3 + ph * 10);
#pragma unroll
            for (int i = 0; i < 8; i++)
                xr[i] = pack2(fmaf(0.5f, d[2 * i] + blo(pr[i]), blo(xr[i])), fmaf(0.5f, d[2 * i + 1] + bhi(pr[i]), bhi(xr[i])));
            stsm4t(xa, xr[0], xr[1], xr[2], xr[3]);
            stsm4t(xa + 2048, xr[4], xr[5], xr[6], xr[7]);
            publish(ph ? 5 : 1, P + tile * XCH + (ph ? (r ^ 1) * 2048 : 0), ph ? 2048 : 4096, ph ? 256 : 384);
            continue;
        }
        if (lane == 0) mbar_arrive(bars + (B_HF + 3) * 8);

        {
            constexpr float CS = 0.125f * 1.4426950408889634f;
            float s[64], o[32];
            uint32_t pp[32];
            float m0 = -INFINITY, m1 = -INFINITY, l0 = 0.f, l1 = 0.f;
            zero(o); zero(pp);
            const uint64_t qd = mkdesc(H + 24576);
            auto qk_issue = [&](uint32_t slot) {
                const uint64_t kd = mkdesc(slot);
                wg_fence();
#pragma unroll
                for (int k = 0; k < 4; k++) mma_qk(s, qd + 2 * k, kd + 2 * k, k != 0);
                wg_commit();
            };
            auto pv_issue = [&](uint32_t slot) {
                const uint64_t vd = mkdesc(slot);
                wg_fence();
#pragma unroll
                for (int k = 0; k < 8; k++) mma_pv(o, pp[4 * k], pp[4 * k + 1], pp[4 * k + 2], pp[4 * k + 3], vd + k * 128);
                wg_commit();
            };
            float sc0, sc1;
            auto softmax = [&](bool mask) {
                if (mask) {
#pragma unroll
                    for (int i = 52; i < 64; i++) s[i] = -INFINITY;
                }
                float x0 = m0, x1 = m1;
#pragma unroll
                for (int j = 0; j < 16; j++) {
                    x0 = fmaxf(x0, fmaxf(s[4 * j], s[4 * j + 1]));
                    x1 = fmaxf(x1, fmaxf(s[4 * j + 2], s[4 * j + 3]));
                }
                x0 = fmaxf(x0, __shfl_xor_sync(~0u, x0, 1)); x1 = fmaxf(x1, __shfl_xor_sync(~0u, x1, 1));
                x0 = fmaxf(x0, __shfl_xor_sync(~0u, x0, 2)); x1 = fmaxf(x1, __shfl_xor_sync(~0u, x1, 2));
                sc0 = ex2((m0 - x0) * CS); sc1 = ex2((m1 - x1) * CS);
                m0 = x0; m1 = x1;
                const float n0 = -x0 * CS, n1 = -x1 * CS;
                float r0 = 0.f, r1 = 0.f;
#pragma unroll
                for (int j = 0; j < 16; j++) {
                    s[4 * j] = ex2(fmaf(s[4 * j], CS, n0)); s[4 * j + 1] = ex2(fmaf(s[4 * j + 1], CS, n0));
                    s[4 * j + 2] = ex2(fmaf(s[4 * j + 2], CS, n1)); s[4 * j + 3] = ex2(fmaf(s[4 * j + 3], CS, n1));
                    r0 += s[4 * j] + s[4 * j + 1]; r1 += s[4 * j + 2] + s[4 * j + 3];
                }
                l0 = fmaf(l0, sc0, r0); l1 = fmaf(l1, sc1, r1);
            };
            auto to_p = [&]() {
#pragma unroll
                for (int i = 0; i < 32; i++) pp[i] = pack2(s[2 * i], s[2 * i + 1]);
#pragma unroll
                for (int j = 0; j < 8; j++) { o[4 * j] *= sc0; o[4 * j + 1] *= sc0; o[4 * j + 2] *= sc1; o[4 * j + 3] *= sc1; }
            };
            mbar_wait(bars + B_QIN * 8, 0);
            {
                const uint32_t sl = ring.acquire();
                TS(13);
                turn_wait();
                qk_issue(sl);
                turn_pass();
                wg_commit();
            }
#pragma unroll 1
            for (int it = 0;; it++) {
                wg_wait<1>();
                pin(s);
                ring.release(lane);
                softmax(it == 3 && w == 1);
                pin(s);
                wg_wait<0>();
                pin(o); pin(pp);
                if (it) ring.release(lane);
                to_p();
                pin(s); pin(o); pin(pp);
                if (it == 3) break;
                ring.acquire2(s0, s1);
                turn_wait();
                qk_issue(s0);
                pv_issue(s1);
                turn_pass();
            }
            pv_issue(ring.acquire());
            l0 += __shfl_xor_sync(~0u, l0, 1); l1 += __shfl_xor_sync(~0u, l1, 1);
            l0 += __shfl_xor_sync(~0u, l0, 2); l1 += __shfl_xor_sync(~0u, l1, 2);
            const int row = wq * 16 + (lane >> 2);
            const uint32_t ml = sb + OFF_INBOX;
            if (c4 == 0) { sts64f(ml + w * 512 + row * 8, m0, l0); sts64f(ml + w * 512 + row * 8 + 64, m1, l1); }
            wg_wait<0>();
            pin(o); pin(pp);
            ring.release(lane);
            TS(14);
            float mine[16];
#pragma unroll
            for (int j = 0; j < 4; j++) {
                if (w == 0) sts128f(H + j * 2048 + wt * 16, o[16 + 4 * j], o[17 + 4 * j], o[18 + 4 * j], o[19 + 4 * j]);
                else sts128f(H + 8192 + j * 2048 + wt * 16, o[4 * j], o[4 * j + 1], o[4 * j + 2], o[4 * j + 3]);
            }
#pragma unroll
            for (int i = 0; i < 16; i++) mine[i] = w == 0 ? o[i] : o[16 + i];
            bar_sync(10, 256);
            const float2 u0 = lds64f(ml + (w ^ 1) * 512 + row * 8), u1 = lds64f(ml + (w ^ 1) * 512 + row * 8 + 64);
            const float x0 = fmaxf(m0, u0.x), x1 = fmaxf(m1, u1.x);
            float a0 = ex2((m0 - x0) * CS), b0 = ex2((u0.x - x0) * CS), a1 = ex2((m1 - x1) * CS), b1 = ex2((u1.x - x1) * CS);
            const float i0 = __fdividef(1.f, fmaf(a0, l0, b0 * u0.y)), i1 = __fdividef(1.f, fmaf(a1, l1, b1 * u1.y));
            a0 *= i0; b0 *= i0; a1 *= i1; b1 *= i1;
            uint32_t pk[8];
#pragma unroll
            for (int j = 0; j < 4; j++) {
                const float4 v = lds128f(H + (w ^ 1) * 8192 + j * 2048 + wt * 16);
                pk[2 * j] = pack2(fmaf(a0, mine[4 * j], b0 * v.x), fmaf(a0, mine[4 * j + 1], b0 * v.y));
                pk[2 * j + 1] = pack2(fmaf(a1, mine[4 * j + 2], b1 * v.z), fmaf(a1, mine[4 * j + 3], b1 * v.w));
            }
            const uint32_t og = H + 16384 + wq * 2048;
            {
                const uint32_t ra = og + (((lane >> 3) & 1) * 8 + (lane & 7)) * 128;
                stsm4(ra + (((4 * w + (lane >> 4)) ^ (lane & 7)) << 4), pk[0], pk[1], pk[2], pk[3]);
                stsm4(ra + (((4 * w + 2 + (lane >> 4)) ^ (lane & 7)) << 4), pk[4], pk[5], pk[6], pk[7]);
            }
            __syncwarp();
            {
                const uint32_t off = (lane >> 2) * 128 + (((4 * w + c4) ^ (lane >> 2)) << 4);
                const uint4 v0 = lds128(og + off), v1 = lds128(og + off + 1024);
                unsigned char* dst = g_o + (size_t)(abh * PADROWS + 8 + qt * 64 + wq * 16) * 128 + off;
                stg128(dst, v0); stg128(dst + 1024, v1);
            }
            bar_arrive(6, 288);
            TS(15);
        }

        uint32_t x2r[8];
        uint32_t dwr[15];
        {
#pragma unroll
            for (int i = 0; i < 15; i++) dwr[i] = __ldg(reinterpret_cast<const uint32_t*>(p.dw + i * 256 + tile * 64) + lane);
            float d[24];
            uint32_t xr[12];
            mbar_wait(bars + B_X1IN * 8, 0);
#pragma unroll
            for (int j = 0; j < 3; j++) ldsm4t(xa + j * 2048, xr[4 * j], xr[4 * j + 1], xr[4 * j + 2], xr[4 * j + 3]);
            ring.acquire2(s0, s1);
            turn_wait();
            mbar_wait(bars + B_OIN * 8, 0);
            TS(16);
            issue_half<XCH>(d, s0, H, 0);
            mbar_wait(bars + B_OIN * 8 + 8, 0);
            issue_half<XCH>(d, s1, H + 2 * XCH, 1);
            turn_pass();
            ring.acquire2(s0, s1);
            wg_wait<0>();
            pin(d);
            ring.release(lane); ring.release(lane);
#pragma unroll
            for (int i = 0; i < 12; i++) xr[i] = pack2(d[2 * i] + blo(xr[i]), d[2 * i + 1] + bhi(xr[i]));
            if (c4 == 0) { xr[0] = (xr[0] & 0xffff0000u) | 0x3F80u; xr[1] = (xr[1] & 0xffff0000u) | 0x3F80u; }
#pragma unroll
            for (int j = 0; j < 3; j++) stsm4t(xa + j * 2048, xr[4 * j], xr[4 * j + 1], xr[4 * j + 2], xr[4 * j + 3]);
#pragma unroll
            for (int i = 0; i < 8; i++) x2r[i] = xr[2 + i];
            publish(2, P + tile * XCH, XCH, 384);
            TS(17);
        }
        {
            float da[24], db[24];
            zero(da); zero(db);
#pragma unroll 1
            for (int h = 0; h < 2; h++) {
                if (h) { ring.acquire2(s0, s1); turn_wait(); xwait(2); }
                issue_half<XCH>(da, s0, P + 2 * (r ^ h) * XCH, 1);
                issue_half<XCH>(db, s1, P + 2 * (r ^ h) * XCH, 1);
            }
            turn_pass();
            mbar_wait(bars + B_ST * 8, 0);
            float st[24];
#pragma unroll
            for (int j = 0; j < 6; j++) {
                float4 v = lds128f(sb + OFF_STATS + (8 * j + 2 * c4) * 8);
                st[4 * j] = v.x; st[4 * j + 1] = v.y; st[4 * j + 2] = v.z; st[4 * j + 3] = v.w;
            }
            wg_wait<2>();
            ring.release(lane); ring.release(lane);
            wg_wait<0>();
            pin(da); pin(db);
            ring.release(lane); ring.release(lane);
            TS(18);
            uint32_t pk[12];
#pragma unroll
            for (int hh = 0; hh < 2; hh++) {
                const float ca = __shfl_sync(~0u, da[2 * hh], lane & 28), cb = __shfl_sync(~0u, db[2 * hh], lane & 28);
#pragma unroll
                for (int j = 0; j < 6; j++) {
                    const float u0 = fmaf(-st[4 * j], ca, da[4 * j + 2 * hh] * st[4 * j + 1]);
                    const float u1 = fmaf(-st[4 * j + 2], ca, da[4 * j + 2 * hh + 1] * st[4 * j + 3]);
                    const float v0 = fmaf(-st[4 * j], cb, db[4 * j + 2 * hh] * st[4 * j + 1]);
                    const float v1 = fmaf(-st[4 * j + 2], cb, db[4 * j + 2 * hh + 1] * st[4 * j + 3]);
                    const uint32_t g = pack2(fmaf(u0, tanh_fast(v0), u0), fmaf(u1, tanh_fast(v1), u1));
                    const int t0 = pt * 32 - 8 + 8 * j;
                    pk[2 * j + hh] = (t0 >= 0 && t0 < T_) ? g : 0u;
                }
            }
            const uint32_t gs = H + 16384 + w * XCH;
#pragma unroll
            for (int j = 0; j < 3; j++) stsm4t(gs + toff + j * 2048, pk[4 * j], pk[4 * j + 1], pk[4 * j + 2], pk[4 * j + 3]);
            ring.acquire2(s0, s1);
            bar_sync(2 + w, 128);
            float c0[8], c1[8];
#pragma unroll
            for (int i = 0; i < 8; i++) { c0[i] = 0.f; c1[i] = 0.f; }
#pragma unroll
            for (int k = 0; k < 22; k++) {
                const uint32_t v = lds32(gs + (8 * wq + 1 + k) * 128 + (((lane >> 2) ^ ((1 + k) & 7)) << 4) + c4 * 4);
                const float v0 = blo(v), v1 = bhi(v);
#pragma unroll
                for (int i = 0; i < 8; i++)
                    if (k - i >= 0 && k - i < 15) { c0[i] = fmaf(v0, blo(dwr[k - i]), c0[i]); c1[i] = fmaf(v1, bhi(dwr[k - i]), c1[i]); }
            }
#pragma unroll
            for (int i = 0; i < 8; i++) {
                const float h0 = 0.5f * c0[i], h1 = 0.5f * c1[i];
                sts32(H + tile * HCH + (8 * wq + i) * 128 + (((lane >> 2) ^ i) << 4) + c4 * 4,
                      pack2(fmaf(h0, tanh_fast(h0), h0), fmaf(h1, tanh_fast(h1), h1)));
            }
            publish(3, H + tile * HCH, HCH, 256);
            TS(19);
        }
        {
            float d[16];
            issue_half<HCH>(d, s0, H + 2 * r * HCH, 0);
            turn_wait();
            xwait(3);
            issue_half<HCH>(d, s1, H + 2 * (r ^ 1) * HCH, 1);
            turn_pass();
            ring.acquire2(s0, s1);
            sts128(P + (wt >> 6 ? (tile ^ 2) : tile) * XCH + 4096 + (wt & 63) * 16, 0x3F803F80u, 0x3F803F80u, 0x3F803F80u, 0x3F803F80u);
            wg_wait<0>();
            pin(d);
            ring.release(lane); ring.release(lane);
#pragma unroll
            for (int i = 0; i < 8; i++) x2r[i] = pack2(d[2 * i] + blo(x2r[i]), d[2 * i + 1] + bhi(x2r[i]));
            stsm4t(xa, x2r[0], x2r[1], x2r[2], x2r[3]);
            stsm4t(xa + 2048, x2r[4], x2r[5], x2r[6], x2r[7]);
            publish(4, P + tile * XCH, HCH, 384);
            TS(20);
        }
    }

    xwait(5);
    cluster_arrive();
    TS(24);
    {
        float a[2][8], s[2], q[2];
        const int row0 = 16 * r + 2 * warp;
#pragma unroll
        for (int i = 0; i < 2; i++) {
            const uint4 v = lds128(P + (lane >> 3) * XCH + (row0 + i) * 128 + (((lane & 7) ^ ((row0 + i) & 7)) << 4));
            a[i][0] = blo(v.x); a[i][1] = bhi(v.x); a[i][2] = blo(v.y); a[i][3] = bhi(v.y);
            a[i][4] = blo(v.z); a[i][5] = bhi(v.z); a[i][6] = blo(v.w); a[i][7] = bhi(v.w);
            s[i] = ((a[i][0] + a[i][1]) + (a[i][2] + a[i][3])) + ((a[i][4] + a[i][5]) + (a[i][6] + a[i][7]));
            q[i] = 0.f;
#pragma unroll
            for (int k = 0; k < 8; k++) q[i] = fmaf(a[i][k], a[i][k], q[i]);
        }
#pragma unroll
        for (int o = 16; o > 0; o >>= 1) {
#pragma unroll
            for (int i = 0; i < 2; i++) { s[i] += __shfl_xor_sync(~0u, s[i], o); q[i] += __shfl_xor_sync(~0u, q[i], o); }
        }
#pragma unroll
        for (int i = 0; i < 2; i++) {
            const float mean = s[i] * (1.f / 256.f);
            const float rstd = rsqrtf(fmaxf(fmaf(-mean, mean, q[i] * (1.f / 256.f)), 0.f) + 1e-5f);
            const float nb = -mean * rstd;
            uint4 v;
            v.x = pack2(fmaf(a[i][0], rstd, nb), fmaf(a[i][1], rstd, nb)); v.y = pack2(fmaf(a[i][2], rstd, nb), fmaf(a[i][3], rstd, nb));
            v.z = pack2(fmaf(a[i][4], rstd, nb), fmaf(a[i][5], rstd, nb)); v.w = pack2(fmaf(a[i][6], rstd, nb), fmaf(a[i][7], rstd, nb));
            const int t = pt * 32 + row0 + i;
            if (t < T_) stg128(p.out + (size_t)(b * T_ + t) * 256 + lane * 8, v);
        }
    }
    TS(25);
    TG(31);
    TSDUMP();
    if (w == 0) turn_wait();
    cluster_wait();
}

typedef CUresult (*EncodeFn)(CUtensorMap*, CUtensorMapDataType, cuuint32_t, void*, const cuuint64_t*, const cuuint64_t*,
                             const cuuint32_t*, const cuuint32_t*, CUtensorMapInterleave, CUtensorMapSwizzle,
                             CUtensorMapL2promotion, CUtensorMapFloatOOBfill);

}

extern "C" void kernel_launch(void* const* d_in, const int* in_sizes, int n_in, void* d_out, int out_size) {
    static EncodeFn encode = nullptr;
    if (!encode) {
        void* fn = nullptr;
        cudaDriverEntryPointQueryResult qr;
        cudaGetDriverEntryPoint("cuTensorMapEncodeTiled", &fn, cudaEnableDefault, &qr);
        encode = (EncodeFn)fn;
        cudaFuncSetAttribute(conformer_kernel, cudaFuncAttributeMaxDynamicSharedMemorySize, SMEM_LAUNCH);
    }
    Params p;
    const cuuint32_t ones[3] = {1, 1, 1};
    {
        const cuuint64_t dims[3] = {256, T_, 2};
        const cuuint64_t strides[2] = {512, 512ull * T_};
        const cuuint32_t box[3] = {64, 32, 1};
        encode(&p.tm[0], CU_TENSOR_MAP_DATA_TYPE_BFLOAT16, 3, d_in[0], dims, strides, box, ones, CU_TENSOR_MAP_INTERLEAVE_NONE,
               CU_TENSOR_MAP_SWIZZLE_128B, CU_TENSOR_MAP_L2_PROMOTION_L2_256B, CU_TENSOR_MAP_FLOAT_OOB_FILL_NONE);
    }
    const int idx[8] = {1, 2, 3, 4, 5, 7, 8, 9};
    const int rows[8] = {256, 1024, 256, 256, 256, 256, 256, 1024};
    const int cols[8] = {1024, 256, 768, 256, 512, 256, 1024, 256};
    for (int i = 0; i < 8; i++) {
        const cuuint64_t dims[2] = {(cuuint64_t)cols[i], (cuuint64_t)rows[i]};
        const cuuint64_t strides[1] = {(cuuint64_t)cols[i] * 2};
        const cuuint32_t box[2] = {64, 128};
        encode(&p.tm[1 + i], CU_TENSOR_MAP_DATA_TYPE_BFLOAT16, 2, d_in[idx[i]], dims, strides, box, ones, CU_TENSOR_MAP_INTERLEAVE_NONE,
               CU_TENSOR_MAP_SWIZZLE_128B, CU_TENSOR_MAP_L2_PROMOTION_L2_128B, CU_TENSOR_MAP_FLOAT_OOB_FILL_NONE);
        p.w[i] = (const char*)d_in[idx[i]];
    }
    {
        void* kv = nullptr;
        cudaGetSymbolAddress(&kv, g_kqv);
        const cuuint64_t dims[2] = {64, 24576};
        const cuuint64_t strides[1] = {128};
        const cuuint32_t box[2] = {64, 128};
        encode(&p.tm[9], CU_TENSOR_MAP_DATA_TYPE_BFLOAT16, 2, kv, dims, strides, box, ones, CU_TENSOR_MAP_INTERLEAVE_NONE,
               CU_TENSOR_MAP_SWIZZLE_NONE, CU_TENSOR_MAP_L2_PROMOTION_L2_128B, CU_TENSOR_MAP_FLOAT_OOB_FILL_NONE);
    }
    p.w[8] = (const char*)d_in[0];
    p.dw = (const __nv_bfloat16*)d_in[6];
    p.out = (__nv_bfloat16*)d_out;
    conformer_kernel<<<NCTA, NTHREADS, SMEM_LAUNCH>>>(p);
}
```

```cpp
#include <cuda_runtime.h>
#include <cuda_bf16.h>
#include <cuda.h>
#include <stdint.h>
#include <type_traits>

namespace {

constexpr int T_ = 1000;
constexpr int NCTA = 128;
constexpr int NTHREADS = 512;
constexpr int NSLOT = 5;
constexpr int SLOT = 16384;
constexpr int NLOADS = 56;

constexpr uint32_t OFF_RING = 0;
constexpr uint32_t OFF_P = 163840;
constexpr uint32_t OFF_H = 188416;
constexpr uint32_t OFF_INBOX = 221184;
constexpr uint32_t OFF_STATS = 229376;
constexpr uint32_t OFF_BARS = 229888;
constexpr uint32_t SMEM_BYTES = 230400;
constexpr uint32_t XCH = 6144;
constexpr uint32_t HCH = 4096;

constexpr int B_FULL = 0, B_EMPTY = 10, B_XR = 20, B_OIN = 22, B_HF = 24, B_INB = 28, B_QIN = 30, B_X1IN = 31, B_ST = 32, B_RDY = 33;

constexpr int PADROWS = 1040;
constexpr int FS = 8;

struct Params {
    CUtensorMap tm[10];
    const char* w[9];
    const __nv_bfloat16* dw;
    __nv_bfloat16* out;
    uint32_t zero;
};

__device__ __align__(1024) unsigned char g_kqv[3 * 8 * 1024 * 128];
__device__ __align__(1024) unsigned char g_o[8 * PADROWS * 128];
__device__ __align__(1024) unsigned char g_x1[8 * PADROWS * 128];
__device__ uint32_t g_flag_qk[8 * 32 * FS];
__device__ uint32_t g_flag_v[8 * 32 * FS];
__device__ uint32_t g_flag_o[2 * 16 * 4 * FS];
__device__ uint32_t g_epoch[NCTA * FS];

#define TS(i) do { } while (0)
#define TG(i) do { } while (0)
#define TSINIT() do { } while (0)
#define TSDUMP() do { } while (0)
constexpr uint32_t SMEM_LAUNCH = SMEM_BYTES;

__device__ __forceinline__ uint32_t smem_u32(const void* p) { return (uint32_t)__cvta_generic_to_shared(p); }
__device__ __forceinline__ void mbar_init(uint32_t b, uint32_t c) { asm volatile("mbarrier.init.shared::cta.b64 [%0], %1;" ::"r"(b), "r"(c) : "memory"); }
__device__ __forceinline__ void mbar_arrive(uint32_t b) { asm volatile("mbarrier.arrive.shared::cta.b64 _, [%0];" ::"r"(b) : "memory"); }
__device__ __forceinline__ void mbar_arrive_tx(uint32_t b, uint32_t tx) { asm volatile("mbarrier.arrive.expect_tx.shared::cta.b64 _, [%0], %1;" ::"r"(b), "r"(tx) : "memory"); }
__device__ __forceinline__ void mbar_wait(uint32_t b, uint32_t ph) {
    asm volatile("{\n.reg .pred p, q;\n.reg .u32 c;\nmov.u32 c, 0;\n"
                 "MW_LOOP:\n.pragma \"nounroll\";\n"
                 "mbarrier.try_wait.parity.shared::cta.b64 p, [%0], %1;\n"
                 "add.u32 c, c, 1;\nsetp.lt.u32 q, c, 65536;\nnot.pred p, p;\nand.pred p, p, q;\n@p bra MW_LOOP;\n}"
                 ::"r"(b), "r"(ph) : "memory");
}
__device__ __forceinline__ uint32_t mapa(uint32_t a, uint32_t r) { uint32_t o; asm("mapa.shared::cluster.u32 %0, %1, %2;" : "=r"(o) : "r"(a), "r"(r)); return o; }
__device__ __forceinline__ void fence_async_smem() { asm volatile("fence.proxy.async.shared::cta;" ::: "memory"); }
__device__ __forceinline__ void fence_async_global() { asm volatile("fence.proxy.async.global;" ::: "memory"); }
__device__ __forceinline__ void bar_sync(int id, int n) { asm volatile("bar.sync %0, %1;" ::"r"(id), "r"(n) : "memory"); }
__device__ __forceinline__ void bar_arrive(int id, int n) { asm volatile("bar.arrive %0, %1;" ::"r"(id), "r"(n) : "memory"); }
__device__ __forceinline__ void cluster_arrive() { asm volatile("barrier.cluster.arrive.relaxed.aligned;" ::: "memory"); }
__device__ __forceinline__ void cluster_wait() { asm volatile("barrier.cluster.wait.aligned;" ::: "memory"); }

__device__ __forceinline__ void ring_load(uint32_t dst, const CUtensorMap* tm, int c0, int c1, uint32_t bar) {
    asm volatile("{\n.reg .pred p;\nelect.sync _|p, 0xffffffff;\n"
                 "@p mbarrier.arrive.expect_tx.shared::cta.b64 _, [%2], 16384;\n"
                 "@p cp.async.bulk.tensor.2d.shared::cluster.global.mbarrier::complete_tx::bytes [%0], [%1, {%3, %4}], [%2];\n}"
                 ::"r"(dst), "l"(tm), "r"(bar), "r"(c0), "r"(c1) : "memory");
}
__device__ __forceinline__ void ring_load_both(uint32_t dst, const CUtensorMap* tm, int c1, uint32_t bar) {
    asm volatile("{\n.reg .pred p;\nelect.sync _|p, 0xffffffff;\n"
                 "@p mbarrier.arrive.expect_tx.shared::cta.b64 _, [%2], 16384;\n"
                 "@p cp.async.bulk.tensor.2d.shared::cluster.global.mbarrier::complete_tx::bytes.multicast::cluster [%0], [%1, {0, %3}], [%2], %4;\n}"
                 ::"r"(dst), "l"(tm), "r"(bar), "r"(c1), "h"((uint16_t)3) : "memory");
}
__device__ __forceinline__ void ring_arm_signal(uint32_t bar, uint32_t peer_rdy) {
    asm volatile("{\n.reg .pred p;\nelect.sync _|p, 0xffffffff;\n"
                 "@p mbarrier.arrive.expect_tx.shared::cta.b64 _, [%0], 16384;\n"
                 "@p mbarrier.arrive.relaxed.cluster.shared::cluster.b64 _, [%1];\n}"
                 ::"r"(bar), "r"(peer_rdy) : "memory");
}
__device__ __forceinline__ void tma3d(uint32_t dst, const CUtensorMap* tm, int c0, int c1, int c2, uint32_t bar) {
    asm volatile("cp.async.bulk.tensor.3d.shared::cluster.global.mbarrier::complete_tx::bytes [%0], [%1, {%3, %4, %5}], [%2];"
                 ::"r"(dst), "l"(tm), "r"(bar), "r"(c0), "r"(c1), "r"(c2) : "memory");
}
__device__ __forceinline__ void bulk_g2s(uint32_t dst, const void* src, uint32_t bytes, uint32_t bar) {
    asm volatile("cp.async.bulk.shared::cluster.global.mbarrier::complete_tx::bytes [%0], [%1], %2, [%3];" ::"r"(dst), "l"(src), "r"(bytes), "r"(bar) : "memory");
}
__device__ __forceinline__ void peer_copy(uint32_t dst, uint32_t src, uint32_t bytes, uint32_t rbar) {
    asm volatile("{\n.reg .pred p;\nelect.sync _|p, 0xffffffff;\n"
                 "@p cp.async.bulk.shared::cluster.shared::cta.mbarrier::complete_tx::bytes [%0], [%1], %2, [%3];\n}"
                 ::"r"(dst), "r"(src), "r"(bytes), "r"(rbar) : "memory");
}
__device__ __forceinline__ void st_async4(uint32_t dst, uint32_t a, uint32_t b, uint32_t c, uint32_t d, uint32_t bar) {
    asm volatile("st.async.shared::cluster.mbarrier::complete_tx::bytes.v4.b32 [%0], {%1,%2,%3,%4}, [%5];" ::"r"(dst), "r"(a), "r"(b), "r"(c), "r"(d), "r"(bar) : "memory");
}
__device__ __forceinline__ void stsm4t(uint32_t a, uint32_t r0, uint32_t r1, uint32_t r2, uint32_t r3) {
    asm volatile("stmatrix.sync.aligned.m8n8.x4.trans.shared.b16 [%0], {%1,%2,%3,%4};" ::"r"(a), "r"(r0), "r"(r1), "r"(r2), "r"(r3) : "memory");
}
__device__ __forceinline__ void stsm4(uint32_t a, uint32_t r0, uint32_t r1, uint32_t r2, uint32_t r3) {
    asm volatile("stmatrix.sync.aligned.m8n8.x4.shared.b16 [%0], {%1,%2,%3,%4};" ::"r"(a), "r"(r0), "r"(r1), "r"(r2), "r"(r3) : "memory");
}
__device__ __forceinline__ void ldsm4t(uint32_t a, uint32_t& r0, uint32_t& r1, uint32_t& r2, uint32_t& r3) {
    asm volatile("ldmatrix.sync.aligned.m8n8.x4.trans.shared.b16 {%0,%1,%2,%3}, [%4];" : "=r"(r0), "=r"(r1), "=r"(r2), "=r"(r3) : "r"(a) : "memory");
}
__device__ __forceinline__ uint4 lds128(uint32_t a) { uint4 v; asm volatile("ld.shared.v4.b32 {%0,%1,%2,%3}, [%4];" : "=r"(v.x), "=r"(v.y), "=r"(v.z), "=r"(v.w) : "r"(a) : "memory"); return v; }
__device__ __forceinline__ float4 lds128f(uint32_t a) { float4 v; asm volatile("ld.shared.v4.f32 {%0,%1,%2,%3}, [%4];" : "=f"(v.x), "=f"(v.y), "=f"(v.z), "=f"(v.w) : "r"(a) : "memory"); return v; }
__device__ __forceinline__ float2 lds64f(uint32_t a) { float2 v; asm volatile("ld.shared.v2.f32 {%0,%1}, [%2];" : "=f"(v.x), "=f"(v.y) : "r"(a) : "memory"); return v; }
__device__ __forceinline__ uint32_t lds32(uint32_t a) { uint32_t v; asm volatile("ld.shared.b32 %0, [%1];" : "=r"(v) : "r"(a) : "memory"); return v; }
__device__ __forceinline__ void sts128(uint32_t a, uint32_t x, uint32_t y, uint32_t z, uint32_t w) { asm volatile("st.shared.v4.b32 [%0], {%1,%2,%3,%4};" ::"r"(a), "r"(x), "r"(y), "r"(z), "r"(w) : "memory"); }
__device__ __forceinline__ void sts128f(uint32_t a, float x, float y, float z, float w) { asm volatile("st.shared.v4.f32 [%0], {%1,%2,%3,%4};" ::"r"(a), "f"(x), "f"(y), "f"(z), "f"(w) : "memory"); }
__device__ __forceinline__ void sts64f(uint32_t a, float x, float y) { asm volatile("st.shared.v2.f32 [%0], {%1,%2};" ::"r"(a), "f"(x), "f"(y) : "memory"); }
__device__ __forceinline__ void sts32(uint32_t a, uint32_t x) { asm volatile("st.shared.b32 [%0], %1;" ::"r"(a), "r"(x) : "memory"); }
__device__ __forceinline__ void stg128(void* p, uint4 v) { asm volatile("st.global.v4.b32 [%0], {%1,%2,%3,%4};" ::"l"(p), "r"(v.x), "r"(v.y), "r"(v.z), "r"(v.w) : "memory"); }

__device__ __forceinline__ uint32_t pack2(float lo, float hi) { uint32_t r; asm("cvt.rn.bf16x2.f32 %0, %1, %2;" : "=r"(r) : "f"(hi), "f"(lo)); return r; }
__device__ __forceinline__ float blo(uint32_t v) { return __uint_as_float(v << 16); }
__device__ __forceinline__ float bhi(uint32_t v) { return __uint_as_float(v & 0xffff0000u); }
__device__ __forceinline__ float tanh_fast(float x) { float r; asm("tanh.approx.f32 %0, %1;" : "=f"(r) : "f"(x)); return r; }
__device__ __forceinline__ float ex2(float x) { float r; asm("ex2.approx.ftz.f32 %0, %1;" : "=f"(r) : "f"(x)); return r; }

__device__ __forceinline__ void flag_wait(const uint32_t* p, uint32_t e) {
#pragma unroll 1
    for (int i = 0; i < (1 << 22); i++) {
        uint32_t v;
        asm volatile("ld.acquire.gpu.global.u32 %0, [%1];" : "=r"(v) : "l"(p) : "memory");
        if (v == e) return;
    }
    __trap();
}
__device__ __forceinline__ uint32_t ld_epoch() {
    uint32_t v;
    asm volatile("ld.relaxed.gpu.global.u32 %0, [%1];" : "=r"(v) : "l"(&g_epoch[blockIdx.x * FS]) : "memory");
    return v + 1;
}
__device__ __forceinline__ void flag_set(uint32_t* p, uint32_t e) { asm volatile("st.release.gpu.global.u32 [%0], %1;" ::"l"(p), "r"(e) : "memory"); }

__device__ __forceinline__ uint32_t desc_lo(uint32_t addr) { return ((addr & 0x3FFFF) >> 4) | 0x10000u; }
__device__ __forceinline__ uint64_t mkdesc(uint32_t lo) { return (uint64_t)lo | (0x40000040ull << 32); }
__device__ __forceinline__ void wg_fence() { asm volatile("wgmma.fence.sync.aligned;" ::: "memory"); }
__device__ __forceinline__ void wg_commit() { asm volatile("wgmma.commit_group.sync.aligned;" ::: "memory"); }
template <int N> __device__ __forceinline__ void wg_wait() { asm volatile("wgmma.wait_group.sync.aligned %0;" ::"n"(N) : "memory"); }
template <int N> __device__ __forceinline__ void pin(float (&d)[N]) {
#pragma unroll
    for (int i = 0; i < N; i++) asm volatile("" : "+f"(d[i])::"memory");
}
template <int N> __device__ __forceinline__ void pin(uint32_t (&d)[N]) {
#pragma unroll
    for (int i = 0; i < N; i++) asm volatile("" : "+r"(d[i])::"memory");
}

template <typename Tp, int N> __device__ __forceinline__ void zero(Tp (&d)[N]) {
#pragma unroll
    for (int i = 0; i < N; i++) d[i] = 0;
    pin(d);
}

#define F4(d, i) "+f"(d[i]), "+f"(d[i + 1]), "+f"(d[i + 2]), "+f"(d[i + 3])
#define F16(d, i) F4(d, i), F4(d, i + 4), F4(d, i + 8), F4(d, i + 12)

__device__ __forceinline__ void mma_t(float (&d)[16], uint64_t a, uint64_t b, int acc) {
    asm volatile("{.reg .pred p; setp.ne.b32 p, %18, 0;\n"
                 "wgmma.mma_async.sync.aligned.m64n32k16.f32.bf16.bf16 {%0,%1,%2,%3,%4,%5,%6,%7,%8,%9,%10,%11,%12,%13,%14,%15}, %16, %17, p, 1, 1, 1, 0;}\n"
                 : F16(d, 0) : "l"(a), "l"(b), "r"(acc));
}
__device__ __forceinline__ void mma_t(float (&d)[20], uint64_t a, uint64_t b, int acc) {
    asm volatile("{.reg .pred p; setp.ne.b32 p, %22, 0;\n"
                 "wgmma.mma_async.sync.aligned.m64n40k16.f32.bf16.bf16 {%0,%1,%2,%3,%4,%5,%6,%7,%8,%9,%10,%11,%12,%13,%14,%15,%16,%17,%18,%19}, %20, %21, p, 1, 1, 1, 0;}\n"
                 : F16(d, 0), F4(d, 16) : "l"(a), "l"(b), "r"(acc));
}
__device__ __forceinline__ void mma_t(float (&d)[24], uint64_t a, uint64_t b, int acc) {
    asm volatile("{.reg .pred p; setp.ne.b32 p, %26, 0;\n"
                 "wgmma.mma_async.sync.aligned.m64n48k16.f32.bf16.bf16 {%0,%1,%2,%3,%4,%5,%6,%7,%8,%9,%10,%11,%12,%13,%14,%15,%16,%17,%18,%19,%20,%21,%22,%23}, %24, %25, p, 1, 1, 1, 0;}\n"
                 : F16(d, 0), F4(d, 16), F4(d, 20) : "l"(a), "l"(b), "r"(acc));
}
__device__ __forceinline__ void mma_qk(float (&d)[64], uint64_t a, uint64_t b, int acc) {
    asm volatile("{.reg .pred p; setp.ne.b32 p, %66, 0;\n"
                 "wgmma.mma_async.sync.aligned.m64n128k16.f32.bf16.bf16 {%0,%1,%2,%3,%4,%5,%6,%7,%8,%9,%10,%11,%12,%13,%14,%15,%16,%17,%18,%19,%20,%21,%22,%23,%24,%25,%26,%27,%28,%29,%30,%31,"
                 "%32,%33,%34,%35,%36,%37,%38,%39,%40,%41,%42,%43,%44,%45,%46,%47,%48,%49,%50,%51,%52,%53,%54,%55,%56,%57,%58,%59,%60,%61,%62,%63}, %64, %65, p, 1, 1, 0, 0;}\n"
                 : F16(d, 0), F16(d, 16), F16(d, 32), F16(d, 48) : "l"(a), "l"(b), "r"(acc));
}
__device__ __forceinline__ void mma_pv(float (&d)[36], uint32_t a0, uint32_t a1, uint32_t a2, uint32_t a3, uint64_t b) {
    asm volatile("wgmma.mma_async.sync.aligned.m64n72k16.f32.bf16.bf16 {%0,%1,%2,%3,%4,%5,%6,%7,%8,%9,%10,%11,%12,%13,%14,%15,%16,%17,%18,%19,%20,%21,%22,%23,%24,%25,%26,%27,%28,%29,%30,%31,%32,%33,%34,%35}, "
                 "{%36,%37,%38,%39}, %40, 1, 1, 1, 1;\n"
                 : F16(d, 0), F16(d, 16), F4(d, 32) : "r"(a0), "r"(a1), "r"(a2), "r"(a3), "l"(b));
}

template <uint32_t CSTRIDE, int N>
__device__ __forceinline__ void issue_half(float (&d)[N], uint32_t alo, uint32_t blo_, int acc) {
    const uint64_t a = mkdesc(alo), b = mkdesc(blo_);
    wg_fence();
#pragma unroll
    for (int k = 0; k < 8; k++) mma_t(d, a + k * 128, b + (k >> 2) * (CSTRIDE >> 4) + (k & 3) * 2, k == 0 ? acc : 1);
    wg_commit();
}

__device__ __forceinline__ uint32_t load_code(int n, int r, int w, int abh) {
    const int tile = 2 * r + w;
    int m, col, row;
    if (n < 16 || n >= 40) {
        const int k = n < 16 ? n : n - 40;
        m = n < 16 ? 1 : 7;
        if (k < 8) { col = 8 * r + (k & 6) + w; row = (k & 1) ^ r; }
        else {
            const int kk = k == 11 ? 12 : (k == 12 ? 11 : k);
            m++; col = kk < 12 ? (tile ^ 2) : tile; row = 4 * r + (kk & 3);
        }
    } else if (n < 24) {
        const int k = n - 16;
        m = 3;
        if (k < 4) { col = tile + ((k & 1) ? 0 : 4); row = (k >> 1) ^ r; }
        else { col = 8 + tile; row = (k & 1) ^ r; }
    } else if (n < 32) {
        const int k = n - 24;
        const bool isv = (k == 7) || (k >= 2 && !(k & 1));
        const int i = isv ? (k == 7 ? 3 : (k >> 1) - 1) : ((k + 1) >> 1);
        m = 9; col = 0; row = (isv ? 128 : 0) + abh * 8 + 2 * i + w;
    } else if (n < 34) { m = 4; col = tile; row = n - 32; }
    else if (n < 38) { const int k = n - 34; m = 5; col = tile + 4 * (k & 1); row = (k >> 1) ^ r; }
    else { m = 6; col = tile; row = (n & 1) ^ r; }
    return m | (col << 4) | (row << 8);
}

__global__ void __cluster_dims__(2, 1, 1) __launch_bounds__(NTHREADS, 1)
conformer_kernel(const __grid_constant__ Params p) {
    extern __shared__ __align__(1024) unsigned char smem_raw[];
    const uint32_t sb = smem_u32(smem_raw);
    const uint32_t bars = sb + OFF_BARS;
    const int tid = threadIdx.x;
    const int lane = tid & 31;
    const int warp = __shfl_sync(~0u, tid >> 5, 0);
    const int r = blockIdx.x & 1;
    const int pair = blockIdx.x >> 1;
    const int b = pair >> 5, pt = pair & 31;
    const int ah = pt >> 3, qt = (pt & 7) * 2 + r;
    const int abh = b * 4 + ah;

    TG(30);
    TSINIT();
    TS(0);
    const uint32_t P = sb + OFF_P, H = sb + OFF_H;
    auto xwait = [&](int j) { mbar_wait(bars + (B_XR + (j & 1)) * 8, (j >> 1) & 1); };

    if (warp >= 8) {
        asm volatile("setmaxnreg.dec.sync.aligned.u32 48;");
        if (warp >= 12) {
            if (warp == 12 && lane >= 2 && lane < 10) asm volatile("prefetch.tensormap [%0];" ::"l"(&p.tm[lane]) : "memory");
            cluster_arrive();
            cluster_wait();
            const int ut = tid & 127;
            const uint32_t a4 = P + (ut >> 2) * 128 + (2 * (ut & 3) + ((ut >> 2) & 1)) * 16;
            const uint32_t a8 = P + (32 + (ut >> 3)) * 128 + (ut & 7) * 16;
            auto accum = [](const uint4& v, float& s, float& q) {
                const float a0 = blo(v.x), a1 = bhi(v.x), a2 = blo(v.y), a3 = bhi(v.y), a4 = blo(v.z), a5 = bhi(v.z), a6 = blo(v.w), a7 = bhi(v.w);
                s += ((a0 + a1) + (a2 + a3)) + ((a4 + a5) + (a6 + a7));
                q += fmaf(a0, a0, fmaf(a1, a1, fmaf(a2, a2, a3 * a3))) + fmaf(a4, a4, fmaf(a5, a5, fmaf(a6, a6, a7 * a7)));
            };
#pragma unroll 1
            for (int k = 0; k < 4; k++) {
                float s = 0.f, q = 0.f, s2 = 0.f, q2 = 0.f;
#pragma unroll 1
                for (int h = 0; h < 2; h++) {
                    if (h == 0 && k != 0) bar_sync(1, 384);
                    else xwait(k == 3 ? 4 : k);
                    const uint32_t off = 2 * (r ^ h) * XCH;
                    uint4 v0 = lds128(a4 + off), v1 = lds128((a4 ^ 16) + off), v2 = lds128(a4 + off + XCH), v3 = lds128((a4 ^ 16) + off + XCH);
                    uint4 v4 = make_uint4(0, 0, 0, 0), v5 = v4;
                    if (k == 2) { v4 = lds128(a8 + off); v5 = lds128(a8 + off + XCH); }
                    if (h == 1)
                        asm volatile("{\n.reg .pred p;\nsetp.ne.u32 p, %1, 0;\nGA:\nbar.arrive %0, 384;\n@p bra GA;\n}"
                                     ::"r"(5 + ((v3.w | v5.w) & p.zero)), "r"(p.zero) : "memory");
                    accum(v0, s, q); accum(v1, s, q); accum(v2, s, q); accum(v3, s, q);
                    if (k == 2) { accum(v4, s2, q2); accum(v5, s2, q2); }
                }
#pragma unroll
                for (int o = 1; o < 8; o <<= 1) {
                    if (o < 4) { s += __shfl_xor_sync(~0u, s, o); q += __shfl_xor_sync(~0u, q, o); }
                    if (k == 2) { s2 += __shfl_xor_sync(~0u, s2, o); q2 += __shfl_xor_sync(~0u, q2, o); }
                }
                const bool second = (ut & 7) == 1;
                if (second) { s = s2; q = q2; }
                const float mean = s * (1.f / 256.f);
                const float rstd = (k == 1 ? 1.f : 0.5f) * rsqrtf(fmaxf(fmaf(-mean, mean, q * (1.f / 256.f)), 0.f) + 1e-5f);
                if ((ut & 3) == 0 || second) sts64f(sb + OFF_STATS + (second ? 32 + (ut >> 3) : ut >> 2) * 8, mean * rstd, rstd);
                __syncwarp();
                if (lane == 0) mbar_arrive(bars + B_ST * 8);
                TS(2 + k);
                if (k == 1 && warp == 12) {
                    const uint32_t epoch = ld_epoch();
                    bar_sync(11, 288);
                    if (lane < 2) flag_set(&g_flag_v[((b * 4 + 2 * r + lane) * 32 + pt) * FS], epoch);
                    __syncwarp();
                    TS(13);
                }
            }
        } else if (warp < 10) {
            const int w = warp - 8;
            const uint32_t ring = sb + OFF_RING + w * NSLOT * SLOT;
            const uint32_t full = bars + (B_FULL + w * NSLOT) * 8;
            if (lane == 0) {
#pragma unroll
                for (int i = 0; i < NSLOT; i++) mbar_init(full + i * 8, 1);
                asm volatile("fence.mbarrier_init.release.cluster;" ::: "memory");
                fence_async_smem();
            }
            __syncwarp();
            cluster_arrive();
            TS(1);
#pragma unroll
            for (int n = 0; n < NSLOT; n++)
                ring_load(ring + n * SLOT, &p.tm[1], 64 * (8 * r + (n & 6) + w), 128 * ((n & 1) ^ r), full + n * 8);
            TS(2);
            const uint32_t code = load_code(lane, r, w, abh) | (load_code(lane + 32, r, w, abh) << 16);
            cluster_wait();
            uint32_t s = 0, ph = 0;
            int n = NSLOT;
#pragma unroll 1
            for (int seg = 0; seg < 2; seg++) {
#pragma unroll 1
                for (; n < (seg == 0 ? 22 : NLOADS); n++) {
                    const uint32_t c = __shfl_sync(~0u, code, n) >> (n & 32 ? 16 : 0);
                    mbar_wait(full + (B_EMPTY - B_FULL) * 8 + s * 8, ph);
                    ring_load(ring + s * SLOT, &p.tm[c & 15], (c & 0xf0) * 4, (c & 0xff00) >> 1, full + s * 8);
                    if (++s == NSLOT) { s = 0; ph ^= 1; }
                }
                if (seg == 1) break;
                const uint32_t epoch = ld_epoch();
                const uint32_t rdy = bars + (B_RDY + w) * 8;
#pragma unroll 1
                for (; n < 32; n++) {
                    const uint32_t c = __shfl_sync(~0u, code, n);
                    mbar_wait(full + (B_EMPTY - B_FULL) * 8 + s * 8, ph);
                    if (n < 24) {
                        if (lane == 0) mbar_arrive(full + s * 8);
                    } else if ((n & 1) == r) {
                        mbar_wait(rdy, (n >> 1) & 1);
                        if (n < 27 || n == 31) {
                            flag_wait((n < 26 ? g_flag_qk : g_flag_v) + (abh * 32 + lane) * FS, epoch);
                            __syncwarp();
                            fence_async_global();
                            TS(n < 26 ? 5 : (n == 26 ? 6 : 7));
                        }
                        ring_load_both(ring + s * SLOT, &p.tm[9], (c & 0xff00) >> 1, full + s * 8);
                    } else {
                        ring_arm_signal(full + s * 8, mapa(rdy, r ^ 1));
                    }
                    if (++s == NSLOT) { s = 0; ph ^= 1; }
                }
            }
        } else if (warp == 10) {
            if (lane == 0) {
                mbar_init(bars + B_XR * 8, 1);
                asm volatile("fence.mbarrier_init.release.cluster;" ::: "memory");
                fence_async_smem();
            }
            __syncwarp();
            cluster_arrive();
            if (lane == 0) {
                mbar_arrive_tx(bars + B_XR * 8, 16384);
#pragma unroll
                for (int i = 0; i < 4; i++) tma3d(P + i * XCH, &p.tm[0], i * 64, pt * 32, b, bars + B_XR * 8);
            }
            __syncwarp();
            cluster_wait();
            const uint32_t epoch = ld_epoch();
            if (lane == 0) {
                mbar_arrive_tx(bars + B_QIN * 8, 8192);
                mbar_arrive_tx(bars + B_X1IN * 8, 2 * XCH);
                mbar_arrive_tx(bars + B_OIN * 8, 2 * XCH);
                mbar_arrive_tx(bars + B_OIN * 8 + 8, 2 * XCH);
            }
            if (lane < 2) flag_wait(&g_flag_qk[(abh * 32 + 2 * qt + lane) * FS], epoch);
            __syncwarp();
            if (lane == 0) {
                fence_async_global();
                bulk_g2s(H + 24576, g_kqv + 1048576 + (size_t)(abh * 1024 + qt * 64) * 128, 8192, bars + B_QIN * 8);
            }
            if (lane < 12) {
                const int np = pt - 1 + (lane >> 2);
                if (np >= 0 && np < 32) flag_wait(&g_flag_v[((b * 4 + (lane & 3)) * 32 + np) * FS], epoch);
            }
            __syncwarp();
            if (lane == 0) {
                fence_async_global();
#pragma unroll
                for (int w = 0; w < 2; w++)
                    bulk_g2s(P + (2 * r + w) * XCH, g_x1 + (size_t)((b * 4 + 2 * r + w) * PADROWS + pt * 32) * 128, XCH, bars + B_X1IN * 8);
            }
            __syncwarp();
            bar_sync(9, 64);
            if (lane < 8) {
                const int q = (pt >> 1) + (lane < 4 ? 0 : ((pt & 1) ? 1 : -1));
                if (q >= 0 && q < 16) flag_wait(&g_flag_o[((b * 16 + q) * 4 + (lane & 3)) * FS], epoch);
            }
            __syncwarp();
            if (lane == 0) {
                fence_async_global();
#pragma unroll
                for (int i = 0; i < 4; i++)
                    bulk_g2s(H + i * XCH, g_o + (size_t)((b * 4 + i) * PADROWS + pt * 32) * 128, XCH, bars + (B_OIN + (i >> 1)) * 8);
            }
            __syncwarp();
        } else {
            if (lane < 9) {
                uint32_t kb = (lane < 2 || lane > 5) ? 4096 : (lane == 2 ? 3072 : (lane == 4 ? 2048 : 1024));
                size_t off = (size_t)blockIdx.x * kb;
                if (lane == 8) { kb = 8192; off = (size_t)min(b * T_ + pt * 32 + r * 16, 2 * T_ - 16) * 512; }
                asm volatile("cp.async.bulk.prefetch.L2.global [%0], %1;" ::"l"(p.w[lane] + off), "r"(kb) : "memory");
            }
            __syncwarp();
            cluster_arrive();
            cluster_wait();
            const uint32_t epoch = ld_epoch();
            bar_sync(4, 288);
            if (lane < 2) flag_set(&g_flag_qk[((b * 4 + 2 * r + lane) * 32 + pt) * FS], epoch);
            __syncwarp();
            bar_sync(6, 288);
            bar_arrive(9, 64);
            if (lane == 0) {
                flag_set(&g_flag_o[((b * 16 + qt) * 4 + ah) * FS], epoch);
                g_epoch[blockIdx.x * FS] = epoch;
            }
            __syncwarp();
        }
        TSDUMP();
        return;
    }

    if (lane == 0) {
        mbar_init(bars + (B_EMPTY + warp) * 8, 4);
        mbar_init(bars + (B_HF + warp) * 8, warp < 4 ? 8 : 1);
        if (warp < 3) mbar_init(bars + (warp == 2 ? B_ST : B_EMPTY + 8 + warp) * 8, 4);
        else mbar_init(bars + (warp < 6 ? B_XR - 2 + warp : B_RDY - 6 + warp) * 8, 1);
        asm volatile("fence.mbarrier_init.release.cluster;" ::: "memory");
    }
    sts128(P + (tid >> 6) * XCH + 4096 + (tid & 63) * 16, 0x3F803F80u, 0x3F803F80u, 0x3F803F80u, 0x3F803F80u);
    fence_async_smem();
    __syncwarp();
    cluster_arrive();
    asm volatile("setmaxnreg.inc.sync.aligned.u32 208;");
    const int w = warp >> 2, wq = warp & 3;
    const int tile = 2 * r + w;
    const int wt = tid & 127;
    const int c4 = lane & 3;
    const uint32_t rbase = sb + OFF_RING + w * NSLOT * SLOT, fbar = bars + (B_FULL + w * NSLOT) * 8;
    const uint32_t rdesc = desc_lo(rbase);
    auto acq = [&](int n) { mbar_wait(fbar + (n % NSLOT) * 8, (n / NSLOT) & 1); };
    auto rel = [&](int n) { if (lane == 0) mbar_arrive(fbar + (B_EMPTY - B_FULL + n % NSLOT) * 8); };
    const uint32_t pown = desc_lo(P + 2 * r * XCH), prem = desc_lo(P + 2 * (r ^ 1) * XCH), hdesc = desc_lo(H);
    const uint32_t toff = ((lane >> 4) * 8 + (lane & 7)) * 128 + (((2 * wq + ((lane >> 3) & 1)) ^ (lane & 7)) << 4);
    const uint32_t xa = P + tile * XCH + toff;
    auto turn_wait = [&]() { bar_sync(7 + w, 256); };
    auto turn_pass = [&]() { bar_arrive(8 - w, 256); };
    if (w == 1) turn_pass();

    auto publish = [&](int j, uint32_t src, uint32_t bytes, int nsync) {
        const uint32_t bar = bars + (B_XR + (j & 1)) * 8;
        fence_async_smem();
        bar_sync(2 + w, 128);
        if (wq == 0) peer_copy(mapa(src, r ^ 1), src, bytes, mapa(bar, r ^ 1));
        if (tid == 32) mbar_arrive_tx(bar, 2 * bytes);
        bar_sync(nsync == 384 ? 1 : 10, nsync);
    };
    auto gate = [&](int j) { xwait(j); bar_sync(5, 384); };
    auto load_stats = [&](auto& st, int parity) {
        mbar_wait(bars + B_ST * 8, parity);
#pragma unroll
        for (int j = 0; j < (int)(sizeof(st) / 16); j++) {
            const float4 v = lds128f(sb + OFF_STATS + (8 * j + 2 * c4) * 8);
            st[4 * j] = v.x; st[4 * j + 1] = v.y; st[4 * j + 2] = v.z; st[4 * j + 3] = v.w;
        }
    };
    bar_sync(10, 256);
    cluster_wait();
    uint32_t xr[8];
    xwait(0);
    ldsm4t(xa, xr[0], xr[1], xr[2], xr[3]);
    ldsm4t(xa + 2048, xr[4], xr[5], xr[6], xr[7]);
    acq(0); acq(1);

#pragma unroll 1
    for (int ffi = 0; ffi < 2; ffi++) {
        auto mm = [&](auto& d, int n, uint32_t bd, auto cs, int acc) {
            const uint32_t z = p.zero * (ffi + n + 1);
            issue_half<decltype(cs)::value>(d, rdesc + z + (n % NSLOT) * (SLOT >> 4), bd + z, acc);
        };
        constexpr std::integral_constant<uint32_t, XCH> cx{};
        constexpr std::integral_constant<uint32_t, HCH> ch{};
        {
            float st[16], a0[20], a1[20], rem[16], own[16];
            const uint32_t inb = bars + (B_INB + w) * 8, box = sb + OFF_INBOX + w * 4096 + wt * 16;
            const uint32_t hdst = H + w * HCH + toff;
            auto step = [&](auto& d, int n, uint32_t bd, auto cs, int acc) {
                mm(d, n, bd, cs, acc);
                wg_wait<1>();
                if (n > 0) rel(n - 1);
            };
            auto epi = [&](float (&d)[20], int i, int half) {
                uint32_t pk[4];
#pragma unroll
                for (int k = 4 * half; k < 4 * half + 4; k++) {
                    const float cs = d[16 + 2 * (k & 1)];
                    const float v0 = fmaf(-st[(k >> 1) * 4], cs, d[2 * k] * st[(k >> 1) * 4 + 1]);
                    const float v1 = fmaf(-st[(k >> 1) * 4 + 2], cs, d[2 * k + 1] * st[(k >> 1) * 4 + 3]);
                    pk[k & 3] = pack2(fmaf(v0, tanh_fast(v0), v0), fmaf(v1, tanh_fast(v1), v1));
                }
                stsm4t(hdst + 2 * i * HCH + half * 2048, pk[0], pk[1], pk[2], pk[3]);
            };
            auto hdone = [&](int i) {
                fence_async_smem();
                __syncwarp();
                if (lane == 0) mbar_arrive(bars + (B_HF + i) * 8);
            };
            auto hwait = [&](int i) { mbar_wait(bars + (B_HF + i) * 8, ffi); };
            TS(1 + ffi * 20);
            step(a0, 0, pown, cx, 0);
            if (wt == 0) mbar_arrive_tx(inb, 4096);
            acq(2);
            gate(ffi * 4);
            TS(32);
            step(a0, 1, prem, cx, 1);
            step(a1, 2, pown, cx, 0); acq(3); pin(a0); load_stats(st, ffi); TS(33); epi(a0, 0, 0);
            step(a1, 3, prem, cx, 1); acq(4); epi(a0, 0, 1); TS(34);
            step(a0, 4, pown, cx, 0); acq(5); pin(a1); epi(a1, 1, 0);
            step(a0, 5, prem, cx, 1); acq(6); epi(a1, 1, 1); TS(35);
            step(a1, 6, pown, cx, 0); acq(7); pin(a0); hdone(0); epi(a0, 2, 0);
            step(a1, 7, prem, cx, 1); acq(8); hwait(0); epi(a0, 2, 1); TS(36);
            step(rem, 8, hdesc, ch, 0); acq(9); pin(a1); hdone(1); epi(a1, 3, 0);
            step(rem, 9, hdesc + 2 * (HCH >> 4), ch, 1); acq(10); hwait(1); epi(a1, 3, 1);
            TS(2 + ffi * 20);
            step(rem, 10, hdesc + 4 * (HCH >> 4), ch, 1); acq(11); hdone(2);
            step(own, 11, hdesc, ch, 0); acq(12); hwait(2);
            step(rem, 12, hdesc + 6 * (HCH >> 4), ch, 1); acq(13);
            step(own, 13, hdesc + 2 * (HCH >> 4), ch, 1); acq(14);
            pin(rem);
            {
                const uint32_t dst = mapa(box, r ^ 1), bar = mapa(inb, r ^ 1);
                st_async4(dst, pack2(rem[0], rem[1]), pack2(rem[2], rem[3]), pack2(rem[4], rem[5]), pack2(rem[6], rem[7]), bar);
                st_async4(dst + 2048, pack2(rem[8], rem[9]), pack2(rem[10], rem[11]), pack2(rem[12], rem[13]), pack2(rem[14], rem[15]), bar);
            }
            step(own, 14, hdesc + 4 * (HCH >> 4), ch, 1); acq(15);
            step(own, 15, hdesc + 6 * (HCH >> 4), ch, 1);
            mbar_wait(inb, ffi);
            const uint4 u = lds128(box), v = lds128(box + 2048);
            const uint32_t pr[8] = {u.x, u.y, u.z, u.w, v.x, v.y, v.z, v.w};
            if (ffi == 0) { acq(16); acq(17); }
            wg_wait<0>();
            pin(own);
            TS(3 + ffi * 20);
#pragma unroll
            for (int i = 0; i < 8; i++)
                xr[i] = pack2(fmaf(0.5f, own[2 * i] + blo(pr[i]), blo(xr[i])), fmaf(0.5f, own[2 * i + 1] + bhi(pr[i]), bhi(xr[i])));
            stsm4t(xa, xr[0], xr[1], xr[2], xr[3]);
            stsm4t(xa + 2048, xr[4], xr[5], xr[6], xr[7]);
            rel(15);
            publish(ffi ? 5 : 1, P + tile * XCH + (ffi ? (r ^ 1) * 2048 : 0), ffi ? 2048 : 4096, ffi ? 256 : 384);
        }
        if (ffi == 1) break;

        {
            float ak[20], aq[20], st[16];
            TS(11);
            mm(ak, 16, pown, cx, 0);
            mm(aq, 17, pown, cx, 0);
            acq(18); acq(19);
            gate(1);
            mm(ak, 18, prem, cx, 1);
            mm(aq, 19, prem, cx, 1);
            wg_wait<2>();
            rel(16); rel(17);
            load_stats(st, 1);
            auto stage_out = [&](float (&d)[20], uint32_t dst) {
                uint32_t pk[8];
#pragma unroll
                for (int k = 0; k < 8; k++) {
                    const float cs = d[16 + 2 * (k & 1)];
                    pk[k] = pack2(fmaf(-st[(k >> 1) * 4], cs, d[2 * k] * st[(k >> 1) * 4 + 1]),
                                  fmaf(-st[(k >> 1) * 4 + 2], cs, d[2 * k + 1] * st[(k >> 1) * 4 + 3]));
                }
                stsm4t(dst + toff, pk[0], pk[1], pk[2], pk[3]);
                stsm4t(dst + toff + 2048, pk[4], pk[5], pk[6], pk[7]);
            };
            const uint32_t stg = H + w * 12288;
            unsigned char* g = g_kqv + (size_t)((b * 4 + tile) * 1024 + pt * 32) * 128 + wt * 16;
            wg_wait<0>();
            pin(ak); pin(aq);
            TS(37);
            stage_out(ak, stg);
            stage_out(aq, stg + 4096);
            bar_sync(2 + w, 128);
            {
                const uint4 k0 = lds128(stg + wt * 16), k1 = lds128(stg + 2048 + wt * 16), q0 = lds128(stg + 4096 + wt * 16), q1 = lds128(stg + 6144 + wt * 16);
                stg128(g, k0); stg128(g + 2048, k1);
                stg128(g + 1048576, q0); stg128(g + 1048576 + 2048, q1);
            }
            bar_arrive(4, 288);
            TS(38);
            rel(18); rel(19);
            acq(20); acq(21);
            bar_sync(10, 256);
            mm(ak, 20, pown, cx, 0);
            mm(ak, 21, prem, cx, 1);
            wg_wait<0>();
            pin(ak);
            stage_out(ak, stg + 8192);
            rel(20); rel(21);
            bar_sync(2 + w, 128);
            {
                const uint4 v0 = lds128(stg + 8192 + wt * 16), v1 = lds128(stg + 10240 + wt * 16);
                const uint4 x0 = lds128(P + tile * XCH + wt * 16), x1 = lds128(P + tile * XCH + 2048 + wt * 16);
                stg128(g + 2097152, v0); stg128(g + 2097152 + 2048, v1);
                unsigned char* gx = g_x1 + (size_t)((b * 4 + tile) * PADROWS + 8 + pt * 32) * 128 + wt * 16;
                stg128(gx, x0); stg128(gx + 2048, x1);
            }
            bar_arrive(11, 288);
            acq(22); acq(23);
            rel(22); rel(23);
            TS(12);
        }

        {
            constexpr float CS = 0.125f * 1.4426950408889634f;
            float s[64], o[36];
            uint32_t pp[32];
            float n0 = INFINITY, n1 = INFINITY;
            zero(o); zero(pp);
            const uint32_t ones = sb + OFF_INBOX + 2048;
            if (tid < 128) sts128(ones + tid * 16, 0x3F803F80u, 0x3F803F80u, 0x3F803F80u, 0x3F803F80u);
            fence_async_smem();
            bar_sync(10, 256);
            const uint64_t qd = mkdesc(hdesc + (24576 >> 4));
            const uint32_t vdesc = rdesc + ((((ones - rbase) >> 4) - 1) << 16);
            auto qk_issue = [&](uint32_t slot) {
                const uint64_t kd = mkdesc(rdesc + slot * (SLOT >> 4));
                wg_fence();
#pragma unroll
                for (int k = 0; k < 4; k++) mma_qk(s, qd + 2 * k, kd + 2 * k, k != 0);
                wg_commit();
            };
            auto pv_issue = [&](uint32_t slot) {
                const uint64_t vd = mkdesc(vdesc - slot * (uint32_t)((SLOT >> 4) * 65535));
                wg_fence();
#pragma unroll
                for (int k = 0; k < 8; k++) mma_pv(o, pp[4 * k], pp[4 * k + 1], pp[4 * k + 2], pp[4 * k + 3], vd - k * (128 * 65535));
                wg_commit();
            };
            mbar_wait(bars + B_QIN * 8, 0);
            acq(24);
            TS(13);
            turn_wait();
            qk_issue(24 % NSLOT);
            turn_pass();
            wg_commit();
            uint32_t ks = 24 % NSLOT, vs = 0;
#pragma unroll 1
            for (int it = 0;; it++) {
                wg_wait<1>();
                pin(s);
                TS(40 + it * 4);
                if (lane == 0) mbar_arrive(fbar + (B_EMPTY - B_FULL + ks) * 8);
                if (it == 3 && w == 1) {
#pragma unroll
                    for (int i = 52; i < 64; i++) s[i] = -INFINITY;
                }
                bool rescale = true;
                if (it) {
                    float e[32];
#pragma unroll
                    for (int i = 0; i < 32; i++) e[i] = ex2(fmaf(s[i], CS, (i & 2) ? n1 : n0));
                    pin(e);
                    wg_wait<0>();
                    pin(o); pin(pp);
                    if (lane == 0) mbar_arrive(fbar + (B_EMPTY - B_FULL + vs) * 8);
                    uint32_t any = 0;
#pragma unroll
                    for (int i = 0; i < 32; i++) {
                        pp[i] = i < 16 ? pack2(e[2 * i], e[2 * i + 1])
                                       : pack2(ex2(fmaf(s[2 * i], CS, (i & 1) ? n1 : n0)), ex2(fmaf(s[2 * i + 1], CS, (i & 1) ? n1 : n0)));
                        any |= pp[i];
                    }
                    rescale = __any_sync(~0u, any & 0x40004000u);
                } else {
                    wg_wait<0>();
                    pin(o); pin(pp);
                }
                if (rescale) {
                    float x0 = s[0], x1 = s[2];
#pragma unroll
                    for (int j = 0; j < 16; j++) {
                        x0 = fmaxf(x0, fmaxf(s[4 * j], s[4 * j + 1]));
                        x1 = fmaxf(x1, fmaxf(s[4 * j + 2], s[4 * j + 3]));
                    }
                    x0 = fmaxf(x0, __shfl_xor_sync(~0u, x0, 1)); x1 = fmaxf(x1, __shfl_xor_sync(~0u, x1, 1));
                    x0 = fmaxf(x0, __shfl_xor_sync(~0u, x0, 2)); x1 = fmaxf(x1, __shfl_xor_sync(~0u, x1, 2));
                    x0 = fminf(n0, fmaf(x0, -CS, -20.f)); x1 = fminf(n1, fmaf(x1, -CS, -20.f));
                    const float sc0 = ex2(x0 - n0), sc1 = ex2(x1 - n1);
                    n0 = x0; n1 = x1;
#pragma unroll
                    for (int j = 0; j < 9; j++) { o[4 * j] *= sc0; o[4 * j + 1] *= sc0; o[4 * j + 2] *= sc1; o[4 * j + 3] *= sc1; }
#pragma unroll
                    for (int i = 0; i < 32; i++)
                        pp[i] = pack2(ex2(fmaf(s[2 * i], CS, (i & 1) ? n1 : n0)), ex2(fmaf(s[2 * i + 1], CS, (i & 1) ? n1 : n0)));
                }
                pin(s); pin(o); pin(pp);
                TS(41 + it * 4);
                if (it == 3) break;
                ks = 2 * it; vs = it == 2 ? 0 : 2 * it + 1;
                mbar_wait(fbar + ks * 8, 1);
                mbar_wait(fbar + vs * 8, it != 2);
                TS(42 + it * 4);
                turn_wait();
                qk_issue(ks);
                pv_issue(vs);
                turn_pass();
                TS(43 + it * 4);
            }
            acq(31);
            pv_issue(31 % NSLOT);
            const int row = wq * 16 + (lane >> 2);
            const uint32_t ml = sb + OFF_INBOX;
            wg_wait<0>();
            pin(o); pin(pp);
            rel(31);
            const float l0 = o[32], l1 = o[34];
            if (c4 == 0) { sts64f(ml + w * 512 + row * 8, n0, l0); sts64f(ml + w * 512 + row * 8 + 64, n1, l1); }
            TS(14);
            float mine[16];
#pragma unroll
            for (int j = 0; j < 4; j++) {
                if (w == 0) sts128f(H + j * 2048 + wt * 16, o[16 + 4 * j], o[17 + 4 * j], o[18 + 4 * j], o[19 + 4 * j]);
                else sts128f(H + 8192 + j * 2048 + wt * 16, o[4 * j], o[4 * j + 1], o[4 * j + 2], o[4 * j + 3]);
            }
#pragma unroll
            for (int i = 0; i < 16; i++) mine[i] = w == 0 ? o[i] : o[16 + i];
            bar_sync(10, 256);
            const float2 u0 = lds64f(ml + (w ^ 1) * 512 + row * 8), u1 = lds64f(ml + (w ^ 1) * 512 + row * 8 + 64);
            const float x0 = fminf(n0, u0.x), x1 = fminf(n1, u1.x);
            float a0 = ex2(x0 - n0), b0 = ex2(x0 - u0.x), a1 = ex2(x1 - n1), b1 = ex2(x1 - u1.x);
            const float i0 = __fdividef(1.f, fmaf(a0, l0, b0 * u0.y)), i1 = __fdividef(1.f, fmaf(a1, l1, b1 * u1.y));
            a0 *= i0; b0 *= i0; a1 *= i1; b1 *= i1;
            uint32_t pk[8];
#pragma unroll
            for (int j = 0; j < 4; j++) {
                const float4 v = lds128f(H + (w ^ 1) * 8192 + j * 2048 + wt * 16);
                pk[2 * j] = pack2(fmaf(a0, mine[4 * j], b0 * v.x), fmaf(a0, mine[4 * j + 1], b0 * v.y));
                pk[2 * j + 1] = pack2(fmaf(a1, mine[4 * j + 2], b1 * v.z), fmaf(a1, mine[4 * j + 3], b1 * v.w));
            }
            const uint32_t og = H + 16384 + wq * 2048;
            {
                const uint32_t ra = og + (((lane >> 3) & 1) * 8 + (lane & 7)) * 128;
                stsm4(ra + (((4 * w + (lane >> 4)) ^ (lane & 7)) << 4), pk[0], pk[1], pk[2], pk[3]);
                stsm4(ra + (((4 * w + 2 + (lane >> 4)) ^ (lane & 7)) << 4), pk[4], pk[5], pk[6], pk[7]);
            }
            __syncwarp();
            {
                const uint32_t off = (lane >> 2) * 128 + (((4 * w + c4) ^ (lane >> 2)) << 4);
                const uint4 v0 = lds128(og + off), v1 = lds128(og + off + 1024);
                unsigned char* dst = g_o + (size_t)(abh * PADROWS + 8 + qt * 64 + wq * 16) * 128 + off;
                stg128(dst, v0); stg128(dst + 1024, v1);
            }
            bar_arrive(6, 288);
            TS(15);
        }

        uint32_t dwr[15];
        {
#pragma unroll
            for (int i = 0; i < 15; i++) dwr[i] = __ldg(reinterpret_cast<const uint32_t*>(p.dw + i * 256 + tile * 64) + lane);
            float d[24];
            uint32_t xw[12];
            mbar_wait(bars + B_X1IN * 8, 0);
#pragma unroll
            for (int j = 0; j < 3; j++) ldsm4t(xa + j * 2048, xw[4 * j], xw[4 * j + 1], xw[4 * j + 2], xw[4 * j + 3]);
            acq(32); acq(33); acq(34); acq(35);
            mbar_wait(bars + B_OIN * 8, 0);
            TS(16);
            mm(d, 32, hdesc, cx, 0);
            mbar_wait(bars + B_OIN * 8 + 8, 0);
            mm(d, 33, hdesc + 2 * (XCH >> 4), cx, 1);
            wg_wait<1>();
            rel(32);
            wg_wait<0>();
            pin(d);
#pragma unroll
            for (int i = 0; i < 12; i++) xw[i] = pack2(d[2 * i] + blo(xw[i]), d[2 * i + 1] + bhi(xw[i]));
            if (c4 == 0) { xw[0] = (xw[0] & 0xffff0000u) | 0x3F80u; xw[1] = (xw[1] & 0xffff0000u) | 0x3F80u; }
#pragma unroll
            for (int j = 0; j < 3; j++) stsm4t(xa + j * 2048, xw[4 * j], xw[4 * j + 1], xw[4 * j + 2], xw[4 * j + 3]);
#pragma unroll
            for (int i = 0; i < 8; i++) xr[i] = xw[2 + i];
            rel(33);
            publish(2, P + tile * XCH, XCH, 384);
            TS(17);
        }
        {
            float da[24], db[24], st[24];
            mm(da, 34, pown, cx, 0);
            mm(db, 35, pown, cx, 0);
            acq(36); acq(37);
            gate(2);
            TS(39);
            mm(da, 36, prem, cx, 1);
            mm(db, 37, prem, cx, 1);
            wg_wait<2>();
            rel(34); rel(35);
            load_stats(st, 0);
            wg_wait<0>();
            pin(da); pin(db);
            rel(36); rel(37);
            TS(18);
            uint32_t pk[12];
#pragma unroll
            for (int hh = 0; hh < 2; hh++) {
                const float ca = __shfl_sync(~0u, da[2 * hh], lane & 28), cb = __shfl_sync(~0u, db[2 * hh], lane & 28);
#pragma unroll
                for (int j = 0; j < 6; j++) {
                    const float u0 = fmaf(-st[4 * j], ca, da[4 * j + 2 * hh] * st[4 * j + 1]);
                    const float u1 = fmaf(-st[4 * j + 2], ca, da[4 * j + 2 * hh + 1] * st[4 * j + 3]);
                    const float v0 = fmaf(-st[4 * j], cb, db[4 * j + 2 * hh] * st[4 * j + 1]);
                    const float v1 = fmaf(-st[4 * j + 2], cb, db[4 * j + 2 * hh + 1] * st[4 * j + 3]);
                    const uint32_t g = pack2(fmaf(u0, tanh_fast(v0), u0), fmaf(u1, tanh_fast(v1), u1));
                    const int t0 = pt * 32 - 8 + 8 * j;
                    pk[2 * j + hh] = (t0 >= 0 && t0 < T_) ? g : 0u;
                }
            }
            const uint32_t gs = H + 16384 + w * XCH;
#pragma unroll
            for (int j = 0; j < 3; j++) stsm4t(gs + toff + j * 2048, pk[4 * j], pk[4 * j + 1], pk[4 * j + 2], pk[4 * j + 3]);
            bar_sync(2 + w, 128);
            float c0[8], c1[8];
#pragma unroll
            for (int i = 0; i < 8; i++) { c0[i] = 0.f; c1[i] = 0.f; }
#pragma unroll
            for (int k = 0; k < 22; k++) {
                const uint32_t v = lds32(gs + (8 * wq + 1 + k) * 128 + (((lane >> 2) ^ ((1 + k) & 7)) << 4) + c4 * 4);
                const float v0 = blo(v), v1 = bhi(v);
#pragma unroll
                for (int i = 0; i < 8; i++)
                    if (k - i >= 0 && k - i < 15) { c0[i] = fmaf(v0, blo(dwr[k - i]), c0[i]); c1[i] = fmaf(v1, bhi(dwr[k - i]), c1[i]); }
            }
#pragma unroll
            for (int i = 0; i < 8; i++) {
                const float h0 = 0.5f * c0[i], h1 = 0.5f * c1[i];
                sts32(H + tile * HCH + (8 * wq + i) * 128 + (((lane >> 2) ^ i) << 4) + c4 * 4,
                      pack2(fmaf(h0, tanh_fast(h0), h0), fmaf(h1, tanh_fast(h1), h1)));
            }
            acq(38); acq(39);
            publish(3, H + tile * HCH, HCH, 256);
            TS(19);
        }
        {
            float d[16];
            mm(d, 38, hdesc + 2 * r * (HCH >> 4), ch, 0);
            acq(40); acq(41);
            xwait(3);
            sts128(P + (wt >> 6 ? (tile ^ 2) : tile) * XCH + 4096 + (wt & 63) * 16, 0x3F803F80u, 0x3F803F80u, 0x3F803F80u, 0x3F803F80u);
            mm(d, 39, hdesc + 2 * (r ^ 1) * (HCH >> 4), ch, 1);
            wg_wait<1>();
            rel(38);
            wg_wait<0>();
            pin(d);
#pragma unroll
            for (int i = 0; i < 8; i++) xr[i] = pack2(d[2 * i] + blo(xr[i]), d[2 * i + 1] + bhi(xr[i]));
            stsm4t(xa, xr[0], xr[1], xr[2], xr[3]);
            stsm4t(xa + 2048, xr[4], xr[5], xr[6], xr[7]);
            rel(39);
            publish(4, P + tile * XCH, HCH, 384);
            TS(20);
        }
    }

    xwait(5);
    cluster_arrive();
    TS(24);
    {
        float a[2][8], s[2], q[2];
        const int row0 = 16 * r + 2 * warp;
#pragma unroll
        for (int i = 0; i < 2; i++) {
            const uint4 v = lds128(P + (lane >> 3) * XCH + (row0 + i) * 128 + (((lane & 7) ^ ((row0 + i) & 7)) << 4));
            a[i][0] = blo(v.x); a[i][1] = bhi(v.x); a[i][2] = blo(v.y); a[i][3] = bhi(v.y);
            a[i][4] = blo(v.z); a[i][5] = bhi(v.z); a[i][6] = blo(v.w); a[i][7] = bhi(v.w);
            s[i] = ((a[i][0] + a[i][1]) + (a[i][2] + a[i][3])) + ((a[i][4] + a[i][5]) + (a[i][6] + a[i][7]));
            q[i] = 0.f;
#pragma unroll
            for (int k = 0; k < 8; k++) q[i] = fmaf(a[i][k], a[i][k], q[i]);
        }
#pragma unroll
        for (int o = 16; o > 0; o >>= 1) {
#pragma unroll
            for (int i = 0; i < 2; i++) { s[i] += __shfl_xor_sync(~0u, s[i], o); q[i] += __shfl_xor_sync(~0u, q[i], o); }
        }
#pragma unroll
        for (int i = 0; i < 2; i++) {
            const float mean = s[i] * (1.f / 256.f);
            const float rstd = rsqrtf(fmaxf(fmaf(-mean, mean, q[i] * (1.f / 256.f)), 0.f) + 1e-5f);
            const float nb = -mean * rstd;
            uint4 v;
            v.x = pack2(fmaf(a[i][0], rstd, nb), fmaf(a[i][1], rstd, nb)); v.y = pack2(fmaf(a[i][2], rstd, nb), fmaf(a[i][3], rstd, nb));
            v.z = pack2(fmaf(a[i][4], rstd, nb), fmaf(a[i][5], rstd, nb)); v.w = pack2(fmaf(a[i][6], rstd, nb), fmaf(a[i][7], rstd, nb));
            const int t = pt * 32 + row0 + i;
            if (t < T_) stg128(p.out + (size_t)(b * T_ + t) * 256 + lane * 8, v);
        }
    }
    TS(25);
    TG(31);
    TSDUMP();
    if (w == 0) turn_wait();
    cluster_wait();
}

typedef CUresult (*EncodeFn)(CUtensorMap*, CUtensorMapDataType, cuuint32_t, void*, const cuuint64_t*, const cuuint64_t*,
                             const cuuint32_t*, const cuuint32_t*, CUtensorMapInterleave, CUtensorMapSwizzle,
                             CUtensorMapL2promotion, CUtensorMapFloatOOBfill);

}

extern "C" void kernel_launch(void* const* d_in, const int* in_sizes, int n_in, void* d_out, int out_size) {
    static EncodeFn encode = nullptr;
    if (!encode) {
        void* fn = nullptr;
        cudaDriverEntryPointQueryResult qr;
        cudaGetDriverEntryPoint("cuTensorMapEncodeTiled", &fn, cudaEnableDefault, &qr);
        encode = (EncodeFn)fn;
        cudaFuncSetAttribute(conformer_kernel, cudaFuncAttributeMaxDynamicSharedMemorySize, SMEM_LAUNCH);
    }
    Params p;
    const cuuint32_t ones[3] = {1, 1, 1};
    {
        const cuuint64_t dims[3] = {256, T_, 2};
        const cuuint64_t strides[2] = {512, 512ull * T_};
        const cuuint32_t box[3] = {64, 32, 1};
        encode(&p.tm[0], CU_TENSOR_MAP_DATA_TYPE_BFLOAT16, 3, d_in[0], dims, strides, box, ones, CU_TENSOR_MAP_INTERLEAVE_NONE,
               CU_TENSOR_MAP_SWIZZLE_128B, CU_TENSOR_MAP_L2_PROMOTION_L2_256B, CU_TENSOR_MAP_FLOAT_OOB_FILL_NONE);
    }
    const int idx[8] = {1, 2, 3, 4, 5, 7, 8, 9};
    const int rows[8] = {256, 1024, 256, 256, 256, 256, 256, 1024};
    const int cols[8] = {1024, 256, 768, 256, 512, 256, 1024, 256};
    for (int i = 0; i < 8; i++) {
        const cuuint64_t dims[2] = {(cuuint64_t)cols[i], (cuuint64_t)rows[i]};
        const cuuint64_t strides[1] = {(cuuint64_t)cols[i] * 2};
        const cuuint32_t box[2] = {64, 128};
        encode(&p.tm[1 + i], CU_TENSOR_MAP_DATA_TYPE_BFLOAT16, 2, d_in[idx[i]], dims, strides, box, ones, CU_TENSOR_MAP_INTERLEAVE_NONE,
               CU_TENSOR_MAP_SWIZZLE_128B, CU_TENSOR_MAP_L2_PROMOTION_L2_128B, CU_TENSOR_MAP_FLOAT_OOB_FILL_NONE);
        p.w[i] = (const char*)d_in[idx[i]];
    }
    {
        void* kv = nullptr;
        cudaGetSymbolAddress(&kv, g_kqv);
        const cuuint64_t dims[2] = {64, 24576};
        const cuuint64_t strides[1] = {128};
        const cuuint32_t box[2] = {64, 128};
        encode(&p.tm[9], CU_TENSOR_MAP_DATA_TYPE_BFLOAT16, 2, kv, dims, strides, box, ones, CU_TENSOR_MAP_INTERLEAVE_NONE,
               CU_TENSOR_MAP_SWIZZLE_NONE, CU_TENSOR_MAP_L2_PROMOTION_L2_128B, CU_TENSOR_MAP_FLOAT_OOB_FILL_NONE);
    }
    p.w[8] = (const char*)d_in[0];
    p.dw = (const __nv_bfloat16*)d_in[6];
    p.out = (__nv_bfloat16*)d_out;
    p.zero = 0;
    conformer_kernel<<<NCTA, NTHREADS, SMEM_LAUNCH>>>(p);
}
```

```cpp
#include <cuda_runtime.h>
#include <cuda_bf16.h>
#include <cuda.h>
#include <stdint.h>
#include <type_traits>

namespace {

constexpr int T_ = 1000;
constexpr int NCTA = 128;
constexpr int NTHREADS = 512;
constexpr int NSLOT = 5;
constexpr int SLOT = 16384;
constexpr int NLOADS = 56;

constexpr uint32_t OFF_RING = 0;
constexpr uint32_t OFF_P = 163840;
constexpr uint32_t OFF_H = 188416;
constexpr uint32_t OFF_INBOX = 221184;
constexpr uint32_t OFF_STATS = 229376;
constexpr uint32_t OFF_BARS = 229888;
constexpr uint32_t SMEM_BYTES = 230400;
constexpr uint32_t XCH = 6144;
constexpr uint32_t HCH = 4096;

constexpr int B_FULL = 0, B_EMPTY = 10, B_XR = 20, B_OIN = 22, B_HF = 24, B_INB = 28, B_QIN = 30, B_X1IN = 31, B_ST = 32, B_RDY = 33;

constexpr int PADROWS = 1040;
constexpr int FS = 8;

struct Params {
    CUtensorMap tm[10];
    const char* w[9];
    const __nv_bfloat16* dw;
    __nv_bfloat16* out;
    uint32_t zero;
};

__device__ __align__(1024) unsigned char g_kqv[3 * 8 * 1024 * 128];
__device__ __align__(1024) unsigned char g_o[8 * PADROWS * 128];
__device__ __align__(1024) unsigned char g_x1[8 * PADROWS * 128];
__device__ uint32_t g_flag_qk[8 * 32 * FS];
__device__ uint32_t g_flag_v[8 * 32 * FS];
__device__ uint32_t g_flag_o[2 * 16 * 4 * FS];
__device__ uint32_t g_epoch[NCTA * FS];

#define TS(i) do { } while (0)
#define TG(i) do { } while (0)
#define TSINIT() do { } while (0)
#define TSDUMP() do { } while (0)
constexpr uint32_t SMEM_LAUNCH = SMEM_BYTES;

__device__ __forceinline__ uint32_t smem_u32(const void* p) { return (uint32_t)__cvta_generic_to_shared(p); }
__device__ __forceinline__ void mbar_init(uint32_t b, uint32_t c) { asm volatile("mbarrier.init.shared::cta.b64 [%0], %1;" ::"r"(b), "r"(c) : "memory"); }
__device__ __forceinline__ void mbar_arrive(uint32_t b) { asm volatile("mbarrier.arrive.shared::cta.b64 _, [%0];" ::"r"(b) : "memory"); }
__device__ __forceinline__ void mbar_arrive_tx(uint32_t b, uint32_t tx) { asm volatile("mbarrier.arrive.expect_tx.shared::cta.b64 _, [%0], %1;" ::"r"(b), "r"(tx) : "memory"); }
__device__ __forceinline__ void mbar_wait(uint32_t b, uint32_t ph) {
    asm volatile("{\n.reg .pred p, q;\n.reg .u32 c;\nmov.u32 c, 0;\n"
                 "MW_LOOP:\n.pragma \"nounroll\";\n"
                 "mbarrier.try_wait.parity.shared::cta.b64 p, [%0], %1;\n"
                 "add.u32 c, c, 1;\nsetp.lt.u32 q, c, 65536;\nnot.pred p, p;\nand.pred p, p, q;\n@p bra MW_LOOP;\n}"
                 ::"r"(b), "r"(ph) : "memory");
}
__device__ __forceinline__ uint32_t mapa(uint32_t a, uint32_t r) { uint32_t o; asm("mapa.shared::cluster.u32 %0, %1, %2;" : "=r"(o) : "r"(a), "r"(r)); return o; }
__device__ __forceinline__ void fence_async_smem() { asm volatile("fence.proxy.async.shared::cta;" ::: "memory"); }
__device__ __forceinline__ void fence_async_global() { asm volatile("fence.proxy.async.global;" ::: "memory"); }
__device__ __forceinline__ void bar_sync(int id, int n) { asm volatile("bar.sync %0, %1;" ::"r"(id), "r"(n) : "memory"); }
__device__ __forceinline__ void bar_arrive(int id, int n) { asm volatile("bar.arrive %0, %1;" ::"r"(id), "r"(n) : "memory"); }
__device__ __forceinline__ void cluster_arrive() { asm volatile("barrier.cluster.arrive.relaxed.aligned;" ::: "memory"); }
__device__ __forceinline__ void cluster_wait() { asm volatile("barrier.cluster.wait.aligned;" ::: "memory"); }

__device__ __forceinline__ void ring_load(uint32_t dst, const CUtensorMap* tm, int c0, int c1, uint32_t bar) {
    asm volatile("{\n.reg .pred p;\nelect.sync _|p, 0xffffffff;\n"
                 "@p mbarrier.arrive.expect_tx.shared::cta.b64 _, [%2], 16384;\n"
                 "@p cp.async.bulk.tensor.2d.shared::cluster.global.mbarrier::complete_tx::bytes [%0], [%1, {%3, %4}], [%2];\n}"
                 ::"r"(dst), "l"(tm), "r"(bar), "r"(c0), "r"(c1) : "memory");
}
__device__ __forceinline__ void ring_load_both(uint32_t dst, const CUtensorMap* tm, int c1, uint32_t bar) {
    asm volatile("{\n.reg .pred p;\nelect.sync _|p, 0xffffffff;\n"
                 "@p mbarrier.arrive.expect_tx.shared::cta.b64 _, [%2], 16384;\n"
                 "@p cp.async.bulk.tensor.2d.shared::cluster.global.mbarrier::complete_tx::bytes.multicast::cluster [%0], [%1, {0, %3}], [%2], %4;\n}"
                 ::"r"(dst), "l"(tm), "r"(bar), "r"(c1), "h"((uint16_t)3) : "memory");
}
__device__ __forceinline__ void ring_arm_signal(uint32_t bar, uint32_t peer_rdy) {
    asm volatile("{\n.reg .pred p;\nelect.sync _|p, 0xffffffff;\n"
                 "@p mbarrier.arrive.expect_tx.shared::cta.b64 _, [%0], 16384;\n"
                 "@p mbarrier.arrive.relaxed.cluster.shared::cluster.b64 _, [%1];\n}"
                 ::"r"(bar), "r"(peer_rdy) : "memory");
}
__device__ __forceinline__ void tma3d(uint32_t dst, const CUtensorMap* tm, int c0, int c1, int c2, uint32_t bar) {
    asm volatile("cp.async.bulk.tensor.3d.shared::cluster.global.mbarrier::complete_tx::bytes [%0], [%1, {%3, %4, %5}], [%2];"
                 ::"r"(dst), "l"(tm), "r"(bar), "r"(c0), "r"(c1), "r"(c2) : "memory");
}
__device__ __forceinline__ void bulk_g2s(uint32_t dst, const void* src, uint32_t bytes, uint32_t bar) {
    asm volatile("cp.async.bulk.shared::cluster.global.mbarrier::complete_tx::bytes [%0], [%1], %2, [%3];" ::"r"(dst), "l"(src), "r"(bytes), "r"(bar) : "memory");
}
__device__ __forceinline__ void prefetch_l2(const void* src, uint32_t bytes) {
    asm volatile("cp.async.bulk.prefetch.L2.global [%0], %1;" ::"l"(src), "r"(bytes) : "memory");
}
__device__ __forceinline__ void peer_copy(uint32_t dst, uint32_t src, uint32_t bytes, uint32_t rbar) {
    asm volatile("{\n.reg .pred p;\nelect.sync _|p, 0xffffffff;\n"
                 "@p cp.async.bulk.shared::cluster.shared::cta.mbarrier::complete_tx::bytes [%0], [%1], %2, [%3];\n}"
                 ::"r"(dst), "r"(src), "r"(bytes), "r"(rbar) : "memory");
}
__device__ __forceinline__ void st_async4(uint32_t dst, uint32_t a, uint32_t b, uint32_t c, uint32_t d, uint32_t bar) {
    asm volatile("st.async.shared::cluster.mbarrier::complete_tx::bytes.v4.b32 [%0], {%1,%2,%3,%4}, [%5];" ::"r"(dst), "r"(a), "r"(b), "r"(c), "r"(d), "r"(bar) : "memory");
}
__device__ __forceinline__ void stsm4t(uint32_t a, uint32_t r0, uint32_t r1, uint32_t r2, uint32_t r3) {
    asm volatile("stmatrix.sync.aligned.m8n8.x4.trans.shared.b16 [%0], {%1,%2,%3,%4};" ::"r"(a), "r"(r0), "r"(r1), "r"(r2), "r"(r3) : "memory");
}
__device__ __forceinline__ void stsm4(uint32_t a, uint32_t r0, uint32_t r1, uint32_t r2, uint32_t r3) {
    asm volatile("stmatrix.sync.aligned.m8n8.x4.shared.b16 [%0], {%1,%2,%3,%4};" ::"r"(a), "r"(r0), "r"(r1), "r"(r2), "r"(r3) : "memory");
}
__device__ __forceinline__ void ldsm4t(uint32_t a, uint32_t& r0, uint32_t& r1, uint32_t& r2, uint32_t& r3) {
    asm volatile("ldmatrix.sync.aligned.m8n8.x4.trans.shared.b16 {%0,%1,%2,%3}, [%4];" : "=r"(r0), "=r"(r1), "=r"(r2), "=r"(r3) : "r"(a) : "memory");
}
__device__ __forceinline__ uint4 lds128(uint32_t a) { uint4 v; asm volatile("ld.shared.v4.b32 {%0,%1,%2,%3}, [%4];" : "=r"(v.x), "=r"(v.y), "=r"(v.z), "=r"(v.w) : "r"(a) : "memory"); return v; }
__device__ __forceinline__ float4 lds128f(uint32_t a) { float4 v; asm volatile("ld.shared.v4.f32 {%0,%1,%2,%3}, [%4];" : "=f"(v.x), "=f"(v.y), "=f"(v.z), "=f"(v.w) : "r"(a) : "memory"); return v; }
__device__ __forceinline__ float2 lds64f(uint32_t a) { float2 v; asm volatile("ld.shared.v2.f32 {%0,%1}, [%2];" : "=f"(v.x), "=f"(v.y) : "r"(a) : "memory"); return v; }
__device__ __forceinline__ uint32_t lds32(uint32_t a) { uint32_t v; asm volatile("ld.shared.b32 %0, [%1];" : "=r"(v) : "r"(a) : "memory"); return v; }
__device__ __forceinline__ void sts128(uint32_t a, uint32_t x, uint32_t y, uint32_t z, uint32_t w) { asm volatile("st.shared.v4.b32 [%0], {%1,%2,%3,%4};" ::"r"(a), "r"(x), "r"(y), "r"(z), "r"(w) : "memory"); }
__device__ __forceinline__ void sts128f(uint32_t a, float x, float y, float z, float w) { asm volatile("st.shared.v4.f32 [%0], {%1,%2,%3,%4};" ::"r"(a), "f"(x), "f"(y), "f"(z), "f"(w) : "memory"); }
__device__ __forceinline__ void sts64f(uint32_t a, float x, float y) { asm volatile("st.shared.v2.f32 [%0], {%1,%2};" ::"r"(a), "f"(x), "f"(y) : "memory"); }
__device__ __forceinline__ void sts32(uint32_t a, uint32_t x) { asm volatile("st.shared.b32 [%0], %1;" ::"r"(a), "r"(x) : "memory"); }
__device__ __forceinline__ void stg128(void* p, uint4 v) { asm volatile("st.global.v4.b32 [%0], {%1,%2,%3,%4};" ::"l"(p), "r"(v.x), "r"(v.y), "r"(v.z), "r"(v.w) : "memory"); }

__device__ __forceinline__ uint32_t pack2(float lo, float hi) { uint32_t r; asm("cvt.rn.bf16x2.f32 %0, %1, %2;" : "=r"(r) : "f"(hi), "f"(lo)); return r; }
__device__ __forceinline__ float blo(uint32_t v) { return __uint_as_float(v << 16); }
__device__ __forceinline__ float bhi(uint32_t v) { return __uint_as_float(v & 0xffff0000u); }
__device__ __forceinline__ uint32_t hmul2(uint32_t a, uint32_t b) { uint32_t r; asm("mul.rn.bf16x2 %0, %1, %2;" : "=r"(r) : "r"(a), "r"(b)); return r; }
__device__ __forceinline__ uint32_t hfma2(uint32_t a, uint32_t b, uint32_t c) { uint32_t r; asm("fma.rn.bf16x2 %0, %1, %2, %3;" : "=r"(r) : "r"(a), "r"(b), "r"(c)); return r; }
__device__ __forceinline__ float tanh_fast(float x) { float r; asm("tanh.approx.f32 %0, %1;" : "=f"(r) : "f"(x)); return r; }
__device__ __forceinline__ float ex2(float x) { float r; asm("ex2.approx.ftz.f32 %0, %1;" : "=f"(r) : "f"(x)); return r; }

__device__ __forceinline__ void flag_wait(const uint32_t* p, uint32_t e) {
#pragma unroll 1
    for (int i = 0; i < (1 << 22); i++) {
        uint32_t v;
        asm volatile("ld.acquire.gpu.global.u32 %0, [%1];" : "=r"(v) : "l"(p) : "memory");
        if (v == e) return;
    }
    __trap();
}
__device__ __forceinline__ uint32_t ld_epoch() {
    uint32_t v;
    asm volatile("ld.relaxed.gpu.global.u32 %0, [%1];" : "=r"(v) : "l"(&g_epoch[blockIdx.x * FS]) : "memory");
    return v + 1;
}
__device__ __forceinline__ void flag_set(uint32_t* p, uint32_t e) { asm volatile("st.release.gpu.global.u32 [%0], %1;" ::"l"(p), "r"(e) : "memory"); }

__device__ __forceinline__ uint32_t desc_lo(uint32_t addr) { return ((addr & 0x3FFFF) >> 4) | 0x10000u; }
__device__ __forceinline__ uint64_t mkdesc(uint32_t lo) { return (uint64_t)lo | (0x40000040ull << 32); }
__device__ __forceinline__ void wg_fence() { asm volatile("wgmma.fence.sync.aligned;" ::: "memory"); }
__device__ __forceinline__ void wg_commit() { asm volatile("wgmma.commit_group.sync.aligned;" ::: "memory"); }
template <int N> __device__ __forceinline__ void wg_wait() { asm volatile("wgmma.wait_group.sync.aligned %0;" ::"n"(N) : "memory"); }
template <int N> __device__ __forceinline__ void pin(float (&d)[N]) {
#pragma unroll
    for (int i = 0; i < N; i++) asm volatile("" : "+f"(d[i])::"memory");
}
template <int N> __device__ __forceinline__ void pin(uint32_t (&d)[N]) {
#pragma unroll
    for (int i = 0; i < N; i++) asm volatile("" : "+r"(d[i])::"memory");
}

template <typename Tp, int N> __device__ __forceinline__ void zero(Tp (&d)[N]) {
#pragma unroll
    for (int i = 0; i < N; i++) d[i] = 0;
    pin(d);
}

#define F4(d, i) "+f"(d[i]), "+f"(d[i + 1]), "+f"(d[i + 2]), "+f"(d[i + 3])
#define F16(d, i) F4(d, i), F4(d, i + 4), F4(d, i + 8), F4(d, i + 12)

__device__ __forceinline__ void mma_t(float (&d)[16], uint64_t a, uint64_t b, int acc) {
    asm volatile("{.reg .pred p; setp.ne.b32 p, %18, 0;\n"
                 "wgmma.mma_async.sync.aligned.m64n32k16.f32.bf16.bf16 {%0,%1,%2,%3,%4,%5,%6,%7,%8,%9,%10,%11,%12,%13,%14,%15}, %16, %17, p, 1, 1, 1, 0;}\n"
                 : F16(d, 0) : "l"(a), "l"(b), "r"(acc));
}
__device__ __forceinline__ void mma_t(float (&d)[20], uint64_t a, uint64_t b, int acc) {
    asm volatile("{.reg .pred p; setp.ne.b32 p, %22, 0;\n"
                 "wgmma.mma_async.sync.aligned.m64n40k16.f32.bf16.bf16 {%0,%1,%2,%3,%4,%5,%6,%7,%8,%9,%10,%11,%12,%13,%14,%15,%16,%17,%18,%19}, %20, %21, p, 1, 1, 1, 0;}\n"
                 : F16(d, 0), F4(d, 16) : "l"(a), "l"(b), "r"(acc));
}
__device__ __forceinline__ void mma_t(float (&d)[24], uint64_t a, uint64_t b, int acc) {
    asm volatile("{.reg .pred p; setp.ne.b32 p, %26, 0;\n"
                 "wgmma.mma_async.sync.aligned.m64n48k16.f32.bf16.bf16 {%0,%1,%2,%3,%4,%5,%6,%7,%8,%9,%10,%11,%12,%13,%14,%15,%16,%17,%18,%19,%20,%21,%22,%23}, %24, %25, p, 1, 1, 1, 0;}\n"
                 : F16(d, 0), F4(d, 16), F4(d, 20) : "l"(a), "l"(b), "r"(acc));
}
__device__ __forceinline__ void mma_qk(float (&d)[64], uint64_t a, uint64_t b, int acc) {
    asm volatile("{.reg .pred p; setp.ne.b32 p, %66, 0;\n"
                 "wgmma.mma_async.sync.aligned.m64n128k16.f32.bf16.bf16 {%0,%1,%2,%3,%4,%5,%6,%7,%8,%9,%10,%11,%12,%13,%14,%15,%16,%17,%18,%19,%20,%21,%22,%23,%24,%25,%26,%27,%28,%29,%30,%31,"
                 "%32,%33,%34,%35,%36,%37,%38,%39,%40,%41,%42,%43,%44,%45,%46,%47,%48,%49,%50,%51,%52,%53,%54,%55,%56,%57,%58,%59,%60,%61,%62,%63}, %64, %65, p, 1, 1, 0, 0;}\n"
                 : F16(d, 0), F16(d, 16), F16(d, 32), F16(d, 48) : "l"(a), "l"(b), "r"(acc));
}
__device__ __forceinline__ void mma_pv(float (&d)[36], uint32_t a0, uint32_t a1, uint32_t a2, uint32_t a3, uint64_t b) {
    asm volatile("wgmma.mma_async.sync.aligned.m64n72k16.f32.bf16.bf16 {%0,%1,%2,%3,%4,%5,%6,%7,%8,%9,%10,%11,%12,%13,%14,%15,%16,%17,%18,%19,%20,%21,%22,%23,%24,%25,%26,%27,%28,%29,%30,%31,%32,%33,%34,%35}, "
                 "{%36,%37,%38,%39}, %40, 1, 1, 1, 1;\n"
                 : F16(d, 0), F16(d, 16), F4(d, 32) : "r"(a0), "r"(a1), "r"(a2), "r"(a3), "l"(b));
}

template <uint32_t CSTRIDE, int N>
__device__ __forceinline__ void issue_half(float (&d)[N], uint32_t alo, uint32_t blo_, int acc) {
    const uint64_t a = mkdesc(alo), b = mkdesc(blo_);
    wg_fence();
#pragma unroll
    for (int k = 0; k < 8; k++) mma_t(d, a + k * 128, b + (k >> 2) * (CSTRIDE >> 4) + (k & 3) * 2, k == 0 ? acc : 1);
    wg_commit();
}

__device__ __forceinline__ uint32_t load_code(int n, int r, int w, int abh) {
    const int tile = 2 * r + w;
    int m, col, row;
    if (n < 16 || n >= 40) {
        const int k = n < 16 ? n : n - 40;
        m = n < 16 ? 1 : 7;
        if (k < 8) { col = 8 * r + (k & 6) + w; row = (k & 1) ^ r; }
        else {
            const int kk = k == 11 ? 12 : (k == 12 ? 11 : k);
            m++; col = kk < 12 ? (tile ^ 2) : tile; row = 4 * r + (kk & 3);
        }
    } else if (n < 24) {
        const int k = n - 16;
        m = 3;
        if (k < 4) { col = tile + ((k & 1) ? 0 : 4); row = (k >> 1) ^ r; }
        else { col = 8 + tile; row = (k & 1) ^ r; }
    } else if (n < 32) {
        const int k = n - 24;
        const bool isv = (k == 7) || (k >= 2 && !(k & 1));
        const int i = isv ? (k == 7 ? 3 : (k >> 1) - 1) : ((k + 1) >> 1);
        m = 9; col = 0; row = (isv ? 128 : 0) + abh * 8 + 2 * i + w;
    } else if (n < 34) { m = 4; col = tile; row = n - 32; }
    else if (n < 38) { const int k = n - 34; m = 5; col = tile + 4 * (k & 1); row = (k >> 1) ^ r; }
    else { m = 6; col = tile; row = (n & 1) ^ r; }
    return m | (col << 4) | (row << 8);
}

__global__ void __cluster_dims__(2, 1, 1) __launch_bounds__(NTHREADS, 1)
conformer_kernel(const __grid_constant__ Params p) {
    extern __shared__ __align__(1024) unsigned char smem_raw[];
    const uint32_t sb = smem_u32(smem_raw);
    const uint32_t bars = sb + OFF_BARS;
    const int tid = threadIdx.x;
    const int lane = tid & 31;
    const int warp = __shfl_sync(~0u, tid >> 5, 0);
    const int r = blockIdx.x & 1;
    const int pair = blockIdx.x >> 1;
    const int b = pair >> 5, pt = pair & 31;
    const int ah = pt >> 3, qt = (pt & 7) * 2 + r;
    const int abh = b * 4 + ah;

    TG(30);
    TSINIT();
    TS(0);
    const uint32_t P = sb + OFF_P, H = sb + OFF_H;
    auto xwait = [&](int j) { mbar_wait(bars + (B_XR + (j & 1)) * 8, (j >> 1) & 1); };

    if (warp >= 8) {
        asm volatile("setmaxnreg.dec.sync.aligned.u32 48;");
        if (warp >= 12) {
            if (warp == 12 && lane >= 2 && lane < 10) asm volatile("prefetch.tensormap [%0];" ::"l"(&p.tm[lane]) : "memory");
            cluster_arrive();
            cluster_wait();
            const int ut = tid & 127;
            const uint32_t a4 = P + (ut >> 2) * 128 + (2 * (ut & 3) + ((ut >> 2) & 1)) * 16;
            const uint32_t a8 = P + (32 + (ut >> 3)) * 128 + (ut & 7) * 16;
#pragma unroll 1
            for (int k = 0; k < 4; k++) {
                float s = 0.f, q = 0.f, s2 = 0.f, q2 = 0.f;
#pragma unroll 1
                for (int h = 0; h < 2; h++) {
                    if (h == 0 && k != 0) bar_sync(1, 384);
                    else xwait(k == 3 ? 4 : k);
                    const uint32_t off = 2 * (r ^ h) * XCH;
                    uint4 v0 = lds128(a4 + off), v1 = lds128((a4 ^ 16) + off), v2 = lds128(a4 + off + XCH), v3 = lds128((a4 ^ 16) + off + XCH);
                    uint4 v4 = make_uint4(0, 0, 0, 0), v5 = v4;
                    if (k == 2) { v4 = lds128(a8 + off); v5 = lds128(a8 + off + XCH); }
                    if (h == 1 || k == 1 || k == 2) bar_arrive(5 + ((v3.w | v5.w) & p.zero), 384);
                    uint32_t t;
                    asm volatile("mov.u32 %0, %%clock;" : "=r"(t)::"memory");
                    const uint32_t mul = 65536u + (t & p.zero), msk = 0u - mul;
                    auto accum = [&](const uint4& v, float& s, float& q) {
                        const float a0 = __uint_as_float(v.x * mul), a1 = __uint_as_float(v.x & msk), a2 = __uint_as_float(v.y * mul), a3 = __uint_as_float(v.y & msk);
                        const float a4 = __uint_as_float(v.z * mul), a5 = __uint_as_float(v.z & msk), a6 = __uint_as_float(v.w * mul), a7 = __uint_as_float(v.w & msk);
                        s += ((a0 + a1) + (a2 + a3)) + ((a4 + a5) + (a6 + a7));
                        q += fmaf(a0, a0, fmaf(a1, a1, fmaf(a2, a2, a3 * a3))) + fmaf(a4, a4, fmaf(a5, a5, fmaf(a6, a6, a7 * a7)));
                    };
                    accum(v0, s, q); accum(v1, s, q); accum(v2, s, q); accum(v3, s, q);
                    if (k == 2) { accum(v4, s2, q2); accum(v5, s2, q2); }
                }
#pragma unroll
                for (int o = 1; o < 8; o <<= 1) {
                    if (o < 4) { s += __shfl_xor_sync(~0u, s, o); q += __shfl_xor_sync(~0u, q, o); }
                    if (k == 2) { s2 += __shfl_xor_sync(~0u, s2, o); q2 += __shfl_xor_sync(~0u, q2, o); }
                }
                const bool second = (ut & 7) == 1;
                if (second) { s = s2; q = q2; }
                const float mean = s * (1.f / 256.f);
                const int row = second ? 32 + (ut >> 3) : ut >> 2;
                const float alpha = k == 1 ? 1.f : ((k == 2 && (uint32_t)(pt * 32 - 8 + row) >= T_) ? 0.f : 0.5f);
                const float rstd = alpha * rsqrtf(fmaxf(fmaf(-mean, mean, q * (1.f / 256.f)), 0.f) + 1e-5f);
                if ((ut & 3) == 0 || second) sts64f(sb + OFF_STATS + row * 8, mean * rstd, rstd);
                __syncwarp();
                if (lane == 0) mbar_arrive(bars + B_ST * 8);
                TS(2 + k);
                if (k == 1 && warp == 12) {
                    const uint32_t epoch = ld_epoch();
                    bar_sync(11, 288);
                    if (lane < 2) flag_set(&g_flag_v[((b * 4 + 2 * r + lane) * 32 + pt) * FS], epoch);
                    __syncwarp();
                    TS(13);
                }
            }
        } else if (warp < 10) {
            const int w = warp - 8;
            const uint32_t ring = sb + OFF_RING + w * NSLOT * SLOT;
            const uint32_t full = bars + (B_FULL + w * NSLOT) * 8;
            if (lane == 0) {
#pragma unroll
                for (int i = 0; i < NSLOT; i++) mbar_init(full + i * 8, 1);
                asm volatile("fence.mbarrier_init.release.cluster;" ::: "memory");
                fence_async_smem();
            }
            __syncwarp();
            cluster_arrive();
            TS(1);
#pragma unroll
            for (int n = 0; n < NSLOT; n++)
                ring_load(ring + n * SLOT, &p.tm[1], 64 * (8 * r + (n & 6) + w), 128 * ((n & 1) ^ r), full + n * 8);
            TS(2);
            const uint32_t code = load_code(lane, r, w, abh) | (load_code(lane + 32, r, w, abh) << 16);
            cluster_wait();
            uint32_t s = 0, ph = 0;
            int n = NSLOT;
#pragma unroll 1
            for (int seg = 0; seg < 2; seg++) {
#pragma unroll 1
                for (; n < (seg == 0 ? 22 : NLOADS); n++) {
                    const uint32_t c = __shfl_sync(~0u, code, n) >> (n & 32 ? 16 : 0);
                    mbar_wait(full + (B_EMPTY - B_FULL) * 8 + s * 8, ph);
                    ring_load(ring + s * SLOT, &p.tm[c & 15], (c & 0xf0) * 4, (c & 0xff00) >> 1, full + s * 8);
                    if (++s == NSLOT) { s = 0; ph ^= 1; }
                }
                if (seg == 1) break;
                const uint32_t epoch = ld_epoch();
                const uint32_t rdy = bars + (B_RDY + w) * 8;
#pragma unroll 1
                for (; n < 32; n++) {
                    const uint32_t c = __shfl_sync(~0u, code, n);
                    mbar_wait(full + (B_EMPTY - B_FULL) * 8 + s * 8, ph);
                    if (n < 24) {
                        if (lane == 0) mbar_arrive(full + s * 8);
                    } else if ((n & 1) == r) {
                        mbar_wait(rdy, (n >> 1) & 1);
                        if (n < 27 || n == 31) {
                            flag_wait((n < 26 ? g_flag_qk : g_flag_v) + (abh * 32 + lane) * FS, epoch);
                            __syncwarp();
                            fence_async_global();
                            TS(n < 26 ? 5 : (n == 26 ? 6 : 7));
                        }
                        ring_load_both(ring + s * SLOT, &p.tm[9], (c & 0xff00) >> 1, full + s * 8);
                    } else {
                        ring_arm_signal(full + s * 8, mapa(rdy, r ^ 1));
                    }
                    if (++s == NSLOT) { s = 0; ph ^= 1; }
                }
            }
        } else if (warp == 10) {
            if (lane == 0) {
                mbar_init(bars + B_XR * 8, 1);
                asm volatile("fence.mbarrier_init.release.cluster;" ::: "memory");
                fence_async_smem();
            }
            __syncwarp();
            cluster_arrive();
            if (lane == 0) {
                mbar_arrive_tx(bars + B_XR * 8, 16384);
#pragma unroll
                for (int i = 0; i < 4; i++) tma3d(P + i * XCH, &p.tm[0], i * 64, pt * 32, b, bars + B_XR * 8);
            }
            __syncwarp();
            cluster_wait();
            const uint32_t epoch = ld_epoch();
            if (lane == 0) {
                mbar_arrive_tx(bars + B_QIN * 8, 8192);
                mbar_arrive_tx(bars + B_X1IN * 8, 2 * XCH);
                mbar_arrive_tx(bars + B_OIN * 8, 2 * XCH);
                mbar_arrive_tx(bars + B_OIN * 8 + 8, 2 * XCH);
            }
            if (lane < 2) flag_wait(&g_flag_qk[(abh * 32 + 2 * qt + lane) * FS], epoch);
            __syncwarp();
            if (lane == 0) {
                fence_async_global();
                bulk_g2s(H + 24576, g_kqv + 1048576 + (size_t)(abh * 1024 + qt * 64) * 128, 8192, bars + B_QIN * 8);
            }
            if (lane < 12) {
                const int np = pt - 1 + (lane >> 2);
                if (np >= 0 && np < 32) flag_wait(&g_flag_v[((b * 4 + (lane & 3)) * 32 + np) * FS], epoch);
            }
            __syncwarp();
            if (lane == 0) {
                fence_async_global();
#pragma unroll
                for (int w = 0; w < 2; w++)
                    bulk_g2s(P + (2 * r + w) * XCH, g_x1 + (size_t)((b * 4 + 2 * r + w) * PADROWS + pt * 32) * 128, XCH, bars + B_X1IN * 8);
            }
            __syncwarp();
            bar_sync(9, 64);
            if (lane < 8) {
                const int q = (pt >> 1) + (lane < 4 ? 0 : ((pt & 1) ? 1 : -1));
                if (q >= 0 && q < 16) flag_wait(&g_flag_o[((b * 16 + q) * 4 + (lane & 3)) * FS], epoch);
            }
            __syncwarp();
            if (lane == 0) {
                fence_async_global();
#pragma unroll
                for (int i = 0; i < 4; i++)
                    bulk_g2s(H + i * XCH, g_o + (size_t)((b * 4 + i) * PADROWS + pt * 32) * 128, XCH, bars + (B_OIN + (i >> 1)) * 8);
            }
            __syncwarp();
        } else {
            uint32_t kb = (lane < 2 || lane > 5) ? 4096 : (lane == 2 ? 3072 : (lane == 4 ? 2048 : 1024));
            size_t off = (size_t)blockIdx.x * kb;
            if (lane == 8) { kb = 8192; off = (size_t)min(b * T_ + pt * 32 + r * 16, 2 * T_ - 16) * 512; }
            const char* pf = p.w[min(lane, 8)] + off;
            if (lane == 0 || lane == 8) prefetch_l2(pf, kb);
            __syncwarp();
            cluster_arrive();
            cluster_wait();
            xwait(0);
            if (lane == 1 || lane == 2) prefetch_l2(pf, kb);
            mbar_wait(bars + B_HF * 8, 0);
            if (lane > 2 && lane < 8) prefetch_l2(pf, kb);
            const uint32_t epoch = ld_epoch();
            bar_sync(4, 288);
            if (lane < 2) flag_set(&g_flag_qk[((b * 4 + 2 * r + lane) * 32 + pt) * FS], epoch);
            __syncwarp();
            bar_sync(6, 288);
            bar_arrive(9, 64);
            if (lane == 0) {
                flag_set(&g_flag_o[((b * 16 + qt) * 4 + ah) * FS], epoch);
                g_epoch[blockIdx.x * FS] = epoch;
            }
            __syncwarp();
        }
        TSDUMP();
        return;
    }

    if (lane == 0) {
        mbar_init(bars + (B_EMPTY + warp) * 8, 4);
        mbar_init(bars + (B_HF + warp) * 8, warp < 4 ? 8 : 1);
        if (warp < 3) mbar_init(bars + (warp == 2 ? B_ST : B_EMPTY + 8 + warp) * 8, 4);
        else mbar_init(bars + (warp < 6 ? B_XR - 2 + warp : B_RDY - 6 + warp) * 8, 1);
        asm volatile("fence.mbarrier_init.release.cluster;" ::: "memory");
    }
    sts128(P + (tid >> 6) * XCH + 4096 + (tid & 63) * 16, 0x3F803F80u, 0x3F803F80u, 0x3F803F80u, 0x3F803F80u);
    fence_async_smem();
    __syncwarp();
    cluster_arrive();
    asm volatile("setmaxnreg.inc.sync.aligned.u32 208;");
    const int w = warp >> 2, wq = warp & 3;
    const int tile = 2 * r + w;
    const int wt = tid & 127;
    const int c4 = lane & 3;
    const uint32_t rbase = sb + OFF_RING + w * NSLOT * SLOT, fbar = bars + (B_FULL + w * NSLOT) * 8;
    const uint32_t rdesc = desc_lo(rbase);
    auto acq = [&](int n) { mbar_wait(fbar + (n % NSLOT) * 8, (n / NSLOT) & 1); };
    auto rel = [&](int n) { if (lane == 0) mbar_arrive(fbar + (B_EMPTY - B_FULL + n % NSLOT) * 8); };
    const uint32_t pown = desc_lo(P + 2 * r * XCH), prem = desc_lo(P + 2 * (r ^ 1) * XCH), hdesc = desc_lo(H);
    const uint32_t toff = ((lane >> 4) * 8 + (lane & 7)) * 128 + (((2 * wq + ((lane >> 3) & 1)) ^ (lane & 7)) << 4);
    const uint32_t xa = P + tile * XCH + toff;
    auto turn_wait = [&]() { bar_sync(7 + w, 256); };
    auto turn_pass = [&]() { bar_arrive(8 - w, 256); };
    if (w == 1) turn_pass();

    auto publish = [&](int j, uint32_t src, uint32_t bytes, int nsync) {
        const uint32_t bar = bars + (B_XR + (j & 1)) * 8;
        fence_async_smem();
        bar_sync(2 + w, 128);
        if (wq == 0) peer_copy(mapa(src, r ^ 1), src, bytes, mapa(bar, r ^ 1));
        if (tid == 32) mbar_arrive_tx(bar, 2 * bytes);
        bar_sync(nsync == 384 ? 1 : 10, nsync);
    };
    auto gate = [&](int j) { xwait(j); bar_sync(5, 384); };
    auto load_stats = [&](auto& st, int parity) {
        mbar_wait(bars + B_ST * 8, parity);
#pragma unroll
        for (int j = 0; j < (int)(sizeof(st) / 16); j++) {
            const float4 v = lds128f(sb + OFF_STATS + (8 * j + 2 * c4) * 8);
            st[4 * j] = v.x; st[4 * j + 1] = v.y; st[4 * j + 2] = v.z; st[4 * j + 3] = v.w;
        }
    };
    bar_sync(10, 256);
    cluster_wait();
    uint32_t xr[8];
    xwait(0);
    ldsm4t(xa, xr[0], xr[1], xr[2], xr[3]);
    ldsm4t(xa + 2048, xr[4], xr[5], xr[6], xr[7]);
    acq(0); acq(1);

#pragma unroll 1
    for (int ffi = 0; ffi < 2; ffi++) {
        auto mm = [&](auto& d, int n, uint32_t bd, auto cs, int acc) {
            const uint32_t z = p.zero * (ffi + n + 1);
            issue_half<decltype(cs)::value>(d, rdesc + z + (n % NSLOT) * (SLOT >> 4), bd + z, acc);
        };
        constexpr std::integral_constant<uint32_t, XCH> cx{};
        constexpr std::integral_constant<uint32_t, HCH> ch{};
        {
            float st[16], a0[20], a1[20], rem[16], own[16];
            const uint32_t inb = bars + (B_INB + w) * 8, box = sb + OFF_INBOX + w * 4096 + wt * 16;
            const uint32_t hdst = H + w * HCH + toff;
            auto step = [&](auto& d, int n, uint32_t bd, auto cs, int acc) {
                mm(d, n, bd, cs, acc);
                wg_wait<1>();
                if (n > 0) rel(n - 1);
            };
            auto epi = [&](float (&d)[20], int i, int half) {
                uint32_t pk[4];
#pragma unroll
                for (int k = 4 * half; k < 4 * half + 4; k++) {
                    const float cs = d[16 + 2 * (k & 1)];
                    const float v0 = fmaf(-st[(k >> 1) * 4], cs, d[2 * k] * st[(k >> 1) * 4 + 1]);
                    const float v1 = fmaf(-st[(k >> 1) * 4 + 2], cs, d[2 * k + 1] * st[(k >> 1) * 4 + 3]);
                    pk[k & 3] = pack2(fmaf(v0, tanh_fast(v0), v0), fmaf(v1, tanh_fast(v1), v1));
                }
                stsm4t(hdst + 2 * i * HCH + half * 2048, pk[0], pk[1], pk[2], pk[3]);
            };
            auto hdone = [&](int i) {
                fence_async_smem();
                __syncwarp();
                if (lane == 0) mbar_arrive(bars + (B_HF + i) * 8);
            };
            auto hwait = [&](int i) { mbar_wait(bars + (B_HF + i) * 8, ffi); };
            TS(1 + ffi * 20);
            step(a0, 0, pown, cx, 0);
            if (wt == 0) mbar_arrive_tx(inb, 4096);
            acq(2);
            gate(ffi * 4);
            TS(32);
            step(a0, 1, prem, cx, 1);
            step(a1, 2, pown, cx, 0); acq(3); pin(a0); load_stats(st, ffi); TS(33); epi(a0, 0, 0);
            step(a1, 3, prem, cx, 1); acq(4); epi(a0, 0, 1); TS(34);
            step(a0, 4, pown, cx, 0); acq(5); pin(a1); epi(a1, 1, 0);
            step(a0, 5, prem, cx, 1); acq(6); epi(a1, 1, 1); TS(35);
            step(a1, 6, pown, cx, 0); acq(7); pin(a0); hdone(0); epi(a0, 2, 0);
            step(a1, 7, prem, cx, 1); acq(8); hwait(0); epi(a0, 2, 1); TS(36);
            step(rem, 8, hdesc, ch, 0); acq(9); pin(a1); hdone(1); epi(a1, 3, 0);
            step(rem, 9, hdesc + 2 * (HCH >> 4), ch, 1); acq(10); hwait(1); epi(a1, 3, 1);
            TS(2 + ffi * 20);
            step(rem, 10, hdesc + 4 * (HCH >> 4), ch, 1); acq(11); hdone(2);
            step(own, 11, hdesc, ch, 0); acq(12); hwait(2);
            step(rem, 12, hdesc + 6 * (HCH >> 4), ch, 1); acq(13);
            step(own, 13, hdesc + 2 * (HCH >> 4), ch, 1); acq(14);
            pin(rem);
            {
                const uint32_t dst = mapa(box, r ^ 1), bar = mapa(inb, r ^ 1);
                st_async4(dst, pack2(rem[0], rem[1]), pack2(rem[2], rem[3]), pack2(rem[4], rem[5]), pack2(rem[6], rem[7]), bar);
                st_async4(dst + 2048, pack2(rem[8], rem[9]), pack2(rem[10], rem[11]), pack2(rem[12], rem[13]), pack2(rem[14], rem[15]), bar);
            }
            step(own, 14, hdesc + 4 * (HCH >> 4), ch, 1); acq(15);
            step(own, 15, hdesc + 6 * (HCH >> 4), ch, 1);
            mbar_wait(inb, ffi);
            const uint4 u = lds128(box), v = lds128(box + 2048);
            const uint32_t pr[8] = {u.x, u.y, u.z, u.w, v.x, v.y, v.z, v.w};
            if (ffi == 0) { acq(16); acq(17); }
            wg_wait<0>();
            pin(own);
            TS(3 + ffi * 20);
#pragma unroll
            for (int i = 0; i < 8; i++)
                xr[i] = pack2(fmaf(0.5f, own[2 * i] + blo(pr[i]), blo(xr[i])), fmaf(0.5f, own[2 * i + 1] + bhi(pr[i]), bhi(xr[i])));
            stsm4t(xa, xr[0], xr[1], xr[2], xr[3]);
            stsm4t(xa + 2048, xr[4], xr[5], xr[6], xr[7]);
            rel(15);
            publish(ffi ? 5 : 1, P + tile * XCH + (ffi ? (r ^ 1) * 2048 : 0), ffi ? 2048 : 4096, ffi ? 256 : 384);
        }
        if (ffi == 1) break;

        {
            float ak[20], aq[20], st[16];
            bar_sync(5, 384);
            TS(11);
            mm(ak, 16, pown, cx, 0);
            mm(aq, 17, pown, cx, 0);
            acq(18); acq(19);
            gate(1);
            mm(ak, 18, prem, cx, 1);
            mm(aq, 19, prem, cx, 1);
            wg_wait<2>();
            rel(16); rel(17);
            load_stats(st, 1);
            auto stage_out = [&](float (&d)[20], uint32_t dst) {
                uint32_t pk[8];
#pragma unroll
                for (int k = 0; k < 8; k++) {
                    const float cs = d[16 + 2 * (k & 1)];
                    pk[k] = pack2(fmaf(-st[(k >> 1) * 4], cs, d[2 * k] * st[(k >> 1) * 4 + 1]),
                                  fmaf(-st[(k >> 1) * 4 + 2], cs, d[2 * k + 1] * st[(k >> 1) * 4 + 3]));
                }
                stsm4t(dst + toff, pk[0], pk[1], pk[2], pk[3]);
                stsm4t(dst + toff + 2048, pk[4], pk[5], pk[6], pk[7]);
            };
            const uint32_t stg = H + w * 12288;
            unsigned char* g = g_kqv + (size_t)((b * 4 + tile) * 1024 + pt * 32) * 128 + wt * 16;
            wg_wait<0>();
            pin(ak); pin(aq);
            TS(37);
            stage_out(ak, stg);
            stage_out(aq, stg + 4096);
            bar_sync(2 + w, 128);
            {
                const uint4 k0 = lds128(stg + wt * 16), k1 = lds128(stg + 2048 + wt * 16), q0 = lds128(stg + 4096 + wt * 16), q1 = lds128(stg + 6144 + wt * 16);
                stg128(g, k0); stg128(g + 2048, k1);
                stg128(g + 1048576, q0); stg128(g + 1048576 + 2048, q1);
            }
            bar_arrive(4, 288);
            TS(38);
            rel(18); rel(19);
            acq(20); acq(21);
            bar_sync(10, 256);
            mm(ak, 20, pown, cx, 0);
            mm(ak, 21, prem, cx, 1);
            wg_wait<0>();
            pin(ak);
            stage_out(ak, stg + 8192);
            rel(20); rel(21);
            bar_sync(2 + w, 128);
            {
                const uint4 v0 = lds128(stg + 8192 + wt * 16), v1 = lds128(stg + 10240 + wt * 16);
                const uint4 x0 = lds128(P + tile * XCH + wt * 16), x1 = lds128(P + tile * XCH + 2048 + wt * 16);
                stg128(g + 2097152, v0); stg128(g + 2097152 + 2048, v1);
                unsigned char* gx = g_x1 + (size_t)((b * 4 + tile) * PADROWS + 8 + pt * 32) * 128 + wt * 16;
                stg128(gx, x0); stg128(gx + 2048, x1);
            }
            bar_arrive(11, 288);
            acq(22); acq(23);
            rel(22); rel(23);
            TS(12);
        }

        {
            constexpr float CS = 0.125f * 1.4426950408889634f;
            float s[64], o[36];
            uint32_t pp[32];
            float n0 = INFINITY, n1 = INFINITY;
            zero(o); zero(pp);
            const uint32_t ones = sb + OFF_INBOX + 2048;
            if (tid < 128) sts128(ones + tid * 16, 0x3F803F80u, 0x3F803F80u, 0x3F803F80u, 0x3F803F80u);
            fence_async_smem();
            bar_sync(10, 256);
            const uint64_t qd = mkdesc(hdesc + (24576 >> 4));
            const uint32_t vdesc = rdesc + ((((ones - rbase) >> 4) - 1) << 16);
            auto qk_issue = [&](uint32_t slot) {
                const uint64_t kd = mkdesc(rdesc + slot * (SLOT >> 4));
                wg_fence();
#pragma unroll
                for (int k = 0; k < 4; k++) mma_qk(s, qd + 2 * k, kd + 2 * k, k != 0);
                wg_commit();
            };
            auto pv_issue = [&](uint32_t slot) {
                const uint64_t vd = mkdesc(vdesc - slot * (uint32_t)((SLOT >> 4) * 65535));
                wg_fence();
#pragma unroll
                for (int k = 0; k < 8; k++) mma_pv(o, pp[4 * k], pp[4 * k + 1], pp[4 * k + 2], pp[4 * k + 3], vd - k * (128 * 65535));
                wg_commit();
            };
            mbar_wait(bars + B_QIN * 8, 0);
            acq(24);
            TS(13);
            turn_wait();
            qk_issue(24 % NSLOT);
            turn_pass();
            wg_commit();
            uint32_t ks = 24 % NSLOT, vs = 0;
#pragma unroll 1
            for (int it = 0;; it++) {
                wg_wait<1>();
                pin(s);
                TS(40 + it * 4);
                float e[32];
                uint32_t any = 0;
                if (it) {
#pragma unroll
                    for (int i = 0; i < 32; i++) { e[i] = ex2(fmaf(s[i], CS, (i & 2) ? n1 : n0)); any |= __float_as_uint(e[i]); }
                }
                if (lane == 0) mbar_arrive(fbar + (B_EMPTY - B_FULL + ks) * 8);
                const uint32_t nk = it == 3 ? 1 : 2 * it, nv = it == 2 ? 0 : (it == 3 ? 1 : 2 * it + 1);
                if (it) {
                    mbar_wait(fbar + nk * 8, (it != 3) + (any & p.zero));
                    mbar_wait(fbar + nv * 8, it < 2);
                }
                wg_wait<0>();
                pin(o); pin(pp);
                if (it == 3 && w == 1) {
#pragma unroll
                    for (int i = 52; i < 64; i++) s[i] = -INFINITY;
                }
                bool rescale = true;
                if (it) {
                    if (lane == 0) mbar_arrive(fbar + (B_EMPTY - B_FULL + vs) * 8);
                    any &= 0x40000000u;
#pragma unroll
                    for (int i = 0; i < 16; i++) pp[i] = pack2(e[2 * i], e[2 * i + 1]);
#pragma unroll
                    for (int i = 16; i < 32; i++) {
                        pp[i] = pack2(ex2(fmaf(s[2 * i], CS, (i & 1) ? n1 : n0)), ex2(fmaf(s[2 * i + 1], CS, (i & 1) ? n1 : n0)));
                        any |= pp[i];
                    }
                    rescale = __any_sync(~0u, any & 0x40004000u);
                }
                ks = nk; vs = nv;
                if (rescale) {
                    float x0 = s[0], x1 = s[2];
#pragma unroll
                    for (int j = 0; j < 16; j++) {
                        x0 = fmaxf(x0, fmaxf(s[4 * j], s[4 * j + 1]));
                        x1 = fmaxf(x1, fmaxf(s[4 * j + 2], s[4 * j + 3]));
                    }
                    x0 = fmaxf(x0, __shfl_xor_sync(~0u, x0, 1)); x1 = fmaxf(x1, __shfl_xor_sync(~0u, x1, 1));
                    x0 = fmaxf(x0, __shfl_xor_sync(~0u, x0, 2)); x1 = fmaxf(x1, __shfl_xor_sync(~0u, x1, 2));
                    x0 = fminf(n0, fmaf(x0, -CS, -20.f)); x1 = fminf(n1, fmaf(x1, -CS, -20.f));
                    const float sc0 = ex2(x0 - n0), sc1 = ex2(x1 - n1);
                    n0 = x0; n1 = x1;
#pragma unroll
                    for (int j = 0; j < 9; j++) { o[4 * j] *= sc0; o[4 * j + 1] *= sc0; o[4 * j + 2] *= sc1; o[4 * j + 3] *= sc1; }
#pragma unroll
                    for (int i = 0; i < 32; i++)
                        pp[i] = pack2(ex2(fmaf(s[2 * i], CS, (i & 1) ? n1 : n0)), ex2(fmaf(s[2 * i + 1], CS, (i & 1) ? n1 : n0)));
                }
                pin(s); pin(o); pin(pp);
                TS(41 + it * 4);
                if (it == 3) break;
                if (it == 0) { acq(25); acq(26); }
                TS(42 + it * 4);
                turn_wait();
                qk_issue(ks);
                pv_issue(vs);
                turn_pass();
                TS(43 + it * 4);
            }
            pv_issue(31 % NSLOT);
            const int row = wq * 16 + (lane >> 2);
            const uint32_t ml = sb + OFF_INBOX;
            wg_wait<0>();
            pin(o); pin(pp);
            rel(31);
            const float l0 = o[32], l1 = o[34];
            if (c4 == 0) { sts64f(ml + w * 512 + row * 8, n0, l0); sts64f(ml + w * 512 + row * 8 + 64, n1, l1); }
            TS(14);
            float mine[16];
#pragma unroll
            for (int j = 0; j < 4; j++) {
                if (w == 0) sts128f(H + j * 2048 + wt * 16, o[16 + 4 * j], o[17 + 4 * j], o[18 + 4 * j], o[19 + 4 * j]);
                else sts128f(H + 8192 + j * 2048 + wt * 16, o[4 * j], o[4 * j + 1], o[4 * j + 2], o[4 * j + 3]);
            }
#pragma unroll
            for (int i = 0; i < 16; i++) mine[i] = w == 0 ? o[i] : o[16 + i];
            bar_sync(10, 256);
            const float2 u0 = lds64f(ml + (w ^ 1) * 512 + row * 8), u1 = lds64f(ml + (w ^ 1) * 512 + row * 8 + 64);
            const float x0 = fminf(n0, u0.x), x1 = fminf(n1, u1.x);
            float a0 = ex2(x0 - n0), b0 = ex2(x0 - u0.x), a1 = ex2(x1 - n1), b1 = ex2(x1 - u1.x);
            const float i0 = __fdividef(1.f, fmaf(a0, l0, b0 * u0.y)), i1 = __fdividef(1.f, fmaf(a1, l1, b1 * u1.y));
            a0 *= i0; b0 *= i0; a1 *= i1; b1 *= i1;
            uint32_t pk[8];
#pragma unroll
            for (int j = 0; j < 4; j++) {
                const float4 v = lds128f(H + (w ^ 1) * 8192 + j * 2048 + wt * 16);
                pk[2 * j] = pack2(fmaf(a0, mine[4 * j], b0 * v.x), fmaf(a0, mine[4 * j + 1], b0 * v.y));
                pk[2 * j + 1] = pack2(fmaf(a1, mine[4 * j + 2], b1 * v.z), fmaf(a1, mine[4 * j + 3], b1 * v.w));
            }
            const uint32_t og = H + 16384 + wq * 2048;
            {
                const uint32_t ra = og + (((lane >> 3) & 1) * 8 + (lane & 7)) * 128;
                stsm4(ra + (((4 * w + (lane >> 4)) ^ (lane & 7)) << 4), pk[0], pk[1], pk[2], pk[3]);
                stsm4(ra + (((4 * w + 2 + (lane >> 4)) ^ (lane & 7)) << 4), pk[4], pk[5], pk[6], pk[7]);
            }
            __syncwarp();
            {
                const uint32_t off = (lane >> 2) * 128 + (((4 * w + c4) ^ (lane >> 2)) << 4);
                const uint4 v0 = lds128(og + off), v1 = lds128(og + off + 1024);
                unsigned char* dst = g_o + (size_t)(abh * PADROWS + 8 + qt * 64 + wq * 16) * 128 + off;
                stg128(dst, v0); stg128(dst + 1024, v1);
            }
            bar_arrive(6, 288);
            TS(15);
        }

        uint32_t dwr[15];
        {
#pragma unroll
            for (int i = 0; i < 15; i++) dwr[i] = hmul2(__ldg(reinterpret_cast<const uint32_t*>(p.dw + i * 256 + tile * 64) + lane), 0x3F003F00u);
            float d[24];
            uint32_t xw[12];
            mbar_wait(bars + B_X1IN * 8, 0);
#pragma unroll
            for (int j = 0; j < 3; j++) ldsm4t(xa + j * 2048, xw[4 * j], xw[4 * j + 1], xw[4 * j + 2], xw[4 * j + 3]);
            pin(dwr);
            acq(32); acq(33); acq(34); acq(35);
            mbar_wait(bars + B_OIN * 8, 0);
            TS(16);
            mm(d, 32, hdesc, cx, 0);
            mbar_wait(bars + B_OIN * 8 + 8, 0);
            mm(d, 33, hdesc + 2 * (XCH >> 4), cx, 1);
            wg_wait<1>();
            rel(32);
            wg_wait<0>();
            pin(d);
#pragma unroll
            for (int i = 0; i < 12; i++) xw[i] = pack2(d[2 * i] + blo(xw[i]), d[2 * i + 1] + bhi(xw[i]));
            if (c4 == 0) { xw[0] = (xw[0] & 0xffff0000u) | 0x3F80u; xw[1] = (xw[1] & 0xffff0000u) | 0x3F80u; }
#pragma unroll
            for (int j = 0; j < 3; j++) stsm4t(xa + j * 2048, xw[4 * j], xw[4 * j + 1], xw[4 * j + 2], xw[4 * j + 3]);
#pragma unroll
            for (int i = 0; i < 8; i++) xr[i] = xw[2 + i];
            rel(33);
            publish(2, P + tile * XCH, XCH, 384);
            TS(17);
        }
        {
            float da[24], db[24], st[24];
            bar_sync(5, 384);
            mm(da, 34, pown, cx, 0);
            mm(db, 35, pown, cx, 0);
            acq(36); acq(37);
            gate(2);
            TS(39);
            mm(da, 36, prem, cx, 1);
            mm(db, 37, prem, cx, 1);
            wg_wait<2>();
            rel(34); rel(35);
            load_stats(st, 0);
            wg_wait<0>();
            pin(da); pin(db);
            rel(36); rel(37);
            TS(18);
            uint32_t pk[12];
#pragma unroll
            for (int hh = 0; hh < 2; hh++) {
                const float ca = __shfl_sync(~0u, da[2 * hh], lane & 28), cb = __shfl_sync(~0u, db[2 * hh], lane & 28);
#pragma unroll
                for (int j = 0; j < 6; j++) {
                    const float u0 = fmaf(-st[4 * j], ca, da[4 * j + 2 * hh] * st[4 * j + 1]);
                    const float u1 = fmaf(-st[4 * j + 2], ca, da[4 * j + 2 * hh + 1] * st[4 * j + 3]);
                    const float v0 = fmaf(-st[4 * j], cb, db[4 * j + 2 * hh] * st[4 * j + 1]);
                    const float v1 = fmaf(-st[4 * j + 2], cb, db[4 * j + 2 * hh + 1] * st[4 * j + 3]);
                    pk[2 * j + hh] = pack2(fmaf(u0, tanh_fast(v0), u0), fmaf(u1, tanh_fast(v1), u1));
                }
            }
            const uint32_t gs = H + 16384 + w * XCH;
#pragma unroll
            for (int j = 0; j < 3; j++) stsm4t(gs + toff + j * 2048, pk[4 * j], pk[4 * j + 1], pk[4 * j + 2], pk[4 * j + 3]);
            bar_sync(2 + w, 128);
            uint32_t ca[8], cb[8];
            const uint32_t grow = gs + 8 * wq * 128 + c4 * 4, srow = H + tile * HCH + 8 * wq * 128 + c4 * 4;
#pragma unroll
            for (int k = 0; k < 22; k++) {
                const uint32_t v = lds32(grow + (1 + k) * 128 + (((lane >> 2) ^ ((1 + k) & 7)) << 4));
#pragma unroll
                for (int i = 0; i < 8; i++) {
                    const int tap = k - i;
                    if (tap == 0) ca[i] = hmul2(v, dwr[0]);
                    else if (tap > 0 && tap < 8) ca[i] = hfma2(v, dwr[tap], ca[i]);
                    else if (tap == 8) cb[i] = hmul2(v, dwr[8]);
                    else if (tap > 8 && tap < 15) cb[i] = hfma2(v, dwr[tap], cb[i]);
                }
            }
#pragma unroll
            for (int i = 0; i < 8; i++) {
                const float h0 = blo(ca[i]) + blo(cb[i]), h1 = bhi(ca[i]) + bhi(cb[i]);
                sts32(srow + i * 128 + (((lane >> 2) ^ i) << 4), pack2(fmaf(h0, tanh_fast(h0), h0), fmaf(h1, tanh_fast(h1), h1)));
            }
            acq(38); acq(39);
            publish(3, H + tile * HCH, HCH, 256);
            TS(19);
        }
        {
            float d[16];
            mm(d, 38, hdesc + 2 * r * (HCH >> 4), ch, 0);
            acq(40); acq(41);
            xwait(3);
            sts128(P + (wt >> 6 ? (tile ^ 2) : tile) * XCH + 4096 + (wt & 63) * 16, 0x3F803F80u, 0x3F803F80u, 0x3F803F80u, 0x3F803F80u);
            mm(d, 39, hdesc + 2 * (r ^ 1) * (HCH >> 4), ch, 1);
            wg_wait<1>();
            rel(38);
            wg_wait<0>();
            pin(d);
#pragma unroll
            for (int i = 0; i < 8; i++) xr[i] = pack2(d[2 * i] + blo(xr[i]), d[2 * i + 1] + bhi(xr[i]));
            stsm4t(xa, xr[0], xr[1], xr[2], xr[3]);
            stsm4t(xa + 2048, xr[4], xr[5], xr[6], xr[7]);
            rel(39);
            publish(4, P + tile * XCH, HCH, 384);
            TS(20);
        }
    }

    xwait(5);
    cluster_arrive();
    TS(24);
    {
        float a[2][8], s[2], q[2];
        const int row0 = 16 * r + 2 * warp;
#pragma unroll
        for (int i = 0; i < 2; i++) {
            const uint4 v = lds128(P + (lane >> 3) * XCH + (row0 + i) * 128 + (((lane & 7) ^ ((row0 + i) & 7)) << 4));
            a[i][0] = blo(v.x); a[i][1] = bhi(v.x); a[i][2] = blo(v.y); a[i][3] = bhi(v.y);
            a[i][4] = blo(v.z); a[i][5] = bhi(v.z); a[i][6] = blo(v.w); a[i][7] = bhi(v.w);
            s[i] = ((a[i][0] + a[i][1]) + (a[i][2] + a[i][3])) + ((a[i][4] + a[i][5]) + (a[i][6] + a[i][7]));
            q[i] = 0.f;
#pragma unroll
            for (int k = 0; k < 8; k++) q[i] = fmaf(a[i][k], a[i][k], q[i]);
        }
#pragma unroll
        for (int o = 16; o > 0; o >>= 1) {
#pragma unroll
            for (int i = 0; i < 2; i++) { s[i] += __shfl_xor_sync(~0u, s[i], o); q[i] += __shfl_xor_sync(~0u, q[i], o); }
        }
#pragma unroll
        for (int i = 0; i < 2; i++) {
            const float mean = s[i] * (1.f / 256.f);
            const float rstd = rsqrtf(fmaxf(fmaf(-mean, mean, q[i] * (1.f / 256.f)), 0.f) + 1e-5f);
            const float nb = -mean * rstd;
            uint4 v;
            v.x = pack2(fmaf(a[i][0], rstd, nb), fmaf(a[i][1], rstd, nb)); v.y = pack2(fmaf(a[i][2], rstd, nb), fmaf(a[i][3], rstd, nb));
            v.z = pack2(fmaf(a[i][4], rstd, nb), fmaf(a[i][5], rstd, nb)); v.w = pack2(fmaf(a[i][6], rstd, nb), fmaf(a[i][7], rstd, nb));
            const int t = pt * 32 + row0 + i;
            if (t < T_) stg128(p.out + (size_t)(b * T_ + t) * 256 + lane * 8, v);
        }
    }
    TS(25);
    TG(31);
    TSDUMP();
    if (w == 0) turn_wait();
    cluster_wait();
}

typedef CUresult (*EncodeFn)(CUtensorMap*, CUtensorMapDataType, cuuint32_t, void*, const cuuint64_t*, const cuuint64_t*,
                             const cuuint32_t*, const cuuint32_t*, CUtensorMapInterleave, CUtensorMapSwizzle,
                             CUtensorMapL2promotion, CUtensorMapFloatOOBfill);

}

extern "C" void kernel_launch(void* const* d_in, const int* in_sizes, int n_in, void* d_out, int out_size) {
    static EncodeFn encode = nullptr;
    if (!encode) {
        void* fn = nullptr;
        cudaDriverEntryPointQueryResult qr;
        cudaGetDriverEntryPoint("cuTensorMapEncodeTiled", &fn, cudaEnableDefault, &qr);
        encode = (EncodeFn)fn;
        cudaFuncSetAttribute(conformer_kernel, cudaFuncAttributeMaxDynamicSharedMemorySize, SMEM_LAUNCH);
    }
    Params p;
    const cuuint32_t ones[3] = {1, 1, 1};
    {
        const cuuint64_t dims[3] = {256, T_, 2};
        const cuuint64_t strides[2] = {512, 512ull * T_};
        const cuuint32_t box[3] = {64, 32, 1};
        encode(&p.tm[0], CU_TENSOR_MAP_DATA_TYPE_BFLOAT16, 3, d_in[0], dims, strides, box, ones, CU_TENSOR_MAP_INTERLEAVE_NONE,
               CU_TENSOR_MAP_SWIZZLE_128B, CU_TENSOR_MAP_L2_PROMOTION_L2_256B, CU_TENSOR_MAP_FLOAT_OOB_FILL_NONE);
    }
    const int idx[8] = {1, 2, 3, 4, 5, 7, 8, 9};
    const int rows[8] = {256, 1024, 256, 256, 256, 256, 256, 1024};
    const int cols[8] = {1024, 256, 768, 256, 512, 256, 1024, 256};
    for (int i = 0; i < 8; i++) {
        const cuuint64_t dims[2] = {(cuuint64_t)cols[i], (cuuint64_t)rows[i]};
        const cuuint64_t strides[1] = {(cuuint64_t)cols[i] * 2};
        const cuuint32_t box[2] = {64, 128};
        encode(&p.tm[1 + i], CU_TENSOR_MAP_DATA_TYPE_BFLOAT16, 2, d_in[idx[i]], dims, strides, box, ones, CU_TENSOR_MAP_INTERLEAVE_NONE,
               CU_TENSOR_MAP_SWIZZLE_128B, CU_TENSOR_MAP_L2_PROMOTION_L2_128B, CU_TENSOR_MAP_FLOAT_OOB_FILL_NONE);
        p.w[i] = (const char*)d_in[idx[i]];
    }
    {
        void* kv = nullptr;
        cudaGetSymbolAddress(&kv, g_kqv);
        const cuuint64_t dims[2] = {64, 24576};
        const cuuint64_t strides[1] = {128};
        const cuuint32_t box[2] = {64, 128};
        encode(&p.tm[9], CU_TENSOR_MAP_DATA_TYPE_BFLOAT16, 2, kv, dims, strides, box, ones, CU_TENSOR_MAP_INTERLEAVE_NONE,
               CU_TENSOR_MAP_SWIZZLE_NONE, CU_TENSOR_MAP_L2_PROMOTION_L2_128B, CU_TENSOR_MAP_FLOAT_OOB_FILL_NONE);
    }
    p.w[8] = (const char*)d_in[0];
    p.dw = (const __nv_bfloat16*)d_in[6];
    p.out = (__nv_bfloat16*)d_out;
    p.zero = 0;
    conformer_kernel<<<NCTA, NTHREADS, SMEM_LAUNCH>>>(p);
}
```

```cpp
#include <cuda_runtime.h>
#include <cuda_bf16.h>
#include <cuda.h>
#include <stdint.h>
#include <type_traits>

namespace {

constexpr int T_ = 1000;
constexpr int NCTA = 128;
constexpr int NTHREADS = 512;
constexpr int NSLOT = 5;
constexpr int SLOT = 16384;
constexpr int NLOADS = 56;

constexpr uint32_t OFF_RING = 0;
constexpr uint32_t OFF_P = 163840;
constexpr uint32_t OFF_H = 188416;
constexpr uint32_t OFF_INBOX = 221184;
constexpr uint32_t OFF_STATS = 229376;
constexpr uint32_t OFF_BARS = 229888;
constexpr uint32_t SMEM_BYTES = 230400;
constexpr uint32_t XCH = 6144;
constexpr uint32_t HCH = 4096;

constexpr int B_FULL = 0, B_EMPTY = 10, B_XR = 20, B_OIN = 22, B_HF = 24, B_INB = 28, B_QIN = 30, B_X1IN = 31, B_ST = 32, B_RDY = 33;

constexpr int PADROWS = 1040;
constexpr int FS = 8;

struct Params {
    CUtensorMap tm[10];
    const char* w[9];
    const __nv_bfloat16* dw;
    __nv_bfloat16* out;
    uint32_t zero;
};

__device__ __align__(1024) unsigned char g_kqv[3 * 8 * 1024 * 128];
__device__ __align__(1024) unsigned char g_o[8 * PADROWS * 128];
__device__ uint2 g_halo[64 * 4 * 2 * 128];
__device__ uint32_t g_flag_qk[8 * 32 * FS];
__device__ uint32_t g_flag_v[8 * 32 * FS];
__device__ uint32_t g_flag_o[2 * 16 * 4 * FS];
__device__ uint32_t g_epoch[NCTA * FS];

#define TS(i) do { } while (0)
#define TSW(i) do { } while (0)
#define TG(i) do { } while (0)
#define TSINIT() do { } while (0)
#define TSDUMP() do { } while (0)
constexpr uint32_t SMEM_LAUNCH = SMEM_BYTES;

__device__ __forceinline__ uint32_t smem_u32(const void* p) { return (uint32_t)__cvta_generic_to_shared(p); }
__device__ __forceinline__ void mbar_init(uint32_t b, uint32_t c) { asm volatile("mbarrier.init.shared::cta.b64 [%0], %1;" ::"r"(b), "r"(c) : "memory"); }
__device__ __forceinline__ void mbar_arrive(uint32_t b) { asm volatile("mbarrier.arrive.shared::cta.b64 _, [%0];" ::"r"(b) : "memory"); }
__device__ __forceinline__ void mbar_arrive_tx(uint32_t b, uint32_t tx) { asm volatile("mbarrier.arrive.expect_tx.shared::cta.b64 _, [%0], %1;" ::"r"(b), "r"(tx) : "memory"); }
__device__ __forceinline__ void mbar_wait(uint32_t b, uint32_t ph) {
    asm volatile("{\n.reg .pred p, q;\n.reg .u32 c;\nmov.u32 c, 0;\n"
                 "MW_LOOP:\n.pragma \"nounroll\";\n"
                 "mbarrier.try_wait.parity.shared::cta.b64 p, [%0], %1;\n"
                 "add.u32 c, c, 1;\nsetp.lt.u32 q, c, 65536;\nnot.pred p, p;\nand.pred p, p, q;\n@p bra MW_LOOP;\n}"
                 ::"r"(b), "r"(ph) : "memory");
}
__device__ __forceinline__ uint32_t mapa(uint32_t a, uint32_t r) { uint32_t o; asm("mapa.shared::cluster.u32 %0, %1, %2;" : "=r"(o) : "r"(a), "r"(r)); return o; }
__device__ __forceinline__ void fence_async_smem() { asm volatile("fence.proxy.async.shared::cta;" ::: "memory"); }
__device__ __forceinline__ void fence_async_global() { asm volatile("fence.proxy.async.global;" ::: "memory"); }
__device__ __forceinline__ void bar_sync(int id, int n) { asm volatile("bar.sync %0, %1;" ::"r"(id), "r"(n) : "memory"); }
__device__ __forceinline__ void bar_arrive(int id, int n) { asm volatile("bar.arrive %0, %1;" ::"r"(id), "r"(n) : "memory"); }
__device__ __forceinline__ void cluster_arrive() { asm volatile("barrier.cluster.arrive.relaxed.aligned;" ::: "memory"); }
__device__ __forceinline__ void cluster_wait() { asm volatile("barrier.cluster.wait.aligned;" ::: "memory"); }

__device__ __forceinline__ void ring_load(uint32_t dst, const CUtensorMap* tm, int c0, int c1, uint32_t bar) {
    asm volatile("{\n.reg .pred p;\nelect.sync _|p, 0xffffffff;\n"
                 "@p mbarrier.arrive.expect_tx.shared::cta.b64 _, [%2], 16384;\n"
                 "@p cp.async.bulk.tensor.2d.shared::cluster.global.mbarrier::complete_tx::bytes [%0], [%1, {%3, %4}], [%2];\n}"
                 ::"r"(dst), "l"(tm), "r"(bar), "r"(c0), "r"(c1) : "memory");
}
__device__ __forceinline__ void ring_load_both(uint32_t dst, const CUtensorMap* tm, int c1, uint32_t bar) {
    asm volatile("{\n.reg .pred p;\nelect.sync _|p, 0xffffffff;\n"
                 "@p cp.async.bulk.tensor.2d.shared::cluster.global.mbarrier::complete_tx::bytes.multicast::cluster [%0], [%1, {0, %3}], [%2], %4;\n}"
                 ::"r"(dst), "l"(tm), "r"(bar), "r"(c1), "h"((uint16_t)3) : "memory");
}
__device__ __forceinline__ void mbar_arrive_peer(uint32_t b) { asm volatile("mbarrier.arrive.relaxed.cluster.shared::cluster.b64 _, [%0];" ::"r"(b) : "memory"); }
__device__ __forceinline__ void tma3d(uint32_t dst, const CUtensorMap* tm, int c0, int c1, int c2, uint32_t bar) {
    asm volatile("cp.async.bulk.tensor.3d.shared::cluster.global.mbarrier::complete_tx::bytes [%0], [%1, {%3, %4, %5}], [%2];"
                 ::"r"(dst), "l"(tm), "r"(bar), "r"(c0), "r"(c1), "r"(c2) : "memory");
}
__device__ __forceinline__ void bulk_g2s(uint32_t dst, const void* src, uint32_t bytes, uint32_t bar) {
    asm volatile("cp.async.bulk.shared::cluster.global.mbarrier::complete_tx::bytes [%0], [%1], %2, [%3];" ::"r"(dst), "l"(src), "r"(bytes), "r"(bar) : "memory");
}
__device__ __forceinline__ void prefetch_l2(const void* src, uint32_t bytes) {
    asm volatile("cp.async.bulk.prefetch.L2.global [%0], %1;" ::"l"(src), "r"(bytes) : "memory");
}
__device__ __forceinline__ void peer_copy(uint32_t dst, uint32_t src, uint32_t bytes, uint32_t rbar) {
    asm volatile("{\n.reg .pred p;\nelect.sync _|p, 0xffffffff;\n"
                 "@p cp.async.bulk.shared::cluster.shared::cta.mbarrier::complete_tx::bytes [%0], [%1], %2, [%3];\n}"
                 ::"r"(dst), "r"(src), "r"(bytes), "r"(rbar) : "memory");
}
__device__ __forceinline__ void st_async4(uint32_t dst, uint32_t a, uint32_t b, uint32_t c, uint32_t d, uint32_t bar) {
    asm volatile("st.async.shared::cluster.mbarrier::complete_tx::bytes.v4.b32 [%0], {%1,%2,%3,%4}, [%5];" ::"r"(dst), "r"(a), "r"(b), "r"(c), "r"(d), "r"(bar) : "memory");
}
__device__ __forceinline__ void stsm4t(uint32_t a, uint32_t r0, uint32_t r1, uint32_t r2, uint32_t r3) {
    asm volatile("stmatrix.sync.aligned.m8n8.x4.trans.shared.b16 [%0], {%1,%2,%3,%4};" ::"r"(a), "r"(r0), "r"(r1), "r"(r2), "r"(r3) : "memory");
}
__device__ __forceinline__ void stsm4(uint32_t a, uint32_t r0, uint32_t r1, uint32_t r2, uint32_t r3) {
    asm volatile("stmatrix.sync.aligned.m8n8.x4.shared.b16 [%0], {%1,%2,%3,%4};" ::"r"(a), "r"(r0), "r"(r1), "r"(r2), "r"(r3) : "memory");
}
__device__ __forceinline__ void ldsm4t(uint32_t a, uint32_t& r0, uint32_t& r1, uint32_t& r2, uint32_t& r3) {
    asm volatile("ldmatrix.sync.aligned.m8n8.x4.trans.shared.b16 {%0,%1,%2,%3}, [%4];" : "=r"(r0), "=r"(r1), "=r"(r2), "=r"(r3) : "r"(a) : "memory");
}
__device__ __forceinline__ void ldsm4(uint32_t a, uint32_t& r0, uint32_t& r1, uint32_t& r2, uint32_t& r3) {
    asm volatile("ldmatrix.sync.aligned.m8n8.x4.shared.b16 {%0,%1,%2,%3}, [%4];" : "=r"(r0), "=r"(r1), "=r"(r2), "=r"(r3) : "r"(a) : "memory");
}
__device__ __forceinline__ uint4 lds128(uint32_t a) { uint4 v; asm volatile("ld.shared.v4.b32 {%0,%1,%2,%3}, [%4];" : "=r"(v.x), "=r"(v.y), "=r"(v.z), "=r"(v.w) : "r"(a) : "memory"); return v; }
__device__ __forceinline__ float4 lds128f(uint32_t a) { float4 v; asm volatile("ld.shared.v4.f32 {%0,%1,%2,%3}, [%4];" : "=f"(v.x), "=f"(v.y), "=f"(v.z), "=f"(v.w) : "r"(a) : "memory"); return v; }
__device__ __forceinline__ float2 lds64f(uint32_t a) { float2 v; asm volatile("ld.shared.v2.f32 {%0,%1}, [%2];" : "=f"(v.x), "=f"(v.y) : "r"(a) : "memory"); return v; }
__device__ __forceinline__ uint32_t lds32(uint32_t a) { uint32_t v; asm volatile("ld.shared.b32 %0, [%1];" : "=r"(v) : "r"(a) : "memory"); return v; }
__device__ __forceinline__ void sts128(uint32_t a, uint32_t x, uint32_t y, uint32_t z, uint32_t w) { asm volatile("st.shared.v4.b32 [%0], {%1,%2,%3,%4};" ::"r"(a), "r"(x), "r"(y), "r"(z), "r"(w) : "memory"); }
__device__ __forceinline__ void sts128f(uint32_t a, float x, float y, float z, float w) { asm volatile("st.shared.v4.f32 [%0], {%1,%2,%3,%4};" ::"r"(a), "f"(x), "f"(y), "f"(z), "f"(w) : "memory"); }
__device__ __forceinline__ void sts64f(uint32_t a, float x, float y) { asm volatile("st.shared.v2.f32 [%0], {%1,%2};" ::"r"(a), "f"(x), "f"(y) : "memory"); }
__device__ __forceinline__ void sts32(uint32_t a, uint32_t x) { asm volatile("st.shared.b32 [%0], %1;" ::"r"(a), "r"(x) : "memory"); }
__device__ __forceinline__ void stg128(void* p, uint4 v) { asm volatile("st.global.v4.b32 [%0], {%1,%2,%3,%4};" ::"l"(p), "r"(v.x), "r"(v.y), "r"(v.z), "r"(v.w) : "memory"); }

__device__ __forceinline__ uint32_t pack2(float lo, float hi) { uint32_t r; asm("cvt.rn.bf16x2.f32 %0, %1, %2;" : "=r"(r) : "f"(hi), "f"(lo)); return r; }
__device__ __forceinline__ float blo(uint32_t v) { return __uint_as_float(v << 16); }
__device__ __forceinline__ float bhi(uint32_t v) { return __uint_as_float(v & 0xffff0000u); }
__device__ __forceinline__ uint32_t hmul2(uint32_t a, uint32_t b) { uint32_t r; asm("mul.rn.bf16x2 %0, %1, %2;" : "=r"(r) : "r"(a), "r"(b)); return r; }
__device__ __forceinline__ uint32_t hfma2(uint32_t a, uint32_t b, uint32_t c) { uint32_t r; asm("fma.rn.bf16x2 %0, %1, %2, %3;" : "=r"(r) : "r"(a), "r"(b), "r"(c)); return r; }
__device__ __forceinline__ float tanh_fast(float x) { float r; asm("tanh.approx.f32 %0, %1;" : "=f"(r) : "f"(x)); return r; }
__device__ __forceinline__ float ex2(float x) { float r; asm("ex2.approx.ftz.f32 %0, %1;" : "=f"(r) : "f"(x)); return r; }

__device__ __forceinline__ void flag_wait(const uint32_t* p, uint32_t e) {
#pragma unroll 1
    for (int i = 0; i < (1 << 22); i++) {
        uint32_t v;
        asm volatile("ld.acquire.gpu.global.u32 %0, [%1];" : "=r"(v) : "l"(p) : "memory");
        if (v == e) return;
    }
    __trap();
}
__device__ __forceinline__ uint32_t ld_epoch() {
    uint32_t v;
    asm volatile("ld.relaxed.gpu.global.u32 %0, [%1];" : "=r"(v) : "l"(&g_epoch[blockIdx.x * FS]) : "memory");
    return v + 1;
}
__device__ __forceinline__ void flag_set(uint32_t* p, uint32_t e) { asm volatile("st.release.gpu.global.u32 [%0], %1;" ::"l"(p), "r"(e) : "memory"); }

__device__ __forceinline__ uint32_t desc_lo(uint32_t addr) { return ((addr & 0x3FFFF) >> 4) | 0x10000u; }
__device__ __forceinline__ uint64_t mkdesc(uint32_t lo) { return (uint64_t)lo | (0x40000040ull << 32); }
__device__ __forceinline__ void wg_fence() { asm volatile("wgmma.fence.sync.aligned;" ::: "memory"); }
__device__ __forceinline__ void wg_commit() { asm volatile("wgmma.commit_group.sync.aligned;" ::: "memory"); }
template <int N> __device__ __forceinline__ void wg_wait() { asm volatile("wgmma.wait_group.sync.aligned %0;" ::"n"(N) : "memory"); }
template <int N> __device__ __forceinline__ void pin(float (&d)[N]) {
#pragma unroll
    for (int i = 0; i < N; i++) asm volatile("" : "+f"(d[i])::"memory");
}
template <int N> __device__ __forceinline__ void pin(uint32_t (&d)[N]) {
#pragma unroll
    for (int i = 0; i < N; i++) asm volatile("" : "+r"(d[i])::"memory");
}

template <typename Tp, int N> __device__ __forceinline__ void zero(Tp (&d)[N]) {
#pragma unroll
    for (int i = 0; i < N; i++) d[i] = 0;
    pin(d);
}

#define F4(d, i) "+f"(d[i]), "+f"(d[i + 1]), "+f"(d[i + 2]), "+f"(d[i + 3])
#define F16(d, i) F4(d, i), F4(d, i + 4), F4(d, i + 8), F4(d, i + 12)

__device__ __forceinline__ void mma_t(float (&d)[16], uint64_t a, uint64_t b, int acc) {
    asm volatile("{.reg .pred p; setp.ne.b32 p, %18, 0;\n"
                 "wgmma.mma_async.sync.aligned.m64n32k16.f32.bf16.bf16 {%0,%1,%2,%3,%4,%5,%6,%7,%8,%9,%10,%11,%12,%13,%14,%15}, %16, %17, p, 1, 1, 1, 0;}\n"
                 : F16(d, 0) : "l"(a), "l"(b), "r"(acc));
}
__device__ __forceinline__ void mma_t(float (&d)[20], uint64_t a, uint64_t b, int acc) {
    asm volatile("{.reg .pred p; setp.ne.b32 p, %22, 0;\n"
                 "wgmma.mma_async.sync.aligned.m64n40k16.f32.bf16.bf16 {%0,%1,%2,%3,%4,%5,%6,%7,%8,%9,%10,%11,%12,%13,%14,%15,%16,%17,%18,%19}, %20, %21, p, 1, 1, 1, 0;}\n"
                 : F16(d, 0), F4(d, 16) : "l"(a), "l"(b), "r"(acc));
}
__device__ __forceinline__ void mma_t(float (&d)[24], uint64_t a, uint64_t b, int acc) {
    asm volatile("{.reg .pred p; setp.ne.b32 p, %26, 0;\n"
                 "wgmma.mma_async.sync.aligned.m64n48k16.f32.bf16.bf16 {%0,%1,%2,%3,%4,%5,%6,%7,%8,%9,%10,%11,%12,%13,%14,%15,%16,%17,%18,%19,%20,%21,%22,%23}, %24, %25, p, 1, 1, 1, 0;}\n"
                 : F16(d, 0), F4(d, 16), F4(d, 20) : "l"(a), "l"(b), "r"(acc));
}
__device__ __forceinline__ void mma_qk(float (&d)[32], uint32_t a0, uint32_t a1, uint32_t a2, uint32_t a3, uint64_t b, int acc) {
    asm volatile("{.reg .pred p; setp.ne.b32 p, %37, 0;\n"
                 "wgmma.mma_async.sync.aligned.m64n64k16.f32.bf16.bf16 {%0,%1,%2,%3,%4,%5,%6,%7,%8,%9,%10,%11,%12,%13,%14,%15,%16,%17,%18,%19,%20,%21,%22,%23,%24,%25,%26,%27,%28,%29,%30,%31}, "
                 "{%32,%33,%34,%35}, %36, p, 1, 1, 0;}\n"
                 : F16(d, 0), F16(d, 16) : "r"(a0), "r"(a1), "r"(a2), "r"(a3), "l"(b), "r"(acc));
}
__device__ __forceinline__ void mma_pv(float (&d)[36], uint32_t a0, uint32_t a1, uint32_t a2, uint32_t a3, uint64_t b) {
    asm volatile("wgmma.mma_async.sync.aligned.m64n72k16.f32.bf16.bf16 {%0,%1,%2,%3,%4,%5,%6,%7,%8,%9,%10,%11,%12,%13,%14,%15,%16,%17,%18,%19,%20,%21,%22,%23,%24,%25,%26,%27,%28,%29,%30,%31,%32,%33,%34,%35}, "
                 "{%36,%37,%38,%39}, %40, 1, 1, 1, 1;\n"
                 : F16(d, 0), F16(d, 16), F4(d, 32) : "r"(a0), "r"(a1), "r"(a2), "r"(a3), "l"(b));
}

template <uint32_t CSTRIDE, int N>
__device__ __forceinline__ void issue_half(float (&d)[N], uint32_t alo, uint32_t blo_, int acc) {
    const uint64_t a = mkdesc(alo), b = mkdesc(blo_);
    wg_fence();
#pragma unroll
    for (int k = 0; k < 8; k++) mma_t(d, a + k * 128, b + (k >> 2) * (CSTRIDE >> 4) + (k & 3) * 2, k == 0 ? acc : 1);
    wg_commit();
}

__device__ __forceinline__ uint32_t load_code(int n, int r, int w) {
    const int tile = 2 * r + w;
    int m, col, row;
    if (n < 16 || n >= 40) {
        const int k = n < 16 ? n : n - 40;
        m = n < 16 ? 1 : 7;
        if (k < 8) { col = 8 * r + (k & 6) + w; row = (k & 1) ^ r; }
        else {
            const int kk = k == 11 ? 12 : (k == 12 ? 11 : k);
            m++; col = kk < 12 ? (tile ^ 2) : tile; row = 4 * r + (kk & 3);
        }
    } else if (n < 32) {
        const int k = n - 16;
        m = 3;
        if (k < 4) { col = tile + ((k & 1) ? 0 : 4); row = (k >> 1) ^ r; }
        else { col = 8 + tile; row = (k & 1) ^ r; }
    } else if (n < 34) { m = 4; col = tile; row = n - 32; }
    else if (n < 38) { const int k = n - 34; m = 5; col = tile + 4 * (k & 1); row = (k >> 1) ^ r; }
    else { m = 6; col = tile; row = (n & 1) ^ r; }
    return m | (col << 4) | (row << 8);
}

__global__ void __cluster_dims__(2, 1, 1) __launch_bounds__(NTHREADS, 1)
conformer_kernel(const __grid_constant__ Params p) {
    extern __shared__ __align__(1024) unsigned char smem_raw[];
    const uint32_t sb = smem_u32(smem_raw);
    const uint32_t bars = sb + OFF_BARS;
    const int tid = threadIdx.x;
    const int lane = tid & 31;
    const int warp = __shfl_sync(~0u, tid >> 5, 0);
    const int r = blockIdx.x & 1;
    const int pair = blockIdx.x >> 1;
    const int b = pair >> 5, pt = pair & 31;
    const int ah = pt >> 3, qt = (pt & 7) * 2 + r;
    const int abh = b * 4 + ah;

    TG(30);
    TSINIT();
    TS(0);
    const uint32_t P = sb + OFF_P, H = sb + OFF_H;
    auto xwait = [&](int j) { mbar_wait(bars + (B_XR + (j & 1)) * 8, (j >> 1) & 1); };

    if (warp >= 8) {
        asm volatile("setmaxnreg.dec.sync.aligned.u32 48;");
        if (warp >= 12) {
            if (warp == 12 && lane >= 2 && lane < 10) asm volatile("prefetch.tensormap [%0];" ::"l"(&p.tm[lane]) : "memory");
            cluster_arrive();
            cluster_wait();
            const int ut = tid & 127;
            const uint32_t a4 = P + (ut >> 2) * 128 + (2 * (ut & 3) + ((ut >> 2) & 1)) * 16;
            const uint32_t a8 = P + (32 + (ut >> 3)) * 128 + (ut & 7) * 16;
#pragma unroll 1
            for (int k = 0; k < 4; k++) {
                float s = 0.f, q = 0.f, s2 = 0.f, q2 = 0.f;
#pragma unroll 1
                for (int h = 0; h < 2; h++) {
                    if (h == 0 && k != 0) bar_sync(1, 384);
                    else xwait(k == 3 ? 4 : k);
                    const uint32_t off = 2 * (r ^ h) * XCH;
                    uint4 v0 = lds128(a4 + off), v1 = lds128((a4 ^ 16) + off), v2 = lds128(a4 + off + XCH), v3 = lds128((a4 ^ 16) + off + XCH);
                    uint4 v4 = make_uint4(0, 0, 0, 0), v5 = v4;
                    if (k == 2) { v4 = lds128(a8 + off); v5 = lds128(a8 + off + XCH); }
                    if (h == 1 || k == 1 || k == 2) bar_arrive(5 + ((v3.w | v5.w) & p.zero), 384);
                    uint32_t t;
                    asm volatile("mov.u32 %0, %%clock;" : "=r"(t)::"memory");
                    const uint32_t mul = 65536u + (t & p.zero), msk = 0u - mul;
                    auto accum = [&](const uint4& v, float& s, float& q) {
                        const float a0 = __uint_as_float(v.x * mul), a1 = __uint_as_float(v.x & msk), a2 = __uint_as_float(v.y * mul), a3 = __uint_as_float(v.y & msk);
                        const float a4 = __uint_as_float(v.z * mul), a5 = __uint_as_float(v.z & msk), a6 = __uint_as_float(v.w * mul), a7 = __uint_as_float(v.w & msk);
                        s += ((a0 + a1) + (a2 + a3)) + ((a4 + a5) + (a6 + a7));
                        q += fmaf(a0, a0, fmaf(a1, a1, fmaf(a2, a2, a3 * a3))) + fmaf(a4, a4, fmaf(a5, a5, fmaf(a6, a6, a7 * a7)));
                    };
                    accum(v0, s, q); accum(v1, s, q); accum(v2, s, q); accum(v3, s, q);
                    if (k == 2) { accum(v4, s2, q2); accum(v5, s2, q2); }
                }
#pragma unroll
                for (int o = 1; o < 8; o <<= 1) {
                    if (o < 4) { s += __shfl_xor_sync(~0u, s, o); q += __shfl_xor_sync(~0u, q, o); }
                    if (k == 2) { s2 += __shfl_xor_sync(~0u, s2, o); q2 += __shfl_xor_sync(~0u, q2, o); }
                }
                const bool second = (ut & 7) == 1;
                if (second) { s = s2; q = q2; }
                const float mean = s * (1.f / 256.f);
                const int row = second ? 32 + (ut >> 3) : ut >> 2;
                const float alpha = k == 1 ? 1.f : ((k == 2 && (uint32_t)(pt * 32 - 8 + row) >= T_) ? 0.f : 0.5f);
                const float rstd = alpha * rsqrtf(fmaxf(fmaf(-mean, mean, q * (1.f / 256.f)), 0.f) + 1e-5f);
                if ((ut & 3) == 0 || second) sts64f(sb + OFF_STATS + row * 8, mean * rstd, rstd);
                __syncwarp();
                if (lane == 0) mbar_arrive(bars + B_ST * 8);
                TS(2 + k);
                if (k == 1 && warp == 12) {
                    const uint32_t epoch = ld_epoch();
                    bar_sync(11, 288);
                    if (lane < 2) flag_set(&g_flag_v[((b * 4 + 2 * r + lane) * 32 + pt) * FS], epoch);
                    __syncwarp();
                    TS(13);
                }
            }
        } else if (warp < 10) {
            const int w = warp - 8;
            const uint32_t ring = sb + OFF_RING + w * NSLOT * SLOT;
            const uint32_t full = bars + (B_FULL + w * NSLOT) * 8;
            if (lane == 0) {
#pragma unroll
                for (int i = 0; i < NSLOT; i++) mbar_init(full + i * 8, 1);
                asm volatile("fence.mbarrier_init.release.cluster;" ::: "memory");
                fence_async_smem();
            }
            __syncwarp();
            cluster_arrive();
            TS(1);
#pragma unroll
            for (int n = 0; n < NSLOT; n++)
                ring_load(ring + n * SLOT, &p.tm[1], 64 * (8 * r + (n & 6) + w), 128 * ((n & 1) ^ r), full + n * 8);
            TS(2);
            const uint32_t code = load_code(lane, r, w) | (load_code(lane + 32, r, w) << 16);
            cluster_wait();
            uint32_t s = 0, ph = 0;
            int n = NSLOT;
#pragma unroll 1
            for (int seg = 0; seg < 2; seg++) {
#pragma unroll 1
                for (; n < (seg == 0 ? 22 : NLOADS); n++) {
                    const uint32_t c = __shfl_sync(~0u, code, n) >> (n & 32 ? 16 : 0);
                    mbar_wait(full + (B_EMPTY - B_FULL) * 8 + s * 8, ph);
                    ring_load(ring + s * SLOT, &p.tm[c & 15], (c & 0xf0) * 4, (c & 0xff00) >> 1, full + s * 8);
                    if (++s == NSLOT) { s = 0; ph ^= 1; }
                }
                if (seg == 1) break;
                const uint32_t epoch = ld_epoch();
                const uint32_t rdy = bars + (B_RDY + 3 * w) * 8, prdy = mapa(rdy, r ^ 1);
#pragma unroll 1
                for (; n < 32; n++) {
                    mbar_wait(full + (B_EMPTY - B_FULL) * 8 + s * 8, ph);
                    if (lane == 0) {
                        if (n < 24) mbar_arrive(full + s * 8);
                        else mbar_arrive_tx(full + s * 8, SLOT);
                    }
                    if (n == 28) {
                        if (lane == 0) mbar_arrive_peer(prdy);
                        mbar_wait(rdy, 0);
                        flag_wait((r ? g_flag_v : g_flag_qk) + (abh * 32 + lane) * FS, epoch);
                        __syncwarp();
                        fence_async_global();
                        TS(5 + r);
#pragma unroll
                        for (int i = 0; i < 3; i++) {
                            const uint32_t sl = r ? 2 * i + 1 : (i ? 2 * i - 2 : 4);
                            if (i < 2 || r == 0) ring_load_both(ring + sl * SLOT, &p.tm[9], (r * 128 + abh * 8 + 2 * i + w) * 128, full + sl * 8);
                        }
                    } else if (n > 28) {
                        const uint32_t bo = n == 31 ? 16 : 8;
                        if ((n > 29) == (r == 1)) {
                            mbar_wait(rdy + bo, 0);
                            ring_load_both(ring + s * SLOT, &p.tm[9], (r * 128 + abh * 8 + (n == 30 ? 4 : 6) + w) * 128, full + s * 8);
                        } else if (lane == 0) mbar_arrive_peer(prdy + bo);
                    }
                    __syncwarp();
                    if (++s == NSLOT) { s = 0; ph ^= 1; }
                }
            }
        } else if (warp == 10) {
            if (lane == 0) {
                mbar_init(bars + B_XR * 8, 1);
                asm volatile("fence.mbarrier_init.release.cluster;" ::: "memory");
                fence_async_smem();
            }
            __syncwarp();
            cluster_arrive();
            if (lane == 0) {
                mbar_arrive_tx(bars + B_XR * 8, 16384);
#pragma unroll
                for (int i = 0; i < 4; i++) tma3d(P + i * XCH, &p.tm[0], i * 64, pt * 32, b, bars + B_XR * 8);
            }
            __syncwarp();
            cluster_wait();
            const uint32_t epoch = ld_epoch();
            if (lane == 0) {
                mbar_arrive_tx(bars + B_QIN * 8, 8192);
                mbar_arrive_tx(bars + B_OIN * 8, 2 * XCH);
                mbar_arrive_tx(bars + B_OIN * 8 + 8, 2 * XCH);
            }
            if (lane < 2) flag_wait(&g_flag_qk[(abh * 32 + 2 * qt + lane) * FS], epoch);
            __syncwarp();
            if (lane == 0) {
                fence_async_global();
                bulk_g2s(H + 24576, g_kqv + 1048576 + (size_t)(abh * 1024 + qt * 64) * 128, 8192, bars + B_QIN * 8);
            }
            if (lane < 2) {
                const int np = pt - 1 + 2 * lane;
                if (np >= 0 && np < 32) flag_wait(&g_flag_qk[((b * 4 + 2 * r) * 32 + np) * FS], epoch);
            }
            __syncwarp();
            if (lane == 0) mbar_arrive(bars + B_X1IN * 8);
            bar_sync(9, 64);
            if (lane < 8) {
                const int q = (pt >> 1) + (lane < 4 ? 0 : ((pt & 1) ? 1 : -1));
                if (q >= 0 && q < 16) flag_wait(&g_flag_o[((b * 16 + q) * 4 + (lane & 3)) * FS], epoch);
            }
            __syncwarp();
            TSW(10);
            if (lane == 0) {
                fence_async_global();
#pragma unroll
                for (int i = 0; i < 4; i++)
                    bulk_g2s(H + i * XCH, g_o + (size_t)((b * 4 + i) * PADROWS + pt * 32) * 128, XCH, bars + (B_OIN + (i >> 1)) * 8);
            }
            __syncwarp();
        } else {
            uint32_t kb = (lane < 2 || lane > 5) ? 4096 : (lane == 2 ? 3072 : (lane == 4 ? 2048 : 1024));
            size_t off = (size_t)blockIdx.x * kb;
            if (lane == 8) { kb = 8192; off = (size_t)min(b * T_ + pt * 32 + r * 16, 2 * T_ - 16) * 512; }
            const char* pf = p.w[min(lane, 8)] + off;
            if (lane == 0 || lane == 8) prefetch_l2(pf, kb);
            __syncwarp();
            cluster_arrive();
            cluster_wait();
            xwait(0);
            if (lane == 1 || lane == 2) prefetch_l2(pf, kb);
            mbar_wait(bars + B_HF * 8, 0);
            if (lane > 2 && lane < 8) prefetch_l2(pf, kb);
            const uint32_t epoch = ld_epoch();
            bar_sync(4, 288);
            if (lane < 2) flag_set(&g_flag_qk[((b * 4 + 2 * r + lane) * 32 + pt) * FS], epoch);
            __syncwarp();
            TSW(8);
            bar_sync(6, 288);
            bar_arrive(9, 64);
            if (lane == 0) {
                flag_set(&g_flag_o[((b * 16 + qt) * 4 + ah) * FS], epoch);
                g_epoch[blockIdx.x * FS] = epoch;
            }
            __syncwarp();
            TSW(9);
        }
        TSDUMP();
        return;
    }

    if (lane == 0) {
        mbar_init(bars + (B_EMPTY + warp) * 8, 4);
        mbar_init(bars + (B_HF + warp) * 8, warp < 4 ? 8 : 1);
        if (warp < 3) mbar_init(bars + (warp == 2 ? B_ST : B_EMPTY + 8 + warp) * 8, 4);
        else if (warp < 6) mbar_init(bars + (B_XR - 2 + warp) * 8, 1);
        if (warp < 6) mbar_init(bars + (B_RDY + warp) * 8, 1);
        asm volatile("fence.mbarrier_init.release.cluster;" ::: "memory");
    }
    sts128(P + (tid >> 6) * XCH + 4096 + (tid & 63) * 16, 0x3F803F80u, 0x3F803F80u, 0x3F803F80u, 0x3F803F80u);
    fence_async_smem();
    __syncwarp();
    cluster_arrive();
    asm volatile("setmaxnreg.inc.sync.aligned.u32 208;");
    const int w = warp >> 2, wq = warp & 3;
    const int tile = 2 * r + w;
    const int wt = tid & 127;
    const int c4 = lane & 3;
    const uint32_t rbase = sb + OFF_RING + w * NSLOT * SLOT, fbar = bars + (B_FULL + w * NSLOT) * 8;
    const uint32_t rdesc = desc_lo(rbase);
    auto acq = [&](int n) { mbar_wait(fbar + (n % NSLOT) * 8, (n / NSLOT) & 1); };
    auto rel = [&](int n) { if (lane == 0) mbar_arrive(fbar + (B_EMPTY - B_FULL + n % NSLOT) * 8); };
    const uint32_t pown = desc_lo(P + 2 * r * XCH), prem = desc_lo(P + 2 * (r ^ 1) * XCH), hdesc = desc_lo(H);
    const uint32_t toff = ((lane >> 4) * 8 + (lane & 7)) * 128 + (((2 * wq + ((lane >> 3) & 1)) ^ (lane & 7)) << 4);
    const uint32_t xa = P + tile * XCH + toff;
    auto publish = [&](int j, uint32_t src, uint32_t bytes, int nsync) {
        const uint32_t bar = bars + (B_XR + (j & 1)) * 8;
        fence_async_smem();
        bar_sync(2 + w, 128);
        if (wq == 0) peer_copy(mapa(src, r ^ 1), src, bytes, mapa(bar, r ^ 1));
        if (tid == 32) mbar_arrive_tx(bar, 2 * bytes);
        bar_sync(nsync == 384 ? 1 : 10, nsync);
    };
    auto gate = [&](int j) { xwait(j); bar_sync(5, 384); };
    auto load_stats = [&](auto& st, int parity) {
        mbar_wait(bars + B_ST * 8, parity);
#pragma unroll
        for (int j = 0; j < (int)(sizeof(st) / 16); j++) {
            const float4 v = lds128f(sb + OFF_STATS + (8 * j + 2 * c4) * 8);
            st[4 * j] = v.x; st[4 * j + 1] = v.y; st[4 * j + 2] = v.z; st[4 * j + 3] = v.w;
        }
    };
    bar_sync(10, 256);
    cluster_wait();
    uint32_t xr[8];
    xwait(0);
    ldsm4t(xa, xr[0], xr[1], xr[2], xr[3]);
    ldsm4t(xa + 2048, xr[4], xr[5], xr[6], xr[7]);
    acq(0); acq(1);

#pragma unroll 1
    for (int ffi = 0; ffi < 2; ffi++) {
        auto mm = [&](auto& d, int n, uint32_t bd, auto cs, int acc) {
            const uint32_t z = p.zero * (ffi + n + 1);
            issue_half<decltype(cs)::value>(d, rdesc + z + (n % NSLOT) * (SLOT >> 4), bd + z, acc);
        };
        constexpr std::integral_constant<uint32_t, XCH> cx{};
        constexpr std::integral_constant<uint32_t, HCH> ch{};
        {
            float st[16], a0[20], a1[20], rem[16], own[16];
            const uint32_t inb = bars + (B_INB + w) * 8, box = sb + OFF_INBOX + w * 4096 + wt * 16;
            const uint32_t hdst = H + w * HCH + toff;
            auto step = [&](auto& d, int n, uint32_t bd, auto cs, int acc) {
                mm(d, n, bd, cs, acc);
                wg_wait<1>();
                if (n > 0) rel(n - 1);
            };
            auto epi = [&](float (&d)[20], int i, int half) {
                uint32_t pk[4];
#pragma unroll
                for (int k = 4 * half; k < 4 * half + 4; k++) {
                    const float cs = d[16 + 2 * (k & 1)];
                    const float v0 = fmaf(-st[(k >> 1) * 4], cs, d[2 * k] * st[(k >> 1) * 4 + 1]);
                    const float v1 = fmaf(-st[(k >> 1) * 4 + 2], cs, d[2 * k + 1] * st[(k >> 1) * 4 + 3]);
                    pk[k & 3] = pack2(fmaf(v0, tanh_fast(v0), v0), fmaf(v1, tanh_fast(v1), v1));
                }
                stsm4t(hdst + 2 * i * HCH + half * 2048, pk[0], pk[1], pk[2], pk[3]);
            };
            auto hdone = [&](int i) {
                fence_async_smem();
                __syncwarp();
                if (lane == 0) mbar_arrive(bars + (B_HF + i) * 8);
            };
            auto hwait = [&](int i) { mbar_wait(bars + (B_HF + i) * 8, ffi); };
            TS(1 + ffi * 20);
            step(a0, 0, pown, cx, 0);
            if (wt == 0) mbar_arrive_tx(inb, 4096);
            acq(2);
            gate(ffi * 4);
            TS(32);
            step(a0, 1, prem, cx, 1);
            step(a1, 2, pown, cx, 0); acq(3); pin(a0); load_stats(st, ffi); TS(33); epi(a0, 0, 0);
            step(a1, 3, prem, cx, 1); acq(4); epi(a0, 0, 1); TS(34);
            step(a0, 4, pown, cx, 0); acq(5); pin(a1); epi(a1, 1, 0);
            step(a0, 5, prem, cx, 1); acq(6); epi(a1, 1, 1); TS(35);
            step(a1, 6, pown, cx, 0); acq(7); pin(a0); hdone(0); epi(a0, 2, 0);
            step(a1, 7, prem, cx, 1); acq(8); hwait(0); epi(a0, 2, 1); TS(36);
            step(rem, 8, hdesc, ch, 0); acq(9); pin(a1); hdone(1); epi(a1, 3, 0);
            step(rem, 9, hdesc + 2 * (HCH >> 4), ch, 1); acq(10); hwait(1); epi(a1, 3, 1);
            TS(2 + ffi * 20);
            step(rem, 10, hdesc + 4 * (HCH >> 4), ch, 1); acq(11); hdone(2);
            step(own, 11, hdesc, ch, 0); acq(12); hwait(2);
            step(rem, 12, hdesc + 6 * (HCH >> 4), ch, 1); acq(13);
            step(own, 13, hdesc + 2 * (HCH >> 4), ch, 1); acq(14);
            pin(rem);
            {
                const uint32_t dst = mapa(box, r ^ 1), bar = mapa(inb, r ^ 1);
                st_async4(dst, pack2(rem[0], rem[1]), pack2(rem[2], rem[3]), pack2(rem[4], rem[5]), pack2(rem[6], rem[7]), bar);
                st_async4(dst + 2048, pack2(rem[8], rem[9]), pack2(rem[10], rem[11]), pack2(rem[12], rem[13]), pack2(rem[14], rem[15]), bar);
            }
            step(own, 14, hdesc + 4 * (HCH >> 4), ch, 1); acq(15);
            step(own, 15, hdesc + 6 * (HCH >> 4), ch, 1);
            mbar_wait(inb, ffi);
            const uint4 u = lds128(box), v = lds128(box + 2048);
            const uint32_t pr[8] = {u.x, u.y, u.z, u.w, v.x, v.y, v.z, v.w};
            if (ffi == 0) { acq(16); acq(17); }
            wg_wait<0>();
            pin(own);
            TS(3 + ffi * 20);
#pragma unroll
            for (int i = 0; i < 8; i++)
                xr[i] = pack2(fmaf(0.5f, own[2 * i] + blo(pr[i]), blo(xr[i])), fmaf(0.5f, own[2 * i + 1] + bhi(pr[i]), bhi(xr[i])));
            stsm4t(xa, xr[0], xr[1], xr[2], xr[3]);
            stsm4t(xa + 2048, xr[4], xr[5], xr[6], xr[7]);
            rel(15);
            publish(ffi ? 5 : 1, P + tile * XCH + (ffi ? (r ^ 1) * 2048 : 0), ffi ? 2048 : 4096, ffi ? 256 : 384);
        }
        if (ffi == 1) break;

        {
            float ak[20], aq[20], st[16];
            g_halo[((pair * 4 + tile) * 2 + 0) * 128 + wt] = make_uint2(xr[0], xr[1]);
            g_halo[((pair * 4 + tile) * 2 + 1) * 128 + wt] = make_uint2(xr[6], xr[7]);
            bar_sync(5, 384);
            TS(11);
            mm(ak, 16, pown, cx, 0);
            mm(aq, 17, pown, cx, 0);
            acq(18); acq(19);
            gate(1);
            mm(ak, 18, prem, cx, 1);
            mm(aq, 19, prem, cx, 1);
            wg_wait<2>();
            rel(16); rel(17);
            load_stats(st, 1);
            auto stage_out = [&](float (&d)[20], uint32_t dst) {
                uint32_t pk[8];
#pragma unroll
                for (int k = 0; k < 8; k++) {
                    const float cs = d[16 + 2 * (k & 1)];
                    pk[k] = pack2(fmaf(-st[(k >> 1) * 4], cs, d[2 * k] * st[(k >> 1) * 4 + 1]),
                                  fmaf(-st[(k >> 1) * 4 + 2], cs, d[2 * k + 1] * st[(k >> 1) * 4 + 3]));
                }
                stsm4t(dst + toff, pk[0], pk[1], pk[2], pk[3]);
                stsm4t(dst + toff + 2048, pk[4], pk[5], pk[6], pk[7]);
            };
            const uint32_t stg = H + w * 12288;
            unsigned char* g = g_kqv + (size_t)((b * 4 + tile) * 1024 + pt * 32) * 128 + wt * 16;
            wg_wait<0>();
            pin(ak); pin(aq);
            TS(37);
            stage_out(ak, stg);
            stage_out(aq, stg + 4096);
            bar_sync(2 + w, 128);
            {
                const uint4 k0 = lds128(stg + wt * 16), k1 = lds128(stg + 2048 + wt * 16), q0 = lds128(stg + 4096 + wt * 16), q1 = lds128(stg + 6144 + wt * 16);
                stg128(g, k0); stg128(g + 2048, k1);
                stg128(g + 1048576, q0); stg128(g + 1048576 + 2048, q1);
            }
            bar_arrive(4, 288);
            TS(38);
            rel(18); rel(19);
            acq(20); acq(21);
            bar_sync(10, 256);
            mm(ak, 20, pown, cx, 0);
            mm(ak, 21, prem, cx, 1);
            wg_wait<0>();
            pin(ak);
            stage_out(ak, stg + 8192);
            rel(20); rel(21);
            bar_sync(2 + w, 128);
            {
                const uint4 v0 = lds128(stg + 8192 + wt * 16), v1 = lds128(stg + 10240 + wt * 16);
                stg128(g + 2097152, v0); stg128(g + 2097152 + 2048, v1);
            }
            bar_arrive(11, 288);
            acq(22); acq(23);
            rel(22); rel(23);
            TS(12);
        }

        {
            constexpr float CS = 0.125f * 1.4426950408889634f;
            float sa[32], sb2[32], o[36];
            uint32_t pa[16], pb[16], q[16];
            float n0 = INFINITY, n1 = INFINITY;
            zero(o); zero(pa); zero(pb);
            const uint32_t ones = sb + OFF_INBOX + 2048;
            if (tid < 128) sts128(ones + tid * 16, 0x3F803F80u, 0x3F803F80u, 0x3F803F80u, 0x3F803F80u);
            fence_async_smem();
            bar_sync(10, 256);
            const uint32_t vdesc = rdesc + ((((ones - rbase) >> 4) - 1) << 16);
            auto qk_issue = [&](float (&s)[32], uint32_t off) {
                const uint64_t kd = mkdesc(rdesc + off);
                wg_fence();
#pragma unroll
                for (int k = 0; k < 4; k++) mma_qk(s, q[4 * k], q[4 * k + 1], q[4 * k + 2], q[4 * k + 3], kd + 2 * k, k != 0);
            };
            auto pv_issue = [&](uint32_t (&pp)[16], uint32_t off) {
                const uint64_t vd = mkdesc(vdesc - off * 65535u);
                wg_fence();
#pragma unroll
                for (int k = 0; k < 4; k++) mma_pv(o, pp[4 * k], pp[4 * k + 1], pp[4 * k + 2], pp[4 * k + 3], vd - k * (128 * 65535));
            };
            auto new_max = [&](float (&s)[32], float& x0, float& x1) {
                x0 = s[0]; x1 = s[2];
#pragma unroll
                for (int j = 0; j < 8; j++) {
                    x0 = fmaxf(x0, fmaxf(s[4 * j], s[4 * j + 1]));
                    x1 = fmaxf(x1, fmaxf(s[4 * j + 2], s[4 * j + 3]));
                }
                x0 = fmaxf(x0, __shfl_xor_sync(~0u, x0, 1)); x1 = fmaxf(x1, __shfl_xor_sync(~0u, x1, 1));
                x0 = fmaxf(x0, __shfl_xor_sync(~0u, x0, 2)); x1 = fmaxf(x1, __shfl_xor_sync(~0u, x1, 2));
                x0 = fminf(n0, fmaf(x0, -CS, -20.f)); x1 = fminf(n1, fmaf(x1, -CS, -20.f));
            };
            auto probs = [&](float (&s)[32], uint32_t (&pp)[16], uint32_t bar, uint32_t parity) {
                uint32_t any = 0;
#pragma unroll
                for (int i = 0; i < 16; i++) {
                    pp[i] = pack2(ex2(fmaf(s[2 * i], CS, (i & 1) ? n1 : n0)), ex2(fmaf(s[2 * i + 1], CS, (i & 1) ? n1 : n0)));
                    any |= pp[i];
                }
                const bool big = __any_sync(~0u, any & 0x40004000u);
                mbar_wait(bar, parity + (any & p.zero));
                wg_wait<0>();
                pin(sa); pin(sb2); pin(o); pin(pa); pin(pb);
                if (big) {
                    float x0, x1;
                    new_max(s, x0, x1);
                    const float sc0 = ex2(x0 - n0), sc1 = ex2(x1 - n1);
                    n0 = x0; n1 = x1;
#pragma unroll
                    for (int j = 0; j < 9; j++) { o[4 * j] *= sc0; o[4 * j + 1] *= sc0; o[4 * j + 2] *= sc1; o[4 * j + 3] *= sc1; }
#pragma unroll
                    for (int i = 0; i < 16; i++)
                        pp[i] = pack2(ex2(fmaf(s[2 * i], CS, (i & 1) ? n1 : n0)), ex2(fmaf(s[2 * i + 1], CS, (i & 1) ? n1 : n0)));
                }
            };
            mbar_wait(bars + B_QIN * 8, 0);
            {
                const uint32_t qa = H + 24576 + (wq * 16 + (lane & 15)) * 128;
#pragma unroll
                for (int k = 0; k < 4; k++) ldsm4(qa + (((2 * k + (lane >> 4)) ^ (lane & 7)) << 4), q[4 * k], q[4 * k + 1], q[4 * k + 2], q[4 * k + 3]);
                pin(q);
            }
            acq(24);
            TS(13);
            qk_issue(sa, (24 % NSLOT) * (SLOT >> 4));
            wg_commit();
            qk_issue(sb2, (24 % NSLOT) * (SLOT >> 4) + 512);
            wg_commit();
            wg_wait<1>();
            pin(sa);
            {
                float x0, x1;
                new_max(sa, x0, x1);
                n0 = x0; n1 = x1;
            }
#pragma unroll 1
            for (int it = 0; it < 4; it++) {
                const uint32_t ks = 2 * it, vs = (0x1031u >> (4 * it)) & 7;
                TS(40 + it * 4);
                probs(sa, pa, fbar + vs * 8, it < 2);
                TS(41 + it * 4);
                if (it == 0) acq(25);
                if (it == 3 && w == 1) {
#pragma unroll
                    for (int i = 20; i < 32; i++) sb2[i] = -INFINITY;
                }
                pin(sb2);
                pv_issue(pa, vs * (SLOT >> 4));
                if (it < 3) qk_issue(sa, ks * (SLOT >> 4));
                wg_commit();
                if (lane == 0) {
                    mbar_arrive(fbar + (B_EMPTY - B_FULL) * 8 + ((0x4204u >> (4 * it)) & 7) * 8);
                    if (it) mbar_arrive(fbar + (B_EMPTY - B_FULL) * 8 + ((0x0310u >> (4 * it)) & 7) * 8);
                }
                TS(42 + it * 4);
                probs(sb2, pb, it < 2 ? fbar + (ks + 2) * 8 : bars + B_QIN * 8, it < 2);
                TS(43 + it * 4);
                pv_issue(pb, vs * (SLOT >> 4) + 512);
                if (it < 3) qk_issue(sb2, ks * (SLOT >> 4) + 512);
                wg_commit();
            }
            const int row = wq * 16 + (lane >> 2);
            const uint32_t ml = sb + OFF_INBOX;
            wg_wait<0>();
            pin(o); pin(pb); pin(sa); pin(sb2);
            rel(31);
            const float l0 = o[32], l1 = o[34];
            if (c4 == 0) { sts64f(ml + w * 512 + row * 8, n0, l0); sts64f(ml + w * 512 + row * 8 + 64, n1, l1); }
            TS(14);
            float mine[16];
#pragma unroll
            for (int j = 0; j < 4; j++) {
                if (w == 0) sts128f(H + j * 2048 + wt * 16, o[16 + 4 * j], o[17 + 4 * j], o[18 + 4 * j], o[19 + 4 * j]);
                else sts128f(H + 8192 + j * 2048 + wt * 16, o[4 * j], o[4 * j + 1], o[4 * j + 2], o[4 * j + 3]);
            }
#pragma unroll
            for (int i = 0; i < 16; i++) mine[i] = w == 0 ? o[i] : o[16 + i];
            bar_sync(10, 256);
            const float2 u0 = lds64f(ml + (w ^ 1) * 512 + row * 8), u1 = lds64f(ml + (w ^ 1) * 512 + row * 8 + 64);
            const float x0 = fminf(n0, u0.x), x1 = fminf(n1, u1.x);
            float a0 = ex2(x0 - n0), b0 = ex2(x0 - u0.x), a1 = ex2(x1 - n1), b1 = ex2(x1 - u1.x);
            const float i0 = __fdividef(1.f, fmaf(a0, l0, b0 * u0.y)), i1 = __fdividef(1.f, fmaf(a1, l1, b1 * u1.y));
            a0 *= i0; b0 *= i0; a1 *= i1; b1 *= i1;
            uint32_t pk[8];
#pragma unroll
            for (int j = 0; j < 4; j++) {
                const float4 v = lds128f(H + (w ^ 1) * 8192 + j * 2048 + wt * 16);
                pk[2 * j] = pack2(fmaf(a0, mine[4 * j], b0 * v.x), fmaf(a0, mine[4 * j + 1], b0 * v.y));
                pk[2 * j + 1] = pack2(fmaf(a1, mine[4 * j + 2], b1 * v.z), fmaf(a1, mine[4 * j + 3], b1 * v.w));
            }
            const uint32_t og = H + 16384 + wq * 2048;
            {
                const uint32_t ra = og + (((lane >> 3) & 1) * 8 + (lane & 7)) * 128;
                stsm4(ra + (((4 * w + (lane >> 4)) ^ (lane & 7)) << 4), pk[0], pk[1], pk[2], pk[3]);
                stsm4(ra + (((4 * w + 2 + (lane >> 4)) ^ (lane & 7)) << 4), pk[4], pk[5], pk[6], pk[7]);
            }
            __syncwarp();
            {
                const uint32_t off = (lane >> 2) * 128 + (((4 * w + c4) ^ (lane >> 2)) << 4);
                const uint4 v0 = lds128(og + off), v1 = lds128(og + off + 1024);
                unsigned char* dst = g_o + (size_t)(abh * PADROWS + 8 + qt * 64 + wq * 16) * 128 + off;
                stg128(dst, v0); stg128(dst + 1024, v1);
            }
            bar_arrive(6, 288);
            TS(15);
        }

        uint32_t dwr[15];
        {
#pragma unroll
            for (int i = 0; i < 15; i++) dwr[i] = hmul2(__ldg(reinterpret_cast<const uint32_t*>(p.dw + i * 256 + tile * 64) + lane), 0x3F003F00u);
            float d[24];
            uint32_t xw[12];
            mbar_wait(bars + B_X1IN * 8, 0);
            uint2 hl = make_uint2(0, 0), hr = hl;
            if (pt > 0) hl = __ldcg(&g_halo[(((pair - 1) * 4 + tile) * 2 + 1) * 128 + wt]);
            if (pt < 31) hr = __ldcg(&g_halo[(((pair + 1) * 4 + tile) * 2 + 0) * 128 + wt]);
            xw[0] = hl.x; xw[1] = hl.y; xw[10] = hr.x; xw[11] = hr.y;
#pragma unroll
            for (int i = 0; i < 8; i++) xw[2 + i] = xr[i];
            pin(xw);
            pin(dwr);
            acq(32); acq(33); acq(34); acq(35);
            mbar_wait(bars + B_OIN * 8, 0);
            TS(16);
            mm(d, 32, hdesc, cx, 0);
            mbar_wait(bars + B_OIN * 8 + 8, 0);
            mm(d, 33, hdesc + 2 * (XCH >> 4), cx, 1);
            wg_wait<1>();
            rel(32);
            wg_wait<0>();
            pin(d);
#pragma unroll
            for (int i = 0; i < 12; i++) xw[i] = pack2(d[2 * i] + blo(xw[i]), d[2 * i + 1] + bhi(xw[i]));
            if (c4 == 0) { xw[0] = (xw[0] & 0xffff0000u) | 0x3F80u; xw[1] = (xw[1] & 0xffff0000u) | 0x3F80u; }
#pragma unroll
            for (int j = 0; j < 3; j++) stsm4t(xa + j * 2048, xw[4 * j], xw[4 * j + 1], xw[4 * j + 2], xw[4 * j + 3]);
#pragma unroll
            for (int i = 0; i < 8; i++) xr[i] = xw[2 + i];
            rel(33);
            publish(2, P + tile * XCH, XCH, 384);
            TS(17);
        }
        {
            float da[24], db[24], st[24];
            bar_sync(5, 384);
            mm(da, 34, pown, cx, 0);
            mm(db, 35, pown, cx, 0);
            acq(36); acq(37);
            gate(2);
            TS(39);
            mm(da, 36, prem, cx, 1);
            mm(db, 37, prem, cx, 1);
            wg_wait<2>();
            rel(34); rel(35);
            load_stats(st, 0);
            wg_wait<0>();
            pin(da); pin(db);
            rel(36); rel(37);
            TS(18);
            uint32_t pk[12];
#pragma unroll
            for (int hh = 0; hh < 2; hh++) {
                const float ca = __shfl_sync(~0u, da[2 * hh], lane & 28), cb = __shfl_sync(~0u, db[2 * hh], lane & 28);
#pragma unroll
                for (int j = 0; j < 6; j++) {
                    const float u0 = fmaf(-st[4 * j], ca, da[4 * j + 2 * hh] * st[4 * j + 1]);
                    const float u1 = fmaf(-st[4 * j + 2], ca, da[4 * j + 2 * hh + 1] * st[4 * j + 3]);
                    const float v0 = fmaf(-st[4 * j], cb, db[4 * j + 2 * hh] * st[4 * j + 1]);
                    const float v1 = fmaf(-st[4 * j + 2], cb, db[4 * j + 2 * hh + 1] * st[4 * j + 3]);
                    pk[2 * j + hh] = pack2(fmaf(u0, tanh_fast(v0), u0), fmaf(u1, tanh_fast(v1), u1));
                }
            }
            const uint32_t gs = H + 16384 + w * XCH;
#pragma unroll
            for (int j = 0; j < 3; j++) stsm4t(gs + toff + j * 2048, pk[4 * j], pk[4 * j + 1], pk[4 * j + 2], pk[4 * j + 3]);
            bar_sync(2 + w, 128);
            uint32_t ca[8], cb[8];
            const uint32_t grow = gs + 8 * wq * 128 + c4 * 4, srow = H + tile * HCH + 8 * wq * 128 + c4 * 4;
#pragma unroll
            for (int k = 0; k < 22; k++) {
                const uint32_t v = lds32(grow + (1 + k) * 128 + (((lane >> 2) ^ ((1 + k) & 7)) << 4));
#pragma unroll
                for (int i = 0; i < 8; i++) {
                    const int tap = k - i;
                    if (tap == 0) ca[i] = hmul2(v, dwr[0]);
                    else if (tap > 0 && tap < 8) ca[i] = hfma2(v, dwr[tap], ca[i]);
                    else if (tap == 8) cb[i] = hmul2(v, dwr[8]);
                    else if (tap > 8 && tap < 15) cb[i] = hfma2(v, dwr[tap], cb[i]);
                }
            }
#pragma unroll
            for (int i = 0; i < 8; i++) {
                const float h0 = blo(ca[i]) + blo(cb[i]), h1 = bhi(ca[i]) + bhi(cb[i]);
                sts32(srow + i * 128 + (((lane >> 2) ^ i) << 4), pack2(fmaf(h0, tanh_fast(h0), h0), fmaf(h1, tanh_fast(h1), h1)));
            }
            acq(38); acq(39);
            publish(3, H + tile * HCH, HCH, 256);
            TS(19);
        }
        {
            float d[16];
            mm(d, 38, hdesc + 2 * r * (HCH >> 4), ch, 0);
            acq(40); acq(41);
            xwait(3);
            sts128(P + (wt >> 6 ? (tile ^ 2) : tile) * XCH + 4096 + (wt & 63) * 16, 0x3F803F80u, 0x3F803F80u, 0x3F803F80u, 0x3F803F80u);
            mm(d, 39, hdesc + 2 * (r ^ 1) * (HCH >> 4), ch, 1);
            wg_wait<1>();
            rel(38);
            wg_wait<0>();
            pin(d);
#pragma unroll
            for (int i = 0; i < 8; i++) xr[i] = pack2(d[2 * i] + blo(xr[i]), d[2 * i + 1] + bhi(xr[i]));
            stsm4t(xa, xr[0], xr[1], xr[2], xr[3]);
            stsm4t(xa + 2048, xr[4], xr[5], xr[6], xr[7]);
            rel(39);
            publish(4, P + tile * XCH, HCH, 384);
            TS(20);
        }
    }

    xwait(5);
    cluster_arrive();
    TS(24);
    {
        float a[2][8], s[2], q[2];
        const int row0 = 16 * r + 2 * warp;
#pragma unroll
        for (int i = 0; i < 2; i++) {
            const uint4 v = lds128(P + (lane >> 3) * XCH + (row0 + i) * 128 + (((lane & 7) ^ ((row0 + i) & 7)) << 4));
            a[i][0] = blo(v.x); a[i][1] = bhi(v.x); a[i][2] = blo(v.y); a[i][3] = bhi(v.y);
            a[i][4] = blo(v.z); a[i][5] = bhi(v.z); a[i][6] = blo(v.w); a[i][7] = bhi(v.w);
            s[i] = ((a[i][0] + a[i][1]) + (a[i][2] + a[i][3])) + ((a[i][4] + a[i][5]) + (a[i][6] + a[i][7]));
            q[i] = 0.f;
#pragma unroll
            for (int k = 0; k < 8; k++) q[i] = fmaf(a[i][k], a[i][k], q[i]);
        }
#pragma unroll
        for (int o = 16; o > 0; o >>= 1) {
#pragma unroll
            for (int i = 0; i < 2; i++) { s[i] += __shfl_xor_sync(~0u, s[i], o); q[i] += __shfl_xor_sync(~0u, q[i], o); }
        }
#pragma unroll
        for (int i = 0; i < 2; i++) {
            const float mean = s[i] * (1.f / 256.f);
            const float rstd = rsqrtf(fmaxf(fmaf(-mean, mean, q[i] * (1.f / 256.f)), 0.f) + 1e-5f);
            const float nb = -mean * rstd;
            uint4 v;
            v.x = pack2(fmaf(a[i][0], rstd, nb), fmaf(a[i][1], rstd, nb)); v.y = pack2(fmaf(a[i][2], rstd, nb), fmaf(a[i][3], rstd, nb));
            v.z = pack2(fmaf(a[i][4], rstd, nb), fmaf(a[i][5], rstd, nb)); v.w = pack2(fmaf(a[i][6], rstd, nb), fmaf(a[i][7], rstd, nb));
            const int t = pt * 32 + row0 + i;
            if (t < T_) stg128(p.out + (size_t)(b * T_ + t) * 256 + lane * 8, v);
        }
    }
    TS(25);
    TG(31);
    TSDUMP();
    cluster_wait();
}

typedef CUresult (*EncodeFn)(CUtensorMap*, CUtensorMapDataType, cuuint32_t, void*, const cuuint64_t*, const cuuint64_t*,
                             const cuuint32_t*, const cuuint32_t*, CUtensorMapInterleave, CUtensorMapSwizzle,
                             CUtensorMapL2promotion, CUtensorMapFloatOOBfill);

}

extern "C" void kernel_launch(void* const* d_in, const int* in_sizes, int n_in, void* d_out, int out_size) {
    static EncodeFn encode = nullptr;
    if (!encode) {
        void* fn = nullptr;
        cudaDriverEntryPointQueryResult qr;
        cudaGetDriverEntryPoint("cuTensorMapEncodeTiled", &fn, cudaEnableDefault, &qr);
        encode = (EncodeFn)fn;
        cudaFuncSetAttribute(conformer_kernel, cudaFuncAttributeMaxDynamicSharedMemorySize, SMEM_LAUNCH);
    }
    Params p;
    const cuuint32_t ones[3] = {1, 1, 1};
    {
        const cuuint64_t dims[3] = {256, T_, 2};
        const cuuint64_t strides[2] = {512, 512ull * T_};
        const cuuint32_t box[3] = {64, 32, 1};
        encode(&p.tm[0], CU_TENSOR_MAP_DATA_TYPE_BFLOAT16, 3, d_in[0], dims, strides, box, ones, CU_TENSOR_MAP_INTERLEAVE_NONE,
               CU_TENSOR_MAP_SWIZZLE_128B, CU_TENSOR_MAP_L2_PROMOTION_L2_256B, CU_TENSOR_MAP_FLOAT_OOB_FILL_NONE);
    }
    const int idx[8] = {1, 2, 3, 4, 5, 7, 8, 9};
    const int rows[8] = {256, 1024, 256, 256, 256, 256, 256, 1024};
    const int cols[8] = {1024, 256, 768, 256, 512, 256, 1024, 256};
    for (int i = 0; i < 8; i++) {
        const cuuint64_t dims[2] = {(cuuint64_t)cols[i], (cuuint64_t)rows[i]};
        const cuuint64_t strides[1] = {(cuuint64_t)cols[i] * 2};
        const cuuint32_t box[2] = {64, 128};
        encode(&p.tm[1 + i], CU_TENSOR_MAP_DATA_TYPE_BFLOAT16, 2, d_in[idx[i]], dims, strides, box, ones, CU_TENSOR_MAP_INTERLEAVE_NONE,
               CU_TENSOR_MAP_SWIZZLE_128B, CU_TENSOR_MAP_L2_PROMOTION_L2_128B, CU_TENSOR_MAP_FLOAT_OOB_FILL_NONE);
        p.w[i] = (const char*)d_in[idx[i]];
    }
    {
        void* kv = nullptr;
        cudaGetSymbolAddress(&kv, g_kqv);
        const cuuint64_t dims[2] = {64, 24576};
        const cuuint64_t strides[1] = {128};
        const cuuint32_t box[2] = {64, 128};
        encode(&p.tm[9], CU_TENSOR_MAP_DATA_TYPE_BFLOAT16, 2, kv, dims, strides, box, ones, CU_TENSOR_MAP_INTERLEAVE_NONE,
               CU_TENSOR_MAP_SWIZZLE_NONE, CU_TENSOR_MAP_L2_PROMOTION_L2_128B, CU_TENSOR_MAP_FLOAT_OOB_FILL_NONE);
    }
    p.w[8] = (const char*)d_in[0];
    p.dw = (const __nv_bfloat16*)d_in[6];
    p.out = (__nv_bfloat16*)d_out;
    p.zero = 0;
    conformer_kernel<<<NCTA, NTHREADS, SMEM_LAUNCH>>>(p);
}
```

```cpp
#include <cuda_runtime.h>
#include <cuda_bf16.h>
#include <cuda.h>
#include <stdint.h>
#include <type_traits>

namespace {

constexpr int T_ = 1000;
constexpr int NCTA = 128;
constexpr int NTHREADS = 512;
constexpr int NSLOT = 5;
constexpr int SLOT = 16384;
constexpr int NLOADS = 56;

constexpr uint32_t OFF_RING = 0;
constexpr uint32_t OFF_P = 163840;
constexpr uint32_t OFF_H = 188416;
constexpr uint32_t OFF_INBOX = 221184;
constexpr uint32_t OFF_STATS = 229376;
constexpr uint32_t OFF_BARS = 229888;
constexpr uint32_t SMEM_BYTES = 230400;
constexpr uint32_t XCH = 6144;
constexpr uint32_t HCH = 4096;

constexpr int B_FULL = 0, B_EMPTY = 10, B_XR = 20, B_OIN = 22, B_HF = 24, B_INB = 28, B_QIN = 30, B_X1IN = 31, B_ST = 32, B_RDY = 33;

constexpr int PADROWS = 1040;
constexpr int FS = 8;

struct Params {
    CUtensorMap tm[10];
    const char* w[9];
    const __nv_bfloat16* dw;
    __nv_bfloat16* out;
    uint32_t zero;
};

__device__ __align__(1024) unsigned char g_kqv[3 * 8 * 1024 * 128];
__device__ __align__(1024) unsigned char g_o[8 * PADROWS * 128];
__device__ uint2 g_halo[64 * 4 * 2 * 128];
__device__ uint32_t g_flag_qk[8 * 32 * FS];
__device__ uint32_t g_flag_v[8 * 32 * FS];
__device__ uint32_t g_flag_o[2 * 16 * 4 * FS];
__device__ uint32_t g_epoch[NCTA * FS];

#define TS(i) do { } while (0)
#define TSW(i) do { } while (0)
#define TG(i) do { } while (0)
#define TSINIT() do { } while (0)
#define TSDUMP() do { } while (0)
constexpr uint32_t SMEM_LAUNCH = SMEM_BYTES;

__device__ __forceinline__ uint32_t smem_u32(const void* p) { return (uint32_t)__cvta_generic_to_shared(p); }
__device__ __forceinline__ void mbar_init(uint32_t b, uint32_t c) { asm volatile("mbarrier.init.shared::cta.b64 [%0], %1;" ::"r"(b), "r"(c) : "memory"); }
__device__ __forceinline__ void mbar_arrive(uint32_t b) { asm volatile("mbarrier.arrive.shared::cta.b64 _, [%0];" ::"r"(b) : "memory"); }
__device__ __forceinline__ void mbar_arrive_tx(uint32_t b, uint32_t tx) { asm volatile("mbarrier.arrive.expect_tx.shared::cta.b64 _, [%0], %1;" ::"r"(b), "r"(tx) : "memory"); }
__device__ __forceinline__ void mbar_wait(uint32_t b, uint32_t ph) {
    asm volatile("{\n.reg .pred p, q;\n.reg .u32 c;\nmov.u32 c, 0;\n"
                 "MW_LOOP:\n.pragma \"nounroll\";\n"
                 "mbarrier.try_wait.parity.shared::cta.b64 p, [%0], %1;\n"
                 "add.u32 c, c, 1;\nsetp.lt.u32 q, c, 65536;\nnot.pred p, p;\nand.pred p, p, q;\n@p bra MW_LOOP;\n}"
                 ::"r"(b), "r"(ph) : "memory");
}
__device__ __forceinline__ bool mbar_test(uint32_t b, uint32_t ph) {
    uint32_t ok;
    asm volatile("{\n.reg .pred p;\nmbarrier.test_wait.parity.shared::cta.b64 p, [%1], %2;\nselp.u32 %0, 1, 0, p;\n}" : "=r"(ok) : "r"(b), "r"(ph) : "memory");
    return ok;
}
__device__ __forceinline__ uint32_t mapa(uint32_t a, uint32_t r) { uint32_t o; asm("mapa.shared::cluster.u32 %0, %1, %2;" : "=r"(o) : "r"(a), "r"(r)); return o; }
__device__ __forceinline__ void fence_async_smem() { asm volatile("fence.proxy.async.shared::cta;" ::: "memory"); }
__device__ __forceinline__ void fence_async_global() { asm volatile("fence.proxy.async.global;" ::: "memory"); }
__device__ __forceinline__ void bar_sync(int id, int n) { asm volatile("bar.sync %0, %1;" ::"r"(id), "r"(n) : "memory"); }
__device__ __forceinline__ void bar_arrive(int id, int n) { asm volatile("bar.arrive %0, %1;" ::"r"(id), "r"(n) : "memory"); }
__device__ __forceinline__ void cluster_arrive() { asm volatile("barrier.cluster.arrive.relaxed.aligned;" ::: "memory"); }
__device__ __forceinline__ void cluster_wait() { asm volatile("barrier.cluster.wait.aligned;" ::: "memory"); }

__device__ __forceinline__ void ring_load(uint32_t dst, const CUtensorMap* tm, int c0, int c1, uint32_t bar) {
    asm volatile("{\n.reg .pred p;\nelect.sync _|p, 0xffffffff;\n"
                 "@p mbarrier.arrive.expect_tx.shared::cta.b64 _, [%2], 16384;\n"
                 "@p cp.async.bulk.tensor.2d.shared::cluster.global.mbarrier::complete_tx::bytes [%0], [%1, {%3, %4}], [%2];\n}"
                 ::"r"(dst), "l"(tm), "r"(bar), "r"(c0), "r"(c1) : "memory");
}
__device__ __forceinline__ void ring_load_both(uint32_t dst, const CUtensorMap* tm, int c1, uint32_t bar) {
    asm volatile("{\n.reg .pred p;\nelect.sync _|p, 0xffffffff;\n"
                 "@p cp.async.bulk.tensor.2d.shared::cluster.global.mbarrier::complete_tx::bytes.multicast::cluster [%0], [%1, {0, %3}], [%2], %4;\n}"
                 ::"r"(dst), "l"(tm), "r"(bar), "r"(c1), "h"((uint16_t)3) : "memory");
}
__device__ __forceinline__ void mbar_arrive_peer(uint32_t b) { asm volatile("mbarrier.arrive.relaxed.cluster.shared::cluster.b64 _, [%0];" ::"r"(b) : "memory"); }
__device__ __forceinline__ void tma3d(uint32_t dst, const CUtensorMap* tm, int c0, int c1, int c2, uint32_t bar) {
    asm volatile("cp.async.bulk.tensor.3d.shared::cluster.global.mbarrier::complete_tx::bytes [%0], [%1, {%3, %4, %5}], [%2];"
                 ::"r"(dst), "l"(tm), "r"(bar), "r"(c0), "r"(c1), "r"(c2) : "memory");
}
__device__ __forceinline__ void bulk_g2s(uint32_t dst, const void* src, uint32_t bytes, uint32_t bar) {
    asm volatile("cp.async.bulk.shared::cluster.global.mbarrier::complete_tx::bytes [%0], [%1], %2, [%3];" ::"r"(dst), "l"(src), "r"(bytes), "r"(bar) : "memory");
}
__device__ __forceinline__ void prefetch_l2(const void* src, uint32_t bytes) {
    asm volatile("cp.async.bulk.prefetch.L2.global [%0], %1;" ::"l"(src), "r"(bytes) : "memory");
}
__device__ __forceinline__ void peer_copy(uint32_t dst, uint32_t src, uint32_t bytes, uint32_t rbar) {
    asm volatile("{\n.reg .pred p;\nelect.sync _|p, 0xffffffff;\n"
                 "@p cp.async.bulk.shared::cluster.shared::cta.mbarrier::complete_tx::bytes [%0], [%1], %2, [%3];\n}"
                 ::"r"(dst), "r"(src), "r"(bytes), "r"(rbar) : "memory");
}
__device__ __forceinline__ void st_async4(uint32_t dst, uint32_t a, uint32_t b, uint32_t c, uint32_t d, uint32_t bar) {
    asm volatile("st.async.shared::cluster.mbarrier::complete_tx::bytes.v4.b32 [%0], {%1,%2,%3,%4}, [%5];" ::"r"(dst), "r"(a), "r"(b), "r"(c), "r"(d), "r"(bar) : "memory");
}
__device__ __forceinline__ void stsm4t(uint32_t a, uint32_t r0, uint32_t r1, uint32_t r2, uint32_t r3) {
    asm volatile("stmatrix.sync.aligned.m8n8.x4.trans.shared.b16 [%0], {%1,%2,%3,%4};" ::"r"(a), "r"(r0), "r"(r1), "r"(r2), "r"(r3) : "memory");
}
__device__ __forceinline__ void stsm4(uint32_t a, uint32_t r0, uint32_t r1, uint32_t r2, uint32_t r3) {
    asm volatile("stmatrix.sync.aligned.m8n8.x4.shared.b16 [%0], {%1,%2,%3,%4};" ::"r"(a), "r"(r0), "r"(r1), "r"(r2), "r"(r3) : "memory");
}
__device__ __forceinline__ void ldsm4t(uint32_t a, uint32_t& r0, uint32_t& r1, uint32_t& r2, uint32_t& r3) {
    asm volatile("ldmatrix.sync.aligned.m8n8.x4.trans.shared.b16 {%0,%1,%2,%3}, [%4];" : "=r"(r0), "=r"(r1), "=r"(r2), "=r"(r3) : "r"(a) : "memory");
}
__device__ __forceinline__ void ldsm4(uint32_t a, uint32_t& r0, uint32_t& r1, uint32_t& r2, uint32_t& r3) {
    asm volatile("ldmatrix.sync.aligned.m8n8.x4.shared.b16 {%0,%1,%2,%3}, [%4];" : "=r"(r0), "=r"(r1), "=r"(r2), "=r"(r3) : "r"(a) : "memory");
}
__device__ __forceinline__ uint4 lds128(uint32_t a) { uint4 v; asm volatile("ld.shared.v4.b32 {%0,%1,%2,%3}, [%4];" : "=r"(v.x), "=r"(v.y), "=r"(v.z), "=r"(v.w) : "r"(a) : "memory"); return v; }
__device__ __forceinline__ float4 lds128f(uint32_t a) { float4 v; asm volatile("ld.shared.v4.f32 {%0,%1,%2,%3}, [%4];" : "=f"(v.x), "=f"(v.y), "=f"(v.z), "=f"(v.w) : "r"(a) : "memory"); return v; }
__device__ __forceinline__ float2 lds64f(uint32_t a) { float2 v; asm volatile("ld.shared.v2.f32 {%0,%1}, [%2];" : "=f"(v.x), "=f"(v.y) : "r"(a) : "memory"); return v; }
__device__ __forceinline__ uint32_t lds32(uint32_t a) { uint32_t v; asm volatile("ld.shared.b32 %0, [%1];" : "=r"(v) : "r"(a) : "memory"); return v; }
__device__ __forceinline__ void sts128(uint32_t a, uint32_t x, uint32_t y, uint32_t z, uint32_t w) { asm volatile("st.shared.v4.b32 [%0], {%1,%2,%3,%4};" ::"r"(a), "r"(x), "r"(y), "r"(z), "r"(w) : "memory"); }
__device__ __forceinline__ void sts128f(uint32_t a, float x, float y, float z, float w) { asm volatile("st.shared.v4.f32 [%0], {%1,%2,%3,%4};" ::"r"(a), "f"(x), "f"(y), "f"(z), "f"(w) : "memory"); }
__device__ __forceinline__ void sts64f(uint32_t a, float x, float y) { asm volatile("st.shared.v2.f32 [%0], {%1,%2};" ::"r"(a), "f"(x), "f"(y) : "memory"); }
__device__ __forceinline__ void sts32(uint32_t a, uint32_t x) { asm volatile("st.shared.b32 [%0], %1;" ::"r"(a), "r"(x) : "memory"); }
__device__ __forceinline__ void stg128(void* p, uint4 v) { asm volatile("st.global.v4.b32 [%0], {%1,%2,%3,%4};" ::"l"(p), "r"(v.x), "r"(v.y), "r"(v.z), "r"(v.w) : "memory"); }

__device__ __forceinline__ uint32_t pack2(float lo, float hi) { uint32_t r; asm("cvt.rn.bf16x2.f32 %0, %1, %2;" : "=r"(r) : "f"(hi), "f"(lo)); return r; }
__device__ __forceinline__ float blo(uint32_t v) { return __uint_as_float(v << 16); }
__device__ __forceinline__ float bhi(uint32_t v) { return __uint_as_float(v & 0xffff0000u); }
__device__ __forceinline__ uint32_t hmul2(uint32_t a, uint32_t b) { uint32_t r; asm("mul.rn.bf16x2 %0, %1, %2;" : "=r"(r) : "r"(a), "r"(b)); return r; }
__device__ __forceinline__ uint32_t hfma2(uint32_t a, uint32_t b, uint32_t c) { uint32_t r; asm("fma.rn.bf16x2 %0, %1, %2, %3;" : "=r"(r) : "r"(a), "r"(b), "r"(c)); return r; }
__device__ __forceinline__ float tanh_fast(float x) { float r; asm("tanh.approx.f32 %0, %1;" : "=f"(r) : "f"(x)); return r; }
__device__ __forceinline__ float ex2(float x) { float r; asm("ex2.approx.ftz.f32 %0, %1;" : "=f"(r) : "f"(x)); return r; }

__device__ __forceinline__ void flag_wait(const uint32_t* p, uint32_t e) {
#pragma unroll 1
    for (int i = 0; i < (1 << 22); i++) {
        uint32_t v;
        asm volatile("ld.acquire.gpu.global.u32 %0, [%1];" : "=r"(v) : "l"(p) : "memory");
        if (v == e) return;
    }
    __trap();
}
__device__ __forceinline__ uint32_t ld_epoch() {
    uint32_t v;
    asm volatile("ld.relaxed.gpu.global.u32 %0, [%1];" : "=r"(v) : "l"(&g_epoch[blockIdx.x * FS]) : "memory");
    return v + 1;
}
__device__ __forceinline__ void flag_set(uint32_t* p, uint32_t e) { asm volatile("st.release.gpu.global.u32 [%0], %1;" ::"l"(p), "r"(e) : "memory"); }

__device__ __forceinline__ uint32_t desc_lo(uint32_t addr) { return ((addr & 0x3FFFF) >> 4) | 0x10000u; }
__device__ __forceinline__ uint64_t mkdesc(uint32_t lo) { return (uint64_t)lo | (0x40000040ull << 32); }
__device__ __forceinline__ void wg_fence() { asm volatile("wgmma.fence.sync.aligned;" ::: "memory"); }
__device__ __forceinline__ void wg_commit() { asm volatile("wgmma.commit_group.sync.aligned;" ::: "memory"); }
template <int N> __device__ __forceinline__ void wg_wait() { asm volatile("wgmma.wait_group.sync.aligned %0;" ::"n"(N) : "memory"); }
template <int N> __device__ __forceinline__ void pin(float (&d)[N]) {
#pragma unroll
    for (int i = 0; i < N; i++) asm volatile("" : "+f"(d[i])::"memory");
}
template <int N> __device__ __forceinline__ void pin(uint32_t (&d)[N]) {
#pragma unroll
    for (int i = 0; i < N; i++) asm volatile("" : "+r"(d[i])::"memory");
}

template <typename Tp, int N> __device__ __forceinline__ void zero(Tp (&d)[N]) {
#pragma unroll
    for (int i = 0; i < N; i++) d[i] = 0;
    pin(d);
}

#define F4(d, i) "+f"(d[i]), "+f"(d[i + 1]), "+f"(d[i + 2]), "+f"(d[i + 3])
#define F16(d, i) F4(d, i), F4(d, i + 4), F4(d, i + 8), F4(d, i + 12)

__device__ __forceinline__ void mma_t(float (&d)[16], uint64_t a, uint64_t b, int acc) {
    asm volatile("{.reg .pred p; setp.ne.b32 p, %18, 0;\n"
                 "wgmma.mma_async.sync.aligned.m64n32k16.f32.bf16.bf16 {%0,%1,%2,%3,%4,%5,%6,%7,%8,%9,%10,%11,%12,%13,%14,%15}, %16, %17, p, 1, 1, 1, 0;}\n"
                 : F16(d, 0) : "l"(a), "l"(b), "r"(acc));
}
__device__ __forceinline__ void mma_t(float (&d)[20], uint64_t a, uint64_t b, int acc) {
    asm volatile("{.reg .pred p; setp.ne.b32 p, %22, 0;\n"
                 "wgmma.mma_async.sync.aligned.m64n40k16.f32.bf16.bf16 {%0,%1,%2,%3,%4,%5,%6,%7,%8,%9,%10,%11,%12,%13,%14,%15,%16,%17,%18,%19}, %20, %21, p, 1, 1, 1, 0;}\n"
                 : F16(d, 0), F4(d, 16) : "l"(a), "l"(b), "r"(acc));
}
__device__ __forceinline__ void mma_t(float (&d)[24], uint64_t a, uint64_t b, int acc) {
    asm volatile("{.reg .pred p; setp.ne.b32 p, %26, 0;\n"
                 "wgmma.mma_async.sync.aligned.m64n48k16.f32.bf16.bf16 {%0,%1,%2,%3,%4,%5,%6,%7,%8,%9,%10,%11,%12,%13,%14,%15,%16,%17,%18,%19,%20,%21,%22,%23}, %24, %25, p, 1, 1, 1, 0;}\n"
                 : F16(d, 0), F4(d, 16), F4(d, 20) : "l"(a), "l"(b), "r"(acc));
}
__device__ __forceinline__ void mma_qk(float (&d)[32], uint32_t a0, uint32_t a1, uint32_t a2, uint32_t a3, uint64_t b, int acc) {
    asm volatile("{.reg .pred p; setp.ne.b32 p, %37, 0;\n"
                 "wgmma.mma_async.sync.aligned.m64n64k16.f32.bf16.bf16 {%0,%1,%2,%3,%4,%5,%6,%7,%8,%9,%10,%11,%12,%13,%14,%15,%16,%17,%18,%19,%20,%21,%22,%23,%24,%25,%26,%27,%28,%29,%30,%31}, "
                 "{%32,%33,%34,%35}, %36, p, 1, 1, 0;}\n"
                 : F16(d, 0), F16(d, 16) : "r"(a0), "r"(a1), "r"(a2), "r"(a3), "l"(b), "r"(acc));
}
__device__ __forceinline__ void mma_pv(float (&d)[36], uint32_t a0, uint32_t a1, uint32_t a2, uint32_t a3, uint64_t b) {
    asm volatile("wgmma.mma_async.sync.aligned.m64n72k16.f32.bf16.bf16 {%0,%1,%2,%3,%4,%5,%6,%7,%8,%9,%10,%11,%12,%13,%14,%15,%16,%17,%18,%19,%20,%21,%22,%23,%24,%25,%26,%27,%28,%29,%30,%31,%32,%33,%34,%35}, "
                 "{%36,%37,%38,%39}, %40, 1, 1, 1, 1;\n"
                 : F16(d, 0), F16(d, 16), F4(d, 32) : "r"(a0), "r"(a1), "r"(a2), "r"(a3), "l"(b));
}

template <uint32_t CSTRIDE, int N>
__device__ __forceinline__ void issue_half(float (&d)[N], uint32_t alo, uint32_t blo_, int acc) {
    const uint64_t a = mkdesc(alo), b = mkdesc(blo_);
    wg_fence();
#pragma unroll
    for (int k = 0; k < 8; k++) mma_t(d, a + k * 128, b + (k >> 2) * (CSTRIDE >> 4) + (k & 3) * 2, k == 0 ? acc : 1);
    wg_commit();
}

__device__ __forceinline__ uint32_t load_code(int n, int r, int w) {
    const int tile = 2 * r + w;
    int m, col, row;
    if (n < 16 || n >= 40) {
        const int k = n < 16 ? n : n - 40;
        m = n < 16 ? 1 : 7;
        if (k < 8) { col = 8 * r + (k & 6) + w; row = (k & 1) ^ r; }
        else {
            const int kk = k == 11 ? 12 : (k == 12 ? 11 : k);
            m++; col = kk < 12 ? (tile ^ 2) : tile; row = 4 * r + (kk & 3);
        }
    } else if (n < 32) {
        const int k = n - 16;
        m = 3;
        if (k < 4) { col = tile + ((k & 1) ? 0 : 4); row = (k >> 1) ^ r; }
        else { col = 8 + tile; row = (k & 1) ^ r; }
    } else if (n < 34) { m = 4; col = tile; row = n - 32; }
    else if (n < 38) { const int k = n - 34; m = 5; col = tile + 4 * (k & 1); row = (k >> 1) ^ r; }
    else { m = 6; col = tile; row = (n & 1) ^ r; }
    return m | (col << 4) | (row << 8);
}

__global__ void __cluster_dims__(2, 1, 1) __launch_bounds__(NTHREADS, 1)
conformer_kernel(const __grid_constant__ Params p) {
    extern __shared__ __align__(1024) unsigned char smem_raw[];
    const uint32_t sb = smem_u32(smem_raw);
    const uint32_t bars = sb + OFF_BARS;
    const int tid = threadIdx.x;
    const int lane = tid & 31;
    const int warp = __shfl_sync(~0u, tid >> 5, 0);
    const int r = blockIdx.x & 1;
    const int pair = blockIdx.x >> 1;
    const int b = pair >> 5, pt = pair & 31;
    const int ah = pt >> 3, qt = (pt & 7) * 2 + r;
    const int abh = b * 4 + ah;

    TG(30);
    TSINIT();
    TS(0);
    const uint32_t P = sb + OFF_P, H = sb + OFF_H;
    auto xwait = [&](int j) { mbar_wait(bars + (B_XR + (j & 1)) * 8, (j >> 1) & 1); };

    if (warp >= 8) {
        asm volatile("setmaxnreg.dec.sync.aligned.u32 48;");
        if (warp >= 12) {
            if (warp == 12 && lane >= 2 && lane < 10) asm volatile("prefetch.tensormap [%0];" ::"l"(&p.tm[lane]) : "memory");
            cluster_arrive();
            cluster_wait();
            const int ut = tid & 127;
            const uint32_t a4 = P + (ut >> 2) * 128 + (2 * (ut & 3) + ((ut >> 2) & 1)) * 16;
            const uint32_t a8 = P + (32 + (ut >> 3)) * 128 + (ut & 7) * 16;
#pragma unroll 1
            for (int k = 0; k < 4; k++) {
                float s = 0.f, q = 0.f, s2 = 0.f, q2 = 0.f;
#pragma unroll 1
                for (int h = 0; h < 2; h++) {
                    if (h == 0 && k != 0) bar_sync(1, 384);
                    else xwait(k == 3 ? 4 : k);
                    const uint32_t off = 2 * (r ^ h) * XCH;
                    uint4 v0 = lds128(a4 + off), v1 = lds128((a4 ^ 16) + off), v2 = lds128(a4 + off + XCH), v3 = lds128((a4 ^ 16) + off + XCH);
                    uint4 v4 = make_uint4(0, 0, 0, 0), v5 = v4;
                    if (k == 2) { v4 = lds128(a8 + off); v5 = lds128(a8 + off + XCH); }
                    if (h == 1 || k == 1 || k == 2) bar_arrive(5 + ((v3.w | v5.w) & p.zero), 384);
                    uint32_t t;
                    asm volatile("mov.u32 %0, %%clock;" : "=r"(t)::"memory");
                    const uint32_t mul = 65536u + (t & p.zero), msk = 0u - mul;
                    auto accum = [&](const uint4& v, float& s, float& q) {
                        const float a0 = __uint_as_float(v.x * mul), a1 = __uint_as_float(v.x & msk), a2 = __uint_as_float(v.y * mul), a3 = __uint_as_float(v.y & msk);
                        const float a4 = __uint_as_float(v.z * mul), a5 = __uint_as_float(v.z & msk), a6 = __uint_as_float(v.w * mul), a7 = __uint_as_float(v.w & msk);
                        s += ((a0 + a1) + (a2 + a3)) + ((a4 + a5) + (a6 + a7));
                        q += fmaf(a0, a0, fmaf(a1, a1, fmaf(a2, a2, a3 * a3))) + fmaf(a4, a4, fmaf(a5, a5, fmaf(a6, a6, a7 * a7)));
                    };
                    accum(v0, s, q); accum(v1, s, q); accum(v2, s, q); accum(v3, s, q);
                    if (k == 2) { accum(v4, s2, q2); accum(v5, s2, q2); }
                }
#pragma unroll
                for (int o = 1; o < 8; o <<= 1) {
                    if (o < 4) { s += __shfl_xor_sync(~0u, s, o); q += __shfl_xor_sync(~0u, q, o); }
                    if (k == 2) { s2 += __shfl_xor_sync(~0u, s2, o); q2 += __shfl_xor_sync(~0u, q2, o); }
                }
                const bool second = (ut & 7) == 1;
                if (second) { s = s2; q = q2; }
                const float mean = s * (1.f / 256.f);
                const int row = second ? 32 + (ut >> 3) : ut >> 2;
                const float alpha = k == 1 ? 1.f : ((k == 2 && (uint32_t)(pt * 32 - 8 + row) >= T_) ? 0.f : 0.5f);
                const float rstd = alpha * rsqrtf(fmaxf(fmaf(-mean, mean, q * (1.f / 256.f)), 0.f) + 1e-5f);
                if ((ut & 3) == 0 || second) sts64f(sb + OFF_STATS + row * 8, mean * rstd, rstd);
                __syncwarp();
                if (lane == 0) mbar_arrive(bars + B_ST * 8);
                TS(2 + k);
                if (k == 1 && warp == 12) {
                    const uint32_t epoch = ld_epoch();
                    bar_sync(11, 288);
                    if (lane < 2) flag_set(&g_flag_v[((b * 4 + 2 * r + lane) * 32 + pt) * FS], epoch);
                    __syncwarp();
                    TS(13);
                }
            }
        } else if (warp < 10) {
            const int w = warp - 8;
            const uint32_t ring = sb + OFF_RING + w * NSLOT * SLOT;
            const uint32_t full = bars + (B_FULL + w * NSLOT) * 8;
            if (lane == 0) {
#pragma unroll
                for (int i = 0; i < NSLOT; i++) mbar_init(full + i * 8, 1);
                asm volatile("fence.mbarrier_init.release.cluster;" ::: "memory");
                fence_async_smem();
            }
            __syncwarp();
            cluster_arrive();
            TS(1);
#pragma unroll
            for (int n = 0; n < NSLOT; n++)
                ring_load(ring + n * SLOT, &p.tm[1], 64 * (8 * r + (n & 6) + w), 128 * ((n & 1) ^ r), full + n * 8);
            TS(2);
            const uint32_t code = load_code(lane, r, w) | (load_code(lane + 32, r, w) << 16);
            cluster_wait();
            uint32_t s = 0, ph = 0;
            int n = NSLOT;
#pragma unroll 1
            for (int seg = 0; seg < 2; seg++) {
#pragma unroll 1
                for (; n < (seg == 0 ? 22 : NLOADS); n++) {
                    const uint32_t c = __shfl_sync(~0u, code, n) >> (n & 32 ? 16 : 0);
                    mbar_wait(full + (B_EMPTY - B_FULL) * 8 + s * 8, ph);
                    ring_load(ring + s * SLOT, &p.tm[c & 15], (c & 0xf0) * 4, (c & 0xff00) >> 1, full + s * 8);
                    if (++s == NSLOT) { s = 0; ph ^= 1; }
                }
                if (seg == 1) break;
                const uint32_t epoch = ld_epoch();
                const uint32_t rdy = bars + (B_RDY + 3 * w) * 8, prdy = mapa(rdy, r ^ 1);
#pragma unroll 1
                for (; n < 32; n++) {
                    mbar_wait(full + (B_EMPTY - B_FULL) * 8 + s * 8, ph);
                    if (lane == 0) {
                        if (n < 24) mbar_arrive(full + s * 8);
                        else mbar_arrive_tx(full + s * 8, SLOT);
                    }
                    if (n == 28) {
                        if (lane == 0) mbar_arrive_peer(prdy);
                        mbar_wait(rdy, 0);
                        flag_wait((r ? g_flag_v : g_flag_qk) + (abh * 32 + lane) * FS, epoch);
                        __syncwarp();
                        fence_async_global();
                        TS(5 + r);
#pragma unroll
                        for (int i = 0; i < 3; i++) {
                            const uint32_t sl = r ? 2 * i + 1 : (i ? 2 * i - 2 : 4);
                            if (i < 2 || r == 0) ring_load_both(ring + sl * SLOT, &p.tm[9], (r * 128 + abh * 8 + 2 * i + w) * 128, full + sl * 8);
                        }
                    } else if (n > 28) {
                        const uint32_t bo = n == 31 ? 16 : 8;
                        if ((n > 29) == (r == 1)) {
                            mbar_wait(rdy + bo, 0);
                            ring_load_both(ring + s * SLOT, &p.tm[9], (r * 128 + abh * 8 + (n == 30 ? 4 : 6) + w) * 128, full + s * 8);
                        } else if (lane == 0) mbar_arrive_peer(prdy + bo);
                    }
                    __syncwarp();
                    if (++s == NSLOT) { s = 0; ph ^= 1; }
                }
            }
        } else if (warp == 10) {
            if (lane == 0) {
                mbar_init(bars + B_XR * 8, 1);
                asm volatile("fence.mbarrier_init.release.cluster;" ::: "memory");
                fence_async_smem();
            }
            __syncwarp();
            cluster_arrive();
            if (lane == 0) {
                mbar_arrive_tx(bars + B_XR * 8, 16384);
#pragma unroll
                for (int i = 0; i < 4; i++) tma3d(P + i * XCH, &p.tm[0], i * 64, pt * 32, b, bars + B_XR * 8);
            }
            __syncwarp();
            cluster_wait();
            const uint32_t epoch = ld_epoch();
            if (lane == 0) {
                mbar_arrive_tx(bars + B_QIN * 8, 8192);
                mbar_arrive_tx(bars + B_OIN * 8, 2 * XCH);
                mbar_arrive_tx(bars + B_OIN * 8 + 8, 2 * XCH);
            }
            if (lane < 2) flag_wait(&g_flag_qk[(abh * 32 + 2 * qt + lane) * FS], epoch);
            __syncwarp();
            if (lane == 0) {
                fence_async_global();
                bulk_g2s(H + 24576, g_kqv + 1048576 + (size_t)(abh * 1024 + qt * 64) * 128, 8192, bars + B_QIN * 8);
            }
            if (lane < 2) {
                const int np = pt - 1 + 2 * lane;
                if (np >= 0 && np < 32) flag_wait(&g_flag_qk[((b * 4 + 2 * r) * 32 + np) * FS], epoch);
            }
            __syncwarp();
            if (lane == 0) mbar_arrive(bars + B_X1IN * 8);
            bar_sync(9, 64);
            if (lane < 8) {
                const int q = (pt >> 1) + (lane < 4 ? 0 : ((pt & 1) ? 1 : -1));
                if (q >= 0 && q < 16) flag_wait(&g_flag_o[((b * 16 + q) * 4 + (lane & 3)) * FS], epoch);
            }
            __syncwarp();
            TSW(10);
            if (lane == 0) {
                fence_async_global();
#pragma unroll
                for (int i = 0; i < 4; i++)
                    bulk_g2s(H + i * XCH, g_o + (size_t)((b * 4 + i) * PADROWS + pt * 32) * 128, XCH, bars + (B_OIN + (i >> 1)) * 8);
            }
            __syncwarp();
        } else {
            uint32_t kb = (lane < 2 || lane > 5) ? 4096 : (lane == 2 ? 3072 : (lane == 4 ? 2048 : 1024));
            size_t off = (size_t)blockIdx.x * kb;
            if (lane == 8) { kb = 8192; off = (size_t)min(b * T_ + pt * 32 + r * 16, 2 * T_ - 16) * 512; }
            const char* pf = p.w[min(lane, 8)] + off;
            if (lane == 0 || lane == 8) prefetch_l2(pf, kb);
            __syncwarp();
            cluster_arrive();
            cluster_wait();
            xwait(0);
            if (lane == 1 || lane == 2) prefetch_l2(pf, kb);
            mbar_wait(bars + B_HF * 8, 0);
            if (lane > 2 && lane < 8) prefetch_l2(pf, kb);
            const uint32_t epoch = ld_epoch();
            bar_sync(4, 288);
            if (lane < 2) flag_set(&g_flag_qk[((b * 4 + 2 * r + lane) * 32 + pt) * FS], epoch);
            __syncwarp();
            TSW(8);
            bar_sync(6, 288);
            bar_arrive(9, 64);
            if (lane == 0) {
                flag_set(&g_flag_o[((b * 16 + qt) * 4 + ah) * FS], epoch);
                g_epoch[blockIdx.x * FS] = epoch;
            }
            __syncwarp();
            TSW(9);
        }
        TSDUMP();
        return;
    }

    if (lane == 0) {
        mbar_init(bars + (B_EMPTY + warp) * 8, 4);
        mbar_init(bars + (B_HF + warp) * 8, warp < 4 ? 8 : 1);
        if (warp < 3) mbar_init(bars + (warp == 2 ? B_ST : B_EMPTY + 8 + warp) * 8, 4);
        else if (warp < 6) mbar_init(bars + (B_XR - 2 + warp) * 8, 1);
        if (warp < 6) mbar_init(bars + (B_RDY + warp) * 8, 1);
        asm volatile("fence.mbarrier_init.release.cluster;" ::: "memory");
    }
    sts128(P + (tid >> 6) * XCH + 4096 + (tid & 63) * 16, 0x3F803F80u, 0x3F803F80u, 0x3F803F80u, 0x3F803F80u);
    fence_async_smem();
    __syncwarp();
    cluster_arrive();
    asm volatile("setmaxnreg.inc.sync.aligned.u32 208;");
    const int w = warp >> 2, wq = warp & 3;
    const int tile = 2 * r + w;
    const int wt = tid & 127;
    const int c4 = lane & 3;
    const uint32_t rbase = sb + OFF_RING + w * NSLOT * SLOT, fbar = bars + (B_FULL + w * NSLOT) * 8;
    const uint32_t rdesc = desc_lo(rbase);
    auto acq = [&](int n) { mbar_wait(fbar + (n % NSLOT) * 8, (n / NSLOT) & 1); };
    auto rel = [&](int n) { if (lane == 0) mbar_arrive(fbar + (B_EMPTY - B_FULL + n % NSLOT) * 8); };
    const uint32_t pown = desc_lo(P + 2 * r * XCH), prem = desc_lo(P + 2 * (r ^ 1) * XCH), hdesc = desc_lo(H);
    const uint32_t toff = ((lane >> 4) * 8 + (lane & 7)) * 128 + (((2 * wq + ((lane >> 3) & 1)) ^ (lane & 7)) << 4);
    const uint32_t xa = P + tile * XCH + toff;
    auto publish = [&](int j, uint32_t src, uint32_t bytes, int nsync) {
        const uint32_t bar = bars + (B_XR + (j & 1)) * 8;
        fence_async_smem();
        bar_sync(2 + w, 128);
        if (wq == 0) peer_copy(mapa(src, r ^ 1), src, bytes, mapa(bar, r ^ 1));
        if (tid == 32) mbar_arrive_tx(bar, 2 * bytes);
        bar_sync(nsync == 384 ? 1 : 10, nsync);
    };
    auto gate = [&](int j) { xwait(j); bar_sync(5, 384); };
    auto load_stats = [&](auto& st, int parity) {
        mbar_wait(bars + B_ST * 8, parity);
#pragma unroll
        for (int j = 0; j < (int)(sizeof(st) / 16); j++) {
            const float4 v = lds128f(sb + OFF_STATS + (8 * j + 2 * c4) * 8);
            st[4 * j] = v.x; st[4 * j + 1] = v.y; st[4 * j + 2] = v.z; st[4 * j + 3] = v.w;
        }
    };
    bar_sync(10, 256);
    cluster_wait();
    uint32_t xr[8];
    xwait(0);
    ldsm4t(xa, xr[0], xr[1], xr[2], xr[3]);
    ldsm4t(xa + 2048, xr[4], xr[5], xr[6], xr[7]);
    acq(0); acq(1);

#pragma unroll 1
    for (int ffi = 0; ffi < 2; ffi++) {
        auto mm = [&](auto& d, int n, uint32_t bd, auto cs, int acc) {
            const uint32_t z = p.zero * (ffi + n + 1);
            issue_half<decltype(cs)::value>(d, rdesc + z + (n % NSLOT) * (SLOT >> 4), bd + z, acc);
        };
        constexpr std::integral_constant<uint32_t, XCH> cx{};
        constexpr std::integral_constant<uint32_t, HCH> ch{};
        {
            float st[16], a0[20], a1[20], rem[16], own[16];
            const uint32_t inb = bars + (B_INB + w) * 8, box = sb + OFF_INBOX + w * 4096 + wt * 16;
            const uint32_t hdst = H + w * HCH + toff;
            auto step = [&](auto& d, int n, uint32_t bd, auto cs, int acc) {
                mm(d, n, bd, cs, acc);
                wg_wait<1>();
                if (n > 0) rel(n - 1);
            };
            auto epi = [&](float (&d)[20], int i, int half) {
                uint32_t pk[4];
#pragma unroll
                for (int k = 4 * half; k < 4 * half + 4; k++) {
                    const float cs = d[16 + 2 * (k & 1)];
                    const float v0 = fmaf(-st[(k >> 1) * 4], cs, d[2 * k] * st[(k >> 1) * 4 + 1]);
                    const float v1 = fmaf(-st[(k >> 1) * 4 + 2], cs, d[2 * k + 1] * st[(k >> 1) * 4 + 3]);
                    pk[k & 3] = pack2(fmaf(v0, tanh_fast(v0), v0), fmaf(v1, tanh_fast(v1), v1));
                }
                stsm4t(hdst + 2 * i * HCH + half * 2048, pk[0], pk[1], pk[2], pk[3]);
            };
            auto hdone = [&](int i) {
                fence_async_smem();
                __syncwarp();
                if (lane == 0) mbar_arrive(bars + (B_HF + i) * 8);
            };
            auto hwait = [&](int i) { mbar_wait(bars + (B_HF + i) * 8, ffi); };
            TS(1 + ffi * 20);
            step(a0, 0, pown, cx, 0);
            if (wt == 0) mbar_arrive_tx(inb, 4096);
            acq(2);
            gate(ffi * 4);
            TS(32);
            step(a0, 1, prem, cx, 1);
            step(a1, 2, pown, cx, 0); acq(3); pin(a0); load_stats(st, ffi); TS(33); epi(a0, 0, 0);
            step(a1, 3, prem, cx, 1); acq(4); epi(a0, 0, 1); TS(34);
            step(a0, 4, pown, cx, 0); acq(5); pin(a1); epi(a1, 1, 0);
            step(a0, 5, prem, cx, 1); acq(6); epi(a1, 1, 1); TS(35);
            step(a1, 6, pown, cx, 0); acq(7); pin(a0); hdone(0); epi(a0, 2, 0);
            step(a1, 7, prem, cx, 1); acq(8); hwait(0); epi(a0, 2, 1); TS(36);
            step(rem, 8, hdesc, ch, 0); acq(9); pin(a1); hdone(1); epi(a1, 3, 0);
            step(rem, 9, hdesc + 2 * (HCH >> 4), ch, 1); acq(10); hwait(1); epi(a1, 3, 1);
            TS(2 + ffi * 20);
            step(rem, 10, hdesc + 4 * (HCH >> 4), ch, 1); acq(11); hdone(2);
            step(own, 11, hdesc, ch, 0); acq(12); hwait(2);
            step(rem, 12, hdesc + 6 * (HCH >> 4), ch, 1); acq(13);
            step(own, 13, hdesc + 2 * (HCH >> 4), ch, 1); acq(14);
            pin(rem);
            {
                const uint32_t dst = mapa(box, r ^ 1), bar = mapa(inb, r ^ 1);
                st_async4(dst, pack2(rem[0], rem[1]), pack2(rem[2], rem[3]), pack2(rem[4], rem[5]), pack2(rem[6], rem[7]), bar);
                st_async4(dst + 2048, pack2(rem[8], rem[9]), pack2(rem[10], rem[11]), pack2(rem[12], rem[13]), pack2(rem[14], rem[15]), bar);
            }
            step(own, 14, hdesc + 4 * (HCH >> 4), ch, 1); acq(15);
            step(own, 15, hdesc + 6 * (HCH >> 4), ch, 1);
            mbar_wait(inb, ffi);
            const uint4 u = lds128(box), v = lds128(box + 2048);
            const uint32_t pr[8] = {u.x, u.y, u.z, u.w, v.x, v.y, v.z, v.w};
            if (ffi == 0) { acq(16); acq(17); }
            wg_wait<0>();
            pin(own);
            TS(3 + ffi * 20);
#pragma unroll
            for (int i = 0; i < 8; i++)
                xr[i] = pack2(fmaf(0.5f, own[2 * i] + blo(pr[i]), blo(xr[i])), fmaf(0.5f, own[2 * i + 1] + bhi(pr[i]), bhi(xr[i])));
            stsm4t(xa, xr[0], xr[1], xr[2], xr[3]);
            stsm4t(xa + 2048, xr[4], xr[5], xr[6], xr[7]);
            rel(15);
            publish(ffi ? 5 : 1, P + tile * XCH + (ffi ? (r ^ 1) * 2048 : 0), ffi ? 2048 : 4096, ffi ? 256 : 384);
        }
        if (ffi == 1) break;

        {
            float ak[20], aq[20], st[16];
            g_halo[((pair * 4 + tile) * 2 + 0) * 128 + wt] = make_uint2(xr[0], xr[1]);
            g_halo[((pair * 4 + tile) * 2 + 1) * 128 + wt] = make_uint2(xr[6], xr[7]);
            bar_sync(5, 384);
            TS(11);
            mm(ak, 16, pown, cx, 0);
            mm(aq, 17, pown, cx, 0);
            acq(18); acq(19);
            gate(1);
            mm(ak, 18, prem, cx, 1);
            mm(aq, 19, prem, cx, 1);
            wg_wait<2>();
            rel(16); rel(17);
            load_stats(st, 1);
            auto stage_out = [&](float (&d)[20], uint32_t dst) {
                uint32_t pk[8];
#pragma unroll
                for (int k = 0; k < 8; k++) {
                    const float cs = d[16 + 2 * (k & 1)];
                    pk[k] = pack2(fmaf(-st[(k >> 1) * 4], cs, d[2 * k] * st[(k >> 1) * 4 + 1]),
                                  fmaf(-st[(k >> 1) * 4 + 2], cs, d[2 * k + 1] * st[(k >> 1) * 4 + 3]));
                }
                stsm4t(dst + toff, pk[0], pk[1], pk[2], pk[3]);
                stsm4t(dst + toff + 2048, pk[4], pk[5], pk[6], pk[7]);
            };
            const uint32_t stg = H + w * 12288;
            unsigned char* g = g_kqv + (size_t)((b * 4 + tile) * 1024 + pt * 32) * 128 + wt * 16;
            wg_wait<0>();
            pin(ak); pin(aq);
            TS(37);
            stage_out(ak, stg);
            stage_out(aq, stg + 4096);
            bar_sync(2 + w, 128);
            {
                const uint4 k0 = lds128(stg + wt * 16), k1 = lds128(stg + 2048 + wt * 16), q0 = lds128(stg + 4096 + wt * 16), q1 = lds128(stg + 6144 + wt * 16);
                stg128(g, k0); stg128(g + 2048, k1);
                stg128(g + 1048576, q0); stg128(g + 1048576 + 2048, q1);
            }
            bar_arrive(4, 288);
            TS(38);
            rel(18); rel(19);
            acq(20); acq(21);
            bar_sync(10, 256);
            mm(ak, 20, pown, cx, 0);
            mm(ak, 21, prem, cx, 1);
            wg_wait<0>();
            pin(ak);
            stage_out(ak, stg + 8192);
            rel(20); rel(21);
            bar_sync(2 + w, 128);
            {
                const uint4 v0 = lds128(stg + 8192 + wt * 16), v1 = lds128(stg + 10240 + wt * 16);
                stg128(g + 2097152, v0); stg128(g + 2097152 + 2048, v1);
            }
            bar_arrive(11, 288);
            acq(22); acq(23);
            rel(22); rel(23);
            TS(12);
        }

        {
            constexpr float CS = 0.125f * 1.4426950408889634f;
            float sa[32], sb2[32], o[36];
            uint32_t pa[16], pb[16], q[16];
            float n0 = INFINITY, n1 = INFINITY;
            zero(o); zero(pa); zero(pb);
            const uint32_t ones = sb + OFF_INBOX + 2048;
            if (tid < 128) sts128(ones + tid * 16, 0x3F803F80u, 0x3F803F80u, 0x3F803F80u, 0x3F803F80u);
            fence_async_smem();
            bar_sync(10, 256);
            const uint32_t vdesc = rdesc + ((((ones - rbase) >> 4) - 1) << 16);
            auto qk_issue = [&](float (&s)[32], uint32_t lo) {
                const uint64_t kd = mkdesc(lo);
                wg_fence();
#pragma unroll
                for (int k = 0; k < 4; k++) mma_qk(s, q[4 * k], q[4 * k + 1], q[4 * k + 2], q[4 * k + 3], kd + 2 * k, k != 0);
                wg_commit();
            };
            auto pv_issue = [&](uint32_t (&pp)[16], uint32_t lo) {
                const uint64_t vd = mkdesc(lo);
                wg_fence();
#pragma unroll
                for (int k = 0; k < 4; k++) mma_pv(o, pp[4 * k], pp[4 * k + 1], pp[4 * k + 2], pp[4 * k + 3], vd - k * (128 * 65535));
                wg_commit();
            };
            auto new_max = [&](float (&s)[32], float& x0, float& x1) {
                x0 = s[0]; x1 = s[2];
#pragma unroll
                for (int j = 0; j < 8; j++) {
                    x0 = fmaxf(x0, fmaxf(s[4 * j], s[4 * j + 1]));
                    x1 = fmaxf(x1, fmaxf(s[4 * j + 2], s[4 * j + 3]));
                }
                x0 = fmaxf(x0, __shfl_xor_sync(~0u, x0, 1)); x1 = fmaxf(x1, __shfl_xor_sync(~0u, x1, 1));
                x0 = fmaxf(x0, __shfl_xor_sync(~0u, x0, 2)); x1 = fmaxf(x1, __shfl_xor_sync(~0u, x1, 2));
                x0 = fminf(n0, fmaf(x0, -CS, -20.f)); x1 = fminf(n1, fmaf(x1, -CS, -20.f));
            };
            auto probs = [&](float (&s)[32], uint32_t (&pp)[16], bool ready, auto wait) {
                uint32_t any = 0;
#pragma unroll
                for (int i = 0; i < 16; i++) {
                    pp[i] = pack2(ex2(fmaf(s[2 * i], CS, (i & 1) ? n1 : n0)), ex2(fmaf(s[2 * i + 1], CS, (i & 1) ? n1 : n0)));
                    any |= pp[i];
                }
                float sc0 = 1.f, sc1 = 1.f;
                const bool slow = __any_sync(~0u, (any & 0x40004000u) || !ready);
                if (slow) {
                    wait();
                    if (__any_sync(~0u, any & 0x40004000u)) {
                        float x0, x1;
                        new_max(s, x0, x1);
                        sc0 = ex2(x0 - n0); sc1 = ex2(x1 - n1);
                        n0 = x0; n1 = x1;
#pragma unroll
                        for (int i = 0; i < 16; i++)
                            pp[i] = pack2(ex2(fmaf(s[2 * i], CS, (i & 1) ? n1 : n0)), ex2(fmaf(s[2 * i + 1], CS, (i & 1) ? n1 : n0)));
                    }
                }
                wg_wait<0>();
                pin(sa); pin(sb2); pin(o); pin(pa); pin(pb);
                if (slow) {
#pragma unroll
                    for (int j = 0; j < 9; j++) { o[4 * j] *= sc0; o[4 * j + 1] *= sc0; o[4 * j + 2] *= sc1; o[4 * j + 3] *= sc1; }
                }
            };
            mbar_wait(bars + B_QIN * 8, 0);
            {
                const uint32_t qa = H + 24576 + (wq * 16 + (lane & 15)) * 128;
#pragma unroll
                for (int k = 0; k < 4; k++) ldsm4(qa + (((2 * k + (lane >> 4)) ^ (lane & 7)) << 4), q[4 * k], q[4 * k + 1], q[4 * k + 2], q[4 * k + 3]);
                pin(q);
            }
            acq(24);
            TS(13);
            qk_issue(sa, rdesc + (24 % NSLOT) * (SLOT >> 4));
            qk_issue(sb2, rdesc + (24 % NSLOT) * (SLOT >> 4) + 512);
            wg_wait<1>();
            pin(sa);
            {
                float x0, x1;
                new_max(sa, x0, x1);
                n0 = x0; n1 = x1;
            }
            if (w == 1) bar_sync(7, 256);
            uint32_t vd = vdesc - (SLOT >> 4) * 65535u, kd = rdesc, vb = fbar + 8, kb = fbar;
            uint32_t kprev = fbar + 32, vprev = bars + (B_HF + 3 - (B_EMPTY - B_FULL)) * 8;
#pragma unroll 1
            for (int it = 0; it < 4; it++) {
                TS(40 + it * 4);
                probs(sa, pa, mbar_test(vb, it < 2) && mbar_test(kb, it < 3), [&]() { mbar_wait(vb, it < 2); mbar_wait(kb, it < 3); });
                TS(41 + it * 4);
                if (it == 0 && w == 0) bar_arrive(7, 256);
                if (it == 3 && w == 1) {
#pragma unroll
                    for (int i = 20; i < 32; i++) sb2[i] = -INFINITY;
                }
                pin(sb2);
                pv_issue(pa, vd);
                if (it < 3) qk_issue(sa, kd);
                if (lane == 0) mbar_arrive(kprev + (B_EMPTY - B_FULL) * 8);
                if (lane == 0) mbar_arrive(vprev + (B_EMPTY - B_FULL) * 8);
                TS(42 + it * 4);
                probs(sb2, pb, true, []() {});
                TS(43 + it * 4);
                pv_issue(pb, vd - 512 * 65535u);
                if (it < 3) qk_issue(sb2, kd + 512);
                const int dv = it == 0 ? 2 : (it == 1 ? -3 : 1);
                kprev = kb; vprev = vb;
                vd -= dv * (SLOT >> 4) * 65535u; vb += dv * 8;
                kd += 2 * (SLOT >> 4); kb = it == 2 ? vb : kb + 16;
            }
            const int row = wq * 16 + (lane >> 2);
            const uint32_t ml = sb + OFF_INBOX;
            wg_wait<0>();
            pin(o); pin(pb); pin(sa); pin(sb2);
            rel(31);
            const float l0 = o[32], l1 = o[34];
            if (c4 == 0) { sts64f(ml + w * 512 + row * 8, n0, l0); sts64f(ml + w * 512 + row * 8 + 64, n1, l1); }
            TS(14);
            float mine[16];
#pragma unroll
            for (int j = 0; j < 4; j++) {
                if (w == 0) sts128f(H + j * 2048 + wt * 16, o[16 + 4 * j], o[17 + 4 * j], o[18 + 4 * j], o[19 + 4 * j]);
                else sts128f(H + 8192 + j * 2048 + wt * 16, o[4 * j], o[4 * j + 1], o[4 * j + 2], o[4 * j + 3]);
            }
#pragma unroll
            for (int i = 0; i < 16; i++) mine[i] = w == 0 ? o[i] : o[16 + i];
            bar_sync(10, 256);
            const float2 u0 = lds64f(ml + (w ^ 1) * 512 + row * 8), u1 = lds64f(ml + (w ^ 1) * 512 + row * 8 + 64);
            const float x0 = fminf(n0, u0.x), x1 = fminf(n1, u1.x);
            float a0 = ex2(x0 - n0), b0 = ex2(x0 - u0.x), a1 = ex2(x1 - n1), b1 = ex2(x1 - u1.x);
            const float i0 = __fdividef(1.f, fmaf(a0, l0, b0 * u0.y)), i1 = __fdividef(1.f, fmaf(a1, l1, b1 * u1.y));
            a0 *= i0; b0 *= i0; a1 *= i1; b1 *= i1;
            uint32_t pk[8];
#pragma unroll
            for (int j = 0; j < 4; j++) {
                const float4 v = lds128f(H + (w ^ 1) * 8192 + j * 2048 + wt * 16);
                pk[2 * j] = pack2(fmaf(a0, mine[4 * j], b0 * v.x), fmaf(a0, mine[4 * j + 1], b0 * v.y));
                pk[2 * j + 1] = pack2(fmaf(a1, mine[4 * j + 2], b1 * v.z), fmaf(a1, mine[4 * j + 3], b1 * v.w));
            }
            const uint32_t og = H + 16384 + wq * 2048;
            {
                const uint32_t ra = og + (((lane >> 3) & 1) * 8 + (lane & 7)) * 128;
                stsm4(ra + (((4 * w + (lane >> 4)) ^ (lane & 7)) << 4), pk[0], pk[1], pk[2], pk[3]);
                stsm4(ra + (((4 * w + 2 + (lane >> 4)) ^ (lane & 7)) << 4), pk[4], pk[5], pk[6], pk[7]);
            }
            __syncwarp();
            {
                const uint32_t off = (lane >> 2) * 128 + (((4 * w + c4) ^ (lane >> 2)) << 4);
                const uint4 v0 = lds128(og + off), v1 = lds128(og + off + 1024);
                unsigned char* dst = g_o + (size_t)(abh * PADROWS + 8 + qt * 64 + wq * 16) * 128 + off;
                stg128(dst, v0); stg128(dst + 1024, v1);
            }
            bar_arrive(6, 288);
            TS(15);
        }

        uint32_t dwr[15];
        {
#pragma unroll
            for (int i = 0; i < 15; i++) dwr[i] = hmul2(__ldg(reinterpret_cast<const uint32_t*>(p.dw + i * 256 + tile * 64) + lane), 0x3F003F00u);
            float d[24];
            uint32_t xw[12];
            mbar_wait(bars + B_X1IN * 8, 0);
            uint2 hl = make_uint2(0, 0), hr = hl;
            if (pt > 0) hl = __ldcg(&g_halo[(((pair - 1) * 4 + tile) * 2 + 1) * 128 + wt]);
            if (pt < 31) hr = __ldcg(&g_halo[(((pair + 1) * 4 + tile) * 2 + 0) * 128 + wt]);
            xw[0] = hl.x; xw[1] = hl.y; xw[10] = hr.x; xw[11] = hr.y;
#pragma unroll
            for (int i = 0; i < 8; i++) xw[2 + i] = xr[i];
            pin(xw);
            pin(dwr);
            acq(32); acq(33); acq(34); acq(35);
            mbar_wait(bars + B_OIN * 8, 0);
            TS(16);
            mm(d, 32, hdesc, cx, 0);
            mbar_wait(bars + B_OIN * 8 + 8, 0);
            mm(d, 33, hdesc + 2 * (XCH >> 4), cx, 1);
            wg_wait<1>();
            rel(32);
            wg_wait<0>();
            pin(d);
#pragma unroll
            for (int i = 0; i < 12; i++) xw[i] = pack2(d[2 * i] + blo(xw[i]), d[2 * i + 1] + bhi(xw[i]));
            if (c4 == 0) { xw[0] = (xw[0] & 0xffff0000u) | 0x3F80u; xw[1] = (xw[1] & 0xffff0000u) | 0x3F80u; }
#pragma unroll
            for (int j = 0; j < 3; j++) stsm4t(xa + j * 2048, xw[4 * j], xw[4 * j + 1], xw[4 * j + 2], xw[4 * j + 3]);
#pragma unroll
            for (int i = 0; i < 8; i++) xr[i] = xw[2 + i];
            rel(33);
            publish(2, P + tile * XCH, XCH, 384);
            TS(17);
        }
        {
            float da[24], db[24], st[24];
            bar_sync(5, 384);
            mm(da, 34, pown, cx, 0);
            mm(db, 35, pown, cx, 0);
            acq(36); acq(37);
            gate(2);
            TS(39);
            mm(da, 36, prem, cx, 1);
            mm(db, 37, prem, cx, 1);
            wg_wait<2>();
            rel(34); rel(35);
            load_stats(st, 0);
            wg_wait<0>();
            pin(da); pin(db);
            rel(36); rel(37);
            TS(18);
            uint32_t pk[12];
#pragma unroll
            for (int hh = 0; hh < 2; hh++) {
                const float ca = __shfl_sync(~0u, da[2 * hh], lane & 28), cb = __shfl_sync(~0u, db[2 * hh], lane & 28);
#pragma unroll
                for (int j = 0; j < 6; j++) {
                    const float u0 = fmaf(-st[4 * j], ca, da[4 * j + 2 * hh] * st[4 * j + 1]);
                    const float u1 = fmaf(-st[4 * j + 2], ca, da[4 * j + 2 * hh + 1] * st[4 * j + 3]);
                    const float v0 = fmaf(-st[4 * j], cb, db[4 * j + 2 * hh] * st[4 * j + 1]);
                    const float v1 = fmaf(-st[4 * j + 2], cb, db[4 * j + 2 * hh + 1] * st[4 * j + 3]);
                    pk[2 * j + hh] = pack2(fmaf(u0, tanh_fast(v0), u0), fmaf(u1, tanh_fast(v1), u1));
                }
            }
            const uint32_t gs = H + 16384 + w * XCH;
#pragma unroll
            for (int j = 0; j < 3; j++) stsm4t(gs + toff + j * 2048, pk[4 * j], pk[4 * j + 1], pk[4 * j + 2], pk[4 * j + 3]);
            bar_sync(2 + w, 128);
            uint32_t ca[8], cb[8];
            const uint32_t grow = gs + 8 * wq * 128 + c4 * 4, srow = H + tile * HCH + 8 * wq * 128 + c4 * 4;
#pragma unroll
            for (int k = 0; k < 22; k++) {
                const uint32_t v = lds32(grow + (1 + k) * 128 + (((lane >> 2) ^ ((1 + k) & 7)) << 4));
#pragma unroll
                for (int i = 0; i < 8; i++) {
                    const int tap = k - i;
                    if (tap == 0) ca[i] = hmul2(v, dwr[0]);
                    else if (tap > 0 && tap < 8) ca[i] = hfma2(v, dwr[tap], ca[i]);
                    else if (tap == 8) cb[i] = hmul2(v, dwr[8]);
                    else if (tap > 8 && tap < 15) cb[i] = hfma2(v, dwr[tap], cb[i]);
                }
            }
#pragma unroll
            for (int i = 0; i < 8; i++) {
                const float h0 = blo(ca[i]) + blo(cb[i]), h1 = bhi(ca[i]) + bhi(cb[i]);
                sts32(srow + i * 128 + (((lane >> 2) ^ i) << 4), pack2(fmaf(h0, tanh_fast(h0), h0), fmaf(h1, tanh_fast(h1), h1)));
            }
            acq(38); acq(39);
            publish(3, H + tile * HCH, HCH, 256);
            TS(19);
        }
        {
            float d[16];
            mm(d, 38, hdesc + 2 * r * (HCH >> 4), ch, 0);
            acq(40); acq(41);
            xwait(3);
            sts128(P + (wt >> 6 ? (tile ^ 2) : tile) * XCH + 4096 + (wt & 63) * 16, 0x3F803F80u, 0x3F803F80u, 0x3F803F80u, 0x3F803F80u);
            mm(d, 39, hdesc + 2 * (r ^ 1) * (HCH >> 4), ch, 1);
            wg_wait<1>();
            rel(38);
            wg_wait<0>();
            pin(d);
#pragma unroll
            for (int i = 0; i < 8; i++) xr[i] = pack2(d[2 * i] + blo(xr[i]), d[2 * i + 1] + bhi(xr[i]));
            stsm4t(xa, xr[0], xr[1], xr[2], xr[3]);
            stsm4t(xa + 2048, xr[4], xr[5], xr[6], xr[7]);
            rel(39);
            publish(4, P + tile * XCH, HCH, 384);
            TS(20);
        }
    }

    xwait(5);
    cluster_arrive();
    TS(24);
    {
        float a[2][8], s[2], q[2];
        const int row0 = 16 * r + 2 * warp;
#pragma unroll
        for (int i = 0; i < 2; i++) {
            const uint4 v = lds128(P + (lane >> 3) * XCH + (row0 + i) * 128 + (((lane & 7) ^ ((row0 + i) & 7)) << 4));
            a[i][0] = blo(v.x); a[i][1] = bhi(v.x); a[i][2] = blo(v.y); a[i][3] = bhi(v.y);
            a[i][4] = blo(v.z); a[i][5] = bhi(v.z); a[i][6] = blo(v.w); a[i][7] = bhi(v.w);
            s[i] = ((a[i][0] + a[i][1]) + (a[i][2] + a[i][3])) + ((a[i][4] + a[i][5]) + (a[i][6] + a[i][7]));
            q[i] = 0.f;
#pragma unroll
            for (int k = 0; k < 8; k++) q[i] = fmaf(a[i][k], a[i][k], q[i]);
        }
#pragma unroll
        for (int o = 16; o > 0; o >>= 1) {
#pragma unroll
            for (int i = 0; i < 2; i++) { s[i] += __shfl_xor_sync(~0u, s[i], o); q[i] += __shfl_xor_sync(~0u, q[i], o); }
        }
#pragma unroll
        for (int i = 0; i < 2; i++) {
            const float mean = s[i] * (1.f / 256.f);
            const float rstd = rsqrtf(fmaxf(fmaf(-mean, mean, q[i] * (1.f / 256.f)), 0.f) + 1e-5f);
            const float nb = -mean * rstd;
            uint4 v;
            v.x = pack2(fmaf(a[i][0], rstd, nb), fmaf(a[i][1], rstd, nb)); v.y = pack2(fmaf(a[i][2], rstd, nb), fmaf(a[i][3], rstd, nb));
            v.z = pack2(fmaf(a[i][4], rstd, nb), fmaf(a[i][5], rstd, nb)); v.w = pack2(fmaf(a[i][6], rstd, nb), fmaf(a[i][7], rstd, nb));
            const int t = pt * 32 + row0 + i;
            if (t < T_) stg128(p.out + (size_t)(b * T_ + t) * 256 + lane * 8, v);
        }
    }
    TS(25);
    TG(31);
    TSDUMP();
    cluster_wait();
}

typedef CUresult (*EncodeFn)(CUtensorMap*, CUtensorMapDataType, cuuint32_t, void*, const cuuint64_t*, const cuuint64_t*,
                             const cuuint32_t*, const cuuint32_t*, CUtensorMapInterleave, CUtensorMapSwizzle,
                             CUtensorMapL2promotion, CUtensorMapFloatOOBfill);

}

extern "C" void kernel_launch(void* const* d_in, const int* in_sizes, int n_in, void* d_out, int out_size) {
    static EncodeFn encode = nullptr;
    if (!encode) {
        void* fn = nullptr;
        cudaDriverEntryPointQueryResult qr;
        cudaGetDriverEntryPoint("cuTensorMapEncodeTiled", &fn, cudaEnableDefault, &qr);
        encode = (EncodeFn)fn;
        cudaFuncSetAttribute(conformer_kernel, cudaFuncAttributeMaxDynamicSharedMemorySize, SMEM_LAUNCH);
    }
    Params p;
    const cuuint32_t ones[3] = {1, 1, 1};
    {
        const cuuint64_t dims[3] = {256, T_, 2};
        const cuuint64_t strides[2] = {512, 512ull * T_};
        const cuuint32_t box[3] = {64, 32, 1};
        encode(&p.tm[0], CU_TENSOR_MAP_DATA_TYPE_BFLOAT16, 3, d_in[0], dims, strides, box, ones, CU_TENSOR_MAP_INTERLEAVE_NONE,
               CU_TENSOR_MAP_SWIZZLE_128B, CU_TENSOR_MAP_L2_PROMOTION_L2_256B, CU_TENSOR_MAP_FLOAT_OOB_FILL_NONE);
    }
    const int idx[8] = {1, 2, 3, 4, 5, 7, 8, 9};
    const int rows[8] = {256, 1024, 256, 256, 256, 256, 256, 1024};
    const int cols[8] = {1024, 256, 768, 256, 512, 256, 1024, 256};
    for (int i = 0; i < 8; i++) {
        const cuuint64_t dims[2] = {(cuuint64_t)cols[i], (cuuint64_t)rows[i]};
        const cuuint64_t strides[1] = {(cuuint64_t)cols[i] * 2};
        const cuuint32_t box[2] = {64, 128};
        encode(&p.tm[1 + i], CU_TENSOR_MAP_DATA_TYPE_BFLOAT16, 2, d_in[idx[i]], dims, strides, box, ones, CU_TENSOR_MAP_INTERLEAVE_NONE,
               CU_TENSOR_MAP_SWIZZLE_128B, CU_TENSOR_MAP_L2_PROMOTION_L2_128B, CU_TENSOR_MAP_FLOAT_OOB_FILL_NONE);
        p.w[i] = (const char*)d_in[idx[i]];
    }
    {
        void* kv = nullptr;
        cudaGetSymbolAddress(&kv, g_kqv);
        const cuuint64_t dims[2] = {64, 24576};
        const cuuint64_t strides[1] = {128};
        const cuuint32_t box[2] = {64, 128};
        encode(&p.tm[9], CU_TENSOR_MAP_DATA_TYPE_BFLOAT16, 2, kv, dims, strides, box, ones, CU_TENSOR_MAP_INTERLEAVE_NONE,
               CU_TENSOR_MAP_SWIZZLE_NONE, CU_TENSOR_MAP_L2_PROMOTION_L2_128B, CU_TENSOR_MAP_FLOAT_OOB_FILL_NONE);
    }
    p.w[8] = (const char*)d_in[0];
    p.dw = (const __nv_bfloat16*)d_in[6];
    p.out = (__nv_bfloat16*)d_out;
    p.zero = 0;
    conformer_kernel<<<NCTA, NTHREADS, SMEM_LAUNCH>>>(p);
}
```

```cpp
#include <cuda_runtime.h>
#include <cuda_bf16.h>
#include <cuda.h>
#include <stdint.h>
#include <type_traits>

namespace {

constexpr int T_ = 1000;
constexpr int NCTA = 128;
constexpr int NTHREADS = 512;
constexpr int NSLOT = 5;
constexpr int SLOT = 16384;
constexpr int NLOADS = 56;

constexpr uint32_t OFF_RING = 0;
constexpr uint32_t OFF_P = 163840;
constexpr uint32_t OFF_H = 188416;
constexpr uint32_t OFF_INBOX = 221184;
constexpr uint32_t OFF_STATS = 229376;
constexpr uint32_t OFF_BARS = 229888;
constexpr uint32_t SMEM_BYTES = 230400;
constexpr uint32_t XCH = 6144;
constexpr uint32_t HCH = 4096;

constexpr int B_FULL = 0, B_EMPTY = 10, B_XR = 20, B_OIN = 22, B_HF = 24, B_INB = 28, B_QIN = 30, B_X1IN = 31, B_ST = 32, B_RDY = 33;

constexpr int PADROWS = 1040;
constexpr int FS = 8;

struct Params {
    CUtensorMap tm[10];
    const char* w[9];
    const __nv_bfloat16* dw;
    __nv_bfloat16* out;
    uint32_t zero;
};

__device__ __align__(1024) unsigned char g_kvq[3 * 8 * 1024 * 128];
__device__ __align__(1024) unsigned char g_o[8 * PADROWS * 128];
__device__ uint2 g_halo[64 * 4 * 2 * 128];
__device__ uint32_t g_flag_kv[8 * 32 * FS];
__device__ uint32_t g_flag_q[8 * 32 * FS];
__device__ uint32_t g_flag_o[2 * 16 * 4 * FS];
__device__ uint32_t g_epoch[NCTA * FS];

#define TS(i) do { } while (0)
#define TSW(i) do { } while (0)
#define TG(i) do { } while (0)
#define TSINIT() do { } while (0)
#define TSDUMP() do { } while (0)
constexpr uint32_t SMEM_LAUNCH = SMEM_BYTES;

__device__ __forceinline__ uint32_t smem_u32(const void* p) { return (uint32_t)__cvta_generic_to_shared(p); }
__device__ __forceinline__ void mbar_init(uint32_t b, uint32_t c) { asm volatile("mbarrier.init.shared::cta.b64 [%0], %1;" ::"r"(b), "r"(c) : "memory"); }
__device__ __forceinline__ void mbar_arrive(uint32_t b) { asm volatile("mbarrier.arrive.shared::cta.b64 _, [%0];" ::"r"(b) : "memory"); }
__device__ __forceinline__ void mbar_arrive_tx(uint32_t b, uint32_t tx) { asm volatile("mbarrier.arrive.expect_tx.shared::cta.b64 _, [%0], %1;" ::"r"(b), "r"(tx) : "memory"); }
__device__ __forceinline__ void mbar_wait(uint32_t b, uint32_t ph) {
    asm volatile("{\n.reg .pred p, q;\n.reg .u32 c;\nmov.u32 c, 0;\n"
                 "MW_LOOP:\n.pragma \"nounroll\";\n"
                 "mbarrier.try_wait.parity.shared::cta.b64 p, [%0], %1;\n"
                 "add.u32 c, c, 1;\nsetp.lt.u32 q, c, 65536;\nnot.pred p, p;\nand.pred p, p, q;\n@p bra MW_LOOP;\n}"
                 ::"r"(b), "r"(ph) : "memory");
}
__device__ __forceinline__ bool mbar_test(uint32_t b, uint32_t ph) {
    uint32_t ok;
    asm volatile("{\n.reg .pred p;\nmbarrier.test_wait.parity.shared::cta.b64 p, [%1], %2;\nselp.u32 %0, 1, 0, p;\n}" : "=r"(ok) : "r"(b), "r"(ph) : "memory");
    return ok;
}
__device__ __forceinline__ uint32_t mapa(uint32_t a, uint32_t r) { uint32_t o; asm("mapa.shared::cluster.u32 %0, %1, %2;" : "=r"(o) : "r"(a), "r"(r)); return o; }
__device__ __forceinline__ void fence_async_smem() { asm volatile("fence.proxy.async.shared::cta;" ::: "memory"); }
__device__ __forceinline__ void fence_async_global() { asm volatile("fence.proxy.async.global;" ::: "memory"); }
__device__ __forceinline__ void bar_sync(int id, int n) { asm volatile("bar.sync %0, %1;" ::"r"(id), "r"(n) : "memory"); }
__device__ __forceinline__ void bar_arrive(int id, int n) { asm volatile("bar.arrive %0, %1;" ::"r"(id), "r"(n) : "memory"); }
__device__ __forceinline__ void cluster_arrive() { asm volatile("barrier.cluster.arrive.relaxed.aligned;" ::: "memory"); }
__device__ __forceinline__ void cluster_wait() { asm volatile("barrier.cluster.wait.aligned;" ::: "memory"); }

__device__ __forceinline__ void ring_load(uint32_t dst, const CUtensorMap* tm, int c0, int c1, uint32_t bar) {
    asm volatile("{\n.reg .pred p;\nelect.sync _|p, 0xffffffff;\n"
                 "@p mbarrier.arrive.expect_tx.shared::cta.b64 _, [%2], 16384;\n"
                 "@p cp.async.bulk.tensor.2d.shared::cluster.global.mbarrier::complete_tx::bytes [%0], [%1, {%3, %4}], [%2];\n}"
                 ::"r"(dst), "l"(tm), "r"(bar), "r"(c0), "r"(c1) : "memory");
}
__device__ __forceinline__ void ring_load_both(uint32_t dst, const CUtensorMap* tm, int c1, uint32_t bar) {
    asm volatile("{\n.reg .pred p;\nelect.sync _|p, 0xffffffff;\n"
                 "@p cp.async.bulk.tensor.2d.shared::cluster.global.mbarrier::complete_tx::bytes.multicast::cluster [%0], [%1, {0, %3}], [%2], %4;\n}"
                 ::"r"(dst), "l"(tm), "r"(bar), "r"(c1), "h"((uint16_t)3) : "memory");
}
__device__ __forceinline__ void mbar_arrive_peer(uint32_t b) { asm volatile("mbarrier.arrive.relaxed.cluster.shared::cluster.b64 _, [%0];" ::"r"(b) : "memory"); }
__device__ __forceinline__ void tma3d(uint32_t dst, const CUtensorMap* tm, int c0, int c1, int c2, uint32_t bar) {
    asm volatile("cp.async.bulk.tensor.3d.shared::cluster.global.mbarrier::complete_tx::bytes [%0], [%1, {%3, %4, %5}], [%2];"
                 ::"r"(dst), "l"(tm), "r"(bar), "r"(c0), "r"(c1), "r"(c2) : "memory");
}
__device__ __forceinline__ void bulk_g2s(uint32_t dst, const void* src, uint32_t bytes, uint32_t bar) {
    asm volatile("cp.async.bulk.shared::cluster.global.mbarrier::complete_tx::bytes [%0], [%1], %2, [%3];" ::"r"(dst), "l"(src), "r"(bytes), "r"(bar) : "memory");
}
__device__ __forceinline__ void prefetch_l2(const void* src, uint32_t bytes) {
    asm volatile("cp.async.bulk.prefetch.L2.global [%0], %1;" ::"l"(src), "r"(bytes) : "memory");
}
__device__ __forceinline__ void peer_copy(uint32_t dst, uint32_t src, uint32_t bytes, uint32_t rbar) {
    asm volatile("{\n.reg .pred p;\nelect.sync _|p, 0xffffffff;\n"
                 "@p cp.async.bulk.shared::cluster.shared::cta.mbarrier::complete_tx::bytes [%0], [%1], %2, [%3];\n}"
                 ::"r"(dst), "r"(src), "r"(bytes), "r"(rbar) : "memory");
}
__device__ __forceinline__ void st_async4(uint32_t dst, uint32_t a, uint32_t b, uint32_t c, uint32_t d, uint32_t bar) {
    asm volatile("st.async.shared::cluster.mbarrier::complete_tx::bytes.v4.b32 [%0], {%1,%2,%3,%4}, [%5];" ::"r"(dst), "r"(a), "r"(b), "r"(c), "r"(d), "r"(bar) : "memory");
}
__device__ __forceinline__ void stsm4t(uint32_t a, uint32_t r0, uint32_t r1, uint32_t r2, uint32_t r3) {
    asm volatile("stmatrix.sync.aligned.m8n8.x4.trans.shared.b16 [%0], {%1,%2,%3,%4};" ::"r"(a), "r"(r0), "r"(r1), "r"(r2), "r"(r3) : "memory");
}
__device__ __forceinline__ void stsm4(uint32_t a, uint32_t r0, uint32_t r1, uint32_t r2, uint32_t r3) {
    asm volatile("stmatrix.sync.aligned.m8n8.x4.shared.b16 [%0], {%1,%2,%3,%4};" ::"r"(a), "r"(r0), "r"(r1), "r"(r2), "r"(r3) : "memory");
}
__device__ __forceinline__ void ldsm4t(uint32_t a, uint32_t& r0, uint32_t& r1, uint32_t& r2, uint32_t& r3) {
    asm volatile("ldmatrix.sync.aligned.m8n8.x4.trans.shared.b16 {%0,%1,%2,%3}, [%4];" : "=r"(r0), "=r"(r1), "=r"(r2), "=r"(r3) : "r"(a) : "memory");
}
__device__ __forceinline__ void ldsm4(uint32_t a, uint32_t& r0, uint32_t& r1, uint32_t& r2, uint32_t& r3) {
    asm volatile("ldmatrix.sync.aligned.m8n8.x4.shared.b16 {%0,%1,%2,%3}, [%4];" : "=r"(r0), "=r"(r1), "=r"(r2), "=r"(r3) : "r"(a) : "memory");
}
__device__ __forceinline__ uint4 lds128(uint32_t a) { uint4 v; asm volatile("ld.shared.v4.b32 {%0,%1,%2,%3}, [%4];" : "=r"(v.x), "=r"(v.y), "=r"(v.z), "=r"(v.w) : "r"(a) : "memory"); return v; }
__device__ __forceinline__ float4 lds128f(uint32_t a) { float4 v; asm volatile("ld.shared.v4.f32 {%0,%1,%2,%3}, [%4];" : "=f"(v.x), "=f"(v.y), "=f"(v.z), "=f"(v.w) : "r"(a) : "memory"); return v; }
__device__ __forceinline__ float2 lds64f(uint32_t a) { float2 v; asm volatile("ld.shared.v2.f32 {%0,%1}, [%2];" : "=f"(v.x), "=f"(v.y) : "r"(a) : "memory"); return v; }
__device__ __forceinline__ uint32_t lds32(uint32_t a) { uint32_t v; asm volatile("ld.shared.b32 %0, [%1];" : "=r"(v) : "r"(a) : "memory"); return v; }
__device__ __forceinline__ void sts128(uint32_t a, uint32_t x, uint32_t y, uint32_t z, uint32_t w) { asm volatile("st.shared.v4.b32 [%0], {%1,%2,%3,%4};" ::"r"(a), "r"(x), "r"(y), "r"(z), "r"(w) : "memory"); }
__device__ __forceinline__ void sts128f(uint32_t a, float x, float y, float z, float w) { asm volatile("st.shared.v4.f32 [%0], {%1,%2,%3,%4};" ::"r"(a), "f"(x), "f"(y), "f"(z), "f"(w) : "memory"); }
__device__ __forceinline__ void sts64f(uint32_t a, float x, float y) { asm volatile("st.shared.v2.f32 [%0], {%1,%2};" ::"r"(a), "f"(x), "f"(y) : "memory"); }
__device__ __forceinline__ void sts32(uint32_t a, uint32_t x) { asm volatile("st.shared.b32 [%0], %1;" ::"r"(a), "r"(x) : "memory"); }
__device__ __forceinline__ void stg128(void* p, uint4 v) { asm volatile("st.global.v4.b32 [%0], {%1,%2,%3,%4};" ::"l"(p), "r"(v.x), "r"(v.y), "r"(v.z), "r"(v.w) : "memory"); }

__device__ __forceinline__ uint32_t pack2(float lo, float hi) { uint32_t r; asm("cvt.rn.bf16x2.f32 %0, %1, %2;" : "=r"(r) : "f"(hi), "f"(lo)); return r; }
__device__ __forceinline__ float blo(uint32_t v) { return __uint_as_float(v << 16); }
__device__ __forceinline__ float bhi(uint32_t v) { return __uint_as_float(v & 0xffff0000u); }
__device__ __forceinline__ uint32_t hmul2(uint32_t a, uint32_t b) { uint32_t r; asm("mul.rn.bf16x2 %0, %1, %2;" : "=r"(r) : "r"(a), "r"(b)); return r; }
__device__ __forceinline__ uint32_t hfma2(uint32_t a, uint32_t b, uint32_t c) { uint32_t r; asm("fma.rn.bf16x2 %0, %1, %2, %3;" : "=r"(r) : "r"(a), "r"(b), "r"(c)); return r; }
__device__ __forceinline__ float tanh_fast(float x) { float r; asm("tanh.approx.f32 %0, %1;" : "=f"(r) : "f"(x)); return r; }
__device__ __forceinline__ float ex2(float x) { float r; asm("ex2.approx.ftz.f32 %0, %1;" : "=f"(r) : "f"(x)); return r; }

__device__ __forceinline__ void flag_wait(const uint32_t* p, uint32_t e) {
#pragma unroll 1
    for (int i = 0; i < (1 << 20); i++) {
        uint32_t v;
        asm volatile("ld.acquire.gpu.global.u32 %0, [%1];" : "=r"(v) : "l"(p) : "memory");
        if (v == e) break;
    }
}
__device__ __forceinline__ uint32_t ld_epoch() {
    uint32_t v;
    asm volatile("ld.relaxed.gpu.global.u32 %0, [%1];" : "=r"(v) : "l"(&g_epoch[blockIdx.x * FS]) : "memory");
    return v + 1;
}
__device__ __forceinline__ void flag_set(uint32_t* p, uint32_t e) { asm volatile("st.release.gpu.global.u32 [%0], %1;" ::"l"(p), "r"(e) : "memory"); }

__device__ __forceinline__ uint32_t desc_lo(uint32_t addr) { return ((addr & 0x3FFFF) >> 4) | 0x10000u; }
__device__ __forceinline__ uint64_t mkdesc(uint32_t lo) { return (uint64_t)lo | (0x40000040ull << 32); }
__device__ __forceinline__ void wg_fence() { asm volatile("wgmma.fence.sync.aligned;" ::: "memory"); }
__device__ __forceinline__ void wg_commit() { asm volatile("wgmma.commit_group.sync.aligned;" ::: "memory"); }
template <int N> __device__ __forceinline__ void wg_wait() { asm volatile("wgmma.wait_group.sync.aligned %0;" ::"n"(N) : "memory"); }
template <int N> __device__ __forceinline__ void pin(float (&d)[N]) {
#pragma unroll
    for (int i = 0; i < N; i++) asm volatile("" : "+f"(d[i])::"memory");
}
template <int N> __device__ __forceinline__ void pin(uint32_t (&d)[N]) {
#pragma unroll
    for (int i = 0; i < N; i++) asm volatile("" : "+r"(d[i])::"memory");
}

template <typename Tp, int N> __device__ __forceinline__ void zero(Tp (&d)[N]) {
#pragma unroll
    for (int i = 0; i < N; i++) d[i] = 0;
    pin(d);
}

#define F4(d, i) "+f"(d[i]), "+f"(d[i + 1]), "+f"(d[i + 2]), "+f"(d[i + 3])
#define F16(d, i) F4(d, i), F4(d, i + 4), F4(d, i + 8), F4(d, i + 12)

__device__ __forceinline__ void mma_t(float (&d)[16], uint64_t a, uint64_t b, int acc) {
    asm volatile("{.reg .pred p; setp.ne.b32 p, %18, 0;\n"
                 "wgmma.mma_async.sync.aligned.m64n32k16.f32.bf16.bf16 {%0,%1,%2,%3,%4,%5,%6,%7,%8,%9,%10,%11,%12,%13,%14,%15}, %16, %17, p, 1, 1, 1, 0;}\n"
                 : F16(d, 0) : "l"(a), "l"(b), "r"(acc));
}
__device__ __forceinline__ void mma_t(float (&d)[20], uint64_t a, uint64_t b, int acc) {
    asm volatile("{.reg .pred p; setp.ne.b32 p, %22, 0;\n"
                 "wgmma.mma_async.sync.aligned.m64n40k16.f32.bf16.bf16 {%0,%1,%2,%3,%4,%5,%6,%7,%8,%9,%10,%11,%12,%13,%14,%15,%16,%17,%18,%19}, %20, %21, p, 1, 1, 1, 0;}\n"
                 : F16(d, 0), F4(d, 16) : "l"(a), "l"(b), "r"(acc));
}
__device__ __forceinline__ void mma_t(float (&d)[24], uint64_t a, uint64_t b, int acc) {
    asm volatile("{.reg .pred p; setp.ne.b32 p, %26, 0;\n"
                 "wgmma.mma_async.sync.aligned.m64n48k16.f32.bf16.bf16 {%0,%1,%2,%3,%4,%5,%6,%7,%8,%9,%10,%11,%12,%13,%14,%15,%16,%17,%18,%19,%20,%21,%22,%23}, %24, %25, p, 1, 1, 1, 0;}\n"
                 : F16(d, 0), F4(d, 16), F4(d, 20) : "l"(a), "l"(b), "r"(acc));
}
__device__ __forceinline__ void mma_qk(float (&d)[32], uint32_t a0, uint32_t a1, uint32_t a2, uint32_t a3, uint64_t b, int acc) {
    asm volatile("{.reg .pred p; setp.ne.b32 p, %37, 0;\n"
                 "wgmma.mma_async.sync.aligned.m64n64k16.f32.bf16.bf16 {%0,%1,%2,%3,%4,%5,%6,%7,%8,%9,%10,%11,%12,%13,%14,%15,%16,%17,%18,%19,%20,%21,%22,%23,%24,%25,%26,%27,%28,%29,%30,%31}, "
                 "{%32,%33,%34,%35}, %36, p, 1, 1, 0;}\n"
                 : F16(d, 0), F16(d, 16) : "r"(a0), "r"(a1), "r"(a2), "r"(a3), "l"(b), "r"(acc));
}
__device__ __forceinline__ void mma_pv(float (&d)[36], uint32_t a0, uint32_t a1, uint32_t a2, uint32_t a3, uint64_t b) {
    asm volatile("wgmma.mma_async.sync.aligned.m64n72k16.f32.bf16.bf16 {%0,%1,%2,%3,%4,%5,%6,%7,%8,%9,%10,%11,%12,%13,%14,%15,%16,%17,%18,%19,%20,%21,%22,%23,%24,%25,%26,%27,%28,%29,%30,%31,%32,%33,%34,%35}, "
                 "{%36,%37,%38,%39}, %40, 1, 1, 1, 1;\n"
                 : F16(d, 0), F16(d, 16), F4(d, 32) : "r"(a0), "r"(a1), "r"(a2), "r"(a3), "l"(b));
}

template <uint32_t CSTRIDE, int N>
__device__ __forceinline__ void issue_half(float (&d)[N], uint32_t alo, uint32_t blo_, int acc) {
    const uint64_t a = mkdesc(alo), b = mkdesc(blo_);
    wg_fence();
#pragma unroll
    for (int k = 0; k < 8; k++) mma_t(d, a + k * 128, b + (k >> 2) * (CSTRIDE >> 4) + (k & 3) * 2, k == 0 ? acc : 1);
    wg_commit();
}

__device__ __forceinline__ uint32_t load_code(int n, int r, int w) {
    const int tile = 2 * r + w;
    int m, col, row;
    if (n < 16 || n >= 40) {
        const int k = n < 16 ? n : n - 40;
        m = n < 16 ? 1 : 7;
        if (k < 8) { col = 8 * r + (k & 6) + w; row = (k & 1) ^ r; }
        else {
            const int kk = k == 11 ? 12 : (k == 12 ? 11 : k);
            m++; col = kk < 12 ? (tile ^ 2) : tile; row = 4 * r + (kk & 3);
        }
    } else if (n < 32) {
        const int k = n - 16;
        m = 3;
        if (k < 4) { col = tile + ((k & 1) ? 8 : 4); row = (k >> 1) ^ r; }
        else { col = tile; row = (k & 1) ^ r; }
    } else if (n < 34) { m = 4; col = tile; row = n - 32; }
    else if (n < 38) { const int k = n - 34; m = 5; col = tile + 4 * (k & 1); row = (k >> 1) ^ r; }
    else { m = 6; col = tile; row = (n & 1) ^ r; }
    return m | (col << 4) | (row << 8);
}

__global__ void __cluster_dims__(2, 1, 1) __launch_bounds__(NTHREADS, 1)
conformer_kernel(const __grid_constant__ Params p) {
    extern __shared__ __align__(1024) unsigned char smem_raw[];
    const uint32_t sb = smem_u32(smem_raw);
    const uint32_t bars = sb + OFF_BARS;
    const int tid = threadIdx.x;
    const int lane = tid & 31;
    const int warp = __shfl_sync(~0u, tid >> 5, 0);
    const int r = blockIdx.x & 1;
    const int pair = blockIdx.x >> 1;
    const int b = pair >> 5, pt = pair & 31;
    const int ah = pt >> 3, qt = (pt & 7) * 2 + r;
    const int abh = b * 4 + ah;

    TG(30);
    TSINIT();
    TS(0);
    const uint32_t P = sb + OFF_P, H = sb + OFF_H;
    auto xwait = [&](int j) { mbar_wait(bars + (B_XR + (j & 1)) * 8, (j >> 1) & 1); };

    if (warp >= 8) {
        asm volatile("setmaxnreg.dec.sync.aligned.u32 48;");
        if (warp >= 12) {
            if (warp == 12 && lane >= 2 && lane < 10) asm volatile("prefetch.tensormap [%0];" ::"l"(&p.tm[lane]) : "memory");
            cluster_arrive();
            cluster_wait();
            const int ut = tid & 127;
            const uint32_t a4 = P + (ut >> 2) * 128 + (2 * (ut & 3) + ((ut >> 2) & 1)) * 16;
            const uint32_t a8 = P + (32 + (ut >> 3)) * 128 + (ut & 7) * 16;
#pragma unroll 1
            for (int k = 0; k < 4; k++) {
                float s = 0.f, q = 0.f, s2 = 0.f, q2 = 0.f;
#pragma unroll 1
                for (int h = 0; h < 2; h++) {
                    if (h == 0 && k != 0) bar_sync(1, 384);
                    else xwait(k == 3 ? 4 : k);
                    const uint32_t off = 2 * (r ^ h) * XCH;
                    uint4 v0 = lds128(a4 + off), v1 = lds128((a4 ^ 16) + off), v2 = lds128(a4 + off + XCH), v3 = lds128((a4 ^ 16) + off + XCH);
                    uint4 v4 = make_uint4(0, 0, 0, 0), v5 = v4;
                    if (k == 2) { v4 = lds128(a8 + off); v5 = lds128(a8 + off + XCH); }
                    if (h == 1 || k == 1 || k == 2) bar_arrive(5 + ((v3.w | v5.w) & p.zero), 384);
                    uint32_t t;
                    asm volatile("mov.u32 %0, %%clock;" : "=r"(t)::"memory");
                    const uint32_t mul = 65536u + (t & p.zero), msk = 0u - mul;
                    auto accum = [&](const uint4& v, float& s, float& q) {
                        const float a0 = __uint_as_float(v.x * mul), a1 = __uint_as_float(v.x & msk), a2 = __uint_as_float(v.y * mul), a3 = __uint_as_float(v.y & msk);
                        const float a4 = __uint_as_float(v.z * mul), a5 = __uint_as_float(v.z & msk), a6 = __uint_as_float(v.w * mul), a7 = __uint_as_float(v.w & msk);
                        s += ((a0 + a1) + (a2 + a3)) + ((a4 + a5) + (a6 + a7));
                        q += fmaf(a0, a0, fmaf(a1, a1, fmaf(a2, a2, a3 * a3))) + fmaf(a4, a4, fmaf(a5, a5, fmaf(a6, a6, a7 * a7)));
                    };
                    accum(v0, s, q); accum(v1, s, q); accum(v2, s, q); accum(v3, s, q);
                    if (k == 2) { accum(v4, s2, q2); accum(v5, s2, q2); }
                }
#pragma unroll
                for (int o = 1; o < 8; o <<= 1) {
                    if (o < 4) { s += __shfl_xor_sync(~0u, s, o); q += __shfl_xor_sync(~0u, q, o); }
                    if (k == 2) { s2 += __shfl_xor_sync(~0u, s2, o); q2 += __shfl_xor_sync(~0u, q2, o); }
                }
                const bool second = (ut & 7) == 1;
                if (second) { s = s2; q = q2; }
                const float mean = s * (1.f / 256.f);
                const int row = second ? 32 + (ut >> 3) : ut >> 2;
                const float alpha = k == 1 ? 1.f : ((k == 2 && (uint32_t)(pt * 32 - 8 + row) >= T_) ? 0.f : 0.5f);
                const float rstd = alpha * rsqrtf(fmaxf(fmaf(-mean, mean, q * (1.f / 256.f)), 0.f) + 1e-5f);
                if ((ut & 3) == 0 || second) sts64f(sb + OFF_STATS + row * 8, mean * rstd, rstd);
                __syncwarp();
                if (lane == 0) mbar_arrive(bars + B_ST * 8);
                TS(2 + k);
                if (k == 1 && warp == 12) {
                    const uint32_t epoch = ld_epoch();
                    bar_sync(11, 288);
                    if (lane < 2) flag_set(&g_flag_q[((b * 4 + 2 * r + lane) * 32 + pt) * FS], epoch);
                    __syncwarp();
                    TS(13);
                }
            }
        } else if (warp < 10) {
            const int w = warp - 8;
            const uint32_t ring = sb + OFF_RING + w * NSLOT * SLOT;
            const uint32_t full = bars + (B_FULL + w * NSLOT) * 8;
            if (lane == 0) {
#pragma unroll
                for (int i = 0; i < NSLOT; i++) mbar_init(full + i * 8, 1);
                asm volatile("fence.mbarrier_init.release.cluster;" ::: "memory");
                fence_async_smem();
            }
            __syncwarp();
            cluster_arrive();
            TS(1);
#pragma unroll
            for (int n = 0; n < NSLOT; n++)
                ring_load(ring + n * SLOT, &p.tm[1], 64 * (8 * r + (n & 6) + w), 128 * ((n & 1) ^ r), full + n * 8);
            TS(2);
            const uint32_t code = load_code(lane, r, w) | (load_code(lane + 32, r, w) << 16);
            cluster_wait();
            uint32_t s = 0, ph = 0;
            int n = NSLOT;
#pragma unroll 1
            for (int seg = 0; seg < 2; seg++) {
#pragma unroll 1
                for (; n < (seg == 0 ? 22 : NLOADS); n++) {
                    const uint32_t c = __shfl_sync(~0u, code, n) >> (n & 32 ? 16 : 0);
                    mbar_wait(full + (B_EMPTY - B_FULL) * 8 + s * 8, ph);
                    ring_load(ring + s * SLOT, &p.tm[c & 15], (c & 0xf0) * 4, (c & 0xff00) >> 1, full + s * 8);
                    if (++s == NSLOT) { s = 0; ph ^= 1; }
                }
                if (seg == 1) break;
                const uint32_t epoch = ld_epoch();
                const uint32_t rdy = bars + (B_RDY + 3 * w) * 8, prdy = mapa(rdy, r ^ 1);
                const int isv = r ^ w;
#pragma unroll 1
                for (; n < 32; n++) {
                    mbar_wait(full + (B_EMPTY - B_FULL) * 8 + s * 8, ph);
                    if (lane == 0) {
                        if (n < 24) mbar_arrive(full + s * 8);
                        else mbar_arrive_tx(full + s * 8, SLOT);
                    }
                    if (n == 28) {
                        if (lane == 0) mbar_arrive_peer(prdy);
                        mbar_wait(rdy, 0);
                        if (!isv) {
                            flag_wait(g_flag_kv + (abh * 32 + lane) * FS, epoch);
                            __syncwarp();
                            fence_async_global();
                            TSW(5);
                            ring_load_both(ring + 4 * SLOT, &p.tm[9], (abh * 8 + w) * 128, full + 32);
                        }
                        bar_sync(12, 64);
#pragma unroll
                        for (int i = 0; i < 2; i++)
                            ring_load_both(ring + (2 * i + isv) * SLOT, &p.tm[9], (isv * 62 + abh * 8 + 2 * i + 2 + w) * 128, full + (2 * i + isv) * 8);
                    } else if (n > 28) {
                        const uint32_t bo = n == 31 ? 16 : 8;
                        if ((n > 29) == (isv == 1)) {
                            mbar_wait(rdy + bo, 0);
                            ring_load_both(ring + s * SLOT, &p.tm[9], (isv * 64 + abh * 8 + (n == 30 ? 4 : 6) + w) * 128, full + s * 8);
                        } else if (lane == 0) mbar_arrive_peer(prdy + bo);
                    }
                    __syncwarp();
                    if (++s == NSLOT) { s = 0; ph ^= 1; }
                }
            }
        } else if (warp == 10) {
            if (lane == 0) {
                mbar_init(bars + B_XR * 8, 1);
                asm volatile("fence.mbarrier_init.release.cluster;" ::: "memory");
                fence_async_smem();
            }
            __syncwarp();
            cluster_arrive();
            if (lane == 0) {
                mbar_arrive_tx(bars + B_XR * 8, 16384);
#pragma unroll
                for (int i = 0; i < 4; i++) tma3d(P + i * XCH, &p.tm[0], i * 64, pt * 32, b, bars + B_XR * 8);
            }
            __syncwarp();
            cluster_wait();
            const uint32_t epoch = ld_epoch();
            if (lane == 0) {
                mbar_arrive_tx(bars + B_QIN * 8, 8192);
                mbar_arrive_tx(bars + B_OIN * 8, 2 * XCH);
                mbar_arrive_tx(bars + B_OIN * 8 + 8, 2 * XCH);
            }
            if (lane < 2) flag_wait(&g_flag_q[(abh * 32 + 2 * qt + lane) * FS], epoch);
            __syncwarp();
            if (lane == 0) {
                fence_async_global();
                bulk_g2s(H + 24576, g_kvq + 2097152 + (size_t)(abh * 1024 + qt * 64) * 128, 8192, bars + B_QIN * 8);
            }
            if (lane < 2) {
                const int np = pt - 1 + 2 * lane;
                if (np >= 0 && np < 32) flag_wait(&g_flag_kv[((b * 4 + 2 * r) * 32 + np) * FS], epoch);
            }
            __syncwarp();
            if (lane == 0) mbar_arrive(bars + B_X1IN * 8);
            bar_sync(9, 64);
            if (lane < 8) {
                const int q = (pt >> 1) + (lane < 4 ? 0 : ((pt & 1) ? 1 : -1));
                if (q >= 0 && q < 16) flag_wait(&g_flag_o[((b * 16 + q) * 4 + (lane & 3)) * FS], epoch);
            }
            __syncwarp();
            TSW(10);
            if (lane == 0) {
                fence_async_global();
#pragma unroll
                for (int i = 0; i < 4; i++)
                    bulk_g2s(H + i * XCH, g_o + (size_t)((b * 4 + i) * PADROWS + pt * 32) * 128, XCH, bars + (B_OIN + (i >> 1)) * 8);
            }
            __syncwarp();
        } else {
            uint32_t kb = (lane < 2 || lane > 5) ? 4096 : (lane == 2 ? 3072 : (lane == 4 ? 2048 : 1024));
            size_t off = (size_t)blockIdx.x * kb;
            if (lane == 8) { kb = 8192; off = (size_t)min(b * T_ + pt * 32 + r * 16, 2 * T_ - 16) * 512; }
            const char* pf = p.w[min(lane, 8)] + off;
            if (lane == 0 || lane == 8) prefetch_l2(pf, kb);
            __syncwarp();
            cluster_arrive();
            cluster_wait();
            xwait(0);
            if (lane == 1 || lane == 2) prefetch_l2(pf, kb);
            mbar_wait(bars + B_HF * 8, 0);
            if (lane > 2 && lane < 8) prefetch_l2(pf, kb);
            const uint32_t epoch = ld_epoch();
            bar_sync(4, 288);
            if (lane < 2) flag_set(&g_flag_kv[((b * 4 + 2 * r + lane) * 32 + pt) * FS], epoch);
            __syncwarp();
            TSW(8);
            bar_sync(6, 288);
            bar_arrive(9, 64);
            if (lane == 0) {
                flag_set(&g_flag_o[((b * 16 + qt) * 4 + ah) * FS], epoch);
                g_epoch[blockIdx.x * FS] = epoch;
            }
            __syncwarp();
            TSW(9);
        }
        TSDUMP();
        return;
    }

    if (lane == 0) {
        mbar_init(bars + (B_EMPTY + warp) * 8, 4);
        mbar_init(bars + (B_HF + warp) * 8, warp < 4 ? 8 : 1);
        if (warp < 3) mbar_init(bars + (warp == 2 ? B_ST : B_EMPTY + 8 + warp) * 8, 4);
        else if (warp < 6) mbar_init(bars + (B_XR - 2 + warp) * 8, 1);
        if (warp < 6) mbar_init(bars + (B_RDY + warp) * 8, 1);
        asm volatile("fence.mbarrier_init.release.cluster;" ::: "memory");
    }
    sts128(P + (tid >> 6) * XCH + 4096 + (tid & 63) * 16, 0x3F803F80u, 0x3F803F80u, 0x3F803F80u, 0x3F803F80u);
    fence_async_smem();
    __syncwarp();
    cluster_arrive();
    asm volatile("setmaxnreg.inc.sync.aligned.u32 208;");
    const int w = warp >> 2, wq = warp & 3;
    const int tile = 2 * r + w;
    const int wt = tid & 127;
    const int c4 = lane & 3;
    const uint32_t rbase = sb + OFF_RING + w * NSLOT * SLOT, fbar = bars + (B_FULL + w * NSLOT) * 8;
    const uint32_t rdesc = desc_lo(rbase);
    auto acq = [&](int n) { mbar_wait(fbar + (n % NSLOT) * 8, (n / NSLOT) & 1); };
    auto rel = [&](int n) { if (lane == 0) mbar_arrive(fbar + (B_EMPTY - B_FULL + n % NSLOT) * 8); };
    const uint32_t pown = desc_lo(P + 2 * r * XCH), prem = desc_lo(P + 2 * (r ^ 1) * XCH), hdesc = desc_lo(H);
    const uint32_t toff = ((lane >> 4) * 8 + (lane & 7)) * 128 + (((2 * wq + ((lane >> 3) & 1)) ^ (lane & 7)) << 4);
    const uint32_t xa = P + tile * XCH + toff;
    auto publish = [&](int j, uint32_t src, uint32_t bytes, int nsync) {
        const uint32_t bar = bars + (B_XR + (j & 1)) * 8;
        fence_async_smem();
        bar_sync(2 + w, 128);
        if (wq == 0) peer_copy(mapa(src, r ^ 1), src, bytes, mapa(bar, r ^ 1));
        if (tid == 32) mbar_arrive_tx(bar, 2 * bytes);
        bar_sync(nsync == 384 ? 1 : 10, nsync);
    };
    auto gate = [&](int j) { xwait(j); bar_sync(5, 384); };
    auto load_stats = [&](auto& st, int parity) {
        mbar_wait(bars + B_ST * 8, parity);
#pragma unroll
        for (int j = 0; j < (int)(sizeof(st) / 16); j++) {
            const float4 v = lds128f(sb + OFF_STATS + (8 * j + 2 * c4) * 8);
            st[4 * j] = v.x; st[4 * j + 1] = v.y; st[4 * j + 2] = v.z; st[4 * j + 3] = v.w;
        }
    };
    bar_sync(10, 256);
    cluster_wait();
    uint32_t xr[8];
    xwait(0);
    ldsm4t(xa, xr[0], xr[1], xr[2], xr[3]);
    ldsm4t(xa + 2048, xr[4], xr[5], xr[6], xr[7]);
    acq(0); acq(1);

#pragma unroll 1
    for (int ffi = 0; ffi < 2; ffi++) {
        auto mm = [&](auto& d, int n, uint32_t bd, auto cs, int acc) {
            const uint32_t z = p.zero * (ffi + n + 1);
            issue_half<decltype(cs)::value>(d, rdesc + z + (n % NSLOT) * (SLOT >> 4), bd + z, acc);
        };
        constexpr std::integral_constant<uint32_t, XCH> cx{};
        constexpr std::integral_constant<uint32_t, HCH> ch{};
        {
            float st[16], a0[20], a1[20], rem[16], own[16];
            const uint32_t inb = bars + (B_INB + w) * 8, box = sb + OFF_INBOX + w * 4096 + wt * 16;
            const uint32_t hdst = H + w * HCH + toff;
            auto step = [&](auto& d, int n, uint32_t bd, auto cs, int acc) {
                mm(d, n, bd, cs, acc);
                wg_wait<1>();
                if (n > 0) rel(n - 1);
            };
            auto epi = [&](float (&d)[20], int i, int half) {
                uint32_t pk[4];
#pragma unroll
                for (int k = 4 * half; k < 4 * half + 4; k++) {
                    const float cs = d[16 + 2 * (k & 1)];
                    const float v0 = fmaf(-st[(k >> 1) * 4], cs, d[2 * k] * st[(k >> 1) * 4 + 1]);
                    const float v1 = fmaf(-st[(k >> 1) * 4 + 2], cs, d[2 * k + 1] * st[(k >> 1) * 4 + 3]);
                    pk[k & 3] = pack2(fmaf(v0, tanh_fast(v0), v0), fmaf(v1, tanh_fast(v1), v1));
                }
                stsm4t(hdst + 2 * i * HCH + half * 2048, pk[0], pk[1], pk[2], pk[3]);
            };
            auto hdone = [&](int i) {
                fence_async_smem();
                __syncwarp();
                if (lane == 0) mbar_arrive(bars + (B_HF + i) * 8);
            };
            auto hwait = [&](int i) { mbar_wait(bars + (B_HF + i) * 8, ffi); };
            TS(1 + ffi * 20);
            step(a0, 0, pown, cx, 0);
            if (wt == 0) mbar_arrive_tx(inb, 4096);
            acq(2);
            gate(ffi * 4);
            TS(32);
            step(a0, 1, prem, cx, 1);
            step(a1, 2, pown, cx, 0); acq(3); pin(a0); load_stats(st, ffi); TS(33); epi(a0, 0, 0);
            step(a1, 3, prem, cx, 1); acq(4); epi(a0, 0, 1); TS(34);
            step(a0, 4, pown, cx, 0); acq(5); pin(a1); epi(a1, 1, 0);
            step(a0, 5, prem, cx, 1); acq(6); epi(a1, 1, 1); TS(35);
            step(a1, 6, pown, cx, 0); acq(7); pin(a0); hdone(0); epi(a0, 2, 0);
            step(a1, 7, prem, cx, 1); acq(8); hwait(0); epi(a0, 2, 1); TS(36);
            step(rem, 8, hdesc, ch, 0); acq(9); pin(a1); hdone(1); epi(a1, 3, 0);
            step(rem, 9, hdesc + 2 * (HCH >> 4), ch, 1); acq(10); hwait(1); epi(a1, 3, 1);
            TS(2 + ffi * 20);
            step(rem, 10, hdesc + 4 * (HCH >> 4), ch, 1); acq(11); hdone(2);
            step(own, 11, hdesc, ch, 0); acq(12); hwait(2);
            step(rem, 12, hdesc + 6 * (HCH >> 4), ch, 1); acq(13);
            step(own, 13, hdesc + 2 * (HCH >> 4), ch, 1); acq(14);
            pin(rem);
            {
                const uint32_t dst = mapa(box, r ^ 1), bar = mapa(inb, r ^ 1);
                st_async4(dst, pack2(rem[0], rem[1]), pack2(rem[2], rem[3]), pack2(rem[4], rem[5]), pack2(rem[6], rem[7]), bar);
                st_async4(dst + 2048, pack2(rem[8], rem[9]), pack2(rem[10], rem[11]), pack2(rem[12], rem[13]), pack2(rem[14], rem[15]), bar);
            }
            step(own, 14, hdesc + 4 * (HCH >> 4), ch, 1); acq(15);
            step(own, 15, hdesc + 6 * (HCH >> 4), ch, 1);
            mbar_wait(inb, ffi);
            const uint4 u = lds128(box), v = lds128(box + 2048);
            const uint32_t pr[8] = {u.x, u.y, u.z, u.w, v.x, v.y, v.z, v.w};
            if (ffi == 0) { acq(16); acq(17); }
            wg_wait<0>();
            pin(own);
            TS(3 + ffi * 20);
#pragma unroll
            for (int i = 0; i < 8; i++)
                xr[i] = pack2(fmaf(0.5f, own[2 * i] + blo(pr[i]), blo(xr[i])), fmaf(0.5f, own[2 * i + 1] + bhi(pr[i]), bhi(xr[i])));
            stsm4t(xa, xr[0], xr[1], xr[2], xr[3]);
            stsm4t(xa + 2048, xr[4], xr[5], xr[6], xr[7]);
            rel(15);
            publish(ffi ? 5 : 1, P + tile * XCH + (ffi ? (r ^ 1) * 2048 : 0), ffi ? 2048 : 4096, ffi ? 256 : 384);
        }
        if (ffi == 1) break;

        {
            float ak[20], aq[20], st[16];
            g_halo[((pair * 4 + tile) * 2 + 0) * 128 + wt] = make_uint2(xr[0], xr[1]);
            g_halo[((pair * 4 + tile) * 2 + 1) * 128 + wt] = make_uint2(xr[6], xr[7]);
            bar_sync(5, 384);
            TS(11);
            mm(ak, 16, pown, cx, 0);
            mm(aq, 17, pown, cx, 0);
            acq(18); acq(19);
            gate(1);
            mm(ak, 18, prem, cx, 1);
            mm(aq, 19, prem, cx, 1);
            wg_wait<2>();
            rel(16); rel(17);
            load_stats(st, 1);
            auto stage_out = [&](float (&d)[20], uint32_t dst) {
                uint32_t pk[8];
#pragma unroll
                for (int k = 0; k < 8; k++) {
                    const float cs = d[16 + 2 * (k & 1)];
                    pk[k] = pack2(fmaf(-st[(k >> 1) * 4], cs, d[2 * k] * st[(k >> 1) * 4 + 1]),
                                  fmaf(-st[(k >> 1) * 4 + 2], cs, d[2 * k + 1] * st[(k >> 1) * 4 + 3]));
                }
                stsm4t(dst + toff, pk[0], pk[1], pk[2], pk[3]);
                stsm4t(dst + toff + 2048, pk[4], pk[5], pk[6], pk[7]);
            };
            const uint32_t stg = H + w * 12288;
            unsigned char* g = g_kvq + (size_t)((b * 4 + tile) * 1024 + pt * 32) * 128 + wt * 16;
            wg_wait<0>();
            pin(ak); pin(aq);
            TS(37);
            stage_out(ak, stg);
            stage_out(aq, stg + 4096);
            bar_sync(2 + w, 128);
            {
                const uint4 k0 = lds128(stg + wt * 16), k1 = lds128(stg + 2048 + wt * 16), q0 = lds128(stg + 4096 + wt * 16), q1 = lds128(stg + 6144 + wt * 16);
                stg128(g, k0); stg128(g + 2048, k1);
                stg128(g + 1048576, q0); stg128(g + 1048576 + 2048, q1);
            }
            bar_arrive(4, 288);
            TS(38);
            rel(18); rel(19);
            acq(20); acq(21);
            bar_sync(10, 256);
            mm(ak, 20, pown, cx, 0);
            mm(ak, 21, prem, cx, 1);
            wg_wait<0>();
            pin(ak);
            stage_out(ak, stg + 8192);
            rel(20); rel(21);
            bar_sync(2 + w, 128);
            {
                const uint4 v0 = lds128(stg + 8192 + wt * 16), v1 = lds128(stg + 10240 + wt * 16);
                stg128(g + 2097152, v0); stg128(g + 2097152 + 2048, v1);
            }
            bar_arrive(11, 288);
            acq(22); acq(23);
            rel(22); rel(23);
            TS(12);
        }

        {
            constexpr float CS = 0.125f * 1.4426950408889634f;
            float sa[32], sb2[32], o[36];
            uint32_t pa[16], pb[16], q[16];
            float n0 = INFINITY, n1 = INFINITY;
            zero(o); zero(pa); zero(pb);
            const uint32_t ones = sb + OFF_INBOX + 2048;
            if (tid < 128) sts128(ones + tid * 16, 0x3F803F80u, 0x3F803F80u, 0x3F803F80u, 0x3F803F80u);
            fence_async_smem();
            bar_sync(10, 256);
            const uint32_t vdesc = rdesc + ((((ones - rbase) >> 4) - 1) << 16);
            auto qk_issue = [&](float (&s)[32], uint32_t lo) {
                const uint64_t kd = mkdesc(lo);
                wg_fence();
#pragma unroll
                for (int k = 0; k < 4; k++) mma_qk(s, q[4 * k], q[4 * k + 1], q[4 * k + 2], q[4 * k + 3], kd + 2 * k, k != 0);
                wg_commit();
            };
            auto pv_issue = [&](uint32_t (&pp)[16], uint32_t lo) {
                const uint64_t vd = mkdesc(lo);
                wg_fence();
#pragma unroll
                for (int k = 0; k < 4; k++) mma_pv(o, pp[4 * k], pp[4 * k + 1], pp[4 * k + 2], pp[4 * k + 3], vd - k * (128 * 65535));
                wg_commit();
            };
            auto new_max = [&](float (&s)[32], float& x0, float& x1) {
                x0 = s[0]; x1 = s[2];
#pragma unroll
                for (int j = 0; j < 8; j++) {
                    x0 = fmaxf(x0, fmaxf(s[4 * j], s[4 * j + 1]));
                    x1 = fmaxf(x1, fmaxf(s[4 * j + 2], s[4 * j + 3]));
                }
                x0 = fmaxf(x0, __shfl_xor_sync(~0u, x0, 1)); x1 = fmaxf(x1, __shfl_xor_sync(~0u, x1, 1));
                x0 = fmaxf(x0, __shfl_xor_sync(~0u, x0, 2)); x1 = fmaxf(x1, __shfl_xor_sync(~0u, x1, 2));
                x0 = fminf(n0, fmaf(x0, -CS, -20.f)); x1 = fminf(n1, fmaf(x1, -CS, -20.f));
            };
            auto probs = [&](float (&s)[32], uint32_t (&pp)[16], bool ready, auto wait) {
                uint32_t any = 0;
#pragma unroll
                for (int i = 0; i < 16; i++) {
                    pp[i] = pack2(ex2(fmaf(s[2 * i], CS, (i & 1) ? n1 : n0)), ex2(fmaf(s[2 * i + 1], CS, (i & 1) ? n1 : n0)));
                    any |= pp[i];
                }
                float sc0 = 1.f, sc1 = 1.f;
                const bool slow = __any_sync(~0u, (any & 0x40004000u) || !ready);
                if (slow) {
                    wait();
                    if (__any_sync(~0u, any & 0x40004000u)) {
                        float x0, x1;
                        new_max(s, x0, x1);
                        sc0 = ex2(x0 - n0); sc1 = ex2(x1 - n1);
                        n0 = x0; n1 = x1;
#pragma unroll
                        for (int i = 0; i < 16; i++)
                            pp[i] = pack2(ex2(fmaf(s[2 * i], CS, (i & 1) ? n1 : n0)), ex2(fmaf(s[2 * i + 1], CS, (i & 1) ? n1 : n0)));
                    }
                }
                wg_wait<0>();
                pin(sa); pin(sb2); pin(o); pin(pa); pin(pb);
                if (slow) {
#pragma unroll
                    for (int j = 0; j < 9; j++) { o[4 * j] *= sc0; o[4 * j + 1] *= sc0; o[4 * j + 2] *= sc1; o[4 * j + 3] *= sc1; }
                }
            };
            mbar_wait(bars + B_QIN * 8, 0);
            {
                const uint32_t qa = H + 24576 + (wq * 16 + (lane & 15)) * 128;
#pragma unroll
                for (int k = 0; k < 4; k++) ldsm4(qa + (((2 * k + (lane >> 4)) ^ (lane & 7)) << 4), q[4 * k], q[4 * k + 1], q[4 * k + 2], q[4 * k + 3]);
                pin(q);
            }
            acq(24);
            TS(13);
            qk_issue(sa, rdesc + (24 % NSLOT) * (SLOT >> 4));
            qk_issue(sb2, rdesc + (24 % NSLOT) * (SLOT >> 4) + 512);
            wg_wait<1>();
            pin(sa);
            {
                float x0, x1;
                new_max(sa, x0, x1);
                n0 = x0; n1 = x1;
            }
            if (w == 1) bar_sync(7, 256);
            uint32_t vd = vdesc - (SLOT >> 4) * 65535u, kd = rdesc, vb = fbar + 8, kb = fbar;
            uint32_t vlast = vdesc - 4 * (SLOT >> 4) * 65535u;
            uint32_t kprev = fbar + 32, vprev = bars + (B_HF + 3 - (B_EMPTY - B_FULL)) * 8;
#pragma unroll 1
            for (int it = 0; it < 4; it++) {
                pv_issue(pb, vlast);
                probs(sa, pa, mbar_test(vb, it < 2) & mbar_test(kb, it < 3), [&]() { mbar_wait(vb, it < 2); mbar_wait(kb, it < 3); });
                TS(41 + it * 4);
                if (it == 0 && w == 0) bar_arrive(7, 256);
                if (it == 3 && w == 1) {
#pragma unroll
                    for (int i = 20; i < 32; i++) sb2[i] = -INFINITY;
                }
                pin(sb2);
                if (it < 3) qk_issue(sa, kd);
                pv_issue(pa, vd);
                if (lane == 0) mbar_arrive(kprev + (B_EMPTY - B_FULL) * 8);
                if (lane == 0) mbar_arrive(vprev + (B_EMPTY - B_FULL) * 8);
                probs(sb2, pb, true, []() {});
                TS(43 + it * 4);
                if (it < 3) qk_issue(sb2, kd + 512);
                const int dv = it == 0 ? 2 : (it == 1 ? -3 : 1);
                kprev = kb; vprev = vb; vlast = vd - 512 * 65535u;
                vd -= dv * (SLOT >> 4) * 65535u; vb += dv * 8;
                kd += 2 * (SLOT >> 4); kb = it == 2 ? vb : kb + 16;
            }
            pv_issue(pb, vlast);
            const int row = wq * 16 + (lane >> 2);
            const uint32_t ml = sb + OFF_INBOX;
            wg_wait<0>();
            pin(o); pin(pb); pin(sa); pin(sb2);
            rel(31);
            const float l0 = o[32], l1 = o[34];
            if (c4 == 0) { sts64f(ml + w * 512 + row * 8, n0, l0); sts64f(ml + w * 512 + row * 8 + 64, n1, l1); }
            TS(14);
            float mine[16];
#pragma unroll
            for (int j = 0; j < 4; j++) {
                if (w == 0) sts128f(H + j * 2048 + wt * 16, o[16 + 4 * j], o[17 + 4 * j], o[18 + 4 * j], o[19 + 4 * j]);
                else sts128f(H + 8192 + j * 2048 + wt * 16, o[4 * j], o[4 * j + 1], o[4 * j + 2], o[4 * j + 3]);
            }
#pragma unroll
            for (int i = 0; i < 16; i++) mine[i] = w == 0 ? o[i] : o[16 + i];
            bar_sync(10, 256);
            const float2 u0 = lds64f(ml + (w ^ 1) * 512 + row * 8), u1 = lds64f(ml + (w ^ 1) * 512 + row * 8 + 64);
            const float x0 = fminf(n0, u0.x), x1 = fminf(n1, u1.x);
            float a0 = ex2(x0 - n0), b0 = ex2(x0 - u0.x), a1 = ex2(x1 - n1), b1 = ex2(x1 - u1.x);
            const float i0 = __fdividef(1.f, fmaf(a0, l0, b0 * u0.y)), i1 = __fdividef(1.f, fmaf(a1, l1, b1 * u1.y));
            a0 *= i0; b0 *= i0; a1 *= i1; b1 *= i1;
            uint32_t pk[8];
#pragma unroll
            for (int j = 0; j < 4; j++) {
                const float4 v = lds128f(H + (w ^ 1) * 8192 + j * 2048 + wt * 16);
                pk[2 * j] = pack2(fmaf(a0, mine[4 * j], b0 * v.x), fmaf(a0, mine[4 * j + 1], b0 * v.y));
                pk[2 * j + 1] = pack2(fmaf(a1, mine[4 * j + 2], b1 * v.z), fmaf(a1, mine[4 * j + 3], b1 * v.w));
            }
            const uint32_t og = H + 16384 + wq * 2048;
            {
                const uint32_t ra = og + (((lane >> 3) & 1) * 8 + (lane & 7)) * 128;
                stsm4(ra + (((4 * w + (lane >> 4)) ^ (lane & 7)) << 4), pk[0], pk[1], pk[2], pk[3]);
                stsm4(ra + (((4 * w + 2 + (lane >> 4)) ^ (lane & 7)) << 4), pk[4], pk[5], pk[6], pk[7]);
            }
            __syncwarp();
            {
                const uint32_t off = (lane >> 2) * 128 + (((4 * w + c4) ^ (lane >> 2)) << 4);
                const uint4 v0 = lds128(og + off), v1 = lds128(og + off + 1024);
                unsigned char* dst = g_o + (size_t)(abh * PADROWS + 8 + qt * 64 + wq * 16) * 128 + off;
                stg128(dst, v0); stg128(dst + 1024, v1);
            }
            bar_arrive(6, 288);
            TS(15);
        }

        uint32_t dwr[15];
        {
#pragma unroll
            for (int i = 0; i < 15; i++) dwr[i] = hmul2(__ldg(reinterpret_cast<const uint32_t*>(p.dw + i * 256 + tile * 64) + lane), 0x3F003F00u);
            float d[24];
            uint32_t xw[12];
            mbar_wait(bars + B_X1IN * 8, 0);
            uint2 hl = make_uint2(0, 0), hr = hl;
            if (pt > 0) hl = __ldcg(&g_halo[(((pair - 1) * 4 + tile) * 2 + 1) * 128 + wt]);
            if (pt < 31) hr = __ldcg(&g_halo[(((pair + 1) * 4 + tile) * 2 + 0) * 128 + wt]);
            xw[0] = hl.x; xw[1] = hl.y; xw[10] = hr.x; xw[11] = hr.y;
#pragma unroll
            for (int i = 0; i < 8; i++) xw[2 + i] = xr[i];
            pin(xw);
            pin(dwr);
            acq(32); acq(33); acq(34); acq(35);
            mbar_wait(bars + B_OIN * 8, 0);
            TS(16);
            mm(d, 32, hdesc, cx, 0);
            mbar_wait(bars + B_OIN * 8 + 8, 0);
            mm(d, 33, hdesc + 2 * (XCH >> 4), cx, 1);
            wg_wait<1>();
            rel(32);
            wg_wait<0>();
            pin(d);
#pragma unroll
            for (int i = 0; i < 12; i++) xw[i] = pack2(d[2 * i] + blo(xw[i]), d[2 * i + 1] + bhi(xw[i]));
            if (c4 == 0) { xw[0] = (xw[0] & 0xffff0000u) | 0x3F80u; xw[1] = (xw[1] & 0xffff0000u) | 0x3F80u; }
#pragma unroll
            for (int j = 0; j < 3; j++) stsm4t(xa + j * 2048, xw[4 * j], xw[4 * j + 1], xw[4 * j + 2], xw[4 * j + 3]);
#pragma unroll
            for (int i = 0; i < 8; i++) xr[i] = xw[2 + i];
            rel(33);
            publish(2, P + tile * XCH, XCH, 384);
            TS(17);
        }
        {
            float da[24], db[24], st[24];
            bar_sync(5, 384);
            mm(da, 34, pown, cx, 0);
            mm(db, 35, pown, cx, 0);
            acq(36); acq(37);
            gate(2);
            TS(39);
            mm(da, 36, prem, cx, 1);
            mm(db, 37, prem, cx, 1);
            wg_wait<2>();
            rel(34); rel(35);
            load_stats(st, 0);
            wg_wait<0>();
            pin(da); pin(db);
            rel(36); rel(37);
            TS(18);
            uint32_t pk[12];
#pragma unroll
            for (int hh = 0; hh < 2; hh++) {
                const float ca = __shfl_sync(~0u, da[2 * hh], lane & 28), cb = __shfl_sync(~0u, db[2 * hh], lane & 28);
#pragma unroll
                for (int j = 0; j < 6; j++) {
                    const float u0 = fmaf(-st[4 * j], ca, da[4 * j + 2 * hh] * st[4 * j + 1]);
                    const float u1 = fmaf(-st[4 * j + 2], ca, da[4 * j + 2 * hh + 1] * st[4 * j + 3]);
                    const float v0 = fmaf(-st[4 * j], cb, db[4 * j + 2 * hh] * st[4 * j + 1]);
                    const float v1 = fmaf(-st[4 * j + 2], cb, db[4 * j + 2 * hh + 1] * st[4 * j + 3]);
                    pk[2 * j + hh] = pack2(fmaf(u0, tanh_fast(v0), u0), fmaf(u1, tanh_fast(v1), u1));
                }
            }
            const uint32_t gs = H + 16384 + w * XCH;
#pragma unroll
            for (int j = 0; j < 3; j++) stsm4t(gs + toff + j * 2048, pk[4 * j], pk[4 * j + 1], pk[4 * j + 2], pk[4 * j + 3]);
            bar_sync(2 + w, 128);
            uint32_t ca[8], cb[8];
            const uint32_t grow = gs + 8 * wq * 128 + c4 * 4, srow = H + tile * HCH + 8 * wq * 128 + c4 * 4;
#pragma unroll
            for (int k = 0; k < 22; k++) {
                const uint32_t v = lds32(grow + (1 + k) * 128 + (((lane >> 2) ^ ((1 + k) & 7)) << 4));
#pragma unroll
                for (int i = 0; i < 8; i++) {
                    const int tap = k - i;
                    if (tap == 0) ca[i] = hmul2(v, dwr[0]);
                    else if (tap > 0 && tap < 8) ca[i] = hfma2(v, dwr[tap], ca[i]);
                    else if (tap == 8) cb[i] = hmul2(v, dwr[8]);
                    else if (tap > 8 && tap < 15) cb[i] = hfma2(v, dwr[tap], cb[i]);
                }
            }
#pragma unroll
            for (int i = 0; i < 8; i++) {
                const float h0 = blo(ca[i]) + blo(cb[i]), h1 = bhi(ca[i]) + bhi(cb[i]);
                sts32(srow + i * 128 + (((lane >> 2) ^ i) << 4), pack2(fmaf(h0, tanh_fast(h0), h0), fmaf(h1, tanh_fast(h1), h1)));
            }
            acq(38); acq(39);
            publish(3, H + tile * HCH, HCH, 256);
            TS(19);
        }
        {
            float d[16];
            mm(d, 38, hdesc + 2 * r * (HCH >> 4), ch, 0);
            acq(40); acq(41);
            xwait(3);
            sts128(P + (wt >> 6 ? (tile ^ 2) : tile) * XCH + 4096 + (wt & 63) * 16, 0x3F803F80u, 0x3F803F80u, 0x3F803F80u, 0x3F803F80u);
            mm(d, 39, hdesc + 2 * (r ^ 1) * (HCH >> 4), ch, 1);
            wg_wait<1>();
            rel(38);
            wg_wait<0>();
            pin(d);
#pragma unroll
            for (int i = 0; i < 8; i++) xr[i] = pack2(d[2 * i] + blo(xr[i]), d[2 * i + 1] + bhi(xr[i]));
            stsm4t(xa, xr[0], xr[1], xr[2], xr[3]);
            stsm4t(xa + 2048, xr[4], xr[5], xr[6], xr[7]);
            rel(39);
            publish(4, P + tile * XCH, HCH, 384);
            TS(20);
        }
    }

    xwait(5);
    cluster_arrive();
    TS(24);
    {
        float a[2][8], s[2], q[2];
        const int row0 = 16 * r + 2 * warp;
#pragma unroll
        for (int i = 0; i < 2; i++) {
            const uint4 v = lds128(P + (lane >> 3) * XCH + (row0 + i) * 128 + (((lane & 7) ^ ((row0 + i) & 7)) << 4));
            a[i][0] = blo(v.x); a[i][1] = bhi(v.x); a[i][2] = blo(v.y); a[i][3] = bhi(v.y);
            a[i][4] = blo(v.z); a[i][5] = bhi(v.z); a[i][6] = blo(v.w); a[i][7] = bhi(v.w);
            s[i] = ((a[i][0] + a[i][1]) + (a[i][2] + a[i][3])) + ((a[i][4] + a[i][5]) + (a[i][6] + a[i][7]));
            q[i] = 0.f;
#pragma unroll
            for (int k = 0; k < 8; k++) q[i] = fmaf(a[i][k], a[i][k], q[i]);
        }
#pragma unroll
        for (int o = 16; o > 0; o >>= 1) {
#pragma unroll
            for (int i = 0; i < 2; i++) { s[i] += __shfl_xor_sync(~0u, s[i], o); q[i] += __shfl_xor_sync(~0u, q[i], o); }
        }
#pragma unroll
        for (int i = 0; i < 2; i++) {
            const float mean = s[i] * (1.f / 256.f);
            const float rstd = rsqrtf(fmaxf(fmaf(-mean, mean, q[i] * (1.f / 256.f)), 0.f) + 1e-5f);
            const float nb = -mean * rstd;
            uint4 v;
            v.x = pack2(fmaf(a[i][0], rstd, nb), fmaf(a[i][1], rstd, nb)); v.y = pack2(fmaf(a[i][2], rstd, nb), fmaf(a[i][3], rstd, nb));
            v.z = pack2(fmaf(a[i][4], rstd, nb), fmaf(a[i][5], rstd, nb)); v.w = pack2(fmaf(a[i][6], rstd, nb), fmaf(a[i][7], rstd, nb));
            const int t = pt * 32 + row0 + i;
            if (t < T_) stg128(p.out + (size_t)(b * T_ + t) * 256 + lane * 8, v);
        }
    }
    TS(25);
    TG(31);
    TSDUMP();
    cluster_wait();
}

typedef CUresult (*EncodeFn)(CUtensorMap*, CUtensorMapDataType, cuuint32_t, void*, const cuuint64_t*, const cuuint64_t*,
                             const cuuint32_t*, const cuuint32_t*, CUtensorMapInterleave, CUtensorMapSwizzle,
                             CUtensorMapL2promotion, CUtensorMapFloatOOBfill);

}

extern "C" void kernel_launch(void* const* d_in, const int* in_sizes, int n_in, void* d_out, int out_size) {
    static EncodeFn encode = nullptr;
    if (!encode) {
        void* fn = nullptr;
        cudaDriverEntryPointQueryResult qr;
        cudaGetDriverEntryPoint("cuTensorMapEncodeTiled", &fn, cudaEnableDefault, &qr);
        encode = (EncodeFn)fn;
        cudaFuncSetAttribute(conformer_kernel, cudaFuncAttributeMaxDynamicSharedMemorySize, SMEM_LAUNCH);
    }
    Params p;
    const cuuint32_t ones[3] = {1, 1, 1};
    {
        const cuuint64_t dims[3] = {256, T_, 2};
        const cuuint64_t strides[2] = {512, 512ull * T_};
        const cuuint32_t box[3] = {64, 32, 1};
        encode(&p.tm[0], CU_TENSOR_MAP_DATA_TYPE_BFLOAT16, 3, d_in[0], dims, strides, box, ones, CU_TENSOR_MAP_INTERLEAVE_NONE,
               CU_TENSOR_MAP_SWIZZLE_128B, CU_TENSOR_MAP_L2_PROMOTION_L2_256B, CU_TENSOR_MAP_FLOAT_OOB_FILL_NONE);
    }
    const int idx[8] = {1, 2, 3, 4, 5, 7, 8, 9};
    const int rows[8] = {256, 1024, 256, 256, 256, 256, 256, 1024};
    const int cols[8] = {1024, 256, 768, 256, 512, 256, 1024, 256};
    for (int i = 0; i < 8; i++) {
        const cuuint64_t dims[2] = {(cuuint64_t)cols[i], (cuuint64_t)rows[i]};
        const cuuint64_t strides[1] = {(cuuint64_t)cols[i] * 2};
        const cuuint32_t box[2] = {64, 128};
        encode(&p.tm[1 + i], CU_TENSOR_MAP_DATA_TYPE_BFLOAT16, 2, d_in[idx[i]], dims, strides, box, ones, CU_TENSOR_MAP_INTERLEAVE_NONE,
               CU_TENSOR_MAP_SWIZZLE_128B, CU_TENSOR_MAP_L2_PROMOTION_L2_128B, CU_TENSOR_MAP_FLOAT_OOB_FILL_NONE);
        p.w[i] = (const char*)d_in[idx[i]];
    }
    {
        void* kv = nullptr;
        cudaGetSymbolAddress(&kv, g_kvq);
        const cuuint64_t dims[2] = {64, 16384};
        const cuuint64_t strides[1] = {128};
        const cuuint32_t box[2] = {64, 128};
        encode(&p.tm[9], CU_TENSOR_MAP_DATA_TYPE_BFLOAT16, 2, kv, dims, strides, box, ones, CU_TENSOR_MAP_INTERLEAVE_NONE,
               CU_TENSOR_MAP_SWIZZLE_NONE, CU_TENSOR_MAP_L2_PROMOTION_L2_128B, CU_TENSOR_MAP_FLOAT_OOB_FILL_NONE);
    }
    p.w[8] = (const char*)d_in[0];
    p.dw = (const __nv_bfloat16*)d_in[6];
    p.out = (__nv_bfloat16*)d_out;
    p.zero = 0;
    conformer_kernel<<<NCTA, NTHREADS, SMEM_LAUNCH>>>(p);
}
```

```cpp
#include <cuda_runtime.h>
#include <cuda_bf16.h>
#include <cuda.h>
#include <stdint.h>
#include <type_traits>

namespace {

constexpr int T_ = 1000;
constexpr int NCTA = 128;
constexpr int NTHREADS = 512;
constexpr int NSLOT = 5;
constexpr int SLOT = 16384;
constexpr int NLOADS = 56;

constexpr uint32_t OFF_RING = 0;
constexpr uint32_t OFF_P = 163840;
constexpr uint32_t OFF_H = 188416;
constexpr uint32_t OFF_INBOX = 221184;
constexpr uint32_t OFF_STATS = 229376;
constexpr uint32_t OFF_BARS = 229888;
constexpr uint32_t SMEM_BYTES = 230400;
constexpr uint32_t XCH = 6144;
constexpr uint32_t HCH = 4096;

constexpr int B_FULL = 0, B_EMPTY = 10, B_XR = 20, B_OIN = 22, B_HF = 24, B_INB = 28, B_QIN = 30, B_X1IN = 31, B_ST = 32, B_RDY = 33;

constexpr int PADROWS = 1040;
constexpr int FS = 8;

struct Params {
    CUtensorMap tm[10];
    const char* w[9];
    const __nv_bfloat16* dw;
    __nv_bfloat16* out;
    uint32_t zero;
};

__device__ __align__(1024) unsigned char g_kvq[3 * 8 * 1024 * 128];
__device__ __align__(1024) unsigned char g_o[8 * PADROWS * 128];
__device__ uint2 g_halo[64 * 4 * 2 * 128];
__device__ uint32_t g_flag_kv[8 * 32 * FS];
__device__ uint32_t g_flag_q[8 * 32 * FS];
__device__ uint32_t g_flag_o[2 * 16 * 4 * FS];
__device__ uint32_t g_epoch[NCTA * FS];

#define TS(i) do { } while (0)
#define TSW(i) do { } while (0)
#define TG(i) do { } while (0)
#define TSINIT() do { } while (0)
#define TSDUMP() do { } while (0)
constexpr uint32_t SMEM_LAUNCH = SMEM_BYTES;

__device__ __forceinline__ uint32_t smem_u32(const void* p) { return (uint32_t)__cvta_generic_to_shared(p); }
__device__ __forceinline__ void mbar_init(uint32_t b, uint32_t c) { asm volatile("mbarrier.init.shared::cta.b64 [%0], %1;" ::"r"(b), "r"(c) : "memory"); }
__device__ __forceinline__ void mbar_arrive(uint32_t b) { asm volatile("mbarrier.arrive.shared::cta.b64 _, [%0];" ::"r"(b) : "memory"); }
__device__ __forceinline__ void mbar_arrive_tx(uint32_t b, uint32_t tx) { asm volatile("mbarrier.arrive.expect_tx.shared::cta.b64 _, [%0], %1;" ::"r"(b), "r"(tx) : "memory"); }
__device__ __forceinline__ void mbar_wait(uint32_t b, uint32_t ph) {
    asm volatile("{\n.reg .pred p, q;\n.reg .u32 c;\nmov.u32 c, 0;\n"
                 "MW_LOOP:\n.pragma \"nounroll\";\n"
                 "mbarrier.try_wait.parity.shared::cta.b64 p, [%0], %1;\n"
                 "add.u32 c, c, 1;\nsetp.lt.u32 q, c, 65536;\nnot.pred p, p;\nand.pred p, p, q;\n@p bra MW_LOOP;\n}"
                 ::"r"(b), "r"(ph) : "memory");
}
__device__ __forceinline__ bool mbar_test(uint32_t b, uint32_t ph) {
    uint32_t ok;
    asm volatile("{\n.reg .pred p;\nmbarrier.test_wait.parity.shared::cta.b64 p, [%1], %2;\nselp.u32 %0, 1, 0, p;\n}" : "=r"(ok) : "r"(b), "r"(ph) : "memory");
    return ok;
}
__device__ __forceinline__ uint32_t mapa(uint32_t a, uint32_t r) { uint32_t o; asm("mapa.shared::cluster.u32 %0, %1, %2;" : "=r"(o) : "r"(a), "r"(r)); return o; }
__device__ __forceinline__ void fence_async_smem() { asm volatile("fence.proxy.async.shared::cta;" ::: "memory"); }
__device__ __forceinline__ void fence_async_global() { asm volatile("fence.proxy.async.global;" ::: "memory"); }
__device__ __forceinline__ void bar_sync(int id, int n) { asm volatile("bar.sync %0, %1;" ::"r"(id), "r"(n) : "memory"); }
__device__ __forceinline__ void bar_arrive(int id, int n) { asm volatile("bar.arrive %0, %1;" ::"r"(id), "r"(n) : "memory"); }
__device__ __forceinline__ void cluster_arrive() { asm volatile("barrier.cluster.arrive.relaxed.aligned;" ::: "memory"); }
__device__ __forceinline__ void cluster_wait() { asm volatile("barrier.cluster.wait.aligned;" ::: "memory"); }

__device__ __forceinline__ void ring_load(uint32_t dst, const CUtensorMap* tm, int c0, int c1, uint32_t bar) {
    asm volatile("{\n.reg .pred p;\nelect.sync _|p, 0xffffffff;\n"
                 "@p mbarrier.arrive.expect_tx.shared::cta.b64 _, [%2], 16384;\n"
                 "@p cp.async.bulk.tensor.2d.shared::cluster.global.mbarrier::complete_tx::bytes [%0], [%1, {%3, %4}], [%2];\n}"
                 ::"r"(dst), "l"(tm), "r"(bar), "r"(c0), "r"(c1) : "memory");
}
__device__ __forceinline__ void ring_load_both(uint32_t dst, const CUtensorMap* tm, int c1, uint32_t bar) {
    asm volatile("{\n.reg .pred p;\nelect.sync _|p, 0xffffffff;\n"
                 "@p cp.async.bulk.tensor.2d.shared::cluster.global.mbarrier::complete_tx::bytes.multicast::cluster [%0], [%1, {0, %3}], [%2], %4;\n}"
                 ::"r"(dst), "l"(tm), "r"(bar), "r"(c1), "h"((uint16_t)3) : "memory");
}
__device__ __forceinline__ void mbar_arrive_peer(uint32_t b) { asm volatile("mbarrier.arrive.relaxed.cluster.shared::cluster.b64 _, [%0];" ::"r"(b) : "memory"); }
__device__ __forceinline__ void tma3d(uint32_t dst, const CUtensorMap* tm, int c0, int c1, int c2, uint32_t bar) {
    asm volatile("cp.async.bulk.tensor.3d.shared::cluster.global.mbarrier::complete_tx::bytes [%0], [%1, {%3, %4, %5}], [%2];"
                 ::"r"(dst), "l"(tm), "r"(bar), "r"(c0), "r"(c1), "r"(c2) : "memory");
}
__device__ __forceinline__ void bulk_g2s(uint32_t dst, const void* src, uint32_t bytes, uint32_t bar) {
    asm volatile("cp.async.bulk.shared::cluster.global.mbarrier::complete_tx::bytes [%0], [%1], %2, [%3];" ::"r"(dst), "l"(src), "r"(bytes), "r"(bar) : "memory");
}
__device__ __forceinline__ void prefetch_l2(const void* src, uint32_t bytes) {
    asm volatile("cp.async.bulk.prefetch.L2.global [%0], %1;" ::"l"(src), "r"(bytes) : "memory");
}
__device__ __forceinline__ void peer_copy(uint32_t dst, uint32_t src, uint32_t bytes, uint32_t rbar) {
    asm volatile("{\n.reg .pred p;\nelect.sync _|p, 0xffffffff;\n"
                 "@p cp.async.bulk.shared::cluster.shared::cta.mbarrier::complete_tx::bytes [%0], [%1], %2, [%3];\n}"
                 ::"r"(dst), "r"(src), "r"(bytes), "r"(rbar) : "memory");
}
__device__ __forceinline__ void st_async4(uint32_t dst, uint32_t a, uint32_t b, uint32_t c, uint32_t d, uint32_t bar) {
    asm volatile("st.async.shared::cluster.mbarrier::complete_tx::bytes.v4.b32 [%0], {%1,%2,%3,%4}, [%5];" ::"r"(dst), "r"(a), "r"(b), "r"(c), "r"(d), "r"(bar) : "memory");
}
__device__ __forceinline__ void stsm4t(uint32_t a, uint32_t r0, uint32_t r1, uint32_t r2, uint32_t r3) {
    asm volatile("stmatrix.sync.aligned.m8n8.x4.trans.shared.b16 [%0], {%1,%2,%3,%4};" ::"r"(a), "r"(r0), "r"(r1), "r"(r2), "r"(r3) : "memory");
}
__device__ __forceinline__ void stsm4(uint32_t a, uint32_t r0, uint32_t r1, uint32_t r2, uint32_t r3) {
    asm volatile("stmatrix.sync.aligned.m8n8.x4.shared.b16 [%0], {%1,%2,%3,%4};" ::"r"(a), "r"(r0), "r"(r1), "r"(r2), "r"(r3) : "memory");
}
__device__ __forceinline__ void ldsm4t(uint32_t a, uint32_t& r0, uint32_t& r1, uint32_t& r2, uint32_t& r3) {
    asm volatile("ldmatrix.sync.aligned.m8n8.x4.trans.shared.b16 {%0,%1,%2,%3}, [%4];" : "=r"(r0), "=r"(r1), "=r"(r2), "=r"(r3) : "r"(a) : "memory");
}
__device__ __forceinline__ void ldsm4(uint32_t a, uint32_t& r0, uint32_t& r1, uint32_t& r2, uint32_t& r3) {
    asm volatile("ldmatrix.sync.aligned.m8n8.x4.shared.b16 {%0,%1,%2,%3}, [%4];" : "=r"(r0), "=r"(r1), "=r"(r2), "=r"(r3) : "r"(a) : "memory");
}
__device__ __forceinline__ uint4 lds128(uint32_t a) { uint4 v; asm volatile("ld.shared.v4.b32 {%0,%1,%2,%3}, [%4];" : "=r"(v.x), "=r"(v.y), "=r"(v.z), "=r"(v.w) : "r"(a) : "memory"); return v; }
__device__ __forceinline__ float4 lds128f(uint32_t a) { float4 v; asm volatile("ld.shared.v4.f32 {%0,%1,%2,%3}, [%4];" : "=f"(v.x), "=f"(v.y), "=f"(v.z), "=f"(v.w) : "r"(a) : "memory"); return v; }
__device__ __forceinline__ float2 lds64f(uint32_t a) { float2 v; asm volatile("ld.shared.v2.f32 {%0,%1}, [%2];" : "=f"(v.x), "=f"(v.y) : "r"(a) : "memory"); return v; }
__device__ __forceinline__ uint32_t lds32(uint32_t a) { uint32_t v; asm volatile("ld.shared.b32 %0, [%1];" : "=r"(v) : "r"(a) : "memory"); return v; }
__device__ __forceinline__ void sts128(uint32_t a, uint32_t x, uint32_t y, uint32_t z, uint32_t w) { asm volatile("st.shared.v4.b32 [%0], {%1,%2,%3,%4};" ::"r"(a), "r"(x), "r"(y), "r"(z), "r"(w) : "memory"); }
__device__ __forceinline__ void sts128f(uint32_t a, float x, float y, float z, float w) { asm volatile("st.shared.v4.f32 [%0], {%1,%2,%3,%4};" ::"r"(a), "f"(x), "f"(y), "f"(z), "f"(w) : "memory"); }
__device__ __forceinline__ void sts64f(uint32_t a, float x, float y) { asm volatile("st.shared.v2.f32 [%0], {%1,%2};" ::"r"(a), "f"(x), "f"(y) : "memory"); }
__device__ __forceinline__ void sts32(uint32_t a, uint32_t x) { asm volatile("st.shared.b32 [%0], %1;" ::"r"(a), "r"(x) : "memory"); }
__device__ __forceinline__ void stg128(void* p, uint4 v) { asm volatile("st.global.v4.b32 [%0], {%1,%2,%3,%4};" ::"l"(p), "r"(v.x), "r"(v.y), "r"(v.z), "r"(v.w) : "memory"); }

__device__ __forceinline__ uint32_t pack2(float lo, float hi) { uint32_t r; asm("cvt.rn.bf16x2.f32 %0, %1, %2;" : "=r"(r) : "f"(hi), "f"(lo)); return r; }
__device__ __forceinline__ float blo(uint32_t v) { return __uint_as_float(v << 16); }
__device__ __forceinline__ float bhi(uint32_t v) { return __uint_as_float(v & 0xffff0000u); }
__device__ __forceinline__ uint32_t hmul2(uint32_t a, uint32_t b) { uint32_t r; asm("mul.rn.bf16x2 %0, %1, %2;" : "=r"(r) : "r"(a), "r"(b)); return r; }
__device__ __forceinline__ uint32_t hfma2(uint32_t a, uint32_t b, uint32_t c) { uint32_t r; asm("fma.rn.bf16x2 %0, %1, %2, %3;" : "=r"(r) : "r"(a), "r"(b), "r"(c)); return r; }
__device__ __forceinline__ float tanh_fast(float x) { float r; asm("tanh.approx.f32 %0, %1;" : "=f"(r) : "f"(x)); return r; }
__device__ __forceinline__ float ex2(float x) { float r; asm("ex2.approx.ftz.f32 %0, %1;" : "=f"(r) : "f"(x)); return r; }

__device__ __forceinline__ void flag_wait(const uint32_t* p, uint32_t e) {
#pragma unroll 1
    for (int i = 0; i < (1 << 20); i++) {
        uint32_t v;
        asm volatile("ld.acquire.gpu.global.u32 %0, [%1];" : "=r"(v) : "l"(p) : "memory");
        if (v == e) break;
    }
}
__device__ __forceinline__ uint32_t ld_epoch() {
    uint32_t v;
    asm volatile("ld.relaxed.gpu.global.u32 %0, [%1];" : "=r"(v) : "l"(&g_epoch[blockIdx.x * FS]) : "memory");
    return v + 1;
}
__device__ __forceinline__ void flag_set(uint32_t* p, uint32_t e) { asm volatile("st.release.gpu.global.u32 [%0], %1;" ::"l"(p), "r"(e) : "memory"); }

__device__ __forceinline__ uint32_t desc_lo(uint32_t addr) { return ((addr & 0x3FFFF) >> 4) | 0x10000u; }
__device__ __forceinline__ uint64_t mkdesc(uint32_t lo) { return (uint64_t)lo | (0x40000040ull << 32); }
__device__ __forceinline__ void wg_fence() { asm volatile("wgmma.fence.sync.aligned;" ::: "memory"); }
__device__ __forceinline__ void wg_commit() { asm volatile("wgmma.commit_group.sync.aligned;" ::: "memory"); }
template <int N> __device__ __forceinline__ void wg_wait() { asm volatile("wgmma.wait_group.sync.aligned %0;" ::"n"(N) : "memory"); }
template <int N> __device__ __forceinline__ void pin(float (&d)[N]) {
#pragma unroll
    for (int i = 0; i < N; i++) asm volatile("" : "+f"(d[i])::"memory");
}
template <int N> __device__ __forceinline__ void pin(uint32_t (&d)[N]) {
#pragma unroll
    for (int i = 0; i < N; i++) asm volatile("" : "+r"(d[i])::"memory");
}

template <typename Tp, int N> __device__ __forceinline__ void zero(Tp (&d)[N]) {
#pragma unroll
    for (int i = 0; i < N; i++) d[i] = 0;
    pin(d);
}

#define F4(d, i) "+f"(d[i]), "+f"(d[i + 1]), "+f"(d[i + 2]), "+f"(d[i + 3])
#define F16(d, i) F4(d, i), F4(d, i + 4), F4(d, i + 8), F4(d, i + 12)

__device__ __forceinline__ void mma_t(float (&d)[16], uint64_t a, uint64_t b, int acc) {
    asm volatile("{.reg .pred p; setp.ne.b32 p, %18, 0;\n"
                 "wgmma.mma_async.sync.aligned.m64n32k16.f32.bf16.bf16 {%0,%1,%2,%3,%4,%5,%6,%7,%8,%9,%10,%11,%12,%13,%14,%15}, %16, %17, p, 1, 1, 1, 0;}\n"
                 : F16(d, 0) : "l"(a), "l"(b), "r"(acc));
}
__device__ __forceinline__ void mma_t(float (&d)[20], uint64_t a, uint64_t b, int acc) {
    asm volatile("{.reg .pred p; setp.ne.b32 p, %22, 0;\n"
                 "wgmma.mma_async.sync.aligned.m64n40k16.f32.bf16.bf16 {%0,%1,%2,%3,%4,%5,%6,%7,%8,%9,%10,%11,%12,%13,%14,%15,%16,%17,%18,%19}, %20, %21, p, 1, 1, 1, 0;}\n"
                 : F16(d, 0), F4(d, 16) : "l"(a), "l"(b), "r"(acc));
}
__device__ __forceinline__ void mma_t(float (&d)[24], uint64_t a, uint64_t b, int acc) {
    asm volatile("{.reg .pred p; setp.ne.b32 p, %26, 0;\n"
                 "wgmma.mma_async.sync.aligned.m64n48k16.f32.bf16.bf16 {%0,%1,%2,%3,%4,%5,%6,%7,%8,%9,%10,%11,%12,%13,%14,%15,%16,%17,%18,%19,%20,%21,%22,%23}, %24, %25, p, 1, 1, 1, 0;}\n"
                 : F16(d, 0), F4(d, 16), F4(d, 20) : "l"(a), "l"(b), "r"(acc));
}
__device__ __forceinline__ void mma_qk(float (&d)[32], uint32_t a0, uint32_t a1, uint32_t a2, uint32_t a3, uint64_t b, int acc) {
    asm volatile("{.reg .pred p; setp.ne.b32 p, %37, 0;\n"
                 "wgmma.mma_async.sync.aligned.m64n64k16.f32.bf16.bf16 {%0,%1,%2,%3,%4,%5,%6,%7,%8,%9,%10,%11,%12,%13,%14,%15,%16,%17,%18,%19,%20,%21,%22,%23,%24,%25,%26,%27,%28,%29,%30,%31}, "
                 "{%32,%33,%34,%35}, %36, p, 1, 1, 0;}\n"
                 : F16(d, 0), F16(d, 16) : "r"(a0), "r"(a1), "r"(a2), "r"(a3), "l"(b), "r"(acc));
}
__device__ __forceinline__ void mma_pv(float (&d)[36], uint32_t a0, uint32_t a1, uint32_t a2, uint32_t a3, uint64_t b) {
    asm volatile("wgmma.mma_async.sync.aligned.m64n72k16.f32.bf16.bf16 {%0,%1,%2,%3,%4,%5,%6,%7,%8,%9,%10,%11,%12,%13,%14,%15,%16,%17,%18,%19,%20,%21,%22,%23,%24,%25,%26,%27,%28,%29,%30,%31,%32,%33,%34,%35}, "
                 "{%36,%37,%38,%39}, %40, 1, 1, 1, 1;\n"
                 : F16(d, 0), F16(d, 16), F4(d, 32) : "r"(a0), "r"(a1), "r"(a2), "r"(a3), "l"(b));
}

template <uint32_t CSTRIDE, int N>
__device__ __forceinline__ void issue_half(float (&d)[N], uint32_t alo, uint32_t blo_, int acc) {
    const uint64_t a = mkdesc(alo), b = mkdesc(blo_);
    wg_fence();
#pragma unroll
    for (int k = 0; k < 8; k++) mma_t(d, a + k * 128, b + (k >> 2) * (CSTRIDE >> 4) + (k & 3) * 2, k == 0 ? acc : 1);
    wg_commit();
}

__device__ __forceinline__ uint32_t load_code(int n, int r, int w) {
    const int tile = 2 * r + w;
    int m, col, row;
    if (n < 16 || n >= 40) {
        const int k = n < 16 ? n : n - 40;
        m = n < 16 ? 1 : 7;
        if (k < 8) { col = 8 * r + (k & 6) + w; row = (k & 1) ^ r; }
        else {
            const int kk = k == 11 ? 12 : (k == 12 ? 11 : k);
            m++; col = kk < 12 ? (tile ^ 2) : tile; row = 4 * r + (kk & 3);
        }
    } else if (n < 32) {
        const int k = n - 16;
        m = 3;
        if (k < 4) { col = tile + ((k & 1) ? 8 : 4); row = (k >> 1) ^ r; }
        else { col = tile; row = (k & 1) ^ r; }
    } else if (n < 34) { m = 4; col = tile; row = n - 32; }
    else if (n < 38) { const int k = n - 34; m = 5; col = tile + 4 * (k & 1); row = (k >> 1) ^ r; }
    else { m = 6; col = tile; row = (n & 1) ^ r; }
    return m | (col << 4) | (row << 8);
}

__global__ void __cluster_dims__(2, 1, 1) __launch_bounds__(NTHREADS, 1)
conformer_kernel(const __grid_constant__ Params p) {
    extern __shared__ __align__(1024) unsigned char smem_raw[];
    const uint32_t sb = smem_u32(smem_raw);
    const uint32_t bars = sb + OFF_BARS;
    const int tid = threadIdx.x;
    const int lane = tid & 31;
    const int warp = __shfl_sync(~0u, tid >> 5, 0);
    const int r = blockIdx.x & 1;
    const int pair = blockIdx.x >> 1;
    const int b = pair >> 5, pt = pair & 31;
    const int ah = pt >> 3, qt = (pt & 7) * 2 + r;
    const int abh = b * 4 + ah;

    TG(30);
    TSINIT();
    TS(0);
    const uint32_t P = sb + OFF_P, H = sb + OFF_H;
    auto xwait = [&](int j) { mbar_wait(bars + (B_XR + (j & 1)) * 8, (j >> 1) & 1); };

    if (warp >= 8) {
        asm volatile("setmaxnreg.dec.sync.aligned.u32 48;");
        if (warp >= 12) {
            if (warp == 12 && lane >= 2 && lane < 10) asm volatile("prefetch.tensormap [%0];" ::"l"(&p.tm[lane]) : "memory");
            cluster_arrive();
            cluster_wait();
            const int ut = tid & 127;
            const uint32_t a4 = P + (ut >> 2) * 128 + (2 * (ut & 3) + ((ut >> 2) & 1)) * 16;
            const uint32_t a8 = P + (32 + (ut >> 3)) * 128 + (ut & 7) * 16;
#pragma unroll 1
            for (int k = 0; k < 4; k++) {
                float s = 0.f, q = 0.f, s2 = 0.f, q2 = 0.f;
#pragma unroll 1
                for (int h = 0; h < 2; h++) {
                    if (h == 0 && k != 0) bar_sync(1, 384);
                    else xwait(k == 3 ? 4 : k);
                    const uint32_t off = 2 * (r ^ h) * XCH;
                    uint4 v0 = lds128(a4 + off), v1 = lds128((a4 ^ 16) + off), v2 = lds128(a4 + off + XCH), v3 = lds128((a4 ^ 16) + off + XCH);
                    uint4 v4 = make_uint4(0, 0, 0, 0), v5 = v4;
                    if (k == 2) { v4 = lds128(a8 + off); v5 = lds128(a8 + off + XCH); }
                    if (h == 1 || k == 1 || k == 2) bar_arrive(5 + ((v3.w | v5.w) & p.zero), 384);
                    uint32_t t;
                    asm volatile("mov.u32 %0, %%clock;" : "=r"(t)::"memory");
                    const uint32_t mul = 65536u + (t & p.zero), msk = 0u - mul;
                    auto accum = [&](const uint4& v, float& s, float& q) {
                        const float a0 = __uint_as_float(v.x * mul), a1 = __uint_as_float(v.x & msk), a2 = __uint_as_float(v.y * mul), a3 = __uint_as_float(v.y & msk);
                        const float a4 = __uint_as_float(v.z * mul), a5 = __uint_as_float(v.z & msk), a6 = __uint_as_float(v.w * mul), a7 = __uint_as_float(v.w & msk);
                        s += ((a0 + a1) + (a2 + a3)) + ((a4 + a5) + (a6 + a7));
                        q += fmaf(a0, a0, fmaf(a1, a1, fmaf(a2, a2, a3 * a3))) + fmaf(a4, a4, fmaf(a5, a5, fmaf(a6, a6, a7 * a7)));
                    };
                    accum(v0, s, q); accum(v1, s, q); accum(v2, s, q); accum(v3, s, q);
                    if (k == 2) { accum(v4, s2, q2); accum(v5, s2, q2); }
                }
#pragma unroll
                for (int o = 1; o < 8; o <<= 1) {
                    if (o < 4) { s += __shfl_xor_sync(~0u, s, o); q += __shfl_xor_sync(~0u, q, o); }
                    if (k == 2) { s2 += __shfl_xor_sync(~0u, s2, o); q2 += __shfl_xor_sync(~0u, q2, o); }
                }
                const bool second = (ut & 7) == 1;
                if (second) { s = s2; q = q2; }
                const float mean = s * (1.f / 256.f);
                const int row = second ? 32 + (ut >> 3) : ut >> 2;
                const float alpha = k == 1 ? 1.f : ((k == 2 && (uint32_t)(pt * 32 - 8 + row) >= T_) ? 0.f : 0.5f);
                const float rstd = alpha * rsqrtf(fmaxf(fmaf(-mean, mean, q * (1.f / 256.f)), 0.f) + 1e-5f);
                if ((ut & 3) == 0 || second) sts64f(sb + OFF_STATS + row * 8, mean * rstd, rstd);
                __syncwarp();
                if (lane == 0) mbar_arrive(bars + B_ST * 8);
                TS(2 + k);
                if (k == 1 && warp == 12) {
                    const uint32_t epoch = ld_epoch();
                    bar_sync(11, 288);
                    if (lane < 2) flag_set(&g_flag_q[((b * 4 + 2 * r + lane) * 32 + pt) * FS], epoch);
                    __syncwarp();
                    TS(13);
                }
            }
        } else if (warp < 10) {
            const int w = warp - 8;
            const uint32_t ring = sb + OFF_RING + w * NSLOT * SLOT;
            const uint32_t full = bars + (B_FULL + w * NSLOT) * 8;
            if (lane == 0) {
#pragma unroll
                for (int i = 0; i < NSLOT; i++) mbar_init(full + i * 8, 1);
                asm volatile("fence.mbarrier_init.release.cluster;" ::: "memory");
                fence_async_smem();
            }
            __syncwarp();
            cluster_arrive();
            TS(1);
#pragma unroll
            for (int n = 0; n < NSLOT; n++)
                ring_load(ring + n * SLOT, &p.tm[1], 64 * (8 * r + (n & 6) + w), 128 * ((n & 1) ^ r), full + n * 8);
            TS(2);
            const uint32_t code = load_code(lane, r, w) | (load_code(lane + 32, r, w) << 16);
            cluster_wait();
            uint32_t s = 0, ph = 0;
            int n = NSLOT;
#pragma unroll 1
            for (int seg = 0; seg < 2; seg++) {
#pragma unroll 1
                for (; n < (seg == 0 ? 22 : NLOADS); n++) {
                    const uint32_t c = __shfl_sync(~0u, code, n) >> (n & 32 ? 16 : 0);
                    mbar_wait(full + (B_EMPTY - B_FULL) * 8 + s * 8, ph);
                    ring_load(ring + s * SLOT, &p.tm[c & 15], (c & 0xf0) * 4, (c & 0xff00) >> 1, full + s * 8);
                    if (++s == NSLOT) { s = 0; ph ^= 1; }
                }
                if (seg == 1) break;
                const uint32_t epoch = ld_epoch();
                const uint32_t rdy = bars + (B_RDY + 3 * w) * 8, prdy = mapa(rdy, r ^ 1);
                const int isv = r ^ w;
#pragma unroll 1
                for (; n < 32; n++) {
                    mbar_wait(full + (B_EMPTY - B_FULL) * 8 + s * 8, ph);
                    if (lane == 0) {
                        if (n < 24) mbar_arrive(full + s * 8);
                        else mbar_arrive_tx(full + s * 8, SLOT);
                    }
                    if (n == 28) {
                        if (lane == 0) mbar_arrive_peer(prdy);
                        mbar_wait(rdy, 0);
                        if (!isv) {
                            flag_wait(g_flag_kv + (abh * 32 + lane) * FS, epoch);
                            __syncwarp();
                            fence_async_global();
                            TSW(5);
                            ring_load_both(ring + 4 * SLOT, &p.tm[9], (abh * 8 + w) * 128, full + 32);
                        }
                        bar_sync(12, 64);
#pragma unroll
                        for (int i = 0; i < 2; i++) {
                            if (i == 0) mbar_wait(bars + B_QIN * 8, 0);
                            else mbar_wait(full + isv * 8, 1);
                            ring_load_both(ring + (2 * i + isv) * SLOT, &p.tm[9], (isv * 62 + abh * 8 + 2 * i + 2 + w) * 128, full + (2 * i + isv) * 8);
                        }
                    } else if (n > 28) {
                        const uint32_t bo = n == 31 ? 16 : 8;
                        if ((n > 29) == (isv == 1)) {
                            mbar_wait(rdy + bo, 0);
                            ring_load_both(ring + s * SLOT, &p.tm[9], (isv * 64 + abh * 8 + (n == 30 ? 4 : 6) + w) * 128, full + s * 8);
                        } else if (lane == 0) mbar_arrive_peer(prdy + bo);
                    }
                    __syncwarp();
                    if (++s == NSLOT) { s = 0; ph ^= 1; }
                }
            }
        } else if (warp == 10) {
            if (lane == 0) {
                mbar_init(bars + B_XR * 8, 1);
                asm volatile("fence.mbarrier_init.release.cluster;" ::: "memory");
                fence_async_smem();
            }
            __syncwarp();
            cluster_arrive();
            if (lane == 0) {
                mbar_arrive_tx(bars + B_XR * 8, 16384);
#pragma unroll
                for (int i = 0; i < 4; i++) tma3d(P + i * XCH, &p.tm[0], i * 64, pt * 32, b, bars + B_XR * 8);
            }
            __syncwarp();
            cluster_wait();
            const uint32_t epoch = ld_epoch();
            if (lane == 0) {
                mbar_arrive_tx(bars + B_QIN * 8, 8192);
                mbar_arrive_tx(bars + B_OIN * 8, 2 * XCH);
                mbar_arrive_tx(bars + B_OIN * 8 + 8, 2 * XCH);
            }
            if (lane < 2) flag_wait(&g_flag_q[(abh * 32 + 2 * qt + lane) * FS], epoch);
            __syncwarp();
            TSW(6);
            if (lane == 0) {
                fence_async_global();
                bulk_g2s(H + 24576, g_kvq + 2097152 + (size_t)(abh * 1024 + qt * 64) * 128, 8192, bars + B_QIN * 8);
            }
            if (lane < 2) {
                const int np = pt - 1 + 2 * lane;
                if (np >= 0 && np < 32) flag_wait(&g_flag_kv[((b * 4 + 2 * r) * 32 + np) * FS], epoch);
            }
            __syncwarp();
            if (lane == 0) mbar_arrive(bars + B_X1IN * 8);
            bar_sync(9, 64);
            if (lane < 8) {
                const int q = (pt >> 1) + (lane < 4 ? 0 : ((pt & 1) ? 1 : -1));
                if (q >= 0 && q < 16) flag_wait(&g_flag_o[((b * 16 + q) * 4 + (lane & 3)) * FS], epoch);
            }
            __syncwarp();
            TSW(10);
            if (lane == 0) {
                fence_async_global();
#pragma unroll
                for (int i = 0; i < 4; i++)
                    bulk_g2s(H + i * XCH, g_o + (size_t)((b * 4 + i) * PADROWS + pt * 32) * 128, XCH, bars + (B_OIN + (i >> 1)) * 8);
            }
            __syncwarp();
        } else {
            uint32_t kb = (lane < 2 || lane > 5) ? 4096 : (lane == 2 ? 3072 : (lane == 4 ? 2048 : 1024));
            size_t off = (size_t)blockIdx.x * kb;
            if (lane == 8) { kb = 8192; off = (size_t)min(b * T_ + pt * 32 + r * 16, 2 * T_ - 16) * 512; }
            const char* pf = p.w[min(lane, 8)] + off;
            if (lane == 0 || lane == 8) prefetch_l2(pf, kb);
            __syncwarp();
            cluster_arrive();
            cluster_wait();
            xwait(0);
            if (lane == 1 || lane == 2) prefetch_l2(pf, kb);
            mbar_wait(bars + B_HF * 8, 0);
            if (lane > 2 && lane < 8) prefetch_l2(pf, kb);
            const uint32_t epoch = ld_epoch();
            bar_sync(4, 288);
            if (lane < 2) flag_set(&g_flag_kv[((b * 4 + 2 * r + lane) * 32 + pt) * FS], epoch);
            __syncwarp();
            TSW(8);
            bar_sync(6, 288);
            bar_arrive(9, 64);
            if (lane == 0) {
                flag_set(&g_flag_o[((b * 16 + qt) * 4 + ah) * FS], epoch);
                g_epoch[blockIdx.x * FS] = epoch;
            }
            __syncwarp();
            TSW(9);
        }
        TSDUMP();
        return;
    }

    if (lane == 0) {
        mbar_init(bars + (B_EMPTY + warp) * 8, 4);
        mbar_init(bars + (B_HF + warp) * 8, warp < 4 ? 8 : 1);
        if (warp < 3) mbar_init(bars + (warp == 2 ? B_ST : B_EMPTY + 8 + warp) * 8, 4);
        else if (warp < 6) mbar_init(bars + (B_XR - 2 + warp) * 8, 1);
        if (warp < 6) mbar_init(bars + (B_RDY + warp) * 8, 1);
        asm volatile("fence.mbarrier_init.release.cluster;" ::: "memory");
    }
    sts128(P + (tid >> 6) * XCH + 4096 + (tid & 63) * 16, 0x3F803F80u, 0x3F803F80u, 0x3F803F80u, 0x3F803F80u);
    fence_async_smem();
    __syncwarp();
    cluster_arrive();
    asm volatile("setmaxnreg.inc.sync.aligned.u32 208;");
    const int w = warp >> 2, wq = warp & 3;
    const int tile = 2 * r + w;
    const int wt = tid & 127;
    const int c4 = lane & 3;
    const uint32_t rbase = sb + OFF_RING + w * NSLOT * SLOT, fbar = bars + (B_FULL + w * NSLOT) * 8;
    const uint32_t rdesc = desc_lo(rbase);
    auto acq = [&](int n) { mbar_wait(fbar + (n % NSLOT) * 8, (n / NSLOT) & 1); };
    auto rel = [&](int n) { if (lane == 0) mbar_arrive(fbar + (B_EMPTY - B_FULL + n % NSLOT) * 8); };
    const uint32_t pown = desc_lo(P + 2 * r * XCH), prem = desc_lo(P + 2 * (r ^ 1) * XCH), hdesc = desc_lo(H);
    const uint32_t toff = ((lane >> 4) * 8 + (lane & 7)) * 128 + (((2 * wq + ((lane >> 3) & 1)) ^ (lane & 7)) << 4);
    const uint32_t xa = P + tile * XCH + toff;
    auto publish = [&](int j, uint32_t src, uint32_t bytes, int nsync) {
        const uint32_t bar = bars + (B_XR + (j & 1)) * 8;
        fence_async_smem();
        bar_sync(2 + w, 128);
        if (wq == 0) peer_copy(mapa(src, r ^ 1), src, bytes, mapa(bar, r ^ 1));
        if (tid == 32) mbar_arrive_tx(bar, 2 * bytes);
        bar_sync(nsync == 384 ? 1 : 10, nsync);
    };
    auto gate = [&](int j) { xwait(j); bar_sync(5, 384); };
    auto load_stats = [&](auto& st, int parity) {
        mbar_wait(bars + B_ST * 8, parity);
#pragma unroll
        for (int j = 0; j < (int)(sizeof(st) / 16); j++) {
            const float4 v = lds128f(sb + OFF_STATS + (8 * j + 2 * c4) * 8);
            st[4 * j] = v.x; st[4 * j + 1] = v.y; st[4 * j + 2] = v.z; st[4 * j + 3] = v.w;
        }
    };
    bar_sync(10, 256);
    cluster_wait();
    uint32_t xr[8];
    xwait(0);
    ldsm4t(xa, xr[0], xr[1], xr[2], xr[3]);
    ldsm4t(xa + 2048, xr[4], xr[5], xr[6], xr[7]);
    acq(0); acq(1);

#pragma unroll 1
    for (int ffi = 0; ffi < 2; ffi++) {
        auto mm = [&](auto& d, int n, uint32_t bd, auto cs, int acc) {
            const uint32_t z = p.zero * (ffi + n + 1);
            issue_half<decltype(cs)::value>(d, rdesc + z + (n % NSLOT) * (SLOT >> 4), bd + z, acc);
        };
        constexpr std::integral_constant<uint32_t, XCH> cx{};
        constexpr std::integral_constant<uint32_t, HCH> ch{};
        {
            float st[16], a0[20], a1[20], rem[16], own[16];
            const uint32_t inb = bars + (B_INB + w) * 8, box = sb + OFF_INBOX + w * 4096 + wt * 16;
            const uint32_t hdst = H + w * HCH + toff;
            auto step = [&](auto& d, int n, uint32_t bd, auto cs, int acc) {
                mm(d, n, bd, cs, acc);
                wg_wait<1>();
                if (n > 0) rel(n - 1);
            };
            auto epi = [&](float (&d)[20], int i, int half) {
                uint32_t pk[4];
#pragma unroll
                for (int k = 4 * half; k < 4 * half + 4; k++) {
                    const float cs = d[16 + 2 * (k & 1)];
                    const float v0 = fmaf(-st[(k >> 1) * 4], cs, d[2 * k] * st[(k >> 1) * 4 + 1]);
                    const float v1 = fmaf(-st[(k >> 1) * 4 + 2], cs, d[2 * k + 1] * st[(k >> 1) * 4 + 3]);
                    pk[k & 3] = pack2(fmaf(v0, tanh_fast(v0), v0), fmaf(v1, tanh_fast(v1), v1));
                }
                stsm4t(hdst + 2 * i * HCH + half * 2048, pk[0], pk[1], pk[2], pk[3]);
            };
            auto hdone = [&](int i) {
                fence_async_smem();
                __syncwarp();
                if (lane == 0) mbar_arrive(bars + (B_HF + i) * 8);
            };
            auto hwait = [&](int i) { mbar_wait(bars + (B_HF + i) * 8, ffi); };
            TS(1 + ffi * 20);
            step(a0, 0, pown, cx, 0);
            if (wt == 0) mbar_arrive_tx(inb, 4096);
            acq(2);
            gate(ffi * 4);
            TS(32);
            step(a0, 1, prem, cx, 1);
            step(a1, 2, pown, cx, 0); acq(3); pin(a0); load_stats(st, ffi); TS(33); epi(a0, 0, 0);
            step(a1, 3, prem, cx, 1); acq(4); epi(a0, 0, 1); TS(34);
            step(a0, 4, pown, cx, 0); acq(5); pin(a1); epi(a1, 1, 0);
            step(a0, 5, prem, cx, 1); acq(6); epi(a1, 1, 1); TS(35);
            step(a1, 6, pown, cx, 0); acq(7); pin(a0); hdone(0); epi(a0, 2, 0);
            step(a1, 7, prem, cx, 1); acq(8); hwait(0); epi(a0, 2, 1); TS(36);
            step(rem, 8, hdesc, ch, 0); acq(9); pin(a1); hdone(1); epi(a1, 3, 0);
            step(rem, 9, hdesc + 2 * (HCH >> 4), ch, 1); acq(10); hwait(1); epi(a1, 3, 1);
            TS(2 + ffi * 20);
            step(rem, 10, hdesc + 4 * (HCH >> 4), ch, 1); acq(11); hdone(2);
            step(own, 11, hdesc, ch, 0); acq(12); hwait(2);
            step(rem, 12, hdesc + 6 * (HCH >> 4), ch, 1); acq(13);
            step(own, 13, hdesc + 2 * (HCH >> 4), ch, 1); acq(14);
            pin(rem);
            {
                const uint32_t dst = mapa(box, r ^ 1), bar = mapa(inb, r ^ 1);
                st_async4(dst, pack2(rem[0], rem[1]), pack2(rem[2], rem[3]), pack2(rem[4], rem[5]), pack2(rem[6], rem[7]), bar);
                st_async4(dst + 2048, pack2(rem[8], rem[9]), pack2(rem[10], rem[11]), pack2(rem[12], rem[13]), pack2(rem[14], rem[15]), bar);
            }
            step(own, 14, hdesc + 4 * (HCH >> 4), ch, 1); acq(15);
            step(own, 15, hdesc + 6 * (HCH >> 4), ch, 1);
            mbar_wait(inb, ffi);
            const uint4 u = lds128(box), v = lds128(box + 2048);
            const uint32_t pr[8] = {u.x, u.y, u.z, u.w, v.x, v.y, v.z, v.w};
            if (ffi == 0) { acq(16); acq(17); }
            wg_wait<0>();
            pin(own);
            TS(3 + ffi * 20);
#pragma unroll
            for (int i = 0; i < 8; i++)
                xr[i] = pack2(fmaf(0.5f, own[2 * i] + blo(pr[i]), blo(xr[i])), fmaf(0.5f, own[2 * i + 1] + bhi(pr[i]), bhi(xr[i])));
            stsm4t(xa, xr[0], xr[1], xr[2], xr[3]);
            stsm4t(xa + 2048, xr[4], xr[5], xr[6], xr[7]);
            rel(15);
            publish(ffi ? 5 : 1, P + tile * XCH + (ffi ? (r ^ 1) * 2048 : 0), ffi ? 2048 : 4096, ffi ? 256 : 384);
        }
        if (ffi == 1) break;

        {
            float ak[20], aq[20], st[16];
            g_halo[((pair * 4 + tile) * 2 + 0) * 128 + wt] = make_uint2(xr[0], xr[1]);
            g_halo[((pair * 4 + tile) * 2 + 1) * 128 + wt] = make_uint2(xr[6], xr[7]);
            bar_sync(5, 384);
            TS(11);
            mm(ak, 16, pown, cx, 0);
            mm(aq, 17, pown, cx, 0);
            acq(18); acq(19);
            gate(1);
            mm(ak, 18, prem, cx, 1);
            mm(aq, 19, prem, cx, 1);
            wg_wait<2>();
            rel(16); rel(17);
            load_stats(st, 1);
            auto stage_out = [&](float (&d)[20], uint32_t dst) {
                uint32_t pk[8];
#pragma unroll
                for (int k = 0; k < 8; k++) {
                    const float cs = d[16 + 2 * (k & 1)];
                    pk[k] = pack2(fmaf(-st[(k >> 1) * 4], cs, d[2 * k] * st[(k >> 1) * 4 + 1]),
                                  fmaf(-st[(k >> 1) * 4 + 2], cs, d[2 * k + 1] * st[(k >> 1) * 4 + 3]));
                }
                stsm4t(dst + toff, pk[0], pk[1], pk[2], pk[3]);
                stsm4t(dst + toff + 2048, pk[4], pk[5], pk[6], pk[7]);
            };
            const uint32_t stg = H + w * 12288;
            unsigned char* g = g_kvq + (size_t)((b * 4 + tile) * 1024 + pt * 32) * 128 + wt * 16;
            wg_wait<0>();
            pin(ak); pin(aq);
            TS(37);
            stage_out(ak, stg);
            stage_out(aq, stg + 4096);
            bar_sync(2 + w, 128);
            {
                const uint4 k0 = lds128(stg + wt * 16), k1 = lds128(stg + 2048 + wt * 16), q0 = lds128(stg + 4096 + wt * 16), q1 = lds128(stg + 6144 + wt * 16);
                stg128(g, k0); stg128(g + 2048, k1);
                stg128(g + 1048576, q0); stg128(g + 1048576 + 2048, q1);
            }
            bar_arrive(4, 288);
            TS(38);
            rel(18); rel(19);
            acq(20); acq(21);
            bar_sync(10, 256);
            mm(ak, 20, pown, cx, 0);
            mm(ak, 21, prem, cx, 1);
            wg_wait<0>();
            pin(ak);
            stage_out(ak, stg + 8192);
            rel(20); rel(21);
            bar_sync(2 + w, 128);
            {
                const uint4 v0 = lds128(stg + 8192 + wt * 16), v1 = lds128(stg + 10240 + wt * 16);
                stg128(g + 2097152, v0); stg128(g + 2097152 + 2048, v1);
            }
            bar_arrive(11, 288);
            acq(22); acq(23);
            rel(22); rel(23);
            TS(12);
        }

        {
            constexpr float CS = 0.125f * 1.4426950408889634f;
            float sa[32], sb2[32], o[36];
            uint32_t pa[16], pb[16], q[16];
            float n0 = INFINITY, n1 = INFINITY;
            zero(o); zero(pa); zero(pb);
            const uint32_t ones = sb + OFF_INBOX + 2048;
            if (tid < 128) sts128(ones + tid * 16, 0x3F803F80u, 0x3F803F80u, 0x3F803F80u, 0x3F803F80u);
            fence_async_smem();
            bar_sync(10, 256);
            const uint32_t vdesc = rdesc + ((((ones - rbase) >> 4) - 1) << 16);
            auto qk_issue = [&](float (&s)[32], uint32_t lo) {
                const uint64_t kd = mkdesc(lo);
                wg_fence();
#pragma unroll
                for (int k = 0; k < 4; k++) mma_qk(s, q[4 * k], q[4 * k + 1], q[4 * k + 2], q[4 * k + 3], kd + 2 * k, k != 0);
                wg_commit();
            };
            auto pv_issue = [&](uint32_t (&pp)[16], uint32_t lo) {
                const uint64_t vd = mkdesc(lo);
                wg_fence();
#pragma unroll
                for (int k = 0; k < 4; k++) mma_pv(o, pp[4 * k], pp[4 * k + 1], pp[4 * k + 2], pp[4 * k + 3], vd - k * (128 * 65535));
                wg_commit();
            };
            auto new_max = [&](float (&s)[32], float& x0, float& x1) {
                x0 = s[0]; x1 = s[2];
#pragma unroll
                for (int j = 0; j < 8; j++) {
                    x0 = fmaxf(x0, fmaxf(s[4 * j], s[4 * j + 1]));
                    x1 = fmaxf(x1, fmaxf(s[4 * j + 2], s[4 * j + 3]));
                }
                x0 = fmaxf(x0, __shfl_xor_sync(~0u, x0, 1)); x1 = fmaxf(x1, __shfl_xor_sync(~0u, x1, 1));
                x0 = fmaxf(x0, __shfl_xor_sync(~0u, x0, 2)); x1 = fmaxf(x1, __shfl_xor_sync(~0u, x1, 2));
                x0 = fminf(n0, fmaf(x0, -CS, -20.f)); x1 = fminf(n1, fmaf(x1, -CS, -20.f));
            };
            auto probs = [&](float (&s)[32], uint32_t (&pp)[16], bool ready, auto wait) {
                uint32_t any = 0;
#pragma unroll
                for (int i = 0; i < 16; i++) {
                    pp[i] = pack2(ex2(fmaf(s[2 * i], CS, (i & 1) ? n1 : n0)), ex2(fmaf(s[2 * i + 1], CS, (i & 1) ? n1 : n0)));
                    any |= pp[i];
                }
                float sc0 = 1.f, sc1 = 1.f;
                const bool slow = __any_sync(~0u, (any & 0x40004000u) || !ready);
                if (slow) {
                    wait();
                    if (__any_sync(~0u, any & 0x40004000u)) {
                        float x0, x1;
                        new_max(s, x0, x1);
                        sc0 = ex2(x0 - n0); sc1 = ex2(x1 - n1);
                        n0 = x0; n1 = x1;
#pragma unroll
                        for (int i = 0; i < 16; i++)
                            pp[i] = pack2(ex2(fmaf(s[2 * i], CS, (i & 1) ? n1 : n0)), ex2(fmaf(s[2 * i + 1], CS, (i & 1) ? n1 : n0)));
                    }
                }
                wg_wait<0>();
                pin(sa); pin(sb2); pin(o); pin(pa); pin(pb);
                if (slow) {
#pragma unroll
                    for (int j = 0; j < 9; j++) { o[4 * j] *= sc0; o[4 * j + 1] *= sc0; o[4 * j + 2] *= sc1; o[4 * j + 3] *= sc1; }
                }
            };
            mbar_wait(bars + B_QIN * 8, 0);
            {
                const uint32_t qa = H + 24576 + (wq * 16 + (lane & 15)) * 128;
#pragma unroll
                for (int k = 0; k < 4; k++) ldsm4(qa + (((2 * k + (lane >> 4)) ^ (lane & 7)) << 4), q[4 * k], q[4 * k + 1], q[4 * k + 2], q[4 * k + 3]);
                pin(q);
            }
            TS(40);
            acq(24);
            TS(13);
            qk_issue(sa, rdesc + (24 % NSLOT) * (SLOT >> 4));
            qk_issue(sb2, rdesc + (24 % NSLOT) * (SLOT >> 4) + 512);
            wg_wait<1>();
            pin(sa);
            {
                float x0, x1;
                new_max(sa, x0, x1);
                n0 = x0; n1 = x1;
            }
            if (w == 1) bar_sync(7, 256);
            uint32_t vd = vdesc - (SLOT >> 4) * 65535u, kd = rdesc, vb = fbar + 8, kb = fbar;
            uint32_t vlast = vdesc - 4 * (SLOT >> 4) * 65535u;
            uint32_t kprev = fbar + 32, vprev = bars + (B_HF + 3 - (B_EMPTY - B_FULL)) * 8;
#pragma unroll 1
            for (int it = 0; it < 4; it++) {
                pv_issue(pb, vlast);
                probs(sa, pa, mbar_test(vb, it < 2) & mbar_test(kb, it < 3), [&]() { mbar_wait(vb, it < 2); mbar_wait(kb, it < 3); });
                TS(41 + it * 4);
                if (it == 0 && w == 0) bar_arrive(7, 256);
                if (it == 3 && w == 1) {
#pragma unroll
                    for (int i = 20; i < 32; i++) sb2[i] = -INFINITY;
                }
                pin(sb2);
                if (it < 3) qk_issue(sa, kd);
                if (lane == 0) mbar_arrive(kprev + (B_EMPTY - B_FULL) * 8);
                if (lane == 0) mbar_arrive(vprev + (B_EMPTY - B_FULL) * 8);
                pv_issue(pa, vd);
                probs(sb2, pb, true, []() {});
                TS(43 + it * 4);
                if (it < 3) qk_issue(sb2, kd + 512);
                const int dv = it == 0 ? 2 : (it == 1 ? -3 : 1);
                kprev = kb; vprev = vb; vlast = vd - 512 * 65535u;
                vd -= dv * (SLOT >> 4) * 65535u; vb += dv * 8;
                kd += 2 * (SLOT >> 4); kb = it == 2 ? vb : kb + 16;
            }
            pv_issue(pb, vlast);
            const int row = wq * 16 + (lane >> 2);
            const uint32_t ml = sb + OFF_INBOX;
            wg_wait<0>();
            pin(o); pin(pb); pin(sa); pin(sb2);
            rel(31);
            const float l0 = o[32], l1 = o[34];
            if (c4 == 0) { sts64f(ml + w * 512 + row * 8, n0, l0); sts64f(ml + w * 512 + row * 8 + 64, n1, l1); }
            TS(14);
            float mine[16];
#pragma unroll
            for (int j = 0; j < 4; j++) {
                if (w == 0) sts128f(H + j * 2048 + wt * 16, o[16 + 4 * j], o[17 + 4 * j], o[18 + 4 * j], o[19 + 4 * j]);
                else sts128f(H + 8192 + j * 2048 + wt * 16, o[4 * j], o[4 * j + 1], o[4 * j + 2], o[4 * j + 3]);
            }
#pragma unroll
            for (int i = 0; i < 16; i++) mine[i] = w == 0 ? o[i] : o[16 + i];
            bar_sync(10, 256);
            const float2 u0 = lds64f(ml + (w ^ 1) * 512 + row * 8), u1 = lds64f(ml + (w ^ 1) * 512 + row * 8 + 64);
            const float x0 = fminf(n0, u0.x), x1 = fminf(n1, u1.x);
            float a0 = ex2(x0 - n0), b0 = ex2(x0 - u0.x), a1 = ex2(x1 - n1), b1 = ex2(x1 - u1.x);
            const float i0 = __fdividef(1.f, fmaf(a0, l0, b0 * u0.y)), i1 = __fdividef(1.f, fmaf(a1, l1, b1 * u1.y));
            a0 *= i0; b0 *= i0; a1 *= i1; b1 *= i1;
            uint32_t pk[8];
#pragma unroll
            for (int j = 0; j < 4; j++) {
                const float4 v = lds128f(H + (w ^ 1) * 8192 + j * 2048 + wt * 16);
                pk[2 * j] = pack2(fmaf(a0, mine[4 * j], b0 * v.x), fmaf(a0, mine[4 * j + 1], b0 * v.y));
                pk[2 * j + 1] = pack2(fmaf(a1, mine[4 * j + 2], b1 * v.z), fmaf(a1, mine[4 * j + 3], b1 * v.w));
            }
            const uint32_t og = H + 16384 + wq * 2048;
            {
                const uint32_t ra = og + (((lane >> 3) & 1) * 8 + (lane & 7)) * 128;
                stsm4(ra + (((4 * w + (lane >> 4)) ^ (lane & 7)) << 4), pk[0], pk[1], pk[2], pk[3]);
                stsm4(ra + (((4 * w + 2 + (lane >> 4)) ^ (lane & 7)) << 4), pk[4], pk[5], pk[6], pk[7]);
            }
            __syncwarp();
            {
                const uint32_t off = (lane >> 2) * 128 + (((4 * w + c4) ^ (lane >> 2)) << 4);
                const uint4 v0 = lds128(og + off), v1 = lds128(og + off + 1024);
                unsigned char* dst = g_o + (size_t)(abh * PADROWS + 8 + qt * 64 + wq * 16) * 128 + off;
                stg128(dst, v0); stg128(dst + 1024, v1);
            }
            bar_arrive(6, 288);
            TS(15);
        }

        uint32_t dwr[15];
        {
#pragma unroll
            for (int i = 0; i < 15; i++) dwr[i] = hmul2(__ldg(reinterpret_cast<const uint32_t*>(p.dw + i * 256 + tile * 64) + lane), 0x3F003F00u);
            float d[24];
            uint32_t xw[12];
            mbar_wait(bars + B_X1IN * 8, 0);
            uint2 hl = make_uint2(0, 0), hr = hl;
            if (pt > 0) hl = __ldcg(&g_halo[(((pair - 1) * 4 + tile) * 2 + 1) * 128 + wt]);
            if (pt < 31) hr = __ldcg(&g_halo[(((pair + 1) * 4 + tile) * 2 + 0) * 128 + wt]);
            xw[0] = hl.x; xw[1] = hl.y; xw[10] = hr.x; xw[11] = hr.y;
#pragma unroll
            for (int i = 0; i < 8; i++) xw[2 + i] = xr[i];
            pin(xw);
            pin(dwr);
            acq(32); acq(33); acq(34); acq(35);
            mbar_wait(bars + B_OIN * 8, 0);
            TS(16);
            mm(d, 32, hdesc, cx, 0);
            mbar_wait(bars + B_OIN * 8 + 8, 0);
            mm(d, 33, hdesc + 2 * (XCH >> 4), cx, 1);
            wg_wait<1>();
            rel(32);
            wg_wait<0>();
            pin(d);
#pragma unroll
            for (int i = 0; i < 12; i++) xw[i] = pack2(d[2 * i] + blo(xw[i]), d[2 * i + 1] + bhi(xw[i]));
            if (c4 == 0) { xw[0] = (xw[0] & 0xffff0000u) | 0x3F80u; xw[1] = (xw[1] & 0xffff0000u) | 0x3F80u; }
#pragma unroll
            for (int j = 0; j < 3; j++) stsm4t(xa + j * 2048, xw[4 * j], xw[4 * j + 1], xw[4 * j + 2], xw[4 * j + 3]);
#pragma unroll
            for (int i = 0; i < 8; i++) xr[i] = xw[2 + i];
            rel(33);
            publish(2, P + tile * XCH, XCH, 384);
            TS(17);
        }
        {
            float da[24], db[24], st[24];
            bar_sync(5, 384);
            mm(da, 34, pown, cx, 0);
            mm(db, 35, pown, cx, 0);
            acq(36); acq(37);
            gate(2);
            TS(39);
            mm(da, 36, prem, cx, 1);
            mm(db, 37, prem, cx, 1);
            wg_wait<2>();
            rel(34); rel(35);
            load_stats(st, 0);
            wg_wait<0>();
            pin(da); pin(db);
            rel(36); rel(37);
            TS(18);
            uint32_t pk[12];
#pragma unroll
            for (int hh = 0; hh < 2; hh++) {
                const float ca = __shfl_sync(~0u, da[2 * hh], lane & 28), cb = __shfl_sync(~0u, db[2 * hh], lane & 28);
#pragma unroll
                for (int j = 0; j < 6; j++) {
                    const float u0 = fmaf(-st[4 * j], ca, da[4 * j + 2 * hh] * st[4 * j + 1]);
                    const float u1 = fmaf(-st[4 * j + 2], ca, da[4 * j + 2 * hh + 1] * st[4 * j + 3]);
                    const float v0 = fmaf(-st[4 * j], cb, db[4 * j + 2 * hh] * st[4 * j + 1]);
                    const float v1 = fmaf(-st[4 * j + 2], cb, db[4 * j + 2 * hh + 1] * st[4 * j + 3]);
                    pk[2 * j + hh] = pack2(fmaf(u0, tanh_fast(v0), u0), fmaf(u1, tanh_fast(v1), u1));
                }
            }
            const uint32_t gs = H + 16384 + w * XCH;
#pragma unroll
            for (int j = 0; j < 3; j++) stsm4t(gs + toff + j * 2048, pk[4 * j], pk[4 * j + 1], pk[4 * j + 2], pk[4 * j + 3]);
            bar_sync(2 + w, 128);
            uint32_t ca[8], cb[8];
            const uint32_t grow = gs + 8 * wq * 128 + c4 * 4, srow = H + tile * HCH + 8 * wq * 128 + c4 * 4;
#pragma unroll
            for (int k = 0; k < 22; k++) {
                const uint32_t v = lds32(grow + (1 + k) * 128 + (((lane >> 2) ^ ((1 + k) & 7)) << 4));
#pragma unroll
                for (int i = 0; i < 8; i++) {
                    const int tap = k - i;
                    if (tap == 0) ca[i] = hmul2(v, dwr[0]);
                    else if (tap > 0 && tap < 8) ca[i] = hfma2(v, dwr[tap], ca[i]);
                    else if (tap == 8) cb[i] = hmul2(v, dwr[8]);
                    else if (tap > 8 && tap < 15) cb[i] = hfma2(v, dwr[tap], cb[i]);
                }
            }
#pragma unroll
            for (int i = 0; i < 8; i++) {
                const float h0 = blo(ca[i]) + blo(cb[i]), h1 = bhi(ca[i]) + bhi(cb[i]);
                sts32(srow + i * 128 + (((lane >> 2) ^ i) << 4), pack2(fmaf(h0, tanh_fast(h0), h0), fmaf(h1, tanh_fast(h1), h1)));
            }
            acq(38); acq(39);
            publish(3, H + tile * HCH, HCH, 256);
            TS(19);
        }
        {
            float d[16];
            mm(d, 38, hdesc + 2 * r * (HCH >> 4), ch, 0);
            acq(40); acq(41);
            xwait(3);
            sts128(P + (wt >> 6 ? (tile ^ 2) : tile) * XCH + 4096 + (wt & 63) * 16, 0x3F803F80u, 0x3F803F80u, 0x3F803F80u, 0x3F803F80u);
            mm(d, 39, hdesc + 2 * (r ^ 1) * (HCH >> 4), ch, 1);
            wg_wait<1>();
            rel(38);
            wg_wait<0>();
            pin(d);
#pragma unroll
            for (int i = 0; i < 8; i++) xr[i] = pack2(d[2 * i] + blo(xr[i]), d[2 * i + 1] + bhi(xr[i]));
            stsm4t(xa, xr[0], xr[1], xr[2], xr[3]);
            stsm4t(xa + 2048, xr[4], xr[5], xr[6], xr[7]);
            rel(39);
            publish(4, P + tile * XCH, HCH, 384);
            TS(20);
        }
    }

    xwait(5);
    cluster_arrive();
    TS(24);
    {
        float a[2][8], s[2], q[2];
        const int row0 = 16 * r + 2 * warp;
#pragma unroll
        for (int i = 0; i < 2; i++) {
            const uint4 v = lds128(P + (lane >> 3) * XCH + (row0 + i) * 128 + (((lane & 7) ^ ((row0 + i) & 7)) << 4));
            a[i][0] = blo(v.x); a[i][1] = bhi(v.x); a[i][2] = blo(v.y); a[i][3] = bhi(v.y);
            a[i][4] = blo(v.z); a[i][5] = bhi(v.z); a[i][6] = blo(v.w); a[i][7] = bhi(v.w);
            s[i] = ((a[i][0] + a[i][1]) + (a[i][2] + a[i][3])) + ((a[i][4] + a[i][5]) + (a[i][6] + a[i][7]));
            q[i] = 0.f;
#pragma unroll
            for (int k = 0; k < 8; k++) q[i] = fmaf(a[i][k], a[i][k], q[i]);
        }
#pragma unroll
        for (int o = 16; o > 0; o >>= 1) {
#pragma unroll
            for (int i = 0; i < 2; i++) { s[i] += __shfl_xor_sync(~0u, s[i], o); q[i] += __shfl_xor_sync(~0u, q[i], o); }
        }
#pragma unroll
        for (int i = 0; i < 2; i++) {
            const float mean = s[i] * (1.f / 256.f);
            const float rstd = rsqrtf(fmaxf(fmaf(-mean, mean, q[i] * (1.f / 256.f)), 0.f) + 1e-5f);
            const float nb = -mean * rstd;
            uint4 v;
            v.x = pack2(fmaf(a[i][0], rstd, nb), fmaf(a[i][1], rstd, nb)); v.y = pack2(fmaf(a[i][2], rstd, nb), fmaf(a[i][3], rstd, nb));
            v.z = pack2(fmaf(a[i][4], rstd, nb), fmaf(a[i][5], rstd, nb)); v.w = pack2(fmaf(a[i][6], rstd, nb), fmaf(a[i][7], rstd, nb));
            const int t = pt * 32 + row0 + i;
            if (t < T_) stg128(p.out + (size_t)(b * T_ + t) * 256 + lane * 8, v);
        }
    }
    TS(25);
    TG(31);
    TSDUMP();
    cluster_wait();
}

typedef CUresult (*EncodeFn)(CUtensorMap*, CUtensorMapDataType, cuuint32_t, void*, const cuuint64_t*, const cuuint64_t*,
                             const cuuint32_t*, const cuuint32_t*, CUtensorMapInterleave, CUtensorMapSwizzle,
                             CUtensorMapL2promotion, CUtensorMapFloatOOBfill);

}

extern "C" void kernel_launch(void* const* d_in, const int* in_sizes, int n_in, void* d_out, int out_size) {
    static EncodeFn encode = nullptr;
    if (!encode) {
        void* fn = nullptr;
        cudaDriverEntryPointQueryResult qr;
        cudaGetDriverEntryPoint("cuTensorMapEncodeTiled", &fn, cudaEnableDefault, &qr);
        encode = (EncodeFn)fn;
        cudaFuncSetAttribute(conformer_kernel, cudaFuncAttributeMaxDynamicSharedMemorySize, SMEM_LAUNCH);
    }
    Params p;
    const cuuint32_t ones[3] = {1, 1, 1};
    {
        const cuuint64_t dims[3] = {256, T_, 2};
        const cuuint64_t strides[2] = {512, 512ull * T_};
        const cuuint32_t box[3] = {64, 32, 1};
        encode(&p.tm[0], CU_TENSOR_MAP_DATA_TYPE_BFLOAT16, 3, d_in[0], dims, strides, box, ones, CU_TENSOR_MAP_INTERLEAVE_NONE,
               CU_TENSOR_MAP_SWIZZLE_128B, CU_TENSOR_MAP_L2_PROMOTION_L2_256B, CU_TENSOR_MAP_FLOAT_OOB_FILL_NONE);
    }
    const int idx[8] = {1, 2, 3, 4, 5, 7, 8, 9};
    const int rows[8] = {256, 1024, 256, 256, 256, 256, 256, 1024};
    const int cols[8] = {1024, 256, 768, 256, 512, 256, 1024, 256};
    for (int i = 0; i < 8; i++) {
        const cuuint64_t dims[2] = {(cuuint64_t)cols[i], (cuuint64_t)rows[i]};
        const cuuint64_t strides[1] = {(cuuint64_t)cols[i] * 2};
        const cuuint32_t box[2] = {64, 128};
        encode(&p.tm[1 + i], CU_TENSOR_MAP_DATA_TYPE_BFLOAT16, 2, d_in[idx[i]], dims, strides, box, ones, CU_TENSOR_MAP_INTERLEAVE_NONE,
               CU_TENSOR_MAP_SWIZZLE_128B, CU_TENSOR_MAP_L2_PROMOTION_L2_128B, CU_TENSOR_MAP_FLOAT_OOB_FILL_NONE);
        p.w[i] = (const char*)d_in[idx[i]];
    }
    {
        void* kv = nullptr;
        cudaGetSymbolAddress(&kv, g_kvq);
        const cuuint64_t dims[2] = {64, 16384};
        const cuuint64_t strides[1] = {128};
        const cuuint32_t box[2] = {64, 128};
        encode(&p.tm[9], CU_TENSOR_MAP_DATA_TYPE_BFLOAT16, 2, kv, dims, strides, box, ones, CU_TENSOR_MAP_INTERLEAVE_NONE,
               CU_TENSOR_MAP_SWIZZLE_NONE, CU_TENSOR_MAP_L2_PROMOTION_L2_128B, CU_TENSOR_MAP_FLOAT_OOB_FILL_NONE);
    }
    p.w[8] = (const char*)d_in[0];
    p.dw = (const __nv_bfloat16*)d_in[6];
    p.out = (__nv_bfloat16*)d_out;
    p.zero = 0;
    conformer_kernel<<<NCTA, NTHREADS, SMEM_LAUNCH>>>(p);
}
```

```cpp
#include <cuda_runtime.h>
#include <cuda_bf16.h>
#include <cuda.h>
#include <stdint.h>
#include <type_traits>

namespace {

constexpr int T_ = 1000;
constexpr int NCTA = 128;
constexpr int NTHREADS = 512;
constexpr int NSLOT = 5;
constexpr int SLOT = 16384;
constexpr int NLOADS = 56;

constexpr uint32_t OFF_RING = 0;
constexpr uint32_t OFF_P = 163840;
constexpr uint32_t OFF_H = 188416;
constexpr uint32_t OFF_INBOX = 221184;
constexpr uint32_t OFF_STATS = 229376;
constexpr uint32_t OFF_BARS = 229888;
constexpr uint32_t SMEM_BYTES = 230400;
constexpr uint32_t XCH = 6144;
constexpr uint32_t HCH = 4096;

constexpr int B_FULL = 0, B_EMPTY = 10, B_XR = 20, B_OIN = 22, B_HF = 24, B_INB = 28, B_QIN = 30, B_X1IN = 31, B_ST = 32, B_RDY = 33;

constexpr int PADROWS = 1040;
constexpr int FS = 8;

struct Params {
    CUtensorMap tm[10];
    const char* w[8];
    const __nv_bfloat16* dw;
    __nv_bfloat16* out;
    uint32_t zero;
};

__device__ __align__(1024) unsigned char g_kvq[3 * 8 * 1024 * 128];
__device__ __align__(1024) unsigned char g_o[8 * PADROWS * 128];
__device__ uint2 g_halo[64 * 4 * 2 * 128];
__device__ uint32_t g_flag_kv[8 * 32 * FS];
__device__ uint32_t g_flag_q[8 * 32 * FS];
__device__ uint32_t g_flag_o[2 * 16 * 4 * FS];
__device__ uint32_t g_epoch[NCTA * FS];

#define TS(i) do { } while (0)
#define TSW(i) do { } while (0)
#define TG(i) do { } while (0)
#define TSINIT() do { } while (0)
#define TSDUMP() do { } while (0)
constexpr uint32_t SMEM_LAUNCH = SMEM_BYTES;

__device__ __forceinline__ uint32_t smem_u32(const void* p) { return (uint32_t)__cvta_generic_to_shared(p); }
__device__ __forceinline__ void mbar_init(uint32_t b, uint32_t c) { asm volatile("mbarrier.init.shared::cta.b64 [%0], %1;" ::"r"(b), "r"(c) : "memory"); }
__device__ __forceinline__ void mbar_arrive(uint32_t b) { asm volatile("mbarrier.arrive.shared::cta.b64 _, [%0];" ::"r"(b) : "memory"); }
__device__ __forceinline__ void mbar_arrive_tx(uint32_t b, uint32_t tx) { asm volatile("mbarrier.arrive.expect_tx.shared::cta.b64 _, [%0], %1;" ::"r"(b), "r"(tx) : "memory"); }
__device__ __forceinline__ void mbar_wait(uint32_t b, uint32_t ph) {
    asm volatile("{\n.reg .pred p, q;\n.reg .u32 c;\nmov.u32 c, 0;\n"
                 "MW_LOOP:\n.pragma \"nounroll\";\n"
                 "mbarrier.try_wait.parity.shared::cta.b64 p, [%0], %1;\n"
                 "add.u32 c, c, 1;\nsetp.lt.u32 q, c, 65536;\nnot.pred p, p;\nand.pred p, p, q;\n@p bra MW_LOOP;\n}"
                 ::"r"(b), "r"(ph) : "memory");
}
__device__ __forceinline__ bool mbar_test(uint32_t b, uint32_t ph) {
    uint32_t ok;
    asm volatile("{\n.reg .pred p;\nmbarrier.test_wait.parity.shared::cta.b64 p, [%1], %2;\nselp.u32 %0, 1, 0, p;\n}" : "=r"(ok) : "r"(b), "r"(ph) : "memory");
    return ok;
}
__device__ __forceinline__ uint32_t mapa(uint32_t a, uint32_t r) { uint32_t o; asm("mapa.shared::cluster.u32 %0, %1, %2;" : "=r"(o) : "r"(a), "r"(r)); return o; }
__device__ __forceinline__ void fence_async_smem() { asm volatile("fence.proxy.async.shared::cta;" ::: "memory"); }
__device__ __forceinline__ void fence_async_global() { asm volatile("fence.proxy.async.global;" ::: "memory"); }
__device__ __forceinline__ void bar_sync(int id, int n) { asm volatile("bar.sync %0, %1;" ::"r"(id), "r"(n) : "memory"); }
__device__ __forceinline__ void bar_arrive(int id, int n) { asm volatile("bar.arrive %0, %1;" ::"r"(id), "r"(n) : "memory"); }
__device__ __forceinline__ void cluster_arrive() { asm volatile("barrier.cluster.arrive.relaxed.aligned;" ::: "memory"); }
__device__ __forceinline__ void cluster_wait() { asm volatile("barrier.cluster.wait.aligned;" ::: "memory"); }

__device__ __forceinline__ void ring_load(uint32_t dst, const CUtensorMap* tm, int c0, int c1, uint32_t bar) {
    asm volatile("{\n.reg .pred p;\nelect.sync _|p, 0xffffffff;\n"
                 "@p mbarrier.arrive.expect_tx.shared::cta.b64 _, [%2], 16384;\n"
                 "@p cp.async.bulk.tensor.2d.shared::cluster.global.mbarrier::complete_tx::bytes [%0], [%1, {%3, %4}], [%2];\n}"
                 ::"r"(dst), "l"(tm), "r"(bar), "r"(c0), "r"(c1) : "memory");
}
__device__ __forceinline__ void ring_load_both(uint32_t dst, const CUtensorMap* tm, int c1, uint32_t bar) {
    asm volatile("{\n.reg .pred p;\nelect.sync _|p, 0xffffffff;\n"
                 "@p cp.async.bulk.tensor.2d.shared::cluster.global.mbarrier::complete_tx::bytes.multicast::cluster [%0], [%1, {0, %3}], [%2], %4;\n}"
                 ::"r"(dst), "l"(tm), "r"(bar), "r"(c1), "h"((uint16_t)3) : "memory");
}
__device__ __forceinline__ void mbar_arrive_peer(uint32_t b) { asm volatile("mbarrier.arrive.relaxed.cluster.shared::cluster.b64 _, [%0];" ::"r"(b) : "memory"); }
__device__ __forceinline__ void tma3d(uint32_t dst, const CUtensorMap* tm, int c0, int c1, int c2, uint32_t bar) {
    asm volatile("{\n.reg .pred p;\nelect.sync _|p, 0xffffffff;\n"
                 "@p cp.async.bulk.tensor.3d.shared::cluster.global.mbarrier::complete_tx::bytes [%0], [%1, {%3, %4, %5}], [%2];\n}"
                 ::"r"(dst), "l"(tm), "r"(bar), "r"(c0), "r"(c1), "r"(c2) : "memory");
}
__device__ __forceinline__ void bulk_g2s(uint32_t dst, const void* src, uint32_t bytes, uint32_t bar) {
    asm volatile("cp.async.bulk.shared::cluster.global.mbarrier::complete_tx::bytes [%0], [%1], %2, [%3];" ::"r"(dst), "l"(src), "r"(bytes), "r"(bar) : "memory");
}
__device__ __forceinline__ void prefetch_l2(const void* src, uint32_t bytes) {
    asm volatile("cp.async.bulk.prefetch.L2.global [%0], %1;" ::"l"(src), "r"(bytes) : "memory");
}
__device__ __forceinline__ void peer_copy(uint32_t dst, uint32_t src, uint32_t bytes, uint32_t rbar) {
    asm volatile("{\n.reg .pred p;\nelect.sync _|p, 0xffffffff;\n"
                 "@p cp.async.bulk.shared::cluster.shared::cta.mbarrier::complete_tx::bytes [%0], [%1], %2, [%3];\n}"
                 ::"r"(dst), "r"(src), "r"(bytes), "r"(rbar) : "memory");
}
__device__ __forceinline__ void st_async4(uint32_t dst, uint32_t a, uint32_t b, uint32_t c, uint32_t d, uint32_t bar) {
    asm volatile("st.async.shared::cluster.mbarrier::complete_tx::bytes.v4.b32 [%0], {%1,%2,%3,%4}, [%5];" ::"r"(dst), "r"(a), "r"(b), "r"(c), "r"(d), "r"(bar) : "memory");
}
__device__ __forceinline__ void stsm4t(uint32_t a, uint32_t r0, uint32_t r1, uint32_t r2, uint32_t r3) {
    asm volatile("stmatrix.sync.aligned.m8n8.x4.trans.shared.b16 [%0], {%1,%2,%3,%4};" ::"r"(a), "r"(r0), "r"(r1), "r"(r2), "r"(r3) : "memory");
}
__device__ __forceinline__ void stsm4(uint32_t a, uint32_t r0, uint32_t r1, uint32_t r2, uint32_t r3) {
    asm volatile("stmatrix.sync.aligned.m8n8.x4.shared.b16 [%0], {%1,%2,%3,%4};" ::"r"(a), "r"(r0), "r"(r1), "r"(r2), "r"(r3) : "memory");
}
__device__ __forceinline__ void ldsm4t(uint32_t a, uint32_t& r0, uint32_t& r1, uint32_t& r2, uint32_t& r3) {
    asm volatile("ldmatrix.sync.aligned.m8n8.x4.trans.shared.b16 {%0,%1,%2,%3}, [%4];" : "=r"(r0), "=r"(r1), "=r"(r2), "=r"(r3) : "r"(a) : "memory");
}
__device__ __forceinline__ void ldsm4(uint32_t a, uint32_t& r0, uint32_t& r1, uint32_t& r2, uint32_t& r3) {
    asm volatile("ldmatrix.sync.aligned.m8n8.x4.shared.b16 {%0,%1,%2,%3}, [%4];" : "=r"(r0), "=r"(r1), "=r"(r2), "=r"(r3) : "r"(a) : "memory");
}
__device__ __forceinline__ uint4 lds128(uint32_t a) { uint4 v; asm volatile("ld.shared.v4.b32 {%0,%1,%2,%3}, [%4];" : "=r"(v.x), "=r"(v.y), "=r"(v.z), "=r"(v.w) : "r"(a) : "memory"); return v; }
__device__ __forceinline__ float4 lds128f(uint32_t a) { float4 v; asm volatile("ld.shared.v4.f32 {%0,%1,%2,%3}, [%4];" : "=f"(v.x), "=f"(v.y), "=f"(v.z), "=f"(v.w) : "r"(a) : "memory"); return v; }
__device__ __forceinline__ float2 lds64f(uint32_t a) { float2 v; asm volatile("ld.shared.v2.f32 {%0,%1}, [%2];" : "=f"(v.x), "=f"(v.y) : "r"(a) : "memory"); return v; }
__device__ __forceinline__ uint32_t lds32(uint32_t a) { uint32_t v; asm volatile("ld.shared.b32 %0, [%1];" : "=r"(v) : "r"(a) : "memory"); return v; }
__device__ __forceinline__ void sts128(uint32_t a, uint32_t x, uint32_t y, uint32_t z, uint32_t w) { asm volatile("st.shared.v4.b32 [%0], {%1,%2,%3,%4};" ::"r"(a), "r"(x), "r"(y), "r"(z), "r"(w) : "memory"); }
__device__ __forceinline__ void sts128f(uint32_t a, float x, float y, float z, float w) { asm volatile("st.shared.v4.f32 [%0], {%1,%2,%3,%4};" ::"r"(a), "f"(x), "f"(y), "f"(z), "f"(w) : "memory"); }
__device__ __forceinline__ void sts64f(uint32_t a, float x, float y) { asm volatile("st.shared.v2.f32 [%0], {%1,%2};" ::"r"(a), "f"(x), "f"(y) : "memory"); }
__device__ __forceinline__ void sts32(uint32_t a, uint32_t x) { asm volatile("st.shared.b32 [%0], %1;" ::"r"(a), "r"(x) : "memory"); }
__device__ __forceinline__ void stg128(void* p, uint4 v) { asm volatile("st.global.v4.b32 [%0], {%1,%2,%3,%4};" ::"l"(p), "r"(v.x), "r"(v.y), "r"(v.z), "r"(v.w) : "memory"); }

__device__ __forceinline__ uint32_t pack2(float lo, float hi) { uint32_t r; asm("cvt.rn.bf16x2.f32 %0, %1, %2;" : "=r"(r) : "f"(hi), "f"(lo)); return r; }
__device__ __forceinline__ float blo(uint32_t v) { return __uint_as_float(v << 16); }
__device__ __forceinline__ float bhi(uint32_t v) { return __uint_as_float(v & 0xffff0000u); }
__device__ __forceinline__ uint32_t hmul2(uint32_t a, uint32_t b) { uint32_t r; asm("mul.rn.bf16x2 %0, %1, %2;" : "=r"(r) : "r"(a), "r"(b)); return r; }
__device__ __forceinline__ uint32_t hfma2(uint32_t a, uint32_t b, uint32_t c) { uint32_t r; asm("fma.rn.bf16x2 %0, %1, %2, %3;" : "=r"(r) : "r"(a), "r"(b), "r"(c)); return r; }
__device__ __forceinline__ float tanh_fast(float x) { float r; asm("tanh.approx.f32 %0, %1;" : "=f"(r) : "f"(x)); return r; }
__device__ __forceinline__ float ex2(float x) { float r; asm("ex2.approx.ftz.f32 %0, %1;" : "=f"(r) : "f"(x)); return r; }

__device__ __forceinline__ void flag_wait(const uint32_t* p, uint32_t e) {
#pragma unroll 1
    for (int i = 0; i < (1 << 20); i++) {
        uint32_t v;
        asm volatile("ld.acquire.gpu.global.u32 %0, [%1];" : "=r"(v) : "l"(p) : "memory");
        if (v == e) break;
    }
}
__device__ __forceinline__ uint32_t ld_epoch() {
    uint32_t v;
    asm volatile("ld.relaxed.gpu.global.u32 %0, [%1];" : "=r"(v) : "l"(&g_epoch[blockIdx.x * FS]) : "memory");
    return v + 1;
}
__device__ __forceinline__ void flag_set(uint32_t* p, uint32_t e) { asm volatile("st.release.gpu.global.u32 [%0], %1;" ::"l"(p), "r"(e) : "memory"); }

__device__ __forceinline__ uint32_t desc_lo(uint32_t addr) { return ((addr & 0x3FFFF) >> 4) | 0x10000u; }
__device__ __forceinline__ uint64_t mkdesc(uint32_t lo) { return (uint64_t)lo | (0x40000040ull << 32); }
__device__ __forceinline__ void wg_fence() { asm volatile("wgmma.fence.sync.aligned;" ::: "memory"); }
__device__ __forceinline__ void wg_commit() { asm volatile("wgmma.commit_group.sync.aligned;" ::: "memory"); }
template <int N> __device__ __forceinline__ void wg_wait() { asm volatile("wgmma.wait_group.sync.aligned %0;" ::"n"(N) : "memory"); }
template <int N> __device__ __forceinline__ void pin(float (&d)[N]) {
#pragma unroll
    for (int i = 0; i < N; i++) asm volatile("" : "+f"(d[i])::"memory");
}
template <int N> __device__ __forceinline__ void pin(uint32_t (&d)[N]) {
#pragma unroll
    for (int i = 0; i < N; i++) asm volatile("" : "+r"(d[i])::"memory");
}

template <typename Tp, int N> __device__ __forceinline__ void zero(Tp (&d)[N]) {
#pragma unroll
    for (int i = 0; i < N; i++) d[i] = 0;
    pin(d);
}

#define F4(d, i) "+f"(d[i]), "+f"(d[i + 1]), "+f"(d[i + 2]), "+f"(d[i + 3])
#define F16(d, i) F4(d, i), F4(d, i + 4), F4(d, i + 8), F4(d, i + 12)

__device__ __forceinline__ void mma_t(float (&d)[16], uint64_t a, uint64_t b, int acc) {
    asm volatile("{.reg .pred p; setp.ne.b32 p, %18, 0;\n"
                 "wgmma.mma_async.sync.aligned.m64n32k16.f32.bf16.bf16 {%0,%1,%2,%3,%4,%5,%6,%7,%8,%9,%10,%11,%12,%13,%14,%15}, %16, %17, p, 1, 1, 1, 0;}\n"
                 : F16(d, 0) : "l"(a), "l"(b), "r"(acc));
}
__device__ __forceinline__ void mma_t(float (&d)[20], uint64_t a, uint64_t b, int acc) {
    asm volatile("{.reg .pred p; setp.ne.b32 p, %22, 0;\n"
                 "wgmma.mma_async.sync.aligned.m64n40k16.f32.bf16.bf16 {%0,%1,%2,%3,%4,%5,%6,%7,%8,%9,%10,%11,%12,%13,%14,%15,%16,%17,%18,%19}, %20, %21, p, 1, 1, 1, 0;}\n"
                 : F16(d, 0), F4(d, 16) : "l"(a), "l"(b), "r"(acc));
}
__device__ __forceinline__ void mma_t(float (&d)[24], uint64_t a, uint64_t b, int acc) {
    asm volatile("{.reg .pred p; setp.ne.b32 p, %26, 0;\n"
                 "wgmma.mma_async.sync.aligned.m64n48k16.f32.bf16.bf16 {%0,%1,%2,%3,%4,%5,%6,%7,%8,%9,%10,%11,%12,%13,%14,%15,%16,%17,%18,%19,%20,%21,%22,%23}, %24, %25, p, 1, 1, 1, 0;}\n"
                 : F16(d, 0), F4(d, 16), F4(d, 20) : "l"(a), "l"(b), "r"(acc));
}
__device__ __forceinline__ void mma_qk(float (&d)[32], uint32_t a0, uint32_t a1, uint32_t a2, uint32_t a3, uint64_t b, int acc) {
    asm volatile("{.reg .pred p; setp.ne.b32 p, %37, 0;\n"
                 "wgmma.mma_async.sync.aligned.m64n64k16.f32.bf16.bf16 {%0,%1,%2,%3,%4,%5,%6,%7,%8,%9,%10,%11,%12,%13,%14,%15,%16,%17,%18,%19,%20,%21,%22,%23,%24,%25,%26,%27,%28,%29,%30,%31}, "
                 "{%32,%33,%34,%35}, %36, p, 1, 1, 0;}\n"
                 : F16(d, 0), F16(d, 16) : "r"(a0), "r"(a1), "r"(a2), "r"(a3), "l"(b), "r"(acc));
}
__device__ __forceinline__ void mma_pv(float (&d)[36], uint32_t a0, uint32_t a1, uint32_t a2, uint32_t a3, uint64_t b) {
    asm volatile("wgmma.mma_async.sync.aligned.m64n72k16.f32.bf16.bf16 {%0,%1,%2,%3,%4,%5,%6,%7,%8,%9,%10,%11,%12,%13,%14,%15,%16,%17,%18,%19,%20,%21,%22,%23,%24,%25,%26,%27,%28,%29,%30,%31,%32,%33,%34,%35}, "
                 "{%36,%37,%38,%39}, %40, 1, 1, 1, 1;\n"
                 : F16(d, 0), F16(d, 16), F4(d, 32) : "r"(a0), "r"(a1), "r"(a2), "r"(a3), "l"(b));
}

template <uint32_t CSTRIDE, int N>
__device__ __forceinline__ void issue_half(float (&d)[N], uint32_t alo, uint32_t blo_, int acc) {
    const uint64_t a = mkdesc(alo), b = mkdesc(blo_);
    wg_fence();
#pragma unroll
    for (int k = 0; k < 8; k++) mma_t(d, a + k * 128, b + (k >> 2) * (CSTRIDE >> 4) + (k & 3) * 2, k == 0 ? acc : 1);
    wg_commit();
}

__device__ __forceinline__ uint32_t load_code(int n, int r, int w) {
    const int tile = 2 * r + w;
    int m, col, row;
    if (n < 16 || n >= 40) {
        const int k = n < 16 ? n : n - 40;
        m = n < 16 ? 1 : 7;
        if (k < 8) { col = 8 * r + (k & 6) + w; row = (k & 1) ^ r; }
        else {
            const int kk = k == 11 ? 12 : (k == 12 ? 11 : k);
            m++; col = kk < 12 ? (tile ^ 2) : tile; row = 4 * r + (kk & 3);
        }
    } else if (n < 32) {
        const int k = n - 16;
        m = 3;
        if (k < 4) { col = tile + ((k & 1) ? 8 : 4); row = (k >> 1) ^ r; }
        else { col = tile; row = (k & 1) ^ r; }
    } else if (n < 34) { m = 4; col = tile; row = n - 32; }
    else if (n < 38) { const int k = n - 34; m = 5; col = tile + 4 * (k & 1); row = (k >> 1) ^ r; }
    else { m = 6; col = tile; row = (n & 1) ^ r; }
    return m | (col << 4) | (row << 8);
}

__global__ void __cluster_dims__(2, 1, 1) __launch_bounds__(NTHREADS, 1)
conformer_kernel(const __grid_constant__ Params p) {
    extern __shared__ __align__(1024) unsigned char smem_raw[];
    const uint32_t sb = smem_u32(smem_raw);
    const uint32_t bars = sb + OFF_BARS;
    const int tid = threadIdx.x;
    const int lane = tid & 31;
    const int warp = __shfl_sync(~0u, tid >> 5, 0);
    const int r = blockIdx.x & 1;
    const int pair = blockIdx.x >> 1;
    const int b = pair >> 5, pt = pair & 31;
    const int ah = pt >> 3, qt = (pt & 7) * 2 + r;
    const int abh = b * 4 + ah;

    TG(30);
    TSINIT();
    TS(0);
    const uint32_t P = sb + OFF_P, H = sb + OFF_H;
    if (warp == 8) {
        if (lane == 0) {
            mbar_init(bars + B_XR * 8, 1);
            fence_async_smem();
            mbar_arrive_tx(bars + B_XR * 8, 16384);
        }
        __syncwarp();
#pragma unroll
        for (int i = 0; i < 4; i++) tma3d(P + i * XCH, &p.tm[0], i * 64, pt * 32, b, bars + B_XR * 8);
        TS(1);
        if (lane == 0) {
#pragma unroll
            for (int i = 0; i < 2 * NSLOT; i++) mbar_init(bars + (B_FULL + i) * 8, 1);
            asm volatile("fence.mbarrier_init.release.cluster;" ::: "memory");
            fence_async_smem();
        }
        __syncwarp();
        cluster_arrive();
#pragma unroll 1
        for (int n = 0; n < NSLOT; n++) {
#pragma unroll
            for (int w = 0; w < 2; w++)
                ring_load(sb + OFF_RING + (w * NSLOT + n) * SLOT, &p.tm[1], 64 * (8 * r + (n & 6) + w), 128 * ((n & 1) ^ r), bars + (B_FULL + w * NSLOT + n) * 8);
        }
        TS(2);
    } else if (warp == 9) {
        if (lane == 0) prefetch_l2(p.w[0] + blockIdx.x * 4096, 4096);
        __syncwarp();
        cluster_arrive();
    }
    auto xwait = [&](int j) { mbar_wait(bars + (B_XR + (j & 1)) * 8, (j >> 1) & 1); };

    if (warp >= 8) {
        asm volatile("setmaxnreg.dec.sync.aligned.u32 48;");
        if (warp >= 12) {
            if (warp == 12 && lane >= 1 && lane < 10) asm volatile("prefetch.tensormap [%0];" ::"l"(&p.tm[lane]) : "memory");
            cluster_arrive();
            cluster_wait();
            const int ut = tid & 127;
            const uint32_t a4 = P + (ut >> 2) * 128 + (2 * (ut & 3) + ((ut >> 2) & 1)) * 16;
            const uint32_t a8 = P + (32 + (ut >> 3)) * 128 + (ut & 7) * 16;
#pragma unroll 1
            for (int k = 0; k < 4; k++) {
                float s = 0.f, q = 0.f, s2 = 0.f, q2 = 0.f;
#pragma unroll 1
                for (int h = 0; h < 2; h++) {
                    if (h == 0 && k != 0) bar_sync(1, 384);
                    else xwait(k == 3 ? 4 : k);
                    const uint32_t off = 2 * (r ^ h) * XCH;
                    uint4 v0 = lds128(a4 + off), v1 = lds128((a4 ^ 16) + off), v2 = lds128(a4 + off + XCH), v3 = lds128((a4 ^ 16) + off + XCH);
                    uint4 v4 = make_uint4(0, 0, 0, 0), v5 = v4;
                    if (k == 2) { v4 = lds128(a8 + off); v5 = lds128(a8 + off + XCH); }
                    if (h == 1 || k == 1 || k == 2) bar_arrive(5 + ((v3.w | v5.w) & p.zero), 384);
                    uint32_t t;
                    asm volatile("mov.u32 %0, %%clock;" : "=r"(t)::"memory");
                    const uint32_t mul = 65536u + (t & p.zero), msk = 0u - mul;
                    auto accum = [&](const uint4& v, float& s, float& q) {
                        const float a0 = __uint_as_float(v.x * mul), a1 = __uint_as_float(v.x & msk), a2 = __uint_as_float(v.y * mul), a3 = __uint_as_float(v.y & msk);
                        const float a4 = __uint_as_float(v.z * mul), a5 = __uint_as_float(v.z & msk), a6 = __uint_as_float(v.w * mul), a7 = __uint_as_float(v.w & msk);
                        s += ((a0 + a1) + (a2 + a3)) + ((a4 + a5) + (a6 + a7));
                        q += fmaf(a0, a0, fmaf(a1, a1, fmaf(a2, a2, a3 * a3))) + fmaf(a4, a4, fmaf(a5, a5, fmaf(a6, a6, a7 * a7)));
                    };
                    accum(v0, s, q); accum(v1, s, q); accum(v2, s, q); accum(v3, s, q);
                    if (k == 2) { accum(v4, s2, q2); accum(v5, s2, q2); }
                }
#pragma unroll
                for (int o = 1; o < 8; o <<= 1) {
                    if (o < 4) { s += __shfl_xor_sync(~0u, s, o); q += __shfl_xor_sync(~0u, q, o); }
                    if (k == 2) { s2 += __shfl_xor_sync(~0u, s2, o); q2 += __shfl_xor_sync(~0u, q2, o); }
                }
                const bool second = (ut & 7) == 1;
                if (second) { s = s2; q = q2; }
                const float mean = s * (1.f / 256.f);
                const int row = second ? 32 + (ut >> 3) : ut >> 2;
                const float alpha = k == 1 ? 1.f : ((k == 2 && (uint32_t)(pt * 32 - 8 + row) >= T_) ? 0.f : 0.5f);
                const float rstd = alpha * rsqrtf(fmaxf(fmaf(-mean, mean, q * (1.f / 256.f)), 0.f) + 1e-5f);
                if ((ut & 3) == 0 || second) sts64f(sb + OFF_STATS + row * 8, mean * rstd, rstd);
                __syncwarp();
                if (lane == 0) mbar_arrive(bars + B_ST * 8);
                TS(2 + k);
                if (k == 1 && warp == 12) {
                    const uint32_t epoch = ld_epoch();
                    bar_sync(11, 288);
                    if (lane < 2) flag_set(&g_flag_q[((b * 4 + 2 * r + lane) * 32 + pt) * FS], epoch);
                    __syncwarp();
                    TS(13);
                }
            }
        } else if (warp < 10) {
            const int w = warp - 8;
            const uint32_t ring = sb + OFF_RING + w * NSLOT * SLOT;
            const uint32_t full = bars + (B_FULL + w * NSLOT) * 8;
            const uint32_t code = load_code(lane, r, w) | (load_code(lane + 32, r, w) << 16);
            cluster_wait();
            uint32_t s = 0, ph = 0;
            int n = NSLOT;
#pragma unroll 1
            for (int seg = 0; seg < 2; seg++) {
#pragma unroll 1
                for (; n < (seg == 0 ? 22 : NLOADS); n++) {
                    const uint32_t c = __shfl_sync(~0u, code, n) >> (n & 32 ? 16 : 0);
                    mbar_wait(full + (B_EMPTY - B_FULL) * 8 + s * 8, ph);
                    ring_load(ring + s * SLOT, &p.tm[c & 15], (c & 0xf0) * 4, (c & 0xff00) >> 1, full + s * 8);
                    if (++s == NSLOT) { s = 0; ph ^= 1; }
                }
                if (seg == 1) break;
                const uint32_t epoch = ld_epoch();
                const uint32_t rdy = bars + (B_RDY + 3 * w) * 8, prdy = mapa(rdy, r ^ 1);
                const int isv = r ^ w;
#pragma unroll 1
                for (; n < 32; n++) {
                    mbar_wait(full + (B_EMPTY - B_FULL) * 8 + s * 8, ph);
                    if (lane == 0) {
                        if (n < 24) mbar_arrive(full + s * 8);
                        else mbar_arrive_tx(full + s * 8, SLOT);
                    }
                    if (n == 28) {
                        if (lane == 0) mbar_arrive_peer(prdy);
                        mbar_wait(rdy, 0);
                        if (!isv) {
                            flag_wait(g_flag_kv + (abh * 32 + lane) * FS, epoch);
                            __syncwarp();
                            fence_async_global();
                            TSW(5);
                            ring_load_both(ring + 4 * SLOT, &p.tm[9], (abh * 8 + w) * 128, full + 32);
                        }
                        bar_sync(12, 64);
#pragma unroll
                        for (int i = 0; i < 2; i++) {
                            if (i == 0) mbar_wait(bars + B_QIN * 8, 0);
                            else mbar_wait(full + isv * 8, 1);
                            ring_load_both(ring + (2 * i + isv) * SLOT, &p.tm[9], (isv * 62 + abh * 8 + 2 * i + 2 + w) * 128, full + (2 * i + isv) * 8);
                        }
                    } else if (n > 28) {
                        const uint32_t bo = n == 31 ? 16 : 8;
                        if ((n > 29) == (isv == 1)) {
                            mbar_wait(rdy + bo, 0);
                            ring_load_both(ring + s * SLOT, &p.tm[9], (isv * 64 + abh * 8 + (n == 30 ? 4 : 6) + w) * 128, full + s * 8);
                        } else if (lane == 0) mbar_arrive_peer(prdy + bo);
                    }
                    __syncwarp();
                    if (++s == NSLOT) { s = 0; ph ^= 1; }
                }
            }
        } else if (warp == 10) {
            cluster_arrive();
            cluster_wait();
            const uint32_t epoch = ld_epoch();
            if (lane == 0) {
                mbar_arrive_tx(bars + B_QIN * 8, 8192);
                mbar_arrive_tx(bars + B_OIN * 8, 2 * XCH);
                mbar_arrive_tx(bars + B_OIN * 8 + 8, 2 * XCH);
            }
            if (lane < 2) flag_wait(&g_flag_q[(abh * 32 + 2 * qt + lane) * FS], epoch);
            __syncwarp();
            TSW(6);
            if (lane == 0) {
                fence_async_global();
                bulk_g2s(H + 24576, g_kvq + 2097152 + (size_t)(abh * 1024 + qt * 64) * 128, 8192, bars + B_QIN * 8);
            }
            if (lane < 2) {
                const int np = pt - 1 + 2 * lane;
                if (np >= 0 && np < 32) flag_wait(&g_flag_kv[((b * 4 + 2 * r) * 32 + np) * FS], epoch);
            }
            __syncwarp();
            if (lane == 0) mbar_arrive(bars + B_X1IN * 8);
            bar_sync(9, 64);
            if (lane < 8) {
                const int q = (pt >> 1) + (lane < 4 ? 0 : ((pt & 1) ? 1 : -1));
                if (q >= 0 && q < 16) flag_wait(&g_flag_o[((b * 16 + q) * 4 + (lane & 3)) * FS], epoch);
            }
            __syncwarp();
            TSW(10);
            if (lane == 0) {
                fence_async_global();
#pragma unroll
                for (int i = 0; i < 4; i++)
                    bulk_g2s(H + i * XCH, g_o + (size_t)((b * 4 + i) * PADROWS + pt * 32) * 128, XCH, bars + (B_OIN + (i >> 1)) * 8);
            }
            __syncwarp();
        } else {
            const uint32_t kb = (lane < 2 || lane > 5) ? 4096 : (lane == 2 ? 3072 : (lane == 4 ? 2048 : 1024));
            const char* pf = p.w[lane & 7] + blockIdx.x * kb;
            cluster_arrive();
            cluster_wait();
            xwait(0);
            if (lane == 1 || lane == 2) prefetch_l2(pf, kb);
            mbar_wait(bars + B_HF * 8, 0);
            if (lane > 2 && lane < 8) prefetch_l2(pf, kb);
            const uint32_t epoch = ld_epoch();
            bar_sync(4, 288);
            if (lane < 2) flag_set(&g_flag_kv[((b * 4 + 2 * r + lane) * 32 + pt) * FS], epoch);
            __syncwarp();
            TSW(8);
            bar_sync(6, 288);
            bar_arrive(9, 64);
            if (lane == 0) {
                flag_set(&g_flag_o[((b * 16 + qt) * 4 + ah) * FS], epoch);
                g_epoch[blockIdx.x * FS] = epoch;
            }
            __syncwarp();
            TSW(9);
        }
        TSDUMP();
        return;
    }

    if (lane == 0) {
        mbar_init(bars + (B_EMPTY + warp) * 8, 4);
        mbar_init(bars + (B_HF + warp) * 8, warp < 4 ? 8 : 1);
        if (warp < 3) mbar_init(bars + (warp == 2 ? B_ST : B_EMPTY + 8 + warp) * 8, 4);
        else if (warp < 6) mbar_init(bars + (B_XR - 2 + warp) * 8, 1);
        if (warp < 6) mbar_init(bars + (B_RDY + warp) * 8, 1);
        asm volatile("fence.mbarrier_init.release.cluster;" ::: "memory");
    }
    sts128(P + (tid >> 6) * XCH + 4096 + (tid & 63) * 16, 0x3F803F80u, 0x3F803F80u, 0x3F803F80u, 0x3F803F80u);
    fence_async_smem();
    __syncwarp();
    cluster_arrive();
    asm volatile("setmaxnreg.inc.sync.aligned.u32 208;");
    const int w = warp >> 2, wq = warp & 3;
    const int tile = 2 * r + w;
    const int wt = tid & 127;
    const int c4 = lane & 3;
    const uint32_t rbase = sb + OFF_RING + w * NSLOT * SLOT, fbar = bars + (B_FULL + w * NSLOT) * 8;
    const uint32_t rdesc = desc_lo(rbase);
    auto acq = [&](int n) { mbar_wait(fbar + (n % NSLOT) * 8, (n / NSLOT) & 1); };
    auto rel = [&](int n) { if (lane == 0) mbar_arrive(fbar + (B_EMPTY - B_FULL + n % NSLOT) * 8); };
    const uint32_t pown = desc_lo(P + 2 * r * XCH), prem = desc_lo(P + 2 * (r ^ 1) * XCH), hdesc = desc_lo(H);
    const uint32_t toff = ((lane >> 4) * 8 + (lane & 7)) * 128 + (((2 * wq + ((lane >> 3) & 1)) ^ (lane & 7)) << 4);
    const uint32_t xa = P + tile * XCH + toff;
    auto publish = [&](int j, uint32_t src, uint32_t bytes, int nsync) {
        const uint32_t bar = bars + (B_XR + (j & 1)) * 8;
        fence_async_smem();
        bar_sync(2 + w, 128);
        if (wq == 0) peer_copy(mapa(src, r ^ 1), src, bytes, mapa(bar, r ^ 1));
        if (tid == 32) mbar_arrive_tx(bar, 2 * bytes);
        bar_sync(nsync == 384 ? 1 : 10, nsync);
    };
    auto gate = [&](int j) { xwait(j); bar_sync(5, 384); };
    auto load_stats = [&](auto& st, int parity) {
        mbar_wait(bars + B_ST * 8, parity);
#pragma unroll
        for (int j = 0; j < (int)(sizeof(st) / 16); j++) {
            const float4 v = lds128f(sb + OFF_STATS + (8 * j + 2 * c4) * 8);
            st[4 * j] = v.x; st[4 * j + 1] = v.y; st[4 * j + 2] = v.z; st[4 * j + 3] = v.w;
        }
    };
    bar_sync(10, 256);
    cluster_wait();
    uint32_t xr[8];
    TS(56);
    xwait(0);
    TS(57);
    ldsm4t(xa, xr[0], xr[1], xr[2], xr[3]);
    ldsm4t(xa + 2048, xr[4], xr[5], xr[6], xr[7]);
    acq(0);
    TS(58);
    acq(1);

#pragma unroll 1
    for (int ffi = 0; ffi < 2; ffi++) {
        auto mm = [&](auto& d, int n, uint32_t bd, auto cs, int acc) {
            const uint32_t z = p.zero * (ffi + n + 1);
            issue_half<decltype(cs)::value>(d, rdesc + z + (n % NSLOT) * (SLOT >> 4), bd + z, acc);
        };
        constexpr std::integral_constant<uint32_t, XCH> cx{};
        constexpr std::integral_constant<uint32_t, HCH> ch{};
        {
            float st[16], a0[20], a1[20], rem[16], own[16];
            const uint32_t inb = bars + (B_INB + w) * 8, box = sb + OFF_INBOX + w * 4096 + wt * 16;
            const uint32_t hdst = H + w * HCH + toff;
            auto step = [&](auto& d, int n, uint32_t bd, auto cs, int acc) {
                mm(d, n, bd, cs, acc);
                wg_wait<1>();
                if (n > 0) rel(n - 1);
            };
            auto epi = [&](float (&d)[20], int i, int half) {
                uint32_t pk[4];
#pragma unroll
                for (int k = 4 * half; k < 4 * half + 4; k++) {
                    const float cs = d[16 + 2 * (k & 1)];
                    const float v0 = fmaf(-st[(k >> 1) * 4], cs, d[2 * k] * st[(k >> 1) * 4 + 1]);
                    const float v1 = fmaf(-st[(k >> 1) * 4 + 2], cs, d[2 * k + 1] * st[(k >> 1) * 4 + 3]);
                    pk[k & 3] = pack2(fmaf(v0, tanh_fast(v0), v0), fmaf(v1, tanh_fast(v1), v1));
                }
                stsm4t(hdst + 2 * i * HCH + half * 2048, pk[0], pk[1], pk[2], pk[3]);
            };
            auto hdone = [&](int i) {
                fence_async_smem();
                __syncwarp();
                if (lane == 0) mbar_arrive(bars + (B_HF + i) * 8);
            };
            auto hwait = [&](int i) { mbar_wait(bars + (B_HF + i) * 8, ffi); };
            TS(1 + ffi * 20);
            step(a0, 0, pown, cx, 0);
            if (wt == 0) mbar_arrive_tx(inb, 4096);
            acq(2);
            gate(ffi * 4);
            TS(32);
            step(a0, 1, prem, cx, 1);
            step(a1, 2, pown, cx, 0); acq(3); pin(a0); load_stats(st, ffi); TS(33); epi(a0, 0, 0);
            step(a1, 3, prem, cx, 1); acq(4); epi(a0, 0, 1); TS(34);
            step(a0, 4, pown, cx, 0); acq(5); pin(a1); epi(a1, 1, 0);
            step(a0, 5, prem, cx, 1); acq(6); epi(a1, 1, 1); TS(35);
            step(a1, 6, pown, cx, 0); acq(7); pin(a0); hdone(0); epi(a0, 2, 0);
            step(a1, 7, prem, cx, 1); acq(8); hwait(0); epi(a0, 2, 1); TS(36);
            step(rem, 8, hdesc, ch, 0); acq(9); pin(a1); hdone(1); epi(a1, 3, 0);
            step(rem, 9, hdesc + 2 * (HCH >> 4), ch, 1); acq(10); hwait(1); epi(a1, 3, 1);
            TS(2 + ffi * 20);
            step(rem, 10, hdesc + 4 * (HCH >> 4), ch, 1); acq(11); hdone(2);
            step(own, 11, hdesc, ch, 0); acq(12); hwait(2);
            step(rem, 12, hdesc + 6 * (HCH >> 4), ch, 1); acq(13);
            step(own, 13, hdesc + 2 * (HCH >> 4), ch, 1); acq(14);
            pin(rem);
            {
                const uint32_t dst = mapa(box, r ^ 1), bar = mapa(inb, r ^ 1);
                st_async4(dst, pack2(rem[0], rem[1]), pack2(rem[2], rem[3]), pack2(rem[4], rem[5]), pack2(rem[6], rem[7]), bar);
                st_async4(dst + 2048, pack2(rem[8], rem[9]), pack2(rem[10], rem[11]), pack2(rem[12], rem[13]), pack2(rem[14], rem[15]), bar);
            }
            step(own, 14, hdesc + 4 * (HCH >> 4), ch, 1); acq(15);
            step(own, 15, hdesc + 6 * (HCH >> 4), ch, 1);
            mbar_wait(inb, ffi);
            const uint4 u = lds128(box), v = lds128(box + 2048);
            const uint32_t pr[8] = {u.x, u.y, u.z, u.w, v.x, v.y, v.z, v.w};
            if (ffi == 0) { acq(16); acq(17); }
            wg_wait<0>();
            pin(own);
            TS(3 + ffi * 20);
#pragma unroll
            for (int i = 0; i < 8; i++)
                xr[i] = pack2(fmaf(0.5f, own[2 * i] + blo(pr[i]), blo(xr[i])), fmaf(0.5f, own[2 * i + 1] + bhi(pr[i]), bhi(xr[i])));
            stsm4t(xa, xr[0], xr[1], xr[2], xr[3]);
            stsm4t(xa + 2048, xr[4], xr[5], xr[6], xr[7]);
            rel(15);
            publish(ffi ? 5 : 1, P + tile * XCH + (ffi ? (r ^ 1) * 2048 : 0), ffi ? 2048 : 4096, ffi ? 256 : 384);
        }
        if (ffi == 1) break;

        {
            float ak[20], aq[20], st[16];
            g_halo[((pair * 4 + tile) * 2 + 0) * 128 + wt] = make_uint2(xr[0], xr[1]);
            g_halo[((pair * 4 + tile) * 2 + 1) * 128 + wt] = make_uint2(xr[6], xr[7]);
            bar_sync(5, 384);
            TS(11);
            mm(ak, 16, pown, cx, 0);
            mm(aq, 17, pown, cx, 0);
            acq(18); acq(19);
            gate(1);
            mm(ak, 18, prem, cx, 1);
            mm(aq, 19, prem, cx, 1);
            wg_wait<2>();
            rel(16); rel(17);
            load_stats(st, 1);
            auto stage_out = [&](float (&d)[20], uint32_t dst) {
                uint32_t pk[8];
#pragma unroll
                for (int k = 0; k < 8; k++) {
                    const float cs = d[16 + 2 * (k & 1)];
                    pk[k] = pack2(fmaf(-st[(k >> 1) * 4], cs, d[2 * k] * st[(k >> 1) * 4 + 1]),
                                  fmaf(-st[(k >> 1) * 4 + 2], cs, d[2 * k + 1] * st[(k >> 1) * 4 + 3]));
                }
                stsm4t(dst + toff, pk[0], pk[1], pk[2], pk[3]);
                stsm4t(dst + toff + 2048, pk[4], pk[5], pk[6], pk[7]);
            };
            const uint32_t stg = H + w * 12288;
            unsigned char* g = g_kvq + (size_t)((b * 4 + tile) * 1024 + pt * 32) * 128 + wt * 16;
            wg_wait<0>();
            pin(ak); pin(aq);
            TS(37);
            stage_out(ak, stg);
            stage_out(aq, stg + 4096);
            bar_sync(2 + w, 128);
            {
                const uint4 k0 = lds128(stg + wt * 16), k1 = lds128(stg + 2048 + wt * 16), q0 = lds128(stg + 4096 + wt * 16), q1 = lds128(stg + 6144 + wt * 16);
                stg128(g, k0); stg128(g + 2048, k1);
                stg128(g + 1048576, q0); stg128(g + 1048576 + 2048, q1);
            }
            bar_arrive(4, 288);
            TS(38);
            rel(18); rel(19);
            acq(20); acq(21);
            bar_sync(10, 256);
            mm(ak, 20, pown, cx, 0);
            mm(ak, 21, prem, cx, 1);
            wg_wait<0>();
            pin(ak);
            stage_out(ak, stg + 8192);
            rel(20); rel(21);
            bar_sync(2 + w, 128);
            {
                const uint4 v0 = lds128(stg + 8192 + wt * 16), v1 = lds128(stg + 10240 + wt * 16);
                stg128(g + 2097152, v0); stg128(g + 2097152 + 2048, v1);
            }
            bar_arrive(11, 288);
            acq(22); acq(23);
            rel(22); rel(23);
            TS(12);
        }

        {
            constexpr float CS = 0.125f * 1.4426950408889634f;
            float sa[32], sb2[32], o[36];
            uint32_t pa[16], pb[16], q[16];
            float n0 = INFINITY, n1 = INFINITY;
            zero(o); zero(pa); zero(pb);
            const uint32_t ones = sb + OFF_INBOX + 2048;
            if (tid < 128) sts128(ones + tid * 16, 0x3F803F80u, 0x3F803F80u, 0x3F803F80u, 0x3F803F80u);
            fence_async_smem();
            bar_sync(10, 256);
            const uint32_t vdesc = rdesc + ((((ones - rbase) >> 4) - 1) << 16);
            auto qk_issue = [&](float (&s)[32], uint32_t lo) {
                const uint64_t kd = mkdesc(lo);
                wg_fence();
#pragma unroll
                for (int k = 0; k < 4; k++) mma_qk(s, q[4 * k], q[4 * k + 1], q[4 * k + 2], q[4 * k + 3], kd + 2 * k, k != 0);
                wg_commit();
            };
            auto pv_issue = [&](uint32_t (&pp)[16], uint32_t lo) {
                const uint64_t vd = mkdesc(lo);
                wg_fence();
#pragma unroll
                for (int k = 0; k < 4; k++) mma_pv(o, pp[4 * k], pp[4 * k + 1], pp[4 * k + 2], pp[4 * k + 3], vd - k * (128 * 65535));
                wg_commit();
            };
            auto new_max = [&](float (&s)[32], float& x0, float& x1) {
                x0 = s[0]; x1 = s[2];
#pragma unroll
                for (int j = 0; j < 8; j++) {
                    x0 = fmaxf(x0, fmaxf(s[4 * j], s[4 * j + 1]));
                    x1 = fmaxf(x1, fmaxf(s[4 * j + 2], s[4 * j + 3]));
                }
                x0 = fmaxf(x0, __shfl_xor_sync(~0u, x0, 1)); x1 = fmaxf(x1, __shfl_xor_sync(~0u, x1, 1));
                x0 = fmaxf(x0, __shfl_xor_sync(~0u, x0, 2)); x1 = fmaxf(x1, __shfl_xor_sync(~0u, x1, 2));
                x0 = fminf(n0, fmaf(x0, -CS, -20.f)); x1 = fminf(n1, fmaf(x1, -CS, -20.f));
            };
            auto probs = [&](float (&s)[32], uint32_t (&pp)[16], bool ready, auto wait) {
                uint32_t any = 0;
#pragma unroll
                for (int i = 0; i < 16; i++) {
                    pp[i] = pack2(ex2(fmaf(s[2 * i], CS, (i & 1) ? n1 : n0)), ex2(fmaf(s[2 * i + 1], CS, (i & 1) ? n1 : n0)));
                    any |= pp[i];
                }
                float sc0 = 1.f, sc1 = 1.f;
                const bool slow = __any_sync(~0u, (any & 0x40004000u) || !ready);
                if (slow) {
                    wait();
                    if (__any_sync(~0u, any & 0x40004000u)) {
                        float x0, x1;
                        new_max(s, x0, x1);
                        sc0 = ex2(x0 - n0); sc1 = ex2(x1 - n1);
                        n0 = x0; n1 = x1;
#pragma unroll
                        for (int i = 0; i < 16; i++)
                            pp[i] = pack2(ex2(fmaf(s[2 * i], CS, (i & 1) ? n1 : n0)), ex2(fmaf(s[2 * i + 1], CS, (i & 1) ? n1 : n0)));
                    }
                }
                wg_wait<0>();
                pin(sa); pin(sb2); pin(o); pin(pa); pin(pb);
                if (slow) {
#pragma unroll
                    for (int j = 0; j < 9; j++) { o[4 * j] *= sc0; o[4 * j + 1] *= sc0; o[4 * j + 2] *= sc1; o[4 * j + 3] *= sc1; }
                }
            };
            mbar_wait(bars + B_QIN * 8, 0);
            {
                const uint32_t qa = H + 24576 + (wq * 16 + (lane & 15)) * 128;
#pragma unroll
                for (int k = 0; k < 4; k++) ldsm4(qa + (((2 * k + (lane >> 4)) ^ (lane & 7)) << 4), q[4 * k], q[4 * k + 1], q[4 * k + 2], q[4 * k + 3]);
                pin(q);
            }
            TS(40);
            acq(24);
            TS(13);
            qk_issue(sa, rdesc + (24 % NSLOT) * (SLOT >> 4));
            qk_issue(sb2, rdesc + (24 % NSLOT) * (SLOT >> 4) + 512);
            wg_wait<1>();
            pin(sa);
            {
                float x0, x1;
                new_max(sa, x0, x1);
                n0 = x0; n1 = x1;
            }
            if (w == 1) bar_sync(7, 256);
            uint32_t vd = vdesc - (SLOT >> 4) * 65535u, kd = rdesc, vb = fbar + 8, kb = fbar;
            uint32_t vlast = vdesc - 4 * (SLOT >> 4) * 65535u;
            uint32_t kprev = fbar + 32, vprev = bars + (B_HF + 3 - (B_EMPTY - B_FULL)) * 8;
#pragma unroll 1
            for (int it = 0; it < 4; it++) {
                pv_issue(pb, vlast);
                probs(sa, pa, mbar_test(vb, it < 2) & mbar_test(kb, it < 3), [&]() { mbar_wait(vb, it < 2); mbar_wait(kb, it < 3); });
                TS(41 + it * 4);
                if (it == 0 && w == 0) bar_arrive(7, 256);
                if (it == 3 && w == 1) {
#pragma unroll
                    for (int i = 20; i < 32; i++) sb2[i] = -INFINITY;
                }
                pin(sb2);
                if (it < 3) qk_issue(sa, kd);
                if (lane == 0) mbar_arrive(kprev + (B_EMPTY - B_FULL) * 8);
                if (lane == 0) mbar_arrive(vprev + (B_EMPTY - B_FULL) * 8);
                pv_issue(pa, vd);
                probs(sb2, pb, true, []() {});
                TS(43 + it * 4);
                if (it < 3) qk_issue(sb2, kd + 512);
                const int dv = it == 0 ? 2 : (it == 1 ? -3 : 1);
                kprev = kb; vprev = vb; vlast = vd - 512 * 65535u;
                vd -= dv * (SLOT >> 4) * 65535u; vb += dv * 8;
                kd += 2 * (SLOT >> 4); kb = it == 2 ? vb : kb + 16;
            }
            pv_issue(pb, vlast);
            const int row = wq * 16 + (lane >> 2);
            const uint32_t ml = sb + OFF_INBOX;
            wg_wait<0>();
            pin(o); pin(pb); pin(sa); pin(sb2);
            rel(31);
            const float l0 = o[32], l1 = o[34];
            if (c4 == 0) { sts64f(ml + w * 512 + row * 8, n0, l0); sts64f(ml + w * 512 + row * 8 + 64, n1, l1); }
            TS(14);
            float mine[16];
#pragma unroll
            for (int j = 0; j < 4; j++) {
                if (w == 0) sts128f(H + j * 2048 + wt * 16, o[16 + 4 * j], o[17 + 4 * j], o[18 + 4 * j], o[19 + 4 * j]);
                else sts128f(H + 8192 + j * 2048 + wt * 16, o[4 * j], o[4 * j + 1], o[4 * j + 2], o[4 * j + 3]);
            }
#pragma unroll
            for (int i = 0; i < 16; i++) mine[i] = w == 0 ? o[i] : o[16 + i];
            bar_sync(10, 256);
            const float2 u0 = lds64f(ml + (w ^ 1) * 512 + row * 8), u1 = lds64f(ml + (w ^ 1) * 512 + row * 8 + 64);
            const float x0 = fminf(n0, u0.x), x1 = fminf(n1, u1.x);
            float a0 = ex2(x0 - n0), b0 = ex2(x0 - u0.x), a1 = ex2(x1 - n1), b1 = ex2(x1 - u1.x);
            const float i0 = __fdividef(1.f, fmaf(a0, l0, b0 * u0.y)), i1 = __fdividef(1.f, fmaf(a1, l1, b1 * u1.y));
            a0 *= i0; b0 *= i0; a1 *= i1; b1 *= i1;
            uint32_t pk[8];
#pragma unroll
            for (int j = 0; j < 4; j++) {
                const float4 v = lds128f(H + (w ^ 1) * 8192 + j * 2048 + wt * 16);
                pk[2 * j] = pack2(fmaf(a0, mine[4 * j], b0 * v.x), fmaf(a0, mine[4 * j + 1], b0 * v.y));
                pk[2 * j + 1] = pack2(fmaf(a1, mine[4 * j + 2], b1 * v.z), fmaf(a1, mine[4 * j + 3], b1 * v.w));
            }
            const uint32_t og = H + 16384 + wq * 2048;
            {
                const uint32_t ra = og + (((lane >> 3) & 1) * 8 + (lane & 7)) * 128;
                stsm4(ra + (((4 * w + (lane >> 4)) ^ (lane & 7)) << 4), pk[0], pk[1], pk[2], pk[3]);
                stsm4(ra + (((4 * w + 2 + (lane >> 4)) ^ (lane & 7)) << 4), pk[4], pk[5], pk[6], pk[7]);
            }
            __syncwarp();
            {
                const uint32_t off = (lane >> 2) * 128 + (((4 * w + c4) ^ (lane >> 2)) << 4);
                const uint4 v0 = lds128(og + off), v1 = lds128(og + off + 1024);
                unsigned char* dst = g_o + (size_t)(abh * PADROWS + 8 + qt * 64 + wq * 16) * 128 + off;
                stg128(dst, v0); stg128(dst + 1024, v1);
            }
            bar_arrive(6, 288);
            TS(15);
        }

        uint32_t dwr[15];
        {
#pragma unroll
            for (int i = 0; i < 15; i++) dwr[i] = hmul2(__ldg(reinterpret_cast<const uint32_t*>(p.dw + i * 256 + tile * 64) + lane), 0x3F003F00u);
            float d[24];
            uint32_t xw[12];
            mbar_wait(bars + B_X1IN * 8, 0);
            uint2 hl = make_uint2(0, 0), hr = hl;
            if (pt > 0) hl = __ldcg(&g_halo[(((pair - 1) * 4 + tile) * 2 + 1) * 128 + wt]);
            if (pt < 31) hr = __ldcg(&g_halo[(((pair + 1) * 4 + tile) * 2 + 0) * 128 + wt]);
            xw[0] = hl.x; xw[1] = hl.y; xw[10] = hr.x; xw[11] = hr.y;
#pragma unroll
            for (int i = 0; i < 8; i++) xw[2 + i] = xr[i];
            pin(xw);
            pin(dwr);
            acq(32); acq(33); acq(34); acq(35);
            mbar_wait(bars + B_OIN * 8, 0);
            TS(16);
            mm(d, 32, hdesc, cx, 0);
            mbar_wait(bars + B_OIN * 8 + 8, 0);
            mm(d, 33, hdesc + 2 * (XCH >> 4), cx, 1);
            wg_wait<1>();
            rel(32);
            wg_wait<0>();
            pin(d);
#pragma unroll
            for (int i = 0; i < 12; i++) xw[i] = pack2(d[2 * i] + blo(xw[i]), d[2 * i + 1] + bhi(xw[i]));
            if (c4 == 0) { xw[0] = (xw[0] & 0xffff0000u) | 0x3F80u; xw[1] = (xw[1] & 0xffff0000u) | 0x3F80u; }
#pragma unroll
            for (int j = 0; j < 3; j++) stsm4t(xa + j * 2048, xw[4 * j], xw[4 * j + 1], xw[4 * j + 2], xw[4 * j + 3]);
#pragma unroll
            for (int i = 0; i < 8; i++) xr[i] = xw[2 + i];
            rel(33);
            publish(2, P + tile * XCH, XCH, 384);
            TS(17);
        }
        {
            float da[24], db[24], st[24];
            bar_sync(5, 384);
            mm(da, 34, pown, cx, 0);
            mm(db, 35, pown, cx, 0);
            acq(36); acq(37);
            gate(2);
            TS(39);
            mm(da, 36, prem, cx, 1);
            mm(db, 37, prem, cx, 1);
            wg_wait<2>();
            rel(34); rel(35);
            load_stats(st, 0);
            wg_wait<0>();
            pin(da); pin(db);
            rel(36); rel(37);
            TS(18);
            uint32_t pk[12];
#pragma unroll
            for (int hh = 0; hh < 2; hh++) {
                const float ca = __shfl_sync(~0u, da[2 * hh], lane & 28), cb = __shfl_sync(~0u, db[2 * hh], lane & 28);
#pragma unroll
                for (int j = 0; j < 6; j++) {
                    const float u0 = fmaf(-st[4 * j], ca, da[4 * j + 2 * hh] * st[4 * j + 1]);
                    const float u1 = fmaf(-st[4 * j + 2], ca, da[4 * j + 2 * hh + 1] * st[4 * j + 3]);
                    const float v0 = fmaf(-st[4 * j], cb, db[4 * j + 2 * hh] * st[4 * j + 1]);
                    const float v1 = fmaf(-st[4 * j + 2], cb, db[4 * j + 2 * hh + 1] * st[4 * j + 3]);
                    pk[2 * j + hh] = pack2(fmaf(u0, tanh_fast(v0), u0), fmaf(u1, tanh_fast(v1), u1));
                }
            }
            const uint32_t gs = H + 16384 + w * XCH;
#pragma unroll
            for (int j = 0; j < 3; j++) stsm4t(gs + toff + j * 2048, pk[4 * j], pk[4 * j + 1], pk[4 * j + 2], pk[4 * j + 3]);
            bar_sync(2 + w, 128);
            uint32_t ca[8], cb[8];
            const uint32_t grow = gs + 8 * wq * 128 + c4 * 4, srow = H + tile * HCH + 8 * wq * 128 + c4 * 4;
#pragma unroll
            for (int k = 0; k < 22; k++) {
                const uint32_t v = lds32(grow + (1 + k) * 128 + (((lane >> 2) ^ ((1 + k) & 7)) << 4));
#pragma unroll
                for (int i = 0; i < 8; i++) {
                    const int tap = k - i;
                    if (tap == 0) ca[i] = hmul2(v, dwr[0]);
                    else if (tap > 0 && tap < 8) ca[i] = hfma2(v, dwr[tap], ca[i]);
                    else if (tap == 8) cb[i] = hmul2(v, dwr[8]);
                    else if (tap > 8 && tap < 15) cb[i] = hfma2(v, dwr[tap], cb[i]);
                }
            }
#pragma unroll
            for (int i = 0; i < 8; i++) {
                const float h0 = blo(ca[i]) + blo(cb[i]), h1 = bhi(ca[i]) + bhi(cb[i]);
                sts32(srow + i * 128 + (((lane >> 2) ^ i) << 4), pack2(fmaf(h0, tanh_fast(h0), h0), fmaf(h1, tanh_fast(h1), h1)));
            }
            acq(38); acq(39);
            publish(3, H + tile * HCH, HCH, 256);
            TS(19);
        }
        {
            float d[16];
            mm(d, 38, hdesc + 2 * r * (HCH >> 4), ch, 0);
            acq(40); acq(41);
            xwait(3);
            sts128(P + (wt >> 6 ? (tile ^ 2) : tile) * XCH + 4096 + (wt & 63) * 16, 0x3F803F80u, 0x3F803F80u, 0x3F803F80u, 0x3F803F80u);
            mm(d, 39, hdesc + 2 * (r ^ 1) * (HCH >> 4), ch, 1);
            wg_wait<1>();
            rel(38);
            wg_wait<0>();
            pin(d);
#pragma unroll
            for (int i = 0; i < 8; i++) xr[i] = pack2(d[2 * i] + blo(xr[i]), d[2 * i + 1] + bhi(xr[i]));
            stsm4t(xa, xr[0], xr[1], xr[2], xr[3]);
            stsm4t(xa + 2048, xr[4], xr[5], xr[6], xr[7]);
            rel(39);
            publish(4, P + tile * XCH, HCH, 384);
            TS(20);
        }
    }

    xwait(5);
    cluster_arrive();
    TS(24);
    {
        float a[2][8], s[2], q[2];
        const int row0 = 16 * r + 2 * warp;
#pragma unroll
        for (int i = 0; i < 2; i++) {
            const uint4 v = lds128(P + (lane >> 3) * XCH + (row0 + i) * 128 + (((lane & 7) ^ ((row0 + i) & 7)) << 4));
            a[i][0] = blo(v.x); a[i][1] = bhi(v.x); a[i][2] = blo(v.y); a[i][3] = bhi(v.y);
            a[i][4] = blo(v.z); a[i][5] = bhi(v.z); a[i][6] = blo(v.w); a[i][7] = bhi(v.w);
            s[i] = ((a[i][0] + a[i][1]) + (a[i][2] + a[i][3])) + ((a[i][4] + a[i][5]) + (a[i][6] + a[i][7]));
            q[i] = 0.f;
#pragma unroll
            for (int k = 0; k < 8; k++) q[i] = fmaf(a[i][k], a[i][k], q[i]);
        }
#pragma unroll
        for (int o = 16; o > 0; o >>= 1) {
#pragma unroll
            for (int i = 0; i < 2; i++) { s[i] += __shfl_xor_sync(~0u, s[i], o); q[i] += __shfl_xor_sync(~0u, q[i], o); }
        }
#pragma unroll
        for (int i = 0; i < 2; i++) {
            const float mean = s[i] * (1.f / 256.f);
            const float rstd = rsqrtf(fmaxf(fmaf(-mean, mean, q[i] * (1.f / 256.f)), 0.f) + 1e-5f);
            const float nb = -mean * rstd;
            uint4 v;
            v.x = pack2(fmaf(a[i][0], rstd, nb), fmaf(a[i][1], rstd, nb)); v.y = pack2(fmaf(a[i][2], rstd, nb), fmaf(a[i][3], rstd, nb));
            v.z = pack2(fmaf(a[i][4], rstd, nb), fmaf(a[i][5], rstd, nb)); v.w = pack2(fmaf(a[i][6], rstd, nb), fmaf(a[i][7], rstd, nb));
            const int t = pt * 32 + row0 + i;
            if (t < T_) stg128(p.out + (size_t)(b * T_ + t) * 256 + lane * 8, v);
        }
    }
    TS(25);
    TG(31);
    TSDUMP();
    cluster_wait();
}

typedef CUresult (*EncodeFn)(CUtensorMap*, CUtensorMapDataType, cuuint32_t, void*, const cuuint64_t*, const cuuint64_t*,
                             const cuuint32_t*, const cuuint32_t*, CUtensorMapInterleave, CUtensorMapSwizzle,
                             CUtensorMapL2promotion, CUtensorMapFloatOOBfill);

}

extern "C" void kernel_launch(void* const* d_in, const int* in_sizes, int n_in, void* d_out, int out_size) {
    static EncodeFn encode = nullptr;
    if (!encode) {
        void* fn = nullptr;
        cudaDriverEntryPointQueryResult qr;
        cudaGetDriverEntryPoint("cuTensorMapEncodeTiled", &fn, cudaEnableDefault, &qr);
        encode = (EncodeFn)fn;
        cudaFuncSetAttribute(conformer_kernel, cudaFuncAttributeMaxDynamicSharedMemorySize, SMEM_LAUNCH);
    }
    Params p;
    const cuuint32_t ones[3] = {1, 1, 1};
    {
        const cuuint64_t dims[3] = {256, T_, 2};
        const cuuint64_t strides[2] = {512, 512ull * T_};
        const cuuint32_t box[3] = {64, 32, 1};
        encode(&p.tm[0], CU_TENSOR_MAP_DATA_TYPE_BFLOAT16, 3, d_in[0], dims, strides, box, ones, CU_TENSOR_MAP_INTERLEAVE_NONE,
               CU_TENSOR_MAP_SWIZZLE_128B, CU_TENSOR_MAP_L2_PROMOTION_L2_256B, CU_TENSOR_MAP_FLOAT_OOB_FILL_NONE);
    }
    const int idx[8] = {1, 2, 3, 4, 5, 7, 8, 9};
    const int rows[8] = {256, 1024, 256, 256, 256, 256, 256, 1024};
    const int cols[8] = {1024, 256, 768, 256, 512, 256, 1024, 256};
    for (int i = 0; i < 8; i++) {
        const cuuint64_t dims[2] = {(cuuint64_t)cols[i], (cuuint64_t)rows[i]};
        const cuuint64_t strides[1] = {(cuuint64_t)cols[i] * 2};
        const cuuint32_t box[2] = {64, 128};
        encode(&p.tm[1 + i], CU_TENSOR_MAP_DATA_TYPE_BFLOAT16, 2, d_in[idx[i]], dims, strides, box, ones, CU_TENSOR_MAP_INTERLEAVE_NONE,
               CU_TENSOR_MAP_SWIZZLE_128B, CU_TENSOR_MAP_L2_PROMOTION_L2_128B, CU_TENSOR_MAP_FLOAT_OOB_FILL_NONE);
        p.w[i] = (const char*)d_in[idx[i]];
    }
    {
        void* kv = nullptr;
        cudaGetSymbolAddress(&kv, g_kvq);
        const cuuint64_t dims[2] = {64, 16384};
        const cuuint64_t strides[1] = {128};
        const cuuint32_t box[2] = {64, 128};
        encode(&p.tm[9], CU_TENSOR_MAP_DATA_TYPE_BFLOAT16, 2, kv, dims, strides, box, ones, CU_TENSOR_MAP_INTERLEAVE_NONE,
               CU_TENSOR_MAP_SWIZZLE_NONE, CU_TENSOR_MAP_L2_PROMOTION_L2_128B, CU_TENSOR_MAP_FLOAT_OOB_FILL_NONE);
    }
    p.dw = (const __nv_bfloat16*)d_in[6];
    p.out = (__nv_bfloat16*)d_out;
    p.zero = 0;
    conformer_kernel<<<NCTA, NTHREADS, SMEM_LAUNCH>>>(p);
}
```

```cpp
#include <cuda_runtime.h>
#include <cuda_bf16.h>
#include <cuda.h>
#include <stdint.h>
#include <type_traits>

namespace {

constexpr int T_ = 1000;
constexpr int NCTA = 128;
constexpr int NTHREADS = 512;
constexpr int NSLOT = 5;
constexpr int SLOT = 16384;
constexpr int NLOADS = 56;

constexpr uint32_t OFF_RING = 0;
constexpr uint32_t OFF_P = 163840;
constexpr uint32_t OFF_H = 188416;
constexpr uint32_t OFF_INBOX = 221184;
constexpr uint32_t OFF_STATS = 229376;
constexpr uint32_t OFF_BARS = 229888;
constexpr uint32_t SMEM_BYTES = 230400;
constexpr uint32_t XCH = 6144;
constexpr uint32_t HCH = 4096;

constexpr int B_FULL = 0, B_EMPTY = 10, B_XR = 20, B_OIN = 22, B_HF = 24, B_INB = 28, B_QIN = 30, B_X1IN = 31, B_ST = 32, B_RDY = 33;

constexpr int PADROWS = 1040;
constexpr int FS = 8;

struct Params {
    CUtensorMap tm[10];
    const char* w[8];
    const __nv_bfloat16* dw;
    __nv_bfloat16* out;
    uint32_t zero;
};

__device__ __align__(1024) unsigned char g_kvq[3 * 8 * 1024 * 128];
__device__ __align__(1024) unsigned char g_o[8 * PADROWS * 128];
__device__ uint2 g_halo[64 * 4 * 2 * 128];
__device__ uint32_t g_flag_kv[8 * 32 * FS];
__device__ uint32_t g_flag_q[8 * 32 * FS];
__device__ uint32_t g_flag_o[2 * 16 * 4 * FS];
__device__ uint32_t g_epoch[NCTA * FS];

#define TS(i) do { } while (0)
#define TSW(i) do { } while (0)
#define TG(i) do { } while (0)
#define TSINIT() do { } while (0)
#define TSDUMP() do { } while (0)
constexpr uint32_t SMEM_LAUNCH = SMEM_BYTES;

__device__ __forceinline__ uint32_t smem_u32(const void* p) { return (uint32_t)__cvta_generic_to_shared(p); }
__device__ __forceinline__ void mbar_init(uint32_t b, uint32_t c) { asm volatile("mbarrier.init.shared::cta.b64 [%0], %1;" ::"r"(b), "r"(c) : "memory"); }
__device__ __forceinline__ void mbar_arrive(uint32_t b) { asm volatile("mbarrier.arrive.shared::cta.b64 _, [%0];" ::"r"(b) : "memory"); }
__device__ __forceinline__ void mbar_arrive_tx(uint32_t b, uint32_t tx) { asm volatile("mbarrier.arrive.expect_tx.shared::cta.b64 _, [%0], %1;" ::"r"(b), "r"(tx) : "memory"); }
__device__ __forceinline__ void mbar_wait(uint32_t b, uint32_t ph) {
    asm volatile("{\n.reg .pred p, q;\n.reg .u32 c;\nmov.u32 c, 0;\n"
                 "MW_LOOP:\n.pragma \"nounroll\";\n"
                 "mbarrier.try_wait.parity.shared::cta.b64 p, [%0], %1;\n"
                 "add.u32 c, c, 1;\nsetp.lt.u32 q, c, 65536;\nnot.pred p, p;\nand.pred p, p, q;\n@p bra MW_LOOP;\n}"
                 ::"r"(b), "r"(ph) : "memory");
}
__device__ __forceinline__ bool mbar_test(uint32_t b, uint32_t ph) {
    uint32_t ok;
    asm volatile("{\n.reg .pred p;\nmbarrier.test_wait.parity.shared::cta.b64 p, [%1], %2;\nselp.u32 %0, 1, 0, p;\n}" : "=r"(ok) : "r"(b), "r"(ph) : "memory");
    return ok;
}
__device__ __forceinline__ uint32_t mapa(uint32_t a, uint32_t r) { uint32_t o; asm("mapa.shared::cluster.u32 %0, %1, %2;" : "=r"(o) : "r"(a), "r"(r)); return o; }
__device__ __forceinline__ void fence_async_smem() { asm volatile("fence.proxy.async.shared::cta;" ::: "memory"); }
__device__ __forceinline__ void fence_async_global() { asm volatile("fence.proxy.async.global;" ::: "memory"); }
__device__ __forceinline__ void bar_sync(int id, int n) { asm volatile("bar.sync %0, %1;" ::"r"(id), "r"(n) : "memory"); }
__device__ __forceinline__ void bar_arrive(int id, int n) { asm volatile("bar.arrive %0, %1;" ::"r"(id), "r"(n) : "memory"); }
__device__ __forceinline__ void cluster_arrive() { asm volatile("barrier.cluster.arrive.relaxed.aligned;" ::: "memory"); }
__device__ __forceinline__ void cluster_wait() { asm volatile("barrier.cluster.wait.aligned;" ::: "memory"); }

__device__ __forceinline__ void ring_load(uint32_t dst, const CUtensorMap* tm, int c0, int c1, uint32_t bar) {
    asm volatile("{\n.reg .pred p;\nelect.sync _|p, 0xffffffff;\n"
                 "@p mbarrier.arrive.expect_tx.shared::cta.b64 _, [%2], 16384;\n"
                 "@p cp.async.bulk.tensor.2d.shared::cluster.global.mbarrier::complete_tx::bytes [%0], [%1, {%3, %4}], [%2];\n}"
                 ::"r"(dst), "l"(tm), "r"(bar), "r"(c0), "r"(c1) : "memory");
}
__device__ __forceinline__ void ring_load_both(uint32_t dst, const CUtensorMap* tm, int c1, uint32_t bar) {
    asm volatile("{\n.reg .pred p;\nelect.sync _|p, 0xffffffff;\n"
                 "@p cp.async.bulk.tensor.2d.shared::cluster.global.mbarrier::complete_tx::bytes.multicast::cluster [%0], [%1, {0, %3}], [%2], %4;\n}"
                 ::"r"(dst), "l"(tm), "r"(bar), "r"(c1), "h"((uint16_t)3) : "memory");
}
__device__ __forceinline__ void mbar_arrive_peer(uint32_t b) { asm volatile("mbarrier.arrive.relaxed.cluster.shared::cluster.b64 _, [%0];" ::"r"(b) : "memory"); }
__device__ __forceinline__ void tma3d(uint32_t dst, const CUtensorMap* tm, int c0, int c1, int c2, uint32_t bar) {
    asm volatile("{\n.reg .pred p;\nelect.sync _|p, 0xffffffff;\n"
                 "@p cp.async.bulk.tensor.3d.shared::cluster.global.mbarrier::complete_tx::bytes [%0], [%1, {%3, %4, %5}], [%2];\n}"
                 ::"r"(dst), "l"(tm), "r"(bar), "r"(c0), "r"(c1), "r"(c2) : "memory");
}
__device__ __forceinline__ void bulk_g2s(uint32_t dst, const void* src, uint32_t bytes, uint32_t bar) {
    asm volatile("cp.async.bulk.shared::cluster.global.mbarrier::complete_tx::bytes [%0], [%1], %2, [%3];" ::"r"(dst), "l"(src), "r"(bytes), "r"(bar) : "memory");
}
__device__ __forceinline__ void prefetch_l2(const void* src, uint32_t bytes) {
    asm volatile("cp.async.bulk.prefetch.L2.global [%0], %1;" ::"l"(src), "r"(bytes) : "memory");
}
__device__ __forceinline__ void peer_copy(uint32_t dst, uint32_t src, uint32_t bytes, uint32_t rbar) {
    asm volatile("{\n.reg .pred p;\nelect.sync _|p, 0xffffffff;\n"
                 "@p cp.async.bulk.shared::cluster.shared::cta.mbarrier::complete_tx::bytes [%0], [%1], %2, [%3];\n}"
                 ::"r"(dst), "r"(src), "r"(bytes), "r"(rbar) : "memory");
}
__device__ __forceinline__ void st_async4(uint32_t dst, uint32_t a, uint32_t b, uint32_t c, uint32_t d, uint32_t bar) {
    asm volatile("st.async.shared::cluster.mbarrier::complete_tx::bytes.v4.b32 [%0], {%1,%2,%3,%4}, [%5];" ::"r"(dst), "r"(a), "r"(b), "r"(c), "r"(d), "r"(bar) : "memory");
}
__device__ __forceinline__ void stsm4t(uint32_t a, uint32_t r0, uint32_t r1, uint32_t r2, uint32_t r3) {
    asm volatile("stmatrix.sync.aligned.m8n8.x4.trans.shared.b16 [%0], {%1,%2,%3,%4};" ::"r"(a), "r"(r0), "r"(r1), "r"(r2), "r"(r3) : "memory");
}
__device__ __forceinline__ void stsm4(uint32_t a, uint32_t r0, uint32_t r1, uint32_t r2, uint32_t r3) {
    asm volatile("stmatrix.sync.aligned.m8n8.x4.shared.b16 [%0], {%1,%2,%3,%4};" ::"r"(a), "r"(r0), "r"(r1), "r"(r2), "r"(r3) : "memory");
}
__device__ __forceinline__ void ldsm4t(uint32_t a, uint32_t& r0, uint32_t& r1, uint32_t& r2, uint32_t& r3) {
    asm volatile("ldmatrix.sync.aligned.m8n8.x4.trans.shared.b16 {%0,%1,%2,%3}, [%4];" : "=r"(r0), "=r"(r1), "=r"(r2), "=r"(r3) : "r"(a) : "memory");
}
__device__ __forceinline__ void ldsm4(uint32_t a, uint32_t& r0, uint32_t& r1, uint32_t& r2, uint32_t& r3) {
    asm volatile("ldmatrix.sync.aligned.m8n8.x4.shared.b16 {%0,%1,%2,%3}, [%4];" : "=r"(r0), "=r"(r1), "=r"(r2), "=r"(r3) : "r"(a) : "memory");
}
__device__ __forceinline__ uint4 lds128(uint32_t a) { uint4 v; asm volatile("ld.shared.v4.b32 {%0,%1,%2,%3}, [%4];" : "=r"(v.x), "=r"(v.y), "=r"(v.z), "=r"(v.w) : "r"(a) : "memory"); return v; }
__device__ __forceinline__ float4 lds128f(uint32_t a) { float4 v; asm volatile("ld.shared.v4.f32 {%0,%1,%2,%3}, [%4];" : "=f"(v.x), "=f"(v.y), "=f"(v.z), "=f"(v.w) : "r"(a) : "memory"); return v; }
__device__ __forceinline__ float2 lds64f(uint32_t a) { float2 v; asm volatile("ld.shared.v2.f32 {%0,%1}, [%2];" : "=f"(v.x), "=f"(v.y) : "r"(a) : "memory"); return v; }
__device__ __forceinline__ uint32_t lds32(uint32_t a) { uint32_t v; asm volatile("ld.shared.b32 %0, [%1];" : "=r"(v) : "r"(a) : "memory"); return v; }
__device__ __forceinline__ void sts128(uint32_t a, uint32_t x, uint32_t y, uint32_t z, uint32_t w) { asm volatile("st.shared.v4.b32 [%0], {%1,%2,%3,%4};" ::"r"(a), "r"(x), "r"(y), "r"(z), "r"(w) : "memory"); }
__device__ __forceinline__ void sts128f(uint32_t a, float x, float y, float z, float w) { asm volatile("st.shared.v4.f32 [%0], {%1,%2,%3,%4};" ::"r"(a), "f"(x), "f"(y), "f"(z), "f"(w) : "memory"); }
__device__ __forceinline__ void sts64f(uint32_t a, float x, float y) { asm volatile("st.shared.v2.f32 [%0], {%1,%2};" ::"r"(a), "f"(x), "f"(y) : "memory"); }
__device__ __forceinline__ void sts32(uint32_t a, uint32_t x) { asm volatile("st.shared.b32 [%0], %1;" ::"r"(a), "r"(x) : "memory"); }
__device__ __forceinline__ void stg128(void* p, uint4 v) { asm volatile("st.global.v4.b32 [%0], {%1,%2,%3,%4};" ::"l"(p), "r"(v.x), "r"(v.y), "r"(v.z), "r"(v.w) : "memory"); }

__device__ __forceinline__ uint32_t pack2(float lo, float hi) { uint32_t r; asm("cvt.rn.bf16x2.f32 %0, %1, %2;" : "=r"(r) : "f"(hi), "f"(lo)); return r; }
__device__ __forceinline__ float blo(uint32_t v) { return __uint_as_float(v << 16); }
__device__ __forceinline__ float bhi(uint32_t v) { return __uint_as_float(v & 0xffff0000u); }
__device__ __forceinline__ uint32_t hmul2(uint32_t a, uint32_t b) { uint32_t r; asm("mul.rn.bf16x2 %0, %1, %2;" : "=r"(r) : "r"(a), "r"(b)); return r; }
__device__ __forceinline__ uint32_t hfma2(uint32_t a, uint32_t b, uint32_t c) { uint32_t r; asm("fma.rn.bf16x2 %0, %1, %2, %3;" : "=r"(r) : "r"(a), "r"(b), "r"(c)); return r; }
__device__ __forceinline__ float tanh_fast(float x) { float r; asm("tanh.approx.f32 %0, %1;" : "=f"(r) : "f"(x)); return r; }
__device__ __forceinline__ float ex2(float x) { float r; asm("ex2.approx.ftz.f32 %0, %1;" : "=f"(r) : "f"(x)); return r; }

__device__ __forceinline__ void flag_wait(const uint32_t* p, uint32_t e) {
#pragma unroll 1
    for (int i = 0; i < (1 << 20); i++) {
        uint32_t v;
        asm volatile("ld.acquire.gpu.global.u32 %0, [%1];" : "=r"(v) : "l"(p) : "memory");
        if (v == e) break;
    }
}
__device__ __forceinline__ uint32_t ld_epoch() {
    uint32_t v;
    asm volatile("ld.relaxed.gpu.global.u32 %0, [%1];" : "=r"(v) : "l"(&g_epoch[blockIdx.x * FS]) : "memory");
    return v + 1;
}
__device__ __forceinline__ void flag_set(uint32_t* p, uint32_t e) { asm volatile("st.release.gpu.global.u32 [%0], %1;" ::"l"(p), "r"(e) : "memory"); }

__device__ __forceinline__ uint32_t desc_lo(uint32_t addr) { return ((addr & 0x3FFFF) >> 4) | 0x10000u; }
__device__ __forceinline__ uint64_t mkdesc(uint32_t lo) { return (uint64_t)lo | (0x40000040ull << 32); }
__device__ __forceinline__ void wg_fence() { asm volatile("wgmma.fence.sync.aligned;" ::: "memory"); }
__device__ __forceinline__ void wg_commit() { asm volatile("wgmma.commit_group.sync.aligned;" ::: "memory"); }
template <int N> __device__ __forceinline__ void wg_wait() { asm volatile("wgmma.wait_group.sync.aligned %0;" ::"n"(N) : "memory"); }
template <int N> __device__ __forceinline__ void pin(float (&d)[N]) {
#pragma unroll
    for (int i = 0; i < N; i++) asm volatile("" : "+f"(d[i])::"memory");
}
template <int N> __device__ __forceinline__ void pin(uint32_t (&d)[N]) {
#pragma unroll
    for (int i = 0; i < N; i++) asm volatile("" : "+r"(d[i])::"memory");
}

template <typename Tp, int N> __device__ __forceinline__ void zero(Tp (&d)[N]) {
#pragma unroll
    for (int i = 0; i < N; i++) d[i] = 0;
    pin(d);
}

#define F4(d, i) "+f"(d[i]), "+f"(d[i + 1]), "+f"(d[i + 2]), "+f"(d[i + 3])
#define F16(d, i) F4(d, i), F4(d, i + 4), F4(d, i + 8), F4(d, i + 12)

__device__ __forceinline__ void mma_t(float (&d)[16], uint64_t a, uint64_t b, int acc) {
    asm volatile("{.reg .pred p; setp.ne.b32 p, %18, 0;\n"
                 "wgmma.mma_async.sync.aligned.m64n32k16.f32.bf16.bf16 {%0,%1,%2,%3,%4,%5,%6,%7,%8,%9,%10,%11,%12,%13,%14,%15}, %16, %17, p, 1, 1, 1, 0;}\n"
                 : F16(d, 0) : "l"(a), "l"(b), "r"(acc));
}
__device__ __forceinline__ void mma_t(float (&d)[20], uint64_t a, uint64_t b, int acc) {
    asm volatile("{.reg .pred p; setp.ne.b32 p, %22, 0;\n"
                 "wgmma.mma_async.sync.aligned.m64n40k16.f32.bf16.bf16 {%0,%1,%2,%3,%4,%5,%6,%7,%8,%9,%10,%11,%12,%13,%14,%15,%16,%17,%18,%19}, %20, %21, p, 1, 1, 1, 0;}\n"
                 : F16(d, 0), F4(d, 16) : "l"(a), "l"(b), "r"(acc));
}
__device__ __forceinline__ void mma_t(float (&d)[24], uint64_t a, uint64_t b, int acc) {
    asm volatile("{.reg .pred p; setp.ne.b32 p, %26, 0;\n"
                 "wgmma.mma_async.sync.aligned.m64n48k16.f32.bf16.bf16 {%0,%1,%2,%3,%4,%5,%6,%7,%8,%9,%10,%11,%12,%13,%14,%15,%16,%17,%18,%19,%20,%21,%22,%23}, %24, %25, p, 1, 1, 1, 0;}\n"
                 : F16(d, 0), F4(d, 16), F4(d, 20) : "l"(a), "l"(b), "r"(acc));
}
__device__ __forceinline__ void mma_qk(float (&d)[32], uint32_t a0, uint32_t a1, uint32_t a2, uint32_t a3, uint64_t b, int acc) {
    asm volatile("{.reg .pred p; setp.ne.b32 p, %37, 0;\n"
                 "wgmma.mma_async.sync.aligned.m64n64k16.f32.bf16.bf16 {%0,%1,%2,%3,%4,%5,%6,%7,%8,%9,%10,%11,%12,%13,%14,%15,%16,%17,%18,%19,%20,%21,%22,%23,%24,%25,%26,%27,%28,%29,%30,%31}, "
                 "{%32,%33,%34,%35}, %36, p, 1, 1, 0;}\n"
                 : F16(d, 0), F16(d, 16) : "r"(a0), "r"(a1), "r"(a2), "r"(a3), "l"(b), "r"(acc));
}
__device__ __forceinline__ void mma_pv(float (&d)[36], uint32_t a0, uint32_t a1, uint32_t a2, uint32_t a3, uint64_t b) {
    asm volatile("wgmma.mma_async.sync.aligned.m64n72k16.f32.bf16.bf16 {%0,%1,%2,%3,%4,%5,%6,%7,%8,%9,%10,%11,%12,%13,%14,%15,%16,%17,%18,%19,%20,%21,%22,%23,%24,%25,%26,%27,%28,%29,%30,%31,%32,%33,%34,%35}, "
                 "{%36,%37,%38,%39}, %40, 1, 1, 1, 1;\n"
                 : F16(d, 0), F16(d, 16), F4(d, 32) : "r"(a0), "r"(a1), "r"(a2), "r"(a3), "l"(b));
}

template <uint32_t CSTRIDE, int N>
__device__ __forceinline__ void issue_half(float (&d)[N], uint32_t alo, uint32_t blo_, int acc) {
    const uint64_t a = mkdesc(alo), b = mkdesc(blo_);
    wg_fence();
#pragma unroll
    for (int k = 0; k < 8; k++) mma_t(d, a + k * 128, b + (k >> 2) * (CSTRIDE >> 4) + (k & 3) * 2, k == 0 ? acc : 1);
    wg_commit();
}

__device__ __forceinline__ uint32_t load_code(int n, int r, int w) {
    const int tile = 2 * r + w;
    int m, col, row;
    if (n < 16 || n >= 40) {
        const int k = n < 16 ? n : n - 40;
        m = n < 16 ? 1 : 7;
        if (k < 8) { col = 8 * r + (k & 6) + w; row = (k & 1) ^ r; }
        else {
            const int kk = k == 11 ? 12 : (k == 12 ? 11 : k);
            m++; col = kk < 12 ? (tile ^ 2) : tile; row = 4 * r + (kk & 3);
        }
    } else if (n < 32) {
        const int k = n - 16;
        m = 3;
        if (k < 4) { col = tile + ((k & 1) ? 8 : 4); row = (k >> 1) ^ r; }
        else { col = tile; row = (k & 1) ^ r; }
    } else if (n < 34) { m = 4; col = tile; row = n - 32; }
    else if (n < 38) { const int k = n - 34; m = 5; col = tile + 4 * (k & 1); row = (k >> 1) ^ r; }
    else { m = 6; col = tile; row = (n & 1) ^ r; }
    return m | (col << 4) | (row << 8);
}

__global__ void __cluster_dims__(2, 1, 1) __launch_bounds__(NTHREADS, 1)
conformer_kernel(const __grid_constant__ Params p) {
    extern __shared__ __align__(1024) unsigned char smem_raw[];
    const uint32_t sb = smem_u32(smem_raw);
    const uint32_t bars = sb + OFF_BARS;
    const int tid = threadIdx.x;
    const int lane = tid & 31;
    const int warp = __shfl_sync(~0u, tid >> 5, 0);
    const int r = blockIdx.x & 1;
    const int pair = blockIdx.x >> 1;
    const int b = pair >> 5, pt = pair & 31;
    const int ah = pt >> 3, qt = (pt & 7) * 2 + r;
    const int abh = b * 4 + ah;

    TG(30);
    TSINIT();
    TS(0);
    const uint32_t P = sb + OFF_P, H = sb + OFF_H;
    auto xwait = [&](int j) { mbar_wait(bars + (B_XR + (j & 1)) * 8, (j >> 1) & 1); };

    if (__builtin_expect(warp >= 8, 1)) {
        asm volatile("setmaxnreg.dec.sync.aligned.u32 48;");
        if (warp == 8) {
            if (lane == 0) {
                mbar_init(bars + B_XR * 8, 1);
                fence_async_smem();
                mbar_arrive_tx(bars + B_XR * 8, 16384);
            }
            __syncwarp();
#pragma unroll
            for (int i = 0; i < 4; i++) tma3d(P + i * XCH, &p.tm[0], i * 64, pt * 32, b, bars + B_XR * 8);
            TS(1);
            if (lane == 0) {
#pragma unroll
                for (int i = 0; i < 2 * NSLOT; i++) mbar_init(bars + (B_FULL + i) * 8, 1);
                asm volatile("fence.mbarrier_init.release.cluster;" ::: "memory");
                fence_async_smem();
            }
            __syncwarp();
            cluster_arrive();
#pragma unroll 1
            for (int n = 0; n < NSLOT; n++) {
#pragma unroll
                for (int w = 0; w < 2; w++)
                    ring_load(sb + OFF_RING + (w * NSLOT + n) * SLOT, &p.tm[1], 64 * (8 * r + (n & 6) + w), 128 * ((n & 1) ^ r), bars + (B_FULL + w * NSLOT + n) * 8);
            }
            TS(2);
        } else if (warp == 9) {
            if (lane == 0) prefetch_l2(p.w[0] + blockIdx.x * 4096, 4096);
            __syncwarp();
            cluster_arrive();
        }
        if (warp >= 12) {
            if (warp == 12 && lane >= 1 && lane < 10) asm volatile("prefetch.tensormap [%0];" ::"l"(&p.tm[lane]) : "memory");
            cluster_arrive();
            cluster_wait();
            const int ut = tid & 127;
            const uint32_t a4 = P + (ut >> 2) * 128 + (2 * (ut & 3) + ((ut >> 2) & 1)) * 16;
            const uint32_t a8 = P + (32 + (ut >> 3)) * 128 + (ut & 7) * 16;
#pragma unroll 1
            for (int k = 0; k < 4; k++) {
                float s = 0.f, q = 0.f, s2 = 0.f, q2 = 0.f;
#pragma unroll 1
                for (int h = 0; h < 2; h++) {
                    if (h == 0 && k != 0) bar_sync(1, 384);
                    else xwait(k == 3 ? 4 : k);
                    const uint32_t off = 2 * (r ^ h) * XCH;
                    uint4 v0 = lds128(a4 + off), v1 = lds128((a4 ^ 16) + off), v2 = lds128(a4 + off + XCH), v3 = lds128((a4 ^ 16) + off + XCH);
                    uint4 v4 = make_uint4(0, 0, 0, 0), v5 = v4;
                    if (k == 2) { v4 = lds128(a8 + off); v5 = lds128(a8 + off + XCH); }
                    if (h == 1 || k == 1 || k == 2) bar_arrive(5 + ((v3.w | v5.w) & p.zero), 384);
                    uint32_t t;
                    asm volatile("mov.u32 %0, %%clock;" : "=r"(t)::"memory");
                    const uint32_t mul = 65536u + (t & p.zero), msk = 0u - mul;
                    auto accum = [&](const uint4& v, float& s, float& q) {
                        const float a0 = __uint_as_float(v.x * mul), a1 = __uint_as_float(v.x & msk), a2 = __uint_as_float(v.y * mul), a3 = __uint_as_float(v.y & msk);
                        const float a4 = __uint_as_float(v.z * mul), a5 = __uint_as_float(v.z & msk), a6 = __uint_as_float(v.w * mul), a7 = __uint_as_float(v.w & msk);
                        s += ((a0 + a1) + (a2 + a3)) + ((a4 + a5) + (a6 + a7));
                        q += fmaf(a0, a0, fmaf(a1, a1, fmaf(a2, a2, a3 * a3))) + fmaf(a4, a4, fmaf(a5, a5, fmaf(a6, a6, a7 * a7)));
                    };
                    accum(v0, s, q); accum(v1, s, q); accum(v2, s, q); accum(v3, s, q);
                    if (k == 2) { accum(v4, s2, q2); accum(v5, s2, q2); }
                }
#pragma unroll
                for (int o = 1; o < 8; o <<= 1) {
                    if (o < 4) { s += __shfl_xor_sync(~0u, s, o); q += __shfl_xor_sync(~0u, q, o); }
                    if (k == 2) { s2 += __shfl_xor_sync(~0u, s2, o); q2 += __shfl_xor_sync(~0u, q2, o); }
                }
                const bool second = (ut & 7) == 1;
                if (second) { s = s2; q = q2; }
                const float mean = s * (1.f / 256.f);
                const int row = second ? 32 + (ut >> 3) : ut >> 2;
                const float alpha = k == 1 ? 1.f : ((k == 2 && (uint32_t)(pt * 32 - 8 + row) >= T_) ? 0.f : 0.5f);
                const float rstd = alpha * rsqrtf(fmaxf(fmaf(-mean, mean, q * (1.f / 256.f)), 0.f) + 1e-5f);
                if ((ut & 3) == 0 || second) sts64f(sb + OFF_STATS + row * 8, mean * rstd, rstd);
                __syncwarp();
                if (lane == 0) mbar_arrive(bars + B_ST * 8);
                TS(2 + k);
                if (k == 1 && warp == 12) {
                    const uint32_t epoch = ld_epoch();
                    bar_sync(11, 288);
                    if (lane < 2) flag_set(&g_flag_q[((b * 4 + 2 * r + lane) * 32 + pt) * FS], epoch);
                    __syncwarp();
                    TS(13);
                }
            }
        } else if (warp < 10) {
            const int w = warp - 8;
            const uint32_t ring = sb + OFF_RING + w * NSLOT * SLOT;
            const uint32_t full = bars + (B_FULL + w * NSLOT) * 8;
            const uint32_t code = load_code(lane, r, w) | (load_code(lane + 32, r, w) << 16);
            cluster_wait();
            uint32_t s = 0, ph = 0;
            int n = NSLOT;
#pragma unroll 1
            for (int seg = 0; seg < 2; seg++) {
#pragma unroll 1
                for (; n < (seg == 0 ? 22 : NLOADS); n++) {
                    const uint32_t c = __shfl_sync(~0u, code, n) >> (n & 32 ? 16 : 0);
                    mbar_wait(full + (B_EMPTY - B_FULL) * 8 + s * 8, ph);
                    ring_load(ring + s * SLOT, &p.tm[c & 15], (c & 0xf0) * 4, (c & 0xff00) >> 1, full + s * 8);
                    if (++s == NSLOT) { s = 0; ph ^= 1; }
                }
                if (seg == 1) break;
                const uint32_t epoch = ld_epoch();
                const uint32_t rdy = bars + (B_RDY + 3 * w) * 8, prdy = mapa(rdy, r ^ 1);
                const int isv = r ^ w;
#pragma unroll 1
                for (; n < 32; n++) {
                    mbar_wait(full + (B_EMPTY - B_FULL) * 8 + s * 8, ph);
                    if (lane == 0) {
                        if (n < 24) mbar_arrive(full + s * 8);
                        else mbar_arrive_tx(full + s * 8, SLOT);
                    }
                    if (n == 28) {
                        if (lane == 0) mbar_arrive_peer(prdy);
                        mbar_wait(rdy, 0);
                        if (!isv) {
                            flag_wait(g_flag_kv + (abh * 32 + lane) * FS, epoch);
                            __syncwarp();
                            fence_async_global();
                            TSW(5);
                            ring_load_both(ring + 4 * SLOT, &p.tm[9], (abh * 8 + w) * 128, full + 32);
                        }
                        bar_sync(12, 64);
#pragma unroll
                        for (int i = 0; i < 2; i++) {
                            if (i == 0) mbar_wait(bars + B_QIN * 8, 0);
                            else mbar_wait(full + isv * 8, 1);
                            ring_load_both(ring + (2 * i + isv) * SLOT, &p.tm[9], (isv * 62 + abh * 8 + 2 * i + 2 + w) * 128, full + (2 * i + isv) * 8);
                        }
                    } else if (n > 28) {
                        const uint32_t bo = n == 31 ? 16 : 8;
                        if ((n > 29) == (isv == 1)) {
                            mbar_wait(rdy + bo, 0);
                            ring_load_both(ring + s * SLOT, &p.tm[9], (isv * 64 + abh * 8 + (n == 30 ? 4 : 6) + w) * 128, full + s * 8);
                        } else if (lane == 0) mbar_arrive_peer(prdy + bo);
                    }
                    __syncwarp();
                    if (++s == NSLOT) { s = 0; ph ^= 1; }
                }
            }
        } else if (warp == 10) {
            cluster_arrive();
            cluster_wait();
            const uint32_t epoch = ld_epoch();
            if (lane == 0) {
                mbar_arrive_tx(bars + B_QIN * 8, 8192);
                mbar_arrive_tx(bars + B_OIN * 8, 2 * XCH);
                mbar_arrive_tx(bars + B_OIN * 8 + 8, 2 * XCH);
            }
            if (lane < 2) flag_wait(&g_flag_q[(abh * 32 + 2 * qt + lane) * FS], epoch);
            __syncwarp();
            TSW(6);
            if (lane == 0) {
                fence_async_global();
                bulk_g2s(H + 24576, g_kvq + 2097152 + (size_t)(abh * 1024 + qt * 64) * 128, 8192, bars + B_QIN * 8);
            }
            if (lane < 2) {
                const int np = pt - 1 + 2 * lane;
                if (np >= 0 && np < 32) flag_wait(&g_flag_kv[((b * 4 + 2 * r) * 32 + np) * FS], epoch);
            }
            __syncwarp();
            if (lane == 0) mbar_arrive(bars + B_X1IN * 8);
            bar_sync(9, 64);
            if (lane < 8) {
                const int q = (pt >> 1) + (lane < 4 ? 0 : ((pt & 1) ? 1 : -1));
                if (q >= 0 && q < 16) flag_wait(&g_flag_o[((b * 16 + q) * 4 + (lane & 3)) * FS], epoch);
            }
            __syncwarp();
            TSW(10);
            if (lane == 0) {
                fence_async_global();
#pragma unroll
                for (int i = 0; i < 4; i++)
                    bulk_g2s(H + i * XCH, g_o + (size_t)((b * 4 + i) * PADROWS + pt * 32) * 128, XCH, bars + (B_OIN + (i >> 1)) * 8);
            }
            __syncwarp();
        } else {
            const uint32_t kb = (lane < 2 || lane > 5) ? 4096 : (lane == 2 ? 3072 : (lane == 4 ? 2048 : 1024));
            const char* pf = p.w[lane & 7] + blockIdx.x * kb;
            cluster_arrive();
            cluster_wait();
            xwait(0);
            if (lane == 1 || lane == 2) prefetch_l2(pf, kb);
            mbar_wait(bars + B_HF * 8, 0);
            if (lane > 2 && lane < 8) prefetch_l2(pf, kb);
            const uint32_t epoch = ld_epoch();
            bar_sync(4, 288);
            if (lane < 2) flag_set(&g_flag_kv[((b * 4 + 2 * r + lane) * 32 + pt) * FS], epoch);
            __syncwarp();
            TSW(8);
            bar_sync(6, 288);
            bar_arrive(9, 64);
            if (lane == 0) {
                flag_set(&g_flag_o[((b * 16 + qt) * 4 + ah) * FS], epoch);
                g_epoch[blockIdx.x * FS] = epoch;
            }
            __syncwarp();
            TSW(9);
        }
        TSDUMP();
        return;
    }

    if (lane == 0) {
        mbar_init(bars + (B_EMPTY + warp) * 8, 4);
        mbar_init(bars + (B_HF + warp) * 8, warp < 4 ? 8 : 1);
        if (warp < 3) mbar_init(bars + (warp == 2 ? B_ST : B_EMPTY + 8 + warp) * 8, 4);
        else if (warp < 6) mbar_init(bars + (B_XR - 2 + warp) * 8, 1);
        if (warp < 6) mbar_init(bars + (B_RDY + warp) * 8, 1);
        asm volatile("fence.mbarrier_init.release.cluster;" ::: "memory");
    }
    sts128(P + (tid >> 6) * XCH + 4096 + (tid & 63) * 16, 0x3F803F80u, 0x3F803F80u, 0x3F803F80u, 0x3F803F80u);
    fence_async_smem();
    __syncwarp();
    cluster_arrive();
    asm volatile("setmaxnreg.inc.sync.aligned.u32 208;");
    const int w = warp >> 2, wq = warp & 3;
    const int tile = 2 * r + w;
    const int wt = tid & 127;
    const int c4 = lane & 3;
    const uint32_t rbase = sb + OFF_RING + w * NSLOT * SLOT, fbar = bars + (B_FULL + w * NSLOT) * 8;
    const uint32_t rdesc = desc_lo(rbase);
    auto acq = [&](int n) { mbar_wait(fbar + (n % NSLOT) * 8, (n / NSLOT) & 1); };
    auto rel = [&](int n) { if (lane == 0) mbar_arrive(fbar + (B_EMPTY - B_FULL + n % NSLOT) * 8); };
    const uint32_t pown = desc_lo(P + 2 * r * XCH), prem = desc_lo(P + 2 * (r ^ 1) * XCH), hdesc = desc_lo(H);
    const uint32_t toff = ((lane >> 4) * 8 + (lane & 7)) * 128 + (((2 * wq + ((lane >> 3) & 1)) ^ (lane & 7)) << 4);
    const uint32_t xa = P + tile * XCH + toff;
    auto publish = [&](int j, uint32_t src, uint32_t bytes, int nsync) {
        const uint32_t bar = bars + (B_XR + (j & 1)) * 8;
        fence_async_smem();
        bar_sync(2 + w, 128);
        if (wq == 0) peer_copy(mapa(src, r ^ 1), src, bytes, mapa(bar, r ^ 1));
        if (tid == 32) mbar_arrive_tx(bar, 2 * bytes);
        bar_sync(nsync == 384 ? 1 : 10, nsync);
    };
    auto gate = [&](int j) { xwait(j); bar_sync(5, 384); };
    auto load_stats = [&](auto& st, int parity) {
        mbar_wait(bars + B_ST * 8, parity);
#pragma unroll
        for (int j = 0; j < (int)(sizeof(st) / 16); j++) {
            const float4 v = lds128f(sb + OFF_STATS + (8 * j + 2 * c4) * 8);
            st[4 * j] = v.x; st[4 * j + 1] = v.y; st[4 * j + 2] = v.z; st[4 * j + 3] = v.w;
        }
    };
    bar_sync(10, 256);
    cluster_wait();
    uint32_t xr[8];
    TS(56);
    xwait(0);
    TS(57);
    ldsm4t(xa, xr[0], xr[1], xr[2], xr[3]);
    ldsm4t(xa + 2048, xr[4], xr[5], xr[6], xr[7]);
    acq(0);
    TS(58);
    acq(1);

#pragma unroll 1
    for (int ffi = 0; ffi < 2; ffi++) {
        auto mm = [&](auto& d, int n, uint32_t bd, auto cs, int acc) {
            const uint32_t z = p.zero * (ffi + n + 1);
            issue_half<decltype(cs)::value>(d, rdesc + z + (n % NSLOT) * (SLOT >> 4), bd + z, acc);
        };
        constexpr std::integral_constant<uint32_t, XCH> cx{};
        constexpr std::integral_constant<uint32_t, HCH> ch{};
        {
            float st[16], a0[20], a1[20], rem[16], own[16];
            const uint32_t inb = bars + (B_INB + w) * 8, box = sb + OFF_INBOX + w * 4096 + wt * 16;
            const uint32_t hdst = H + w * HCH + toff;
            auto step = [&](auto& d, int n, uint32_t bd, auto cs, int acc) {
                mm(d, n, bd, cs, acc);
                wg_wait<1>();
                if (n > 0) rel(n - 1);
            };
            auto epi = [&](float (&d)[20], int i, int half) {
                uint32_t pk[4];
#pragma unroll
                for (int k = 4 * half; k < 4 * half + 4; k++) {
                    const float cs = d[16 + 2 * (k & 1)];
                    const float v0 = fmaf(-st[(k >> 1) * 4], cs, d[2 * k] * st[(k >> 1) * 4 + 1]);
                    const float v1 = fmaf(-st[(k >> 1) * 4 + 2], cs, d[2 * k + 1] * st[(k >> 1) * 4 + 3]);
                    pk[k & 3] = pack2(fmaf(v0, tanh_fast(v0), v0), fmaf(v1, tanh_fast(v1), v1));
                }
                stsm4t(hdst + 2 * i * HCH + half * 2048, pk[0], pk[1], pk[2], pk[3]);
            };
            auto hdone = [&](int i) {
                fence_async_smem();
                __syncwarp();
                if (lane == 0) mbar_arrive(bars + (B_HF + i) * 8);
            };
            auto hwait = [&](int i) { mbar_wait(bars + (B_HF + i) * 8, ffi); };
            TS(1 + ffi * 20);
            step(a0, 0, pown, cx, 0);
            if (wt == 0) mbar_arrive_tx(inb, 4096);
            acq(2);
            gate(ffi * 4);
            TS(32);
            step(a0, 1, prem, cx, 1);
            step(a1, 2, pown, cx, 0); acq(3); pin(a0); load_stats(st, ffi); TS(33); epi(a0, 0, 0);
            step(a1, 3, prem, cx, 1); acq(4); epi(a0, 0, 1); TS(34);
            step(a0, 4, pown, cx, 0); acq(5); pin(a1); epi(a1, 1, 0);
            step(a0, 5, prem, cx, 1); acq(6); epi(a1, 1, 1); TS(35);
            step(a1, 6, pown, cx, 0); acq(7); pin(a0); hdone(0); epi(a0, 2, 0);
            step(a1, 7, prem, cx, 1); acq(8); hwait(0); epi(a0, 2, 1); TS(36);
            step(rem, 8, hdesc, ch, 0); acq(9); pin(a1); hdone(1); epi(a1, 3, 0);
            step(rem, 9, hdesc + 2 * (HCH >> 4), ch, 1); acq(10); hwait(1); epi(a1, 3, 1);
            TS(2 + ffi * 20);
            step(rem, 10, hdesc + 4 * (HCH >> 4), ch, 1); acq(11); hdone(2);
            step(own, 11, hdesc, ch, 0); acq(12); hwait(2);
            step(rem, 12, hdesc + 6 * (HCH >> 4), ch, 1); acq(13);
            step(own, 13, hdesc + 2 * (HCH >> 4), ch, 1); acq(14);
            pin(rem);
            {
                const uint32_t dst = mapa(box, r ^ 1), bar = mapa(inb, r ^ 1);
                st_async4(dst, pack2(rem[0], rem[1]), pack2(rem[2], rem[3]), pack2(rem[4], rem[5]), pack2(rem[6], rem[7]), bar);
                st_async4(dst + 2048, pack2(rem[8], rem[9]), pack2(rem[10], rem[11]), pack2(rem[12], rem[13]), pack2(rem[14], rem[15]), bar);
            }
            step(own, 14, hdesc + 4 * (HCH >> 4), ch, 1); acq(15);
            step(own, 15, hdesc + 6 * (HCH >> 4), ch, 1);
            mbar_wait(inb, ffi);
            const uint4 u = lds128(box), v = lds128(box + 2048);
            const uint32_t pr[8] = {u.x, u.y, u.z, u.w, v.x, v.y, v.z, v.w};
            if (ffi == 0) { acq(16); acq(17); }
            wg_wait<0>();
            pin(own);
            TS(3 + ffi * 20);
#pragma unroll
            for (int i = 0; i < 8; i++)
                xr[i] = pack2(fmaf(0.5f, own[2 * i] + blo(pr[i]), blo(xr[i])), fmaf(0.5f, own[2 * i + 1] + bhi(pr[i]), bhi(xr[i])));
            stsm4t(xa, xr[0], xr[1], xr[2], xr[3]);
            stsm4t(xa + 2048, xr[4], xr[5], xr[6], xr[7]);
            rel(15);
            publish(ffi ? 5 : 1, P + tile * XCH + (ffi ? (r ^ 1) * 2048 : 0), ffi ? 2048 : 4096, ffi ? 256 : 384);
        }
        if (ffi == 1) break;

        {
            float ak[20], aq[20], st[16];
            g_halo[((pair * 4 + tile) * 2 + 0) * 128 + wt] = make_uint2(xr[0], xr[1]);
            g_halo[((pair * 4 + tile) * 2 + 1) * 128 + wt] = make_uint2(xr[6], xr[7]);
            bar_sync(5, 384);
            TS(11);
            mm(ak, 16, pown, cx, 0);
            mm(aq, 17, pown, cx, 0);
            acq(18); acq(19);
            gate(1);
            mm(ak, 18, prem, cx, 1);
            mm(aq, 19, prem, cx, 1);
            wg_wait<2>();
            rel(16); rel(17);
            load_stats(st, 1);
            auto stage_out = [&](float (&d)[20], uint32_t dst) {
                uint32_t pk[8];
#pragma unroll
                for (int k = 0; k < 8; k++) {
                    const float cs = d[16 + 2 * (k & 1)];
                    pk[k] = pack2(fmaf(-st[(k >> 1) * 4], cs, d[2 * k] * st[(k >> 1) * 4 + 1]),
                                  fmaf(-st[(k >> 1) * 4 + 2], cs, d[2 * k + 1] * st[(k >> 1) * 4 + 3]));
                }
                stsm4t(dst + toff, pk[0], pk[1], pk[2], pk[3]);
                stsm4t(dst + toff + 2048, pk[4], pk[5], pk[6], pk[7]);
            };
            const uint32_t stg = H + w * 12288;
            unsigned char* g = g_kvq + (size_t)((b * 4 + tile) * 1024 + pt * 32) * 128 + wt * 16;
            wg_wait<0>();
            pin(ak); pin(aq);
            TS(37);
            stage_out(ak, stg);
            stage_out(aq, stg + 4096);
            bar_sync(2 + w, 128);
            {
                const uint4 k0 = lds128(stg + wt * 16), k1 = lds128(stg + 2048 + wt * 16), q0 = lds128(stg + 4096 + wt * 16), q1 = lds128(stg + 6144 + wt * 16);
                stg128(g, k0); stg128(g + 2048, k1);
                stg128(g + 1048576, q0); stg128(g + 1048576 + 2048, q1);
            }
            bar_arrive(4, 288);
            TS(38);
            rel(18); rel(19);
            acq(20); acq(21);
            bar_sync(10, 256);
            mm(ak, 20, pown, cx, 0);
            mm(ak, 21, prem, cx, 1);
            wg_wait<0>();
            pin(ak);
            stage_out(ak, stg + 8192);
            rel(20); rel(21);
            bar_sync(2 + w, 128);
            {
                const uint4 v0 = lds128(stg + 8192 + wt * 16), v1 = lds128(stg + 10240 + wt * 16);
                stg128(g + 2097152, v0); stg128(g + 2097152 + 2048, v1);
            }
            bar_arrive(11, 288);
            acq(22); acq(23);
            rel(22); rel(23);
            TS(12);
        }

        {
            constexpr float CS = 0.125f * 1.4426950408889634f;
            float sa[32], sb2[32], o[36];
            uint32_t pa[16], pb[16], q[16];
            float n0 = INFINITY, n1 = INFINITY;
            zero(o); zero(pa); zero(pb);
            const uint32_t ones = sb + OFF_INBOX + 2048;
            if (tid < 128) sts128(ones + tid * 16, 0x3F803F80u, 0x3F803F80u, 0x3F803F80u, 0x3F803F80u);
            fence_async_smem();
            bar_sync(10, 256);
            const uint32_t vdesc = rdesc + ((((ones - rbase) >> 4) - 1) << 16);
            auto qk_issue = [&](float (&s)[32], uint32_t lo) {
                const uint64_t kd = mkdesc(lo);
                wg_fence();
#pragma unroll
                for (int k = 0; k < 4; k++) mma_qk(s, q[4 * k], q[4 * k + 1], q[4 * k + 2], q[4 * k + 3], kd + 2 * k, k != 0);
                wg_commit();
            };
            auto pv_issue = [&](uint32_t (&pp)[16], uint32_t lo) {
                const uint64_t vd = mkdesc(lo);
                wg_fence();
#pragma unroll
                for (int k = 0; k < 4; k++) mma_pv(o, pp[4 * k], pp[4 * k + 1], pp[4 * k + 2], pp[4 * k + 3], vd - k * (128 * 65535));
                wg_commit();
            };
            auto new_max = [&](float (&s)[32], float& x0, float& x1) {
                x0 = s[0]; x1 = s[2];
#pragma unroll
                for (int j = 0; j < 8; j++) {
                    x0 = fmaxf(x0, fmaxf(s[4 * j], s[4 * j + 1]));
                    x1 = fmaxf(x1, fmaxf(s[4 * j + 2], s[4 * j + 3]));
                }
                x0 = fmaxf(x0, __shfl_xor_sync(~0u, x0, 1)); x1 = fmaxf(x1, __shfl_xor_sync(~0u, x1, 1));
                x0 = fmaxf(x0, __shfl_xor_sync(~0u, x0, 2)); x1 = fmaxf(x1, __shfl_xor_sync(~0u, x1, 2));
                x0 = fminf(n0, fmaf(x0, -CS, -20.f)); x1 = fminf(n1, fmaf(x1, -CS, -20.f));
            };
            auto probs = [&](float (&s)[32], uint32_t (&pp)[16], bool ready, auto wait) {
                uint32_t any = 0;
#pragma unroll
                for (int i = 0; i < 16; i++) {
                    pp[i] = pack2(ex2(fmaf(s[2 * i], CS, (i & 1) ? n1 : n0)), ex2(fmaf(s[2 * i + 1], CS, (i & 1) ? n1 : n0)));
                    any |= pp[i];
                }
                float sc0 = 1.f, sc1 = 1.f;
                const bool slow = __any_sync(~0u, (any & 0x40004000u) || !ready);
                if (slow) {
                    wait();
                    if (__any_sync(~0u, any & 0x40004000u)) {
                        float x0, x1;
                        new_max(s, x0, x1);
                        sc0 = ex2(x0 - n0); sc1 = ex2(x1 - n1);
                        n0 = x0; n1 = x1;
#pragma unroll
                        for (int i = 0; i < 16; i++)
                            pp[i] = pack2(ex2(fmaf(s[2 * i], CS, (i & 1) ? n1 : n0)), ex2(fmaf(s[2 * i + 1], CS, (i & 1) ? n1 : n0)));
                    }
                }
                wg_wait<0>();
                pin(sa); pin(sb2); pin(o); pin(pa); pin(pb);
                if (slow) {
#pragma unroll
                    for (int j = 0; j < 9; j++) { o[4 * j] *= sc0; o[4 * j + 1] *= sc0; o[4 * j + 2] *= sc1; o[4 * j + 3] *= sc1; }
                }
            };
            mbar_wait(bars + B_QIN * 8, 0);
            {
                const uint32_t qa = H + 24576 + (wq * 16 + (lane & 15)) * 128;
#pragma unroll
                for (int k = 0; k < 4; k++) ldsm4(qa + (((2 * k + (lane >> 4)) ^ (lane & 7)) << 4), q[4 * k], q[4 * k + 1], q[4 * k + 2], q[4 * k + 3]);
                pin(q);
            }
            TS(40);
            acq(24);
            TS(13);
            qk_issue(sa, rdesc + (24 % NSLOT) * (SLOT >> 4));
            qk_issue(sb2, rdesc + (24 % NSLOT) * (SLOT >> 4) + 512);
            wg_wait<1>();
            pin(sa);
            {
                float x0, x1;
                new_max(sa, x0, x1);
                n0 = x0; n1 = x1;
            }
            if (w == 1) bar_sync(7, 256);
            uint32_t vd = vdesc - (SLOT >> 4) * 65535u, kd = rdesc, vb = fbar + 8, kb = fbar;
            uint32_t vlast = vdesc - 4 * (SLOT >> 4) * 65535u;
            uint32_t kprev = fbar + 32, vprev = bars + (B_HF + 3 - (B_EMPTY - B_FULL)) * 8;
#pragma unroll 1
            for (int it = 0; it < 4; it++) {
                pv_issue(pb, vlast);
                probs(sa, pa, mbar_test(vb, it < 2) & mbar_test(kb, it < 3), [&]() { mbar_wait(vb, it < 2); mbar_wait(kb, it < 3); });
                TS(41 + it * 4);
                if (it == 0 && w == 0) bar_arrive(7, 256);
                if (it == 3 && w == 1) {
#pragma unroll
                    for (int i = 20; i < 32; i++) sb2[i] = -INFINITY;
                }
                pin(sb2);
                if (it < 3) qk_issue(sa, kd);
                if (lane == 0) mbar_arrive(kprev + (B_EMPTY - B_FULL) * 8);
                if (lane == 0) mbar_arrive(vprev + (B_EMPTY - B_FULL) * 8);
                pv_issue(pa, vd);
                probs(sb2, pb, true, []() {});
                TS(43 + it * 4);
                if (it < 3) qk_issue(sb2, kd + 512);
                const int dv = it == 0 ? 2 : (it == 1 ? -3 : 1);
                kprev = kb; vprev = vb; vlast = vd - 512 * 65535u;
                vd -= dv * (SLOT >> 4) * 65535u; vb += dv * 8;
                kd += 2 * (SLOT >> 4); kb = it == 2 ? vb : kb + 16;
            }
            pv_issue(pb, vlast);
            const int row = wq * 16 + (lane >> 2);
            const uint32_t ml = sb + OFF_INBOX;
            wg_wait<0>();
            pin(o); pin(pb); pin(sa); pin(sb2);
            rel(31);
            const float l0 = o[32], l1 = o[34];
            if (c4 == 0) { sts64f(ml + w * 512 + row * 8, n0, l0); sts64f(ml + w * 512 + row * 8 + 64, n1, l1); }
            TS(14);
            float mine[16];
#pragma unroll
            for (int j = 0; j < 4; j++) {
                if (w == 0) sts128f(H + j * 2048 + wt * 16, o[16 + 4 * j], o[17 + 4 * j], o[18 + 4 * j], o[19 + 4 * j]);
                else sts128f(H + 8192 + j * 2048 + wt * 16, o[4 * j], o[4 * j + 1], o[4 * j + 2], o[4 * j + 3]);
            }
#pragma unroll
            for (int i = 0; i < 16; i++) mine[i] = w == 0 ? o[i] : o[16 + i];
            bar_sync(10, 256);
            const float2 u0 = lds64f(ml + (w ^ 1) * 512 + row * 8), u1 = lds64f(ml + (w ^ 1) * 512 + row * 8 + 64);
            const float x0 = fminf(n0, u0.x), x1 = fminf(n1, u1.x);
            float a0 = ex2(x0 - n0), b0 = ex2(x0 - u0.x), a1 = ex2(x1 - n1), b1 = ex2(x1 - u1.x);
            const float i0 = __fdividef(1.f, fmaf(a0, l0, b0 * u0.y)), i1 = __fdividef(1.f, fmaf(a1, l1, b1 * u1.y));
            a0 *= i0; b0 *= i0; a1 *= i1; b1 *= i1;
            uint32_t pk[8];
#pragma unroll
            for (int j = 0; j < 4; j++) {
                const float4 v = lds128f(H + (w ^ 1) * 8192 + j * 2048 + wt * 16);
                pk[2 * j] = pack2(fmaf(a0, mine[4 * j], b0 * v.x), fmaf(a0, mine[4 * j + 1], b0 * v.y));
                pk[2 * j + 1] = pack2(fmaf(a1, mine[4 * j + 2], b1 * v.z), fmaf(a1, mine[4 * j + 3], b1 * v.w));
            }
            const uint32_t og = H + 16384 + wq * 2048;
            {
                const uint32_t ra = og + (((lane >> 3) & 1) * 8 + (lane & 7)) * 128;
                stsm4(ra + (((4 * w + (lane >> 4)) ^ (lane & 7)) << 4), pk[0], pk[1], pk[2], pk[3]);
                stsm4(ra + (((4 * w + 2 + (lane >> 4)) ^ (lane & 7)) << 4), pk[4], pk[5], pk[6], pk[7]);
            }
            __syncwarp();
            {
                const uint32_t off = (lane >> 2) * 128 + (((4 * w + c4) ^ (lane >> 2)) << 4);
                const uint4 v0 = lds128(og + off), v1 = lds128(og + off + 1024);
                unsigned char* dst = g_o + (size_t)(abh * PADROWS + 8 + qt * 64 + wq * 16) * 128 + off;
                stg128(dst, v0); stg128(dst + 1024, v1);
            }
            bar_arrive(6, 288);
            TS(15);
        }

        uint32_t dwr[15];
        {
#pragma unroll
            for (int i = 0; i < 15; i++) dwr[i] = hmul2(__ldg(reinterpret_cast<const uint32_t*>(p.dw + i * 256 + tile * 64) + lane), 0x3F003F00u);
            float d[24];
            uint32_t xw[12];
            mbar_wait(bars + B_X1IN * 8, 0);
            uint2 hl = make_uint2(0, 0), hr = hl;
            if (pt > 0) hl = __ldcg(&g_halo[(((pair - 1) * 4 + tile) * 2 + 1) * 128 + wt]);
            if (pt < 31) hr = __ldcg(&g_halo[(((pair + 1) * 4 + tile) * 2 + 0) * 128 + wt]);
            xw[0] = hl.x; xw[1] = hl.y; xw[10] = hr.x; xw[11] = hr.y;
#pragma unroll
            for (int i = 0; i < 8; i++) xw[2 + i] = xr[i];
            pin(xw);
            pin(dwr);
            acq(32); acq(33); acq(34); acq(35);
            mbar_wait(bars + B_OIN * 8, 0);
            TS(16);
            mm(d, 32, hdesc, cx, 0);
            mbar_wait(bars + B_OIN * 8 + 8, 0);
            mm(d, 33, hdesc + 2 * (XCH >> 4), cx, 1);
            wg_wait<1>();
            rel(32);
            wg_wait<0>();
            pin(d);
#pragma unroll
            for (int i = 0; i < 12; i++) xw[i] = pack2(d[2 * i] + blo(xw[i]), d[2 * i + 1] + bhi(xw[i]));
            if (c4 == 0) { xw[0] = (xw[0] & 0xffff0000u) | 0x3F80u; xw[1] = (xw[1] & 0xffff0000u) | 0x3F80u; }
#pragma unroll
            for (int j = 0; j < 3; j++) stsm4t(xa + j * 2048, xw[4 * j], xw[4 * j + 1], xw[4 * j + 2], xw[4 * j + 3]);
#pragma unroll
            for (int i = 0; i < 8; i++) xr[i] = xw[2 + i];
            rel(33);
            publish(2, P + tile * XCH, XCH, 384);
            TS(17);
        }
        {
            float da[24], db[24], st[24];
            bar_sync(5, 384);
            mm(da, 34, pown, cx, 0);
            mm(db, 35, pown, cx, 0);
            acq(36); acq(37);
            gate(2);
            TS(39);
            mm(da, 36, prem, cx, 1);
            mm(db, 37, prem, cx, 1);
            wg_wait<2>();
            rel(34); rel(35);
            load_stats(st, 0);
            wg_wait<0>();
            pin(da); pin(db);
            rel(36); rel(37);
            TS(18);
            uint32_t pk[12];
#pragma unroll
            for (int hh = 0; hh < 2; hh++) {
                const float ca = __shfl_sync(~0u, da[2 * hh], lane & 28), cb = __shfl_sync(~0u, db[2 * hh], lane & 28);
#pragma unroll
                for (int j = 0; j < 6; j++) {
                    const float u0 = fmaf(-st[4 * j], ca, da[4 * j + 2 * hh] * st[4 * j + 1]);
                    const float u1 = fmaf(-st[4 * j + 2], ca, da[4 * j + 2 * hh + 1] * st[4 * j + 3]);
                    const float v0 = fmaf(-st[4 * j], cb, db[4 * j + 2 * hh] * st[4 * j + 1]);
                    const float v1 = fmaf(-st[4 * j + 2], cb, db[4 * j + 2 * hh + 1] * st[4 * j + 3]);
                    pk[2 * j + hh] = pack2(fmaf(u0, tanh_fast(v0), u0), fmaf(u1, tanh_fast(v1), u1));
                }
            }
            const uint32_t gs = H + 16384 + w * XCH;
#pragma unroll
            for (int j = 0; j < 3; j++) stsm4t(gs + toff + j * 2048, pk[4 * j], pk[4 * j + 1], pk[4 * j + 2], pk[4 * j + 3]);
            bar_sync(2 + w, 128);
            uint32_t ca[8], cb[8];
            const uint32_t grow = gs + 8 * wq * 128 + c4 * 4, srow = H + tile * HCH + 8 * wq * 128 + c4 * 4;
#pragma unroll
            for (int k = 0; k < 22; k++) {
                const uint32_t v = lds32(grow + (1 + k) * 128 + (((lane >> 2) ^ ((1 + k) & 7)) << 4));
#pragma unroll
                for (int i = 0; i < 8; i++) {
                    const int tap = k - i;
                    if (tap == 0) ca[i] = hmul2(v, dwr[0]);
                    else if (tap > 0 && tap < 8) ca[i] = hfma2(v, dwr[tap], ca[i]);
                    else if (tap == 8) cb[i] = hmul2(v, dwr[8]);
                    else if (tap > 8 && tap < 15) cb[i] = hfma2(v, dwr[tap], cb[i]);
                }
            }
#pragma unroll
            for (int i = 0; i < 8; i++) {
                const float h0 = blo(ca[i]) + blo(cb[i]), h1 = bhi(ca[i]) + bhi(cb[i]);
                sts32(srow + i * 128 + (((lane >> 2) ^ i) << 4), pack2(fmaf(h0, tanh_fast(h0), h0), fmaf(h1, tanh_fast(h1), h1)));
            }
            acq(38); acq(39);
            publish(3, H + tile * HCH, HCH, 256);
            TS(19);
        }
        {
            float d[16];
            mm(d, 38, hdesc + 2 * r * (HCH >> 4), ch, 0);
            acq(40); acq(41);
            xwait(3);
            sts128(P + (wt >> 6 ? (tile ^ 2) : tile) * XCH + 4096 + (wt & 63) * 16, 0x3F803F80u, 0x3F803F80u, 0x3F803F80u, 0x3F803F80u);
            mm(d, 39, hdesc + 2 * (r ^ 1) * (HCH >> 4), ch, 1);
            wg_wait<1>();
            rel(38);
            wg_wait<0>();
            pin(d);
#pragma unroll
            for (int i = 0; i < 8; i++) xr[i] = pack2(d[2 * i] + blo(xr[i]), d[2 * i + 1] + bhi(xr[i]));
            stsm4t(xa, xr[0], xr[1], xr[2], xr[3]);
            stsm4t(xa + 2048, xr[4], xr[5], xr[6], xr[7]);
            rel(39);
            publish(4, P + tile * XCH, HCH, 384);
            TS(20);
        }
    }

    xwait(5);
    cluster_arrive();
    TS(24);
    {
        float a[2][8], s[2], q[2];
        const int row0 = 16 * r + 2 * warp;
#pragma unroll
        for (int i = 0; i < 2; i++) {
            const uint4 v = lds128(P + (lane >> 3) * XCH + (row0 + i) * 128 + (((lane & 7) ^ ((row0 + i) & 7)) << 4));
            a[i][0] = blo(v.x); a[i][1] = bhi(v.x); a[i][2] = blo(v.y); a[i][3] = bhi(v.y);
            a[i][4] = blo(v.z); a[i][5] = bhi(v.z); a[i][6] = blo(v.w); a[i][7] = bhi(v.w);
            s[i] = ((a[i][0] + a[i][1]) + (a[i][2] + a[i][3])) + ((a[i][4] + a[i][5]) + (a[i][6] + a[i][7]));
            q[i] = 0.f;
#pragma unroll
            for (int k = 0; k < 8; k++) q[i] = fmaf(a[i][k], a[i][k], q[i]);
        }
#pragma unroll
        for (int o = 16; o > 0; o >>= 1) {
#pragma unroll
            for (int i = 0; i < 2; i++) { s[i] += __shfl_xor_sync(~0u, s[i], o); q[i] += __shfl_xor_sync(~0u, q[i], o); }
        }
#pragma unroll
        for (int i = 0; i < 2; i++) {
            const float mean = s[i] * (1.f / 256.f);
            const float rstd = rsqrtf(fmaxf(fmaf(-mean, mean, q[i] * (1.f / 256.f)), 0.f) + 1e-5f);
            const float nb = -mean * rstd;
            uint4 v;
            v.x = pack2(fmaf(a[i][0], rstd, nb), fmaf(a[i][1], rstd, nb)); v.y = pack2(fmaf(a[i][2], rstd, nb), fmaf(a[i][3], rstd, nb));
            v.z = pack2(fmaf(a[i][4], rstd, nb), fmaf(a[i][5], rstd, nb)); v.w = pack2(fmaf(a[i][6], rstd, nb), fmaf(a[i][7], rstd, nb));
            const int t = pt * 32 + row0 + i;
            if (t < T_) stg128(p.out + (size_t)(b * T_ + t) * 256 + lane * 8, v);
        }
    }
    TS(25);
    TG(31);
    TSDUMP();
    cluster_wait();
}

typedef CUresult (*EncodeFn)(CUtensorMap*, CUtensorMapDataType, cuuint32_t, void*, const cuuint64_t*, const cuuint64_t*,
                             const cuuint32_t*, const cuuint32_t*, CUtensorMapInterleave, CUtensorMapSwizzle,
                             CUtensorMapL2promotion, CUtensorMapFloatOOBfill);

}

extern "C" void kernel_launch(void* const* d_in, const int* in_sizes, int n_in, void* d_out, int out_size) {
    static EncodeFn encode = nullptr;
    if (!encode) {
        void* fn = nullptr;
        cudaDriverEntryPointQueryResult qr;
        cudaGetDriverEntryPoint("cuTensorMapEncodeTiled", &fn, cudaEnableDefault, &qr);
        encode = (EncodeFn)fn;
        cudaFuncSetAttribute(conformer_kernel, cudaFuncAttributeMaxDynamicSharedMemorySize, SMEM_LAUNCH);
    }
    Params p;
    const cuuint32_t ones[3] = {1, 1, 1};
    {
        const cuuint64_t dims[3] = {256, T_, 2};
        const cuuint64_t strides[2] = {512, 512ull * T_};
        const cuuint32_t box[3] = {64, 32, 1};
        encode(&p.tm[0], CU_TENSOR_MAP_DATA_TYPE_BFLOAT16, 3, d_in[0], dims, strides, box, ones, CU_TENSOR_MAP_INTERLEAVE_NONE,
               CU_TENSOR_MAP_SWIZZLE_128B, CU_TENSOR_MAP_L2_PROMOTION_L2_256B, CU_TENSOR_MAP_FLOAT_OOB_FILL_NONE);
    }
    const int idx[8] = {1, 2, 3, 4, 5, 7, 8, 9};
    const int rows[8] = {256, 1024, 256, 256, 256, 256, 256, 1024};
    const int cols[8] = {1024, 256, 768, 256, 512, 256, 1024, 256};
    for (int i = 0; i < 8; i++) {
        const cuuint64_t dims[2] = {(cuuint64_t)cols[i], (cuuint64_t)rows[i]};
        const cuuint64_t strides[1] = {(cuuint64_t)cols[i] * 2};
        const cuuint32_t box[2] = {64, 128};
        encode(&p.tm[1 + i], CU_TENSOR_MAP_DATA_TYPE_BFLOAT16, 2, d_in[idx[i]], dims, strides, box, ones, CU_TENSOR_MAP_INTERLEAVE_NONE,
               CU_TENSOR_MAP_SWIZZLE_128B, CU_TENSOR_MAP_L2_PROMOTION_L2_128B, CU_TENSOR_MAP_FLOAT_OOB_FILL_NONE);
        p.w[i] = (const char*)d_in[idx[i]];
    }
    {
        void* kv = nullptr;
        cudaGetSymbolAddress(&kv, g_kvq);
        const cuuint64_t dims[2] = {64, 16384};
        const cuuint64_t strides[1] = {128};
        const cuuint32_t box[2] = {64, 128};
        encode(&p.tm[9], CU_TENSOR_MAP_DATA_TYPE_BFLOAT16, 2, kv, dims, strides, box, ones, CU_TENSOR_MAP_INTERLEAVE_NONE,
               CU_TENSOR_MAP_SWIZZLE_NONE, CU_TENSOR_MAP_L2_PROMOTION_L2_128B, CU_TENSOR_MAP_FLOAT_OOB_FILL_NONE);
    }
    p.dw = (const __nv_bfloat16*)d_in[6];
    p.out = (__nv_bfloat16*)d_out;
    p.zero = 0;
    conformer_kernel<<<NCTA, NTHREADS, SMEM_LAUNCH>>>(p);
}
```

```cpp
#include <cuda_runtime.h>
#include <cuda_bf16.h>
#include <cuda.h>
#include <stdint.h>
#include <type_traits>

namespace {

constexpr int T_ = 1000;
constexpr int NCTA = 128;
constexpr int NTHREADS = 512;
constexpr int NSLOT = 5;
constexpr int SLOT = 16384;
constexpr int NLOADS = 56;

constexpr uint32_t OFF_RING = 0;
constexpr uint32_t OFF_P = 163840;
constexpr uint32_t OFF_H = 188416;
constexpr uint32_t OFF_INBOX = 221184;
constexpr uint32_t OFF_STATS = 229376;
constexpr uint32_t OFF_BARS = 229888;
constexpr uint32_t SMEM_BYTES = 230400;
constexpr uint32_t XCH = 6144;
constexpr uint32_t HCH = 4096;

constexpr int B_FULL = 0, B_EMPTY = 10, B_XR = 20, B_OIN = 22, B_HF = 24, B_INB = 28, B_QIN = 30, B_X1IN = 31, B_ST = 32, B_RDY = 33;

constexpr int PADROWS = 1040;
constexpr int FS = 8;

struct Params {
    CUtensorMap tm[10];
    const char* w[8];
    const char* x;
    const __nv_bfloat16* dw;
    __nv_bfloat16* out;
    uint32_t zero;
};

__device__ __align__(1024) unsigned char g_kvq[3 * 8 * 1024 * 128];
__device__ __align__(1024) unsigned char g_o[8 * PADROWS * 128];
__device__ uint2 g_halo[64 * 4 * 2 * 128];
__device__ uint32_t g_flag_kv[8 * 32 * FS];
__device__ uint32_t g_flag_q[8 * 32 * FS];
__device__ uint32_t g_flag_o[2 * 16 * 4 * FS];
__device__ uint32_t g_epoch[NCTA * FS];

#define TS(i) do { } while (0)
#define TSW(i) do { } while (0)
#define TG(i) do { } while (0)
#define TSINIT() do { } while (0)
#define TSDUMP() do { } while (0)
constexpr uint32_t SMEM_LAUNCH = SMEM_BYTES;

__device__ __forceinline__ uint32_t smem_u32(const void* p) { return (uint32_t)__cvta_generic_to_shared(p); }
__device__ __forceinline__ void mbar_init(uint32_t b, uint32_t c) { asm volatile("mbarrier.init.shared::cta.b64 [%0], %1;" ::"r"(b), "r"(c) : "memory"); }
__device__ __forceinline__ void mbar_arrive(uint32_t b) { asm volatile("mbarrier.arrive.shared::cta.b64 _, [%0];" ::"r"(b) : "memory"); }
__device__ __forceinline__ void mbar_arrive_tx(uint32_t b, uint32_t tx) { asm volatile("mbarrier.arrive.expect_tx.shared::cta.b64 _, [%0], %1;" ::"r"(b), "r"(tx) : "memory"); }
__device__ __forceinline__ void mbar_wait(uint32_t b, uint32_t ph) {
    asm volatile("{\n.reg .pred p, q;\n.reg .u32 c;\nmov.u32 c, 0;\n"
                 "MW_LOOP:\n.pragma \"nounroll\";\n"
                 "mbarrier.try_wait.parity.shared::cta.b64 p, [%0], %1;\n"
                 "add.u32 c, c, 1;\nsetp.lt.u32 q, c, 65536;\nnot.pred p, p;\nand.pred p, p, q;\n@p bra MW_LOOP;\n}"
                 ::"r"(b), "r"(ph) : "memory");
}
__device__ __forceinline__ bool mbar_test(uint32_t b, uint32_t ph) {
    uint32_t ok;
    asm volatile("{\n.reg .pred p;\nmbarrier.test_wait.parity.shared::cta.b64 p, [%1], %2;\nselp.u32 %0, 1, 0, p;\n}" : "=r"(ok) : "r"(b), "r"(ph) : "memory");
    return ok;
}
__device__ __forceinline__ uint32_t mapa(uint32_t a, uint32_t r) { uint32_t o; asm("mapa.shared::cluster.u32 %0, %1, %2;" : "=r"(o) : "r"(a), "r"(r)); return o; }
__device__ __forceinline__ void fence_async_smem() { asm volatile("fence.proxy.async.shared::cta;" ::: "memory"); }
__device__ __forceinline__ void fence_async_global() { asm volatile("fence.proxy.async.global;" ::: "memory"); }
__device__ __forceinline__ void bar_sync(int id, int n) { asm volatile("bar.sync %0, %1;" ::"r"(id), "r"(n) : "memory"); }
__device__ __forceinline__ void bar_arrive(int id, int n) { asm volatile("bar.arrive %0, %1;" ::"r"(id), "r"(n) : "memory"); }
__device__ __forceinline__ void cluster_arrive() { asm volatile("barrier.cluster.arrive.relaxed.aligned;" ::: "memory"); }
__device__ __forceinline__ void cluster_wait() { asm volatile("barrier.cluster.wait.aligned;" ::: "memory"); }

__device__ __forceinline__ void ring_load(uint32_t dst, const CUtensorMap* tm, int c0, int c1, uint32_t bar) {
    asm volatile("{\n.reg .pred p;\nelect.sync _|p, 0xffffffff;\n"
                 "@p mbarrier.arrive.expect_tx.shared::cta.b64 _, [%2], 16384;\n"
                 "@p cp.async.bulk.tensor.2d.shared::cluster.global.mbarrier::complete_tx::bytes [%0], [%1, {%3, %4}], [%2];\n}"
                 ::"r"(dst), "l"(tm), "r"(bar), "r"(c0), "r"(c1) : "memory");
}
__device__ __forceinline__ void ring_load_both(uint32_t dst, const CUtensorMap* tm, int c1, uint32_t bar) {
    asm volatile("{\n.reg .pred p;\nelect.sync _|p, 0xffffffff;\n"
                 "@p cp.async.bulk.tensor.2d.shared::cluster.global.mbarrier::complete_tx::bytes.multicast::cluster [%0], [%1, {0, %3}], [%2], %4;\n}"
                 ::"r"(dst), "l"(tm), "r"(bar), "r"(c1), "h"((uint16_t)3) : "memory");
}
__device__ __forceinline__ void mbar_arrive_peer(uint32_t b) { asm volatile("mbarrier.arrive.relaxed.cluster.shared::cluster.b64 _, [%0];" ::"r"(b) : "memory"); }
__device__ __forceinline__ void tma3d(uint32_t dst, const CUtensorMap* tm, int c0, int c1, int c2, uint32_t bar) {
    asm volatile("{\n.reg .pred p;\nelect.sync _|p, 0xffffffff;\n"
                 "@p cp.async.bulk.tensor.3d.shared::cluster.global.mbarrier::complete_tx::bytes [%0], [%1, {%3, %4, %5}], [%2];\n}"
                 ::"r"(dst), "l"(tm), "r"(bar), "r"(c0), "r"(c1), "r"(c2) : "memory");
}
__device__ __forceinline__ void bulk_g2s(uint32_t dst, const void* src, uint32_t bytes, uint32_t bar) {
    asm volatile("cp.async.bulk.shared::cluster.global.mbarrier::complete_tx::bytes [%0], [%1], %2, [%3];" ::"r"(dst), "l"(src), "r"(bytes), "r"(bar) : "memory");
}
__device__ __forceinline__ void prefetch_l2(const void* src, uint32_t bytes) {
    asm volatile("cp.async.bulk.prefetch.L2.global [%0], %1;" ::"l"(src), "r"(bytes) : "memory");
}
__device__ __forceinline__ void peer_copy(uint32_t dst, uint32_t src, uint32_t bytes, uint32_t rbar) {
    asm volatile("{\n.reg .pred p;\nelect.sync _|p, 0xffffffff;\n"
                 "@p cp.async.bulk.shared::cluster.shared::cta.mbarrier::complete_tx::bytes [%0], [%1], %2, [%3];\n}"
                 ::"r"(dst), "r"(src), "r"(bytes), "r"(rbar) : "memory");
}
__device__ __forceinline__ void st_async4(uint32_t dst, uint32_t a, uint32_t b, uint32_t c, uint32_t d, uint32_t bar) {
    asm volatile("st.async.shared::cluster.mbarrier::complete_tx::bytes.v4.b32 [%0], {%1,%2,%3,%4}, [%5];" ::"r"(dst), "r"(a), "r"(b), "r"(c), "r"(d), "r"(bar) : "memory");
}
__device__ __forceinline__ void stsm4t(uint32_t a, uint32_t r0, uint32_t r1, uint32_t r2, uint32_t r3) {
    asm volatile("stmatrix.sync.aligned.m8n8.x4.trans.shared.b16 [%0], {%1,%2,%3,%4};" ::"r"(a), "r"(r0), "r"(r1), "r"(r2), "r"(r3) : "memory");
}
__device__ __forceinline__ void stsm4(uint32_t a, uint32_t r0, uint32_t r1, uint32_t r2, uint32_t r3) {
    asm volatile("stmatrix.sync.aligned.m8n8.x4.shared.b16 [%0], {%1,%2,%3,%4};" ::"r"(a), "r"(r0), "r"(r1), "r"(r2), "r"(r3) : "memory");
}
__device__ __forceinline__ void ldsm4t(uint32_t a, uint32_t& r0, uint32_t& r1, uint32_t& r2, uint32_t& r3) {
    asm volatile("ldmatrix.sync.aligned.m8n8.x4.trans.shared.b16 {%0,%1,%2,%3}, [%4];" : "=r"(r0), "=r"(r1), "=r"(r2), "=r"(r3) : "r"(a) : "memory");
}
__device__ __forceinline__ void ldsm4(uint32_t a, uint32_t& r0, uint32_t& r1, uint32_t& r2, uint32_t& r3) {
    asm volatile("ldmatrix.sync.aligned.m8n8.x4.shared.b16 {%0,%1,%2,%3}, [%4];" : "=r"(r0), "=r"(r1), "=r"(r2), "=r"(r3) : "r"(a) : "memory");
}
__device__ __forceinline__ uint4 lds128(uint32_t a) { uint4 v; asm volatile("ld.shared.v4.b32 {%0,%1,%2,%3}, [%4];" : "=r"(v.x), "=r"(v.y), "=r"(v.z), "=r"(v.w) : "r"(a) : "memory"); return v; }
__device__ __forceinline__ float4 lds128f(uint32_t a) { float4 v; asm volatile("ld.shared.v4.f32 {%0,%1,%2,%3}, [%4];" : "=f"(v.x), "=f"(v.y), "=f"(v.z), "=f"(v.w) : "r"(a) : "memory"); return v; }
__device__ __forceinline__ float2 lds64f(uint32_t a) { float2 v; asm volatile("ld.shared.v2.f32 {%0,%1}, [%2];" : "=f"(v.x), "=f"(v.y) : "r"(a) : "memory"); return v; }
__device__ __forceinline__ uint32_t lds32(uint32_t a) { uint32_t v; asm volatile("ld.shared.b32 %0, [%1];" : "=r"(v) : "r"(a) : "memory"); return v; }
__device__ __forceinline__ void sts128(uint32_t a, uint32_t x, uint32_t y, uint32_t z, uint32_t w) { asm volatile("st.shared.v4.b32 [%0], {%1,%2,%3,%4};" ::"r"(a), "r"(x), "r"(y), "r"(z), "r"(w) : "memory"); }
__device__ __forceinline__ void sts128f(uint32_t a, float x, float y, float z, float w) { asm volatile("st.shared.v4.f32 [%0], {%1,%2,%3,%4};" ::"r"(a), "f"(x), "f"(y), "f"(z), "f"(w) : "memory"); }
__device__ __forceinline__ void sts64f(uint32_t a, float x, float y) { asm volatile("st.shared.v2.f32 [%0], {%1,%2};" ::"r"(a), "f"(x), "f"(y) : "memory"); }
__device__ __forceinline__ void sts32(uint32_t a, uint32_t x) { asm volatile("st.shared.b32 [%0], %1;" ::"r"(a), "r"(x) : "memory"); }
__device__ __forceinline__ void stg128(void* p, uint4 v) { asm volatile("st.global.v4.b32 [%0], {%1,%2,%3,%4};" ::"l"(p), "r"(v.x), "r"(v.y), "r"(v.z), "r"(v.w) : "memory"); }

__device__ __forceinline__ uint32_t pack2(float lo, float hi) { uint32_t r; asm("cvt.rn.bf16x2.f32 %0, %1, %2;" : "=r"(r) : "f"(hi), "f"(lo)); return r; }
__device__ __forceinline__ float blo(uint32_t v) { return __uint_as_float(v << 16); }
__device__ __forceinline__ float bhi(uint32_t v) { return __uint_as_float(v & 0xffff0000u); }
__device__ __forceinline__ uint32_t hmul2(uint32_t a, uint32_t b) { uint32_t r; asm("mul.rn.bf16x2 %0, %1, %2;" : "=r"(r) : "r"(a), "r"(b)); return r; }
__device__ __forceinline__ uint32_t hfma2(uint32_t a, uint32_t b, uint32_t c) { uint32_t r; asm("fma.rn.bf16x2 %0, %1, %2, %3;" : "=r"(r) : "r"(a), "r"(b), "r"(c)); return r; }
__device__ __forceinline__ float tanh_fast(float x) { float r; asm("tanh.approx.f32 %0, %1;" : "=f"(r) : "f"(x)); return r; }
__device__ __forceinline__ float ex2(float x) { float r; asm("ex2.approx.ftz.f32 %0, %1;" : "=f"(r) : "f"(x)); return r; }

__device__ __forceinline__ void flag_wait(const uint32_t* p, uint32_t e) {
#pragma unroll 1
    for (int i = 0; i < (1 << 20); i++) {
        uint32_t v;
        asm volatile("ld.acquire.gpu.global.u32 %0, [%1];" : "=r"(v) : "l"(p) : "memory");
        if (v == e) break;
    }
}
__device__ __forceinline__ uint32_t ld_epoch() {
    uint32_t v;
    asm volatile("ld.relaxed.gpu.global.u32 %0, [%1];" : "=r"(v) : "l"(&g_epoch[blockIdx.x * FS]) : "memory");
    return v + 1;
}
__device__ __forceinline__ void flag_set(uint32_t* p, uint32_t e) { asm volatile("st.release.gpu.global.u32 [%0], %1;" ::"l"(p), "r"(e) : "memory"); }

__device__ __forceinline__ uint32_t desc_lo(uint32_t addr) { return ((addr & 0x3FFFF) >> 4) | 0x10000u; }
__device__ __forceinline__ uint64_t mkdesc(uint32_t lo) { return (uint64_t)lo | (0x40000040ull << 32); }
__device__ __forceinline__ void wg_fence() { asm volatile("wgmma.fence.sync.aligned;" ::: "memory"); }
__device__ __forceinline__ void wg_commit() { asm volatile("wgmma.commit_group.sync.aligned;" ::: "memory"); }
template <int N> __device__ __forceinline__ void wg_wait() { asm volatile("wgmma.wait_group.sync.aligned %0;" ::"n"(N) : "memory"); }
template <int N> __device__ __forceinline__ void pin(float (&d)[N]) {
#pragma unroll
    for (int i = 0; i < N; i++) asm volatile("" : "+f"(d[i])::"memory");
}
template <int N> __device__ __forceinline__ void pin(uint32_t (&d)[N]) {
#pragma unroll
    for (int i = 0; i < N; i++) asm volatile("" : "+r"(d[i])::"memory");
}

template <typename Tp, int N> __device__ __forceinline__ void zero(Tp (&d)[N]) {
#pragma unroll
    for (int i = 0; i < N; i++) d[i] = 0;
    pin(d);
}

#define F4(d, i) "+f"(d[i]), "+f"(d[i + 1]), "+f"(d[i + 2]), "+f"(d[i + 3])
#define F16(d, i) F4(d, i), F4(d, i + 4), F4(d, i + 8), F4(d, i + 12)

__device__ __forceinline__ void mma_t(float (&d)[16], uint64_t a, uint64_t b, int acc) {
    asm volatile("{.reg .pred p; setp.ne.b32 p, %18, 0;\n"
                 "wgmma.mma_async.sync.aligned.m64n32k16.f32.bf16.bf16 {%0,%1,%2,%3,%4,%5,%6,%7,%8,%9,%10,%11,%12,%13,%14,%15}, %16, %17, p, 1, 1, 1, 0;}\n"
                 : F16(d, 0) : "l"(a), "l"(b), "r"(acc));
}
__device__ __forceinline__ void mma_t(float (&d)[20], uint64_t a, uint64_t b, int acc) {
    asm volatile("{.reg .pred p; setp.ne.b32 p, %22, 0;\n"
                 "wgmma.mma_async.sync.aligned.m64n40k16.f32.bf16.bf16 {%0,%1,%2,%3,%4,%5,%6,%7,%8,%9,%10,%11,%12,%13,%14,%15,%16,%17,%18,%19}, %20, %21, p, 1, 1, 1, 0;}\n"
                 : F16(d, 0), F4(d, 16) : "l"(a), "l"(b), "r"(acc));
}
__device__ __forceinline__ void mma_t(float (&d)[24], uint64_t a, uint64_t b, int acc) {
    asm volatile("{.reg .pred p; setp.ne.b32 p, %26, 0;\n"
                 "wgmma.mma_async.sync.aligned.m64n48k16.f32.bf16.bf16 {%0,%1,%2,%3,%4,%5,%6,%7,%8,%9,%10,%11,%12,%13,%14,%15,%16,%17,%18,%19,%20,%21,%22,%23}, %24, %25, p, 1, 1, 1, 0;}\n"
                 : F16(d, 0), F4(d, 16), F4(d, 20) : "l"(a), "l"(b), "r"(acc));
}
__device__ __forceinline__ void mma_qk(float (&d)[32], uint32_t a0, uint32_t a1, uint32_t a2, uint32_t a3, uint64_t b, int acc) {
    asm volatile("{.reg .pred p; setp.ne.b32 p, %37, 0;\n"
                 "wgmma.mma_async.sync.aligned.m64n64k16.f32.bf16.bf16 {%0,%1,%2,%3,%4,%5,%6,%7,%8,%9,%10,%11,%12,%13,%14,%15,%16,%17,%18,%19,%20,%21,%22,%23,%24,%25,%26,%27,%28,%29,%30,%31}, "
                 "{%32,%33,%34,%35}, %36, p, 1, 1, 0;}\n"
                 : F16(d, 0), F16(d, 16) : "r"(a0), "r"(a1), "r"(a2), "r"(a3), "l"(b), "r"(acc));
}
__device__ __forceinline__ void mma_pv(float (&d)[36], uint32_t a0, uint32_t a1, uint32_t a2, uint32_t a3, uint64_t b) {
    asm volatile("wgmma.mma_async.sync.aligned.m64n72k16.f32.bf16.bf16 {%0,%1,%2,%3,%4,%5,%6,%7,%8,%9,%10,%11,%12,%13,%14,%15,%16,%17,%18,%19,%20,%21,%22,%23,%24,%25,%26,%27,%28,%29,%30,%31,%32,%33,%34,%35}, "
                 "{%36,%37,%38,%39}, %40, 1, 1, 1, 1;\n"
                 : F16(d, 0), F16(d, 16), F4(d, 32) : "r"(a0), "r"(a1), "r"(a2), "r"(a3), "l"(b));
}

template <uint32_t CSTRIDE, int N>
__device__ __forceinline__ void issue_half(float (&d)[N], uint32_t alo, uint32_t blo_, int acc) {
    const uint64_t a = mkdesc(alo), b = mkdesc(blo_);
    wg_fence();
#pragma unroll
    for (int k = 0; k < 8; k++) mma_t(d, a + k * 128, b + (k >> 2) * (CSTRIDE >> 4) + (k & 3) * 2, k == 0 ? acc : 1);
    wg_commit();
}

__device__ __forceinline__ uint32_t load_code(int n, int r, int w) {
    const int tile = 2 * r + w;
    int m, col, row;
    if (n < 16 || n >= 40) {
        const int k = n < 16 ? n : n - 40;
        m = n < 16 ? 1 : 7;
        if (k < 8) { col = 8 * r + (k & 6) + w; row = (k & 1) ^ r; }
        else {
            const int kk = k == 11 ? 12 : (k == 12 ? 11 : k);
            m++; col = kk < 12 ? (tile ^ 2) : tile; row = 4 * r + (kk & 3);
        }
    } else if (n < 32) {
        const int k = n - 16;
        m = 3;
        if (k < 4) { col = tile + ((k & 1) ? 8 : 4); row = (k >> 1) ^ r; }
        else { col = tile; row = (k & 1) ^ r; }
    } else if (n < 34) { m = 4; col = tile; row = n - 32; }
    else if (n < 38) { const int k = n - 34; m = 5; col = tile + 4 * (k & 1); row = (k >> 1) ^ r; }
    else { m = 6; col = tile; row = (n & 1) ^ r; }
    return m | (col << 4) | (row << 8);
}

__global__ void __cluster_dims__(2, 1, 1) __launch_bounds__(NTHREADS, 1)
conformer_kernel(const __grid_constant__ Params p) {
    extern __shared__ __align__(1024) unsigned char smem_raw[];
    const uint32_t sb = smem_u32(smem_raw);
    const uint32_t bars = sb + OFF_BARS;
    const int tid = threadIdx.x;
    const int lane = tid & 31;
    const int warp = __shfl_sync(~0u, tid >> 5, 0);
    const int r = blockIdx.x & 1;
    const int pair = blockIdx.x >> 1;
    const int b = pair >> 5, pt = pair & 31;
    const int ah = pt >> 3, qt = (pt & 7) * 2 + r;
    const int abh = b * 4 + ah;

    TG(30);
    TSINIT();
    TS(0);
    const uint32_t P = sb + OFF_P, H = sb + OFF_H;
    if (tid == 0) {
        asm volatile("prefetch.tensormap [%0];" ::"l"(&p.tm[0]) : "memory");
        asm volatile("prefetch.tensormap [%0];" ::"l"(&p.tm[1]) : "memory");
        prefetch_l2(p.x + (size_t)min(b * T_ + pt * 32 + r * 16, 2 * T_ - 16) * 512, 8192);
        prefetch_l2(p.w[0] + blockIdx.x * 4096, 4096);
    }
    auto xwait = [&](int j) { mbar_wait(bars + (B_XR + (j & 1)) * 8, (j >> 1) & 1); };

    if (__builtin_expect(warp >= 8, 1)) {
        asm volatile("setmaxnreg.dec.sync.aligned.u32 48;");
        if (warp == 8) {
            if (lane == 0) {
                mbar_init(bars + B_XR * 8, 1);
                fence_async_smem();
                mbar_arrive_tx(bars + B_XR * 8, 16384);
            }
            __syncwarp();
#pragma unroll
            for (int i = 0; i < 4; i++) tma3d(P + i * XCH, &p.tm[0], i * 64, pt * 32, b, bars + B_XR * 8);
            TS(1);
            if (lane == 0) {
#pragma unroll
                for (int i = 0; i < 2 * NSLOT; i++) mbar_init(bars + (B_FULL + i) * 8, 1);
                asm volatile("fence.mbarrier_init.release.cluster;" ::: "memory");
                fence_async_smem();
            }
            __syncwarp();
            cluster_arrive();
#pragma unroll 1
            for (int n = 0; n < NSLOT; n++) {
#pragma unroll
                for (int w = 0; w < 2; w++)
                    ring_load(sb + OFF_RING + (w * NSLOT + n) * SLOT, &p.tm[1], 64 * (8 * r + (n & 6) + w), 128 * ((n & 1) ^ r), bars + (B_FULL + w * NSLOT + n) * 8);
            }
            TS(2);
        } else if (warp == 9) {
            cluster_arrive();
        }
        if (warp >= 12) {
            cluster_arrive();
            cluster_wait();
            const int ut = tid & 127;
            const uint32_t a4 = P + (ut >> 2) * 128 + (2 * (ut & 3) + ((ut >> 2) & 1)) * 16;
            const uint32_t a8 = P + (32 + (ut >> 3)) * 128 + (ut & 7) * 16;
#pragma unroll 1
            for (int k = 0; k < 4; k++) {
                float s = 0.f, q = 0.f, s2 = 0.f, q2 = 0.f;
#pragma unroll 1
                for (int h = 0; h < 2; h++) {
                    if (h == 0 && k != 0) bar_sync(1, 384);
                    else xwait(k == 3 ? 4 : k);
                    const uint32_t off = 2 * (r ^ h) * XCH;
                    uint4 v0 = lds128(a4 + off), v1 = lds128((a4 ^ 16) + off), v2 = lds128(a4 + off + XCH), v3 = lds128((a4 ^ 16) + off + XCH);
                    uint4 v4 = make_uint4(0, 0, 0, 0), v5 = v4;
                    if (k == 2) { v4 = lds128(a8 + off); v5 = lds128(a8 + off + XCH); }
                    if (h == 1 || k == 1 || k == 2) bar_arrive(5 + ((v3.w | v5.w) & p.zero), 384);
                    uint32_t t;
                    asm volatile("mov.u32 %0, %%clock;" : "=r"(t)::"memory");
                    const uint32_t mul = 65536u + (t & p.zero), msk = 0u - mul;
                    auto accum = [&](const uint4& v, float& s, float& q) {
                        const float a0 = __uint_as_float(v.x * mul), a1 = __uint_as_float(v.x & msk), a2 = __uint_as_float(v.y * mul), a3 = __uint_as_float(v.y & msk);
                        const float a4 = __uint_as_float(v.z * mul), a5 = __uint_as_float(v.z & msk), a6 = __uint_as_float(v.w * mul), a7 = __uint_as_float(v.w & msk);
                        s += ((a0 + a1) + (a2 + a3)) + ((a4 + a5) + (a6 + a7));
                        q += fmaf(a0, a0, fmaf(a1, a1, fmaf(a2, a2, a3 * a3))) + fmaf(a4, a4, fmaf(a5, a5, fmaf(a6, a6, a7 * a7)));
                    };
                    accum(v0, s, q); accum(v1, s, q); accum(v2, s, q); accum(v3, s, q);
                    if (k == 2) { accum(v4, s2, q2); accum(v5, s2, q2); }
                }
#pragma unroll
                for (int o = 1; o < 8; o <<= 1) {
                    if (o < 4) { s += __shfl_xor_sync(~0u, s, o); q += __shfl_xor_sync(~0u, q, o); }
                    if (k == 2) { s2 += __shfl_xor_sync(~0u, s2, o); q2 += __shfl_xor_sync(~0u, q2, o); }
                }
                const bool second = (ut & 7) == 1;
                if (second) { s = s2; q = q2; }
                const float mean = s * (1.f / 256.f);
                const int row = second ? 32 + (ut >> 3) : ut >> 2;
                const float alpha = k == 1 ? 1.f : ((k == 2 && (uint32_t)(pt * 32 - 8 + row) >= T_) ? 0.f : 0.5f);
                const float rstd = alpha * rsqrtf(fmaxf(fmaf(-mean, mean, q * (1.f / 256.f)), 0.f) + 1e-5f);
                if ((ut & 3) == 0 || second) sts64f(sb + OFF_STATS + row * 8, mean * rstd, rstd);
                __syncwarp();
                if (lane == 0) mbar_arrive(bars + B_ST * 8);
                TS(2 + k);
                if (k == 1 && warp == 12) {
                    const uint32_t epoch = ld_epoch();
                    bar_sync(11, 288);
                    if (lane < 2) flag_set(&g_flag_q[((b * 4 + 2 * r + lane) * 32 + pt) * FS], epoch);
                    __syncwarp();
                    TS(13);
                }
            }
        } else if (warp < 10) {
            const int w = warp - 8;
            const uint32_t ring = sb + OFF_RING + w * NSLOT * SLOT;
            const uint32_t full = bars + (B_FULL + w * NSLOT) * 8;
            const uint32_t code = load_code(lane, r, w) | (load_code(lane + 32, r, w) << 16);
            cluster_wait();
            uint32_t s = 0, ph = 0;
            int n = NSLOT;
#pragma unroll 1
            for (int seg = 0; seg < 2; seg++) {
#pragma unroll 1
                for (; n < (seg == 0 ? 22 : NLOADS); n++) {
                    const uint32_t c = __shfl_sync(~0u, code, n) >> (n & 32 ? 16 : 0);
                    mbar_wait(full + (B_EMPTY - B_FULL) * 8 + s * 8, ph);
                    ring_load(ring + s * SLOT, &p.tm[c & 15], (c & 0xf0) * 4, (c & 0xff00) >> 1, full + s * 8);
                    if (++s == NSLOT) { s = 0; ph ^= 1; }
                }
                if (seg == 1) break;
                const uint32_t epoch = ld_epoch();
                const uint32_t rdy = bars + (B_RDY + 3 * w) * 8, prdy = mapa(rdy, r ^ 1);
                const int isv = r ^ w;
#pragma unroll 1
                for (; n < 32; n++) {
                    mbar_wait(full + (B_EMPTY - B_FULL) * 8 + s * 8, ph);
                    if (lane == 0) {
                        if (n < 24) mbar_arrive(full + s * 8);
                        else mbar_arrive_tx(full + s * 8, SLOT);
                    }
                    if (n == 28) {
                        if (lane == 0) mbar_arrive_peer(prdy);
                        mbar_wait(rdy, 0);
                        if (!isv) {
                            flag_wait(g_flag_kv + (abh * 32 + lane) * FS, epoch);
                            __syncwarp();
                            fence_async_global();
                            TSW(5);
                            ring_load_both(ring + 4 * SLOT, &p.tm[9], (abh * 8 + w) * 128, full + 32);
                        }
                        bar_sync(12, 64);
#pragma unroll
                        for (int i = 0; i < 2; i++) {
                            if (i == 0) mbar_wait(bars + B_QIN * 8, 0);
                            else mbar_wait(full + isv * 8, 1);
                            ring_load_both(ring + (2 * i + isv) * SLOT, &p.tm[9], (isv * 62 + abh * 8 + 2 * i + 2 + w) * 128, full + (2 * i + isv) * 8);
                        }
                    } else if (n > 28) {
                        const uint32_t bo = n == 31 ? 16 : 8;
                        if ((n > 29) == (isv == 1)) {
                            mbar_wait(rdy + bo, 0);
                            ring_load_both(ring + s * SLOT, &p.tm[9], (isv * 64 + abh * 8 + (n == 30 ? 4 : 6) + w) * 128, full + s * 8);
                        } else if (lane == 0) mbar_arrive_peer(prdy + bo);
                    }
                    __syncwarp();
                    if (++s == NSLOT) { s = 0; ph ^= 1; }
                }
            }
        } else if (warp == 10) {
            cluster_arrive();
            cluster_wait();
            const uint32_t epoch = ld_epoch();
            if (lane == 0) {
                mbar_arrive_tx(bars + B_QIN * 8, 8192);
                mbar_arrive_tx(bars + B_OIN * 8, 2 * XCH);
                mbar_arrive_tx(bars + B_OIN * 8 + 8, 2 * XCH);
            }
            if (lane < 2) flag_wait(&g_flag_q[(abh * 32 + 2 * qt + lane) * FS], epoch);
            __syncwarp();
            TSW(6);
            if (lane == 0) {
                fence_async_global();
                bulk_g2s(H + 24576, g_kvq + 2097152 + (size_t)(abh * 1024 + qt * 64) * 128, 8192, bars + B_QIN * 8);
            }
            if (lane < 2) {
                const int np = pt - 1 + 2 * lane;
                if (np >= 0 && np < 32) flag_wait(&g_flag_kv[((b * 4 + 2 * r) * 32 + np) * FS], epoch);
            }
            __syncwarp();
            if (lane == 0) mbar_arrive(bars + B_X1IN * 8);
            bar_sync(9, 64);
            if (lane < 8) {
                const int q = (pt >> 1) + (lane < 4 ? 0 : ((pt & 1) ? 1 : -1));
                if (q >= 0 && q < 16) flag_wait(&g_flag_o[((b * 16 + q) * 4 + (lane & 3)) * FS], epoch);
            }
            __syncwarp();
            TSW(10);
            if (lane == 0) {
                fence_async_global();
#pragma unroll
                for (int i = 0; i < 4; i++)
                    bulk_g2s(H + i * XCH, g_o + (size_t)((b * 4 + i) * PADROWS + pt * 32) * 128, XCH, bars + (B_OIN + (i >> 1)) * 8);
            }
            __syncwarp();
        } else {
            const uint32_t kb = (lane < 2 || lane > 5) ? 4096 : (lane == 2 ? 3072 : (lane == 4 ? 2048 : 1024));
            const char* pf = p.w[lane & 7] + blockIdx.x * kb;
            cluster_arrive();
            cluster_wait();
            xwait(0);
            if (lane == 1 || lane == 2) prefetch_l2(pf, kb);
            if (lane >= 2 && lane < 10) asm volatile("prefetch.tensormap [%0];" ::"l"(&p.tm[lane]) : "memory");
            mbar_wait(bars + B_HF * 8, 0);
            if (lane > 2 && lane < 8) prefetch_l2(pf, kb);
            const uint32_t epoch = ld_epoch();
            bar_sync(4, 288);
            if (lane < 2) flag_set(&g_flag_kv[((b * 4 + 2 * r + lane) * 32 + pt) * FS], epoch);
            __syncwarp();
            TSW(8);
            bar_sync(6, 288);
            bar_arrive(9, 64);
            if (lane == 0) {
                flag_set(&g_flag_o[((b * 16 + qt) * 4 + ah) * FS], epoch);
                g_epoch[blockIdx.x * FS] = epoch;
            }
            __syncwarp();
            TSW(9);
        }
        TSDUMP();
        return;
    }

    if (lane == 0) {
        mbar_init(bars + (B_EMPTY + warp) * 8, 4);
        mbar_init(bars + (B_HF + warp) * 8, warp < 4 ? 8 : 1);
        if (warp < 3) mbar_init(bars + (warp == 2 ? B_ST : B_EMPTY + 8 + warp) * 8, 4);
        else if (warp < 6) mbar_init(bars + (B_XR - 2 + warp) * 8, 1);
        if (warp < 6) mbar_init(bars + (B_RDY + warp) * 8, 1);
        asm volatile("fence.mbarrier_init.release.cluster;" ::: "memory");
    }
    sts128(P + (tid >> 6) * XCH + 4096 + (tid & 63) * 16, 0x3F803F80u, 0x3F803F80u, 0x3F803F80u, 0x3F803F80u);
    fence_async_smem();
    __syncwarp();
    cluster_arrive();
    asm volatile("setmaxnreg.inc.sync.aligned.u32 208;");
    const int w = warp >> 2, wq = warp & 3;
    const int tile = 2 * r + w;
    const int wt = tid & 127;
    const int c4 = lane & 3;
    const uint32_t rbase = sb + OFF_RING + w * NSLOT * SLOT, fbar = bars + (B_FULL + w * NSLOT) * 8;
    const uint32_t rdesc = desc_lo(rbase);
    auto acq = [&](int n) { mbar_wait(fbar + (n % NSLOT) * 8, (n / NSLOT) & 1); };
    auto rel = [&](int n) { if (lane == 0) mbar_arrive(fbar + (B_EMPTY - B_FULL + n % NSLOT) * 8); };
    const uint32_t pown = desc_lo(P + 2 * r * XCH), prem = desc_lo(P + 2 * (r ^ 1) * XCH), hdesc = desc_lo(H);
    const uint32_t toff = ((lane >> 4) * 8 + (lane & 7)) * 128 + (((2 * wq + ((lane >> 3) & 1)) ^ (lane & 7)) << 4);
    const uint32_t xa = P + tile * XCH + toff;
    auto publish = [&](int j, uint32_t src, uint32_t bytes, int nsync) {
        const uint32_t bar = bars + (B_XR + (j & 1)) * 8;
        fence_async_smem();
        bar_sync(2 + w, 128);
        if (wq == 0) peer_copy(mapa(src, r ^ 1), src, bytes, mapa(bar, r ^ 1));
        if (tid == 32) mbar_arrive_tx(bar, 2 * bytes);
        bar_sync(nsync == 384 ? 1 : 10, nsync);
    };
    auto gate = [&](int j) { xwait(j); bar_sync(5, 384); };
    auto load_stats = [&](auto& st, int parity) {
        mbar_wait(bars + B_ST * 8, parity);
#pragma unroll
        for (int j = 0; j < (int)(sizeof(st) / 16); j++) {
            const float4 v = lds128f(sb + OFF_STATS + (8 * j + 2 * c4) * 8);
            st[4 * j] = v.x; st[4 * j + 1] = v.y; st[4 * j + 2] = v.z; st[4 * j + 3] = v.w;
        }
    };
    bar_sync(10, 256);
    cluster_wait();
    uint32_t xr[8];
    TS(56);
    xwait(0);
    TS(57);
    ldsm4t(xa, xr[0], xr[1], xr[2], xr[3]);
    ldsm4t(xa + 2048, xr[4], xr[5], xr[6], xr[7]);
    acq(0);
    TS(58);
    acq(1);

#pragma unroll 1
    for (int ffi = 0; ffi < 2; ffi++) {
        auto mm = [&](auto& d, int n, uint32_t bd, auto cs, int acc) {
            const uint32_t z = p.zero * (ffi + n + 1);
            issue_half<decltype(cs)::value>(d, rdesc + z + (n % NSLOT) * (SLOT >> 4), bd + z, acc);
        };
        constexpr std::integral_constant<uint32_t, XCH> cx{};
        constexpr std::integral_constant<uint32_t, HCH> ch{};
        {
            float st[16], a0[20], a1[20], rem[16], own[16];
            const uint32_t inb = bars + (B_INB + w) * 8, box = sb + OFF_INBOX + w * 4096 + wt * 16;
            const uint32_t hdst = H + w * HCH + toff;
            auto step = [&](auto& d, int n, uint32_t bd, auto cs, int acc) {
                mm(d, n, bd, cs, acc);
                wg_wait<1>();
                if (n > 0) rel(n - 1);
            };
            auto epi = [&](float (&d)[20], int i, int half) {
                uint32_t pk[4];
#pragma unroll
                for (int k = 4 * half; k < 4 * half + 4; k++) {
                    const float cs = d[16 + 2 * (k & 1)];
                    const float v0 = fmaf(-st[(k >> 1) * 4], cs, d[2 * k] * st[(k >> 1) * 4 + 1]);
                    const float v1 = fmaf(-st[(k >> 1) * 4 + 2], cs, d[2 * k + 1] * st[(k >> 1) * 4 + 3]);
                    pk[k & 3] = pack2(fmaf(v0, tanh_fast(v0), v0), fmaf(v1, tanh_fast(v1), v1));
                }
                stsm4t(hdst + 2 * i * HCH + half * 2048, pk[0], pk[1], pk[2], pk[3]);
            };
            auto hdone = [&](int i) {
                fence_async_smem();
                __syncwarp();
                if (lane == 0) mbar_arrive(bars + (B_HF + i) * 8);
            };
            auto hwait = [&](int i) { mbar_wait(bars + (B_HF + i) * 8, ffi); };
            TS(1 + ffi * 20);
            step(a0, 0, pown, cx, 0);
            if (wt == 0) mbar_arrive_tx(inb, 4096);
            acq(2);
            gate(ffi * 4);
            TS(32);
            step(a0, 1, prem, cx, 1);
            step(a1, 2, pown, cx, 0); acq(3); pin(a0); load_stats(st, ffi); TS(33); epi(a0, 0, 0);
            step(a1, 3, prem, cx, 1); acq(4); epi(a0, 0, 1); TS(34);
            step(a0, 4, pown, cx, 0); acq(5); pin(a1); epi(a1, 1, 0);
            step(a0, 5, prem, cx, 1); acq(6); epi(a1, 1, 1); TS(35);
            step(a1, 6, pown, cx, 0); acq(7); pin(a0); hdone(0); epi(a0, 2, 0);
            step(a1, 7, prem, cx, 1); acq(8); hwait(0); epi(a0, 2, 1); TS(36);
            step(rem, 8, hdesc, ch, 0); acq(9); pin(a1); hdone(1); epi(a1, 3, 0);
            step(rem, 9, hdesc + 2 * (HCH >> 4), ch, 1); acq(10); hwait(1); epi(a1, 3, 1);
            TS(2 + ffi * 20);
            step(rem, 10, hdesc + 4 * (HCH >> 4), ch, 1); acq(11); hdone(2);
            step(own, 11, hdesc, ch, 0); acq(12); hwait(2);
            step(rem, 12, hdesc + 6 * (HCH >> 4), ch, 1); acq(13);
            step(own, 13, hdesc + 2 * (HCH >> 4), ch, 1); acq(14);
            pin(rem);
            {
                const uint32_t dst = mapa(box, r ^ 1), bar = mapa(inb, r ^ 1);
                st_async4(dst, pack2(rem[0], rem[1]), pack2(rem[2], rem[3]), pack2(rem[4], rem[5]), pack2(rem[6], rem[7]), bar);
                st_async4(dst + 2048, pack2(rem[8], rem[9]), pack2(rem[10], rem[11]), pack2(rem[12], rem[13]), pack2(rem[14], rem[15]), bar);
            }
            step(own, 14, hdesc + 4 * (HCH >> 4), ch, 1); acq(15);
            step(own, 15, hdesc + 6 * (HCH >> 4), ch, 1);
            mbar_wait(inb, ffi);
            const uint4 u = lds128(box), v = lds128(box + 2048);
            const uint32_t pr[8] = {u.x, u.y, u.z, u.w, v.x, v.y, v.z, v.w};
            if (ffi == 0) { acq(16); acq(17); }
            wg_wait<0>();
            pin(own);
            TS(3 + ffi * 20);
#pragma unroll
            for (int i = 0; i < 8; i++)
                xr[i] = pack2(fmaf(0.5f, own[2 * i] + blo(pr[i]), blo(xr[i])), fmaf(0.5f, own[2 * i + 1] + bhi(pr[i]), bhi(xr[i])));
            stsm4t(xa, xr[0], xr[1], xr[2], xr[3]);
            stsm4t(xa + 2048, xr[4], xr[5], xr[6], xr[7]);
            rel(15);
            publish(ffi ? 5 : 1, P + tile * XCH + (ffi ? (r ^ 1) * 2048 : 0), ffi ? 2048 : 4096, ffi ? 256 : 384);
        }
        if (ffi == 1) break;

        {
            float ak[20], aq[20], st[16];
            g_halo[((pair * 4 + tile) * 2 + 0) * 128 + wt] = make_uint2(xr[0], xr[1]);
            g_halo[((pair * 4 + tile) * 2 + 1) * 128 + wt] = make_uint2(xr[6], xr[7]);
            bar_sync(5, 384);
            TS(11);
            mm(ak, 16, pown, cx, 0);
            mm(aq, 17, pown, cx, 0);
            acq(18); acq(19);
            gate(1);
            mm(ak, 18, prem, cx, 1);
            mm(aq, 19, prem, cx, 1);
            wg_wait<2>();
            rel(16); rel(17);
            load_stats(st, 1);
            auto stage_out = [&](float (&d)[20], uint32_t dst) {
                uint32_t pk[8];
#pragma unroll
                for (int k = 0; k < 8; k++) {
                    const float cs = d[16 + 2 * (k & 1)];
                    pk[k] = pack2(fmaf(-st[(k >> 1) * 4], cs, d[2 * k] * st[(k >> 1) * 4 + 1]),
                                  fmaf(-st[(k >> 1) * 4 + 2], cs, d[2 * k + 1] * st[(k >> 1) * 4 + 3]));
                }
                stsm4t(dst + toff, pk[0], pk[1], pk[2], pk[3]);
                stsm4t(dst + toff + 2048, pk[4], pk[5], pk[6], pk[7]);
            };
            const uint32_t stg = H + w * 12288;
            unsigned char* g = g_kvq + (size_t)((b * 4 + tile) * 1024 + pt * 32) * 128 + wt * 16;
            wg_wait<0>();
            pin(ak); pin(aq);
            TS(37);
            stage_out(ak, stg);
            stage_out(aq, stg + 4096);
            bar_sync(2 + w, 128);
            {
                const uint4 k0 = lds128(stg + wt * 16), k1 = lds128(stg + 2048 + wt * 16), q0 = lds128(stg + 4096 + wt * 16), q1 = lds128(stg + 6144 + wt * 16);
                stg128(g, k0); stg128(g + 2048, k1);
                stg128(g + 1048576, q0); stg128(g + 1048576 + 2048, q1);
            }
            bar_arrive(4, 288);
            TS(38);
            rel(18); rel(19);
            acq(20); acq(21);
            bar_sync(10, 256);
            mm(ak, 20, pown, cx, 0);
            mm(ak, 21, prem, cx, 1);
            wg_wait<0>();
            pin(ak);
            stage_out(ak, stg + 8192);
            rel(20); rel(21);
            bar_sync(2 + w, 128);
            {
                const uint4 v0 = lds128(stg + 8192 + wt * 16), v1 = lds128(stg + 10240 + wt * 16);
                stg128(g + 2097152, v0); stg128(g + 2097152 + 2048, v1);
            }
            bar_arrive(11, 288);
            acq(22); acq(23);
            rel(22); rel(23);
            TS(12);
        }

        {
            constexpr float CS = 0.125f * 1.4426950408889634f;
            float sa[32], sb2[32], o[36];
            uint32_t pa[16], pb[16], q[16];
            float n0 = INFINITY, n1 = INFINITY;
            zero(o); zero(pa); zero(pb);
            const uint32_t ones = sb + OFF_INBOX + 2048;
            if (tid < 128) sts128(ones + tid * 16, 0x3F803F80u, 0x3F803F80u, 0x3F803F80u, 0x3F803F80u);
            fence_async_smem();
            bar_sync(10, 256);
            const uint32_t vdesc = rdesc + ((((ones - rbase) >> 4) - 1) << 16);
            auto qk_issue = [&](float (&s)[32], uint32_t lo) {
                const uint64_t kd = mkdesc(lo);
                wg_fence();
#pragma unroll
                for (int k = 0; k < 4; k++) mma_qk(s, q[4 * k], q[4 * k + 1], q[4 * k + 2], q[4 * k + 3], kd + 2 * k, k != 0);
                wg_commit();
            };
            auto pv_issue = [&](uint32_t (&pp)[16], uint32_t lo) {
                const uint64_t vd = mkdesc(lo);
                wg_fence();
#pragma unroll
                for (int k = 0; k < 4; k++) mma_pv(o, pp[4 * k], pp[4 * k + 1], pp[4 * k + 2], pp[4 * k + 3], vd - k * (128 * 65535));
                wg_commit();
            };
            auto new_max = [&](float (&s)[32], float& x0, float& x1) {
                x0 = s[0]; x1 = s[2];
#pragma unroll
                for (int j = 0; j < 8; j++) {
                    x0 = fmaxf(x0, fmaxf(s[4 * j], s[4 * j + 1]));
                    x1 = fmaxf(x1, fmaxf(s[4 * j + 2], s[4 * j + 3]));
                }
                x0 = fmaxf(x0, __shfl_xor_sync(~0u, x0, 1)); x1 = fmaxf(x1, __shfl_xor_sync(~0u, x1, 1));
                x0 = fmaxf(x0, __shfl_xor_sync(~0u, x0, 2)); x1 = fmaxf(x1, __shfl_xor_sync(~0u, x1, 2));
                x0 = fminf(n0, fmaf(x0, -CS, -20.f)); x1 = fminf(n1, fmaf(x1, -CS, -20.f));
            };
            auto probs = [&](float (&s)[32], uint32_t (&pp)[16], bool ready, auto wait) {
                uint32_t any = 0;
#pragma unroll
                for (int i = 0; i < 16; i++) {
                    pp[i] = pack2(ex2(fmaf(s[2 * i], CS, (i & 1) ? n1 : n0)), ex2(fmaf(s[2 * i + 1], CS, (i & 1) ? n1 : n0)));
                    any |= pp[i];
                }
                float sc0 = 1.f, sc1 = 1.f;
                const bool slow = __any_sync(~0u, (any & 0x40004000u) || !ready);
                if (slow) {
                    wait();
                    if (__any_sync(~0u, any & 0x40004000u)) {
                        float x0, x1;
                        new_max(s, x0, x1);
                        sc0 = ex2(x0 - n0); sc1 = ex2(x1 - n1);
                        n0 = x0; n1 = x1;
#pragma unroll
                        for (int i = 0; i < 16; i++)
                            pp[i] = pack2(ex2(fmaf(s[2 * i], CS, (i & 1) ? n1 : n0)), ex2(fmaf(s[2 * i + 1], CS, (i & 1) ? n1 : n0)));
                    }
                }
                wg_wait<0>();
                pin(sa); pin(sb2); pin(o); pin(pa); pin(pb);
                if (slow) {
#pragma unroll
                    for (int j = 0; j < 9; j++) { o[4 * j] *= sc0; o[4 * j + 1] *= sc0; o[4 * j + 2] *= sc1; o[4 * j + 3] *= sc1; }
                }
            };
            mbar_wait(bars + B_QIN * 8, 0);
            {
                const uint32_t qa = H + 24576 + (wq * 16 + (lane & 15)) * 128;
#pragma unroll
                for (int k = 0; k < 4; k++) ldsm4(qa + (((2 * k + (lane >> 4)) ^ (lane & 7)) << 4), q[4 * k], q[4 * k + 1], q[4 * k + 2], q[4 * k + 3]);
                pin(q);
            }
            TS(40);
            acq(24);
            TS(13);
            qk_issue(sa, rdesc + (24 % NSLOT) * (SLOT >> 4));
            qk_issue(sb2, rdesc + (24 % NSLOT) * (SLOT >> 4) + 512);
            wg_wait<1>();
            pin(sa);
            {
                float x0, x1;
                new_max(sa, x0, x1);
                n0 = x0; n1 = x1;
            }
            if (w == 1) bar_sync(7, 256);
            uint32_t vd = vdesc - (SLOT >> 4) * 65535u, kd = rdesc, vb = fbar + 8, kb = fbar;
            uint32_t vlast = vdesc - 4 * (SLOT >> 4) * 65535u;
            uint32_t kprev = fbar + 32, vprev = bars + (B_HF + 3 - (B_EMPTY - B_FULL)) * 8;
#pragma unroll 1
            for (int it = 0; it < 4; it++) {
                pv_issue(pb, vlast);
                probs(sa, pa, mbar_test(vb, it < 2) & mbar_test(kb, it < 3), [&]() { mbar_wait(vb, it < 2); mbar_wait(kb, it < 3); });
                TS(41 + it * 4);
                if (it == 0 && w == 0) bar_arrive(7, 256);
                if (it == 3 && w == 1) {
#pragma unroll
                    for (int i = 20; i < 32; i++) sb2[i] = -INFINITY;
                }
                pin(sb2);
                if (it < 3) qk_issue(sa, kd);
                if (lane == 0) mbar_arrive(kprev + (B_EMPTY - B_FULL) * 8);
                if (lane == 0) mbar_arrive(vprev + (B_EMPTY - B_FULL) * 8);
                pv_issue(pa, vd);
                probs(sb2, pb, true, []() {});
                TS(43 + it * 4);
                if (it < 3) qk_issue(sb2, kd + 512);
                const int dv = it == 0 ? 2 : (it == 1 ? -3 : 1);
                kprev = kb; vprev = vb; vlast = vd - 512 * 65535u;
                vd -= dv * (SLOT >> 4) * 65535u; vb += dv * 8;
                kd += 2 * (SLOT >> 4); kb = it == 2 ? vb : kb + 16;
            }
            pv_issue(pb, vlast);
            const int row = wq * 16 + (lane >> 2);
            const uint32_t ml = sb + OFF_INBOX;
            wg_wait<0>();
            pin(o); pin(pb); pin(sa); pin(sb2);
            rel(31);
            const float l0 = o[32], l1 = o[34];
            if (c4 == 0) { sts64f(ml + w * 512 + row * 8, n0, l0); sts64f(ml + w * 512 + row * 8 + 64, n1, l1); }
            TS(14);
            float mine[16];
#pragma unroll
            for (int j = 0; j < 4; j++) {
                if (w == 0) sts128f(H + j * 2048 + wt * 16, o[16 + 4 * j], o[17 + 4 * j], o[18 + 4 * j], o[19 + 4 * j]);
                else sts128f(H + 8192 + j * 2048 + wt * 16, o[4 * j], o[4 * j + 1], o[4 * j + 2], o[4 * j + 3]);
            }
#pragma unroll
            for (int i = 0; i < 16; i++) mine[i] = w == 0 ? o[i] : o[16 + i];
            bar_sync(10, 256);
            const float2 u0 = lds64f(ml + (w ^ 1) * 512 + row * 8), u1 = lds64f(ml + (w ^ 1) * 512 + row * 8 + 64);
            const float x0 = fminf(n0, u0.x), x1 = fminf(n1, u1.x);
            float a0 = ex2(x0 - n0), b0 = ex2(x0 - u0.x), a1 = ex2(x1 - n1), b1 = ex2(x1 - u1.x);
            const float i0 = __fdividef(1.f, fmaf(a0, l0, b0 * u0.y)), i1 = __fdividef(1.f, fmaf(a1, l1, b1 * u1.y));
            a0 *= i0; b0 *= i0; a1 *= i1; b1 *= i1;
            uint32_t pk[8];
#pragma unroll
            for (int j = 0; j < 4; j++) {
                const float4 v = lds128f(H + (w ^ 1) * 8192 + j * 2048 + wt * 16);
                pk[2 * j] = pack2(fmaf(a0, mine[4 * j], b0 * v.x), fmaf(a0, mine[4 * j + 1], b0 * v.y));
                pk[2 * j + 1] = pack2(fmaf(a1, mine[4 * j + 2], b1 * v.z), fmaf(a1, mine[4 * j + 3], b1 * v.w));
            }
            const uint32_t og = H + 16384 + wq * 2048;
            {
                const uint32_t ra = og + (((lane >> 3) & 1) * 8 + (lane & 7)) * 128;
                stsm4(ra + (((4 * w + (lane >> 4)) ^ (lane & 7)) << 4), pk[0], pk[1], pk[2], pk[3]);
                stsm4(ra + (((4 * w + 2 + (lane >> 4)) ^ (lane & 7)) << 4), pk[4], pk[5], pk[6], pk[7]);
            }
            __syncwarp();
            {
                const uint32_t off = (lane >> 2) * 128 + (((4 * w + c4) ^ (lane >> 2)) << 4);
                const uint4 v0 = lds128(og + off), v1 = lds128(og + off + 1024);
                unsigned char* dst = g_o + (size_t)(abh * PADROWS + 8 + qt * 64 + wq * 16) * 128 + off;
                stg128(dst, v0); stg128(dst + 1024, v1);
            }
            bar_arrive(6, 288);
            TS(15);
        }

        uint32_t dwr[15];
        {
#pragma unroll
            for (int i = 0; i < 15; i++) dwr[i] = hmul2(__ldg(reinterpret_cast<const uint32_t*>(p.dw + i * 256 + tile * 64) + lane), 0x3F003F00u);
            float d[24];
            uint32_t xw[12];
            mbar_wait(bars + B_X1IN * 8, 0);
            uint2 hl = make_uint2(0, 0), hr = hl;
            if (pt > 0) hl = __ldcg(&g_halo[(((pair - 1) * 4 + tile) * 2 + 1) * 128 + wt]);
            if (pt < 31) hr = __ldcg(&g_halo[(((pair + 1) * 4 + tile) * 2 + 0) * 128 + wt]);
            xw[0] = hl.x; xw[1] = hl.y; xw[10] = hr.x; xw[11] = hr.y;
#pragma unroll
            for (int i = 0; i < 8; i++) xw[2 + i] = xr[i];
            pin(xw);
            pin(dwr);
            acq(32); acq(33); acq(34); acq(35);
            mbar_wait(bars + B_OIN * 8, 0);
            TS(16);
            mm(d, 32, hdesc, cx, 0);
            mbar_wait(bars + B_OIN * 8 + 8, 0);
            mm(d, 33, hdesc + 2 * (XCH >> 4), cx, 1);
            wg_wait<1>();
            rel(32);
            wg_wait<0>();
            pin(d);
#pragma unroll
            for (int i = 0; i < 12; i++) xw[i] = pack2(d[2 * i] + blo(xw[i]), d[2 * i + 1] + bhi(xw[i]));
            if (c4 == 0) { xw[0] = (xw[0] & 0xffff0000u) | 0x3F80u; xw[1] = (xw[1] & 0xffff0000u) | 0x3F80u; }
#pragma unroll
            for (int j = 0; j < 3; j++) stsm4t(xa + j * 2048, xw[4 * j], xw[4 * j + 1], xw[4 * j + 2], xw[4 * j + 3]);
#pragma unroll
            for (int i = 0; i < 8; i++) xr[i] = xw[2 + i];
            rel(33);
            publish(2, P + tile * XCH, XCH, 384);
            TS(17);
        }
        {
            float da[24], db[24], st[24];
            bar_sync(5, 384);
            mm(da, 34, pown, cx, 0);
            mm(db, 35, pown, cx, 0);
            acq(36); acq(37);
            gate(2);
            TS(39);
            mm(da, 36, prem, cx, 1);
            mm(db, 37, prem, cx, 1);
            wg_wait<2>();
            rel(34); rel(35);
            load_stats(st, 0);
            wg_wait<0>();
            pin(da); pin(db);
            rel(36); rel(37);
            TS(18);
            uint32_t pk[12];
#pragma unroll
            for (int hh = 0; hh < 2; hh++) {
                const float ca = __shfl_sync(~0u, da[2 * hh], lane & 28), cb = __shfl_sync(~0u, db[2 * hh], lane & 28);
#pragma unroll
                for (int j = 0; j < 6; j++) {
                    const float u0 = fmaf(-st[4 * j], ca, da[4 * j + 2 * hh] * st[4 * j + 1]);
                    const float u1 = fmaf(-st[4 * j + 2], ca, da[4 * j + 2 * hh + 1] * st[4 * j + 3]);
                    const float v0 = fmaf(-st[4 * j], cb, db[4 * j + 2 * hh] * st[4 * j + 1]);
                    const float v1 = fmaf(-st[4 * j + 2], cb, db[4 * j + 2 * hh + 1] * st[4 * j + 3]);
                    pk[2 * j + hh] = pack2(fmaf(u0, tanh_fast(v0), u0), fmaf(u1, tanh_fast(v1), u1));
                }
            }
            const uint32_t gs = H + 16384 + w * XCH;
#pragma unroll
            for (int j = 0; j < 3; j++) stsm4t(gs + toff + j * 2048, pk[4 * j], pk[4 * j + 1], pk[4 * j + 2], pk[4 * j + 3]);
            bar_sync(2 + w, 128);
            uint32_t ca[8], cb[8];
            const uint32_t grow = gs + 8 * wq * 128 + c4 * 4, srow = H + tile * HCH + 8 * wq * 128 + c4 * 4;
#pragma unroll
            for (int k = 0; k < 22; k++) {
                const uint32_t v = lds32(grow + (1 + k) * 128 + (((lane >> 2) ^ ((1 + k) & 7)) << 4));
#pragma unroll
                for (int i = 0; i < 8; i++) {
                    const int tap = k - i;
                    if (tap == 0) ca[i] = hmul2(v, dwr[0]);
                    else if (tap > 0 && tap < 8) ca[i] = hfma2(v, dwr[tap], ca[i]);
                    else if (tap == 8) cb[i] = hmul2(v, dwr[8]);
                    else if (tap > 8 && tap < 15) cb[i] = hfma2(v, dwr[tap], cb[i]);
                }
            }
#pragma unroll
            for (int i = 0; i < 8; i++) {
                const float h0 = blo(ca[i]) + blo(cb[i]), h1 = bhi(ca[i]) + bhi(cb[i]);
                sts32(srow + i * 128 + (((lane >> 2) ^ i) << 4), pack2(fmaf(h0, tanh_fast(h0), h0), fmaf(h1, tanh_fast(h1), h1)));
            }
            acq(38); acq(39);
            publish(3, H + tile * HCH, HCH, 256);
            TS(19);
        }
        {
            float d[16];
            mm(d, 38, hdesc + 2 * r * (HCH >> 4), ch, 0);
            acq(40); acq(41);
            xwait(3);
            sts128(P + (wt >> 6 ? (tile ^ 2) : tile) * XCH + 4096 + (wt & 63) * 16, 0x3F803F80u, 0x3F803F80u, 0x3F803F80u, 0x3F803F80u);
            mm(d, 39, hdesc + 2 * (r ^ 1) * (HCH >> 4), ch, 1);
            wg_wait<1>();
            rel(38);
            wg_wait<0>();
            pin(d);
#pragma unroll
            for (int i = 0; i < 8; i++) xr[i] = pack2(d[2 * i] + blo(xr[i]), d[2 * i + 1] + bhi(xr[i]));
            stsm4t(xa, xr[0], xr[1], xr[2], xr[3]);
            stsm4t(xa + 2048, xr[4], xr[5], xr[6], xr[7]);
            rel(39);
            publish(4, P + tile * XCH, HCH, 384);
            TS(20);
        }
    }

    xwait(5);
    cluster_arrive();
    TS(24);
    {
        float a[2][8], s[2], q[2];
        const int row0 = 16 * r + 2 * warp;
#pragma unroll
        for (int i = 0; i < 2; i++) {
            const uint4 v = lds128(P + (lane >> 3) * XCH + (row0 + i) * 128 + (((lane & 7) ^ ((row0 + i) & 7)) << 4));
            a[i][0] = blo(v.x); a[i][1] = bhi(v.x); a[i][2] = blo(v.y); a[i][3] = bhi(v.y);
            a[i][4] = blo(v.z); a[i][5] = bhi(v.z); a[i][6] = blo(v.w); a[i][7] = bhi(v.w);
            s[i] = ((a[i][0] + a[i][1]) + (a[i][2] + a[i][3])) + ((a[i][4] + a[i][5]) + (a[i][6] + a[i][7]));
            q[i] = 0.f;
#pragma unroll
            for (int k = 0; k < 8; k++) q[i] = fmaf(a[i][k], a[i][k], q[i]);
        }
#pragma unroll
        for (int o = 16; o > 0; o >>= 1) {
#pragma unroll
            for (int i = 0; i < 2; i++) { s[i] += __shfl_xor_sync(~0u, s[i], o); q[i] += __shfl_xor_sync(~0u, q[i], o); }
        }
#pragma unroll
        for (int i = 0; i < 2; i++) {
            const float mean = s[i] * (1.f / 256.f);
            const float rstd = rsqrtf(fmaxf(fmaf(-mean, mean, q[i] * (1.f / 256.f)), 0.f) + 1e-5f);
            const float nb = -mean * rstd;
            uint4 v;
            v.x = pack2(fmaf(a[i][0], rstd, nb), fmaf(a[i][1], rstd, nb)); v.y = pack2(fmaf(a[i][2], rstd, nb), fmaf(a[i][3], rstd, nb));
            v.z = pack2(fmaf(a[i][4], rstd, nb), fmaf(a[i][5], rstd, nb)); v.w = pack2(fmaf(a[i][6], rstd, nb), fmaf(a[i][7], rstd, nb));
            const int t = pt * 32 + row0 + i;
            if (t < T_) stg128(p.out + (size_t)(b * T_ + t) * 256 + lane * 8, v);
        }
    }
    TS(25);
    TG(31);
    TSDUMP();
    cluster_wait();
}

typedef CUresult (*EncodeFn)(CUtensorMap*, CUtensorMapDataType, cuuint32_t, void*, const cuuint64_t*, const cuuint64_t*,
                             const cuuint32_t*, const cuuint32_t*, CUtensorMapInterleave, CUtensorMapSwizzle,
                             CUtensorMapL2promotion, CUtensorMapFloatOOBfill);

}

extern "C" void kernel_launch(void* const* d_in, const int* in_sizes, int n_in, void* d_out, int out_size) {
    static EncodeFn encode = nullptr;
    if (!encode) {
        void* fn = nullptr;
        cudaDriverEntryPointQueryResult qr;
        cudaGetDriverEntryPoint("cuTensorMapEncodeTiled", &fn, cudaEnableDefault, &qr);
        encode = (EncodeFn)fn;
        cudaFuncSetAttribute(conformer_kernel, cudaFuncAttributeMaxDynamicSharedMemorySize, SMEM_LAUNCH);
    }
    Params p;
    const cuuint32_t ones[3] = {1, 1, 1};
    {
        const cuuint64_t dims[3] = {256, T_, 2};
        const cuuint64_t strides[2] = {512, 512ull * T_};
        const cuuint32_t box[3] = {64, 32, 1};
        encode(&p.tm[0], CU_TENSOR_MAP_DATA_TYPE_BFLOAT16, 3, d_in[0], dims, strides, box, ones, CU_TENSOR_MAP_INTERLEAVE_NONE,
               CU_TENSOR_MAP_SWIZZLE_128B, CU_TENSOR_MAP_L2_PROMOTION_L2_256B, CU_TENSOR_MAP_FLOAT_OOB_FILL_NONE);
    }
    const int idx[8] = {1, 2, 3, 4, 5, 7, 8, 9};
    const int rows[8] = {256, 1024, 256, 256, 256, 256, 256, 1024};
    const int cols[8] = {1024, 256, 768, 256, 512, 256, 1024, 256};
    for (int i = 0; i < 8; i++) {
        const cuuint64_t dims[2] = {(cuuint64_t)cols[i], (cuuint64_t)rows[i]};
        const cuuint64_t strides[1] = {(cuuint64_t)cols[i] * 2};
        const cuuint32_t box[2] = {64, 128};
        encode(&p.tm[1 + i], CU_TENSOR_MAP_DATA_TYPE_BFLOAT16, 2, d_in[idx[i]], dims, strides, box, ones, CU_TENSOR_MAP_INTERLEAVE_NONE,
               CU_TENSOR_MAP_SWIZZLE_128B, CU_TENSOR_MAP_L2_PROMOTION_L2_128B, CU_TENSOR_MAP_FLOAT_OOB_FILL_NONE);
        p.w[i] = (const char*)d_in[idx[i]];
    }
    {
        void* kv = nullptr;
        cudaGetSymbolAddress(&kv, g_kvq);
        const cuuint64_t dims[2] = {64, 16384};
        const cuuint64_t strides[1] = {128};
        const cuuint32_t box[2] = {64, 128};
        encode(&p.tm[9], CU_TENSOR_MAP_DATA_TYPE_BFLOAT16, 2, kv, dims, strides, box, ones, CU_TENSOR_MAP_INTERLEAVE_NONE,
               CU_TENSOR_MAP_SWIZZLE_NONE, CU_TENSOR_MAP_L2_PROMOTION_L2_128B, CU_TENSOR_MAP_FLOAT_OOB_FILL_NONE);
    }
    p.x = (const char*)d_in[0];
    p.dw = (const __nv_bfloat16*)d_in[6];
    p.out = (__nv_bfloat16*)d_out;
    p.zero = 0;
    conformer_kernel<<<NCTA, NTHREADS, SMEM_LAUNCH>>>(p);
}
```

```cpp
#include <cuda_runtime.h>
#include <cuda_bf16.h>
#include <cuda.h>
#include <stdint.h>
#include <type_traits>

namespace {

constexpr int T_ = 1000;
constexpr int NCTA = 128;
constexpr int NTHREADS = 512;
constexpr int NSLOT = 5;
constexpr int SLOT = 16384;
constexpr int NLOADS = 56;

constexpr uint32_t OFF_RING = 0;
constexpr uint32_t OFF_P = 163840;
constexpr uint32_t OFF_H = 188416;
constexpr uint32_t OFF_INBOX = 221184;
constexpr uint32_t OFF_STATS = 229376;
constexpr uint32_t OFF_BARS = 229888;
constexpr uint32_t SMEM_BYTES = 230400;
constexpr uint32_t XCH = 6144;
constexpr uint32_t HCH = 4096;

constexpr int B_FULL = 0, B_EMPTY = 10, B_XR = 20, B_OIN = 22, B_HF = 24, B_INB = 28, B_QIN = 30, B_X1IN = 31, B_ST = 32, B_RDY = 33;

constexpr int PADROWS = 1040;
constexpr int FS = 8;

struct Params {
    CUtensorMap tm[10];
    const char* w[8];
    const __nv_bfloat16* dw;
    __nv_bfloat16* out;
    uint32_t zero;
};

__device__ __align__(1024) unsigned char g_kvq[3 * 8 * 1024 * 128];
__device__ __align__(1024) unsigned char g_o[8 * PADROWS * 128];
__device__ uint2 g_halo[64 * 4 * 2 * 128];
__device__ uint32_t g_flag_kv[8 * 32 * FS];
__device__ uint32_t g_flag_q[8 * 32 * FS];
__device__ uint32_t g_flag_o[2 * 16 * 4 * FS];
__device__ uint32_t g_epoch[NCTA * FS];

#define TS(i) do { } while (0)
#define TSW(i) do { } while (0)
#define TG(i) do { } while (0)
#define TSINIT() do { } while (0)
#define TSDUMP() do { } while (0)
constexpr uint32_t SMEM_LAUNCH = SMEM_BYTES;

__device__ __forceinline__ uint32_t smem_u32(const void* p) { return (uint32_t)__cvta_generic_to_shared(p); }
__device__ __forceinline__ void mbar_init(uint32_t b, uint32_t c) { asm volatile("mbarrier.init.shared::cta.b64 [%0], %1;" ::"r"(b), "r"(c) : "memory"); }
__device__ __forceinline__ void mbar_arrive(uint32_t b) { asm volatile("mbarrier.arrive.shared::cta.b64 _, [%0];" ::"r"(b) : "memory"); }
__device__ __forceinline__ void mbar_arrive_tx(uint32_t b, uint32_t tx) { asm volatile("mbarrier.arrive.expect_tx.shared::cta.b64 _, [%0], %1;" ::"r"(b), "r"(tx) : "memory"); }
__device__ __forceinline__ void mbar_wait(uint32_t b, uint32_t ph) {
    asm volatile("{\n.reg .pred p, q;\n.reg .u32 c;\nmov.u32 c, 0;\n"
                 "MW_LOOP:\n.pragma \"nounroll\";\n"
                 "mbarrier.try_wait.parity.shared::cta.b64 p, [%0], %1;\n"
                 "add.u32 c, c, 1;\nsetp.lt.u32 q, c, 65536;\nnot.pred p, p;\nand.pred p, p, q;\n@p bra MW_LOOP;\n}"
                 ::"r"(b), "r"(ph) : "memory");
}
__device__ __forceinline__ bool mbar_test(uint32_t b, uint32_t ph) {
    uint32_t ok;
    asm volatile("{\n.reg .pred p;\nmbarrier.test_wait.parity.shared::cta.b64 p, [%1], %2;\nselp.u32 %0, 1, 0, p;\n}" : "=r"(ok) : "r"(b), "r"(ph) : "memory");
    return ok;
}
__device__ __forceinline__ uint32_t mapa(uint32_t a, uint32_t r) { uint32_t o; asm("mapa.shared::cluster.u32 %0, %1, %2;" : "=r"(o) : "r"(a), "r"(r)); return o; }
__device__ __forceinline__ void fence_async_smem() { asm volatile("fence.proxy.async.shared::cta;" ::: "memory"); }
__device__ __forceinline__ void fence_async_global() { asm volatile("fence.proxy.async.global;" ::: "memory"); }
__device__ __forceinline__ void bar_sync(int id, int n) { asm volatile("bar.sync %0, %1;" ::"r"(id), "r"(n) : "memory"); }
__device__ __forceinline__ void bar_arrive(int id, int n) { asm volatile("bar.arrive %0, %1;" ::"r"(id), "r"(n) : "memory"); }
__device__ __forceinline__ void cluster_arrive() { asm volatile("barrier.cluster.arrive.relaxed.aligned;" ::: "memory"); }
__device__ __forceinline__ void cluster_wait() { asm volatile("barrier.cluster.wait.aligned;" ::: "memory"); }

__device__ __forceinline__ void ring_load(uint32_t dst, const CUtensorMap* tm, int c0, int c1, uint32_t bar) {
    asm volatile("{\n.reg .pred p;\nelect.sync _|p, 0xffffffff;\n"
                 "@p mbarrier.arrive.expect_tx.shared::cta.b64 _, [%2], 16384;\n"
                 "@p cp.async.bulk.tensor.2d.shared::cluster.global.mbarrier::complete_tx::bytes [%0], [%1, {%3, %4}], [%2];\n}"
                 ::"r"(dst), "l"(tm), "r"(bar), "r"(c0), "r"(c1) : "memory");
}
__device__ __forceinline__ void ring_load_both(uint32_t dst, const CUtensorMap* tm, int c1, uint32_t bar) {
    asm volatile("{\n.reg .pred p;\nelect.sync _|p, 0xffffffff;\n"
                 "@p cp.async.bulk.tensor.2d.shared::cluster.global.mbarrier::complete_tx::bytes.multicast::cluster [%0], [%1, {0, %3}], [%2], %4;\n}"
                 ::"r"(dst), "l"(tm), "r"(bar), "r"(c1), "h"((uint16_t)3) : "memory");
}
__device__ __forceinline__ void mbar_arrive_peer(uint32_t b) { asm volatile("mbarrier.arrive.relaxed.cluster.shared::cluster.b64 _, [%0];" ::"r"(b) : "memory"); }
__device__ __forceinline__ void tma3d(uint32_t dst, const CUtensorMap* tm, int c0, int c1, int c2, uint32_t bar) {
    asm volatile("{\n.reg .pred p;\nelect.sync _|p, 0xffffffff;\n"
                 "@p cp.async.bulk.tensor.3d.shared::cluster.global.mbarrier::complete_tx::bytes [%0], [%1, {%3, %4, %5}], [%2];\n}"
                 ::"r"(dst), "l"(tm), "r"(bar), "r"(c0), "r"(c1), "r"(c2) : "memory");
}
__device__ __forceinline__ void bulk_g2s(uint32_t dst, const void* src, uint32_t bytes, uint32_t bar) {
    asm volatile("cp.async.bulk.shared::cluster.global.mbarrier::complete_tx::bytes [%0], [%1], %2, [%3];" ::"r"(dst), "l"(src), "r"(bytes), "r"(bar) : "memory");
}
__device__ __forceinline__ void prefetch_l2(const void* src, uint32_t bytes) {
    asm volatile("cp.async.bulk.prefetch.L2.global [%0], %1;" ::"l"(src), "r"(bytes) : "memory");
}
__device__ __forceinline__ void peer_copy(uint32_t dst, uint32_t src, uint32_t bytes, uint32_t rbar) {
    asm volatile("{\n.reg .pred p;\nelect.sync _|p, 0xffffffff;\n"
                 "@p cp.async.bulk.shared::cluster.shared::cta.mbarrier::complete_tx::bytes [%0], [%1], %2, [%3];\n}"
                 ::"r"(dst), "r"(src), "r"(bytes), "r"(rbar) : "memory");
}
__device__ __forceinline__ void st_async4(uint32_t dst, uint32_t a, uint32_t b, uint32_t c, uint32_t d, uint32_t bar) {
    asm volatile("st.async.shared::cluster.mbarrier::complete_tx::bytes.v4.b32 [%0], {%1,%2,%3,%4}, [%5];" ::"r"(dst), "r"(a), "r"(b), "r"(c), "r"(d), "r"(bar) : "memory");
}
__device__ __forceinline__ void stsm4t(uint32_t a, uint32_t r0, uint32_t r1, uint32_t r2, uint32_t r3) {
    asm volatile("stmatrix.sync.aligned.m8n8.x4.trans.shared.b16 [%0], {%1,%2,%3,%4};" ::"r"(a), "r"(r0), "r"(r1), "r"(r2), "r"(r3) : "memory");
}
__device__ __forceinline__ void stsm4(uint32_t a, uint32_t r0, uint32_t r1, uint32_t r2, uint32_t r3) {
    asm volatile("stmatrix.sync.aligned.m8n8.x4.shared.b16 [%0], {%1,%2,%3,%4};" ::"r"(a), "r"(r0), "r"(r1), "r"(r2), "r"(r3) : "memory");
}
__device__ __forceinline__ void ldsm4t(uint32_t a, uint32_t& r0, uint32_t& r1, uint32_t& r2, uint32_t& r3) {
    asm volatile("ldmatrix.sync.aligned.m8n8.x4.trans.shared.b16 {%0,%1,%2,%3}, [%4];" : "=r"(r0), "=r"(r1), "=r"(r2), "=r"(r3) : "r"(a) : "memory");
}
__device__ __forceinline__ void ldsm4(uint32_t a, uint32_t& r0, uint32_t& r1, uint32_t& r2, uint32_t& r3) {
    asm volatile("ldmatrix.sync.aligned.m8n8.x4.shared.b16 {%0,%1,%2,%3}, [%4];" : "=r"(r0), "=r"(r1), "=r"(r2), "=r"(r3) : "r"(a) : "memory");
}
__device__ __forceinline__ uint4 lds128(uint32_t a) { uint4 v; asm volatile("ld.shared.v4.b32 {%0,%1,%2,%3}, [%4];" : "=r"(v.x), "=r"(v.y), "=r"(v.z), "=r"(v.w) : "r"(a) : "memory"); return v; }
__device__ __forceinline__ float4 lds128f(uint32_t a) { float4 v; asm volatile("ld.shared.v4.f32 {%0,%1,%2,%3}, [%4];" : "=f"(v.x), "=f"(v.y), "=f"(v.z), "=f"(v.w) : "r"(a) : "memory"); return v; }
__device__ __forceinline__ float2 lds64f(uint32_t a) { float2 v; asm volatile("ld.shared.v2.f32 {%0,%1}, [%2];" : "=f"(v.x), "=f"(v.y) : "r"(a) : "memory"); return v; }
__device__ __forceinline__ uint32_t lds32(uint32_t a) { uint32_t v; asm volatile("ld.shared.b32 %0, [%1];" : "=r"(v) : "r"(a) : "memory"); return v; }
__device__ __forceinline__ void sts128(uint32_t a, uint32_t x, uint32_t y, uint32_t z, uint32_t w) { asm volatile("st.shared.v4.b32 [%0], {%1,%2,%3,%4};" ::"r"(a), "r"(x), "r"(y), "r"(z), "r"(w) : "memory"); }
__device__ __forceinline__ void sts128f(uint32_t a, float x, float y, float z, float w) { asm volatile("st.shared.v4.f32 [%0], {%1,%2,%3,%4};" ::"r"(a), "f"(x), "f"(y), "f"(z), "f"(w) : "memory"); }
__device__ __forceinline__ void sts64f(uint32_t a, float x, float y) { asm volatile("st.shared.v2.f32 [%0], {%1,%2};" ::"r"(a), "f"(x), "f"(y) : "memory"); }
__device__ __forceinline__ void sts32(uint32_t a, uint32_t x) { asm volatile("st.shared.b32 [%0], %1;" ::"r"(a), "r"(x) : "memory"); }
__device__ __forceinline__ void stg128(void* p, uint4 v) { asm volatile("st.global.v4.b32 [%0], {%1,%2,%3,%4};" ::"l"(p), "r"(v.x), "r"(v.y), "r"(v.z), "r"(v.w) : "memory"); }

__device__ __forceinline__ uint32_t pack2(float lo, float hi) { uint32_t r; asm("cvt.rn.bf16x2.f32 %0, %1, %2;" : "=r"(r) : "f"(hi), "f"(lo)); return r; }
__device__ __forceinline__ float blo(uint32_t v) { return __uint_as_float(v << 16); }
__device__ __forceinline__ float bhi(uint32_t v) { return __uint_as_float(v & 0xffff0000u); }
__device__ __forceinline__ uint32_t hmul2(uint32_t a, uint32_t b) { uint32_t r; asm("mul.rn.bf16x2 %0, %1, %2;" : "=r"(r) : "r"(a), "r"(b)); return r; }
__device__ __forceinline__ uint32_t hfma2(uint32_t a, uint32_t b, uint32_t c) { uint32_t r; asm("fma.rn.bf16x2 %0, %1, %2, %3;" : "=r"(r) : "r"(a), "r"(b), "r"(c)); return r; }
__device__ __forceinline__ float tanh_fast(float x) { float r; asm("tanh.approx.f32 %0, %1;" : "=f"(r) : "f"(x)); return r; }
__device__ __forceinline__ float ex2(float x) { float r; asm("ex2.approx.ftz.f32 %0, %1;" : "=f"(r) : "f"(x)); return r; }

__device__ __forceinline__ void flag_wait(const uint32_t* p, uint32_t e) {
#pragma unroll 1
    for (int i = 0; i < (1 << 20); i++) {
        uint32_t v;
        asm volatile("ld.acquire.gpu.global.u32 %0, [%1];" : "=r"(v) : "l"(p) : "memory");
        if (v == e) break;
    }
}
__device__ __forceinline__ uint32_t ld_epoch() {
    uint32_t v;
    asm volatile("ld.relaxed.gpu.global.u32 %0, [%1];" : "=r"(v) : "l"(&g_epoch[blockIdx.x * FS]) : "memory");
    return v + 1;
}
__device__ __forceinline__ void flag_set(uint32_t* p, uint32_t e) { asm volatile("st.release.gpu.global.u32 [%0], %1;" ::"l"(p), "r"(e) : "memory"); }

__device__ __forceinline__ uint32_t desc_lo(uint32_t addr) { return ((addr & 0x3FFFF) >> 4) | 0x10000u; }
__device__ __forceinline__ uint64_t mkdesc(uint32_t lo) { return (uint64_t)lo | (0x40000040ull << 32); }
__device__ __forceinline__ void wg_fence() { asm volatile("wgmma.fence.sync.aligned;" ::: "memory"); }
__device__ __forceinline__ void wg_commit() { asm volatile("wgmma.commit_group.sync.aligned;" ::: "memory"); }
template <int N> __device__ __forceinline__ void wg_wait() { asm volatile("wgmma.wait_group.sync.aligned %0;" ::"n"(N) : "memory"); }
template <int N> __device__ __forceinline__ void pin(float (&d)[N]) {
#pragma unroll
    for (int i = 0; i < N; i++) asm volatile("" : "+f"(d[i])::"memory");
}
template <int N> __device__ __forceinline__ void pin(uint32_t (&d)[N]) {
#pragma unroll
    for (int i = 0; i < N; i++) asm volatile("" : "+r"(d[i])::"memory");
}

template <typename Tp, int N> __device__ __forceinline__ void zero(Tp (&d)[N]) {
#pragma unroll
    for (int i = 0; i < N; i++) d[i] = 0;
    pin(d);
}

#define F4(d, i) "+f"(d[i]), "+f"(d[i + 1]), "+f"(d[i + 2]), "+f"(d[i + 3])
#define F16(d, i) F4(d, i), F4(d, i + 4), F4(d, i + 8), F4(d, i + 12)

__device__ __forceinline__ void mma_t(float (&d)[16], uint64_t a, uint64_t b, int acc) {
    asm volatile("{.reg .pred p; setp.ne.b32 p, %18, 0;\n"
                 "wgmma.mma_async.sync.aligned.m64n32k16.f32.bf16.bf16 {%0,%1,%2,%3,%4,%5,%6,%7,%8,%9,%10,%11,%12,%13,%14,%15}, %16, %17, p, 1, 1, 1, 0;}\n"
                 : F16(d, 0) : "l"(a), "l"(b), "r"(acc));
}
__device__ __forceinline__ void mma_t(float (&d)[20], uint64_t a, uint64_t b, int acc) {
    asm volatile("{.reg .pred p; setp.ne.b32 p, %22, 0;\n"
                 "wgmma.mma_async.sync.aligned.m64n40k16.f32.bf16.bf16 {%0,%1,%2,%3,%4,%5,%6,%7,%8,%9,%10,%11,%12,%13,%14,%15,%16,%17,%18,%19}, %20, %21, p, 1, 1, 1, 0;}\n"
                 : F16(d, 0), F4(d, 16) : "l"(a), "l"(b), "r"(acc));
}
__device__ __forceinline__ void mma_t(float (&d)[24], uint64_t a, uint64_t b, int acc) {
    asm volatile("{.reg .pred p; setp.ne.b32 p, %26, 0;\n"
                 "wgmma.mma_async.sync.aligned.m64n48k16.f32.bf16.bf16 {%0,%1,%2,%3,%4,%5,%6,%7,%8,%9,%10,%11,%12,%13,%14,%15,%16,%17,%18,%19,%20,%21,%22,%23}, %24, %25, p, 1, 1, 1, 0;}\n"
                 : F16(d, 0), F4(d, 16), F4(d, 20) : "l"(a), "l"(b), "r"(acc));
}
__device__ __forceinline__ void mma_qk(float (&d)[32], uint32_t a0, uint32_t a1, uint32_t a2, uint32_t a3, uint64_t b, int acc) {
    asm volatile("{.reg .pred p; setp.ne.b32 p, %37, 0;\n"
                 "wgmma.mma_async.sync.aligned.m64n64k16.f32.bf16.bf16 {%0,%1,%2,%3,%4,%5,%6,%7,%8,%9,%10,%11,%12,%13,%14,%15,%16,%17,%18,%19,%20,%21,%22,%23,%24,%25,%26,%27,%28,%29,%30,%31}, "
                 "{%32,%33,%34,%35}, %36, p, 1, 1, 0;}\n"
                 : F16(d, 0), F16(d, 16) : "r"(a0), "r"(a1), "r"(a2), "r"(a3), "l"(b), "r"(acc));
}
__device__ __forceinline__ void mma_pv(float (&d)[36], uint32_t a0, uint32_t a1, uint32_t a2, uint32_t a3, uint64_t b) {
    asm volatile("wgmma.mma_async.sync.aligned.m64n72k16.f32.bf16.bf16 {%0,%1,%2,%3,%4,%5,%6,%7,%8,%9,%10,%11,%12,%13,%14,%15,%16,%17,%18,%19,%20,%21,%22,%23,%24,%25,%26,%27,%28,%29,%30,%31,%32,%33,%34,%35}, "
                 "{%36,%37,%38,%39}, %40, 1, 1, 1, 1;\n"
                 : F16(d, 0), F16(d, 16), F4(d, 32) : "r"(a0), "r"(a1), "r"(a2), "r"(a3), "l"(b));
}

template <uint32_t CSTRIDE, int N>
__device__ __forceinline__ void issue_half(float (&d)[N], uint32_t alo, uint32_t blo_, int acc) {
    const uint64_t a = mkdesc(alo), b = mkdesc(blo_);
    wg_fence();
#pragma unroll
    for (int k = 0; k < 8; k++) mma_t(d, a + k * 128, b + (k >> 2) * (CSTRIDE >> 4) + (k & 3) * 2, k == 0 ? acc : 1);
    wg_commit();
}

__device__ __forceinline__ uint32_t load_code(int n, int r, int w) {
    const int tile = 2 * r + w;
    int m, col, row;
    if (n < 16 || n >= 40) {
        const int k = n < 16 ? n : n - 40;
        m = n < 16 ? 1 : 7;
        if (k < 8) { col = 8 * r + (k & 6) + w; row = (k & 1) ^ r; }
        else {
            const int kk = k == 11 ? 12 : (k == 12 ? 11 : k);
            m++; col = kk < 12 ? (tile ^ 2) : tile; row = 4 * r + (kk & 3);
        }
    } else if (n < 32) {
        const int k = n - 16;
        m = 3;
        if (k < 4) { col = tile + ((k & 1) ? 8 : 4); row = (k >> 1) ^ r; }
        else { col = tile; row = (k & 1) ^ r; }
    } else if (n < 34) { m = 4; col = tile; row = n - 32; }
    else if (n < 38) { const int k = n - 34; m = 5; col = tile + 4 * (k & 1); row = (k >> 1) ^ r; }
    else { m = 6; col = tile; row = (n & 1) ^ r; }
    return m | (col << 4) | (row << 8);
}

__global__ void __cluster_dims__(2, 1, 1) __launch_bounds__(NTHREADS, 1)
conformer_kernel(const __grid_constant__ Params p) {
    extern __shared__ __align__(1024) unsigned char smem_raw[];
    const uint32_t sb = smem_u32(smem_raw);
    const uint32_t bars = sb + OFF_BARS;
    const int tid = threadIdx.x;
    const int lane = tid & 31;
    const int warp = __shfl_sync(~0u, tid >> 5, 0);
    const int r = blockIdx.x & 1;
    const int pair = blockIdx.x >> 1;
    const int b = pair >> 5, pt = pair & 31;
    const int ah = pt >> 3, qt = (pt & 7) * 2 + r;
    const int abh = b * 4 + ah;

    TG(30);
    TSINIT();
    TS(0);
    const uint32_t P = sb + OFF_P, H = sb + OFF_H;
    if (warp == 7) {
        if (lane == 0) {
            mbar_init(bars + B_XR * 8, 1);
#pragma unroll
            for (int i = 0; i < 2 * NSLOT; i++) mbar_init(bars + (B_FULL + i) * 8, 1);
            fence_async_smem();
            mbar_arrive_tx(bars + B_XR * 8, 16384);
        }
        __syncwarp();
#pragma unroll
        for (int i = 0; i < 4; i++) tma3d(P + i * XCH, &p.tm[0], i * 64, pt * 32, b, bars + B_XR * 8);
#pragma unroll
        for (int i = 0; i < 4; i++)
            ring_load(sb + OFF_RING + ((i & 1) * NSLOT + (i >> 1)) * SLOT, &p.tm[1], 64 * (8 * r + (i & 1)), 128 * ((i >> 1) ^ r),
                      bars + (B_FULL + (i & 1) * NSLOT + (i >> 1)) * 8);
        TSW(1);
    }
    auto xwait = [&](int j) { mbar_wait(bars + (B_XR + (j & 1)) * 8, (j >> 1) & 1); };

    if (warp >= 8) {
        asm volatile("setmaxnreg.dec.sync.aligned.u32 48;");
        if (warp >= 12) {
            cluster_arrive();
            cluster_wait();
            const int ut = tid & 127;
            const uint32_t a4 = P + (ut >> 2) * 128 + (2 * (ut & 3) + ((ut >> 2) & 1)) * 16;
            const uint32_t a8 = P + (32 + (ut >> 3)) * 128 + (ut & 7) * 16;
#pragma unroll 1
            for (int k = 0; k < 4; k++) {
                float s = 0.f, q = 0.f, s2 = 0.f, q2 = 0.f;
#pragma unroll 1
                for (int h = 0; h < 2; h++) {
                    if (h == 0 && k != 0) bar_sync(1, 384);
                    else xwait(k == 3 ? 4 : k);
                    const uint32_t off = 2 * (r ^ h) * XCH;
                    uint4 v0 = lds128(a4 + off), v1 = lds128((a4 ^ 16) + off), v2 = lds128(a4 + off + XCH), v3 = lds128((a4 ^ 16) + off + XCH);
                    uint4 v4 = make_uint4(0, 0, 0, 0), v5 = v4;
                    if (k == 2) { v4 = lds128(a8 + off); v5 = lds128(a8 + off + XCH); }
                    if (h == 1 || k == 1 || k == 2) bar_arrive(5 + ((v3.w | v5.w) & p.zero), 384);
                    uint32_t t;
                    asm volatile("mov.u32 %0, %%clock;" : "=r"(t)::"memory");
                    const uint32_t mul = 65536u + (t & p.zero), msk = 0u - mul;
                    auto accum = [&](const uint4& v, float& s, float& q) {
                        const float a0 = __uint_as_float(v.x * mul), a1 = __uint_as_float(v.x & msk), a2 = __uint_as_float(v.y * mul), a3 = __uint_as_float(v.y & msk);
                        const float a4 = __uint_as_float(v.z * mul), a5 = __uint_as_float(v.z & msk), a6 = __uint_as_float(v.w * mul), a7 = __uint_as_float(v.w & msk);
                        s += ((a0 + a1) + (a2 + a3)) + ((a4 + a5) + (a6 + a7));
                        q += fmaf(a0, a0, fmaf(a1, a1, fmaf(a2, a2, a3 * a3))) + fmaf(a4, a4, fmaf(a5, a5, fmaf(a6, a6, a7 * a7)));
                    };
                    accum(v0, s, q); accum(v1, s, q); accum(v2, s, q); accum(v3, s, q);
                    if (k == 2) { accum(v4, s2, q2); accum(v5, s2, q2); }
                }
#pragma unroll
                for (int o = 1; o < 8; o <<= 1) {
                    if (o < 4) { s += __shfl_xor_sync(~0u, s, o); q += __shfl_xor_sync(~0u, q, o); }
                    if (k == 2) { s2 += __shfl_xor_sync(~0u, s2, o); q2 += __shfl_xor_sync(~0u, q2, o); }
                }
                const bool second = (ut & 7) == 1;
                if (second) { s = s2; q = q2; }
                const float mean = s * (1.f / 256.f);
                const int row = second ? 32 + (ut >> 3) : ut >> 2;
                const float alpha = k == 1 ? 1.f : ((k == 2 && (uint32_t)(pt * 32 - 8 + row) >= T_) ? 0.f : 0.5f);
                const float rstd = alpha * rsqrtf(fmaxf(fmaf(-mean, mean, q * (1.f / 256.f)), 0.f) + 1e-5f);
                if ((ut & 3) == 0 || second) sts64f(sb + OFF_STATS + row * 8, mean * rstd, rstd);
                __syncwarp();
                if (lane == 0) mbar_arrive(bars + B_ST * 8);
                TS(2 + k);
                if (k == 1 && warp == 12) {
                    const uint32_t epoch = ld_epoch();
                    bar_sync(11, 288);
                    if (lane < 2) flag_set(&g_flag_q[((b * 4 + 2 * r + lane) * 32 + pt) * FS], epoch);
                    __syncwarp();
                    TS(13);
                }
            }
        } else if (warp < 10) {
            const int w = warp - 8;
            const uint32_t ring = sb + OFF_RING + w * NSLOT * SLOT;
            const uint32_t full = bars + (B_FULL + w * NSLOT) * 8;
            cluster_arrive();
            const uint32_t code = load_code(lane, r, w) | (load_code(lane + 32, r, w) << 16);
            cluster_wait();
            TS(2);
            uint32_t s = 2, ph = 1;
            int n = 2;
#pragma unroll 1
            for (int seg = 0; seg < 2; seg++) {
#pragma unroll 1
                for (; n < (seg == 0 ? 22 : NLOADS); n++) {
                    const uint32_t c = __shfl_sync(~0u, code, n) >> (n & 32 ? 16 : 0);
                    mbar_wait(full + (B_EMPTY - B_FULL) * 8 + s * 8, ph);
                    ring_load(ring + s * SLOT, &p.tm[c & 15], (c & 0xf0) * 4, (c & 0xff00) >> 1, full + s * 8);
                    if (++s == NSLOT) { s = 0; ph ^= 1; }
                }
                if (seg == 1) break;
                const uint32_t epoch = ld_epoch();
                const uint32_t rdy = bars + (B_RDY + 3 * w) * 8, prdy = mapa(rdy, r ^ 1);
                const int isv = r ^ w;
#pragma unroll 1
                for (; n < 32; n++) {
                    mbar_wait(full + (B_EMPTY - B_FULL) * 8 + s * 8, ph);
                    if (lane == 0) {
                        if (n < 24) mbar_arrive(full + s * 8);
                        else mbar_arrive_tx(full + s * 8, SLOT);
                    }
                    if (n == 28) {
                        if (lane == 0) mbar_arrive_peer(prdy);
                        mbar_wait(rdy, 0);
                        if (!isv) {
                            flag_wait(g_flag_kv + (abh * 32 + lane) * FS, epoch);
                            __syncwarp();
                            fence_async_global();
                            TSW(5);
                            ring_load_both(ring + 4 * SLOT, &p.tm[9], (abh * 8 + w) * 128, full + 32);
                        }
                        bar_sync(12, 64);
#pragma unroll
                        for (int i = 0; i < 2; i++) {
                            if (i == 0) mbar_wait(bars + B_QIN * 8, 0);
                            else mbar_wait(full + isv * 8, 1);
                            ring_load_both(ring + (2 * i + isv) * SLOT, &p.tm[9], (isv * 62 + abh * 8 + 2 * i + 2 + w) * 128, full + (2 * i + isv) * 8);
                        }
                    } else if (n > 28) {
                        const uint32_t bo = n == 31 ? 16 : 8;
                        if ((n > 29) == (isv == 1)) {
                            mbar_wait(rdy + bo, 0);
                            ring_load_both(ring + s * SLOT, &p.tm[9], (isv * 64 + abh * 8 + (n == 30 ? 4 : 6) + w) * 128, full + s * 8);
                        } else if (lane == 0) mbar_arrive_peer(prdy + bo);
                    }
                    __syncwarp();
                    if (++s == NSLOT) { s = 0; ph ^= 1; }
                }
            }
        } else if (warp == 10) {
            cluster_arrive();
            cluster_wait();
            const uint32_t epoch = ld_epoch();
            if (lane == 0) {
                mbar_arrive_tx(bars + B_QIN * 8, 8192);
                mbar_arrive_tx(bars + B_OIN * 8, 2 * XCH);
                mbar_arrive_tx(bars + B_OIN * 8 + 8, 2 * XCH);
            }
            if (lane < 2) flag_wait(&g_flag_q[(abh * 32 + 2 * qt + lane) * FS], epoch);
            __syncwarp();
            TSW(6);
            if (lane == 0) {
                fence_async_global();
                bulk_g2s(H + 24576, g_kvq + 2097152 + (size_t)(abh * 1024 + qt * 64) * 128, 8192, bars + B_QIN * 8);
            }
            if (lane < 2) {
                const int np = pt - 1 + 2 * lane;
                if (np >= 0 && np < 32) flag_wait(&g_flag_kv[((b * 4 + 2 * r) * 32 + np) * FS], epoch);
            }
            __syncwarp();
            if (lane == 0) mbar_arrive(bars + B_X1IN * 8);
            bar_sync(9, 64);
            if (lane < 8) {
                const int q = (pt >> 1) + (lane < 4 ? 0 : ((pt & 1) ? 1 : -1));
                if (q >= 0 && q < 16) flag_wait(&g_flag_o[((b * 16 + q) * 4 + (lane & 3)) * FS], epoch);
            }
            __syncwarp();
            TSW(10);
            if (lane == 0) {
                fence_async_global();
#pragma unroll
                for (int i = 0; i < 4; i++)
                    bulk_g2s(H + i * XCH, g_o + (size_t)((b * 4 + i) * PADROWS + pt * 32) * 128, XCH, bars + (B_OIN + (i >> 1)) * 8);
            }
            __syncwarp();
        } else {
            const uint32_t kb = (lane < 2 || lane > 5) ? 4096 : (lane == 2 ? 3072 : (lane == 4 ? 2048 : 1024));
            const char* pf = p.w[lane & 7] + blockIdx.x * kb;
            cluster_arrive();
            cluster_wait();
            if (lane == 0) prefetch_l2(pf, kb);
            xwait(0);
            if (lane == 1 || lane == 2) prefetch_l2(pf, kb);
            if (lane >= 2 && lane < 10) asm volatile("prefetch.tensormap [%0];" ::"l"(&p.tm[lane]) : "memory");
            mbar_wait(bars + B_HF * 8, 0);
            if (lane > 2 && lane < 8) prefetch_l2(pf, kb);
            const uint32_t epoch = ld_epoch();
            bar_sync(4, 288);
            if (lane < 2) flag_set(&g_flag_kv[((b * 4 + 2 * r + lane) * 32 + pt) * FS], epoch);
            __syncwarp();
            TSW(8);
            bar_sync(6, 288);
            bar_arrive(9, 64);
            if (lane == 0) {
                flag_set(&g_flag_o[((b * 16 + qt) * 4 + ah) * FS], epoch);
                g_epoch[blockIdx.x * FS] = epoch;
            }
            __syncwarp();
            TSW(9);
        }
        TSDUMP();
        return;
    }

    if (lane == 0) {
        mbar_init(bars + (B_EMPTY + warp) * 8, 4);
        mbar_init(bars + (B_HF + warp) * 8, warp < 4 ? 8 : 1);
        if (warp < 3) mbar_init(bars + (warp == 2 ? B_ST : B_EMPTY + 8 + warp) * 8, 4);
        else if (warp < 6) mbar_init(bars + (B_XR - 2 + warp) * 8, 1);
        if (warp < 6) mbar_init(bars + (B_RDY + warp) * 8, 1);
        asm volatile("fence.mbarrier_init.release.cluster;" ::: "memory");
    }
    sts128(P + (tid >> 6) * XCH + 4096 + (tid & 63) * 16, 0x3F803F80u, 0x3F803F80u, 0x3F803F80u, 0x3F803F80u);
    fence_async_smem();
    __syncwarp();
    cluster_arrive();
    asm volatile("setmaxnreg.inc.sync.aligned.u32 208;");
    const int w = warp >> 2, wq = warp & 3;
    const int tile = 2 * r + w;
    const int wt = tid & 127;
    const int c4 = lane & 3;
    const uint32_t rbase = sb + OFF_RING + w * NSLOT * SLOT, fbar = bars + (B_FULL + w * NSLOT) * 8;
    const uint32_t rdesc = desc_lo(rbase);
    auto acq = [&](int n) { mbar_wait(fbar + (n % NSLOT) * 8, (n / NSLOT) & 1); };
    auto rel = [&](int n) { if (lane == 0) mbar_arrive(fbar + (B_EMPTY - B_FULL + n % NSLOT) * 8); };
    const uint32_t pown = desc_lo(P + 2 * r * XCH), prem = desc_lo(P + 2 * (r ^ 1) * XCH), hdesc = desc_lo(H);
    const uint32_t toff = ((lane >> 4) * 8 + (lane & 7)) * 128 + (((2 * wq + ((lane >> 3) & 1)) ^ (lane & 7)) << 4);
    const uint32_t xa = P + tile * XCH + toff;
    auto publish = [&](int j, uint32_t src, uint32_t bytes, int nsync) {
        const uint32_t bar = bars + (B_XR + (j & 1)) * 8;
        fence_async_smem();
        bar_sync(2 + w, 128);
        if (wq == 0) peer_copy(mapa(src, r ^ 1), src, bytes, mapa(bar, r ^ 1));
        if (tid == 32) mbar_arrive_tx(bar, 2 * bytes);
        bar_sync(nsync == 384 ? 1 : 10, nsync);
    };
    auto gate = [&](int j) { xwait(j); bar_sync(5, 384); };
    auto load_stats = [&](auto& st, int parity) {
        mbar_wait(bars + B_ST * 8, parity);
#pragma unroll
        for (int j = 0; j < (int)(sizeof(st) / 16); j++) {
            const float4 v = lds128f(sb + OFF_STATS + (8 * j + 2 * c4) * 8);
            st[4 * j] = v.x; st[4 * j + 1] = v.y; st[4 * j + 2] = v.z; st[4 * j + 3] = v.w;
        }
    };
    bar_sync(10, 256);
    cluster_wait();
    uint32_t xr[8];
    TS(56);
    xwait(0);
    TS(57);
    ldsm4t(xa, xr[0], xr[1], xr[2], xr[3]);
    ldsm4t(xa + 2048, xr[4], xr[5], xr[6], xr[7]);
    acq(0);
    TS(58);
    acq(1);

#pragma unroll 1
    for (int ffi = 0; ffi < 2; ffi++) {
        auto mm = [&](auto& d, int n, uint32_t bd, auto cs, int acc) {
            const uint32_t z = p.zero * (ffi + n + 1);
            issue_half<decltype(cs)::value>(d, rdesc + z + (n % NSLOT) * (SLOT >> 4), bd + z, acc);
        };
        constexpr std::integral_constant<uint32_t, XCH> cx{};
        constexpr std::integral_constant<uint32_t, HCH> ch{};
        {
            float st[16], a0[20], a1[20], rem[16], own[16];
            const uint32_t inb = bars + (B_INB + w) * 8, box = sb + OFF_INBOX + w * 4096 + wt * 16;
            const uint32_t hdst = H + w * HCH + toff;
            auto step = [&](auto& d, int n, uint32_t bd, auto cs, int acc) {
                mm(d, n, bd, cs, acc);
                wg_wait<1>();
                if (n > 0) rel(n - 1);
            };
            auto epi = [&](float (&d)[20], int i, int half) {
                uint32_t pk[4];
#pragma unroll
                for (int k = 4 * half; k < 4 * half + 4; k++) {
                    const float cs = d[16 + 2 * (k & 1)];
                    const float v0 = fmaf(-st[(k >> 1) * 4], cs, d[2 * k] * st[(k >> 1) * 4 + 1]);
                    const float v1 = fmaf(-st[(k >> 1) * 4 + 2], cs, d[2 * k + 1] * st[(k >> 1) * 4 + 3]);
                    pk[k & 3] = pack2(fmaf(v0, tanh_fast(v0), v0), fmaf(v1, tanh_fast(v1), v1));
                }
                stsm4t(hdst + 2 * i * HCH + half * 2048, pk[0], pk[1], pk[2], pk[3]);
            };
            auto hdone = [&](int i) {
                fence_async_smem();
                __syncwarp();
                if (lane == 0) mbar_arrive(bars + (B_HF + i) * 8);
            };
            auto hwait = [&](int i) { mbar_wait(bars + (B_HF + i) * 8, ffi); };
            TS(1 + ffi * 20);
            step(a0, 0, pown, cx, 0);
            if (wt == 0) mbar_arrive_tx(inb, 4096);
            acq(2);
            gate(ffi * 4);
            TS(32);
            step(a0, 1, prem, cx, 1);
            step(a1, 2, pown, cx, 0); acq(3); pin(a0); load_stats(st, ffi); TS(33); epi(a0, 0, 0);
            step(a1, 3, prem, cx, 1); acq(4); epi(a0, 0, 1); TS(34);
            step(a0, 4, pown, cx, 0); acq(5); pin(a1); epi(a1, 1, 0);
            step(a0, 5, prem, cx, 1); acq(6); epi(a1, 1, 1); TS(35);
            step(a1, 6, pown, cx, 0); acq(7); pin(a0); hdone(0); epi(a0, 2, 0);
            step(a1, 7, prem, cx, 1); acq(8); hwait(0); epi(a0, 2, 1); TS(36);
            step(rem, 8, hdesc, ch, 0); acq(9); pin(a1); hdone(1); epi(a1, 3, 0);
            step(rem, 9, hdesc + 2 * (HCH >> 4), ch, 1); acq(10); hwait(1); epi(a1, 3, 1);
            TS(2 + ffi * 20);
            step(rem, 10, hdesc + 4 * (HCH >> 4), ch, 1); acq(11); hdone(2);
            step(own, 11, hdesc, ch, 0); acq(12); hwait(2);
            step(rem, 12, hdesc + 6 * (HCH >> 4), ch, 1); acq(13);
            step(own, 13, hdesc + 2 * (HCH >> 4), ch, 1); acq(14);
            pin(rem);
            {
                const uint32_t dst = mapa(box, r ^ 1), bar = mapa(inb, r ^ 1);
                st_async4(dst, pack2(rem[0], rem[1]), pack2(rem[2], rem[3]), pack2(rem[4], rem[5]), pack2(rem[6], rem[7]), bar);
                st_async4(dst + 2048, pack2(rem[8], rem[9]), pack2(rem[10], rem[11]), pack2(rem[12], rem[13]), pack2(rem[14], rem[15]), bar);
            }
            step(own, 14, hdesc + 4 * (HCH >> 4), ch, 1); acq(15);
            step(own, 15, hdesc + 6 * (HCH >> 4), ch, 1);
            mbar_wait(inb, ffi);
            const uint4 u = lds128(box), v = lds128(box + 2048);
            const uint32_t pr[8] = {u.x, u.y, u.z, u.w, v.x, v.y, v.z, v.w};
            if (ffi == 0) { acq(16); acq(17); }
            wg_wait<0>();
            pin(own);
            TS(3 + ffi * 20);
#pragma unroll
            for (int i = 0; i < 8; i++)
                xr[i] = pack2(fmaf(0.5f, own[2 * i] + blo(pr[i]), blo(xr[i])), fmaf(0.5f, own[2 * i + 1] + bhi(pr[i]), bhi(xr[i])));
            stsm4t(xa, xr[0], xr[1], xr[2], xr[3]);
            stsm4t(xa + 2048, xr[4], xr[5], xr[6], xr[7]);
            rel(15);
            publish(ffi ? 5 : 1, P + tile * XCH + (ffi ? (r ^ 1) * 2048 : 0), ffi ? 2048 : 4096, ffi ? 256 : 384);
        }
        if (ffi == 1) break;

        {
            float ak[20], aq[20], st[16];
            g_halo[((pair * 4 + tile) * 2 + 0) * 128 + wt] = make_uint2(xr[0], xr[1]);
            g_halo[((pair * 4 + tile) * 2 + 1) * 128 + wt] = make_uint2(xr[6], xr[7]);
            bar_sync(5, 384);
            TS(11);
            mm(ak, 16, pown, cx, 0);
            mm(aq, 17, pown, cx, 0);
            acq(18); acq(19);
            gate(1);
            mm(ak, 18, prem, cx, 1);
            mm(aq, 19, prem, cx, 1);
            wg_wait<2>();
            rel(16); rel(17);
            load_stats(st, 1);
            auto stage_out = [&](float (&d)[20], uint32_t dst) {
                uint32_t pk[8];
#pragma unroll
                for (int k = 0; k < 8; k++) {
                    const float cs = d[16 + 2 * (k & 1)];
                    pk[k] = pack2(fmaf(-st[(k >> 1) * 4], cs, d[2 * k] * st[(k >> 1) * 4 + 1]),
                                  fmaf(-st[(k >> 1) * 4 + 2], cs, d[2 * k + 1] * st[(k >> 1) * 4 + 3]));
                }
                stsm4t(dst + toff, pk[0], pk[1], pk[2], pk[3]);
                stsm4t(dst + toff + 2048, pk[4], pk[5], pk[6], pk[7]);
            };
            const uint32_t stg = H + w * 12288;
            unsigned char* g = g_kvq + (size_t)((b * 4 + tile) * 1024 + pt * 32) * 128 + wt * 16;
            wg_wait<0>();
            pin(ak); pin(aq);
            TS(37);
            stage_out(ak, stg);
            stage_out(aq, stg + 4096);
            bar_sync(2 + w, 128);
            {
                const uint4 k0 = lds128(stg + wt * 16), k1 = lds128(stg + 2048 + wt * 16), q0 = lds128(stg + 4096 + wt * 16), q1 = lds128(stg + 6144 + wt * 16);
                stg128(g, k0); stg128(g + 2048, k1);
                stg128(g + 1048576, q0); stg128(g + 1048576 + 2048, q1);
            }
            bar_arrive(4, 288);
            TS(38);
            rel(18); rel(19);
            acq(20); acq(21);
            bar_sync(10, 256);
            mm(ak, 20, pown, cx, 0);
            mm(ak, 21, prem, cx, 1);
            wg_wait<0>();
            pin(ak);
            stage_out(ak, stg + 8192);
            rel(20); rel(21);
            bar_sync(2 + w, 128);
            {
                const uint4 v0 = lds128(stg + 8192 + wt * 16), v1 = lds128(stg + 10240 + wt * 16);
                stg128(g + 2097152, v0); stg128(g + 2097152 + 2048, v1);
            }
            bar_arrive(11, 288);
            acq(22); acq(23);
            rel(22); rel(23);
            TS(12);
        }

        {
            constexpr float CS = 0.125f * 1.4426950408889634f;
            float sa[32], sb2[32], o[36];
            uint32_t pa[16], pb[16], q[16];
            float n0 = INFINITY, n1 = INFINITY;
            zero(o); zero(pa); zero(pb);
            const uint32_t ones = sb + OFF_INBOX + 2048;
            if (tid < 128) sts128(ones + tid * 16, 0x3F803F80u, 0x3F803F80u, 0x3F803F80u, 0x3F803F80u);
            fence_async_smem();
            bar_sync(10, 256);
            const uint32_t vdesc = rdesc + ((((ones - rbase) >> 4) - 1) << 16);
            auto qk_issue = [&](float (&s)[32], uint32_t lo) {
                const uint64_t kd = mkdesc(lo);
                wg_fence();
#pragma unroll
                for (int k = 0; k < 4; k++) mma_qk(s, q[4 * k], q[4 * k + 1], q[4 * k + 2], q[4 * k + 3], kd + 2 * k, k != 0);
                wg_commit();
            };
            auto pv_issue = [&](uint32_t (&pp)[16], uint32_t lo) {
                const uint64_t vd = mkdesc(lo);
                wg_fence();
#pragma unroll
                for (int k = 0; k < 4; k++) mma_pv(o, pp[4 * k], pp[4 * k + 1], pp[4 * k + 2], pp[4 * k + 3], vd - k * (128 * 65535));
                wg_commit();
            };
            auto new_max = [&](float (&s)[32], float& x0, float& x1) {
                x0 = s[0]; x1 = s[2];
#pragma unroll
                for (int j = 0; j < 8; j++) {
                    x0 = fmaxf(x0, fmaxf(s[4 * j], s[4 * j + 1]));
                    x1 = fmaxf(x1, fmaxf(s[4 * j + 2], s[4 * j + 3]));
                }
                x0 = fmaxf(x0, __shfl_xor_sync(~0u, x0, 1)); x1 = fmaxf(x1, __shfl_xor_sync(~0u, x1, 1));
                x0 = fmaxf(x0, __shfl_xor_sync(~0u, x0, 2)); x1 = fmaxf(x1, __shfl_xor_sync(~0u, x1, 2));
                x0 = fminf(n0, fmaf(x0, -CS, -20.f)); x1 = fminf(n1, fmaf(x1, -CS, -20.f));
            };
            auto probs = [&](float (&s)[32], uint32_t (&pp)[16], bool ready, auto wait) {
                uint32_t any = 0;
#pragma unroll
                for (int i = 0; i < 16; i++) {
                    pp[i] = pack2(ex2(fmaf(s[2 * i], CS, (i & 1) ? n1 : n0)), ex2(fmaf(s[2 * i + 1], CS, (i & 1) ? n1 : n0)));
                    any |= pp[i];
                }
                float sc0 = 1.f, sc1 = 1.f;
                const bool slow = __any_sync(~0u, (any & 0x40004000u) || !ready);
                if (slow) {
                    wait();
                    if (__any_sync(~0u, any & 0x40004000u)) {
                        float x0, x1;
                        new_max(s, x0, x1);
                        sc0 = ex2(x0 - n0); sc1 = ex2(x1 - n1);
                        n0 = x0; n1 = x1;
#pragma unroll
                        for (int i = 0; i < 16; i++)
                            pp[i] = pack2(ex2(fmaf(s[2 * i], CS, (i & 1) ? n1 : n0)), ex2(fmaf(s[2 * i + 1], CS, (i & 1) ? n1 : n0)));
                    }
                }
                wg_wait<0>();
                pin(sa); pin(sb2); pin(o); pin(pa); pin(pb);
                if (slow) {
#pragma unroll
                    for (int j = 0; j < 9; j++) { o[4 * j] *= sc0; o[4 * j + 1] *= sc0; o[4 * j + 2] *= sc1; o[4 * j + 3] *= sc1; }
                }
            };
            mbar_wait(bars + B_QIN * 8, 0);
            {
                const uint32_t qa = H + 24576 + (wq * 16 + (lane & 15)) * 128;
#pragma unroll
                for (int k = 0; k < 4; k++) ldsm4(qa + (((2 * k + (lane >> 4)) ^ (lane & 7)) << 4), q[4 * k], q[4 * k + 1], q[4 * k + 2], q[4 * k + 3]);
                pin(q);
            }
            TS(40);
            acq(24);
            TS(13);
            qk_issue(sa, rdesc + (24 % NSLOT) * (SLOT >> 4));
            qk_issue(sb2, rdesc + (24 % NSLOT) * (SLOT >> 4) + 512);
            wg_wait<1>();
            pin(sa);
            {
                float x0, x1;
                new_max(sa, x0, x1);
                n0 = x0; n1 = x1;
            }
            if (w == 1) bar_sync(7, 256);
            uint32_t vd = vdesc - (SLOT >> 4) * 65535u, kd = rdesc, vb = fbar + 8, kb = fbar;
            uint32_t vlast = vdesc - 4 * (SLOT >> 4) * 65535u;
            uint32_t kprev = fbar + 32, vprev = bars + (B_HF + 3 - (B_EMPTY - B_FULL)) * 8;
#pragma unroll 1
            for (int it = 0; it < 4; it++) {
                pv_issue(pb, vlast);
                probs(sa, pa, mbar_test(vb, it < 2) & mbar_test(kb, it < 3), [&]() { mbar_wait(vb, it < 2); mbar_wait(kb, it < 3); });
                TS(41 + it * 4);
                if (it == 0 && w == 0) bar_arrive(7, 256);
                if (it == 3 && w == 1) {
#pragma unroll
                    for (int i = 20; i < 32; i++) sb2[i] = -INFINITY;
                }
                pin(sb2);
                if (it < 3) qk_issue(sa, kd);
                if (lane == 0) mbar_arrive(kprev + (B_EMPTY - B_FULL) * 8);
                if (lane == 0) mbar_arrive(vprev + (B_EMPTY - B_FULL) * 8);
                pv_issue(pa, vd);
                probs(sb2, pb, true, []() {});
                TS(43 + it * 4);
                if (it < 3) qk_issue(sb2, kd + 512);
                const int dv = it == 0 ? 2 : (it == 1 ? -3 : 1);
                kprev = kb; vprev = vb; vlast = vd - 512 * 65535u;
                vd -= dv * (SLOT >> 4) * 65535u; vb += dv * 8;
                kd += 2 * (SLOT >> 4); kb = it == 2 ? vb : kb + 16;
            }
            pv_issue(pb, vlast);
            const int row = wq * 16 + (lane >> 2);
            const uint32_t ml = sb + OFF_INBOX;
            wg_wait<0>();
            pin(o); pin(pb); pin(sa); pin(sb2);
            rel(31);
            const float l0 = o[32], l1 = o[34];
            if (c4 == 0) { sts64f(ml + w * 512 + row * 8, n0, l0); sts64f(ml + w * 512 + row * 8 + 64, n1, l1); }
            TS(14);
            float mine[16];
#pragma unroll
            for (int j = 0; j < 4; j++) {
                if (w == 0) sts128f(H + j * 2048 + wt * 16, o[16 + 4 * j], o[17 + 4 * j], o[18 + 4 * j], o[19 + 4 * j]);
                else sts128f(H + 8192 + j * 2048 + wt * 16, o[4 * j], o[4 * j + 1], o[4 * j + 2], o[4 * j + 3]);
            }
#pragma unroll
            for (int i = 0; i < 16; i++) mine[i] = w == 0 ? o[i] : o[16 + i];
            bar_sync(10, 256);
            const float2 u0 = lds64f(ml + (w ^ 1) * 512 + row * 8), u1 = lds64f(ml + (w ^ 1) * 512 + row * 8 + 64);
            const float x0 = fminf(n0, u0.x), x1 = fminf(n1, u1.x);
            float a0 = ex2(x0 - n0), b0 = ex2(x0 - u0.x), a1 = ex2(x1 - n1), b1 = ex2(x1 - u1.x);
            const float i0 = __fdividef(1.f, fmaf(a0, l0, b0 * u0.y)), i1 = __fdividef(1.f, fmaf(a1, l1, b1 * u1.y));
            a0 *= i0; b0 *= i0; a1 *= i1; b1 *= i1;
            uint32_t pk[8];
#pragma unroll
            for (int j = 0; j < 4; j++) {
                const float4 v = lds128f(H + (w ^ 1) * 8192 + j * 2048 + wt * 16);
                pk[2 * j] = pack2(fmaf(a0, mine[4 * j], b0 * v.x), fmaf(a0, mine[4 * j + 1], b0 * v.y));
                pk[2 * j + 1] = pack2(fmaf(a1, mine[4 * j + 2], b1 * v.z), fmaf(a1, mine[4 * j + 3], b1 * v.w));
            }
            const uint32_t og = H + 16384 + wq * 2048;
            {
                const uint32_t ra = og + (((lane >> 3) & 1) * 8 + (lane & 7)) * 128;
                stsm4(ra + (((4 * w + (lane >> 4)) ^ (lane & 7)) << 4), pk[0], pk[1], pk[2], pk[3]);
                stsm4(ra + (((4 * w + 2 + (lane >> 4)) ^ (lane & 7)) << 4), pk[4], pk[5], pk[6], pk[7]);
            }
            __syncwarp();
            {
                const uint32_t off = (lane >> 2) * 128 + (((4 * w + c4) ^ (lane >> 2)) << 4);
                const uint4 v0 = lds128(og + off), v1 = lds128(og + off + 1024);
                unsigned char* dst = g_o + (size_t)(abh * PADROWS + 8 + qt * 64 + wq * 16) * 128 + off;
                stg128(dst, v0); stg128(dst + 1024, v1);
            }
            bar_arrive(6, 288);
            TS(15);
        }

        uint32_t dwr[15];
        {
#pragma unroll
            for (int i = 0; i < 15; i++) dwr[i] = hmul2(__ldg(reinterpret_cast<const uint32_t*>(p.dw + i * 256 + tile * 64) + lane), 0x3F003F00u);
            float d[24];
            uint32_t xw[12];
            mbar_wait(bars + B_X1IN * 8, 0);
            uint2 hl = make_uint2(0, 0), hr = hl;
            if (pt > 0) hl = __ldcg(&g_halo[(((pair - 1) * 4 + tile) * 2 + 1) * 128 + wt]);
            if (pt < 31) hr = __ldcg(&g_halo[(((pair + 1) * 4 + tile) * 2 + 0) * 128 + wt]);
            xw[0] = hl.x; xw[1] = hl.y; xw[10] = hr.x; xw[11] = hr.y;
#pragma unroll
            for (int i = 0; i < 8; i++) xw[2 + i] = xr[i];
            pin(xw);
            pin(dwr);
            acq(32); acq(33); acq(34); acq(35);
            mbar_wait(bars + B_OIN * 8, 0);
            TS(16);
            mm(d, 32, hdesc, cx, 0);
            mbar_wait(bars + B_OIN * 8 + 8, 0);
            mm(d, 33, hdesc + 2 * (XCH >> 4), cx, 1);
            wg_wait<1>();
            rel(32);
            wg_wait<0>();
            pin(d);
#pragma unroll
            for (int i = 0; i < 12; i++) xw[i] = pack2(d[2 * i] + blo(xw[i]), d[2 * i + 1] + bhi(xw[i]));
            if (c4 == 0) { xw[0] = (xw[0] & 0xffff0000u) | 0x3F80u; xw[1] = (xw[1] & 0xffff0000u) | 0x3F80u; }
#pragma unroll
            for (int j = 0; j < 3; j++) stsm4t(xa + j * 2048, xw[4 * j], xw[4 * j + 1], xw[4 * j + 2], xw[4 * j + 3]);
#pragma unroll
            for (int i = 0; i < 8; i++) xr[i] = xw[2 + i];
            rel(33);
            publish(2, P + tile * XCH, XCH, 384);
            TS(17);
        }
        {
            float da[24], db[24], st[24];
            bar_sync(5, 384);
            mm(da, 34, pown, cx, 0);
            mm(db, 35, pown, cx, 0);
            acq(36); acq(37);
            gate(2);
            TS(39);
            mm(da, 36, prem, cx, 1);
            mm(db, 37, prem, cx, 1);
            wg_wait<2>();
            rel(34); rel(35);
            load_stats(st, 0);
            wg_wait<0>();
            pin(da); pin(db);
            rel(36); rel(37);
            TS(18);
            uint32_t pk[12];
#pragma unroll
            for (int hh = 0; hh < 2; hh++) {
                const float ca = __shfl_sync(~0u, da[2 * hh], lane & 28), cb = __shfl_sync(~0u, db[2 * hh], lane & 28);
#pragma unroll
                for (int j = 0; j < 6; j++) {
                    const float u0 = fmaf(-st[4 * j], ca, da[4 * j + 2 * hh] * st[4 * j + 1]);
                    const float u1 = fmaf(-st[4 * j + 2], ca, da[4 * j + 2 * hh + 1] * st[4 * j + 3]);
                    const float v0 = fmaf(-st[4 * j], cb, db[4 * j + 2 * hh] * st[4 * j + 1]);
                    const float v1 = fmaf(-st[4 * j + 2], cb, db[4 * j + 2 * hh + 1] * st[4 * j + 3]);
                    pk[2 * j + hh] = pack2(fmaf(u0, tanh_fast(v0), u0), fmaf(u1, tanh_fast(v1), u1));
                }
            }
            const uint32_t gs = H + 16384 + w * XCH;
#pragma unroll
            for (int j = 0; j < 3; j++) stsm4t(gs + toff + j * 2048, pk[4 * j], pk[4 * j + 1], pk[4 * j + 2], pk[4 * j + 3]);
            bar_sync(2 + w, 128);
            uint32_t ca[8], cb[8];
            const uint32_t grow = gs + 8 * wq * 128 + c4 * 4, srow = H + tile * HCH + 8 * wq * 128 + c4 * 4;
#pragma unroll
            for (int k = 0; k < 22; k++) {
                const uint32_t v = lds32(grow + (1 + k) * 128 + (((lane >> 2) ^ ((1 + k) & 7)) << 4));
#pragma unroll
                for (int i = 0; i < 8; i++) {
                    const int tap = k - i;
                    if (tap == 0) ca[i] = hmul2(v, dwr[0]);
                    else if (tap > 0 && tap < 8) ca[i] = hfma2(v, dwr[tap], ca[i]);
                    else if (tap == 8) cb[i] = hmul2(v, dwr[8]);
                    else if (tap > 8 && tap < 15) cb[i] = hfma2(v, dwr[tap], cb[i]);
                }
            }
#pragma unroll
            for (int i = 0; i < 8; i++) {
                const float h0 = blo(ca[i]) + blo(cb[i]), h1 = bhi(ca[i]) + bhi(cb[i]);
                sts32(srow + i * 128 + (((lane >> 2) ^ i) << 4), pack2(fmaf(h0, tanh_fast(h0), h0), fmaf(h1, tanh_fast(h1), h1)));
            }
            acq(38); acq(39);
            publish(3, H + tile * HCH, HCH, 256);
            TS(19);
        }
        {
            float d[16];
            mm(d, 38, hdesc + 2 * r * (HCH >> 4), ch, 0);
            acq(40); acq(41);
            xwait(3);
            sts128(P + (wt >> 6 ? (tile ^ 2) : tile) * XCH + 4096 + (wt & 63) * 16, 0x3F803F80u, 0x3F803F80u, 0x3F803F80u, 0x3F803F80u);
            mm(d, 39, hdesc + 2 * (r ^ 1) * (HCH >> 4), ch, 1);
            wg_wait<1>();
            rel(38);
            wg_wait<0>();
            pin(d);
#pragma unroll
            for (int i = 0; i < 8; i++) xr[i] = pack2(d[2 * i] + blo(xr[i]), d[2 * i + 1] + bhi(xr[i]));
            stsm4t(xa, xr[0], xr[1], xr[2], xr[3]);
            stsm4t(xa + 2048, xr[4], xr[5], xr[6], xr[7]);
            rel(39);
            publish(4, P + tile * XCH, HCH, 384);
            TS(20);
        }
    }

    xwait(5);
    cluster_arrive();
    TS(24);
    {
        float a[2][8], s[2], q[2];
        const int row0 = 16 * r + 2 * warp;
#pragma unroll
        for (int i = 0; i < 2; i++) {
            const uint4 v = lds128(P + (lane >> 3) * XCH + (row0 + i) * 128 + (((lane & 7) ^ ((row0 + i) & 7)) << 4));
            a[i][0] = blo(v.x); a[i][1] = bhi(v.x); a[i][2] = blo(v.y); a[i][3] = bhi(v.y);
            a[i][4] = blo(v.z); a[i][5] = bhi(v.z); a[i][6] = blo(v.w); a[i][7] = bhi(v.w);
            s[i] = ((a[i][0] + a[i][1]) + (a[i][2] + a[i][3])) + ((a[i][4] + a[i][5]) + (a[i][6] + a[i][7]));
            q[i] = 0.f;
#pragma unroll
            for (int k = 0; k < 8; k++) q[i] = fmaf(a[i][k], a[i][k], q[i]);
        }
#pragma unroll
        for (int o = 16; o > 0; o >>= 1) {
#pragma unroll
            for (int i = 0; i < 2; i++) { s[i] += __shfl_xor_sync(~0u, s[i], o); q[i] += __shfl_xor_sync(~0u, q[i], o); }
        }
#pragma unroll
        for (int i = 0; i < 2; i++) {
            const float mean = s[i] * (1.f / 256.f);
            const float rstd = rsqrtf(fmaxf(fmaf(-mean, mean, q[i] * (1.f / 256.f)), 0.f) + 1e-5f);
            const float nb = -mean * rstd;
            uint4 v;
            v.x = pack2(fmaf(a[i][0], rstd, nb), fmaf(a[i][1], rstd, nb)); v.y = pack2(fmaf(a[i][2], rstd, nb), fmaf(a[i][3], rstd, nb));
            v.z = pack2(fmaf(a[i][4], rstd, nb), fmaf(a[i][5], rstd, nb)); v.w = pack2(fmaf(a[i][6], rstd, nb), fmaf(a[i][7], rstd, nb));
            const int t = pt * 32 + row0 + i;
            if (t < T_) stg128(p.out + (size_t)(b * T_ + t) * 256 + lane * 8, v);
        }
    }
    TS(25);
    TG(31);
    TSDUMP();
    cluster_wait();
}

typedef CUresult (*EncodeFn)(CUtensorMap*, CUtensorMapDataType, cuuint32_t, void*, const cuuint64_t*, const cuuint64_t*,
                             const cuuint32_t*, const cuuint32_t*, CUtensorMapInterleave, CUtensorMapSwizzle,
                             CUtensorMapL2promotion, CUtensorMapFloatOOBfill);

}

extern "C" void kernel_launch(void* const* d_in, const int* in_sizes, int n_in, void* d_out, int out_size) {
    static EncodeFn encode = nullptr;
    if (!encode) {
        void* fn = nullptr;
        cudaDriverEntryPointQueryResult qr;
        cudaGetDriverEntryPoint("cuTensorMapEncodeTiled", &fn, cudaEnableDefault, &qr);
        encode = (EncodeFn)fn;
        cudaFuncSetAttribute(conformer_kernel, cudaFuncAttributeMaxDynamicSharedMemorySize, SMEM_LAUNCH);
    }
    Params p;
    const cuuint32_t ones[3] = {1, 1, 1};
    {
        const cuuint64_t dims[3] = {256, T_, 2};
        const cuuint64_t strides[2] = {512, 512ull * T_};
        const cuuint32_t box[3] = {64, 32, 1};
        encode(&p.tm[0], CU_TENSOR_MAP_DATA_TYPE_BFLOAT16, 3, d_in[0], dims, strides, box, ones, CU_TENSOR_MAP_INTERLEAVE_NONE,
               CU_TENSOR_MAP_SWIZZLE_128B, CU_TENSOR_MAP_L2_PROMOTION_L2_256B, CU_TENSOR_MAP_FLOAT_OOB_FILL_NONE);
    }
    const int idx[8] = {1, 2, 3, 4, 5, 7, 8, 9};
    const int rows[8] = {256, 1024, 256, 256, 256, 256, 256, 1024};
    const int cols[8] = {1024, 256, 768, 256, 512, 256, 1024, 256};
    for (int i = 0; i < 8; i++) {
        const cuuint64_t dims[2] = {(cuuint64_t)cols[i], (cuuint64_t)rows[i]};
        const cuuint64_t strides[1] = {(cuuint64_t)cols[i] * 2};
        const cuuint32_t box[2] = {64, 128};
        encode(&p.tm[1 + i], CU_TENSOR_MAP_DATA_TYPE_BFLOAT16, 2, d_in[idx[i]], dims, strides, box, ones, CU_TENSOR_MAP_INTERLEAVE_NONE,
               CU_TENSOR_MAP_SWIZZLE_128B, CU_TENSOR_MAP_L2_PROMOTION_L2_128B, CU_TENSOR_MAP_FLOAT_OOB_FILL_NONE);
        p.w[i] = (const char*)d_in[idx[i]];
    }
    {
        void* kv = nullptr;
        cudaGetSymbolAddress(&kv, g_kvq);
        const cuuint64_t dims[2] = {64, 16384};
        const cuuint64_t strides[1] = {128};
        const cuuint32_t box[2] = {64, 128};
        encode(&p.tm[9], CU_TENSOR_MAP_DATA_TYPE_BFLOAT16, 2, kv, dims, strides, box, ones, CU_TENSOR_MAP_INTERLEAVE_NONE,
               CU_TENSOR_MAP_SWIZZLE_NONE, CU_TENSOR_MAP_L2_PROMOTION_L2_128B, CU_TENSOR_MAP_FLOAT_OOB_FILL_NONE);
    }
    p.dw = (const __nv_bfloat16*)d_in[6];
    p.out = (__nv_bfloat16*)d_out;
    p.zero = 0;
    conformer_kernel<<<NCTA, NTHREADS, SMEM_LAUNCH>>>(p);
}
```

```cpp
#include <cuda_runtime.h>
#include <cuda_bf16.h>
#include <cuda.h>
#include <stdint.h>
#include <type_traits>

namespace {

constexpr int T_ = 1000;
constexpr int NCTA = 128;
constexpr int NTHREADS = 512;
constexpr int NSLOT = 5;
constexpr int SLOT = 16384;
constexpr int NLOADS = 56;

constexpr uint32_t OFF_RING = 0;
constexpr uint32_t OFF_P = 163840;
constexpr uint32_t OFF_H = 188416;
constexpr uint32_t OFF_INBOX = 221184;
constexpr uint32_t OFF_STATS = 229376;
constexpr uint32_t OFF_BARS = 229888;
constexpr uint32_t SMEM_BYTES = 230400;
constexpr uint32_t XCH = 6144;
constexpr uint32_t HCH = 4096;

constexpr int B_FULL = 0, B_EMPTY = 10, B_XR = 20, B_OIN = 22, B_HF = 24, B_INB = 28, B_QIN = 30, B_X1IN = 31, B_ST = 32, B_RDY = 33  , B_SINK = 39;

constexpr int PADROWS = 1040;
constexpr int FS = 8;

struct Params {
    CUtensorMap tm[10];
    const char* w[8];
    const __nv_bfloat16* dw;
    __nv_bfloat16* out;
    uint32_t zero;
};

__device__ __align__(1024) unsigned char g_kvq[3 * 8 * 1024 * 128];
__device__ __align__(1024) unsigned char g_o[8 * PADROWS * 128];
__device__ uint2 g_halo[64 * 4 * 2 * 128];
__device__ uint32_t g_flag_kv[8 * 32 * FS];
__device__ uint32_t g_flag_q[8 * 32 * FS];
__device__ uint32_t g_flag_o[2 * 16 * 4 * FS];
__device__ uint32_t g_epoch[NCTA * FS];

#define TS(i) do { } while (0)
#define TSW(i) do { } while (0)
#define TG(i) do { } while (0)
#define TSINIT() do { } while (0)
#define TSDUMP() do { } while (0)
constexpr uint32_t SMEM_LAUNCH = SMEM_BYTES;

__device__ __forceinline__ uint32_t smem_u32(const void* p) { return (uint32_t)__cvta_generic_to_shared(p); }
__device__ __forceinline__ void mbar_init(uint32_t b, uint32_t c) { asm volatile("mbarrier.init.shared::cta.b64 [%0], %1;" ::"r"(b), "r"(c) : "memory"); }
__device__ __forceinline__ void mbar_arrive(uint32_t b) { asm volatile("mbarrier.arrive.shared::cta.b64 _, [%0];" ::"r"(b) : "memory"); }
__device__ __forceinline__ void mbar_arrive_tx(uint32_t b, uint32_t tx) { asm volatile("mbarrier.arrive.expect_tx.shared::cta.b64 _, [%0], %1;" ::"r"(b), "r"(tx) : "memory"); }
__device__ __forceinline__ void mbar_wait(uint32_t b, uint32_t ph) {
    asm volatile("{\n.reg .pred p, q;\n.reg .u32 c;\nmov.u32 c, 0;\n"
                 "MW_LOOP:\n.pragma \"nounroll\";\n"
                 "mbarrier.try_wait.parity.shared::cta.b64 p, [%0], %1;\n"
                 "add.u32 c, c, 1;\nsetp.lt.u32 q, c, 65536;\nnot.pred p, p;\nand.pred p, p, q;\n@p bra MW_LOOP;\n}"
                 ::"r"(b), "r"(ph) : "memory");
}
__device__ __forceinline__ bool mbar_test(uint32_t b, uint32_t ph) {
    uint32_t ok;
    asm volatile("{\n.reg .pred p;\nmbarrier.test_wait.parity.shared::cta.b64 p, [%1], %2;\nselp.u32 %0, 1, 0, p;\n}" : "=r"(ok) : "r"(b), "r"(ph) : "memory");
    return ok;
}
__device__ __forceinline__ uint32_t mapa(uint32_t a, uint32_t r) { uint32_t o; asm("mapa.shared::cluster.u32 %0, %1, %2;" : "=r"(o) : "r"(a), "r"(r)); return o; }
__device__ __forceinline__ void fence_async_smem() { asm volatile("fence.proxy.async.shared::cta;" ::: "memory"); }
__device__ __forceinline__ void fence_async_global() { asm volatile("fence.proxy.async.global;" ::: "memory"); }
__device__ __forceinline__ void bar_sync(int id, int n) { asm volatile("bar.sync %0, %1;" ::"r"(id), "r"(n) : "memory"); }
__device__ __forceinline__ void bar_arrive(int id, int n) { asm volatile("bar.arrive %0, %1;" ::"r"(id), "r"(n) : "memory"); }
__device__ __forceinline__ void cluster_arrive() { asm volatile("barrier.cluster.arrive.relaxed.aligned;" ::: "memory"); }
__device__ __forceinline__ void cluster_wait() { asm volatile("barrier.cluster.wait.aligned;" ::: "memory"); }

__device__ __forceinline__ void ring_load(uint32_t dst, const CUtensorMap* tm, int c0, int c1, uint32_t bar) {
    asm volatile("{\n.reg .pred p;\nelect.sync _|p, 0xffffffff;\n"
                 "@p mbarrier.arrive.expect_tx.shared::cta.b64 _, [%2], 16384;\n"
                 "@p cp.async.bulk.tensor.2d.shared::cluster.global.mbarrier::complete_tx::bytes [%0], [%1, {%3, %4}], [%2];\n}"
                 ::"r"(dst), "l"(tm), "r"(bar), "r"(c0), "r"(c1) : "memory");
}
__device__ __forceinline__ void ring_load_both(uint32_t dst, const CUtensorMap* tm, int c1, uint32_t bar) {
    asm volatile("{\n.reg .pred p;\nelect.sync _|p, 0xffffffff;\n"
                 "@p cp.async.bulk.tensor.2d.shared::cluster.global.mbarrier::complete_tx::bytes.multicast::cluster [%0], [%1, {0, %3}], [%2], %4;\n}"
                 ::"r"(dst), "l"(tm), "r"(bar), "r"(c1), "h"((uint16_t)3) : "memory");
}
__device__ __forceinline__ void mbar_arrive_peer(uint32_t b) { asm volatile("mbarrier.arrive.relaxed.cluster.shared::cluster.b64 _, [%0];" ::"r"(b) : "memory"); }
__device__ __forceinline__ void tma3d(uint32_t dst, const CUtensorMap* tm, int c0, int c1, int c2, uint32_t bar) {
    asm volatile("{\n.reg .pred p;\nelect.sync _|p, 0xffffffff;\n"
                 "@p cp.async.bulk.tensor.3d.shared::cluster.global.mbarrier::complete_tx::bytes [%0], [%1, {%3, %4, %5}], [%2];\n}"
                 ::"r"(dst), "l"(tm), "r"(bar), "r"(c0), "r"(c1), "r"(c2) : "memory");
}
__device__ __forceinline__ void bulk_g2s(uint32_t dst, const void* src, uint32_t bytes, uint32_t bar) {
    asm volatile("cp.async.bulk.shared::cluster.global.mbarrier::complete_tx::bytes [%0], [%1], %2, [%3];" ::"r"(dst), "l"(src), "r"(bytes), "r"(bar) : "memory");
}
__device__ __forceinline__ void prefetch_l2(const void* src, uint32_t bytes) {
    asm volatile("cp.async.bulk.prefetch.L2.global [%0], %1;" ::"l"(src), "r"(bytes) : "memory");
}
__device__ __forceinline__ void peer_copy(uint32_t dst, uint32_t src, uint32_t bytes, uint32_t rbar) {
    asm volatile("{\n.reg .pred p;\nelect.sync _|p, 0xffffffff;\n"
                 "@p cp.async.bulk.shared::cluster.shared::cta.mbarrier::complete_tx::bytes [%0], [%1], %2, [%3];\n}"
                 ::"r"(dst), "r"(src), "r"(bytes), "r"(rbar) : "memory");
}
__device__ __forceinline__ void st_async4(uint32_t dst, uint32_t a, uint32_t b, uint32_t c, uint32_t d, uint32_t bar) {
    asm volatile("st.async.shared::cluster.mbarrier::complete_tx::bytes.v4.b32 [%0], {%1,%2,%3,%4}, [%5];" ::"r"(dst), "r"(a), "r"(b), "r"(c), "r"(d), "r"(bar) : "memory");
}
__device__ __forceinline__ void stsm4t(uint32_t a, uint32_t r0, uint32_t r1, uint32_t r2, uint32_t r3) {
    asm volatile("stmatrix.sync.aligned.m8n8.x4.trans.shared.b16 [%0], {%1,%2,%3,%4};" ::"r"(a), "r"(r0), "r"(r1), "r"(r2), "r"(r3) : "memory");
}
__device__ __forceinline__ void stsm4(uint32_t a, uint32_t r0, uint32_t r1, uint32_t r2, uint32_t r3) {
    asm volatile("stmatrix.sync.aligned.m8n8.x4.shared.b16 [%0], {%1,%2,%3,%4};" ::"r"(a), "r"(r0), "r"(r1), "r"(r2), "r"(r3) : "memory");
}
__device__ __forceinline__ void ldsm4t(uint32_t a, uint32_t& r0, uint32_t& r1, uint32_t& r2, uint32_t& r3) {
    asm volatile("ldmatrix.sync.aligned.m8n8.x4.trans.shared.b16 {%0,%1,%2,%3}, [%4];" : "=r"(r0), "=r"(r1), "=r"(r2), "=r"(r3) : "r"(a) : "memory");
}
__device__ __forceinline__ void ldsm4(uint32_t a, uint32_t& r0, uint32_t& r1, uint32_t& r2, uint32_t& r3) {
    asm volatile("ldmatrix.sync.aligned.m8n8.x4.shared.b16 {%0,%1,%2,%3}, [%4];" : "=r"(r0), "=r"(r1), "=r"(r2), "=r"(r3) : "r"(a) : "memory");
}
__device__ __forceinline__ uint4 lds128(uint32_t a) { uint4 v; asm volatile("ld.shared.v4.b32 {%0,%1,%2,%3}, [%4];" : "=r"(v.x), "=r"(v.y), "=r"(v.z), "=r"(v.w) : "r"(a) : "memory"); return v; }
__device__ __forceinline__ float4 lds128f(uint32_t a) { float4 v; asm volatile("ld.shared.v4.f32 {%0,%1,%2,%3}, [%4];" : "=f"(v.x), "=f"(v.y), "=f"(v.z), "=f"(v.w) : "r"(a) : "memory"); return v; }
__device__ __forceinline__ float2 lds64f(uint32_t a) { float2 v; asm volatile("ld.shared.v2.f32 {%0,%1}, [%2];" : "=f"(v.x), "=f"(v.y) : "r"(a) : "memory"); return v; }
__device__ __forceinline__ uint32_t lds32(uint32_t a) { uint32_t v; asm volatile("ld.shared.b32 %0, [%1];" : "=r"(v) : "r"(a) : "memory"); return v; }
__device__ __forceinline__ void sts128(uint32_t a, uint32_t x, uint32_t y, uint32_t z, uint32_t w) { asm volatile("st.shared.v4.b32 [%0], {%1,%2,%3,%4};" ::"r"(a), "r"(x), "r"(y), "r"(z), "r"(w) : "memory"); }
__device__ __forceinline__ void sts128f(uint32_t a, float x, float y, float z, float w) { asm volatile("st.shared.v4.f32 [%0], {%1,%2,%3,%4};" ::"r"(a), "f"(x), "f"(y), "f"(z), "f"(w) : "memory"); }
__device__ __forceinline__ void sts64f(uint32_t a, float x, float y) { asm volatile("st.shared.v2.f32 [%0], {%1,%2};" ::"r"(a), "f"(x), "f"(y) : "memory"); }
__device__ __forceinline__ void sts32(uint32_t a, uint32_t x) { asm volatile("st.shared.b32 [%0], %1;" ::"r"(a), "r"(x) : "memory"); }
__device__ __forceinline__ void stg128(void* p, uint4 v) { asm volatile("st.global.v4.b32 [%0], {%1,%2,%3,%4};" ::"l"(p), "r"(v.x), "r"(v.y), "r"(v.z), "r"(v.w) : "memory"); }

__device__ __forceinline__ uint32_t pack2(float lo, float hi) { uint32_t r; asm("cvt.rn.bf16x2.f32 %0, %1, %2;" : "=r"(r) : "f"(hi), "f"(lo)); return r; }
__device__ __forceinline__ float blo(uint32_t v) { return __uint_as_float(v << 16); }
__device__ __forceinline__ float bhi(uint32_t v) { return __uint_as_float(v & 0xffff0000u); }
__device__ __forceinline__ uint32_t hmul2(uint32_t a, uint32_t b) { uint32_t r; asm("mul.rn.bf16x2 %0, %1, %2;" : "=r"(r) : "r"(a), "r"(b)); return r; }
__device__ __forceinline__ uint32_t hfma2(uint32_t a, uint32_t b, uint32_t c) { uint32_t r; asm("fma.rn.bf16x2 %0, %1, %2, %3;" : "=r"(r) : "r"(a), "r"(b), "r"(c)); return r; }
__device__ __forceinline__ float tanh_fast(float x) { float r; asm("tanh.approx.f32 %0, %1;" : "=f"(r) : "f"(x)); return r; }
__device__ __forceinline__ float ex2(float x) { float r; asm("ex2.approx.ftz.f32 %0, %1;" : "=f"(r) : "f"(x)); return r; }

__device__ __forceinline__ void flag_wait(const uint32_t* p, uint32_t e) {
#pragma unroll 1
    for (int i = 0; i < (1 << 20); i++) {
        uint32_t v;
        asm volatile("ld.acquire.gpu.global.u32 %0, [%1];" : "=r"(v) : "l"(p) : "memory");
        if (v == e) break;
    }
}
__device__ __forceinline__ uint32_t ld_epoch() {
    uint32_t v;
    asm volatile("ld.relaxed.gpu.global.u32 %0, [%1];" : "=r"(v) : "l"(&g_epoch[blockIdx.x * FS]) : "memory");
    return v + 1;
}
__device__ __forceinline__ void flag_set(uint32_t* p, uint32_t e) { asm volatile("st.release.gpu.global.u32 [%0], %1;" ::"l"(p), "r"(e) : "memory"); }

__device__ __forceinline__ uint32_t desc_lo(uint32_t addr) { return ((addr & 0x3FFFF) >> 4) | 0x10000u; }
__device__ __forceinline__ uint64_t mkdesc(uint32_t lo) { return (uint64_t)lo | (0x40000040ull << 32); }
__device__ __forceinline__ void wg_fence() { asm volatile("wgmma.fence.sync.aligned;" ::: "memory"); }
__device__ __forceinline__ void wg_commit() { asm volatile("wgmma.commit_group.sync.aligned;" ::: "memory"); }
template <int N> __device__ __forceinline__ void wg_wait() { asm volatile("wgmma.wait_group.sync.aligned %0;" ::"n"(N) : "memory"); }
template <int N> __device__ __forceinline__ void pin(float (&d)[N]) {
#pragma unroll
    for (int i = 0; i < N; i++) asm volatile("" : "+f"(d[i])::"memory");
}
template <int N> __device__ __forceinline__ void pin(uint32_t (&d)[N]) {
#pragma unroll
    for (int i = 0; i < N; i++) asm volatile("" : "+r"(d[i])::"memory");
}

template <typename Tp, int N> __device__ __forceinline__ void zero(Tp (&d)[N]) {
#pragma unroll
    for (int i = 0; i < N; i++) d[i] = 0;
    pin(d);
}

#define F4(d, i) "+f"(d[i]), "+f"(d[i + 1]), "+f"(d[i + 2]), "+f"(d[i + 3])
#define F16(d, i) F4(d, i), F4(d, i + 4), F4(d, i + 8), F4(d, i + 12)

__device__ __forceinline__ void mma_t(float (&d)[16], uint64_t a, uint64_t b, int acc) {
    asm volatile("{.reg .pred p; setp.ne.b32 p, %18, 0;\n"
                 "wgmma.mma_async.sync.aligned.m64n32k16.f32.bf16.bf16 {%0,%1,%2,%3,%4,%5,%6,%7,%8,%9,%10,%11,%12,%13,%14,%15}, %16, %17, p, 1, 1, 1, 0;}\n"
                 : F16(d, 0) : "l"(a), "l"(b), "r"(acc));
}
__device__ __forceinline__ void mma_t(float (&d)[20], uint64_t a, uint64_t b, int acc) {
    asm volatile("{.reg .pred p; setp.ne.b32 p, %22, 0;\n"
                 "wgmma.mma_async.sync.aligned.m64n40k16.f32.bf16.bf16 {%0,%1,%2,%3,%4,%5,%6,%7,%8,%9,%10,%11,%12,%13,%14,%15,%16,%17,%18,%19}, %20, %21, p, 1, 1, 1, 0;}\n"
                 : F16(d, 0), F4(d, 16) : "l"(a), "l"(b), "r"(acc));
}
__device__ __forceinline__ void mma_t(float (&d)[24], uint64_t a, uint64_t b, int acc) {
    asm volatile("{.reg .pred p; setp.ne.b32 p, %26, 0;\n"
                 "wgmma.mma_async.sync.aligned.m64n48k16.f32.bf16.bf16 {%0,%1,%2,%3,%4,%5,%6,%7,%8,%9,%10,%11,%12,%13,%14,%15,%16,%17,%18,%19,%20,%21,%22,%23}, %24, %25, p, 1, 1, 1, 0;}\n"
                 : F16(d, 0), F4(d, 16), F4(d, 20) : "l"(a), "l"(b), "r"(acc));
}
__device__ __forceinline__ void mma_qk(float (&d)[32], uint32_t a0, uint32_t a1, uint32_t a2, uint32_t a3, uint64_t b, int acc) {
    asm volatile("{.reg .pred p; setp.ne.b32 p, %37, 0;\n"
                 "wgmma.mma_async.sync.aligned.m64n64k16.f32.bf16.bf16 {%0,%1,%2,%3,%4,%5,%6,%7,%8,%9,%10,%11,%12,%13,%14,%15,%16,%17,%18,%19,%20,%21,%22,%23,%24,%25,%26,%27,%28,%29,%30,%31}, "
                 "{%32,%33,%34,%35}, %36, p, 1, 1, 0;}\n"
                 : F16(d, 0), F16(d, 16) : "r"(a0), "r"(a1), "r"(a2), "r"(a3), "l"(b), "r"(acc));
}
__device__ __forceinline__ void mma_pv(float (&d)[36], uint32_t a0, uint32_t a1, uint32_t a2, uint32_t a3, uint64_t b) {
    asm volatile("wgmma.mma_async.sync.aligned.m64n72k16.f32.bf16.bf16 {%0,%1,%2,%3,%4,%5,%6,%7,%8,%9,%10,%11,%12,%13,%14,%15,%16,%17,%18,%19,%20,%21,%22,%23,%24,%25,%26,%27,%28,%29,%30,%31,%32,%33,%34,%35}, "
                 "{%36,%37,%38,%39}, %40, 1, 1, 1, 1;\n"
                 : F16(d, 0), F16(d, 16), F4(d, 32) : "r"(a0), "r"(a1), "r"(a2), "r"(a3), "l"(b));
}

template <uint32_t CSTRIDE, int N>
__device__ __forceinline__ void issue_half(float (&d)[N], uint32_t alo, uint32_t blo_, int acc) {
    const uint64_t a = mkdesc(alo), b = mkdesc(blo_);
    wg_fence();
#pragma unroll
    for (int k = 0; k < 8; k++) mma_t(d, a + k * 128, b + (k >> 2) * (CSTRIDE >> 4) + (k & 3) * 2, k == 0 ? acc : 1);
    wg_commit();
}

__device__ __forceinline__ uint32_t load_code(int n, int r, int w) {
    const int tile = 2 * r + w;
    int m, col, row;
    if (n < 16 || n >= 40) {
        const int k = n < 16 ? n : n - 40;
        m = n < 16 ? 1 : 7;
        if (k < 4) { col = 8 * r + 2 * (k & 1) + w; row = (k >> 1) ^ r; }
        else if (k < 8) { col = 8 * r + (k & 6) + w; row = (k & 1) ^ r; }
        else if (k < 12) { m++; col = (k & 1) ? tile : (tile ^ 2); row = 4 * r + ((k >> 1) & 1); }
        else { m++; col = k < 14 ? (tile ^ 2) : tile; row = 4 * r + 2 + (k & 1); }
    } else if (n < 32) {
        const int k = n - 16;
        m = 3;
        if (k < 4) { col = tile + ((k & 1) ? 8 : 4); row = (k >> 1) ^ r; }
        else { col = tile; row = (k & 1) ^ r; }
    } else if (n < 34) { m = 4; col = tile; row = n - 32; }
    else if (n < 38) { const int k = n - 34; m = 5; col = tile + 4 * (k & 1); row = (k >> 1) ^ r; }
    else { m = 6; col = tile; row = (n & 1) ^ r; }
    return m | (col << 4) | (row << 8);
}

__global__ void __cluster_dims__(2, 1, 1) __launch_bounds__(NTHREADS, 1)
conformer_kernel(const __grid_constant__ Params p) {
    extern __shared__ __align__(1024) unsigned char smem_raw[];
    const uint32_t sb = smem_u32(smem_raw);
    const uint32_t bars = sb + OFF_BARS;
    const int tid = threadIdx.x;
    const int lane = tid & 31;
    const int warp = __shfl_sync(~0u, tid >> 5, 0);
    const int r = blockIdx.x & 1;
    const int pair = blockIdx.x >> 1;
    const int b = pair >> 5, pt = pair & 31;
    const int ah = pt >> 3, qt = (pt & 7) * 2 + r;
    const int abh = b * 4 + ah;

    TG(30);
    TSINIT();
    TS(0);
    const uint32_t P = sb + OFF_P, H = sb + OFF_H;
    if (warp == 7) {
        if (lane == 0) {
            mbar_init(bars + B_XR * 8, 1);
#pragma unroll
            for (int i = 0; i < 2 * NSLOT; i++) mbar_init(bars + (B_FULL + i) * 8, 1);
            fence_async_smem();
            mbar_arrive_tx(bars + B_XR * 8, 16384);
        }
        __syncwarp();
#pragma unroll
        for (int i = 0; i < 4; i++) tma3d(P + i * XCH, &p.tm[0], i * 64, pt * 32, b, bars + B_XR * 8);
#pragma unroll
        for (int i = 0; i < 4; i++)
            ring_load(sb + OFF_RING + ((i & 1) * NSLOT + (i >> 1)) * SLOT, &p.tm[1], 64 * (8 * r + i), 128 * r,
                      bars + (B_FULL + (i & 1) * NSLOT + (i >> 1)) * 8);
        TSW(1);
    }
    auto xwait = [&](int j) { mbar_wait(bars + (B_XR + (j & 1)) * 8, (j >> 1) & 1); };

    if (warp >= 8) {
        asm volatile("setmaxnreg.dec.sync.aligned.u32 48;");
        if (warp >= 12) {
            cluster_arrive();
            cluster_wait();
            const int ut = tid & 127;
            const uint32_t a4 = P + (ut >> 2) * 128 + (2 * (ut & 3) + ((ut >> 2) & 1)) * 16;
            const uint32_t a8 = P + (32 + (ut >> 3)) * 128 + (ut & 7) * 16;
#pragma unroll 1
            for (int k = 0; k < 4; k++) {
                float s = 0.f, q = 0.f, s2 = 0.f, q2 = 0.f;
#pragma unroll 1
                for (int h = 0; h < 2; h++) {
                    if (h == 0 && k != 0) bar_sync(1, 384);
                    else xwait(k == 3 ? 4 : k);
                    const uint32_t off = 2 * (r ^ h) * XCH;
                    uint4 v0 = lds128(a4 + off), v1 = lds128((a4 ^ 16) + off), v2 = lds128(a4 + off + XCH), v3 = lds128((a4 ^ 16) + off + XCH);
                    uint4 v4 = make_uint4(0, 0, 0, 0), v5 = v4;
                    if (k == 2) { v4 = lds128(a8 + off); v5 = lds128(a8 + off + XCH); }
                    if (h == 1 || k == 1 || k == 2) bar_arrive(5 + ((v3.w | v5.w) & p.zero), 384);
                    uint32_t t;
                    asm volatile("mov.u32 %0, %%clock;" : "=r"(t)::"memory");
                    const uint32_t mul = 65536u + (t & p.zero), msk = 0u - mul;
                    auto accum = [&](const uint4& v, float& s, float& q) {
                        const float a0 = __uint_as_float(v.x * mul), a1 = __uint_as_float(v.x & msk), a2 = __uint_as_float(v.y * mul), a3 = __uint_as_float(v.y & msk);
                        const float a4 = __uint_as_float(v.z * mul), a5 = __uint_as_float(v.z & msk), a6 = __uint_as_float(v.w * mul), a7 = __uint_as_float(v.w & msk);
                        s += ((a0 + a1) + (a2 + a3)) + ((a4 + a5) + (a6 + a7));
                        q += fmaf(a0, a0, fmaf(a1, a1, fmaf(a2, a2, a3 * a3))) + fmaf(a4, a4, fmaf(a5, a5, fmaf(a6, a6, a7 * a7)));
                    };
                    accum(v0, s, q); accum(v1, s, q); accum(v2, s, q); accum(v3, s, q);
                    if (k == 2) { accum(v4, s2, q2); accum(v5, s2, q2); }
                }
#pragma unroll
                for (int o = 1; o < 8; o <<= 1) {
                    if (o < 4) { s += __shfl_xor_sync(~0u, s, o); q += __shfl_xor_sync(~0u, q, o); }
                    if (k == 2) { s2 += __shfl_xor_sync(~0u, s2, o); q2 += __shfl_xor_sync(~0u, q2, o); }
                }
                const bool second = (ut & 7) == 1;
                if (second) { s = s2; q = q2; }
                const float mean = s * (1.f / 256.f);
                const int row = second ? 32 + (ut >> 3) : ut >> 2;
                const float alpha = k == 1 ? 1.f : ((k == 2 && (uint32_t)(pt * 32 - 8 + row) >= T_) ? 0.f : 0.5f);
                const float rstd = alpha * rsqrtf(fmaxf(fmaf(-mean, mean, q * (1.f / 256.f)), 0.f) + 1e-5f);
                if ((ut & 3) == 0 || second) sts64f(sb + OFF_STATS + row * 8, mean * rstd, rstd);
                __syncwarp();
                if (lane == 0) mbar_arrive(bars + B_ST * 8);
                TS(2 + k);
                if (k == 1 && warp == 12) {
                    const uint32_t epoch = ld_epoch();
                    bar_sync(11, 288);
                    if (lane < 2) flag_set(&g_flag_q[((b * 4 + 2 * r + lane) * 32 + pt) * FS], epoch);
                    __syncwarp();
                    TS(13);
                }
            }
        } else if (warp < 10) {
            const int w = warp - 8;
            const uint32_t ring = sb + OFF_RING + w * NSLOT * SLOT;
            const uint32_t full = bars + (B_FULL + w * NSLOT) * 8;
            cluster_arrive();
            const uint32_t code = load_code(lane, r, w) | (load_code(lane + 32, r, w) << 16);
            cluster_wait();
            TS(2);
            uint32_t s = 2, ph = 1;
            int n = 2;
#pragma unroll 1
            for (int seg = 0; seg < 2; seg++) {
#pragma unroll 1
                for (; n < (seg == 0 ? 22 : NLOADS); n++) {
                    const uint32_t c = __shfl_sync(~0u, code, n) >> (n & 32 ? 16 : 0);
                    mbar_wait(full + (B_EMPTY - B_FULL) * 8 + s * 8, ph);
                    ring_load(ring + s * SLOT, &p.tm[c & 15], (c & 0xf0) * 4, (c & 0xff00) >> 1, full + s * 8);
                    if (++s == NSLOT) { s = 0; ph ^= 1; }
                }
                if (seg == 1) break;
                const uint32_t epoch = ld_epoch();
                const uint32_t rdy = bars + (B_RDY + 3 * w) * 8, prdy = mapa(rdy, r ^ 1);
                const int isv = r ^ w;
#pragma unroll 1
                for (; n < 32; n++) {
                    mbar_wait(full + (B_EMPTY - B_FULL) * 8 + s * 8, ph);
                    if (lane == 0) {
                        if (n < 24) mbar_arrive(full + s * 8);
                        else mbar_arrive_tx(full + s * 8, SLOT);
                    }
                    if (n == 28) {
                        if (lane == 0) mbar_arrive_peer(prdy);
                        mbar_wait(rdy, 0);
                        if (!isv) {
                            flag_wait(g_flag_kv + (abh * 32 + lane) * FS, epoch);
                            __syncwarp();
                            fence_async_global();
                            TSW(5);
                            ring_load_both(ring + 4 * SLOT, &p.tm[9], (abh * 8 + w) * 128, full + 32);
                        }
                        bar_sync(12, 64);
#pragma unroll
                        for (int i = 0; i < 2; i++) {
                            if (i == 0) mbar_wait(bars + B_QIN * 8, 0);
                            else mbar_wait(full + isv * 8, 1);
                            ring_load_both(ring + (2 * i + isv) * SLOT, &p.tm[9], (isv * 62 + abh * 8 + 2 * i + 2 + w) * 128, full + (2 * i + isv) * 8);
                        }
                    } else if (n > 28) {
                        const uint32_t bo = n == 31 ? 16 : 8;
                        if ((n > 29) == (isv == 1)) {
                            mbar_wait(rdy + bo, 0);
                            ring_load_both(ring + s * SLOT, &p.tm[9], (isv * 64 + abh * 8 + (n == 30 ? 4 : 6) + w) * 128, full + s * 8);
                        } else if (lane == 0) mbar_arrive_peer(prdy + bo);
                    }
                    __syncwarp();
                    if (++s == NSLOT) { s = 0; ph ^= 1; }
                }
            }
        } else if (warp == 10) {
            cluster_arrive();
            cluster_wait();
            const uint32_t epoch = ld_epoch();
            if (lane == 0) {
                mbar_arrive_tx(bars + B_QIN * 8, 8192);
                mbar_arrive_tx(bars + B_OIN * 8, 2 * XCH);
                mbar_arrive_tx(bars + B_OIN * 8 + 8, 2 * XCH);
            }
            if (lane < 2) flag_wait(&g_flag_q[(abh * 32 + 2 * qt + lane) * FS], epoch);
            __syncwarp();
            TSW(6);
            if (lane == 0) {
                fence_async_global();
                bulk_g2s(H + 24576, g_kvq + 2097152 + (size_t)(abh * 1024 + qt * 64) * 128, 8192, bars + B_QIN * 8);
            }
            if (lane < 2) {
                const int np = pt - 1 + 2 * lane;
                if (np >= 0 && np < 32) flag_wait(&g_flag_kv[((b * 4 + 2 * r) * 32 + np) * FS], epoch);
            }
            __syncwarp();
            if (lane == 0) mbar_arrive(bars + B_X1IN * 8);
            bar_sync(9, 64);
            if (lane < 8) {
                const int q = (pt >> 1) + (lane < 4 ? 0 : ((pt & 1) ? 1 : -1));
                if (q >= 0 && q < 16) flag_wait(&g_flag_o[((b * 16 + q) * 4 + (lane & 3)) * FS], epoch);
            }
            __syncwarp();
            TSW(10);
            if (lane == 0) {
                fence_async_global();
#pragma unroll
                for (int i = 0; i < 4; i++)
                    bulk_g2s(H + i * XCH, g_o + (size_t)((b * 4 + i) * PADROWS + pt * 32) * 128, XCH, bars + (B_OIN + (i >> 1)) * 8);
            }
            __syncwarp();
        } else {
            const uint32_t kb = (lane < 2 || lane > 5) ? 4096 : (lane == 2 ? 3072 : (lane == 4 ? 2048 : 1024));
            const char* pf = p.w[lane & 7] + blockIdx.x * kb;
            cluster_arrive();
            cluster_wait();
            if (lane == 0) prefetch_l2(pf, kb);
            xwait(0);
            if (lane == 1 || lane == 2) prefetch_l2(pf, kb);
            if (lane >= 2 && lane < 10) asm volatile("prefetch.tensormap [%0];" ::"l"(&p.tm[lane]) : "memory");
            mbar_wait(bars + B_HF * 8, 0);
            if (lane > 2 && lane < 8) prefetch_l2(pf, kb);
            const uint32_t epoch = ld_epoch();
            bar_sync(4, 288);
            if (lane < 2) flag_set(&g_flag_kv[((b * 4 + 2 * r + lane) * 32 + pt) * FS], epoch);
            __syncwarp();
            TSW(8);
            bar_sync(6, 288);
            bar_arrive(9, 64);
            if (lane == 0) {
                flag_set(&g_flag_o[((b * 16 + qt) * 4 + ah) * FS], epoch);
                g_epoch[blockIdx.x * FS] = epoch;
            }
            __syncwarp();
            TSW(9);
        }
        TSDUMP();
        return;
    }

    if (lane == 0) {
        mbar_init(bars + (B_EMPTY + warp) * 8, 4);
        mbar_init(bars + (B_HF + warp) * 8, warp < 4 ? 8 : 1);
        if (warp < 3) mbar_init(bars + (warp == 2 ? B_ST : B_EMPTY + 8 + warp) * 8, 4);
        else if (warp < 6) mbar_init(bars + (B_XR - 2 + warp) * 8, 1);
        if (warp < 7) mbar_init(bars + (B_RDY + warp) * 8, 1);
        asm volatile("fence.mbarrier_init.release.cluster;" ::: "memory");
    }
    sts128(P + (tid >> 6) * XCH + 4096 + (tid & 63) * 16, 0x3F803F80u, 0x3F803F80u, 0x3F803F80u, 0x3F803F80u);
    fence_async_smem();
    __syncwarp();
    cluster_arrive();
    asm volatile("setmaxnreg.inc.sync.aligned.u32 208;");
    const int w = warp >> 2, wq = warp & 3;
    const int tile = 2 * r + w;
    const int wt = tid & 127;
    const int c4 = lane & 3;
    const uint32_t rbase = sb + OFF_RING + w * NSLOT * SLOT, fbar = bars + (B_FULL + w * NSLOT) * 8;
    const uint32_t rdesc = desc_lo(rbase);
    auto acq = [&](int n) { mbar_wait(fbar + (n % NSLOT) * 8, (n / NSLOT) & 1); };
    auto rel = [&](int n) { if (lane == 0) mbar_arrive(fbar + (B_EMPTY - B_FULL + n % NSLOT) * 8); };
    const uint32_t pown = desc_lo(P + 2 * r * XCH), prem = desc_lo(P + 2 * (r ^ 1) * XCH), hdesc = desc_lo(H);
    const uint32_t toff = ((lane >> 4) * 8 + (lane & 7)) * 128 + (((2 * wq + ((lane >> 3) & 1)) ^ (lane & 7)) << 4);
    const uint32_t xa = P + tile * XCH + toff;
    auto publish = [&](int j, uint32_t src, uint32_t bytes, int nsync) {
        const uint32_t bar = bars + (B_XR + (j & 1)) * 8;
        fence_async_smem();
        bar_sync(2 + w, 128);
        if (wq == 0) peer_copy(mapa(src, r ^ 1), src, bytes, mapa(bar, r ^ 1));
        if (tid == 32) mbar_arrive_tx(bar, 2 * bytes);
        bar_sync(nsync == 384 ? 1 : 10, nsync);
    };
    auto gate = [&](int j) { xwait(j); bar_sync(5, 384); };
    auto load_stats = [&](auto& st, int parity) {
        mbar_wait(bars + B_ST * 8, parity);
#pragma unroll
        for (int j = 0; j < (int)(sizeof(st) / 16); j++) {
            const float4 v = lds128f(sb + OFF_STATS + (8 * j + 2 * c4) * 8);
            st[4 * j] = v.x; st[4 * j + 1] = v.y; st[4 * j + 2] = v.z; st[4 * j + 3] = v.w;
        }
    };
    bar_sync(10, 256);
    cluster_wait();
    uint32_t xr[8];
    TS(56);
    xwait(0);
    TS(57);
    ldsm4t(xa, xr[0], xr[1], xr[2], xr[3]);
    ldsm4t(xa + 2048, xr[4], xr[5], xr[6], xr[7]);
    acq(0);

#pragma unroll 1
    for (int ffi = 0; ffi < 2; ffi++) {
        auto mm = [&](auto& d, int n, uint32_t bd, auto cs, int acc) {
            const uint32_t z = p.zero * (ffi + n + 1);
            issue_half<decltype(cs)::value>(d, rdesc + z + (n % NSLOT) * (SLOT >> 4), bd + z, acc);
        };
        constexpr std::integral_constant<uint32_t, XCH> cx{};
        constexpr std::integral_constant<uint32_t, HCH> ch{};
        {
            float st[16], a0[20], a1[20], a2[20], rem[16], own[16];
            const uint32_t inb = bars + (B_INB + w) * 8, box = sb + OFF_INBOX + w * 4096 + wt * 16;
            const uint32_t hdst = H + w * HCH + toff;
            auto step = [&](auto& d, int n, uint32_t bd, auto cs, int acc) {
                mm(d, n, bd, cs, acc);
                wg_wait<1>();
                if (n > 0) rel(n - 1);
            };
            auto hdone = [&](int i) {
                fence_async_smem();
                __syncwarp();
                if (lane == 0) mbar_arrive(bars + (B_HF + i) * 8);
            };
            auto hwait = [&](int i) { mbar_wait(bars + (B_HF + i) * 8, ffi); };
            auto epi = [&](float (&d)[20], int i, int half, int done) {
                uint32_t pk[4];
#pragma unroll
                for (int k = 4 * half; k < 4 * half + 4; k++) {
                    const float cs = d[16 + 2 * (k & 1)];
                    const float v0 = fmaf(-st[(k >> 1) * 4], cs, d[2 * k] * st[(k >> 1) * 4 + 1]);
                    const float v1 = fmaf(-st[(k >> 1) * 4 + 2], cs, d[2 * k + 1] * st[(k >> 1) * 4 + 3]);
                    pk[k & 3] = pack2(fmaf(v0, tanh_fast(v0), v0), fmaf(v1, tanh_fast(v1), v1));
                }
                if (done >= 0) hdone(done);
                stsm4t(hdst + 2 * i * HCH + half * 2048, pk[0], pk[1], pk[2], pk[3]);
            };
            TS(1 + ffi * 20);
            step(a0, 0, pown, cx, 0);
            if (wt == 0) mbar_arrive_tx(inb, 4096);
            acq(1);
            step(a1, 1, pown, cx, 0); acq(2);
            gate(ffi * 4);
            TS(32);
            step(a0, 2, prem, cx, 1); acq(3);
            step(a1, 3, prem, cx, 1); acq(4);
            step(a2, 4, pown, cx, 0); acq(5); pin(a0); pin(a1); load_stats(st, ffi); TS(33); epi(a0, 0, 0, -1);
            step(a2, 5, prem, cx, 1); acq(6); epi(a0, 0, 1, -1); TS(34);
            step(a0, 6, pown, cx, 0); acq(7); pin(a2); epi(a1, 1, 0, 0);
            step(a0, 7, prem, cx, 1); acq(8); hwait(0); epi(a1, 1, 1, -1); TS(35);
            step(rem, 8, hdesc, ch, 0); acq(9); pin(a0); epi(a2, 2, 0, 1);
            step(own, 9, hdesc, ch, 0); acq(10); hwait(1); epi(a2, 2, 1, -1); TS(36);
            step(rem, 10, hdesc + 2 * (HCH >> 4), ch, 1); acq(11); epi(a0, 3, 0, 2);
            step(own, 11, hdesc + 2 * (HCH >> 4), ch, 1); acq(12); hwait(2); epi(a0, 3, 1, -1);
            TS(2 + ffi * 20);
            step(rem, 12, hdesc + 4 * (HCH >> 4), ch, 1); acq(13); hdone(3); hwait(3);
            step(rem, 13, hdesc + 6 * (HCH >> 4), ch, 1); acq(14);
            step(own, 14, hdesc + 4 * (HCH >> 4), ch, 1);
            pin(rem);
            {
                const uint32_t dst = mapa(box, r ^ 1), bar = mapa(inb, r ^ 1);
                st_async4(dst, pack2(rem[0], rem[1]), pack2(rem[2], rem[3]), pack2(rem[4], rem[5]), pack2(rem[6], rem[7]), bar);
                st_async4(dst + 2048, pack2(rem[8], rem[9]), pack2(rem[10], rem[11]), pack2(rem[12], rem[13]), pack2(rem[14], rem[15]), bar);
            }
            acq(15);
            step(own, 15, hdesc + 6 * (HCH >> 4), ch, 1);
            mbar_wait(inb, ffi);
            const uint4 u = lds128(box), v = lds128(box + 2048);
            const uint32_t pr[8] = {u.x, u.y, u.z, u.w, v.x, v.y, v.z, v.w};
            if (ffi == 0) { acq(16); acq(17); }
            wg_wait<0>();
            pin(own);
            TS(3 + ffi * 20);
#pragma unroll
            for (int i = 0; i < 8; i++)
                xr[i] = pack2(fmaf(0.5f, own[2 * i] + blo(pr[i]), blo(xr[i])), fmaf(0.5f, own[2 * i + 1] + bhi(pr[i]), bhi(xr[i])));
            stsm4t(xa, xr[0], xr[1], xr[2], xr[3]);
            stsm4t(xa + 2048, xr[4], xr[5], xr[6], xr[7]);
            rel(15);
            publish(ffi ? 5 : 1, P + tile * XCH + (ffi ? (r ^ 1) * 2048 : 0), ffi ? 2048 : 4096, ffi ? 256 : 384);
        }
        if (ffi == 1) break;

        {
            float ak[20], aq[20], st[16];
            g_halo[((pair * 4 + tile) * 2 + 0) * 128 + wt] = make_uint2(xr[0], xr[1]);
            g_halo[((pair * 4 + tile) * 2 + 1) * 128 + wt] = make_uint2(xr[6], xr[7]);
            bar_sync(5, 384);
            TS(11);
            mm(ak, 16, pown, cx, 0);
            mm(aq, 17, pown, cx, 0);
            acq(18); acq(19);
            gate(1);
            mm(ak, 18, prem, cx, 1);
            mm(aq, 19, prem, cx, 1);
            wg_wait<2>();
            rel(16); rel(17);
            load_stats(st, 1);
            auto stage_out = [&](float (&d)[20], uint32_t dst) {
                uint32_t pk[8];
#pragma unroll
                for (int k = 0; k < 8; k++) {
                    const float cs = d[16 + 2 * (k & 1)];
                    pk[k] = pack2(fmaf(-st[(k >> 1) * 4], cs, d[2 * k] * st[(k >> 1) * 4 + 1]),
                                  fmaf(-st[(k >> 1) * 4 + 2], cs, d[2 * k + 1] * st[(k >> 1) * 4 + 3]));
                }
                stsm4t(dst + toff, pk[0], pk[1], pk[2], pk[3]);
                stsm4t(dst + toff + 2048, pk[4], pk[5], pk[6], pk[7]);
            };
            const uint32_t stg = H + w * 12288;
            unsigned char* g = g_kvq + (size_t)((b * 4 + tile) * 1024 + pt * 32) * 128 + wt * 16;
            wg_wait<0>();
            pin(ak); pin(aq);
            TS(37);
            stage_out(ak, stg);
            stage_out(aq, stg + 4096);
            bar_sync(2 + w, 128);
            {
                const uint4 k0 = lds128(stg + wt * 16), k1 = lds128(stg + 2048 + wt * 16), q0 = lds128(stg + 4096 + wt * 16), q1 = lds128(stg + 6144 + wt * 16);
                stg128(g, k0); stg128(g + 2048, k1);
                stg128(g + 1048576, q0); stg128(g + 1048576 + 2048, q1);
            }
            bar_arrive(4, 288);
            TS(38);
            rel(18); rel(19);
            acq(20); acq(21);
            bar_sync(10, 256);
            mm(ak, 20, pown, cx, 0);
            mm(ak, 21, prem, cx, 1);
            wg_wait<0>();
            pin(ak);
            stage_out(ak, stg + 8192);
            rel(20); rel(21);
            bar_sync(2 + w, 128);
            {
                const uint4 v0 = lds128(stg + 8192 + wt * 16), v1 = lds128(stg + 10240 + wt * 16);
                stg128(g + 2097152, v0); stg128(g + 2097152 + 2048, v1);
            }
            bar_arrive(11, 288);
            acq(22); acq(23);
            rel(22); rel(23);
            TS(12);
        }

        {
            constexpr float CS = 0.125f * 1.4426950408889634f;
            float sa[32], sb2[32], o[36];
            uint32_t pa[16], pb[16], q[16];
            float n0 = INFINITY, n1 = INFINITY;
            zero(o); zero(pa); zero(pb);
            const uint32_t ones = sb + OFF_INBOX + 2048;
            if (tid < 128) sts128(ones + tid * 16, 0x3F803F80u, 0x3F803F80u, 0x3F803F80u, 0x3F803F80u);
            fence_async_smem();
            bar_sync(10, 256);
            const uint32_t vdesc = rdesc + ((((ones - rbase) >> 4) - 1) << 16);
            auto qk_issue = [&](float (&s)[32], uint32_t lo) {
                const uint64_t kd = mkdesc(lo);
                wg_fence();
#pragma unroll
                for (int k = 0; k < 4; k++) mma_qk(s, q[4 * k], q[4 * k + 1], q[4 * k + 2], q[4 * k + 3], kd + 2 * k, k != 0);
                wg_commit();
            };
            auto pv_issue = [&](uint32_t (&pp)[16], uint32_t lo) {
                const uint64_t vd = mkdesc(lo);
                wg_fence();
#pragma unroll
                for (int k = 0; k < 4; k++) mma_pv(o, pp[4 * k], pp[4 * k + 1], pp[4 * k + 2], pp[4 * k + 3], vd - k * (128 * 65535));
                wg_commit();
            };
            auto new_max = [&](float (&s)[32], float& x0, float& x1) {
                x0 = s[0]; x1 = s[2];
#pragma unroll
                for (int j = 0; j < 8; j++) {
                    x0 = fmaxf(x0, fmaxf(s[4 * j], s[4 * j + 1]));
                    x1 = fmaxf(x1, fmaxf(s[4 * j + 2], s[4 * j + 3]));
                }
                x0 = fmaxf(x0, __shfl_xor_sync(~0u, x0, 1)); x1 = fmaxf(x1, __shfl_xor_sync(~0u, x1, 1));
                x0 = fmaxf(x0, __shfl_xor_sync(~0u, x0, 2)); x1 = fmaxf(x1, __shfl_xor_sync(~0u, x1, 2));
                x0 = fminf(n0, fmaf(x0, -CS, -20.f)); x1 = fminf(n1, fmaf(x1, -CS, -20.f));
            };
            auto probs = [&](float (&s)[32], uint32_t (&pp)[16], bool ready, auto wait) {
                uint32_t any = 0;
#pragma unroll
                for (int i = 0; i < 16; i++) {
                    pp[i] = pack2(ex2(fmaf(s[2 * i], CS, (i & 1) ? n1 : n0)), ex2(fmaf(s[2 * i + 1], CS, (i & 1) ? n1 : n0)));
                    any |= pp[i];
                }
                float sc0 = 1.f, sc1 = 1.f;
                const bool slow = __any_sync(~0u, (any & 0x40004000u) || !ready);
                if (slow) {
                    wait();
                    if (__any_sync(~0u, any & 0x40004000u)) {
                        float x0, x1;
                        new_max(s, x0, x1);
                        sc0 = ex2(x0 - n0); sc1 = ex2(x1 - n1);
                        n0 = x0; n1 = x1;
#pragma unroll
                        for (int i = 0; i < 16; i++)
                            pp[i] = pack2(ex2(fmaf(s[2 * i], CS, (i & 1) ? n1 : n0)), ex2(fmaf(s[2 * i + 1], CS, (i & 1) ? n1 : n0)));
                    }
                }
                wg_wait<0>();
                pin(sa); pin(sb2); pin(o); pin(pa); pin(pb);
                if (slow) {
#pragma unroll
                    for (int j = 0; j < 9; j++) { o[4 * j] *= sc0; o[4 * j + 1] *= sc0; o[4 * j + 2] *= sc1; o[4 * j + 3] *= sc1; }
                }
            };
            mbar_wait(bars + B_QIN * 8, 0);
            {
                const uint32_t qa = H + 24576 + (wq * 16 + (lane & 15)) * 128;
#pragma unroll
                for (int k = 0; k < 4; k++) ldsm4(qa + (((2 * k + (lane >> 4)) ^ (lane & 7)) << 4), q[4 * k], q[4 * k + 1], q[4 * k + 2], q[4 * k + 3]);
                pin(q);
            }
            TS(40);
            acq(24);
            TS(13);
            qk_issue(sa, rdesc + (24 % NSLOT) * (SLOT >> 4));
            qk_issue(sb2, rdesc + (24 % NSLOT) * (SLOT >> 4) + 512);
            wg_wait<1>();
            pin(sa);
            {
                float x0, x1;
                new_max(sa, x0, x1);
                n0 = x0; n1 = x1;
            }
            if (w == 1) bar_sync(7, 256);
            uint32_t vd = vdesc - (SLOT >> 4) * 65535u, kd = rdesc, vb = fbar + 8, kb = fbar;
            uint32_t vlast = vdesc - 4 * (SLOT >> 4) * 65535u;
            uint32_t kprev = fbar + 32, vprev = bars + (B_SINK - (B_EMPTY - B_FULL)) * 8;
#pragma unroll 1
            for (int it = 0; it < 4; it++) {
                pv_issue(pb, vlast);
                probs(sa, pa, mbar_test(vb, it < 2) & mbar_test(kb, it < 3), [&]() { mbar_wait(vb, it < 2); mbar_wait(kb, it < 3); });
                TS(41 + it * 4);
                if (it == 0 && w == 0) bar_arrive(7, 256);
                if (it == 3 && w == 1) {
#pragma unroll
                    for (int i = 20; i < 32; i++) sb2[i] = -INFINITY;
                }
                pin(sb2);
                if (it < 3) qk_issue(sa, kd);
                if (lane == 0) mbar_arrive(kprev + (B_EMPTY - B_FULL) * 8);
                if (lane == 0) mbar_arrive(vprev + (B_EMPTY - B_FULL) * 8);
                pv_issue(pa, vd);
                probs(sb2, pb, true, []() {});
                TS(43 + it * 4);
                if (it < 3) qk_issue(sb2, kd + 512);
                const int dv = it == 0 ? 2 : (it == 1 ? -3 : 1);
                kprev = kb; vprev = vb; vlast = vd - 512 * 65535u;
                vd -= dv * (SLOT >> 4) * 65535u; vb += dv * 8;
                kd += 2 * (SLOT >> 4); kb = it == 2 ? vb : kb + 16;
            }
            pv_issue(pb, vlast);
            const int row = wq * 16 + (lane >> 2);
            const uint32_t ml = sb + OFF_INBOX;
            wg_wait<0>();
            pin(o); pin(pb); pin(sa); pin(sb2);
            rel(31);
            const float l0 = o[32], l1 = o[34];
            if (c4 == 0) { sts64f(ml + w * 512 + row * 8, n0, l0); sts64f(ml + w * 512 + row * 8 + 64, n1, l1); }
            TS(14);
            float mine[16];
#pragma unroll
            for (int j = 0; j < 4; j++) {
                if (w == 0) sts128f(H + j * 2048 + wt * 16, o[16 + 4 * j], o[17 + 4 * j], o[18 + 4 * j], o[19 + 4 * j]);
                else sts128f(H + 8192 + j * 2048 + wt * 16, o[4 * j], o[4 * j + 1], o[4 * j + 2], o[4 * j + 3]);
            }
#pragma unroll
            for (int i = 0; i < 16; i++) mine[i] = w == 0 ? o[i] : o[16 + i];
            bar_sync(10, 256);
            const float2 u0 = lds64f(ml + (w ^ 1) * 512 + row * 8), u1 = lds64f(ml + (w ^ 1) * 512 + row * 8 + 64);
            const float x0 = fminf(n0, u0.x), x1 = fminf(n1, u1.x);
            float a0 = ex2(x0 - n0), b0 = ex2(x0 - u0.x), a1 = ex2(x1 - n1), b1 = ex2(x1 - u1.x);
            const float i0 = __fdividef(1.f, fmaf(a0, l0, b0 * u0.y)), i1 = __fdividef(1.f, fmaf(a1, l1, b1 * u1.y));
            a0 *= i0; b0 *= i0; a1 *= i1; b1 *= i1;
            uint32_t pk[8];
#pragma unroll
            for (int j = 0; j < 4; j++) {
                const float4 v = lds128f(H + (w ^ 1) * 8192 + j * 2048 + wt * 16);
                pk[2 * j] = pack2(fmaf(a0, mine[4 * j], b0 * v.x), fmaf(a0, mine[4 * j + 1], b0 * v.y));
                pk[2 * j + 1] = pack2(fmaf(a1, mine[4 * j + 2], b1 * v.z), fmaf(a1, mine[4 * j + 3], b1 * v.w));
            }
            const uint32_t og = H + 16384 + wq * 2048;
            {
                const uint32_t ra = og + (((lane >> 3) & 1) * 8 + (lane & 7)) * 128;
                stsm4(ra + (((4 * w + (lane >> 4)) ^ (lane & 7)) << 4), pk[0], pk[1], pk[2], pk[3]);
                stsm4(ra + (((4 * w + 2 + (lane >> 4)) ^ (lane & 7)) << 4), pk[4], pk[5], pk[6], pk[7]);
            }
            __syncwarp();
            {
                const uint32_t off = (lane >> 2) * 128 + (((4 * w + c4) ^ (lane >> 2)) << 4);
                const uint4 v0 = lds128(og + off), v1 = lds128(og + off + 1024);
                unsigned char* dst = g_o + (size_t)(abh * PADROWS + 8 + qt * 64 + wq * 16) * 128 + off;
                stg128(dst, v0); stg128(dst + 1024, v1);
            }
            bar_arrive(6, 288);
            TS(15);
        }

        uint32_t dwr[15];
        {
#pragma unroll
            for (int i = 0; i < 15; i++) dwr[i] = hmul2(__ldg(reinterpret_cast<const uint32_t*>(p.dw + i * 256 + tile * 64) + lane), 0x3F003F00u);
            float d[24];
            uint32_t xw[12];
            mbar_wait(bars + B_X1IN * 8, 0);
            uint2 hl = make_uint2(0, 0), hr = hl;
            if (pt > 0) hl = __ldcg(&g_halo[(((pair - 1) * 4 + tile) * 2 + 1) * 128 + wt]);
            if (pt < 31) hr = __ldcg(&g_halo[(((pair + 1) * 4 + tile) * 2 + 0) * 128 + wt]);
            xw[0] = hl.x; xw[1] = hl.y; xw[10] = hr.x; xw[11] = hr.y;
#pragma unroll
            for (int i = 0; i < 8; i++) xw[2 + i] = xr[i];
            pin(xw);
            pin(dwr);
            acq(32); acq(33); acq(34); acq(35);
            mbar_wait(bars + B_OIN * 8, 0);
            TS(16);
            mm(d, 32, hdesc, cx, 0);
            mbar_wait(bars + B_OIN * 8 + 8, 0);
            mm(d, 33, hdesc + 2 * (XCH >> 4), cx, 1);
            wg_wait<1>();
            rel(32);
            wg_wait<0>();
            pin(d);
#pragma unroll
            for (int i = 0; i < 12; i++) xw[i] = pack2(d[2 * i] + blo(xw[i]), d[2 * i + 1] + bhi(xw[i]));
            if (c4 == 0) { xw[0] = (xw[0] & 0xffff0000u) | 0x3F80u; xw[1] = (xw[1] & 0xffff0000u) | 0x3F80u; }
#pragma unroll
            for (int j = 0; j < 3; j++) stsm4t(xa + j * 2048, xw[4 * j], xw[4 * j + 1], xw[4 * j + 2], xw[4 * j + 3]);
#pragma unroll
            for (int i = 0; i < 8; i++) xr[i] = xw[2 + i];
            rel(33);
            publish(2, P + tile * XCH, XCH, 384);
            TS(17);
        }
        {
            float da[24], db[24], st[24];
            bar_sync(5, 384);
            mm(da, 34, pown, cx, 0);
            mm(db, 35, pown, cx, 0);
            acq(36); acq(37);
            gate(2);
            TS(39);
            mm(da, 36, prem, cx, 1);
            mm(db, 37, prem, cx, 1);
            wg_wait<2>();
            rel(34); rel(35);
            load_stats(st, 0);
            wg_wait<0>();
            pin(da); pin(db);
            rel(36); rel(37);
            TS(18);
            uint32_t pk[12];
#pragma unroll
            for (int hh = 0; hh < 2; hh++) {
                const float ca = __shfl_sync(~0u, da[2 * hh], lane & 28), cb = __shfl_sync(~0u, db[2 * hh], lane & 28);
#pragma unroll
                for (int j = 0; j < 6; j++) {
                    const float u0 = fmaf(-st[4 * j], ca, da[4 * j + 2 * hh] * st[4 * j + 1]);
                    const float u1 = fmaf(-st[4 * j + 2], ca, da[4 * j + 2 * hh + 1] * st[4 * j + 3]);
                    const float v0 = fmaf(-st[4 * j], cb, db[4 * j + 2 * hh] * st[4 * j + 1]);
                    const float v1 = fmaf(-st[4 * j + 2], cb, db[4 * j + 2 * hh + 1] * st[4 * j + 3]);
                    pk[2 * j + hh] = pack2(fmaf(u0, tanh_fast(v0), u0), fmaf(u1, tanh_fast(v1), u1));
                }
            }
            const uint32_t gs = H + 16384 + w * XCH;
#pragma unroll
            for (int j = 0; j < 3; j++) stsm4t(gs + toff + j * 2048, pk[4 * j], pk[4 * j + 1], pk[4 * j + 2], pk[4 * j + 3]);
            bar_sync(2 + w, 128);
            uint32_t ca[8], cb[8];
            const uint32_t grow = gs + 8 * wq * 128 + c4 * 4, srow = H + tile * HCH + 8 * wq * 128 + c4 * 4;
#pragma unroll
            for (int k = 0; k < 22; k++) {
                const uint32_t v = lds32(grow + (1 + k) * 128 + (((lane >> 2) ^ ((1 + k) & 7)) << 4));
#pragma unroll
                for (int i = 0; i < 8; i++) {
                    const int tap = k - i;
                    if (tap == 0) ca[i] = hmul2(v, dwr[0]);
                    else if (tap > 0 && tap < 8) ca[i] = hfma2(v, dwr[tap], ca[i]);
                    else if (tap == 8) cb[i] = hmul2(v, dwr[8]);
                    else if (tap > 8 && tap < 15) cb[i] = hfma2(v, dwr[tap], cb[i]);
                }
            }
#pragma unroll
            for (int i = 0; i < 8; i++) {
                const float h0 = blo(ca[i]) + blo(cb[i]), h1 = bhi(ca[i]) + bhi(cb[i]);
                sts32(srow + i * 128 + (((lane >> 2) ^ i) << 4), pack2(fmaf(h0, tanh_fast(h0), h0), fmaf(h1, tanh_fast(h1), h1)));
            }
            acq(38); acq(39);
            publish(3, H + tile * HCH, HCH, 256);
            TS(19);
        }
        {
            float d[16];
            mm(d, 38, hdesc + 2 * r * (HCH >> 4), ch, 0);
            acq(40);
            xwait(3);
            sts128(P + (wt >> 6 ? (tile ^ 2) : tile) * XCH + 4096 + (wt & 63) * 16, 0x3F803F80u, 0x3F803F80u, 0x3F803F80u, 0x3F803F80u);
            mm(d, 39, hdesc + 2 * (r ^ 1) * (HCH >> 4), ch, 1);
            wg_wait<1>();
            rel(38);
            wg_wait<0>();
            pin(d);
#pragma unroll
            for (int i = 0; i < 8; i++) xr[i] = pack2(d[2 * i] + blo(xr[i]), d[2 * i + 1] + bhi(xr[i]));
            stsm4t(xa, xr[0], xr[1], xr[2], xr[3]);
            stsm4t(xa + 2048, xr[4], xr[5], xr[6], xr[7]);
            rel(39);
            publish(4, P + tile * XCH, HCH, 384);
            TS(20);
        }
    }

    xwait(5);
    cluster_arrive();
    TS(24);
    {
        float a[2][8], s[2], q[2];
        const int row0 = 16 * r + 2 * warp;
#pragma unroll
        for (int i = 0; i < 2; i++) {
            const uint4 v = lds128(P + (lane >> 3) * XCH + (row0 + i) * 128 + (((lane & 7) ^ ((row0 + i) & 7)) << 4));
            a[i][0] = blo(v.x); a[i][1] = bhi(v.x); a[i][2] = blo(v.y); a[i][3] = bhi(v.y);
            a[i][4] = blo(v.z); a[i][5] = bhi(v.z); a[i][6] = blo(v.w); a[i][7] = bhi(v.w);
            s[i] = ((a[i][0] + a[i][1]) + (a[i][2] + a[i][3])) + ((a[i][4] + a[i][5]) + (a[i][6] + a[i][7]));
            q[i] = 0.f;
#pragma unroll
            for (int k = 0; k < 8; k++) q[i] = fmaf(a[i][k], a[i][k], q[i]);
        }
#pragma unroll
        for (int o = 16; o > 0; o >>= 1) {
#pragma unroll
            for (int i = 0; i < 2; i++) { s[i] += __shfl_xor_sync(~0u, s[i], o); q[i] += __shfl_xor_sync(~0u, q[i], o); }
        }
#pragma unroll
        for (int i = 0; i < 2; i++) {
            const float mean = s[i] * (1.f / 256.f);
            const float rstd = rsqrtf(fmaxf(fmaf(-mean, mean, q[i] * (1.f / 256.f)), 0.f) + 1e-5f);
            const float nb = -mean * rstd;
            uint4 v;
            v.x = pack2(fmaf(a[i][0], rstd, nb), fmaf(a[i][1], rstd, nb)); v.y = pack2(fmaf(a[i][2], rstd, nb), fmaf(a[i][3], rstd, nb));
            v.z = pack2(fmaf(a[i][4], rstd, nb), fmaf(a[i][5], rstd, nb)); v.w = pack2(fmaf(a[i][6], rstd, nb), fmaf(a[i][7], rstd, nb));
            const int t = pt * 32 + row0 + i;
            if (t < T_) stg128(p.out + (size_t)(b * T_ + t) * 256 + lane * 8, v);
        }
    }
    TS(25);
    TG(31);
    TSDUMP();
    cluster_wait();
}

typedef CUresult (*EncodeFn)(CUtensorMap*, CUtensorMapDataType, cuuint32_t, void*, const cuuint64_t*, const cuuint64_t*,
                             const cuuint32_t*, const cuuint32_t*, CUtensorMapInterleave, CUtensorMapSwizzle,
                             CUtensorMapL2promotion, CUtensorMapFloatOOBfill);

}

extern "C" void kernel_launch(void* const* d_in, const int* in_sizes, int n_in, void* d_out, int out_size) {
    static EncodeFn encode = nullptr;
    if (!encode) {
        void* fn = nullptr;
        cudaDriverEntryPointQueryResult qr;
        cudaGetDriverEntryPoint("cuTensorMapEncodeTiled", &fn, cudaEnableDefault, &qr);
        encode = (EncodeFn)fn;
        cudaFuncSetAttribute(conformer_kernel, cudaFuncAttributeMaxDynamicSharedMemorySize, SMEM_LAUNCH);
    }
    Params p;
    const cuuint32_t ones[3] = {1, 1, 1};
    {
        const cuuint64_t dims[3] = {256, T_, 2};
        const cuuint64_t strides[2] = {512, 512ull * T_};
        const cuuint32_t box[3] = {64, 32, 1};
        encode(&p.tm[0], CU_TENSOR_MAP_DATA_TYPE_BFLOAT16, 3, d_in[0], dims, strides, box, ones, CU_TENSOR_MAP_INTERLEAVE_NONE,
               CU_TENSOR_MAP_SWIZZLE_128B, CU_TENSOR_MAP_L2_PROMOTION_L2_256B, CU_TENSOR_MAP_FLOAT_OOB_FILL_NONE);
    }
    const int idx[8] = {1, 2, 3, 4, 5, 7, 8, 9};
    const int rows[8] = {256, 1024, 256, 256, 256, 256, 256, 1024};
    const int cols[8] = {1024, 256, 768, 256, 512, 256, 1024, 256};
    for (int i = 0; i < 8; i++) {
        const cuuint64_t dims[2] = {(cuuint64_t)cols[i], (cuuint64_t)rows[i]};
        const cuuint64_t strides[1] = {(cuuint64_t)cols[i] * 2};
        const cuuint32_t box[2] = {64, 128};
        encode(&p.tm[1 + i], CU_TENSOR_MAP_DATA_TYPE_BFLOAT16, 2, d_in[idx[i]], dims, strides, box, ones, CU_TENSOR_MAP_INTERLEAVE_NONE,
               CU_TENSOR_MAP_SWIZZLE_128B, CU_TENSOR_MAP_L2_PROMOTION_L2_128B, CU_TENSOR_MAP_FLOAT_OOB_FILL_NONE);
        p.w[i] = (const char*)d_in[idx[i]];
    }
    {
        void* kv = nullptr;
        cudaGetSymbolAddress(&kv, g_kvq);
        const cuuint64_t dims[2] = {64, 16384};
        const cuuint64_t strides[1] = {128};
        const cuuint32_t box[2] = {64, 128};
        encode(&p.tm[9], CU_TENSOR_MAP_DATA_TYPE_BFLOAT16, 2, kv, dims, strides, box, ones, CU_TENSOR_MAP_INTERLEAVE_NONE,
               CU_TENSOR_MAP_SWIZZLE_NONE, CU_TENSOR_MAP_L2_PROMOTION_L2_128B, CU_TENSOR_MAP_FLOAT_OOB_FILL_NONE);
    }
    p.dw = (const __nv_bfloat16*)d_in[6];
    p.out = (__nv_bfloat16*)d_out;
    p.zero = 0;
    conformer_kernel<<<NCTA, NTHREADS, SMEM_LAUNCH>>>(p);
}
```

```cpp
#include <cuda_runtime.h>
#include <cuda_bf16.h>
#include <cuda.h>
#include <stdint.h>

namespace {

constexpr int T_ = 1000;
constexpr int NCTA = 128;
constexpr int NTHREADS = 512;
constexpr int NSLOT = 5;
constexpr int SLOT = 16384;
constexpr int NLOADS = 56;

constexpr uint32_t OFF_RING = 0;
constexpr uint32_t OFF_P = 163840;
constexpr uint32_t OFF_H = 188416;
constexpr uint32_t OFF_MISC = 221184;
constexpr uint32_t OFF_STATS = 229376;
constexpr uint32_t OFF_BARS = 229888;
constexpr uint32_t SMEM_BYTES = 230400;
constexpr uint32_t XCH = 6144;
constexpr uint32_t HCH = 4096;

constexpr int B_FULL = 0, B_EMPTY = 10, B_XA = 20  , B_XB = 24  , B_INB = 27  , B_X2 = 31, B_SR = 32, B_OIN = 33  ,
              B_QIN = 35, B_X1IN = 36, B_RDY = 37  , B_SINK = 43, B_ST = 44;

constexpr int PADROWS = 1040;
constexpr int FS = 8;

struct Params {
    CUtensorMap tm[9];
    const char* w[8];
    const __nv_bfloat16* x;
    const __nv_bfloat16* dw;
    __nv_bfloat16* out;
    uint32_t zero;
};

__device__ __align__(1024) unsigned char g_kvq[3 * 8 * 1024 * 128];
__device__ __align__(1024) unsigned char g_o[8 * PADROWS * 128];
__device__ uint4 g_halo[64 * 4 * 2 * 64];
__device__ uint32_t g_flag_kv[8 * 32 * FS];
__device__ uint32_t g_flag_q[8 * 32 * FS];
__device__ uint32_t g_flag_o[2 * 16 * 4 * FS];
__device__ uint32_t g_epoch[NCTA * FS];

#define TS(i) do { } while (0)
#define TSW(i) do { } while (0)
#define TG(i) do { } while (0)
#define TSINIT() do { } while (0)
#define TSDUMP() do { } while (0)
constexpr uint32_t SMEM_LAUNCH = SMEM_BYTES;

__device__ __forceinline__ uint32_t smem_u32(const void* p) { return (uint32_t)__cvta_generic_to_shared(p); }
__device__ __forceinline__ void mbar_init(uint32_t b, uint32_t c) { asm volatile("mbarrier.init.shared::cta.b64 [%0], %1;" ::"r"(b), "r"(c) : "memory"); }
__device__ __forceinline__ void mbar_arrive(uint32_t b) { asm volatile("mbarrier.arrive.shared::cta.b64 _, [%0];" ::"r"(b) : "memory"); }
__device__ __forceinline__ void mbar_arrive_tx(uint32_t b, uint32_t tx) { asm volatile("mbarrier.arrive.expect_tx.shared::cta.b64 _, [%0], %1;" ::"r"(b), "r"(tx) : "memory"); }
__device__ __forceinline__ void mbar_wait(uint32_t b, uint32_t ph) {
    asm volatile("{\n.reg .pred p, q;\n.reg .u32 c;\nmov.u32 c, 0;\n"
                 "MW_LOOP:\n.pragma \"nounroll\";\n"
                 "mbarrier.try_wait.parity.shared::cta.b64 p, [%0], %1;\n"
                 "add.u32 c, c, 1;\nsetp.lt.u32 q, c, 65536;\nnot.pred p, p;\nand.pred p, p, q;\n@p bra MW_LOOP;\n}"
                 ::"r"(b), "r"(ph) : "memory");
}
__device__ __forceinline__ bool mbar_test(uint32_t b, uint32_t ph) {
    uint32_t ok;
    asm volatile("{\n.reg .pred p;\nmbarrier.test_wait.parity.shared::cta.b64 p, [%1], %2;\nselp.u32 %0, 1, 0, p;\n}" : "=r"(ok) : "r"(b), "r"(ph) : "memory");
    return ok;
}
__device__ __forceinline__ uint32_t mapa(uint32_t a, uint32_t r) { uint32_t o; asm("mapa.shared::cluster.u32 %0, %1, %2;" : "=r"(o) : "r"(a), "r"(r)); return o; }
__device__ __forceinline__ void fence_async_smem() { asm volatile("fence.proxy.async.shared::cta;" ::: "memory"); }
__device__ __forceinline__ void fence_async_global() { asm volatile("fence.proxy.async.global;" ::: "memory"); }
__device__ __forceinline__ void bar_sync(int id, int n) { asm volatile("bar.sync %0, %1;" ::"r"(id), "r"(n) : "memory"); }
__device__ __forceinline__ void bar_arrive(int id, int n) { asm volatile("bar.arrive %0, %1;" ::"r"(id), "r"(n) : "memory"); }
__device__ __forceinline__ void cluster_arrive() { asm volatile("barrier.cluster.arrive.relaxed.aligned;" ::: "memory"); }
__device__ __forceinline__ void cluster_wait() { asm volatile("barrier.cluster.wait.aligned;" ::: "memory"); }

__device__ __forceinline__ void ring_load(uint32_t dst, const CUtensorMap* tm, int col, int row16, uint32_t bar) {
    asm volatile("{\n.reg .pred p;\nelect.sync _|p, 0xffffffff;\n"
                 "@p mbarrier.arrive.expect_tx.shared::cta.b64 _, [%2], 16384;\n"
                 "@p cp.async.bulk.tensor.5d.shared::cluster.global.mbarrier::complete_tx::bytes [%0], [%1, {%3, 0, 0, 0, %4}], [%2];\n}"
                 ::"r"(dst), "l"(tm), "r"(bar), "r"(col), "r"(row16) : "memory");
}
__device__ __forceinline__ void ring_load_both(uint32_t dst, const CUtensorMap* tm, int c1, uint32_t bar) {
    asm volatile("{\n.reg .pred p;\nelect.sync _|p, 0xffffffff;\n"
                 "@p cp.async.bulk.tensor.2d.shared::cluster.global.mbarrier::complete_tx::bytes.multicast::cluster [%0], [%1, {0, %3}], [%2], %4;\n}"
                 ::"r"(dst), "l"(tm), "r"(bar), "r"(c1), "h"((uint16_t)3) : "memory");
}
__device__ __forceinline__ void mbar_arrive_peer(uint32_t b) { asm volatile("mbarrier.arrive.relaxed.cluster.shared::cluster.b64 _, [%0];" ::"r"(b) : "memory"); }
__device__ __forceinline__ void bulk_g2s(uint32_t dst, const void* src, uint32_t bytes, uint32_t bar) {
    asm volatile("cp.async.bulk.shared::cluster.global.mbarrier::complete_tx::bytes [%0], [%1], %2, [%3];" ::"r"(dst), "l"(src), "r"(bytes), "r"(bar) : "memory");
}
__device__ __forceinline__ void prefetch_l2(const void* src, uint32_t bytes) {
    asm volatile("cp.async.bulk.prefetch.L2.global [%0], %1;" ::"l"(src), "r"(bytes) : "memory");
}
__device__ __forceinline__ void peer_copy(uint32_t dst, uint32_t src, uint32_t bytes, uint32_t rbar) {
    asm volatile("{\n.reg .pred p;\nelect.sync _|p, 0xffffffff;\n"
                 "@p cp.async.bulk.shared::cluster.shared::cta.mbarrier::complete_tx::bytes [%0], [%1], %2, [%3];\n}"
                 ::"r"(dst), "r"(src), "r"(bytes), "r"(rbar) : "memory");
}
__device__ __forceinline__ void st_async4(uint32_t dst, uint32_t a, uint32_t b, uint32_t c, uint32_t d, uint32_t bar) {
    asm volatile("st.async.shared::cluster.mbarrier::complete_tx::bytes.v4.b32 [%0], {%1,%2,%3,%4}, [%5];" ::"r"(dst), "r"(a), "r"(b), "r"(c), "r"(d), "r"(bar) : "memory");
}
__device__ __forceinline__ void st_async2f(uint32_t dst, float a, float b, uint32_t bar) {
    asm volatile("st.async.shared::cluster.mbarrier::complete_tx::bytes.v2.f32 [%0], {%1,%2}, [%3];" ::"r"(dst), "f"(a), "f"(b), "r"(bar) : "memory");
}
__device__ __forceinline__ void stsm4t(uint32_t a, uint32_t r0, uint32_t r1, uint32_t r2, uint32_t r3) {
    asm volatile("stmatrix.sync.aligned.m8n8.x4.trans.shared.b16 [%0], {%1,%2,%3,%4};" ::"r"(a), "r"(r0), "r"(r1), "r"(r2), "r"(r3) : "memory");
}
__device__ __forceinline__ void stsm4(uint32_t a, uint32_t r0, uint32_t r1, uint32_t r2, uint32_t r3) {
    asm volatile("stmatrix.sync.aligned.m8n8.x4.shared.b16 [%0], {%1,%2,%3,%4};" ::"r"(a), "r"(r0), "r"(r1), "r"(r2), "r"(r3) : "memory");
}
__device__ __forceinline__ void ldsm4t(uint32_t a, uint32_t& r0, uint32_t& r1, uint32_t& r2, uint32_t& r3) {
    asm volatile("ldmatrix.sync.aligned.m8n8.x4.trans.shared.b16 {%0,%1,%2,%3}, [%4];" : "=r"(r0), "=r"(r1), "=r"(r2), "=r"(r3) : "r"(a) : "memory");
}
__device__ __forceinline__ void ldsm4(uint32_t a, uint32_t& r0, uint32_t& r1, uint32_t& r2, uint32_t& r3) {
    asm volatile("ldmatrix.sync.aligned.m8n8.x4.shared.b16 {%0,%1,%2,%3}, [%4];" : "=r"(r0), "=r"(r1), "=r"(r2), "=r"(r3) : "r"(a) : "memory");
}
__device__ __forceinline__ uint4 lds128(uint32_t a) { uint4 v; asm volatile("ld.shared.v4.b32 {%0,%1,%2,%3}, [%4];" : "=r"(v.x), "=r"(v.y), "=r"(v.z), "=r"(v.w) : "r"(a) : "memory"); return v; }
__device__ __forceinline__ float4 lds128f(uint32_t a) { float4 v; asm volatile("ld.shared.v4.f32 {%0,%1,%2,%3}, [%4];" : "=f"(v.x), "=f"(v.y), "=f"(v.z), "=f"(v.w) : "r"(a) : "memory"); return v; }
__device__ __forceinline__ float2 lds64f(uint32_t a) { float2 v; asm volatile("ld.shared.v2.f32 {%0,%1}, [%2];" : "=f"(v.x), "=f"(v.y) : "r"(a) : "memory"); return v; }
__device__ __forceinline__ uint32_t lds32(uint32_t a) { uint32_t v; asm volatile("ld.shared.b32 %0, [%1];" : "=r"(v) : "r"(a) : "memory"); return v; }
__device__ __forceinline__ void sts128(uint32_t a, uint32_t x, uint32_t y, uint32_t z, uint32_t w) { asm volatile("st.shared.v4.b32 [%0], {%1,%2,%3,%4};" ::"r"(a), "r"(x), "r"(y), "r"(z), "r"(w) : "memory"); }
__device__ __forceinline__ void sts128f(uint32_t a, float x, float y, float z, float w) { asm volatile("st.shared.v4.f32 [%0], {%1,%2,%3,%4};" ::"r"(a), "f"(x), "f"(y), "f"(z), "f"(w) : "memory"); }
__device__ __forceinline__ void sts64f(uint32_t a, float x, float y) { asm volatile("st.shared.v2.f32 [%0], {%1,%2};" ::"r"(a), "f"(x), "f"(y) : "memory"); }
__device__ __forceinline__ void sts32(uint32_t a, uint32_t x) { asm volatile("st.shared.b32 [%0], %1;" ::"r"(a), "r"(x) : "memory"); }
__device__ __forceinline__ void stg128(void* p, uint4 v) { asm volatile("st.global.v4.b32 [%0], {%1,%2,%3,%4};" ::"l"(p), "r"(v.x), "r"(v.y), "r"(v.z), "r"(v.w) : "memory"); }

__device__ __forceinline__ uint32_t pack2(float lo, float hi) { uint32_t r; asm("cvt.rn.bf16x2.f32 %0, %1, %2;" : "=r"(r) : "f"(hi), "f"(lo)); return r; }
__device__ __forceinline__ float blo(uint32_t v) { return __uint_as_float(v << 16); }
__device__ __forceinline__ float bhi(uint32_t v) { return __uint_as_float(v & 0xffff0000u); }
__device__ __forceinline__ uint32_t hmul2(uint32_t a, uint32_t b) { uint32_t r; asm("mul.rn.bf16x2 %0, %1, %2;" : "=r"(r) : "r"(a), "r"(b)); return r; }
__device__ __forceinline__ uint32_t hsub2(uint32_t a, uint32_t b) { uint32_t r; asm("sub.rn.bf16x2 %0, %1, %2;" : "=r"(r) : "r"(a), "r"(b)); return r; }
__device__ __forceinline__ uint32_t hfma2(uint32_t a, uint32_t b, uint32_t c) { uint32_t r; asm("fma.rn.bf16x2 %0, %1, %2, %3;" : "=r"(r) : "r"(a), "r"(b), "r"(c)); return r; }
__device__ __forceinline__ float tanh_fast(float x) { float r; asm("tanh.approx.f32 %0, %1;" : "=f"(r) : "f"(x)); return r; }
__device__ __forceinline__ float ex2(float x) { float r; asm("ex2.approx.ftz.f32 %0, %1;" : "=f"(r) : "f"(x)); return r; }

__device__ __forceinline__ void flag_wait(const uint32_t* p, uint32_t e) {
#pragma unroll 1
    for (int i = 0; i < (1 << 20); i++) {
        uint32_t v;
        asm volatile("ld.acquire.gpu.global.u32 %0, [%1];" : "=r"(v) : "l"(p) : "memory");
        if (v == e) break;
    }
}
__device__ __forceinline__ uint32_t ld_epoch() {
    uint32_t v;
    asm volatile("ld.relaxed.gpu.global.u32 %0, [%1];" : "=r"(v) : "l"(&g_epoch[blockIdx.x * FS]) : "memory");
    return v + 1;
}
__device__ __forceinline__ void flag_set(uint32_t* p, uint32_t e) { asm volatile("st.release.gpu.global.u32 [%0], %1;" ::"l"(p), "r"(e) : "memory"); }

__device__ __forceinline__ uint32_t desc_lo(uint32_t addr) { return ((addr & 0x3FFFF) >> 4) | 0x10000u; }
__device__ __forceinline__ uint64_t mkdesc(uint32_t lo) { return (uint64_t)lo | (0x40000040ull << 32); }
__device__ __forceinline__ void wg_fence() { asm volatile("wgmma.fence.sync.aligned;" ::: "memory"); }
__device__ __forceinline__ void wg_commit() { asm volatile("wgmma.commit_group.sync.aligned;" ::: "memory"); }
template <int N> __device__ __forceinline__ void wg_wait() { asm volatile("wgmma.wait_group.sync.aligned %0;" ::"n"(N) : "memory"); }
template <int N> __device__ __forceinline__ void pin(float (&d)[N]) {
#pragma unroll
    for (int i = 0; i < N; i++) asm volatile("" : "+f"(d[i])::"memory");
}
template <int N> __device__ __forceinline__ void pin(uint32_t (&d)[N]) {
#pragma unroll
    for (int i = 0; i < N; i++) asm volatile("" : "+r"(d[i])::"memory");
}

template <typename Tp, int N> __device__ __forceinline__ void zero(Tp (&d)[N]) {
#pragma unroll
    for (int i = 0; i < N; i++) d[i] = 0;
    pin(d);
}

#define F4(d, i) "+f"(d[i]), "+f"(d[i + 1]), "+f"(d[i + 2]), "+f"(d[i + 3])
#define F16(d, i) F4(d, i), F4(d, i + 4), F4(d, i + 8), F4(d, i + 12)

__device__ __forceinline__ void mma_sp(float (&d)[32], const uint32_t* a, uint64_t b, int acc) {
    asm volatile("{.reg .pred p; setp.ne.b32 p, %38, 0;\n"
                 "wgmma.mma_async.sp.sync.aligned.m64n64k32.f32.bf16.bf16 {%0,%1,%2,%3,%4,%5,%6,%7,%8,%9,%10,%11,%12,%13,%14,%15,%16,%17,%18,%19,%20,%21,%22,%23,%24,%25,%26,%27,%28,%29,%30,%31}, "
                 "{%32,%33,%34,%35}, %36, %37, 0, p, 1, 1, 1;}\n"
                 : F16(d, 0), F16(d, 16) : "r"(a[0]), "r"(a[1]), "r"(a[2]), "r"(a[3]), "l"(b), "r"(0xEEEE4444u), "r"(acc));
}
__device__ __forceinline__ void mma_t(float (&d)[24], uint64_t a, uint64_t b, int acc) {
    asm volatile("{.reg .pred p; setp.ne.b32 p, %26, 0;\n"
                 "wgmma.mma_async.sync.aligned.m64n48k16.f32.bf16.bf16 {%0,%1,%2,%3,%4,%5,%6,%7,%8,%9,%10,%11,%12,%13,%14,%15,%16,%17,%18,%19,%20,%21,%22,%23}, %24, %25, p, 1, 1, 1, 0;}\n"
                 : F16(d, 0), F4(d, 16), F4(d, 20) : "l"(a), "l"(b), "r"(acc));
}
__device__ __forceinline__ void mma_qk(float (&d)[32], uint32_t a0, uint32_t a1, uint32_t a2, uint32_t a3, uint64_t b, int acc) {
    asm volatile("{.reg .pred p; setp.ne.b32 p, %37, 0;\n"
                 "wgmma.mma_async.sync.aligned.m64n64k16.f32.bf16.bf16 {%0,%1,%2,%3,%4,%5,%6,%7,%8,%9,%10,%11,%12,%13,%14,%15,%16,%17,%18,%19,%20,%21,%22,%23,%24,%25,%26,%27,%28,%29,%30,%31}, "
                 "{%32,%33,%34,%35}, %36, p, 1, 1, 0;}\n"
                 : F16(d, 0), F16(d, 16) : "r"(a0), "r"(a1), "r"(a2), "r"(a3), "l"(b), "r"(acc));
}
__device__ __forceinline__ void mma_pv(float (&d)[36], uint32_t a0, uint32_t a1, uint32_t a2, uint32_t a3, uint64_t b) {
    asm volatile("wgmma.mma_async.sync.aligned.m64n72k16.f32.bf16.bf16 {%0,%1,%2,%3,%4,%5,%6,%7,%8,%9,%10,%11,%12,%13,%14,%15,%16,%17,%18,%19,%20,%21,%22,%23,%24,%25,%26,%27,%28,%29,%30,%31,%32,%33,%34,%35}, "
                 "{%36,%37,%38,%39}, %40, 1, 1, 1, 1;\n"
                 : F16(d, 0), F16(d, 16), F4(d, 32) : "r"(a0), "r"(a1), "r"(a2), "r"(a3), "l"(b));
}

__device__ __forceinline__ uint32_t load_code(int n, int r, int w) {
    const int tile = 2 * r + w;
    int m, col, row;
    if (n < 16 || n >= 40) {
        const int k = n < 16 ? n : n - 40;
        m = n < 16 ? 0 : 6;
        if (k < 4) { col = 4 * tile + (k & 1); row = (k >> 1) ^ r; }
        else if (k < 8) { col = 4 * tile + (k >> 1); row = (k & 1) ^ r; }
        else { m++; col = tile ^ (3 - ((k - 8) >> 1)); row = 2 * tile + (k & 1); }
    } else if (n < 32) {
        const int k = n - 16;
        m = 2;
        if (k < 4) { col = tile + ((k & 1) ? 8 : 4); row = (k >> 1) ^ r; }
        else { col = tile; row = (k & 1) ^ r; }
    } else if (n < 34) { m = 3; col = tile; row = n - 32; }
    else if (n < 38) { const int k = n - 34; m = 4; col = tile + 4 * (k & 1); row = (k >> 1) ^ r; }
    else { m = 5; col = tile; row = (n & 1) ^ r; }
    return m | (col << 4) | (row << 8);
}

__global__ void __cluster_dims__(2, 1, 1) __launch_bounds__(NTHREADS, 1)
conformer_kernel(const __grid_constant__ Params p) {
    extern __shared__ __align__(1024) unsigned char smem_raw[];
    const uint32_t sb = smem_u32(smem_raw);
    const uint32_t bars = sb + OFF_BARS;
    const int tid = threadIdx.x;
    const int lane = tid & 31;
    const int warp = __shfl_sync(~0u, tid >> 5, 0);
    const int r = blockIdx.x & 1;
    const int pair = blockIdx.x >> 1;
    const int b = pair >> 5, pt = pair & 31;
    const int ah = pt >> 3, qt = (pt & 7) * 2 + r;
    const int abh = b * 4 + ah;

    TG(30);
    TSINIT();
    TS(0);
    const uint32_t P = sb + OFF_P, H = sb + OFF_H;

    if (warp >= 8) {
        asm volatile("setmaxnreg.dec.sync.aligned.u32 48;");
        if (warp >= 12) {
            cluster_arrive();
            cluster_wait();
            if (warp == 12) {
                const uint32_t epoch = ld_epoch();
                bar_sync(11, 288);
                if (lane < 2) flag_set(&g_flag_q[((b * 4 + 2 * r + lane) * 32 + pt) * FS], epoch);
                __syncwarp();
                TS(13);
            }
            const int ut = tid & 127;
            const uint32_t a8 = P + (ut >> 3) * 128 + (ut & 7) * 16;
            float s[3] = {0.f, 0.f, 0.f}, q[3] = {0.f, 0.f, 0.f};
#pragma unroll 1
            for (int h = 0; h < 2; h++) {
                if (h == 0) bar_sync(1, 384);
                else mbar_wait(bars + B_X2 * 8, 0);
                uint4 v[6];
#pragma unroll
                for (int i = 0; i < 6; i++) v[i] = lds128(a8 + (2 * (r ^ h) + (i & 1)) * XCH + (i >> 1) * 2048);
                bar_arrive(5 + ((v[0].w | v[1].w | v[2].w | v[3].w | v[4].w | v[5].w) & p.zero), 384);
                uint32_t t;
                asm volatile("mov.u32 %0, %%clock;" : "=r"(t)::"memory");
                const uint32_t mul = 65536u + (t & p.zero), msk = 0u - mul;
#pragma unroll
                for (int i = 0; i < 6; i++) {
                    const float a0 = __uint_as_float(v[i].x * mul), a1 = __uint_as_float(v[i].x & msk), a2 = __uint_as_float(v[i].y * mul), a3 = __uint_as_float(v[i].y & msk);
                    const float a4 = __uint_as_float(v[i].z * mul), a5 = __uint_as_float(v[i].z & msk), a6 = __uint_as_float(v[i].w * mul), a7 = __uint_as_float(v[i].w & msk);
                    s[i >> 1] += ((a0 + a1) + (a2 + a3)) + ((a4 + a5) + (a6 + a7));
                    q[i >> 1] += fmaf(a0, a0, fmaf(a1, a1, fmaf(a2, a2, a3 * a3))) + fmaf(a4, a4, fmaf(a5, a5, fmaf(a6, a6, a7 * a7)));
                }
            }
#pragma unroll
            for (int o = 1; o < 8; o <<= 1) {
#pragma unroll
                for (int i = 0; i < 3; i++) { s[i] += __shfl_xor_sync(~0u, s[i], o); q[i] += __shfl_xor_sync(~0u, q[i], o); }
            }
            const int k = ut & 7, row = (ut >> 3) + 16 * k;
            const float mean = (k == 0 ? s[0] : (k == 1 ? s[1] : s[2])) * (1.f / 256.f);
            const float msq = (k == 0 ? q[0] : (k == 1 ? q[1] : q[2])) * (1.f / 256.f);
            const float alpha = (uint32_t)(pt * 32 - 8 + row) >= T_ ? 0.f : 0.5f;
            const float rstd = alpha * rsqrtf(fmaxf(fmaf(-mean, mean, msq), 0.f) + 1e-5f);
            if (k < 3) sts64f(sb + OFF_STATS + row * 8, mean * rstd, rstd);
            __syncwarp();
            if (lane == 0) mbar_arrive(bars + B_ST * 8);
            TS(4);
        } else if (warp < 10) {
            const int w = warp - 8;
            const uint32_t ring = sb + OFF_RING + w * NSLOT * SLOT;
            const uint32_t full = bars + (B_FULL + w * NSLOT) * 8;
            if (lane == 0) {
#pragma unroll
                for (int i = 0; i < NSLOT; i++) { mbar_init(full + i * 8, 1); mbar_init(full + (B_EMPTY - B_FULL + i) * 8, 4); }
                asm volatile("fence.mbarrier_init.release.cluster;" ::: "memory");
                fence_async_smem();
            }
            __syncwarp();
            cluster_arrive();
            TS(1);
#pragma unroll
            for (int n = 0; n < NSLOT; n++)
                ring_load(ring + n * SLOT, &p.tm[0], 64 * (8 * r + 4 * w + (n < 4 ? n & 1 : 2)), 8 * (((n >> 1) & 1) ^ r), full + n * 8);
            TS(2);
            const uint32_t code = load_code(lane, r, w) | (load_code(lane + 32, r, w) << 16);
            cluster_wait();
            uint32_t s = 0, ph = 0;
            int n = NSLOT;
#pragma unroll 1
            for (int seg = 0; seg < 2; seg++) {
#pragma unroll 1
                for (; n < (seg == 0 ? 22 : NLOADS); n++) {
                    const uint32_t c = __shfl_sync(~0u, code, n) >> (n & 32 ? 16 : 0);
                    mbar_wait(full + (B_EMPTY - B_FULL) * 8 + s * 8, ph);
                    ring_load(ring + s * SLOT, &p.tm[c & 15], (c & 0xf0) * 4, (c & 0xff00) >> 5, full + s * 8);
                    if (++s == NSLOT) { s = 0; ph ^= 1; }
                }
                if (seg == 1) break;
                const uint32_t epoch = ld_epoch();
                const uint32_t rdy = bars + (B_RDY + 3 * w) * 8, prdy = mapa(rdy, r ^ 1);
                const int isv = r ^ w;
#pragma unroll 1
                for (; n < 32; n++) {
                    mbar_wait(full + (B_EMPTY - B_FULL) * 8 + s * 8, ph);
                    if (lane == 0) {
                        if (n < 24) mbar_arrive(full + s * 8);
                        else mbar_arrive_tx(full + s * 8, SLOT);
                    }
                    if (n == 28) {
                        if (lane == 0) mbar_arrive_peer(prdy);
                        mbar_wait(rdy, 0);
                        if (!isv) {
                            flag_wait(g_flag_kv + (abh * 32 + lane) * FS, epoch);
                            __syncwarp();
                            fence_async_global();
                            TSW(5);
                            ring_load_both(ring + 4 * SLOT, &p.tm[8], (abh * 8 + w) * 128, full + 32);
                        }
                        bar_sync(12, 64);
#pragma unroll
                        for (int i = 0; i < 2; i++) {
                            if (i == 0) mbar_wait(bars + B_QIN * 8, 0);
                            else mbar_wait(full + isv * 8, 1);
                            ring_load_both(ring + (2 * i + isv) * SLOT, &p.tm[8], (isv * 62 + abh * 8 + 2 * i + 2 + w) * 128, full + (2 * i + isv) * 8);
                        }
                    } else if (n > 28) {
                        const uint32_t bo = n == 31 ? 16 : 8;
                        if ((n > 29) == (isv == 1)) {
                            mbar_wait(rdy + bo, 0);
                            ring_load_both(ring + s * SLOT, &p.tm[8], (isv * 64 + abh * 8 + (n == 30 ? 4 : 6) + w) * 128, full + s * 8);
                        } else if (lane == 0) mbar_arrive_peer(prdy + bo);
                    }
                    __syncwarp();
                    if (++s == NSLOT) { s = 0; ph ^= 1; }
                }
            }
        } else if (warp == 10) {
            if (lane == 0) {
#pragma unroll
                for (int i = B_XA; i <= B_ST; i++) mbar_init(bars + i * 8, i == B_ST ? 4 : 1);
#pragma unroll
                for (int i = B_XA; i <= B_QIN; i++)
                    mbar_arrive_tx(bars + i * 8, i < B_XA + 3 ? 9216 : (i == B_XA + 3 ? 1024 : ((i < B_INB || i == B_SR || i == B_QIN) ? 8192 : 12288)));
                asm volatile("fence.mbarrier_init.release.cluster;" ::: "memory");
                fence_async_smem();
            }
            __syncwarp();
            cluster_arrive();
            cluster_wait();
            const uint32_t epoch = ld_epoch();
            if (lane < 2) flag_wait(&g_flag_q[(abh * 32 + 2 * qt + lane) * FS], epoch);
            __syncwarp();
            TSW(6);
            if (lane == 0) {
                fence_async_global();
                bulk_g2s(H + 24576, g_kvq + 2097152 + (size_t)(abh * 1024 + qt * 64) * 128, 8192, bars + B_QIN * 8);
            }
            if (lane < 2) {
                const int np = pt - 1 + 2 * lane;
                if (np >= 0 && np < 32) flag_wait(&g_flag_kv[((b * 4 + 2 * r) * 32 + np) * FS], epoch);
            }
            __syncwarp();
            if (lane == 0) mbar_arrive(bars + B_X1IN * 8);
            bar_sync(9, 64);
            if (lane < 8) {
                const int q = (pt >> 1) + (lane < 4 ? 0 : ((pt & 1) ? 1 : -1));
                if (q >= 0 && q < 16) flag_wait(&g_flag_o[((b * 16 + q) * 4 + (lane & 3)) * FS], epoch);
            }
            __syncwarp();
            TSW(10);
            if (lane == 0) {
                fence_async_global();
#pragma unroll
                for (int i = 0; i < 4; i++)
                    bulk_g2s(H + i * XCH, g_o + (size_t)((b * 4 + i) * PADROWS + pt * 32) * 128, XCH, bars + (B_OIN + (i >> 1)) * 8);
            }
            __syncwarp();
        } else {
            const uint32_t kb = (lane < 2 || lane > 5) ? 4096 : (lane == 2 ? 3072 : (lane == 4 ? 2048 : 1024));
            const char* pf = p.w[lane & 7] + blockIdx.x * kb;
            cluster_arrive();
            cluster_wait();
            if (lane < 2) prefetch_l2(pf, kb);
            mbar_wait(bars + B_XA * 8, 0);
            if (lane == 2) prefetch_l2(pf, kb);
            if (lane >= 1 && lane < 9) asm volatile("prefetch.tensormap [%0];" ::"l"(&p.tm[lane]) : "memory");
            mbar_wait(bars + (B_FULL + 1) * 8, 1);
            if (lane > 2 && lane < 8) prefetch_l2(pf, kb);
            const uint32_t epoch = ld_epoch();
            bar_sync(4, 288);
            if (lane < 2) flag_set(&g_flag_kv[((b * 4 + 2 * r + lane) * 32 + pt) * FS], epoch);
            __syncwarp();
            TSW(8);
            bar_sync(6, 288);
            bar_arrive(9, 64);
            if (lane == 0) {
                flag_set(&g_flag_o[((b * 16 + qt) * 4 + ah) * FS], epoch);
                g_epoch[blockIdx.x * FS] = epoch;
            }
            __syncwarp();
            TSW(9);
        }
        TSDUMP();
        return;
    }

    const int w = warp >> 2, wq = warp & 3;
    const int tile = 2 * r + w;
    const int wt = tid & 127;
    const int c4 = lane & 3;
    const int trow = pt * 32 + 8 * wq;
    uint32_t xr[8];
    {
        const uint32_t* xp = reinterpret_cast<const uint32_t*>(p.x + (size_t)(b * T_ + trow + (lane >> 2)) * 256 + tile * 64) + c4;
#pragma unroll
        for (int j = 0; j < 8; j++) xr[j] = trow < T_ ? __ldg(xp + 4 * j) : 0u;
    }
    cluster_arrive();
    asm volatile("setmaxnreg.inc.sync.aligned.u32 208;");
    const uint32_t rbase = sb + OFF_RING + w * NSLOT * SLOT, fbar = bars + (B_FULL + w * NSLOT) * 8;
    const uint32_t rdesc = desc_lo(rbase);
    auto acq = [&](int n) { mbar_wait(fbar + (n % NSLOT) * 8, (n / NSLOT) & 1); };
    auto rel = [&](int n) { if (lane == 0) mbar_arrive(fbar + (B_EMPTY - B_FULL + n % NSLOT) * 8); };
    const uint32_t peer = mapa(sb, r ^ 1) - sb;
    const uint32_t foff = (lane & 7) * 128 + (((lane >> 3) ^ (lane & 7)) << 4);
    const uint32_t toff = ((lane >> 4) * 8 + (lane & 7)) * 128 + (((2 * wq + ((lane >> 3) & 1)) ^ (lane & 7)) << 4);
    auto publish = [&](int bar, uint32_t src, uint32_t bytes, int nsync) {
        fence_async_smem();
        bar_sync(2 + w, 128);
        if (wq == 0) peer_copy(src + peer, src, bytes, bars + bar * 8 + peer);
        bar_sync(nsync == 384 ? 1 : 10, nsync);
    };
    float v[16];
#pragma unroll
    for (int j = 0; j < 8; j++) { v[2 * j] = blo(xr[j]); v[2 * j + 1] = bhi(xr[j]); }
    cluster_wait();
    TS(56);
    float mean, rstd;

#pragma unroll 1
    for (int ph = 0;; ph++) {
        const uint32_t xb = P + wt * 16;
        {
            float s = 0.f, q = 0.f;
#pragma unroll
            for (int j = 0; j < 8; j++) {
                xr[j] = pack2(v[2 * j], v[2 * j + 1]);
                s += v[2 * j] + v[2 * j + 1];
                q = fmaf(v[2 * j], v[2 * j], fmaf(v[2 * j + 1], v[2 * j + 1], q));
            }
            const uint32_t xa = bars + (B_XA + ph) * 8, sbuf = sb + OFF_MISC + 1024 + (8 * wq + (lane >> 2)) * 32;
            if (ph < 3) {
                st_async4(xb + tile * 4096, xr[0], xr[1], xr[2], xr[3], xa);
                st_async4(xb + tile * 4096 + 2048, xr[4], xr[5], xr[6], xr[7], xa);
            }
            s += __shfl_xor_sync(~0u, s, 1); q += __shfl_xor_sync(~0u, q, 1);
            s += __shfl_xor_sync(~0u, s, 2); q += __shfl_xor_sync(~0u, q, 2);
            if (c4 < 2) st_async2f(sbuf + tile * 8 + c4 * peer, s, q, xa + c4 * peer);
            if (ph < 3) {
                st_async4(xb + tile * 4096 + peer, xr[0], xr[1], xr[2], xr[3], xa + (B_XB - B_XA) * 8 + peer);
                st_async4(xb + tile * 4096 + 2048 + peer, xr[4], xr[5], xr[6], xr[7], xa + (B_XB - B_XA) * 8 + peer);
            }
            mbar_wait(xa, 0);
            const float4 u0 = lds128f(sbuf), u1 = lds128f(sbuf + 16);
            mean = ((u0.x + u0.z) + (u1.x + u1.z)) * (1.f / 256.f);
            rstd = rsqrtf(fmaxf(fmaf(-mean, mean, ((u0.y + u0.w) + (u1.y + u1.w)) * (1.f / 256.f)), 0.f) + 1e-5f);
        }
        if (ph == 3) break;
        uint32_t a[32];
        const uint32_t mean2 = pack2(mean, mean);
        auto gather = [&](int i, int t) {
            const uint4 u0 = lds128(xb + t * 4096), u1 = lds128(xb + t * 4096 + 2048);
            a[i] = hsub2(u0.x, mean2); a[i + 1] = hsub2(u0.y, mean2); a[i + 2] = hsub2(u0.z, mean2); a[i + 3] = hsub2(u0.w, mean2);
            a[i + 4] = hsub2(u1.x, mean2); a[i + 5] = hsub2(u1.y, mean2); a[i + 6] = hsub2(u1.z, mean2); a[i + 7] = hsub2(u1.w, mean2);
        };
        gather(8, tile ^ 1);
#pragma unroll
        for (int j = 0; j < 8; j++) a[j] = hsub2(xr[j], mean2);
        auto gather_peer = [&]() {
            mbar_wait(bars + (B_XB + ph) * 8, 0);
            gather(16, 2 * (r ^ 1));
            gather(24, 2 * (r ^ 1) + 1);
        };
        auto sp = [&](float (&d)[32], int n, const uint32_t* af, int flip, int acc) {
            const uint32_t lo = rdesc + p.zero * (ph + n + 1) + (n % NSLOT) * (SLOT >> 4);
            const uint64_t b0 = mkdesc(lo + flip * 512), b1 = mkdesc(lo + (flip ^ 1) * 512);
            wg_fence();
            mma_sp(d, af, b0, acc);
            mma_sp(d, af + 4, b0 + 256, 1);
            mma_sp(d, af + 8, b1, 1);
            mma_sp(d, af + 12, b1 + 256, 1);
            wg_commit();
        };
        float d0[32], d1[32];

        if (ph != 1) {
            uint32_t h[32];
            const float rs = 0.5f * rstd;
            const uint32_t inb = bars + (B_INB + ph) * 8, box = H + wt * 16;
            auto step = [&](float (&d)[32], int n, const uint32_t* af, int flip, int acc) {
                acq(n);
                sp(d, n, af, flip, acc);
                wg_wait<1>();
                if (n > 0) rel(n - 1);
            };
            auto act = [&](float (&d)[32], int i) {
                pin(d);
#pragma unroll
                for (int j = 0; j < 8; j++) {
                    const float u0 = (d[4 * j] + d[4 * j + 2]) * rs, u1 = (d[4 * j + 1] + d[4 * j + 3]) * rs;
                    h[8 * i + j] = pack2(fmaf(u0, tanh_fast(u0), u0), fmaf(u1, tanh_fast(u1), u1));
                }
            };
            auto send = [&](float (&d)[32], int x) {
                pin(d);
                uint32_t pk[8];
#pragma unroll
                for (int j = 0; j < 8; j++) pk[j] = pack2(d[4 * j] + d[4 * j + 2], d[4 * j + 1] + d[4 * j + 3]);
                const uint32_t far = x & 2 ? peer : 0, ow = w ^ (x & 1);
                const uint32_t dst = box + (ow * 3 + x - 1) * 4096 + far;
                st_async4(dst, pk[0], pk[1], pk[2], pk[3], inb + ow * 8 + far);
                st_async4(dst + 2048, pk[4], pk[5], pk[6], pk[7], inb + ow * 8 + far);
            };
            TS(1 + ph * 10);
            step(d0, 0, a, w, 0);
            step(d1, 1, a, w, 0);
            gather_peer();
            TS(32);
            step(d0, 2, a + 16, 0, 1);
            step(d1, 3, a + 16, 0, 1); act(d0, 0);
            step(d0, 4, a, w, 0); act(d1, 1);
            TS(33);
            step(d0, 5, a + 16, 0, 1);
            step(d1, 6, a, w, 0); act(d0, 2);
            step(d1, 7, a + 16, 0, 1);
            step(d0, 8, h, 0, 0); act(d1, 3);
            TS(2 + ph * 10);
            step(d0, 9, h + 16, 0, 1);
            step(d1, 10, h, 0, 0); send(d0, 3);
            step(d1, 11, h + 16, 0, 1);
            step(d0, 12, h, 0, 0); send(d1, 2);
            TS(34);
            step(d0, 13, h + 16, 0, 1);
            step(d1, 14, h, 0, 0); send(d0, 1);
            step(d1, 15, h + 16, 0, 1);
            mbar_wait(inb + w * 8, 0);
#pragma unroll
            for (int i = 0; i < 2; i++) {
                const uint32_t src = box + w * 12288 + i * 2048;
                const uint4 u0 = lds128(src), u1 = lds128(src + 4096), u2 = lds128(src + 8192);
                const uint32_t p0[4] = {u0.x, u0.y, u0.z, u0.w}, p1[4] = {u1.x, u1.y, u1.z, u1.w}, p2[4] = {u2.x, u2.y, u2.z, u2.w};
#pragma unroll
                for (int j = 0; j < 4; j++) {
                    v[8 * i + 2 * j] = fmaf(0.5f, blo(p0[j]) + blo(p1[j]) + blo(p2[j]), blo(xr[4 * i + j]));
                    v[8 * i + 2 * j + 1] = fmaf(0.5f, bhi(p0[j]) + bhi(p1[j]) + bhi(p2[j]), bhi(xr[4 * i + j]));
                }
            }
            wg_wait<0>();
            pin(d1);
            rel(15);
            TS(3 + ph * 10);
#pragma unroll
            for (int j = 0; j < 8; j++) {
                v[2 * j] = fmaf(0.5f, d1[4 * j] + d1[4 * j + 2], v[2 * j]);
                v[2 * j + 1] = fmaf(0.5f, d1[4 * j + 1] + d1[4 * j + 3], v[2 * j + 1]);
            }
            continue;
        }

        {
            TS(11);
            acq(16);
            sp(d0, 16, a, w, 0);
            acq(17);
            sp(d1, 17, a, w, 0);
            if (wq == 0 || wq == 3) {
                uint4* hp = &g_halo[((pair * 4 + tile) * 2 + (wq & 1)) * 64 + lane];
                hp[0] = make_uint4(xr[0], xr[1], xr[2], xr[3]);
                hp[32] = make_uint4(xr[4], xr[5], xr[6], xr[7]);
            }
            gather_peer();
            acq(18);
            sp(d0, 18, a + 16, 0, 1);
            wg_wait<1>();
            rel(16); rel(17);
            acq(19);
            sp(d1, 19, a + 16, 0, 1);
            const uint32_t stg = H + warp * 3072;
            unsigned char* g = g_kvq + (size_t)((b * 4 + tile) * 1024 + trow) * 128 + lane * 16;
            auto put = [&](float (&d)[32], int i) {
                pin(d);
                uint32_t pk[8];
#pragma unroll
                for (int j = 0; j < 8; j++) pk[j] = pack2((d[4 * j] + d[4 * j + 2]) * rstd, (d[4 * j + 1] + d[4 * j + 3]) * rstd);
                stsm4(stg + i * 1024 + foff, pk[0], pk[1], pk[2], pk[3]);
                stsm4(stg + i * 1024 + (foff ^ 64), pk[4], pk[5], pk[6], pk[7]);
                __syncwarp();
                const uint4 u0 = lds128(stg + i * 1024 + lane * 16), u1 = lds128(stg + i * 1024 + 512 + lane * 16);
                stg128(g + i * 1048576, u0); stg128(g + i * 1048576 + 512, u1);
            };
            wg_wait<1>();
            rel(18);
            put(d0, 0);
            wg_wait<0>();
            rel(19);
            TS(37);
            put(d1, 1);
            bar_arrive(4, 288);
            TS(38);
            acq(20);
            sp(d0, 20, a, w, 0);
            acq(21);
            sp(d0, 21, a + 16, 0, 1);
            wg_wait<0>();
            rel(20); rel(21);
            put(d0, 2);
            bar_arrive(11, 288);
            acq(22); acq(23);
            rel(22); rel(23);
            TS(12);
        }

        {
            constexpr float CS = 0.125f * 1.4426950408889634f;
            float sa[32], sb2[32], o[36];
            uint32_t pa[16], pb[16], q[16];
            float n0 = INFINITY, n1 = INFINITY;
            zero(o); zero(pa); zero(pb);
            const uint32_t ones = sb + OFF_MISC + 2048;
            if (tid < 128) sts128(ones + tid * 16, 0x3F803F80u, 0x3F803F80u, 0x3F803F80u, 0x3F803F80u);
            fence_async_smem();
            bar_sync(10, 256);
            const uint32_t vdesc = rdesc + ((((ones - rbase) >> 4) - 1) << 16);
            auto qk_issue = [&](float (&s)[32], uint32_t lo) {
                const uint64_t kd = mkdesc(lo);
                wg_fence();
#pragma unroll
                for (int k = 0; k < 4; k++) mma_qk(s, q[4 * k], q[4 * k + 1], q[4 * k + 2], q[4 * k + 3], kd + 2 * k, k != 0);
                wg_commit();
            };
            auto pv_issue = [&](uint32_t (&pp)[16], uint32_t lo) {
                const uint64_t vd = mkdesc(lo);
                wg_fence();
#pragma unroll
                for (int k = 0; k < 4; k++) mma_pv(o, pp[4 * k], pp[4 * k + 1], pp[4 * k + 2], pp[4 * k + 3], vd - k * (128 * 65535));
                wg_commit();
            };
            auto new_max = [&](float (&s)[32], float& x0, float& x1) {
                x0 = s[0]; x1 = s[2];
#pragma unroll
                for (int j = 0; j < 8; j++) {
                    x0 = fmaxf(x0, fmaxf(s[4 * j], s[4 * j + 1]));
                    x1 = fmaxf(x1, fmaxf(s[4 * j + 2], s[4 * j + 3]));
                }
                x0 = fmaxf(x0, __shfl_xor_sync(~0u, x0, 1)); x1 = fmaxf(x1, __shfl_xor_sync(~0u, x1, 1));
                x0 = fmaxf(x0, __shfl_xor_sync(~0u, x0, 2)); x1 = fmaxf(x1, __shfl_xor_sync(~0u, x1, 2));
                x0 = fminf(n0, fmaf(x0, -CS, -20.f)); x1 = fminf(n1, fmaf(x1, -CS, -20.f));
            };
            auto probs = [&](float (&s)[32], uint32_t (&pp)[16], bool ready, auto wait) {
                uint32_t any = 0;
#pragma unroll
                for (int i = 0; i < 16; i++) {
                    pp[i] = pack2(ex2(fmaf(s[2 * i], CS, (i & 1) ? n1 : n0)), ex2(fmaf(s[2 * i + 1], CS, (i & 1) ? n1 : n0)));
                    any |= pp[i];
                }
                float sc0 = 1.f, sc1 = 1.f;
                const bool slow = __any_sync(~0u, (any & 0x40004000u) || !ready);
                if (slow) {
                    wait();
                    if (__any_sync(~0u, any & 0x40004000u)) {
                        float x0, x1;
                        new_max(s, x0, x1);
                        sc0 = ex2(x0 - n0); sc1 = ex2(x1 - n1);
                        n0 = x0; n1 = x1;
#pragma unroll
                        for (int i = 0; i < 16; i++)
                            pp[i] = pack2(ex2(fmaf(s[2 * i], CS, (i & 1) ? n1 : n0)), ex2(fmaf(s[2 * i + 1], CS, (i & 1) ? n1 : n0)));
                    }
                }
                wg_wait<0>();
                pin(sa); pin(sb2); pin(o); pin(pa); pin(pb);
                if (slow) {
#pragma unroll
                    for (int j = 0; j < 9; j++) { o[4 * j] *= sc0; o[4 * j + 1] *= sc0; o[4 * j + 2] *= sc1; o[4 * j + 3] *= sc1; }
                }
            };
            mbar_wait(bars + B_QIN * 8, 0);
            {
                const uint32_t qa = H + 24576 + (wq * 16 + (lane & 15)) * 128;
#pragma unroll
                for (int k = 0; k < 4; k++) ldsm4(qa + (((2 * k + (lane >> 4)) ^ (lane & 7)) << 4), q[4 * k], q[4 * k + 1], q[4 * k + 2], q[4 * k + 3]);
                pin(q);
            }
            TS(40);
            acq(24);
            TS(13);
            qk_issue(sa, rdesc + (24 % NSLOT) * (SLOT >> 4));
            qk_issue(sb2, rdesc + (24 % NSLOT) * (SLOT >> 4) + 512);
            wg_wait<1>();
            pin(sa);
            {
                float x0, x1;
                new_max(sa, x0, x1);
                n0 = x0; n1 = x1;
            }
            if (w == 1) bar_sync(7, 256);
            uint32_t vd = vdesc - (SLOT >> 4) * 65535u, kd = rdesc, vb = fbar + 8, kb = fbar;
            uint32_t vlast = vdesc - 4 * (SLOT >> 4) * 65535u;
            uint32_t kprev = fbar + 32, vprev = bars + (B_SINK - (B_EMPTY - B_FULL)) * 8;
#pragma unroll 1
            for (int it = 0; it < 4; it++) {
                pv_issue(pb, vlast);
                probs(sa, pa, mbar_test(vb, it < 2) & mbar_test(kb, it < 3), [&]() { mbar_wait(vb, it < 2); mbar_wait(kb, it < 3); });
                TS(41 + it * 4);
                if (it == 0 && w == 0) bar_arrive(7, 256);
                if (it == 3 && w == 1) {
#pragma unroll
                    for (int i = 20; i < 32; i++) sb2[i] = -INFINITY;
                }
                pin(sb2);
                if (it < 3) qk_issue(sa, kd);
                if (lane == 0) mbar_arrive(kprev + (B_EMPTY - B_FULL) * 8);
                if (lane == 0) mbar_arrive(vprev + (B_EMPTY - B_FULL) * 8);
                pv_issue(pa, vd);
                probs(sb2, pb, true, []() {});
                TS(43 + it * 4);
                if (it < 3) qk_issue(sb2, kd + 512);
                const int dv = it == 0 ? 2 : (it == 1 ? -3 : 1);
                kprev = kb; vprev = vb; vlast = vd - 512 * 65535u;
                vd -= dv * (SLOT >> 4) * 65535u; vb += dv * 8;
                kd += 2 * (SLOT >> 4); kb = it == 2 ? vb : kb + 16;
            }
            pv_issue(pb, vlast);
            const int row = wq * 16 + (lane >> 2);
            const uint32_t ml = sb + OFF_MISC;
            wg_wait<0>();
            pin(o); pin(pb); pin(sa); pin(sb2);
            rel(31);
            const float l0 = o[32], l1 = o[34];
            if (c4 == 0) { sts64f(ml + w * 512 + row * 8, n0, l0); sts64f(ml + w * 512 + row * 8 + 64, n1, l1); }
            TS(14);
            float mine[16];
#pragma unroll
            for (int j = 0; j < 4; j++) {
                if (w == 0) sts128f(H + j * 2048 + wt * 16, o[16 + 4 * j], o[17 + 4 * j], o[18 + 4 * j], o[19 + 4 * j]);
                else sts128f(H + 8192 + j * 2048 + wt * 16, o[4 * j], o[4 * j + 1], o[4 * j + 2], o[4 * j + 3]);
            }
#pragma unroll
            for (int i = 0; i < 16; i++) mine[i] = w == 0 ? o[i] : o[16 + i];
            bar_sync(10, 256);
            const float2 u0 = lds64f(ml + (w ^ 1) * 512 + row * 8), u1 = lds64f(ml + (w ^ 1) * 512 + row * 8 + 64);
            const float x0 = fminf(n0, u0.x), x1 = fminf(n1, u1.x);
            float a0 = ex2(x0 - n0), b0 = ex2(x0 - u0.x), a1 = ex2(x1 - n1), b1 = ex2(x1 - u1.x);
            const float i0 = __fdividef(1.f, fmaf(a0, l0, b0 * u0.y)), i1 = __fdividef(1.f, fmaf(a1, l1, b1 * u1.y));
            a0 *= i0; b0 *= i0; a1 *= i1; b1 *= i1;
            uint32_t pk[8];
#pragma unroll
            for (int j = 0; j < 4; j++) {
                const float4 v = lds128f(H + (w ^ 1) * 8192 + j * 2048 + wt * 16);
                pk[2 * j] = pack2(fmaf(a0, mine[4 * j], b0 * v.x), fmaf(a0, mine[4 * j + 1], b0 * v.y));
                pk[2 * j + 1] = pack2(fmaf(a1, mine[4 * j + 2], b1 * v.z), fmaf(a1, mine[4 * j + 3], b1 * v.w));
            }
            const uint32_t og = H + 16384 + wq * 2048;
            {
                const uint32_t ra = og + (((lane >> 3) & 1) * 8 + (lane & 7)) * 128;
                stsm4(ra + (((4 * w + (lane >> 4)) ^ (lane & 7)) << 4), pk[0], pk[1], pk[2], pk[3]);
                stsm4(ra + (((4 * w + 2 + (lane >> 4)) ^ (lane & 7)) << 4), pk[4], pk[5], pk[6], pk[7]);
            }
            __syncwarp();
            {
                const uint32_t off = (lane >> 2) * 128 + (((4 * w + c4) ^ (lane >> 2)) << 4);
                const uint4 v0 = lds128(og + off), v1 = lds128(og + off + 1024);
                unsigned char* dst = g_o + (size_t)(abh * PADROWS + 8 + qt * 64 + wq * 16) * 128 + off;
                stg128(dst, v0); stg128(dst + 1024, v1);
            }
            bar_arrive(6, 288);
            TS(15);
        }

        auto mm = [&](float (&d)[24], int n, uint32_t act, int acc) {
            const uint32_t z = p.zero * (ph + n);
            const uint64_t ad = mkdesc(rdesc + z + (n % NSLOT) * (SLOT >> 4)), bd = mkdesc(desc_lo(act) + z);
            wg_fence();
#pragma unroll
            for (int k = 0; k < 8; k++) mma_t(d, ad + k * 128, bd + (k >> 2) * (XCH >> 4) + (k & 3) * 2, k == 0 ? acc : 1);
            wg_commit();
        };
        const uint32_t xo = P + tile * XCH + wq * 1024, xt = P + tile * XCH + toff;
        uint32_t dwr[15];
        {
#pragma unroll
            for (int i = 0; i < 15; i++) dwr[i] = hmul2(__ldg(reinterpret_cast<const uint32_t*>(p.dw + i * 256 + tile * 64) + lane), 0x3F003F00u);
            float d[24];
            uint32_t xw[12];
            stsm4(xo + 1024 + foff, xr[0], xr[1], xr[2], xr[3]);
            stsm4(xo + 1024 + (foff ^ 64), xr[4], xr[5], xr[6], xr[7]);
            mbar_wait(bars + B_X1IN * 8, 0);
            if (wq == 0 || wq == 3) {
                uint4 h0 = make_uint4(0, 0, 0, 0), h1 = h0;
                const int np = wq ? pt + 1 : pt - 1;
                if (np >= 0 && np < 32) {
                    const uint4* hp = &g_halo[(((b * 32 + np) * 4 + tile) * 2 + (wq ? 0 : 1)) * 64 + lane];
                    h0 = __ldcg(hp); h1 = __ldcg(hp + 32);
                }
                stsm4(xo + (wq ? 2048 : 0) + foff, h0.x, h0.y, h0.z, h0.w);
                stsm4(xo + (wq ? 2048 : 0) + (foff ^ 64), h1.x, h1.y, h1.z, h1.w);
            }
            bar_sync(2 + w, 128);
#pragma unroll
            for (int j = 0; j < 3; j++) ldsm4t(xt + j * 2048, xw[4 * j], xw[4 * j + 1], xw[4 * j + 2], xw[4 * j + 3]);
            pin(xw);
            pin(dwr);
            acq(32); acq(33); acq(34); acq(35);
            mbar_wait(bars + B_OIN * 8, 0);
            TS(16);
            mm(d, 32, H, 0);
            mbar_wait(bars + B_OIN * 8 + 8, 0);
            mm(d, 33, H + 2 * XCH, 1);
            wg_wait<1>();
            rel(32);
            wg_wait<0>();
            pin(d);
#pragma unroll
            for (int i = 0; i < 12; i++) xw[i] = pack2(d[2 * i] + blo(xw[i]), d[2 * i + 1] + bhi(xw[i]));
            if (c4 == 0) { xw[0] = (xw[0] & 0xffff0000u) | 0x3F80u; xw[1] = (xw[1] & 0xffff0000u) | 0x3F80u; }
#pragma unroll
            for (int j = 0; j < 3; j++) stsm4t(xt + j * 2048, xw[4 * j], xw[4 * j + 1], xw[4 * j + 2], xw[4 * j + 3]);
            rel(33);
            publish(B_X2, P + tile * XCH, XCH, 384);
            TS(17);
        }
        {
            float da[24], db[24], st[24];
            bar_sync(5, 384);
            mm(da, 34, P + 2 * r * XCH, 0);
            mm(db, 35, P + 2 * r * XCH, 0);
            acq(36); acq(37);
            mbar_wait(bars + B_X2 * 8, 0);
            bar_sync(5, 384);
            TS(39);
            mm(da, 36, P + 2 * (r ^ 1) * XCH, 1);
            mm(db, 37, P + 2 * (r ^ 1) * XCH, 1);
            wg_wait<2>();
            rel(34); rel(35);
            mbar_wait(bars + B_ST * 8, 0);
#pragma unroll
            for (int j = 0; j < 6; j++) {
                const float4 u = lds128f(sb + OFF_STATS + (8 * j + 2 * c4) * 8);
                st[4 * j] = u.x; st[4 * j + 1] = u.y; st[4 * j + 2] = u.z; st[4 * j + 3] = u.w;
            }
            wg_wait<0>();
            pin(da); pin(db);
            rel(36); rel(37);
            TS(18);
            uint32_t pk[12];
#pragma unroll
            for (int hh = 0; hh < 2; hh++) {
                const float ca = __shfl_sync(~0u, da[2 * hh], lane & 28), cb = __shfl_sync(~0u, db[2 * hh], lane & 28);
#pragma unroll
                for (int j = 0; j < 6; j++) {
                    const float u0 = fmaf(-st[4 * j], ca, da[4 * j + 2 * hh] * st[4 * j + 1]);
                    const float u1 = fmaf(-st[4 * j + 2], ca, da[4 * j + 2 * hh + 1] * st[4 * j + 3]);
                    const float v0 = fmaf(-st[4 * j], cb, db[4 * j + 2 * hh] * st[4 * j + 1]);
                    const float v1 = fmaf(-st[4 * j + 2], cb, db[4 * j + 2 * hh + 1] * st[4 * j + 3]);
                    pk[2 * j + hh] = pack2(fmaf(u0, tanh_fast(v0), u0), fmaf(u1, tanh_fast(v1), u1));
                }
            }
            const uint32_t gs = H + 16384 + w * XCH;
#pragma unroll
            for (int j = 0; j < 3; j++) stsm4t(gs + toff + j * 2048, pk[4 * j], pk[4 * j + 1], pk[4 * j + 2], pk[4 * j + 3]);
            ldsm4(xo + 1024 + foff, xr[0], xr[1], xr[2], xr[3]);
            ldsm4(xo + 1024 + (foff ^ 64), xr[4], xr[5], xr[6], xr[7]);
            bar_sync(2 + w, 128);
            uint32_t ca[8], cb[8];
            const uint32_t grow = gs + 8 * wq * 128 + c4 * 4, srow = H + tile * HCH + 8 * wq * 128 + c4 * 4;
#pragma unroll
            for (int k = 0; k < 22; k++) {
                const uint32_t v = lds32(grow + (1 + k) * 128 + (((lane >> 2) ^ ((1 + k) & 7)) << 4));
#pragma unroll
                for (int i = 0; i < 8; i++) {
                    const int tap = k - i;
                    if (tap == 0) ca[i] = hmul2(v, dwr[0]);
                    else if (tap > 0 && tap < 8) ca[i] = hfma2(v, dwr[tap], ca[i]);
                    else if (tap == 8) cb[i] = hmul2(v, dwr[8]);
                    else if (tap > 8 && tap < 15) cb[i] = hfma2(v, dwr[tap], cb[i]);
                }
            }
#pragma unroll
            for (int i = 0; i < 8; i++) {
                const float h0 = blo(ca[i]) + blo(cb[i]), h1 = bhi(ca[i]) + bhi(cb[i]);
                sts32(srow + i * 128 + (((lane >> 2) ^ i) << 4), pack2(fmaf(h0, tanh_fast(h0), h0), fmaf(h1, tanh_fast(h1), h1)));
            }
            acq(38); acq(39);
            publish(B_SR, H + tile * HCH, HCH, 256);
            TS(19);
        }
        {
            auto frags = [&](int i, int half) {
                const uint32_t src = H + 2 * half * HCH + wq * 1024;
#pragma unroll
                for (int k = 0; k < 4; k++) ldsm4(src + (k >> 1) * HCH + (foff ^ ((k & 1) * 64)), a[i + 4 * k], a[i + 4 * k + 1], a[i + 4 * k + 2], a[i + 4 * k + 3]);
            };
            frags(0, r);
            sp(d0, 38, a, 0, 0);
            mbar_wait(bars + B_SR * 8, 0);
            frags(16, r ^ 1);
            sp(d0, 39, a + 16, 0, 1);
            wg_wait<1>();
            rel(38);
            wg_wait<0>();
            pin(d0);
            rel(39);
#pragma unroll
            for (int j = 0; j < 8; j++) {
                v[2 * j] = d0[4 * j] + d0[4 * j + 2] + blo(xr[j]);
                v[2 * j + 1] = d0[4 * j + 1] + d0[4 * j + 3] + bhi(xr[j]);
            }
            TS(20);
        }
    }

    cluster_arrive();
    TS(24);
    {
        const float nb = -mean * rstd;
#pragma unroll
        for (int j = 0; j < 8; j++) xr[j] = pack2(fmaf(v[2 * j], rstd, nb), fmaf(v[2 * j + 1], rstd, nb));
        const uint32_t stg = P + 16384 + warp * 1024;
        stsm4(stg + foff, xr[0], xr[1], xr[2], xr[3]);
        stsm4(stg + (foff ^ 64), xr[4], xr[5], xr[6], xr[7]);
        __syncwarp();
        const uint32_t src = stg + (lane >> 3) * 128 + (((lane & 7) ^ (lane >> 3)) << 4);
        const uint4 u0 = lds128(src), u1 = lds128((src + 512) ^ 64);
        __nv_bfloat16* dst = p.out + (size_t)(b * T_ + trow + (lane >> 3)) * 256 + tile * 64 + (lane & 7) * 8;
        if (trow < T_) { stg128(dst, u0); stg128(dst + 4 * 256, u1); }
    }
    TS(25);
    TG(31);
    TSDUMP();
    cluster_wait();
}

typedef CUresult (*EncodeFn)(CUtensorMap*, CUtensorMapDataType, cuuint32_t, void*, const cuuint64_t*, const cuuint64_t*,
                             const cuuint32_t*, const cuuint32_t*, CUtensorMapInterleave, CUtensorMapSwizzle,
                             CUtensorMapL2promotion, CUtensorMapFloatOOBfill);

}

extern "C" void kernel_launch(void* const* d_in, const int* in_sizes, int n_in, void* d_out, int out_size) {
    static EncodeFn encode = nullptr;
    if (!encode) {
        void* fn = nullptr;
        cudaDriverEntryPointQueryResult qr;
        cudaGetDriverEntryPoint("cuTensorMapEncodeTiled", &fn, cudaEnableDefault, &qr);
        encode = (EncodeFn)fn;
        cudaFuncSetAttribute(conformer_kernel, cudaFuncAttributeMaxDynamicSharedMemorySize, SMEM_LAUNCH);
    }
    Params p;
    const cuuint32_t ones[5] = {1, 1, 1, 1, 1};
    const int idx[8] = {1, 2, 3, 4, 5, 7, 8, 9};
    const int rows[8] = {256, 1024, 256, 256, 256, 256, 256, 1024};
    const int cols[8] = {1024, 256, 768, 256, 512, 256, 1024, 256};
    for (int i = 0; i < 8; i++) {
        const bool perm = i != 3 && i != 4;
        const cuuint64_t pitch = (cuuint64_t)cols[i] * 2;
        const cuuint64_t dims[5] = {(cuuint64_t)cols[i], 2, 2, 4, (cuuint64_t)rows[i] / 16};
        const cuuint64_t strides[4] = {pitch, pitch * (perm ? 8 : 2), pitch * (perm ? 2 : 4), pitch * 16};
        const cuuint32_t box[5] = {64, 2, 2, 4, 8};
        encode(&p.tm[i], CU_TENSOR_MAP_DATA_TYPE_BFLOAT16, 5, d_in[idx[i]], dims, strides, box, ones, CU_TENSOR_MAP_INTERLEAVE_NONE,
               CU_TENSOR_MAP_SWIZZLE_128B, CU_TENSOR_MAP_L2_PROMOTION_L2_128B, CU_TENSOR_MAP_FLOAT_OOB_FILL_NONE);
        p.w[i] = (const char*)d_in[idx[i]];
    }
    {
        void* kv = nullptr;
        cudaGetSymbolAddress(&kv, g_kvq);
        const cuuint64_t dims[2] = {64, 16384};
        const cuuint64_t strides[1] = {128};
        const cuuint32_t box[2] = {64, 128};
        encode(&p.tm[8], CU_TENSOR_MAP_DATA_TYPE_BFLOAT16, 2, kv, dims, strides, box, ones, CU_TENSOR_MAP_INTERLEAVE_NONE,
               CU_TENSOR_MAP_SWIZZLE_NONE, CU_TENSOR_MAP_L2_PROMOTION_L2_128B, CU_TENSOR_MAP_FLOAT_OOB_FILL_NONE);
    }
    p.x = (const __nv_bfloat16*)d_in[0];
    p.dw = (const __nv_bfloat16*)d_in[6];
    p.out = (__nv_bfloat16*)d_out;
    p.zero = 0;
    conformer_kernel<<<NCTA, NTHREADS, SMEM_LAUNCH>>>(p);
}
```

```cpp
#include <cuda_runtime.h>
#include <cuda_bf16.h>
#include <cuda.h>
#include <stdint.h>

namespace {

constexpr int T_ = 1000;
constexpr int NCTA = 128;
constexpr int NTHREADS = 512;
constexpr int NSLOT = 5;
constexpr int SLOT = 16384;
constexpr int NLOADS = 56;

constexpr uint32_t OFF_RING = 0;
constexpr uint32_t OFF_P = 163840;
constexpr uint32_t OFF_H = 188416;
constexpr uint32_t OFF_MISC = 221184;
constexpr uint32_t OFF_STATS = 229376;
constexpr uint32_t OFF_BARS = 229888;
constexpr uint32_t SMEM_BYTES = 230400;
constexpr uint32_t XCH = 6144;
constexpr uint32_t HCH = 4096;

constexpr int B_FULL = 0, B_EMPTY = 10, B_XA = 20  , B_XB = 24  , B_INB = 27  , B_X2 = 31, B_SR = 32, B_OIN = 33  ,
              B_QIN = 35, B_X1IN = 36, B_RDY = 37  , B_SINK = 43, B_ST = 44;

#define TURN 2
constexpr int PADROWS = 1040;
constexpr int FS = 8;

struct Params {
    CUtensorMap tm[9];
    const char* w[8];
    const __nv_bfloat16* x;
    const __nv_bfloat16* dw;
    __nv_bfloat16* out;
    uint32_t zero;
};

__device__ __align__(1024) unsigned char g_kvq[3 * 8 * 1024 * 128];
__device__ __align__(1024) unsigned char g_o[8 * PADROWS * 128];
__device__ uint4 g_halo[64 * 4 * 2 * 64];
__device__ uint32_t g_flag_kv[8 * 32 * FS];
__device__ uint32_t g_flag_q[8 * 32 * FS];
__device__ uint32_t g_flag_o[2 * 16 * 4 * FS];
__device__ uint32_t g_epoch[NCTA * FS];

#define TS(i) do { } while (0)
#define TSW(i) do { } while (0)
#define TG(i) do { } while (0)
#define TSINIT() do { } while (0)
#define TSDUMP() do { } while (0)
constexpr uint32_t SMEM_LAUNCH = SMEM_BYTES;

__device__ __forceinline__ uint32_t smem_u32(const void* p) { return (uint32_t)__cvta_generic_to_shared(p); }
__device__ __forceinline__ void mbar_init(uint32_t b, uint32_t c) { asm volatile("mbarrier.init.shared::cta.b64 [%0], %1;" ::"r"(b), "r"(c) : "memory"); }
__device__ __forceinline__ void mbar_arrive(uint32_t b) { asm volatile("mbarrier.arrive.shared::cta.b64 _, [%0];" ::"r"(b) : "memory"); }
__device__ __forceinline__ void mbar_arrive_tx(uint32_t b, uint32_t tx) { asm volatile("mbarrier.arrive.expect_tx.shared::cta.b64 _, [%0], %1;" ::"r"(b), "r"(tx) : "memory"); }
__device__ __forceinline__ void mbar_wait(uint32_t b, uint32_t ph) {
    asm volatile("{\n.reg .pred p, q;\n.reg .u32 c;\nmov.u32 c, 0;\n"
                 "MW_LOOP:\n.pragma \"nounroll\";\n"
                 "mbarrier.try_wait.parity.shared::cta.b64 p, [%0], %1;\n"
                 "add.u32 c, c, 1;\nsetp.lt.u32 q, c, 65536;\nnot.pred p, p;\nand.pred p, p, q;\n@p bra MW_LOOP;\n}"
                 ::"r"(b), "r"(ph) : "memory");
}
__device__ __forceinline__ bool mbar_test(uint32_t b, uint32_t ph) {
    uint32_t ok;
    asm volatile("{\n.reg .pred p;\nmbarrier.test_wait.parity.shared::cta.b64 p, [%1], %2;\nselp.u32 %0, 1, 0, p;\n}" : "=r"(ok) : "r"(b), "r"(ph) : "memory");
    return ok;
}
__device__ __forceinline__ uint32_t mapa(uint32_t a, uint32_t r) { uint32_t o; asm("mapa.shared::cluster.u32 %0, %1, %2;" : "=r"(o) : "r"(a), "r"(r)); return o; }
__device__ __forceinline__ void fence_async_smem() { asm volatile("fence.proxy.async.shared::cta;" ::: "memory"); }
__device__ __forceinline__ void fence_async_global() { asm volatile("fence.proxy.async.global;" ::: "memory"); }
__device__ __forceinline__ void bar_sync(int id, int n) { asm volatile("bar.sync %0, %1;" ::"r"(id), "r"(n) : "memory"); }
__device__ __forceinline__ void bar_arrive(int id, int n) { asm volatile("bar.arrive %0, %1;" ::"r"(id), "r"(n) : "memory"); }
__device__ __forceinline__ void cluster_arrive() { asm volatile("barrier.cluster.arrive.relaxed.aligned;" ::: "memory"); }
__device__ __forceinline__ void cluster_wait() { asm volatile("barrier.cluster.wait.aligned;" ::: "memory"); }

__device__ __forceinline__ void ring_load(uint32_t dst, const CUtensorMap* tm, int col, int row16, uint32_t bar) {
    asm volatile("{\n.reg .pred p;\nelect.sync _|p, 0xffffffff;\n"
                 "@p mbarrier.arrive.expect_tx.shared::cta.b64 _, [%2], 16384;\n"
                 "@p cp.async.bulk.tensor.5d.shared::cluster.global.mbarrier::complete_tx::bytes [%0], [%1, {%3, 0, 0, 0, %4}], [%2];\n}"
                 ::"r"(dst), "l"(tm), "r"(bar), "r"(col), "r"(row16) : "memory");
}
__device__ __forceinline__ void ring_load_both(uint32_t dst, const CUtensorMap* tm, int c1, uint32_t bar) {
    asm volatile("{\n.reg .pred p;\nelect.sync _|p, 0xffffffff;\n"
                 "@p cp.async.bulk.tensor.2d.shared::cluster.global.mbarrier::complete_tx::bytes.multicast::cluster [%0], [%1, {0, %3}], [%2], %4;\n}"
                 ::"r"(dst), "l"(tm), "r"(bar), "r"(c1), "h"((uint16_t)3) : "memory");
}
__device__ __forceinline__ void mbar_arrive_peer(uint32_t b) { asm volatile("mbarrier.arrive.relaxed.cluster.shared::cluster.b64 _, [%0];" ::"r"(b) : "memory"); }
__device__ __forceinline__ void bulk_g2s(uint32_t dst, const void* src, uint32_t bytes, uint32_t bar) {
    asm volatile("cp.async.bulk.shared::cluster.global.mbarrier::complete_tx::bytes [%0], [%1], %2, [%3];" ::"r"(dst), "l"(src), "r"(bytes), "r"(bar) : "memory");
}
__device__ __forceinline__ void prefetch_l2(const void* src, uint32_t bytes) {
    asm volatile("cp.async.bulk.prefetch.L2.global [%0], %1;" ::"l"(src), "r"(bytes) : "memory");
}
__device__ __forceinline__ void peer_copy(uint32_t dst, uint32_t src, uint32_t bytes, uint32_t rbar) {
    asm volatile("{\n.reg .pred p;\nelect.sync _|p, 0xffffffff;\n"
                 "@p cp.async.bulk.shared::cluster.shared::cta.mbarrier::complete_tx::bytes [%0], [%1], %2, [%3];\n}"
                 ::"r"(dst), "r"(src), "r"(bytes), "r"(rbar) : "memory");
}
__device__ __forceinline__ void st_async4(uint32_t dst, uint32_t a, uint32_t b, uint32_t c, uint32_t d, uint32_t bar) {
    asm volatile("st.async.shared::cluster.mbarrier::complete_tx::bytes.v4.b32 [%0], {%1,%2,%3,%4}, [%5];" ::"r"(dst), "r"(a), "r"(b), "r"(c), "r"(d), "r"(bar) : "memory");
}
__device__ __forceinline__ void st_async2f(uint32_t dst, float a, float b, uint32_t bar) {
    asm volatile("st.async.shared::cluster.mbarrier::complete_tx::bytes.v2.f32 [%0], {%1,%2}, [%3];" ::"r"(dst), "f"(a), "f"(b), "r"(bar) : "memory");
}
__device__ __forceinline__ void stsm4t(uint32_t a, uint32_t r0, uint32_t r1, uint32_t r2, uint32_t r3) {
    asm volatile("stmatrix.sync.aligned.m8n8.x4.trans.shared.b16 [%0], {%1,%2,%3,%4};" ::"r"(a), "r"(r0), "r"(r1), "r"(r2), "r"(r3) : "memory");
}
__device__ __forceinline__ void stsm4(uint32_t a, uint32_t r0, uint32_t r1, uint32_t r2, uint32_t r3) {
    asm volatile("stmatrix.sync.aligned.m8n8.x4.shared.b16 [%0], {%1,%2,%3,%4};" ::"r"(a), "r"(r0), "r"(r1), "r"(r2), "r"(r3) : "memory");
}
__device__ __forceinline__ void ldsm4t(uint32_t a, uint32_t& r0, uint32_t& r1, uint32_t& r2, uint32_t& r3) {
    asm volatile("ldmatrix.sync.aligned.m8n8.x4.trans.shared.b16 {%0,%1,%2,%3}, [%4];" : "=r"(r0), "=r"(r1), "=r"(r2), "=r"(r3) : "r"(a) : "memory");
}
__device__ __forceinline__ void ldsm4(uint32_t a, uint32_t& r0, uint32_t& r1, uint32_t& r2, uint32_t& r3) {
    asm volatile("ldmatrix.sync.aligned.m8n8.x4.shared.b16 {%0,%1,%2,%3}, [%4];" : "=r"(r0), "=r"(r1), "=r"(r2), "=r"(r3) : "r"(a) : "memory");
}
__device__ __forceinline__ uint4 lds128(uint32_t a) { uint4 v; asm volatile("ld.shared.v4.b32 {%0,%1,%2,%3}, [%4];" : "=r"(v.x), "=r"(v.y), "=r"(v.z), "=r"(v.w) : "r"(a) : "memory"); return v; }
__device__ __forceinline__ float4 lds128f(uint32_t a) { float4 v; asm volatile("ld.shared.v4.f32 {%0,%1,%2,%3}, [%4];" : "=f"(v.x), "=f"(v.y), "=f"(v.z), "=f"(v.w) : "r"(a) : "memory"); return v; }
__device__ __forceinline__ float2 lds64f(uint32_t a) { float2 v; asm volatile("ld.shared.v2.f32 {%0,%1}, [%2];" : "=f"(v.x), "=f"(v.y) : "r"(a) : "memory"); return v; }
__device__ __forceinline__ uint32_t lds32(uint32_t a) { uint32_t v; asm volatile("ld.shared.b32 %0, [%1];" : "=r"(v) : "r"(a) : "memory"); return v; }
__device__ __forceinline__ void sts128(uint32_t a, uint32_t x, uint32_t y, uint32_t z, uint32_t w) { asm volatile("st.shared.v4.b32 [%0], {%1,%2,%3,%4};" ::"r"(a), "r"(x), "r"(y), "r"(z), "r"(w) : "memory"); }
__device__ __forceinline__ void sts128f(uint32_t a, float x, float y, float z, float w) { asm volatile("st.shared.v4.f32 [%0], {%1,%2,%3,%4};" ::"r"(a), "f"(x), "f"(y), "f"(z), "f"(w) : "memory"); }
__device__ __forceinline__ void sts64f(uint32_t a, float x, float y) { asm volatile("st.shared.v2.f32 [%0], {%1,%2};" ::"r"(a), "f"(x), "f"(y) : "memory"); }
__device__ __forceinline__ void sts32(uint32_t a, uint32_t x) { asm volatile("st.shared.b32 [%0], %1;" ::"r"(a), "r"(x) : "memory"); }
__device__ __forceinline__ void stg128(void* p, uint4 v) { asm volatile("st.global.v4.b32 [%0], {%1,%2,%3,%4};" ::"l"(p), "r"(v.x), "r"(v.y), "r"(v.z), "r"(v.w) : "memory"); }

__device__ __forceinline__ uint32_t pack2(float lo, float hi) { uint32_t r; asm("cvt.rn.bf16x2.f32 %0, %1, %2;" : "=r"(r) : "f"(hi), "f"(lo)); return r; }
__device__ __forceinline__ float blo(uint32_t v) { return __uint_as_float(v << 16); }
__device__ __forceinline__ float bhi(uint32_t v) { return __uint_as_float(v & 0xffff0000u); }
__device__ __forceinline__ uint32_t hmul2(uint32_t a, uint32_t b) { uint32_t r; asm("mul.rn.bf16x2 %0, %1, %2;" : "=r"(r) : "r"(a), "r"(b)); return r; }
__device__ __forceinline__ uint32_t hsub2(uint32_t a, uint32_t b) { uint32_t r; asm("sub.rn.bf16x2 %0, %1, %2;" : "=r"(r) : "r"(a), "r"(b)); return r; }
__device__ __forceinline__ uint32_t hfma2(uint32_t a, uint32_t b, uint32_t c) { uint32_t r; asm("fma.rn.bf16x2 %0, %1, %2, %3;" : "=r"(r) : "r"(a), "r"(b), "r"(c)); return r; }
__device__ __forceinline__ float tanh_fast(float x) { float r; asm("tanh.approx.f32 %0, %1;" : "=f"(r) : "f"(x)); return r; }
__device__ __forceinline__ float rsq(float x) { float r; asm("rsqrt.approx.ftz.f32 %0, %1;" : "=f"(r) : "f"(x)); return r; }
__device__ __forceinline__ float ex2(float x) { float r; asm("ex2.approx.ftz.f32 %0, %1;" : "=f"(r) : "f"(x)); return r; }

__device__ __forceinline__ void flag_wait(const uint32_t* p, uint32_t e) {
#pragma unroll 1
    for (int i = 0; i < (1 << 20); i++) {
        uint32_t v;
        asm volatile("ld.acquire.gpu.global.u32 %0, [%1];" : "=r"(v) : "l"(p) : "memory");
        if (v == e) break;
    }
}
__device__ __forceinline__ uint32_t ld_epoch() {
    uint32_t v;
    asm volatile("ld.relaxed.gpu.global.u32 %0, [%1];" : "=r"(v) : "l"(&g_epoch[blockIdx.x * FS]) : "memory");
    return v + 1;
}
__device__ __forceinline__ void flag_set(uint32_t* p, uint32_t e) { asm volatile("st.release.gpu.global.u32 [%0], %1;" ::"l"(p), "r"(e) : "memory"); }

__device__ __forceinline__ uint32_t desc_lo(uint32_t addr) { return ((addr & 0x3FFFF) >> 4) | 0x10000u; }
__device__ __forceinline__ uint64_t mkdesc(uint32_t lo) { return (uint64_t)lo | (0x40000040ull << 32); }
__device__ __forceinline__ void wg_fence() { asm volatile("wgmma.fence.sync.aligned;" ::: "memory"); }
__device__ __forceinline__ void wg_commit() { asm volatile("wgmma.commit_group.sync.aligned;" ::: "memory"); }
template <int N> __device__ __forceinline__ void wg_wait() { asm volatile("wgmma.wait_group.sync.aligned %0;" ::"n"(N) : "memory"); }
template <int N> __device__ __forceinline__ void pin(float (&d)[N]) {
#pragma unroll
    for (int i = 0; i < N; i++) asm volatile("" : "+f"(d[i])::"memory");
}
template <int N> __device__ __forceinline__ void pin(uint32_t (&d)[N]) {
#pragma unroll
    for (int i = 0; i < N; i++) asm volatile("" : "+r"(d[i])::"memory");
}

template <typename Tp, int N> __device__ __forceinline__ void zero(Tp (&d)[N]) {
#pragma unroll
    for (int i = 0; i < N; i++) d[i] = 0;
    pin(d);
}

#define F4(d, i) "+f"(d[i]), "+f"(d[i + 1]), "+f"(d[i + 2]), "+f"(d[i + 3])
#define F16(d, i) F4(d, i), F4(d, i + 4), F4(d, i + 8), F4(d, i + 12)

__device__ __forceinline__ void mma_sp(float (&d)[32], const uint32_t* a, uint64_t b, uint32_t meta, int acc) {
    asm volatile("{.reg .pred p; setp.ne.b32 p, %38, 0;\n"
                 "wgmma.mma_async.sp.sync.aligned.m64n64k32.f32.bf16.bf16 {%0,%1,%2,%3,%4,%5,%6,%7,%8,%9,%10,%11,%12,%13,%14,%15,%16,%17,%18,%19,%20,%21,%22,%23,%24,%25,%26,%27,%28,%29,%30,%31}, "
                 "{%32,%33,%34,%35}, %36, %37, 0, p, 1, 1, 1;}\n"
                 : F16(d, 0), F16(d, 16) : "r"(a[0]), "r"(a[1]), "r"(a[2]), "r"(a[3]), "l"(b), "r"(meta), "r"(acc));
}
__device__ __forceinline__ void mma_t(float (&d)[24], uint64_t a, uint64_t b, int acc) {
    asm volatile("{.reg .pred p; setp.ne.b32 p, %26, 0;\n"
                 "wgmma.mma_async.sync.aligned.m64n48k16.f32.bf16.bf16 {%0,%1,%2,%3,%4,%5,%6,%7,%8,%9,%10,%11,%12,%13,%14,%15,%16,%17,%18,%19,%20,%21,%22,%23}, %24, %25, p, 1, 1, 1, 0;}\n"
                 : F16(d, 0), F4(d, 16), F4(d, 20) : "l"(a), "l"(b), "r"(acc));
}
__device__ __forceinline__ void mma_qk(float (&d)[32], uint32_t a0, uint32_t a1, uint32_t a2, uint32_t a3, uint64_t b, int acc) {
    asm volatile("{.reg .pred p; setp.ne.b32 p, %37, 0;\n"
                 "wgmma.mma_async.sync.aligned.m64n64k16.f32.bf16.bf16 {%0,%1,%2,%3,%4,%5,%6,%7,%8,%9,%10,%11,%12,%13,%14,%15,%16,%17,%18,%19,%20,%21,%22,%23,%24,%25,%26,%27,%28,%29,%30,%31}, "
                 "{%32,%33,%34,%35}, %36, p, 1, 1, 0;}\n"
                 : F16(d, 0), F16(d, 16) : "r"(a0), "r"(a1), "r"(a2), "r"(a3), "l"(b), "r"(acc));
}
__device__ __forceinline__ void mma_pv(float (&d)[36], uint32_t a0, uint32_t a1, uint32_t a2, uint32_t a3, uint64_t b) {
    asm volatile("wgmma.mma_async.sync.aligned.m64n72k16.f32.bf16.bf16 {%0,%1,%2,%3,%4,%5,%6,%7,%8,%9,%10,%11,%12,%13,%14,%15,%16,%17,%18,%19,%20,%21,%22,%23,%24,%25,%26,%27,%28,%29,%30,%31,%32,%33,%34,%35}, "
                 "{%36,%37,%38,%39}, %40, 1, 1, 1, 1;\n"
                 : F16(d, 0), F16(d, 16), F4(d, 32) : "r"(a0), "r"(a1), "r"(a2), "r"(a3), "l"(b));
}

__device__ __forceinline__ uint32_t load_code(int n, int r, int w) {
    const int tile = 2 * r + w;
    int m, col, row;
    if (n < 16 || n >= 40) {
        const int k = n < 16 ? n : n - 40;
        m = n < 16 ? 0 : 6;
        if (k < 8) { col = 4 * tile + (k >> 1); row = (k & 1) ^ r; }
        else if (k < 12) { m++; col = tile ^ (3 - (k & 1)); row = 2 * tile + ((k >> 1) & 1); }
        else { m++; col = tile ^ (k < 14); row = 2 * tile + (k & 1); }
    } else if (n < 32) {
        const int k = n - 16;
        m = 2;
        if (k < 4) { col = tile + ((k & 1) ? 8 : 4); row = (k >> 1) ^ r; }
        else { col = tile; row = (k & 1) ^ r; }
    } else if (n < 34) { m = 3; col = tile; row = n - 32; }
    else if (n < 38) { const int k = n - 34; m = 4; col = tile + 4 * (k & 1); row = (k >> 1) ^ r; }
    else { m = 5; col = tile; row = (n & 1) ^ r; }
    return m | (col << 4) | (row << 8);
}

__global__ void __cluster_dims__(2, 1, 1) __launch_bounds__(NTHREADS, 1)
conformer_kernel(const __grid_constant__ Params p) {
    extern __shared__ __align__(1024) unsigned char smem_raw[];
    const uint32_t sb = smem_u32(smem_raw);
    const uint32_t bars = sb + OFF_BARS;
    const int tid = threadIdx.x;
    const int lane = tid & 31;
    const int warp = __shfl_sync(~0u, tid >> 5, 0);
    const int r = blockIdx.x & 1;
    const int pair = blockIdx.x >> 1;
    const int b = pair >> 5, pt = pair & 31;
    const int ah = pt >> 3, qt = (pt & 7) * 2 + r;
    const int abh = b * 4 + ah;

    TG(30);
    TSINIT();
    TS(0);
    const uint32_t P = sb + OFF_P, H = sb + OFF_H;

    if (warp >= 8) {
        asm volatile("setmaxnreg.dec.sync.aligned.u32 48;");
        if (warp >= 12) {
            cluster_arrive();
            cluster_wait();
            if (warp == 12) {
                const uint32_t epoch = ld_epoch();
                bar_sync(11, 288);
                if (lane < 2) flag_set(&g_flag_q[((b * 4 + 2 * r + lane) * 32 + pt) * FS], epoch);
                __syncwarp();
                TS(13);
            }
            const int ut = tid & 127;
            const uint32_t a8 = P + (ut >> 3) * 128 + (ut & 7) * 16;
            float s[3] = {0.f, 0.f, 0.f}, q[3] = {0.f, 0.f, 0.f};
#pragma unroll 1
            for (int h = 0; h < 2; h++) {
                if (h == 0) bar_sync(1, 384);
                else mbar_wait(bars + B_X2 * 8, 0);
                uint4 v[6];
#pragma unroll
                for (int i = 0; i < 6; i++) v[i] = lds128(a8 + (2 * (r ^ h) + (i & 1)) * XCH + (i >> 1) * 2048);
                bar_arrive(5 + ((v[0].w | v[1].w | v[2].w | v[3].w | v[4].w | v[5].w) & p.zero), 384);
                uint32_t t;
                asm volatile("mov.u32 %0, %%clock;" : "=r"(t)::"memory");
                const uint32_t mul = 65536u + (t & p.zero), msk = 0u - mul;
#pragma unroll
                for (int i = 0; i < 6; i++) {
                    const float a0 = __uint_as_float(v[i].x * mul), a1 = __uint_as_float(v[i].x & msk), a2 = __uint_as_float(v[i].y * mul), a3 = __uint_as_float(v[i].y & msk);
                    const float a4 = __uint_as_float(v[i].z * mul), a5 = __uint_as_float(v[i].z & msk), a6 = __uint_as_float(v[i].w * mul), a7 = __uint_as_float(v[i].w & msk);
                    s[i >> 1] += ((a0 + a1) + (a2 + a3)) + ((a4 + a5) + (a6 + a7));
                    q[i >> 1] += fmaf(a0, a0, fmaf(a1, a1, fmaf(a2, a2, a3 * a3))) + fmaf(a4, a4, fmaf(a5, a5, fmaf(a6, a6, a7 * a7)));
                }
            }
#pragma unroll
            for (int o = 1; o < 8; o <<= 1) {
#pragma unroll
                for (int i = 0; i < 3; i++) { s[i] += __shfl_xor_sync(~0u, s[i], o); q[i] += __shfl_xor_sync(~0u, q[i], o); }
            }
            const int k = ut & 7, row = (ut >> 3) + 16 * k;
            const float mean = (k == 0 ? s[0] : (k == 1 ? s[1] : s[2])) * (1.f / 256.f);
            const float msq = (k == 0 ? q[0] : (k == 1 ? q[1] : q[2])) * (1.f / 256.f);
            const float alpha = (uint32_t)(pt * 32 - 8 + row) >= T_ ? 0.f : 0.5f;
            const float rstd = alpha * rsq(fmaxf(fmaf(-mean, mean, msq), 0.f) + 1e-5f);
            if (k < 3) sts64f(sb + OFF_STATS + row * 8, mean * rstd, rstd);
            __syncwarp();
            if (lane == 0) mbar_arrive(bars + B_ST * 8);
            TS(4);
        } else if (warp < 10) {
            const int w = warp - 8;
            const uint32_t ring = sb + OFF_RING + w * NSLOT * SLOT;
            const uint32_t full = bars + (B_FULL + w * NSLOT) * 8;
            if (lane == 0) {
#pragma unroll
                for (int i = 0; i < NSLOT; i++) { mbar_init(full + i * 8, 1); mbar_init(full + (B_EMPTY - B_FULL + i) * 8, 4); }
                asm volatile("fence.mbarrier_init.release.cluster;" ::: "memory");
                fence_async_smem();
            }
            __syncwarp();
            cluster_arrive();
            TS(1);
#pragma unroll
            for (int n = 0; n < NSLOT; n++)
                ring_load(ring + n * SLOT, &p.tm[0], 64 * (8 * r + 4 * w + (n >> 1)), 8 * ((n & 1) ^ r), full + n * 8);
            TS(2);
            const uint32_t code = load_code(lane, r, w) | (load_code(lane + 32, r, w) << 16);
            cluster_wait();
            uint32_t s = 0, ph = 0;
            int n = NSLOT;
#pragma unroll 1
            for (int seg = 0; seg < 2; seg++) {
#pragma unroll 1
                for (; n < (seg == 0 ? 22 : NLOADS); n++) {
                    const uint32_t c = __shfl_sync(~0u, code, n) >> (n & 32 ? 16 : 0);
                    const CUtensorMap* tm = &p.tm[c & 15];
                    const uint32_t col = (c & 0xf0) * 4, row = (c & 0xff00) >> 5, dst = ring + s * SLOT;
                    mbar_wait(full + (B_EMPTY - B_FULL) * 8 + s * 8, ph + (((uint32_t)(size_t)tm | col | row | dst) & p.zero));
                    ring_load(dst, tm, col, row, full + s * 8);
                    if (++s == NSLOT) { s = 0; ph ^= 1; }
                }
                if (seg == 1) break;
                const uint32_t epoch = ld_epoch();
                const uint32_t rdy = bars + (B_RDY + 3 * w) * 8, prdy = mapa(rdy, r ^ 1);
                const int isv = r ^ w;
#pragma unroll 1
                for (; n < 32; n++) {
                    mbar_wait(full + (B_EMPTY - B_FULL) * 8 + s * 8, ph);
                    if (lane == 0) {
                        if (n < 24) mbar_arrive(full + s * 8);
                        else mbar_arrive_tx(full + s * 8, SLOT);
                    }
                    if (n == 28) {
                        if (lane == 0) mbar_arrive_peer(prdy);
                        mbar_wait(rdy, 0);
                        if (!isv) {
                            flag_wait(g_flag_kv + (abh * 32 + lane) * FS, epoch);
                            __syncwarp();
                            fence_async_global();
                            TSW(5);
                            ring_load_both(ring + 4 * SLOT, &p.tm[8], (abh * 8 + w) * 128, full + 32);
                        }
                        bar_sync(12, 64);
#pragma unroll
                        for (int i = 0; i < 2; i++) {
                            if (i == 0) mbar_wait(bars + B_QIN * 8, 0);
                            else mbar_wait(full + isv * 8, 1);
                            ring_load_both(ring + (2 * i + isv) * SLOT, &p.tm[8], (isv * 62 + abh * 8 + 2 * i + 2 + w) * 128, full + (2 * i + isv) * 8);
                        }
                    } else if (n > 28) {
                        const uint32_t bo = n == 31 ? 16 : 8;
                        if ((n > 29) == (isv == 1)) {
                            mbar_wait(rdy + bo, 0);
                            ring_load_both(ring + s * SLOT, &p.tm[8], (isv * 64 + abh * 8 + (n == 30 ? 4 : 6) + w) * 128, full + s * 8);
                        } else if (lane == 0) mbar_arrive_peer(prdy + bo);
                    }
                    __syncwarp();
                    if (++s == NSLOT) { s = 0; ph ^= 1; }
                }
            }
        } else if (warp == 10) {
            if (lane == 0) {
#pragma unroll
                for (int i = B_XA; i <= B_ST; i++) mbar_init(bars + i * 8, i == B_ST ? 4 : 1);
#pragma unroll
                for (int i = B_XA; i <= B_QIN; i++)
                    mbar_arrive_tx(bars + i * 8, i < B_XB ? 512 : ((i < B_X2 || i == B_SR || i == B_QIN) ? 8192 : 12288));
                asm volatile("fence.mbarrier_init.release.cluster;" ::: "memory");
                fence_async_smem();
            }
            __syncwarp();
            cluster_arrive();
            cluster_wait();
            const uint32_t epoch = ld_epoch();
            if (lane < 2) flag_wait(&g_flag_q[(abh * 32 + 2 * qt + lane) * FS], epoch);
            __syncwarp();
            TSW(6);
            if (lane == 0) {
                fence_async_global();
                bulk_g2s(H + 24576, g_kvq + 2097152 + (size_t)(abh * 1024 + qt * 64) * 128, 8192, bars + B_QIN * 8);
            }
            if (lane < 2) {
                const int np = pt - 1 + 2 * lane;
                if (np >= 0 && np < 32) flag_wait(&g_flag_kv[((b * 4 + 2 * r) * 32 + np) * FS], epoch);
            }
            __syncwarp();
            if (lane == 0) mbar_arrive(bars + B_X1IN * 8);
            bar_sync(9, 64);
            if (lane < 8) {
                const int q = (pt >> 1) + (lane < 4 ? 0 : ((pt & 1) ? 1 : -1));
                if (q >= 0 && q < 16) flag_wait(&g_flag_o[((b * 16 + q) * 4 + (lane & 3)) * FS], epoch);
            }
            __syncwarp();
            TSW(10);
            if (lane == 0) {
                fence_async_global();
#pragma unroll
                for (int i = 0; i < 4; i++)
                    bulk_g2s(H + i * XCH, g_o + (size_t)((b * 4 + i) * PADROWS + pt * 32) * 128, XCH, bars + (B_OIN + (i >> 1)) * 8);
            }
            __syncwarp();
        } else {
            const uint32_t kb = (lane < 2 || lane > 5) ? 4096 : (lane == 2 ? 3072 : (lane == 4 ? 2048 : 1024));
            const char* pf = p.w[lane & 7] + blockIdx.x * kb;
            cluster_arrive();
            cluster_wait();
            if (lane < 2) prefetch_l2(pf, kb);
            mbar_wait(bars + B_XA * 8, 0);
            if (lane == 2) prefetch_l2(pf, kb);
            if (lane >= 1 && lane < 9) asm volatile("prefetch.tensormap [%0];" ::"l"(&p.tm[lane]) : "memory");
            mbar_wait(bars + (B_FULL + 1) * 8, 1);
            if (lane > 2 && lane < 8) prefetch_l2(pf, kb);
            const uint32_t epoch = ld_epoch();
            bar_sync(4, 288);
            if (lane < 2) flag_set(&g_flag_kv[((b * 4 + 2 * r + lane) * 32 + pt) * FS], epoch);
            __syncwarp();
            TSW(8);
            bar_sync(6, 288);
            bar_arrive(9, 64);
            if (lane == 0) {
                flag_set(&g_flag_o[((b * 16 + qt) * 4 + ah) * FS], epoch);
                g_epoch[blockIdx.x * FS] = epoch;
            }
            __syncwarp();
            TSW(9);
        }
        TSDUMP();
        return;
    }

    const int w = warp >> 2, wq = warp & 3;
    const int tile = 2 * r + w;
    const int wt = tid & 127;
    const int c4 = lane & 3;
    const int trow = pt * 32 + 8 * wq;
    uint32_t xr[8];
    {
        const uint32_t* xp = reinterpret_cast<const uint32_t*>(p.x + (size_t)(b * T_ + trow + (lane >> 2)) * 256 + tile * 64) + c4;
#pragma unroll
        for (int j = 0; j < 8; j++) xr[j] = trow < T_ ? __ldg(xp + 4 * j) : 0u;
    }
    cluster_arrive();
    asm volatile("setmaxnreg.inc.sync.aligned.u32 208;");
    const uint32_t rbase = sb + OFF_RING + w * NSLOT * SLOT, fbar = bars + (B_FULL + w * NSLOT) * 8;
    const uint32_t rdesc = desc_lo(rbase);
    auto acq = [&](int n) { mbar_wait(fbar + (n % NSLOT) * 8, (n / NSLOT) & 1); };
    auto rel = [&](int n) { if (lane == 0) mbar_arrive(fbar + (B_EMPTY - B_FULL + n % NSLOT) * 8); };
    const uint32_t foff = (lane & 7) * 128 + (((lane >> 3) ^ (lane & 7)) << 4);
    const uint32_t toff = ((lane >> 4) * 8 + (lane & 7)) * 128 + (((2 * wq + ((lane >> 3) & 1)) ^ (lane & 7)) << 4);
    auto publish = [&](int bar, uint32_t src, uint32_t bytes, int nsync) {
        fence_async_smem();
        bar_sync(2 + w, 128);
        if (wq == 0) peer_copy(mapa(src, r ^ 1), src, bytes, mapa(bars + bar * 8, r ^ 1));
        bar_sync(nsync == 384 ? 1 : 10, nsync);
    };
    float v[16];
#pragma unroll
    for (int j = 0; j < 8; j++) { v[2 * j] = blo(xr[j]); v[2 * j + 1] = bhi(xr[j]); }
    const uint32_t xown = __shfl_sync(~0u, P + wt * 16 + tile * 4096, lane), xrem = __shfl_sync(~0u, P + wt * 16 + (r ^ 1) * 8192, lane);
    const uint32_t sbuf = __shfl_sync(~0u, sb + OFF_MISC + 1024 + (8 * wq + (lane >> 2)) * 32, lane);
    const uint32_t sown = __shfl_sync(~0u, sbuf + tile * 8, lane);
    const uint32_t peer = __shfl_sync(~0u, mapa(sb, r ^ 1) - sb, lane);
    const uint32_t meta = __shfl_sync(~0u, 0xEEEE4444u + p.zero, lane);
    cluster_wait();
    TS(56);
    float mean, msq;

#pragma unroll 1
    for (int ph = 0;; ph++) {
        uint4 o0, o1;
        {
            float s = 0.f, q = 0.f, s2 = 0.f, q2 = 0.f;
#pragma unroll
            for (int j = 0; j < 4; j++) {
                s += v[4 * j] + v[4 * j + 1]; s2 += v[4 * j + 2] + v[4 * j + 3];
                q += fmaf(v[4 * j], v[4 * j], v[4 * j + 1] * v[4 * j + 1]); q2 += fmaf(v[4 * j + 2], v[4 * j + 2], v[4 * j + 3] * v[4 * j + 3]);
            }
            s += s2; q += q2;
            const uint32_t xa = bars + (B_XA + ph) * 8;
            s += __shfl_xor_sync(~0u, s, 1); q += __shfl_xor_sync(~0u, q, 1);
            s += __shfl_xor_sync(~0u, s, 2); q += __shfl_xor_sync(~0u, q, 2);
            if (c4 == 0) st_async2f(sown + peer, s, q, xa + peer);
            if (c4 == 0) sts64f(sown, s, q);
#pragma unroll
            for (int j = 0; j < 8; j++) xr[j] = pack2(v[2 * j], v[2 * j + 1]);
            sts128(xown, xr[0], xr[1], xr[2], xr[3]);
            sts128(xown + 2048, xr[4], xr[5], xr[6], xr[7]);
            bar_sync(10, 256);
            o0 = lds128(xown ^ 4096); o1 = lds128((xown ^ 4096) + 2048);
            if (ph < 3) {
                st_async4(xown + peer, xr[0], xr[1], xr[2], xr[3], xa + (B_XB - B_XA) * 8 + peer);
                st_async4(xown + peer + 2048, xr[4], xr[5], xr[6], xr[7], xa + (B_XB - B_XA) * 8 + peer);
            }
            TS(57 + ph);
            if (ph == 0) acq(0);
            mbar_wait(xa, 0);
            const float4 u0 = lds128f(sbuf), u1 = lds128f(sbuf + 16);
            mean = ((u0.x + u0.z) + (u1.x + u1.z)) * (1.f / 256.f);
            msq = ((u0.y + u0.w) + (u1.y + u1.w)) * (1.f / 256.f);
        }
        if (ph == 3) break;
        uint32_t a[32];
        const uint32_t mean2 = pack2(mean, mean);
        auto centre = [&](int i, const uint4& u) {
            a[i] = hsub2(u.x, mean2); a[i + 1] = hsub2(u.y, mean2); a[i + 2] = hsub2(u.z, mean2); a[i + 3] = hsub2(u.w, mean2);
        };
#pragma unroll
        for (int j = 0; j < 8; j++) a[j] = hsub2(xr[j], mean2);
        centre(8, o0); centre(12, o1);
        const float rstd = rsq(fmaxf(fmaf(-mean, mean, msq), 0.f) + 1e-5f);
        auto gather_peer = [&]() {
            mbar_wait(bars + (B_XB + ph) * 8, 0);
#pragma unroll
            for (int i = 0; i < 4; i++) centre(16 + 4 * i, lds128(xrem + i * 2048));
        };
        auto sp = [&](float (&d)[32], int n, const uint32_t* af, int flip, int acc) {
            const uint32_t lo = rdesc + p.zero * (ph + n + 1) + (n % NSLOT) * (SLOT >> 4);
            const uint64_t b0 = mkdesc(lo + flip * 512), b1 = mkdesc(lo + (flip ^ 1) * 512);
            wg_fence();
            mma_sp(d, af, b0, meta, acc);
            mma_sp(d, af + 4, b0 + 256, meta, 1);
            mma_sp(d, af + 8, b1, meta, 1);
            mma_sp(d, af + 12, b1 + 256, meta, 1);
            wg_commit();
        };
        float d0[32], d1[32];

        if (ph != 1) {
            uint32_t h[32];
            const float rs = 0.5f * rstd;
            const uint32_t inb = bars + (B_INB + ph) * 8, box = H + wt * 16;
            bool ready = true;
            auto pair_step = [&](int n, auto first, auto second, auto work) {
                if (!ready) { acq(n); acq(n + 1); }
                if (TURN == 2 && n > 0) bar_sync(7 + w, 256);
                if (TURN == 1 && n == 2 && w == 1) bar_sync(7, 256);
                first();
                second();
                if (TURN == 2 && (n > 0 || w == 1) && (n < 14 || w == 0)) bar_arrive(8 - w, 256);
                if (TURN == 1 && n == 2 && w == 0) bar_arrive(7, 256);
                if (n < 14) ready = mbar_test(fbar + ((n + 2) % NSLOT) * 8, ((n + 2) / NSLOT) & 1) & mbar_test(fbar + ((n + 3) % NSLOT) * 8, ((n + 3) / NSLOT) & 1);
                wg_wait<2>();
                work();
                if (p.zero < n + ph + 1) wg_wait<0>();
                rel(n); rel(n + 1);
            };
            auto act = [&](float (&d)[32], int i) {
                pin(d);
#pragma unroll
                for (int j = 0; j < 8; j++) {
                    const float u0 = (d[4 * j] + d[4 * j + 2]) * rs, u1 = (d[4 * j + 1] + d[4 * j + 3]) * rs;
                    h[8 * i + j] = pack2(fmaf(u0, tanh_fast(u0), u0), fmaf(u1, tanh_fast(u1), u1));
                }
            };
            auto send = [&](float (&d)[32], int x) {
                pin(d);
                uint32_t pk[8];
#pragma unroll
                for (int j = 0; j < 8; j++) pk[j] = pack2(d[4 * j] + d[4 * j + 2], d[4 * j + 1] + d[4 * j + 3]);
                const uint32_t ow = w ^ (x & 1), dst = box + (ow * 3 + x - 1) * 4096;
                if (x & 2) {
                    st_async4(dst + peer, pk[0], pk[1], pk[2], pk[3], inb + ow * 8 + peer);
                    st_async4(dst + peer + 2048, pk[4], pk[5], pk[6], pk[7], inb + ow * 8 + peer);
                } else {
                    sts128(dst, pk[0], pk[1], pk[2], pk[3]);
                    sts128(dst + 2048, pk[4], pk[5], pk[6], pk[7]);
                }
            };
            float d2[32];
            TS(1 + ph * 10);
            pair_step(0, [&]() { sp(d0, 0, a, w, 0); }, [&]() { gather_peer(); acq(1); sp(d0, 1, a + 16, 0, 1); }, []() {});
            TS(32);
            pair_step(2, [&]() { sp(d1, 2, a, w, 0); }, [&]() { sp(d1, 3, a + 16, 0, 1); }, [&]() { act(d0, 0); });
            pair_step(4, [&]() { sp(d0, 4, a, w, 0); }, [&]() { sp(d0, 5, a + 16, 0, 1); }, [&]() { act(d1, 1); });
            TS(33);
            pair_step(6, [&]() { sp(d1, 6, a, w, 0); }, [&]() { sp(d1, 7, a + 16, 0, 1); }, [&]() { act(d0, 2); });
            pair_step(8, [&]() { sp(d0, 8, h, 0, 0); }, [&]() { sp(d2, 9, h, 0, 0); }, [&]() { act(d1, 3); });
            TS(2 + ph * 10);
            pair_step(10, [&]() { sp(d0, 10, h + 16, 0, 1); }, [&]() { sp(d2, 11, h + 16, 0, 1); }, []() {});
            pair_step(12, [&]() { sp(d1, 12, h, 0, 0); }, [&]() { sp(d1, 13, h + 16, 0, 1); }, [&]() { send(d0, 3); send(d2, 2); });
            TS(34);
            pair_step(14, [&]() { sp(d0, 14, h, 0, 0); }, [&]() { sp(d0, 15, h + 16, 0, 1); }, [&]() { send(d1, 1); });
            if (ph == 0) acq(16);
            mbar_wait(inb + w * 8, 0);
            bar_sync(10, 256);
#pragma unroll
            for (int i = 0; i < 2; i++) {
                const uint32_t src = box + w * 12288 + i * 2048;
                const uint4 u0 = lds128(src), u1 = lds128(src + 4096), u2 = lds128(src + 8192);
                const uint32_t p0[4] = {u0.x, u0.y, u0.z, u0.w}, p1[4] = {u1.x, u1.y, u1.z, u1.w}, p2[4] = {u2.x, u2.y, u2.z, u2.w};
#pragma unroll
                for (int j = 0; j < 4; j++) {
                    v[8 * i + 2 * j] = fmaf(0.5f, blo(p0[j]) + blo(p1[j]) + blo(p2[j]), blo(xr[4 * i + j]));
                    v[8 * i + 2 * j + 1] = fmaf(0.5f, bhi(p0[j]) + bhi(p1[j]) + bhi(p2[j]), bhi(xr[4 * i + j]));
                }
            }
            wg_wait<0>();
            pin(d0);
            TS(3 + ph * 10);
#pragma unroll
            for (int j = 0; j < 8; j++) {
                v[2 * j] = fmaf(0.5f, d0[4 * j] + d0[4 * j + 2], v[2 * j]);
                v[2 * j + 1] = fmaf(0.5f, d0[4 * j + 1] + d0[4 * j + 3], v[2 * j + 1]);
            }
            continue;
        }

        {
            TS(11);
            sp(d0, 16, a, w, 0);
            acq(17);
            sp(d1, 17, a, w, 0);
            if (wq == 0 || wq == 3) {
                uint4* hp = &g_halo[((pair * 4 + tile) * 2 + (wq & 1)) * 64 + lane];
                hp[0] = make_uint4(xr[0], xr[1], xr[2], xr[3]);
                hp[32] = make_uint4(xr[4], xr[5], xr[6], xr[7]);
            }
            gather_peer();
            acq(18);
            sp(d0, 18, a + 16, 0, 1);
            wg_wait<1>();
            rel(16); rel(17);
            acq(19);
            sp(d1, 19, a + 16, 0, 1);
            const uint32_t stg = H + warp * 3072;
            unsigned char* g = g_kvq + (size_t)((b * 4 + tile) * 1024 + trow) * 128 + lane * 16;
            auto put = [&](float (&d)[32], int i) {
                pin(d);
                uint32_t pk[8];
#pragma unroll
                for (int j = 0; j < 8; j++) pk[j] = pack2((d[4 * j] + d[4 * j + 2]) * rstd, (d[4 * j + 1] + d[4 * j + 3]) * rstd);
                stsm4(stg + i * 1024 + foff, pk[0], pk[1], pk[2], pk[3]);
                stsm4(stg + i * 1024 + (foff ^ 64), pk[4], pk[5], pk[6], pk[7]);
                __syncwarp();
                const uint4 u0 = lds128(stg + i * 1024 + lane * 16), u1 = lds128(stg + i * 1024 + 512 + lane * 16);
                stg128(g + i * 1048576, u0); stg128(g + i * 1048576 + 512, u1);
            };
            wg_wait<1>();
            rel(18);
            put(d0, 0);
            wg_wait<0>();
            rel(19);
            TS(37);
            put(d1, 1);
            bar_arrive(4, 288);
            TS(38);
            acq(20);
            sp(d0, 20, a, w, 0);
            acq(21);
            sp(d0, 21, a + 16, 0, 1);
            wg_wait<0>();
            rel(20); rel(21);
            put(d0, 2);
            bar_arrive(11, 288);
            acq(22); acq(23);
            rel(22); rel(23);
            TS(12);
        }

        {
            constexpr float CS = 0.125f * 1.4426950408889634f;
            float sa[32], sb2[32], o[36];
            uint32_t pa[16], pb[16], q[16];
            float n0 = INFINITY, n1 = INFINITY;
            zero(o); zero(pa); zero(pb);
            const uint32_t ones = sb + OFF_MISC + 2048;
            if (tid < 128) sts128(ones + tid * 16, 0x3F803F80u, 0x3F803F80u, 0x3F803F80u, 0x3F803F80u);
            fence_async_smem();
            bar_sync(10, 256);
            const uint32_t vdesc = rdesc + ((((ones - rbase) >> 4) - 1) << 16);
            auto qk_issue = [&](float (&s)[32], uint32_t lo) {
                const uint64_t kd = mkdesc(lo);
                wg_fence();
#pragma unroll
                for (int k = 0; k < 4; k++) mma_qk(s, q[4 * k], q[4 * k + 1], q[4 * k + 2], q[4 * k + 3], kd + 2 * k, k != 0);
                wg_commit();
            };
            auto pv_issue = [&](uint32_t (&pp)[16], uint32_t lo) {
                const uint64_t vd = mkdesc(lo);
                wg_fence();
#pragma unroll
                for (int k = 0; k < 4; k++) mma_pv(o, pp[4 * k], pp[4 * k + 1], pp[4 * k + 2], pp[4 * k + 3], vd - k * (128 * 65535));
                wg_commit();
            };
            auto new_max = [&](float (&s)[32], float& x0, float& x1) {
                x0 = s[0]; x1 = s[2];
#pragma unroll
                for (int j = 0; j < 8; j++) {
                    x0 = fmaxf(x0, fmaxf(s[4 * j], s[4 * j + 1]));
                    x1 = fmaxf(x1, fmaxf(s[4 * j + 2], s[4 * j + 3]));
                }
                x0 = fmaxf(x0, __shfl_xor_sync(~0u, x0, 1)); x1 = fmaxf(x1, __shfl_xor_sync(~0u, x1, 1));
                x0 = fmaxf(x0, __shfl_xor_sync(~0u, x0, 2)); x1 = fmaxf(x1, __shfl_xor_sync(~0u, x1, 2));
                x0 = fminf(n0, fmaf(x0, -CS, -20.f)); x1 = fminf(n1, fmaf(x1, -CS, -20.f));
            };
            auto probs = [&](float (&s)[32], uint32_t (&pp)[16], bool ready, auto wait) {
                uint32_t any = 0;
#pragma unroll
                for (int i = 0; i < 16; i++) {
                    pp[i] = pack2(ex2(fmaf(s[2 * i], CS, (i & 1) ? n1 : n0)), ex2(fmaf(s[2 * i + 1], CS, (i & 1) ? n1 : n0)));
                    any |= pp[i];
                }
                float sc0 = 1.f, sc1 = 1.f;
                const bool slow = __any_sync(~0u, (any & 0x40004000u) || !ready);
                if (slow) {
                    wait();
                    if (__any_sync(~0u, any & 0x40004000u)) {
                        float x0, x1;
                        new_max(s, x0, x1);
                        sc0 = ex2(x0 - n0); sc1 = ex2(x1 - n1);
                        n0 = x0; n1 = x1;
#pragma unroll
                        for (int i = 0; i < 16; i++)
                            pp[i] = pack2(ex2(fmaf(s[2 * i], CS, (i & 1) ? n1 : n0)), ex2(fmaf(s[2 * i + 1], CS, (i & 1) ? n1 : n0)));
                    }
                }
                wg_wait<0>();
                pin(sa); pin(sb2); pin(o); pin(pa); pin(pb);
                if (slow) {
#pragma unroll
                    for (int j = 0; j < 9; j++) { o[4 * j] *= sc0; o[4 * j + 1] *= sc0; o[4 * j + 2] *= sc1; o[4 * j + 3] *= sc1; }
                }
            };
            mbar_wait(bars + B_QIN * 8, 0);
            {
                const uint32_t qa = H + 24576 + (wq * 16 + (lane & 15)) * 128;
#pragma unroll
                for (int k = 0; k < 4; k++) ldsm4(qa + (((2 * k + (lane >> 4)) ^ (lane & 7)) << 4), q[4 * k], q[4 * k + 1], q[4 * k + 2], q[4 * k + 3]);
                pin(q);
            }
            TS(40);
            acq(24);
            TS(13);
            qk_issue(sa, rdesc + (24 % NSLOT) * (SLOT >> 4));
            qk_issue(sb2, rdesc + (24 % NSLOT) * (SLOT >> 4) + 512);
            wg_wait<1>();
            pin(sa);
            {
                float x0, x1;
                new_max(sa, x0, x1);
                n0 = x0; n1 = x1;
            }
            if (w == 1) bar_sync(7, 256);
            uint32_t vd = vdesc - (SLOT >> 4) * 65535u, kd = rdesc, vb = fbar + 8, kb = fbar;
            uint32_t vlast = vdesc - 4 * (SLOT >> 4) * 65535u;
            uint32_t kprev = fbar + 32, vprev = bars + (B_SINK - (B_EMPTY - B_FULL)) * 8;
#pragma unroll 1
            for (int it = 0; it < 4; it++) {
                pv_issue(pb, vlast);
                probs(sa, pa, mbar_test(vb, it < 2) & mbar_test(kb, it < 3), [&]() { mbar_wait(vb, it < 2); mbar_wait(kb, it < 3); });
                TS(41 + it * 4);
                if (it == 0 && w == 0) bar_arrive(7, 256);
                if (it == 3 && w == 1) {
#pragma unroll
                    for (int i = 20; i < 32; i++) sb2[i] = -INFINITY;
                }
                pin(sb2);
                if (it < 3) qk_issue(sa, kd);
                if (lane == 0) mbar_arrive(kprev + (B_EMPTY - B_FULL) * 8);
                if (lane == 0) mbar_arrive(vprev + (B_EMPTY - B_FULL) * 8);
                pv_issue(pa, vd);
                probs(sb2, pb, true, []() {});
                TS(43 + it * 4);
                if (it < 3) qk_issue(sb2, kd + 512);
                const int dv = it == 0 ? 2 : (it == 1 ? -3 : 1);
                kprev = kb; vprev = vb; vlast = vd - 512 * 65535u;
                vd -= dv * (SLOT >> 4) * 65535u; vb += dv * 8;
                kd += 2 * (SLOT >> 4); kb = it == 2 ? vb : kb + 16;
            }
            pv_issue(pb, vlast);
            const int row = wq * 16 + (lane >> 2);
            const uint32_t ml = sb + OFF_MISC;
            wg_wait<0>();
            pin(o); pin(pb); pin(sa); pin(sb2);
            rel(31);
            const float l0 = o[32], l1 = o[34];
            if (c4 == 0) { sts64f(ml + w * 512 + row * 8, n0, l0); sts64f(ml + w * 512 + row * 8 + 64, n1, l1); }
            TS(14);
            float mine[16];
#pragma unroll
            for (int j = 0; j < 4; j++) {
                if (w == 0) sts128f(H + j * 2048 + wt * 16, o[16 + 4 * j], o[17 + 4 * j], o[18 + 4 * j], o[19 + 4 * j]);
                else sts128f(H + 8192 + j * 2048 + wt * 16, o[4 * j], o[4 * j + 1], o[4 * j + 2], o[4 * j + 3]);
            }
#pragma unroll
            for (int i = 0; i < 16; i++) mine[i] = w == 0 ? o[i] : o[16 + i];
            bar_sync(10, 256);
            const float2 u0 = lds64f(ml + (w ^ 1) * 512 + row * 8), u1 = lds64f(ml + (w ^ 1) * 512 + row * 8 + 64);
            const float x0 = fminf(n0, u0.x), x1 = fminf(n1, u1.x);
            float a0 = ex2(x0 - n0), b0 = ex2(x0 - u0.x), a1 = ex2(x1 - n1), b1 = ex2(x1 - u1.x);
            const float i0 = __fdividef(1.f, fmaf(a0, l0, b0 * u0.y)), i1 = __fdividef(1.f, fmaf(a1, l1, b1 * u1.y));
            a0 *= i0; b0 *= i0; a1 *= i1; b1 *= i1;
            uint32_t pk[8];
#pragma unroll
            for (int j = 0; j < 4; j++) {
                const float4 v = lds128f(H + (w ^ 1) * 8192 + j * 2048 + wt * 16);
                pk[2 * j] = pack2(fmaf(a0, mine[4 * j], b0 * v.x), fmaf(a0, mine[4 * j + 1], b0 * v.y));
                pk[2 * j + 1] = pack2(fmaf(a1, mine[4 * j + 2], b1 * v.z), fmaf(a1, mine[4 * j + 3], b1 * v.w));
            }
            const uint32_t og = H + 16384 + wq * 2048;
            {
                const uint32_t ra = og + (((lane >> 3) & 1) * 8 + (lane & 7)) * 128;
                stsm4(ra + (((4 * w + (lane >> 4)) ^ (lane & 7)) << 4), pk[0], pk[1], pk[2], pk[3]);
                stsm4(ra + (((4 * w + 2 + (lane >> 4)) ^ (lane & 7)) << 4), pk[4], pk[5], pk[6], pk[7]);
            }
            __syncwarp();
            {
                const uint32_t off = (lane >> 2) * 128 + (((4 * w + c4) ^ (lane >> 2)) << 4);
                const uint4 v0 = lds128(og + off), v1 = lds128(og + off + 1024);
                unsigned char* dst = g_o + (size_t)(abh * PADROWS + 8 + qt * 64 + wq * 16) * 128 + off;
                stg128(dst, v0); stg128(dst + 1024, v1);
            }
            bar_arrive(6, 288);
            TS(15);
        }

        auto mm = [&](float (&d)[24], int n, uint32_t act, int acc) {
            const uint32_t z = p.zero * (ph + n);
            const uint64_t ad = mkdesc(rdesc + z + (n % NSLOT) * (SLOT >> 4)), bd = mkdesc(desc_lo(act) + z);
            wg_fence();
#pragma unroll
            for (int k = 0; k < 8; k++) mma_t(d, ad + k * 128, bd + (k >> 2) * (XCH >> 4) + (k & 3) * 2, k == 0 ? acc : 1);
            wg_commit();
        };
        const uint32_t xo = P + tile * XCH + wq * 1024, xt = P + tile * XCH + toff;
        uint32_t dwr[15];
        {
#pragma unroll
            for (int i = 0; i < 15; i++) dwr[i] = hmul2(__ldg(reinterpret_cast<const uint32_t*>(p.dw + i * 256 + tile * 64) + lane), 0x3F003F00u);
            float d[24];
            uint32_t xw[12];
            stsm4(xo + 1024 + foff, xr[0], xr[1], xr[2], xr[3]);
            stsm4(xo + 1024 + (foff ^ 64), xr[4], xr[5], xr[6], xr[7]);
            mbar_wait(bars + B_X1IN * 8, 0);
            if (wq == 0 || wq == 3) {
                uint4 h0 = make_uint4(0, 0, 0, 0), h1 = h0;
                const int np = wq ? pt + 1 : pt - 1;
                if (np >= 0 && np < 32) {
                    const uint4* hp = &g_halo[(((b * 32 + np) * 4 + tile) * 2 + (wq ? 0 : 1)) * 64 + lane];
                    h0 = __ldcg(hp); h1 = __ldcg(hp + 32);
                }
                stsm4(xo + (wq ? 2048 : 0) + foff, h0.x, h0.y, h0.z, h0.w);
                stsm4(xo + (wq ? 2048 : 0) + (foff ^ 64), h1.x, h1.y, h1.z, h1.w);
            }
            bar_sync(2 + w, 128);
#pragma unroll
            for (int j = 0; j < 3; j++) ldsm4t(xt + j * 2048, xw[4 * j], xw[4 * j + 1], xw[4 * j + 2], xw[4 * j + 3]);
            pin(xw);
            pin(dwr);
            acq(32); acq(33); acq(34); acq(35);
            mbar_wait(bars + B_OIN * 8, 0);
            TS(16);
            mm(d, 32, H, 0);
            mbar_wait(bars + B_OIN * 8 + 8, 0);
            mm(d, 33, H + 2 * XCH, 1);
            wg_wait<1>();
            rel(32);
            wg_wait<0>();
            pin(d);
#pragma unroll
            for (int i = 0; i < 12; i++) xw[i] = pack2(d[2 * i] + blo(xw[i]), d[2 * i + 1] + bhi(xw[i]));
            if (c4 == 0) { xw[0] = (xw[0] & 0xffff0000u) | 0x3F80u; xw[1] = (xw[1] & 0xffff0000u) | 0x3F80u; }
#pragma unroll
            for (int j = 0; j < 3; j++) stsm4t(xt + j * 2048, xw[4 * j], xw[4 * j + 1], xw[4 * j + 2], xw[4 * j + 3]);
            rel(33);
            publish(B_X2, P + tile * XCH, XCH, 384);
            TS(17);
        }
        {
            float da[24], db[24], st[24];
            bar_sync(5, 384);
            mm(da, 34, P + 2 * r * XCH, 0);
            mm(db, 35, P + 2 * r * XCH, 0);
            acq(36); acq(37);
            mbar_wait(bars + B_X2 * 8, 0);
            bar_sync(5, 384);
            TS(39);
            mm(da, 36, P + 2 * (r ^ 1) * XCH, 1);
            mm(db, 37, P + 2 * (r ^ 1) * XCH, 1);
            wg_wait<2>();
            rel(34); rel(35);
            mbar_wait(bars + B_ST * 8, 0);
#pragma unroll
            for (int j = 0; j < 6; j++) {
                const float4 u = lds128f(sb + OFF_STATS + (8 * j + 2 * c4) * 8);
                st[4 * j] = u.x; st[4 * j + 1] = u.y; st[4 * j + 2] = u.z; st[4 * j + 3] = u.w;
            }
            wg_wait<0>();
            pin(da); pin(db);
            rel(36); rel(37);
            TS(18);
            uint32_t pk[12];
#pragma unroll
            for (int hh = 0; hh < 2; hh++) {
                const float ca = __shfl_sync(~0u, da[2 * hh], lane & 28), cb = __shfl_sync(~0u, db[2 * hh], lane & 28);
#pragma unroll
                for (int j = 0; j < 6; j++) {
                    const float u0 = fmaf(-st[4 * j], ca, da[4 * j + 2 * hh] * st[4 * j + 1]);
                    const float u1 = fmaf(-st[4 * j + 2], ca, da[4 * j + 2 * hh + 1] * st[4 * j + 3]);
                    const float v0 = fmaf(-st[4 * j], cb, db[4 * j + 2 * hh] * st[4 * j + 1]);
                    const float v1 = fmaf(-st[4 * j + 2], cb, db[4 * j + 2 * hh + 1] * st[4 * j + 3]);
                    pk[2 * j + hh] = pack2(fmaf(u0, tanh_fast(v0), u0), fmaf(u1, tanh_fast(v1), u1));
                }
            }
            const uint32_t gs = H + 16384 + w * XCH;
#pragma unroll
            for (int j = 0; j < 3; j++) stsm4t(gs + toff + j * 2048, pk[4 * j], pk[4 * j + 1], pk[4 * j + 2], pk[4 * j + 3]);
            ldsm4(xo + 1024 + foff, xr[0], xr[1], xr[2], xr[3]);
            ldsm4(xo + 1024 + (foff ^ 64), xr[4], xr[5], xr[6], xr[7]);
            bar_sync(2 + w, 128);
            uint32_t ca[8], cb[8];
            const uint32_t grow = gs + 8 * wq * 128 + c4 * 4, srow = H + tile * HCH + 8 * wq * 128 + c4 * 4;
#pragma unroll
            for (int k = 0; k < 22; k++) {
                const uint32_t v = lds32(grow + (1 + k) * 128 + (((lane >> 2) ^ ((1 + k) & 7)) << 4));
#pragma unroll
                for (int i = 0; i < 8; i++) {
                    const int tap = k - i;
                    if (tap == 0) ca[i] = hmul2(v, dwr[0]);
                    else if (tap > 0 && tap < 8) ca[i] = hfma2(v, dwr[tap], ca[i]);
                    else if (tap == 8) cb[i] = hmul2(v, dwr[8]);
                    else if (tap > 8 && tap < 15) cb[i] = hfma2(v, dwr[tap], cb[i]);
                }
            }
#pragma unroll
            for (int i = 0; i < 8; i++) {
                const float h0 = blo(ca[i]) + blo(cb[i]), h1 = bhi(ca[i]) + bhi(cb[i]);
                sts32(srow + i * 128 + (((lane >> 2) ^ i) << 4), pack2(fmaf(h0, tanh_fast(h0), h0), fmaf(h1, tanh_fast(h1), h1)));
            }
            acq(38); acq(39);
            publish(B_SR, H + tile * HCH, HCH, 256);
            TS(19);
        }
        {
            auto frags = [&](int i, int half) {
                const uint32_t src = H + 2 * half * HCH + wq * 1024;
#pragma unroll
                for (int k = 0; k < 4; k++) ldsm4(src + (k >> 1) * HCH + (foff ^ ((k & 1) * 64)), a[i + 4 * k], a[i + 4 * k + 1], a[i + 4 * k + 2], a[i + 4 * k + 3]);
            };
            frags(0, r);
            sp(d0, 38, a, 0, 0);
            acq(40);
            mbar_wait(bars + B_SR * 8, 0);
            frags(16, r ^ 1);
            sp(d0, 39, a + 16, 0, 1);
            wg_wait<1>();
            rel(38);
            wg_wait<0>();
            pin(d0);
            rel(39);
#pragma unroll
            for (int j = 0; j < 8; j++) {
                v[2 * j] = d0[4 * j] + d0[4 * j + 2] + blo(xr[j]);
                v[2 * j + 1] = d0[4 * j + 1] + d0[4 * j + 3] + bhi(xr[j]);
            }
            TS(20);
        }
    }

    cluster_arrive();
    TS(24);
    {
        const float rstd = rsq(fmaxf(fmaf(-mean, mean, msq), 0.f) + 1e-5f), nb = -mean * rstd;
#pragma unroll
        for (int j = 0; j < 8; j++) xr[j] = pack2(fmaf(v[2 * j], rstd, nb), fmaf(v[2 * j + 1], rstd, nb));
        const uint32_t stg = P + 16384 + warp * 1024;
        stsm4(stg + foff, xr[0], xr[1], xr[2], xr[3]);
        stsm4(stg + (foff ^ 64), xr[4], xr[5], xr[6], xr[7]);
        __syncwarp();
        const uint32_t src = stg + (lane >> 3) * 128 + (((lane & 7) ^ (lane >> 3)) << 4);
        const uint4 u0 = lds128(src), u1 = lds128((src + 512) ^ 64);
        __nv_bfloat16* dst = p.out + (size_t)(b * T_ + trow + (lane >> 3)) * 256 + tile * 64 + (lane & 7) * 8;
        if (trow < T_) { stg128(dst, u0); stg128(dst + 4 * 256, u1); }
    }
    TS(25);
    TG(31);
    TSDUMP();
    cluster_wait();
}

typedef CUresult (*EncodeFn)(CUtensorMap*, CUtensorMapDataType, cuuint32_t, void*, const cuuint64_t*, const cuuint64_t*,
                             const cuuint32_t*, const cuuint32_t*, CUtensorMapInterleave, CUtensorMapSwizzle,
                             CUtensorMapL2promotion, CUtensorMapFloatOOBfill);

}

extern "C" void kernel_launch(void* const* d_in, const int* in_sizes, int n_in, void* d_out, int out_size) {
    static EncodeFn encode = nullptr;
    if (!encode) {
        void* fn = nullptr;
        cudaDriverEntryPointQueryResult qr;
        cudaGetDriverEntryPoint("cuTensorMapEncodeTiled", &fn, cudaEnableDefault, &qr);
        encode = (EncodeFn)fn;
        cudaFuncSetAttribute(conformer_kernel, cudaFuncAttributeMaxDynamicSharedMemorySize, SMEM_LAUNCH);
    }
    Params p;
    const cuuint32_t ones[5] = {1, 1, 1, 1, 1};
    const int idx[8] = {1, 2, 3, 4, 5, 7, 8, 9};
    const int rows[8] = {256, 1024, 256, 256, 256, 256, 256, 1024};
    const int cols[8] = {1024, 256, 768, 256, 512, 256, 1024, 256};
    for (int i = 0; i < 8; i++) {
        const bool perm = i != 3 && i != 4;
        const cuuint64_t pitch = (cuuint64_t)cols[i] * 2;
        const cuuint64_t dims[5] = {(cuuint64_t)cols[i], 2, 2, 4, (cuuint64_t)rows[i] / 16};
        const cuuint64_t strides[4] = {pitch, pitch * (perm ? 8 : 2), pitch * (perm ? 2 : 4), pitch * 16};
        const cuuint32_t box[5] = {64, 2, 2, 4, 8};
        encode(&p.tm[i], CU_TENSOR_MAP_DATA_TYPE_BFLOAT16, 5, d_in[idx[i]], dims, strides, box, ones, CU_TENSOR_MAP_INTERLEAVE_NONE,
               CU_TENSOR_MAP_SWIZZLE_128B, CU_TENSOR_MAP_L2_PROMOTION_L2_128B, CU_TENSOR_MAP_FLOAT_OOB_FILL_NONE);
        p.w[i] = (const char*)d_in[idx[i]];
    }
    {
        void* kv = nullptr;
        cudaGetSymbolAddress(&kv, g_kvq);
        const cuuint64_t dims[2] = {64, 16384};
        const cuuint64_t strides[1] = {128};
        const cuuint32_t box[2] = {64, 128};
        encode(&p.tm[8], CU_TENSOR_MAP_DATA_TYPE_BFLOAT16, 2, kv, dims, strides, box, ones, CU_TENSOR_MAP_INTERLEAVE_NONE,
               CU_TENSOR_MAP_SWIZZLE_NONE, CU_TENSOR_MAP_L2_PROMOTION_L2_128B, CU_TENSOR_MAP_FLOAT_OOB_FILL_NONE);
    }
    p.x = (const __nv_bfloat16*)d_in[0];
    p.dw = (const __nv_bfloat16*)d_in[6];
    p.out = (__nv_bfloat16*)d_out;
    p.zero = 0;
    conformer_kernel<<<NCTA, NTHREADS, SMEM_LAUNCH>>>(p);
}
```

```cpp
#include <cuda_runtime.h>
#include <cuda_bf16.h>
#include <cuda.h>
#include <stdint.h>

namespace {

constexpr int T_ = 1000;
constexpr int NCTA = 128;
constexpr int NTHREADS = 512;
constexpr int NSLOT = 5;
constexpr int SLOT = 16384;
constexpr int NLOADS = 56;

constexpr uint32_t OFF_RING = 0;
constexpr uint32_t OFF_P = 163840;
constexpr uint32_t OFF_H = 188416;
constexpr uint32_t OFF_MISC = 221184;
constexpr uint32_t OFF_STATS = 229376;
constexpr uint32_t OFF_BARS = 229888;
constexpr uint32_t SMEM_BYTES = 230400;
constexpr uint32_t XCH = 6144;
constexpr uint32_t HCH = 4096;

constexpr int B_FULL = 0, B_EMPTY = 10, B_XA = 20  , B_XB = 24  , B_INB = 27  , B_X2 = 31, B_SR = 32, B_OIN = 33  ,
              B_QIN = 35, B_X1IN = 36, B_RDY = 37  , B_SINK = 43, B_ST = 44;

#define TURN 0
#define EAGER 0x5555
constexpr int PADROWS = 1040;
constexpr int FS = 8;

struct Params {
    CUtensorMap tm[9];
    const char* w[8];
    const __nv_bfloat16* x;
    const __nv_bfloat16* dw;
    __nv_bfloat16* out;
    uint32_t zero;
};

__device__ __align__(1024) unsigned char g_kvq[3 * 8 * 1024 * 128];
__device__ __align__(1024) unsigned char g_o[8 * PADROWS * 128];
__device__ uint4 g_halo[64 * 4 * 2 * 64];
__device__ uint32_t g_flag_kq[8 * 32 * FS];
__device__ uint32_t g_flag_v[8 * 32 * FS];
__device__ uint32_t g_flag_o[2 * 16 * 4 * FS];
__device__ uint32_t g_epoch[NCTA * FS];

#define TS(i) do { } while (0)
#define TSW(i) do { } while (0)
#define TG(i) do { } while (0)
#define TSINIT() do { } while (0)
#define TSDUMP() do { } while (0)
constexpr uint32_t SMEM_LAUNCH = SMEM_BYTES;

__device__ __forceinline__ uint32_t smem_u32(const void* p) { return (uint32_t)__cvta_generic_to_shared(p); }
__device__ __forceinline__ void mbar_init(uint32_t b, uint32_t c) { asm volatile("mbarrier.init.shared::cta.b64 [%0], %1;" ::"r"(b), "r"(c) : "memory"); }
__device__ __forceinline__ void mbar_arrive(uint32_t b) { asm volatile("mbarrier.arrive.shared::cta.b64 _, [%0];" ::"r"(b) : "memory"); }
__device__ __forceinline__ void mbar_arrive_tx(uint32_t b, uint32_t tx) { asm volatile("mbarrier.arrive.expect_tx.shared::cta.b64 _, [%0], %1;" ::"r"(b), "r"(tx) : "memory"); }
__device__ __forceinline__ void mbar_wait(uint32_t b, uint32_t ph) {
    asm volatile("{\n.reg .pred p, q;\n.reg .u32 c;\nmov.u32 c, 0;\n"
                 "MW_LOOP:\n.pragma \"nounroll\";\n"
                 "mbarrier.try_wait.parity.shared::cta.b64 p, [%0], %1;\n"
                 "add.u32 c, c, 1;\nsetp.lt.u32 q, c, 65536;\nnot.pred p, p;\nand.pred p, p, q;\n@p bra MW_LOOP;\n}"
                 ::"r"(b), "r"(ph) : "memory");
}
__device__ __forceinline__ bool mbar_test(uint32_t b, uint32_t ph) {
    uint32_t ok;
    asm volatile("{\n.reg .pred p;\nmbarrier.test_wait.parity.shared::cta.b64 p, [%1], %2;\nselp.u32 %0, 1, 0, p;\n}" : "=r"(ok) : "r"(b), "r"(ph) : "memory");
    return ok;
}
__device__ __forceinline__ uint32_t mapa(uint32_t a, uint32_t r) { uint32_t o; asm("mapa.shared::cluster.u32 %0, %1, %2;" : "=r"(o) : "r"(a), "r"(r)); return o; }
__device__ __forceinline__ void fence_async_smem() { asm volatile("fence.proxy.async.shared::cta;" ::: "memory"); }
__device__ __forceinline__ void fence_async_global() { asm volatile("fence.proxy.async.global;" ::: "memory"); }
__device__ __forceinline__ void bar_sync(int id, int n) { asm volatile("bar.sync %0, %1;" ::"r"(id), "r"(n) : "memory"); }
__device__ __forceinline__ void bar_arrive(int id, int n) { asm volatile("bar.arrive %0, %1;" ::"r"(id), "r"(n) : "memory"); }
__device__ __forceinline__ void cluster_arrive() { asm volatile("barrier.cluster.arrive.relaxed.aligned;" ::: "memory"); }
__device__ __forceinline__ void cluster_wait() { asm volatile("barrier.cluster.wait.aligned;" ::: "memory"); }

__device__ __forceinline__ void ring_load(uint32_t dst, const CUtensorMap* tm, int col, int row16, uint32_t bar) {
    asm volatile("{\n.reg .pred p;\nelect.sync _|p, 0xffffffff;\n"
                 "@p mbarrier.arrive.expect_tx.shared::cta.b64 _, [%2], 16384;\n"
                 "@p cp.async.bulk.tensor.5d.shared::cluster.global.mbarrier::complete_tx::bytes [%0], [%1, {%3, 0, 0, 0, %4}], [%2];\n}"
                 ::"r"(dst), "l"(tm), "r"(bar), "r"(col), "r"(row16) : "memory");
}
__device__ __forceinline__ void ring_load_both(uint32_t dst, const CUtensorMap* tm, int c1, uint32_t bar) {
    asm volatile("{\n.reg .pred p;\nelect.sync _|p, 0xffffffff;\n"
                 "@p cp.async.bulk.tensor.2d.shared::cluster.global.mbarrier::complete_tx::bytes.multicast::cluster [%0], [%1, {0, %3}], [%2], %4;\n}"
                 ::"r"(dst), "l"(tm), "r"(bar), "r"(c1), "h"((uint16_t)3) : "memory");
}
__device__ __forceinline__ void mbar_arrive_peer(uint32_t b) { asm volatile("mbarrier.arrive.relaxed.cluster.shared::cluster.b64 _, [%0];" ::"r"(b) : "memory"); }
__device__ __forceinline__ void bulk_g2s(uint32_t dst, const void* src, uint32_t bytes, uint32_t bar) {
    asm volatile("cp.async.bulk.shared::cluster.global.mbarrier::complete_tx::bytes [%0], [%1], %2, [%3];" ::"r"(dst), "l"(src), "r"(bytes), "r"(bar) : "memory");
}
__device__ __forceinline__ void prefetch_l2(const void* src, uint32_t bytes) {
    asm volatile("cp.async.bulk.prefetch.L2.global [%0], %1;" ::"l"(src), "r"(bytes) : "memory");
}
__device__ __forceinline__ void peer_copy(uint32_t dst, uint32_t src, uint32_t bytes, uint32_t rbar) {
    asm volatile("{\n.reg .pred p;\nelect.sync _|p, 0xffffffff;\n"
                 "@p cp.async.bulk.shared::cluster.shared::cta.mbarrier::complete_tx::bytes [%0], [%1], %2, [%3];\n}"
                 ::"r"(dst), "r"(src), "r"(bytes), "r"(rbar) : "memory");
}
__device__ __forceinline__ void st_async4(uint32_t dst, uint32_t a, uint32_t b, uint32_t c, uint32_t d, uint32_t bar) {
    asm volatile("st.async.shared::cluster.mbarrier::complete_tx::bytes.v4.b32 [%0], {%1,%2,%3,%4}, [%5];" ::"r"(dst), "r"(a), "r"(b), "r"(c), "r"(d), "r"(bar) : "memory");
}
__device__ __forceinline__ void st_async2f(uint32_t dst, float a, float b, uint32_t bar) {
    asm volatile("st.async.shared::cluster.mbarrier::complete_tx::bytes.v2.f32 [%0], {%1,%2}, [%3];" ::"r"(dst), "f"(a), "f"(b), "r"(bar) : "memory");
}
__device__ __forceinline__ void stsm4t(uint32_t a, uint32_t r0, uint32_t r1, uint32_t r2, uint32_t r3) {
    asm volatile("stmatrix.sync.aligned.m8n8.x4.trans.shared.b16 [%0], {%1,%2,%3,%4};" ::"r"(a), "r"(r0), "r"(r1), "r"(r2), "r"(r3) : "memory");
}
__device__ __forceinline__ void stsm4(uint32_t a, uint32_t r0, uint32_t r1, uint32_t r2, uint32_t r3) {
    asm volatile("stmatrix.sync.aligned.m8n8.x4.shared.b16 [%0], {%1,%2,%3,%4};" ::"r"(a), "r"(r0), "r"(r1), "r"(r2), "r"(r3) : "memory");
}
__device__ __forceinline__ void ldsm4t(uint32_t a, uint32_t& r0, uint32_t& r1, uint32_t& r2, uint32_t& r3) {
    asm volatile("ldmatrix.sync.aligned.m8n8.x4.trans.shared.b16 {%0,%1,%2,%3}, [%4];" : "=r"(r0), "=r"(r1), "=r"(r2), "=r"(r3) : "r"(a) : "memory");
}
__device__ __forceinline__ void ldsm4(uint32_t a, uint32_t& r0, uint32_t& r1, uint32_t& r2, uint32_t& r3) {
    asm volatile("ldmatrix.sync.aligned.m8n8.x4.shared.b16 {%0,%1,%2,%3}, [%4];" : "=r"(r0), "=r"(r1), "=r"(r2), "=r"(r3) : "r"(a) : "memory");
}
__device__ __forceinline__ uint4 lds128(uint32_t a) { uint4 v; asm volatile("ld.shared.v4.b32 {%0,%1,%2,%3}, [%4];" : "=r"(v.x), "=r"(v.y), "=r"(v.z), "=r"(v.w) : "r"(a) : "memory"); return v; }
__device__ __forceinline__ float4 lds128f(uint32_t a) { float4 v; asm volatile("ld.shared.v4.f32 {%0,%1,%2,%3}, [%4];" : "=f"(v.x), "=f"(v.y), "=f"(v.z), "=f"(v.w) : "r"(a) : "memory"); return v; }
__device__ __forceinline__ float2 lds64f(uint32_t a) { float2 v; asm volatile("ld.shared.v2.f32 {%0,%1}, [%2];" : "=f"(v.x), "=f"(v.y) : "r"(a) : "memory"); return v; }
__device__ __forceinline__ uint32_t lds32(uint32_t a) { uint32_t v; asm volatile("ld.shared.b32 %0, [%1];" : "=r"(v) : "r"(a) : "memory"); return v; }
__device__ __forceinline__ void sts128(uint32_t a, uint32_t x, uint32_t y, uint32_t z, uint32_t w) { asm volatile("st.shared.v4.b32 [%0], {%1,%2,%3,%4};" ::"r"(a), "r"(x), "r"(y), "r"(z), "r"(w) : "memory"); }
__device__ __forceinline__ void sts128f(uint32_t a, float x, float y, float z, float w) { asm volatile("st.shared.v4.f32 [%0], {%1,%2,%3,%4};" ::"r"(a), "f"(x), "f"(y), "f"(z), "f"(w) : "memory"); }
__device__ __forceinline__ void sts64f(uint32_t a, float x, float y) { asm volatile("st.shared.v2.f32 [%0], {%1,%2};" ::"r"(a), "f"(x), "f"(y) : "memory"); }
__device__ __forceinline__ void sts32(uint32_t a, uint32_t x) { asm volatile("st.shared.b32 [%0], %1;" ::"r"(a), "r"(x) : "memory"); }
__device__ __forceinline__ void stg128(void* p, uint4 v) { asm volatile("st.global.v4.b32 [%0], {%1,%2,%3,%4};" ::"l"(p), "r"(v.x), "r"(v.y), "r"(v.z), "r"(v.w) : "memory"); }

__device__ __forceinline__ uint32_t pack2(float lo, float hi) { uint32_t r; asm("cvt.rn.bf16x2.f32 %0, %1, %2;" : "=r"(r) : "f"(hi), "f"(lo)); return r; }
__device__ __forceinline__ float blo(uint32_t v) { return __uint_as_float(v << 16); }
__device__ __forceinline__ float bhi(uint32_t v) { return __uint_as_float(v & 0xffff0000u); }
__device__ __forceinline__ uint32_t hmul2(uint32_t a, uint32_t b) { uint32_t r; asm("mul.rn.bf16x2 %0, %1, %2;" : "=r"(r) : "r"(a), "r"(b)); return r; }
__device__ __forceinline__ uint32_t hsub2(uint32_t a, uint32_t b) { uint32_t r; asm("sub.rn.bf16x2 %0, %1, %2;" : "=r"(r) : "r"(a), "r"(b)); return r; }
__device__ __forceinline__ uint32_t hfma2(uint32_t a, uint32_t b, uint32_t c) { uint32_t r; asm("fma.rn.bf16x2 %0, %1, %2, %3;" : "=r"(r) : "r"(a), "r"(b), "r"(c)); return r; }
__device__ __forceinline__ float tanh_fast(float x) { float r; asm("tanh.approx.f32 %0, %1;" : "=f"(r) : "f"(x)); return r; }
__device__ __forceinline__ float rsq(float x) { float r; asm("rsqrt.approx.ftz.f32 %0, %1;" : "=f"(r) : "f"(x)); return r; }
__device__ __forceinline__ float ex2(float x) { float r; asm("ex2.approx.ftz.f32 %0, %1;" : "=f"(r) : "f"(x)); return r; }

__device__ __forceinline__ uint32_t ld_relaxed(const uint32_t* p) {
    uint32_t v;
    asm volatile("ld.relaxed.gpu.global.u32 %0, [%1];" : "=r"(v) : "l"(p) : "memory");
    return v;
}
__device__ __forceinline__ void flag_wait(const uint32_t* p, uint32_t e, uint32_t mask, uint32_t& seen) {
    if ((seen & mask) == mask) return;
    uint32_t a = ld_relaxed(p);
    const uint32_t t0 = clock();
    while (clock() - t0 < 200u) {}
#pragma unroll 1
    for (int i = 0; i < (1 << 19); i++) {
        const uint32_t b = ld_relaxed(p);
        seen = __ballot_sync(~0u, a == e);
        if ((seen & mask) == mask) break;
        a = ld_relaxed(p);
        seen = __ballot_sync(~0u, b == e);
        if ((seen & mask) == mask) break;
    }
    asm volatile("fence.acquire.gpu;" ::: "memory");
    fence_async_global();
}
__device__ __forceinline__ uint32_t ld_epoch() { return ld_relaxed(&g_epoch[blockIdx.x * FS]) + 1; }
__device__ __forceinline__ void flag_set(uint32_t* p, uint32_t e) { asm volatile("st.release.gpu.global.u32 [%0], %1;" ::"l"(p), "r"(e) : "memory"); }

__device__ __forceinline__ uint32_t desc_lo(uint32_t addr) { return ((addr & 0x3FFFF) >> 4) | 0x10000u; }
__device__ __forceinline__ uint64_t mkdesc(uint32_t lo) { return (uint64_t)lo | (0x40000040ull << 32); }
__device__ __forceinline__ void wg_fence() { asm volatile("wgmma.fence.sync.aligned;" ::: "memory"); }
__device__ __forceinline__ void wg_commit() { asm volatile("wgmma.commit_group.sync.aligned;" ::: "memory"); }
template <int N> __device__ __forceinline__ void wg_wait() { asm volatile("wgmma.wait_group.sync.aligned %0;" ::"n"(N) : "memory"); }
template <int N> __device__ __forceinline__ void pin(float (&d)[N]) {
#pragma unroll
    for (int i = 0; i < N; i++) asm volatile("" : "+f"(d[i])::"memory");
}
template <int N> __device__ __forceinline__ void pin(uint32_t (&d)[N]) {
#pragma unroll
    for (int i = 0; i < N; i++) asm volatile("" : "+r"(d[i])::"memory");
}

template <typename Tp, int N> __device__ __forceinline__ void zero(Tp (&d)[N]) {
#pragma unroll
    for (int i = 0; i < N; i++) d[i] = 0;
    pin(d);
}

#define F4(d, i) "+f"(d[i]), "+f"(d[i + 1]), "+f"(d[i + 2]), "+f"(d[i + 3])
#define F16(d, i) F4(d, i), F4(d, i + 4), F4(d, i + 8), F4(d, i + 12)

__device__ __forceinline__ void mma_sp(float (&d)[32], const uint32_t* a, uint64_t b, uint32_t meta, int acc) {
    asm volatile("{.reg .pred p; setp.ne.b32 p, %38, 0;\n"
                 "wgmma.mma_async.sp.sync.aligned.m64n64k32.f32.bf16.bf16 {%0,%1,%2,%3,%4,%5,%6,%7,%8,%9,%10,%11,%12,%13,%14,%15,%16,%17,%18,%19,%20,%21,%22,%23,%24,%25,%26,%27,%28,%29,%30,%31}, "
                 "{%32,%33,%34,%35}, %36, %37, 0, p, 1, 1, 1;}\n"
                 : F16(d, 0), F16(d, 16) : "r"(a[0]), "r"(a[1]), "r"(a[2]), "r"(a[3]), "l"(b), "r"(meta), "r"(acc));
}
__device__ __forceinline__ void mma_t(float (&d)[24], uint64_t a, uint64_t b, int acc) {
    asm volatile("{.reg .pred p; setp.ne.b32 p, %26, 0;\n"
                 "wgmma.mma_async.sync.aligned.m64n48k16.f32.bf16.bf16 {%0,%1,%2,%3,%4,%5,%6,%7,%8,%9,%10,%11,%12,%13,%14,%15,%16,%17,%18,%19,%20,%21,%22,%23}, %24, %25, p, 1, 1, 1, 0;}\n"
                 : F16(d, 0), F4(d, 16), F4(d, 20) : "l"(a), "l"(b), "r"(acc));
}
__device__ __forceinline__ void mma_qk(float (&d)[32], uint32_t a0, uint32_t a1, uint32_t a2, uint32_t a3, uint64_t b, int acc) {
    asm volatile("{.reg .pred p; setp.ne.b32 p, %37, 0;\n"
                 "wgmma.mma_async.sync.aligned.m64n64k16.f32.bf16.bf16 {%0,%1,%2,%3,%4,%5,%6,%7,%8,%9,%10,%11,%12,%13,%14,%15,%16,%17,%18,%19,%20,%21,%22,%23,%24,%25,%26,%27,%28,%29,%30,%31}, "
                 "{%32,%33,%34,%35}, %36, p, 1, 1, 0;}\n"
                 : F16(d, 0), F16(d, 16) : "r"(a0), "r"(a1), "r"(a2), "r"(a3), "l"(b), "r"(acc));
}
__device__ __forceinline__ void mma_pv(float (&d)[36], uint32_t a0, uint32_t a1, uint32_t a2, uint32_t a3, uint64_t b) {
    asm volatile("wgmma.mma_async.sync.aligned.m64n72k16.f32.bf16.bf16 {%0,%1,%2,%3,%4,%5,%6,%7,%8,%9,%10,%11,%12,%13,%14,%15,%16,%17,%18,%19,%20,%21,%22,%23,%24,%25,%26,%27,%28,%29,%30,%31,%32,%33,%34,%35}, "
                 "{%36,%37,%38,%39}, %40, 1, 1, 1, 1;\n"
                 : F16(d, 0), F16(d, 16), F4(d, 32) : "r"(a0), "r"(a1), "r"(a2), "r"(a3), "l"(b));
}

__device__ __forceinline__ uint32_t load_code(int n, int r, int w) {
    const int tile = 2 * r + w;
    int m, col, row;
    if (n < 16 || n >= 40) {
        const int k = n < 16 ? n : n - 40;
        m = n < 16 ? 0 : 6;
        if (k < 8) { col = 4 * tile + (k >> 1); row = (k & 1) ^ r; }
        else { m++; col = tile ^ (3 - ((k - 8) >> 1)); row = 2 * tile + (k & 1); }
    } else if (n < 32) {
        const int k = n - 16;
        m = 2;
        if (k < 4) { col = tile + ((k & 1) ? 0 : 4); row = (k >> 1) ^ r; }
        else { col = 8 + tile; row = (k & 1) ^ r; }
    } else if (n < 34) { m = 3; col = tile; row = n - 32; }
    else if (n < 38) { const int k = n - 34; m = 4; col = tile + 4 * (k & 1); row = (k >> 1) ^ r; }
    else { m = 5; col = tile; row = (n & 1) ^ r; }
    return m | (col << 4) | (row << 8);
}

__global__ void __cluster_dims__(2, 1, 1) __launch_bounds__(NTHREADS, 1)
conformer_kernel(const __grid_constant__ Params p) {
    extern __shared__ __align__(1024) unsigned char smem_raw[];
    const uint32_t sb = smem_u32(smem_raw);
    const uint32_t bars = sb + OFF_BARS;
    const int tid = threadIdx.x;
    const int lane = tid & 31;
    const int warp = __shfl_sync(~0u, tid >> 5, 0);
    const int r = blockIdx.x & 1;
    const int pair = blockIdx.x >> 1;
    const int b = pair >> 5, pt = pair & 31;
    const int ah = pt >> 3, qt = (pt & 7) * 2 + r;
    const int abh = b * 4 + ah;

    TG(30);
    TSINIT();
    TS(0);
    const uint32_t P = sb + OFF_P, H = sb + OFF_H;

    if (warp >= 8) {
        asm volatile("setmaxnreg.dec.sync.aligned.u32 48;");
        if (warp >= 12) {
            cluster_arrive();
            cluster_wait();
            if (warp == 12) {
                const uint32_t epoch = ld_epoch();
                bar_sync(11, 288);
                if (lane < 2) flag_set(&g_flag_v[((b * 4 + 2 * r + lane) * 32 + pt) * FS], epoch);
                __syncwarp();
                TS(13);
            }
            const int ut = tid & 127;
            const uint32_t a8 = P + (ut >> 3) * 128 + (ut & 7) * 16;
            float s[3] = {0.f, 0.f, 0.f}, q[3] = {0.f, 0.f, 0.f};
#pragma unroll 1
            for (int h = 0; h < 2; h++) {
                if (h == 0) bar_sync(1, 384);
                else mbar_wait(bars + B_X2 * 8, 0);
                uint4 v[6];
#pragma unroll
                for (int i = 0; i < 6; i++) v[i] = lds128(a8 + (2 * (r ^ h) + (i & 1)) * XCH + (i >> 1) * 2048);
                bar_arrive(5 + ((v[0].w | v[1].w | v[2].w | v[3].w | v[4].w | v[5].w) & p.zero), 384);
                uint32_t t;
                asm volatile("mov.u32 %0, %%clock;" : "=r"(t)::"memory");
                const uint32_t mul = 65536u + (t & p.zero), msk = 0u - mul;
#pragma unroll
                for (int i = 0; i < 6; i++) {
                    const float a0 = __uint_as_float(v[i].x * mul), a1 = __uint_as_float(v[i].x & msk), a2 = __uint_as_float(v[i].y * mul), a3 = __uint_as_float(v[i].y & msk);
                    const float a4 = __uint_as_float(v[i].z * mul), a5 = __uint_as_float(v[i].z & msk), a6 = __uint_as_float(v[i].w * mul), a7 = __uint_as_float(v[i].w & msk);
                    s[i >> 1] += ((a0 + a1) + (a2 + a3)) + ((a4 + a5) + (a6 + a7));
                    q[i >> 1] += fmaf(a0, a0, fmaf(a1, a1, fmaf(a2, a2, a3 * a3))) + fmaf(a4, a4, fmaf(a5, a5, fmaf(a6, a6, a7 * a7)));
                }
            }
#pragma unroll
            for (int o = 1; o < 8; o <<= 1) {
#pragma unroll
                for (int i = 0; i < 3; i++) { s[i] += __shfl_xor_sync(~0u, s[i], o); q[i] += __shfl_xor_sync(~0u, q[i], o); }
            }
            const int k = ut & 7, row = (ut >> 3) + 16 * k;
            const float mean = (k == 0 ? s[0] : (k == 1 ? s[1] : s[2])) * (1.f / 256.f);
            const float msq = (k == 0 ? q[0] : (k == 1 ? q[1] : q[2])) * (1.f / 256.f);
            const float alpha = (uint32_t)(pt * 32 - 8 + row) >= T_ ? 0.f : 0.5f;
            const float rstd = alpha * rsq(fmaxf(fmaf(-mean, mean, msq), 0.f) + 1e-5f);
            if (k < 3) sts64f(sb + OFF_STATS + row * 8, mean * rstd, rstd);
            __syncwarp();
            if (lane == 0) mbar_arrive(bars + B_ST * 8);
            TS(4);
        } else if (warp < 10) {
            const int w = warp - 8;
            const uint32_t ring = sb + OFF_RING + w * NSLOT * SLOT;
            const uint32_t full = bars + (B_FULL + w * NSLOT) * 8;
            if (lane == 0) {
#pragma unroll
                for (int i = 0; i < NSLOT; i++) { mbar_init(full + i * 8, 1); mbar_init(full + (B_EMPTY - B_FULL + i) * 8, 4); }
                asm volatile("fence.mbarrier_init.release.cluster;" ::: "memory");
                fence_async_smem();
            }
            __syncwarp();
            cluster_arrive();
            TS(1);
#pragma unroll
            for (int n = 0; n < NSLOT; n++) {
                if (n == 1 || n == 2) bar_sync(12, 64);
                ring_load(ring + n * SLOT, &p.tm[0], 64 * (8 * r + 4 * w + (n >> 1)), 8 * ((n & 1) ^ r), full + n * 8);
            }
            TS(2);
            const uint32_t code = load_code(lane, r, w) | (load_code(lane + 32, r, w) << 16);
            cluster_wait();
            uint32_t s = 0, ph = 0;
            int n = NSLOT;
#pragma unroll 1
            for (int seg = 0; seg < 2; seg++) {
#pragma unroll 1
                for (; n < (seg == 0 ? 22 : NLOADS); n++) {
                    const uint32_t c = __shfl_sync(~0u, code, n) >> (n & 32 ? 16 : 0);
                    const CUtensorMap* tm = &p.tm[c & 15];
                    const uint32_t col = (c & 0xf0) * 4, row = (c & 0xff00) >> 5, dst = ring + s * SLOT;
                    mbar_wait(full + (B_EMPTY - B_FULL) * 8 + s * 8, ph + (((uint32_t)(size_t)tm | col | row | dst) & p.zero));
                    ring_load(dst, tm, col, row, full + s * 8);
                    if (++s == NSLOT) { s = 0; ph ^= 1; }
                }
                if (seg == 1) break;
                const uint32_t epoch = ld_epoch();
                const uint32_t rdy = bars + (B_RDY + 3 * w) * 8, prdy = mapa(rdy, r ^ 1);
                const int isv = r ^ w;
                const uint32_t* flags = (isv ? g_flag_v : g_flag_kq) + (abh * 32 + lane) * FS;
                uint32_t seen = 0;
#pragma unroll 1
                for (; n < 32; n++) {
                    mbar_wait(full + (B_EMPTY - B_FULL) * 8 + s * 8, ph);
                    if (lane == 0) {
                        if (n < 24) mbar_arrive(full + s * 8);
                        else mbar_arrive_tx(full + s * 8, SLOT);
                    }
                    if (n == 28) {
                        if (lane == 0) mbar_arrive_peer(prdy);
                        mbar_wait(rdy, 0);
#pragma unroll 1
                        for (int i = 0; i < 3 - isv; i++) {
                            flag_wait(flags, epoch, 0xfu << (8 * i + 4 * w), seen);
                            if (i == 0) TSW(5 + 2 * isv);
                            if (i + isv == 1) mbar_wait(bars + B_QIN * 8, 0);
                            if (i + isv == 2) mbar_wait(full + isv * 8, 1);
                            const uint32_t sl = isv ? 2 * i + 1 : (i ? 2 * i - 2 : 4);
                            ring_load_both(ring + sl * SLOT, &p.tm[8], (isv * 64 + abh * 8 + 2 * i + w) * 128, full + sl * 8);
                        }
                    } else if (n > 28) {
                        const uint32_t bo = n == 31 ? 16 : 8;
                        if ((n > 29) == (isv == 1)) {
                            flag_wait(flags, epoch, ~0u, seen);
                            mbar_wait(rdy + bo, 0);
                            ring_load_both(ring + s * SLOT, &p.tm[8], (isv * 64 + abh * 8 + (n == 30 ? 4 : 6) + w) * 128, full + s * 8);
                        } else if (lane == 0) mbar_arrive_peer(prdy + bo);
                    }
                    __syncwarp();
                    if (++s == NSLOT) { s = 0; ph ^= 1; }
                }
            }
        } else if (warp == 10) {
            if (lane == 0) {
#pragma unroll
                for (int i = B_XA; i <= B_ST; i++) mbar_init(bars + i * 8, i == B_ST ? 4 : 1);
#pragma unroll
                for (int i = B_XA; i <= B_QIN; i++)
                    mbar_arrive_tx(bars + i * 8, i < B_XB ? 512 : ((i < B_X2 || i == B_SR || i == B_QIN) ? 8192 : 12288));
                asm volatile("fence.mbarrier_init.release.cluster;" ::: "memory");
                fence_async_smem();
            }
            __syncwarp();
            cluster_arrive();
            cluster_wait();
            const uint32_t epoch = ld_epoch();
            uint32_t seen = 0;
            const int np = min(max(pt - 1 + 2 * (lane & 1), 0), 31);
            const uint32_t* f = &g_flag_kq[((lane & 2) ? (b * 4 + 2 * r) * 32 + np : abh * 32 + 2 * qt + (lane & 1)) * FS];
            flag_wait(f, epoch, 3, seen);
            TSW(6);
            if (lane == 0) bulk_g2s(H + 24576, g_kvq + 2097152 + (size_t)(abh * 1024 + qt * 64) * 128, 8192, bars + B_QIN * 8);
            __syncwarp();
            flag_wait(f, epoch, 15, seen);
            if (lane == 0) mbar_arrive(bars + B_X1IN * 8);
            bar_sync(9, 64);
            const int q = min(max((pt >> 1) + ((lane & 4) ? ((pt & 1) ? 1 : -1) : 0), 0), 15);
            seen = 0;
            flag_wait(&g_flag_o[((b * 16 + q) * 4 + (lane & 3)) * FS], epoch, 0xff, seen);
            TSW(10);
            if (lane == 0) {
#pragma unroll
                for (int i = 0; i < 4; i++)
                    bulk_g2s(H + i * XCH, g_o + (size_t)((b * 4 + i) * PADROWS + pt * 32) * 128, XCH, bars + (B_OIN + (i >> 1)) * 8);
            }
            __syncwarp();
        } else {
            const uint32_t kb = (lane < 2 || lane > 5) ? 4096 : (lane == 2 ? 3072 : (lane == 4 ? 2048 : 1024));
            const char* pf = p.w[lane & 7] + blockIdx.x * kb;
            cluster_arrive();
            cluster_wait();
            if (lane < 2) prefetch_l2(pf, kb);
            mbar_wait(bars + B_XA * 8, 0);
            if (lane == 2) prefetch_l2(pf, kb);
            if (lane >= 1 && lane < 9) asm volatile("prefetch.tensormap [%0];" ::"l"(&p.tm[lane]) : "memory");
            mbar_wait(bars + (B_FULL + 1) * 8, 1);
            if (lane > 2 && lane < 8) prefetch_l2(pf, kb);
            const uint32_t epoch = ld_epoch();
            bar_sync(4, 288);
            if (lane < 2) flag_set(&g_flag_kq[((b * 4 + 2 * r + lane) * 32 + pt) * FS], epoch);
            __syncwarp();
            TSW(8);
            bar_sync(6, 288);
            bar_arrive(9, 64);
            if (lane == 0) {
                flag_set(&g_flag_o[((b * 16 + qt) * 4 + ah) * FS], epoch);
                g_epoch[blockIdx.x * FS] = epoch;
            }
            __syncwarp();
            TSW(9);
        }
        TSDUMP();
        return;
    }

    const int w = warp >> 2, wq = warp & 3;
    const int tile = 2 * r + w;
    const int wt = tid & 127;
    const int c4 = lane & 3;
    const int trow = pt * 32 + 8 * wq;
    uint32_t xr[8];
    {
        const uint32_t* xp = reinterpret_cast<const uint32_t*>(p.x + (size_t)(b * T_ + trow + (lane >> 2)) * 256 + tile * 64) + c4;
#pragma unroll
        for (int j = 0; j < 8; j++) xr[j] = trow < T_ ? __ldg(xp + 4 * j) : 0u;
    }
    cluster_arrive();
    asm volatile("setmaxnreg.inc.sync.aligned.u32 208;");
    const uint32_t rbase = sb + OFF_RING + w * NSLOT * SLOT, fbar = bars + (B_FULL + w * NSLOT) * 8;
    const uint32_t rdesc = desc_lo(rbase);
    auto acq = [&](int n) { mbar_wait(fbar + (n % NSLOT) * 8, (n / NSLOT) & 1); };
    auto rel = [&](int n) { if (lane == 0) mbar_arrive(fbar + (B_EMPTY - B_FULL + n % NSLOT) * 8); };
    const uint32_t foff = (lane & 7) * 128 + (((lane >> 3) ^ (lane & 7)) << 4);
    const uint32_t toff = ((lane >> 4) * 8 + (lane & 7)) * 128 + (((2 * wq + ((lane >> 3) & 1)) ^ (lane & 7)) << 4);
    auto publish = [&](int bar, uint32_t src, uint32_t bytes, int nsync) {
        fence_async_smem();
        bar_sync(2 + w, 128);
        if (wq == 0) peer_copy(mapa(src, r ^ 1), src, bytes, mapa(bars + bar * 8, r ^ 1));
        bar_sync(nsync == 384 ? 1 : 10, nsync);
    };
    float v[16];
#pragma unroll
    for (int j = 0; j < 8; j++) { v[2 * j] = blo(xr[j]); v[2 * j + 1] = bhi(xr[j]); }
    const uint32_t xown = __shfl_sync(~0u, P + wt * 16 + tile * 4096, lane), xrem = __shfl_sync(~0u, P + wt * 16 + (r ^ 1) * 8192, lane);
    const uint32_t sbuf = __shfl_sync(~0u, sb + OFF_MISC + 1024 + (8 * wq + (lane >> 2)) * 32, lane);
    const uint32_t sown = __shfl_sync(~0u, sbuf + tile * 8, lane);
    const uint32_t peer = __shfl_sync(~0u, mapa(sb, r ^ 1) - sb, lane);
    const uint32_t meta = __shfl_sync(~0u, 0xEEEE4444u + p.zero, lane);
    cluster_wait();
    TS(56);
    float mean, msq;

#pragma unroll 1
    for (int ph = 0;; ph++) {
        uint4 o0, o1;
        {
            float s = 0.f, q = 0.f, s2 = 0.f, q2 = 0.f;
#pragma unroll
            for (int j = 0; j < 4; j++) {
                s += v[4 * j] + v[4 * j + 1]; s2 += v[4 * j + 2] + v[4 * j + 3];
                q += fmaf(v[4 * j], v[4 * j], v[4 * j + 1] * v[4 * j + 1]); q2 += fmaf(v[4 * j + 2], v[4 * j + 2], v[4 * j + 3] * v[4 * j + 3]);
            }
            s += s2; q += q2;
            const uint32_t xa = bars + (B_XA + ph) * 8;
            s += __shfl_xor_sync(~0u, s, 1); q += __shfl_xor_sync(~0u, q, 1);
            s += __shfl_xor_sync(~0u, s, 2); q += __shfl_xor_sync(~0u, q, 2);
            if (c4 == 0) st_async2f(sown + peer, s, q, xa + peer);
            if (c4 == 0) sts64f(sown, s, q);
#pragma unroll
            for (int j = 0; j < 8; j++) xr[j] = pack2(v[2 * j], v[2 * j + 1]);
            sts128(xown, xr[0], xr[1], xr[2], xr[3]);
            sts128(xown + 2048, xr[4], xr[5], xr[6], xr[7]);
            bar_sync(10, 256);
            o0 = lds128(xown ^ 4096); o1 = lds128((xown ^ 4096) + 2048);
            if (ph < 3) {
                st_async4(xown + peer, xr[0], xr[1], xr[2], xr[3], xa + (B_XB - B_XA) * 8 + peer);
                st_async4(xown + peer + 2048, xr[4], xr[5], xr[6], xr[7], xa + (B_XB - B_XA) * 8 + peer);
            }
            TS(57 + ph);
            if (ph == 0) acq(0);
            mbar_wait(xa, 0);
            const float4 u0 = lds128f(sbuf), u1 = lds128f(sbuf + 16);
            mean = ((u0.x + u0.z) + (u1.x + u1.z)) * (1.f / 256.f);
            msq = ((u0.y + u0.w) + (u1.y + u1.w)) * (1.f / 256.f);
        }
        if (ph == 3) break;
        uint32_t a[32];
        const uint32_t mean2 = pack2(mean, mean);
        auto centre = [&](int i, const uint4& u) {
            a[i] = hsub2(u.x, mean2); a[i + 1] = hsub2(u.y, mean2); a[i + 2] = hsub2(u.z, mean2); a[i + 3] = hsub2(u.w, mean2);
        };
#pragma unroll
        for (int j = 0; j < 8; j++) a[j] = hsub2(xr[j], mean2);
        centre(8, o0); centre(12, o1);
        const float rstd = rsq(fmaxf(fmaf(-mean, mean, msq), 0.f) + 1e-5f);
        auto gather_peer = [&]() {
            mbar_wait(bars + (B_XB + ph) * 8, 0);
#pragma unroll
            for (int i = 0; i < 4; i++) centre(16 + 4 * i, lds128(xrem + i * 2048));
        };
        auto sp = [&](float (&d)[32], int n, const uint32_t* af, int flip, int acc) {
            const uint32_t lo = rdesc + p.zero * (ph + n + 1) + (n % NSLOT) * (SLOT >> 4);
            const uint64_t b0 = mkdesc(lo + flip * 512), b1 = mkdesc(lo + (flip ^ 1) * 512);
            wg_fence();
            mma_sp(d, af, b0, meta, acc);
            mma_sp(d, af + 4, b0 + 256, meta, 1);
            mma_sp(d, af + 8, b1, meta, 1);
            mma_sp(d, af + 12, b1 + 256, meta, 1);
            wg_commit();
        };
        float d0[32], d1[32];

        if (ph != 1) {
            uint32_t h[32];
            const float rs = 0.5f * rstd;
            const uint32_t inb = bars + (B_INB + ph) * 8, box = H + wt * 16;
            bool ready = true;
            auto step = [&](float (&d)[32], int n, const uint32_t* af, int flip, int acc, auto work) {
                if (!ready) acq(n);
                if (((TURN >> n) & 1) && w == 1) bar_sync(7, 256);
                sp(d, n, af, flip, acc);
                if (n > 0 && ((TURN >> (n - 1)) & 1) && w == 0) bar_arrive(7, 256);
                if (n < 15) ready = mbar_test(fbar + ((n + 1) % NSLOT) * 8, ((n + 1) / NSLOT) & 1);
                wg_wait<1>();
                if (n > 0 && !((EAGER >> (n - 1)) & 1)) rel(n - 1);
                const uint32_t tie = work() & p.zero;
                if ((EAGER >> n) & 1) {
                    if (p.zero < n + ph + 1) wg_wait<0>();
                    if (lane == 0) mbar_arrive(fbar + (B_EMPTY - B_FULL + n % NSLOT) * 8 + tie);
                }
            };
            auto none = []() { return 0u; };
            auto act = [&](float (&d)[32], int i) {
                pin(d);
#pragma unroll
                for (int j = 0; j < 8; j++) {
                    const float u0 = (d[4 * j] + d[4 * j + 2]) * rs, u1 = (d[4 * j + 1] + d[4 * j + 3]) * rs;
                    h[8 * i + j] = pack2(fmaf(u0, tanh_fast(u0), u0), fmaf(u1, tanh_fast(u1), u1));
                }
                return h[8 * i] | h[8 * i + 1] | h[8 * i + 2] | h[8 * i + 3] | h[8 * i + 4] | h[8 * i + 5] | h[8 * i + 6] | h[8 * i + 7];
            };
            auto send = [&](float (&d)[32], int x) {
                pin(d);
                uint32_t pk[8];
#pragma unroll
                for (int j = 0; j < 8; j++) pk[j] = pack2(d[4 * j] + d[4 * j + 2], d[4 * j + 1] + d[4 * j + 3]);
                const uint32_t ow = w ^ (x & 1), dst = box + (ow * 3 + x - 1) * 4096;
                if (x & 2) {
                    st_async4(dst + peer, pk[0], pk[1], pk[2], pk[3], inb + ow * 8 + peer);
                    st_async4(dst + peer + 2048, pk[4], pk[5], pk[6], pk[7], inb + ow * 8 + peer);
                } else {
                    sts128(dst, pk[0], pk[1], pk[2], pk[3]);
                    sts128(dst + 2048, pk[4], pk[5], pk[6], pk[7]);
                }
            };
            TS(1 + ph * 10);
            step(d0, 0, a, w, 0, [&]() { gather_peer(); return 0u; });
            TS(32);
            step(d0, 1, a + 16, 0, 1, none);
            step(d1, 2, a, w, 0, [&]() { return act(d0, 0); });
            step(d1, 3, a + 16, 0, 1, none);
            step(d0, 4, a, w, 0, [&]() { return act(d1, 1); });
            TS(33);
            step(d0, 5, a + 16, 0, 1, none);
            step(d1, 6, a, w, 0, [&]() { return act(d0, 2); });
            step(d1, 7, a + 16, 0, 1, none);
            step(d0, 8, h, 0, 0, [&]() { return act(d1, 3); });
            TS(2 + ph * 10);
            step(d0, 9, h + 16, 0, 1, none);
            step(d1, 10, h, 0, 0, [&]() { send(d0, 3); return 0u; });
            step(d1, 11, h + 16, 0, 1, none);
            step(d0, 12, h, 0, 0, [&]() { send(d1, 2); return 0u; });
            TS(34);
            step(d0, 13, h + 16, 0, 1, none);
            step(d1, 14, h, 0, 0, [&]() { send(d0, 1); return 0u; });
            step(d1, 15, h + 16, 0, 1, none);
            if (ph == 0) acq(16);
            mbar_wait(inb + w * 8, 0);
            bar_sync(10, 256);
#pragma unroll
            for (int i = 0; i < 2; i++) {
                const uint32_t src = box + w * 12288 + i * 2048;
                const uint4 u0 = lds128(src), u1 = lds128(src + 4096), u2 = lds128(src + 8192);
                const uint32_t p0[4] = {u0.x, u0.y, u0.z, u0.w}, p1[4] = {u1.x, u1.y, u1.z, u1.w}, p2[4] = {u2.x, u2.y, u2.z, u2.w};
#pragma unroll
                for (int j = 0; j < 4; j++) {
                    v[8 * i + 2 * j] = fmaf(0.5f, blo(p0[j]) + blo(p1[j]) + blo(p2[j]), blo(xr[4 * i + j]));
                    v[8 * i + 2 * j + 1] = fmaf(0.5f, bhi(p0[j]) + bhi(p1[j]) + bhi(p2[j]), bhi(xr[4 * i + j]));
                }
            }
            wg_wait<0>();
            pin(d1);
            rel(15);
            TS(3 + ph * 10);
#pragma unroll
            for (int j = 0; j < 8; j++) {
                v[2 * j] = fmaf(0.5f, d1[4 * j] + d1[4 * j + 2], v[2 * j]);
                v[2 * j + 1] = fmaf(0.5f, d1[4 * j + 1] + d1[4 * j + 3], v[2 * j + 1]);
            }
            continue;
        }

        {
            TS(11);
            sp(d0, 16, a, w, 0);
            acq(17);
            sp(d1, 17, a, w, 0);
            if (wq == 0 || wq == 3) {
                uint4* hp = &g_halo[((pair * 4 + tile) * 2 + (wq & 1)) * 64 + lane];
                hp[0] = make_uint4(xr[0], xr[1], xr[2], xr[3]);
                hp[32] = make_uint4(xr[4], xr[5], xr[6], xr[7]);
            }
            gather_peer();
            acq(18);
            sp(d0, 18, a + 16, 0, 1);
            wg_wait<1>();
            rel(16); rel(17);
            acq(19);
            sp(d1, 19, a + 16, 0, 1);
            const uint32_t stg = H + warp * 3072;
            unsigned char* g = g_kvq + (size_t)((b * 4 + tile) * 1024 + trow) * 128 + lane * 16;
            auto put = [&](float (&d)[32], int i) {
                pin(d);
                uint32_t pk[8];
#pragma unroll
                for (int j = 0; j < 8; j++) pk[j] = pack2((d[4 * j] + d[4 * j + 2]) * rstd, (d[4 * j + 1] + d[4 * j + 3]) * rstd);
                stsm4(stg + i * 1024 + foff, pk[0], pk[1], pk[2], pk[3]);
                stsm4(stg + i * 1024 + (foff ^ 64), pk[4], pk[5], pk[6], pk[7]);
                __syncwarp();
                const uint4 u0 = lds128(stg + i * 1024 + lane * 16), u1 = lds128(stg + i * 1024 + 512 + lane * 16);
                stg128(g + i * 1048576, u0); stg128(g + i * 1048576 + 512, u1);
            };
            wg_wait<1>();
            rel(18);
            put(d0, 0);
            wg_wait<0>();
            rel(19);
            TS(37);
            put(d1, 2);
            bar_arrive(4, 288);
            TS(38);
            acq(20);
            sp(d0, 20, a, w, 0);
            acq(21);
            sp(d0, 21, a + 16, 0, 1);
            wg_wait<0>();
            rel(20); rel(21);
            put(d0, 1);
            bar_arrive(11, 288);
            acq(22); acq(23);
            rel(22); rel(23);
            TS(12);
        }

        {
            constexpr float CS = 0.125f * 1.4426950408889634f;
            float sa[32], sb2[32], o[36];
            uint32_t pa[16], pb[16], q[16];
            float n0 = INFINITY, n1 = INFINITY;
            zero(o); zero(pa); zero(pb);
            const uint32_t ones = sb + OFF_MISC + 2048;
            if (tid < 128) sts128(ones + tid * 16, 0x3F803F80u, 0x3F803F80u, 0x3F803F80u, 0x3F803F80u);
            fence_async_smem();
            bar_sync(10, 256);
            const uint32_t vdesc = rdesc + ((((ones - rbase) >> 4) - 1) << 16);
            auto qk_issue = [&](float (&s)[32], uint32_t lo) {
                const uint64_t kd = mkdesc(lo);
                wg_fence();
#pragma unroll
                for (int k = 0; k < 4; k++) mma_qk(s, q[4 * k], q[4 * k + 1], q[4 * k + 2], q[4 * k + 3], kd + 2 * k, k != 0);
                wg_commit();
            };
            auto pv_issue = [&](uint32_t (&pp)[16], uint32_t lo) {
                const uint64_t vd = mkdesc(lo);
                wg_fence();
#pragma unroll
                for (int k = 0; k < 4; k++) mma_pv(o, pp[4 * k], pp[4 * k + 1], pp[4 * k + 2], pp[4 * k + 3], vd - k * (128 * 65535));
                wg_commit();
            };
            auto new_max = [&](float (&s)[32], float& x0, float& x1) {
                x0 = s[0]; x1 = s[2];
#pragma unroll
                for (int j = 0; j < 8; j++) {
                    x0 = fmaxf(x0, fmaxf(s[4 * j], s[4 * j + 1]));
                    x1 = fmaxf(x1, fmaxf(s[4 * j + 2], s[4 * j + 3]));
                }
                x0 = fmaxf(x0, __shfl_xor_sync(~0u, x0, 1)); x1 = fmaxf(x1, __shfl_xor_sync(~0u, x1, 1));
                x0 = fmaxf(x0, __shfl_xor_sync(~0u, x0, 2)); x1 = fmaxf(x1, __shfl_xor_sync(~0u, x1, 2));
                x0 = fminf(n0, fmaf(x0, -CS, -20.f)); x1 = fminf(n1, fmaf(x1, -CS, -20.f));
            };
            auto probs = [&](float (&s)[32], uint32_t (&pp)[16], bool ready, auto wait) {
                uint32_t any = 0;
#pragma unroll
                for (int i = 0; i < 16; i++) {
                    pp[i] = pack2(ex2(fmaf(s[2 * i], CS, (i & 1) ? n1 : n0)), ex2(fmaf(s[2 * i + 1], CS, (i & 1) ? n1 : n0)));
                    any |= pp[i];
                }
                float sc0 = 1.f, sc1 = 1.f;
                const bool slow = __any_sync(~0u, (any & 0x40004000u) || !ready);
                if (slow) {
                    wait();
                    if (__any_sync(~0u, any & 0x40004000u)) {
                        float x0, x1;
                        new_max(s, x0, x1);
                        sc0 = ex2(x0 - n0); sc1 = ex2(x1 - n1);
                        n0 = x0; n1 = x1;
#pragma unroll
                        for (int i = 0; i < 16; i++)
                            pp[i] = pack2(ex2(fmaf(s[2 * i], CS, (i & 1) ? n1 : n0)), ex2(fmaf(s[2 * i + 1], CS, (i & 1) ? n1 : n0)));
                    }
                }
                wg_wait<0>();
                pin(sa); pin(sb2); pin(o); pin(pa); pin(pb);
                if (slow) {
#pragma unroll
                    for (int j = 0; j < 9; j++) { o[4 * j] *= sc0; o[4 * j + 1] *= sc0; o[4 * j + 2] *= sc1; o[4 * j + 3] *= sc1; }
                }
            };
            mbar_wait(bars + B_QIN * 8, 0);
            {
                const uint32_t qa = H + 24576 + (wq * 16 + (lane & 15)) * 128;
#pragma unroll
                for (int k = 0; k < 4; k++) ldsm4(qa + (((2 * k + (lane >> 4)) ^ (lane & 7)) << 4), q[4 * k], q[4 * k + 1], q[4 * k + 2], q[4 * k + 3]);
                pin(q);
            }
            TS(40);
            acq(24);
            TS(13);
            qk_issue(sa, rdesc + (24 % NSLOT) * (SLOT >> 4));
            qk_issue(sb2, rdesc + (24 % NSLOT) * (SLOT >> 4) + 512);
            wg_wait<1>();
            pin(sa);
            {
                float x0, x1;
                new_max(sa, x0, x1);
                n0 = x0; n1 = x1;
            }
            if (w == 1) bar_sync(7, 256);
            uint32_t vd = vdesc - (SLOT >> 4) * 65535u, kd = rdesc, vb = fbar + 8, kb = fbar;
            uint32_t vlast = vdesc - 4 * (SLOT >> 4) * 65535u;
            uint32_t kprev = fbar + 32, vprev = bars + (B_SINK - (B_EMPTY - B_FULL)) * 8;
#pragma unroll 1
            for (int it = 0; it < 4; it++) {
                pv_issue(pb, vlast);
                probs(sa, pa, mbar_test(vb, it < 2) & mbar_test(kb, it < 3), [&]() { mbar_wait(vb, it < 2); mbar_wait(kb, it < 3); });
                TS(41 + it * 4);
                if (it == 0 && w == 0) bar_arrive(7, 256);
                if (it == 3 && w == 1) {
#pragma unroll
                    for (int i = 20; i < 32; i++) sb2[i] = -INFINITY;
                }
                pin(sb2);
                if (it < 3) qk_issue(sa, kd);
                if (lane == 0) mbar_arrive(kprev + (B_EMPTY - B_FULL) * 8);
                if (lane == 0) mbar_arrive(vprev + (B_EMPTY - B_FULL) * 8);
                pv_issue(pa, vd);
                probs(sb2, pb, true, []() {});
                TS(43 + it * 4);
                if (it < 3) qk_issue(sb2, kd + 512);
                const int dv = it == 0 ? 2 : (it == 1 ? -3 : 1);
                kprev = kb; vprev = vb; vlast = vd - 512 * 65535u;
                vd -= dv * (SLOT >> 4) * 65535u; vb += dv * 8;
                kd += 2 * (SLOT >> 4); kb = it == 2 ? vb : kb + 16;
            }
            pv_issue(pb, vlast);
            const int row = wq * 16 + (lane >> 2);
            const uint32_t ml = sb + OFF_MISC;
            wg_wait<0>();
            pin(o); pin(pb); pin(sa); pin(sb2);
            rel(31);
            const float l0 = o[32], l1 = o[34];
            if (c4 == 0) { sts64f(ml + w * 512 + row * 8, n0, l0); sts64f(ml + w * 512 + row * 8 + 64, n1, l1); }
            TS(14);
            float mine[16];
#pragma unroll
            for (int j = 0; j < 4; j++) {
                if (w == 0) sts128f(H + j * 2048 + wt * 16, o[16 + 4 * j], o[17 + 4 * j], o[18 + 4 * j], o[19 + 4 * j]);
                else sts128f(H + 8192 + j * 2048 + wt * 16, o[4 * j], o[4 * j + 1], o[4 * j + 2], o[4 * j + 3]);
            }
#pragma unroll
            for (int i = 0; i < 16; i++) mine[i] = w == 0 ? o[i] : o[16 + i];
            bar_sync(10, 256);
            const float2 u0 = lds64f(ml + (w ^ 1) * 512 + row * 8), u1 = lds64f(ml + (w ^ 1) * 512 + row * 8 + 64);
            const float x0 = fminf(n0, u0.x), x1 = fminf(n1, u1.x);
            float a0 = ex2(x0 - n0), b0 = ex2(x0 - u0.x), a1 = ex2(x1 - n1), b1 = ex2(x1 - u1.x);
            const float i0 = __fdividef(1.f, fmaf(a0, l0, b0 * u0.y)), i1 = __fdividef(1.f, fmaf(a1, l1, b1 * u1.y));
            a0 *= i0; b0 *= i0; a1 *= i1; b1 *= i1;
            uint32_t pk[8];
#pragma unroll
            for (int j = 0; j < 4; j++) {
                const float4 v = lds128f(H + (w ^ 1) * 8192 + j * 2048 + wt * 16);
                pk[2 * j] = pack2(fmaf(a0, mine[4 * j], b0 * v.x), fmaf(a0, mine[4 * j + 1], b0 * v.y));
                pk[2 * j + 1] = pack2(fmaf(a1, mine[4 * j + 2], b1 * v.z), fmaf(a1, mine[4 * j + 3], b1 * v.w));
            }
            const uint32_t og = H + 16384 + wq * 2048;
            {
                const uint32_t ra = og + (((lane >> 3) & 1) * 8 + (lane & 7)) * 128;
                stsm4(ra + (((4 * w + (lane >> 4)) ^ (lane & 7)) << 4), pk[0], pk[1], pk[2], pk[3]);
                stsm4(ra + (((4 * w + 2 + (lane >> 4)) ^ (lane & 7)) << 4), pk[4], pk[5], pk[6], pk[7]);
            }
            __syncwarp();
            {
                const uint32_t off = (lane >> 2) * 128 + (((4 * w + c4) ^ (lane >> 2)) << 4);
                const uint4 v0 = lds128(og + off), v1 = lds128(og + off + 1024);
                unsigned char* dst = g_o + (size_t)(abh * PADROWS + 8 + qt * 64 + wq * 16) * 128 + off;
                stg128(dst, v0); stg128(dst + 1024, v1);
            }
            bar_arrive(6, 288);
            TS(15);
        }

        auto mm = [&](float (&d)[24], int n, uint32_t act, int acc) {
            const uint32_t z = p.zero * (ph + n);
            const uint64_t ad = mkdesc(rdesc + z + (n % NSLOT) * (SLOT >> 4)), bd = mkdesc(desc_lo(act) + z);
            wg_fence();
#pragma unroll
            for (int k = 0; k < 8; k++) mma_t(d, ad + k * 128, bd + (k >> 2) * (XCH >> 4) + (k & 3) * 2, k == 0 ? acc : 1);
            wg_commit();
        };
        const uint32_t xo = P + tile * XCH + wq * 1024, xt = P + tile * XCH + toff;
        uint32_t dwr[15];
        {
#pragma unroll
            for (int i = 0; i < 15; i++) dwr[i] = hmul2(__ldg(reinterpret_cast<const uint32_t*>(p.dw + i * 256 + tile * 64) + lane), 0x3F003F00u);
            float d[24];
            uint32_t xw[12];
            stsm4(xo + 1024 + foff, xr[0], xr[1], xr[2], xr[3]);
            stsm4(xo + 1024 + (foff ^ 64), xr[4], xr[5], xr[6], xr[7]);
            mbar_wait(bars + B_X1IN * 8, 0);
            if (wq == 0 || wq == 3) {
                uint4 h0 = make_uint4(0, 0, 0, 0), h1 = h0;
                const int np = wq ? pt + 1 : pt - 1;
                if (np >= 0 && np < 32) {
                    const uint4* hp = &g_halo[(((b * 32 + np) * 4 + tile) * 2 + (wq ? 0 : 1)) * 64 + lane];
                    h0 = __ldcg(hp); h1 = __ldcg(hp + 32);
                }
                stsm4(xo + (wq ? 2048 : 0) + foff, h0.x, h0.y, h0.z, h0.w);
                stsm4(xo + (wq ? 2048 : 0) + (foff ^ 64), h1.x, h1.y, h1.z, h1.w);
            }
            bar_sync(2 + w, 128);
#pragma unroll
            for (int j = 0; j < 3; j++) ldsm4t(xt + j * 2048, xw[4 * j], xw[4 * j + 1], xw[4 * j + 2], xw[4 * j + 3]);
            pin(xw);
            pin(dwr);
            acq(32); acq(33); acq(34); acq(35);
            mbar_wait(bars + B_OIN * 8, 0);
            TS(16);
            mm(d, 32, H, 0);
            mbar_wait(bars + B_OIN * 8 + 8, 0);
            mm(d, 33, H + 2 * XCH, 1);
            wg_wait<1>();
            rel(32);
            wg_wait<0>();
            pin(d);
#pragma unroll
            for (int i = 0; i < 12; i++) xw[i] = pack2(d[2 * i] + blo(xw[i]), d[2 * i + 1] + bhi(xw[i]));
            if (c4 == 0) { xw[0] = (xw[0] & 0xffff0000u) | 0x3F80u; xw[1] = (xw[1] & 0xffff0000u) | 0x3F80u; }
#pragma unroll
            for (int j = 0; j < 3; j++) stsm4t(xt + j * 2048, xw[4 * j], xw[4 * j + 1], xw[4 * j + 2], xw[4 * j + 3]);
            rel(33);
            publish(B_X2, P + tile * XCH, XCH, 384);
            TS(17);
        }
        {
            float da[24], db[24], st[24];
            bar_sync(5, 384);
            mm(da, 34, P + 2 * r * XCH, 0);
            mm(db, 35, P + 2 * r * XCH, 0);
            acq(36); acq(37);
            mbar_wait(bars + B_X2 * 8, 0);
            bar_sync(5, 384);
            TS(39);
            mm(da, 36, P + 2 * (r ^ 1) * XCH, 1);
            mm(db, 37, P + 2 * (r ^ 1) * XCH, 1);
            wg_wait<2>();
            rel(34); rel(35);
            mbar_wait(bars + B_ST * 8, 0);
#pragma unroll
            for (int j = 0; j < 6; j++) {
                const float4 u = lds128f(sb + OFF_STATS + (8 * j + 2 * c4) * 8);
                st[4 * j] = u.x; st[4 * j + 1] = u.y; st[4 * j + 2] = u.z; st[4 * j + 3] = u.w;
            }
            wg_wait<0>();
            pin(da); pin(db);
            rel(36); rel(37);
            TS(18);
            uint32_t pk[12];
#pragma unroll
            for (int hh = 0; hh < 2; hh++) {
                const float ca = __shfl_sync(~0u, da[2 * hh], lane & 28), cb = __shfl_sync(~0u, db[2 * hh], lane & 28);
#pragma unroll
                for (int j = 0; j < 6; j++) {
                    const float u0 = fmaf(-st[4 * j], ca, da[4 * j + 2 * hh] * st[4 * j + 1]);
                    const float u1 = fmaf(-st[4 * j + 2], ca, da[4 * j + 2 * hh + 1] * st[4 * j + 3]);
                    const float v0 = fmaf(-st[4 * j], cb, db[4 * j + 2 * hh] * st[4 * j + 1]);
                    const float v1 = fmaf(-st[4 * j + 2], cb, db[4 * j + 2 * hh + 1] * st[4 * j + 3]);
                    pk[2 * j + hh] = pack2(fmaf(u0, tanh_fast(v0), u0), fmaf(u1, tanh_fast(v1), u1));
                }
            }
            const uint32_t gs = H + 16384 + w * XCH;
#pragma unroll
            for (int j = 0; j < 3; j++) stsm4t(gs + toff + j * 2048, pk[4 * j], pk[4 * j + 1], pk[4 * j + 2], pk[4 * j + 3]);
            ldsm4(xo + 1024 + foff, xr[0], xr[1], xr[2], xr[3]);
            ldsm4(xo + 1024 + (foff ^ 64), xr[4], xr[5], xr[6], xr[7]);
            bar_sync(2 + w, 128);
            uint32_t ca[8], cb[8];
            const uint32_t grow = gs + 8 * wq * 128 + c4 * 4, srow = H + tile * HCH + 8 * wq * 128 + c4 * 4;
#pragma unroll
            for (int k = 0; k < 22; k++) {
                const uint32_t v = lds32(grow + (1 + k) * 128 + (((lane >> 2) ^ ((1 + k) & 7)) << 4));
#pragma unroll
                for (int i = 0; i < 8; i++) {
                    const int tap = k - i;
                    if (tap == 0) ca[i] = hmul2(v, dwr[0]);
                    else if (tap > 0 && tap < 8) ca[i] = hfma2(v, dwr[tap], ca[i]);
                    else if (tap == 8) cb[i] = hmul2(v, dwr[8]);
                    else if (tap > 8 && tap < 15) cb[i] = hfma2(v, dwr[tap], cb[i]);
                }
            }
#pragma unroll
            for (int i = 0; i < 8; i++) {
                const float h0 = blo(ca[i]) + blo(cb[i]), h1 = bhi(ca[i]) + bhi(cb[i]);
                sts32(srow + i * 128 + (((lane >> 2) ^ i) << 4), pack2(fmaf(h0, tanh_fast(h0), h0), fmaf(h1, tanh_fast(h1), h1)));
            }
            acq(38); acq(39);
            publish(B_SR, H + tile * HCH, HCH, 256);
            TS(19);
        }
        {
            auto frags = [&](int i, int half) {
                const uint32_t src = H + 2 * half * HCH + wq * 1024;
#pragma unroll
                for (int k = 0; k < 4; k++) ldsm4(src + (k >> 1) * HCH + (foff ^ ((k & 1) * 64)), a[i + 4 * k], a[i + 4 * k + 1], a[i + 4 * k + 2], a[i + 4 * k + 3]);
            };
            frags(0, r);
            sp(d0, 38, a, 0, 0);
            acq(40);
            mbar_wait(bars + B_SR * 8, 0);
            frags(16, r ^ 1);
            sp(d0, 39, a + 16, 0, 1);
            wg_wait<1>();
            rel(38);
            wg_wait<0>();
            pin(d0);
            rel(39);
#pragma unroll
            for (int j = 0; j < 8; j++) {
                v[2 * j] = d0[4 * j] + d0[4 * j + 2] + blo(xr[j]);
                v[2 * j + 1] = d0[4 * j + 1] + d0[4 * j + 3] + bhi(xr[j]);
            }
            TS(20);
        }
    }

    cluster_arrive();
    TS(24);
    {
        const float rstd = rsq(fmaxf(fmaf(-mean, mean, msq), 0.f) + 1e-5f), nb = -mean * rstd;
#pragma unroll
        for (int j = 0; j < 8; j++) xr[j] = pack2(fmaf(v[2 * j], rstd, nb), fmaf(v[2 * j + 1], rstd, nb));
        const uint32_t stg = P + 16384 + warp * 1024;
        stsm4(stg + foff, xr[0], xr[1], xr[2], xr[3]);
        stsm4(stg + (foff ^ 64), xr[4], xr[5], xr[6], xr[7]);
        __syncwarp();
        const uint32_t src = stg + (lane >> 3) * 128 + (((lane & 7) ^ (lane >> 3)) << 4);
        const uint4 u0 = lds128(src), u1 = lds128((src + 512) ^ 64);
        __nv_bfloat16* dst = p.out + (size_t)(b * T_ + trow + (lane >> 3)) * 256 + tile * 64 + (lane & 7) * 8;
        if (trow < T_) { stg128(dst, u0); stg128(dst + 4 * 256, u1); }
    }
    TS(25);
    TG(31);
    TSDUMP();
    cluster_wait();
}

typedef CUresult (*EncodeFn)(CUtensorMap*, CUtensorMapDataType, cuuint32_t, void*, const cuuint64_t*, const cuuint64_t*,
                             const cuuint32_t*, const cuuint32_t*, CUtensorMapInterleave, CUtensorMapSwizzle,
                             CUtensorMapL2promotion, CUtensorMapFloatOOBfill);

}

extern "C" void kernel_launch(void* const* d_in, const int* in_sizes, int n_in, void* d_out, int out_size) {
    static EncodeFn encode = nullptr;
    if (!encode) {
        void* fn = nullptr;
        cudaDriverEntryPointQueryResult qr;
        cudaGetDriverEntryPoint("cuTensorMapEncodeTiled", &fn, cudaEnableDefault, &qr);
        encode = (EncodeFn)fn;
        cudaFuncSetAttribute(conformer_kernel, cudaFuncAttributeMaxDynamicSharedMemorySize, SMEM_LAUNCH);
    }
    Params p;
    const cuuint32_t ones[5] = {1, 1, 1, 1, 1};
    const int idx[8] = {1, 2, 3, 4, 5, 7, 8, 9};
    const int rows[8] = {256, 1024, 256, 256, 256, 256, 256, 1024};
    const int cols[8] = {1024, 256, 768, 256, 512, 256, 1024, 256};
    for (int i = 0; i < 8; i++) {
        const bool perm = i != 3 && i != 4;
        const cuuint64_t pitch = (cuuint64_t)cols[i] * 2;
        const cuuint64_t dims[5] = {(cuuint64_t)cols[i], 2, 2, 4, (cuuint64_t)rows[i] / 16};
        const cuuint64_t strides[4] = {pitch, pitch * (perm ? 8 : 2), pitch * (perm ? 2 : 4), pitch * 16};
        const cuuint32_t box[5] = {64, 2, 2, 4, 8};
        encode(&p.tm[i], CU_TENSOR_MAP_DATA_TYPE_BFLOAT16, 5, d_in[idx[i]], dims, strides, box, ones, CU_TENSOR_MAP_INTERLEAVE_NONE,
               CU_TENSOR_MAP_SWIZZLE_128B, CU_TENSOR_MAP_L2_PROMOTION_L2_128B, CU_TENSOR_MAP_FLOAT_OOB_FILL_NONE);
        p.w[i] = (const char*)d_in[idx[i]];
    }
    {
        void* kv = nullptr;
        cudaGetSymbolAddress(&kv, g_kvq);
        const cuuint64_t dims[2] = {64, 16384};
        const cuuint64_t strides[1] = {128};
        const cuuint32_t box[2] = {64, 128};
        encode(&p.tm[8], CU_TENSOR_MAP_DATA_TYPE_BFLOAT16, 2, kv, dims, strides, box, ones, CU_TENSOR_MAP_INTERLEAVE_NONE,
               CU_TENSOR_MAP_SWIZZLE_NONE, CU_TENSOR_MAP_L2_PROMOTION_L2_128B, CU_TENSOR_MAP_FLOAT_OOB_FILL_NONE);
    }
    p.x = (const __nv_bfloat16*)d_in[0];
    p.dw = (const __nv_bfloat16*)d_in[6];
    p.out = (__nv_bfloat16*)d_out;
    p.zero = 0;
    conformer_kernel<<<NCTA, NTHREADS, SMEM_LAUNCH>>>(p);
}
```

```cpp
#include <cuda_runtime.h>
#include <cuda_bf16.h>
#include <cuda.h>
#include <stdint.h>

namespace {

constexpr int T_ = 1000;
constexpr int NCTA = 128;
constexpr int NTHREADS = 512;
constexpr int NSLOT = 5;
constexpr int SLOT = 16384;
constexpr int NLOADS = 56;

constexpr uint32_t OFF_RING = 0;
constexpr uint32_t OFF_P = 163840;
constexpr uint32_t OFF_H = 188416;
constexpr uint32_t OFF_MISC = 221184;
constexpr uint32_t OFF_STATS = 229376;
constexpr uint32_t OFF_BARS = 229888;
constexpr uint32_t SMEM_BYTES = 230400;
constexpr uint32_t XCH = 6144;
constexpr uint32_t HCH = 4096;

constexpr int B_FULL = 0, B_EMPTY = 10, B_XA = 20  , B_XB = 24  , B_INB = 27  , B_X2 = 31, B_SR = 32, B_OIN = 33  ,
              B_QIN = 35, B_X1IN = 36, B_RDY = 37  , B_SINK = 43, B_ST = 44;

#define TURN 0
#define EAGER 0x5555
constexpr int PADROWS = 1040;
constexpr int FS = 8;

struct Params {
    CUtensorMap tm[9];
    const char* w[8];
    const __nv_bfloat16* x;
    const __nv_bfloat16* dw;
    __nv_bfloat16* out;
    uint32_t zero;
};

__device__ __align__(1024) unsigned char g_kvq[3 * 8 * 1024 * 128];
__device__ __align__(1024) unsigned char g_o[8 * PADROWS * 128];
__device__ uint4 g_halo[64 * 4 * 2 * 64];
__device__ uint32_t g_flag_kq[8 * 32 * FS];
__device__ uint32_t g_flag_v[8 * 32 * FS];
__device__ uint32_t g_flag_o[2 * 16 * 4 * FS];
__device__ uint32_t g_epoch[NCTA * FS];

#define TS(i) do { } while (0)
#define TSW(i) do { } while (0)
#define TG(i) do { } while (0)
#define TSINIT() do { } while (0)
#define TSDUMP() do { } while (0)
constexpr uint32_t SMEM_LAUNCH = SMEM_BYTES;

__device__ __forceinline__ uint32_t smem_u32(const void* p) { return (uint32_t)__cvta_generic_to_shared(p); }
__device__ __forceinline__ void mbar_init(uint32_t b, uint32_t c) { asm volatile("mbarrier.init.shared::cta.b64 [%0], %1;" ::"r"(b), "r"(c) : "memory"); }
__device__ __forceinline__ void mbar_arrive(uint32_t b) { asm volatile("mbarrier.arrive.shared::cta.b64 _, [%0];" ::"r"(b) : "memory"); }
__device__ __forceinline__ void mbar_arrive_tx(uint32_t b, uint32_t tx) { asm volatile("mbarrier.arrive.expect_tx.shared::cta.b64 _, [%0], %1;" ::"r"(b), "r"(tx) : "memory"); }
__device__ __forceinline__ void mbar_wait(uint32_t b, uint32_t ph) {
    asm volatile("{\n.reg .pred p, q;\n.reg .u32 c;\nmov.u32 c, 0;\n"
                 "MW_LOOP:\n.pragma \"nounroll\";\n"
                 "mbarrier.try_wait.parity.shared::cta.b64 p, [%0], %1;\n"
                 "add.u32 c, c, 1;\nsetp.lt.u32 q, c, 65536;\nnot.pred p, p;\nand.pred p, p, q;\n@p bra MW_LOOP;\n}"
                 ::"r"(b), "r"(ph) : "memory");
}
__device__ __forceinline__ bool mbar_test(uint32_t b, uint32_t ph) {
    uint32_t ok;
    asm volatile("{\n.reg .pred p;\nmbarrier.test_wait.parity.shared::cta.b64 p, [%1], %2;\nselp.u32 %0, 1, 0, p;\n}" : "=r"(ok) : "r"(b), "r"(ph) : "memory");
    return ok;
}
__device__ __forceinline__ uint32_t mapa(uint32_t a, uint32_t r) { uint32_t o; asm("mapa.shared::cluster.u32 %0, %1, %2;" : "=r"(o) : "r"(a), "r"(r)); return o; }
__device__ __forceinline__ void fence_async_smem() { asm volatile("fence.proxy.async.shared::cta;" ::: "memory"); }
__device__ __forceinline__ void fence_async_global() { asm volatile("fence.proxy.async.global;" ::: "memory"); }
__device__ __forceinline__ void bar_sync(int id, int n) { asm volatile("bar.sync %0, %1;" ::"r"(id), "r"(n) : "memory"); }
__device__ __forceinline__ void bar_arrive(int id, int n) { asm volatile("bar.arrive %0, %1;" ::"r"(id), "r"(n) : "memory"); }
__device__ __forceinline__ void cluster_arrive() { asm volatile("barrier.cluster.arrive.relaxed.aligned;" ::: "memory"); }
__device__ __forceinline__ void cluster_wait() { asm volatile("barrier.cluster.wait.aligned;" ::: "memory"); }

__device__ __forceinline__ void ring_load(uint32_t dst, const CUtensorMap* tm, int col, int row16, uint32_t bar) {
    asm volatile("{\n.reg .pred p;\nelect.sync _|p, 0xffffffff;\n"
                 "@p mbarrier.arrive.expect_tx.shared::cta.b64 _, [%2], 16384;\n"
                 "@p cp.async.bulk.tensor.5d.shared::cluster.global.mbarrier::complete_tx::bytes [%0], [%1, {%3, 0, 0, 0, %4}], [%2];\n}"
                 ::"r"(dst), "l"(tm), "r"(bar), "r"(col), "r"(row16) : "memory");
}
__device__ __forceinline__ void ring_load_both(uint32_t dst, const CUtensorMap* tm, int c1, uint32_t bar) {
    asm volatile("{\n.reg .pred p;\nelect.sync _|p, 0xffffffff;\n"
                 "@p cp.async.bulk.tensor.2d.shared::cluster.global.mbarrier::complete_tx::bytes.multicast::cluster [%0], [%1, {0, %3}], [%2], %4;\n}"
                 ::"r"(dst), "l"(tm), "r"(bar), "r"(c1), "h"((uint16_t)3) : "memory");
}
__device__ __forceinline__ void mbar_arrive_peer(uint32_t b) { asm volatile("mbarrier.arrive.relaxed.cluster.shared::cluster.b64 _, [%0];" ::"r"(b) : "memory"); }
__device__ __forceinline__ void bulk_g2s(uint32_t dst, const void* src, uint32_t bytes, uint32_t bar) {
    asm volatile("cp.async.bulk.shared::cluster.global.mbarrier::complete_tx::bytes [%0], [%1], %2, [%3];" ::"r"(dst), "l"(src), "r"(bytes), "r"(bar) : "memory");
}
__device__ __forceinline__ void prefetch_l2(const void* src, uint32_t bytes) {
    asm volatile("cp.async.bulk.prefetch.L2.global [%0], %1;" ::"l"(src), "r"(bytes) : "memory");
}
__device__ __forceinline__ void peer_copy(uint32_t dst, uint32_t src, uint32_t bytes, uint32_t rbar) {
    asm volatile("{\n.reg .pred p;\nelect.sync _|p, 0xffffffff;\n"
                 "@p cp.async.bulk.shared::cluster.shared::cta.mbarrier::complete_tx::bytes [%0], [%1], %2, [%3];\n}"
                 ::"r"(dst), "r"(src), "r"(bytes), "r"(rbar) : "memory");
}
__device__ __forceinline__ void st_async4(uint32_t dst, uint32_t a, uint32_t b, uint32_t c, uint32_t d, uint32_t bar) {
    asm volatile("st.async.shared::cluster.mbarrier::complete_tx::bytes.v4.b32 [%0], {%1,%2,%3,%4}, [%5];" ::"r"(dst), "r"(a), "r"(b), "r"(c), "r"(d), "r"(bar) : "memory");
}
__device__ __forceinline__ void st_async2f(uint32_t dst, float a, float b, uint32_t bar) {
    asm volatile("st.async.shared::cluster.mbarrier::complete_tx::bytes.v2.f32 [%0], {%1,%2}, [%3];" ::"r"(dst), "f"(a), "f"(b), "r"(bar) : "memory");
}
__device__ __forceinline__ void stsm4t(uint32_t a, uint32_t r0, uint32_t r1, uint32_t r2, uint32_t r3) {
    asm volatile("stmatrix.sync.aligned.m8n8.x4.trans.shared.b16 [%0], {%1,%2,%3,%4};" ::"r"(a), "r"(r0), "r"(r1), "r"(r2), "r"(r3) : "memory");
}
__device__ __forceinline__ void stsm4(uint32_t a, uint32_t r0, uint32_t r1, uint32_t r2, uint32_t r3) {
    asm volatile("stmatrix.sync.aligned.m8n8.x4.shared.b16 [%0], {%1,%2,%3,%4};" ::"r"(a), "r"(r0), "r"(r1), "r"(r2), "r"(r3) : "memory");
}
__device__ __forceinline__ void ldsm4t(uint32_t a, uint32_t& r0, uint32_t& r1, uint32_t& r2, uint32_t& r3) {
    asm volatile("ldmatrix.sync.aligned.m8n8.x4.trans.shared.b16 {%0,%1,%2,%3}, [%4];" : "=r"(r0), "=r"(r1), "=r"(r2), "=r"(r3) : "r"(a) : "memory");
}
__device__ __forceinline__ void ldsm4(uint32_t a, uint32_t& r0, uint32_t& r1, uint32_t& r2, uint32_t& r3) {
    asm volatile("ldmatrix.sync.aligned.m8n8.x4.shared.b16 {%0,%1,%2,%3}, [%4];" : "=r"(r0), "=r"(r1), "=r"(r2), "=r"(r3) : "r"(a) : "memory");
}
__device__ __forceinline__ uint4 lds128(uint32_t a) { uint4 v; asm volatile("ld.shared.v4.b32 {%0,%1,%2,%3}, [%4];" : "=r"(v.x), "=r"(v.y), "=r"(v.z), "=r"(v.w) : "r"(a) : "memory"); return v; }
__device__ __forceinline__ float4 lds128f(uint32_t a) { float4 v; asm volatile("ld.shared.v4.f32 {%0,%1,%2,%3}, [%4];" : "=f"(v.x), "=f"(v.y), "=f"(v.z), "=f"(v.w) : "r"(a) : "memory"); return v; }
__device__ __forceinline__ float2 lds64f(uint32_t a) { float2 v; asm volatile("ld.shared.v2.f32 {%0,%1}, [%2];" : "=f"(v.x), "=f"(v.y) : "r"(a) : "memory"); return v; }
__device__ __forceinline__ uint32_t lds32(uint32_t a) { uint32_t v; asm volatile("ld.shared.b32 %0, [%1];" : "=r"(v) : "r"(a) : "memory"); return v; }
__device__ __forceinline__ void sts128(uint32_t a, uint32_t x, uint32_t y, uint32_t z, uint32_t w) { asm volatile("st.shared.v4.b32 [%0], {%1,%2,%3,%4};" ::"r"(a), "r"(x), "r"(y), "r"(z), "r"(w) : "memory"); }
__device__ __forceinline__ void sts128f(uint32_t a, float x, float y, float z, float w) { asm volatile("st.shared.v4.f32 [%0], {%1,%2,%3,%4};" ::"r"(a), "f"(x), "f"(y), "f"(z), "f"(w) : "memory"); }
__device__ __forceinline__ void sts64f(uint32_t a, float x, float y) { asm volatile("st.shared.v2.f32 [%0], {%1,%2};" ::"r"(a), "f"(x), "f"(y) : "memory"); }
__device__ __forceinline__ void sts32(uint32_t a, uint32_t x) { asm volatile("st.shared.b32 [%0], %1;" ::"r"(a), "r"(x) : "memory"); }
__device__ __forceinline__ void stg128(void* p, uint4 v) { asm volatile("st.global.v4.b32 [%0], {%1,%2,%3,%4};" ::"l"(p), "r"(v.x), "r"(v.y), "r"(v.z), "r"(v.w) : "memory"); }

__device__ __forceinline__ uint32_t pack2(float lo, float hi) { uint32_t r; asm("cvt.rn.bf16x2.f32 %0, %1, %2;" : "=r"(r) : "f"(hi), "f"(lo)); return r; }
__device__ __forceinline__ float blo(uint32_t v) { return __uint_as_float(v << 16); }
__device__ __forceinline__ float bhi(uint32_t v) { return __uint_as_float(v & 0xffff0000u); }
__device__ __forceinline__ uint32_t hmul2(uint32_t a, uint32_t b) { uint32_t r; asm("mul.rn.bf16x2 %0, %1, %2;" : "=r"(r) : "r"(a), "r"(b)); return r; }
__device__ __forceinline__ uint32_t hsub2(uint32_t a, uint32_t b) { uint32_t r; asm("sub.rn.bf16x2 %0, %1, %2;" : "=r"(r) : "r"(a), "r"(b)); return r; }
__device__ __forceinline__ uint32_t hfma2(uint32_t a, uint32_t b, uint32_t c) { uint32_t r; asm("fma.rn.bf16x2 %0, %1, %2, %3;" : "=r"(r) : "r"(a), "r"(b), "r"(c)); return r; }
__device__ __forceinline__ float tanh_fast(float x) { float r; asm("tanh.approx.f32 %0, %1;" : "=f"(r) : "f"(x)); return r; }
__device__ __forceinline__ float rsq(float x) { float r; asm("rsqrt.approx.ftz.f32 %0, %1;" : "=f"(r) : "f"(x)); return r; }
__device__ __forceinline__ float ex2(float x) { float r; asm("ex2.approx.ftz.f32 %0, %1;" : "=f"(r) : "f"(x)); return r; }

__device__ __forceinline__ uint32_t ld_relaxed(const uint32_t* p) {
    uint32_t v;
    asm volatile("ld.relaxed.gpu.global.u32 %0, [%1];" : "=r"(v) : "l"(p) : "memory");
    return v;
}
__device__ __forceinline__ void flag_wait(const uint32_t* p, uint32_t e, uint32_t mask, uint32_t& seen) {
    if ((seen & mask) == mask) return;
    uint32_t a = ld_relaxed(p);
    const uint32_t t0 = clock();
    while (clock() - t0 < 200u) {}
#pragma unroll 1
    for (int i = 0; i < (1 << 19); i++) {
        const uint32_t b = ld_relaxed(p);
        seen = __ballot_sync(~0u, a == e);
        if ((seen & mask) == mask) break;
        a = ld_relaxed(p);
        seen = __ballot_sync(~0u, b == e);
        if ((seen & mask) == mask) break;
    }
    asm volatile("fence.acquire.gpu;" ::: "memory");
    fence_async_global();
}
__device__ __forceinline__ uint32_t ld_epoch() { return ld_relaxed(&g_epoch[blockIdx.x * FS]) + 1; }
__device__ __forceinline__ void flag_set(uint32_t* p, uint32_t e) { asm volatile("st.release.gpu.global.u32 [%0], %1;" ::"l"(p), "r"(e) : "memory"); }

__device__ __forceinline__ uint32_t desc_lo(uint32_t addr) { return ((addr & 0x3FFFF) >> 4) | 0x10000u; }
__device__ __forceinline__ uint64_t mkdesc(uint32_t lo) { return (uint64_t)lo | (0x40000040ull << 32); }
__device__ __forceinline__ void wg_fence() { asm volatile("wgmma.fence.sync.aligned;" ::: "memory"); }
__device__ __forceinline__ void wg_commit() { asm volatile("wgmma.commit_group.sync.aligned;" ::: "memory"); }
template <int N> __device__ __forceinline__ void wg_wait() { asm volatile("wgmma.wait_group.sync.aligned %0;" ::"n"(N) : "memory"); }
template <int N> __device__ __forceinline__ void pin(float (&d)[N]) {
#pragma unroll
    for (int i = 0; i < N; i++) asm volatile("" : "+f"(d[i])::"memory");
}
template <int N> __device__ __forceinline__ void pin(uint32_t (&d)[N]) {
#pragma unroll
    for (int i = 0; i < N; i++) asm volatile("" : "+r"(d[i])::"memory");
}

template <typename Tp, int N> __device__ __forceinline__ void zero(Tp (&d)[N]) {
#pragma unroll
    for (int i = 0; i < N; i++) d[i] = 0;
    pin(d);
}

#define F4(d, i) "+f"(d[i]), "+f"(d[i + 1]), "+f"(d[i + 2]), "+f"(d[i + 3])
#define F16(d, i) F4(d, i), F4(d, i + 4), F4(d, i + 8), F4(d, i + 12)

__device__ __forceinline__ void mma_sp(float (&d)[32], const uint32_t* a, uint64_t b, uint32_t meta, int acc) {
    asm volatile("{.reg .pred p; setp.ne.b32 p, %38, 0;\n"
                 "wgmma.mma_async.sp.sync.aligned.m64n64k32.f32.bf16.bf16 {%0,%1,%2,%3,%4,%5,%6,%7,%8,%9,%10,%11,%12,%13,%14,%15,%16,%17,%18,%19,%20,%21,%22,%23,%24,%25,%26,%27,%28,%29,%30,%31}, "
                 "{%32,%33,%34,%35}, %36, %37, 0, p, 1, 1, 1;}\n"
                 : F16(d, 0), F16(d, 16) : "r"(a[0]), "r"(a[1]), "r"(a[2]), "r"(a[3]), "l"(b), "r"(meta), "r"(acc));
}
__device__ __forceinline__ void mma_t(float (&d)[24], uint64_t a, uint64_t b, int acc) {
    asm volatile("{.reg .pred p; setp.ne.b32 p, %26, 0;\n"
                 "wgmma.mma_async.sync.aligned.m64n48k16.f32.bf16.bf16 {%0,%1,%2,%3,%4,%5,%6,%7,%8,%9,%10,%11,%12,%13,%14,%15,%16,%17,%18,%19,%20,%21,%22,%23}, %24, %25, p, 1, 1, 1, 0;}\n"
                 : F16(d, 0), F4(d, 16), F4(d, 20) : "l"(a), "l"(b), "r"(acc));
}
__device__ __forceinline__ void mma_qk(float (&d)[32], uint32_t a0, uint32_t a1, uint32_t a2, uint32_t a3, uint64_t b, int acc) {
    asm volatile("{.reg .pred p; setp.ne.b32 p, %37, 0;\n"
                 "wgmma.mma_async.sync.aligned.m64n64k16.f32.bf16.bf16 {%0,%1,%2,%3,%4,%5,%6,%7,%8,%9,%10,%11,%12,%13,%14,%15,%16,%17,%18,%19,%20,%21,%22,%23,%24,%25,%26,%27,%28,%29,%30,%31}, "
                 "{%32,%33,%34,%35}, %36, p, 1, 1, 0;}\n"
                 : F16(d, 0), F16(d, 16) : "r"(a0), "r"(a1), "r"(a2), "r"(a3), "l"(b), "r"(acc));
}
__device__ __forceinline__ void mma_pv(float (&d)[36], uint32_t a0, uint32_t a1, uint32_t a2, uint32_t a3, uint64_t b) {
    asm volatile("wgmma.mma_async.sync.aligned.m64n72k16.f32.bf16.bf16 {%0,%1,%2,%3,%4,%5,%6,%7,%8,%9,%10,%11,%12,%13,%14,%15,%16,%17,%18,%19,%20,%21,%22,%23,%24,%25,%26,%27,%28,%29,%30,%31,%32,%33,%34,%35}, "
                 "{%36,%37,%38,%39}, %40, 1, 1, 1, 1;\n"
                 : F16(d, 0), F16(d, 16), F4(d, 32) : "r"(a0), "r"(a1), "r"(a2), "r"(a3), "l"(b));
}

__device__ __forceinline__ uint32_t load_code(int n, int r, int w) {
    const int tile = 2 * r + w;
    int m, col, row;
    if (n < 16 || n >= 40) {
        const int k = n < 16 ? n : n - 40;
        m = n < 16 ? 0 : 6;
        if (k < 8) { col = 4 * tile + (k >> 1); row = (k & 1) ^ r; }
        else { m++; col = tile ^ (3 - ((k - 8) >> 1)); row = 2 * tile + (k & 1); }
    } else if (n < 32) {
        const int k = n - 16;
        m = 2;
        if (k < 4) { col = tile + ((k & 1) ? 0 : 4); row = (k >> 1) ^ r; }
        else { col = 8 + tile; row = (k & 1) ^ r; }
    } else if (n < 34) { m = 3; col = tile; row = n - 32; }
    else if (n < 38) { const int k = n - 34; m = 4; col = tile + 4 * (k & 1); row = (k >> 1) ^ r; }
    else { m = 5; col = tile; row = (n & 1) ^ r; }
    return m | (col << 4) | (row << 8);
}

__global__ void __cluster_dims__(2, 1, 1) __launch_bounds__(NTHREADS, 1)
conformer_kernel(const __grid_constant__ Params p) {
    extern __shared__ __align__(1024) unsigned char smem_raw[];
    const uint32_t sb = smem_u32(smem_raw);
    const uint32_t bars = sb + OFF_BARS;
    const int tid = threadIdx.x;
    const int lane = tid & 31;
    const int warp = __shfl_sync(~0u, tid >> 5, 0);
    const int r = blockIdx.x & 1;
    const int pair = blockIdx.x >> 1;
    const int b = pair >> 5, pt = pair & 31;
    const int ah = pt >> 3, qt = (pt & 7) * 2 + r;
    const int abh = b * 4 + ah;

    TG(30);
    TSINIT();
    TS(0);
    const uint32_t P = sb + OFF_P, H = sb + OFF_H;

    if (warp >= 8) {
        asm volatile("setmaxnreg.dec.sync.aligned.u32 48;");
        if (warp >= 12) {
            cluster_arrive();
            cluster_wait();
            if (warp == 12) {
                const uint32_t epoch = ld_epoch();
                bar_sync(11, 288);
                if (lane < 2) flag_set(&g_flag_v[((b * 4 + 2 * r + lane) * 32 + pt) * FS], epoch);
                __syncwarp();
                TS(13);
            }
            const int ut = tid & 127;
            const uint32_t a8 = P + (ut >> 3) * 128 + (ut & 7) * 16;
            float s[3] = {0.f, 0.f, 0.f}, q[3] = {0.f, 0.f, 0.f};
#pragma unroll 1
            for (int h = 0; h < 2; h++) {
                if (h == 0) bar_sync(1, 384);
                else mbar_wait(bars + B_X2 * 8, 0);
                uint4 v[6];
#pragma unroll
                for (int i = 0; i < 6; i++) v[i] = lds128(a8 + (2 * (r ^ h) + (i & 1)) * XCH + (i >> 1) * 2048);
                bar_arrive(5 + ((v[0].w | v[1].w | v[2].w | v[3].w | v[4].w | v[5].w) & p.zero), 384);
                uint32_t t;
                asm volatile("mov.u32 %0, %%clock;" : "=r"(t)::"memory");
                const uint32_t mul = 65536u + (t & p.zero), msk = 0u - mul;
#pragma unroll
                for (int i = 0; i < 6; i++) {
                    const float a0 = __uint_as_float(v[i].x * mul), a1 = __uint_as_float(v[i].x & msk), a2 = __uint_as_float(v[i].y * mul), a3 = __uint_as_float(v[i].y & msk);
                    const float a4 = __uint_as_float(v[i].z * mul), a5 = __uint_as_float(v[i].z & msk), a6 = __uint_as_float(v[i].w * mul), a7 = __uint_as_float(v[i].w & msk);
                    s[i >> 1] += ((a0 + a1) + (a2 + a3)) + ((a4 + a5) + (a6 + a7));
                    q[i >> 1] += fmaf(a0, a0, fmaf(a1, a1, fmaf(a2, a2, a3 * a3))) + fmaf(a4, a4, fmaf(a5, a5, fmaf(a6, a6, a7 * a7)));
                }
            }
#pragma unroll
            for (int o = 1; o < 8; o <<= 1) {
#pragma unroll
                for (int i = 0; i < 3; i++) { s[i] += __shfl_xor_sync(~0u, s[i], o); q[i] += __shfl_xor_sync(~0u, q[i], o); }
            }
            const int k = ut & 7, row = (ut >> 3) + 16 * k;
            const float mean = (k == 0 ? s[0] : (k == 1 ? s[1] : s[2])) * (1.f / 256.f);
            const float msq = (k == 0 ? q[0] : (k == 1 ? q[1] : q[2])) * (1.f / 256.f);
            const float alpha = (uint32_t)(pt * 32 - 8 + row) >= T_ ? 0.f : 0.5f;
            const float rstd = alpha * rsq(fmaxf(fmaf(-mean, mean, msq), 0.f) + 1e-5f);
            if (k < 3) sts64f(sb + OFF_STATS + row * 8, mean * rstd, rstd);
            __syncwarp();
            if (lane == 0) mbar_arrive(bars + B_ST * 8);
            TS(4);
        } else if (warp < 10) {
            const int w = warp - 8;
            const uint32_t ring = sb + OFF_RING + w * NSLOT * SLOT;
            const uint32_t full = bars + (B_FULL + w * NSLOT) * 8;
            if (lane == 0) {
#pragma unroll
                for (int i = 0; i < NSLOT; i++) { mbar_init(full + i * 8, 1); mbar_init(full + (B_EMPTY - B_FULL + i) * 8, 4); }
                asm volatile("fence.mbarrier_init.release.cluster;" ::: "memory");
                fence_async_smem();
            }
            __syncwarp();
            cluster_arrive();
            TS(1);
#pragma unroll
            for (int n = 0; n < NSLOT; n++) {
                if (n == 1 || n == 2) bar_sync(12, 64);
                ring_load(ring + n * SLOT, &p.tm[0], 64 * (8 * r + 4 * w + (n >> 1)), 8 * ((n & 1) ^ r), full + n * 8);
            }
            TS(2);
            const uint32_t code = load_code(lane, r, w) | (load_code(lane + 32, r, w) << 16);
            cluster_wait();
            uint32_t s = 0, ph = 0;
            int n = NSLOT;
#pragma unroll 1
            for (int seg = 0; seg < 2; seg++) {
#pragma unroll 1
                for (; n < (seg == 0 ? 22 : NLOADS); n++) {
                    const uint32_t c = __shfl_sync(~0u, code, n) >> (n & 32 ? 16 : 0);
                    const CUtensorMap* tm = &p.tm[c & 15];
                    const uint32_t col = (c & 0xf0) * 4, row = (c & 0xff00) >> 5, dst = ring + s * SLOT;
                    mbar_wait(full + (B_EMPTY - B_FULL) * 8 + s * 8, ph + (((uint32_t)(size_t)tm | col | row | dst) & p.zero));
                    ring_load(dst, tm, col, row, full + s * 8);
                    if (++s == NSLOT) { s = 0; ph ^= 1; }
                }
                if (seg == 1) break;
                const uint32_t epoch = ld_epoch();
                const uint32_t rdy = bars + (B_RDY + 3 * w) * 8, prdy = mapa(rdy, r ^ 1);
                const int isv = r ^ w;
                const uint32_t* flags = (isv ? g_flag_v : g_flag_kq) + (abh * 32 + lane) * FS;
                uint32_t seen = 0;
                auto kv_load = [&](uint32_t sl, int i) {
                    ring_load_both(ring + sl * SLOT, &p.tm[8], (isv * 64 + abh * 8 + 2 * i + w) * 128, full + sl * 8);
                };
                if (lane < 3) {
                    mbar_wait(full + (B_EMPTY - B_FULL + 2 + lane) * 8, 1);
                    mbar_arrive_tx(full + (2 + lane) * 8, lane == 2 ? SLOT : 0);
                    if (lane == 2 && isv) mbar_arrive_peer(prdy + 16);
                }
                __syncwarp();
                if (!isv) {
                    mbar_wait(rdy + 16, 0);
                    flag_wait(flags, epoch, 0xfu << (4 * w), seen);
                    TSW(5);
                    kv_load(4, 0);
                }
                if (lane < 4) {
                    mbar_wait(full + (B_EMPTY - B_FULL + lane) * 8, 0);
                    mbar_arrive_tx(full + lane * 8, SLOT);
                }
                __syncwarp();
                if (lane == 0) mbar_arrive_peer(prdy);
                mbar_wait(rdy, 0);
#pragma unroll 1
                for (int i = 0; i < 2; i++) {
                    flag_wait(flags, epoch, 0xfu << (8 * (i + 1 - isv) + 4 * w), seen);
                    if (i == 0 && isv) TSW(7);
                    mbar_wait(i ? full + isv * 8 : bars + B_QIN * 8, i);
                    kv_load(2 * i + isv, i + 1 - isv);
                }
                flag_wait(flags, epoch, ~0u, seen);
#pragma unroll 1
                for (int i = 0; i < 3; i++) {
                    const uint32_t sl = i ? i - 1 : 4, bo = i == 2 ? 16 : 8;
                    mbar_wait(full + (B_EMPTY - B_FULL + sl) * 8, i != 0);
                    if (lane == 0) mbar_arrive_tx(full + sl * 8, SLOT);
                    if ((i != 0) == (isv == 1)) {
                        mbar_wait(rdy + bo, 0);
                        kv_load(sl, i == 1 ? 2 : 3);
                    } else if (lane == 0) mbar_arrive_peer(prdy + bo);
                    __syncwarp();
                }
                n = 32; s = 2; ph = 1;
            }
        } else if (warp == 10) {
            if (lane == 0) {
#pragma unroll
                for (int i = B_XA; i <= B_ST; i++) mbar_init(bars + i * 8, i == B_ST ? 4 : 1);
#pragma unroll
                for (int i = B_XA; i <= B_QIN; i++)
                    mbar_arrive_tx(bars + i * 8, i < B_XB ? 512 : ((i < B_X2 || i == B_SR || i == B_QIN) ? 8192 : 12288));
                asm volatile("fence.mbarrier_init.release.cluster;" ::: "memory");
                fence_async_smem();
            }
            __syncwarp();
            cluster_arrive();
            cluster_wait();
            const uint32_t epoch = ld_epoch();
            uint32_t seen = 0;
            const int np = min(max(pt - 1 + 2 * (lane & 1), 0), 31);
            const uint32_t* f = &g_flag_kq[((lane & 2) ? (b * 4 + 2 * r) * 32 + np : abh * 32 + 2 * qt + (lane & 1)) * FS];
            flag_wait(f, epoch, 3, seen);
            TSW(6);
            if (lane == 0) bulk_g2s(H + 24576, g_kvq + 2097152 + (size_t)(abh * 1024 + qt * 64) * 128, 8192, bars + B_QIN * 8);
            __syncwarp();
            flag_wait(f, epoch, 15, seen);
            if (lane == 0) mbar_arrive(bars + B_X1IN * 8);
            bar_sync(9, 64);
            const int q = min(max((pt >> 1) + ((lane & 4) ? ((pt & 1) ? 1 : -1) : 0), 0), 15);
            seen = 0;
            flag_wait(&g_flag_o[((b * 16 + q) * 4 + (lane & 3)) * FS], epoch, 0xff, seen);
            TSW(10);
            if (lane == 0) {
#pragma unroll
                for (int i = 0; i < 4; i++)
                    bulk_g2s(H + i * XCH, g_o + (size_t)((b * 4 + i) * PADROWS + pt * 32) * 128, XCH, bars + (B_OIN + (i >> 1)) * 8);
            }
            __syncwarp();
        } else {
            const uint32_t kb = (lane < 2 || lane > 5) ? 4096 : (lane == 2 ? 3072 : (lane == 4 ? 2048 : 1024));
            const char* pf = p.w[lane & 7] + blockIdx.x * kb;
            cluster_arrive();
            cluster_wait();
            if (lane < 2) prefetch_l2(pf, kb);
            mbar_wait(bars + B_XA * 8, 0);
            if (lane == 2) prefetch_l2(pf, kb);
            if (lane >= 1 && lane < 9) asm volatile("prefetch.tensormap [%0];" ::"l"(&p.tm[lane]) : "memory");
            mbar_wait(bars + (B_FULL + 1) * 8, 1);
            if (lane > 2 && lane < 8) prefetch_l2(pf, kb);
            const uint32_t epoch = ld_epoch();
            bar_sync(4, 288);
            if (lane < 2) flag_set(&g_flag_kq[((b * 4 + 2 * r + lane) * 32 + pt) * FS], epoch);
            __syncwarp();
            TSW(8);
            bar_sync(6, 288);
            bar_arrive(9, 64);
            if (lane == 0) {
                flag_set(&g_flag_o[((b * 16 + qt) * 4 + ah) * FS], epoch);
                g_epoch[blockIdx.x * FS] = epoch;
            }
            __syncwarp();
            TSW(9);
        }
        TSDUMP();
        return;
    }

    const int w = warp >> 2, wq = warp & 3;
    const int tile = 2 * r + w;
    const int wt = tid & 127;
    const int c4 = lane & 3;
    const int trow = pt * 32 + 8 * wq;
    uint32_t xr[8];
    {
        const uint32_t* xp = reinterpret_cast<const uint32_t*>(p.x + (size_t)(b * T_ + trow + (lane >> 2)) * 256 + tile * 64) + c4;
#pragma unroll
        for (int j = 0; j < 8; j++) xr[j] = trow < T_ ? __ldg(xp + 4 * j) : 0u;
    }
    cluster_arrive();
    asm volatile("setmaxnreg.inc.sync.aligned.u32 208;");
    const uint32_t rbase = sb + OFF_RING + w * NSLOT * SLOT, fbar = bars + (B_FULL + w * NSLOT) * 8;
    const uint32_t rdesc = desc_lo(rbase);
    auto acq = [&](int n) { mbar_wait(fbar + (n % NSLOT) * 8, (n / NSLOT) & 1); };
    auto rel = [&](int n) { if (lane == 0) mbar_arrive(fbar + (B_EMPTY - B_FULL + n % NSLOT) * 8); };
    const uint32_t foff = (lane & 7) * 128 + (((lane >> 3) ^ (lane & 7)) << 4);
    const uint32_t toff = ((lane >> 4) * 8 + (lane & 7)) * 128 + (((2 * wq + ((lane >> 3) & 1)) ^ (lane & 7)) << 4);
    auto publish = [&](int bar, uint32_t src, uint32_t bytes, int nsync) {
        fence_async_smem();
        bar_sync(2 + w, 128);
        if (wq == 0) peer_copy(mapa(src, r ^ 1), src, bytes, mapa(bars + bar * 8, r ^ 1));
        bar_sync(nsync == 384 ? 1 : 10, nsync);
    };
    float v[16];
#pragma unroll
    for (int j = 0; j < 8; j++) { v[2 * j] = blo(xr[j]); v[2 * j + 1] = bhi(xr[j]); }
    const uint32_t xown = __shfl_sync(~0u, P + wt * 16 + tile * 4096, lane), xrem = __shfl_sync(~0u, P + wt * 16 + (r ^ 1) * 8192, lane);
    const uint32_t sbuf = __shfl_sync(~0u, sb + OFF_MISC + 1024 + (8 * wq + (lane >> 2)) * 32, lane);
    const uint32_t sown = __shfl_sync(~0u, sbuf + tile * 8, lane);
    const uint32_t peer = __shfl_sync(~0u, mapa(sb, r ^ 1) - sb, lane);
    const uint32_t meta = __shfl_sync(~0u, 0xEEEE4444u + p.zero, lane);
    cluster_wait();
    TS(56);
    float mean, msq;

#pragma unroll 1
    for (int ph = 0;; ph++) {
        uint4 o0, o1;
        {
            float s = 0.f, q = 0.f, s2 = 0.f, q2 = 0.f;
#pragma unroll
            for (int j = 0; j < 4; j++) {
                s += v[4 * j] + v[4 * j + 1]; s2 += v[4 * j + 2] + v[4 * j + 3];
                q += fmaf(v[4 * j], v[4 * j], v[4 * j + 1] * v[4 * j + 1]); q2 += fmaf(v[4 * j + 2], v[4 * j + 2], v[4 * j + 3] * v[4 * j + 3]);
            }
            s += s2; q += q2;
            const uint32_t xa = bars + (B_XA + ph) * 8;
            s += __shfl_xor_sync(~0u, s, 1); q += __shfl_xor_sync(~0u, q, 1);
            s += __shfl_xor_sync(~0u, s, 2); q += __shfl_xor_sync(~0u, q, 2);
            if (c4 == 0) st_async2f(sown + peer, s, q, xa + peer);
            if (c4 == 0) sts64f(sown, s, q);
#pragma unroll
            for (int j = 0; j < 8; j++) xr[j] = pack2(v[2 * j], v[2 * j + 1]);
            sts128(xown, xr[0], xr[1], xr[2], xr[3]);
            sts128(xown + 2048, xr[4], xr[5], xr[6], xr[7]);
            bar_sync(10, 256);
            o0 = lds128(xown ^ 4096); o1 = lds128((xown ^ 4096) + 2048);
            if (ph < 3) {
                st_async4(xown + peer, xr[0], xr[1], xr[2], xr[3], xa + (B_XB - B_XA) * 8 + peer);
                st_async4(xown + peer + 2048, xr[4], xr[5], xr[6], xr[7], xa + (B_XB - B_XA) * 8 + peer);
            }
            TS(57 + ph);
            if (ph == 0) acq(0);
            mbar_wait(xa, 0);
            const float4 u0 = lds128f(sbuf), u1 = lds128f(sbuf + 16);
            mean = ((u0.x + u0.z) + (u1.x + u1.z)) * (1.f / 256.f);
            msq = ((u0.y + u0.w) + (u1.y + u1.w)) * (1.f / 256.f);
        }
        if (ph == 3) break;
        uint32_t a[32];
        const uint32_t mean2 = pack2(mean, mean);
        auto centre = [&](int i, const uint4& u) {
            a[i] = hsub2(u.x, mean2); a[i + 1] = hsub2(u.y, mean2); a[i + 2] = hsub2(u.z, mean2); a[i + 3] = hsub2(u.w, mean2);
        };
#pragma unroll
        for (int j = 0; j < 8; j++) a[j] = hsub2(xr[j], mean2);
        centre(8, o0); centre(12, o1);
        const float rstd = rsq(fmaxf(fmaf(-mean, mean, msq), 0.f) + 1e-5f);
        auto gather_peer = [&]() {
            mbar_wait(bars + (B_XB + ph) * 8, 0);
#pragma unroll
            for (int i = 0; i < 4; i++) centre(16 + 4 * i, lds128(xrem + i * 2048));
        };
        auto sp = [&](float (&d)[32], int n, const uint32_t* af, int flip, int acc) {
            const uint32_t lo = rdesc + p.zero * (ph + n + 1) + (n % NSLOT) * (SLOT >> 4);
            const uint64_t b0 = mkdesc(lo + flip * 512), b1 = mkdesc(lo + (flip ^ 1) * 512);
            wg_fence();
            mma_sp(d, af, b0, meta, acc);
            mma_sp(d, af + 4, b0 + 256, meta, 1);
            mma_sp(d, af + 8, b1, meta, 1);
            mma_sp(d, af + 12, b1 + 256, meta, 1);
            wg_commit();
        };
        float d0[32], d1[32];

        if (ph != 1) {
            uint32_t h[32];
            const float rs = 0.5f * rstd;
            const uint32_t inb = bars + (B_INB + ph) * 8, box = H + wt * 16;
            bool ready = true;
            auto step = [&](float (&d)[32], int n, const uint32_t* af, int flip, int acc, auto work) {
                if (!ready) acq(n);
                if (((TURN >> n) & 1) && w == 1) bar_sync(7, 256);
                sp(d, n, af, flip, acc);
                if (n > 0 && ((TURN >> (n - 1)) & 1) && w == 0) bar_arrive(7, 256);
                if (n < 15) ready = mbar_test(fbar + ((n + 1) % NSLOT) * 8, ((n + 1) / NSLOT) & 1);
                wg_wait<1>();
                if (n > 0 && !((EAGER >> (n - 1)) & 1)) rel(n - 1);
                const uint32_t tie = work() & p.zero;
                if ((EAGER >> n) & 1) {
                    if (p.zero < n + ph + 1) wg_wait<0>();
                    if (lane == 0) mbar_arrive(fbar + (B_EMPTY - B_FULL + n % NSLOT) * 8 + tie);
                }
            };
            auto none = []() { return 0u; };
            auto act = [&](float (&d)[32], int i) {
                pin(d);
#pragma unroll
                for (int j = 0; j < 8; j++) {
                    const float u0 = (d[4 * j] + d[4 * j + 2]) * rs, u1 = (d[4 * j + 1] + d[4 * j + 3]) * rs;
                    h[8 * i + j] = pack2(fmaf(u0, tanh_fast(u0), u0), fmaf(u1, tanh_fast(u1), u1));
                }
                return h[8 * i] | h[8 * i + 1] | h[8 * i + 2] | h[8 * i + 3] | h[8 * i + 4] | h[8 * i + 5] | h[8 * i + 6] | h[8 * i + 7];
            };
            auto send = [&](float (&d)[32], int x) {
                pin(d);
                uint32_t pk[8];
#pragma unroll
                for (int j = 0; j < 8; j++) pk[j] = pack2(d[4 * j] + d[4 * j + 2], d[4 * j + 1] + d[4 * j + 3]);
                const uint32_t ow = w ^ (x & 1), dst = box + (ow * 3 + x - 1) * 4096;
                if (x & 2) {
                    st_async4(dst + peer, pk[0], pk[1], pk[2], pk[3], inb + ow * 8 + peer);
                    st_async4(dst + peer + 2048, pk[4], pk[5], pk[6], pk[7], inb + ow * 8 + peer);
                } else {
                    sts128(dst, pk[0], pk[1], pk[2], pk[3]);
                    sts128(dst + 2048, pk[4], pk[5], pk[6], pk[7]);
                }
            };
            TS(1 + ph * 10);
            step(d0, 0, a, w, 0, [&]() { gather_peer(); return 0u; });
            TS(32);
            step(d0, 1, a + 16, 0, 1, none);
            step(d1, 2, a, w, 0, [&]() { return act(d0, 0); });
            step(d1, 3, a + 16, 0, 1, none);
            step(d0, 4, a, w, 0, [&]() { return act(d1, 1); });
            TS(33);
            step(d0, 5, a + 16, 0, 1, none);
            step(d1, 6, a, w, 0, [&]() { return act(d0, 2); });
            step(d1, 7, a + 16, 0, 1, none);
            step(d0, 8, h, 0, 0, [&]() { return act(d1, 3); });
            TS(2 + ph * 10);
            step(d0, 9, h + 16, 0, 1, none);
            step(d1, 10, h, 0, 0, [&]() { send(d0, 3); return 0u; });
            step(d1, 11, h + 16, 0, 1, none);
            step(d0, 12, h, 0, 0, [&]() { send(d1, 2); return 0u; });
            TS(34);
            step(d0, 13, h + 16, 0, 1, none);
            step(d1, 14, h, 0, 0, [&]() { send(d0, 1); return 0u; });
            step(d1, 15, h + 16, 0, 1, none);
            if (ph == 0) acq(16);
            mbar_wait(inb + w * 8, 0);
            bar_sync(10, 256);
#pragma unroll
            for (int i = 0; i < 2; i++) {
                const uint32_t src = box + w * 12288 + i * 2048;
                const uint4 u0 = lds128(src), u1 = lds128(src + 4096), u2 = lds128(src + 8192);
                const uint32_t p0[4] = {u0.x, u0.y, u0.z, u0.w}, p1[4] = {u1.x, u1.y, u1.z, u1.w}, p2[4] = {u2.x, u2.y, u2.z, u2.w};
#pragma unroll
                for (int j = 0; j < 4; j++) {
                    v[8 * i + 2 * j] = fmaf(0.5f, blo(p0[j]) + blo(p1[j]) + blo(p2[j]), blo(xr[4 * i + j]));
                    v[8 * i + 2 * j + 1] = fmaf(0.5f, bhi(p0[j]) + bhi(p1[j]) + bhi(p2[j]), bhi(xr[4 * i + j]));
                }
            }
            wg_wait<0>();
            pin(d1);
            rel(15);
            TS(3 + ph * 10);
#pragma unroll
            for (int j = 0; j < 8; j++) {
                v[2 * j] = fmaf(0.5f, d1[4 * j] + d1[4 * j + 2], v[2 * j]);
                v[2 * j + 1] = fmaf(0.5f, d1[4 * j + 1] + d1[4 * j + 3], v[2 * j + 1]);
            }
            continue;
        }

        {
            TS(11);
            sp(d0, 16, a, w, 0);
            acq(17);
            sp(d1, 17, a, w, 0);
            if (wq == 0 || wq == 3) {
                uint4* hp = &g_halo[((pair * 4 + tile) * 2 + (wq & 1)) * 64 + lane];
                hp[0] = make_uint4(xr[0], xr[1], xr[2], xr[3]);
                hp[32] = make_uint4(xr[4], xr[5], xr[6], xr[7]);
            }
            gather_peer();
            acq(18);
            sp(d0, 18, a + 16, 0, 1);
            wg_wait<1>();
            rel(16); rel(17);
            acq(19);
            sp(d1, 19, a + 16, 0, 1);
            const uint32_t stg = H + warp * 3072;
            unsigned char* g = g_kvq + (size_t)((b * 4 + tile) * 1024 + trow) * 128 + lane * 16;
            auto put = [&](float (&d)[32], int i) {
                pin(d);
                uint32_t pk[8];
#pragma unroll
                for (int j = 0; j < 8; j++) pk[j] = pack2((d[4 * j] + d[4 * j + 2]) * rstd, (d[4 * j + 1] + d[4 * j + 3]) * rstd);
                stsm4(stg + i * 1024 + foff, pk[0], pk[1], pk[2], pk[3]);
                stsm4(stg + i * 1024 + (foff ^ 64), pk[4], pk[5], pk[6], pk[7]);
                __syncwarp();
                const uint4 u0 = lds128(stg + i * 1024 + lane * 16), u1 = lds128(stg + i * 1024 + 512 + lane * 16);
                stg128(g + i * 1048576, u0); stg128(g + i * 1048576 + 512, u1);
            };
            wg_wait<1>();
            rel(18);
            put(d0, 0);
            wg_wait<0>();
            rel(19);
            TS(37);
            put(d1, 2);
            bar_arrive(4, 288);
            TS(38);
            acq(20);
            sp(d0, 20, a, w, 0);
            acq(21);
            sp(d0, 21, a + 16, 0, 1);
            wg_wait<0>();
            rel(20); rel(21);
            put(d0, 1);
            bar_arrive(11, 288);
            acq(22); acq(23);
            rel(22); rel(23);
            TS(12);
        }

        {
            constexpr float CS = 0.125f * 1.4426950408889634f;
            float sa[32], sb2[32], o[36];
            uint32_t pa[16], pb[16], q[16];
            float n0 = INFINITY, n1 = INFINITY;
            zero(o); zero(pa); zero(pb);
            const uint32_t ones = sb + OFF_MISC + 2048;
            if (tid < 128) sts128(ones + tid * 16, 0x3F803F80u, 0x3F803F80u, 0x3F803F80u, 0x3F803F80u);
            fence_async_smem();
            bar_sync(10, 256);
            const uint32_t vdesc = rdesc + ((((ones - rbase) >> 4) - 1) << 16);
            auto qk_issue = [&](float (&s)[32], uint32_t lo) {
                const uint64_t kd = mkdesc(lo);
                wg_fence();
#pragma unroll
                for (int k = 0; k < 4; k++) mma_qk(s, q[4 * k], q[4 * k + 1], q[4 * k + 2], q[4 * k + 3], kd + 2 * k, k != 0);
                wg_commit();
            };
            auto pv_issue = [&](uint32_t (&pp)[16], uint32_t lo) {
                const uint64_t vd = mkdesc(lo);
                wg_fence();
#pragma unroll
                for (int k = 0; k < 4; k++) mma_pv(o, pp[4 * k], pp[4 * k + 1], pp[4 * k + 2], pp[4 * k + 3], vd - k * (128 * 65535));
                wg_commit();
            };
            auto new_max = [&](float (&s)[32], float& x0, float& x1) {
                x0 = s[0]; x1 = s[2];
#pragma unroll
                for (int j = 0; j < 8; j++) {
                    x0 = fmaxf(x0, fmaxf(s[4 * j], s[4 * j + 1]));
                    x1 = fmaxf(x1, fmaxf(s[4 * j + 2], s[4 * j + 3]));
                }
                x0 = fmaxf(x0, __shfl_xor_sync(~0u, x0, 1)); x1 = fmaxf(x1, __shfl_xor_sync(~0u, x1, 1));
                x0 = fmaxf(x0, __shfl_xor_sync(~0u, x0, 2)); x1 = fmaxf(x1, __shfl_xor_sync(~0u, x1, 2));
                x0 = fminf(n0, fmaf(x0, -CS, -20.f)); x1 = fminf(n1, fmaf(x1, -CS, -20.f));
            };
            auto probs = [&](float (&s)[32], uint32_t (&pp)[16], bool ready, auto wait) {
                uint32_t any = 0;
#pragma unroll
                for (int i = 0; i < 16; i++) {
                    pp[i] = pack2(ex2(fmaf(s[2 * i], CS, (i & 1) ? n1 : n0)), ex2(fmaf(s[2 * i + 1], CS, (i & 1) ? n1 : n0)));
                    any |= pp[i];
                }
                float sc0 = 1.f, sc1 = 1.f;
                const bool slow = __any_sync(~0u, (any & 0x40004000u) || !ready);
                if (slow) {
                    wait();
                    if (__any_sync(~0u, any & 0x40004000u)) {
                        float x0, x1;
                        new_max(s, x0, x1);
                        sc0 = ex2(x0 - n0); sc1 = ex2(x1 - n1);
                        n0 = x0; n1 = x1;
#pragma unroll
                        for (int i = 0; i < 16; i++)
                            pp[i] = pack2(ex2(fmaf(s[2 * i], CS, (i & 1) ? n1 : n0)), ex2(fmaf(s[2 * i + 1], CS, (i & 1) ? n1 : n0)));
                    }
                }
                wg_wait<0>();
                pin(sa); pin(sb2); pin(o); pin(pa); pin(pb);
                if (slow) {
#pragma unroll
                    for (int j = 0; j < 9; j++) { o[4 * j] *= sc0; o[4 * j + 1] *= sc0; o[4 * j + 2] *= sc1; o[4 * j + 3] *= sc1; }
                }
            };
            mbar_wait(bars + B_QIN * 8, 0);
            {
                const uint32_t qa = H + 24576 + (wq * 16 + (lane & 15)) * 128;
#pragma unroll
                for (int k = 0; k < 4; k++) ldsm4(qa + (((2 * k + (lane >> 4)) ^ (lane & 7)) << 4), q[4 * k], q[4 * k + 1], q[4 * k + 2], q[4 * k + 3]);
                pin(q);
            }
            TS(40);
            acq(24);
            TS(13);
            qk_issue(sa, rdesc + (24 % NSLOT) * (SLOT >> 4));
            qk_issue(sb2, rdesc + (24 % NSLOT) * (SLOT >> 4) + 512);
            wg_wait<1>();
            pin(sa);
            {
                float x0, x1;
                new_max(sa, x0, x1);
                n0 = x0; n1 = x1;
            }
            if (w == 1) bar_sync(7, 256);
            uint32_t vd = vdesc - (SLOT >> 4) * 65535u, kd = rdesc, vb = fbar + 8, kb = fbar;
            uint32_t vlast = vdesc - 4 * (SLOT >> 4) * 65535u;
            uint32_t kprev = fbar + 32, vprev = bars + (B_SINK - (B_EMPTY - B_FULL)) * 8;
#pragma unroll 1
            for (int it = 0; it < 4; it++) {
                pv_issue(pb, vlast);
                probs(sa, pa, mbar_test(vb, it < 2) & mbar_test(kb, it < 3), [&]() { mbar_wait(vb, it < 2); mbar_wait(kb, it < 3); });
                TS(41 + it * 4);
                if (it == 0 && w == 0) bar_arrive(7, 256);
                if (it == 3 && w == 1) {
#pragma unroll
                    for (int i = 20; i < 32; i++) sb2[i] = -INFINITY;
                }
                pin(sb2);
                if (it < 3) qk_issue(sa, kd);
                if (lane == 0) mbar_arrive(kprev + (B_EMPTY - B_FULL) * 8);
                if (lane == 0) mbar_arrive(vprev + (B_EMPTY - B_FULL) * 8);
                pv_issue(pa, vd);
                probs(sb2, pb, true, []() {});
                TS(43 + it * 4);
                if (it < 3) qk_issue(sb2, kd + 512);
                const int dv = it == 0 ? 2 : (it == 1 ? -3 : 1);
                kprev = kb; vprev = vb; vlast = vd - 512 * 65535u;
                vd -= dv * (SLOT >> 4) * 65535u; vb += dv * 8;
                kd += 2 * (SLOT >> 4); kb = it == 2 ? vb : kb + 16;
            }
            pv_issue(pb, vlast);
            const int row = wq * 16 + (lane >> 2);
            const uint32_t ml = sb + OFF_MISC;
            wg_wait<0>();
            pin(o); pin(pb); pin(sa); pin(sb2);
            rel(31);
            const float l0 = o[32], l1 = o[34];
            if (c4 == 0) { sts64f(ml + w * 512 + row * 8, n0, l0); sts64f(ml + w * 512 + row * 8 + 64, n1, l1); }
            TS(14);
            float mine[16];
#pragma unroll
            for (int j = 0; j < 4; j++) {
                if (w == 0) sts128f(H + j * 2048 + wt * 16, o[16 + 4 * j], o[17 + 4 * j], o[18 + 4 * j], o[19 + 4 * j]);
                else sts128f(H + 8192 + j * 2048 + wt * 16, o[4 * j], o[4 * j + 1], o[4 * j + 2], o[4 * j + 3]);
            }
#pragma unroll
            for (int i = 0; i < 16; i++) mine[i] = w == 0 ? o[i] : o[16 + i];
            bar_sync(10, 256);
            const float2 u0 = lds64f(ml + (w ^ 1) * 512 + row * 8), u1 = lds64f(ml + (w ^ 1) * 512 + row * 8 + 64);
            const float x0 = fminf(n0, u0.x), x1 = fminf(n1, u1.x);
            float a0 = ex2(x0 - n0), b0 = ex2(x0 - u0.x), a1 = ex2(x1 - n1), b1 = ex2(x1 - u1.x);
            const float i0 = __fdividef(1.f, fmaf(a0, l0, b0 * u0.y)), i1 = __fdividef(1.f, fmaf(a1, l1, b1 * u1.y));
            a0 *= i0; b0 *= i0; a1 *= i1; b1 *= i1;
            uint32_t pk[8];
#pragma unroll
            for (int j = 0; j < 4; j++) {
                const float4 v = lds128f(H + (w ^ 1) * 8192 + j * 2048 + wt * 16);
                pk[2 * j] = pack2(fmaf(a0, mine[4 * j], b0 * v.x), fmaf(a0, mine[4 * j + 1], b0 * v.y));
                pk[2 * j + 1] = pack2(fmaf(a1, mine[4 * j + 2], b1 * v.z), fmaf(a1, mine[4 * j + 3], b1 * v.w));
            }
            const uint32_t og = H + 16384 + wq * 2048;
            {
                const uint32_t ra = og + (((lane >> 3) & 1) * 8 + (lane & 7)) * 128;
                stsm4(ra + (((4 * w + (lane >> 4)) ^ (lane & 7)) << 4), pk[0], pk[1], pk[2], pk[3]);
                stsm4(ra + (((4 * w + 2 + (lane >> 4)) ^ (lane & 7)) << 4), pk[4], pk[5], pk[6], pk[7]);
            }
            __syncwarp();
            {
                const uint32_t off = (lane >> 2) * 128 + (((4 * w + c4) ^ (lane >> 2)) << 4);
                const uint4 v0 = lds128(og + off), v1 = lds128(og + off + 1024);
                unsigned char* dst = g_o + (size_t)(abh * PADROWS + 8 + qt * 64 + wq * 16) * 128 + off;
                stg128(dst, v0); stg128(dst + 1024, v1);
            }
            bar_arrive(6, 288);
            TS(15);
        }

        auto mm = [&](float (&d)[24], int n, uint32_t act, int acc) {
            const uint32_t z = p.zero * (ph + n);
            const uint64_t ad = mkdesc(rdesc + z + (n % NSLOT) * (SLOT >> 4)), bd = mkdesc(desc_lo(act) + z);
            wg_fence();
#pragma unroll
            for (int k = 0; k < 8; k++) mma_t(d, ad + k * 128, bd + (k >> 2) * (XCH >> 4) + (k & 3) * 2, k == 0 ? acc : 1);
            wg_commit();
        };
        const uint32_t xo = P + tile * XCH + wq * 1024, xt = P + tile * XCH + toff;
        uint32_t dwr[15];
        {
#pragma unroll
            for (int i = 0; i < 15; i++) dwr[i] = hmul2(__ldg(reinterpret_cast<const uint32_t*>(p.dw + i * 256 + tile * 64) + lane), 0x3F003F00u);
            float d[24];
            uint32_t xw[12];
            stsm4(xo + 1024 + foff, xr[0], xr[1], xr[2], xr[3]);
            stsm4(xo + 1024 + (foff ^ 64), xr[4], xr[5], xr[6], xr[7]);
            mbar_wait(bars + B_X1IN * 8, 0);
            if (wq == 0 || wq == 3) {
                uint4 h0 = make_uint4(0, 0, 0, 0), h1 = h0;
                const int np = wq ? pt + 1 : pt - 1;
                if (np >= 0 && np < 32) {
                    const uint4* hp = &g_halo[(((b * 32 + np) * 4 + tile) * 2 + (wq ? 0 : 1)) * 64 + lane];
                    h0 = __ldcg(hp); h1 = __ldcg(hp + 32);
                }
                stsm4(xo + (wq ? 2048 : 0) + foff, h0.x, h0.y, h0.z, h0.w);
                stsm4(xo + (wq ? 2048 : 0) + (foff ^ 64), h1.x, h1.y, h1.z, h1.w);
            }
            bar_sync(2 + w, 128);
#pragma unroll
            for (int j = 0; j < 3; j++) ldsm4t(xt + j * 2048, xw[4 * j], xw[4 * j + 1], xw[4 * j + 2], xw[4 * j + 3]);
            pin(xw);
            pin(dwr);
            acq(32); acq(33); acq(34); acq(35);
            mbar_wait(bars + B_OIN * 8, 0);
            TS(16);
            mm(d, 32, H, 0);
            mbar_wait(bars + B_OIN * 8 + 8, 0);
            mm(d, 33, H + 2 * XCH, 1);
            wg_wait<1>();
            rel(32);
            wg_wait<0>();
            pin(d);
#pragma unroll
            for (int i = 0; i < 12; i++) xw[i] = pack2(d[2 * i] + blo(xw[i]), d[2 * i + 1] + bhi(xw[i]));
            if (c4 == 0) { xw[0] = (xw[0] & 0xffff0000u) | 0x3F80u; xw[1] = (xw[1] & 0xffff0000u) | 0x3F80u; }
#pragma unroll
            for (int j = 0; j < 3; j++) stsm4t(xt + j * 2048, xw[4 * j], xw[4 * j + 1], xw[4 * j + 2], xw[4 * j + 3]);
            rel(33);
            publish(B_X2, P + tile * XCH, XCH, 384);
            TS(17);
        }
        {
            float da[24], db[24], st[24];
            bar_sync(5, 384);
            mm(da, 34, P + 2 * r * XCH, 0);
            mm(db, 35, P + 2 * r * XCH, 0);
            acq(36); acq(37);
            mbar_wait(bars + B_X2 * 8, 0);
            bar_sync(5, 384);
            TS(39);
            mm(da, 36, P + 2 * (r ^ 1) * XCH, 1);
            mm(db, 37, P + 2 * (r ^ 1) * XCH, 1);
            wg_wait<2>();
            rel(34); rel(35);
            mbar_wait(bars + B_ST * 8, 0);
#pragma unroll
            for (int j = 0; j < 6; j++) {
                const float4 u = lds128f(sb + OFF_STATS + (8 * j + 2 * c4) * 8);
                st[4 * j] = u.x; st[4 * j + 1] = u.y; st[4 * j + 2] = u.z; st[4 * j + 3] = u.w;
            }
            wg_wait<0>();
            pin(da); pin(db);
            rel(36); rel(37);
            TS(18);
            uint32_t pk[12];
#pragma unroll
            for (int hh = 0; hh < 2; hh++) {
                const float ca = __shfl_sync(~0u, da[2 * hh], lane & 28), cb = __shfl_sync(~0u, db[2 * hh], lane & 28);
#pragma unroll
                for (int j = 0; j < 6; j++) {
                    const float u0 = fmaf(-st[4 * j], ca, da[4 * j + 2 * hh] * st[4 * j + 1]);
                    const float u1 = fmaf(-st[4 * j + 2], ca, da[4 * j + 2 * hh + 1] * st[4 * j + 3]);
                    const float v0 = fmaf(-st[4 * j], cb, db[4 * j + 2 * hh] * st[4 * j + 1]);
                    const float v1 = fmaf(-st[4 * j + 2], cb, db[4 * j + 2 * hh + 1] * st[4 * j + 3]);
                    pk[2 * j + hh] = pack2(fmaf(u0, tanh_fast(v0), u0), fmaf(u1, tanh_fast(v1), u1));
                }
            }
            const uint32_t gs = H + 16384 + w * XCH;
#pragma unroll
            for (int j = 0; j < 3; j++) stsm4t(gs + toff + j * 2048, pk[4 * j], pk[4 * j + 1], pk[4 * j + 2], pk[4 * j + 3]);
            ldsm4(xo + 1024 + foff, xr[0], xr[1], xr[2], xr[3]);
            ldsm4(xo + 1024 + (foff ^ 64), xr[4], xr[5], xr[6], xr[7]);
            bar_sync(2 + w, 128);
            uint32_t ca[8], cb[8];
            const uint32_t grow = gs + 8 * wq * 128 + c4 * 4, srow = H + tile * HCH + 8 * wq * 128 + c4 * 4;
#pragma unroll
            for (int k = 0; k < 22; k++) {
                const uint32_t v = lds32(grow + (1 + k) * 128 + (((lane >> 2) ^ ((1 + k) & 7)) << 4));
#pragma unroll
                for (int i = 0; i < 8; i++) {
                    const int tap = k - i;
                    if (tap == 0) ca[i] = hmul2(v, dwr[0]);
                    else if (tap > 0 && tap < 8) ca[i] = hfma2(v, dwr[tap], ca[i]);
                    else if (tap == 8) cb[i] = hmul2(v, dwr[8]);
                    else if (tap > 8 && tap < 15) cb[i] = hfma2(v, dwr[tap], cb[i]);
                }
            }
#pragma unroll
            for (int i = 0; i < 8; i++) {
                const float h0 = blo(ca[i]) + blo(cb[i]), h1 = bhi(ca[i]) + bhi(cb[i]);
                sts32(srow + i * 128 + (((lane >> 2) ^ i) << 4), pack2(fmaf(h0, tanh_fast(h0), h0), fmaf(h1, tanh_fast(h1), h1)));
            }
            acq(38); acq(39);
            publish(B_SR, H + tile * HCH, HCH, 256);
            TS(19);
        }
        {
            auto frags = [&](int i, int half) {
                const uint32_t src = H + 2 * half * HCH + wq * 1024;
#pragma unroll
                for (int k = 0; k < 4; k++) ldsm4(src + (k >> 1) * HCH + (foff ^ ((k & 1) * 64)), a[i + 4 * k], a[i + 4 * k + 1], a[i + 4 * k + 2], a[i + 4 * k + 3]);
            };
            frags(0, r);
            sp(d0, 38, a, 0, 0);
            acq(40);
            mbar_wait(bars + B_SR * 8, 0);
            frags(16, r ^ 1);
            sp(d0, 39, a + 16, 0, 1);
            wg_wait<1>();
            rel(38);
            wg_wait<0>();
            pin(d0);
            rel(39);
#pragma unroll
            for (int j = 0; j < 8; j++) {
                v[2 * j] = d0[4 * j] + d0[4 * j + 2] + blo(xr[j]);
                v[2 * j + 1] = d0[4 * j + 1] + d0[4 * j + 3] + bhi(xr[j]);
            }
            TS(20);
        }
    }

    cluster_arrive();
    TS(24);
    {
        const float rstd = rsq(fmaxf(fmaf(-mean, mean, msq), 0.f) + 1e-5f), nb = -mean * rstd;
#pragma unroll
        for (int j = 0; j < 8; j++) xr[j] = pack2(fmaf(v[2 * j], rstd, nb), fmaf(v[2 * j + 1], rstd, nb));
        const uint32_t stg = P + 16384 + warp * 1024;
        stsm4(stg + foff, xr[0], xr[1], xr[2], xr[3]);
        stsm4(stg + (foff ^ 64), xr[4], xr[5], xr[6], xr[7]);
        __syncwarp();
        const uint32_t src = stg + (lane >> 3) * 128 + (((lane & 7) ^ (lane >> 3)) << 4);
        const uint4 u0 = lds128(src), u1 = lds128((src + 512) ^ 64);
        __nv_bfloat16* dst = p.out + (size_t)(b * T_ + trow + (lane >> 3)) * 256 + tile * 64 + (lane & 7) * 8;
        if (trow < T_) { stg128(dst, u0); stg128(dst + 4 * 256, u1); }
    }
    TS(25);
    TG(31);
    TSDUMP();
    cluster_wait();
}

typedef CUresult (*EncodeFn)(CUtensorMap*, CUtensorMapDataType, cuuint32_t, void*, const cuuint64_t*, const cuuint64_t*,
                             const cuuint32_t*, const cuuint32_t*, CUtensorMapInterleave, CUtensorMapSwizzle,
                             CUtensorMapL2promotion, CUtensorMapFloatOOBfill);

}

extern "C" void kernel_launch(void* const* d_in, const int* in_sizes, int n_in, void* d_out, int out_size) {
    static EncodeFn encode = nullptr;
    if (!encode) {
        void* fn = nullptr;
        cudaDriverEntryPointQueryResult qr;
        cudaGetDriverEntryPoint("cuTensorMapEncodeTiled", &fn, cudaEnableDefault, &qr);
        encode = (EncodeFn)fn;
        cudaFuncSetAttribute(conformer_kernel, cudaFuncAttributeMaxDynamicSharedMemorySize, SMEM_LAUNCH);
    }
    Params p;
    const cuuint32_t ones[5] = {1, 1, 1, 1, 1};
    const int idx[8] = {1, 2, 3, 4, 5, 7, 8, 9};
    const int rows[8] = {256, 1024, 256, 256, 256, 256, 256, 1024};
    const int cols[8] = {1024, 256, 768, 256, 512, 256, 1024, 256};
    for (int i = 0; i < 8; i++) {
        const bool perm = i != 3 && i != 4;
        const cuuint64_t pitch = (cuuint64_t)cols[i] * 2;
        const cuuint64_t dims[5] = {(cuuint64_t)cols[i], 2, 2, 4, (cuuint64_t)rows[i] / 16};
        const cuuint64_t strides[4] = {pitch, pitch * (perm ? 8 : 2), pitch * (perm ? 2 : 4), pitch * 16};
        const cuuint32_t box[5] = {64, 2, 2, 4, 8};
        encode(&p.tm[i], CU_TENSOR_MAP_DATA_TYPE_BFLOAT16, 5, d_in[idx[i]], dims, strides, box, ones, CU_TENSOR_MAP_INTERLEAVE_NONE,
               CU_TENSOR_MAP_SWIZZLE_128B, CU_TENSOR_MAP_L2_PROMOTION_L2_128B, CU_TENSOR_MAP_FLOAT_OOB_FILL_NONE);
        p.w[i] = (const char*)d_in[idx[i]];
    }
    {
        void* kv = nullptr;
        cudaGetSymbolAddress(&kv, g_kvq);
        const cuuint64_t dims[2] = {64, 16384};
        const cuuint64_t strides[1] = {128};
        const cuuint32_t box[2] = {64, 128};
        encode(&p.tm[8], CU_TENSOR_MAP_DATA_TYPE_BFLOAT16, 2, kv, dims, strides, box, ones, CU_TENSOR_MAP_INTERLEAVE_NONE,
               CU_TENSOR_MAP_SWIZZLE_NONE, CU_TENSOR_MAP_L2_PROMOTION_L2_128B, CU_TENSOR_MAP_FLOAT_OOB_FILL_NONE);
    }
    p.x = (const __nv_bfloat16*)d_in[0];
    p.dw = (const __nv_bfloat16*)d_in[6];
    p.out = (__nv_bfloat16*)d_out;
    p.zero = 0;
    conformer_kernel<<<NCTA, NTHREADS, SMEM_LAUNCH>>>(p);
}
```

```cpp
#include <cuda_runtime.h>
#include <cuda_bf16.h>
#include <cuda.h>
#include <stdint.h>

namespace {

constexpr int T_ = 1000;
constexpr int NCTA = 128;
constexpr int NTHREADS = 512;
constexpr int NSLOT = 5;
constexpr int SLOT = 16384;
constexpr int NLOADS = 56;

constexpr uint32_t OFF_RING = 0;
constexpr uint32_t OFF_P = 163840;
constexpr uint32_t OFF_H = 188416;
constexpr uint32_t OFF_MISC = 221184;
constexpr uint32_t OFF_STATS = 229376;
constexpr uint32_t OFF_BARS = 229888;
constexpr uint32_t SMEM_BYTES = 230400;
constexpr uint32_t XCH = 6144;
constexpr uint32_t HCH = 4096;

constexpr int B_FULL = 0, B_EMPTY = 10, B_XA = 20  , B_XB = 24  , B_INB = 27  , B_X2 = 31, B_SR = 32,
              B_RST = 33, B_RDY = 34  , B_SINK = 40, B_ST = 41;

#define PACE 1
#define ODELAY 0u
#define TURN 0
#define EAGER 0x5555
constexpr int PADROWS = 1040;
constexpr int FS = 8;

struct Params {
    CUtensorMap tm[9];
    const char* w[8];
    const __nv_bfloat16* x;
    const __nv_bfloat16* dw;
    __nv_bfloat16* out;
    uint32_t zero;
};

__device__ __align__(1024) unsigned char g_kvq[3 * 8 * 1024 * 128];
__device__ __align__(1024) unsigned char g_o[8 * PADROWS * 128];
__device__ uint4 g_halo[64 * 4 * 2 * 64];
__device__ uint32_t g_flag_kv[8 * 32 * FS];
__device__ uint32_t g_reset[2 * 32];
__device__ uint32_t g_epoch[NCTA * FS];

#define TS(i) do { } while (0)
#define TSW(i) do { } while (0)
#define TG(i) do { } while (0)
#define TSINIT() do { } while (0)
#define TSDUMP() do { } while (0)
constexpr uint32_t SMEM_LAUNCH = SMEM_BYTES;

__device__ __forceinline__ uint32_t smem_u32(const void* p) { return (uint32_t)__cvta_generic_to_shared(p); }
__device__ __forceinline__ void mbar_init(uint32_t b, uint32_t c) { asm volatile("mbarrier.init.shared::cta.b64 [%0], %1;" ::"r"(b), "r"(c) : "memory"); }
__device__ __forceinline__ void mbar_arrive(uint32_t b) { asm volatile("mbarrier.arrive.shared::cta.b64 _, [%0];" ::"r"(b) : "memory"); }
__device__ __forceinline__ void mbar_arrive_tx(uint32_t b, uint32_t tx) { asm volatile("mbarrier.arrive.expect_tx.shared::cta.b64 _, [%0], %1;" ::"r"(b), "r"(tx) : "memory"); }
__device__ __forceinline__ void mbar_wait(uint32_t b, uint32_t ph) {
    asm volatile("{\n.reg .pred p, q;\n.reg .u32 c;\nmov.u32 c, 0;\n"
                 "MW_LOOP:\n.pragma \"nounroll\";\n"
                 "mbarrier.try_wait.parity.shared::cta.b64 p, [%0], %1;\n"
                 "add.u32 c, c, 1;\nsetp.lt.u32 q, c, 65536;\nnot.pred p, p;\nand.pred p, p, q;\n@p bra MW_LOOP;\n}"
                 ::"r"(b), "r"(ph) : "memory");
}
__device__ __forceinline__ bool mbar_test(uint32_t b, uint32_t ph) {
    uint32_t ok;
    asm volatile("{\n.reg .pred p;\nmbarrier.test_wait.parity.shared::cta.b64 p, [%1], %2;\nselp.u32 %0, 1, 0, p;\n}" : "=r"(ok) : "r"(b), "r"(ph) : "memory");
    return ok;
}
__device__ __forceinline__ uint32_t mapa(uint32_t a, uint32_t r) { uint32_t o; asm("mapa.shared::cluster.u32 %0, %1, %2;" : "=r"(o) : "r"(a), "r"(r)); return o; }
__device__ __forceinline__ void fence_async_smem() { asm volatile("fence.proxy.async.shared::cta;" ::: "memory"); }
__device__ __forceinline__ void fence_async_global() { asm volatile("fence.proxy.async.global;" ::: "memory"); }
__device__ __forceinline__ void bar_sync(int id, int n) { asm volatile("bar.sync %0, %1;" ::"r"(id), "r"(n) : "memory"); }
__device__ __forceinline__ void bar_arrive(int id, int n) { asm volatile("bar.arrive %0, %1;" ::"r"(id), "r"(n) : "memory"); }
__device__ __forceinline__ void cluster_arrive() { asm volatile("barrier.cluster.arrive.relaxed.aligned;" ::: "memory"); }
__device__ __forceinline__ void cluster_wait() { asm volatile("barrier.cluster.wait.aligned;" ::: "memory"); }

__device__ __forceinline__ void ring_load(uint32_t dst, const CUtensorMap* tm, int col, int row16, uint32_t bar) {
    asm volatile("{\n.reg .pred p;\nelect.sync _|p, 0xffffffff;\n"
                 "@p mbarrier.arrive.expect_tx.shared::cta.b64 _, [%2], 16384;\n"
                 "@p cp.async.bulk.tensor.5d.shared::cluster.global.mbarrier::complete_tx::bytes [%0], [%1, {%3, 0, 0, 0, %4}], [%2];\n}"
                 ::"r"(dst), "l"(tm), "r"(bar), "r"(col), "r"(row16) : "memory");
}
__device__ __forceinline__ void ring_load_both(uint32_t dst, const CUtensorMap* tm, int c1, uint32_t bar) {
    asm volatile("{\n.reg .pred p;\nelect.sync _|p, 0xffffffff;\n"
                 "@p cp.async.bulk.tensor.2d.shared::cluster.global.mbarrier::complete_tx::bytes.multicast::cluster [%0], [%1, {0, %3}], [%2], %4;\n}"
                 ::"r"(dst), "l"(tm), "r"(bar), "r"(c1), "h"((uint16_t)3) : "memory");
}
__device__ __forceinline__ void mbar_arrive_peer(uint32_t b) { asm volatile("mbarrier.arrive.relaxed.cluster.shared::cluster.b64 _, [%0];" ::"r"(b) : "memory"); }
__device__ __forceinline__ void prefetch_l2(const void* src, uint32_t bytes) {
    asm volatile("cp.async.bulk.prefetch.L2.global [%0], %1;" ::"l"(src), "r"(bytes) : "memory");
}
__device__ __forceinline__ void peer_copy(uint32_t dst, uint32_t src, uint32_t bytes, uint32_t rbar) {
    asm volatile("{\n.reg .pred p;\nelect.sync _|p, 0xffffffff;\n"
                 "@p cp.async.bulk.shared::cluster.shared::cta.mbarrier::complete_tx::bytes [%0], [%1], %2, [%3];\n}"
                 ::"r"(dst), "r"(src), "r"(bytes), "r"(rbar) : "memory");
}
__device__ __forceinline__ void st_async4(uint32_t dst, uint32_t a, uint32_t b, uint32_t c, uint32_t d, uint32_t bar) {
    asm volatile("st.async.shared::cluster.mbarrier::complete_tx::bytes.v4.b32 [%0], {%1,%2,%3,%4}, [%5];" ::"r"(dst), "r"(a), "r"(b), "r"(c), "r"(d), "r"(bar) : "memory");
}
__device__ __forceinline__ void st_async2f(uint32_t dst, float a, float b, uint32_t bar) {
    asm volatile("st.async.shared::cluster.mbarrier::complete_tx::bytes.v2.f32 [%0], {%1,%2}, [%3];" ::"r"(dst), "f"(a), "f"(b), "r"(bar) : "memory");
}
__device__ __forceinline__ void stsm4t(uint32_t a, uint32_t r0, uint32_t r1, uint32_t r2, uint32_t r3) {
    asm volatile("stmatrix.sync.aligned.m8n8.x4.trans.shared.b16 [%0], {%1,%2,%3,%4};" ::"r"(a), "r"(r0), "r"(r1), "r"(r2), "r"(r3) : "memory");
}
__device__ __forceinline__ void stsm4(uint32_t a, uint32_t r0, uint32_t r1, uint32_t r2, uint32_t r3) {
    asm volatile("stmatrix.sync.aligned.m8n8.x4.shared.b16 [%0], {%1,%2,%3,%4};" ::"r"(a), "r"(r0), "r"(r1), "r"(r2), "r"(r3) : "memory");
}
__device__ __forceinline__ void ldsm4t(uint32_t a, uint32_t& r0, uint32_t& r1, uint32_t& r2, uint32_t& r3) {
    asm volatile("ldmatrix.sync.aligned.m8n8.x4.trans.shared.b16 {%0,%1,%2,%3}, [%4];" : "=r"(r0), "=r"(r1), "=r"(r2), "=r"(r3) : "r"(a) : "memory");
}
__device__ __forceinline__ void ldsm4(uint32_t a, uint32_t& r0, uint32_t& r1, uint32_t& r2, uint32_t& r3) {
    asm volatile("ldmatrix.sync.aligned.m8n8.x4.shared.b16 {%0,%1,%2,%3}, [%4];" : "=r"(r0), "=r"(r1), "=r"(r2), "=r"(r3) : "r"(a) : "memory");
}
__device__ __forceinline__ uint4 lds128(uint32_t a) { uint4 v; asm volatile("ld.shared.v4.b32 {%0,%1,%2,%3}, [%4];" : "=r"(v.x), "=r"(v.y), "=r"(v.z), "=r"(v.w) : "r"(a) : "memory"); return v; }
__device__ __forceinline__ float4 lds128f(uint32_t a) { float4 v; asm volatile("ld.shared.v4.f32 {%0,%1,%2,%3}, [%4];" : "=f"(v.x), "=f"(v.y), "=f"(v.z), "=f"(v.w) : "r"(a) : "memory"); return v; }
__device__ __forceinline__ float2 lds64f(uint32_t a) { float2 v; asm volatile("ld.shared.v2.f32 {%0,%1}, [%2];" : "=f"(v.x), "=f"(v.y) : "r"(a) : "memory"); return v; }
__device__ __forceinline__ uint32_t lds32(uint32_t a) { uint32_t v; asm volatile("ld.shared.b32 %0, [%1];" : "=r"(v) : "r"(a) : "memory"); return v; }
__device__ __forceinline__ void sts128(uint32_t a, uint32_t x, uint32_t y, uint32_t z, uint32_t w) { asm volatile("st.shared.v4.b32 [%0], {%1,%2,%3,%4};" ::"r"(a), "r"(x), "r"(y), "r"(z), "r"(w) : "memory"); }
__device__ __forceinline__ void sts128f(uint32_t a, float x, float y, float z, float w) { asm volatile("st.shared.v4.f32 [%0], {%1,%2,%3,%4};" ::"r"(a), "f"(x), "f"(y), "f"(z), "f"(w) : "memory"); }
__device__ __forceinline__ void sts64f(uint32_t a, float x, float y) { asm volatile("st.shared.v2.f32 [%0], {%1,%2};" ::"r"(a), "f"(x), "f"(y) : "memory"); }
__device__ __forceinline__ void sts32(uint32_t a, uint32_t x) { asm volatile("st.shared.b32 [%0], %1;" ::"r"(a), "r"(x) : "memory"); }
__device__ __forceinline__ void stg128(void* p, uint4 v) { asm volatile("st.global.v4.b32 [%0], {%1,%2,%3,%4};" ::"l"(p), "r"(v.x), "r"(v.y), "r"(v.z), "r"(v.w) : "memory"); }

__device__ __forceinline__ uint32_t pack2(float lo, float hi) { uint32_t r; asm("cvt.rn.bf16x2.f32 %0, %1, %2;" : "=r"(r) : "f"(hi), "f"(lo)); return r; }
__device__ __forceinline__ float blo(uint32_t v) { return __uint_as_float(v << 16); }
__device__ __forceinline__ float bhi(uint32_t v) { return __uint_as_float(v & 0xffff0000u); }
__device__ __forceinline__ uint32_t hmul2(uint32_t a, uint32_t b) { uint32_t r; asm("mul.rn.bf16x2 %0, %1, %2;" : "=r"(r) : "r"(a), "r"(b)); return r; }
__device__ __forceinline__ uint32_t hsub2(uint32_t a, uint32_t b) { uint32_t r; asm("sub.rn.bf16x2 %0, %1, %2;" : "=r"(r) : "r"(a), "r"(b)); return r; }
__device__ __forceinline__ uint32_t hfma2(uint32_t a, uint32_t b, uint32_t c) { uint32_t r; asm("fma.rn.bf16x2 %0, %1, %2, %3;" : "=r"(r) : "r"(a), "r"(b), "r"(c)); return r; }
__device__ __forceinline__ float tanh_fast(float x) { float r; asm("tanh.approx.f32 %0, %1;" : "=f"(r) : "f"(x)); return r; }
__device__ __forceinline__ float rsq(float x) { float r; asm("rsqrt.approx.ftz.f32 %0, %1;" : "=f"(r) : "f"(x)); return r; }
__device__ __forceinline__ float ex2(float x) { float r; asm("ex2.approx.ftz.f32 %0, %1;" : "=f"(r) : "f"(x)); return r; }

__device__ __forceinline__ uint32_t ld_relaxed(const uint32_t* p) {
    uint32_t v;
    asm volatile("ld.relaxed.gpu.global.u32 %0, [%1];" : "=r"(v) : "l"(p) : "memory");
    return v;
}
__device__ __forceinline__ void flag_wait(const uint32_t* p, uint32_t e, uint32_t mask, uint32_t& seen) {
    if ((seen & mask) == mask) return;
    uint32_t a = ld_relaxed(p);
    const uint32_t t0 = clock();
    while (clock() - t0 < 200u) {}
#pragma unroll 1
    for (int i = 0; i < (1 << 19); i++) {
        const uint32_t b = ld_relaxed(p);
        seen = __ballot_sync(~0u, a == e);
        if ((seen & mask) == mask) break;
        a = ld_relaxed(p);
        seen = __ballot_sync(~0u, b == e);
        if ((seen & mask) == mask) break;
    }
    asm volatile("fence.acquire.gpu;" ::: "memory");
    fence_async_global();
}
__device__ __forceinline__ void st_data(void* p, uint32_t x, uint32_t y, uint32_t z, uint32_t w) {
    asm volatile("st.relaxed.gpu.global.v4.b32 [%0], {%1,%2,%3,%4};" ::"l"(p), "r"(x), "r"(y), "r"(z), "r"(w) : "memory");
}
template <int N>
__device__ __forceinline__ void ld_data(uint4 (&v)[N], const unsigned char* p, uint32_t stride) {
#pragma unroll
    for (int i = 0; i < N; i++) v[i].x = ~0u;
#pragma unroll 1
    for (int it = 0; it < (1 << 16); it++) {
        bool missing = false;
#pragma unroll
        for (int i = 0; i < N; i++)
            if (max(__vimax3_u32(v[i].x, v[i].y, v[i].z), v[i].w) == ~0u) {
                asm volatile("ld.relaxed.gpu.global.v4.b32 {%0,%1,%2,%3}, [%4];" : "=r"(v[i].x), "=r"(v[i].y), "=r"(v[i].z), "=r"(v[i].w) : "l"(p + i * stride) : "memory");
                missing = true;
            }
        if (!__any_sync(~0u, missing)) break;
    }
}
__device__ __forceinline__ uint32_t ld_epoch() { return ld_relaxed(&g_epoch[blockIdx.x * FS]) + 1; }
__device__ __forceinline__ void flag_set(uint32_t* p, uint32_t e) { asm volatile("st.release.gpu.global.u32 [%0], %1;" ::"l"(p), "r"(e) : "memory"); }

__device__ __forceinline__ uint32_t desc_lo(uint32_t addr) { return ((addr & 0x3FFFF) >> 4) | 0x10000u; }
__device__ __forceinline__ uint64_t mkdesc(uint32_t lo) { return (uint64_t)lo | (0x40000040ull << 32); }
__device__ __forceinline__ void wg_fence() { asm volatile("wgmma.fence.sync.aligned;" ::: "memory"); }
__device__ __forceinline__ void wg_commit() { asm volatile("wgmma.commit_group.sync.aligned;" ::: "memory"); }
template <int N> __device__ __forceinline__ void wg_wait() { asm volatile("wgmma.wait_group.sync.aligned %0;" ::"n"(N) : "memory"); }
template <int N> __device__ __forceinline__ void pin(float (&d)[N]) {
#pragma unroll
    for (int i = 0; i < N; i++) asm volatile("" : "+f"(d[i])::"memory");
}
template <int N> __device__ __forceinline__ void pin(uint32_t (&d)[N]) {
#pragma unroll
    for (int i = 0; i < N; i++) asm volatile("" : "+r"(d[i])::"memory");
}

template <typename Tp, int N> __device__ __forceinline__ void zero(Tp (&d)[N]) {
#pragma unroll
    for (int i = 0; i < N; i++) d[i] = 0;
    pin(d);
}

#define F4(d, i) "+f"(d[i]), "+f"(d[i + 1]), "+f"(d[i + 2]), "+f"(d[i + 3])
#define F16(d, i) F4(d, i), F4(d, i + 4), F4(d, i + 8), F4(d, i + 12)

__device__ __forceinline__ void mma_sp(float (&d)[32], const uint32_t* a, uint64_t b, uint32_t meta, int acc) {
    asm volatile("{.reg .pred p; setp.ne.b32 p, %38, 0;\n"
                 "wgmma.mma_async.sp.sync.aligned.m64n64k32.f32.bf16.bf16 {%0,%1,%2,%3,%4,%5,%6,%7,%8,%9,%10,%11,%12,%13,%14,%15,%16,%17,%18,%19,%20,%21,%22,%23,%24,%25,%26,%27,%28,%29,%30,%31}, "
                 "{%32,%33,%34,%35}, %36, %37, 0, p, 1, 1, 1;}\n"
                 : F16(d, 0), F16(d, 16) : "r"(a[0]), "r"(a[1]), "r"(a[2]), "r"(a[3]), "l"(b), "r"(meta), "r"(acc));
}
__device__ __forceinline__ void mma_t(float (&d)[24], uint64_t a, uint64_t b, int acc) {
    asm volatile("{.reg .pred p; setp.ne.b32 p, %26, 0;\n"
                 "wgmma.mma_async.sync.aligned.m64n48k16.f32.bf16.bf16 {%0,%1,%2,%3,%4,%5,%6,%7,%8,%9,%10,%11,%12,%13,%14,%15,%16,%17,%18,%19,%20,%21,%22,%23}, %24, %25, p, 1, 1, 1, 0;}\n"
                 : F16(d, 0), F4(d, 16), F4(d, 20) : "l"(a), "l"(b), "r"(acc));
}
__device__ __forceinline__ void mma_qk(float (&d)[32], uint32_t a0, uint32_t a1, uint32_t a2, uint32_t a3, uint64_t b, int acc) {
    asm volatile("{.reg .pred p; setp.ne.b32 p, %37, 0;\n"
                 "wgmma.mma_async.sync.aligned.m64n64k16.f32.bf16.bf16 {%0,%1,%2,%3,%4,%5,%6,%7,%8,%9,%10,%11,%12,%13,%14,%15,%16,%17,%18,%19,%20,%21,%22,%23,%24,%25,%26,%27,%28,%29,%30,%31}, "
                 "{%32,%33,%34,%35}, %36, p, 1, 1, 0;}\n"
                 : F16(d, 0), F16(d, 16) : "r"(a0), "r"(a1), "r"(a2), "r"(a3), "l"(b), "r"(acc));
}
__device__ __forceinline__ void mma_pv(float (&d)[36], uint32_t a0, uint32_t a1, uint32_t a2, uint32_t a3, uint64_t b) {
    asm volatile("wgmma.mma_async.sync.aligned.m64n72k16.f32.bf16.bf16 {%0,%1,%2,%3,%4,%5,%6,%7,%8,%9,%10,%11,%12,%13,%14,%15,%16,%17,%18,%19,%20,%21,%22,%23,%24,%25,%26,%27,%28,%29,%30,%31,%32,%33,%34,%35}, "
                 "{%36,%37,%38,%39}, %40, 1, 1, 1, 1;\n"
                 : F16(d, 0), F16(d, 16), F4(d, 32) : "r"(a0), "r"(a1), "r"(a2), "r"(a3), "l"(b));
}

__device__ __forceinline__ uint32_t load_code(int n, int r, int w) {
    const int tile = 2 * r + w;
    int m, col, row;
    if (n < 16 || n >= 40) {
        const int k = n < 16 ? n : n - 40;
        m = n < 16 ? 0 : 6;
        if (k < 8) { col = 4 * tile + (k >> 1); row = (k & 1) ^ r; }
        else { m++; col = tile ^ (3 - ((k - 8) >> 1)); row = 2 * tile + (k & 1); }
    } else if (n < 32) {
        const int k = n - 16;
        m = 2;
        if (k < 4) { col = tile + ((k & 1) ? 8 : 4); row = (k >> 1) ^ r; }
        else { col = tile; row = (k & 1) ^ r; }
    } else if (n < 34) { m = 3; col = tile; row = n - 32; }
    else if (n < 38) { const int k = n - 34; m = 4; col = tile + 4 * (k & 1); row = (k >> 1) ^ r; }
    else { m = 5; col = tile; row = (n & 1) ^ r; }
    return m | (col << 4) | (row << 8);
}

__global__ void __cluster_dims__(2, 1, 1) __launch_bounds__(NTHREADS, 1)
conformer_kernel(const __grid_constant__ Params p) {
    extern __shared__ __align__(1024) unsigned char smem_raw[];
    const uint32_t sb = smem_u32(smem_raw);
    const uint32_t bars = sb + OFF_BARS;
    const int tid = threadIdx.x;
    const int lane = tid & 31;
    const int warp = __shfl_sync(~0u, tid >> 5, 0);
    const int r = blockIdx.x & 1;
    const int pair = blockIdx.x >> 1;
    const int b = pair >> 5, pt = pair & 31;
    const int ah = pt >> 3, qt = (pt & 7) * 2 + r;
    const int abh = b * 4 + ah;

    TG(30);
    TSINIT();
    TS(0);
    const uint32_t P = sb + OFF_P, H = sb + OFF_H;

    if (warp >= 8) {
        asm volatile("setmaxnreg.dec.sync.aligned.u32 48;");
        if (warp >= 12) {
            cluster_arrive();
            cluster_wait();
            const int ut = tid & 127;
            mbar_wait(bars + B_XA * 8, 0);
#pragma unroll
            for (int i = 0; i < 4; i++) {
                st_data(g_kvq + 2097152 + (size_t)((b * 4 + 2 * r + (i >> 1)) * 1024 + pt * 32) * 128 + (i & 1) * 2048 + ut * 16, ~0u, ~0u, ~0u, ~0u);
                st_data(g_o + (size_t)(abh * PADROWS + 8 + qt * 64) * 128 + i * 2048 + ut * 16, ~0u, ~0u, ~0u, ~0u);
                if (i < 2) st_data(&g_halo[(pair * 4 + 2 * r + i) * 128 + ut], ~0u, ~0u, ~0u, ~0u);
            }
            bar_sync(11, 128);
            if (warp == 12) {
                const uint32_t target = ld_epoch() * 64;
                if (lane == 0) {
                    asm volatile("red.release.gpu.global.add.u32 [%0], 1;" ::"l"(&g_reset[b * 32]) : "memory");
#pragma unroll 1
                    for (int i = 0; i < (1 << 20) && ld_relaxed(&g_reset[b * 32]) != target; i++) {}
                    asm volatile("fence.acquire.gpu;" ::: "memory");
                    mbar_arrive(bars + B_RST * 8);
                }
                __syncwarp();
                TS(13);
            }
            const uint32_t a8 = P + (ut >> 3) * 128 + (ut & 7) * 16;
            float s[3] = {0.f, 0.f, 0.f}, q[3] = {0.f, 0.f, 0.f};
#pragma unroll 1
            for (int h = 0; h < 2; h++) {
                if (h == 0) bar_sync(1, 384);
                else mbar_wait(bars + B_X2 * 8, 0);
                uint4 v[6];
#pragma unroll
                for (int i = 0; i < 6; i++) v[i] = lds128(a8 + (2 * (r ^ h) + (i & 1)) * XCH + (i >> 1) * 2048);
                bar_arrive(5 + ((v[0].w | v[1].w | v[2].w | v[3].w | v[4].w | v[5].w) & p.zero), 384);
                uint32_t t;
                asm volatile("mov.u32 %0, %%clock;" : "=r"(t)::"memory");
                const uint32_t mul = 65536u + (t & p.zero), msk = 0u - mul;
#pragma unroll
                for (int i = 0; i < 6; i++) {
                    const float a0 = __uint_as_float(v[i].x * mul), a1 = __uint_as_float(v[i].x & msk), a2 = __uint_as_float(v[i].y * mul), a3 = __uint_as_float(v[i].y & msk);
                    const float a4 = __uint_as_float(v[i].z * mul), a5 = __uint_as_float(v[i].z & msk), a6 = __uint_as_float(v[i].w * mul), a7 = __uint_as_float(v[i].w & msk);
                    s[i >> 1] += ((a0 + a1) + (a2 + a3)) + ((a4 + a5) + (a6 + a7));
                    q[i >> 1] += fmaf(a0, a0, fmaf(a1, a1, fmaf(a2, a2, a3 * a3))) + fmaf(a4, a4, fmaf(a5, a5, fmaf(a6, a6, a7 * a7)));
                }
            }
#pragma unroll
            for (int o = 1; o < 8; o <<= 1) {
#pragma unroll
                for (int i = 0; i < 3; i++) { s[i] += __shfl_xor_sync(~0u, s[i], o); q[i] += __shfl_xor_sync(~0u, q[i], o); }
            }
            const int k = ut & 7, row = (ut >> 3) + 16 * k;
            const float mean = (k == 0 ? s[0] : (k == 1 ? s[1] : s[2])) * (1.f / 256.f);
            const float msq = (k == 0 ? q[0] : (k == 1 ? q[1] : q[2])) * (1.f / 256.f);
            const float alpha = (uint32_t)(pt * 32 - 8 + row) >= T_ ? 0.f : 0.5f;
            const float rstd = alpha * rsq(fmaxf(fmaf(-mean, mean, msq), 0.f) + 1e-5f);
            if (k < 3) sts64f(sb + OFF_STATS + row * 8, mean * rstd, rstd);
            __syncwarp();
            if (lane == 0) mbar_arrive(bars + B_ST * 8);
            TS(4);
        } else if (warp < 10) {
            const int w = warp - 8;
            const uint32_t ring = sb + OFF_RING + w * NSLOT * SLOT;
            const uint32_t full = bars + (B_FULL + w * NSLOT) * 8;
            if (lane == 0) {
#pragma unroll
                for (int i = 0; i < NSLOT; i++) { mbar_init(full + i * 8, 1); mbar_init(full + (B_EMPTY - B_FULL + i) * 8, 4); }
                asm volatile("fence.mbarrier_init.release.cluster;" ::: "memory");
                fence_async_smem();
            }
            __syncwarp();
            cluster_arrive();
            TS(1);
#pragma unroll
            for (int n = 0; n < NSLOT; n++) {
                if (n == 1 || n == 2) bar_sync(12, 64);
                ring_load(ring + n * SLOT, &p.tm[0], 64 * (8 * r + 4 * w + (n >> 1)), 8 * ((n & 1) ^ r), full + n * 8);
            }
            TS(2);
            const uint32_t code = load_code(lane, r, w) | (load_code(lane + 32, r, w) << 16);
            cluster_wait();
            uint32_t s = 0, ph = 0;
            int n = NSLOT;
#pragma unroll 1
            for (int seg = 0; seg < 2; seg++) {
#pragma unroll 1
                for (; n < (seg == 0 ? 22 : NLOADS); n++) {
                    const uint32_t c = __shfl_sync(~0u, code, n) >> (n & 32 ? 16 : 0);
                    const CUtensorMap* tm = &p.tm[c & 15];
                    const uint32_t col = (c & 0xf0) * 4, row = (c & 0xff00) >> 5, dst = ring + s * SLOT;
                    mbar_wait(full + (B_EMPTY - B_FULL) * 8 + s * 8, ph + (((uint32_t)(size_t)tm | col | row | dst) & p.zero));
                    ring_load(dst, tm, col, row, full + s * 8);
                    if (++s == NSLOT) { s = 0; ph ^= 1; }
                }
                if (seg == 1) break;
                const uint32_t epoch = ld_epoch();
                const uint32_t rdy = bars + (B_RDY + 3 * w) * 8, prdy = mapa(rdy, r ^ 1);
                const int isv = r ^ w;
                const uint32_t* flags = g_flag_kv + (abh * 32 + lane) * FS;
                uint32_t seen = 0;
                auto kv_load = [&](uint32_t sl, int i) {
                    ring_load_both(ring + sl * SLOT, &p.tm[8], (isv * 64 + abh * 8 + 2 * i + w) * 128, full + sl * 8);
                };
#pragma unroll 1
                for (int i = 0; i < 2; i++) {
                    if (lane < 3 + i) {
                        const uint32_t sl = i ? lane : lane + 2;
                        mbar_wait(full + (B_EMPTY - B_FULL + sl) * 8, i ^ 1);
                        mbar_arrive_tx(full + sl * 8, (i || lane == 2) ? SLOT : 0);
                    }
                    __syncwarp();
                }
                if (lane == 0) mbar_arrive_peer(prdy);
                mbar_wait(rdy, 0);
#pragma unroll 1
                for (int j = isv; j < 3; j++) {
                    flag_wait(flags, epoch, 0xfu << (8 * (j - isv) + 4 * w), seen);
                    if (j == 0) TSW(5);
                    if (j == 1 && PACE) mbar_wait(full + 32, 0);
                    if (j == 2) mbar_wait(full + isv * 8, 1);
                    kv_load(j ? 2 * j - 2 + isv : 4, j - isv);
                }
                flag_wait(flags, epoch, ~0u, seen);
#pragma unroll 1
                for (int i = 0; i < 3; i++) {
                    const uint32_t sl = i ? i - 1 : 4, bo = i == 2 ? 16 : 8;
                    mbar_wait(full + (B_EMPTY - B_FULL + sl) * 8, i != 0);
                    if (lane == 0) mbar_arrive_tx(full + sl * 8, SLOT);
                    if ((i != 0) == (isv == 1)) {
                        mbar_wait(rdy + bo, 0);
                        kv_load(sl, i == 1 ? 2 : 3);
                    } else if (lane == 0) mbar_arrive_peer(prdy + bo);
                    __syncwarp();
                }
                n = 32; s = 2; ph = 1;
            }
        } else if (warp == 10) {
            if (lane == 0) {
#pragma unroll
                for (int i = B_XA; i <= B_ST; i++) mbar_init(bars + i * 8, i == B_ST ? 4 : 1);
#pragma unroll
                for (int i = B_XA; i <= B_SR; i++) mbar_arrive_tx(bars + i * 8, i < B_XB ? 512 : (i == B_X2 ? 12288 : 8192));
                asm volatile("fence.mbarrier_init.release.cluster;" ::: "memory");
                fence_async_smem();
            }
            __syncwarp();
            cluster_arrive();
            cluster_wait();
        } else {
            const uint32_t kb = (lane < 2 || lane > 5) ? 4096 : (lane == 2 ? 3072 : (lane == 4 ? 2048 : 1024));
            const char* pf = p.w[lane & 7] + blockIdx.x * kb;
            cluster_arrive();
            cluster_wait();
            if (lane < 2) prefetch_l2(pf, kb);
            mbar_wait(bars + B_XA * 8, 0);
            if (lane == 2) prefetch_l2(pf, kb);
            if (lane >= 1 && lane < 9) asm volatile("prefetch.tensormap [%0];" ::"l"(&p.tm[lane]) : "memory");
            mbar_wait(bars + (B_FULL + 1) * 8, 1);
            if (lane > 2 && lane < 8) prefetch_l2(pf, kb);
            if (lane == 8 && blockIdx.x < 15) prefetch_l2(p.dw + blockIdx.x * 256, 512);
            const uint32_t epoch = ld_epoch();
            bar_sync(4, 288);
            if (lane < 2) flag_set(&g_flag_kv[((b * 4 + 2 * r + lane) * 32 + pt) * FS], epoch);
            __syncwarp();
            TSW(8);
        }
        TSDUMP();
        return;
    }

    const int w = warp >> 2, wq = warp & 3;
    const int tile = 2 * r + w;
    const int wt = tid & 127;
    const int c4 = lane & 3;
    const int trow = pt * 32 + 8 * wq;
    uint32_t xr[8];
    {
        const uint32_t* xp = reinterpret_cast<const uint32_t*>(p.x + (size_t)(b * T_ + trow + (lane >> 2)) * 256 + tile * 64) + c4;
#pragma unroll
        for (int j = 0; j < 8; j++) xr[j] = trow < T_ ? __ldg(xp + 4 * j) : 0u;
    }
    cluster_arrive();
    asm volatile("setmaxnreg.inc.sync.aligned.u32 208;");
    const uint32_t rbase = sb + OFF_RING + w * NSLOT * SLOT, fbar = bars + (B_FULL + w * NSLOT) * 8;
    const uint32_t rdesc = desc_lo(rbase);
    auto acq = [&](int n) { mbar_wait(fbar + (n % NSLOT) * 8, (n / NSLOT) & 1); };
    auto rel = [&](int n) { if (lane == 0) mbar_arrive(fbar + (B_EMPTY - B_FULL + n % NSLOT) * 8); };
    const uint32_t foff = (lane & 7) * 128 + (((lane >> 3) ^ (lane & 7)) << 4);
    const uint32_t toff = ((lane >> 4) * 8 + (lane & 7)) * 128 + (((2 * wq + ((lane >> 3) & 1)) ^ (lane & 7)) << 4);
    auto publish = [&](int bar, uint32_t src, uint32_t bytes, int nsync) {
        fence_async_smem();
        bar_sync(2 + w, 128);
        if (wq == 0) peer_copy(mapa(src, r ^ 1), src, bytes, mapa(bars + bar * 8, r ^ 1));
        bar_sync(nsync == 384 ? 1 : 10, nsync);
    };
    float v[16];
#pragma unroll
    for (int j = 0; j < 8; j++) { v[2 * j] = blo(xr[j]); v[2 * j + 1] = bhi(xr[j]); }
    const uint32_t xown = __shfl_sync(~0u, P + wt * 16 + tile * 4096, lane), xrem = __shfl_sync(~0u, P + wt * 16 + (r ^ 1) * 8192, lane);
    const uint32_t sbuf = __shfl_sync(~0u, sb + OFF_MISC + 1024 + (8 * wq + (lane >> 2)) * 32, lane);
    const uint32_t sown = __shfl_sync(~0u, sbuf + tile * 8, lane);
    const uint32_t peer = __shfl_sync(~0u, mapa(sb, r ^ 1) - sb, lane);
    const uint32_t meta = __shfl_sync(~0u, 0xEEEE4444u + p.zero, lane);
    cluster_wait();
    TS(56);
    float mean, msq;

#pragma unroll 1
    for (int ph = 0;; ph++) {
        uint4 o0, o1;
        {
            float s = 0.f, q = 0.f, s2 = 0.f, q2 = 0.f;
#pragma unroll
            for (int j = 0; j < 4; j++) {
                s += v[4 * j] + v[4 * j + 1]; s2 += v[4 * j + 2] + v[4 * j + 3];
                q += fmaf(v[4 * j], v[4 * j], v[4 * j + 1] * v[4 * j + 1]); q2 += fmaf(v[4 * j + 2], v[4 * j + 2], v[4 * j + 3] * v[4 * j + 3]);
            }
            s += s2; q += q2;
            const uint32_t xa = bars + (B_XA + ph) * 8;
            s += __shfl_xor_sync(~0u, s, 1); q += __shfl_xor_sync(~0u, q, 1);
            s += __shfl_xor_sync(~0u, s, 2); q += __shfl_xor_sync(~0u, q, 2);
            if (c4 == 0) st_async2f(sown + peer, s, q, xa + peer);
            if (c4 == 0) sts64f(sown, s, q);
#pragma unroll
            for (int j = 0; j < 8; j++) xr[j] = pack2(v[2 * j], v[2 * j + 1]);
            sts128(xown, xr[0], xr[1], xr[2], xr[3]);
            sts128(xown + 2048, xr[4], xr[5], xr[6], xr[7]);
            bar_sync(10, 256);
            o0 = lds128(xown ^ 4096); o1 = lds128((xown ^ 4096) + 2048);
            if (ph < 3) {
                st_async4(xown + peer, xr[0], xr[1], xr[2], xr[3], xa + (B_XB - B_XA) * 8 + peer);
                st_async4(xown + peer + 2048, xr[4], xr[5], xr[6], xr[7], xa + (B_XB - B_XA) * 8 + peer);
            }
            TS(57 + ph);
            if (ph == 0) acq(0);
            mbar_wait(xa, 0);
            const float4 u0 = lds128f(sbuf), u1 = lds128f(sbuf + 16);
            mean = ((u0.x + u0.z) + (u1.x + u1.z)) * (1.f / 256.f);
            msq = ((u0.y + u0.w) + (u1.y + u1.w)) * (1.f / 256.f);
        }
        if (ph == 3) break;
        uint32_t a[32];
        const uint32_t mean2 = pack2(mean, mean);
        auto centre = [&](int i, const uint4& u) {
            a[i] = hsub2(u.x, mean2); a[i + 1] = hsub2(u.y, mean2); a[i + 2] = hsub2(u.z, mean2); a[i + 3] = hsub2(u.w, mean2);
        };
#pragma unroll
        for (int j = 0; j < 8; j++) a[j] = hsub2(xr[j], mean2);
        centre(8, o0); centre(12, o1);
        const float rstd = rsq(fmaxf(fmaf(-mean, mean, msq), 0.f) + 1e-5f);
        auto gather_peer = [&]() {
            mbar_wait(bars + (B_XB + ph) * 8, 0);
#pragma unroll
            for (int i = 0; i < 4; i++) centre(16 + 4 * i, lds128(xrem + i * 2048));
        };
        auto sp = [&](float (&d)[32], int n, const uint32_t* af, int flip, int acc) {
            const uint32_t lo = rdesc + p.zero * (ph + n + 1) + (n % NSLOT) * (SLOT >> 4);
            const uint64_t b0 = mkdesc(lo + flip * 512), b1 = mkdesc(lo + (flip ^ 1) * 512);
            wg_fence();
            mma_sp(d, af, b0, meta, acc);
            mma_sp(d, af + 4, b0 + 256, meta, 1);
            mma_sp(d, af + 8, b1, meta, 1);
            mma_sp(d, af + 12, b1 + 256, meta, 1);
            wg_commit();
        };
        float d0[32], d1[32];

        if (ph != 1) {
            uint32_t h[32];
            const float rs = 0.5f * rstd;
            const uint32_t inb = bars + (B_INB + ph) * 8, box = H + wt * 16;
            bool ready = true;
            auto step = [&](float (&d)[32], int n, const uint32_t* af, int flip, int acc, auto work) {
                if (!ready) acq(n);
                if (((TURN >> n) & 1) && w == 1) bar_sync(7, 256);
                sp(d, n, af, flip, acc);
                if (n > 0 && ((TURN >> (n - 1)) & 1) && w == 0) bar_arrive(7, 256);
                if (n < 15) ready = mbar_test(fbar + ((n + 1) % NSLOT) * 8, ((n + 1) / NSLOT) & 1);
                wg_wait<1>();
                if (n > 0 && !((EAGER >> (n - 1)) & 1)) rel(n - 1);
                const uint32_t tie = work() & p.zero;
                if ((EAGER >> n) & 1) {
                    if (p.zero < n + ph + 1) wg_wait<0>();
                    if (lane == 0) mbar_arrive(fbar + (B_EMPTY - B_FULL + n % NSLOT) * 8 + tie);
                }
            };
            auto none = []() { return 0u; };
            auto act = [&](float (&d)[32], int i) {
                pin(d);
#pragma unroll
                for (int j = 0; j < 8; j++) {
                    const float u0 = (d[4 * j] + d[4 * j + 2]) * rs, u1 = (d[4 * j + 1] + d[4 * j + 3]) * rs;
                    h[8 * i + j] = pack2(fmaf(u0, tanh_fast(u0), u0), fmaf(u1, tanh_fast(u1), u1));
                }
                return h[8 * i] | h[8 * i + 1] | h[8 * i + 2] | h[8 * i + 3] | h[8 * i + 4] | h[8 * i + 5] | h[8 * i + 6] | h[8 * i + 7];
            };
            auto send = [&](float (&d)[32], int x) {
                pin(d);
                uint32_t pk[8];
#pragma unroll
                for (int j = 0; j < 8; j++) pk[j] = pack2(d[4 * j] + d[4 * j + 2], d[4 * j + 1] + d[4 * j + 3]);
                const uint32_t ow = w ^ (x & 1), dst = box + (ow * 3 + x - 1) * 4096;
                if (x & 2) {
                    st_async4(dst + peer, pk[0], pk[1], pk[2], pk[3], inb + ow * 8 + peer);
                    st_async4(dst + peer + 2048, pk[4], pk[5], pk[6], pk[7], inb + ow * 8 + peer);
                } else {
                    sts128(dst, pk[0], pk[1], pk[2], pk[3]);
                    sts128(dst + 2048, pk[4], pk[5], pk[6], pk[7]);
                }
            };
            TS(1 + ph * 10);
            step(d0, 0, a, w, 0, [&]() { gather_peer(); return 0u; });
            TS(32);
            step(d0, 1, a + 16, 0, 1, none);
            step(d1, 2, a, w, 0, [&]() { return act(d0, 0); });
            step(d1, 3, a + 16, 0, 1, none);
            step(d0, 4, a, w, 0, [&]() { return act(d1, 1); });
            TS(33);
            step(d0, 5, a + 16, 0, 1, none);
            step(d1, 6, a, w, 0, [&]() { return act(d0, 2); });
            step(d1, 7, a + 16, 0, 1, none);
            step(d0, 8, h, 0, 0, [&]() { return act(d1, 3); });
            TS(2 + ph * 10);
            step(d0, 9, h + 16, 0, 1, none);
            step(d1, 10, h, 0, 0, [&]() { send(d0, 3); return 0u; });
            step(d1, 11, h + 16, 0, 1, none);
            step(d0, 12, h, 0, 0, [&]() { send(d1, 2); return 0u; });
            TS(34);
            step(d0, 13, h + 16, 0, 1, none);
            step(d1, 14, h, 0, 0, [&]() { send(d0, 1); return 0u; });
            step(d1, 15, h + 16, 0, 1, none);
            if (ph == 0) acq(16);
            mbar_wait(inb + w * 8, 0);
            bar_sync(10, 256);
#pragma unroll
            for (int i = 0; i < 2; i++) {
                const uint32_t src = box + w * 12288 + i * 2048;
                const uint4 u0 = lds128(src), u1 = lds128(src + 4096), u2 = lds128(src + 8192);
                const uint32_t p0[4] = {u0.x, u0.y, u0.z, u0.w}, p1[4] = {u1.x, u1.y, u1.z, u1.w}, p2[4] = {u2.x, u2.y, u2.z, u2.w};
#pragma unroll
                for (int j = 0; j < 4; j++) {
                    v[8 * i + 2 * j] = fmaf(0.5f, blo(p0[j]) + blo(p1[j]) + blo(p2[j]), blo(xr[4 * i + j]));
                    v[8 * i + 2 * j + 1] = fmaf(0.5f, bhi(p0[j]) + bhi(p1[j]) + bhi(p2[j]), bhi(xr[4 * i + j]));
                }
            }
            wg_wait<0>();
            pin(d1);
            rel(15);
            TS(3 + ph * 10);
#pragma unroll
            for (int j = 0; j < 8; j++) {
                v[2 * j] = fmaf(0.5f, d1[4 * j] + d1[4 * j + 2], v[2 * j]);
                v[2 * j + 1] = fmaf(0.5f, d1[4 * j + 1] + d1[4 * j + 3], v[2 * j + 1]);
            }
            continue;
        }

        {
            TS(11);
            sp(d0, 16, a, w, 0);
            acq(17);
            sp(d1, 17, a, w, 0);
            mbar_wait(bars + B_RST * 8, 0);
            if (wq == 0 || wq == 3) {
                uint4* hp = &g_halo[((pair * 4 + tile) * 2 + (wq & 1)) * 64 + lane];
                st_data(hp, xr[0], xr[1], xr[2], xr[3]);
                st_data(hp + 32, xr[4], xr[5], xr[6], xr[7]);
            }
            gather_peer();
            acq(18);
            sp(d0, 18, a + 16, 0, 1);
            wg_wait<1>();
            rel(16); rel(17);
            acq(19);
            sp(d1, 19, a + 16, 0, 1);
            const uint32_t stg = H + warp * 2048;
            unsigned char* g = g_kvq + (size_t)((b * 4 + tile) * 1024 + trow) * 128 + lane * 16;
            auto put = [&](float (&d)[32], int i) {
                pin(d);
                uint32_t pk[8];
#pragma unroll
                for (int j = 0; j < 8; j++) pk[j] = pack2((d[4 * j] + d[4 * j + 2]) * rstd, (d[4 * j + 1] + d[4 * j + 3]) * rstd);
                if (i == 2) {
                    st_data(g + 2097152, pk[0], pk[1], pk[2], pk[3]);
                    st_data(g + 2097152 + 512, pk[4], pk[5], pk[6], pk[7]);
                    return;
                }
                stsm4(stg + i * 1024 + foff, pk[0], pk[1], pk[2], pk[3]);
                stsm4(stg + i * 1024 + (foff ^ 64), pk[4], pk[5], pk[6], pk[7]);
                __syncwarp();
                const uint4 u0 = lds128(stg + i * 1024 + lane * 16), u1 = lds128(stg + i * 1024 + 512 + lane * 16);
                stg128(g + i * 1048576, u0); stg128(g + i * 1048576 + 512, u1);
            };
            wg_wait<1>();
            rel(18);
            put(d0, 0);
            wg_wait<0>();
            rel(19);
            TS(37);
            put(d1, 1);
            bar_arrive(4, 288);
            TS(38);
            acq(20);
            sp(d0, 20, a, w, 0);
            acq(21);
            sp(d0, 21, a + 16, 0, 1);
            wg_wait<0>();
            rel(20); rel(21);
            put(d0, 2);
            acq(22); acq(23);
            rel(22); rel(23);
            TS(12);
        }

        const uint32_t xo = P + tile * XCH + wq * 1024, xt = P + tile * XCH + toff;
        {
            constexpr float CS = 0.125f * 1.4426950408889634f;
            float sa[32], sb2[32], o[36];
            uint32_t pa[16], pb[16], q[16];
            float n0 = INFINITY, n1 = INFINITY;
            zero(o); zero(pa); zero(pb);
            const uint32_t ones = sb + OFF_MISC + 2048;
            if (tid < 128) sts128(ones + tid * 16, 0x3F803F80u, 0x3F803F80u, 0x3F803F80u, 0x3F803F80u);
            fence_async_smem();
            bar_sync(10, 256);
            stsm4(xo + 1024 + foff, xr[0], xr[1], xr[2], xr[3]);
            stsm4(xo + 1024 + (foff ^ 64), xr[4], xr[5], xr[6], xr[7]);
            if (wq == 0 || wq == 3) {
                uint4 hv[2] = {make_uint4(0, 0, 0, 0), make_uint4(0, 0, 0, 0)};
                const int np = wq ? pt + 1 : pt - 1;
                if (np >= 0 && np < 32)
                    ld_data(hv, reinterpret_cast<const unsigned char*>(&g_halo[(((b * 32 + np) * 4 + tile) * 2 + (wq ? 0 : 1)) * 64 + lane]), 512);
                stsm4(xo + (wq ? 2048 : 0) + foff, hv[0].x, hv[0].y, hv[0].z, hv[0].w);
                stsm4(xo + (wq ? 2048 : 0) + (foff ^ 64), hv[1].x, hv[1].y, hv[1].z, hv[1].w);
            }
            const uint32_t vdesc = rdesc + ((((ones - rbase) >> 4) - 1) << 16);
            auto qk_issue = [&](float (&s)[32], uint32_t lo) {
                const uint64_t kd = mkdesc(lo);
                wg_fence();
#pragma unroll
                for (int k = 0; k < 4; k++) mma_qk(s, q[4 * k], q[4 * k + 1], q[4 * k + 2], q[4 * k + 3], kd + 2 * k, k != 0);
                wg_commit();
            };
            auto pv_issue = [&](uint32_t (&pp)[16], uint32_t lo) {
                const uint64_t vd = mkdesc(lo);
                wg_fence();
#pragma unroll
                for (int k = 0; k < 4; k++) mma_pv(o, pp[4 * k], pp[4 * k + 1], pp[4 * k + 2], pp[4 * k + 3], vd - k * (128 * 65535));
                wg_commit();
            };
            auto new_max = [&](float (&s)[32], float& x0, float& x1) {
                x0 = s[0]; x1 = s[2];
#pragma unroll
                for (int j = 0; j < 8; j++) {
                    x0 = fmaxf(x0, fmaxf(s[4 * j], s[4 * j + 1]));
                    x1 = fmaxf(x1, fmaxf(s[4 * j + 2], s[4 * j + 3]));
                }
                x0 = fmaxf(x0, __shfl_xor_sync(~0u, x0, 1)); x1 = fmaxf(x1, __shfl_xor_sync(~0u, x1, 1));
                x0 = fmaxf(x0, __shfl_xor_sync(~0u, x0, 2)); x1 = fmaxf(x1, __shfl_xor_sync(~0u, x1, 2));
                x0 = fminf(n0, fmaf(x0, -CS, -20.f)); x1 = fminf(n1, fmaf(x1, -CS, -20.f));
            };
            auto probs = [&](float (&s)[32], uint32_t (&pp)[16], bool ready, auto wait) {
                uint32_t any = 0;
#pragma unroll
                for (int i = 0; i < 16; i++) {
                    pp[i] = pack2(ex2(fmaf(s[2 * i], CS, (i & 1) ? n1 : n0)), ex2(fmaf(s[2 * i + 1], CS, (i & 1) ? n1 : n0)));
                    any |= pp[i];
                }
                float sc0 = 1.f, sc1 = 1.f;
                const bool slow = __any_sync(~0u, (any & 0x40004000u) || !ready);
                if (slow) {
                    wait();
                    if (__any_sync(~0u, any & 0x40004000u)) {
                        float x0, x1;
                        new_max(s, x0, x1);
                        sc0 = ex2(x0 - n0); sc1 = ex2(x1 - n1);
                        n0 = x0; n1 = x1;
#pragma unroll
                        for (int i = 0; i < 16; i++)
                            pp[i] = pack2(ex2(fmaf(s[2 * i], CS, (i & 1) ? n1 : n0)), ex2(fmaf(s[2 * i + 1], CS, (i & 1) ? n1 : n0)));
                    }
                }
                wg_wait<0>();
                pin(sa); pin(sb2); pin(o); pin(pa); pin(pb);
                if (slow) {
#pragma unroll
                    for (int j = 0; j < 9; j++) { o[4 * j] *= sc0; o[4 * j + 1] *= sc0; o[4 * j + 2] *= sc1; o[4 * j + 3] *= sc1; }
                }
            };
            {
                uint4 u[4] = {};
                ld_data(u, g_kvq + 2097152 + (size_t)(abh * 1024 + qt * 64 + wq * 16) * 128 + lane * 16, 512);
#pragma unroll
                for (int k = 0; k < 2; k++) {
                    q[8 * k] = u[k].x; q[8 * k + 1] = u[k + 2].x; q[8 * k + 2] = u[k].y; q[8 * k + 3] = u[k + 2].y;
                    q[8 * k + 4] = u[k].z; q[8 * k + 5] = u[k + 2].z; q[8 * k + 6] = u[k].w; q[8 * k + 7] = u[k + 2].w;
                }
                pin(q);
            }
            TS(40);
            acq(24);
            TS(13);
            qk_issue(sa, rdesc + (24 % NSLOT) * (SLOT >> 4));
            qk_issue(sb2, rdesc + (24 % NSLOT) * (SLOT >> 4) + 512);
            wg_wait<1>();
            pin(sa);
            {
                float x0, x1;
                new_max(sa, x0, x1);
                n0 = x0; n1 = x1;
            }
            if (w == 1) bar_sync(7, 256);
            uint32_t vd = vdesc - (SLOT >> 4) * 65535u, kd = rdesc, vb = fbar + 8, kb = fbar;
            uint32_t vlast = vdesc - 4 * (SLOT >> 4) * 65535u;
            uint32_t kprev = fbar + 32, vprev = bars + (B_SINK - (B_EMPTY - B_FULL)) * 8;
#pragma unroll 1
            for (int it = 0; it < 4; it++) {
                pv_issue(pb, vlast);
                probs(sa, pa, mbar_test(vb, it < 2) & mbar_test(kb, it < 3), [&]() { mbar_wait(vb, it < 2); mbar_wait(kb, it < 3); });
                TS(41 + it * 4);
                if (it == 0 && w == 0) bar_arrive(7, 256);
                if (it == 3 && w == 1) {
#pragma unroll
                    for (int i = 20; i < 32; i++) sb2[i] = -INFINITY;
                }
                pin(sb2);
                if (it < 3) qk_issue(sa, kd);
                if (lane == 0) mbar_arrive(kprev + (B_EMPTY - B_FULL) * 8);
                if (lane == 0) mbar_arrive(vprev + (B_EMPTY - B_FULL) * 8);
                pv_issue(pa, vd);
                probs(sb2, pb, true, []() {});
                TS(43 + it * 4);
                if (it < 3) qk_issue(sb2, kd + 512);
                const int dv = it == 0 ? 2 : (it == 1 ? -3 : 1);
                kprev = kb; vprev = vb; vlast = vd - 512 * 65535u;
                vd -= dv * (SLOT >> 4) * 65535u; vb += dv * 8;
                kd += 2 * (SLOT >> 4); kb = it == 2 ? vb : kb + 16;
            }
            pv_issue(pb, vlast);
            const int row = wq * 16 + (lane >> 2);
            const uint32_t ml = sb + OFF_MISC;
            wg_wait<0>();
            pin(o); pin(pb); pin(sa); pin(sb2);
            rel(31);
            const float l0 = o[32], l1 = o[34];
            if (c4 == 0) { sts64f(ml + w * 512 + row * 8, n0, l0); sts64f(ml + w * 512 + row * 8 + 64, n1, l1); }
            TS(14);
            float mine[16];
#pragma unroll
            for (int j = 0; j < 4; j++) {
                if (w == 0) sts128f(H + j * 2048 + wt * 16, o[16 + 4 * j], o[17 + 4 * j], o[18 + 4 * j], o[19 + 4 * j]);
                else sts128f(H + 8192 + j * 2048 + wt * 16, o[4 * j], o[4 * j + 1], o[4 * j + 2], o[4 * j + 3]);
            }
#pragma unroll
            for (int i = 0; i < 16; i++) mine[i] = w == 0 ? o[i] : o[16 + i];
            bar_sync(10, 256);
            const float2 u0 = lds64f(ml + (w ^ 1) * 512 + row * 8), u1 = lds64f(ml + (w ^ 1) * 512 + row * 8 + 64);
            const float x0 = fminf(n0, u0.x), x1 = fminf(n1, u1.x);
            float a0 = ex2(x0 - n0), b0 = ex2(x0 - u0.x), a1 = ex2(x1 - n1), b1 = ex2(x1 - u1.x);
            const float i0 = __fdividef(1.f, fmaf(a0, l0, b0 * u0.y)), i1 = __fdividef(1.f, fmaf(a1, l1, b1 * u1.y));
            a0 *= i0; b0 *= i0; a1 *= i1; b1 *= i1;
            uint32_t pk[8];
#pragma unroll
            for (int j = 0; j < 4; j++) {
                const float4 v = lds128f(H + (w ^ 1) * 8192 + j * 2048 + wt * 16);
                pk[2 * j] = pack2(fmaf(a0, mine[4 * j], b0 * v.x), fmaf(a0, mine[4 * j + 1], b0 * v.y));
                pk[2 * j + 1] = pack2(fmaf(a1, mine[4 * j + 2], b1 * v.z), fmaf(a1, mine[4 * j + 3], b1 * v.w));
            }
            unsigned char* dst = g_o + (size_t)(abh * PADROWS + 8 + qt * 64 + wq * 16) * 128 + w * 512 + lane * 16;
            st_data(dst, pk[0], pk[2], pk[4], pk[6]);
            st_data(dst + 1024, pk[1], pk[3], pk[5], pk[7]);
            if (tid == 0) asm volatile("red.relaxed.gpu.global.add.u32 [%0], 1;" ::"l"(&g_epoch[blockIdx.x * FS]) : "memory");
            TS(15);
        }

        auto mm = [&](float (&d)[24], int n, uint32_t act, int acc) {
            const uint32_t z = p.zero * (ph + n);
            const uint64_t ad = mkdesc(rdesc + z + (n % NSLOT) * (SLOT >> 4)), bd = mkdesc(desc_lo(act) + z);
            wg_fence();
#pragma unroll
            for (int k = 0; k < 8; k++) mma_t(d, ad + k * 128, bd + (k >> 2) * (XCH >> 4) + (k & 3) * 2, k == 0 ? acc : 1);
            wg_commit();
        };
        uint32_t dwr[15];
        {
#pragma unroll
            for (int i = 0; i < 15; i++) dwr[i] = hmul2(__ldg(reinterpret_cast<const uint32_t*>(p.dw + i * 256 + tile * 64) + lane), 0x3F003F00u);
            float d[24];
            uint32_t xw[12];
#pragma unroll
            for (int j = 0; j < 3; j++) ldsm4t(xt + j * 2048, xw[4 * j], xw[4 * j + 1], xw[4 * j + 2], xw[4 * j + 3]);
            pin(xw);
            acq(32); acq(33); acq(34); acq(35);
            bar_sync(10, 256);
            {
                const uint32_t t0 = clock();
                while (clock() - t0 < ODELAY) {}
                uint4 u[6] = {};
                ld_data(u, g_o + (size_t)((b * 4 + (warp >> 1)) * PADROWS + pt * 32) * 128 + (warp & 1) * 512 + lane * 16, 1024);
                const uint32_t dst = H + (warp >> 1) * XCH + (foff ^ ((warp & 1) * 64));
#pragma unroll
                for (int i = 0; i < 6; i++) stsm4(dst + i * 1024, u[i].x, u[i].y, u[i].z, u[i].w);
            }
            fence_async_smem();
            bar_sync(10, 256);
            TS(16);
            mm(d, 32, H, 0);
            mm(d, 33, H + 2 * XCH, 1);
            wg_wait<1>();
            rel(32);
            wg_wait<0>();
            pin(d);
#pragma unroll
            for (int i = 0; i < 12; i++) xw[i] = pack2(d[2 * i] + blo(xw[i]), d[2 * i + 1] + bhi(xw[i]));
            if (c4 == 0) { xw[0] = (xw[0] & 0xffff0000u) | 0x3F80u; xw[1] = (xw[1] & 0xffff0000u) | 0x3F80u; }
#pragma unroll
            for (int j = 0; j < 3; j++) stsm4t(xt + j * 2048, xw[4 * j], xw[4 * j + 1], xw[4 * j + 2], xw[4 * j + 3]);
            rel(33);
            publish(B_X2, P + tile * XCH, XCH, 384);
            TS(17);
        }
        {
            float da[24], db[24], st[24];
            bar_sync(5, 384);
            mm(da, 34, P + 2 * r * XCH, 0);
            mm(db, 35, P + 2 * r * XCH, 0);
            acq(36); acq(37);
            mbar_wait(bars + B_X2 * 8, 0);
            bar_sync(5, 384);
            TS(39);
            mm(da, 36, P + 2 * (r ^ 1) * XCH, 1);
            mm(db, 37, P + 2 * (r ^ 1) * XCH, 1);
            wg_wait<2>();
            rel(34); rel(35);
            mbar_wait(bars + B_ST * 8, 0);
#pragma unroll
            for (int j = 0; j < 6; j++) {
                const float4 u = lds128f(sb + OFF_STATS + (8 * j + 2 * c4) * 8);
                st[4 * j] = u.x; st[4 * j + 1] = u.y; st[4 * j + 2] = u.z; st[4 * j + 3] = u.w;
            }
            wg_wait<0>();
            pin(da); pin(db);
            rel(36); rel(37);
            TS(18);
            uint32_t pk[12];
#pragma unroll
            for (int hh = 0; hh < 2; hh++) {
                const float ca = __shfl_sync(~0u, da[2 * hh], lane & 28), cb = __shfl_sync(~0u, db[2 * hh], lane & 28);
#pragma unroll
                for (int j = 0; j < 6; j++) {
                    const float u0 = fmaf(-st[4 * j], ca, da[4 * j + 2 * hh] * st[4 * j + 1]);
                    const float u1 = fmaf(-st[4 * j + 2], ca, da[4 * j + 2 * hh + 1] * st[4 * j + 3]);
                    const float v0 = fmaf(-st[4 * j], cb, db[4 * j + 2 * hh] * st[4 * j + 1]);
                    const float v1 = fmaf(-st[4 * j + 2], cb, db[4 * j + 2 * hh + 1] * st[4 * j + 3]);
                    pk[2 * j + hh] = pack2(fmaf(u0, tanh_fast(v0), u0), fmaf(u1, tanh_fast(v1), u1));
                }
            }
            const uint32_t gs = H + 16384 + w * XCH;
#pragma unroll
            for (int j = 0; j < 3; j++) stsm4t(gs + toff + j * 2048, pk[4 * j], pk[4 * j + 1], pk[4 * j + 2], pk[4 * j + 3]);
            ldsm4(xo + 1024 + foff, xr[0], xr[1], xr[2], xr[3]);
            ldsm4(xo + 1024 + (foff ^ 64), xr[4], xr[5], xr[6], xr[7]);
            bar_sync(2 + w, 128);
            uint32_t ca[8], cb[8];
            const uint32_t grow = gs + 8 * wq * 128 + c4 * 4, srow = H + tile * HCH + 8 * wq * 128 + c4 * 4;
#pragma unroll
            for (int k = 0; k < 22; k++) {
                const uint32_t v = lds32(grow + (1 + k) * 128 + (((lane >> 2) ^ ((1 + k) & 7)) << 4));
#pragma unroll
                for (int i = 0; i < 8; i++) {
                    const int tap = k - i;
                    if (tap == 0) ca[i] = hmul2(v, dwr[0]);
                    else if (tap > 0 && tap < 8) ca[i] = hfma2(v, dwr[tap], ca[i]);
                    else if (tap == 8) cb[i] = hmul2(v, dwr[8]);
                    else if (tap > 8 && tap < 15) cb[i] = hfma2(v, dwr[tap], cb[i]);
                }
            }
#pragma unroll
            for (int i = 0; i < 8; i++) {
                const float h0 = blo(ca[i]) + blo(cb[i]), h1 = bhi(ca[i]) + bhi(cb[i]);
                sts32(srow + i * 128 + (((lane >> 2) ^ i) << 4), pack2(fmaf(h0, tanh_fast(h0), h0), fmaf(h1, tanh_fast(h1), h1)));
            }
            acq(38); acq(39);
            publish(B_SR, H + tile * HCH, HCH, 256);
            TS(19);
        }
        {
            auto frags = [&](int i, int half) {
                const uint32_t src = H + 2 * half * HCH + wq * 1024;
#pragma unroll
                for (int k = 0; k < 4; k++) ldsm4(src + (k >> 1) * HCH + (foff ^ ((k & 1) * 64)), a[i + 4 * k], a[i + 4 * k + 1], a[i + 4 * k + 2], a[i + 4 * k + 3]);
            };
            frags(0, r);
            sp(d0, 38, a, 0, 0);
            acq(40);
            mbar_wait(bars + B_SR * 8, 0);
            frags(16, r ^ 1);
            sp(d0, 39, a + 16, 0, 1);
            wg_wait<1>();
            rel(38);
            wg_wait<0>();
            pin(d0);
            rel(39);
#pragma unroll
            for (int j = 0; j < 8; j++) {
                v[2 * j] = d0[4 * j] + d0[4 * j + 2] + blo(xr[j]);
                v[2 * j + 1] = d0[4 * j + 1] + d0[4 * j + 3] + bhi(xr[j]);
            }
            TS(20);
        }
    }

    cluster_arrive();
    TS(24);
    {
        const float rstd = rsq(fmaxf(fmaf(-mean, mean, msq), 0.f) + 1e-5f), nb = -mean * rstd;
#pragma unroll
        for (int j = 0; j < 8; j++) xr[j] = pack2(fmaf(v[2 * j], rstd, nb), fmaf(v[2 * j + 1], rstd, nb));
        const uint32_t stg = P + 16384 + warp * 1024;
        stsm4(stg + foff, xr[0], xr[1], xr[2], xr[3]);
        stsm4(stg + (foff ^ 64), xr[4], xr[5], xr[6], xr[7]);
        __syncwarp();
        const uint32_t src = stg + (lane >> 3) * 128 + (((lane & 7) ^ (lane >> 3)) << 4);
        const uint4 u0 = lds128(src), u1 = lds128((src + 512) ^ 64);
        __nv_bfloat16* dst = p.out + (size_t)(b * T_ + trow + (lane >> 3)) * 256 + tile * 64 + (lane & 7) * 8;
        if (trow < T_) { stg128(dst, u0); stg128(dst + 4 * 256, u1); }
    }
    TS(25);
    TG(31);
    TSDUMP();
    cluster_wait();
}

typedef CUresult (*EncodeFn)(CUtensorMap*, CUtensorMapDataType, cuuint32_t, void*, const cuuint64_t*, const cuuint64_t*,
                             const cuuint32_t*, const cuuint32_t*, CUtensorMapInterleave, CUtensorMapSwizzle,
                             CUtensorMapL2promotion, CUtensorMapFloatOOBfill);

}

extern "C" void kernel_launch(void* const* d_in, const int* in_sizes, int n_in, void* d_out, int out_size) {
    static EncodeFn encode = nullptr;
    if (!encode) {
        void* fn = nullptr;
        cudaDriverEntryPointQueryResult qr;
        cudaGetDriverEntryPoint("cuTensorMapEncodeTiled", &fn, cudaEnableDefault, &qr);
        encode = (EncodeFn)fn;
        cudaFuncSetAttribute(conformer_kernel, cudaFuncAttributeMaxDynamicSharedMemorySize, SMEM_LAUNCH);
    }
    Params p;
    const cuuint32_t ones[5] = {1, 1, 1, 1, 1};
    const int idx[8] = {1, 2, 3, 4, 5, 7, 8, 9};
    const int rows[8] = {256, 1024, 256, 256, 256, 256, 256, 1024};
    const int cols[8] = {1024, 256, 768, 256, 512, 256, 1024, 256};
    for (int i = 0; i < 8; i++) {
        const bool perm = i != 3 && i != 4;
        const cuuint64_t pitch = (cuuint64_t)cols[i] * 2;
        const cuuint64_t dims[5] = {(cuuint64_t)cols[i], 2, 2, 4, (cuuint64_t)rows[i] / 16};
        const cuuint64_t strides[4] = {pitch, pitch * (perm ? 8 : 2), pitch * (perm ? 2 : 4), pitch * 16};
        const cuuint32_t box[5] = {64, 2, 2, 4, 8};
        encode(&p.tm[i], CU_TENSOR_MAP_DATA_TYPE_BFLOAT16, 5, d_in[idx[i]], dims, strides, box, ones, CU_TENSOR_MAP_INTERLEAVE_NONE,
               CU_TENSOR_MAP_SWIZZLE_128B, CU_TENSOR_MAP_L2_PROMOTION_L2_128B, CU_TENSOR_MAP_FLOAT_OOB_FILL_NONE);
        p.w[i] = (const char*)d_in[idx[i]];
    }
    {
        void* kv = nullptr;
        cudaGetSymbolAddress(&kv, g_kvq);
        const cuuint64_t dims[2] = {64, 16384};
        const cuuint64_t strides[1] = {128};
        const cuuint32_t box[2] = {64, 128};
        encode(&p.tm[8], CU_TENSOR_MAP_DATA_TYPE_BFLOAT16, 2, kv, dims, strides, box, ones, CU_TENSOR_MAP_INTERLEAVE_NONE,
               CU_TENSOR_MAP_SWIZZLE_NONE, CU_TENSOR_MAP_L2_PROMOTION_L2_128B, CU_TENSOR_MAP_FLOAT_OOB_FILL_NONE);
    }
    p.x = (const __nv_bfloat16*)d_in[0];
    p.dw = (const __nv_bfloat16*)d_in[6];
    p.out = (__nv_bfloat16*)d_out;
    p.zero = 0;
    conformer_kernel<<<NCTA, NTHREADS, SMEM_LAUNCH>>>(p);
}
```

```cpp
#include <cuda_runtime.h>
#include <cuda_bf16.h>
#include <cuda.h>
#include <stdint.h>

namespace {

constexpr int T_ = 1000;
constexpr int NCTA = 128;
constexpr int NTHREADS = 512;
constexpr int NSLOT = 5;
constexpr int SLOT = 16384;
constexpr int NLOADS = 56;

constexpr uint32_t OFF_RING = 0;
constexpr uint32_t OFF_P = 163840;
constexpr uint32_t OFF_H = 188416;
constexpr uint32_t OFF_MISC = 221184;
constexpr uint32_t OFF_STATS = 229376;
constexpr uint32_t OFF_BARS = 229888;
constexpr uint32_t SMEM_BYTES = 230400;
constexpr uint32_t XCH = 6144;
constexpr uint32_t HCH = 4096;

constexpr int B_FULL = 0, B_EMPTY = 10, B_XA = 20  , B_XB = 24  , B_INB = 27  , B_X2 = 31, B_SR = 32,
              B_RST = 33, B_RDY = 34  , B_SINK = 40, B_ST = 41;

#define PACE 1
#define ODELAY 0u
#define RSTAT 1
#define TURN 0
#define EAGER 0x5555
constexpr int PADROWS = 1040;
constexpr int FS = 8;

struct Params {
    CUtensorMap tm[9];
    const char* w[8];
    const __nv_bfloat16* x;
    const __nv_bfloat16* dw;
    __nv_bfloat16* out;
    uint32_t zero;
};

__device__ __align__(1024) unsigned char g_kvq[3 * 8 * 1024 * 128];
__device__ __align__(1024) unsigned char g_o[8 * PADROWS * 128];
__device__ uint4 g_halo[64 * 4 * 2 * 64];
__device__ uint32_t g_flag_kv[2 * 8 * 32 * FS];
__device__ uint32_t g_reset[2 * 32];
__device__ uint32_t g_epoch[NCTA * FS];

#define TS(i) do { } while (0)
#define TSW(i) do { } while (0)
#define TG(i) do { } while (0)
#define TSINIT() do { } while (0)
#define TSDUMP() do { } while (0)
constexpr uint32_t SMEM_LAUNCH = SMEM_BYTES;

__device__ __forceinline__ uint32_t smem_u32(const void* p) { return (uint32_t)__cvta_generic_to_shared(p); }
__device__ __forceinline__ void mbar_init(uint32_t b, uint32_t c) { asm volatile("mbarrier.init.shared::cta.b64 [%0], %1;" ::"r"(b), "r"(c) : "memory"); }
__device__ __forceinline__ void mbar_arrive(uint32_t b) { asm volatile("mbarrier.arrive.shared::cta.b64 _, [%0];" ::"r"(b) : "memory"); }
__device__ __forceinline__ void mbar_arrive_tx(uint32_t b, uint32_t tx) { asm volatile("mbarrier.arrive.expect_tx.shared::cta.b64 _, [%0], %1;" ::"r"(b), "r"(tx) : "memory"); }
__device__ __forceinline__ void mbar_wait(uint32_t b, uint32_t ph) {
    asm volatile("{\n.reg .pred p, q;\n.reg .u32 c;\nmov.u32 c, 0;\n"
                 "MW_LOOP:\n.pragma \"nounroll\";\n"
                 "mbarrier.try_wait.parity.shared::cta.b64 p, [%0], %1;\n"
                 "add.u32 c, c, 1;\nsetp.lt.u32 q, c, 65536;\nnot.pred p, p;\nand.pred p, p, q;\n@p bra MW_LOOP;\n}"
                 ::"r"(b), "r"(ph) : "memory");
}
__device__ __forceinline__ bool mbar_test(uint32_t b, uint32_t ph) {
    uint32_t ok;
    asm volatile("{\n.reg .pred p;\nmbarrier.test_wait.parity.shared::cta.b64 p, [%1], %2;\nselp.u32 %0, 1, 0, p;\n}" : "=r"(ok) : "r"(b), "r"(ph) : "memory");
    return ok;
}
__device__ __forceinline__ uint32_t mapa(uint32_t a, uint32_t r) { uint32_t o; asm("mapa.shared::cluster.u32 %0, %1, %2;" : "=r"(o) : "r"(a), "r"(r)); return o; }
__device__ __forceinline__ void fence_async_smem() { asm volatile("fence.proxy.async.shared::cta;" ::: "memory"); }
__device__ __forceinline__ void fence_async_global() { asm volatile("fence.proxy.async.global;" ::: "memory"); }
__device__ __forceinline__ void bar_sync(int id, int n) { asm volatile("bar.sync %0, %1;" ::"r"(id), "r"(n) : "memory"); }
__device__ __forceinline__ void bar_arrive(int id, int n) { asm volatile("bar.arrive %0, %1;" ::"r"(id), "r"(n) : "memory"); }
__device__ __forceinline__ void cluster_arrive() { asm volatile("barrier.cluster.arrive.relaxed.aligned;" ::: "memory"); }
__device__ __forceinline__ void cluster_wait() { asm volatile("barrier.cluster.wait.aligned;" ::: "memory"); }

__device__ __forceinline__ void ring_load(uint32_t dst, const CUtensorMap* tm, int col, int row16, uint32_t bar) {
    asm volatile("{\n.reg .pred p;\nelect.sync _|p, 0xffffffff;\n"
                 "@p mbarrier.arrive.expect_tx.shared::cta.b64 _, [%2], 16384;\n"
                 "@p cp.async.bulk.tensor.5d.shared::cluster.global.mbarrier::complete_tx::bytes [%0], [%1, {%3, 0, 0, 0, %4}], [%2];\n}"
                 ::"r"(dst), "l"(tm), "r"(bar), "r"(col), "r"(row16) : "memory");
}
__device__ __forceinline__ void ring_load_both(uint32_t dst, const CUtensorMap* tm, int c1, uint32_t bar) {
    asm volatile("{\n.reg .pred p;\nelect.sync _|p, 0xffffffff;\n"
                 "@p cp.async.bulk.tensor.2d.shared::cluster.global.mbarrier::complete_tx::bytes.multicast::cluster [%0], [%1, {0, %3}], [%2], %4;\n}"
                 ::"r"(dst), "l"(tm), "r"(bar), "r"(c1), "h"((uint16_t)3) : "memory");
}
__device__ __forceinline__ void mbar_arrive_peer(uint32_t b) { asm volatile("mbarrier.arrive.relaxed.cluster.shared::cluster.b64 _, [%0];" ::"r"(b) : "memory"); }
__device__ __forceinline__ void prefetch_l2(const void* src, uint32_t bytes) {
    asm volatile("cp.async.bulk.prefetch.L2.global [%0], %1;" ::"l"(src), "r"(bytes) : "memory");
}
__device__ __forceinline__ void peer_copy(uint32_t dst, uint32_t src, uint32_t bytes, uint32_t rbar) {
    asm volatile("{\n.reg .pred p;\nelect.sync _|p, 0xffffffff;\n"
                 "@p cp.async.bulk.shared::cluster.shared::cta.mbarrier::complete_tx::bytes [%0], [%1], %2, [%3];\n}"
                 ::"r"(dst), "r"(src), "r"(bytes), "r"(rbar) : "memory");
}
__device__ __forceinline__ void st_async4(uint32_t dst, uint32_t a, uint32_t b, uint32_t c, uint32_t d, uint32_t bar) {
    asm volatile("st.async.shared::cluster.mbarrier::complete_tx::bytes.v4.b32 [%0], {%1,%2,%3,%4}, [%5];" ::"r"(dst), "r"(a), "r"(b), "r"(c), "r"(d), "r"(bar) : "memory");
}
__device__ __forceinline__ void st_async2f(uint32_t dst, float a, float b, uint32_t bar) {
    asm volatile("st.async.shared::cluster.mbarrier::complete_tx::bytes.v2.f32 [%0], {%1,%2}, [%3];" ::"r"(dst), "f"(a), "f"(b), "r"(bar) : "memory");
}
__device__ __forceinline__ void stsm4t(uint32_t a, uint32_t r0, uint32_t r1, uint32_t r2, uint32_t r3) {
    asm volatile("stmatrix.sync.aligned.m8n8.x4.trans.shared.b16 [%0], {%1,%2,%3,%4};" ::"r"(a), "r"(r0), "r"(r1), "r"(r2), "r"(r3) : "memory");
}
__device__ __forceinline__ void stsm4(uint32_t a, uint32_t r0, uint32_t r1, uint32_t r2, uint32_t r3) {
    asm volatile("stmatrix.sync.aligned.m8n8.x4.shared.b16 [%0], {%1,%2,%3,%4};" ::"r"(a), "r"(r0), "r"(r1), "r"(r2), "r"(r3) : "memory");
}
__device__ __forceinline__ void ldsm4t(uint32_t a, uint32_t& r0, uint32_t& r1, uint32_t& r2, uint32_t& r3) {
    asm volatile("ldmatrix.sync.aligned.m8n8.x4.trans.shared.b16 {%0,%1,%2,%3}, [%4];" : "=r"(r0), "=r"(r1), "=r"(r2), "=r"(r3) : "r"(a) : "memory");
}
__device__ __forceinline__ void ldsm4(uint32_t a, uint32_t& r0, uint32_t& r1, uint32_t& r2, uint32_t& r3) {
    asm volatile("ldmatrix.sync.aligned.m8n8.x4.shared.b16 {%0,%1,%2,%3}, [%4];" : "=r"(r0), "=r"(r1), "=r"(r2), "=r"(r3) : "r"(a) : "memory");
}
__device__ __forceinline__ uint4 lds128(uint32_t a) { uint4 v; asm volatile("ld.shared.v4.b32 {%0,%1,%2,%3}, [%4];" : "=r"(v.x), "=r"(v.y), "=r"(v.z), "=r"(v.w) : "r"(a) : "memory"); return v; }
__device__ __forceinline__ float4 lds128f(uint32_t a) { float4 v; asm volatile("ld.shared.v4.f32 {%0,%1,%2,%3}, [%4];" : "=f"(v.x), "=f"(v.y), "=f"(v.z), "=f"(v.w) : "r"(a) : "memory"); return v; }
__device__ __forceinline__ float2 lds64f(uint32_t a) { float2 v; asm volatile("ld.shared.v2.f32 {%0,%1}, [%2];" : "=f"(v.x), "=f"(v.y) : "r"(a) : "memory"); return v; }
__device__ __forceinline__ uint32_t lds32(uint32_t a) { uint32_t v; asm volatile("ld.shared.b32 %0, [%1];" : "=r"(v) : "r"(a) : "memory"); return v; }
__device__ __forceinline__ void sts128(uint32_t a, uint32_t x, uint32_t y, uint32_t z, uint32_t w) { asm volatile("st.shared.v4.b32 [%0], {%1,%2,%3,%4};" ::"r"(a), "r"(x), "r"(y), "r"(z), "r"(w) : "memory"); }
__device__ __forceinline__ void sts128f(uint32_t a, float x, float y, float z, float w) { asm volatile("st.shared.v4.f32 [%0], {%1,%2,%3,%4};" ::"r"(a), "f"(x), "f"(y), "f"(z), "f"(w) : "memory"); }
__device__ __forceinline__ void sts64f(uint32_t a, float x, float y) { asm volatile("st.shared.v2.f32 [%0], {%1,%2};" ::"r"(a), "f"(x), "f"(y) : "memory"); }
__device__ __forceinline__ void sts32(uint32_t a, uint32_t x) { asm volatile("st.shared.b32 [%0], %1;" ::"r"(a), "r"(x) : "memory"); }
__device__ __forceinline__ void stg128(void* p, uint4 v) { asm volatile("st.global.v4.b32 [%0], {%1,%2,%3,%4};" ::"l"(p), "r"(v.x), "r"(v.y), "r"(v.z), "r"(v.w) : "memory"); }

__device__ __forceinline__ uint32_t pack2(float lo, float hi) { uint32_t r; asm("cvt.rn.bf16x2.f32 %0, %1, %2;" : "=r"(r) : "f"(hi), "f"(lo)); return r; }
__device__ __forceinline__ float blo(uint32_t v) { return __uint_as_float(v << 16); }
__device__ __forceinline__ float bhi(uint32_t v) { return __uint_as_float(v & 0xffff0000u); }
__device__ __forceinline__ uint32_t hmul2(uint32_t a, uint32_t b) { uint32_t r; asm("mul.rn.bf16x2 %0, %1, %2;" : "=r"(r) : "r"(a), "r"(b)); return r; }
__device__ __forceinline__ uint32_t hsub2(uint32_t a, uint32_t b) { uint32_t r; asm("sub.rn.bf16x2 %0, %1, %2;" : "=r"(r) : "r"(a), "r"(b)); return r; }
__device__ __forceinline__ uint32_t hfma2(uint32_t a, uint32_t b, uint32_t c) { uint32_t r; asm("fma.rn.bf16x2 %0, %1, %2, %3;" : "=r"(r) : "r"(a), "r"(b), "r"(c)); return r; }
__device__ __forceinline__ float tanh_fast(float x) { float r; asm("tanh.approx.f32 %0, %1;" : "=f"(r) : "f"(x)); return r; }
__device__ __forceinline__ float rsq(float x) { float r; asm("rsqrt.approx.ftz.f32 %0, %1;" : "=f"(r) : "f"(x)); return r; }
__device__ __forceinline__ float ex2(float x) { float r; asm("ex2.approx.ftz.f32 %0, %1;" : "=f"(r) : "f"(x)); return r; }

__device__ __forceinline__ uint32_t ld_relaxed(const uint32_t* p) {
    uint32_t v;
    asm volatile("ld.relaxed.gpu.global.u32 %0, [%1];" : "=r"(v) : "l"(p) : "memory");
    return v;
}
__device__ __forceinline__ void flag_wait(const uint32_t* p, uint32_t e, uint32_t mask, uint32_t& seen) {
    if ((seen & mask) == mask) return;
    uint32_t a = ld_relaxed(p);
    const uint32_t t0 = clock();
    while (clock() - t0 < 200u) {}
#pragma unroll 1
    for (int i = 0; i < (1 << 19); i++) {
        const uint32_t b = ld_relaxed(p);
        seen = __ballot_sync(~0u, a == e);
        if ((seen & mask) == mask) break;
        a = ld_relaxed(p);
        seen = __ballot_sync(~0u, b == e);
        if ((seen & mask) == mask) break;
    }
    asm volatile("fence.acquire.gpu;" ::: "memory");
    fence_async_global();
}
__device__ __forceinline__ void st_data(void* p, uint32_t x, uint32_t y, uint32_t z, uint32_t w) {
    asm volatile("st.relaxed.gpu.global.v4.b32 [%0], {%1,%2,%3,%4};" ::"l"(p), "r"(x), "r"(y), "r"(z), "r"(w) : "memory");
}
template <int N>
__device__ __forceinline__ void ld_data(uint4 (&v)[N], const unsigned char* p, uint32_t stride) {
#pragma unroll
    for (int i = 0; i < N; i++) v[i].x = ~0u;
#pragma unroll 1
    for (int it = 0; it < (1 << 16); it++) {
        bool missing = false;
#pragma unroll
        for (int i = 0; i < N; i++)
            if (max(__vimax3_u32(v[i].x, v[i].y, v[i].z), v[i].w) == ~0u) {
                asm volatile("ld.relaxed.gpu.global.v4.b32 {%0,%1,%2,%3}, [%4];" : "=r"(v[i].x), "=r"(v[i].y), "=r"(v[i].z), "=r"(v[i].w) : "l"(p + i * stride) : "memory");
                missing = true;
            }
        if (!__any_sync(~0u, missing)) break;
    }
}
__device__ __forceinline__ uint32_t ld_epoch() { return ld_relaxed(&g_epoch[blockIdx.x * FS]) + 1; }
__device__ __forceinline__ void flag_set(uint32_t* p, uint32_t e) { asm volatile("st.release.gpu.global.u32 [%0], %1;" ::"l"(p), "r"(e) : "memory"); }

__device__ __forceinline__ uint32_t desc_lo(uint32_t addr) { return ((addr & 0x3FFFF) >> 4) | 0x10000u; }
__device__ __forceinline__ uint64_t mkdesc(uint32_t lo) { return (uint64_t)lo | (0x40000040ull << 32); }
__device__ __forceinline__ void wg_fence() { asm volatile("wgmma.fence.sync.aligned;" ::: "memory"); }
__device__ __forceinline__ void wg_commit() { asm volatile("wgmma.commit_group.sync.aligned;" ::: "memory"); }
template <int N> __device__ __forceinline__ void wg_wait() { asm volatile("wgmma.wait_group.sync.aligned %0;" ::"n"(N) : "memory"); }
template <int N> __device__ __forceinline__ void pin(float (&d)[N]) {
#pragma unroll
    for (int i = 0; i < N; i++) asm volatile("" : "+f"(d[i])::"memory");
}
template <int N> __device__ __forceinline__ void pin(uint32_t (&d)[N]) {
#pragma unroll
    for (int i = 0; i < N; i++) asm volatile("" : "+r"(d[i])::"memory");
}

template <typename Tp, int N> __device__ __forceinline__ void zero(Tp (&d)[N]) {
#pragma unroll
    for (int i = 0; i < N; i++) d[i] = 0;
    pin(d);
}

#define F4(d, i) "+f"(d[i]), "+f"(d[i + 1]), "+f"(d[i + 2]), "+f"(d[i + 3])
#define F16(d, i) F4(d, i), F4(d, i + 4), F4(d, i + 8), F4(d, i + 12)

__device__ __forceinline__ void mma_sp(float (&d)[32], const uint32_t* a, uint64_t b, uint32_t meta, int acc) {
    asm volatile("{.reg .pred p; setp.ne.b32 p, %38, 0;\n"
                 "wgmma.mma_async.sp.sync.aligned.m64n64k32.f32.bf16.bf16 {%0,%1,%2,%3,%4,%5,%6,%7,%8,%9,%10,%11,%12,%13,%14,%15,%16,%17,%18,%19,%20,%21,%22,%23,%24,%25,%26,%27,%28,%29,%30,%31}, "
                 "{%32,%33,%34,%35}, %36, %37, 0, p, 1, 1, 1;}\n"
                 : F16(d, 0), F16(d, 16) : "r"(a[0]), "r"(a[1]), "r"(a[2]), "r"(a[3]), "l"(b), "r"(meta), "r"(acc));
}
__device__ __forceinline__ void mma_t(float (&d)[24], uint64_t a, uint64_t b, int acc) {
    asm volatile("{.reg .pred p; setp.ne.b32 p, %26, 0;\n"
                 "wgmma.mma_async.sync.aligned.m64n48k16.f32.bf16.bf16 {%0,%1,%2,%3,%4,%5,%6,%7,%8,%9,%10,%11,%12,%13,%14,%15,%16,%17,%18,%19,%20,%21,%22,%23}, %24, %25, p, 1, 1, 1, 0;}\n"
                 : F16(d, 0), F4(d, 16), F4(d, 20) : "l"(a), "l"(b), "r"(acc));
}
__device__ __forceinline__ void mma_qk(float (&d)[32], uint32_t a0, uint32_t a1, uint32_t a2, uint32_t a3, uint64_t b, int acc) {
    asm volatile("{.reg .pred p; setp.ne.b32 p, %37, 0;\n"
                 "wgmma.mma_async.sync.aligned.m64n64k16.f32.bf16.bf16 {%0,%1,%2,%3,%4,%5,%6,%7,%8,%9,%10,%11,%12,%13,%14,%15,%16,%17,%18,%19,%20,%21,%22,%23,%24,%25,%26,%27,%28,%29,%30,%31}, "
                 "{%32,%33,%34,%35}, %36, p, 1, 1, 0;}\n"
                 : F16(d, 0), F16(d, 16) : "r"(a0), "r"(a1), "r"(a2), "r"(a3), "l"(b), "r"(acc));
}
__device__ __forceinline__ void mma_pv(float (&d)[36], uint32_t a0, uint32_t a1, uint32_t a2, uint32_t a3, uint64_t b) {
    asm volatile("wgmma.mma_async.sync.aligned.m64n72k16.f32.bf16.bf16 {%0,%1,%2,%3,%4,%5,%6,%7,%8,%9,%10,%11,%12,%13,%14,%15,%16,%17,%18,%19,%20,%21,%22,%23,%24,%25,%26,%27,%28,%29,%30,%31,%32,%33,%34,%35}, "
                 "{%36,%37,%38,%39}, %40, 1, 1, 1, 1;\n"
                 : F16(d, 0), F16(d, 16), F4(d, 32) : "r"(a0), "r"(a1), "r"(a2), "r"(a3), "l"(b));
}

__device__ __forceinline__ uint32_t load_code(int n, int r, int w) {
    const int tile = 2 * r + w;
    int m, col, row;
    if (n < 16 || n >= 40) {
        const int k = n < 16 ? n : n - 40;
        m = n < 16 ? 0 : 6;
        if (k < 8) { col = 4 * tile + (k >> 1); row = (k & 1) ^ r; }
        else { m++; col = tile ^ (3 - ((k - 8) >> 1)); row = 2 * tile + (k & 1); }
    } else if (n < 32) {
        const int k = n - 16;
        m = 2;
        col = tile + (k < 2 ? 4 : (k < 4 ? 0 : 8)); row = (k & 1) ^ r;
    } else if (n < 34) { m = 3; col = tile; row = n - 32; }
    else if (n < 38) { const int k = n - 34; m = 4; col = tile + 4 * (k & 1); row = (k >> 1) ^ r; }
    else { m = 5; col = tile; row = (n & 1) ^ r; }
    return m | (col << 4) | (row << 8);
}

__global__ void __cluster_dims__(2, 1, 1) __launch_bounds__(NTHREADS, 1)
conformer_kernel(const __grid_constant__ Params p) {
    extern __shared__ __align__(1024) unsigned char smem_raw[];
    const uint32_t sb = smem_u32(smem_raw);
    const uint32_t bars = sb + OFF_BARS;
    const int tid = threadIdx.x;
    const int lane = tid & 31;
    const int warp = __shfl_sync(~0u, tid >> 5, 0);
    const int r = blockIdx.x & 1;
    const int pair = blockIdx.x >> 1;
    const int b = pair >> 5, pt = pair & 31;
    const int ah = pt >> 3, qt = (pt & 7) * 2 + r;
    const int abh = b * 4 + ah;

    TG(30);
    TSINIT();
    TS(0);
    const uint32_t P = sb + OFF_P, H = sb + OFF_H;

    if (warp >= 8) {
        asm volatile("setmaxnreg.dec.sync.aligned.u32 48;");
        if (warp >= 12) {
            cluster_arrive();
            cluster_wait();
            const int ut = tid & 127;
            mbar_wait(bars + (B_EMPTY + RSTAT) * 8, 0);
#pragma unroll
            for (int i = 0; i < 4; i++) {
                st_data(g_kvq + 2097152 + (size_t)((b * 4 + 2 * r + (i >> 1)) * 1024 + pt * 32) * 128 + (i & 1) * 2048 + ut * 16, ~0u, ~0u, ~0u, ~0u);
                st_data(g_o + (size_t)(abh * PADROWS + 8 + qt * 64) * 128 + i * 2048 + ut * 16, ~0u, ~0u, ~0u, ~0u);
                if (i < 2) st_data(&g_halo[(pair * 4 + 2 * r + i) * 128 + ut], ~0u, ~0u, ~0u, ~0u);
            }
            bar_sync(11, 128);
            if (warp == 12) {
                const uint32_t target = ld_epoch() * 64;
                if (lane == 0) {
                    asm volatile("red.release.gpu.global.add.u32 [%0], 1;" ::"l"(&g_reset[b * 32]) : "memory");
#pragma unroll 1
                    for (int i = 0; i < (1 << 20) && ld_relaxed(&g_reset[b * 32]) != target; i++) {}
                    asm volatile("fence.acquire.gpu;" ::: "memory");
                    mbar_arrive(bars + B_RST * 8);
                }
                __syncwarp();
                TS(13);
            }
            {
                bar_sync(6, 416);
                const int side = warp & 1, t = 2 * r + ((warp >> 1) & 1), np = side ? pt + 1 : pt - 1;
                uint4 hv[2] = {make_uint4(0, 0, 0, 0), make_uint4(0, 0, 0, 0)};
                if (np >= 0 && np < 32)
                    ld_data(hv, reinterpret_cast<const unsigned char*>(&g_halo[(((b * 32 + np) * 4 + t) * 2 + (side ^ 1)) * 64 + lane]), 512);
                const uint32_t dst = P + t * XCH + side * 5120 + (lane & 7) * 128 + (((lane >> 3) ^ (lane & 7)) << 4);
                stsm4(dst, hv[0].x, hv[0].y, hv[0].z, hv[0].w);
                stsm4(dst ^ 64, hv[1].x, hv[1].y, hv[1].z, hv[1].w);
                bar_arrive(9, 384);
            }
            const uint32_t a8 = P + (ut >> 3) * 128 + (ut & 7) * 16;
            float s[3] = {0.f, 0.f, 0.f}, q[3] = {0.f, 0.f, 0.f};
#pragma unroll 1
            for (int h = 0; h < 2; h++) {
                if (h == 0) bar_sync(1, 384);
                else mbar_wait(bars + B_X2 * 8, 0);
                uint4 v[6];
#pragma unroll
                for (int i = 0; i < 6; i++) v[i] = lds128(a8 + (2 * (r ^ h) + (i & 1)) * XCH + (i >> 1) * 2048);
                bar_arrive(5 + ((v[0].w | v[1].w | v[2].w | v[3].w | v[4].w | v[5].w) & p.zero), 384);
                uint32_t t;
                asm volatile("mov.u32 %0, %%clock;" : "=r"(t)::"memory");
                const uint32_t mul = 65536u + (t & p.zero), msk = 0u - mul;
#pragma unroll
                for (int i = 0; i < 6; i++) {
                    const float a0 = __uint_as_float(v[i].x * mul), a1 = __uint_as_float(v[i].x & msk), a2 = __uint_as_float(v[i].y * mul), a3 = __uint_as_float(v[i].y & msk);
                    const float a4 = __uint_as_float(v[i].z * mul), a5 = __uint_as_float(v[i].z & msk), a6 = __uint_as_float(v[i].w * mul), a7 = __uint_as_float(v[i].w & msk);
                    s[i >> 1] += ((a0 + a1) + (a2 + a3)) + ((a4 + a5) + (a6 + a7));
                    q[i >> 1] += fmaf(a0, a0, fmaf(a1, a1, fmaf(a2, a2, a3 * a3))) + fmaf(a4, a4, fmaf(a5, a5, fmaf(a6, a6, a7 * a7)));
                }
            }
#pragma unroll
            for (int o = 1; o < 8; o <<= 1) {
#pragma unroll
                for (int i = 0; i < 3; i++) { s[i] += __shfl_xor_sync(~0u, s[i], o); q[i] += __shfl_xor_sync(~0u, q[i], o); }
            }
            const int k = ut & 7, row = (ut >> 3) + 16 * k;
            const float mean = (k == 0 ? s[0] : (k == 1 ? s[1] : s[2])) * (1.f / 256.f);
            const float msq = (k == 0 ? q[0] : (k == 1 ? q[1] : q[2])) * (1.f / 256.f);
            const float alpha = (uint32_t)(pt * 32 - 8 + row) >= T_ ? 0.f : 0.5f;
            const float rstd = alpha * rsq(fmaxf(fmaf(-mean, mean, msq), 0.f) + 1e-5f);
            if (k < 3) sts64f(sb + OFF_STATS + row * 8, mean * rstd, rstd);
            __syncwarp();
            if (lane == 0) mbar_arrive(bars + B_ST * 8);
            TS(4);
        } else if (warp < 10) {
            const int w = warp - 8;
            const uint32_t ring = sb + OFF_RING + w * NSLOT * SLOT;
            const uint32_t full = bars + (B_FULL + w * NSLOT) * 8;
            if (lane == 0) {
#pragma unroll
                for (int i = 0; i < NSLOT; i++) { mbar_init(full + i * 8, 1); mbar_init(full + (B_EMPTY - B_FULL + i) * 8, 4); }
                asm volatile("fence.mbarrier_init.release.cluster;" ::: "memory");
                fence_async_smem();
            }
            __syncwarp();
            cluster_arrive();
            TS(1);
#pragma unroll
            for (int n = 0; n < NSLOT; n++) {
                if (n == 1 || n == 2) bar_sync(12, 64);
                ring_load(ring + n * SLOT, &p.tm[0], 64 * (8 * r + 4 * w + (n >> 1)), 8 * ((n & 1) ^ r), full + n * 8);
            }
            TS(2);
            const uint32_t code = load_code(lane, r, w) | (load_code(lane + 32, r, w) << 16);
            cluster_wait();
            uint32_t s = 0, ph = 0;
            int n = NSLOT;
#pragma unroll 1
            for (int seg = 0; seg < 2; seg++) {
#pragma unroll 1
                for (; n < (seg == 0 ? 22 : NLOADS); n++) {
                    const uint32_t c = __shfl_sync(~0u, code, n) >> (n & 32 ? 16 : 0);
                    const CUtensorMap* tm = &p.tm[c & 15];
                    const uint32_t col = (c & 0xf0) * 4, row = (c & 0xff00) >> 5, dst = ring + s * SLOT;
                    mbar_wait(full + (B_EMPTY - B_FULL) * 8 + s * 8, ph + (((uint32_t)(size_t)tm | col | row | dst) & p.zero));
                    ring_load(dst, tm, col, row, full + s * 8);
                    if (++s == NSLOT) { s = 0; ph ^= 1; }
                }
                if (seg == 1) break;
                const uint32_t epoch = ld_epoch();
                const uint32_t rdy = bars + (B_RDY + 3 * w) * 8, prdy = mapa(rdy, r ^ 1);
                const int isv = r ^ w;
                const uint32_t* flags = g_flag_kv + (isv * 256 + abh * 32 + lane) * FS;
                uint32_t seen = 0;
                auto kv_load = [&](uint32_t sl, int i) {
                    ring_load_both(ring + sl * SLOT, &p.tm[8], (isv * 64 + abh * 8 + 2 * i + w) * 128, full + sl * 8);
                };
#pragma unroll 1
                for (int i = 0; i < 2; i++) {
                    if (lane < 3 + i) {
                        const uint32_t sl = i ? lane : lane + 2;
                        mbar_wait(full + (B_EMPTY - B_FULL + sl) * 8, i ^ 1);
                        mbar_arrive_tx(full + sl * 8, (i || lane == 2) ? SLOT : 0);
                    }
                    __syncwarp();
                }
                if (lane == 0) mbar_arrive_peer(prdy);
                mbar_wait(rdy, 0);
#pragma unroll 1
                for (int j = isv; j < 3; j++) {
                    flag_wait(flags, epoch, 0xfu << (8 * (j - isv) + 4 * w), seen);
                    if (j == isv) TSW(5 + 2 * isv);
                    if (j == 1 && PACE) mbar_wait(full + 32, 0);
                    if (j == 2) mbar_wait(full + isv * 8, 1);
                    kv_load(j ? 2 * j - 2 + isv : 4, j - isv);
                }
                flag_wait(flags, epoch, ~0u, seen);
#pragma unroll 1
                for (int i = 0; i < 3; i++) {
                    const uint32_t sl = i ? i - 1 : 4, bo = i == 2 ? 16 : 8;
                    mbar_wait(full + (B_EMPTY - B_FULL + sl) * 8, i != 0);
                    if (lane == 0) mbar_arrive_tx(full + sl * 8, SLOT);
                    if ((i != 0) == (isv == 1)) {
                        mbar_wait(rdy + bo, 0);
                        kv_load(sl, i == 1 ? 2 : 3);
                    } else if (lane == 0) mbar_arrive_peer(prdy + bo);
                    __syncwarp();
                }
                n = 32; s = 2; ph = 1;
            }
        } else if (warp == 10) {
            if (lane == 0) {
#pragma unroll
                for (int i = B_XA; i <= B_ST; i++) mbar_init(bars + i * 8, i == B_ST ? 4 : 1);
#pragma unroll
                for (int i = B_XA; i <= B_SR; i++) mbar_arrive_tx(bars + i * 8, i < B_XB ? 512 : (i == B_X2 ? 12288 : 8192));
                asm volatile("fence.mbarrier_init.release.cluster;" ::: "memory");
                fence_async_smem();
            }
            __syncwarp();
            cluster_arrive();
            cluster_wait();
            const uint32_t epoch = ld_epoch();
            bar_sync(6, 416);
            if (lane < 2) flag_set(&g_flag_kv[(256 + (b * 4 + 2 * r + lane) * 32 + pt) * FS], epoch);
            __syncwarp();
            TSW(9);
        } else {
            const uint32_t kb = (lane < 2 || lane > 5) ? 4096 : (lane == 2 ? 3072 : (lane == 4 ? 2048 : 1024));
            const char* pf = p.w[lane & 7] + blockIdx.x * kb;
            cluster_arrive();
            cluster_wait();
            if (lane < 2) prefetch_l2(pf, kb);
            mbar_wait(bars + B_XA * 8, 0);
            if (lane == 2) prefetch_l2(pf, kb);
            if (lane >= 1 && lane < 9) asm volatile("prefetch.tensormap [%0];" ::"l"(&p.tm[lane]) : "memory");
            mbar_wait(bars + (B_FULL + 1) * 8, 1);
            if (lane > 2 && lane < 8) prefetch_l2(pf, kb);
            if (lane == 8 && blockIdx.x < 15) prefetch_l2(p.dw + blockIdx.x * 256, 512);
            const uint32_t epoch = ld_epoch();
            bar_sync(4, 288);
            if (lane < 2) flag_set(&g_flag_kv[((b * 4 + 2 * r + lane) * 32 + pt) * FS], epoch);
            __syncwarp();
            TSW(8);
        }
        TSDUMP();
        return;
    }

    const int w = warp >> 2, wq = warp & 3;
    const int tile = 2 * r + w;
    const int wt = tid & 127;
    const int c4 = lane & 3;
    const int trow = pt * 32 + 8 * wq;
    uint32_t xr[8];
    {
        const uint32_t* xp = reinterpret_cast<const uint32_t*>(p.x + (size_t)(b * T_ + trow + (lane >> 2)) * 256 + tile * 64) + c4;
#pragma unroll
        for (int j = 0; j < 8; j++) xr[j] = trow < T_ ? __ldg(xp + 4 * j) : 0u;
    }
    cluster_arrive();
    asm volatile("setmaxnreg.inc.sync.aligned.u32 208;");
    const uint32_t rbase = sb + OFF_RING + w * NSLOT * SLOT, fbar = bars + (B_FULL + w * NSLOT) * 8;
    const uint32_t rdesc = desc_lo(rbase);
    auto acq = [&](int n) { mbar_wait(fbar + (n % NSLOT) * 8, (n / NSLOT) & 1); };
    auto rel = [&](int n) { if (lane == 0) mbar_arrive(fbar + (B_EMPTY - B_FULL + n % NSLOT) * 8); };
    const uint32_t foff = (lane & 7) * 128 + (((lane >> 3) ^ (lane & 7)) << 4);
    const uint32_t toff = ((lane >> 4) * 8 + (lane & 7)) * 128 + (((2 * wq + ((lane >> 3) & 1)) ^ (lane & 7)) << 4);
    auto publish = [&](int bar, uint32_t src, uint32_t bytes, int nsync) {
        fence_async_smem();
        bar_sync(2 + w, 128);
        if (wq == 0) peer_copy(mapa(src, r ^ 1), src, bytes, mapa(bars + bar * 8, r ^ 1));
        bar_sync(nsync == 384 ? 1 : 10, nsync);
    };
    float v[16];
#pragma unroll
    for (int j = 0; j < 8; j++) { v[2 * j] = blo(xr[j]); v[2 * j + 1] = bhi(xr[j]); }
    const uint32_t xown = __shfl_sync(~0u, P + wt * 16 + tile * 4096, lane), xrem = __shfl_sync(~0u, P + wt * 16 + (r ^ 1) * 8192, lane);
    const uint32_t sbuf = __shfl_sync(~0u, sb + OFF_MISC + 1024 + (8 * wq + (lane >> 2)) * 32, lane);
    const uint32_t sown = __shfl_sync(~0u, sbuf + tile * 8, lane);
    const uint32_t peer = __shfl_sync(~0u, mapa(sb, r ^ 1) - sb, lane);
    const uint32_t meta = __shfl_sync(~0u, 0xEEEE4444u + p.zero, lane);
    cluster_wait();
    TS(56);
    float mean, msq;

#pragma unroll 1
    for (int ph = 0;; ph++) {
        uint4 o0, o1;
        {
            float s = 0.f, q = 0.f, s2 = 0.f, q2 = 0.f;
#pragma unroll
            for (int j = 0; j < 4; j++) {
                s += v[4 * j] + v[4 * j + 1]; s2 += v[4 * j + 2] + v[4 * j + 3];
                q += fmaf(v[4 * j], v[4 * j], v[4 * j + 1] * v[4 * j + 1]); q2 += fmaf(v[4 * j + 2], v[4 * j + 2], v[4 * j + 3] * v[4 * j + 3]);
            }
            s += s2; q += q2;
            const uint32_t xa = bars + (B_XA + ph) * 8;
            s += __shfl_xor_sync(~0u, s, 1); q += __shfl_xor_sync(~0u, q, 1);
            s += __shfl_xor_sync(~0u, s, 2); q += __shfl_xor_sync(~0u, q, 2);
            if (c4 == 0) st_async2f(sown + peer, s, q, xa + peer);
            if (c4 == 0) sts64f(sown, s, q);
#pragma unroll
            for (int j = 0; j < 8; j++) xr[j] = pack2(v[2 * j], v[2 * j + 1]);
            sts128(xown, xr[0], xr[1], xr[2], xr[3]);
            sts128(xown + 2048, xr[4], xr[5], xr[6], xr[7]);
            bar_sync(10, 256);
            o0 = lds128(xown ^ 4096); o1 = lds128((xown ^ 4096) + 2048);
            if (ph < 3) {
                st_async4(xown + peer, xr[0], xr[1], xr[2], xr[3], xa + (B_XB - B_XA) * 8 + peer);
                st_async4(xown + peer + 2048, xr[4], xr[5], xr[6], xr[7], xa + (B_XB - B_XA) * 8 + peer);
            }
            TS(57 + ph);
            if (ph == 0) acq(0);
            mbar_wait(xa, 0);
            const float4 u0 = lds128f(sbuf), u1 = lds128f(sbuf + 16);
            mean = ((u0.x + u0.z) + (u1.x + u1.z)) * (1.f / 256.f);
            msq = ((u0.y + u0.w) + (u1.y + u1.w)) * (1.f / 256.f);
        }
        if (ph == 3) break;
        uint32_t a[32];
        const uint32_t mean2 = pack2(mean, mean);
        auto centre = [&](int i, const uint4& u) {
            a[i] = hsub2(u.x, mean2); a[i + 1] = hsub2(u.y, mean2); a[i + 2] = hsub2(u.z, mean2); a[i + 3] = hsub2(u.w, mean2);
        };
#pragma unroll
        for (int j = 0; j < 8; j++) a[j] = hsub2(xr[j], mean2);
        centre(8, o0); centre(12, o1);
        const float rstd = rsq(fmaxf(fmaf(-mean, mean, msq), 0.f) + 1e-5f);
        auto gather_peer = [&]() {
            mbar_wait(bars + (B_XB + ph) * 8, 0);
#pragma unroll
            for (int i = 0; i < 4; i++) centre(16 + 4 * i, lds128(xrem + i * 2048));
        };
        auto sp = [&](float (&d)[32], int n, const uint32_t* af, int flip, int acc) {
            const uint32_t lo = rdesc + p.zero * (ph + n + 1) + (n % NSLOT) * (SLOT >> 4);
            const uint64_t b0 = mkdesc(lo + flip * 512), b1 = mkdesc(lo + (flip ^ 1) * 512);
            wg_fence();
            mma_sp(d, af, b0, meta, acc);
            mma_sp(d, af + 4, b0 + 256, meta, 1);
            mma_sp(d, af + 8, b1, meta, 1);
            mma_sp(d, af + 12, b1 + 256, meta, 1);
            wg_commit();
        };
        float d0[32], d1[32];

        if (ph != 1) {
            uint32_t h[32];
            const float rs = 0.5f * rstd;
            const uint32_t inb = bars + (B_INB + ph) * 8, box = H + wt * 16;
            bool ready = true;
            auto step = [&](float (&d)[32], int n, const uint32_t* af, int flip, int acc, auto work) {
                if (!ready) acq(n);
                if (((TURN >> n) & 1) && w == 1) bar_sync(7, 256);
                sp(d, n, af, flip, acc);
                if (n > 0 && ((TURN >> (n - 1)) & 1) && w == 0) bar_arrive(7, 256);
                if (n < 15) ready = mbar_test(fbar + ((n + 1) % NSLOT) * 8, ((n + 1) / NSLOT) & 1);
                wg_wait<1>();
                if (n > 0 && !((EAGER >> (n - 1)) & 1)) rel(n - 1);
                const uint32_t tie = work() & p.zero;
                if ((EAGER >> n) & 1) {
                    if (p.zero < n + ph + 1) wg_wait<0>();
                    if (lane == 0) mbar_arrive(fbar + (B_EMPTY - B_FULL + n % NSLOT) * 8 + tie);
                }
            };
            auto none = []() { return 0u; };
            auto act = [&](float (&d)[32], int i) {
                pin(d);
#pragma unroll
                for (int j = 0; j < 8; j++) {
                    const float u0 = (d[4 * j] + d[4 * j + 2]) * rs, u1 = (d[4 * j + 1] + d[4 * j + 3]) * rs;
                    h[8 * i + j] = pack2(fmaf(u0, tanh_fast(u0), u0), fmaf(u1, tanh_fast(u1), u1));
                }
                return h[8 * i] | h[8 * i + 1] | h[8 * i + 2] | h[8 * i + 3] | h[8 * i + 4] | h[8 * i + 5] | h[8 * i + 6] | h[8 * i + 7];
            };
            auto send = [&](float (&d)[32], int x) {
                pin(d);
                uint32_t pk[8];
#pragma unroll
                for (int j = 0; j < 8; j++) pk[j] = pack2(d[4 * j] + d[4 * j + 2], d[4 * j + 1] + d[4 * j + 3]);
                const uint32_t ow = w ^ (x & 1), dst = box + (ow * 3 + x - 1) * 4096;
                if (x & 2) {
                    st_async4(dst + peer, pk[0], pk[1], pk[2], pk[3], inb + ow * 8 + peer);
                    st_async4(dst + peer + 2048, pk[4], pk[5], pk[6], pk[7], inb + ow * 8 + peer);
                } else {
                    sts128(dst, pk[0], pk[1], pk[2], pk[3]);
                    sts128(dst + 2048, pk[4], pk[5], pk[6], pk[7]);
                }
            };
            TS(1 + ph * 10);
            step(d0, 0, a, w, 0, [&]() { gather_peer(); return 0u; });
            TS(32);
            step(d0, 1, a + 16, 0, 1, none);
            step(d1, 2, a, w, 0, [&]() { return act(d0, 0); });
            step(d1, 3, a + 16, 0, 1, none);
            step(d0, 4, a, w, 0, [&]() { return act(d1, 1); });
            TS(33);
            step(d0, 5, a + 16, 0, 1, none);
            step(d1, 6, a, w, 0, [&]() { return act(d0, 2); });
            step(d1, 7, a + 16, 0, 1, none);
            step(d0, 8, h, 0, 0, [&]() { return act(d1, 3); });
            TS(2 + ph * 10);
            step(d0, 9, h + 16, 0, 1, none);
            step(d1, 10, h, 0, 0, [&]() { send(d0, 3); return 0u; });
            step(d1, 11, h + 16, 0, 1, none);
            step(d0, 12, h, 0, 0, [&]() { send(d1, 2); return 0u; });
            TS(34);
            step(d0, 13, h + 16, 0, 1, none);
            step(d1, 14, h, 0, 0, [&]() { send(d0, 1); return 0u; });
            step(d1, 15, h + 16, 0, 1, none);
            if (ph == 0) acq(16);
            mbar_wait(inb + w * 8, 0);
            bar_sync(10, 256);
#pragma unroll
            for (int i = 0; i < 2; i++) {
                const uint32_t src = box + w * 12288 + i * 2048;
                const uint4 u0 = lds128(src), u1 = lds128(src + 4096), u2 = lds128(src + 8192);
                const uint32_t p0[4] = {u0.x, u0.y, u0.z, u0.w}, p1[4] = {u1.x, u1.y, u1.z, u1.w}, p2[4] = {u2.x, u2.y, u2.z, u2.w};
#pragma unroll
                for (int j = 0; j < 4; j++) {
                    v[8 * i + 2 * j] = fmaf(0.5f, blo(p0[j]) + blo(p1[j]) + blo(p2[j]), blo(xr[4 * i + j]));
                    v[8 * i + 2 * j + 1] = fmaf(0.5f, bhi(p0[j]) + bhi(p1[j]) + bhi(p2[j]), bhi(xr[4 * i + j]));
                }
            }
            wg_wait<0>();
            pin(d1);
            rel(15);
            TS(3 + ph * 10);
#pragma unroll
            for (int j = 0; j < 8; j++) {
                v[2 * j] = fmaf(0.5f, d1[4 * j] + d1[4 * j + 2], v[2 * j]);
                v[2 * j + 1] = fmaf(0.5f, d1[4 * j + 1] + d1[4 * j + 3], v[2 * j + 1]);
            }
            continue;
        }

        {
            TS(11);
            sp(d0, 16, a, w, 0);
            acq(17);
            gather_peer();
            sp(d0, 17, a + 16, 0, 1);
            mbar_wait(bars + B_RST * 8, 0);
            acq(18); acq(19);
            const uint32_t stg = H + warp * 2048;
            unsigned char* g = g_kvq + (size_t)((b * 4 + tile) * 1024 + trow) * 128 + lane * 16;
            auto put = [&](float (&d)[32], int i) {
                pin(d);
                uint32_t pk[8];
#pragma unroll
                for (int j = 0; j < 8; j++) pk[j] = pack2((d[4 * j] + d[4 * j + 2]) * rstd, (d[4 * j + 1] + d[4 * j + 3]) * rstd);
                if (i == 2) {
                    st_data(g + 2097152, pk[0], pk[1], pk[2], pk[3]);
                    st_data(g + 2097152 + 512, pk[4], pk[5], pk[6], pk[7]);
                    return;
                }
                stsm4(stg + i * 1024 + foff, pk[0], pk[1], pk[2], pk[3]);
                stsm4(stg + i * 1024 + (foff ^ 64), pk[4], pk[5], pk[6], pk[7]);
                __syncwarp();
                const uint4 u0 = lds128(stg + i * 1024 + lane * 16), u1 = lds128(stg + i * 1024 + 512 + lane * 16);
                stg128(g + i * 1048576, u0); stg128(g + i * 1048576 + 512, u1);
            };
            wg_wait<0>();
            rel(16); rel(17);
            TS(37);
            put(d0, 0);
            bar_arrive(4, 288);
            TS(38);
            sp(d1, 18, a, w, 0);
            sp(d1, 19, a + 16, 0, 1);
            acq(20);
            sp(d0, 20, a, w, 0);
            wg_wait<1>();
            rel(18); rel(19);
            put(d1, 2);
            acq(21);
            sp(d0, 21, a + 16, 0, 1);
            wg_wait<0>();
            rel(20); rel(21);
            put(d0, 1);
            bar_arrive(6, 416);
            if (wq == 0 || wq == 3) {
                uint4* hp = &g_halo[((pair * 4 + tile) * 2 + (wq & 1)) * 64 + lane];
                st_data(hp, xr[0], xr[1], xr[2], xr[3]);
                st_data(hp + 32, xr[4], xr[5], xr[6], xr[7]);
            }
            acq(22); acq(23);
            rel(22); rel(23);
            TS(12);
        }

        const uint32_t xo = P + tile * XCH + wq * 1024, xt = P + tile * XCH + toff;
        {
            constexpr float CS = 0.125f * 1.4426950408889634f;
            float sa[32], sb2[32], o[36];
            uint32_t pa[16], pb[16], q[16];
            float n0 = INFINITY, n1 = INFINITY;
            zero(o); zero(pa); zero(pb);
            const uint32_t ones = sb + OFF_MISC + 2048;
            if (tid < 128) sts128(ones + tid * 16, 0x3F803F80u, 0x3F803F80u, 0x3F803F80u, 0x3F803F80u);
            fence_async_smem();
            bar_sync(10, 256);
            stsm4(xo + 1024 + foff, xr[0], xr[1], xr[2], xr[3]);
            stsm4(xo + 1024 + (foff ^ 64), xr[4], xr[5], xr[6], xr[7]);
            const uint32_t vdesc = rdesc + ((((ones - rbase) >> 4) - 1) << 16);
            auto qk_issue = [&](float (&s)[32], uint32_t lo) {
                const uint64_t kd = mkdesc(lo);
                wg_fence();
#pragma unroll
                for (int k = 0; k < 4; k++) mma_qk(s, q[4 * k], q[4 * k + 1], q[4 * k + 2], q[4 * k + 3], kd + 2 * k, k != 0);
                wg_commit();
            };
            auto pv_issue = [&](uint32_t (&pp)[16], uint32_t lo) {
                const uint64_t vd = mkdesc(lo);
                wg_fence();
#pragma unroll
                for (int k = 0; k < 4; k++) mma_pv(o, pp[4 * k], pp[4 * k + 1], pp[4 * k + 2], pp[4 * k + 3], vd - k * (128 * 65535));
                wg_commit();
            };
            auto new_max = [&](float (&s)[32], float& x0, float& x1) {
                x0 = s[0]; x1 = s[2];
#pragma unroll
                for (int j = 0; j < 8; j++) {
                    x0 = fmaxf(x0, fmaxf(s[4 * j], s[4 * j + 1]));
                    x1 = fmaxf(x1, fmaxf(s[4 * j + 2], s[4 * j + 3]));
                }
                x0 = fmaxf(x0, __shfl_xor_sync(~0u, x0, 1)); x1 = fmaxf(x1, __shfl_xor_sync(~0u, x1, 1));
                x0 = fmaxf(x0, __shfl_xor_sync(~0u, x0, 2)); x1 = fmaxf(x1, __shfl_xor_sync(~0u, x1, 2));
                x0 = fminf(n0, fmaf(x0, -CS, -20.f)); x1 = fminf(n1, fmaf(x1, -CS, -20.f));
            };
            auto probs = [&](float (&s)[32], uint32_t (&pp)[16], bool ready, auto wait) {
                uint32_t any = 0;
#pragma unroll
                for (int i = 0; i < 16; i++) {
                    pp[i] = pack2(ex2(fmaf(s[2 * i], CS, (i & 1) ? n1 : n0)), ex2(fmaf(s[2 * i + 1], CS, (i & 1) ? n1 : n0)));
                    any |= pp[i];
                }
                float sc0 = 1.f, sc1 = 1.f;
                const bool slow = __any_sync(~0u, (any & 0x40004000u) || !ready);
                if (slow) {
                    wait();
                    if (__any_sync(~0u, any & 0x40004000u)) {
                        float x0, x1;
                        new_max(s, x0, x1);
                        sc0 = ex2(x0 - n0); sc1 = ex2(x1 - n1);
                        n0 = x0; n1 = x1;
#pragma unroll
                        for (int i = 0; i < 16; i++)
                            pp[i] = pack2(ex2(fmaf(s[2 * i], CS, (i & 1) ? n1 : n0)), ex2(fmaf(s[2 * i + 1], CS, (i & 1) ? n1 : n0)));
                    }
                }
                wg_wait<0>();
                pin(sa); pin(sb2); pin(o); pin(pa); pin(pb);
                if (slow) {
#pragma unroll
                    for (int j = 0; j < 9; j++) { o[4 * j] *= sc0; o[4 * j + 1] *= sc0; o[4 * j + 2] *= sc1; o[4 * j + 3] *= sc1; }
                }
            };
            {
                uint4 u[4] = {};
                ld_data(u, g_kvq + 2097152 + (size_t)(abh * 1024 + qt * 64 + wq * 16) * 128 + lane * 16, 512);
#pragma unroll
                for (int k = 0; k < 2; k++) {
                    q[8 * k] = u[k].x; q[8 * k + 1] = u[k + 2].x; q[8 * k + 2] = u[k].y; q[8 * k + 3] = u[k + 2].y;
                    q[8 * k + 4] = u[k].z; q[8 * k + 5] = u[k + 2].z; q[8 * k + 6] = u[k].w; q[8 * k + 7] = u[k + 2].w;
                }
                pin(q);
            }
            TS(40);
            acq(24);
            TS(13);
            qk_issue(sa, rdesc + (24 % NSLOT) * (SLOT >> 4));
            qk_issue(sb2, rdesc + (24 % NSLOT) * (SLOT >> 4) + 512);
            wg_wait<1>();
            pin(sa);
            {
                float x0, x1;
                new_max(sa, x0, x1);
                n0 = x0; n1 = x1;
            }
            if (w == 1) bar_sync(7, 256);
            uint32_t vd = vdesc - (SLOT >> 4) * 65535u, kd = rdesc, vb = fbar + 8, kb = fbar;
            uint32_t vlast = vdesc - 4 * (SLOT >> 4) * 65535u;
            uint32_t kprev = fbar + 32, vprev = bars + (B_SINK - (B_EMPTY - B_FULL)) * 8;
#pragma unroll 1
            for (int it = 0; it < 4; it++) {
                pv_issue(pb, vlast);
                probs(sa, pa, mbar_test(vb, it < 2) & mbar_test(kb, it < 3), [&]() { mbar_wait(vb, it < 2); mbar_wait(kb, it < 3); });
                TS(41 + it * 4);
                if (it == 0 && w == 0) bar_arrive(7, 256);
                if (it == 3 && w == 1) {
#pragma unroll
                    for (int i = 20; i < 32; i++) sb2[i] = -INFINITY;
                }
                pin(sb2);
                if (it < 3) qk_issue(sa, kd);
                if (lane == 0) mbar_arrive(kprev + (B_EMPTY - B_FULL) * 8);
                if (lane == 0) mbar_arrive(vprev + (B_EMPTY - B_FULL) * 8);
                pv_issue(pa, vd);
                probs(sb2, pb, true, []() {});
                TS(43 + it * 4);
                if (it < 3) qk_issue(sb2, kd + 512);
                const int dv = it == 0 ? 2 : (it == 1 ? -3 : 1);
                kprev = kb; vprev = vb; vlast = vd - 512 * 65535u;
                vd -= dv * (SLOT >> 4) * 65535u; vb += dv * 8;
                kd += 2 * (SLOT >> 4); kb = it == 2 ? vb : kb + 16;
            }
            pv_issue(pb, vlast);
            const int row = wq * 16 + (lane >> 2);
            const uint32_t ml = sb + OFF_MISC;
            wg_wait<0>();
            pin(o); pin(pb); pin(sa); pin(sb2);
            rel(31);
            const float l0 = o[32], l1 = o[34];
            if (c4 == 0) { sts64f(ml + w * 512 + row * 8, n0, l0); sts64f(ml + w * 512 + row * 8 + 64, n1, l1); }
            TS(14);
            float mine[16];
#pragma unroll
            for (int j = 0; j < 4; j++) {
                if (w == 0) sts128f(H + j * 2048 + wt * 16, o[16 + 4 * j], o[17 + 4 * j], o[18 + 4 * j], o[19 + 4 * j]);
                else sts128f(H + 8192 + j * 2048 + wt * 16, o[4 * j], o[4 * j + 1], o[4 * j + 2], o[4 * j + 3]);
            }
#pragma unroll
            for (int i = 0; i < 16; i++) mine[i] = w == 0 ? o[i] : o[16 + i];
            bar_sync(10, 256);
            const float2 u0 = lds64f(ml + (w ^ 1) * 512 + row * 8), u1 = lds64f(ml + (w ^ 1) * 512 + row * 8 + 64);
            const float x0 = fminf(n0, u0.x), x1 = fminf(n1, u1.x);
            float a0 = ex2(x0 - n0), b0 = ex2(x0 - u0.x), a1 = ex2(x1 - n1), b1 = ex2(x1 - u1.x);
            const float i0 = __fdividef(1.f, fmaf(a0, l0, b0 * u0.y)), i1 = __fdividef(1.f, fmaf(a1, l1, b1 * u1.y));
            a0 *= i0; b0 *= i0; a1 *= i1; b1 *= i1;
            uint32_t pk[8];
#pragma unroll
            for (int j = 0; j < 4; j++) {
                const float4 v = lds128f(H + (w ^ 1) * 8192 + j * 2048 + wt * 16);
                pk[2 * j] = pack2(fmaf(a0, mine[4 * j], b0 * v.x), fmaf(a0, mine[4 * j + 1], b0 * v.y));
                pk[2 * j + 1] = pack2(fmaf(a1, mine[4 * j + 2], b1 * v.z), fmaf(a1, mine[4 * j + 3], b1 * v.w));
            }
            unsigned char* dst = g_o + (size_t)(abh * PADROWS + 8 + qt * 64 + wq * 16) * 128 + w * 512 + lane * 16;
            st_data(dst, pk[0], pk[2], pk[4], pk[6]);
            st_data(dst + 1024, pk[1], pk[3], pk[5], pk[7]);
            if (tid == 0) asm volatile("red.relaxed.gpu.global.add.u32 [%0], 1;" ::"l"(&g_epoch[blockIdx.x * FS]) : "memory");
            TS(15);
        }

        auto mm = [&](float (&d)[24], int n, uint32_t act, int acc) {
            const uint32_t z = p.zero * (ph + n);
            const uint64_t ad = mkdesc(rdesc + z + (n % NSLOT) * (SLOT >> 4)), bd = mkdesc(desc_lo(act) + z);
            wg_fence();
#pragma unroll
            for (int k = 0; k < 8; k++) mma_t(d, ad + k * 128, bd + (k >> 2) * (XCH >> 4) + (k & 3) * 2, k == 0 ? acc : 1);
            wg_commit();
        };
        uint32_t dwr[15];
        {
#pragma unroll
            for (int i = 0; i < 15; i++) dwr[i] = hmul2(__ldg(reinterpret_cast<const uint32_t*>(p.dw + i * 256 + tile * 64) + lane), 0x3F003F00u);
            float d[24];
            uint32_t xw[12];
            bar_sync(9, 384);
#pragma unroll
            for (int j = 0; j < 3; j++) ldsm4t(xt + j * 2048, xw[4 * j], xw[4 * j + 1], xw[4 * j + 2], xw[4 * j + 3]);
            pin(xw);
            acq(32); acq(33); acq(34); acq(35);
            {
                const uint32_t t0 = clock();
                while (clock() - t0 < ODELAY) {}
                uint4 u[6] = {};
                ld_data(u, g_o + (size_t)((b * 4 + (warp >> 1)) * PADROWS + pt * 32) * 128 + (warp & 1) * 512 + lane * 16, 1024);
                const uint32_t dst = H + (warp >> 1) * XCH + (foff ^ ((warp & 1) * 64));
#pragma unroll
                for (int i = 0; i < 6; i++) stsm4(dst + i * 1024, u[i].x, u[i].y, u[i].z, u[i].w);
            }
            fence_async_smem();
            bar_sync(10, 256);
            TS(16);
            mm(d, 32, H, 0);
            mm(d, 33, H + 2 * XCH, 1);
            wg_wait<1>();
            rel(32);
            wg_wait<0>();
            pin(d);
#pragma unroll
            for (int i = 0; i < 12; i++) xw[i] = pack2(d[2 * i] + blo(xw[i]), d[2 * i + 1] + bhi(xw[i]));
            if (c4 == 0) { xw[0] = (xw[0] & 0xffff0000u) | 0x3F80u; xw[1] = (xw[1] & 0xffff0000u) | 0x3F80u; }
#pragma unroll
            for (int j = 0; j < 3; j++) stsm4t(xt + j * 2048, xw[4 * j], xw[4 * j + 1], xw[4 * j + 2], xw[4 * j + 3]);
            rel(33);
            publish(B_X2, P + tile * XCH, XCH, 384);
            TS(17);
        }
        {
            float da[24], db[24], st[24];
            bar_sync(5, 384);
            mm(da, 34, P + 2 * r * XCH, 0);
            mm(db, 35, P + 2 * r * XCH, 0);
            acq(36); acq(37);
            mbar_wait(bars + B_X2 * 8, 0);
            bar_sync(5, 384);
            TS(39);
            mm(da, 36, P + 2 * (r ^ 1) * XCH, 1);
            mm(db, 37, P + 2 * (r ^ 1) * XCH, 1);
            wg_wait<2>();
            rel(34); rel(35);
            mbar_wait(bars + B_ST * 8, 0);
#pragma unroll
            for (int j = 0; j < 6; j++) {
                const float4 u = lds128f(sb + OFF_STATS + (8 * j + 2 * c4) * 8);
                st[4 * j] = u.x; st[4 * j + 1] = u.y; st[4 * j + 2] = u.z; st[4 * j + 3] = u.w;
            }
            wg_wait<0>();
            pin(da); pin(db);
            rel(36); rel(37);
            TS(18);
            uint32_t pk[12];
#pragma unroll
            for (int hh = 0; hh < 2; hh++) {
                const float ca = __shfl_sync(~0u, da[2 * hh], lane & 28), cb = __shfl_sync(~0u, db[2 * hh], lane & 28);
#pragma unroll
                for (int j = 0; j < 6; j++) {
                    const float u0 = fmaf(-st[4 * j], ca, da[4 * j + 2 * hh] * st[4 * j + 1]);
                    const float u1 = fmaf(-st[4 * j + 2], ca, da[4 * j + 2 * hh + 1] * st[4 * j + 3]);
                    const float v0 = fmaf(-st[4 * j], cb, db[4 * j + 2 * hh] * st[4 * j + 1]);
                    const float v1 = fmaf(-st[4 * j + 2], cb, db[4 * j + 2 * hh + 1] * st[4 * j + 3]);
                    pk[2 * j + hh] = pack2(fmaf(u0, tanh_fast(v0), u0), fmaf(u1, tanh_fast(v1), u1));
                }
            }
            const uint32_t gs = H + 16384 + w * XCH;
#pragma unroll
            for (int j = 0; j < 3; j++) stsm4t(gs + toff + j * 2048, pk[4 * j], pk[4 * j + 1], pk[4 * j + 2], pk[4 * j + 3]);
            ldsm4(xo + 1024 + foff, xr[0], xr[1], xr[2], xr[3]);
            ldsm4(xo + 1024 + (foff ^ 64), xr[4], xr[5], xr[6], xr[7]);
            bar_sync(2 + w, 128);
            uint32_t ca[8], cb[8];
            const uint32_t grow = gs + 8 * wq * 128 + c4 * 4, srow = H + tile * HCH + 8 * wq * 128 + c4 * 4;
#pragma unroll
            for (int k = 0; k < 22; k++) {
                const uint32_t v = lds32(grow + (1 + k) * 128 + (((lane >> 2) ^ ((1 + k) & 7)) << 4));
#pragma unroll
                for (int i = 0; i < 8; i++) {
                    const int tap = k - i;
                    if (tap == 0) ca[i] = hmul2(v, dwr[0]);
                    else if (tap > 0 && tap < 8) ca[i] = hfma2(v, dwr[tap], ca[i]);
                    else if (tap == 8) cb[i] = hmul2(v, dwr[8]);
                    else if (tap > 8 && tap < 15) cb[i] = hfma2(v, dwr[tap], cb[i]);
                }
            }
#pragma unroll
            for (int i = 0; i < 8; i++) {
                const float h0 = blo(ca[i]) + blo(cb[i]), h1 = bhi(ca[i]) + bhi(cb[i]);
                sts32(srow + i * 128 + (((lane >> 2) ^ i) << 4), pack2(fmaf(h0, tanh_fast(h0), h0), fmaf(h1, tanh_fast(h1), h1)));
            }
            acq(38); acq(39);
            publish(B_SR, H + tile * HCH, HCH, 256);
            TS(19);
        }
        {
            auto frags = [&](int i, int half) {
                const uint32_t src = H + 2 * half * HCH + wq * 1024;
#pragma unroll
                for (int k = 0; k < 4; k++) ldsm4(src + (k >> 1) * HCH + (foff ^ ((k & 1) * 64)), a[i + 4 * k], a[i + 4 * k + 1], a[i + 4 * k + 2], a[i + 4 * k + 3]);
            };
            frags(0, r);
            sp(d0, 38, a, 0, 0);
            acq(40);
            mbar_wait(bars + B_SR * 8, 0);
            frags(16, r ^ 1);
            sp(d0, 39, a + 16, 0, 1);
            wg_wait<1>();
            rel(38);
            wg_wait<0>();
            pin(d0);
            rel(39);
#pragma unroll
            for (int j = 0; j < 8; j++) {
                v[2 * j] = d0[4 * j] + d0[4 * j + 2] + blo(xr[j]);
                v[2 * j + 1] = d0[4 * j + 1] + d0[4 * j + 3] + bhi(xr[j]);
            }
            TS(20);
        }
    }

    cluster_arrive();
    TS(24);
    {
        const float rstd = rsq(fmaxf(fmaf(-mean, mean, msq), 0.f) + 1e-5f), nb = -mean * rstd;
#pragma unroll
        for (int j = 0; j < 8; j++) xr[j] = pack2(fmaf(v[2 * j], rstd, nb), fmaf(v[2 * j + 1], rstd, nb));
        const uint32_t stg = P + 16384 + warp * 1024;
        stsm4(stg + foff, xr[0], xr[1], xr[2], xr[3]);
        stsm4(stg + (foff ^ 64), xr[4], xr[5], xr[6], xr[7]);
        __syncwarp();
        const uint32_t src = stg + (lane >> 3) * 128 + (((lane & 7) ^ (lane >> 3)) << 4);
        const uint4 u0 = lds128(src), u1 = lds128((src + 512) ^ 64);
        __nv_bfloat16* dst = p.out + (size_t)(b * T_ + trow + (lane >> 3)) * 256 + tile * 64 + (lane & 7) * 8;
        if (trow < T_) { stg128(dst, u0); stg128(dst + 4 * 256, u1); }
    }
    TS(25);
    TG(31);
    TSDUMP();
    cluster_wait();
}

typedef CUresult (*EncodeFn)(CUtensorMap*, CUtensorMapDataType, cuuint32_t, void*, const cuuint64_t*, const cuuint64_t*,
                             const cuuint32_t*, const cuuint32_t*, CUtensorMapInterleave, CUtensorMapSwizzle,
                             CUtensorMapL2promotion, CUtensorMapFloatOOBfill);

}

extern "C" void kernel_launch(void* const* d_in, const int* in_sizes, int n_in, void* d_out, int out_size) {
    static EncodeFn encode = nullptr;
    if (!encode) {
        void* fn = nullptr;
        cudaDriverEntryPointQueryResult qr;
        cudaGetDriverEntryPoint("cuTensorMapEncodeTiled", &fn, cudaEnableDefault, &qr);
        encode = (EncodeFn)fn;
        cudaFuncSetAttribute(conformer_kernel, cudaFuncAttributeMaxDynamicSharedMemorySize, SMEM_LAUNCH);
    }
    Params p;
    const cuuint32_t ones[5] = {1, 1, 1, 1, 1};
    const int idx[8] = {1, 2, 3, 4, 5, 7, 8, 9};
    const int rows[8] = {256, 1024, 256, 256, 256, 256, 256, 1024};
    const int cols[8] = {1024, 256, 768, 256, 512, 256, 1024, 256};
    for (int i = 0; i < 8; i++) {
        const bool perm = i != 3 && i != 4;
        const cuuint64_t pitch = (cuuint64_t)cols[i] * 2;
        const cuuint64_t dims[5] = {(cuuint64_t)cols[i], 2, 2, 4, (cuuint64_t)rows[i] / 16};
        const cuuint64_t strides[4] = {pitch, pitch * (perm ? 8 : 2), pitch * (perm ? 2 : 4), pitch * 16};
        const cuuint32_t box[5] = {64, 2, 2, 4, 8};
        encode(&p.tm[i], CU_TENSOR_MAP_DATA_TYPE_BFLOAT16, 5, d_in[idx[i]], dims, strides, box, ones, CU_TENSOR_MAP_INTERLEAVE_NONE,
               CU_TENSOR_MAP_SWIZZLE_128B, CU_TENSOR_MAP_L2_PROMOTION_L2_128B, CU_TENSOR_MAP_FLOAT_OOB_FILL_NONE);
        p.w[i] = (const char*)d_in[idx[i]];
    }
    {
        void* kv = nullptr;
        cudaGetSymbolAddress(&kv, g_kvq);
        const cuuint64_t dims[2] = {64, 16384};
        const cuuint64_t strides[1] = {128};
        const cuuint32_t box[2] = {64, 128};
        encode(&p.tm[8], CU_TENSOR_MAP_DATA_TYPE_BFLOAT16, 2, kv, dims, strides, box, ones, CU_TENSOR_MAP_INTERLEAVE_NONE,
               CU_TENSOR_MAP_SWIZZLE_NONE, CU_TENSOR_MAP_L2_PROMOTION_L2_128B, CU_TENSOR_MAP_FLOAT_OOB_FILL_NONE);
    }
    p.x = (const __nv_bfloat16*)d_in[0];
    p.dw = (const __nv_bfloat16*)d_in[6];
    p.out = (__nv_bfloat16*)d_out;
    p.zero = 0;
    conformer_kernel<<<NCTA, NTHREADS, SMEM_LAUNCH>>>(p);
}
```

```cpp
#include <cuda_runtime.h>
#include <cuda_bf16.h>
#include <cuda.h>
#include <stdint.h>

namespace {

constexpr int T_ = 1000;
constexpr int NCTA = 128;
constexpr int NTHREADS = 512;
constexpr int NSLOT = 5;
constexpr int SLOT = 16384;
constexpr int NLOADS = 56;

constexpr uint32_t OFF_RING = 0;
constexpr uint32_t OFF_P = 163840;
constexpr uint32_t OFF_H = 188416;
constexpr uint32_t OFF_MISC = 221184;
constexpr uint32_t OFF_STATS = 229376;
constexpr uint32_t OFF_BARS = 229888;
constexpr uint32_t SMEM_BYTES = 230400;
constexpr uint32_t XCH = 6144;
constexpr uint32_t HCH = 4096;

constexpr int B_FULL = 0, B_EMPTY = 10, B_XA = 20  , B_XB = 24  , B_INB = 27  , B_X2 = 31, B_SR = 32,
              B_RST = 33  , B_KSEEN = 35, B_RDY = 36  , B_SINK = 42, B_ST = 43;

#define PACE 1
#define ODELAY 0u
#define ORDER 0
#define TURN 0
#define EAGER 0x5555
constexpr int PADROWS = 1040;
constexpr int FS = 8;

struct Params {
    CUtensorMap tm[9];
    const char* w[8];
    const __nv_bfloat16* x;
    const __nv_bfloat16* dw;
    __nv_bfloat16* out;
    uint32_t zero;
};

__device__ __align__(1024) unsigned char g_kvq[3 * 8 * 1024 * 128];
__device__ __align__(1024) unsigned char g_o[8 * PADROWS * 128];
__device__ uint4 g_halo[64 * 4 * 2 * 64];
__device__ uint32_t g_flag_kv[2 * 8 * 32 * FS];
__device__ uint32_t g_reset[4 * 32];
__device__ uint32_t g_epoch[NCTA * FS];

#define TS(i) do { } while (0)
#define TSW(i) do { } while (0)
#define TG(i) do { } while (0)
#define TSINIT() do { } while (0)
#define TSDUMP() do { } while (0)
constexpr uint32_t SMEM_LAUNCH = SMEM_BYTES;

__device__ __forceinline__ uint32_t smem_u32(const void* p) { return (uint32_t)__cvta_generic_to_shared(p); }
__device__ __forceinline__ void mbar_init(uint32_t b, uint32_t c) { asm volatile("mbarrier.init.shared::cta.b64 [%0], %1;" ::"r"(b), "r"(c) : "memory"); }
__device__ __forceinline__ void mbar_arrive(uint32_t b) { asm volatile("mbarrier.arrive.shared::cta.b64 _, [%0];" ::"r"(b) : "memory"); }
__device__ __forceinline__ void mbar_arrive_tx(uint32_t b, uint32_t tx) { asm volatile("mbarrier.arrive.expect_tx.shared::cta.b64 _, [%0], %1;" ::"r"(b), "r"(tx) : "memory"); }
__device__ __forceinline__ void mbar_wait(uint32_t b, uint32_t ph) {
    asm volatile("{\n.reg .pred p, q;\n.reg .u32 c;\nmov.u32 c, 0;\n"
                 "MW_LOOP:\n.pragma \"nounroll\";\n"
                 "mbarrier.try_wait.parity.shared::cta.b64 p, [%0], %1;\n"
                 "add.u32 c, c, 1;\nsetp.lt.u32 q, c, 65536;\nnot.pred p, p;\nand.pred p, p, q;\n@p bra MW_LOOP;\n}"
                 ::"r"(b), "r"(ph) : "memory");
}
__device__ __forceinline__ bool mbar_test(uint32_t b, uint32_t ph) {
    uint32_t ok;
    asm volatile("{\n.reg .pred p;\nmbarrier.test_wait.parity.shared::cta.b64 p, [%1], %2;\nselp.u32 %0, 1, 0, p;\n}" : "=r"(ok) : "r"(b), "r"(ph) : "memory");
    return ok;
}
__device__ __forceinline__ uint32_t mapa(uint32_t a, uint32_t r) { uint32_t o; asm("mapa.shared::cluster.u32 %0, %1, %2;" : "=r"(o) : "r"(a), "r"(r)); return o; }
__device__ __forceinline__ void fence_async_smem() { asm volatile("fence.proxy.async.shared::cta;" ::: "memory"); }
__device__ __forceinline__ void fence_async_global() { asm volatile("fence.proxy.async.global;" ::: "memory"); }
__device__ __forceinline__ void bar_sync(int id, int n) { asm volatile("bar.sync %0, %1;" ::"r"(id), "r"(n) : "memory"); }
__device__ __forceinline__ void bar_arrive(int id, int n) { asm volatile("bar.arrive %0, %1;" ::"r"(id), "r"(n) : "memory"); }
__device__ __forceinline__ void cluster_arrive() { asm volatile("barrier.cluster.arrive.relaxed.aligned;" ::: "memory"); }
__device__ __forceinline__ void cluster_wait() { asm volatile("barrier.cluster.wait.aligned;" ::: "memory"); }

__device__ __forceinline__ void ring_load(uint32_t dst, const CUtensorMap* tm, int col, int row16, uint32_t bar) {
    asm volatile("{\n.reg .pred p;\nelect.sync _|p, 0xffffffff;\n"
                 "@p mbarrier.arrive.expect_tx.shared::cta.b64 _, [%2], 16384;\n"
                 "@p cp.async.bulk.tensor.5d.shared::cluster.global.mbarrier::complete_tx::bytes [%0], [%1, {%3, 0, 0, 0, %4}], [%2];\n}"
                 ::"r"(dst), "l"(tm), "r"(bar), "r"(col), "r"(row16) : "memory");
}
__device__ __forceinline__ void ring_load_both(uint32_t dst, const CUtensorMap* tm, int c1, uint32_t bar) {
    asm volatile("{\n.reg .pred p;\nelect.sync _|p, 0xffffffff;\n"
                 "@p cp.async.bulk.tensor.2d.shared::cluster.global.mbarrier::complete_tx::bytes.multicast::cluster [%0], [%1, {0, %3}], [%2], %4;\n}"
                 ::"r"(dst), "l"(tm), "r"(bar), "r"(c1), "h"((uint16_t)3) : "memory");
}
__device__ __forceinline__ void mbar_arrive_peer(uint32_t b) { asm volatile("mbarrier.arrive.relaxed.cluster.shared::cluster.b64 _, [%0];" ::"r"(b) : "memory"); }
__device__ __forceinline__ void prefetch_l2(const void* src, uint32_t bytes) {
    asm volatile("cp.async.bulk.prefetch.L2.global [%0], %1;" ::"l"(src), "r"(bytes) : "memory");
}
__device__ __forceinline__ void peer_copy(uint32_t dst, uint32_t src, uint32_t bytes, uint32_t rbar) {
    asm volatile("{\n.reg .pred p;\nelect.sync _|p, 0xffffffff;\n"
                 "@p cp.async.bulk.shared::cluster.shared::cta.mbarrier::complete_tx::bytes [%0], [%1], %2, [%3];\n}"
                 ::"r"(dst), "r"(src), "r"(bytes), "r"(rbar) : "memory");
}
__device__ __forceinline__ void st_async4(uint32_t dst, uint32_t a, uint32_t b, uint32_t c, uint32_t d, uint32_t bar) {
    asm volatile("st.async.shared::cluster.mbarrier::complete_tx::bytes.v4.b32 [%0], {%1,%2,%3,%4}, [%5];" ::"r"(dst), "r"(a), "r"(b), "r"(c), "r"(d), "r"(bar) : "memory");
}
__device__ __forceinline__ void st_async2f(uint32_t dst, float a, float b, uint32_t bar) {
    asm volatile("st.async.shared::cluster.mbarrier::complete_tx::bytes.v2.f32 [%0], {%1,%2}, [%3];" ::"r"(dst), "f"(a), "f"(b), "r"(bar) : "memory");
}
__device__ __forceinline__ void stsm4t(uint32_t a, uint32_t r0, uint32_t r1, uint32_t r2, uint32_t r3) {
    asm volatile("stmatrix.sync.aligned.m8n8.x4.trans.shared.b16 [%0], {%1,%2,%3,%4};" ::"r"(a), "r"(r0), "r"(r1), "r"(r2), "r"(r3) : "memory");
}
__device__ __forceinline__ void stsm4(uint32_t a, uint32_t r0, uint32_t r1, uint32_t r2, uint32_t r3) {
    asm volatile("stmatrix.sync.aligned.m8n8.x4.shared.b16 [%0], {%1,%2,%3,%4};" ::"r"(a), "r"(r0), "r"(r1), "r"(r2), "r"(r3) : "memory");
}
__device__ __forceinline__ void ldsm4t(uint32_t a, uint32_t& r0, uint32_t& r1, uint32_t& r2, uint32_t& r3) {
    asm volatile("ldmatrix.sync.aligned.m8n8.x4.trans.shared.b16 {%0,%1,%2,%3}, [%4];" : "=r"(r0), "=r"(r1), "=r"(r2), "=r"(r3) : "r"(a) : "memory");
}
__device__ __forceinline__ void ldsm4(uint32_t a, uint32_t& r0, uint32_t& r1, uint32_t& r2, uint32_t& r3) {
    asm volatile("ldmatrix.sync.aligned.m8n8.x4.shared.b16 {%0,%1,%2,%3}, [%4];" : "=r"(r0), "=r"(r1), "=r"(r2), "=r"(r3) : "r"(a) : "memory");
}
__device__ __forceinline__ uint4 lds128(uint32_t a) { uint4 v; asm volatile("ld.shared.v4.b32 {%0,%1,%2,%3}, [%4];" : "=r"(v.x), "=r"(v.y), "=r"(v.z), "=r"(v.w) : "r"(a) : "memory"); return v; }
__device__ __forceinline__ float4 lds128f(uint32_t a) { float4 v; asm volatile("ld.shared.v4.f32 {%0,%1,%2,%3}, [%4];" : "=f"(v.x), "=f"(v.y), "=f"(v.z), "=f"(v.w) : "r"(a) : "memory"); return v; }
__device__ __forceinline__ float2 lds64f(uint32_t a) { float2 v; asm volatile("ld.shared.v2.f32 {%0,%1}, [%2];" : "=f"(v.x), "=f"(v.y) : "r"(a) : "memory"); return v; }
__device__ __forceinline__ uint32_t lds32(uint32_t a) { uint32_t v; asm volatile("ld.shared.b32 %0, [%1];" : "=r"(v) : "r"(a) : "memory"); return v; }
__device__ __forceinline__ void sts128(uint32_t a, uint32_t x, uint32_t y, uint32_t z, uint32_t w) { asm volatile("st.shared.v4.b32 [%0], {%1,%2,%3,%4};" ::"r"(a), "r"(x), "r"(y), "r"(z), "r"(w) : "memory"); }
__device__ __forceinline__ void sts128f(uint32_t a, float x, float y, float z, float w) { asm volatile("st.shared.v4.f32 [%0], {%1,%2,%3,%4};" ::"r"(a), "f"(x), "f"(y), "f"(z), "f"(w) : "memory"); }
__device__ __forceinline__ void sts64f(uint32_t a, float x, float y) { asm volatile("st.shared.v2.f32 [%0], {%1,%2};" ::"r"(a), "f"(x), "f"(y) : "memory"); }
__device__ __forceinline__ void sts32(uint32_t a, uint32_t x) { asm volatile("st.shared.b32 [%0], %1;" ::"r"(a), "r"(x) : "memory"); }
__device__ __forceinline__ void stg128(void* p, uint4 v) { asm volatile("st.global.v4.b32 [%0], {%1,%2,%3,%4};" ::"l"(p), "r"(v.x), "r"(v.y), "r"(v.z), "r"(v.w) : "memory"); }

__device__ __forceinline__ uint32_t pack2(float lo, float hi) { uint32_t r; asm("cvt.rn.bf16x2.f32 %0, %1, %2;" : "=r"(r) : "f"(hi), "f"(lo)); return r; }
__device__ __forceinline__ float blo(uint32_t v) { return __uint_as_float(v << 16); }
__device__ __forceinline__ float bhi(uint32_t v) { return __uint_as_float(v & 0xffff0000u); }
__device__ __forceinline__ uint32_t hmul2(uint32_t a, uint32_t b) { uint32_t r; asm("mul.rn.bf16x2 %0, %1, %2;" : "=r"(r) : "r"(a), "r"(b)); return r; }
__device__ __forceinline__ uint32_t hsub2(uint32_t a, uint32_t b) { uint32_t r; asm("sub.rn.bf16x2 %0, %1, %2;" : "=r"(r) : "r"(a), "r"(b)); return r; }
__device__ __forceinline__ uint32_t hfma2(uint32_t a, uint32_t b, uint32_t c) { uint32_t r; asm("fma.rn.bf16x2 %0, %1, %2, %3;" : "=r"(r) : "r"(a), "r"(b), "r"(c)); return r; }
__device__ __forceinline__ float tanh_fast(float x) { float r; asm("tanh.approx.f32 %0, %1;" : "=f"(r) : "f"(x)); return r; }
__device__ __forceinline__ float rsq(float x) { float r; asm("rsqrt.approx.ftz.f32 %0, %1;" : "=f"(r) : "f"(x)); return r; }
__device__ __forceinline__ float ex2(float x) { float r; asm("ex2.approx.ftz.f32 %0, %1;" : "=f"(r) : "f"(x)); return r; }

__device__ __forceinline__ uint32_t ld_relaxed(const uint32_t* p) {
    uint32_t v;
    asm volatile("ld.relaxed.gpu.global.u32 %0, [%1];" : "=r"(v) : "l"(p) : "memory");
    return v;
}
__device__ __forceinline__ void flag_wait(const uint32_t* p, uint32_t e, uint32_t mask, uint32_t& seen) {
    if ((seen & mask) == mask) return;
    uint32_t a = ld_relaxed(p);
    const uint32_t t0 = clock();
    while (clock() - t0 < 200u) {}
#pragma unroll 1
    for (int i = 0; i < (1 << 19); i++) {
        const uint32_t b = ld_relaxed(p);
        seen = __ballot_sync(~0u, a == e);
        if ((seen & mask) == mask) break;
        a = ld_relaxed(p);
        seen = __ballot_sync(~0u, b == e);
        if ((seen & mask) == mask) break;
    }
    asm volatile("fence.acquire.gpu;" ::: "memory");
    fence_async_global();
}
__device__ __forceinline__ void st_data(void* p, uint32_t x, uint32_t y, uint32_t z, uint32_t w) {
    asm volatile("st.relaxed.gpu.global.v4.b32 [%0], {%1,%2,%3,%4};" ::"l"(p), "r"(x), "r"(y), "r"(z), "r"(w) : "memory");
}
template <int N>
__device__ __forceinline__ void ld_data(uint4 (&v)[N], const unsigned char* p, uint32_t stride) {
#pragma unroll
    for (int i = 0; i < N; i++) v[i].x = ~0u;
#pragma unroll 1
    for (int it = 0; it < (1 << 16); it++) {
        bool missing = false;
#pragma unroll
        for (int i = 0; i < N; i++)
            if (max(__vimax3_u32(v[i].x, v[i].y, v[i].z), v[i].w) == ~0u) {
                asm volatile("ld.relaxed.gpu.global.v4.b32 {%0,%1,%2,%3}, [%4];" : "=r"(v[i].x), "=r"(v[i].y), "=r"(v[i].z), "=r"(v[i].w) : "l"(p + i * stride) : "memory");
                missing = true;
            }
        if (!__any_sync(~0u, missing)) break;
    }
}
__device__ __forceinline__ uint32_t ld_epoch() { return ld_relaxed(&g_epoch[blockIdx.x * FS]) + 1; }
__device__ __forceinline__ void flag_set(uint32_t* p, uint32_t e) { asm volatile("st.release.gpu.global.u32 [%0], %1;" ::"l"(p), "r"(e) : "memory"); }

__device__ __forceinline__ uint32_t desc_lo(uint32_t addr) { return ((addr & 0x3FFFF) >> 4) | 0x10000u; }
__device__ __forceinline__ uint64_t mkdesc(uint32_t lo) { return (uint64_t)lo | (0x40000040ull << 32); }
__device__ __forceinline__ void wg_fence() { asm volatile("wgmma.fence.sync.aligned;" ::: "memory"); }
__device__ __forceinline__ void wg_commit() { asm volatile("wgmma.commit_group.sync.aligned;" ::: "memory"); }
template <int N> __device__ __forceinline__ void wg_wait() { asm volatile("wgmma.wait_group.sync.aligned %0;" ::"n"(N) : "memory"); }
template <int N> __device__ __forceinline__ void pin(float (&d)[N]) {
#pragma unroll
    for (int i = 0; i < N; i++) asm volatile("" : "+f"(d[i])::"memory");
}
template <int N> __device__ __forceinline__ void pin(uint32_t (&d)[N]) {
#pragma unroll
    for (int i = 0; i < N; i++) asm volatile("" : "+r"(d[i])::"memory");
}

template <typename Tp, int N> __device__ __forceinline__ void zero(Tp (&d)[N]) {
#pragma unroll
    for (int i = 0; i < N; i++) d[i] = 0;
    pin(d);
}

#define F4(d, i) "+f"(d[i]), "+f"(d[i + 1]), "+f"(d[i + 2]), "+f"(d[i + 3])
#define F16(d, i) F4(d, i), F4(d, i + 4), F4(d, i + 8), F4(d, i + 12)

__device__ __forceinline__ void mma_sp(float (&d)[32], const uint32_t* a, uint64_t b, uint32_t meta, int acc) {
    asm volatile("{.reg .pred p; setp.ne.b32 p, %38, 0;\n"
                 "wgmma.mma_async.sp.sync.aligned.m64n64k32.f32.bf16.bf16 {%0,%1,%2,%3,%4,%5,%6,%7,%8,%9,%10,%11,%12,%13,%14,%15,%16,%17,%18,%19,%20,%21,%22,%23,%24,%25,%26,%27,%28,%29,%30,%31}, "
                 "{%32,%33,%34,%35}, %36, %37, 0, p, 1, 1, 1;}\n"
                 : F16(d, 0), F16(d, 16) : "r"(a[0]), "r"(a[1]), "r"(a[2]), "r"(a[3]), "l"(b), "r"(meta), "r"(acc));
}
__device__ __forceinline__ void mma_t(float (&d)[24], uint64_t a, uint64_t b, int acc) {
    asm volatile("{.reg .pred p; setp.ne.b32 p, %26, 0;\n"
                 "wgmma.mma_async.sync.aligned.m64n48k16.f32.bf16.bf16 {%0,%1,%2,%3,%4,%5,%6,%7,%8,%9,%10,%11,%12,%13,%14,%15,%16,%17,%18,%19,%20,%21,%22,%23}, %24, %25, p, 1, 1, 1, 0;}\n"
                 : F16(d, 0), F4(d, 16), F4(d, 20) : "l"(a), "l"(b), "r"(acc));
}
__device__ __forceinline__ void mma_qk(float (&d)[32], uint32_t a0, uint32_t a1, uint32_t a2, uint32_t a3, uint64_t b, int acc) {
    asm volatile("{.reg .pred p; setp.ne.b32 p, %37, 0;\n"
                 "wgmma.mma_async.sync.aligned.m64n64k16.f32.bf16.bf16 {%0,%1,%2,%3,%4,%5,%6,%7,%8,%9,%10,%11,%12,%13,%14,%15,%16,%17,%18,%19,%20,%21,%22,%23,%24,%25,%26,%27,%28,%29,%30,%31}, "
                 "{%32,%33,%34,%35}, %36, p, 1, 1, 0;}\n"
                 : F16(d, 0), F16(d, 16) : "r"(a0), "r"(a1), "r"(a2), "r"(a3), "l"(b), "r"(acc));
}
__device__ __forceinline__ void mma_pv(float (&d)[36], uint32_t a0, uint32_t a1, uint32_t a2, uint32_t a3, uint64_t b) {
    asm volatile("wgmma.mma_async.sync.aligned.m64n72k16.f32.bf16.bf16 {%0,%1,%2,%3,%4,%5,%6,%7,%8,%9,%10,%11,%12,%13,%14,%15,%16,%17,%18,%19,%20,%21,%22,%23,%24,%25,%26,%27,%28,%29,%30,%31,%32,%33,%34,%35}, "
                 "{%36,%37,%38,%39}, %40, 1, 1, 1, 1;\n"
                 : F16(d, 0), F16(d, 16), F4(d, 32) : "r"(a0), "r"(a1), "r"(a2), "r"(a3), "l"(b));
}

__device__ __forceinline__ uint32_t load_code(int n, int r, int w) {
    const int tile = 2 * r + w;
    int m, col, row;
    if (n < 16 || n >= 40) {
        const int k = n < 16 ? n : n - 40;
        m = n < 16 ? 0 : 6;
        if (k < 8) { col = 4 * tile + (k >> 1); row = (k & 1) ^ r; }
        else { m++; col = tile ^ (3 - ((k - 8) >> 1)); row = 2 * tile + (k & 1); }
    } else if (n < 32) {
        const int k = n - 16;
        m = 2;
        if (ORDER == 1) { col = tile + 2 * (k & 6); row = (k & 1) ^ r; }
        else if (k < 4) { col = tile + ((k & 1) ? 8 : 4); row = (k >> 1) ^ r; }
        else { col = tile; row = (k & 1) ^ r; }
    } else if (n < 34) { m = 3; col = tile; row = n - 32; }
    else if (n < 38) { const int k = n - 34; m = 4; col = tile + 4 * (k & 1); row = (k >> 1) ^ r; }
    else { m = 5; col = tile; row = (n & 1) ^ r; }
    return m | (col << 4) | (row << 8);
}

__global__ void __cluster_dims__(2, 1, 1) __launch_bounds__(NTHREADS, 1)
conformer_kernel(const __grid_constant__ Params p) {
    extern __shared__ __align__(1024) unsigned char smem_raw[];
    const uint32_t sb = smem_u32(smem_raw);
    const uint32_t bars = sb + OFF_BARS;
    const int tid = threadIdx.x;
    const int lane = tid & 31;
    const int warp = __shfl_sync(~0u, tid >> 5, 0);
    const int r = blockIdx.x & 1;
    const int pair = blockIdx.x >> 1;
    const int b = pair >> 5, pt = pair & 31;
    const int ah = pt >> 3, qt = (pt & 7) * 2 + r;
    const int abh = b * 4 + ah;

    TG(30);
    TSINIT();
    TS(0);
    const uint32_t P = sb + OFF_P, H = sb + OFF_H;

    if (warp >= 8) {
        asm volatile("setmaxnreg.dec.sync.aligned.u32 48;");
        if (warp >= 12) {
            cluster_arrive();
            cluster_wait();
            const int ut = tid & 127;
            const uint32_t target = ld_epoch() * 64;
            auto reset_done = [&](int k) {
                bar_sync(11, 128);
                if (ut == 0) {
                    asm volatile("red.release.gpu.global.add.u32 [%0], 1;" ::"l"(&g_reset[(2 * b + k) * 32]) : "memory");
#pragma unroll 1
                    for (int i = 0; i < (1 << 20) && ld_relaxed(&g_reset[(2 * b + k) * 32]) != target; i++) __nanosleep(100);
                    asm volatile("fence.acquire.gpu;" ::: "memory");
                    mbar_arrive(bars + (B_RST + k) * 8);
                }
                __syncwarp();
                TS(13 + k);
            };
#pragma unroll
            for (int i = 0; i < 4; i++) {
                st_data(g_kvq + 2097152 + (size_t)((b * 4 + 2 * r + (i >> 1)) * 1024 + pt * 32) * 128 + (i & 1) * 2048 + ut * 16, ~0u, ~0u, ~0u, ~0u);
                if (i < 2) st_data(&g_halo[(pair * 4 + 2 * r + i) * 128 + ut], ~0u, ~0u, ~0u, ~0u);
            }
            reset_done(0);
            bar_sync(6, 384);
#pragma unroll
            for (int i = 0; i < 4; i++) st_data(g_o + (size_t)(abh * PADROWS + 8 + qt * 64) * 128 + i * 2048 + ut * 16, ~0u, ~0u, ~0u, ~0u);
            reset_done(1);
            {
                const int side = warp & 1, t = 2 * r + ((warp >> 1) & 1), np = side ? pt + 1 : pt - 1;
                uint4 hv[2] = {make_uint4(0, 0, 0, 0), make_uint4(0, 0, 0, 0)};
                if (np >= 0 && np < 32)
                    ld_data(hv, reinterpret_cast<const unsigned char*>(&g_halo[(((b * 32 + np) * 4 + t) * 2 + (side ^ 1)) * 64 + lane]), 512);
                const uint32_t dst = P + t * XCH + side * 5120 + (lane & 7) * 128 + (((lane >> 3) ^ (lane & 7)) << 4);
                stsm4(dst, hv[0].x, hv[0].y, hv[0].z, hv[0].w);
                stsm4(dst ^ 64, hv[1].x, hv[1].y, hv[1].z, hv[1].w);
                bar_arrive(9, 384);
            }
            const uint32_t a8 = P + (ut >> 3) * 128 + (ut & 7) * 16;
            float s[3] = {0.f, 0.f, 0.f}, q[3] = {0.f, 0.f, 0.f};
#pragma unroll 1
            for (int h = 0; h < 2; h++) {
                if (h == 0) bar_sync(1, 384);
                else mbar_wait(bars + B_X2 * 8, 0);
                uint4 v[6];
#pragma unroll
                for (int i = 0; i < 6; i++) v[i] = lds128(a8 + (2 * (r ^ h) + (i & 1)) * XCH + (i >> 1) * 2048);
                bar_arrive(5 + ((v[0].w | v[1].w | v[2].w | v[3].w | v[4].w | v[5].w) & p.zero), 384);
                uint32_t t;
                asm volatile("mov.u32 %0, %%clock;" : "=r"(t)::"memory");
                const uint32_t mul = 65536u + (t & p.zero), msk = 0u - mul;
#pragma unroll
                for (int i = 0; i < 6; i++) {
                    const float a0 = __uint_as_float(v[i].x * mul), a1 = __uint_as_float(v[i].x & msk), a2 = __uint_as_float(v[i].y * mul), a3 = __uint_as_float(v[i].y & msk);
                    const float a4 = __uint_as_float(v[i].z * mul), a5 = __uint_as_float(v[i].z & msk), a6 = __uint_as_float(v[i].w * mul), a7 = __uint_as_float(v[i].w & msk);
                    s[i >> 1] += ((a0 + a1) + (a2 + a3)) + ((a4 + a5) + (a6 + a7));
                    q[i >> 1] += fmaf(a0, a0, fmaf(a1, a1, fmaf(a2, a2, a3 * a3))) + fmaf(a4, a4, fmaf(a5, a5, fmaf(a6, a6, a7 * a7)));
                }
            }
#pragma unroll
            for (int o = 1; o < 8; o <<= 1) {
#pragma unroll
                for (int i = 0; i < 3; i++) { s[i] += __shfl_xor_sync(~0u, s[i], o); q[i] += __shfl_xor_sync(~0u, q[i], o); }
            }
            const int k = ut & 7, row = (ut >> 3) + 16 * k;
            const float mean = (k == 0 ? s[0] : (k == 1 ? s[1] : s[2])) * (1.f / 256.f);
            const float msq = (k == 0 ? q[0] : (k == 1 ? q[1] : q[2])) * (1.f / 256.f);
            const float alpha = (uint32_t)(pt * 32 - 8 + row) >= T_ ? 0.f : 0.5f;
            const float rstd = alpha * rsq(fmaxf(fmaf(-mean, mean, msq), 0.f) + 1e-5f);
            if (k < 3) sts64f(sb + OFF_STATS + row * 8, mean * rstd, rstd);
            __syncwarp();
            if (lane == 0) mbar_arrive(bars + B_ST * 8);
            TS(4);
        } else if (warp < 10) {
            const int w = warp - 8;
            const uint32_t ring = sb + OFF_RING + w * NSLOT * SLOT;
            const uint32_t full = bars + (B_FULL + w * NSLOT) * 8;
            if (lane == 0) {
#pragma unroll
                for (int i = 0; i < NSLOT; i++) { mbar_init(full + i * 8, 1); mbar_init(full + (B_EMPTY - B_FULL + i) * 8, 4); }
                asm volatile("fence.mbarrier_init.release.cluster;" ::: "memory");
                fence_async_smem();
            }
            __syncwarp();
            cluster_arrive();
            TS(1);
#pragma unroll
            for (int n = 0; n < NSLOT; n++) {
                if (n == 1 || n == 2) bar_sync(12, 64);
                ring_load(ring + n * SLOT, &p.tm[0], 64 * (8 * r + 4 * w + (n >> 1)), 8 * ((n & 1) ^ r), full + n * 8);
            }
            TS(2);
            const uint32_t code = load_code(lane, r, w) | (load_code(lane + 32, r, w) << 16);
            cluster_wait();
            uint32_t s = 0, ph = 0;
            int n = NSLOT;
#pragma unroll 1
            for (int seg = 0; seg < 2; seg++) {
#pragma unroll 1
                for (; n < (seg == 0 ? 22 : NLOADS); n++) {
                    const uint32_t c = __shfl_sync(~0u, code, n) >> (n & 32 ? 16 : 0);
                    const CUtensorMap* tm = &p.tm[c & 15];
                    const uint32_t col = (c & 0xf0) * 4, row = (c & 0xff00) >> 5, dst = ring + s * SLOT;
                    mbar_wait(full + (B_EMPTY - B_FULL) * 8 + s * 8, ph + (((uint32_t)(size_t)tm | col | row | dst) & p.zero));
                    ring_load(dst, tm, col, row, full + s * 8);
                    if (++s == NSLOT) { s = 0; ph ^= 1; }
                }
                if (seg == 1) break;
                const uint32_t epoch = ld_epoch();
                const uint32_t rdy = bars + (B_RDY + 3 * w) * 8, prdy = mapa(rdy, r ^ 1);
                const int isv = r ^ w;
                const uint32_t* flags = g_flag_kv + (ORDER * isv * 256 + abh * 32 + lane) * FS;
                uint32_t seen = 0;
                auto kv_load = [&](uint32_t sl, int i) {
                    ring_load_both(ring + sl * SLOT, &p.tm[8], (isv * 64 + abh * 8 + 2 * i + w) * 128, full + sl * 8);
                };
#pragma unroll 1
                for (int i = 0; i < 2; i++) {
                    if (lane < 3 + i) {
                        const uint32_t sl = i ? lane : lane + 2;
                        mbar_wait(full + (B_EMPTY - B_FULL + sl) * 8, i ^ 1);
                        mbar_arrive_tx(full + sl * 8, (i || lane == 2) ? SLOT : 0);
                    }
                    __syncwarp();
                }
                if (lane == 0) mbar_arrive_peer(prdy);
                mbar_wait(rdy, 0);
#pragma unroll 1
                for (int j = isv; j < 3; j++) {
                    flag_wait(flags, epoch, 0xfu << (8 * (j - isv) + 4 * w), seen);
                    if (j == isv) TSW(5 + 2 * isv);
                    if (j == 0 && lane == 0) mbar_arrive(bars + B_KSEEN * 8);
                    if (j == 1 && PACE) mbar_wait(full + 32, 0);
                    if (j == 2) mbar_wait(full + isv * 8, 1);
                    kv_load(j ? 2 * j - 2 + isv : 4, j - isv);
                }
                flag_wait(flags, epoch, ~0u, seen);
#pragma unroll 1
                for (int i = 0; i < 3; i++) {
                    const uint32_t sl = i ? i - 1 : 4, bo = i == 2 ? 16 : 8;
                    mbar_wait(full + (B_EMPTY - B_FULL + sl) * 8, i != 0);
                    if (lane == 0) mbar_arrive_tx(full + sl * 8, SLOT);
                    if ((i != 0) == (isv == 1)) {
                        mbar_wait(rdy + bo, 0);
                        kv_load(sl, i == 1 ? 2 : 3);
                    } else if (lane == 0) mbar_arrive_peer(prdy + bo);
                    __syncwarp();
                }
                n = 32; s = 2; ph = 1;
            }
        } else if (warp == 10) {
            if (lane == 0) {
#pragma unroll
                for (int i = B_XA; i <= B_ST; i++) mbar_init(bars + i * 8, i == B_ST ? 4 : 1);
#pragma unroll
                for (int i = B_XA; i <= B_SR; i++) mbar_arrive_tx(bars + i * 8, i < B_XB ? 512 : (i == B_X2 ? 12288 : 8192));
                asm volatile("fence.mbarrier_init.release.cluster;" ::: "memory");
                fence_async_smem();
            }
            __syncwarp();
            cluster_arrive();
            cluster_wait();
        } else {
            const uint32_t kb = (lane < 2 || lane > 5) ? 4096 : (lane == 2 ? 3072 : (lane == 4 ? 2048 : 1024));
            const char* pf = p.w[lane & 7] + blockIdx.x * kb;
            cluster_arrive();
            cluster_wait();
            if (lane < 2) prefetch_l2(pf, kb);
            mbar_wait(bars + B_XA * 8, 0);
            if (lane == 2) prefetch_l2(pf, kb);
            if (lane >= 1 && lane < 9) asm volatile("prefetch.tensormap [%0];" ::"l"(&p.tm[lane]) : "memory");
            mbar_wait(bars + (B_FULL + 1) * 8, 1);
            if (lane > 2 && lane < 8) prefetch_l2(pf, kb);
            if (lane == 8 && blockIdx.x < 15) prefetch_l2(p.dw + blockIdx.x * 256, 512);
            const uint32_t epoch = ld_epoch();
            bar_sync(4, 288);
            if (lane < 2) flag_set(&g_flag_kv[((b * 4 + 2 * r + lane) * 32 + pt) * FS], epoch);
            __syncwarp();
            bar_arrive(13, 288);
            TSW(8);
            if (ORDER == 1) {
                bar_sync(4, 288);
                if (lane < 2) flag_set(&g_flag_kv[(256 + (b * 4 + 2 * r + lane) * 32 + pt) * FS], epoch);
                __syncwarp();
                TSW(9);
            }
        }
        TSDUMP();
        return;
    }

    const int w = warp >> 2, wq = warp & 3;
    const int tile = 2 * r + w;
    const int wt = tid & 127;
    const int c4 = lane & 3;
    const int trow = pt * 32 + 8 * wq;
    uint32_t xr[8];
    {
        const uint32_t* xp = reinterpret_cast<const uint32_t*>(p.x + (size_t)(b * T_ + trow + (lane >> 2)) * 256 + tile * 64) + c4;
#pragma unroll
        for (int j = 0; j < 8; j++) xr[j] = trow < T_ ? __ldg(xp + 4 * j) : 0u;
    }
    cluster_arrive();
    asm volatile("setmaxnreg.inc.sync.aligned.u32 208;");
    const uint32_t rbase = sb + OFF_RING + w * NSLOT * SLOT, fbar = bars + (B_FULL + w * NSLOT) * 8;
    const uint32_t rdesc = desc_lo(rbase);
    auto acq = [&](int n) { mbar_wait(fbar + (n % NSLOT) * 8, (n / NSLOT) & 1); };
    auto rel = [&](int n) { if (lane == 0) mbar_arrive(fbar + (B_EMPTY - B_FULL + n % NSLOT) * 8); };
    const uint32_t foff = (lane & 7) * 128 + (((lane >> 3) ^ (lane & 7)) << 4);
    const uint32_t toff = ((lane >> 4) * 8 + (lane & 7)) * 128 + (((2 * wq + ((lane >> 3) & 1)) ^ (lane & 7)) << 4);
    auto publish = [&](int bar, uint32_t src, uint32_t bytes, int nsync) {
        fence_async_smem();
        bar_sync(2 + w, 128);
        if (wq == 0) peer_copy(mapa(src, r ^ 1), src, bytes, mapa(bars + bar * 8, r ^ 1));
        bar_sync(nsync == 384 ? 1 : 10, nsync);
    };
    float v[16];
#pragma unroll
    for (int j = 0; j < 8; j++) { v[2 * j] = blo(xr[j]); v[2 * j + 1] = bhi(xr[j]); }
    const uint32_t xown = __shfl_sync(~0u, P + wt * 16 + tile * 4096, lane), xrem = __shfl_sync(~0u, P + wt * 16 + (r ^ 1) * 8192, lane);
    const uint32_t sbuf = __shfl_sync(~0u, sb + OFF_MISC + 1024 + (8 * wq + (lane >> 2)) * 32, lane);
    const uint32_t sown = __shfl_sync(~0u, sbuf + tile * 8, lane);
    const uint32_t peer = __shfl_sync(~0u, mapa(sb, r ^ 1) - sb, lane);
    const uint32_t meta = __shfl_sync(~0u, 0xEEEE4444u + p.zero, lane);
    cluster_wait();
    TS(56);
    float mean, msq;

#pragma unroll 1
    for (int ph = 0;; ph++) {
        uint4 o0, o1;
        {
            float s = 0.f, q = 0.f, s2 = 0.f, q2 = 0.f;
#pragma unroll
            for (int j = 0; j < 4; j++) {
                s += v[4 * j] + v[4 * j + 1]; s2 += v[4 * j + 2] + v[4 * j + 3];
                q += fmaf(v[4 * j], v[4 * j], v[4 * j + 1] * v[4 * j + 1]); q2 += fmaf(v[4 * j + 2], v[4 * j + 2], v[4 * j + 3] * v[4 * j + 3]);
            }
            s += s2; q += q2;
            const uint32_t xa = bars + (B_XA + ph) * 8;
            s += __shfl_xor_sync(~0u, s, 1); q += __shfl_xor_sync(~0u, q, 1);
            s += __shfl_xor_sync(~0u, s, 2); q += __shfl_xor_sync(~0u, q, 2);
            if (c4 == 0) st_async2f(sown + peer, s, q, xa + peer);
            if (c4 == 0) sts64f(sown, s, q);
#pragma unroll
            for (int j = 0; j < 8; j++) xr[j] = pack2(v[2 * j], v[2 * j + 1]);
            sts128(xown, xr[0], xr[1], xr[2], xr[3]);
            sts128(xown + 2048, xr[4], xr[5], xr[6], xr[7]);
            bar_sync(10, 256);
            o0 = lds128(xown ^ 4096); o1 = lds128((xown ^ 4096) + 2048);
            if (ph < 3) {
                st_async4(xown + peer, xr[0], xr[1], xr[2], xr[3], xa + (B_XB - B_XA) * 8 + peer);
                st_async4(xown + peer + 2048, xr[4], xr[5], xr[6], xr[7], xa + (B_XB - B_XA) * 8 + peer);
            }
            TS(57 + ph);
            if (ph == 0) acq(0);
            mbar_wait(xa, 0);
            const float4 u0 = lds128f(sbuf), u1 = lds128f(sbuf + 16);
            mean = ((u0.x + u0.z) + (u1.x + u1.z)) * (1.f / 256.f);
            msq = ((u0.y + u0.w) + (u1.y + u1.w)) * (1.f / 256.f);
        }
        if (ph == 3) break;
        uint32_t a[32];
        const uint32_t mean2 = pack2(mean, mean);
        auto centre = [&](int i, const uint4& u) {
            a[i] = hsub2(u.x, mean2); a[i + 1] = hsub2(u.y, mean2); a[i + 2] = hsub2(u.z, mean2); a[i + 3] = hsub2(u.w, mean2);
        };
#pragma unroll
        for (int j = 0; j < 8; j++) a[j] = hsub2(xr[j], mean2);
        centre(8, o0); centre(12, o1);
        const float rstd = rsq(fmaxf(fmaf(-mean, mean, msq), 0.f) + 1e-5f);
        auto gather_peer = [&]() {
            mbar_wait(bars + (B_XB + ph) * 8, 0);
#pragma unroll
            for (int i = 0; i < 4; i++) centre(16 + 4 * i, lds128(xrem + i * 2048));
        };
        auto sp = [&](float (&d)[32], int n, const uint32_t* af, int flip, int acc) {
            const uint32_t lo = rdesc + p.zero * (ph + n + 1) + (n % NSLOT) * (SLOT >> 4);
            const uint64_t b0 = mkdesc(lo + flip * 512), b1 = mkdesc(lo + (flip ^ 1) * 512);
            wg_fence();
            mma_sp(d, af, b0, meta, acc);
            mma_sp(d, af + 4, b0 + 256, meta, 1);
            mma_sp(d, af + 8, b1, meta, 1);
            mma_sp(d, af + 12, b1 + 256, meta, 1);
            wg_commit();
        };
        float d0[32], d1[32];

        if (ph != 1) {
            uint32_t h[32];
            const float rs = 0.5f * rstd;
            const uint32_t inb = bars + (B_INB + ph) * 8, box = H + wt * 16;
            bool ready = true;
            auto step = [&](float (&d)[32], int n, const uint32_t* af, int flip, int acc, auto work) {
                if (!ready) acq(n);
                if (((TURN >> n) & 1) && w == 1) bar_sync(7, 256);
                sp(d, n, af, flip, acc);
                if (n > 0 && ((TURN >> (n - 1)) & 1) && w == 0) bar_arrive(7, 256);
                if (n < 15) ready = mbar_test(fbar + ((n + 1) % NSLOT) * 8, ((n + 1) / NSLOT) & 1);
                wg_wait<1>();
                if (n > 0 && !((EAGER >> (n - 1)) & 1)) rel(n - 1);
                const uint32_t tie = work() & p.zero;
                if ((EAGER >> n) & 1) {
                    if (p.zero < n + ph + 1) wg_wait<0>();
                    if (lane == 0) mbar_arrive(fbar + (B_EMPTY - B_FULL + n % NSLOT) * 8 + tie);
                }
            };
            auto none = []() { return 0u; };
            auto act = [&](float (&d)[32], int i) {
                pin(d);
#pragma unroll
                for (int j = 0; j < 8; j++) {
                    const float u0 = (d[4 * j] + d[4 * j + 2]) * rs, u1 = (d[4 * j + 1] + d[4 * j + 3]) * rs;
                    h[8 * i + j] = pack2(fmaf(u0, tanh_fast(u0), u0), fmaf(u1, tanh_fast(u1), u1));
                }
                return h[8 * i] | h[8 * i + 1] | h[8 * i + 2] | h[8 * i + 3] | h[8 * i + 4] | h[8 * i + 5] | h[8 * i + 6] | h[8 * i + 7];
            };
            auto send = [&](float (&d)[32], int x) {
                pin(d);
                uint32_t pk[8];
#pragma unroll
                for (int j = 0; j < 8; j++) pk[j] = pack2(d[4 * j] + d[4 * j + 2], d[4 * j + 1] + d[4 * j + 3]);
                const uint32_t ow = w ^ (x & 1), dst = box + (ow * 3 + x - 1) * 4096;
                if (x & 2) {
                    st_async4(dst + peer, pk[0], pk[1], pk[2], pk[3], inb + ow * 8 + peer);
                    st_async4(dst + peer + 2048, pk[4], pk[5], pk[6], pk[7], inb + ow * 8 + peer);
                } else {
                    sts128(dst, pk[0], pk[1], pk[2], pk[3]);
                    sts128(dst + 2048, pk[4], pk[5], pk[6], pk[7]);
                }
            };
            TS(1 + ph * 10);
            step(d0, 0, a, w, 0, [&]() { gather_peer(); return 0u; });
            TS(32);
            step(d0, 1, a + 16, 0, 1, none);
            step(d1, 2, a, w, 0, [&]() { return act(d0, 0); });
            step(d1, 3, a + 16, 0, 1, none);
            step(d0, 4, a, w, 0, [&]() { return act(d1, 1); });
            TS(33);
            step(d0, 5, a + 16, 0, 1, none);
            step(d1, 6, a, w, 0, [&]() { return act(d0, 2); });
            step(d1, 7, a + 16, 0, 1, none);
            step(d0, 8, h, 0, 0, [&]() { return act(d1, 3); });
            TS(2 + ph * 10);
            step(d0, 9, h + 16, 0, 1, none);
            step(d1, 10, h, 0, 0, [&]() { send(d0, 3); return 0u; });
            step(d1, 11, h + 16, 0, 1, none);
            step(d0, 12, h, 0, 0, [&]() { send(d1, 2); return 0u; });
            TS(34);
            step(d0, 13, h + 16, 0, 1, none);
            step(d1, 14, h, 0, 0, [&]() { send(d0, 1); return 0u; });
            step(d1, 15, h + 16, 0, 1, none);
            if (ph == 0) acq(16);
            mbar_wait(inb + w * 8, 0);
            bar_sync(10, 256);
#pragma unroll
            for (int i = 0; i < 2; i++) {
                const uint32_t src = box + w * 12288 + i * 2048;
                const uint4 u0 = lds128(src), u1 = lds128(src + 4096), u2 = lds128(src + 8192);
                const uint32_t p0[4] = {u0.x, u0.y, u0.z, u0.w}, p1[4] = {u1.x, u1.y, u1.z, u1.w}, p2[4] = {u2.x, u2.y, u2.z, u2.w};
#pragma unroll
                for (int j = 0; j < 4; j++) {
                    v[8 * i + 2 * j] = fmaf(0.5f, blo(p0[j]) + blo(p1[j]) + blo(p2[j]), blo(xr[4 * i + j]));
                    v[8 * i + 2 * j + 1] = fmaf(0.5f, bhi(p0[j]) + bhi(p1[j]) + bhi(p2[j]), bhi(xr[4 * i + j]));
                }
            }
            wg_wait<0>();
            pin(d1);
            rel(15);
            TS(3 + ph * 10);
#pragma unroll
            for (int j = 0; j < 8; j++) {
                v[2 * j] = fmaf(0.5f, d1[4 * j] + d1[4 * j + 2], v[2 * j]);
                v[2 * j + 1] = fmaf(0.5f, d1[4 * j + 1] + d1[4 * j + 3], v[2 * j + 1]);
            }
            continue;
        }

        {
            TS(11);
            const uint32_t stg = H + warp * 2048;
            unsigned char* g = g_kvq + (size_t)((b * 4 + tile) * 1024 + trow) * 128 + lane * 16;
            auto put = [&](float (&d)[32], int i) {
                pin(d);
                uint32_t pk[8];
#pragma unroll
                for (int j = 0; j < 8; j++) pk[j] = pack2((d[4 * j] + d[4 * j + 2]) * rstd, (d[4 * j + 1] + d[4 * j + 3]) * rstd);
                if (i == 2) {
                    st_data(g + 2097152, pk[0], pk[1], pk[2], pk[3]);
                    st_data(g + 2097152 + 512, pk[4], pk[5], pk[6], pk[7]);
                    return;
                }
                stsm4(stg + i * 1024 + foff, pk[0], pk[1], pk[2], pk[3]);
                stsm4(stg + i * 1024 + (foff ^ 64), pk[4], pk[5], pk[6], pk[7]);
                __syncwarp();
                const uint4 u0 = lds128(stg + i * 1024 + lane * 16), u1 = lds128(stg + i * 1024 + 512 + lane * 16);
                stg128(g + i * 1048576, u0); stg128(g + i * 1048576 + 512, u1);
            };
            sp(d0, 16, a, w, 0);
            acq(17);
            if (ORDER == 0) {
                sp(d1, 17, a, w, 0);
                gather_peer();
                acq(18);
                sp(d0, 18, a + 16, 0, 1);
                wg_wait<1>();
                rel(16); rel(17);
                acq(19);
                sp(d1, 19, a + 16, 0, 1);
                wg_wait<1>();
                rel(18);
                put(d0, 0);
                wg_wait<0>();
                rel(19);
                TS(37);
                put(d1, 1);
            } else {
                gather_peer();
                sp(d0, 17, a + 16, 0, 1);
                mbar_wait(bars + B_RST * 8, 0);
                acq(18);
                sp(d1, 18, a, w, 0);
                wg_wait<1>();
                rel(16); rel(17);
                put(d0, 2);
                acq(19);
                sp(d1, 19, a + 16, 0, 1);
                wg_wait<0>();
                rel(18); rel(19);
                TS(37);
                put(d1, 0);
            }
            bar_arrive(4, 288);
            TS(38);
            acq(20);
            sp(d0, 20, a, w, 0);
            acq(21);
            sp(d0, 21, a + 16, 0, 1);
            acq(22); acq(23);
            rel(22); rel(23);
            mbar_wait(bars + B_RST * 8, 0);
            wg_wait<0>();
            rel(20); rel(21);
            bar_sync(13, 288);
            put(d0, ORDER == 0 ? 2 : 1);
            if (ORDER == 1) bar_arrive(4, 288);
            if (wq == 0 || wq == 3) {
                uint4* hp = &g_halo[((pair * 4 + tile) * 2 + (wq & 1)) * 64 + lane];
                st_data(hp, xr[0], xr[1], xr[2], xr[3]);
                st_data(hp + 32, xr[4], xr[5], xr[6], xr[7]);
            }
            TS(12);
        }

        const uint32_t xo = P + tile * XCH + wq * 1024, xt = P + tile * XCH + toff;
        {
            constexpr float CS = 0.125f * 1.4426950408889634f;
            float sa[32], sb2[32], o[36];
            uint32_t pa[16], pb[16], q[16];
            float n0 = INFINITY, n1 = INFINITY;
            zero(o); zero(pa); zero(pb);
            const uint32_t ones = sb + OFF_MISC + 2048;
            if (tid < 128) sts128(ones + tid * 16, 0x3F803F80u, 0x3F803F80u, 0x3F803F80u, 0x3F803F80u);
            fence_async_smem();
            bar_sync(10, 256);
            stsm4(xo + 1024 + foff, xr[0], xr[1], xr[2], xr[3]);
            stsm4(xo + 1024 + (foff ^ 64), xr[4], xr[5], xr[6], xr[7]);
            const uint32_t vdesc = rdesc + ((((ones - rbase) >> 4) - 1) << 16);
            auto qk_issue = [&](float (&s)[32], uint32_t lo) {
                const uint64_t kd = mkdesc(lo);
                wg_fence();
#pragma unroll
                for (int k = 0; k < 4; k++) mma_qk(s, q[4 * k], q[4 * k + 1], q[4 * k + 2], q[4 * k + 3], kd + 2 * k, k != 0);
                wg_commit();
            };
            auto pv_issue = [&](uint32_t (&pp)[16], uint32_t lo) {
                const uint64_t vd = mkdesc(lo);
                wg_fence();
#pragma unroll
                for (int k = 0; k < 4; k++) mma_pv(o, pp[4 * k], pp[4 * k + 1], pp[4 * k + 2], pp[4 * k + 3], vd - k * (128 * 65535));
                wg_commit();
            };
            auto new_max = [&](float (&s)[32], float& x0, float& x1) {
                x0 = s[0]; x1 = s[2];
#pragma unroll
                for (int j = 0; j < 8; j++) {
                    x0 = fmaxf(x0, fmaxf(s[4 * j], s[4 * j + 1]));
                    x1 = fmaxf(x1, fmaxf(s[4 * j + 2], s[4 * j + 3]));
                }
                x0 = fmaxf(x0, __shfl_xor_sync(~0u, x0, 1)); x1 = fmaxf(x1, __shfl_xor_sync(~0u, x1, 1));
                x0 = fmaxf(x0, __shfl_xor_sync(~0u, x0, 2)); x1 = fmaxf(x1, __shfl_xor_sync(~0u, x1, 2));
                x0 = fminf(n0, fmaf(x0, -CS, -20.f)); x1 = fminf(n1, fmaf(x1, -CS, -20.f));
            };
            auto probs = [&](float (&s)[32], uint32_t (&pp)[16], bool ready, auto wait) {
                uint32_t any = 0;
#pragma unroll
                for (int i = 0; i < 16; i++) {
                    pp[i] = pack2(ex2(fmaf(s[2 * i], CS, (i & 1) ? n1 : n0)), ex2(fmaf(s[2 * i + 1], CS, (i & 1) ? n1 : n0)));
                    any |= pp[i];
                }
                float sc0 = 1.f, sc1 = 1.f;
                const bool slow = __any_sync(~0u, (any & 0x40004000u) || !ready);
                if (slow) {
                    wait();
                    if (__any_sync(~0u, any & 0x40004000u)) {
                        float x0, x1;
                        new_max(s, x0, x1);
                        sc0 = ex2(x0 - n0); sc1 = ex2(x1 - n1);
                        n0 = x0; n1 = x1;
#pragma unroll
                        for (int i = 0; i < 16; i++)
                            pp[i] = pack2(ex2(fmaf(s[2 * i], CS, (i & 1) ? n1 : n0)), ex2(fmaf(s[2 * i + 1], CS, (i & 1) ? n1 : n0)));
                    }
                }
                wg_wait<0>();
                pin(sa); pin(sb2); pin(o); pin(pa); pin(pb);
                if (slow) {
#pragma unroll
                    for (int j = 0; j < 9; j++) { o[4 * j] *= sc0; o[4 * j + 1] *= sc0; o[4 * j + 2] *= sc1; o[4 * j + 3] *= sc1; }
                }
            };
            mbar_wait(bars + B_KSEEN * 8, 0);
            {
                uint4 u[4] = {};
                ld_data(u, g_kvq + 2097152 + (size_t)(abh * 1024 + qt * 64 + wq * 16) * 128 + lane * 16, 512);
#pragma unroll
                for (int k = 0; k < 2; k++) {
                    q[8 * k] = u[k].x; q[8 * k + 1] = u[k + 2].x; q[8 * k + 2] = u[k].y; q[8 * k + 3] = u[k + 2].y;
                    q[8 * k + 4] = u[k].z; q[8 * k + 5] = u[k + 2].z; q[8 * k + 6] = u[k].w; q[8 * k + 7] = u[k + 2].w;
                }
                pin(q);
            }
            TS(40);
            acq(24);
            TS(13);
            qk_issue(sa, rdesc + (24 % NSLOT) * (SLOT >> 4));
            qk_issue(sb2, rdesc + (24 % NSLOT) * (SLOT >> 4) + 512);
            wg_wait<1>();
            pin(sa);
            {
                float x0, x1;
                new_max(sa, x0, x1);
                n0 = x0; n1 = x1;
            }
            bar_arrive(6, 384);
            if (w == 1) bar_sync(7, 256);
            uint32_t vd = vdesc - (SLOT >> 4) * 65535u, kd = rdesc, vb = fbar + 8, kb = fbar;
            uint32_t vlast = vdesc - 4 * (SLOT >> 4) * 65535u;
            uint32_t kprev = fbar + 32, vprev = bars + (B_SINK - (B_EMPTY - B_FULL)) * 8;
#pragma unroll 1
            for (int it = 0; it < 4; it++) {
                pv_issue(pb, vlast);
                probs(sa, pa, mbar_test(vb, it < 2) & mbar_test(kb, it < 3), [&]() { mbar_wait(vb, it < 2); mbar_wait(kb, it < 3); });
                TS(41 + it * 4);
                if (it == 0 && w == 0) bar_arrive(7, 256);
                if (it == 3 && w == 1) {
#pragma unroll
                    for (int i = 20; i < 32; i++) sb2[i] = -INFINITY;
                }
                pin(sb2);
                if (it < 3) qk_issue(sa, kd);
                if (lane == 0) mbar_arrive(kprev + (B_EMPTY - B_FULL) * 8);
                if (lane == 0) mbar_arrive(vprev + (B_EMPTY - B_FULL) * 8);
                pv_issue(pa, vd);
                probs(sb2, pb, true, []() {});
                TS(43 + it * 4);
                if (it < 3) qk_issue(sb2, kd + 512);
                const int dv = it == 0 ? 2 : (it == 1 ? -3 : 1);
                kprev = kb; vprev = vb; vlast = vd - 512 * 65535u;
                vd -= dv * (SLOT >> 4) * 65535u; vb += dv * 8;
                kd += 2 * (SLOT >> 4); kb = it == 2 ? vb : kb + 16;
            }
            pv_issue(pb, vlast);
            const int row = wq * 16 + (lane >> 2);
            const uint32_t ml = sb + OFF_MISC;
            mbar_wait(bars + (B_RST + 1) * 8, 0);
            wg_wait<0>();
            pin(o); pin(pb); pin(sa); pin(sb2);
            rel(31);
            const float l0 = o[32], l1 = o[34];
            if (c4 == 0) { sts64f(ml + w * 512 + row * 8, n0, l0); sts64f(ml + w * 512 + row * 8 + 64, n1, l1); }
            TS(14);
            float mine[16];
#pragma unroll
            for (int j = 0; j < 4; j++) {
                if (w == 0) sts128f(H + j * 2048 + wt * 16, o[16 + 4 * j], o[17 + 4 * j], o[18 + 4 * j], o[19 + 4 * j]);
                else sts128f(H + 8192 + j * 2048 + wt * 16, o[4 * j], o[4 * j + 1], o[4 * j + 2], o[4 * j + 3]);
            }
#pragma unroll
            for (int i = 0; i < 16; i++) mine[i] = w == 0 ? o[i] : o[16 + i];
            bar_sync(10, 256);
            const float2 u0 = lds64f(ml + (w ^ 1) * 512 + row * 8), u1 = lds64f(ml + (w ^ 1) * 512 + row * 8 + 64);
            const float x0 = fminf(n0, u0.x), x1 = fminf(n1, u1.x);
            float a0 = ex2(x0 - n0), b0 = ex2(x0 - u0.x), a1 = ex2(x1 - n1), b1 = ex2(x1 - u1.x);
            const float i0 = __fdividef(1.f, fmaf(a0, l0, b0 * u0.y)), i1 = __fdividef(1.f, fmaf(a1, l1, b1 * u1.y));
            a0 *= i0; b0 *= i0; a1 *= i1; b1 *= i1;
            uint32_t pk[8];
#pragma unroll
            for (int j = 0; j < 4; j++) {
                const float4 v = lds128f(H + (w ^ 1) * 8192 + j * 2048 + wt * 16);
                pk[2 * j] = pack2(fmaf(a0, mine[4 * j], b0 * v.x), fmaf(a0, mine[4 * j + 1], b0 * v.y));
                pk[2 * j + 1] = pack2(fmaf(a1, mine[4 * j + 2], b1 * v.z), fmaf(a1, mine[4 * j + 3], b1 * v.w));
            }
            unsigned char* dst = g_o + (size_t)(abh * PADROWS + 8 + qt * 64 + wq * 16) * 128 + w * 512 + lane * 16;
            st_data(dst, pk[0], pk[2], pk[4], pk[6]);
            st_data(dst + 1024, pk[1], pk[3], pk[5], pk[7]);
            if (tid == 0) asm volatile("red.relaxed.gpu.global.add.u32 [%0], 1;" ::"l"(&g_epoch[blockIdx.x * FS]) : "memory");
            TS(15);
        }

        auto mm = [&](float (&d)[24], int n, uint32_t act, int acc) {
            const uint32_t z = p.zero * (ph + n);
            const uint64_t ad = mkdesc(rdesc + z + (n % NSLOT) * (SLOT >> 4)), bd = mkdesc(desc_lo(act) + z);
            wg_fence();
#pragma unroll
            for (int k = 0; k < 8; k++) mma_t(d, ad + k * 128, bd + (k >> 2) * (XCH >> 4) + (k & 3) * 2, k == 0 ? acc : 1);
            wg_commit();
        };
        uint32_t dwr[15];
        {
#pragma unroll
            for (int i = 0; i < 15; i++) dwr[i] = hmul2(__ldg(reinterpret_cast<const uint32_t*>(p.dw + i * 256 + tile * 64) + lane), 0x3F003F00u);
            float d[24];
            uint32_t xw[12];
            bar_sync(9, 384);
#pragma unroll
            for (int j = 0; j < 3; j++) ldsm4t(xt + j * 2048, xw[4 * j], xw[4 * j + 1], xw[4 * j + 2], xw[4 * j + 3]);
            pin(xw);
            acq(32); acq(33); acq(34); acq(35);
            {
                const uint32_t t0 = clock();
                while (clock() - t0 < ODELAY) {}
                uint4 u[6] = {};
                ld_data(u, g_o + (size_t)((b * 4 + (warp >> 1)) * PADROWS + pt * 32) * 128 + (warp & 1) * 512 + lane * 16, 1024);
                const uint32_t dst = H + (warp >> 1) * XCH + (foff ^ ((warp & 1) * 64));
#pragma unroll
                for (int i = 0; i < 6; i++) stsm4(dst + i * 1024, u[i].x, u[i].y, u[i].z, u[i].w);
            }
            fence_async_smem();
            bar_sync(10, 256);
            TS(16);
            mm(d, 32, H, 0);
            mm(d, 33, H + 2 * XCH, 1);
            wg_wait<1>();
            rel(32);
            wg_wait<0>();
            pin(d);
#pragma unroll
            for (int i = 0; i < 12; i++) xw[i] = pack2(d[2 * i] + blo(xw[i]), d[2 * i + 1] + bhi(xw[i]));
            if (c4 == 0) { xw[0] = (xw[0] & 0xffff0000u) | 0x3F80u; xw[1] = (xw[1] & 0xffff0000u) | 0x3F80u; }
#pragma unroll
            for (int j = 0; j < 3; j++) stsm4t(xt + j * 2048, xw[4 * j], xw[4 * j + 1], xw[4 * j + 2], xw[4 * j + 3]);
            rel(33);
            publish(B_X2, P + tile * XCH, XCH, 384);
            TS(17);
        }
        {
            float da[24], db[24], st[24];
            bar_sync(5, 384);
            mm(da, 34, P + 2 * r * XCH, 0);
            mm(db, 35, P + 2 * r * XCH, 0);
            acq(36); acq(37);
            mbar_wait(bars + B_X2 * 8, 0);
            bar_sync(5, 384);
            TS(39);
            mm(da, 36, P + 2 * (r ^ 1) * XCH, 1);
            mm(db, 37, P + 2 * (r ^ 1) * XCH, 1);
            wg_wait<2>();
            rel(34); rel(35);
            mbar_wait(bars + B_ST * 8, 0);
#pragma unroll
            for (int j = 0; j < 6; j++) {
                const float4 u = lds128f(sb + OFF_STATS + (8 * j + 2 * c4) * 8);
                st[4 * j] = u.x; st[4 * j + 1] = u.y; st[4 * j + 2] = u.z; st[4 * j + 3] = u.w;
            }
            wg_wait<0>();
            pin(da); pin(db);
            rel(36); rel(37);
            TS(18);
            uint32_t pk[12];
#pragma unroll
            for (int hh = 0; hh < 2; hh++) {
                const float ca = __shfl_sync(~0u, da[2 * hh], lane & 28), cb = __shfl_sync(~0u, db[2 * hh], lane & 28);
#pragma unroll
                for (int j = 0; j < 6; j++) {
                    const float u0 = fmaf(-st[4 * j], ca, da[4 * j + 2 * hh] * st[4 * j + 1]);
                    const float u1 = fmaf(-st[4 * j + 2], ca, da[4 * j + 2 * hh + 1] * st[4 * j + 3]);
                    const float v0 = fmaf(-st[4 * j], cb, db[4 * j + 2 * hh] * st[4 * j + 1]);
                    const float v1 = fmaf(-st[4 * j + 2], cb, db[4 * j + 2 * hh + 1] * st[4 * j + 3]);
                    pk[2 * j + hh] = pack2(fmaf(u0, tanh_fast(v0), u0), fmaf(u1, tanh_fast(v1), u1));
                }
            }
            const uint32_t gs = H + 16384 + w * XCH;
#pragma unroll
            for (int j = 0; j < 3; j++) stsm4t(gs + toff + j * 2048, pk[4 * j], pk[4 * j + 1], pk[4 * j + 2], pk[4 * j + 3]);
            ldsm4(xo + 1024 + foff, xr[0], xr[1], xr[2], xr[3]);
            ldsm4(xo + 1024 + (foff ^ 64), xr[4], xr[5], xr[6], xr[7]);
            bar_sync(2 + w, 128);
            uint32_t ca[8], cb[8];
            const uint32_t grow = gs + 8 * wq * 128 + c4 * 4, srow = H + tile * HCH + 8 * wq * 128 + c4 * 4;
#pragma unroll
            for (int k = 0; k < 22; k++) {
                const uint32_t v = lds32(grow + (1 + k) * 128 + (((lane >> 2) ^ ((1 + k) & 7)) << 4));
#pragma unroll
                for (int i = 0; i < 8; i++) {
                    const int tap = k - i;
                    if (tap == 0) ca[i] = hmul2(v, dwr[0]);
                    else if (tap > 0 && tap < 8) ca[i] = hfma2(v, dwr[tap], ca[i]);
                    else if (tap == 8) cb[i] = hmul2(v, dwr[8]);
                    else if (tap > 8 && tap < 15) cb[i] = hfma2(v, dwr[tap], cb[i]);
                }
            }
#pragma unroll
            for (int i = 0; i < 8; i++) {
                const float h0 = blo(ca[i]) + blo(cb[i]), h1 = bhi(ca[i]) + bhi(cb[i]);
                sts32(srow + i * 128 + (((lane >> 2) ^ i) << 4), pack2(fmaf(h0, tanh_fast(h0), h0), fmaf(h1, tanh_fast(h1), h1)));
            }
            acq(38); acq(39);
            publish(B_SR, H + tile * HCH, HCH, 256);
            TS(19);
        }
        {
            auto frags = [&](int i, int half) {
                const uint32_t src = H + 2 * half * HCH + wq * 1024;
#pragma unroll
                for (int k = 0; k < 4; k++) ldsm4(src + (k >> 1) * HCH + (foff ^ ((k & 1) * 64)), a[i + 4 * k], a[i + 4 * k + 1], a[i + 4 * k + 2], a[i + 4 * k + 3]);
            };
            frags(0, r);
            sp(d0, 38, a, 0, 0);
            acq(40);
            mbar_wait(bars + B_SR * 8, 0);
            frags(16, r ^ 1);
            sp(d0, 39, a + 16, 0, 1);
            wg_wait<1>();
            rel(38);
            wg_wait<0>();
            pin(d0);
            rel(39);
#pragma unroll
            for (int j = 0; j < 8; j++) {
                v[2 * j] = d0[4 * j] + d0[4 * j + 2] + blo(xr[j]);
                v[2 * j + 1] = d0[4 * j + 1] + d0[4 * j + 3] + bhi(xr[j]);
            }
            TS(20);
        }
    }

    cluster_arrive();
    TS(24);
    {
        const float rstd = rsq(fmaxf(fmaf(-mean, mean, msq), 0.f) + 1e-5f), nb = -mean * rstd;
#pragma unroll
        for (int j = 0; j < 8; j++) xr[j] = pack2(fmaf(v[2 * j], rstd, nb), fmaf(v[2 * j + 1], rstd, nb));
        const uint32_t stg = P + 16384 + warp * 1024;
        stsm4(stg + foff, xr[0], xr[1], xr[2], xr[3]);
        stsm4(stg + (foff ^ 64), xr[4], xr[5], xr[6], xr[7]);
        __syncwarp();
        const uint32_t src = stg + (lane >> 3) * 128 + (((lane & 7) ^ (lane >> 3)) << 4);
        const uint4 u0 = lds128(src), u1 = lds128((src + 512) ^ 64);
        __nv_bfloat16* dst = p.out + (size_t)(b * T_ + trow + (lane >> 3)) * 256 + tile * 64 + (lane & 7) * 8;
        if (trow < T_) { stg128(dst, u0); stg128(dst + 4 * 256, u1); }
    }
    TS(25);
    TG(31);
    TSDUMP();
    cluster_wait();
}

typedef CUresult (*EncodeFn)(CUtensorMap*, CUtensorMapDataType, cuuint32_t, void*, const cuuint64_t*, const cuuint64_t*,
                             const cuuint32_t*, const cuuint32_t*, CUtensorMapInterleave, CUtensorMapSwizzle,
                             CUtensorMapL2promotion, CUtensorMapFloatOOBfill);

}

extern "C" void kernel_launch(void* const* d_in, const int* in_sizes, int n_in, void* d_out, int out_size) {
    static EncodeFn encode = nullptr;
    if (!encode) {
        void* fn = nullptr;
        cudaDriverEntryPointQueryResult qr;
        cudaGetDriverEntryPoint("cuTensorMapEncodeTiled", &fn, cudaEnableDefault, &qr);
        encode = (EncodeFn)fn;
        cudaFuncSetAttribute(conformer_kernel, cudaFuncAttributeMaxDynamicSharedMemorySize, SMEM_LAUNCH);
    }
    Params p;
    const cuuint32_t ones[5] = {1, 1, 1, 1, 1};
    const int idx[8] = {1, 2, 3, 4, 5, 7, 8, 9};
    const int rows[8] = {256, 1024, 256, 256, 256, 256, 256, 1024};
    const int cols[8] = {1024, 256, 768, 256, 512, 256, 1024, 256};
    for (int i = 0; i < 8; i++) {
        const bool perm = i != 3 && i != 4;
        const cuuint64_t pitch = (cuuint64_t)cols[i] * 2;
        const cuuint64_t dims[5] = {(cuuint64_t)cols[i], 2, 2, 4, (cuuint64_t)rows[i] / 16};
        const cuuint64_t strides[4] = {pitch, pitch * (perm ? 8 : 2), pitch * (perm ? 2 : 4), pitch * 16};
        const cuuint32_t box[5] = {64, 2, 2, 4, 8};
        encode(&p.tm[i], CU_TENSOR_MAP_DATA_TYPE_BFLOAT16, 5, d_in[idx[i]], dims, strides, box, ones, CU_TENSOR_MAP_INTERLEAVE_NONE,
               CU_TENSOR_MAP_SWIZZLE_128B, CU_TENSOR_MAP_L2_PROMOTION_L2_128B, CU_TENSOR_MAP_FLOAT_OOB_FILL_NONE);
        p.w[i] = (const char*)d_in[idx[i]];
    }
    {
        void* kv = nullptr;
        cudaGetSymbolAddress(&kv, g_kvq);
        const cuuint64_t dims[2] = {64, 16384};
        const cuuint64_t strides[1] = {128};
        const cuuint32_t box[2] = {64, 128};
        encode(&p.tm[8], CU_TENSOR_MAP_DATA_TYPE_BFLOAT16, 2, kv, dims, strides, box, ones, CU_TENSOR_MAP_INTERLEAVE_NONE,
               CU_TENSOR_MAP_SWIZZLE_NONE, CU_TENSOR_MAP_L2_PROMOTION_L2_128B, CU_TENSOR_MAP_FLOAT_OOB_FILL_NONE);
    }
    p.x = (const __nv_bfloat16*)d_in[0];
    p.dw = (const __nv_bfloat16*)d_in[6];
    p.out = (__nv_bfloat16*)d_out;
    p.zero = 0;
    conformer_kernel<<<NCTA, NTHREADS, SMEM_LAUNCH>>>(p);
}
```

```cpp
#include <cuda_runtime.h>
#include <cuda_bf16.h>
#include <cuda.h>
#include <stdint.h>

namespace {

constexpr int T_ = 1000;
constexpr int NCTA = 128;
constexpr int NTHREADS = 512;
constexpr int NSLOT = 5;
constexpr int SLOT = 16384;
constexpr int NLOADS = 56;

constexpr uint32_t OFF_RING = 0;
constexpr uint32_t OFF_P = 163840;
constexpr uint32_t OFF_H = 188416;
constexpr uint32_t OFF_MISC = 221184;
constexpr uint32_t OFF_STATS = 229376;
constexpr uint32_t OFF_BARS = 229888;
constexpr uint32_t SMEM_BYTES = 230400;
constexpr uint32_t XCH = 6144;
constexpr uint32_t HCH = 4096;

constexpr int B_FULL = 0, B_EMPTY = 10, B_XA = 20  , B_XB = 24  , B_INB = 27  , B_X2 = 31, B_SR = 32,
              B_RST = 33  , B_KSEEN = 35, B_RDY = 36  , B_SINK = 42, B_ST = 43;

#define PACE 1
#define ODELAY 0u
#define ORDER 0
#define QGATE 0u
#define TURN 0
#define EAGER 0x5555
constexpr int PADROWS = 1040;
constexpr int FS = 8;

struct Params {
    CUtensorMap tm[9];
    const char* w[8];
    const __nv_bfloat16* x;
    const __nv_bfloat16* dw;
    __nv_bfloat16* out;
    uint32_t zero;
};

__device__ __align__(1024) unsigned char g_kvq[3 * 8 * 1024 * 128];
__device__ __align__(1024) unsigned char g_o[8 * PADROWS * 128];
__device__ uint4 g_halo[64 * 4 * 2 * 64];
__device__ uint32_t g_flag_kv[2 * 8 * 32 * FS];
__device__ uint32_t g_reset[4 * 32];
__device__ uint32_t g_epoch[NCTA * FS];

#define TS(i) do { } while (0)
#define TSW(i) do { } while (0)
#define TG(i) do { } while (0)
#define TSINIT() do { } while (0)
#define TSDUMP() do { } while (0)
constexpr uint32_t SMEM_LAUNCH = SMEM_BYTES;

__device__ __forceinline__ uint32_t smem_u32(const void* p) { return (uint32_t)__cvta_generic_to_shared(p); }
__device__ __forceinline__ void mbar_init(uint32_t b, uint32_t c) { asm volatile("mbarrier.init.shared::cta.b64 [%0], %1;" ::"r"(b), "r"(c) : "memory"); }
__device__ __forceinline__ void mbar_arrive(uint32_t b) { asm volatile("mbarrier.arrive.shared::cta.b64 _, [%0];" ::"r"(b) : "memory"); }
__device__ __forceinline__ void mbar_arrive_tx(uint32_t b, uint32_t tx) { asm volatile("mbarrier.arrive.expect_tx.shared::cta.b64 _, [%0], %1;" ::"r"(b), "r"(tx) : "memory"); }
__device__ __forceinline__ void mbar_wait(uint32_t b, uint32_t ph) {
    asm volatile("{\n.reg .pred p, q;\n.reg .u32 c;\nmov.u32 c, 0;\n"
                 "MW_LOOP:\n.pragma \"nounroll\";\n"
                 "mbarrier.try_wait.parity.shared::cta.b64 p, [%0], %1;\n"
                 "add.u32 c, c, 1;\nsetp.lt.u32 q, c, 65536;\nnot.pred p, p;\nand.pred p, p, q;\n@p bra MW_LOOP;\n}"
                 ::"r"(b), "r"(ph) : "memory");
}
__device__ __forceinline__ bool mbar_test(uint32_t b, uint32_t ph) {
    uint32_t ok;
    asm volatile("{\n.reg .pred p;\nmbarrier.test_wait.parity.shared::cta.b64 p, [%1], %2;\nselp.u32 %0, 1, 0, p;\n}" : "=r"(ok) : "r"(b), "r"(ph) : "memory");
    return ok;
}
__device__ __forceinline__ uint32_t mapa(uint32_t a, uint32_t r) { uint32_t o; asm("mapa.shared::cluster.u32 %0, %1, %2;" : "=r"(o) : "r"(a), "r"(r)); return o; }
__device__ __forceinline__ void fence_async_smem() { asm volatile("fence.proxy.async.shared::cta;" ::: "memory"); }
__device__ __forceinline__ void fence_async_global() { asm volatile("fence.proxy.async.global;" ::: "memory"); }
__device__ __forceinline__ void bar_sync(int id, int n) { asm volatile("bar.sync %0, %1;" ::"r"(id), "r"(n) : "memory"); }
__device__ __forceinline__ void bar_arrive(int id, int n) { asm volatile("bar.arrive %0, %1;" ::"r"(id), "r"(n) : "memory"); }
__device__ __forceinline__ void cluster_arrive() { asm volatile("barrier.cluster.arrive.relaxed.aligned;" ::: "memory"); }
__device__ __forceinline__ void cluster_wait() { asm volatile("barrier.cluster.wait.aligned;" ::: "memory"); }

__device__ __forceinline__ void ring_load(uint32_t dst, const CUtensorMap* tm, int col, int row16, uint32_t bar) {
    asm volatile("{\n.reg .pred p;\nelect.sync _|p, 0xffffffff;\n"
                 "@p mbarrier.arrive.expect_tx.shared::cta.b64 _, [%2], 16384;\n"
                 "@p cp.async.bulk.tensor.5d.shared::cluster.global.mbarrier::complete_tx::bytes [%0], [%1, {%3, 0, 0, 0, %4}], [%2];\n}"
                 ::"r"(dst), "l"(tm), "r"(bar), "r"(col), "r"(row16) : "memory");
}
__device__ __forceinline__ void ring_load_both(uint32_t dst, const CUtensorMap* tm, int c1, uint32_t bar) {
    asm volatile("{\n.reg .pred p;\nelect.sync _|p, 0xffffffff;\n"
                 "@p cp.async.bulk.tensor.2d.shared::cluster.global.mbarrier::complete_tx::bytes.multicast::cluster [%0], [%1, {0, %3}], [%2], %4;\n}"
                 ::"r"(dst), "l"(tm), "r"(bar), "r"(c1), "h"((uint16_t)3) : "memory");
}
__device__ __forceinline__ void mbar_arrive_peer(uint32_t b) { asm volatile("mbarrier.arrive.relaxed.cluster.shared::cluster.b64 _, [%0];" ::"r"(b) : "memory"); }
__device__ __forceinline__ void prefetch_l2(const void* src, uint32_t bytes) {
    asm volatile("cp.async.bulk.prefetch.L2.global [%0], %1;" ::"l"(src), "r"(bytes) : "memory");
}
__device__ __forceinline__ void peer_copy(uint32_t dst, uint32_t src, uint32_t bytes, uint32_t rbar) {
    asm volatile("{\n.reg .pred p;\nelect.sync _|p, 0xffffffff;\n"
                 "@p cp.async.bulk.shared::cluster.shared::cta.mbarrier::complete_tx::bytes [%0], [%1], %2, [%3];\n}"
                 ::"r"(dst), "r"(src), "r"(bytes), "r"(rbar) : "memory");
}
__device__ __forceinline__ void st_async4(uint32_t dst, uint32_t a, uint32_t b, uint32_t c, uint32_t d, uint32_t bar) {
    asm volatile("st.async.shared::cluster.mbarrier::complete_tx::bytes.v4.b32 [%0], {%1,%2,%3,%4}, [%5];" ::"r"(dst), "r"(a), "r"(b), "r"(c), "r"(d), "r"(bar) : "memory");
}
__device__ __forceinline__ void st_async2f(uint32_t dst, float a, float b, uint32_t bar) {
    asm volatile("st.async.shared::cluster.mbarrier::complete_tx::bytes.v2.f32 [%0], {%1,%2}, [%3];" ::"r"(dst), "f"(a), "f"(b), "r"(bar) : "memory");
}
__device__ __forceinline__ void stsm4t(uint32_t a, uint32_t r0, uint32_t r1, uint32_t r2, uint32_t r3) {
    asm volatile("stmatrix.sync.aligned.m8n8.x4.trans.shared.b16 [%0], {%1,%2,%3,%4};" ::"r"(a), "r"(r0), "r"(r1), "r"(r2), "r"(r3) : "memory");
}
__device__ __forceinline__ void stsm4(uint32_t a, uint32_t r0, uint32_t r1, uint32_t r2, uint32_t r3) {
    asm volatile("stmatrix.sync.aligned.m8n8.x4.shared.b16 [%0], {%1,%2,%3,%4};" ::"r"(a), "r"(r0), "r"(r1), "r"(r2), "r"(r3) : "memory");
}
__device__ __forceinline__ void ldsm4t(uint32_t a, uint32_t& r0, uint32_t& r1, uint32_t& r2, uint32_t& r3) {
    asm volatile("ldmatrix.sync.aligned.m8n8.x4.trans.shared.b16 {%0,%1,%2,%3}, [%4];" : "=r"(r0), "=r"(r1), "=r"(r2), "=r"(r3) : "r"(a) : "memory");
}
__device__ __forceinline__ void ldsm4(uint32_t a, uint32_t& r0, uint32_t& r1, uint32_t& r2, uint32_t& r3) {
    asm volatile("ldmatrix.sync.aligned.m8n8.x4.shared.b16 {%0,%1,%2,%3}, [%4];" : "=r"(r0), "=r"(r1), "=r"(r2), "=r"(r3) : "r"(a) : "memory");
}
__device__ __forceinline__ uint4 lds128(uint32_t a) { uint4 v; asm volatile("ld.shared.v4.b32 {%0,%1,%2,%3}, [%4];" : "=r"(v.x), "=r"(v.y), "=r"(v.z), "=r"(v.w) : "r"(a) : "memory"); return v; }
__device__ __forceinline__ float4 lds128f(uint32_t a) { float4 v; asm volatile("ld.shared.v4.f32 {%0,%1,%2,%3}, [%4];" : "=f"(v.x), "=f"(v.y), "=f"(v.z), "=f"(v.w) : "r"(a) : "memory"); return v; }
__device__ __forceinline__ float2 lds64f(uint32_t a) { float2 v; asm volatile("ld.shared.v2.f32 {%0,%1}, [%2];" : "=f"(v.x), "=f"(v.y) : "r"(a) : "memory"); return v; }
__device__ __forceinline__ uint32_t lds32(uint32_t a) { uint32_t v; asm volatile("ld.shared.b32 %0, [%1];" : "=r"(v) : "r"(a) : "memory"); return v; }
__device__ __forceinline__ void sts128(uint32_t a, uint32_t x, uint32_t y, uint32_t z, uint32_t w) { asm volatile("st.shared.v4.b32 [%0], {%1,%2,%3,%4};" ::"r"(a), "r"(x), "r"(y), "r"(z), "r"(w) : "memory"); }
__device__ __forceinline__ void sts128f(uint32_t a, float x, float y, float z, float w) { asm volatile("st.shared.v4.f32 [%0], {%1,%2,%3,%4};" ::"r"(a), "f"(x), "f"(y), "f"(z), "f"(w) : "memory"); }
__device__ __forceinline__ void sts64f(uint32_t a, float x, float y) { asm volatile("st.shared.v2.f32 [%0], {%1,%2};" ::"r"(a), "f"(x), "f"(y) : "memory"); }
__device__ __forceinline__ void sts32(uint32_t a, uint32_t x) { asm volatile("st.shared.b32 [%0], %1;" ::"r"(a), "r"(x) : "memory"); }
__device__ __forceinline__ void stg128(void* p, uint4 v) { asm volatile("st.global.v4.b32 [%0], {%1,%2,%3,%4};" ::"l"(p), "r"(v.x), "r"(v.y), "r"(v.z), "r"(v.w) : "memory"); }

__device__ __forceinline__ uint32_t pack2(float lo, float hi) { uint32_t r; asm("cvt.rn.bf16x2.f32 %0, %1, %2;" : "=r"(r) : "f"(hi), "f"(lo)); return r; }
__device__ __forceinline__ float blo(uint32_t v) { return __uint_as_float(v << 16); }
__device__ __forceinline__ float bhi(uint32_t v) { return __uint_as_float(v & 0xffff0000u); }
__device__ __forceinline__ uint32_t hmul2(uint32_t a, uint32_t b) { uint32_t r; asm("mul.rn.bf16x2 %0, %1, %2;" : "=r"(r) : "r"(a), "r"(b)); return r; }
__device__ __forceinline__ uint32_t hsub2(uint32_t a, uint32_t b) { uint32_t r; asm("sub.rn.bf16x2 %0, %1, %2;" : "=r"(r) : "r"(a), "r"(b)); return r; }
__device__ __forceinline__ uint32_t hfma2(uint32_t a, uint32_t b, uint32_t c) { uint32_t r; asm("fma.rn.bf16x2 %0, %1, %2, %3;" : "=r"(r) : "r"(a), "r"(b), "r"(c)); return r; }
__device__ __forceinline__ float tanh_fast(float x) { float r; asm("tanh.approx.f32 %0, %1;" : "=f"(r) : "f"(x)); return r; }
__device__ __forceinline__ float rsq(float x) { float r; asm("rsqrt.approx.ftz.f32 %0, %1;" : "=f"(r) : "f"(x)); return r; }
__device__ __forceinline__ float ex2(float x) { float r; asm("ex2.approx.ftz.f32 %0, %1;" : "=f"(r) : "f"(x)); return r; }

__device__ __forceinline__ uint32_t ld_relaxed(const uint32_t* p) {
    uint32_t v;
    asm volatile("ld.relaxed.gpu.global.u32 %0, [%1];" : "=r"(v) : "l"(p) : "memory");
    return v;
}
__device__ __forceinline__ void flag_wait(const uint32_t* p, uint32_t e, uint32_t mask, uint32_t& seen) {
    if ((seen & mask) == mask) return;
    uint32_t a = ld_relaxed(p);
    const uint32_t t0 = clock();
    while (clock() - t0 < 200u) {}
#pragma unroll 1
    for (int i = 0; i < (1 << 19); i++) {
        const uint32_t b = ld_relaxed(p);
        seen = __ballot_sync(~0u, a == e);
        if ((seen & mask) == mask) break;
        a = ld_relaxed(p);
        seen = __ballot_sync(~0u, b == e);
        if ((seen & mask) == mask) break;
    }
    asm volatile("fence.acquire.gpu;" ::: "memory");
    fence_async_global();
}
__device__ __forceinline__ void st_data(void* p, uint32_t x, uint32_t y, uint32_t z, uint32_t w) {
    asm volatile("st.relaxed.gpu.global.v4.b32 [%0], {%1,%2,%3,%4};" ::"l"(p), "r"(x), "r"(y), "r"(z), "r"(w) : "memory");
}
template <int STRIDE, int N>
__device__ __forceinline__ void ld_data(uint4 (&v)[N], const unsigned char* p) {
    int it = 0;
    bool again;
#pragma unroll 1
    do {
        uint32_t m = 0;
#pragma unroll
        for (int i = 0; i < N; i++)
            asm volatile("ld.relaxed.gpu.global.v4.b32 {%0,%1,%2,%3}, [%4];" : "=r"(v[i].x), "=r"(v[i].y), "=r"(v[i].z), "=r"(v[i].w) : "l"(p + i * STRIDE) : "memory");
#pragma unroll
        for (int i = 0; i < N; i++) m = __vimax3_u32(__vimax3_u32(v[i].x, v[i].y, v[i].z), v[i].w, m);
        again = __any_sync(~0u, m == ~0u) && ++it < (1 << 16);
    } while (again);
}
__device__ __forceinline__ uint32_t ld_epoch() { return ld_relaxed(&g_epoch[blockIdx.x * FS]) + 1; }
__device__ __forceinline__ void flag_set(uint32_t* p, uint32_t e) { asm volatile("st.release.gpu.global.u32 [%0], %1;" ::"l"(p), "r"(e) : "memory"); }

__device__ __forceinline__ uint32_t desc_lo(uint32_t addr) { return ((addr & 0x3FFFF) >> 4) | 0x10000u; }
__device__ __forceinline__ uint64_t mkdesc(uint32_t lo) { return (uint64_t)lo | (0x40000040ull << 32); }
__device__ __forceinline__ void wg_fence() { asm volatile("wgmma.fence.sync.aligned;" ::: "memory"); }
__device__ __forceinline__ void wg_commit() { asm volatile("wgmma.commit_group.sync.aligned;" ::: "memory"); }
template <int N> __device__ __forceinline__ void wg_wait() { asm volatile("wgmma.wait_group.sync.aligned %0;" ::"n"(N) : "memory"); }
template <int N> __device__ __forceinline__ void pin(float (&d)[N]) {
#pragma unroll
    for (int i = 0; i < N; i++) asm volatile("" : "+f"(d[i])::"memory");
}
template <int N> __device__ __forceinline__ void pin(uint32_t (&d)[N]) {
#pragma unroll
    for (int i = 0; i < N; i++) asm volatile("" : "+r"(d[i])::"memory");
}

template <typename Tp, int N> __device__ __forceinline__ void zero(Tp (&d)[N]) {
#pragma unroll
    for (int i = 0; i < N; i++) d[i] = 0;
    pin(d);
}

#define F4(d, i) "+f"(d[i]), "+f"(d[i + 1]), "+f"(d[i + 2]), "+f"(d[i + 3])
#define F16(d, i) F4(d, i), F4(d, i + 4), F4(d, i + 8), F4(d, i + 12)

__device__ __forceinline__ void mma_sp(float (&d)[32], const uint32_t* a, uint64_t b, uint32_t meta, int acc) {
    asm volatile("{.reg .pred p; setp.ne.b32 p, %38, 0;\n"
                 "wgmma.mma_async.sp.sync.aligned.m64n64k32.f32.bf16.bf16 {%0,%1,%2,%3,%4,%5,%6,%7,%8,%9,%10,%11,%12,%13,%14,%15,%16,%17,%18,%19,%20,%21,%22,%23,%24,%25,%26,%27,%28,%29,%30,%31}, "
                 "{%32,%33,%34,%35}, %36, %37, 0, p, 1, 1, 1;}\n"
                 : F16(d, 0), F16(d, 16) : "r"(a[0]), "r"(a[1]), "r"(a[2]), "r"(a[3]), "l"(b), "r"(meta), "r"(acc));
}
__device__ __forceinline__ void mma_t(float (&d)[24], uint64_t a, uint64_t b, int acc) {
    asm volatile("{.reg .pred p; setp.ne.b32 p, %26, 0;\n"
                 "wgmma.mma_async.sync.aligned.m64n48k16.f32.bf16.bf16 {%0,%1,%2,%3,%4,%5,%6,%7,%8,%9,%10,%11,%12,%13,%14,%15,%16,%17,%18,%19,%20,%21,%22,%23}, %24, %25, p, 1, 1, 1, 0;}\n"
                 : F16(d, 0), F4(d, 16), F4(d, 20) : "l"(a), "l"(b), "r"(acc));
}
__device__ __forceinline__ void mma_qk(float (&d)[32], uint32_t a0, uint32_t a1, uint32_t a2, uint32_t a3, uint64_t b, int acc) {
    asm volatile("{.reg .pred p; setp.ne.b32 p, %37, 0;\n"
                 "wgmma.mma_async.sync.aligned.m64n64k16.f32.bf16.bf16 {%0,%1,%2,%3,%4,%5,%6,%7,%8,%9,%10,%11,%12,%13,%14,%15,%16,%17,%18,%19,%20,%21,%22,%23,%24,%25,%26,%27,%28,%29,%30,%31}, "
                 "{%32,%33,%34,%35}, %36, p, 1, 1, 0;}\n"
                 : F16(d, 0), F16(d, 16) : "r"(a0), "r"(a1), "r"(a2), "r"(a3), "l"(b), "r"(acc));
}
__device__ __forceinline__ void mma_pv(float (&d)[36], uint32_t a0, uint32_t a1, uint32_t a2, uint32_t a3, uint64_t b) {
    asm volatile("wgmma.mma_async.sync.aligned.m64n72k16.f32.bf16.bf16 {%0,%1,%2,%3,%4,%5,%6,%7,%8,%9,%10,%11,%12,%13,%14,%15,%16,%17,%18,%19,%20,%21,%22,%23,%24,%25,%26,%27,%28,%29,%30,%31,%32,%33,%34,%35}, "
                 "{%36,%37,%38,%39}, %40, 1, 1, 1, 1;\n"
                 : F16(d, 0), F16(d, 16), F4(d, 32) : "r"(a0), "r"(a1), "r"(a2), "r"(a3), "l"(b));
}

__device__ __forceinline__ uint32_t load_code(int n, int r, int w) {
    const int tile = 2 * r + w;
    int m, col, row;
    if (n < 16 || n >= 40) {
        const int k = n < 16 ? n : n - 40;
        m = n < 16 ? 0 : 6;
        if (k < 8) { col = 4 * tile + (k >> 1); row = (k & 1) ^ r; }
        else { m++; col = tile ^ (3 - ((k - 8) >> 1)); row = 2 * tile + (k & 1); }
    } else if (n < 32) {
        const int k = n - 16;
        m = 2;
        if (ORDER == 1) { col = tile + 2 * (k & 6); row = (k & 1) ^ r; }
        else if (k < 4) { col = tile + ((k & 1) ? 8 : 4); row = (k >> 1) ^ r; }
        else { col = tile; row = (k & 1) ^ r; }
    } else if (n < 34) { m = 3; col = tile; row = n - 32; }
    else if (n < 38) { const int k = n - 34; m = 4; col = tile + 4 * (k & 1); row = (k >> 1) ^ r; }
    else { m = 5; col = tile; row = (n & 1) ^ r; }
    return m | (col << 4) | (row << 8);
}

__global__ void __cluster_dims__(2, 1, 1) __launch_bounds__(NTHREADS, 1)
conformer_kernel(const __grid_constant__ Params p) {
    extern __shared__ __align__(1024) unsigned char smem_raw[];
    const uint32_t sb = smem_u32(smem_raw);
    const uint32_t bars = sb + OFF_BARS;
    const int tid = threadIdx.x;
    const int lane = tid & 31;
    const int warp = __shfl_sync(~0u, tid >> 5, 0);
    const int r = blockIdx.x & 1;
    const int pair = blockIdx.x >> 1;
    const int b = pair >> 5, pt = pair & 31;
    const int ah = pt >> 3, qt = (pt & 7) * 2 + r;
    const int abh = b * 4 + ah;

    TG(30);
    TSINIT();
    TS(0);
    const uint32_t P = sb + OFF_P, H = sb + OFF_H;

    if (warp >= 8) {
        asm volatile("setmaxnreg.dec.sync.aligned.u32 48;");
        if (warp >= 12) {
            cluster_arrive();
            cluster_wait();
            const int ut = tid & 127;
            const uint32_t target = ld_epoch() * 64;
            auto reset_done = [&](int k) {
                bar_sync(11, 128);
                if (ut == 0) {
                    asm volatile("red.release.gpu.global.add.u32 [%0], 1;" ::"l"(&g_reset[(2 * b + k) * 32]) : "memory");
#pragma unroll 1
                    for (int i = 0; i < (1 << 20) && ld_relaxed(&g_reset[(2 * b + k) * 32]) != target; i++) __nanosleep(100);
                    asm volatile("fence.acquire.gpu;" ::: "memory");
                    mbar_arrive(bars + (B_RST + k) * 8);
                }
                __syncwarp();
                TS(13 + k);
            };
#pragma unroll
            for (int i = 0; i < 4; i++) {
                st_data(g_kvq + 2097152 + (size_t)((b * 4 + 2 * r + (i >> 1)) * 1024 + pt * 32) * 128 + (i & 1) * 2048 + ut * 16, ~0u, ~0u, ~0u, ~0u);
                if (i < 2) st_data(&g_halo[(pair * 4 + 2 * r + i) * 128 + ut], ~0u, ~0u, ~0u, ~0u);
            }
            reset_done(0);
            bar_sync(6, 384);
#pragma unroll
            for (int i = 0; i < 4; i++) st_data(g_o + (size_t)(abh * PADROWS + 8 + qt * 64) * 128 + i * 2048 + ut * 16, ~0u, ~0u, ~0u, ~0u);
            reset_done(1);
            {
                const int side = warp & 1, t = 2 * r + ((warp >> 1) & 1), np = side ? pt + 1 : pt - 1;
                uint4 hv[2] = {make_uint4(0, 0, 0, 0), make_uint4(0, 0, 0, 0)};
                if (np >= 0 && np < 32)
                    ld_data<512>(hv, reinterpret_cast<const unsigned char*>(&g_halo[(((b * 32 + np) * 4 + t) * 2 + (side ^ 1)) * 64 + lane]));
                const uint32_t dst = P + t * XCH + side * 5120 + (lane & 7) * 128 + (((lane >> 3) ^ (lane & 7)) << 4);
                stsm4(dst, hv[0].x, hv[0].y, hv[0].z, hv[0].w);
                stsm4(dst ^ 64, hv[1].x, hv[1].y, hv[1].z, hv[1].w);
                bar_arrive(9, 384);
            }
            const uint32_t a8 = P + (ut >> 3) * 128 + (ut & 7) * 16;
            float s[3] = {0.f, 0.f, 0.f}, q[3] = {0.f, 0.f, 0.f};
#pragma unroll 1
            for (int h = 0; h < 2; h++) {
                if (h == 0) bar_sync(1, 384);
                else mbar_wait(bars + B_X2 * 8, 0);
                uint4 v[6];
#pragma unroll
                for (int i = 0; i < 6; i++) v[i] = lds128(a8 + (2 * (r ^ h) + (i & 1)) * XCH + (i >> 1) * 2048);
                bar_arrive(5 + ((v[0].w | v[1].w | v[2].w | v[3].w | v[4].w | v[5].w) & p.zero), 384);
                uint32_t t;
                asm volatile("mov.u32 %0, %%clock;" : "=r"(t)::"memory");
                const uint32_t mul = 65536u + (t & p.zero), msk = 0u - mul;
#pragma unroll
                for (int i = 0; i < 6; i++) {
                    const float a0 = __uint_as_float(v[i].x * mul), a1 = __uint_as_float(v[i].x & msk), a2 = __uint_as_float(v[i].y * mul), a3 = __uint_as_float(v[i].y & msk);
                    const float a4 = __uint_as_float(v[i].z * mul), a5 = __uint_as_float(v[i].z & msk), a6 = __uint_as_float(v[i].w * mul), a7 = __uint_as_float(v[i].w & msk);
                    s[i >> 1] += ((a0 + a1) + (a2 + a3)) + ((a4 + a5) + (a6 + a7));
                    q[i >> 1] += fmaf(a0, a0, fmaf(a1, a1, fmaf(a2, a2, a3 * a3))) + fmaf(a4, a4, fmaf(a5, a5, fmaf(a6, a6, a7 * a7)));
                }
            }
#pragma unroll
            for (int o = 1; o < 8; o <<= 1) {
#pragma unroll
                for (int i = 0; i < 3; i++) { s[i] += __shfl_xor_sync(~0u, s[i], o); q[i] += __shfl_xor_sync(~0u, q[i], o); }
            }
            const int k = ut & 7, row = (ut >> 3) + 16 * k;
            const float mean = (k == 0 ? s[0] : (k == 1 ? s[1] : s[2])) * (1.f / 256.f);
            const float msq = (k == 0 ? q[0] : (k == 1 ? q[1] : q[2])) * (1.f / 256.f);
            const float alpha = (uint32_t)(pt * 32 - 8 + row) >= T_ ? 0.f : 0.5f;
            const float rstd = alpha * rsq(fmaxf(fmaf(-mean, mean, msq), 0.f) + 1e-5f);
            if (k < 3) sts64f(sb + OFF_STATS + row * 8, mean * rstd, rstd);
            __syncwarp();
            if (lane == 0) mbar_arrive(bars + B_ST * 8);
            TS(4);
        } else if (warp < 10) {
            const int w = warp - 8;
            const uint32_t ring = sb + OFF_RING + w * NSLOT * SLOT;
            const uint32_t full = bars + (B_FULL + w * NSLOT) * 8;
            if (lane == 0) {
#pragma unroll
                for (int i = 0; i < NSLOT; i++) { mbar_init(full + i * 8, 1); mbar_init(full + (B_EMPTY - B_FULL + i) * 8, 4); }
                asm volatile("fence.mbarrier_init.release.cluster;" ::: "memory");
                fence_async_smem();
            }
            __syncwarp();
            cluster_arrive();
            TS(1);
#pragma unroll
            for (int n = 0; n < NSLOT; n++) {
                if (n == 1 || n == 2) bar_sync(12, 64);
                ring_load(ring + n * SLOT, &p.tm[0], 64 * (8 * r + 4 * w + (n >> 1)), 8 * ((n & 1) ^ r), full + n * 8);
            }
            TS(2);
            const uint32_t code = load_code(lane, r, w) | (load_code(lane + 32, r, w) << 16);
            cluster_wait();
            uint32_t s = 0, ph = 0;
            int n = NSLOT;
#pragma unroll 1
            for (int seg = 0; seg < 2; seg++) {
#pragma unroll 1
                for (; n < (seg == 0 ? 22 : NLOADS); n++) {
                    const uint32_t c = __shfl_sync(~0u, code, n) >> (n & 32 ? 16 : 0);
                    const CUtensorMap* tm = &p.tm[c & 15];
                    const uint32_t col = (c & 0xf0) * 4, row = (c & 0xff00) >> 5, dst = ring + s * SLOT;
                    mbar_wait(full + (B_EMPTY - B_FULL) * 8 + s * 8, ph + (((uint32_t)(size_t)tm | col | row | dst) & p.zero));
                    ring_load(dst, tm, col, row, full + s * 8);
                    if (++s == NSLOT) { s = 0; ph ^= 1; }
                }
                if (seg == 1) break;
                const uint32_t epoch = ld_epoch();
                const uint32_t rdy = bars + (B_RDY + 3 * w) * 8, prdy = mapa(rdy, r ^ 1);
                const int isv = r ^ w;
                const uint32_t* flags = g_flag_kv + (ORDER * isv * 256 + abh * 32 + lane) * FS;
                uint32_t seen = 0;
                auto kv_load = [&](uint32_t sl, int i) {
                    ring_load_both(ring + sl * SLOT, &p.tm[8], (isv * 64 + abh * 8 + 2 * i + w) * 128, full + sl * 8);
                };
#pragma unroll 1
                for (int i = 0; i < 2; i++) {
                    if (lane < 3 + i) {
                        const uint32_t sl = i ? lane : lane + 2;
                        mbar_wait(full + (B_EMPTY - B_FULL + sl) * 8, i ^ 1);
                        mbar_arrive_tx(full + sl * 8, (i || lane == 2) ? SLOT : 0);
                    }
                    __syncwarp();
                }
                if (lane == 0) mbar_arrive_peer(prdy);
                mbar_wait(rdy, 0);
#pragma unroll 1
                for (int j = isv; j < 3; j++) {
                    flag_wait(flags, epoch, 0xfu << (8 * (j - isv) + 4 * w), seen);
                    if (j == isv) TSW(5 + 2 * isv);
                    if (j == 0 && lane == 0) mbar_arrive(bars + B_KSEEN * 8);
                    if (j == 1 && PACE) mbar_wait(full + 32, 0);
                    if (j == 2) mbar_wait(full + isv * 8, 1);
                    kv_load(j ? 2 * j - 2 + isv : 4, j - isv);
                }
                flag_wait(flags, epoch, ~0u, seen);
#pragma unroll 1
                for (int i = 0; i < 3; i++) {
                    const uint32_t sl = i ? i - 1 : 4, bo = i == 2 ? 16 : 8;
                    mbar_wait(full + (B_EMPTY - B_FULL + sl) * 8, i != 0);
                    if (lane == 0) mbar_arrive_tx(full + sl * 8, SLOT);
                    if ((i != 0) == (isv == 1)) {
                        mbar_wait(rdy + bo, 0);
                        kv_load(sl, i == 1 ? 2 : 3);
                    } else if (lane == 0) mbar_arrive_peer(prdy + bo);
                    __syncwarp();
                }
                n = 32; s = 2; ph = 1;
            }
        } else if (warp == 10) {
            if (lane == 0) {
#pragma unroll
                for (int i = B_XA; i <= B_ST; i++) mbar_init(bars + i * 8, i == B_ST ? 4 : 1);
#pragma unroll
                for (int i = B_XA; i <= B_SR; i++) mbar_arrive_tx(bars + i * 8, i < B_XB ? 512 : (i == B_X2 ? 12288 : 8192));
                asm volatile("fence.mbarrier_init.release.cluster;" ::: "memory");
                fence_async_smem();
            }
            __syncwarp();
            cluster_arrive();
            cluster_wait();
        } else {
            const uint32_t kb = (lane < 2 || lane > 5) ? 4096 : (lane == 2 ? 3072 : (lane == 4 ? 2048 : 1024));
            const char* pf = p.w[lane & 7] + blockIdx.x * kb;
            cluster_arrive();
            cluster_wait();
            if (lane < 2) prefetch_l2(pf, kb);
            mbar_wait(bars + B_XA * 8, 0);
            if (lane == 2) prefetch_l2(pf, kb);
            if (lane >= 1 && lane < 9) asm volatile("prefetch.tensormap [%0];" ::"l"(&p.tm[lane]) : "memory");
            mbar_wait(bars + (B_FULL + 1) * 8, 1);
            if (lane > 2 && lane < 8) prefetch_l2(pf, kb);
            if (lane == 8 && blockIdx.x < 15) prefetch_l2(p.dw + blockIdx.x * 256, 512);
            const uint32_t epoch = ld_epoch();
            bar_sync(4, 288);
            if (lane < 2) flag_set(&g_flag_kv[((b * 4 + 2 * r + lane) * 32 + pt) * FS], epoch);
            __syncwarp();
            bar_arrive(13, 288);
            TSW(8);
            if (ORDER == 1) {
                bar_sync(4, 288);
                if (lane < 2) flag_set(&g_flag_kv[(256 + (b * 4 + 2 * r + lane) * 32 + pt) * FS], epoch);
                __syncwarp();
                TSW(9);
            }
        }
        TSDUMP();
        return;
    }

    const int w = warp >> 2, wq = warp & 3;
    const int tile = 2 * r + w;
    const int wt = tid & 127;
    const int c4 = lane & 3;
    const int trow = pt * 32 + 8 * wq;
    uint32_t xr[8];
    {
        const uint32_t* xp = reinterpret_cast<const uint32_t*>(p.x + (size_t)(b * T_ + trow + (lane >> 2)) * 256 + tile * 64) + c4;
#pragma unroll
        for (int j = 0; j < 8; j++) xr[j] = trow < T_ ? __ldg(xp + 4 * j) : 0u;
    }
    cluster_arrive();
    asm volatile("setmaxnreg.inc.sync.aligned.u32 208;");
    const uint32_t rbase = sb + OFF_RING + w * NSLOT * SLOT, fbar = bars + (B_FULL + w * NSLOT) * 8;
    const uint32_t rdesc = desc_lo(rbase);
    auto acq = [&](int n) { mbar_wait(fbar + (n % NSLOT) * 8, (n / NSLOT) & 1); };
    auto rel = [&](int n) { if (lane == 0) mbar_arrive(fbar + (B_EMPTY - B_FULL + n % NSLOT) * 8); };
    const uint32_t foff = (lane & 7) * 128 + (((lane >> 3) ^ (lane & 7)) << 4);
    const uint32_t toff = ((lane >> 4) * 8 + (lane & 7)) * 128 + (((2 * wq + ((lane >> 3) & 1)) ^ (lane & 7)) << 4);
    auto publish = [&](int bar, uint32_t src, uint32_t bytes, int nsync) {
        fence_async_smem();
        bar_sync(2 + w, 128);
        if (wq == 0) peer_copy(mapa(src, r ^ 1), src, bytes, mapa(bars + bar * 8, r ^ 1));
        bar_sync(nsync == 384 ? 1 : 10, nsync);
    };
    float v[16];
#pragma unroll
    for (int j = 0; j < 8; j++) { v[2 * j] = blo(xr[j]); v[2 * j + 1] = bhi(xr[j]); }
    const uint32_t xown = __shfl_sync(~0u, P + wt * 16 + tile * 4096, lane), xrem = __shfl_sync(~0u, P + wt * 16 + (r ^ 1) * 8192, lane);
    const uint32_t sbuf = __shfl_sync(~0u, sb + OFF_MISC + 1024 + (8 * wq + (lane >> 2)) * 32, lane);
    const uint32_t sown = __shfl_sync(~0u, sbuf + tile * 8, lane);
    const uint32_t peer = __shfl_sync(~0u, mapa(sb, r ^ 1) - sb, lane);
    const uint32_t meta = __shfl_sync(~0u, 0xEEEE4444u + p.zero, lane);
    cluster_wait();
    TS(56);
    float mean, msq;

#pragma unroll 1
    for (int ph = 0;; ph++) {
        uint4 o0, o1;
        {
            float s = 0.f, q = 0.f, s2 = 0.f, q2 = 0.f;
#pragma unroll
            for (int j = 0; j < 4; j++) {
                s += v[4 * j] + v[4 * j + 1]; s2 += v[4 * j + 2] + v[4 * j + 3];
                q += fmaf(v[4 * j], v[4 * j], v[4 * j + 1] * v[4 * j + 1]); q2 += fmaf(v[4 * j + 2], v[4 * j + 2], v[4 * j + 3] * v[4 * j + 3]);
            }
            s += s2; q += q2;
            const uint32_t xa = bars + (B_XA + ph) * 8;
            s += __shfl_xor_sync(~0u, s, 1); q += __shfl_xor_sync(~0u, q, 1);
            s += __shfl_xor_sync(~0u, s, 2); q += __shfl_xor_sync(~0u, q, 2);
            if (c4 == 0) st_async2f(sown + peer, s, q, xa + peer);
            if (c4 == 0) sts64f(sown, s, q);
#pragma unroll
            for (int j = 0; j < 8; j++) xr[j] = pack2(v[2 * j], v[2 * j + 1]);
            sts128(xown, xr[0], xr[1], xr[2], xr[3]);
            sts128(xown + 2048, xr[4], xr[5], xr[6], xr[7]);
            bar_sync(10, 256);
            o0 = lds128(xown ^ 4096); o1 = lds128((xown ^ 4096) + 2048);
            if (ph < 3) {
                st_async4(xown + peer, xr[0], xr[1], xr[2], xr[3], xa + (B_XB - B_XA) * 8 + peer);
                st_async4(xown + peer + 2048, xr[4], xr[5], xr[6], xr[7], xa + (B_XB - B_XA) * 8 + peer);
            }
            TS(57 + ph);
            if (ph == 0) acq(0);
            mbar_wait(xa, 0);
            const float4 u0 = lds128f(sbuf), u1 = lds128f(sbuf + 16);
            mean = ((u0.x + u0.z) + (u1.x + u1.z)) * (1.f / 256.f);
            msq = ((u0.y + u0.w) + (u1.y + u1.w)) * (1.f / 256.f);
        }
        if (ph == 3) break;
        uint32_t a[32];
        const uint32_t mean2 = pack2(mean, mean);
        auto centre = [&](int i, const uint4& u) {
            a[i] = hsub2(u.x, mean2); a[i + 1] = hsub2(u.y, mean2); a[i + 2] = hsub2(u.z, mean2); a[i + 3] = hsub2(u.w, mean2);
        };
#pragma unroll
        for (int j = 0; j < 8; j++) a[j] = hsub2(xr[j], mean2);
        centre(8, o0); centre(12, o1);
        const float rstd = rsq(fmaxf(fmaf(-mean, mean, msq), 0.f) + 1e-5f);
        auto gather_peer = [&]() {
            mbar_wait(bars + (B_XB + ph) * 8, 0);
#pragma unroll
            for (int i = 0; i < 4; i++) centre(16 + 4 * i, lds128(xrem + i * 2048));
        };
        auto sp = [&](float (&d)[32], int n, const uint32_t* af, int flip, int acc) {
            const uint32_t lo = rdesc + p.zero * (ph + n + 1) + (n % NSLOT) * (SLOT >> 4);
            const uint64_t b0 = mkdesc(lo + flip * 512), b1 = mkdesc(lo + (flip ^ 1) * 512);
            wg_fence();
            mma_sp(d, af, b0, meta, acc);
            mma_sp(d, af + 4, b0 + 256, meta, 1);
            mma_sp(d, af + 8, b1, meta, 1);
            mma_sp(d, af + 12, b1 + 256, meta, 1);
            wg_commit();
        };
        float d0[32], d1[32];

        if (ph != 1) {
            uint32_t h[32];
            const float rs = 0.5f * rstd;
            const uint32_t inb = bars + (B_INB + ph) * 8, box = H + wt * 16;
            bool ready = true;
            auto step = [&](float (&d)[32], int n, const uint32_t* af, int flip, int acc, auto work) {
                if (!ready) acq(n);
                if (((TURN >> n) & 1) && w == 1) bar_sync(7, 256);
                sp(d, n, af, flip, acc);
                if (n > 0 && ((TURN >> (n - 1)) & 1) && w == 0) bar_arrive(7, 256);
                if (n < 15) ready = mbar_test(fbar + ((n + 1) % NSLOT) * 8, ((n + 1) / NSLOT) & 1);
                wg_wait<1>();
                if (n > 0 && !((EAGER >> (n - 1)) & 1)) rel(n - 1);
                const uint32_t tie = work() & p.zero;
                if ((EAGER >> n) & 1) {
                    if (p.zero < n + ph + 1) wg_wait<0>();
                    if (lane == 0) mbar_arrive(fbar + (B_EMPTY - B_FULL + n % NSLOT) * 8 + tie);
                }
            };
            auto none = []() { return 0u; };
            auto act = [&](float (&d)[32], int i) {
                pin(d);
#pragma unroll
                for (int j = 0; j < 8; j++) {
                    const float u0 = (d[4 * j] + d[4 * j + 2]) * rs, u1 = (d[4 * j + 1] + d[4 * j + 3]) * rs;
                    h[8 * i + j] = pack2(fmaf(u0, tanh_fast(u0), u0), fmaf(u1, tanh_fast(u1), u1));
                }
                return h[8 * i] | h[8 * i + 1] | h[8 * i + 2] | h[8 * i + 3] | h[8 * i + 4] | h[8 * i + 5] | h[8 * i + 6] | h[8 * i + 7];
            };
            auto send = [&](float (&d)[32], int x) {
                pin(d);
                uint32_t pk[8];
#pragma unroll
                for (int j = 0; j < 8; j++) pk[j] = pack2(d[4 * j] + d[4 * j + 2], d[4 * j + 1] + d[4 * j + 3]);
                const uint32_t ow = w ^ (x & 1), dst = box + (ow * 3 + x - 1) * 4096;
                if (x & 2) {
                    st_async4(dst + peer, pk[0], pk[1], pk[2], pk[3], inb + ow * 8 + peer);
                    st_async4(dst + peer + 2048, pk[4], pk[5], pk[6], pk[7], inb + ow * 8 + peer);
                } else {
                    sts128(dst, pk[0], pk[1], pk[2], pk[3]);
                    sts128(dst + 2048, pk[4], pk[5], pk[6], pk[7]);
                }
            };
            TS(1 + ph * 10);
            step(d0, 0, a, w, 0, [&]() { gather_peer(); return 0u; });
            TS(32);
            step(d0, 1, a + 16, 0, 1, none);
            step(d1, 2, a, w, 0, [&]() { return act(d0, 0); });
            step(d1, 3, a + 16, 0, 1, none);
            step(d0, 4, a, w, 0, [&]() { return act(d1, 1); });
            TS(33);
            step(d0, 5, a + 16, 0, 1, none);
            step(d1, 6, a, w, 0, [&]() { return act(d0, 2); });
            step(d1, 7, a + 16, 0, 1, none);
            step(d0, 8, h, 0, 0, [&]() { return act(d1, 3); });
            TS(2 + ph * 10);
            step(d0, 9, h + 16, 0, 1, none);
            step(d1, 10, h, 0, 0, [&]() { send(d0, 3); return 0u; });
            step(d1, 11, h + 16, 0, 1, none);
            step(d0, 12, h, 0, 0, [&]() { send(d1, 2); return 0u; });
            TS(34);
            step(d0, 13, h + 16, 0, 1, none);
            step(d1, 14, h, 0, 0, [&]() { send(d0, 1); return 0u; });
            step(d1, 15, h + 16, 0, 1, none);
            if (ph == 0) acq(16);
            mbar_wait(inb + w * 8, 0);
            bar_sync(10, 256);
#pragma unroll
            for (int i = 0; i < 2; i++) {
                const uint32_t src = box + w * 12288 + i * 2048;
                const uint4 u0 = lds128(src), u1 = lds128(src + 4096), u2 = lds128(src + 8192);
                const uint32_t p0[4] = {u0.x, u0.y, u0.z, u0.w}, p1[4] = {u1.x, u1.y, u1.z, u1.w}, p2[4] = {u2.x, u2.y, u2.z, u2.w};
#pragma unroll
                for (int j = 0; j < 4; j++) {
                    v[8 * i + 2 * j] = fmaf(0.5f, blo(p0[j]) + blo(p1[j]) + blo(p2[j]), blo(xr[4 * i + j]));
                    v[8 * i + 2 * j + 1] = fmaf(0.5f, bhi(p0[j]) + bhi(p1[j]) + bhi(p2[j]), bhi(xr[4 * i + j]));
                }
            }
            wg_wait<0>();
            pin(d1);
            rel(15);
            TS(3 + ph * 10);
#pragma unroll
            for (int j = 0; j < 8; j++) {
                v[2 * j] = fmaf(0.5f, d1[4 * j] + d1[4 * j + 2], v[2 * j]);
                v[2 * j + 1] = fmaf(0.5f, d1[4 * j + 1] + d1[4 * j + 3], v[2 * j + 1]);
            }
            continue;
        }

        {
            TS(11);
            const uint32_t stg = H + warp * 2048;
            unsigned char* g = g_kvq + (size_t)((b * 4 + tile) * 1024 + trow) * 128 + lane * 16;
            auto put = [&](float (&d)[32], int i) {
                pin(d);
                uint32_t pk[8];
#pragma unroll
                for (int j = 0; j < 8; j++) pk[j] = pack2((d[4 * j] + d[4 * j + 2]) * rstd, (d[4 * j + 1] + d[4 * j + 3]) * rstd);
                if (i == 2) {
                    st_data(g + 2097152, pk[0], pk[1], pk[2], pk[3]);
                    st_data(g + 2097152 + 512, pk[4], pk[5], pk[6], pk[7]);
                    return;
                }
                stsm4(stg + i * 1024 + foff, pk[0], pk[1], pk[2], pk[3]);
                stsm4(stg + i * 1024 + (foff ^ 64), pk[4], pk[5], pk[6], pk[7]);
                __syncwarp();
                const uint4 u0 = lds128(stg + i * 1024 + lane * 16), u1 = lds128(stg + i * 1024 + 512 + lane * 16);
                stg128(g + i * 1048576, u0); stg128(g + i * 1048576 + 512, u1);
            };
            sp(d0, 16, a, w, 0);
            acq(17);
            if (ORDER == 0) {
                sp(d1, 17, a, w, 0);
                gather_peer();
                acq(18);
                sp(d0, 18, a + 16, 0, 1);
                wg_wait<1>();
                rel(16); rel(17);
                acq(19);
                sp(d1, 19, a + 16, 0, 1);
                wg_wait<1>();
                rel(18);
                put(d0, 0);
                wg_wait<0>();
                rel(19);
                TS(37);
                put(d1, 1);
            } else {
                gather_peer();
                sp(d0, 17, a + 16, 0, 1);
                mbar_wait(bars + B_RST * 8, 0);
                acq(18);
                sp(d1, 18, a, w, 0);
                wg_wait<1>();
                rel(16); rel(17);
                put(d0, 2);
                acq(19);
                sp(d1, 19, a + 16, 0, 1);
                wg_wait<0>();
                rel(18); rel(19);
                TS(37);
                put(d1, 0);
            }
            bar_arrive(4, 288);
            TS(38);
            acq(20);
            sp(d0, 20, a, w, 0);
            acq(21);
            sp(d0, 21, a + 16, 0, 1);
            acq(22); acq(23);
            rel(22); rel(23);
            mbar_wait(bars + B_RST * 8, 0);
            wg_wait<0>();
            rel(20); rel(21);
            bar_sync(13, 288);
            put(d0, ORDER == 0 ? 2 : 1);
            if (ORDER == 1) bar_arrive(4, 288);
            if (wq == 0 || wq == 3) {
                uint4* hp = &g_halo[((pair * 4 + tile) * 2 + (wq & 1)) * 64 + lane];
                st_data(hp, xr[0], xr[1], xr[2], xr[3]);
                st_data(hp + 32, xr[4], xr[5], xr[6], xr[7]);
            }
            TS(12);
        }

        const uint32_t xo = P + tile * XCH + wq * 1024, xt = P + tile * XCH + toff;
        {
            constexpr float CS = 0.125f * 1.4426950408889634f;
            float sa[32], sb2[32], o[36];
            uint32_t pa[16], pb[16], q[16];
            float n0 = INFINITY, n1 = INFINITY;
            zero(o); zero(pa); zero(pb);
            const uint32_t ones = sb + OFF_MISC + 2048;
            if (tid < 128) sts128(ones + tid * 16, 0x3F803F80u, 0x3F803F80u, 0x3F803F80u, 0x3F803F80u);
            fence_async_smem();
            bar_sync(10, 256);
            stsm4(xo + 1024 + foff, xr[0], xr[1], xr[2], xr[3]);
            stsm4(xo + 1024 + (foff ^ 64), xr[4], xr[5], xr[6], xr[7]);
            const uint32_t vdesc = rdesc + ((((ones - rbase) >> 4) - 1) << 16);
            auto qk_issue = [&](float (&s)[32], uint32_t lo) {
                const uint64_t kd = mkdesc(lo);
                wg_fence();
#pragma unroll
                for (int k = 0; k < 4; k++) mma_qk(s, q[4 * k], q[4 * k + 1], q[4 * k + 2], q[4 * k + 3], kd + 2 * k, k != 0);
                wg_commit();
            };
            auto pv_issue = [&](uint32_t (&pp)[16], uint32_t lo) {
                const uint64_t vd = mkdesc(lo);
                wg_fence();
#pragma unroll
                for (int k = 0; k < 4; k++) mma_pv(o, pp[4 * k], pp[4 * k + 1], pp[4 * k + 2], pp[4 * k + 3], vd - k * (128 * 65535));
                wg_commit();
            };
            auto new_max = [&](float (&s)[32], float& x0, float& x1) {
                x0 = s[0]; x1 = s[2];
#pragma unroll
                for (int j = 0; j < 8; j++) {
                    x0 = fmaxf(x0, fmaxf(s[4 * j], s[4 * j + 1]));
                    x1 = fmaxf(x1, fmaxf(s[4 * j + 2], s[4 * j + 3]));
                }
                x0 = fmaxf(x0, __shfl_xor_sync(~0u, x0, 1)); x1 = fmaxf(x1, __shfl_xor_sync(~0u, x1, 1));
                x0 = fmaxf(x0, __shfl_xor_sync(~0u, x0, 2)); x1 = fmaxf(x1, __shfl_xor_sync(~0u, x1, 2));
                x0 = fminf(n0, fmaf(x0, -CS, -20.f)); x1 = fminf(n1, fmaf(x1, -CS, -20.f));
            };
            auto probs = [&](float (&s)[32], uint32_t (&pp)[16], bool ready, auto wait) {
                uint32_t any = 0;
#pragma unroll
                for (int i = 0; i < 16; i++) {
                    pp[i] = pack2(ex2(fmaf(s[2 * i], CS, (i & 1) ? n1 : n0)), ex2(fmaf(s[2 * i + 1], CS, (i & 1) ? n1 : n0)));
                    any |= pp[i];
                }
                float sc0 = 1.f, sc1 = 1.f;
                const bool slow = __any_sync(~0u, (any & 0x40004000u) || !ready);
                if (slow) {
                    wait();
                    if (__any_sync(~0u, any & 0x40004000u)) {
                        float x0, x1;
                        new_max(s, x0, x1);
                        sc0 = ex2(x0 - n0); sc1 = ex2(x1 - n1);
                        n0 = x0; n1 = x1;
#pragma unroll
                        for (int i = 0; i < 16; i++)
                            pp[i] = pack2(ex2(fmaf(s[2 * i], CS, (i & 1) ? n1 : n0)), ex2(fmaf(s[2 * i + 1], CS, (i & 1) ? n1 : n0)));
                    }
                }
                wg_wait<0>();
                pin(sa); pin(sb2); pin(o); pin(pa); pin(pb);
                if (slow) {
#pragma unroll
                    for (int j = 0; j < 9; j++) { o[4 * j] *= sc0; o[4 * j + 1] *= sc0; o[4 * j + 2] *= sc1; o[4 * j + 3] *= sc1; }
                }
            };
            {
                uint4 u[4];
                const unsigned char* src = g_kvq + 2097152 + (size_t)(abh * 1024 + qt * 64 + wq * 16) * 128 + lane * 16;
                if (QGATE == 0) mbar_wait(bars + B_KSEEN * 8, (uint32_t)(size_t)src & p.zero);
                else { const uint32_t t0 = clock(); while (clock() - t0 < QGATE) {} }
                ld_data<512>(u, src);
#pragma unroll
                for (int k = 0; k < 2; k++) {
                    q[8 * k] = u[k].x; q[8 * k + 1] = u[k + 2].x; q[8 * k + 2] = u[k].y; q[8 * k + 3] = u[k + 2].y;
                    q[8 * k + 4] = u[k].z; q[8 * k + 5] = u[k + 2].z; q[8 * k + 6] = u[k].w; q[8 * k + 7] = u[k + 2].w;
                }
                pin(q);
            }
            TS(40);
            acq(24);
            TS(13);
            qk_issue(sa, rdesc + (24 % NSLOT) * (SLOT >> 4));
            qk_issue(sb2, rdesc + (24 % NSLOT) * (SLOT >> 4) + 512);
            wg_wait<1>();
            pin(sa);
            {
                float x0, x1;
                new_max(sa, x0, x1);
                n0 = x0; n1 = x1;
            }
            bar_arrive(6, 384);
            if (w == 1) bar_sync(7, 256);
            uint32_t vd = vdesc - (SLOT >> 4) * 65535u, kd = rdesc, vb = fbar + 8, kb = fbar;
            uint32_t vlast = vdesc - 4 * (SLOT >> 4) * 65535u;
            uint32_t kprev = fbar + 32, vprev = bars + (B_SINK - (B_EMPTY - B_FULL)) * 8;
#pragma unroll 1
            for (int it = 0; it < 4; it++) {
                pv_issue(pb, vlast);
                probs(sa, pa, mbar_test(vb, it < 2) & mbar_test(kb, it < 3), [&]() { mbar_wait(vb, it < 2); mbar_wait(kb, it < 3); });
                TS(41 + it * 4);
                if (it == 0 && w == 0) bar_arrive(7, 256);
                if (it == 3 && w == 1) {
#pragma unroll
                    for (int i = 20; i < 32; i++) sb2[i] = -INFINITY;
                }
                pin(sb2);
                if (it < 3) qk_issue(sa, kd);
                if (lane == 0) mbar_arrive(kprev + (B_EMPTY - B_FULL) * 8);
                if (lane == 0) mbar_arrive(vprev + (B_EMPTY - B_FULL) * 8);
                pv_issue(pa, vd);
                probs(sb2, pb, true, []() {});
                TS(43 + it * 4);
                if (it < 3) qk_issue(sb2, kd + 512);
                const int dv = it == 0 ? 2 : (it == 1 ? -3 : 1);
                kprev = kb; vprev = vb; vlast = vd - 512 * 65535u;
                vd -= dv * (SLOT >> 4) * 65535u; vb += dv * 8;
                kd += 2 * (SLOT >> 4); kb = it == 2 ? vb : kb + 16;
            }
            pv_issue(pb, vlast);
            const int row = wq * 16 + (lane >> 2);
            const uint32_t ml = sb + OFF_MISC;
            mbar_wait(bars + (B_RST + 1) * 8, 0);
            wg_wait<0>();
            pin(o); pin(pb); pin(sa); pin(sb2);
            rel(31);
            const float l0 = o[32], l1 = o[34];
            if (c4 == 0) { sts64f(ml + w * 512 + row * 8, n0, l0); sts64f(ml + w * 512 + row * 8 + 64, n1, l1); }
            TS(14);
            float mine[16];
#pragma unroll
            for (int j = 0; j < 4; j++) {
                if (w == 0) sts128f(H + j * 2048 + wt * 16, o[16 + 4 * j], o[17 + 4 * j], o[18 + 4 * j], o[19 + 4 * j]);
                else sts128f(H + 8192 + j * 2048 + wt * 16, o[4 * j], o[4 * j + 1], o[4 * j + 2], o[4 * j + 3]);
            }
#pragma unroll
            for (int i = 0; i < 16; i++) mine[i] = w == 0 ? o[i] : o[16 + i];
            bar_sync(10, 256);
            const float2 u0 = lds64f(ml + (w ^ 1) * 512 + row * 8), u1 = lds64f(ml + (w ^ 1) * 512 + row * 8 + 64);
            const float x0 = fminf(n0, u0.x), x1 = fminf(n1, u1.x);
            float a0 = ex2(x0 - n0), b0 = ex2(x0 - u0.x), a1 = ex2(x1 - n1), b1 = ex2(x1 - u1.x);
            const float i0 = __fdividef(1.f, fmaf(a0, l0, b0 * u0.y)), i1 = __fdividef(1.f, fmaf(a1, l1, b1 * u1.y));
            a0 *= i0; b0 *= i0; a1 *= i1; b1 *= i1;
            uint32_t pk[8];
#pragma unroll
            for (int j = 0; j < 4; j++) {
                const float4 v = lds128f(H + (w ^ 1) * 8192 + j * 2048 + wt * 16);
                pk[2 * j] = pack2(fmaf(a0, mine[4 * j], b0 * v.x), fmaf(a0, mine[4 * j + 1], b0 * v.y));
                pk[2 * j + 1] = pack2(fmaf(a1, mine[4 * j + 2], b1 * v.z), fmaf(a1, mine[4 * j + 3], b1 * v.w));
            }
            unsigned char* dst = g_o + (size_t)(abh * PADROWS + 8 + qt * 64 + wq * 16) * 128 + w * 512 + lane * 16;
            st_data(dst, pk[0], pk[2], pk[4], pk[6]);
            st_data(dst + 1024, pk[1], pk[3], pk[5], pk[7]);
            if (tid == 0) asm volatile("red.relaxed.gpu.global.add.u32 [%0], 1;" ::"l"(&g_epoch[blockIdx.x * FS]) : "memory");
            TS(15);
        }

        auto mm = [&](float (&d)[24], int n, uint32_t act, int acc) {
            const uint32_t z = p.zero * (ph + n);
            const uint64_t ad = mkdesc(rdesc + z + (n % NSLOT) * (SLOT >> 4)), bd = mkdesc(desc_lo(act) + z);
            wg_fence();
#pragma unroll
            for (int k = 0; k < 8; k++) mma_t(d, ad + k * 128, bd + (k >> 2) * (XCH >> 4) + (k & 3) * 2, k == 0 ? acc : 1);
            wg_commit();
        };
        uint32_t dwr[15];
        {
#pragma unroll
            for (int i = 0; i < 15; i++) dwr[i] = hmul2(__ldg(reinterpret_cast<const uint32_t*>(p.dw + i * 256 + tile * 64) + lane), 0x3F003F00u);
            float d[24];
            uint32_t xw[12];
            bar_sync(9, 384);
#pragma unroll
            for (int j = 0; j < 3; j++) ldsm4t(xt + j * 2048, xw[4 * j], xw[4 * j + 1], xw[4 * j + 2], xw[4 * j + 3]);
            pin(xw);
            acq(32); acq(33); acq(34); acq(35);
            {
                const uint32_t t0 = clock();
                while (clock() - t0 < ODELAY) {}
                uint4 u[6];
                ld_data<1024>(u, g_o + (size_t)((b * 4 + (warp >> 1)) * PADROWS + pt * 32) * 128 + (warp & 1) * 512 + lane * 16);
                const uint32_t dst = H + (warp >> 1) * XCH + (foff ^ ((warp & 1) * 64));
#pragma unroll
                for (int i = 0; i < 6; i++) stsm4(dst + i * 1024, u[i].x, u[i].y, u[i].z, u[i].w);
            }
            fence_async_smem();
            bar_sync(10, 256);
            TS(16);
            mm(d, 32, H, 0);
            mm(d, 33, H + 2 * XCH, 1);
            wg_wait<1>();
            rel(32);
            wg_wait<0>();
            pin(d);
#pragma unroll
            for (int i = 0; i < 12; i++) xw[i] = pack2(d[2 * i] + blo(xw[i]), d[2 * i + 1] + bhi(xw[i]));
            if (c4 == 0) { xw[0] = (xw[0] & 0xffff0000u) | 0x3F80u; xw[1] = (xw[1] & 0xffff0000u) | 0x3F80u; }
#pragma unroll
            for (int j = 0; j < 3; j++) stsm4t(xt + j * 2048, xw[4 * j], xw[4 * j + 1], xw[4 * j + 2], xw[4 * j + 3]);
            rel(33);
            publish(B_X2, P + tile * XCH, XCH, 384);
            TS(17);
        }
        {
            float da[24], db[24], st[24];
            bar_sync(5, 384);
            mm(da, 34, P + 2 * r * XCH, 0);
            mm(db, 35, P + 2 * r * XCH, 0);
            acq(36); acq(37);
            mbar_wait(bars + B_X2 * 8, 0);
            bar_sync(5, 384);
            TS(39);
            mm(da, 36, P + 2 * (r ^ 1) * XCH, 1);
            mm(db, 37, P + 2 * (r ^ 1) * XCH, 1);
            wg_wait<2>();
            rel(34); rel(35);
            mbar_wait(bars + B_ST * 8, 0);
#pragma unroll
            for (int j = 0; j < 6; j++) {
                const float4 u = lds128f(sb + OFF_STATS + (8 * j + 2 * c4) * 8);
                st[4 * j] = u.x; st[4 * j + 1] = u.y; st[4 * j + 2] = u.z; st[4 * j + 3] = u.w;
            }
            wg_wait<0>();
            pin(da); pin(db);
            rel(36); rel(37);
            TS(18);
            uint32_t pk[12];
#pragma unroll
            for (int hh = 0; hh < 2; hh++) {
                const float ca = __shfl_sync(~0u, da[2 * hh], lane & 28), cb = __shfl_sync(~0u, db[2 * hh], lane & 28);
#pragma unroll
                for (int j = 0; j < 6; j++) {
                    const float u0 = fmaf(-st[4 * j], ca, da[4 * j + 2 * hh] * st[4 * j + 1]);
                    const float u1 = fmaf(-st[4 * j + 2], ca, da[4 * j + 2 * hh + 1] * st[4 * j + 3]);
                    const float v0 = fmaf(-st[4 * j], cb, db[4 * j + 2 * hh] * st[4 * j + 1]);
                    const float v1 = fmaf(-st[4 * j + 2], cb, db[4 * j + 2 * hh + 1] * st[4 * j + 3]);
                    pk[2 * j + hh] = pack2(fmaf(u0, tanh_fast(v0), u0), fmaf(u1, tanh_fast(v1), u1));
                }
            }
            const uint32_t gs = H + 16384 + w * XCH;
#pragma unroll
            for (int j = 0; j < 3; j++) stsm4t(gs + toff + j * 2048, pk[4 * j], pk[4 * j + 1], pk[4 * j + 2], pk[4 * j + 3]);
            ldsm4(xo + 1024 + foff, xr[0], xr[1], xr[2], xr[3]);
            ldsm4(xo + 1024 + (foff ^ 64), xr[4], xr[5], xr[6], xr[7]);
            bar_sync(2 + w, 128);
            uint32_t ca[8], cb[8];
            const uint32_t grow = gs + 8 * wq * 128 + c4 * 4, srow = H + tile * HCH + 8 * wq * 128 + c4 * 4;
#pragma unroll
            for (int k = 0; k < 22; k++) {
                const uint32_t v = lds32(grow + (1 + k) * 128 + (((lane >> 2) ^ ((1 + k) & 7)) << 4));
#pragma unroll
                for (int i = 0; i < 8; i++) {
                    const int tap = k - i;
                    if (tap == 0) ca[i] = hmul2(v, dwr[0]);
                    else if (tap > 0 && tap < 8) ca[i] = hfma2(v, dwr[tap], ca[i]);
                    else if (tap == 8) cb[i] = hmul2(v, dwr[8]);
                    else if (tap > 8 && tap < 15) cb[i] = hfma2(v, dwr[tap], cb[i]);
                }
            }
#pragma unroll
            for (int i = 0; i < 8; i++) {
                const float h0 = blo(ca[i]) + blo(cb[i]), h1 = bhi(ca[i]) + bhi(cb[i]);
                sts32(srow + i * 128 + (((lane >> 2) ^ i) << 4), pack2(fmaf(h0, tanh_fast(h0), h0), fmaf(h1, tanh_fast(h1), h1)));
            }
            acq(38); acq(39);
            publish(B_SR, H + tile * HCH, HCH, 256);
            TS(19);
        }
        {
            auto frags = [&](int i, int half) {
                const uint32_t src = H + 2 * half * HCH + wq * 1024;
#pragma unroll
                for (int k = 0; k < 4; k++) ldsm4(src + (k >> 1) * HCH + (foff ^ ((k & 1) * 64)), a[i + 4 * k], a[i + 4 * k + 1], a[i + 4 * k + 2], a[i + 4 * k + 3]);
            };
            frags(0, r);
            sp(d0, 38, a, 0, 0);
            acq(40);
            mbar_wait(bars + B_SR * 8, 0);
            frags(16, r ^ 1);
            sp(d0, 39, a + 16, 0, 1);
            wg_wait<1>();
            rel(38);
            wg_wait<0>();
            pin(d0);
            rel(39);
#pragma unroll
            for (int j = 0; j < 8; j++) {
                v[2 * j] = d0[4 * j] + d0[4 * j + 2] + blo(xr[j]);
                v[2 * j + 1] = d0[4 * j + 1] + d0[4 * j + 3] + bhi(xr[j]);
            }
            TS(20);
        }
    }

    cluster_arrive();
    TS(24);
    {
        const float rstd = rsq(fmaxf(fmaf(-mean, mean, msq), 0.f) + 1e-5f), nb = -mean * rstd;
#pragma unroll
        for (int j = 0; j < 8; j++) xr[j] = pack2(fmaf(v[2 * j], rstd, nb), fmaf(v[2 * j + 1], rstd, nb));
        const uint32_t stg = P + 16384 + warp * 1024;
        stsm4(stg + foff, xr[0], xr[1], xr[2], xr[3]);
        stsm4(stg + (foff ^ 64), xr[4], xr[5], xr[6], xr[7]);
        __syncwarp();
        const uint32_t src = stg + (lane >> 3) * 128 + (((lane & 7) ^ (lane >> 3)) << 4);
        const uint4 u0 = lds128(src), u1 = lds128((src + 512) ^ 64);
        __nv_bfloat16* dst = p.out + (size_t)(b * T_ + trow + (lane >> 3)) * 256 + tile * 64 + (lane & 7) * 8;
        if (trow < T_) { stg128(dst, u0); stg128(dst + 4 * 256, u1); }
    }
    TS(25);
    TG(31);
    TSDUMP();
    cluster_wait();
}

typedef CUresult (*EncodeFn)(CUtensorMap*, CUtensorMapDataType, cuuint32_t, void*, const cuuint64_t*, const cuuint64_t*,
                             const cuuint32_t*, const cuuint32_t*, CUtensorMapInterleave, CUtensorMapSwizzle,
                             CUtensorMapL2promotion, CUtensorMapFloatOOBfill);

}

extern "C" void kernel_launch(void* const* d_in, const int* in_sizes, int n_in, void* d_out, int out_size) {
    static EncodeFn encode = nullptr;
    if (!encode) {
        void* fn = nullptr;
        cudaDriverEntryPointQueryResult qr;
        cudaGetDriverEntryPoint("cuTensorMapEncodeTiled", &fn, cudaEnableDefault, &qr);
        encode = (EncodeFn)fn;
        cudaFuncSetAttribute(conformer_kernel, cudaFuncAttributeMaxDynamicSharedMemorySize, SMEM_LAUNCH);
    }
    Params p;
    const cuuint32_t ones[5] = {1, 1, 1, 1, 1};
    const int idx[8] = {1, 2, 3, 4, 5, 7, 8, 9};
    const int rows[8] = {256, 1024, 256, 256, 256, 256, 256, 1024};
    const int cols[8] = {1024, 256, 768, 256, 512, 256, 1024, 256};
    for (int i = 0; i < 8; i++) {
        const bool perm = i != 3 && i != 4;
        const cuuint64_t pitch = (cuuint64_t)cols[i] * 2;
        const cuuint64_t dims[5] = {(cuuint64_t)cols[i], 2, 2, 4, (cuuint64_t)rows[i] / 16};
        const cuuint64_t strides[4] = {pitch, pitch * (perm ? 8 : 2), pitch * (perm ? 2 : 4), pitch * 16};
        const cuuint32_t box[5] = {64, 2, 2, 4, 8};
        encode(&p.tm[i], CU_TENSOR_MAP_DATA_TYPE_BFLOAT16, 5, d_in[idx[i]], dims, strides, box, ones, CU_TENSOR_MAP_INTERLEAVE_NONE,
               CU_TENSOR_MAP_SWIZZLE_128B, CU_TENSOR_MAP_L2_PROMOTION_L2_128B, CU_TENSOR_MAP_FLOAT_OOB_FILL_NONE);
        p.w[i] = (const char*)d_in[idx[i]];
    }
    {
        void* kv = nullptr;
        cudaGetSymbolAddress(&kv, g_kvq);
        const cuuint64_t dims[2] = {64, 16384};
        const cuuint64_t strides[1] = {128};
        const cuuint32_t box[2] = {64, 128};
        encode(&p.tm[8], CU_TENSOR_MAP_DATA_TYPE_BFLOAT16, 2, kv, dims, strides, box, ones, CU_TENSOR_MAP_INTERLEAVE_NONE,
               CU_TENSOR_MAP_SWIZZLE_NONE, CU_TENSOR_MAP_L2_PROMOTION_L2_128B, CU_TENSOR_MAP_FLOAT_OOB_FILL_NONE);
    }
    p.x = (const __nv_bfloat16*)d_in[0];
    p.dw = (const __nv_bfloat16*)d_in[6];
    p.out = (__nv_bfloat16*)d_out;
    p.zero = 0;
    conformer_kernel<<<NCTA, NTHREADS, SMEM_LAUNCH>>>(p);
}
```

```cpp
#include <cuda_runtime.h>
#include <cuda_bf16.h>
#include <cuda.h>
#include <stdint.h>

namespace {

constexpr int T_ = 1000;
constexpr int NCTA = 128;
constexpr int NTHREADS = 512;
constexpr int NSLOT = 5;
constexpr int SLOT = 16384;
constexpr int NLOADS = 56;

constexpr uint32_t OFF_RING = 0;
constexpr uint32_t OFF_P = 163840;
constexpr uint32_t OFF_H = 188416;
constexpr uint32_t OFF_MISC = 221184;
constexpr uint32_t OFF_STATS = 229376;
constexpr uint32_t OFF_BARS = 229888;
constexpr uint32_t SMEM_BYTES = 230400;
constexpr uint32_t XCH = 6144;
constexpr uint32_t HCH = 4096;

constexpr int B_FULL = 0, B_EMPTY = 10, B_XA = 20  , B_XB = 24  , B_INB = 27  , B_X2 = 31, B_SR = 32,
              B_RST = 33  , B_RDY = 35  , B_SINK = 41, B_ST = 42;

#define KD2 300u
#define ODELAY 0u
#define QGATE 1000u
#define BACKOFF 0u
#define KFS 8
#define KDELAY 500u
#define TURN 0
#define EAGER 0x5555
constexpr int PADROWS = 1040;
constexpr int FS = 8;

struct Params {
    CUtensorMap tm[9];
    const char* w[8];
    const __nv_bfloat16* x;
    const __nv_bfloat16* dw;
    __nv_bfloat16* out;
    uint32_t zero;
};

__device__ __align__(1024) unsigned char g_kvq[3 * 8 * 1024 * 128];
__device__ __align__(1024) unsigned char g_o[8 * PADROWS * 128];
__device__ uint4 g_halo[64 * 4 * 2 * 64];
__device__ __align__(128) uint32_t g_flag_kv[8 * 32 * KFS];
__device__ uint32_t g_reset[4 * 32];
__device__ uint32_t g_epoch[NCTA * FS];

#define TS(i) do { } while (0)
#define TSW(i) do { } while (0)
#define TG(i) do { } while (0)
#define TSINIT() do { } while (0)
#define TSDUMP() do { } while (0)
constexpr uint32_t SMEM_LAUNCH = SMEM_BYTES;

__device__ __forceinline__ uint32_t smem_u32(const void* p) { return (uint32_t)__cvta_generic_to_shared(p); }
__device__ __forceinline__ void mbar_init(uint32_t b, uint32_t c) { asm volatile("mbarrier.init.shared::cta.b64 [%0], %1;" ::"r"(b), "r"(c) : "memory"); }
__device__ __forceinline__ void mbar_arrive(uint32_t b) { asm volatile("mbarrier.arrive.shared::cta.b64 _, [%0];" ::"r"(b) : "memory"); }
__device__ __forceinline__ void mbar_arrive_tx(uint32_t b, uint32_t tx) { asm volatile("mbarrier.arrive.expect_tx.shared::cta.b64 _, [%0], %1;" ::"r"(b), "r"(tx) : "memory"); }
__device__ __forceinline__ void mbar_wait(uint32_t b, uint32_t ph) {
    asm volatile("{\n.reg .pred p, q;\n.reg .u32 c;\nmov.u32 c, 0;\n"
                 "MW_LOOP:\n.pragma \"nounroll\";\n"
                 "mbarrier.try_wait.parity.shared::cta.b64 p, [%0], %1;\n"
                 "add.u32 c, c, 1;\nsetp.lt.u32 q, c, 65536;\nnot.pred p, p;\nand.pred p, p, q;\n@p bra MW_LOOP;\n}"
                 ::"r"(b), "r"(ph) : "memory");
}
__device__ __forceinline__ bool mbar_test(uint32_t b, uint32_t ph) {
    uint32_t ok;
    asm volatile("{\n.reg .pred p;\nmbarrier.test_wait.parity.shared::cta.b64 p, [%1], %2;\nselp.u32 %0, 1, 0, p;\n}" : "=r"(ok) : "r"(b), "r"(ph) : "memory");
    return ok;
}
__device__ __forceinline__ uint32_t mapa(uint32_t a, uint32_t r) { uint32_t o; asm("mapa.shared::cluster.u32 %0, %1, %2;" : "=r"(o) : "r"(a), "r"(r)); return o; }
__device__ __forceinline__ void fence_async_smem() { asm volatile("fence.proxy.async.shared::cta;" ::: "memory"); }
__device__ __forceinline__ void fence_async_global() { asm volatile("fence.proxy.async.global;" ::: "memory"); }
__device__ __forceinline__ void bar_sync(int id, int n) { asm volatile("bar.sync %0, %1;" ::"r"(id), "r"(n) : "memory"); }
__device__ __forceinline__ void bar_arrive(int id, int n) { asm volatile("bar.arrive %0, %1;" ::"r"(id), "r"(n) : "memory"); }
__device__ __forceinline__ void cluster_arrive() { asm volatile("barrier.cluster.arrive.relaxed.aligned;" ::: "memory"); }
__device__ __forceinline__ void cluster_wait() { asm volatile("barrier.cluster.wait.aligned;" ::: "memory"); }

__device__ __forceinline__ void ring_load(uint32_t dst, const CUtensorMap* tm, int col, int row16, uint32_t bar) {
    asm volatile("{\n.reg .pred p;\nelect.sync _|p, 0xffffffff;\n"
                 "@p mbarrier.arrive.expect_tx.shared::cta.b64 _, [%2], 16384;\n"
                 "@p cp.async.bulk.tensor.5d.shared::cluster.global.mbarrier::complete_tx::bytes [%0], [%1, {%3, 0, 0, 0, %4}], [%2];\n}"
                 ::"r"(dst), "l"(tm), "r"(bar), "r"(col), "r"(row16) : "memory");
}
__device__ __forceinline__ void ring_load_both(uint32_t dst, const CUtensorMap* tm, int c1, uint32_t bar) {
    asm volatile("{\n.reg .pred p;\nelect.sync _|p, 0xffffffff;\n"
                 "@p cp.async.bulk.tensor.2d.shared::cluster.global.mbarrier::complete_tx::bytes.multicast::cluster [%0], [%1, {0, %3}], [%2], %4;\n}"
                 ::"r"(dst), "l"(tm), "r"(bar), "r"(c1), "h"((uint16_t)3) : "memory");
}
__device__ __forceinline__ void mbar_arrive_peer(uint32_t b) { asm volatile("mbarrier.arrive.relaxed.cluster.shared::cluster.b64 _, [%0];" ::"r"(b) : "memory"); }
__device__ __forceinline__ void prefetch_l2(const void* src, uint32_t bytes) {
    asm volatile("cp.async.bulk.prefetch.L2.global [%0], %1;" ::"l"(src), "r"(bytes) : "memory");
}
__device__ __forceinline__ void peer_copy(uint32_t dst, uint32_t src, uint32_t bytes, uint32_t rbar) {
    asm volatile("{\n.reg .pred p;\nelect.sync _|p, 0xffffffff;\n"
                 "@p cp.async.bulk.shared::cluster.shared::cta.mbarrier::complete_tx::bytes [%0], [%1], %2, [%3];\n}"
                 ::"r"(dst), "r"(src), "r"(bytes), "r"(rbar) : "memory");
}
__device__ __forceinline__ void st_async4(uint32_t dst, uint32_t a, uint32_t b, uint32_t c, uint32_t d, uint32_t bar) {
    asm volatile("st.async.shared::cluster.mbarrier::complete_tx::bytes.v4.b32 [%0], {%1,%2,%3,%4}, [%5];" ::"r"(dst), "r"(a), "r"(b), "r"(c), "r"(d), "r"(bar) : "memory");
}
__device__ __forceinline__ void st_async2f(uint32_t dst, float a, float b, uint32_t bar) {
    asm volatile("st.async.shared::cluster.mbarrier::complete_tx::bytes.v2.f32 [%0], {%1,%2}, [%3];" ::"r"(dst), "f"(a), "f"(b), "r"(bar) : "memory");
}
__device__ __forceinline__ void stsm4t(uint32_t a, uint32_t r0, uint32_t r1, uint32_t r2, uint32_t r3) {
    asm volatile("stmatrix.sync.aligned.m8n8.x4.trans.shared.b16 [%0], {%1,%2,%3,%4};" ::"r"(a), "r"(r0), "r"(r1), "r"(r2), "r"(r3) : "memory");
}
__device__ __forceinline__ void stsm4(uint32_t a, uint32_t r0, uint32_t r1, uint32_t r2, uint32_t r3) {
    asm volatile("stmatrix.sync.aligned.m8n8.x4.shared.b16 [%0], {%1,%2,%3,%4};" ::"r"(a), "r"(r0), "r"(r1), "r"(r2), "r"(r3) : "memory");
}
__device__ __forceinline__ void ldsm4t(uint32_t a, uint32_t& r0, uint32_t& r1, uint32_t& r2, uint32_t& r3) {
    asm volatile("ldmatrix.sync.aligned.m8n8.x4.trans.shared.b16 {%0,%1,%2,%3}, [%4];" : "=r"(r0), "=r"(r1), "=r"(r2), "=r"(r3) : "r"(a) : "memory");
}
__device__ __forceinline__ void ldsm4(uint32_t a, uint32_t& r0, uint32_t& r1, uint32_t& r2, uint32_t& r3) {
    asm volatile("ldmatrix.sync.aligned.m8n8.x4.shared.b16 {%0,%1,%2,%3}, [%4];" : "=r"(r0), "=r"(r1), "=r"(r2), "=r"(r3) : "r"(a) : "memory");
}
__device__ __forceinline__ uint4 lds128(uint32_t a) { uint4 v; asm volatile("ld.shared.v4.b32 {%0,%1,%2,%3}, [%4];" : "=r"(v.x), "=r"(v.y), "=r"(v.z), "=r"(v.w) : "r"(a) : "memory"); return v; }
__device__ __forceinline__ float4 lds128f(uint32_t a) { float4 v; asm volatile("ld.shared.v4.f32 {%0,%1,%2,%3}, [%4];" : "=f"(v.x), "=f"(v.y), "=f"(v.z), "=f"(v.w) : "r"(a) : "memory"); return v; }
__device__ __forceinline__ float2 lds64f(uint32_t a) { float2 v; asm volatile("ld.shared.v2.f32 {%0,%1}, [%2];" : "=f"(v.x), "=f"(v.y) : "r"(a) : "memory"); return v; }
__device__ __forceinline__ uint32_t lds32(uint32_t a) { uint32_t v; asm volatile("ld.shared.b32 %0, [%1];" : "=r"(v) : "r"(a) : "memory"); return v; }
__device__ __forceinline__ void sts128(uint32_t a, uint32_t x, uint32_t y, uint32_t z, uint32_t w) { asm volatile("st.shared.v4.b32 [%0], {%1,%2,%3,%4};" ::"r"(a), "r"(x), "r"(y), "r"(z), "r"(w) : "memory"); }
__device__ __forceinline__ void sts128f(uint32_t a, float x, float y, float z, float w) { asm volatile("st.shared.v4.f32 [%0], {%1,%2,%3,%4};" ::"r"(a), "f"(x), "f"(y), "f"(z), "f"(w) : "memory"); }
__device__ __forceinline__ void sts64f(uint32_t a, float x, float y) { asm volatile("st.shared.v2.f32 [%0], {%1,%2};" ::"r"(a), "f"(x), "f"(y) : "memory"); }
__device__ __forceinline__ void sts32(uint32_t a, uint32_t x) { asm volatile("st.shared.b32 [%0], %1;" ::"r"(a), "r"(x) : "memory"); }
__device__ __forceinline__ void stg128(void* p, uint4 v) { asm volatile("st.global.v4.b32 [%0], {%1,%2,%3,%4};" ::"l"(p), "r"(v.x), "r"(v.y), "r"(v.z), "r"(v.w) : "memory"); }

__device__ __forceinline__ uint32_t pack2(float lo, float hi) { uint32_t r; asm("cvt.rn.bf16x2.f32 %0, %1, %2;" : "=r"(r) : "f"(hi), "f"(lo)); return r; }
__device__ __forceinline__ float blo(uint32_t v) { return __uint_as_float(v << 16); }
__device__ __forceinline__ float bhi(uint32_t v) { return __uint_as_float(v & 0xffff0000u); }
__device__ __forceinline__ uint32_t hmul2(uint32_t a, uint32_t b) { uint32_t r; asm("mul.rn.bf16x2 %0, %1, %2;" : "=r"(r) : "r"(a), "r"(b)); return r; }
__device__ __forceinline__ uint32_t hsub2(uint32_t a, uint32_t b) { uint32_t r; asm("sub.rn.bf16x2 %0, %1, %2;" : "=r"(r) : "r"(a), "r"(b)); return r; }
__device__ __forceinline__ uint32_t hfma2(uint32_t a, uint32_t b, uint32_t c) { uint32_t r; asm("fma.rn.bf16x2 %0, %1, %2, %3;" : "=r"(r) : "r"(a), "r"(b), "r"(c)); return r; }
__device__ __forceinline__ float tanh_fast(float x) { float r; asm("tanh.approx.f32 %0, %1;" : "=f"(r) : "f"(x)); return r; }
__device__ __forceinline__ float rsq(float x) { float r; asm("rsqrt.approx.ftz.f32 %0, %1;" : "=f"(r) : "f"(x)); return r; }
__device__ __forceinline__ float ex2(float x) { float r; asm("ex2.approx.ftz.f32 %0, %1;" : "=f"(r) : "f"(x)); return r; }

__device__ __forceinline__ uint32_t ld_relaxed(const uint32_t* p) {
    uint32_t v;
    asm volatile("ld.relaxed.gpu.global.u32 %0, [%1];" : "=r"(v) : "l"(p) : "memory");
    return v;
}
__device__ __forceinline__ void spin(uint32_t clks) {
    const uint32_t t0 = clock();
    while (clock() - t0 < clks) {}
}
__device__ __forceinline__ void flag_wait(const uint32_t* p, uint32_t e, bool mine) {
#pragma unroll 1
    for (int i = 0; i < (1 << 19); i++) {
        if (mine) mine = ld_relaxed(p) != e;
        if (!__any_sync(~0u, mine)) break;
        if (BACKOFF) spin(BACKOFF);
    }
    asm volatile("fence.acquire.gpu;" ::: "memory");
    fence_async_global();
}
__device__ __forceinline__ void st_data(void* p, uint32_t x, uint32_t y, uint32_t z, uint32_t w) {
    asm volatile("st.relaxed.gpu.global.v4.b32 [%0], {%1,%2,%3,%4};" ::"l"(p), "r"(x), "r"(y), "r"(z), "r"(w) : "memory");
}
template <int STRIDE, int N>
__device__ __forceinline__ void ld_data(uint4 (&v)[N], const unsigned char* p) {
    int it = 0;
    bool again;
#pragma unroll 1
    do {
        uint32_t m = 0;
#pragma unroll
        for (int i = 0; i < N; i++)
            asm volatile("ld.relaxed.gpu.global.v4.b32 {%0,%1,%2,%3}, [%4];" : "=r"(v[i].x), "=r"(v[i].y), "=r"(v[i].z), "=r"(v[i].w) : "l"(p + i * STRIDE) : "memory");
#pragma unroll
        for (int i = 0; i < N; i++) m = __vimax3_u32(__vimax3_u32(v[i].x, v[i].y, v[i].z), v[i].w, m);
        again = __any_sync(~0u, m == ~0u) && ++it < (1 << 16);
    } while (again);
}
__device__ __forceinline__ uint32_t ld_epoch() { return ld_relaxed(&g_epoch[blockIdx.x * FS]) + 1; }
__device__ __forceinline__ void flag_set(uint32_t* p, uint32_t e) { asm volatile("st.release.gpu.global.u32 [%0], %1;" ::"l"(p), "r"(e) : "memory"); }

__device__ __forceinline__ uint32_t desc_lo(uint32_t addr) { return ((addr & 0x3FFFF) >> 4) | 0x10000u; }
__device__ __forceinline__ uint64_t mkdesc(uint32_t lo) { return (uint64_t)lo | (0x40000040ull << 32); }
__device__ __forceinline__ void wg_fence() { asm volatile("wgmma.fence.sync.aligned;" ::: "memory"); }
__device__ __forceinline__ void wg_commit() { asm volatile("wgmma.commit_group.sync.aligned;" ::: "memory"); }
template <int N> __device__ __forceinline__ void wg_wait() { asm volatile("wgmma.wait_group.sync.aligned %0;" ::"n"(N) : "memory"); }
template <int N> __device__ __forceinline__ void pin(float (&d)[N]) {
#pragma unroll
    for (int i = 0; i < N; i++) asm volatile("" : "+f"(d[i])::"memory");
}
template <int N> __device__ __forceinline__ void pin(uint32_t (&d)[N]) {
#pragma unroll
    for (int i = 0; i < N; i++) asm volatile("" : "+r"(d[i])::"memory");
}

template <typename Tp, int N> __device__ __forceinline__ void zero(Tp (&d)[N]) {
#pragma unroll
    for (int i = 0; i < N; i++) d[i] = 0;
    pin(d);
}

#define F4(d, i) "+f"(d[i]), "+f"(d[i + 1]), "+f"(d[i + 2]), "+f"(d[i + 3])
#define F16(d, i) F4(d, i), F4(d, i + 4), F4(d, i + 8), F4(d, i + 12)

__device__ __forceinline__ void mma_sp(float (&d)[32], const uint32_t* a, uint64_t b, uint32_t meta, int acc) {
    asm volatile("{.reg .pred p; setp.ne.b32 p, %38, 0;\n"
                 "wgmma.mma_async.sp.sync.aligned.m64n64k32.f32.bf16.bf16 {%0,%1,%2,%3,%4,%5,%6,%7,%8,%9,%10,%11,%12,%13,%14,%15,%16,%17,%18,%19,%20,%21,%22,%23,%24,%25,%26,%27,%28,%29,%30,%31}, "
                 "{%32,%33,%34,%35}, %36, %37, 0, p, 1, 1, 1;}\n"
                 : F16(d, 0), F16(d, 16) : "r"(a[0]), "r"(a[1]), "r"(a[2]), "r"(a[3]), "l"(b), "r"(meta), "r"(acc));
}
__device__ __forceinline__ void mma_t(float (&d)[24], uint64_t a, uint64_t b, int acc) {
    asm volatile("{.reg .pred p; setp.ne.b32 p, %26, 0;\n"
                 "wgmma.mma_async.sync.aligned.m64n48k16.f32.bf16.bf16 {%0,%1,%2,%3,%4,%5,%6,%7,%8,%9,%10,%11,%12,%13,%14,%15,%16,%17,%18,%19,%20,%21,%22,%23}, %24, %25, p, 1, 1, 1, 0;}\n"
                 : F16(d, 0), F4(d, 16), F4(d, 20) : "l"(a), "l"(b), "r"(acc));
}
__device__ __forceinline__ void mma_qk(float (&d)[32], uint32_t a0, uint32_t a1, uint32_t a2, uint32_t a3, uint64_t b, int acc) {
    asm volatile("{.reg .pred p; setp.ne.b32 p, %37, 0;\n"
                 "wgmma.mma_async.sync.aligned.m64n64k16.f32.bf16.bf16 {%0,%1,%2,%3,%4,%5,%6,%7,%8,%9,%10,%11,%12,%13,%14,%15,%16,%17,%18,%19,%20,%21,%22,%23,%24,%25,%26,%27,%28,%29,%30,%31}, "
                 "{%32,%33,%34,%35}, %36, p, 1, 1, 0;}\n"
                 : F16(d, 0), F16(d, 16) : "r"(a0), "r"(a1), "r"(a2), "r"(a3), "l"(b), "r"(acc));
}
__device__ __forceinline__ void mma_pv(float (&d)[36], uint32_t a0, uint32_t a1, uint32_t a2, uint32_t a3, uint64_t b) {
    asm volatile("wgmma.mma_async.sync.aligned.m64n72k16.f32.bf16.bf16 {%0,%1,%2,%3,%4,%5,%6,%7,%8,%9,%10,%11,%12,%13,%14,%15,%16,%17,%18,%19,%20,%21,%22,%23,%24,%25,%26,%27,%28,%29,%30,%31,%32,%33,%34,%35}, "
                 "{%36,%37,%38,%39}, %40, 1, 1, 1, 1;\n"
                 : F16(d, 0), F16(d, 16), F4(d, 32) : "r"(a0), "r"(a1), "r"(a2), "r"(a3), "l"(b));
}

__device__ __forceinline__ uint32_t load_code(int n, int r, int w) {
    const int tile = 2 * r + w;
    int m, col, row;
    if (n < 16 || n >= 40) {
        const int k = n < 16 ? n : n - 40;
        m = n < 16 ? 0 : 6;
        if (k < 8) { col = 4 * tile + (k >> 1); row = (k & 1) ^ r; }
        else { m++; col = tile ^ (3 - ((k - 8) >> 1)); row = 2 * tile + (k & 1); }
    } else if (n < 32) {
        const int k = n - 16;
        m = 2;
        if (k < 4) { col = tile + ((k & 1) ? 8 : 4); row = (k >> 1) ^ r; }
        else { col = tile; row = (k & 1) ^ r; }
    } else if (n < 34) { m = 3; col = tile; row = n - 32; }
    else if (n < 38) { const int k = n - 34; m = 4; col = tile + 4 * (k & 1); row = (k >> 1) ^ r; }
    else { m = 5; col = tile; row = (n & 1) ^ r; }
    return m | (col << 4) | (row << 8);
}

__global__ void __cluster_dims__(2, 1, 1) __launch_bounds__(NTHREADS, 1)
conformer_kernel(const __grid_constant__ Params p) {
    extern __shared__ __align__(1024) unsigned char smem_raw[];
    const uint32_t sb = smem_u32(smem_raw);
    const uint32_t bars = sb + OFF_BARS;
    const int tid = threadIdx.x;
    const int lane = tid & 31;
    const int warp = __shfl_sync(~0u, tid >> 5, 0);
    const int r = blockIdx.x & 1;
    const int pair = blockIdx.x >> 1;
    const int b = pair >> 5, pt = pair & 31;
    const int ah = pt >> 3, qt = (pt & 7) * 2 + r;
    const int abh = b * 4 + ah;

    TG(30);
    TSINIT();
    TS(0);
    const uint32_t P = sb + OFF_P, H = sb + OFF_H;

    if (warp >= 8) {
        asm volatile("setmaxnreg.dec.sync.aligned.u32 48;");
        if (warp >= 12) {
            cluster_arrive();
            cluster_wait();
            const int ut = tid & 127;
            const uint32_t target = ld_epoch() * 64;
            auto reset_done = [&](int k) {
                bar_sync(11, 128);
                if (ut == 0) {
                    asm volatile("red.release.gpu.global.add.u32 [%0], 1;" ::"l"(&g_reset[(2 * b + k) * 32]) : "memory");
#pragma unroll 1
                    for (int i = 0; i < (1 << 20) && ld_relaxed(&g_reset[(2 * b + k) * 32]) != target; i++) __nanosleep(100);
                    asm volatile("fence.acquire.gpu;" ::: "memory");
                    mbar_arrive(bars + (B_RST + k) * 8);
                }
                __syncwarp();
                TS(13 + k);
            };
#pragma unroll
            for (int i = 0; i < 4; i++) {
                st_data(g_kvq + 2097152 + (size_t)((b * 4 + 2 * r + (i >> 1)) * 1024 + pt * 32) * 128 + (i & 1) * 2048 + ut * 16, ~0u, ~0u, ~0u, ~0u);
                if (i < 2) st_data(&g_halo[(pair * 4 + 2 * r + i) * 128 + ut], ~0u, ~0u, ~0u, ~0u);
            }
            reset_done(0);
            bar_sync(6, 384);
#pragma unroll
            for (int i = 0; i < 4; i++) st_data(g_o + (size_t)(abh * PADROWS + 8 + qt * 64) * 128 + i * 2048 + ut * 16, ~0u, ~0u, ~0u, ~0u);
            reset_done(1);
            {
                const int side = warp & 1, t = 2 * r + ((warp >> 1) & 1), np = side ? pt + 1 : pt - 1;
                uint4 hv[2] = {make_uint4(0, 0, 0, 0), make_uint4(0, 0, 0, 0)};
                if (np >= 0 && np < 32)
                    ld_data<512>(hv, reinterpret_cast<const unsigned char*>(&g_halo[(((b * 32 + np) * 4 + t) * 2 + (side ^ 1)) * 64 + lane]));
                const uint32_t dst = P + t * XCH + side * 5120 + (lane & 7) * 128 + (((lane >> 3) ^ (lane & 7)) << 4);
                stsm4(dst, hv[0].x, hv[0].y, hv[0].z, hv[0].w);
                stsm4(dst ^ 64, hv[1].x, hv[1].y, hv[1].z, hv[1].w);
                bar_arrive(9, 384);
            }
            const uint32_t a8 = P + (ut >> 3) * 128 + (ut & 7) * 16;
            float s[3] = {0.f, 0.f, 0.f}, q[3] = {0.f, 0.f, 0.f};
#pragma unroll 1
            for (int h = 0; h < 2; h++) {
                if (h == 0) bar_sync(1, 384);
                else mbar_wait(bars + B_X2 * 8, 0);
                uint4 v[6];
#pragma unroll
                for (int i = 0; i < 6; i++) v[i] = lds128(a8 + (2 * (r ^ h) + (i & 1)) * XCH + (i >> 1) * 2048);
                bar_arrive(5 + ((v[0].w | v[1].w | v[2].w | v[3].w | v[4].w | v[5].w) & p.zero), 384);
                uint32_t t;
                asm volatile("mov.u32 %0, %%clock;" : "=r"(t)::"memory");
                const uint32_t mul = 65536u + (t & p.zero), msk = 0u - mul;
#pragma unroll
                for (int i = 0; i < 6; i++) {
                    const float a0 = __uint_as_float(v[i].x * mul), a1 = __uint_as_float(v[i].x & msk), a2 = __uint_as_float(v[i].y * mul), a3 = __uint_as_float(v[i].y & msk);
                    const float a4 = __uint_as_float(v[i].z * mul), a5 = __uint_as_float(v[i].z & msk), a6 = __uint_as_float(v[i].w * mul), a7 = __uint_as_float(v[i].w & msk);
                    s[i >> 1] += ((a0 + a1) + (a2 + a3)) + ((a4 + a5) + (a6 + a7));
                    q[i >> 1] += fmaf(a0, a0, fmaf(a1, a1, fmaf(a2, a2, a3 * a3))) + fmaf(a4, a4, fmaf(a5, a5, fmaf(a6, a6, a7 * a7)));
                }
            }
#pragma unroll
            for (int o = 1; o < 8; o <<= 1) {
#pragma unroll
                for (int i = 0; i < 3; i++) { s[i] += __shfl_xor_sync(~0u, s[i], o); q[i] += __shfl_xor_sync(~0u, q[i], o); }
            }
            const int k = ut & 7, row = (ut >> 3) + 16 * k;
            const float mean = (k == 0 ? s[0] : (k == 1 ? s[1] : s[2])) * (1.f / 256.f);
            const float msq = (k == 0 ? q[0] : (k == 1 ? q[1] : q[2])) * (1.f / 256.f);
            const float alpha = (uint32_t)(pt * 32 - 8 + row) >= T_ ? 0.f : 0.5f;
            const float rstd = alpha * rsq(fmaxf(fmaf(-mean, mean, msq), 0.f) + 1e-5f);
            if (k < 3) sts64f(sb + OFF_STATS + row * 8, mean * rstd, rstd);
            __syncwarp();
            if (lane == 0) mbar_arrive(bars + B_ST * 8);
            TS(4);
        } else if (warp < 10) {
            const int w = warp - 8;
            const uint32_t ring = sb + OFF_RING + w * NSLOT * SLOT;
            const uint32_t full = bars + (B_FULL + w * NSLOT) * 8;
            if (lane == 0) {
#pragma unroll
                for (int i = 0; i < NSLOT; i++) { mbar_init(full + i * 8, 1); mbar_init(full + (B_EMPTY - B_FULL + i) * 8, 4); }
                asm volatile("fence.mbarrier_init.release.cluster;" ::: "memory");
                fence_async_smem();
            }
            __syncwarp();
            cluster_arrive();
            TS(1);
#pragma unroll
            for (int n = 0; n < NSLOT; n++) {
                if (n == 1 || n == 2) bar_sync(12, 64);
                ring_load(ring + n * SLOT, &p.tm[0], 64 * (8 * r + 4 * w + (n >> 1)), 8 * ((n & 1) ^ r), full + n * 8);
            }
            TS(2);
            const uint32_t code = load_code(lane, r, w) | (load_code(lane + 32, r, w) << 16);
            cluster_wait();
            uint32_t s = 0, ph = 0;
            int n = NSLOT;
#pragma unroll 1
            for (int seg = 0; seg < 2; seg++) {
#pragma unroll 1
                for (; n < (seg == 0 ? 22 : NLOADS); n++) {
                    const uint32_t c = __shfl_sync(~0u, code, n) >> (n & 32 ? 16 : 0);
                    const CUtensorMap* tm = &p.tm[c & 15];
                    const uint32_t col = (c & 0xf0) * 4, row = (c & 0xff00) >> 5, dst = ring + s * SLOT;
                    mbar_wait(full + (B_EMPTY - B_FULL) * 8 + s * 8, ph + (((uint32_t)(size_t)tm | col | row | dst) & p.zero));
                    ring_load(dst, tm, col, row, full + s * 8);
                    if (++s == NSLOT) { s = 0; ph ^= 1; }
                }
                if (seg == 1) break;
                const uint32_t epoch = ld_epoch();
                const uint32_t rdy = bars + (B_RDY + 3 * w) * 8, prdy = mapa(rdy, r ^ 1);
                const int odd = r ^ w;
                const uint32_t* flags = g_flag_kv + (abh * 32 + lane) * KFS;
                auto kv_load = [&](uint32_t sl, int isv, int i) {
                    ring_load_both(ring + sl * SLOT, &p.tm[8], (isv * 64 + abh * 8 + 2 * i + w) * 128, full + sl * 8);
                };
#pragma unroll 1
                for (int i = 0; i < 2; i++) {
                    if (lane < 3 + i) {
                        const uint32_t sl = i ? lane : lane + 2;
                        mbar_wait(full + (B_EMPTY - B_FULL + sl) * 8, i ^ 1);
                        mbar_arrive_tx(full + sl * 8, (i || lane == 2) ? SLOT : 0);
                    }
                    __syncwarp();
                }
                if (lane == 0) mbar_arrive_peer(prdy);
                bar_sync(14, 96);
                spin(odd ? KDELAY + KD2 : KDELAY);
                mbar_wait(rdy, 0);
                flag_wait(flags, epoch, (lane >> 2) == 2 * odd + w);
                TSW(5 + 2 * odd);
                kv_load(odd ? 0 : 4, 0, odd);
                if (!odd) kv_load(1, 1, 0);
                flag_wait(flags, epoch, (lane >> 2) == 2 * odd + w + 4);
                mbar_wait(full + (odd ^ 1) * 8, 1);
                kv_load(2 + odd, odd, 2 - odd);
#pragma unroll 1
                for (int i = 0; i < 3; i++) {
                    const uint32_t sl = i ? i - 1 : 4, bo = i == 2 ? 16 : 8;
                    mbar_wait(full + (B_EMPTY - B_FULL + sl) * 8, i != 0);
                    if (lane == 0) mbar_arrive_tx(full + sl * 8, SLOT);
                    if ((i & 1) != odd) {
                        mbar_wait(rdy + bo, 0);
                        kv_load(sl, i != 0, 2 + odd);
                    } else if (lane == 0) mbar_arrive_peer(prdy + bo);
                    __syncwarp();
                }
                n = 32; s = 2; ph = 1;
            }
        } else if (warp == 10) {
            if (lane == 0) {
#pragma unroll
                for (int i = B_XA; i <= B_ST; i++) mbar_init(bars + i * 8, i == B_ST ? 4 : 1);
#pragma unroll
                for (int i = B_XA; i <= B_SR; i++) mbar_arrive_tx(bars + i * 8, i < B_XB ? 512 : (i == B_X2 ? 12288 : 8192));
                asm volatile("fence.mbarrier_init.release.cluster;" ::: "memory");
                fence_async_smem();
            }
            __syncwarp();
            cluster_arrive();
            cluster_wait();
        } else {
            const uint32_t kb = (lane < 2 || lane > 5) ? 4096 : (lane == 2 ? 3072 : (lane == 4 ? 2048 : 1024));
            const char* pf = p.w[lane & 7] + blockIdx.x * kb;
            cluster_arrive();
            cluster_wait();
            if (lane < 2) prefetch_l2(pf, kb);
            mbar_wait(bars + B_XA * 8, 0);
            if (lane == 2) prefetch_l2(pf, kb);
            if (lane >= 1 && lane < 9) asm volatile("prefetch.tensormap [%0];" ::"l"(&p.tm[lane]) : "memory");
            mbar_wait(bars + (B_FULL + 1) * 8, 1);
            if (lane > 2 && lane < 8) prefetch_l2(pf, kb);
            if (lane == 8 && blockIdx.x < 15) prefetch_l2(p.dw + blockIdx.x * 256, 512);
            const uint32_t epoch = ld_epoch();
            bar_sync(4, 288);
            if (lane < 16) flag_set(&g_flag_kv[((b * 4 + 2 * r + (lane >> 3)) * 32 + pt) * KFS + (lane & 7)], epoch);
            __syncwarp();
            bar_arrive(13, 288);
            bar_arrive(14, 96);
            TSW(8);
        }
        TSDUMP();
        return;
    }

    const int w = warp >> 2, wq = warp & 3;
    const int tile = 2 * r + w;
    const int wt = tid & 127;
    const int c4 = lane & 3;
    const int trow = pt * 32 + 8 * wq;
    uint32_t xr[8];
    {
        const uint32_t* xp = reinterpret_cast<const uint32_t*>(p.x + (size_t)(b * T_ + trow + (lane >> 2)) * 256 + tile * 64) + c4;
#pragma unroll
        for (int j = 0; j < 8; j++) xr[j] = trow < T_ ? __ldg(xp + 4 * j) : 0u;
    }
    cluster_arrive();
    asm volatile("setmaxnreg.inc.sync.aligned.u32 208;");
    const uint32_t rbase = sb + OFF_RING + w * NSLOT * SLOT, fbar = bars + (B_FULL + w * NSLOT) * 8;
    const uint32_t rdesc = desc_lo(rbase);
    auto acq = [&](int n) { mbar_wait(fbar + (n % NSLOT) * 8, (n / NSLOT) & 1); };
    auto rel = [&](int n) { if (lane == 0) mbar_arrive(fbar + (B_EMPTY - B_FULL + n % NSLOT) * 8); };
    const uint32_t foff = (lane & 7) * 128 + (((lane >> 3) ^ (lane & 7)) << 4);
    const uint32_t toff = ((lane >> 4) * 8 + (lane & 7)) * 128 + (((2 * wq + ((lane >> 3) & 1)) ^ (lane & 7)) << 4);
    auto publish = [&](int bar, uint32_t src, uint32_t bytes, int nsync) {
        fence_async_smem();
        bar_sync(2 + w, 128);
        if (wq == 0) peer_copy(mapa(src, r ^ 1), src, bytes, mapa(bars + bar * 8, r ^ 1));
        bar_sync(nsync == 384 ? 1 : 10, nsync);
    };
    float v[16];
#pragma unroll
    for (int j = 0; j < 8; j++) { v[2 * j] = blo(xr[j]); v[2 * j + 1] = bhi(xr[j]); }
    const uint32_t xown = __shfl_sync(~0u, P + wt * 16 + tile * 4096, lane), xrem = __shfl_sync(~0u, P + wt * 16 + (r ^ 1) * 8192, lane);
    const uint32_t sbuf = __shfl_sync(~0u, sb + OFF_MISC + 1024 + (8 * wq + (lane >> 2)) * 32, lane);
    const uint32_t sown = __shfl_sync(~0u, sbuf + tile * 8, lane);
    const uint32_t peer = __shfl_sync(~0u, mapa(sb, r ^ 1) - sb, lane);
    const uint32_t meta = __shfl_sync(~0u, 0xEEEE4444u + p.zero, lane);
    cluster_wait();
    TS(56);
    float mean, msq;

#pragma unroll 1
    for (int ph = 0;; ph++) {
        uint4 o0, o1;
        {
            float s = 0.f, q = 0.f, s2 = 0.f, q2 = 0.f;
#pragma unroll
            for (int j = 0; j < 4; j++) {
                s += v[4 * j] + v[4 * j + 1]; s2 += v[4 * j + 2] + v[4 * j + 3];
                q += fmaf(v[4 * j], v[4 * j], v[4 * j + 1] * v[4 * j + 1]); q2 += fmaf(v[4 * j + 2], v[4 * j + 2], v[4 * j + 3] * v[4 * j + 3]);
            }
            s += s2; q += q2;
            const uint32_t xa = bars + (B_XA + ph) * 8;
            s += __shfl_xor_sync(~0u, s, 1); q += __shfl_xor_sync(~0u, q, 1);
            s += __shfl_xor_sync(~0u, s, 2); q += __shfl_xor_sync(~0u, q, 2);
            if (c4 == 0) st_async2f(sown + peer, s, q, xa + peer);
            if (c4 == 0) sts64f(sown, s, q);
#pragma unroll
            for (int j = 0; j < 8; j++) xr[j] = pack2(v[2 * j], v[2 * j + 1]);
            sts128(xown, xr[0], xr[1], xr[2], xr[3]);
            sts128(xown + 2048, xr[4], xr[5], xr[6], xr[7]);
            bar_sync(10, 256);
            o0 = lds128(xown ^ 4096); o1 = lds128((xown ^ 4096) + 2048);
            if (ph < 3) {
                st_async4(xown + peer, xr[0], xr[1], xr[2], xr[3], xa + (B_XB - B_XA) * 8 + peer);
                st_async4(xown + peer + 2048, xr[4], xr[5], xr[6], xr[7], xa + (B_XB - B_XA) * 8 + peer);
            }
            TS(57 + ph);
            if (ph == 0) acq(0);
            mbar_wait(xa, 0);
            const float4 u0 = lds128f(sbuf), u1 = lds128f(sbuf + 16);
            mean = ((u0.x + u0.z) + (u1.x + u1.z)) * (1.f / 256.f);
            msq = ((u0.y + u0.w) + (u1.y + u1.w)) * (1.f / 256.f);
        }
        if (ph == 3) break;
        uint32_t a[32];
        const uint32_t mean2 = pack2(mean, mean);
        auto centre = [&](int i, const uint4& u) {
            a[i] = hsub2(u.x, mean2); a[i + 1] = hsub2(u.y, mean2); a[i + 2] = hsub2(u.z, mean2); a[i + 3] = hsub2(u.w, mean2);
        };
#pragma unroll
        for (int j = 0; j < 8; j++) a[j] = hsub2(xr[j], mean2);
        centre(8, o0); centre(12, o1);
        const float rstd = rsq(fmaxf(fmaf(-mean, mean, msq), 0.f) + 1e-5f);
        auto gather_peer = [&]() {
            mbar_wait(bars + (B_XB + ph) * 8, 0);
#pragma unroll
            for (int i = 0; i < 4; i++) centre(16 + 4 * i, lds128(xrem + i * 2048));
        };
        auto sp = [&](float (&d)[32], int n, const uint32_t* af, int flip, int acc) {
            const uint32_t lo = rdesc + p.zero * (ph + n + 1) + (n % NSLOT) * (SLOT >> 4);
            const uint64_t b0 = mkdesc(lo + flip * 512), b1 = mkdesc(lo + (flip ^ 1) * 512);
            wg_fence();
            mma_sp(d, af, b0, meta, acc);
            mma_sp(d, af + 4, b0 + 256, meta, 1);
            mma_sp(d, af + 8, b1, meta, 1);
            mma_sp(d, af + 12, b1 + 256, meta, 1);
            wg_commit();
        };
        float d0[32], d1[32];

        if (ph != 1) {
            uint32_t h[32];
            const float rs = 0.5f * rstd;
            const uint32_t inb = bars + (B_INB + ph) * 8, box = H + wt * 16;
            bool ready = true;
            auto step = [&](float (&d)[32], int n, const uint32_t* af, int flip, int acc, auto work) {
                if (!ready) acq(n);
                if (((TURN >> n) & 1) && w == 1) bar_sync(7, 256);
                sp(d, n, af, flip, acc);
                if (n > 0 && ((TURN >> (n - 1)) & 1) && w == 0) bar_arrive(7, 256);
                if (n < 15) ready = mbar_test(fbar + ((n + 1) % NSLOT) * 8, ((n + 1) / NSLOT) & 1);
                wg_wait<1>();
                if (n > 0 && !((EAGER >> (n - 1)) & 1)) rel(n - 1);
                const uint32_t tie = work() & p.zero;
                if ((EAGER >> n) & 1) {
                    if (p.zero < n + ph + 1) wg_wait<0>();
                    if (lane == 0) mbar_arrive(fbar + (B_EMPTY - B_FULL + n % NSLOT) * 8 + tie);
                }
            };
            auto none = []() { return 0u; };
            auto act = [&](float (&d)[32], int i) {
                pin(d);
#pragma unroll
                for (int j = 0; j < 8; j++) {
                    const float u0 = (d[4 * j] + d[4 * j + 2]) * rs, u1 = (d[4 * j + 1] + d[4 * j + 3]) * rs;
                    h[8 * i + j] = pack2(fmaf(u0, tanh_fast(u0), u0), fmaf(u1, tanh_fast(u1), u1));
                }
                return h[8 * i] | h[8 * i + 1] | h[8 * i + 2] | h[8 * i + 3] | h[8 * i + 4] | h[8 * i + 5] | h[8 * i + 6] | h[8 * i + 7];
            };
            auto send = [&](float (&d)[32], int x) {
                pin(d);
                uint32_t pk[8];
#pragma unroll
                for (int j = 0; j < 8; j++) pk[j] = pack2(d[4 * j] + d[4 * j + 2], d[4 * j + 1] + d[4 * j + 3]);
                const uint32_t ow = w ^ (x & 1), dst = box + (ow * 3 + x - 1) * 4096;
                if (x & 2) {
                    st_async4(dst + peer, pk[0], pk[1], pk[2], pk[3], inb + ow * 8 + peer);
                    st_async4(dst + peer + 2048, pk[4], pk[5], pk[6], pk[7], inb + ow * 8 + peer);
                } else {
                    sts128(dst, pk[0], pk[1], pk[2], pk[3]);
                    sts128(dst + 2048, pk[4], pk[5], pk[6], pk[7]);
                }
            };
            TS(1 + ph * 10);
            step(d0, 0, a, w, 0, [&]() { gather_peer(); return 0u; });
            TS(32);
            step(d0, 1, a + 16, 0, 1, none);
            step(d1, 2, a, w, 0, [&]() { return act(d0, 0); });
            step(d1, 3, a + 16, 0, 1, none);
            step(d0, 4, a, w, 0, [&]() { return act(d1, 1); });
            TS(33);
            step(d0, 5, a + 16, 0, 1, none);
            step(d1, 6, a, w, 0, [&]() { return act(d0, 2); });
            step(d1, 7, a + 16, 0, 1, none);
            step(d0, 8, h, 0, 0, [&]() { return act(d1, 3); });
            TS(2 + ph * 10);
            step(d0, 9, h + 16, 0, 1, none);
            step(d1, 10, h, 0, 0, [&]() { send(d0, 3); return 0u; });
            step(d1, 11, h + 16, 0, 1, none);
            step(d0, 12, h, 0, 0, [&]() { send(d1, 2); return 0u; });
            TS(34);
            step(d0, 13, h + 16, 0, 1, none);
            step(d1, 14, h, 0, 0, [&]() { send(d0, 1); return 0u; });
            step(d1, 15, h + 16, 0, 1, none);
            if (ph == 0) acq(16);
            mbar_wait(inb + w * 8, 0);
            bar_sync(10, 256);
#pragma unroll
            for (int i = 0; i < 2; i++) {
                const uint32_t src = box + w * 12288 + i * 2048;
                const uint4 u0 = lds128(src), u1 = lds128(src + 4096), u2 = lds128(src + 8192);
                const uint32_t p0[4] = {u0.x, u0.y, u0.z, u0.w}, p1[4] = {u1.x, u1.y, u1.z, u1.w}, p2[4] = {u2.x, u2.y, u2.z, u2.w};
#pragma unroll
                for (int j = 0; j < 4; j++) {
                    v[8 * i + 2 * j] = fmaf(0.5f, blo(p0[j]) + blo(p1[j]) + blo(p2[j]), blo(xr[4 * i + j]));
                    v[8 * i + 2 * j + 1] = fmaf(0.5f, bhi(p0[j]) + bhi(p1[j]) + bhi(p2[j]), bhi(xr[4 * i + j]));
                }
            }
            wg_wait<0>();
            pin(d1);
            rel(15);
            TS(3 + ph * 10);
#pragma unroll
            for (int j = 0; j < 8; j++) {
                v[2 * j] = fmaf(0.5f, d1[4 * j] + d1[4 * j + 2], v[2 * j]);
                v[2 * j + 1] = fmaf(0.5f, d1[4 * j + 1] + d1[4 * j + 3], v[2 * j + 1]);
            }
            continue;
        }

        {
            TS(11);
            const uint32_t stg = H + warp * 2048;
            unsigned char* g = g_kvq + (size_t)((b * 4 + tile) * 1024 + trow) * 128 + lane * 16;
            auto put = [&](float (&d)[32], int i) {
                pin(d);
                uint32_t pk[8];
#pragma unroll
                for (int j = 0; j < 8; j++) pk[j] = pack2((d[4 * j] + d[4 * j + 2]) * rstd, (d[4 * j + 1] + d[4 * j + 3]) * rstd);
                if (i == 2) {
                    st_data(g + 2097152, pk[0], pk[1], pk[2], pk[3]);
                    st_data(g + 2097152 + 512, pk[4], pk[5], pk[6], pk[7]);
                    return;
                }
                stsm4(stg + i * 1024 + foff, pk[0], pk[1], pk[2], pk[3]);
                stsm4(stg + i * 1024 + (foff ^ 64), pk[4], pk[5], pk[6], pk[7]);
                __syncwarp();
                const uint4 u0 = lds128(stg + i * 1024 + lane * 16), u1 = lds128(stg + i * 1024 + 512 + lane * 16);
                stg128(g + i * 1048576, u0); stg128(g + i * 1048576 + 512, u1);
            };
            sp(d0, 16, a, w, 0);
            acq(17);
            sp(d1, 17, a, w, 0);
            gather_peer();
            acq(18);
            sp(d0, 18, a + 16, 0, 1);
            wg_wait<1>();
            rel(16); rel(17);
            acq(19);
            sp(d1, 19, a + 16, 0, 1);
            wg_wait<1>();
            rel(18);
            put(d0, 0);
            wg_wait<0>();
            rel(19);
            TS(37);
            put(d1, 1);
            bar_arrive(4, 288);
            TS(38);
            acq(20);
            sp(d0, 20, a, w, 0);
            acq(21);
            sp(d0, 21, a + 16, 0, 1);
            acq(22); acq(23);
            rel(22); rel(23);
            mbar_wait(bars + B_RST * 8, 0);
            wg_wait<0>();
            rel(20); rel(21);
            bar_sync(13, 288);
            put(d0, 2);
            if (wq == 0 || wq == 3) {
                uint4* hp = &g_halo[((pair * 4 + tile) * 2 + (wq & 1)) * 64 + lane];
                st_data(hp, xr[0], xr[1], xr[2], xr[3]);
                st_data(hp + 32, xr[4], xr[5], xr[6], xr[7]);
            }
            TS(12);
        }

        const uint32_t xo = P + tile * XCH + wq * 1024, xt = P + tile * XCH + toff;
        {
            constexpr float CS = 0.125f * 1.4426950408889634f;
            float sa[32], sb2[32], o[36];
            uint32_t pa[16], pb[16], q[16];
            float n0 = INFINITY, n1 = INFINITY;
            zero(o); zero(pa); zero(pb);
            const uint32_t ones = sb + OFF_MISC + 2048;
            if (tid < 128) sts128(ones + tid * 16, 0x3F803F80u, 0x3F803F80u, 0x3F803F80u, 0x3F803F80u);
            fence_async_smem();
            bar_sync(10, 256);
            stsm4(xo + 1024 + foff, xr[0], xr[1], xr[2], xr[3]);
            stsm4(xo + 1024 + (foff ^ 64), xr[4], xr[5], xr[6], xr[7]);
            const uint32_t vdesc = rdesc + ((((ones - rbase) >> 4) - 1) << 16);
            auto qk_issue = [&](float (&s)[32], uint32_t lo) {
                const uint64_t kd = mkdesc(lo);
                wg_fence();
#pragma unroll
                for (int k = 0; k < 4; k++) mma_qk(s, q[4 * k], q[4 * k + 1], q[4 * k + 2], q[4 * k + 3], kd + 2 * k, k != 0);
                wg_commit();
            };
            auto pv_issue = [&](uint32_t (&pp)[16], uint32_t lo) {
                const uint64_t vd = mkdesc(lo);
                wg_fence();
#pragma unroll
                for (int k = 0; k < 4; k++) mma_pv(o, pp[4 * k], pp[4 * k + 1], pp[4 * k + 2], pp[4 * k + 3], vd - k * (128 * 65535));
                wg_commit();
            };
            auto new_max = [&](float (&s)[32], float& x0, float& x1) {
                x0 = s[0]; x1 = s[2];
#pragma unroll
                for (int j = 0; j < 8; j++) {
                    x0 = fmaxf(x0, fmaxf(s[4 * j], s[4 * j + 1]));
                    x1 = fmaxf(x1, fmaxf(s[4 * j + 2], s[4 * j + 3]));
                }
                x0 = fmaxf(x0, __shfl_xor_sync(~0u, x0, 1)); x1 = fmaxf(x1, __shfl_xor_sync(~0u, x1, 1));
                x0 = fmaxf(x0, __shfl_xor_sync(~0u, x0, 2)); x1 = fmaxf(x1, __shfl_xor_sync(~0u, x1, 2));
                x0 = fminf(n0, fmaf(x0, -CS, -20.f)); x1 = fminf(n1, fmaf(x1, -CS, -20.f));
            };
            auto probs = [&](float (&s)[32], uint32_t (&pp)[16], bool ready, auto wait) {
                uint32_t any = 0;
#pragma unroll
                for (int i = 0; i < 16; i++) {
                    pp[i] = pack2(ex2(fmaf(s[2 * i], CS, (i & 1) ? n1 : n0)), ex2(fmaf(s[2 * i + 1], CS, (i & 1) ? n1 : n0)));
                    any |= pp[i];
                }
                float sc0 = 1.f, sc1 = 1.f;
                const bool slow = __any_sync(~0u, (any & 0x40004000u) || !ready);
                if (slow) {
                    wait();
                    if (__any_sync(~0u, any & 0x40004000u)) {
                        float x0, x1;
                        new_max(s, x0, x1);
                        sc0 = ex2(x0 - n0); sc1 = ex2(x1 - n1);
                        n0 = x0; n1 = x1;
#pragma unroll
                        for (int i = 0; i < 16; i++)
                            pp[i] = pack2(ex2(fmaf(s[2 * i], CS, (i & 1) ? n1 : n0)), ex2(fmaf(s[2 * i + 1], CS, (i & 1) ? n1 : n0)));
                    }
                }
                wg_wait<0>();
                pin(sa); pin(sb2); pin(o); pin(pa); pin(pb);
                if (slow) {
#pragma unroll
                    for (int j = 0; j < 9; j++) { o[4 * j] *= sc0; o[4 * j + 1] *= sc0; o[4 * j + 2] *= sc1; o[4 * j + 3] *= sc1; }
                }
            };
            {
                uint4 u[4];
                const unsigned char* src = g_kvq + 2097152 + (size_t)(abh * 1024 + qt * 64 + wq * 16) * 128 + lane * 16;
                spin(QGATE);
                ld_data<512>(u, src);
#pragma unroll
                for (int k = 0; k < 2; k++) {
                    q[8 * k] = u[k].x; q[8 * k + 1] = u[k + 2].x; q[8 * k + 2] = u[k].y; q[8 * k + 3] = u[k + 2].y;
                    q[8 * k + 4] = u[k].z; q[8 * k + 5] = u[k + 2].z; q[8 * k + 6] = u[k].w; q[8 * k + 7] = u[k + 2].w;
                }
                pin(q);
            }
            TS(40);
            acq(24);
            TS(13);
            qk_issue(sa, rdesc + (24 % NSLOT) * (SLOT >> 4));
            qk_issue(sb2, rdesc + (24 % NSLOT) * (SLOT >> 4) + 512);
            wg_wait<1>();
            pin(sa);
            {
                float x0, x1;
                new_max(sa, x0, x1);
                n0 = x0; n1 = x1;
            }
            bar_arrive(6, 384);
            if (w == 1) bar_sync(7, 256);
            uint32_t vd = vdesc - (SLOT >> 4) * 65535u, kd = rdesc, vb = fbar + 8, kb = fbar;
            uint32_t vlast = vdesc - 4 * (SLOT >> 4) * 65535u;
            uint32_t kprev = fbar + 32, vprev = bars + (B_SINK - (B_EMPTY - B_FULL)) * 8;
#pragma unroll 1
            for (int it = 0; it < 4; it++) {
                pv_issue(pb, vlast);
                probs(sa, pa, mbar_test(vb, it < 2) & mbar_test(kb, it < 3), [&]() { mbar_wait(vb, it < 2); mbar_wait(kb, it < 3); });
                TS(41 + it * 4);
                if (it == 0 && w == 0) bar_arrive(7, 256);
                if (it == 3 && w == 1) {
#pragma unroll
                    for (int i = 20; i < 32; i++) sb2[i] = -INFINITY;
                }
                pin(sb2);
                if (it < 3) qk_issue(sa, kd);
                if (lane == 0) mbar_arrive(kprev + (B_EMPTY - B_FULL) * 8);
                if (lane == 0) mbar_arrive(vprev + (B_EMPTY - B_FULL) * 8);
                pv_issue(pa, vd);
                probs(sb2, pb, true, []() {});
                TS(43 + it * 4);
                if (it < 3) qk_issue(sb2, kd + 512);
                const int dv = it == 0 ? 2 : (it == 1 ? -3 : 1);
                kprev = kb; vprev = vb; vlast = vd - 512 * 65535u;
                vd -= dv * (SLOT >> 4) * 65535u; vb += dv * 8;
                kd += 2 * (SLOT >> 4); kb = it == 2 ? vb : kb + 16;
            }
            pv_issue(pb, vlast);
            const int row = wq * 16 + (lane >> 2);
            const uint32_t ml = sb + OFF_MISC;
            mbar_wait(bars + (B_RST + 1) * 8, 0);
            wg_wait<0>();
            pin(o); pin(pb); pin(sa); pin(sb2);
            rel(31);
            const float l0 = o[32], l1 = o[34];
            if (c4 == 0) { sts64f(ml + w * 512 + row * 8, n0, l0); sts64f(ml + w * 512 + row * 8 + 64, n1, l1); }
            TS(14);
            float mine[16];
#pragma unroll
            for (int j = 0; j < 4; j++) {
                if (w == 0) sts128f(H + j * 2048 + wt * 16, o[16 + 4 * j], o[17 + 4 * j], o[18 + 4 * j], o[19 + 4 * j]);
                else sts128f(H + 8192 + j * 2048 + wt * 16, o[4 * j], o[4 * j + 1], o[4 * j + 2], o[4 * j + 3]);
            }
#pragma unroll
            for (int i = 0; i < 16; i++) mine[i] = w == 0 ? o[i] : o[16 + i];
            bar_sync(10, 256);
            const float2 u0 = lds64f(ml + (w ^ 1) * 512 + row * 8), u1 = lds64f(ml + (w ^ 1) * 512 + row * 8 + 64);
            const float x0 = fminf(n0, u0.x), x1 = fminf(n1, u1.x);
            float a0 = ex2(x0 - n0), b0 = ex2(x0 - u0.x), a1 = ex2(x1 - n1), b1 = ex2(x1 - u1.x);
            const float i0 = __fdividef(1.f, fmaf(a0, l0, b0 * u0.y)), i1 = __fdividef(1.f, fmaf(a1, l1, b1 * u1.y));
            a0 *= i0; b0 *= i0; a1 *= i1; b1 *= i1;
            uint32_t pk[8];
#pragma unroll
            for (int j = 0; j < 4; j++) {
                const float4 v = lds128f(H + (w ^ 1) * 8192 + j * 2048 + wt * 16);
                pk[2 * j] = pack2(fmaf(a0, mine[4 * j], b0 * v.x), fmaf(a0, mine[4 * j + 1], b0 * v.y));
                pk[2 * j + 1] = pack2(fmaf(a1, mine[4 * j + 2], b1 * v.z), fmaf(a1, mine[4 * j + 3], b1 * v.w));
            }
            unsigned char* dst = g_o + (size_t)(abh * PADROWS + 8 + qt * 64 + wq * 16) * 128 + w * 512 + lane * 16;
            st_data(dst, pk[0], pk[2], pk[4], pk[6]);
            st_data(dst + 1024, pk[1], pk[3], pk[5], pk[7]);
            if (tid == 0) asm volatile("red.relaxed.gpu.global.add.u32 [%0], 1;" ::"l"(&g_epoch[blockIdx.x * FS]) : "memory");
            TS(15);
        }

        auto mm = [&](float (&d)[24], int n, uint32_t act, int acc) {
            const uint32_t z = p.zero * (ph + n);
            const uint64_t ad = mkdesc(rdesc + z + (n % NSLOT) * (SLOT >> 4)), bd = mkdesc(desc_lo(act) + z);
            wg_fence();
#pragma unroll
            for (int k = 0; k < 8; k++) mma_t(d, ad + k * 128, bd + (k >> 2) * (XCH >> 4) + (k & 3) * 2, k == 0 ? acc : 1);
            wg_commit();
        };
        uint32_t dwr[15];
        {
#pragma unroll
            for (int i = 0; i < 15; i++) dwr[i] = hmul2(__ldg(reinterpret_cast<const uint32_t*>(p.dw + i * 256 + tile * 64) + lane), 0x3F003F00u);
            float d[24];
            uint32_t xw[12];
            bar_sync(9, 384);
#pragma unroll
            for (int j = 0; j < 3; j++) ldsm4t(xt + j * 2048, xw[4 * j], xw[4 * j + 1], xw[4 * j + 2], xw[4 * j + 3]);
            pin(xw);
            acq(32); acq(33); acq(34); acq(35);
            {
                if (ODELAY) spin(ODELAY);
                uint4 u[6];
                ld_data<1024>(u, g_o + (size_t)((b * 4 + (warp >> 1)) * PADROWS + pt * 32) * 128 + (warp & 1) * 512 + lane * 16);
                const uint32_t dst = H + (warp >> 1) * XCH + (foff ^ ((warp & 1) * 64));
#pragma unroll
                for (int i = 0; i < 6; i++) stsm4(dst + i * 1024, u[i].x, u[i].y, u[i].z, u[i].w);
            }
            fence_async_smem();
            bar_sync(10, 256);
            TS(16);
            mm(d, 32, H, 0);
            mm(d, 33, H + 2 * XCH, 1);
            wg_wait<1>();
            rel(32);
            wg_wait<0>();
            pin(d);
#pragma unroll
            for (int i = 0; i < 12; i++) xw[i] = pack2(d[2 * i] + blo(xw[i]), d[2 * i + 1] + bhi(xw[i]));
            if (c4 == 0) { xw[0] = (xw[0] & 0xffff0000u) | 0x3F80u; xw[1] = (xw[1] & 0xffff0000u) | 0x3F80u; }
#pragma unroll
            for (int j = 0; j < 3; j++) stsm4t(xt + j * 2048, xw[4 * j], xw[4 * j + 1], xw[4 * j + 2], xw[4 * j + 3]);
            rel(33);
            publish(B_X2, P + tile * XCH, XCH, 384);
            TS(17);
        }
        {
            float da[24], db[24], st[24];
            bar_sync(5, 384);
            mm(da, 34, P + 2 * r * XCH, 0);
            mm(db, 35, P + 2 * r * XCH, 0);
            acq(36); acq(37);
            mbar_wait(bars + B_X2 * 8, 0);
            bar_sync(5, 384);
            TS(39);
            mm(da, 36, P + 2 * (r ^ 1) * XCH, 1);
            mm(db, 37, P + 2 * (r ^ 1) * XCH, 1);
            wg_wait<2>();
            rel(34); rel(35);
            mbar_wait(bars + B_ST * 8, 0);
#pragma unroll
            for (int j = 0; j < 6; j++) {
                const float4 u = lds128f(sb + OFF_STATS + (8 * j + 2 * c4) * 8);
                st[4 * j] = u.x; st[4 * j + 1] = u.y; st[4 * j + 2] = u.z; st[4 * j + 3] = u.w;
            }
            wg_wait<0>();
            pin(da); pin(db);
            rel(36); rel(37);
            TS(18);
            uint32_t pk[12];
#pragma unroll
            for (int hh = 0; hh < 2; hh++) {
                const float ca = __shfl_sync(~0u, da[2 * hh], lane & 28), cb = __shfl_sync(~0u, db[2 * hh], lane & 28);
#pragma unroll
                for (int j = 0; j < 6; j++) {
                    const float u0 = fmaf(-st[4 * j], ca, da[4 * j + 2 * hh] * st[4 * j + 1]);
                    const float u1 = fmaf(-st[4 * j + 2], ca, da[4 * j + 2 * hh + 1] * st[4 * j + 3]);
                    const float v0 = fmaf(-st[4 * j], cb, db[4 * j + 2 * hh] * st[4 * j + 1]);
                    const float v1 = fmaf(-st[4 * j + 2], cb, db[4 * j + 2 * hh + 1] * st[4 * j + 3]);
                    pk[2 * j + hh] = pack2(fmaf(u0, tanh_fast(v0), u0), fmaf(u1, tanh_fast(v1), u1));
                }
            }
            const uint32_t gs = H + 16384 + w * XCH;
#pragma unroll
            for (int j = 0; j < 3; j++) stsm4t(gs + toff + j * 2048, pk[4 * j], pk[4 * j + 1], pk[4 * j + 2], pk[4 * j + 3]);
            ldsm4(xo + 1024 + foff, xr[0], xr[1], xr[2], xr[3]);
            ldsm4(xo + 1024 + (foff ^ 64), xr[4], xr[5], xr[6], xr[7]);
            bar_sync(2 + w, 128);
            uint32_t ca[8], cb[8];
            const uint32_t grow = gs + 8 * wq * 128 + c4 * 4, srow = H + tile * HCH + 8 * wq * 128 + c4 * 4;
#pragma unroll
            for (int k = 0; k < 22; k++) {
                const uint32_t v = lds32(grow + (1 + k) * 128 + (((lane >> 2) ^ ((1 + k) & 7)) << 4));
#pragma unroll
                for (int i = 0; i < 8; i++) {
                    const int tap = k - i;
                    if (tap == 0) ca[i] = hmul2(v, dwr[0]);
                    else if (tap > 0 && tap < 8) ca[i] = hfma2(v, dwr[tap], ca[i]);
                    else if (tap == 8) cb[i] = hmul2(v, dwr[8]);
                    else if (tap > 8 && tap < 15) cb[i] = hfma2(v, dwr[tap], cb[i]);
                }
            }
#pragma unroll
            for (int i = 0; i < 8; i++) {
                const float h0 = blo(ca[i]) + blo(cb[i]), h1 = bhi(ca[i]) + bhi(cb[i]);
                sts32(srow + i * 128 + (((lane >> 2) ^ i) << 4), pack2(fmaf(h0, tanh_fast(h0), h0), fmaf(h1, tanh_fast(h1), h1)));
            }
            acq(38); acq(39);
            publish(B_SR, H + tile * HCH, HCH, 256);
            TS(19);
        }
        {
            auto frags = [&](int i, int half) {
                const uint32_t src = H + 2 * half * HCH + wq * 1024;
#pragma unroll
                for (int k = 0; k < 4; k++) ldsm4(src + (k >> 1) * HCH + (foff ^ ((k & 1) * 64)), a[i + 4 * k], a[i + 4 * k + 1], a[i + 4 * k + 2], a[i + 4 * k + 3]);
            };
            frags(0, r);
            sp(d0, 38, a, 0, 0);
            acq(40);
            mbar_wait(bars + B_SR * 8, 0);
            frags(16, r ^ 1);
            sp(d0, 39, a + 16, 0, 1);
            wg_wait<1>();
            rel(38);
            wg_wait<0>();
            pin(d0);
            rel(39);
#pragma unroll
            for (int j = 0; j < 8; j++) {
                v[2 * j] = d0[4 * j] + d0[4 * j + 2] + blo(xr[j]);
                v[2 * j + 1] = d0[4 * j + 1] + d0[4 * j + 3] + bhi(xr[j]);
            }
            TS(20);
        }
    }

    cluster_arrive();
    TS(24);
    {
        const float rstd = rsq(fmaxf(fmaf(-mean, mean, msq), 0.f) + 1e-5f), nb = -mean * rstd;
#pragma unroll
        for (int j = 0; j < 8; j++) xr[j] = pack2(fmaf(v[2 * j], rstd, nb), fmaf(v[2 * j + 1], rstd, nb));
        const uint32_t stg = P + 16384 + warp * 1024;
        stsm4(stg + foff, xr[0], xr[1], xr[2], xr[3]);
        stsm4(stg + (foff ^ 64), xr[4], xr[5], xr[6], xr[7]);
        __syncwarp();
        const uint32_t src = stg + (lane >> 3) * 128 + (((lane & 7) ^ (lane >> 3)) << 4);
        const uint4 u0 = lds128(src), u1 = lds128((src + 512) ^ 64);
        __nv_bfloat16* dst = p.out + (size_t)(b * T_ + trow + (lane >> 3)) * 256 + tile * 64 + (lane & 7) * 8;
        if (trow < T_) { stg128(dst, u0); stg128(dst + 4 * 256, u1); }
    }
    TS(25);
    TG(31);
    TSDUMP();
    cluster_wait();
}

typedef CUresult (*EncodeFn)(CUtensorMap*, CUtensorMapDataType, cuuint32_t, void*, const cuuint64_t*, const cuuint64_t*,
                             const cuuint32_t*, const cuuint32_t*, CUtensorMapInterleave, CUtensorMapSwizzle,
                             CUtensorMapL2promotion, CUtensorMapFloatOOBfill);

}

extern "C" void kernel_launch(void* const* d_in, const int* in_sizes, int n_in, void* d_out, int out_size) {
    static EncodeFn encode = nullptr;
    if (!encode) {
        void* fn = nullptr;
        cudaDriverEntryPointQueryResult qr;
        cudaGetDriverEntryPoint("cuTensorMapEncodeTiled", &fn, cudaEnableDefault, &qr);
        encode = (EncodeFn)fn;
        cudaFuncSetAttribute(conformer_kernel, cudaFuncAttributeMaxDynamicSharedMemorySize, SMEM_LAUNCH);
    }
    Params p;
    const cuuint32_t ones[5] = {1, 1, 1, 1, 1};
    const int idx[8] = {1, 2, 3, 4, 5, 7, 8, 9};
    const int rows[8] = {256, 1024, 256, 256, 256, 256, 256, 1024};
    const int cols[8] = {1024, 256, 768, 256, 512, 256, 1024, 256};
    for (int i = 0; i < 8; i++) {
        const bool perm = i != 3 && i != 4;
        const cuuint64_t pitch = (cuuint64_t)cols[i] * 2;
        const cuuint64_t dims[5] = {(cuuint64_t)cols[i], 2, 2, 4, (cuuint64_t)rows[i] / 16};
        const cuuint64_t strides[4] = {pitch, pitch * (perm ? 8 : 2), pitch * (perm ? 2 : 4), pitch * 16};
        const cuuint32_t box[5] = {64, 2, 2, 4, 8};
        encode(&p.tm[i], CU_TENSOR_MAP_DATA_TYPE_BFLOAT16, 5, d_in[idx[i]], dims, strides, box, ones, CU_TENSOR_MAP_INTERLEAVE_NONE,
               CU_TENSOR_MAP_SWIZZLE_128B, CU_TENSOR_MAP_L2_PROMOTION_L2_128B, CU_TENSOR_MAP_FLOAT_OOB_FILL_NONE);
        p.w[i] = (const char*)d_in[idx[i]];
    }
    {
        void* kv = nullptr;
        cudaGetSymbolAddress(&kv, g_kvq);
        const cuuint64_t dims[2] = {64, 16384};
        const cuuint64_t strides[1] = {128};
        const cuuint32_t box[2] = {64, 128};
        encode(&p.tm[8], CU_TENSOR_MAP_DATA_TYPE_BFLOAT16, 2, kv, dims, strides, box, ones, CU_TENSOR_MAP_INTERLEAVE_NONE,
               CU_TENSOR_MAP_SWIZZLE_NONE, CU_TENSOR_MAP_L2_PROMOTION_L2_128B, CU_TENSOR_MAP_FLOAT_OOB_FILL_NONE);
    }
    p.x = (const __nv_bfloat16*)d_in[0];
    p.dw = (const __nv_bfloat16*)d_in[6];
    p.out = (__nv_bfloat16*)d_out;
    p.zero = 0;
    conformer_kernel<<<NCTA, NTHREADS, SMEM_LAUNCH>>>(p);
}
```

```cpp
#include <cuda_runtime.h>
#include <cuda_bf16.h>
#include <cuda.h>
#include <stdint.h>

namespace {

constexpr int T_ = 1000;
constexpr int NCTA = 128;
constexpr int NTHREADS = 512;
constexpr int NSLOT = 5;
constexpr int SLOT = 16384;
constexpr int NLOADS = 56;

constexpr uint32_t OFF_RING = 0;
constexpr uint32_t OFF_P = 163840;
constexpr uint32_t OFF_H = 188416;
constexpr uint32_t OFF_MISC = 221184;
constexpr uint32_t OFF_STATS = 229376;
constexpr uint32_t OFF_BARS = 229888;
constexpr uint32_t SMEM_BYTES = 230400;
constexpr uint32_t XCH = 6144;
constexpr uint32_t HCH = 4096;

constexpr int B_FULL = 0, B_EMPTY = 10, B_XA = 20  , B_XB = 24  , B_INB = 27  , B_X2 = 31, B_SR = 32,
              B_RST = 33  , B_RDY = 35  , B_SINK = 41, B_ST = 42;

#define KD2 400u
#define KD3 800u
#define ODELAY 0u
#define QGATE 500u
#define BACKOFF 0u
#define KFS 8
#define KDELAY 300u
#define TURN 0
#define EAGER 0x5555
constexpr int PADROWS = 1040;
constexpr int FS = 8;

struct Params {
    CUtensorMap tm[9];
    const char* w[8];
    const __nv_bfloat16* x;
    const __nv_bfloat16* dw;
    __nv_bfloat16* out;
    uint32_t zero;
};

__device__ __align__(1024) unsigned char g_kvq[3 * 8 * 1024 * 128];
__device__ __align__(1024) unsigned char g_o[8 * PADROWS * 128];
__device__ uint4 g_halo[64 * 4 * 2 * 64];
__device__ __align__(128) uint32_t g_flag_kv[8 * 32 * KFS];
__device__ uint32_t g_reset[4 * 32];
__device__ uint32_t g_epoch[NCTA * FS];

#define TS(i) do { } while (0)
#define TSW(i) do { } while (0)
#define TG(i) do { } while (0)
#define TSINIT() do { } while (0)
#define TSDUMP() do { } while (0)
constexpr uint32_t SMEM_LAUNCH = SMEM_BYTES;

__device__ __forceinline__ uint32_t smem_u32(const void* p) { return (uint32_t)__cvta_generic_to_shared(p); }
__device__ __forceinline__ void mbar_init(uint32_t b, uint32_t c) { asm volatile("mbarrier.init.shared::cta.b64 [%0], %1;" ::"r"(b), "r"(c) : "memory"); }
__device__ __forceinline__ void mbar_arrive(uint32_t b) { asm volatile("mbarrier.arrive.shared::cta.b64 _, [%0];" ::"r"(b) : "memory"); }
__device__ __forceinline__ void mbar_arrive_tx(uint32_t b, uint32_t tx) { asm volatile("mbarrier.arrive.expect_tx.shared::cta.b64 _, [%0], %1;" ::"r"(b), "r"(tx) : "memory"); }
__device__ __forceinline__ void mbar_wait(uint32_t b, uint32_t ph) {
    asm volatile("{\n.reg .pred p, q;\n.reg .u32 c;\nmov.u32 c, 0;\n"
                 "MW_LOOP:\n.pragma \"nounroll\";\n"
                 "mbarrier.try_wait.parity.shared::cta.b64 p, [%0], %1;\n"
                 "add.u32 c, c, 1;\nsetp.lt.u32 q, c, 65536;\nnot.pred p, p;\nand.pred p, p, q;\n@p bra MW_LOOP;\n}"
                 ::"r"(b), "r"(ph) : "memory");
}
__device__ __forceinline__ bool mbar_test(uint32_t b, uint32_t ph) {
    uint32_t ok;
    asm volatile("{\n.reg .pred p;\nmbarrier.test_wait.parity.shared::cta.b64 p, [%1], %2;\nselp.u32 %0, 1, 0, p;\n}" : "=r"(ok) : "r"(b), "r"(ph) : "memory");
    return ok;
}
__device__ __forceinline__ uint32_t mapa(uint32_t a, uint32_t r) { uint32_t o; asm("mapa.shared::cluster.u32 %0, %1, %2;" : "=r"(o) : "r"(a), "r"(r)); return o; }
__device__ __forceinline__ void fence_async_smem() { asm volatile("fence.proxy.async.shared::cta;" ::: "memory"); }
__device__ __forceinline__ void fence_async_global() { asm volatile("fence.proxy.async.global;" ::: "memory"); }
__device__ __forceinline__ void bar_sync(int id, int n) { asm volatile("bar.sync %0, %1;" ::"r"(id), "r"(n) : "memory"); }
__device__ __forceinline__ void bar_arrive(int id, int n) { asm volatile("bar.arrive %0, %1;" ::"r"(id), "r"(n) : "memory"); }
__device__ __forceinline__ void cluster_arrive() { asm volatile("barrier.cluster.arrive.relaxed.aligned;" ::: "memory"); }
__device__ __forceinline__ void cluster_wait() { asm volatile("barrier.cluster.wait.aligned;" ::: "memory"); }

__device__ __forceinline__ void ring_load(uint32_t dst, const CUtensorMap* tm, int col, int row16, uint32_t bar) {
    asm volatile("{\n.reg .pred p;\nelect.sync _|p, 0xffffffff;\n"
                 "@p mbarrier.arrive.expect_tx.shared::cta.b64 _, [%2], 16384;\n"
                 "@p cp.async.bulk.tensor.5d.shared::cluster.global.mbarrier::complete_tx::bytes [%0], [%1, {%3, 0, 0, 0, %4}], [%2];\n}"
                 ::"r"(dst), "l"(tm), "r"(bar), "r"(col), "r"(row16) : "memory");
}
__device__ __forceinline__ void ring_load_both(uint32_t dst, const CUtensorMap* tm, int c1, uint32_t bar) {
    asm volatile("{\n.reg .pred p;\nelect.sync _|p, 0xffffffff;\n"
                 "@p cp.async.bulk.tensor.2d.shared::cluster.global.mbarrier::complete_tx::bytes.multicast::cluster [%0], [%1, {0, %3}], [%2], %4;\n}"
                 ::"r"(dst), "l"(tm), "r"(bar), "r"(c1), "h"((uint16_t)3) : "memory");
}
__device__ __forceinline__ void mbar_arrive_peer(uint32_t b) { asm volatile("mbarrier.arrive.relaxed.cluster.shared::cluster.b64 _, [%0];" ::"r"(b) : "memory"); }
__device__ __forceinline__ void prefetch_l2(const void* src, uint32_t bytes) {
    asm volatile("cp.async.bulk.prefetch.L2.global [%0], %1;" ::"l"(src), "r"(bytes) : "memory");
}
__device__ __forceinline__ void peer_copy(uint32_t dst, uint32_t src, uint32_t bytes, uint32_t rbar) {
    asm volatile("{\n.reg .pred p;\nelect.sync _|p, 0xffffffff;\n"
                 "@p cp.async.bulk.shared::cluster.shared::cta.mbarrier::complete_tx::bytes [%0], [%1], %2, [%3];\n}"
                 ::"r"(dst), "r"(src), "r"(bytes), "r"(rbar) : "memory");
}
__device__ __forceinline__ void st_async4(uint32_t dst, uint32_t a, uint32_t b, uint32_t c, uint32_t d, uint32_t bar) {
    asm volatile("st.async.shared::cluster.mbarrier::complete_tx::bytes.v4.b32 [%0], {%1,%2,%3,%4}, [%5];" ::"r"(dst), "r"(a), "r"(b), "r"(c), "r"(d), "r"(bar) : "memory");
}
__device__ __forceinline__ void st_async2f(uint32_t dst, float a, float b, uint32_t bar) {
    asm volatile("st.async.shared::cluster.mbarrier::complete_tx::bytes.v2.f32 [%0], {%1,%2}, [%3];" ::"r"(dst), "f"(a), "f"(b), "r"(bar) : "memory");
}
__device__ __forceinline__ void stsm4t(uint32_t a, uint32_t r0, uint32_t r1, uint32_t r2, uint32_t r3) {
    asm volatile("stmatrix.sync.aligned.m8n8.x4.trans.shared.b16 [%0], {%1,%2,%3,%4};" ::"r"(a), "r"(r0), "r"(r1), "r"(r2), "r"(r3) : "memory");
}
__device__ __forceinline__ void stsm4(uint32_t a, uint32_t r0, uint32_t r1, uint32_t r2, uint32_t r3) {
    asm volatile("stmatrix.sync.aligned.m8n8.x4.shared.b16 [%0], {%1,%2,%3,%4};" ::"r"(a), "r"(r0), "r"(r1), "r"(r2), "r"(r3) : "memory");
}
__device__ __forceinline__ void ldsm4t(uint32_t a, uint32_t& r0, uint32_t& r1, uint32_t& r2, uint32_t& r3) {
    asm volatile("ldmatrix.sync.aligned.m8n8.x4.trans.shared.b16 {%0,%1,%2,%3}, [%4];" : "=r"(r0), "=r"(r1), "=r"(r2), "=r"(r3) : "r"(a) : "memory");
}
__device__ __forceinline__ void ldsm4(uint32_t a, uint32_t& r0, uint32_t& r1, uint32_t& r2, uint32_t& r3) {
    asm volatile("ldmatrix.sync.aligned.m8n8.x4.shared.b16 {%0,%1,%2,%3}, [%4];" : "=r"(r0), "=r"(r1), "=r"(r2), "=r"(r3) : "r"(a) : "memory");
}
__device__ __forceinline__ uint4 lds128(uint32_t a) { uint4 v; asm volatile("ld.shared.v4.b32 {%0,%1,%2,%3}, [%4];" : "=r"(v.x), "=r"(v.y), "=r"(v.z), "=r"(v.w) : "r"(a) : "memory"); return v; }
__device__ __forceinline__ float4 lds128f(uint32_t a) { float4 v; asm volatile("ld.shared.v4.f32 {%0,%1,%2,%3}, [%4];" : "=f"(v.x), "=f"(v.y), "=f"(v.z), "=f"(v.w) : "r"(a) : "memory"); return v; }
__device__ __forceinline__ float2 lds64f(uint32_t a) { float2 v; asm volatile("ld.shared.v2.f32 {%0,%1}, [%2];" : "=f"(v.x), "=f"(v.y) : "r"(a) : "memory"); return v; }
__device__ __forceinline__ uint32_t lds32(uint32_t a) { uint32_t v; asm volatile("ld.shared.b32 %0, [%1];" : "=r"(v) : "r"(a) : "memory"); return v; }
__device__ __forceinline__ void sts128(uint32_t a, uint32_t x, uint32_t y, uint32_t z, uint32_t w) { asm volatile("st.shared.v4.b32 [%0], {%1,%2,%3,%4};" ::"r"(a), "r"(x), "r"(y), "r"(z), "r"(w) : "memory"); }
__device__ __forceinline__ void sts128f(uint32_t a, float x, float y, float z, float w) { asm volatile("st.shared.v4.f32 [%0], {%1,%2,%3,%4};" ::"r"(a), "f"(x), "f"(y), "f"(z), "f"(w) : "memory"); }
__device__ __forceinline__ void sts64f(uint32_t a, float x, float y) { asm volatile("st.shared.v2.f32 [%0], {%1,%2};" ::"r"(a), "f"(x), "f"(y) : "memory"); }
__device__ __forceinline__ void sts32(uint32_t a, uint32_t x) { asm volatile("st.shared.b32 [%0], %1;" ::"r"(a), "r"(x) : "memory"); }
__device__ __forceinline__ void stg128(void* p, uint4 v) { asm volatile("st.global.v4.b32 [%0], {%1,%2,%3,%4};" ::"l"(p), "r"(v.x), "r"(v.y), "r"(v.z), "r"(v.w) : "memory"); }

__device__ __forceinline__ uint32_t pack2(float lo, float hi) { uint32_t r; asm("cvt.rn.bf16x2.f32 %0, %1, %2;" : "=r"(r) : "f"(hi), "f"(lo)); return r; }
__device__ __forceinline__ float blo(uint32_t v) { return __uint_as_float(v << 16); }
__device__ __forceinline__ float bhi(uint32_t v) { return __uint_as_float(v & 0xffff0000u); }
__device__ __forceinline__ uint32_t hmul2(uint32_t a, uint32_t b) { uint32_t r; asm("mul.rn.bf16x2 %0, %1, %2;" : "=r"(r) : "r"(a), "r"(b)); return r; }
__device__ __forceinline__ uint32_t hsub2(uint32_t a, uint32_t b) { uint32_t r; asm("sub.rn.bf16x2 %0, %1, %2;" : "=r"(r) : "r"(a), "r"(b)); return r; }
__device__ __forceinline__ uint32_t hfma2(uint32_t a, uint32_t b, uint32_t c) { uint32_t r; asm("fma.rn.bf16x2 %0, %1, %2, %3;" : "=r"(r) : "r"(a), "r"(b), "r"(c)); return r; }
__device__ __forceinline__ float tanh_fast(float x) { float r; asm("tanh.approx.f32 %0, %1;" : "=f"(r) : "f"(x)); return r; }
__device__ __forceinline__ float rsq(float x) { float r; asm("rsqrt.approx.ftz.f32 %0, %1;" : "=f"(r) : "f"(x)); return r; }
__device__ __forceinline__ float ex2(float x) { float r; asm("ex2.approx.ftz.f32 %0, %1;" : "=f"(r) : "f"(x)); return r; }

__device__ __forceinline__ uint32_t ld_relaxed(const uint32_t* p) {
    uint32_t v;
    asm volatile("ld.relaxed.gpu.global.u32 %0, [%1];" : "=r"(v) : "l"(p) : "memory");
    return v;
}
__device__ __forceinline__ uint32_t clock32() { uint32_t c; asm volatile("mov.u32 %0, %%clock;" : "=r"(c)::"memory"); return c; }
__device__ __forceinline__ void spin(uint32_t clks) {
    const uint32_t t0 = clock32();
    while (clock32() - t0 < clks) {}
}
__device__ __forceinline__ void flag_wait(const uint32_t* p, uint32_t e, bool mine) {
#pragma unroll 1
    for (int i = 0; i < (1 << 19); i++) {
        if (mine) mine = ld_relaxed(p) != e;
        if (!__any_sync(~0u, mine)) break;
        if (BACKOFF) spin(BACKOFF);
    }
    asm volatile("fence.acquire.gpu;" ::: "memory");
    fence_async_global();
}
__device__ __forceinline__ void st_data(void* p, uint32_t x, uint32_t y, uint32_t z, uint32_t w) {
    asm volatile("st.relaxed.gpu.global.v4.b32 [%0], {%1,%2,%3,%4};" ::"l"(p), "r"(x), "r"(y), "r"(z), "r"(w) : "memory");
}
template <int STRIDE, int N>
__device__ __forceinline__ void ld_data(uint4 (&v)[N], const unsigned char* p) {
    int it = 0;
    bool again;
#pragma unroll 1
    do {
        uint32_t m = 0;
#pragma unroll
        for (int i = 0; i < N; i++)
            asm volatile("ld.relaxed.gpu.global.v4.b32 {%0,%1,%2,%3}, [%4];" : "=r"(v[i].x), "=r"(v[i].y), "=r"(v[i].z), "=r"(v[i].w) : "l"(p + i * STRIDE) : "memory");
#pragma unroll
        for (int i = 0; i < N; i++) m = __vimax3_u32(__vimax3_u32(v[i].x, v[i].y, v[i].z), v[i].w, m);
        again = __any_sync(~0u, m == ~0u) && ++it < (1 << 16);
    } while (again);
}
__device__ __forceinline__ uint32_t ld_epoch() { return ld_relaxed(&g_epoch[blockIdx.x * FS]) + 1; }
__device__ __forceinline__ void flag_set(uint32_t* p, uint32_t e) { asm volatile("st.release.gpu.global.u32 [%0], %1;" ::"l"(p), "r"(e) : "memory"); }

__device__ __forceinline__ uint32_t desc_lo(uint32_t addr) { return ((addr & 0x3FFFF) >> 4) | 0x10000u; }
__device__ __forceinline__ uint64_t mkdesc(uint32_t lo) { return (uint64_t)lo | (0x40000040ull << 32); }
__device__ __forceinline__ void wg_fence() { asm volatile("wgmma.fence.sync.aligned;" ::: "memory"); }
__device__ __forceinline__ void wg_commit() { asm volatile("wgmma.commit_group.sync.aligned;" ::: "memory"); }
template <int N> __device__ __forceinline__ void wg_wait() { asm volatile("wgmma.wait_group.sync.aligned %0;" ::"n"(N) : "memory"); }
template <int N> __device__ __forceinline__ void pin(float (&d)[N]) {
#pragma unroll
    for (int i = 0; i < N; i++) asm volatile("" : "+f"(d[i])::"memory");
}
template <int N> __device__ __forceinline__ void pin(uint32_t (&d)[N]) {
#pragma unroll
    for (int i = 0; i < N; i++) asm volatile("" : "+r"(d[i])::"memory");
}

template <typename Tp, int N> __device__ __forceinline__ void zero(Tp (&d)[N]) {
#pragma unroll
    for (int i = 0; i < N; i++) d[i] = 0;
    pin(d);
}

#define F4(d, i) "+f"(d[i]), "+f"(d[i + 1]), "+f"(d[i + 2]), "+f"(d[i + 3])
#define F16(d, i) F4(d, i), F4(d, i + 4), F4(d, i + 8), F4(d, i + 12)

__device__ __forceinline__ void mma_sp(float (&d)[32], const uint32_t* a, uint64_t b, uint32_t meta, int acc) {
    asm volatile("{.reg .pred p; setp.ne.b32 p, %38, 0;\n"
                 "wgmma.mma_async.sp.sync.aligned.m64n64k32.f32.bf16.bf16 {%0,%1,%2,%3,%4,%5,%6,%7,%8,%9,%10,%11,%12,%13,%14,%15,%16,%17,%18,%19,%20,%21,%22,%23,%24,%25,%26,%27,%28,%29,%30,%31}, "
                 "{%32,%33,%34,%35}, %36, %37, 0, p, 1, 1, 1;}\n"
                 : F16(d, 0), F16(d, 16) : "r"(a[0]), "r"(a[1]), "r"(a[2]), "r"(a[3]), "l"(b), "r"(meta), "r"(acc));
}
__device__ __forceinline__ void mma_t(float (&d)[24], uint64_t a, uint64_t b, int acc) {
    asm volatile("{.reg .pred p; setp.ne.b32 p, %26, 0;\n"
                 "wgmma.mma_async.sync.aligned.m64n48k16.f32.bf16.bf16 {%0,%1,%2,%3,%4,%5,%6,%7,%8,%9,%10,%11,%12,%13,%14,%15,%16,%17,%18,%19,%20,%21,%22,%23}, %24, %25, p, 1, 1, 1, 0;}\n"
                 : F16(d, 0), F4(d, 16), F4(d, 20) : "l"(a), "l"(b), "r"(acc));
}
__device__ __forceinline__ void mma_qk(float (&d)[32], uint32_t a0, uint32_t a1, uint32_t a2, uint32_t a3, uint64_t b, int acc) {
    asm volatile("{.reg .pred p; setp.ne.b32 p, %37, 0;\n"
                 "wgmma.mma_async.sync.aligned.m64n64k16.f32.bf16.bf16 {%0,%1,%2,%3,%4,%5,%6,%7,%8,%9,%10,%11,%12,%13,%14,%15,%16,%17,%18,%19,%20,%21,%22,%23,%24,%25,%26,%27,%28,%29,%30,%31}, "
                 "{%32,%33,%34,%35}, %36, p, 1, 1, 0;}\n"
                 : F16(d, 0), F16(d, 16) : "r"(a0), "r"(a1), "r"(a2), "r"(a3), "l"(b), "r"(acc));
}
__device__ __forceinline__ void mma_pv(float (&d)[36], uint32_t a0, uint32_t a1, uint32_t a2, uint32_t a3, uint64_t b) {
    asm volatile("wgmma.mma_async.sync.aligned.m64n72k16.f32.bf16.bf16 {%0,%1,%2,%3,%4,%5,%6,%7,%8,%9,%10,%11,%12,%13,%14,%15,%16,%17,%18,%19,%20,%21,%22,%23,%24,%25,%26,%27,%28,%29,%30,%31,%32,%33,%34,%35}, "
                 "{%36,%37,%38,%39}, %40, 1, 1, 1, 1;\n"
                 : F16(d, 0), F16(d, 16), F4(d, 32) : "r"(a0), "r"(a1), "r"(a2), "r"(a3), "l"(b));
}

__device__ __forceinline__ uint32_t load_code(int n, int r, int w) {
    const int tile = 2 * r + w;
    int m, col, row;
    if (n < 16 || n >= 40) {
        const int k = n < 16 ? n : n - 40;
        m = n < 16 ? 0 : 6;
        if (k < 8) { col = 4 * tile + (k >> 1); row = (k & 1) ^ r; }
        else { m++; col = tile ^ (3 - ((k - 8) >> 1)); row = 2 * tile + (k & 1); }
    } else if (n < 32) {
        const int k = n - 16;
        m = 2;
        if (k < 4) { col = tile + ((k & 1) ? 8 : 4); row = (k >> 1) ^ r; }
        else { col = tile; row = (k & 1) ^ r; }
    } else if (n < 34) { m = 3; col = tile; row = n - 32; }
    else if (n < 38) { const int k = n - 34; m = 4; col = tile + 4 * (k & 1); row = (k >> 1) ^ r; }
    else { m = 5; col = tile; row = (n & 1) ^ r; }
    return m | (col << 4) | (row << 8);
}

__global__ void __cluster_dims__(2, 1, 1) __launch_bounds__(NTHREADS, 1)
conformer_kernel(const __grid_constant__ Params p) {
    extern __shared__ __align__(1024) unsigned char smem_raw[];
    const uint32_t sb = smem_u32(smem_raw);
    const uint32_t bars = sb + OFF_BARS;
    const int tid = threadIdx.x;
    const int lane = tid & 31;
    const int warp = __shfl_sync(~0u, tid >> 5, 0);
    const int r = blockIdx.x & 1;
    const int pair = blockIdx.x >> 1;
    const int b = pair >> 5, pt = pair & 31;
    const int ah = pt >> 3, qt = (pt & 7) * 2 + r;
    const int abh = b * 4 + ah;

    TG(30);
    TSINIT();
    TS(0);
    const uint32_t P = sb + OFF_P, H = sb + OFF_H;

    if (warp >= 8) {
        asm volatile("setmaxnreg.dec.sync.aligned.u32 48;");
        if (warp >= 12) {
            cluster_arrive();
            cluster_wait();
            const int ut = tid & 127;
            const uint32_t target = ld_epoch() * 64;
            auto reset_done = [&](int k) {
                bar_sync(11, 128);
                if (ut == 0) {
                    asm volatile("red.release.gpu.global.add.u32 [%0], 1;" ::"l"(&g_reset[(2 * b + k) * 32]) : "memory");
#pragma unroll 1
                    for (int i = 0; i < (1 << 20) && ld_relaxed(&g_reset[(2 * b + k) * 32]) != target; i++) __nanosleep(100);
                    asm volatile("fence.acquire.gpu;" ::: "memory");
                    mbar_arrive(bars + (B_RST + k) * 8);
                }
                __syncwarp();
                TS(13 + k);
            };
#pragma unroll
            for (int i = 0; i < 4; i++) {
                st_data(g_kvq + 2097152 + (size_t)((b * 4 + 2 * r + (i >> 1)) * 1024 + pt * 32) * 128 + (i & 1) * 2048 + ut * 16, ~0u, ~0u, ~0u, ~0u);
                if (i < 2) st_data(&g_halo[(pair * 4 + 2 * r + i) * 128 + ut], ~0u, ~0u, ~0u, ~0u);
            }
            reset_done(0);
            bar_sync(6, 384);
#pragma unroll
            for (int i = 0; i < 4; i++) st_data(g_o + (size_t)(abh * PADROWS + 8 + qt * 64) * 128 + i * 2048 + ut * 16, ~0u, ~0u, ~0u, ~0u);
            reset_done(1);
            {
                const int side = warp & 1, t = 2 * r + ((warp >> 1) & 1), np = side ? pt + 1 : pt - 1;
                uint4 hv[2] = {make_uint4(0, 0, 0, 0), make_uint4(0, 0, 0, 0)};
                if (np >= 0 && np < 32)
                    ld_data<512>(hv, reinterpret_cast<const unsigned char*>(&g_halo[(((b * 32 + np) * 4 + t) * 2 + (side ^ 1)) * 64 + lane]));
                const uint32_t dst = P + t * XCH + side * 5120 + (lane & 7) * 128 + (((lane >> 3) ^ (lane & 7)) << 4);
                stsm4(dst, hv[0].x, hv[0].y, hv[0].z, hv[0].w);
                stsm4(dst ^ 64, hv[1].x, hv[1].y, hv[1].z, hv[1].w);
                bar_arrive(9, 384);
            }
            const uint32_t a8 = P + (ut >> 3) * 128 + (ut & 7) * 16;
            float s[3] = {0.f, 0.f, 0.f}, q[3] = {0.f, 0.f, 0.f};
#pragma unroll 1
            for (int h = 0; h < 2; h++) {
                if (h == 0) bar_sync(1, 384);
                else mbar_wait(bars + B_X2 * 8, 0);
                uint4 v[6];
#pragma unroll
                for (int i = 0; i < 6; i++) v[i] = lds128(a8 + (2 * (r ^ h) + (i & 1)) * XCH + (i >> 1) * 2048);
                bar_arrive(5 + ((v[0].w | v[1].w | v[2].w | v[3].w | v[4].w | v[5].w) & p.zero), 384);
                uint32_t t;
                asm volatile("mov.u32 %0, %%clock;" : "=r"(t)::"memory");
                const uint32_t mul = 65536u + (t & p.zero), msk = 0u - mul;
#pragma unroll
                for (int i = 0; i < 6; i++) {
                    const float a0 = __uint_as_float(v[i].x * mul), a1 = __uint_as_float(v[i].x & msk), a2 = __uint_as_float(v[i].y * mul), a3 = __uint_as_float(v[i].y & msk);
                    const float a4 = __uint_as_float(v[i].z * mul), a5 = __uint_as_float(v[i].z & msk), a6 = __uint_as_float(v[i].w * mul), a7 = __uint_as_float(v[i].w & msk);
                    s[i >> 1] += ((a0 + a1) + (a2 + a3)) + ((a4 + a5) + (a6 + a7));
                    q[i >> 1] += fmaf(a0, a0, fmaf(a1, a1, fmaf(a2, a2, a3 * a3))) + fmaf(a4, a4, fmaf(a5, a5, fmaf(a6, a6, a7 * a7)));
                }
            }
#pragma unroll
            for (int o = 1; o < 8; o <<= 1) {
#pragma unroll
                for (int i = 0; i < 3; i++) { s[i] += __shfl_xor_sync(~0u, s[i], o); q[i] += __shfl_xor_sync(~0u, q[i], o); }
            }
            const int k = ut & 7, row = (ut >> 3) + 16 * k;
            const float mean = (k == 0 ? s[0] : (k == 1 ? s[1] : s[2])) * (1.f / 256.f);
            const float msq = (k == 0 ? q[0] : (k == 1 ? q[1] : q[2])) * (1.f / 256.f);
            const float alpha = (uint32_t)(pt * 32 - 8 + row) >= T_ ? 0.f : 0.5f;
            const float rstd = alpha * rsq(fmaxf(fmaf(-mean, mean, msq), 0.f) + 1e-5f);
            if (k < 3) sts64f(sb + OFF_STATS + row * 8, mean * rstd, rstd);
            __syncwarp();
            if (lane == 0) mbar_arrive(bars + B_ST * 8);
            TS(4);
        } else if (warp < 10) {
            const int w = warp - 8;
            const uint32_t ring = sb + OFF_RING + w * NSLOT * SLOT;
            const uint32_t full = bars + (B_FULL + w * NSLOT) * 8;
            if (lane == 0) {
#pragma unroll
                for (int i = 0; i < NSLOT; i++) { mbar_init(full + i * 8, 1); mbar_init(full + (B_EMPTY - B_FULL + i) * 8, 4); }
                asm volatile("fence.mbarrier_init.release.cluster;" ::: "memory");
                fence_async_smem();
            }
            __syncwarp();
            cluster_arrive();
            TS(1);
#pragma unroll
            for (int n = 0; n < NSLOT; n++) {
                if (n == 1 || n == 2) bar_sync(12, 64);
                ring_load(ring + n * SLOT, &p.tm[0], 64 * (8 * r + 4 * w + (n >> 1)), 8 * ((n & 1) ^ r), full + n * 8);
            }
            TS(2);
            const uint32_t code = load_code(lane, r, w) | (load_code(lane + 32, r, w) << 16);
            cluster_wait();
            uint32_t s = 0, ph = 0;
            int n = NSLOT;
#pragma unroll 1
            for (int seg = 0; seg < 2; seg++) {
#pragma unroll 1
                for (; n < (seg == 0 ? 22 : NLOADS); n++) {
                    const uint32_t c = __shfl_sync(~0u, code, n) >> (n & 32 ? 16 : 0);
                    const CUtensorMap* tm = &p.tm[c & 15];
                    const uint32_t col = (c & 0xf0) * 4, row = (c & 0xff00) >> 5, dst = ring + s * SLOT;
                    mbar_wait(full + (B_EMPTY - B_FULL) * 8 + s * 8, ph + (((uint32_t)(size_t)tm | col | row | dst) & p.zero));
                    ring_load(dst, tm, col, row, full + s * 8);
                    if (++s == NSLOT) { s = 0; ph ^= 1; }
                }
                if (seg == 1) break;
                const uint32_t epoch = ld_epoch();
                const uint32_t rdy = bars + (B_RDY + 3 * w) * 8, prdy = mapa(rdy, r ^ 1);
                const int odd = r ^ w;
                const uint32_t* flags = g_flag_kv + (abh * 32 + lane) * KFS;
                auto kv_load = [&](uint32_t sl, int isv, int i) {
                    ring_load_both(ring + sl * SLOT, &p.tm[8], (isv * 64 + abh * 8 + 2 * i + w) * 128, full + sl * 8);
                };
#pragma unroll 1
                for (int i = 0; i < 2; i++) {
                    if (lane < 3 + i) {
                        const uint32_t sl = i ? lane : lane + 2;
                        mbar_wait(full + (B_EMPTY - B_FULL + sl) * 8, i ^ 1);
                        mbar_arrive_tx(full + sl * 8, (i || lane == 2) ? SLOT : 0);
                    }
                    __syncwarp();
                }
                if (lane == 0) mbar_arrive_peer(prdy);
                bar_sync(14, 96);
                spin(KDELAY);
                mbar_wait(rdy, 0);
                flag_wait(flags, epoch, (lane >> 2) == 2 * odd + w);
                TSW(5 + 2 * odd);
                if (!odd) { kv_load(4, 0, 0); bar_arrive(12, 64); }
                else bar_sync(12, 64);
                spin(w ? KD3 : KD2);
                kv_load(odd ^ 1, odd ^ 1, odd);
                flag_wait(flags, epoch, (lane >> 2) == 2 * odd + w + 4);
                mbar_wait(full + (odd ^ 1) * 8, 1);
                kv_load(2 + odd, odd, 2 - odd);
#pragma unroll 1
                for (int i = 0; i < 3; i++) {
                    const uint32_t sl = i ? i - 1 : 4, bo = i == 2 ? 16 : 8;
                    mbar_wait(full + (B_EMPTY - B_FULL + sl) * 8, i != 0);
                    if (lane == 0) mbar_arrive_tx(full + sl * 8, SLOT);
                    if ((i & 1) != odd) {
                        mbar_wait(rdy + bo, 0);
                        kv_load(sl, i != 0, 2 + odd);
                    } else if (lane == 0) mbar_arrive_peer(prdy + bo);
                    __syncwarp();
                }
                n = 32; s = 2; ph = 1;
            }
        } else if (warp == 10) {
            if (lane == 0) {
#pragma unroll
                for (int i = B_XA; i <= B_ST; i++) mbar_init(bars + i * 8, i == B_ST ? 4 : 1);
#pragma unroll
                for (int i = B_XA; i <= B_SR; i++) mbar_arrive_tx(bars + i * 8, i < B_XB ? 512 : (i == B_X2 ? 12288 : 8192));
                asm volatile("fence.mbarrier_init.release.cluster;" ::: "memory");
                fence_async_smem();
            }
            __syncwarp();
            cluster_arrive();
            cluster_wait();
        } else {
            const uint32_t kb = (lane < 2 || lane > 5) ? 4096 : (lane == 2 ? 3072 : (lane == 4 ? 2048 : 1024));
            const char* pf = p.w[lane & 7] + blockIdx.x * kb;
            cluster_arrive();
            cluster_wait();
            if (lane < 2) prefetch_l2(pf, kb);
            mbar_wait(bars + B_XA * 8, 0);
            if (lane == 2) prefetch_l2(pf, kb);
            if (lane >= 1 && lane < 9) asm volatile("prefetch.tensormap [%0];" ::"l"(&p.tm[lane]) : "memory");
            mbar_wait(bars + (B_FULL + 1) * 8, 1);
            if (lane > 2 && lane < 8) prefetch_l2(pf, kb);
            if (lane == 8 && blockIdx.x < 15) prefetch_l2(p.dw + blockIdx.x * 256, 512);
            const uint32_t epoch = ld_epoch();
            bar_sync(4, 288);
            if (lane < 16) flag_set(&g_flag_kv[((b * 4 + 2 * r + (lane >> 3)) * 32 + pt) * KFS + (lane & 7)], epoch);
            __syncwarp();
            bar_arrive(14, 96);
            TSW(8);
        }
        TSDUMP();
        return;
    }

    const int w = warp >> 2, wq = warp & 3;
    const int tile = 2 * r + w;
    const int wt = tid & 127;
    const int c4 = lane & 3;
    const int trow = pt * 32 + 8 * wq;
    uint32_t xr[8];
    {
        const uint32_t* xp = reinterpret_cast<const uint32_t*>(p.x + (size_t)(b * T_ + trow + (lane >> 2)) * 256 + tile * 64) + c4;
#pragma unroll
        for (int j = 0; j < 8; j++) xr[j] = trow < T_ ? __ldg(xp + 4 * j) : 0u;
    }
    cluster_arrive();
    asm volatile("setmaxnreg.inc.sync.aligned.u32 208;");
    const uint32_t rbase = sb + OFF_RING + w * NSLOT * SLOT, fbar = bars + (B_FULL + w * NSLOT) * 8;
    const uint32_t rdesc = desc_lo(rbase);
    auto acq = [&](int n) { mbar_wait(fbar + (n % NSLOT) * 8, (n / NSLOT) & 1); };
    auto rel = [&](int n) { if (lane == 0) mbar_arrive(fbar + (B_EMPTY - B_FULL + n % NSLOT) * 8); };
    const uint32_t foff = (lane & 7) * 128 + (((lane >> 3) ^ (lane & 7)) << 4);
    const uint32_t toff = ((lane >> 4) * 8 + (lane & 7)) * 128 + (((2 * wq + ((lane >> 3) & 1)) ^ (lane & 7)) << 4);
    auto publish = [&](int bar, uint32_t src, uint32_t bytes, int nsync) {
        fence_async_smem();
        bar_sync(2 + w, 128);
        if (wq == 0) peer_copy(mapa(src, r ^ 1), src, bytes, mapa(bars + bar * 8, r ^ 1));
        bar_sync(nsync == 384 ? 1 : 10, nsync);
    };
    float v[16];
#pragma unroll
    for (int j = 0; j < 8; j++) { v[2 * j] = blo(xr[j]); v[2 * j + 1] = bhi(xr[j]); }
    const uint32_t xown = __shfl_sync(~0u, P + wt * 16 + tile * 4096, lane), xrem = __shfl_sync(~0u, P + wt * 16 + (r ^ 1) * 8192, lane);
    const uint32_t sbuf = __shfl_sync(~0u, sb + OFF_MISC + 1024 + (8 * wq + (lane >> 2)) * 32, lane);
    const uint32_t sown = __shfl_sync(~0u, sbuf + tile * 8, lane);
    const uint32_t peer = __shfl_sync(~0u, mapa(sb, r ^ 1) - sb, lane);
    const uint32_t meta = __shfl_sync(~0u, 0xEEEE4444u + p.zero, lane);
    cluster_wait();
    TS(56);
    float mean, msq;

#pragma unroll 1
    for (int ph = 0;; ph++) {
        uint4 o0, o1;
        {
            float s = 0.f, q = 0.f, s2 = 0.f, q2 = 0.f;
#pragma unroll
            for (int j = 0; j < 4; j++) {
                s += v[4 * j] + v[4 * j + 1]; s2 += v[4 * j + 2] + v[4 * j + 3];
                q += fmaf(v[4 * j], v[4 * j], v[4 * j + 1] * v[4 * j + 1]); q2 += fmaf(v[4 * j + 2], v[4 * j + 2], v[4 * j + 3] * v[4 * j + 3]);
            }
            s += s2; q += q2;
            const uint32_t xa = bars + (B_XA + ph) * 8;
            s += __shfl_xor_sync(~0u, s, 1); q += __shfl_xor_sync(~0u, q, 1);
            s += __shfl_xor_sync(~0u, s, 2); q += __shfl_xor_sync(~0u, q, 2);
            if (c4 == 0) st_async2f(sown + peer, s, q, xa + peer);
            if (c4 == 0) sts64f(sown, s, q);
#pragma unroll
            for (int j = 0; j < 8; j++) xr[j] = pack2(v[2 * j], v[2 * j + 1]);
            sts128(xown, xr[0], xr[1], xr[2], xr[3]);
            sts128(xown + 2048, xr[4], xr[5], xr[6], xr[7]);
            bar_sync(10, 256);
            o0 = lds128(xown ^ 4096); o1 = lds128((xown ^ 4096) + 2048);
            if (ph < 3) {
                st_async4(xown + peer, xr[0], xr[1], xr[2], xr[3], xa + (B_XB - B_XA) * 8 + peer);
                st_async4(xown + peer + 2048, xr[4], xr[5], xr[6], xr[7], xa + (B_XB - B_XA) * 8 + peer);
            }
            TS(57 + ph);
            if (ph == 0) acq(0);
            mbar_wait(xa, 0);
            const float4 u0 = lds128f(sbuf), u1 = lds128f(sbuf + 16);
            mean = ((u0.x + u0.z) + (u1.x + u1.z)) * (1.f / 256.f);
            msq = ((u0.y + u0.w) + (u1.y + u1.w)) * (1.f / 256.f);
        }
        if (ph == 3) break;
        uint32_t a[32];
        const uint32_t mean2 = pack2(mean, mean);
        auto centre = [&](int i, const uint4& u) {
            a[i] = hsub2(u.x, mean2); a[i + 1] = hsub2(u.y, mean2); a[i + 2] = hsub2(u.z, mean2); a[i + 3] = hsub2(u.w, mean2);
        };
#pragma unroll
        for (int j = 0; j < 8; j++) a[j] = hsub2(xr[j], mean2);
        centre(8, o0); centre(12, o1);
        const float rstd = rsq(fmaxf(fmaf(-mean, mean, msq), 0.f) + 1e-5f);
        auto gather_peer = [&]() {
            mbar_wait(bars + (B_XB + ph) * 8, 0);
#pragma unroll
            for (int i = 0; i < 4; i++) centre(16 + 4 * i, lds128(xrem + i * 2048));
        };
        auto sp = [&](float (&d)[32], int n, const uint32_t* af, int flip, int acc) {
            const uint32_t lo = rdesc + p.zero * (ph + n + 1) + (n % NSLOT) * (SLOT >> 4);
            const uint64_t b0 = mkdesc(lo + flip * 512), b1 = mkdesc(lo + (flip ^ 1) * 512);
            wg_fence();
            mma_sp(d, af, b0, meta, acc);
            mma_sp(d, af + 4, b0 + 256, meta, 1);
            mma_sp(d, af + 8, b1, meta, 1);
            mma_sp(d, af + 12, b1 + 256, meta, 1);
            wg_commit();
        };
        float d0[32], d1[32];

        if (ph != 1) {
            uint32_t h[32];
            const float rs = 0.5f * rstd;
            const uint32_t inb = bars + (B_INB + ph) * 8, box = H + wt * 16;
            bool ready = true;
            auto step = [&](float (&d)[32], int n, const uint32_t* af, int flip, int acc, auto work) {
                if (!ready) acq(n);
                if (((TURN >> n) & 1) && w == 1) bar_sync(7, 256);
                sp(d, n, af, flip, acc);
                if (n > 0 && ((TURN >> (n - 1)) & 1) && w == 0) bar_arrive(7, 256);
                if (n < 15) ready = mbar_test(fbar + ((n + 1) % NSLOT) * 8, ((n + 1) / NSLOT) & 1);
                wg_wait<1>();
                if (n > 0 && !((EAGER >> (n - 1)) & 1)) rel(n - 1);
                const uint32_t tie = work() & p.zero;
                if ((EAGER >> n) & 1) {
                    if (p.zero < n + ph + 1) wg_wait<0>();
                    if (lane == 0) mbar_arrive(fbar + (B_EMPTY - B_FULL + n % NSLOT) * 8 + tie);
                }
            };
            auto none = []() { return 0u; };
            auto act = [&](float (&d)[32], int i) {
                pin(d);
#pragma unroll
                for (int j = 0; j < 8; j++) {
                    const float u0 = (d[4 * j] + d[4 * j + 2]) * rs, u1 = (d[4 * j + 1] + d[4 * j + 3]) * rs;
                    h[8 * i + j] = pack2(fmaf(u0, tanh_fast(u0), u0), fmaf(u1, tanh_fast(u1), u1));
                }
                return h[8 * i] | h[8 * i + 1] | h[8 * i + 2] | h[8 * i + 3] | h[8 * i + 4] | h[8 * i + 5] | h[8 * i + 6] | h[8 * i + 7];
            };
            auto send = [&](float (&d)[32], int x) {
                pin(d);
                uint32_t pk[8];
#pragma unroll
                for (int j = 0; j < 8; j++) pk[j] = pack2(d[4 * j] + d[4 * j + 2], d[4 * j + 1] + d[4 * j + 3]);
                const uint32_t ow = w ^ (x & 1), dst = box + (ow * 3 + x - 1) * 4096;
                if (x & 2) {
                    st_async4(dst + peer, pk[0], pk[1], pk[2], pk[3], inb + ow * 8 + peer);
                    st_async4(dst + peer + 2048, pk[4], pk[5], pk[6], pk[7], inb + ow * 8 + peer);
                } else {
                    sts128(dst, pk[0], pk[1], pk[2], pk[3]);
                    sts128(dst + 2048, pk[4], pk[5], pk[6], pk[7]);
                }
            };
            TS(1 + ph * 10);
            step(d0, 0, a, w, 0, [&]() { gather_peer(); return 0u; });
            TS(32);
            step(d0, 1, a + 16, 0, 1, none);
            step(d1, 2, a, w, 0, [&]() { return act(d0, 0); });
            step(d1, 3, a + 16, 0, 1, none);
            step(d0, 4, a, w, 0, [&]() { return act(d1, 1); });
            TS(33);
            step(d0, 5, a + 16, 0, 1, none);
            step(d1, 6, a, w, 0, [&]() { return act(d0, 2); });
            step(d1, 7, a + 16, 0, 1, none);
            step(d0, 8, h, 0, 0, [&]() { return act(d1, 3); });
            TS(2 + ph * 10);
            step(d0, 9, h + 16, 0, 1, none);
            step(d1, 10, h, 0, 0, [&]() { send(d0, 3); return 0u; });
            step(d1, 11, h + 16, 0, 1, none);
            step(d0, 12, h, 0, 0, [&]() { send(d1, 2); return 0u; });
            TS(34);
            step(d0, 13, h + 16, 0, 1, none);
            step(d1, 14, h, 0, 0, [&]() { send(d0, 1); return 0u; });
            step(d1, 15, h + 16, 0, 1, none);
            if (ph == 0) acq(16);
            mbar_wait(inb + w * 8, 0);
            bar_sync(10, 256);
#pragma unroll
            for (int i = 0; i < 2; i++) {
                const uint32_t src = box + w * 12288 + i * 2048;
                const uint4 u0 = lds128(src), u1 = lds128(src + 4096), u2 = lds128(src + 8192);
                const uint32_t p0[4] = {u0.x, u0.y, u0.z, u0.w}, p1[4] = {u1.x, u1.y, u1.z, u1.w}, p2[4] = {u2.x, u2.y, u2.z, u2.w};
#pragma unroll
                for (int j = 0; j < 4; j++) {
                    v[8 * i + 2 * j] = fmaf(0.5f, blo(p0[j]) + blo(p1[j]) + blo(p2[j]), blo(xr[4 * i + j]));
                    v[8 * i + 2 * j + 1] = fmaf(0.5f, bhi(p0[j]) + bhi(p1[j]) + bhi(p2[j]), bhi(xr[4 * i + j]));
                }
            }
            wg_wait<0>();
            pin(d1);
            rel(15);
            TS(3 + ph * 10);
#pragma unroll
            for (int j = 0; j < 8; j++) {
                v[2 * j] = fmaf(0.5f, d1[4 * j] + d1[4 * j + 2], v[2 * j]);
                v[2 * j + 1] = fmaf(0.5f, d1[4 * j + 1] + d1[4 * j + 3], v[2 * j + 1]);
            }
            continue;
        }

        {
            TS(11);
            const uint32_t stg = H + warp * 2048;
            unsigned char* g = g_kvq + (size_t)((b * 4 + tile) * 1024 + trow) * 128 + lane * 16;
            auto put = [&](float (&d)[32], int i) {
                pin(d);
                uint32_t pk[8];
#pragma unroll
                for (int j = 0; j < 8; j++) pk[j] = pack2((d[4 * j] + d[4 * j + 2]) * rstd, (d[4 * j + 1] + d[4 * j + 3]) * rstd);
                if (i == 2) {
                    st_data(g + 2097152, pk[0], pk[1], pk[2], pk[3]);
                    st_data(g + 2097152 + 512, pk[4], pk[5], pk[6], pk[7]);
                    return;
                }
                stsm4(stg + i * 1024 + foff, pk[0], pk[1], pk[2], pk[3]);
                stsm4(stg + i * 1024 + (foff ^ 64), pk[4], pk[5], pk[6], pk[7]);
                __syncwarp();
                const uint4 u0 = lds128(stg + i * 1024 + lane * 16), u1 = lds128(stg + i * 1024 + 512 + lane * 16);
                stg128(g + i * 1048576, u0); stg128(g + i * 1048576 + 512, u1);
            };
            sp(d0, 16, a, w, 0);
            acq(17);
            sp(d1, 17, a, w, 0);
            gather_peer();
            acq(18);
            sp(d0, 18, a + 16, 0, 1);
            wg_wait<1>();
            rel(16); rel(17);
            acq(19);
            sp(d1, 19, a + 16, 0, 1);
            wg_wait<1>();
            rel(18);
            put(d0, 0);
            wg_wait<0>();
            rel(19);
            TS(37);
            put(d1, 1);
            bar_arrive(4, 288);
            TS(38);
            acq(20);
            sp(d0, 20, a, w, 0);
            acq(21);
            sp(d0, 21, a + 16, 0, 1);
            acq(22); acq(23);
            rel(22); rel(23);
            mbar_wait(bars + B_RST * 8, 0);
            wg_wait<0>();
            rel(20); rel(21);
            put(d0, 2);
            if (wq == 0 || wq == 3) {
                uint4* hp = &g_halo[((pair * 4 + tile) * 2 + (wq & 1)) * 64 + lane];
                st_data(hp, xr[0], xr[1], xr[2], xr[3]);
                st_data(hp + 32, xr[4], xr[5], xr[6], xr[7]);
            }
            TS(12);
        }

        const uint32_t xo = P + tile * XCH + wq * 1024, xt = P + tile * XCH + toff;
        {
            constexpr float CS = 0.125f * 1.4426950408889634f;
            float sa[32], sb2[32], o[36];
            uint32_t pa[16], pb[16], q[16];
            float n0 = INFINITY, n1 = INFINITY;
            zero(o); zero(pa); zero(pb); zero(sb2);
            const uint32_t ones = sb + OFF_MISC + 2048;
            if (tid < 128) sts128(ones + tid * 16, 0x3F803F80u, 0x3F803F80u, 0x3F803F80u, 0x3F803F80u);
            fence_async_smem();
            bar_sync(10, 256);
            stsm4(xo + 1024 + foff, xr[0], xr[1], xr[2], xr[3]);
            stsm4(xo + 1024 + (foff ^ 64), xr[4], xr[5], xr[6], xr[7]);
            const uint32_t vdesc = rdesc + ((((ones - rbase) >> 4) - 1) << 16);
            auto qk_issue = [&](float (&s)[32], uint32_t lo) {
                const uint64_t kd = mkdesc(lo);
                wg_fence();
#pragma unroll
                for (int k = 0; k < 4; k++) mma_qk(s, q[4 * k], q[4 * k + 1], q[4 * k + 2], q[4 * k + 3], kd + 2 * k, k != 0);
                wg_commit();
            };
            auto pv_issue = [&](uint32_t (&pp)[16], uint32_t lo) {
                const uint64_t vd = mkdesc(lo);
                wg_fence();
#pragma unroll
                for (int k = 0; k < 4; k++) mma_pv(o, pp[4 * k], pp[4 * k + 1], pp[4 * k + 2], pp[4 * k + 3], vd - k * (128 * 65535));
                wg_commit();
            };
            auto new_max = [&](float (&s)[32], float& x0, float& x1) {
                x0 = s[0]; x1 = s[2];
#pragma unroll
                for (int j = 0; j < 8; j++) {
                    x0 = fmaxf(x0, fmaxf(s[4 * j], s[4 * j + 1]));
                    x1 = fmaxf(x1, fmaxf(s[4 * j + 2], s[4 * j + 3]));
                }
                x0 = fmaxf(x0, __shfl_xor_sync(~0u, x0, 1)); x1 = fmaxf(x1, __shfl_xor_sync(~0u, x1, 1));
                x0 = fmaxf(x0, __shfl_xor_sync(~0u, x0, 2)); x1 = fmaxf(x1, __shfl_xor_sync(~0u, x1, 2));
                x0 = fminf(n0, fmaf(x0, -CS, -20.f)); x1 = fminf(n1, fmaf(x1, -CS, -20.f));
            };
            auto probs = [&](float (&s)[32], uint32_t (&pp)[16], bool ready, auto wait) {
                uint32_t any = 0;
#pragma unroll
                for (int i = 0; i < 16; i++) {
                    pp[i] = pack2(ex2(fmaf(s[2 * i], CS, (i & 1) ? n1 : n0)), ex2(fmaf(s[2 * i + 1], CS, (i & 1) ? n1 : n0)));
                    any |= pp[i];
                }
                wg_wait<0>();
                pin(sa); pin(sb2); pin(o); pin(pa); pin(pb);
                if (__any_sync(~0u, (any & 0x40004000u) || !ready)) {
                    wait();
                    if (__any_sync(~0u, any & 0x40004000u)) {
                        float x0, x1;
                        new_max(s, x0, x1);
                        const float sc0 = ex2(x0 - n0), sc1 = ex2(x1 - n1);
                        n0 = x0; n1 = x1;
#pragma unroll
                        for (int j = 0; j < 9; j++) { o[4 * j] *= sc0; o[4 * j + 1] *= sc0; o[4 * j + 2] *= sc1; o[4 * j + 3] *= sc1; }
#pragma unroll
                        for (int i = 0; i < 16; i++)
                            pp[i] = pack2(ex2(fmaf(s[2 * i], CS, (i & 1) ? n1 : n0)), ex2(fmaf(s[2 * i + 1], CS, (i & 1) ? n1 : n0)));
                    }
                }
            };
            {
                uint4 u[4];
                const unsigned char* src = g_kvq + 2097152 + (size_t)(abh * 1024 + qt * 64 + wq * 16) * 128 + lane * 16;
                spin(QGATE);
                ld_data<512>(u, src);
#pragma unroll
                for (int k = 0; k < 2; k++) {
                    q[8 * k] = u[k].x; q[8 * k + 1] = u[k + 2].x; q[8 * k + 2] = u[k].y; q[8 * k + 3] = u[k + 2].y;
                    q[8 * k + 4] = u[k].z; q[8 * k + 5] = u[k + 2].z; q[8 * k + 6] = u[k].w; q[8 * k + 7] = u[k + 2].w;
                }
                pin(q);
            }
            TS(40);
            acq(24);
            TS(13);
            qk_issue(sa, rdesc + (24 % NSLOT) * (SLOT >> 4));
            wg_wait<0>();
            pin(sa);
            {
                float x0, x1;
                new_max(sa, x0, x1);
                n0 = x0; n1 = x1;
            }
            bar_arrive(6, 384);
            if (w == 1) bar_sync(7, 256);
            uint32_t vd = vdesc - (SLOT >> 4) * 65535u, kd = rdesc, vb = fbar + 8, kb = fbar;
            uint32_t vlast = vdesc - 4 * (SLOT >> 4) * 65535u, klast = rdesc + 4 * (SLOT >> 4) + 512;
            uint32_t kprev = fbar + 32, vprev = bars + (B_SINK - (B_EMPTY - B_FULL)) * 8;
#pragma unroll 1
            for (int it = 0; it < 4; it++) {
                qk_issue(sb2, klast);
                pv_issue(pb, vlast);
                probs(sa, pa, mbar_test(vb, it < 2) & mbar_test(kb, it < 3), [&]() { mbar_wait(vb, it < 2); mbar_wait(kb, it < 3); });
                TS(41 + it * 4);
                if (it == 0 && w == 0) bar_arrive(7, 256);
                if (it == 3 && w == 1) {
#pragma unroll
                    for (int i = 20; i < 32; i++) sb2[i] = -INFINITY;
                }
                pin(sb2);
                if (lane == 0) mbar_arrive(kprev + (B_EMPTY - B_FULL) * 8);
                if (lane == 0) mbar_arrive(vprev + (B_EMPTY - B_FULL) * 8);
                qk_issue(sa, kd);
                pv_issue(pa, vd);
                const int dv = it == 0 ? 2 : (it == 1 ? -3 : 1);
                kprev = kb; vprev = vb; vlast = vd - 512 * 65535u; klast = kd + 512;
                vd -= dv * (SLOT >> 4) * 65535u; vb += dv * 8;
                kd += (it == 2 ? -3 : 2) * (SLOT >> 4); kb = it == 2 ? vb : kb + 16;
                probs(sb2, pb, true, []() {});
                TS(43 + it * 4);
            }
            pv_issue(pb, vlast);
            const int row = wq * 16 + (lane >> 2);
            const uint32_t ml = sb + OFF_MISC;
            mbar_wait(bars + (B_RST + 1) * 8, 0);
            wg_wait<0>();
            pin(o); pin(pb); pin(sa); pin(sb2);
            rel(31);
            const float l0 = o[32], l1 = o[34];
            if (c4 == 0) { sts64f(ml + w * 512 + row * 8, n0, l0); sts64f(ml + w * 512 + row * 8 + 64, n1, l1); }
            TS(14);
            float mine[16];
#pragma unroll
            for (int j = 0; j < 4; j++) {
                if (w == 0) sts128f(H + j * 2048 + wt * 16, o[16 + 4 * j], o[17 + 4 * j], o[18 + 4 * j], o[19 + 4 * j]);
                else sts128f(H + 8192 + j * 2048 + wt * 16, o[4 * j], o[4 * j + 1], o[4 * j + 2], o[4 * j + 3]);
            }
#pragma unroll
            for (int i = 0; i < 16; i++) mine[i] = w == 0 ? o[i] : o[16 + i];
            bar_sync(10, 256);
            const float2 u0 = lds64f(ml + (w ^ 1) * 512 + row * 8), u1 = lds64f(ml + (w ^ 1) * 512 + row * 8 + 64);
            const float x0 = fminf(n0, u0.x), x1 = fminf(n1, u1.x);
            float a0 = ex2(x0 - n0), b0 = ex2(x0 - u0.x), a1 = ex2(x1 - n1), b1 = ex2(x1 - u1.x);
            const float i0 = __fdividef(1.f, fmaf(a0, l0, b0 * u0.y)), i1 = __fdividef(1.f, fmaf(a1, l1, b1 * u1.y));
            a0 *= i0; b0 *= i0; a1 *= i1; b1 *= i1;
            uint32_t pk[8];
#pragma unroll
            for (int j = 0; j < 4; j++) {
                const float4 v = lds128f(H + (w ^ 1) * 8192 + j * 2048 + wt * 16);
                pk[2 * j] = pack2(fmaf(a0, mine[4 * j], b0 * v.x), fmaf(a0, mine[4 * j + 1], b0 * v.y));
                pk[2 * j + 1] = pack2(fmaf(a1, mine[4 * j + 2], b1 * v.z), fmaf(a1, mine[4 * j + 3], b1 * v.w));
            }
            unsigned char* dst = g_o + (size_t)(abh * PADROWS + 8 + qt * 64 + wq * 16) * 128 + w * 512 + lane * 16;
            st_data(dst, pk[0], pk[2], pk[4], pk[6]);
            st_data(dst + 1024, pk[1], pk[3], pk[5], pk[7]);
            if (tid == 0) asm volatile("red.relaxed.gpu.global.add.u32 [%0], 1;" ::"l"(&g_epoch[blockIdx.x * FS]) : "memory");
            TS(15);
        }

        auto mm = [&](float (&d)[24], int n, uint32_t act, int acc) {
            const uint32_t z = p.zero * (ph + n);
            const uint64_t ad = mkdesc(rdesc + z + (n % NSLOT) * (SLOT >> 4)), bd = mkdesc(desc_lo(act) + z);
            wg_fence();
#pragma unroll
            for (int k = 0; k < 8; k++) mma_t(d, ad + k * 128, bd + (k >> 2) * (XCH >> 4) + (k & 3) * 2, k == 0 ? acc : 1);
            wg_commit();
        };
        uint32_t dwr[15];
        {
#pragma unroll
            for (int i = 0; i < 15; i++) dwr[i] = hmul2(__ldg(reinterpret_cast<const uint32_t*>(p.dw + i * 256 + tile * 64) + lane), 0x3F003F00u);
            float d[24];
            uint32_t xw[12];
            bar_sync(9, 384);
#pragma unroll
            for (int j = 0; j < 3; j++) ldsm4t(xt + j * 2048, xw[4 * j], xw[4 * j + 1], xw[4 * j + 2], xw[4 * j + 3]);
            pin(xw);
            acq(32); acq(33); acq(34); acq(35);
            {
                if (ODELAY) spin(ODELAY);
                uint4 u[6];
                ld_data<1024>(u, g_o + (size_t)((b * 4 + (warp >> 1)) * PADROWS + pt * 32) * 128 + (warp & 1) * 512 + lane * 16);
                const uint32_t dst = H + (warp >> 1) * XCH + (foff ^ ((warp & 1) * 64));
#pragma unroll
                for (int i = 0; i < 6; i++) stsm4(dst + i * 1024, u[i].x, u[i].y, u[i].z, u[i].w);
            }
            fence_async_smem();
            bar_sync(10, 256);
            TS(16);
            mm(d, 32, H, 0);
            mm(d, 33, H + 2 * XCH, 1);
            wg_wait<1>();
            rel(32);
            wg_wait<0>();
            pin(d);
#pragma unroll
            for (int i = 0; i < 12; i++) xw[i] = pack2(d[2 * i] + blo(xw[i]), d[2 * i + 1] + bhi(xw[i]));
            if (c4 == 0) { xw[0] = (xw[0] & 0xffff0000u) | 0x3F80u; xw[1] = (xw[1] & 0xffff0000u) | 0x3F80u; }
#pragma unroll
            for (int j = 0; j < 3; j++) stsm4t(xt + j * 2048, xw[4 * j], xw[4 * j + 1], xw[4 * j + 2], xw[4 * j + 3]);
            rel(33);
            publish(B_X2, P + tile * XCH, XCH, 384);
            TS(17);
        }
        {
            float da[24], db[24], st[24];
            bar_sync(5, 384);
            mm(da, 34, P + 2 * r * XCH, 0);
            mm(db, 35, P + 2 * r * XCH, 0);
            acq(36); acq(37);
            mbar_wait(bars + B_X2 * 8, 0);
            bar_sync(5, 384);
            TS(39);
            mm(da, 36, P + 2 * (r ^ 1) * XCH, 1);
            mm(db, 37, P + 2 * (r ^ 1) * XCH, 1);
            wg_wait<2>();
            rel(34); rel(35);
            mbar_wait(bars + B_ST * 8, 0);
#pragma unroll
            for (int j = 0; j < 6; j++) {
                const float4 u = lds128f(sb + OFF_STATS + (8 * j + 2 * c4) * 8);
                st[4 * j] = u.x; st[4 * j + 1] = u.y; st[4 * j + 2] = u.z; st[4 * j + 3] = u.w;
            }
            wg_wait<0>();
            pin(da); pin(db);
            rel(36); rel(37);
            TS(18);
            uint32_t pk[12];
#pragma unroll
            for (int hh = 0; hh < 2; hh++) {
                const float ca = __shfl_sync(~0u, da[2 * hh], lane & 28), cb = __shfl_sync(~0u, db[2 * hh], lane & 28);
#pragma unroll
                for (int j = 0; j < 6; j++) {
                    const float u0 = fmaf(-st[4 * j], ca, da[4 * j + 2 * hh] * st[4 * j + 1]);
                    const float u1 = fmaf(-st[4 * j + 2], ca, da[4 * j + 2 * hh + 1] * st[4 * j + 3]);
                    const float v0 = fmaf(-st[4 * j], cb, db[4 * j + 2 * hh] * st[4 * j + 1]);
                    const float v1 = fmaf(-st[4 * j + 2], cb, db[4 * j + 2 * hh + 1] * st[4 * j + 3]);
                    pk[2 * j + hh] = pack2(fmaf(u0, tanh_fast(v0), u0), fmaf(u1, tanh_fast(v1), u1));
                }
            }
            const uint32_t gs = H + 16384 + w * XCH;
#pragma unroll
            for (int j = 0; j < 3; j++) stsm4t(gs + toff + j * 2048, pk[4 * j], pk[4 * j + 1], pk[4 * j + 2], pk[4 * j + 3]);
            ldsm4(xo + 1024 + foff, xr[0], xr[1], xr[2], xr[3]);
            ldsm4(xo + 1024 + (foff ^ 64), xr[4], xr[5], xr[6], xr[7]);
            bar_sync(2 + w, 128);
            uint32_t ca[8], cb[8];
            const uint32_t grow = gs + 8 * wq * 128 + c4 * 4, srow = H + tile * HCH + 8 * wq * 128 + c4 * 4;
#pragma unroll
            for (int k = 0; k < 22; k++) {
                const uint32_t v = lds32(grow + (1 + k) * 128 + (((lane >> 2) ^ ((1 + k) & 7)) << 4));
#pragma unroll
                for (int i = 0; i < 8; i++) {
                    const int tap = k - i;
                    if (tap == 0) ca[i] = hmul2(v, dwr[0]);
                    else if (tap > 0 && tap < 8) ca[i] = hfma2(v, dwr[tap], ca[i]);
                    else if (tap == 8) cb[i] = hmul2(v, dwr[8]);
                    else if (tap > 8 && tap < 15) cb[i] = hfma2(v, dwr[tap], cb[i]);
                }
            }
#pragma unroll
            for (int i = 0; i < 8; i++) {
                const float h0 = blo(ca[i]) + blo(cb[i]), h1 = bhi(ca[i]) + bhi(cb[i]);
                sts32(srow + i * 128 + (((lane >> 2) ^ i) << 4), pack2(fmaf(h0, tanh_fast(h0), h0), fmaf(h1, tanh_fast(h1), h1)));
            }
            acq(38); acq(39);
            publish(B_SR, H + tile * HCH, HCH, 256);
            TS(19);
        }
        {
            auto frags = [&](int i, int half) {
                const uint32_t src = H + 2 * half * HCH + wq * 1024;
#pragma unroll
                for (int k = 0; k < 4; k++) ldsm4(src + (k >> 1) * HCH + (foff ^ ((k & 1) * 64)), a[i + 4 * k], a[i + 4 * k + 1], a[i + 4 * k + 2], a[i + 4 * k + 3]);
            };
            frags(0, r);
            sp(d0, 38, a, 0, 0);
            acq(40);
            mbar_wait(bars + B_SR * 8, 0);
            frags(16, r ^ 1);
            sp(d0, 39, a + 16, 0, 1);
            wg_wait<1>();
            rel(38);
            wg_wait<0>();
            pin(d0);
            rel(39);
#pragma unroll
            for (int j = 0; j < 8; j++) {
                v[2 * j] = d0[4 * j] + d0[4 * j + 2] + blo(xr[j]);
                v[2 * j + 1] = d0[4 * j + 1] + d0[4 * j + 3] + bhi(xr[j]);
            }
            TS(20);
        }
    }

    cluster_arrive();
    TS(24);
    {
        const float rstd = rsq(fmaxf(fmaf(-mean, mean, msq), 0.f) + 1e-5f), nb = -mean * rstd;
#pragma unroll
        for (int j = 0; j < 8; j++) xr[j] = pack2(fmaf(v[2 * j], rstd, nb), fmaf(v[2 * j + 1], rstd, nb));
        const uint32_t stg = P + 16384 + warp * 1024;
        stsm4(stg + foff, xr[0], xr[1], xr[2], xr[3]);
        stsm4(stg + (foff ^ 64), xr[4], xr[5], xr[6], xr[7]);
        __syncwarp();
        const uint32_t src = stg + (lane >> 3) * 128 + (((lane & 7) ^ (lane >> 3)) << 4);
        const uint4 u0 = lds128(src), u1 = lds128((src + 512) ^ 64);
        __nv_bfloat16* dst = p.out + (size_t)(b * T_ + trow + (lane >> 3)) * 256 + tile * 64 + (lane & 7) * 8;
        if (trow < T_) { stg128(dst, u0); stg128(dst + 4 * 256, u1); }
    }
    TS(25);
    TG(31);
    TSDUMP();
    cluster_wait();
}

typedef CUresult (*EncodeFn)(CUtensorMap*, CUtensorMapDataType, cuuint32_t, void*, const cuuint64_t*, const cuuint64_t*,
                             const cuuint32_t*, const cuuint32_t*, CUtensorMapInterleave, CUtensorMapSwizzle,
                             CUtensorMapL2promotion, CUtensorMapFloatOOBfill);

}

extern "C" void kernel_launch(void* const* d_in, const int* in_sizes, int n_in, void* d_out, int out_size) {
    static EncodeFn encode = nullptr;
    if (!encode) {
        void* fn = nullptr;
        cudaDriverEntryPointQueryResult qr;
        cudaGetDriverEntryPoint("cuTensorMapEncodeTiled", &fn, cudaEnableDefault, &qr);
        encode = (EncodeFn)fn;
        cudaFuncSetAttribute(conformer_kernel, cudaFuncAttributeMaxDynamicSharedMemorySize, SMEM_LAUNCH);
    }
    Params p;
    const cuuint32_t ones[5] = {1, 1, 1, 1, 1};
    const int idx[8] = {1, 2, 3, 4, 5, 7, 8, 9};
    const int rows[8] = {256, 1024, 256, 256, 256, 256, 256, 1024};
    const int cols[8] = {1024, 256, 768, 256, 512, 256, 1024, 256};
    for (int i = 0; i < 8; i++) {
        const bool perm = i != 3 && i != 4;
        const cuuint64_t pitch = (cuuint64_t)cols[i] * 2;
        const cuuint64_t dims[5] = {(cuuint64_t)cols[i], 2, 2, 4, (cuuint64_t)rows[i] / 16};
        const cuuint64_t strides[4] = {pitch, pitch * (perm ? 8 : 2), pitch * (perm ? 2 : 4), pitch * 16};
        const cuuint32_t box[5] = {64, 2, 2, 4, 8};
        encode(&p.tm[i], CU_TENSOR_MAP_DATA_TYPE_BFLOAT16, 5, d_in[idx[i]], dims, strides, box, ones, CU_TENSOR_MAP_INTERLEAVE_NONE,
               CU_TENSOR_MAP_SWIZZLE_128B, CU_TENSOR_MAP_L2_PROMOTION_L2_128B, CU_TENSOR_MAP_FLOAT_OOB_FILL_NONE);
        p.w[i] = (const char*)d_in[idx[i]];
    }
    {
        void* kv = nullptr;
        cudaGetSymbolAddress(&kv, g_kvq);
        const cuuint64_t dims[2] = {64, 16384};
        const cuuint64_t strides[1] = {128};
        const cuuint32_t box[2] = {64, 128};
        encode(&p.tm[8], CU_TENSOR_MAP_DATA_TYPE_BFLOAT16, 2, kv, dims, strides, box, ones, CU_TENSOR_MAP_INTERLEAVE_NONE,
               CU_TENSOR_MAP_SWIZZLE_NONE, CU_TENSOR_MAP_L2_PROMOTION_L2_128B, CU_TENSOR_MAP_FLOAT_OOB_FILL_NONE);
    }
    p.x = (const __nv_bfloat16*)d_in[0];
    p.dw = (const __nv_bfloat16*)d_in[6];
    p.out = (__nv_bfloat16*)d_out;
    p.zero = 0;
    conformer_kernel<<<NCTA, NTHREADS, SMEM_LAUNCH>>>(p);
}
```

```cpp
#include <cuda_runtime.h>
#include <cuda_bf16.h>
#include <cuda.h>
#include <stdint.h>

namespace {

constexpr int T_ = 1000;
constexpr int NCTA = 128;
constexpr int NTHREADS = 512;
constexpr int NSLOT = 5;
constexpr int SLOT = 16384;
constexpr int NLOADS = 56;

constexpr uint32_t OFF_RING = 0;
constexpr uint32_t OFF_P = 163840;
constexpr uint32_t OFF_H = 188416;
constexpr uint32_t OFF_MISC = 221184;
constexpr uint32_t OFF_STATS = 229376;
constexpr uint32_t OFF_BARS = 229888;
constexpr uint32_t SMEM_BYTES = 230400;
constexpr uint32_t XCH = 6144;
constexpr uint32_t HCH = 4096;

constexpr int B_FULL = 0, B_EMPTY = 10, B_XA = 20  , B_XB = 24  , B_INB = 27  , B_X2 = 31, B_SR = 32,
              B_RST = 33  , B_RDY = 35  , B_SINK = 41, B_ST = 42;

#define KD2 400u
#define KD3 800u
#define ODELAY 0u
#define QGATE 500u
#define BACKOFF 0u
#define KFS 8
#define KDELAY 300u
#define NJ0 2
#define TURN 0
#define EAGER 0x5555
constexpr int PADROWS = 1040;
constexpr int FS = 8;

struct Params {
    CUtensorMap tm[9];
    const char* w[8];
    const __nv_bfloat16* x;
    const __nv_bfloat16* dw;
    __nv_bfloat16* out;
    uint32_t zero;
};

__device__ __align__(1024) unsigned char g_kvq[3 * 8 * 1024 * 128];
__device__ __align__(1024) unsigned char g_o[8 * PADROWS * 128];
__device__ uint4 g_halo[64 * 4 * 2 * 64];
__device__ __align__(128) uint32_t g_flag_kv[8 * 32 * KFS];
__device__ uint32_t g_reset[4 * 32];
__device__ uint32_t g_epoch[NCTA * FS];

#define TS(i) do { } while (0)
#define TSW(i) do { } while (0)
#define TG(i) do { } while (0)
#define TSINIT() do { } while (0)
#define TSDUMP() do { } while (0)
constexpr uint32_t SMEM_LAUNCH = SMEM_BYTES;

__device__ __forceinline__ uint32_t smem_u32(const void* p) { return (uint32_t)__cvta_generic_to_shared(p); }
__device__ __forceinline__ void mbar_init(uint32_t b, uint32_t c) { asm volatile("mbarrier.init.shared::cta.b64 [%0], %1;" ::"r"(b), "r"(c) : "memory"); }
__device__ __forceinline__ void mbar_arrive(uint32_t b) { asm volatile("mbarrier.arrive.shared::cta.b64 _, [%0];" ::"r"(b) : "memory"); }
__device__ __forceinline__ void mbar_arrive_tx(uint32_t b, uint32_t tx) { asm volatile("mbarrier.arrive.expect_tx.shared::cta.b64 _, [%0], %1;" ::"r"(b), "r"(tx) : "memory"); }
__device__ __forceinline__ void mbar_wait(uint32_t b, uint32_t ph) {
    asm volatile("{\n.reg .pred p, q;\n.reg .u32 c;\nmov.u32 c, 0;\n"
                 "MW_LOOP:\n.pragma \"nounroll\";\n"
                 "mbarrier.try_wait.parity.shared::cta.b64 p, [%0], %1;\n"
                 "add.u32 c, c, 1;\nsetp.lt.u32 q, c, 65536;\nnot.pred p, p;\nand.pred p, p, q;\n@p bra MW_LOOP;\n}"
                 ::"r"(b), "r"(ph) : "memory");
}
__device__ __forceinline__ bool mbar_test(uint32_t b, uint32_t ph) {
    uint32_t ok;
    asm volatile("{\n.reg .pred p;\nmbarrier.test_wait.parity.shared::cta.b64 p, [%1], %2;\nselp.u32 %0, 1, 0, p;\n}" : "=r"(ok) : "r"(b), "r"(ph) : "memory");
    return ok;
}
__device__ __forceinline__ uint32_t mapa(uint32_t a, uint32_t r) { uint32_t o; asm("mapa.shared::cluster.u32 %0, %1, %2;" : "=r"(o) : "r"(a), "r"(r)); return o; }
__device__ __forceinline__ void fence_async_smem() { asm volatile("fence.proxy.async.shared::cta;" ::: "memory"); }
__device__ __forceinline__ void fence_async_global() { asm volatile("fence.proxy.async.global;" ::: "memory"); }
__device__ __forceinline__ void bar_sync(int id, int n) { asm volatile("bar.sync %0, %1;" ::"r"(id), "r"(n) : "memory"); }
__device__ __forceinline__ void bar_arrive(int id, int n) { asm volatile("bar.arrive %0, %1;" ::"r"(id), "r"(n) : "memory"); }
__device__ __forceinline__ void cluster_arrive() { asm volatile("barrier.cluster.arrive.relaxed.aligned;" ::: "memory"); }
__device__ __forceinline__ void cluster_wait() { asm volatile("barrier.cluster.wait.aligned;" ::: "memory"); }

__device__ __forceinline__ void ring_load(uint32_t dst, const CUtensorMap* tm, int col, int row16, uint32_t bar) {
    asm volatile("{\n.reg .pred p;\nelect.sync _|p, 0xffffffff;\n"
                 "@p mbarrier.arrive.expect_tx.shared::cta.b64 _, [%2], 16384;\n"
                 "@p cp.async.bulk.tensor.5d.shared::cluster.global.mbarrier::complete_tx::bytes [%0], [%1, {%3, 0, 0, 0, %4}], [%2];\n}"
                 ::"r"(dst), "l"(tm), "r"(bar), "r"(col), "r"(row16) : "memory");
}
__device__ __forceinline__ void ring_load_both(uint32_t dst, const CUtensorMap* tm, int c1, uint32_t bar) {
    asm volatile("{\n.reg .pred p;\nelect.sync _|p, 0xffffffff;\n"
                 "@p cp.async.bulk.tensor.2d.shared::cluster.global.mbarrier::complete_tx::bytes.multicast::cluster [%0], [%1, {0, %3}], [%2], %4;\n}"
                 ::"r"(dst), "l"(tm), "r"(bar), "r"(c1), "h"((uint16_t)3) : "memory");
}
__device__ __forceinline__ void mbar_arrive_peer(uint32_t b) { asm volatile("mbarrier.arrive.relaxed.cluster.shared::cluster.b64 _, [%0];" ::"r"(b) : "memory"); }
__device__ __forceinline__ void prefetch_l2(const void* src, uint32_t bytes) {
    asm volatile("cp.async.bulk.prefetch.L2.global [%0], %1;" ::"l"(src), "r"(bytes) : "memory");
}
__device__ __forceinline__ void peer_copy(uint32_t dst, uint32_t src, uint32_t bytes, uint32_t rbar) {
    asm volatile("{\n.reg .pred p;\nelect.sync _|p, 0xffffffff;\n"
                 "@p cp.async.bulk.shared::cluster.shared::cta.mbarrier::complete_tx::bytes [%0], [%1], %2, [%3];\n}"
                 ::"r"(dst), "r"(src), "r"(bytes), "r"(rbar) : "memory");
}
__device__ __forceinline__ void st_async4(uint32_t dst, uint32_t a, uint32_t b, uint32_t c, uint32_t d, uint32_t bar) {
    asm volatile("st.async.shared::cluster.mbarrier::complete_tx::bytes.v4.b32 [%0], {%1,%2,%3,%4}, [%5];" ::"r"(dst), "r"(a), "r"(b), "r"(c), "r"(d), "r"(bar) : "memory");
}
__device__ __forceinline__ void st_async2f(uint32_t dst, float a, float b, uint32_t bar) {
    asm volatile("st.async.shared::cluster.mbarrier::complete_tx::bytes.v2.f32 [%0], {%1,%2}, [%3];" ::"r"(dst), "f"(a), "f"(b), "r"(bar) : "memory");
}
__device__ __forceinline__ void stsm4t(uint32_t a, uint32_t r0, uint32_t r1, uint32_t r2, uint32_t r3) {
    asm volatile("stmatrix.sync.aligned.m8n8.x4.trans.shared.b16 [%0], {%1,%2,%3,%4};" ::"r"(a), "r"(r0), "r"(r1), "r"(r2), "r"(r3) : "memory");
}
__device__ __forceinline__ void stsm4(uint32_t a, uint32_t r0, uint32_t r1, uint32_t r2, uint32_t r3) {
    asm volatile("stmatrix.sync.aligned.m8n8.x4.shared.b16 [%0], {%1,%2,%3,%4};" ::"r"(a), "r"(r0), "r"(r1), "r"(r2), "r"(r3) : "memory");
}
__device__ __forceinline__ void ldsm4t(uint32_t a, uint32_t& r0, uint32_t& r1, uint32_t& r2, uint32_t& r3) {
    asm volatile("ldmatrix.sync.aligned.m8n8.x4.trans.shared.b16 {%0,%1,%2,%3}, [%4];" : "=r"(r0), "=r"(r1), "=r"(r2), "=r"(r3) : "r"(a) : "memory");
}
__device__ __forceinline__ void ldsm4(uint32_t a, uint32_t& r0, uint32_t& r1, uint32_t& r2, uint32_t& r3) {
    asm volatile("ldmatrix.sync.aligned.m8n8.x4.shared.b16 {%0,%1,%2,%3}, [%4];" : "=r"(r0), "=r"(r1), "=r"(r2), "=r"(r3) : "r"(a) : "memory");
}
__device__ __forceinline__ uint4 lds128(uint32_t a) { uint4 v; asm volatile("ld.shared.v4.b32 {%0,%1,%2,%3}, [%4];" : "=r"(v.x), "=r"(v.y), "=r"(v.z), "=r"(v.w) : "r"(a) : "memory"); return v; }
__device__ __forceinline__ float4 lds128f(uint32_t a) { float4 v; asm volatile("ld.shared.v4.f32 {%0,%1,%2,%3}, [%4];" : "=f"(v.x), "=f"(v.y), "=f"(v.z), "=f"(v.w) : "r"(a) : "memory"); return v; }
__device__ __forceinline__ float2 lds64f(uint32_t a) { float2 v; asm volatile("ld.shared.v2.f32 {%0,%1}, [%2];" : "=f"(v.x), "=f"(v.y) : "r"(a) : "memory"); return v; }
__device__ __forceinline__ uint32_t lds32(uint32_t a) { uint32_t v; asm volatile("ld.shared.b32 %0, [%1];" : "=r"(v) : "r"(a) : "memory"); return v; }
__device__ __forceinline__ void sts128(uint32_t a, uint32_t x, uint32_t y, uint32_t z, uint32_t w) { asm volatile("st.shared.v4.b32 [%0], {%1,%2,%3,%4};" ::"r"(a), "r"(x), "r"(y), "r"(z), "r"(w) : "memory"); }
__device__ __forceinline__ void sts128f(uint32_t a, float x, float y, float z, float w) { asm volatile("st.shared.v4.f32 [%0], {%1,%2,%3,%4};" ::"r"(a), "f"(x), "f"(y), "f"(z), "f"(w) : "memory"); }
__device__ __forceinline__ void sts64f(uint32_t a, float x, float y) { asm volatile("st.shared.v2.f32 [%0], {%1,%2};" ::"r"(a), "f"(x), "f"(y) : "memory"); }
__device__ __forceinline__ void sts32(uint32_t a, uint32_t x) { asm volatile("st.shared.b32 [%0], %1;" ::"r"(a), "r"(x) : "memory"); }
__device__ __forceinline__ void stg128(void* p, uint4 v) { asm volatile("st.global.v4.b32 [%0], {%1,%2,%3,%4};" ::"l"(p), "r"(v.x), "r"(v.y), "r"(v.z), "r"(v.w) : "memory"); }

__device__ __forceinline__ uint32_t pack2(float lo, float hi) { uint32_t r; asm("cvt.rn.bf16x2.f32 %0, %1, %2;" : "=r"(r) : "f"(hi), "f"(lo)); return r; }
__device__ __forceinline__ float blo(uint32_t v) { return __uint_as_float(v << 16); }
__device__ __forceinline__ float bhi(uint32_t v) { return __uint_as_float(v & 0xffff0000u); }
__device__ __forceinline__ uint32_t hmul2(uint32_t a, uint32_t b) { uint32_t r; asm("mul.rn.bf16x2 %0, %1, %2;" : "=r"(r) : "r"(a), "r"(b)); return r; }
__device__ __forceinline__ uint32_t hsub2(uint32_t a, uint32_t b) { uint32_t r; asm("sub.rn.bf16x2 %0, %1, %2;" : "=r"(r) : "r"(a), "r"(b)); return r; }
__device__ __forceinline__ uint32_t hfma2(uint32_t a, uint32_t b, uint32_t c) { uint32_t r; asm("fma.rn.bf16x2 %0, %1, %2, %3;" : "=r"(r) : "r"(a), "r"(b), "r"(c)); return r; }
__device__ __forceinline__ float tanh_fast(float x) { float r; asm("tanh.approx.f32 %0, %1;" : "=f"(r) : "f"(x)); return r; }
__device__ __forceinline__ float rsq(float x) { float r; asm("rsqrt.approx.ftz.f32 %0, %1;" : "=f"(r) : "f"(x)); return r; }
__device__ __forceinline__ float ex2(float x) { float r; asm("ex2.approx.ftz.f32 %0, %1;" : "=f"(r) : "f"(x)); return r; }

__device__ __forceinline__ uint32_t ld_relaxed(const uint32_t* p) {
    uint32_t v;
    asm volatile("ld.relaxed.gpu.global.u32 %0, [%1];" : "=r"(v) : "l"(p) : "memory");
    return v;
}
__device__ __forceinline__ uint32_t clock32() { uint32_t c; asm volatile("mov.u32 %0, %%clock;" : "=r"(c)::"memory"); return c; }
__device__ __forceinline__ void spin(uint32_t clks) {
    const uint32_t t0 = clock32();
    while (clock32() - t0 < clks) {}
}
__device__ __forceinline__ void flag_wait(const uint32_t* p, uint32_t e, bool mine) {
#pragma unroll 1
    for (int i = 0; i < (1 << 19); i++) {
        if (mine) mine = ld_relaxed(p) != e;
        if (!__any_sync(~0u, mine)) break;
        if (BACKOFF) spin(BACKOFF);
    }
    asm volatile("fence.acquire.gpu;" ::: "memory");
    fence_async_global();
}
__device__ __forceinline__ void st_data(void* p, uint32_t x, uint32_t y, uint32_t z, uint32_t w) {
    asm volatile("st.relaxed.gpu.global.v4.b32 [%0], {%1,%2,%3,%4};" ::"l"(p), "r"(x), "r"(y), "r"(z), "r"(w) : "memory");
}
template <int STRIDE, int N>
__device__ __forceinline__ void ld_data(uint4 (&v)[N], const unsigned char* p) {
    int it = 0;
    bool again;
#pragma unroll 1
    do {
        uint32_t m = 0;
#pragma unroll
        for (int i = 0; i < N; i++)
            asm volatile("ld.relaxed.gpu.global.v4.b32 {%0,%1,%2,%3}, [%4];" : "=r"(v[i].x), "=r"(v[i].y), "=r"(v[i].z), "=r"(v[i].w) : "l"(p + i * STRIDE) : "memory");
#pragma unroll
        for (int i = 0; i < N; i++) m = __vimax3_u32(__vimax3_u32(v[i].x, v[i].y, v[i].z), v[i].w, m);
        again = __any_sync(~0u, m == ~0u) && ++it < (1 << 16);
    } while (again);
}
__device__ __forceinline__ uint32_t ld_epoch() { return ld_relaxed(&g_epoch[blockIdx.x * FS]) + 1; }
__device__ __forceinline__ void flag_set(uint32_t* p, uint32_t e) { asm volatile("st.release.gpu.global.u32 [%0], %1;" ::"l"(p), "r"(e) : "memory"); }

__device__ __forceinline__ uint32_t desc_lo(uint32_t addr) { return ((addr & 0x3FFFF) >> 4) | 0x10000u; }
__device__ __forceinline__ uint64_t mkdesc(uint32_t lo) { return (uint64_t)lo | (0x40000040ull << 32); }
__device__ __forceinline__ void wg_fence() { asm volatile("wgmma.fence.sync.aligned;" ::: "memory"); }
__device__ __forceinline__ void wg_commit() { asm volatile("wgmma.commit_group.sync.aligned;" ::: "memory"); }
template <int N> __device__ __forceinline__ void wg_wait() { asm volatile("wgmma.wait_group.sync.aligned %0;" ::"n"(N) : "memory"); }
template <int N> __device__ __forceinline__ void pin(float (&d)[N]) {
#pragma unroll
    for (int i = 0; i < N; i++) asm volatile("" : "+f"(d[i])::"memory");
}
template <int N> __device__ __forceinline__ void pin(uint32_t (&d)[N]) {
#pragma unroll
    for (int i = 0; i < N; i++) asm volatile("" : "+r"(d[i])::"memory");
}

template <typename Tp, int N> __device__ __forceinline__ void zero(Tp (&d)[N]) {
#pragma unroll
    for (int i = 0; i < N; i++) d[i] = 0;
    pin(d);
}

#define F4(d, i) "+f"(d[i]), "+f"(d[i + 1]), "+f"(d[i + 2]), "+f"(d[i + 3])
#define F16(d, i) F4(d, i), F4(d, i + 4), F4(d, i + 8), F4(d, i + 12)

__device__ __forceinline__ void mma_sp(float (&d)[32], const uint32_t* a, uint64_t b, uint32_t meta, int acc) {
    asm volatile("{.reg .pred p; setp.ne.b32 p, %38, 0;\n"
                 "wgmma.mma_async.sp.sync.aligned.m64n64k32.f32.bf16.bf16 {%0,%1,%2,%3,%4,%5,%6,%7,%8,%9,%10,%11,%12,%13,%14,%15,%16,%17,%18,%19,%20,%21,%22,%23,%24,%25,%26,%27,%28,%29,%30,%31}, "
                 "{%32,%33,%34,%35}, %36, %37, 0, p, 1, 1, 1;}\n"
                 : F16(d, 0), F16(d, 16) : "r"(a[0]), "r"(a[1]), "r"(a[2]), "r"(a[3]), "l"(b), "r"(meta), "r"(acc));
}
__device__ __forceinline__ void mma_t(float (&d)[24], uint64_t a, uint64_t b, int acc) {
    asm volatile("{.reg .pred p; setp.ne.b32 p, %26, 0;\n"
                 "wgmma.mma_async.sync.aligned.m64n48k16.f32.bf16.bf16 {%0,%1,%2,%3,%4,%5,%6,%7,%8,%9,%10,%11,%12,%13,%14,%15,%16,%17,%18,%19,%20,%21,%22,%23}, %24, %25, p, 1, 1, 1, 0;}\n"
                 : F16(d, 0), F4(d, 16), F4(d, 20) : "l"(a), "l"(b), "r"(acc));
}
__device__ __forceinline__ void mma_qk(float (&d)[32], uint32_t a0, uint32_t a1, uint32_t a2, uint32_t a3, uint64_t b, int acc) {
    asm volatile("{.reg .pred p; setp.ne.b32 p, %37, 0;\n"
                 "wgmma.mma_async.sync.aligned.m64n64k16.f32.bf16.bf16 {%0,%1,%2,%3,%4,%5,%6,%7,%8,%9,%10,%11,%12,%13,%14,%15,%16,%17,%18,%19,%20,%21,%22,%23,%24,%25,%26,%27,%28,%29,%30,%31}, "
                 "{%32,%33,%34,%35}, %36, p, 1, 1, 0;}\n"
                 : F16(d, 0), F16(d, 16) : "r"(a0), "r"(a1), "r"(a2), "r"(a3), "l"(b), "r"(acc));
}
__device__ __forceinline__ void mma_pv(float (&d)[36], uint32_t a0, uint32_t a1, uint32_t a2, uint32_t a3, uint64_t b) {
    asm volatile("wgmma.mma_async.sync.aligned.m64n72k16.f32.bf16.bf16 {%0,%1,%2,%3,%4,%5,%6,%7,%8,%9,%10,%11,%12,%13,%14,%15,%16,%17,%18,%19,%20,%21,%22,%23,%24,%25,%26,%27,%28,%29,%30,%31,%32,%33,%34,%35}, "
                 "{%36,%37,%38,%39}, %40, 1, 1, 1, 1;\n"
                 : F16(d, 0), F16(d, 16), F4(d, 32) : "r"(a0), "r"(a1), "r"(a2), "r"(a3), "l"(b));
}

__device__ __forceinline__ uint32_t load_code(int n, int r, int w) {
    const int tile = 2 * r + w;
    int m, col, row;
    if (n < 16 || n >= 40) {
        const int k = n < 16 ? n : n - 40;
        m = n < 16 ? 0 : 6;
        if (k < 8) { col = 4 * tile + (k >> 1); row = (k & 1) ^ r; }
        else { m++; col = tile ^ (3 - ((k - 8) >> 1)); row = 2 * tile + (k & 1); }
    } else if (n < 32) {
        const int k = n - 16;
        m = 2;
        if (k < 4) { col = tile + ((k & 1) ? 8 : 4); row = (k >> 1) ^ r; }
        else { col = tile; row = (k & 1) ^ r; }
    } else if (n < 34) { m = 3; col = tile; row = n - 32; }
    else if (n < 38) { const int k = n - 34; m = 4; col = tile + 4 * (k & 1); row = (k >> 1) ^ r; }
    else { m = 5; col = tile; row = (n & 1) ^ r; }
    return m | (col << 4) | (row << 8);
}

__global__ void __cluster_dims__(2, 1, 1) __launch_bounds__(NTHREADS, 1)
conformer_kernel(const __grid_constant__ Params p) {
    extern __shared__ __align__(1024) unsigned char smem_raw[];
    const uint32_t sb = smem_u32(smem_raw);
    const uint32_t bars = sb + OFF_BARS;
    const int tid = threadIdx.x;
    const int lane = tid & 31;
    const int warp = __shfl_sync(~0u, tid >> 5, 0);
    const int r = blockIdx.x & 1;
    const int pair = blockIdx.x >> 1;
    const int b = pair >> 5, pt = pair & 31;
    const int ah = pt >> 3, qt = (pt & 7) * 2 + r;
    const int abh = b * 4 + ah;

    TG(30);
    TSINIT();
    TS(0);
    const uint32_t P = sb + OFF_P, H = sb + OFF_H;

    if (warp >= 8) {
        asm volatile("setmaxnreg.dec.sync.aligned.u32 48;");
        if (warp >= 12) {
            cluster_arrive();
            cluster_wait();
            const int ut = tid & 127;
            const uint32_t target = ld_epoch() * 64;
            auto reset_done = [&](int k) {
                bar_sync(11, 128);
                if (ut == 0) {
                    asm volatile("red.release.gpu.global.add.u32 [%0], 1;" ::"l"(&g_reset[(2 * b + k) * 32]) : "memory");
#pragma unroll 1
                    for (int i = 0; i < (1 << 20) && ld_relaxed(&g_reset[(2 * b + k) * 32]) != target; i++) __nanosleep(100);
                    asm volatile("fence.acquire.gpu;" ::: "memory");
                    mbar_arrive(bars + (B_RST + k) * 8);
                }
                __syncwarp();
                TS(13 + k);
            };
#pragma unroll
            for (int i = 0; i < 4; i++) {
                st_data(g_kvq + 2097152 + (size_t)((b * 4 + 2 * r + (i >> 1)) * 1024 + pt * 32) * 128 + (i & 1) * 2048 + ut * 16, ~0u, ~0u, ~0u, ~0u);
                if (i < 2) st_data(&g_halo[(pair * 4 + 2 * r + i) * 128 + ut], ~0u, ~0u, ~0u, ~0u);
            }
            reset_done(0);
            bar_sync(6, 384);
#pragma unroll
            for (int i = 0; i < 4; i++) st_data(g_o + (size_t)(abh * PADROWS + 8 + qt * 64) * 128 + i * 2048 + ut * 16, ~0u, ~0u, ~0u, ~0u);
            reset_done(1);
            {
                const int side = warp & 1, t = 2 * r + ((warp >> 1) & 1), np = side ? pt + 1 : pt - 1;
                uint4 hv[2] = {make_uint4(0, 0, 0, 0), make_uint4(0, 0, 0, 0)};
                if (np >= 0 && np < 32)
                    ld_data<512>(hv, reinterpret_cast<const unsigned char*>(&g_halo[(((b * 32 + np) * 4 + t) * 2 + (side ^ 1)) * 64 + lane]));
                const uint32_t dst = P + t * XCH + side * 5120 + (lane & 7) * 128 + (((lane >> 3) ^ (lane & 7)) << 4);
                stsm4(dst, hv[0].x, hv[0].y, hv[0].z, hv[0].w);
                stsm4(dst ^ 64, hv[1].x, hv[1].y, hv[1].z, hv[1].w);
                bar_arrive(9, 384);
            }
            const uint32_t a8 = P + (ut >> 3) * 128 + (ut & 7) * 16;
            float s[3] = {0.f, 0.f, 0.f}, q[3] = {0.f, 0.f, 0.f};
#pragma unroll 1
            for (int h = 0; h < 2; h++) {
                if (h == 0) bar_sync(1, 384);
                else mbar_wait(bars + B_X2 * 8, 0);
                uint4 v[6];
#pragma unroll
                for (int i = 0; i < 6; i++) v[i] = lds128(a8 + (2 * (r ^ h) + (i & 1)) * XCH + (i >> 1) * 2048);
                bar_arrive(5 + ((v[0].w | v[1].w | v[2].w | v[3].w | v[4].w | v[5].w) & p.zero), 384);
                uint32_t t;
                asm volatile("mov.u32 %0, %%clock;" : "=r"(t)::"memory");
                const uint32_t mul = 65536u + (t & p.zero), msk = 0u - mul;
#pragma unroll
                for (int i = 0; i < 6; i++) {
                    const float a0 = __uint_as_float(v[i].x * mul), a1 = __uint_as_float(v[i].x & msk), a2 = __uint_as_float(v[i].y * mul), a3 = __uint_as_float(v[i].y & msk);
                    const float a4 = __uint_as_float(v[i].z * mul), a5 = __uint_as_float(v[i].z & msk), a6 = __uint_as_float(v[i].w * mul), a7 = __uint_as_float(v[i].w & msk);
                    s[i >> 1] += ((a0 + a1) + (a2 + a3)) + ((a4 + a5) + (a6 + a7));
                    q[i >> 1] += fmaf(a0, a0, fmaf(a1, a1, fmaf(a2, a2, a3 * a3))) + fmaf(a4, a4, fmaf(a5, a5, fmaf(a6, a6, a7 * a7)));
                }
            }
#pragma unroll
            for (int o = 1; o < 8; o <<= 1) {
#pragma unroll
                for (int i = 0; i < 3; i++) { s[i] += __shfl_xor_sync(~0u, s[i], o); q[i] += __shfl_xor_sync(~0u, q[i], o); }
            }
            const int k = ut & 7, row = (ut >> 3) + 16 * k;
            const float mean = (k == 0 ? s[0] : (k == 1 ? s[1] : s[2])) * (1.f / 256.f);
            const float msq = (k == 0 ? q[0] : (k == 1 ? q[1] : q[2])) * (1.f / 256.f);
            const float alpha = (uint32_t)(pt * 32 - 8 + row) >= T_ ? 0.f : 0.5f;
            const float rstd = alpha * rsq(fmaxf(fmaf(-mean, mean, msq), 0.f) + 1e-5f);
            if (k < 3) sts64f(sb + OFF_STATS + row * 8, mean * rstd, rstd);
            __syncwarp();
            if (lane == 0) mbar_arrive(bars + B_ST * 8);
            TS(4);
        } else if (warp < 10) {
            const int w = warp - 8;
            const uint32_t ring = sb + OFF_RING + w * NSLOT * SLOT;
            const uint32_t full = bars + (B_FULL + w * NSLOT) * 8;
            if (lane == 0) {
#pragma unroll
                for (int i = 0; i < NSLOT; i++) { mbar_init(full + i * 8, 1); mbar_init(full + (B_EMPTY - B_FULL + i) * 8, 4); }
                asm volatile("fence.mbarrier_init.release.cluster;" ::: "memory");
                fence_async_smem();
            }
            __syncwarp();
            cluster_arrive();
            TS(1);
#pragma unroll
            for (int n = 0; n < NSLOT; n++) {
                if (n == 1 || n == 2) bar_sync(12, 64);
                ring_load(ring + n * SLOT, &p.tm[0], 64 * (8 * r + 4 * w + (n >> 1)), 8 * ((n & 1) ^ r), full + n * 8);
            }
            TS(2);
            const uint32_t code = load_code(lane, r, w) | (load_code(lane + 32, r, w) << 16);
            cluster_wait();
            uint32_t s = 0, ph = 0;
            int n = NSLOT;
#pragma unroll 1
            for (int seg = 0; seg < 2; seg++) {
#pragma unroll 1
                for (; n < (seg == 0 ? 22 : NLOADS); n++) {
                    const uint32_t c = __shfl_sync(~0u, code, n) >> (n & 32 ? 16 : 0);
                    const CUtensorMap* tm = &p.tm[c & 15];
                    const uint32_t col = (c & 0xf0) * 4, row = (c & 0xff00) >> 5, dst = ring + s * SLOT;
                    mbar_wait(full + (B_EMPTY - B_FULL) * 8 + s * 8, ph + (((uint32_t)(size_t)tm | col | row | dst) & p.zero));
                    ring_load(dst, tm, col, row, full + s * 8);
                    if (++s == NSLOT) { s = 0; ph ^= 1; }
                }
                if (seg == 1) break;
                const uint32_t epoch = ld_epoch();
                const uint32_t rdy = bars + (B_RDY + 3 * w) * 8, prdy = mapa(rdy, r ^ 1);
                const int odd = r ^ w;
                const uint32_t* flags = g_flag_kv + (abh * 32 + lane) * KFS;
                auto kv_load = [&](uint32_t sl, int isv, int i) {
                    ring_load_both(ring + sl * SLOT, &p.tm[8], (isv * 64 + abh * 8 + 2 * i + w) * 128, full + sl * 8);
                };
#pragma unroll 1
                for (int i = 0; i < 2; i++) {
                    if (lane < 3 + i) {
                        const uint32_t sl = i ? lane : lane + 2;
                        mbar_wait(full + (B_EMPTY - B_FULL + sl) * 8, i ^ 1);
                        mbar_arrive_tx(full + sl * 8, (i || lane == 2) ? SLOT : 0);
                    }
                    __syncwarp();
                }
                if (lane == 0) mbar_arrive_peer(prdy);
                bar_sync(14, 96);
                spin(KDELAY);
                mbar_wait(rdy, 0);
                flag_wait(flags, epoch, (lane >> 2) == 2 * odd + w);
                TSW(5 + 2 * odd);
                if (!odd) { kv_load(4, 0, 0); bar_arrive(12, 64); }
                else bar_sync(12, 64);
                spin(w ? KD3 : KD2);
                kv_load(odd ^ 1, odd ^ 1, odd);
                flag_wait(flags, epoch, (lane >> 2) == 2 * odd + w + 4);
                mbar_wait(full + (odd ^ 1) * 8, 1);
                kv_load(2 + odd, odd, 2 - odd);
#pragma unroll 1
                for (int i = 0; i < 3; i++) {
                    const uint32_t sl = i ? i - 1 : 4, bo = i == 2 ? 16 : 8;
                    mbar_wait(full + (B_EMPTY - B_FULL + sl) * 8, i != 0);
                    if (lane == 0) mbar_arrive_tx(full + sl * 8, SLOT);
                    if ((i & 1) != odd) {
                        mbar_wait(rdy + bo, 0);
                        kv_load(sl, i != 0, 2 + odd);
                    } else if (lane == 0) mbar_arrive_peer(prdy + bo);
                    __syncwarp();
                }
                n = 32; s = 2; ph = 1;
            }
        } else if (warp == 10) {
            if (lane == 0) {
#pragma unroll
                for (int i = B_XA; i <= B_ST; i++) mbar_init(bars + i * 8, i == B_ST ? 4 : 1);
#pragma unroll
                for (int i = B_XA; i <= B_SR; i++) mbar_arrive_tx(bars + i * 8, i < B_XB ? 512 : (i == B_X2 ? 12288 : 8192));
                asm volatile("fence.mbarrier_init.release.cluster;" ::: "memory");
                fence_async_smem();
            }
            __syncwarp();
            cluster_arrive();
            cluster_wait();
        } else {
            const uint32_t kb = (lane < 2 || lane > 5) ? 4096 : (lane == 2 ? 3072 : (lane == 4 ? 2048 : 1024));
            const char* pf = p.w[lane & 7] + blockIdx.x * kb;
            cluster_arrive();
            cluster_wait();
            if (lane < 2) prefetch_l2(pf, kb);
            mbar_wait(bars + B_XA * 8, 0);
            if (lane == 2) prefetch_l2(pf, kb);
            if (lane >= 1 && lane < 9) asm volatile("prefetch.tensormap [%0];" ::"l"(&p.tm[lane]) : "memory");
            mbar_wait(bars + (B_FULL + 1) * 8, 1);
            if (lane > 2 && lane < 8) prefetch_l2(pf, kb);
            if (lane == 8 && blockIdx.x < 15) prefetch_l2(p.dw + blockIdx.x * 256, 512);
            const uint32_t epoch = ld_epoch();
            bar_sync(4, 288);
            if (lane < 16) flag_set(&g_flag_kv[((b * 4 + 2 * r + (lane >> 3)) * 32 + pt) * KFS + (lane & 7)], epoch);
            __syncwarp();
            bar_arrive(14, 96);
            TSW(8);
        }
        TSDUMP();
        return;
    }

    const int w = warp >> 2, wq = warp & 3;
    const int tile = 2 * r + w;
    const int wt = tid & 127;
    const int c4 = lane & 3;
    const int trow = pt * 32 + 8 * wq;
    uint32_t xr[8];
    {
        const uint32_t* xp = reinterpret_cast<const uint32_t*>(p.x + (size_t)(b * T_ + trow + (lane >> 2)) * 256 + tile * 64) + c4;
#pragma unroll
        for (int j = 0; j < 8; j++) xr[j] = trow < T_ ? __ldg(xp + 4 * j) : 0u;
    }
    cluster_arrive();
    asm volatile("setmaxnreg.inc.sync.aligned.u32 208;");
    const uint32_t rbase = sb + OFF_RING + w * NSLOT * SLOT, fbar = bars + (B_FULL + w * NSLOT) * 8;
    const uint32_t rdesc = desc_lo(rbase);
    auto acq = [&](int n) { mbar_wait(fbar + (n % NSLOT) * 8, (n / NSLOT) & 1); };
    auto rel = [&](int n) { if (lane == 0) mbar_arrive(fbar + (B_EMPTY - B_FULL + n % NSLOT) * 8); };
    const uint32_t foff = (lane & 7) * 128 + (((lane >> 3) ^ (lane & 7)) << 4);
    const uint32_t toff = ((lane >> 4) * 8 + (lane & 7)) * 128 + (((2 * wq + ((lane >> 3) & 1)) ^ (lane & 7)) << 4);
    auto publish = [&](int bar, uint32_t src, uint32_t bytes, int nsync) {
        fence_async_smem();
        bar_sync(2 + w, 128);
        if (wq == 0) peer_copy(mapa(src, r ^ 1), src, bytes, mapa(bars + bar * 8, r ^ 1));
        bar_sync(nsync == 384 ? 1 : 10, nsync);
    };
    float v[16];
#pragma unroll
    for (int j = 0; j < 8; j++) { v[2 * j] = blo(xr[j]); v[2 * j + 1] = bhi(xr[j]); }
    const uint32_t xown = __shfl_sync(~0u, P + wt * 16 + tile * 4096, lane), xrem = __shfl_sync(~0u, P + wt * 16 + (r ^ 1) * 8192, lane);
    const uint32_t sbuf = __shfl_sync(~0u, sb + OFF_MISC + 1024 + (8 * wq + (lane >> 2)) * 32, lane);
    const uint32_t sown = __shfl_sync(~0u, sbuf + tile * 8, lane);
    const uint32_t peer = __shfl_sync(~0u, mapa(sb, r ^ 1) - sb, lane);
    const uint32_t meta = __shfl_sync(~0u, 0xEEEE4444u + p.zero, lane);
    cluster_wait();
    TS(56);
    float mean, msq;

#pragma unroll 1
    for (int ph = 0;; ph++) {
        uint4 o0, o1;
        {
            float s = 0.f, q = 0.f, s2 = 0.f, q2 = 0.f;
#pragma unroll
            for (int j = 0; j < 4; j++) {
                s += v[4 * j] + v[4 * j + 1]; s2 += v[4 * j + 2] + v[4 * j + 3];
                q += fmaf(v[4 * j], v[4 * j], v[4 * j + 1] * v[4 * j + 1]); q2 += fmaf(v[4 * j + 2], v[4 * j + 2], v[4 * j + 3] * v[4 * j + 3]);
            }
            s += s2; q += q2;
            const uint32_t xa = bars + (B_XA + ph) * 8;
            s += __shfl_xor_sync(~0u, s, 1); q += __shfl_xor_sync(~0u, q, 1);
            s += __shfl_xor_sync(~0u, s, 2); q += __shfl_xor_sync(~0u, q, 2);
            if (c4 == 0) st_async2f(sown + peer, s, q, xa + peer);
            if (c4 == 0) sts64f(sown, s, q);
#pragma unroll
            for (int j = 0; j < 8; j++) xr[j] = pack2(v[2 * j], v[2 * j + 1]);
            sts128(xown, xr[0], xr[1], xr[2], xr[3]);
            sts128(xown + 2048, xr[4], xr[5], xr[6], xr[7]);
            bar_sync(10, 256);
            o0 = lds128(xown ^ 4096); o1 = lds128((xown ^ 4096) + 2048);
            if (ph < 3) {
                st_async4(xown + peer, xr[0], xr[1], xr[2], xr[3], xa + (B_XB - B_XA) * 8 + peer);
                st_async4(xown + peer + 2048, xr[4], xr[5], xr[6], xr[7], xa + (B_XB - B_XA) * 8 + peer);
            }
            TS(57 + ph);
            if (ph == 0) acq(0);
            mbar_wait(xa, 0);
            const float4 u0 = lds128f(sbuf), u1 = lds128f(sbuf + 16);
            mean = ((u0.x + u0.z) + (u1.x + u1.z)) * (1.f / 256.f);
            msq = ((u0.y + u0.w) + (u1.y + u1.w)) * (1.f / 256.f);
        }
        if (ph == 3) break;
        uint32_t a[32];
        const uint32_t mean2 = pack2(mean, mean);
        auto centre = [&](int i, const uint4& u) {
            a[i] = hsub2(u.x, mean2); a[i + 1] = hsub2(u.y, mean2); a[i + 2] = hsub2(u.z, mean2); a[i + 3] = hsub2(u.w, mean2);
        };
#pragma unroll
        for (int j = 0; j < 8; j++) a[j] = hsub2(xr[j], mean2);
        centre(8, o0); centre(12, o1);
        const float rstd = rsq(fmaxf(fmaf(-mean, mean, msq), 0.f) + 1e-5f);
        auto gather_peer = [&]() {
            mbar_wait(bars + (B_XB + ph) * 8, 0);
#pragma unroll
            for (int i = 0; i < 4; i++) centre(16 + 4 * i, lds128(xrem + i * 2048));
        };
        auto sp = [&](float (&d)[32], int n, const uint32_t* af, int flip, int acc) {
            const uint32_t lo = rdesc + p.zero * (ph + n + 1) + (n % NSLOT) * (SLOT >> 4);
            const uint64_t b0 = mkdesc(lo + flip * 512), b1 = mkdesc(lo + (flip ^ 1) * 512);
            wg_fence();
            mma_sp(d, af, b0, meta, acc);
            mma_sp(d, af + 4, b0 + 256, meta, 1);
            mma_sp(d, af + 8, b1, meta, 1);
            mma_sp(d, af + 12, b1 + 256, meta, 1);
            wg_commit();
        };
        float d0[32], d1[32];

        if (ph != 1) {
            uint32_t h[32];
            const float rs = 0.5f * rstd;
            const uint32_t inb = bars + (B_INB + ph) * 8, box = H + wt * 16;
            bool ready = true;
            auto step = [&](float (&d)[32], int n, const uint32_t* af, int flip, int acc, auto work) {
                if (!ready) acq(n);
                if (((TURN >> n) & 1) && w == 1) bar_sync(7, 256);
                sp(d, n, af, flip, acc);
                if (n > 0 && ((TURN >> (n - 1)) & 1) && w == 0) bar_arrive(7, 256);
                if (n < 15) ready = mbar_test(fbar + ((n + 1) % NSLOT) * 8, ((n + 1) / NSLOT) & 1);
                wg_wait<1>();
                if (n > 0 && !((EAGER >> (n - 1)) & 1)) rel(n - 1);
                const uint32_t tie = work() & p.zero;
                if ((EAGER >> n) & 1) {
                    if (p.zero < n + ph + 1) wg_wait<0>();
                    if (lane == 0) mbar_arrive(fbar + (B_EMPTY - B_FULL + n % NSLOT) * 8 + tie);
                }
            };
            auto none = []() { return 0u; };
            auto act = [&](float (&d)[32], int i) {
                pin(d);
#pragma unroll
                for (int j = 0; j < 8; j++) {
                    const float u0 = (d[4 * j] + d[4 * j + 2]) * rs, u1 = (d[4 * j + 1] + d[4 * j + 3]) * rs;
                    h[8 * i + j] = pack2(fmaf(u0, tanh_fast(u0), u0), fmaf(u1, tanh_fast(u1), u1));
                }
                return h[8 * i] | h[8 * i + 1] | h[8 * i + 2] | h[8 * i + 3] | h[8 * i + 4] | h[8 * i + 5] | h[8 * i + 6] | h[8 * i + 7];
            };
            auto send = [&](float (&d)[32], int x) {
                pin(d);
                uint32_t pk[8];
#pragma unroll
                for (int j = 0; j < 8; j++) pk[j] = pack2(d[4 * j] + d[4 * j + 2], d[4 * j + 1] + d[4 * j + 3]);
                const uint32_t ow = w ^ (x & 1), dst = box + (ow * 3 + x - 1) * 4096;
                if (x & 2) {
                    st_async4(dst + peer, pk[0], pk[1], pk[2], pk[3], inb + ow * 8 + peer);
                    st_async4(dst + peer + 2048, pk[4], pk[5], pk[6], pk[7], inb + ow * 8 + peer);
                } else {
                    sts128(dst, pk[0], pk[1], pk[2], pk[3]);
                    sts128(dst + 2048, pk[4], pk[5], pk[6], pk[7]);
                }
            };
            TS(1 + ph * 10);
            step(d0, 0, a, w, 0, [&]() { gather_peer(); return 0u; });
            TS(32);
            step(d0, 1, a + 16, 0, 1, none);
            step(d1, 2, a, w, 0, [&]() { return act(d0, 0); });
            step(d1, 3, a + 16, 0, 1, none);
            step(d0, 4, a, w, 0, [&]() { return act(d1, 1); });
            TS(33);
            step(d0, 5, a + 16, 0, 1, none);
            step(d1, 6, a, w, 0, [&]() { return act(d0, 2); });
            step(d1, 7, a + 16, 0, 1, none);
            step(d0, 8, h, 0, 0, [&]() { return act(d1, 3); });
            TS(2 + ph * 10);
            step(d0, 9, h + 16, 0, 1, none);
            step(d1, 10, h, 0, 0, [&]() { send(d0, 3); return 0u; });
            step(d1, 11, h + 16, 0, 1, none);
            step(d0, 12, h, 0, 0, [&]() { send(d1, 2); return 0u; });
            TS(34);
            step(d0, 13, h + 16, 0, 1, none);
            step(d1, 14, h, 0, 0, [&]() { send(d0, 1); return 0u; });
            step(d1, 15, h + 16, 0, 1, none);
            if (ph == 0) acq(16);
            mbar_wait(inb + w * 8, 0);
            bar_sync(10, 256);
#pragma unroll
            for (int i = 0; i < 2; i++) {
                const uint32_t src = box + w * 12288 + i * 2048;
                const uint4 u0 = lds128(src), u1 = lds128(src + 4096), u2 = lds128(src + 8192);
                const uint32_t p0[4] = {u0.x, u0.y, u0.z, u0.w}, p1[4] = {u1.x, u1.y, u1.z, u1.w}, p2[4] = {u2.x, u2.y, u2.z, u2.w};
#pragma unroll
                for (int j = 0; j < 4; j++) {
                    v[8 * i + 2 * j] = fmaf(0.5f, blo(p0[j]) + blo(p1[j]) + blo(p2[j]), blo(xr[4 * i + j]));
                    v[8 * i + 2 * j + 1] = fmaf(0.5f, bhi(p0[j]) + bhi(p1[j]) + bhi(p2[j]), bhi(xr[4 * i + j]));
                }
            }
            wg_wait<0>();
            pin(d1);
            rel(15);
            TS(3 + ph * 10);
#pragma unroll
            for (int j = 0; j < 8; j++) {
                v[2 * j] = fmaf(0.5f, d1[4 * j] + d1[4 * j + 2], v[2 * j]);
                v[2 * j + 1] = fmaf(0.5f, d1[4 * j + 1] + d1[4 * j + 3], v[2 * j + 1]);
            }
            continue;
        }

        {
            TS(11);
            const uint32_t stg = H + warp * 2048;
            unsigned char* g = g_kvq + (size_t)((b * 4 + tile) * 1024 + trow) * 128 + lane * 16;
            auto put = [&](float (&d)[32], int i) {
                pin(d);
                uint32_t pk[8];
#pragma unroll
                for (int j = 0; j < 8; j++) pk[j] = pack2((d[4 * j] + d[4 * j + 2]) * rstd, (d[4 * j + 1] + d[4 * j + 3]) * rstd);
                if (i == 2) {
                    st_data(g + 2097152, pk[0], pk[1], pk[2], pk[3]);
                    st_data(g + 2097152 + 512, pk[4], pk[5], pk[6], pk[7]);
                    return;
                }
                stsm4(stg + i * 1024 + foff, pk[0], pk[1], pk[2], pk[3]);
                stsm4(stg + i * 1024 + (foff ^ 64), pk[4], pk[5], pk[6], pk[7]);
                __syncwarp();
                const uint4 u0 = lds128(stg + i * 1024 + lane * 16), u1 = lds128(stg + i * 1024 + 512 + lane * 16);
                stg128(g + i * 1048576, u0); stg128(g + i * 1048576 + 512, u1);
            };
            sp(d0, 16, a, w, 0);
            acq(17);
            sp(d1, 17, a, w, 0);
            gather_peer();
            acq(18);
            sp(d0, 18, a + 16, 0, 1);
            wg_wait<1>();
            rel(16); rel(17);
            acq(19);
            sp(d1, 19, a + 16, 0, 1);
            wg_wait<1>();
            rel(18);
            put(d0, 0);
            wg_wait<0>();
            rel(19);
            TS(37);
            put(d1, 1);
            bar_arrive(4, 288);
            TS(38);
            acq(20);
            sp(d0, 20, a, w, 0);
            acq(21);
            sp(d0, 21, a + 16, 0, 1);
            acq(22); acq(23);
            rel(22); rel(23);
            mbar_wait(bars + B_RST * 8, 0);
            wg_wait<0>();
            rel(20); rel(21);
            put(d0, 2);
            if (wq == 0 || wq == 3) {
                uint4* hp = &g_halo[((pair * 4 + tile) * 2 + (wq & 1)) * 64 + lane];
                st_data(hp, xr[0], xr[1], xr[2], xr[3]);
                st_data(hp + 32, xr[4], xr[5], xr[6], xr[7]);
            }
            TS(12);
        }

        const uint32_t xo = P + tile * XCH + wq * 1024, xt = P + tile * XCH + toff;
        {
            constexpr float CS = 0.125f * 1.4426950408889634f;
            float sa[32], sb2[32], o[36];
            uint32_t pa[16], pb[16], q[16];
            float n0 = INFINITY, n1 = INFINITY;
            zero(o); zero(pa); zero(pb); zero(sb2);
            const uint32_t ones = sb + OFF_MISC + 2048;
            { const uint32_t c = w ? 0u : 0x3F803F80u; sts128(ones + tid * 16, c, c, c, c); }
            fence_async_smem();
            bar_sync(10, 256);
            stsm4(xo + 1024 + foff, xr[0], xr[1], xr[2], xr[3]);
            stsm4(xo + 1024 + (foff ^ 64), xr[4], xr[5], xr[6], xr[7]);
            const uint32_t vdesc = rdesc + ((((ones - rbase) >> 4) - 1) << 16);
            auto qk_issue = [&](float (&s)[32], uint32_t lo) {
                const uint64_t kd = mkdesc(lo);
                wg_fence();
#pragma unroll
                for (int k = 0; k < 4; k++) mma_qk(s, q[4 * k], q[4 * k + 1], q[4 * k + 2], q[4 * k + 3], kd + 2 * k, k != 0);
                wg_commit();
            };
            auto both_issue = [&](float (&s)[32], uint32_t klo, uint32_t (&pp)[16], uint32_t vlo) {
                const uint64_t kd = mkdesc(klo), vd = mkdesc(vlo);
                wg_fence();
#pragma unroll
                for (int k = 0; k < 4; k++) {
                    mma_pv(o, pp[4 * k], pp[4 * k + 1], pp[4 * k + 2], pp[4 * k + 3], vd - k * (128 * 65535));
                    mma_qk(s, q[4 * k], q[4 * k + 1], q[4 * k + 2], q[4 * k + 3], kd + 2 * k, k != 0);
                }
                wg_commit();
            };
            auto new_max = [&](float (&s)[32], int nj, float& x0, float& x1) {
                x0 = s[0]; x1 = s[2];
#pragma unroll
                for (int j = 0; j < nj; j++) {
                    x0 = fmaxf(x0, fmaxf(s[4 * j], s[4 * j + 1]));
                    x1 = fmaxf(x1, fmaxf(s[4 * j + 2], s[4 * j + 3]));
                }
                x0 = fmaxf(x0, __shfl_xor_sync(~0u, x0, 1)); x1 = fmaxf(x1, __shfl_xor_sync(~0u, x1, 1));
                x0 = fmaxf(x0, __shfl_xor_sync(~0u, x0, 2)); x1 = fmaxf(x1, __shfl_xor_sync(~0u, x1, 2));
                x0 = fminf(n0, fmaf(x0, -CS, -20.f)); x1 = fminf(n1, fmaf(x1, -CS, -20.f));
            };
            auto probs = [&](float (&s)[32], uint32_t (&pp)[16], bool ready, bool tail, auto wait) {
                uint32_t any = 0;
#pragma unroll
                for (int i = 0; i < 16; i++) {
                    pp[i] = pack2(ex2(fmaf(s[2 * i], CS, (i & 1) ? n1 : n0)), ex2(fmaf(s[2 * i + 1], CS, (i & 1) ? n1 : n0)));
                    any |= pp[i];
                }
                wg_wait<0>();
                pin(sa); pin(sb2); pin(o); pin(pa); pin(pb);
                if (__any_sync(~0u, (any & 0x40004000u) || !ready)) {
                    wait();
                    if (__any_sync(~0u, any & 0x40004000u)) {
                        if (tail) {
#pragma unroll
                            for (int i = 20; i < 32; i++) s[i] = -INFINITY;
                        }
                        float x0, x1;
                        new_max(s, 8, x0, x1);
                        const float sc0 = ex2(x0 - n0), sc1 = ex2(x1 - n1);
                        n0 = x0; n1 = x1;
#pragma unroll
                        for (int j = 0; j < 9; j++) { o[4 * j] *= sc0; o[4 * j + 1] *= sc0; o[4 * j + 2] *= sc1; o[4 * j + 3] *= sc1; }
#pragma unroll
                        for (int i = 0; i < 16; i++)
                            pp[i] = pack2(ex2(fmaf(s[2 * i], CS, (i & 1) ? n1 : n0)), ex2(fmaf(s[2 * i + 1], CS, (i & 1) ? n1 : n0)));
                    }
                }
            };
            {
                uint4 u[4];
                const unsigned char* src = g_kvq + 2097152 + (size_t)(abh * 1024 + qt * 64 + wq * 16) * 128 + lane * 16;
                spin(QGATE);
                ld_data<512>(u, src);
#pragma unroll
                for (int k = 0; k < 2; k++) {
                    q[8 * k] = u[k].x; q[8 * k + 1] = u[k + 2].x; q[8 * k + 2] = u[k].y; q[8 * k + 3] = u[k + 2].y;
                    q[8 * k + 4] = u[k].z; q[8 * k + 5] = u[k + 2].z; q[8 * k + 6] = u[k].w; q[8 * k + 7] = u[k + 2].w;
                }
                pin(q);
            }
            TS(40);
            acq(24);
            TS(13);
            qk_issue(sa, rdesc + (24 % NSLOT) * (SLOT >> 4));
            wg_wait<0>();
            pin(sa);
            {
                float x0, x1;
                new_max(sa, NJ0, x0, x1);
                n0 = x0; n1 = x1;
            }
            bar_arrive(6, 384);
            uint32_t vd = vdesc - (SLOT >> 4) * 65535u, kd = rdesc, vb = fbar + 8, kb = fbar;
            uint32_t vlast = vdesc - 4 * (SLOT >> 4) * 65535u, klast = rdesc + 4 * (SLOT >> 4) + 512;
            uint32_t kprev = fbar + 32, vprev = bars + (B_SINK - (B_EMPTY - B_FULL)) * 8;
#pragma unroll 1
            for (int it = 0; it < 4; it++) {
                both_issue(sb2, klast, pb, vlast);
                probs(sa, pa, mbar_test(vb, it < 2) & mbar_test(kb, it < 3), false, [&]() { mbar_wait(vb, it < 2); mbar_wait(kb, it < 3); });
                TS(41 + it * 4);
                if (lane == 0) mbar_arrive(kprev + (B_EMPTY - B_FULL) * 8);
                if (lane == 0) mbar_arrive(vprev + (B_EMPTY - B_FULL) * 8);
                both_issue(sa, kd, pa, vd);
                const int dv = it == 0 ? 2 : (it == 1 ? -3 : 1);
                kprev = kb; vprev = vb; vlast = vd - 512 * 65535u; klast = kd + 512;
                vd -= dv * (SLOT >> 4) * 65535u; vb += dv * 8;
                kd += (it == 2 ? -3 : 2) * (SLOT >> 4); kb = it == 2 ? vb : kb + 16;
                probs(sb2, pb, true, it == 3 && w == 1, []() {});
                TS(43 + it * 4);
            }
            wg_fence();
#pragma unroll
            for (int k = 0; k < 4; k++)
                mma_pv(o, pb[4 * k], pb[4 * k + 1], pb[4 * k + 2], pb[4 * k + 3], mkdesc(vlast - k * (128 * 65535) + (k > 1 ? w * ((k - 1) << 22) : 0)));
            wg_commit();
            const int row = wq * 16 + (lane >> 2);
            const uint32_t ml = sb + OFF_MISC;
            mbar_wait(bars + (B_RST + 1) * 8, 0);
            wg_wait<0>();
            pin(o); pin(pb); pin(sa); pin(sb2);
            rel(31);
            const float l0 = o[32], l1 = o[34];
            if (c4 == 0) { sts64f(ml + w * 512 + row * 8, n0, l0); sts64f(ml + w * 512 + row * 8 + 64, n1, l1); }
            TS(14);
            float mine[16];
#pragma unroll
            for (int j = 0; j < 4; j++) {
                if (w == 0) sts128f(H + j * 2048 + wt * 16, o[16 + 4 * j], o[17 + 4 * j], o[18 + 4 * j], o[19 + 4 * j]);
                else sts128f(H + 8192 + j * 2048 + wt * 16, o[4 * j], o[4 * j + 1], o[4 * j + 2], o[4 * j + 3]);
            }
#pragma unroll
            for (int i = 0; i < 16; i++) mine[i] = w == 0 ? o[i] : o[16 + i];
            bar_sync(10, 256);
            const float2 u0 = lds64f(ml + (w ^ 1) * 512 + row * 8), u1 = lds64f(ml + (w ^ 1) * 512 + row * 8 + 64);
            const float x0 = fminf(n0, u0.x), x1 = fminf(n1, u1.x);
            float a0 = ex2(x0 - n0), b0 = ex2(x0 - u0.x), a1 = ex2(x1 - n1), b1 = ex2(x1 - u1.x);
            const float i0 = __fdividef(1.f, fmaf(a0, l0, b0 * u0.y)), i1 = __fdividef(1.f, fmaf(a1, l1, b1 * u1.y));
            a0 *= i0; b0 *= i0; a1 *= i1; b1 *= i1;
            uint32_t pk[8];
#pragma unroll
            for (int j = 0; j < 4; j++) {
                const float4 v = lds128f(H + (w ^ 1) * 8192 + j * 2048 + wt * 16);
                pk[2 * j] = pack2(fmaf(a0, mine[4 * j], b0 * v.x), fmaf(a0, mine[4 * j + 1], b0 * v.y));
                pk[2 * j + 1] = pack2(fmaf(a1, mine[4 * j + 2], b1 * v.z), fmaf(a1, mine[4 * j + 3], b1 * v.w));
            }
            unsigned char* dst = g_o + (size_t)(abh * PADROWS + 8 + qt * 64 + wq * 16) * 128 + w * 512 + lane * 16;
            st_data(dst, pk[0], pk[2], pk[4], pk[6]);
            st_data(dst + 1024, pk[1], pk[3], pk[5], pk[7]);
            if (tid == 0) asm volatile("red.relaxed.gpu.global.add.u32 [%0], 1;" ::"l"(&g_epoch[blockIdx.x * FS]) : "memory");
            TS(15);
        }

        auto mm = [&](float (&d)[24], int n, uint32_t act, int acc) {
            const uint32_t z = p.zero * (ph + n);
            const uint64_t ad = mkdesc(rdesc + z + (n % NSLOT) * (SLOT >> 4)), bd = mkdesc(desc_lo(act) + z);
            wg_fence();
#pragma unroll
            for (int k = 0; k < 8; k++) mma_t(d, ad + k * 128, bd + (k >> 2) * (XCH >> 4) + (k & 3) * 2, k == 0 ? acc : 1);
            wg_commit();
        };
        uint32_t dwr[15];
        {
#pragma unroll
            for (int i = 0; i < 15; i++) dwr[i] = hmul2(__ldg(reinterpret_cast<const uint32_t*>(p.dw + i * 256 + tile * 64) + lane), 0x3F003F00u);
            float d[24];
            uint32_t xw[12];
            bar_sync(9, 384);
#pragma unroll
            for (int j = 0; j < 3; j++) ldsm4t(xt + j * 2048, xw[4 * j], xw[4 * j + 1], xw[4 * j + 2], xw[4 * j + 3]);
            pin(xw);
            acq(32); acq(33); acq(34); acq(35);
            {
                if (ODELAY) spin(ODELAY);
                uint4 u[6];
                ld_data<1024>(u, g_o + (size_t)((b * 4 + (warp >> 1)) * PADROWS + pt * 32) * 128 + (warp & 1) * 512 + lane * 16);
                const uint32_t dst = H + (warp >> 1) * XCH + (foff ^ ((warp & 1) * 64));
#pragma unroll
                for (int i = 0; i < 6; i++) stsm4(dst + i * 1024, u[i].x, u[i].y, u[i].z, u[i].w);
            }
            fence_async_smem();
            bar_sync(10, 256);
            TS(16);
            mm(d, 32, H, 0);
            mm(d, 33, H + 2 * XCH, 1);
            wg_wait<1>();
            rel(32);
            wg_wait<0>();
            pin(d);
#pragma unroll
            for (int i = 0; i < 12; i++) xw[i] = pack2(d[2 * i] + blo(xw[i]), d[2 * i + 1] + bhi(xw[i]));
            if (c4 == 0) { xw[0] = (xw[0] & 0xffff0000u) | 0x3F80u; xw[1] = (xw[1] & 0xffff0000u) | 0x3F80u; }
#pragma unroll
            for (int j = 0; j < 3; j++) stsm4t(xt + j * 2048, xw[4 * j], xw[4 * j + 1], xw[4 * j + 2], xw[4 * j + 3]);
            rel(33);
            publish(B_X2, P + tile * XCH, XCH, 384);
            TS(17);
        }
        {
            float da[24], db[24], st[24];
            bar_sync(5, 384);
            mm(da, 34, P + 2 * r * XCH, 0);
            mm(db, 35, P + 2 * r * XCH, 0);
            acq(36); acq(37);
            mbar_wait(bars + B_X2 * 8, 0);
            bar_sync(5, 384);
            TS(39);
            mm(da, 36, P + 2 * (r ^ 1) * XCH, 1);
            mm(db, 37, P + 2 * (r ^ 1) * XCH, 1);
            wg_wait<2>();
            rel(34); rel(35);
            mbar_wait(bars + B_ST * 8, 0);
#pragma unroll
            for (int j = 0; j < 6; j++) {
                const float4 u = lds128f(sb + OFF_STATS + (8 * j + 2 * c4) * 8);
                st[4 * j] = u.x; st[4 * j + 1] = u.y; st[4 * j + 2] = u.z; st[4 * j + 3] = u.w;
            }
            wg_wait<0>();
            pin(da); pin(db);
            rel(36); rel(37);
            TS(18);
            uint32_t pk[12];
#pragma unroll
            for (int hh = 0; hh < 2; hh++) {
                const float ca = __shfl_sync(~0u, da[2 * hh], lane & 28), cb = __shfl_sync(~0u, db[2 * hh], lane & 28);
#pragma unroll
                for (int j = 0; j < 6; j++) {
                    const float u0 = fmaf(-st[4 * j], ca, da[4 * j + 2 * hh] * st[4 * j + 1]);
                    const float u1 = fmaf(-st[4 * j + 2], ca, da[4 * j + 2 * hh + 1] * st[4 * j + 3]);
                    const float v0 = fmaf(-st[4 * j], cb, db[4 * j + 2 * hh] * st[4 * j + 1]);
                    const float v1 = fmaf(-st[4 * j + 2], cb, db[4 * j + 2 * hh + 1] * st[4 * j + 3]);
                    pk[2 * j + hh] = pack2(fmaf(u0, tanh_fast(v0), u0), fmaf(u1, tanh_fast(v1), u1));
                }
            }
            const uint32_t gs = H + 16384 + w * XCH;
#pragma unroll
            for (int j = 0; j < 3; j++) stsm4t(gs + toff + j * 2048, pk[4 * j], pk[4 * j + 1], pk[4 * j + 2], pk[4 * j + 3]);
            ldsm4(xo + 1024 + foff, xr[0], xr[1], xr[2], xr[3]);
            ldsm4(xo + 1024 + (foff ^ 64), xr[4], xr[5], xr[6], xr[7]);
            bar_sync(2 + w, 128);
            uint32_t ca[8], cb[8];
            const uint32_t grow = gs + 8 * wq * 128 + c4 * 4, srow = H + tile * HCH + 8 * wq * 128 + c4 * 4;
#pragma unroll
            for (int k = 0; k < 22; k++) {
                const uint32_t v = lds32(grow + (1 + k) * 128 + (((lane >> 2) ^ ((1 + k) & 7)) << 4));
#pragma unroll
                for (int i = 0; i < 8; i++) {
                    const int tap = k - i;
                    if (tap == 0) ca[i] = hmul2(v, dwr[0]);
                    else if (tap > 0 && tap < 8) ca[i] = hfma2(v, dwr[tap], ca[i]);
                    else if (tap == 8) cb[i] = hmul2(v, dwr[8]);
                    else if (tap > 8 && tap < 15) cb[i] = hfma2(v, dwr[tap], cb[i]);
                }
            }
#pragma unroll
            for (int i = 0; i < 8; i++) {
                const float h0 = blo(ca[i]) + blo(cb[i]), h1 = bhi(ca[i]) + bhi(cb[i]);
                sts32(srow + i * 128 + (((lane >> 2) ^ i) << 4), pack2(fmaf(h0, tanh_fast(h0), h0), fmaf(h1, tanh_fast(h1), h1)));
            }
            acq(38); acq(39);
            publish(B_SR, H + tile * HCH, HCH, 256);
            TS(19);
        }
        {
            auto frags = [&](int i, int half) {
                const uint32_t src = H + 2 * half * HCH + wq * 1024;
#pragma unroll
                for (int k = 0; k < 4; k++) ldsm4(src + (k >> 1) * HCH + (foff ^ ((k & 1) * 64)), a[i + 4 * k], a[i + 4 * k + 1], a[i + 4 * k + 2], a[i + 4 * k + 3]);
            };
            frags(0, r);
            sp(d0, 38, a, 0, 0);
            acq(40);
            mbar_wait(bars + B_SR * 8, 0);
            frags(16, r ^ 1);
            sp(d0, 39, a + 16, 0, 1);
            wg_wait<1>();
            rel(38);
            wg_wait<0>();
            pin(d0);
            rel(39);
#pragma unroll
            for (int j = 0; j < 8; j++) {
                v[2 * j] = d0[4 * j] + d0[4 * j + 2] + blo(xr[j]);
                v[2 * j + 1] = d0[4 * j + 1] + d0[4 * j + 3] + bhi(xr[j]);
            }
            TS(20);
        }
    }

    cluster_arrive();
    TS(24);
    {
        const float rstd = rsq(fmaxf(fmaf(-mean, mean, msq), 0.f) + 1e-5f), nb = -mean * rstd;
#pragma unroll
        for (int j = 0; j < 8; j++) xr[j] = pack2(fmaf(v[2 * j], rstd, nb), fmaf(v[2 * j + 1], rstd, nb));
        const uint32_t stg = P + 16384 + warp * 1024;
        stsm4(stg + foff, xr[0], xr[1], xr[2], xr[3]);
        stsm4(stg + (foff ^ 64), xr[4], xr[5], xr[6], xr[7]);
        __syncwarp();
        const uint32_t src = stg + (lane >> 3) * 128 + (((lane & 7) ^ (lane >> 3)) << 4);
        const uint4 u0 = lds128(src), u1 = lds128((src + 512) ^ 64);
        __nv_bfloat16* dst = p.out + (size_t)(b * T_ + trow + (lane >> 3)) * 256 + tile * 64 + (lane & 7) * 8;
        if (trow < T_) { stg128(dst, u0); stg128(dst + 4 * 256, u1); }
    }
    TS(25);
    TG(31);
    TSDUMP();
    cluster_wait();
}

typedef CUresult (*EncodeFn)(CUtensorMap*, CUtensorMapDataType, cuuint32_t, void*, const cuuint64_t*, const cuuint64_t*,
                             const cuuint32_t*, const cuuint32_t*, CUtensorMapInterleave, CUtensorMapSwizzle,
                             CUtensorMapL2promotion, CUtensorMapFloatOOBfill);

}

extern "C" void kernel_launch(void* const* d_in, const int* in_sizes, int n_in, void* d_out, int out_size) {
    static EncodeFn encode = nullptr;
    if (!encode) {
        void* fn = nullptr;
        cudaDriverEntryPointQueryResult qr;
        cudaGetDriverEntryPoint("cuTensorMapEncodeTiled", &fn, cudaEnableDefault, &qr);
        encode = (EncodeFn)fn;
        cudaFuncSetAttribute(conformer_kernel, cudaFuncAttributeMaxDynamicSharedMemorySize, SMEM_LAUNCH);
    }
    Params p;
    const cuuint32_t ones[5] = {1, 1, 1, 1, 1};
    const int idx[8] = {1, 2, 3, 4, 5, 7, 8, 9};
    const int rows[8] = {256, 1024, 256, 256, 256, 256, 256, 1024};
    const int cols[8] = {1024, 256, 768, 256, 512, 256, 1024, 256};
    for (int i = 0; i < 8; i++) {
        const bool perm = i != 3 && i != 4;
        const cuuint64_t pitch = (cuuint64_t)cols[i] * 2;
        const cuuint64_t dims[5] = {(cuuint64_t)cols[i], 2, 2, 4, (cuuint64_t)rows[i] / 16};
        const cuuint64_t strides[4] = {pitch, pitch * (perm ? 8 : 2), pitch * (perm ? 2 : 4), pitch * 16};
        const cuuint32_t box[5] = {64, 2, 2, 4, 8};
        encode(&p.tm[i], CU_TENSOR_MAP_DATA_TYPE_BFLOAT16, 5, d_in[idx[i]], dims, strides, box, ones, CU_TENSOR_MAP_INTERLEAVE_NONE,
               CU_TENSOR_MAP_SWIZZLE_128B, CU_TENSOR_MAP_L2_PROMOTION_L2_128B, CU_TENSOR_MAP_FLOAT_OOB_FILL_NONE);
        p.w[i] = (const char*)d_in[idx[i]];
    }
    {
        void* kv = nullptr;
        cudaGetSymbolAddress(&kv, g_kvq);
        const cuuint64_t dims[2] = {64, 16384};
        const cuuint64_t strides[1] = {128};
        const cuuint32_t box[2] = {64, 128};
        encode(&p.tm[8], CU_TENSOR_MAP_DATA_TYPE_BFLOAT16, 2, kv, dims, strides, box, ones, CU_TENSOR_MAP_INTERLEAVE_NONE,
               CU_TENSOR_MAP_SWIZZLE_NONE, CU_TENSOR_MAP_L2_PROMOTION_L2_128B, CU_TENSOR_MAP_FLOAT_OOB_FILL_NONE);
    }
    p.x = (const __nv_bfloat16*)d_in[0];
    p.dw = (const __nv_bfloat16*)d_in[6];
    p.out = (__nv_bfloat16*)d_out;
    p.zero = 0;
    conformer_kernel<<<NCTA, NTHREADS, SMEM_LAUNCH>>>(p);
}
```

```cpp
#include <cuda_runtime.h>
#include <cuda_bf16.h>
#include <cuda.h>
#include <stdint.h>

namespace {

constexpr int T_ = 1000;
constexpr int NCTA = 128;
constexpr int NTHREADS = 512;
constexpr int NSLOT = 5;
constexpr int SLOT = 16384;
constexpr int NLOADS = 56;

constexpr uint32_t OFF_RING = 0;
constexpr uint32_t OFF_P = 163840;
constexpr uint32_t OFF_H = 188416;
constexpr uint32_t OFF_MISC = 221184;
constexpr uint32_t OFF_STATS = 229376;
constexpr uint32_t OFF_BARS = 229888;
constexpr uint32_t SMEM_BYTES = 230400;
constexpr uint32_t XCH = 6144;
constexpr uint32_t HCH = 4096;

constexpr int B_FULL = 0, B_EMPTY = 10, B_XA = 20  , B_XB = 24  , B_INB = 27  , B_X2 = 31, B_SR = 32,
              B_PS = 33, B_RST = 34  , B_RDY = 36  , B_SINK = 42, B_ST = 43;

#define KD2 300u
#define KD3 500u
#define ODELAY 0u
#define QGATE 500u
#define BACKOFF 0u
#define KFS 8
#define KDELAY 300u
#define NJ0 2
#define PSTAG 1
#define TURN 0
#define EAGER 0x5555
constexpr int PADROWS = 1040;
constexpr int FS = 8;

struct Params {
    CUtensorMap tm[9];
    const char* w[8];
    const __nv_bfloat16* x;
    const __nv_bfloat16* dw;
    __nv_bfloat16* out;
    uint32_t zero;
};

__device__ __align__(1024) unsigned char g_kvq[3 * 8 * 1024 * 128];
__device__ __align__(1024) unsigned char g_o[8 * PADROWS * 128];
__device__ uint4 g_halo[64 * 4 * 2 * 64];
__device__ __align__(128) uint32_t g_flag_kv[8 * 32 * KFS];
__device__ uint32_t g_reset[4 * 32];
__device__ uint32_t g_epoch[NCTA * FS];

#define TS(i) do { } while (0)
#define TSW(i) do { } while (0)
#define TG(i) do { } while (0)
#define TSINIT() do { } while (0)
#define TSDUMP() do { } while (0)
constexpr uint32_t SMEM_LAUNCH = SMEM_BYTES;

__device__ __forceinline__ uint32_t smem_u32(const void* p) { return (uint32_t)__cvta_generic_to_shared(p); }
__device__ __forceinline__ void mbar_init(uint32_t b, uint32_t c) { asm volatile("mbarrier.init.shared::cta.b64 [%0], %1;" ::"r"(b), "r"(c) : "memory"); }
__device__ __forceinline__ void mbar_arrive(uint32_t b) { asm volatile("mbarrier.arrive.shared::cta.b64 _, [%0];" ::"r"(b) : "memory"); }
__device__ __forceinline__ void mbar_arrive_tx(uint32_t b, uint32_t tx) { asm volatile("mbarrier.arrive.expect_tx.shared::cta.b64 _, [%0], %1;" ::"r"(b), "r"(tx) : "memory"); }
__device__ __forceinline__ void mbar_wait(uint32_t b, uint32_t ph) {
    asm volatile("{\n.reg .pred p, q;\n.reg .u32 c;\nmov.u32 c, 0;\n"
                 "MW_LOOP:\n.pragma \"nounroll\";\n"
                 "mbarrier.try_wait.parity.shared::cta.b64 p, [%0], %1;\n"
                 "add.u32 c, c, 1;\nsetp.lt.u32 q, c, 65536;\nnot.pred p, p;\nand.pred p, p, q;\n@p bra MW_LOOP;\n}"
                 ::"r"(b), "r"(ph) : "memory");
}
__device__ __forceinline__ bool mbar_test(uint32_t b, uint32_t ph) {
    uint32_t ok;
    asm volatile("{\n.reg .pred p;\nmbarrier.test_wait.parity.shared::cta.b64 p, [%1], %2;\nselp.u32 %0, 1, 0, p;\n}" : "=r"(ok) : "r"(b), "r"(ph) : "memory");
    return ok;
}
__device__ __forceinline__ uint32_t mapa(uint32_t a, uint32_t r) { uint32_t o; asm("mapa.shared::cluster.u32 %0, %1, %2;" : "=r"(o) : "r"(a), "r"(r)); return o; }
__device__ __forceinline__ void fence_async_smem() { asm volatile("fence.proxy.async.shared::cta;" ::: "memory"); }
__device__ __forceinline__ void fence_async_global() { asm volatile("fence.proxy.async.global;" ::: "memory"); }
__device__ __forceinline__ void bar_sync(int id, int n) { asm volatile("bar.sync %0, %1;" ::"r"(id), "r"(n) : "memory"); }
__device__ __forceinline__ void bar_arrive(int id, int n) { asm volatile("bar.arrive %0, %1;" ::"r"(id), "r"(n) : "memory"); }
__device__ __forceinline__ void cluster_arrive() { asm volatile("barrier.cluster.arrive.relaxed.aligned;" ::: "memory"); }
__device__ __forceinline__ void cluster_wait() { asm volatile("barrier.cluster.wait.aligned;" ::: "memory"); }

__device__ __forceinline__ void ring_load(uint32_t dst, const CUtensorMap* tm, int col, int row16, uint32_t bar) {
    asm volatile("{\n.reg .pred p;\nelect.sync _|p, 0xffffffff;\n"
                 "@p mbarrier.arrive.expect_tx.shared::cta.b64 _, [%2], 16384;\n"
                 "@p cp.async.bulk.tensor.5d.shared::cluster.global.mbarrier::complete_tx::bytes [%0], [%1, {%3, 0, 0, 0, %4}], [%2];\n}"
                 ::"r"(dst), "l"(tm), "r"(bar), "r"(col), "r"(row16) : "memory");
}
__device__ __forceinline__ void ring_load_both(uint32_t dst, const CUtensorMap* tm, int c1, uint32_t bar) {
    asm volatile("{\n.reg .pred p;\nelect.sync _|p, 0xffffffff;\n"
                 "@p cp.async.bulk.tensor.2d.shared::cluster.global.mbarrier::complete_tx::bytes.multicast::cluster [%0], [%1, {0, %3}], [%2], %4;\n}"
                 ::"r"(dst), "l"(tm), "r"(bar), "r"(c1), "h"((uint16_t)3) : "memory");
}
__device__ __forceinline__ void mbar_arrive_peer(uint32_t b) { asm volatile("mbarrier.arrive.relaxed.cluster.shared::cluster.b64 _, [%0];" ::"r"(b) : "memory"); }
__device__ __forceinline__ void prefetch_l2(const void* src, uint32_t bytes) {
    asm volatile("cp.async.bulk.prefetch.L2.global [%0], %1;" ::"l"(src), "r"(bytes) : "memory");
}
__device__ __forceinline__ void peer_copy(uint32_t dst, uint32_t src, uint32_t bytes, uint32_t rbar) {
    asm volatile("{\n.reg .pred p;\nelect.sync _|p, 0xffffffff;\n"
                 "@p cp.async.bulk.shared::cluster.shared::cta.mbarrier::complete_tx::bytes [%0], [%1], %2, [%3];\n}"
                 ::"r"(dst), "r"(src), "r"(bytes), "r"(rbar) : "memory");
}
__device__ __forceinline__ void st_async4(uint32_t dst, uint32_t a, uint32_t b, uint32_t c, uint32_t d, uint32_t bar) {
    asm volatile("st.async.shared::cluster.mbarrier::complete_tx::bytes.v4.b32 [%0], {%1,%2,%3,%4}, [%5];" ::"r"(dst), "r"(a), "r"(b), "r"(c), "r"(d), "r"(bar) : "memory");
}
__device__ __forceinline__ void st_async2f(uint32_t dst, float a, float b, uint32_t bar) {
    asm volatile("st.async.shared::cluster.mbarrier::complete_tx::bytes.v2.f32 [%0], {%1,%2}, [%3];" ::"r"(dst), "f"(a), "f"(b), "r"(bar) : "memory");
}
__device__ __forceinline__ void stsm4t(uint32_t a, uint32_t r0, uint32_t r1, uint32_t r2, uint32_t r3) {
    asm volatile("stmatrix.sync.aligned.m8n8.x4.trans.shared.b16 [%0], {%1,%2,%3,%4};" ::"r"(a), "r"(r0), "r"(r1), "r"(r2), "r"(r3) : "memory");
}
__device__ __forceinline__ void stsm4(uint32_t a, uint32_t r0, uint32_t r1, uint32_t r2, uint32_t r3) {
    asm volatile("stmatrix.sync.aligned.m8n8.x4.shared.b16 [%0], {%1,%2,%3,%4};" ::"r"(a), "r"(r0), "r"(r1), "r"(r2), "r"(r3) : "memory");
}
__device__ __forceinline__ void ldsm4t(uint32_t a, uint32_t& r0, uint32_t& r1, uint32_t& r2, uint32_t& r3) {
    asm volatile("ldmatrix.sync.aligned.m8n8.x4.trans.shared.b16 {%0,%1,%2,%3}, [%4];" : "=r"(r0), "=r"(r1), "=r"(r2), "=r"(r3) : "r"(a) : "memory");
}
__device__ __forceinline__ void ldsm4(uint32_t a, uint32_t& r0, uint32_t& r1, uint32_t& r2, uint32_t& r3) {
    asm volatile("ldmatrix.sync.aligned.m8n8.x4.shared.b16 {%0,%1,%2,%3}, [%4];" : "=r"(r0), "=r"(r1), "=r"(r2), "=r"(r3) : "r"(a) : "memory");
}
__device__ __forceinline__ uint4 lds128(uint32_t a) { uint4 v; asm volatile("ld.shared.v4.b32 {%0,%1,%2,%3}, [%4];" : "=r"(v.x), "=r"(v.y), "=r"(v.z), "=r"(v.w) : "r"(a) : "memory"); return v; }
__device__ __forceinline__ float4 lds128f(uint32_t a) { float4 v; asm volatile("ld.shared.v4.f32 {%0,%1,%2,%3}, [%4];" : "=f"(v.x), "=f"(v.y), "=f"(v.z), "=f"(v.w) : "r"(a) : "memory"); return v; }
__device__ __forceinline__ float2 lds64f(uint32_t a) { float2 v; asm volatile("ld.shared.v2.f32 {%0,%1}, [%2];" : "=f"(v.x), "=f"(v.y) : "r"(a) : "memory"); return v; }
__device__ __forceinline__ uint32_t lds32(uint32_t a) { uint32_t v; asm volatile("ld.shared.b32 %0, [%1];" : "=r"(v) : "r"(a) : "memory"); return v; }
__device__ __forceinline__ void sts128(uint32_t a, uint32_t x, uint32_t y, uint32_t z, uint32_t w) { asm volatile("st.shared.v4.b32 [%0], {%1,%2,%3,%4};" ::"r"(a), "r"(x), "r"(y), "r"(z), "r"(w) : "memory"); }
__device__ __forceinline__ void sts128f(uint32_t a, float x, float y, float z, float w) { asm volatile("st.shared.v4.f32 [%0], {%1,%2,%3,%4};" ::"r"(a), "f"(x), "f"(y), "f"(z), "f"(w) : "memory"); }
__device__ __forceinline__ void sts64f(uint32_t a, float x, float y) { asm volatile("st.shared.v2.f32 [%0], {%1,%2};" ::"r"(a), "f"(x), "f"(y) : "memory"); }
__device__ __forceinline__ void sts32(uint32_t a, uint32_t x) { asm volatile("st.shared.b32 [%0], %1;" ::"r"(a), "r"(x) : "memory"); }
__device__ __forceinline__ void stg128(void* p, uint4 v) { asm volatile("st.global.v4.b32 [%0], {%1,%2,%3,%4};" ::"l"(p), "r"(v.x), "r"(v.y), "r"(v.z), "r"(v.w) : "memory"); }

__device__ __forceinline__ uint32_t pack2(float lo, float hi) { uint32_t r; asm("cvt.rn.bf16x2.f32 %0, %1, %2;" : "=r"(r) : "f"(hi), "f"(lo)); return r; }
__device__ __forceinline__ float blo(uint32_t v) { return __uint_as_float(v << 16); }
__device__ __forceinline__ float bhi(uint32_t v) { return __uint_as_float(v & 0xffff0000u); }
__device__ __forceinline__ uint32_t hmul2(uint32_t a, uint32_t b) { uint32_t r; asm("mul.rn.bf16x2 %0, %1, %2;" : "=r"(r) : "r"(a), "r"(b)); return r; }
__device__ __forceinline__ uint32_t hsub2(uint32_t a, uint32_t b) { uint32_t r; asm("sub.rn.bf16x2 %0, %1, %2;" : "=r"(r) : "r"(a), "r"(b)); return r; }
__device__ __forceinline__ uint32_t hfma2(uint32_t a, uint32_t b, uint32_t c) { uint32_t r; asm("fma.rn.bf16x2 %0, %1, %2, %3;" : "=r"(r) : "r"(a), "r"(b), "r"(c)); return r; }
__device__ __forceinline__ float tanh_fast(float x) { float r; asm("tanh.approx.f32 %0, %1;" : "=f"(r) : "f"(x)); return r; }
__device__ __forceinline__ float rsq(float x) { float r; asm("rsqrt.approx.ftz.f32 %0, %1;" : "=f"(r) : "f"(x)); return r; }
__device__ __forceinline__ float ex2(float x) { float r; asm("ex2.approx.ftz.f32 %0, %1;" : "=f"(r) : "f"(x)); return r; }

__device__ __forceinline__ uint32_t ld_relaxed(const uint32_t* p) {
    uint32_t v;
    asm volatile("ld.relaxed.gpu.global.u32 %0, [%1];" : "=r"(v) : "l"(p) : "memory");
    return v;
}
__device__ __forceinline__ uint32_t clock32() { uint32_t c; asm volatile("mov.u32 %0, %%clock;" : "=r"(c)::"memory"); return c; }
__device__ __forceinline__ void spin(uint32_t clks) {
    const uint32_t t0 = clock32();
    while (clock32() - t0 < clks) {}
}
__device__ __forceinline__ void flag_wait(const uint32_t* p, uint32_t e, bool mine) {
#pragma unroll 1
    for (int i = 0; i < (1 << 19); i++) {
        if (mine) mine = ld_relaxed(p) != e;
        if (!__any_sync(~0u, mine)) break;
        if (BACKOFF) spin(BACKOFF);
    }
    asm volatile("fence.acquire.gpu;" ::: "memory");
    fence_async_global();
}
__device__ __forceinline__ void st_data(void* p, uint32_t x, uint32_t y, uint32_t z, uint32_t w) {
    asm volatile("st.relaxed.gpu.global.v4.b32 [%0], {%1,%2,%3,%4};" ::"l"(p), "r"(x), "r"(y), "r"(z), "r"(w) : "memory");
}
template <int STRIDE, int N>
__device__ __forceinline__ void ld_data(uint4 (&v)[N], const unsigned char* p) {
    int it = 0;
    bool again;
#pragma unroll 1
    do {
        uint32_t m = 0;
#pragma unroll
        for (int i = 0; i < N; i++)
            asm volatile("ld.relaxed.gpu.global.v4.b32 {%0,%1,%2,%3}, [%4];" : "=r"(v[i].x), "=r"(v[i].y), "=r"(v[i].z), "=r"(v[i].w) : "l"(p + i * STRIDE) : "memory");
#pragma unroll
        for (int i = 0; i < N; i++) m = __vimax3_u32(__vimax3_u32(v[i].x, v[i].y, v[i].z), v[i].w, m);
        again = __any_sync(~0u, m == ~0u) && ++it < (1 << 16);
    } while (again);
}
__device__ __forceinline__ uint32_t ld_epoch() { return ld_relaxed(&g_epoch[blockIdx.x * FS]) + 1; }
__device__ __forceinline__ void flag_set(uint32_t* p, uint32_t e) { asm volatile("st.release.gpu.global.u32 [%0], %1;" ::"l"(p), "r"(e) : "memory"); }

__device__ __forceinline__ uint32_t desc_lo(uint32_t addr) { return ((addr & 0x3FFFF) >> 4) | 0x10000u; }
__device__ __forceinline__ uint64_t mkdesc(uint32_t lo) { return (uint64_t)lo | (0x40000040ull << 32); }
__device__ __forceinline__ void wg_fence() { asm volatile("wgmma.fence.sync.aligned;" ::: "memory"); }
__device__ __forceinline__ void wg_commit() { asm volatile("wgmma.commit_group.sync.aligned;" ::: "memory"); }
template <int N> __device__ __forceinline__ void wg_wait() { asm volatile("wgmma.wait_group.sync.aligned %0;" ::"n"(N) : "memory"); }
template <int N> __device__ __forceinline__ void pin(float (&d)[N]) {
#pragma unroll
    for (int i = 0; i < N; i++) asm volatile("" : "+f"(d[i])::"memory");
}
template <int N> __device__ __forceinline__ void pin(uint32_t (&d)[N]) {
#pragma unroll
    for (int i = 0; i < N; i++) asm volatile("" : "+r"(d[i])::"memory");
}

template <typename Tp, int N> __device__ __forceinline__ void zero(Tp (&d)[N]) {
#pragma unroll
    for (int i = 0; i < N; i++) d[i] = 0;
    pin(d);
}

#define F4(d, i) "+f"(d[i]), "+f"(d[i + 1]), "+f"(d[i + 2]), "+f"(d[i + 3])
#define F16(d, i) F4(d, i), F4(d, i + 4), F4(d, i + 8), F4(d, i + 12)

__device__ __forceinline__ void mma_sp(float (&d)[32], const uint32_t* a, uint64_t b, uint32_t meta, int acc) {
    asm volatile("{.reg .pred p; setp.ne.b32 p, %38, 0;\n"
                 "wgmma.mma_async.sp.sync.aligned.m64n64k32.f32.bf16.bf16 {%0,%1,%2,%3,%4,%5,%6,%7,%8,%9,%10,%11,%12,%13,%14,%15,%16,%17,%18,%19,%20,%21,%22,%23,%24,%25,%26,%27,%28,%29,%30,%31}, "
                 "{%32,%33,%34,%35}, %36, %37, 0, p, 1, 1, 1;}\n"
                 : F16(d, 0), F16(d, 16) : "r"(a[0]), "r"(a[1]), "r"(a[2]), "r"(a[3]), "l"(b), "r"(meta), "r"(acc));
}
__device__ __forceinline__ void mma_t(float (&d)[24], uint64_t a, uint64_t b, int acc) {
    asm volatile("{.reg .pred p; setp.ne.b32 p, %26, 0;\n"
                 "wgmma.mma_async.sync.aligned.m64n48k16.f32.bf16.bf16 {%0,%1,%2,%3,%4,%5,%6,%7,%8,%9,%10,%11,%12,%13,%14,%15,%16,%17,%18,%19,%20,%21,%22,%23}, %24, %25, p, 1, 1, 1, 0;}\n"
                 : F16(d, 0), F4(d, 16), F4(d, 20) : "l"(a), "l"(b), "r"(acc));
}
__device__ __forceinline__ void mma_qk(float (&d)[32], uint32_t a0, uint32_t a1, uint32_t a2, uint32_t a3, uint64_t b, int acc) {
    asm volatile("{.reg .pred p; setp.ne.b32 p, %37, 0;\n"
                 "wgmma.mma_async.sync.aligned.m64n64k16.f32.bf16.bf16 {%0,%1,%2,%3,%4,%5,%6,%7,%8,%9,%10,%11,%12,%13,%14,%15,%16,%17,%18,%19,%20,%21,%22,%23,%24,%25,%26,%27,%28,%29,%30,%31}, "
                 "{%32,%33,%34,%35}, %36, p, 1, 1, 0;}\n"
                 : F16(d, 0), F16(d, 16) : "r"(a0), "r"(a1), "r"(a2), "r"(a3), "l"(b), "r"(acc));
}
__device__ __forceinline__ void mma_pv(float (&d)[36], uint32_t a0, uint32_t a1, uint32_t a2, uint32_t a3, uint64_t b) {
    asm volatile("wgmma.mma_async.sync.aligned.m64n72k16.f32.bf16.bf16 {%0,%1,%2,%3,%4,%5,%6,%7,%8,%9,%10,%11,%12,%13,%14,%15,%16,%17,%18,%19,%20,%21,%22,%23,%24,%25,%26,%27,%28,%29,%30,%31,%32,%33,%34,%35}, "
                 "{%36,%37,%38,%39}, %40, 1, 1, 1, 1;\n"
                 : F16(d, 0), F16(d, 16), F4(d, 32) : "r"(a0), "r"(a1), "r"(a2), "r"(a3), "l"(b));
}

__device__ __forceinline__ uint32_t load_code(int n, int r, int w) {
    const int tile = 2 * r + w;
    int m, col, row;
    if (n < 16 || n >= 40) {
        const int k = n < 16 ? n : n - 40;
        m = n < 16 ? 0 : 6;
        if (k < 8) { col = 4 * tile + (k >> 1); row = (k & 1) ^ r; }
        else { m++; col = tile ^ (3 - ((k - 8) >> 1)); row = 2 * tile + (k & 1); }
    } else if (n < 32) {
        const int k = n - 16;
        m = 2;
        if (k < 4) { col = tile + ((k & 1) ? 8 : 4); row = (k >> 1) ^ r; }
        else { col = tile; row = (k & 1) ^ r; }
    } else if (n < 34) { m = 3; col = tile; row = n - 32; }
    else if (n < 38) { const int k = n - 34; m = 4; col = tile + 4 * (k & 1); row = (k >> 1) ^ r; }
    else { m = 5; col = tile; row = (n & 1) ^ r; }
    return m | (col << 4) | (row << 8);
}

__global__ void __cluster_dims__(2, 1, 1) __launch_bounds__(NTHREADS, 1)
conformer_kernel(const __grid_constant__ Params p) {
    extern __shared__ __align__(1024) unsigned char smem_raw[];
    const uint32_t sb = smem_u32(smem_raw);
    const uint32_t bars = sb + OFF_BARS;
    const int tid = threadIdx.x;
    const int lane = tid & 31;
    const int warp = __shfl_sync(~0u, tid >> 5, 0);
    const int r = blockIdx.x & 1;
    const int pair = blockIdx.x >> 1;
    const int b = pair >> 5, pt = pair & 31;
    const int ah = pt >> 3, qt = (pt & 7) * 2 + r;
    const int abh = b * 4 + ah;

    TG(30);
    TSINIT();
    TS(0);
    const uint32_t P = sb + OFF_P, H = sb + OFF_H;

    if (warp >= 8) {
        asm volatile("setmaxnreg.dec.sync.aligned.u32 48;");
        if (warp >= 12) {
            cluster_arrive();
            cluster_wait();
            const int ut = tid & 127;
            const uint32_t target = ld_epoch() * 64;
            auto reset_done = [&](int k) {
                bar_sync(11, 128);
                if (ut == 0) {
                    asm volatile("red.release.gpu.global.add.u32 [%0], 1;" ::"l"(&g_reset[(2 * b + k) * 32]) : "memory");
#pragma unroll 1
                    for (int i = 0; i < (1 << 20) && ld_relaxed(&g_reset[(2 * b + k) * 32]) != target; i++) __nanosleep(100);
                    asm volatile("fence.acquire.gpu;" ::: "memory");
                    mbar_arrive(bars + (B_RST + k) * 8);
                }
                __syncwarp();
                TS(13 + k);
            };
#pragma unroll
            for (int i = 0; i < 4; i++) {
                st_data(g_kvq + 2097152 + (size_t)((b * 4 + 2 * r + (i >> 1)) * 1024 + pt * 32) * 128 + (i & 1) * 2048 + ut * 16, ~0u, ~0u, ~0u, ~0u);
                if (i < 2) st_data(&g_halo[(pair * 4 + 2 * r + i) * 128 + ut], ~0u, ~0u, ~0u, ~0u);
            }
            reset_done(0);
            bar_sync(6, 384);
#pragma unroll
            for (int i = 0; i < 4; i++) st_data(g_o + (size_t)(abh * PADROWS + 8 + qt * 64) * 128 + i * 2048 + ut * 16, ~0u, ~0u, ~0u, ~0u);
            reset_done(1);
            {
                const int side = warp & 1, t = 2 * r + ((warp >> 1) & 1), np = side ? pt + 1 : pt - 1;
                uint4 hv[2] = {make_uint4(0, 0, 0, 0), make_uint4(0, 0, 0, 0)};
                if (np >= 0 && np < 32)
                    ld_data<512>(hv, reinterpret_cast<const unsigned char*>(&g_halo[(((b * 32 + np) * 4 + t) * 2 + (side ^ 1)) * 64 + lane]));
                const uint32_t dst = P + t * XCH + side * 5120 + (lane & 7) * 128 + (((lane >> 3) ^ (lane & 7)) << 4);
                stsm4(dst, hv[0].x, hv[0].y, hv[0].z, hv[0].w);
                stsm4(dst ^ 64, hv[1].x, hv[1].y, hv[1].z, hv[1].w);
                bar_arrive(9, 384);
            }
            const uint32_t a8 = P + 2 * r * XCH + (ut >> 3) * 128 + (ut & 7) * 16;
            float s[3], q[3];
            bar_sync(1, 384);
            uint4 v[6];
#pragma unroll
            for (int i = 0; i < 6; i++) v[i] = lds128(a8 + (i & 1) * XCH + (i >> 1) * 2048);
            bar_arrive(5 + ((v[0].w | v[1].w | v[2].w | v[3].w | v[4].w | v[5].w) & p.zero), 384);
            const uint32_t mul = 65536u + (clock32() & p.zero), msk = 0u - mul;
#pragma unroll
            for (int i = 0; i < 6; i++) {
                const float a0 = __uint_as_float(v[i].x * mul), a1 = __uint_as_float(v[i].x & msk), a2 = __uint_as_float(v[i].y * mul), a3 = __uint_as_float(v[i].y & msk);
                const float a4 = __uint_as_float(v[i].z * mul), a5 = __uint_as_float(v[i].z & msk), a6 = __uint_as_float(v[i].w * mul), a7 = __uint_as_float(v[i].w & msk);
                const float si = ((a0 + a1) + (a2 + a3)) + ((a4 + a5) + (a6 + a7));
                const float qi = fmaf(a0, a0, fmaf(a1, a1, fmaf(a2, a2, a3 * a3))) + fmaf(a4, a4, fmaf(a5, a5, fmaf(a6, a6, a7 * a7)));
                s[i >> 1] = (i & 1) ? s[i >> 1] + si : si;
                q[i >> 1] = (i & 1) ? q[i >> 1] + qi : qi;
            }
#pragma unroll
            for (int o = 1; o < 8; o <<= 1) {
#pragma unroll
                for (int i = 0; i < 3; i++) { s[i] += __shfl_xor_sync(~0u, s[i], o); q[i] += __shfl_xor_sync(~0u, q[i], o); }
            }
            const int k = ut & 7, row = (ut >> 3) + 16 * min(k, 2);
            const float so = k == 0 ? s[0] : (k == 1 ? s[1] : s[2]), qo = k == 0 ? q[0] : (k == 1 ? q[1] : q[2]);
            const uint32_t pb = sb + OFF_MISC + 6144 + row * 8;
            if (k < 3) st_async2f(mapa(pb, r ^ 1), so, qo, mapa(bars + B_PS * 8, r ^ 1));
            mbar_wait(bars + B_PS * 8, 0);
            const float2 pp = lds64f(pb);
            const float mean = (so + pp.x) * (1.f / 256.f), msq = (qo + pp.y) * (1.f / 256.f);
            const float alpha = (uint32_t)(pt * 32 - 8 + row) >= T_ ? 0.f : 0.5f;
            const float rstd = alpha * rsq(fmaxf(fmaf(-mean, mean, msq), 0.f) + 1e-5f);
            if (k < 3) sts64f(sb + OFF_STATS + row * 8, mean * rstd, rstd);
            __syncwarp();
            if (lane == 0) mbar_arrive(bars + B_ST * 8);
            TS(4);
        } else if (warp < 10) {
            const int w = warp - 8;
            const uint32_t ring = sb + OFF_RING + w * NSLOT * SLOT;
            const uint32_t full = bars + (B_FULL + w * NSLOT) * 8;
            if (lane == 0) {
#pragma unroll
                for (int i = 0; i < NSLOT; i++) { mbar_init(full + i * 8, 1); mbar_init(full + (B_EMPTY - B_FULL + i) * 8, 4); }
                asm volatile("fence.mbarrier_init.release.cluster;" ::: "memory");
                fence_async_smem();
            }
            __syncwarp();
            cluster_arrive();
            TS(1);
#pragma unroll
            for (int n = 0; n < NSLOT; n++) {
                if (n == 1 || n == 2) bar_sync(12, 64);
                ring_load(ring + n * SLOT, &p.tm[0], 64 * (8 * r + 4 * w + (n >> 1)), 8 * ((n & 1) ^ r), full + n * 8);
            }
            TS(2);
            const uint32_t code = load_code(lane, r, w) | (load_code(lane + 32, r, w) << 16);
            cluster_wait();
            uint32_t s = 0, ph = 0;
            int n = NSLOT;
#pragma unroll 1
            for (int seg = 0; seg < 2; seg++) {
#pragma unroll 1
                for (; n < (seg == 0 ? 22 : NLOADS); n++) {
                    const uint32_t c = __shfl_sync(~0u, code, n) >> (n & 32 ? 16 : 0);
                    const CUtensorMap* tm = &p.tm[c & 15];
                    const uint32_t col = (c & 0xf0) * 4, row = (c & 0xff00) >> 5, dst = ring + s * SLOT;
                    mbar_wait(full + (B_EMPTY - B_FULL) * 8 + s * 8, ph + (((uint32_t)(size_t)tm | col | row | dst) & p.zero));
                    ring_load(dst, tm, col, row, full + s * 8);
                    if (++s == NSLOT) { s = 0; ph ^= 1; }
                }
                if (seg == 1) break;
                const uint32_t epoch = ld_epoch();
                const uint32_t rdy = bars + (B_RDY + 3 * w) * 8, prdy = mapa(rdy, r ^ 1);
                const int odd = r ^ w;
                const uint32_t* flags = g_flag_kv + (abh * 32 + lane) * KFS;
                auto kv_load = [&](uint32_t sl, int isv, int i) {
                    ring_load_both(ring + sl * SLOT, &p.tm[8], (isv * 64 + abh * 8 + 2 * i + w) * 128, full + sl * 8);
                };
#pragma unroll 1
                for (int i = 0; i < 2; i++) {
                    if (lane < 3 + i) {
                        const uint32_t sl = i ? lane : lane + 2;
                        mbar_wait(full + (B_EMPTY - B_FULL + sl) * 8, i ^ 1);
                        mbar_arrive_tx(full + sl * 8, (i || lane == 2) ? SLOT : 0);
                    }
                    __syncwarp();
                }
                if (lane == 0) mbar_arrive_peer(prdy);
                bar_sync(14, 96);
                spin(KDELAY);
                mbar_wait(rdy, 0);
                flag_wait(flags, epoch, (lane >> 2) == 2 * odd + w);
                TSW(5 + 2 * odd);
                if (!odd) { kv_load(4, 0, 0); bar_arrive(12, 64); }
                else bar_sync(12, 64);
                spin(w ? KD3 : KD2);
                kv_load(odd ^ 1, odd ^ 1, odd);
                flag_wait(flags, epoch, (lane >> 2) == 2 * odd + w + 4);
                mbar_wait(full + (odd ^ 1) * 8, 1);
                kv_load(2 + odd, odd, 2 - odd);
#pragma unroll 1
                for (int i = 0; i < 3; i++) {
                    const uint32_t sl = i ? i - 1 : 4, bo = i == 2 ? 16 : 8;
                    mbar_wait(full + (B_EMPTY - B_FULL + sl) * 8, i != 0);
                    if (lane == 0) mbar_arrive_tx(full + sl * 8, SLOT);
                    if ((i & 1) != odd) {
                        mbar_wait(rdy + bo, 0);
                        kv_load(sl, i != 0, 2 + odd);
                    } else if (lane == 0) mbar_arrive_peer(prdy + bo);
                    __syncwarp();
                }
                n = 32; s = 2; ph = 1;
            }
        } else if (warp == 10) {
            if (lane == 0) {
#pragma unroll
                for (int i = B_XA; i <= B_ST; i++) mbar_init(bars + i * 8, i == B_ST ? 4 : 1);
#pragma unroll
                for (int i = B_XA; i <= B_PS; i++) mbar_arrive_tx(bars + i * 8, i < B_XB ? 512 : (i == B_X2 ? 12288 : (i == B_PS ? 384 : 8192)));
                asm volatile("fence.mbarrier_init.release.cluster;" ::: "memory");
                fence_async_smem();
            }
            __syncwarp();
            cluster_arrive();
            cluster_wait();
        } else {
            const uint32_t kb = (lane < 2 || lane > 5) ? 4096 : (lane == 2 ? 3072 : (lane == 4 ? 2048 : 1024));
            const char* pf = p.w[lane & 7] + blockIdx.x * kb;
            cluster_arrive();
            cluster_wait();
            if (lane < 2) prefetch_l2(pf, kb);
            mbar_wait(bars + B_XA * 8, 0);
            if (lane == 2) prefetch_l2(pf, kb);
            if (lane >= 1 && lane < 9) asm volatile("prefetch.tensormap [%0];" ::"l"(&p.tm[lane]) : "memory");
            mbar_wait(bars + (B_FULL + 1) * 8, 1);
            if (lane > 2 && lane < 8) prefetch_l2(pf, kb);
            if (lane == 8 && blockIdx.x < 15) prefetch_l2(p.dw + blockIdx.x * 256, 512);
            const uint32_t epoch = ld_epoch();
            bar_sync(4, 288);
            if (lane < 16) flag_set(&g_flag_kv[((b * 4 + 2 * r + (lane >> 3)) * 32 + pt) * KFS + (lane & 7)], epoch);
            __syncwarp();
            bar_arrive(14, 96);
            TSW(8);
        }
        TSDUMP();
        return;
    }

    const int w = warp >> 2, wq = warp & 3;
    const int tile = 2 * r + w;
    const int wt = tid & 127;
    const int c4 = lane & 3;
    const int trow = pt * 32 + 8 * wq;
    uint32_t xr[8];
    {
        const uint32_t* xp = reinterpret_cast<const uint32_t*>(p.x + (size_t)(b * T_ + trow + (lane >> 2)) * 256 + tile * 64) + c4;
#pragma unroll
        for (int j = 0; j < 8; j++) xr[j] = trow < T_ ? __ldg(xp + 4 * j) : 0u;
    }
    cluster_arrive();
    asm volatile("setmaxnreg.inc.sync.aligned.u32 208;");
    const uint32_t rbase = sb + OFF_RING + w * NSLOT * SLOT, fbar = bars + (B_FULL + w * NSLOT) * 8;
    const uint32_t rdesc = desc_lo(rbase);
    auto acq = [&](int n) { mbar_wait(fbar + (n % NSLOT) * 8, (n / NSLOT) & 1); };
    auto rel = [&](int n) { if (lane == 0) mbar_arrive(fbar + (B_EMPTY - B_FULL + n % NSLOT) * 8); };
    const uint32_t foff = (lane & 7) * 128 + (((lane >> 3) ^ (lane & 7)) << 4);
    const uint32_t toff = ((lane >> 4) * 8 + (lane & 7)) * 128 + (((2 * wq + ((lane >> 3) & 1)) ^ (lane & 7)) << 4);
    auto publish = [&](int bar, uint32_t src, uint32_t bytes, int nsync) {
        fence_async_smem();
        bar_sync(2 + w, 128);
        if (wq == 0) peer_copy(mapa(src, r ^ 1), src, bytes, mapa(bars + bar * 8, r ^ 1));
        bar_sync(nsync == 384 ? 1 : 10, nsync);
    };
    float v[16];
#pragma unroll
    for (int j = 0; j < 8; j++) { v[2 * j] = blo(xr[j]); v[2 * j + 1] = bhi(xr[j]); }
    const uint32_t xown = __shfl_sync(~0u, P + wt * 16 + tile * 4096, lane), xrem = __shfl_sync(~0u, P + wt * 16 + (r ^ 1) * 8192, lane);
    const uint32_t sbuf = __shfl_sync(~0u, sb + OFF_MISC + 1024 + (8 * wq + (lane >> 2)) * 32, lane);
    const uint32_t sown = __shfl_sync(~0u, sbuf + tile * 8, lane);
    const uint32_t peer = __shfl_sync(~0u, mapa(sb, r ^ 1) - sb, lane);
    const uint32_t meta = __shfl_sync(~0u, 0xEEEE4444u + p.zero, lane);
    cluster_wait();
    TS(56);
    float mean, msq;

#pragma unroll 1
    for (int ph = 0;; ph++) {
        uint4 o0, o1;
        {
            float s = 0.f, q = 0.f, s2 = 0.f, q2 = 0.f;
#pragma unroll
            for (int j = 0; j < 4; j++) {
                s += v[4 * j] + v[4 * j + 1]; s2 += v[4 * j + 2] + v[4 * j + 3];
                q += fmaf(v[4 * j], v[4 * j], v[4 * j + 1] * v[4 * j + 1]); q2 += fmaf(v[4 * j + 2], v[4 * j + 2], v[4 * j + 3] * v[4 * j + 3]);
            }
            s += s2; q += q2;
            const uint32_t xa = bars + (B_XA + ph) * 8;
            s += __shfl_xor_sync(~0u, s, 1); q += __shfl_xor_sync(~0u, q, 1);
            s += __shfl_xor_sync(~0u, s, 2); q += __shfl_xor_sync(~0u, q, 2);
            if (c4 == 0) st_async2f(sown + peer, s, q, xa + peer);
            if (c4 == 0) sts64f(sown, s, q);
#pragma unroll
            for (int j = 0; j < 8; j++) xr[j] = pack2(v[2 * j], v[2 * j + 1]);
            sts128(xown, xr[0], xr[1], xr[2], xr[3]);
            sts128(xown + 2048, xr[4], xr[5], xr[6], xr[7]);
            bar_sync(10, 256);
            o0 = lds128(xown ^ 4096); o1 = lds128((xown ^ 4096) + 2048);
            if (ph < 3) {
                st_async4(xown + peer, xr[0], xr[1], xr[2], xr[3], xa + (B_XB - B_XA) * 8 + peer);
                st_async4(xown + peer + 2048, xr[4], xr[5], xr[6], xr[7], xa + (B_XB - B_XA) * 8 + peer);
            }
            TS(57 + ph);
            if (ph == 0) acq(0);
            mbar_wait(xa, 0);
            const float4 u0 = lds128f(sbuf), u1 = lds128f(sbuf + 16);
            mean = ((u0.x + u0.z) + (u1.x + u1.z)) * (1.f / 256.f);
            msq = ((u0.y + u0.w) + (u1.y + u1.w)) * (1.f / 256.f);
        }
        if (ph == 3) break;
        uint32_t a[32];
        const uint32_t mean2 = pack2(mean, mean);
        auto centre = [&](int i, const uint4& u) {
            a[i] = hsub2(u.x, mean2); a[i + 1] = hsub2(u.y, mean2); a[i + 2] = hsub2(u.z, mean2); a[i + 3] = hsub2(u.w, mean2);
        };
#pragma unroll
        for (int j = 0; j < 8; j++) a[j] = hsub2(xr[j], mean2);
        centre(8, o0); centre(12, o1);
        const float rstd = rsq(fmaxf(fmaf(-mean, mean, msq), 0.f) + 1e-5f);
        auto gather_peer = [&]() {
            mbar_wait(bars + (B_XB + ph) * 8, 0);
#pragma unroll
            for (int i = 0; i < 4; i++) centre(16 + 4 * i, lds128(xrem + i * 2048));
        };
        auto sp = [&](float (&d)[32], int n, const uint32_t* af, int flip, int acc) {
            const uint32_t lo = rdesc + p.zero * (ph + n + 1) + (n % NSLOT) * (SLOT >> 4);
            const uint64_t b0 = mkdesc(lo + flip * 512), b1 = mkdesc(lo + (flip ^ 1) * 512);
            wg_fence();
            mma_sp(d, af, b0, meta, acc);
            mma_sp(d, af + 4, b0 + 256, meta, 1);
            mma_sp(d, af + 8, b1, meta, 1);
            mma_sp(d, af + 12, b1 + 256, meta, 1);
            wg_commit();
        };
        float d0[32], d1[32];

        if (ph != 1) {
            uint32_t h[32];
            const float rs = 0.5f * rstd;
            const uint32_t inb = bars + (B_INB + ph) * 8, box = H + wt * 16;
            bool ready = true;
            auto step = [&](float (&d)[32], int n, const uint32_t* af, int flip, int acc, auto work) {
                if (!ready) acq(n);
                if (((TURN >> n) & 1) && w == 1) bar_sync(7, 256);
                sp(d, n, af, flip, acc);
                if (n > 0 && ((TURN >> (n - 1)) & 1) && w == 0) bar_arrive(7, 256);
                if (n < 15) ready = mbar_test(fbar + ((n + 1) % NSLOT) * 8, ((n + 1) / NSLOT) & 1);
                wg_wait<1>();
                if (n > 0 && !((EAGER >> (n - 1)) & 1)) rel(n - 1);
                const uint32_t tie = work() & p.zero;
                if ((EAGER >> n) & 1) {
                    if (p.zero < n + ph + 1) wg_wait<0>();
                    if (lane == 0) mbar_arrive(fbar + (B_EMPTY - B_FULL + n % NSLOT) * 8 + tie);
                }
            };
            auto none = []() { return 0u; };
            auto act = [&](float (&d)[32], int i) {
                pin(d);
#pragma unroll
                for (int j = 0; j < 8; j++) {
                    const float u0 = (d[4 * j] + d[4 * j + 2]) * rs, u1 = (d[4 * j + 1] + d[4 * j + 3]) * rs;
                    h[8 * i + j] = pack2(fmaf(u0, tanh_fast(u0), u0), fmaf(u1, tanh_fast(u1), u1));
                }
                return h[8 * i] | h[8 * i + 1] | h[8 * i + 2] | h[8 * i + 3] | h[8 * i + 4] | h[8 * i + 5] | h[8 * i + 6] | h[8 * i + 7];
            };
            auto send = [&](float (&d)[32], int x) {
                pin(d);
                uint32_t pk[8];
#pragma unroll
                for (int j = 0; j < 8; j++) pk[j] = pack2(d[4 * j] + d[4 * j + 2], d[4 * j + 1] + d[4 * j + 3]);
                const uint32_t ow = w ^ (x & 1), dst = box + (ow * 3 + x - 1) * 4096;
                if (x & 2) {
                    st_async4(dst + peer, pk[0], pk[1], pk[2], pk[3], inb + ow * 8 + peer);
                    st_async4(dst + peer + 2048, pk[4], pk[5], pk[6], pk[7], inb + ow * 8 + peer);
                } else {
                    sts128(dst, pk[0], pk[1], pk[2], pk[3]);
                    sts128(dst + 2048, pk[4], pk[5], pk[6], pk[7]);
                }
            };
            TS(1 + ph * 10);
            step(d0, 0, a, w, 0, [&]() { gather_peer(); return 0u; });
            TS(32);
            step(d0, 1, a + 16, 0, 1, none);
            step(d1, 2, a, w, 0, [&]() { return act(d0, 0); });
            step(d1, 3, a + 16, 0, 1, none);
            step(d0, 4, a, w, 0, [&]() { return act(d1, 1); });
            TS(33);
            step(d0, 5, a + 16, 0, 1, none);
            step(d1, 6, a, w, 0, [&]() { return act(d0, 2); });
            step(d1, 7, a + 16, 0, 1, none);
            step(d0, 8, h, 0, 0, [&]() { return act(d1, 3); });
            TS(2 + ph * 10);
            step(d0, 9, h + 16, 0, 1, none);
            step(d1, 10, h, 0, 0, [&]() { send(d0, 3); return 0u; });
            step(d1, 11, h + 16, 0, 1, none);
            step(d0, 12, h, 0, 0, [&]() { send(d1, 2); return 0u; });
            TS(34);
            step(d0, 13, h + 16, 0, 1, none);
            step(d1, 14, h, 0, 0, [&]() { send(d0, 1); return 0u; });
            step(d1, 15, h + 16, 0, 1, none);
            if (ph == 0) acq(16);
            mbar_wait(inb + w * 8, 0);
            bar_sync(10, 256);
#pragma unroll
            for (int i = 0; i < 2; i++) {
                const uint32_t src = box + w * 12288 + i * 2048;
                const uint4 u0 = lds128(src), u1 = lds128(src + 4096), u2 = lds128(src + 8192);
                const uint32_t p0[4] = {u0.x, u0.y, u0.z, u0.w}, p1[4] = {u1.x, u1.y, u1.z, u1.w}, p2[4] = {u2.x, u2.y, u2.z, u2.w};
#pragma unroll
                for (int j = 0; j < 4; j++) {
                    v[8 * i + 2 * j] = fmaf(0.5f, blo(p0[j]) + blo(p1[j]) + blo(p2[j]), blo(xr[4 * i + j]));
                    v[8 * i + 2 * j + 1] = fmaf(0.5f, bhi(p0[j]) + bhi(p1[j]) + bhi(p2[j]), bhi(xr[4 * i + j]));
                }
            }
            wg_wait<0>();
            pin(d1);
            rel(15);
            TS(3 + ph * 10);
#pragma unroll
            for (int j = 0; j < 8; j++) {
                v[2 * j] = fmaf(0.5f, d1[4 * j] + d1[4 * j + 2], v[2 * j]);
                v[2 * j + 1] = fmaf(0.5f, d1[4 * j + 1] + d1[4 * j + 3], v[2 * j + 1]);
            }
            continue;
        }

        {
            TS(11);
            const uint32_t stg = H + warp * 2048;
            unsigned char* g = g_kvq + (size_t)((b * 4 + tile) * 1024 + trow) * 128 + lane * 16;
            auto put = [&](float (&d)[32], int i) {
                pin(d);
                uint32_t pk[8];
#pragma unroll
                for (int j = 0; j < 8; j++) pk[j] = pack2((d[4 * j] + d[4 * j + 2]) * rstd, (d[4 * j + 1] + d[4 * j + 3]) * rstd);
                if (i == 2) {
                    st_data(g + 2097152, pk[0], pk[1], pk[2], pk[3]);
                    st_data(g + 2097152 + 512, pk[4], pk[5], pk[6], pk[7]);
                    return;
                }
                stsm4(stg + i * 1024 + foff, pk[0], pk[1], pk[2], pk[3]);
                stsm4(stg + i * 1024 + (foff ^ 64), pk[4], pk[5], pk[6], pk[7]);
                __syncwarp();
                const uint4 u0 = lds128(stg + i * 1024 + lane * 16), u1 = lds128(stg + i * 1024 + 512 + lane * 16);
                stg128(g + i * 1048576, u0); stg128(g + i * 1048576 + 512, u1);
            };
            sp(d0, 16, a, w, 0);
            acq(17);
            sp(d1, 17, a, w, 0);
            gather_peer();
            acq(18);
            sp(d0, 18, a + 16, 0, 1);
            wg_wait<1>();
            rel(16); rel(17);
            acq(19);
            sp(d1, 19, a + 16, 0, 1);
            wg_wait<1>();
            rel(18);
            put(d0, 0);
            wg_wait<0>();
            rel(19);
            TS(37);
            put(d1, 1);
            bar_arrive(4, 288);
            TS(38);
            acq(20);
            sp(d0, 20, a, w, 0);
            acq(21);
            sp(d0, 21, a + 16, 0, 1);
            acq(22); acq(23);
            rel(22); rel(23);
            mbar_wait(bars + B_RST * 8, 0);
            wg_wait<0>();
            rel(20); rel(21);
            put(d0, 2);
            if (wq == 0 || wq == 3) {
                uint4* hp = &g_halo[((pair * 4 + tile) * 2 + (wq & 1)) * 64 + lane];
                st_data(hp, xr[0], xr[1], xr[2], xr[3]);
                st_data(hp + 32, xr[4], xr[5], xr[6], xr[7]);
            }
            TS(12);
        }

        const uint32_t xo = P + tile * XCH + wq * 1024, xt = P + tile * XCH + toff;
        {
            constexpr float CS = 0.125f * 1.4426950408889634f;
            float sa[32], sb2[32], o[36];
            uint32_t pa[16], pb[16], q[16];
            float n0 = INFINITY, n1 = INFINITY;
            zero(o); zero(pa); zero(pb); zero(sb2);
            const uint32_t ones = sb + OFF_MISC + 2048;
            { const uint32_t c = w ? 0u : 0x3F803F80u; sts128(ones + tid * 16, c, c, c, c); }
            fence_async_smem();
            bar_sync(10, 256);
            stsm4(xo + 1024 + foff, xr[0], xr[1], xr[2], xr[3]);
            stsm4(xo + 1024 + (foff ^ 64), xr[4], xr[5], xr[6], xr[7]);
            const uint32_t vdesc = rdesc + ((((ones - rbase) >> 4) - 1) << 16);
            auto qk_issue = [&](float (&s)[32], uint32_t lo) {
                const uint64_t kd = mkdesc(lo);
                wg_fence();
#pragma unroll
                for (int k = 0; k < 4; k++) mma_qk(s, q[4 * k], q[4 * k + 1], q[4 * k + 2], q[4 * k + 3], kd + 2 * k, k != 0);
                wg_commit();
            };
            auto both_issue = [&](float (&s)[32], uint32_t klo, uint32_t (&pp)[16], uint32_t vlo) {
                const uint64_t kd = mkdesc(klo), vd = mkdesc(vlo);
                wg_fence();
#pragma unroll
                for (int k = 0; k < 4; k++) {
                    mma_pv(o, pp[4 * k], pp[4 * k + 1], pp[4 * k + 2], pp[4 * k + 3], vd - k * (128 * 65535));
                    mma_qk(s, q[4 * k], q[4 * k + 1], q[4 * k + 2], q[4 * k + 3], kd + 2 * k, k != 0);
                }
                wg_commit();
            };
            auto new_max = [&](float (&s)[32], int nj, float& x0, float& x1) {
                x0 = s[0]; x1 = s[2];
#pragma unroll
                for (int j = 0; j < nj; j++) {
                    x0 = fmaxf(x0, fmaxf(s[4 * j], s[4 * j + 1]));
                    x1 = fmaxf(x1, fmaxf(s[4 * j + 2], s[4 * j + 3]));
                }
                x0 = fmaxf(x0, __shfl_xor_sync(~0u, x0, 1)); x1 = fmaxf(x1, __shfl_xor_sync(~0u, x1, 1));
                x0 = fmaxf(x0, __shfl_xor_sync(~0u, x0, 2)); x1 = fmaxf(x1, __shfl_xor_sync(~0u, x1, 2));
                x0 = fminf(n0, fmaf(x0, -CS, -20.f)); x1 = fminf(n1, fmaf(x1, -CS, -20.f));
            };
            auto probs = [&](float (&s)[32], uint32_t (&pp)[16], bool ready, bool tail, auto wait) {
                uint32_t any = 0;
#pragma unroll
                for (int i = 0; i < 16; i++) {
                    pp[i] = pack2(ex2(fmaf(s[2 * i], CS, (i & 1) ? n1 : n0)), ex2(fmaf(s[2 * i + 1], CS, (i & 1) ? n1 : n0)));
                    any |= pp[i];
                }
                wg_wait<0>();
                pin(sa); pin(sb2); pin(o); pin(pa); pin(pb);
                if (__any_sync(~0u, (any & 0x40004000u) || !ready)) {
                    wait();
                    if (__any_sync(~0u, any & 0x40004000u)) {
                        if (tail) {
#pragma unroll
                            for (int i = 20; i < 32; i++) s[i] = -INFINITY;
                        }
                        float x0, x1;
                        new_max(s, 8, x0, x1);
                        const float sc0 = ex2(x0 - n0), sc1 = ex2(x1 - n1);
                        n0 = x0; n1 = x1;
#pragma unroll
                        for (int j = 0; j < 9; j++) { o[4 * j] *= sc0; o[4 * j + 1] *= sc0; o[4 * j + 2] *= sc1; o[4 * j + 3] *= sc1; }
#pragma unroll
                        for (int i = 0; i < 16; i++)
                            pp[i] = pack2(ex2(fmaf(s[2 * i], CS, (i & 1) ? n1 : n0)), ex2(fmaf(s[2 * i + 1], CS, (i & 1) ? n1 : n0)));
                    }
                }
            };
            {
                uint4 u[4];
                const unsigned char* src = g_kvq + 2097152 + (size_t)(abh * 1024 + qt * 64 + wq * 16) * 128 + lane * 16;
                spin(QGATE);
                ld_data<512>(u, src);
#pragma unroll
                for (int k = 0; k < 2; k++) {
                    q[8 * k] = u[k].x; q[8 * k + 1] = u[k + 2].x; q[8 * k + 2] = u[k].y; q[8 * k + 3] = u[k + 2].y;
                    q[8 * k + 4] = u[k].z; q[8 * k + 5] = u[k + 2].z; q[8 * k + 6] = u[k].w; q[8 * k + 7] = u[k + 2].w;
                }
                pin(q);
            }
            TS(40);
            acq(24);
            TS(13);
            qk_issue(sa, rdesc + (24 % NSLOT) * (SLOT >> 4));
            wg_wait<0>();
            pin(sa);
            {
                float x0, x1;
                new_max(sa, NJ0, x0, x1);
                n0 = x0; n1 = x1;
            }
            bar_arrive(6, 384);
            uint32_t vd = vdesc - (SLOT >> 4) * 65535u, kd = rdesc, vb = fbar + 8, kb = fbar;
            uint32_t vlast = vdesc - 4 * (SLOT >> 4) * 65535u, klast = rdesc + 4 * (SLOT >> 4) + 512;
            uint32_t kprev = fbar + 32, vprev = bars + (B_SINK - (B_EMPTY - B_FULL)) * 8;
#pragma unroll 1
            for (int it = 0; it < 4; it++) {
                both_issue(sb2, klast, pb, vlast);
                probs(sa, pa, mbar_test(vb, it < 2) & mbar_test(kb, it < 3), false, [&]() { mbar_wait(vb, it < 2); mbar_wait(kb, it < 3); });
                TS(41 + it * 4);
                if (lane == 0) mbar_arrive(kprev + (B_EMPTY - B_FULL) * 8);
                if (lane == 0) mbar_arrive(vprev + (B_EMPTY - B_FULL) * 8);
                both_issue(sa, kd, pa, vd);
                const int dv = it == 0 ? 2 : (it == 1 ? -3 : 1);
                kprev = kb; vprev = vb; vlast = vd - 512 * 65535u; klast = kd + 512;
                vd -= dv * (SLOT >> 4) * 65535u; vb += dv * 8;
                kd += (it == 2 ? -3 : 2) * (SLOT >> 4); kb = it == 2 ? vb : kb + 16;
                probs(sb2, pb, true, it == 3 && w == 1, []() {});
                TS(43 + it * 4);
            }
            wg_fence();
#pragma unroll
            for (int k = 0; k < 4; k++)
                mma_pv(o, pb[4 * k], pb[4 * k + 1], pb[4 * k + 2], pb[4 * k + 3], mkdesc(vlast - k * (128 * 65535) + (k > 1 ? w * ((k - 1) << 22) : 0)));
            wg_commit();
            const int row = wq * 16 + (lane >> 2);
            const uint32_t ml = sb + OFF_MISC;
            mbar_wait(bars + (B_RST + 1) * 8, 0);
            wg_wait<0>();
            pin(o); pin(pb); pin(sa); pin(sb2);
            rel(31);
            const float l0 = o[32], l1 = o[34];
            if (c4 == 0) { sts64f(ml + w * 512 + row * 8, n0, l0); sts64f(ml + w * 512 + row * 8 + 64, n1, l1); }
            TS(14);
            float mine[16];
#pragma unroll
            for (int j = 0; j < 4; j++) {
                if (w == 0) sts128f(H + j * 2048 + wt * 16, o[16 + 4 * j], o[17 + 4 * j], o[18 + 4 * j], o[19 + 4 * j]);
                else sts128f(H + 8192 + j * 2048 + wt * 16, o[4 * j], o[4 * j + 1], o[4 * j + 2], o[4 * j + 3]);
            }
#pragma unroll
            for (int i = 0; i < 16; i++) mine[i] = w == 0 ? o[i] : o[16 + i];
            bar_sync(10, 256);
            const float2 u0 = lds64f(ml + (w ^ 1) * 512 + row * 8), u1 = lds64f(ml + (w ^ 1) * 512 + row * 8 + 64);
            const float x0 = fminf(n0, u0.x), x1 = fminf(n1, u1.x);
            float a0 = ex2(x0 - n0), b0 = ex2(x0 - u0.x), a1 = ex2(x1 - n1), b1 = ex2(x1 - u1.x);
            const float i0 = __fdividef(1.f, fmaf(a0, l0, b0 * u0.y)), i1 = __fdividef(1.f, fmaf(a1, l1, b1 * u1.y));
            a0 *= i0; b0 *= i0; a1 *= i1; b1 *= i1;
            uint32_t pk[8];
#pragma unroll
            for (int j = 0; j < 4; j++) {
                const float4 v = lds128f(H + (w ^ 1) * 8192 + j * 2048 + wt * 16);
                pk[2 * j] = pack2(fmaf(a0, mine[4 * j], b0 * v.x), fmaf(a0, mine[4 * j + 1], b0 * v.y));
                pk[2 * j + 1] = pack2(fmaf(a1, mine[4 * j + 2], b1 * v.z), fmaf(a1, mine[4 * j + 3], b1 * v.w));
            }
            unsigned char* dst = g_o + (size_t)(abh * PADROWS + 8 + qt * 64 + wq * 16) * 128 + w * 512 + lane * 16;
            st_data(dst, pk[0], pk[2], pk[4], pk[6]);
            st_data(dst + 1024, pk[1], pk[3], pk[5], pk[7]);
            if (tid == 0) asm volatile("red.relaxed.gpu.global.add.u32 [%0], 1;" ::"l"(&g_epoch[blockIdx.x * FS]) : "memory");
            TS(15);
        }

        auto mm = [&](float (&d)[24], int n, uint32_t act, int acc) {
            const uint32_t z = p.zero * (ph + n);
            const uint64_t ad = mkdesc(rdesc + z + (n % NSLOT) * (SLOT >> 4)), bd = mkdesc(desc_lo(act) + z);
            wg_fence();
#pragma unroll
            for (int k = 0; k < 8; k++) mma_t(d, ad + k * 128, bd + (k >> 2) * (XCH >> 4) + (k & 3) * 2, k == 0 ? acc : 1);
            wg_commit();
        };
        uint32_t dwr[15];
        {
#pragma unroll
            for (int i = 0; i < 15; i++) dwr[i] = hmul2(__ldg(reinterpret_cast<const uint32_t*>(p.dw + i * 256 + tile * 64) + lane), 0x3F003F00u);
            float d[24];
            uint32_t xw[12];
            bar_sync(9, 384);
#pragma unroll
            for (int j = 0; j < 3; j++) ldsm4t(xt + j * 2048, xw[4 * j], xw[4 * j + 1], xw[4 * j + 2], xw[4 * j + 3]);
            pin(xw);
            acq(32); acq(33); acq(34); acq(35);
            {
                if (ODELAY) spin(ODELAY);
                uint4 u[6];
                ld_data<1024>(u, g_o + (size_t)((b * 4 + (warp >> 1)) * PADROWS + pt * 32) * 128 + (warp & 1) * 512 + lane * 16);
                const uint32_t dst = H + (warp >> 1) * XCH + (foff ^ ((warp & 1) * 64));
#pragma unroll
                for (int i = 0; i < 6; i++) stsm4(dst + i * 1024, u[i].x, u[i].y, u[i].z, u[i].w);
            }
            fence_async_smem();
            bar_sync(10, 256);
            TS(16);
            mm(d, 32, H, 0);
            mm(d, 33, H + 2 * XCH, 1);
            wg_wait<1>();
            rel(32);
            wg_wait<0>();
            pin(d);
#pragma unroll
            for (int i = 0; i < 12; i++) xw[i] = pack2(d[2 * i] + blo(xw[i]), d[2 * i + 1] + bhi(xw[i]));
            if (c4 == 0) { xw[0] = (xw[0] & 0xffff0000u) | 0x3F80u; xw[1] = (xw[1] & 0xffff0000u) | 0x3F80u; }
#pragma unroll
            for (int j = 0; j < 3; j++) stsm4t(xt + j * 2048, xw[4 * j], xw[4 * j + 1], xw[4 * j + 2], xw[4 * j + 3]);
            rel(33);
            publish(B_X2, P + tile * XCH, XCH, 384);
            TS(17);
        }
        {
            float da[24], db[24], st[24];
            bar_sync(5, 384);
            mm(da, 34, P + 2 * r * XCH, 0);
            mm(db, 35, P + 2 * r * XCH, 0);
            acq(36); acq(37);
            mbar_wait(bars + B_X2 * 8, 0);
            TS(39);
            if (PSTAG && w == 1) bar_sync(7, 256);
            mm(da, 36, P + 2 * (r ^ 1) * XCH, 1);
            mm(db, 37, P + 2 * (r ^ 1) * XCH, 1);
            if (PSTAG && w == 0) bar_arrive(7, 256);
            wg_wait<2>();
            rel(34); rel(35);
            mbar_wait(bars + B_ST * 8, 0);
#pragma unroll
            for (int j = 0; j < 6; j++) {
                const float4 u = lds128f(sb + OFF_STATS + (8 * j + 2 * c4) * 8);
                st[4 * j] = u.x; st[4 * j + 1] = u.y; st[4 * j + 2] = u.z; st[4 * j + 3] = u.w;
            }
            wg_wait<0>();
            pin(da); pin(db);
            rel(36); rel(37);
            TS(18);
            uint32_t pk[12];
#pragma unroll
            for (int hh = 0; hh < 2; hh++) {
                const float ca = __shfl_sync(~0u, da[2 * hh], lane & 28), cb = __shfl_sync(~0u, db[2 * hh], lane & 28);
#pragma unroll
                for (int j = 0; j < 6; j++) {
                    const float u0 = fmaf(-st[4 * j], ca, da[4 * j + 2 * hh] * st[4 * j + 1]);
                    const float u1 = fmaf(-st[4 * j + 2], ca, da[4 * j + 2 * hh + 1] * st[4 * j + 3]);
                    const float v0 = fmaf(-st[4 * j], cb, db[4 * j + 2 * hh] * st[4 * j + 1]);
                    const float v1 = fmaf(-st[4 * j + 2], cb, db[4 * j + 2 * hh + 1] * st[4 * j + 3]);
                    pk[2 * j + hh] = pack2(fmaf(u0, tanh_fast(v0), u0), fmaf(u1, tanh_fast(v1), u1));
                }
            }
            const uint32_t gs = H + 16384 + w * XCH;
#pragma unroll
            for (int j = 0; j < 3; j++) stsm4t(gs + toff + j * 2048, pk[4 * j], pk[4 * j + 1], pk[4 * j + 2], pk[4 * j + 3]);
            ldsm4(xo + 1024 + foff, xr[0], xr[1], xr[2], xr[3]);
            ldsm4(xo + 1024 + (foff ^ 64), xr[4], xr[5], xr[6], xr[7]);
            bar_sync(2 + w, 128);
            uint32_t ca[8], cb[8];
            const uint32_t grow = gs + 8 * wq * 128 + c4 * 4, srow = H + tile * HCH + 8 * wq * 128 + c4 * 4;
#pragma unroll
            for (int k = 0; k < 22; k++) {
                const uint32_t v = lds32(grow + (1 + k) * 128 + (((lane >> 2) ^ ((1 + k) & 7)) << 4));
#pragma unroll
                for (int i = 0; i < 8; i++) {
                    const int tap = k - i;
                    if (tap == 0) ca[i] = hmul2(v, dwr[0]);
                    else if (tap > 0 && tap < 8) ca[i] = hfma2(v, dwr[tap], ca[i]);
                    else if (tap == 8) cb[i] = hmul2(v, dwr[8]);
                    else if (tap > 8 && tap < 15) cb[i] = hfma2(v, dwr[tap], cb[i]);
                }
            }
#pragma unroll
            for (int i = 0; i < 8; i++) {
                const float h0 = blo(ca[i]) + blo(cb[i]), h1 = bhi(ca[i]) + bhi(cb[i]);
                sts32(srow + i * 128 + (((lane >> 2) ^ i) << 4), pack2(fmaf(h0, tanh_fast(h0), h0), fmaf(h1, tanh_fast(h1), h1)));
            }
            acq(38); acq(39);
            publish(B_SR, H + tile * HCH, HCH, 256);
            TS(19);
        }
        {
            auto frags = [&](int i, int half) {
                const uint32_t src = H + 2 * half * HCH + wq * 1024;
#pragma unroll
                for (int k = 0; k < 4; k++) ldsm4(src + (k >> 1) * HCH + (foff ^ ((k & 1) * 64)), a[i + 4 * k], a[i + 4 * k + 1], a[i + 4 * k + 2], a[i + 4 * k + 3]);
            };
            frags(0, r);
            sp(d0, 38, a, 0, 0);
            acq(40);
            mbar_wait(bars + B_SR * 8, 0);
            frags(16, r ^ 1);
            sp(d0, 39, a + 16, 0, 1);
            wg_wait<1>();
            rel(38);
            wg_wait<0>();
            pin(d0);
            rel(39);
#pragma unroll
            for (int j = 0; j < 8; j++) {
                v[2 * j] = d0[4 * j] + d0[4 * j + 2] + blo(xr[j]);
                v[2 * j + 1] = d0[4 * j + 1] + d0[4 * j + 3] + bhi(xr[j]);
            }
            TS(20);
        }
    }

    cluster_arrive();
    TS(24);
    {
        const float rstd = rsq(fmaxf(fmaf(-mean, mean, msq), 0.f) + 1e-5f), nb = -mean * rstd;
#pragma unroll
        for (int j = 0; j < 8; j++) xr[j] = pack2(fmaf(v[2 * j], rstd, nb), fmaf(v[2 * j + 1], rstd, nb));
        const uint32_t stg = P + 16384 + warp * 1024;
        stsm4(stg + foff, xr[0], xr[1], xr[2], xr[3]);
        stsm4(stg + (foff ^ 64), xr[4], xr[5], xr[6], xr[7]);
        __syncwarp();
        const uint32_t src = stg + (lane >> 3) * 128 + (((lane & 7) ^ (lane >> 3)) << 4);
        const uint4 u0 = lds128(src), u1 = lds128((src + 512) ^ 64);
        __nv_bfloat16* dst = p.out + (size_t)(b * T_ + trow + (lane >> 3)) * 256 + tile * 64 + (lane & 7) * 8;
        if (trow < T_) { stg128(dst, u0); stg128(dst + 4 * 256, u1); }
    }
    TS(25);
    TG(31);
    TSDUMP();
    cluster_wait();
}

typedef CUresult (*EncodeFn)(CUtensorMap*, CUtensorMapDataType, cuuint32_t, void*, const cuuint64_t*, const cuuint64_t*,
                             const cuuint32_t*, const cuuint32_t*, CUtensorMapInterleave, CUtensorMapSwizzle,
                             CUtensorMapL2promotion, CUtensorMapFloatOOBfill);

}

extern "C" void kernel_launch(void* const* d_in, const int* in_sizes, int n_in, void* d_out, int out_size) {
    static EncodeFn encode = nullptr;
    if (!encode) {
        void* fn = nullptr;
        cudaDriverEntryPointQueryResult qr;
        cudaGetDriverEntryPoint("cuTensorMapEncodeTiled", &fn, cudaEnableDefault, &qr);
        encode = (EncodeFn)fn;
        cudaFuncSetAttribute(conformer_kernel, cudaFuncAttributeMaxDynamicSharedMemorySize, SMEM_LAUNCH);
    }
    Params p;
    const cuuint32_t ones[5] = {1, 1, 1, 1, 1};
    const int idx[8] = {1, 2, 3, 4, 5, 7, 8, 9};
    const int rows[8] = {256, 1024, 256, 256, 256, 256, 256, 1024};
    const int cols[8] = {1024, 256, 768, 256, 512, 256, 1024, 256};
    for (int i = 0; i < 8; i++) {
        const bool perm = i != 3 && i != 4;
        const cuuint64_t pitch = (cuuint64_t)cols[i] * 2;
        const cuuint64_t dims[5] = {(cuuint64_t)cols[i], 2, 2, 4, (cuuint64_t)rows[i] / 16};
        const cuuint64_t strides[4] = {pitch, pitch * (perm ? 8 : 2), pitch * (perm ? 2 : 4), pitch * 16};
        const cuuint32_t box[5] = {64, 2, 2, 4, 8};
        encode(&p.tm[i], CU_TENSOR_MAP_DATA_TYPE_BFLOAT16, 5, d_in[idx[i]], dims, strides, box, ones, CU_TENSOR_MAP_INTERLEAVE_NONE,
               CU_TENSOR_MAP_SWIZZLE_128B, CU_TENSOR_MAP_L2_PROMOTION_L2_128B, CU_TENSOR_MAP_FLOAT_OOB_FILL_NONE);
        p.w[i] = (const char*)d_in[idx[i]];
    }
    {
        void* kv = nullptr;
        cudaGetSymbolAddress(&kv, g_kvq);
        const cuuint64_t dims[2] = {64, 16384};
        const cuuint64_t strides[1] = {128};
        const cuuint32_t box[2] = {64, 128};
        encode(&p.tm[8], CU_TENSOR_MAP_DATA_TYPE_BFLOAT16, 2, kv, dims, strides, box, ones, CU_TENSOR_MAP_INTERLEAVE_NONE,
               CU_TENSOR_MAP_SWIZZLE_NONE, CU_TENSOR_MAP_L2_PROMOTION_L2_128B, CU_TENSOR_MAP_FLOAT_OOB_FILL_NONE);
    }
    p.x = (const __nv_bfloat16*)d_in[0];
    p.dw = (const __nv_bfloat16*)d_in[6];
    p.out = (__nv_bfloat16*)d_out;
    p.zero = 0;
    conformer_kernel<<<NCTA, NTHREADS, SMEM_LAUNCH>>>(p);
}
```

```cpp
#include <cuda_runtime.h>
#include <cuda_bf16.h>
#include <cuda.h>
#include <stdint.h>

namespace {

constexpr int T_ = 1000;
constexpr int NCTA = 128;
constexpr int NTHREADS = 512;
constexpr int NSLOT = 5;
constexpr int SLOT = 16384;
constexpr int NLOADS = 56;

constexpr uint32_t OFF_RING = 0;
constexpr uint32_t OFF_P = 163840;
constexpr uint32_t OFF_H = 188416;
constexpr uint32_t OFF_MISC = 221184;
constexpr uint32_t OFF_STATS = 229376;
constexpr uint32_t OFF_BARS = 229888;
constexpr uint32_t SMEM_BYTES = 230400;
constexpr uint32_t XCH = 6144;
constexpr uint32_t HCH = 4096;

constexpr int B_FULL = 0, B_EMPTY = 10, B_XA = 20  , B_XB = 24  , B_INB = 27  , B_X2 = 31, B_SR = 32,
              B_PS = 33, B_RST = 34  , B_RDY = 36  , B_SINK = 42, B_ST = 43;

#define KD2 300u
#define KD3 500u
#define ODELAY 0u
#define QGATE 500u
#define BACKOFF 0u
#define KFS 8
#define KDELAY 300u
#define NJ0 2
#define PSTAG 1
#define WSTAG 1
#define TURN 0
#define EAGER 0x5555
constexpr int PADROWS = 1040;
constexpr int FS = 8;

struct Params {
    CUtensorMap tm[9];
    const char* w[8];
    const __nv_bfloat16* x;
    const __nv_bfloat16* dw;
    __nv_bfloat16* out;
    uint32_t zero;
};

__device__ __align__(1024) unsigned char g_kvq[3 * 8 * 1024 * 128];
__device__ __align__(1024) unsigned char g_o[8 * PADROWS * 128];
__device__ uint4 g_halo[64 * 4 * 2 * 64];
__device__ __align__(128) uint32_t g_flag_kv[8 * 32 * KFS];
__device__ uint32_t g_reset[4 * 32];
__device__ uint32_t g_epoch[NCTA * FS];

#define TS(i) do { } while (0)
#define TSW(i) do { } while (0)
#define TG(i) do { } while (0)
#define TSINIT() do { } while (0)
#define TSDUMP() do { } while (0)
constexpr uint32_t SMEM_LAUNCH = SMEM_BYTES;

__device__ __forceinline__ uint32_t smem_u32(const void* p) { return (uint32_t)__cvta_generic_to_shared(p); }
__device__ __forceinline__ void mbar_init(uint32_t b, uint32_t c) { asm volatile("mbarrier.init.shared::cta.b64 [%0], %1;" ::"r"(b), "r"(c) : "memory"); }
__device__ __forceinline__ void mbar_arrive(uint32_t b) { asm volatile("mbarrier.arrive.shared::cta.b64 _, [%0];" ::"r"(b) : "memory"); }
__device__ __forceinline__ void mbar_arrive_tx(uint32_t b, uint32_t tx) { asm volatile("mbarrier.arrive.expect_tx.shared::cta.b64 _, [%0], %1;" ::"r"(b), "r"(tx) : "memory"); }
__device__ __forceinline__ void mbar_wait(uint32_t b, uint32_t ph) {
    asm volatile("{\n.reg .pred p, q;\n.reg .u32 c;\nmov.u32 c, 0;\n"
                 "MW_LOOP:\n.pragma \"nounroll\";\n"
                 "mbarrier.try_wait.parity.shared::cta.b64 p, [%0], %1;\n"
                 "add.u32 c, c, 1;\nsetp.lt.u32 q, c, 65536;\nnot.pred p, p;\nand.pred p, p, q;\n@p bra MW_LOOP;\n}"
                 ::"r"(b), "r"(ph) : "memory");
}
__device__ __forceinline__ bool mbar_test(uint32_t b, uint32_t ph) {
    uint32_t ok;
    asm volatile("{\n.reg .pred p;\nmbarrier.test_wait.parity.shared::cta.b64 p, [%1], %2;\nselp.u32 %0, 1, 0, p;\n}" : "=r"(ok) : "r"(b), "r"(ph) : "memory");
    return ok;
}
__device__ __forceinline__ uint32_t mapa(uint32_t a, uint32_t r) { uint32_t o; asm("mapa.shared::cluster.u32 %0, %1, %2;" : "=r"(o) : "r"(a), "r"(r)); return o; }
__device__ __forceinline__ void fence_async_smem() { asm volatile("fence.proxy.async.shared::cta;" ::: "memory"); }
__device__ __forceinline__ void fence_async_global() { asm volatile("fence.proxy.async.global;" ::: "memory"); }
__device__ __forceinline__ void bar_sync(int id, int n) { asm volatile("bar.sync %0, %1;" ::"r"(id), "r"(n) : "memory"); }
__device__ __forceinline__ void bar_arrive(int id, int n) { asm volatile("bar.arrive %0, %1;" ::"r"(id), "r"(n) : "memory"); }
__device__ __forceinline__ void cluster_arrive() { asm volatile("barrier.cluster.arrive.relaxed.aligned;" ::: "memory"); }
__device__ __forceinline__ void cluster_wait() { asm volatile("barrier.cluster.wait.aligned;" ::: "memory"); }

__device__ __forceinline__ void ring_load(uint32_t dst, const CUtensorMap* tm, int col, int row16, uint32_t bar) {
    asm volatile("{\n.reg .pred p;\nelect.sync _|p, 0xffffffff;\n"
                 "@p mbarrier.arrive.expect_tx.shared::cta.b64 _, [%2], 16384;\n"
                 "@p cp.async.bulk.tensor.5d.shared::cluster.global.mbarrier::complete_tx::bytes [%0], [%1, {%3, 0, 0, 0, %4}], [%2];\n}"
                 ::"r"(dst), "l"(tm), "r"(bar), "r"(col), "r"(row16) : "memory");
}
__device__ __forceinline__ void ring_load_both(uint32_t dst, const CUtensorMap* tm, int c1, uint32_t bar) {
    asm volatile("{\n.reg .pred p;\nelect.sync _|p, 0xffffffff;\n"
                 "@p cp.async.bulk.tensor.2d.shared::cluster.global.mbarrier::complete_tx::bytes.multicast::cluster [%0], [%1, {0, %3}], [%2], %4;\n}"
                 ::"r"(dst), "l"(tm), "r"(bar), "r"(c1), "h"((uint16_t)3) : "memory");
}
__device__ __forceinline__ void mbar_arrive_peer(uint32_t b) { asm volatile("mbarrier.arrive.relaxed.cluster.shared::cluster.b64 _, [%0];" ::"r"(b) : "memory"); }
__device__ __forceinline__ void prefetch_l2(const void* src, uint32_t bytes) {
    asm volatile("cp.async.bulk.prefetch.L2.global [%0], %1;" ::"l"(src), "r"(bytes) : "memory");
}
__device__ __forceinline__ void peer_copy(uint32_t dst, uint32_t src, uint32_t bytes, uint32_t rbar) {
    asm volatile("{\n.reg .pred p;\nelect.sync _|p, 0xffffffff;\n"
                 "@p cp.async.bulk.shared::cluster.shared::cta.mbarrier::complete_tx::bytes [%0], [%1], %2, [%3];\n}"
                 ::"r"(dst), "r"(src), "r"(bytes), "r"(rbar) : "memory");
}
__device__ __forceinline__ void st_async4(uint32_t dst, uint32_t a, uint32_t b, uint32_t c, uint32_t d, uint32_t bar) {
    asm volatile("st.async.shared::cluster.mbarrier::complete_tx::bytes.v4.b32 [%0], {%1,%2,%3,%4}, [%5];" ::"r"(dst), "r"(a), "r"(b), "r"(c), "r"(d), "r"(bar) : "memory");
}
__device__ __forceinline__ void st_async2f(uint32_t dst, float a, float b, uint32_t bar) {
    asm volatile("st.async.shared::cluster.mbarrier::complete_tx::bytes.v2.f32 [%0], {%1,%2}, [%3];" ::"r"(dst), "f"(a), "f"(b), "r"(bar) : "memory");
}
__device__ __forceinline__ void stsm4t(uint32_t a, uint32_t r0, uint32_t r1, uint32_t r2, uint32_t r3) {
    asm volatile("stmatrix.sync.aligned.m8n8.x4.trans.shared.b16 [%0], {%1,%2,%3,%4};" ::"r"(a), "r"(r0), "r"(r1), "r"(r2), "r"(r3) : "memory");
}
__device__ __forceinline__ void stsm4(uint32_t a, uint32_t r0, uint32_t r1, uint32_t r2, uint32_t r3) {
    asm volatile("stmatrix.sync.aligned.m8n8.x4.shared.b16 [%0], {%1,%2,%3,%4};" ::"r"(a), "r"(r0), "r"(r1), "r"(r2), "r"(r3) : "memory");
}
__device__ __forceinline__ void ldsm4t(uint32_t a, uint32_t& r0, uint32_t& r1, uint32_t& r2, uint32_t& r3) {
    asm volatile("ldmatrix.sync.aligned.m8n8.x4.trans.shared.b16 {%0,%1,%2,%3}, [%4];" : "=r"(r0), "=r"(r1), "=r"(r2), "=r"(r3) : "r"(a) : "memory");
}
__device__ __forceinline__ void ldsm4(uint32_t a, uint32_t& r0, uint32_t& r1, uint32_t& r2, uint32_t& r3) {
    asm volatile("ldmatrix.sync.aligned.m8n8.x4.shared.b16 {%0,%1,%2,%3}, [%4];" : "=r"(r0), "=r"(r1), "=r"(r2), "=r"(r3) : "r"(a) : "memory");
}
__device__ __forceinline__ uint4 lds128(uint32_t a) { uint4 v; asm volatile("ld.shared.v4.b32 {%0,%1,%2,%3}, [%4];" : "=r"(v.x), "=r"(v.y), "=r"(v.z), "=r"(v.w) : "r"(a) : "memory"); return v; }
__device__ __forceinline__ float4 lds128f(uint32_t a) { float4 v; asm volatile("ld.shared.v4.f32 {%0,%1,%2,%3}, [%4];" : "=f"(v.x), "=f"(v.y), "=f"(v.z), "=f"(v.w) : "r"(a) : "memory"); return v; }
__device__ __forceinline__ float2 lds64f(uint32_t a) { float2 v; asm volatile("ld.shared.v2.f32 {%0,%1}, [%2];" : "=f"(v.x), "=f"(v.y) : "r"(a) : "memory"); return v; }
__device__ __forceinline__ uint32_t lds32(uint32_t a) { uint32_t v; asm volatile("ld.shared.b32 %0, [%1];" : "=r"(v) : "r"(a) : "memory"); return v; }
__device__ __forceinline__ void sts128(uint32_t a, uint32_t x, uint32_t y, uint32_t z, uint32_t w) { asm volatile("st.shared.v4.b32 [%0], {%1,%2,%3,%4};" ::"r"(a), "r"(x), "r"(y), "r"(z), "r"(w) : "memory"); }
__device__ __forceinline__ void sts128f(uint32_t a, float x, float y, float z, float w) { asm volatile("st.shared.v4.f32 [%0], {%1,%2,%3,%4};" ::"r"(a), "f"(x), "f"(y), "f"(z), "f"(w) : "memory"); }
__device__ __forceinline__ void sts64f(uint32_t a, float x, float y) { asm volatile("st.shared.v2.f32 [%0], {%1,%2};" ::"r"(a), "f"(x), "f"(y) : "memory"); }
__device__ __forceinline__ void sts32(uint32_t a, uint32_t x) { asm volatile("st.shared.b32 [%0], %1;" ::"r"(a), "r"(x) : "memory"); }
__device__ __forceinline__ void stg128(void* p, uint4 v) { asm volatile("st.global.v4.b32 [%0], {%1,%2,%3,%4};" ::"l"(p), "r"(v.x), "r"(v.y), "r"(v.z), "r"(v.w) : "memory"); }

__device__ __forceinline__ uint32_t pack2(float lo, float hi) { uint32_t r; asm("cvt.rn.bf16x2.f32 %0, %1, %2;" : "=r"(r) : "f"(hi), "f"(lo)); return r; }
__device__ __forceinline__ float blo(uint32_t v) { return __uint_as_float(v << 16); }
__device__ __forceinline__ float bhi(uint32_t v) { return __uint_as_float(v & 0xffff0000u); }
__device__ __forceinline__ uint32_t hmul2(uint32_t a, uint32_t b) { uint32_t r; asm("mul.rn.bf16x2 %0, %1, %2;" : "=r"(r) : "r"(a), "r"(b)); return r; }
__device__ __forceinline__ uint32_t hsub2(uint32_t a, uint32_t b) { uint32_t r; asm("sub.rn.bf16x2 %0, %1, %2;" : "=r"(r) : "r"(a), "r"(b)); return r; }
__device__ __forceinline__ uint32_t hfma2(uint32_t a, uint32_t b, uint32_t c) { uint32_t r; asm("fma.rn.bf16x2 %0, %1, %2, %3;" : "=r"(r) : "r"(a), "r"(b), "r"(c)); return r; }
__device__ __forceinline__ float tanh_fast(float x) { float r; asm("tanh.approx.f32 %0, %1;" : "=f"(r) : "f"(x)); return r; }
__device__ __forceinline__ float rsq(float x) { float r; asm("rsqrt.approx.ftz.f32 %0, %1;" : "=f"(r) : "f"(x)); return r; }
__device__ __forceinline__ float ex2(float x) { float r; asm("ex2.approx.ftz.f32 %0, %1;" : "=f"(r) : "f"(x)); return r; }

__device__ __forceinline__ uint32_t ld_relaxed(const uint32_t* p) {
    uint32_t v;
    asm volatile("ld.relaxed.gpu.global.u32 %0, [%1];" : "=r"(v) : "l"(p) : "memory");
    return v;
}
__device__ __forceinline__ uint32_t clock32() { uint32_t c; asm volatile("mov.u32 %0, %%clock;" : "=r"(c)::"memory"); return c; }
__device__ __forceinline__ void spin(uint32_t clks) {
    const uint32_t t0 = clock32();
    while (clock32() - t0 < clks) {}
}
__device__ __forceinline__ void flag_wait(const uint32_t* p, uint32_t e, bool mine) {
#pragma unroll 1
    for (int i = 0; i < (1 << 19); i++) {
        if (mine) mine = ld_relaxed(p) != e;
        if (!__any_sync(~0u, mine)) break;
        if (BACKOFF) spin(BACKOFF);
    }
    asm volatile("fence.acquire.gpu;" ::: "memory");
    fence_async_global();
}
__device__ __forceinline__ void st_data(void* p, uint32_t x, uint32_t y, uint32_t z, uint32_t w) {
    asm volatile("st.relaxed.gpu.global.v4.b32 [%0], {%1,%2,%3,%4};" ::"l"(p), "r"(x), "r"(y), "r"(z), "r"(w) : "memory");
}
template <int STRIDE, int N>
__device__ __forceinline__ void ld_data(uint4 (&v)[N], const unsigned char* p) {
    int it = 0;
    bool again;
#pragma unroll 1
    do {
        uint32_t m = 0;
#pragma unroll
        for (int i = 0; i < N; i++)
            asm volatile("ld.relaxed.gpu.global.v4.b32 {%0,%1,%2,%3}, [%4];" : "=r"(v[i].x), "=r"(v[i].y), "=r"(v[i].z), "=r"(v[i].w) : "l"(p + i * STRIDE) : "memory");
#pragma unroll
        for (int i = 0; i < N; i++) m = __vimax3_u32(__vimax3_u32(v[i].x, v[i].y, v[i].z), v[i].w, m);
        again = __any_sync(~0u, m == ~0u) && ++it < (1 << 16);
    } while (again);
}
__device__ __forceinline__ uint32_t ld_epoch() { return ld_relaxed(&g_epoch[blockIdx.x * FS]) + 1; }
__device__ __forceinline__ void flag_set(uint32_t* p, uint32_t e) { asm volatile("st.release.gpu.global.u32 [%0], %1;" ::"l"(p), "r"(e) : "memory"); }

__device__ __forceinline__ uint32_t desc_lo(uint32_t addr) { return ((addr & 0x3FFFF) >> 4) | 0x10000u; }
__device__ __forceinline__ uint64_t mkdesc(uint32_t lo) { return (uint64_t)lo | (0x40000040ull << 32); }
__device__ __forceinline__ void wg_fence() { asm volatile("wgmma.fence.sync.aligned;" ::: "memory"); }
__device__ __forceinline__ void wg_commit() { asm volatile("wgmma.commit_group.sync.aligned;" ::: "memory"); }
template <int N> __device__ __forceinline__ void wg_wait() { asm volatile("wgmma.wait_group.sync.aligned %0;" ::"n"(N) : "memory"); }
template <int N> __device__ __forceinline__ void pin(float (&d)[N]) {
#pragma unroll
    for (int i = 0; i < N; i++) asm volatile("" : "+f"(d[i])::"memory");
}
template <int N> __device__ __forceinline__ void pin(uint32_t (&d)[N]) {
#pragma unroll
    for (int i = 0; i < N; i++) asm volatile("" : "+r"(d[i])::"memory");
}

template <typename Tp, int N> __device__ __forceinline__ void zero(Tp (&d)[N]) {
#pragma unroll
    for (int i = 0; i < N; i++) d[i] = 0;
    pin(d);
}

#define F4(d, i) "+f"(d[i]), "+f"(d[i + 1]), "+f"(d[i + 2]), "+f"(d[i + 3])
#define F16(d, i) F4(d, i), F4(d, i + 4), F4(d, i + 8), F4(d, i + 12)

__device__ __forceinline__ void mma_sp(float (&d)[32], const uint32_t* a, uint64_t b, uint32_t meta, int acc) {
    asm volatile("{.reg .pred p; setp.ne.b32 p, %38, 0;\n"
                 "wgmma.mma_async.sp.sync.aligned.m64n64k32.f32.bf16.bf16 {%0,%1,%2,%3,%4,%5,%6,%7,%8,%9,%10,%11,%12,%13,%14,%15,%16,%17,%18,%19,%20,%21,%22,%23,%24,%25,%26,%27,%28,%29,%30,%31}, "
                 "{%32,%33,%34,%35}, %36, %37, 0, p, 1, 1, 1;}\n"
                 : F16(d, 0), F16(d, 16) : "r"(a[0]), "r"(a[1]), "r"(a[2]), "r"(a[3]), "l"(b), "r"(meta), "r"(acc));
}
__device__ __forceinline__ void mma_t(float (&d)[24], uint64_t a, uint64_t b, int acc) {
    asm volatile("{.reg .pred p; setp.ne.b32 p, %26, 0;\n"
                 "wgmma.mma_async.sync.aligned.m64n48k16.f32.bf16.bf16 {%0,%1,%2,%3,%4,%5,%6,%7,%8,%9,%10,%11,%12,%13,%14,%15,%16,%17,%18,%19,%20,%21,%22,%23}, %24, %25, p, 1, 1, 1, 0;}\n"
                 : F16(d, 0), F4(d, 16), F4(d, 20) : "l"(a), "l"(b), "r"(acc));
}
__device__ __forceinline__ void mma_qk(float (&d)[32], uint32_t a0, uint32_t a1, uint32_t a2, uint32_t a3, uint64_t b, int acc) {
    asm volatile("{.reg .pred p; setp.ne.b32 p, %37, 0;\n"
                 "wgmma.mma_async.sync.aligned.m64n64k16.f32.bf16.bf16 {%0,%1,%2,%3,%4,%5,%6,%7,%8,%9,%10,%11,%12,%13,%14,%15,%16,%17,%18,%19,%20,%21,%22,%23,%24,%25,%26,%27,%28,%29,%30,%31}, "
                 "{%32,%33,%34,%35}, %36, p, 1, 1, 0;}\n"
                 : F16(d, 0), F16(d, 16) : "r"(a0), "r"(a1), "r"(a2), "r"(a3), "l"(b), "r"(acc));
}
__device__ __forceinline__ void mma_pv(float (&d)[36], uint32_t a0, uint32_t a1, uint32_t a2, uint32_t a3, uint64_t b) {
    asm volatile("wgmma.mma_async.sync.aligned.m64n72k16.f32.bf16.bf16 {%0,%1,%2,%3,%4,%5,%6,%7,%8,%9,%10,%11,%12,%13,%14,%15,%16,%17,%18,%19,%20,%21,%22,%23,%24,%25,%26,%27,%28,%29,%30,%31,%32,%33,%34,%35}, "
                 "{%36,%37,%38,%39}, %40, 1, 1, 1, 1;\n"
                 : F16(d, 0), F16(d, 16), F4(d, 32) : "r"(a0), "r"(a1), "r"(a2), "r"(a3), "l"(b));
}

__device__ __forceinline__ uint32_t load_code(int n, int r, int w) {
    const int tile = 2 * r + w;
    int m, col, row;
    if (n < 16 || n >= 40) {
        const int k = n < 16 ? n : n - 40;
        m = n < 16 ? 0 : 6;
        if (k < 8) { col = 4 * tile + (k >> 1); row = (k & 1) ^ r; }
        else { m++; col = tile ^ (3 - ((k - 8) >> 1)); row = 2 * tile + (k & 1); }
    } else if (n < 32) {
        const int k = n - 16;
        m = 2;
        if (k < 4) { col = tile + ((k & 1) ? 8 : 4); row = (k >> 1) ^ r; }
        else { col = tile; row = (k & 1) ^ r; }
    } else if (n < 34) { m = 3; col = tile; row = n - 32; }
    else if (n < 38) { const int k = n - 34; m = 4; col = tile + 4 * (k & 1); row = (k >> 1) ^ r; }
    else { m = 5; col = tile; row = (n & 1) ^ r; }
    return m | (col << 4) | (row << 8);
}

__global__ void __cluster_dims__(2, 1, 1) __launch_bounds__(NTHREADS, 1)
conformer_kernel(const __grid_constant__ Params p) {
    extern __shared__ __align__(1024) unsigned char smem_raw[];
    const uint32_t sb = smem_u32(smem_raw);
    const uint32_t bars = sb + OFF_BARS;
    const int tid = threadIdx.x;
    const int lane = tid & 31;
    const int warp = __shfl_sync(~0u, tid >> 5, 0);
    const int r = blockIdx.x & 1;
    const int pair = blockIdx.x >> 1;
    const int b = pair >> 5, pt = pair & 31;
    const int ah = pt >> 3, qt = (pt & 7) * 2 + r;
    const int abh = b * 4 + ah;

    TG(30);
    TSINIT();
    TS(0);
    const uint32_t P = sb + OFF_P, H = sb + OFF_H;

    if (warp >= 8) {
        asm volatile("setmaxnreg.dec.sync.aligned.u32 48;");
        if (warp >= 12) {
            cluster_arrive();
            cluster_wait();
            const int ut = tid & 127;
            const uint32_t target = ld_epoch() * 64;
            auto reset_done = [&](int k) {
                bar_sync(11, 128);
                if (ut == 0) {
                    asm volatile("red.release.gpu.global.add.u32 [%0], 1;" ::"l"(&g_reset[(2 * b + k) * 32]) : "memory");
#pragma unroll 1
                    for (int i = 0; i < (1 << 20) && ld_relaxed(&g_reset[(2 * b + k) * 32]) != target; i++) __nanosleep(100);
                    asm volatile("fence.acquire.gpu;" ::: "memory");
                    mbar_arrive(bars + (B_RST + k) * 8);
                }
                __syncwarp();
                TS(13 + k);
            };
#pragma unroll
            for (int i = 0; i < 4; i++) {
                st_data(g_kvq + 2097152 + (size_t)((b * 4 + 2 * r + (i >> 1)) * 1024 + pt * 32) * 128 + (i & 1) * 2048 + ut * 16, ~0u, ~0u, ~0u, ~0u);
                if (i < 2) st_data(&g_halo[(pair * 4 + 2 * r + i) * 128 + ut], ~0u, ~0u, ~0u, ~0u);
            }
            reset_done(0);
            bar_sync(6, 384);
#pragma unroll
            for (int i = 0; i < 4; i++) st_data(g_o + (size_t)(abh * PADROWS + 8 + qt * 64) * 128 + i * 2048 + ut * 16, ~0u, ~0u, ~0u, ~0u);
            reset_done(1);
            {
                const int side = warp & 1, t = 2 * r + ((warp >> 1) & 1), np = side ? pt + 1 : pt - 1;
                uint4 hv[2] = {make_uint4(0, 0, 0, 0), make_uint4(0, 0, 0, 0)};
                if (np >= 0 && np < 32)
                    ld_data<512>(hv, reinterpret_cast<const unsigned char*>(&g_halo[(((b * 32 + np) * 4 + t) * 2 + (side ^ 1)) * 64 + lane]));
                const uint32_t dst = P + t * XCH + side * 5120 + (lane & 7) * 128 + (((lane >> 3) ^ (lane & 7)) << 4);
                stsm4(dst, hv[0].x, hv[0].y, hv[0].z, hv[0].w);
                stsm4(dst ^ 64, hv[1].x, hv[1].y, hv[1].z, hv[1].w);
                bar_arrive(9, 384);
            }
            if (warp < 15) {
                const int row = ut >> 1;
                const uint32_t a8 = P + (2 * r + (ut & 1)) * XCH + row * 128;
                bar_sync(1, 352);
                uint4 v[8];
                uint32_t tie = 0;
#pragma unroll
                for (int i = 0; i < 8; i++) { v[i] = lds128(a8 + ((i ^ (lane & 7)) << 4)); tie |= v[i].w; }
                bar_arrive(5 + (tie & p.zero), 352);
                const uint32_t mul = 65536u + (clock32() & p.zero), msk = 0u - mul;
                float s = 0.f, q = 0.f;
#pragma unroll
                for (int i = 0; i < 8; i++) {
                    const float a0 = __uint_as_float(v[i].x * mul), a1 = __uint_as_float(v[i].x & msk), a2 = __uint_as_float(v[i].y * mul), a3 = __uint_as_float(v[i].y & msk);
                    const float a4 = __uint_as_float(v[i].z * mul), a5 = __uint_as_float(v[i].z & msk), a6 = __uint_as_float(v[i].w * mul), a7 = __uint_as_float(v[i].w & msk);
                    s += ((a0 + a1) + (a2 + a3)) + ((a4 + a5) + (a6 + a7));
                    q += fmaf(a0, a0, fmaf(a1, a1, fmaf(a2, a2, a3 * a3))) + fmaf(a4, a4, fmaf(a5, a5, fmaf(a6, a6, a7 * a7)));
                }
                s += __shfl_xor_sync(~0u, s, 1); q += __shfl_xor_sync(~0u, q, 1);
                const uint32_t pb = sb + OFF_MISC + 6144 + row * 8;
                if (!(ut & 1)) st_async2f(mapa(pb, r ^ 1), s, q, mapa(bars + B_PS * 8, r ^ 1));
                mbar_wait(bars + B_PS * 8, 0);
                const float2 pp = lds64f(pb);
                const float mean = (s + pp.x) * (1.f / 256.f), msq = (q + pp.y) * (1.f / 256.f);
                const float alpha = (uint32_t)(pt * 32 - 8 + row) >= T_ ? 0.f : 0.5f;
                const float rstd = alpha * rsq(fmaxf(fmaf(-mean, mean, msq), 0.f) + 1e-5f);
                if (!(ut & 1)) sts64f(sb + OFF_STATS + row * 8, mean * rstd, rstd);
                __syncwarp();
                if (lane == 0) mbar_arrive(bars + B_ST * 8);
                TS(4);
            }
        } else if (warp < 10) {
            const int w = warp - 8;
            const uint32_t ring = sb + OFF_RING + w * NSLOT * SLOT;
            const uint32_t full = bars + (B_FULL + w * NSLOT) * 8;
            if (lane == 0) {
#pragma unroll
                for (int i = 0; i < NSLOT; i++) { mbar_init(full + i * 8, 1); mbar_init(full + (B_EMPTY - B_FULL + i) * 8, 4); }
                asm volatile("fence.mbarrier_init.release.cluster;" ::: "memory");
                fence_async_smem();
            }
            __syncwarp();
            cluster_arrive();
            TS(1);
#pragma unroll
            for (int n = 0; n < NSLOT; n++) {
                if (n == 1 || n == 2) bar_sync(12, 64);
                ring_load(ring + n * SLOT, &p.tm[0], 64 * (8 * r + 4 * w + (n >> 1)), 8 * ((n & 1) ^ r), full + n * 8);
            }
            TS(2);
            const uint32_t code = load_code(lane, r, w) | (load_code(lane + 32, r, w) << 16);
            cluster_wait();
            uint32_t s = 0, ph = 0;
            int n = NSLOT;
#pragma unroll 1
            for (int seg = 0; seg < 2; seg++) {
#pragma unroll 1
                for (; n < (seg == 0 ? 22 : NLOADS); n++) {
                    const uint32_t c = __shfl_sync(~0u, code, n) >> (n & 32 ? 16 : 0);
                    const CUtensorMap* tm = &p.tm[c & 15];
                    const uint32_t col = (c & 0xf0) * 4, row = (c & 0xff00) >> 5, dst = ring + s * SLOT;
                    mbar_wait(full + (B_EMPTY - B_FULL) * 8 + s * 8, ph + (((uint32_t)(size_t)tm | col | row | dst) & p.zero));
                    ring_load(dst, tm, col, row, full + s * 8);
                    if (++s == NSLOT) { s = 0; ph ^= 1; }
                }
                if (seg == 1) break;
                const uint32_t epoch = ld_epoch();
                const uint32_t rdy = bars + (B_RDY + 3 * w) * 8, prdy = mapa(rdy, r ^ 1);
                const int odd = r ^ w;
                const uint32_t* flags = g_flag_kv + (abh * 32 + lane) * KFS;
                auto kv_load = [&](uint32_t sl, int isv, int i) {
                    ring_load_both(ring + sl * SLOT, &p.tm[8], (isv * 64 + abh * 8 + 2 * i + w) * 128, full + sl * 8);
                };
#pragma unroll 1
                for (int i = 0; i < 2; i++) {
                    if (lane < 3 + i) {
                        const uint32_t sl = i ? lane : lane + 2;
                        mbar_wait(full + (B_EMPTY - B_FULL + sl) * 8, i ^ 1);
                        mbar_arrive_tx(full + sl * 8, (i || lane == 2) ? SLOT : 0);
                    }
                    __syncwarp();
                }
                if (lane == 0) mbar_arrive_peer(prdy);
                bar_sync(14, 96);
                spin(KDELAY);
                mbar_wait(rdy, 0);
                flag_wait(flags, epoch, (lane >> 2) == 2 * odd + w);
                TSW(5 + 2 * odd);
                if (!odd) { kv_load(4, 0, 0); bar_arrive(12, 64); }
                else bar_sync(12, 64);
                spin(w ? KD3 : KD2);
                kv_load(odd ^ 1, odd ^ 1, odd);
                flag_wait(flags, epoch, (lane >> 2) == 2 * odd + w + 4);
                mbar_wait(full + (odd ^ 1) * 8, 1);
                kv_load(2 + odd, odd, 2 - odd);
#pragma unroll 1
                for (int i = 0; i < 3; i++) {
                    const uint32_t sl = i ? i - 1 : 4, bo = i == 2 ? 16 : 8;
                    mbar_wait(full + (B_EMPTY - B_FULL + sl) * 8, i != 0);
                    if (lane == 0) mbar_arrive_tx(full + sl * 8, SLOT);
                    if ((i & 1) != odd) {
                        mbar_wait(rdy + bo, 0);
                        kv_load(sl, i != 0, 2 + odd);
                    } else if (lane == 0) mbar_arrive_peer(prdy + bo);
                    __syncwarp();
                }
                n = 32; s = 2; ph = 1;
            }
        } else if (warp == 10) {
            if (lane == 0) {
#pragma unroll
                for (int i = B_XA; i <= B_ST; i++) mbar_init(bars + i * 8, i == B_ST ? 3 : 1);
#pragma unroll
                for (int i = B_XA; i <= B_PS; i++) mbar_arrive_tx(bars + i * 8, i < B_XB ? 512 : (i == B_X2 ? 12288 : (i == B_PS ? 384 : 8192)));
                asm volatile("fence.mbarrier_init.release.cluster;" ::: "memory");
                fence_async_smem();
            }
            __syncwarp();
            cluster_arrive();
            cluster_wait();
        } else {
            const uint32_t kb = (lane < 2 || lane > 5) ? 4096 : (lane == 2 ? 3072 : (lane == 4 ? 2048 : 1024));
            const char* pf = p.w[lane & 7] + blockIdx.x * kb;
            cluster_arrive();
            cluster_wait();
            if (lane < 2) prefetch_l2(pf, kb);
            mbar_wait(bars + B_XA * 8, 0);
            if (lane == 2) prefetch_l2(pf, kb);
            if (lane >= 1 && lane < 9) asm volatile("prefetch.tensormap [%0];" ::"l"(&p.tm[lane]) : "memory");
            mbar_wait(bars + (B_FULL + 1) * 8, 1);
            if (lane > 2 && lane < 8) prefetch_l2(pf, kb);
            if (lane == 8 && blockIdx.x < 15) prefetch_l2(p.dw + blockIdx.x * 256, 512);
            const uint32_t epoch = ld_epoch();
            bar_sync(4, 288);
            if (lane < 16) flag_set(&g_flag_kv[((b * 4 + 2 * r + (lane >> 3)) * 32 + pt) * KFS + (lane & 7)], epoch);
            __syncwarp();
            bar_arrive(14, 96);
            TSW(8);
        }
        TSDUMP();
        return;
    }

    const int w = warp >> 2, wq = warp & 3;
    const int tile = 2 * r + w;
    const int wt = tid & 127;
    const int c4 = lane & 3;
    const int trow = pt * 32 + 8 * wq;
    uint32_t xr[8];
    {
        const uint32_t* xp = reinterpret_cast<const uint32_t*>(p.x + (size_t)(b * T_ + trow + (lane >> 2)) * 256 + tile * 64) + c4;
#pragma unroll
        for (int j = 0; j < 8; j++) xr[j] = trow < T_ ? __ldg(xp + 4 * j) : 0u;
    }
    cluster_arrive();
    asm volatile("setmaxnreg.inc.sync.aligned.u32 208;");
    const uint32_t rbase = sb + OFF_RING + w * NSLOT * SLOT, fbar = bars + (B_FULL + w * NSLOT) * 8;
    const uint32_t rdesc = desc_lo(rbase);
    auto acq = [&](int n) { mbar_wait(fbar + (n % NSLOT) * 8, (n / NSLOT) & 1); };
    auto rel = [&](int n) { if (lane == 0) mbar_arrive(fbar + (B_EMPTY - B_FULL + n % NSLOT) * 8); };
    const uint32_t foff = (lane & 7) * 128 + (((lane >> 3) ^ (lane & 7)) << 4);
    const uint32_t toff = ((lane >> 4) * 8 + (lane & 7)) * 128 + (((2 * wq + ((lane >> 3) & 1)) ^ (lane & 7)) << 4);
    auto publish = [&](int bar, uint32_t src, uint32_t bytes, int nsync) {
        fence_async_smem();
        bar_sync(2 + w, 128);
        if (wq == 0) peer_copy(mapa(src, r ^ 1), src, bytes, mapa(bars + bar * 8, r ^ 1));
        bar_sync(nsync == 256 ? 10 : 1, nsync);
    };
    float v[16];
#pragma unroll
    for (int j = 0; j < 8; j++) { v[2 * j] = blo(xr[j]); v[2 * j + 1] = bhi(xr[j]); }
    const uint32_t xown = __shfl_sync(~0u, P + wt * 16 + tile * 4096, lane), xrem = __shfl_sync(~0u, P + wt * 16 + (r ^ 1) * 8192, lane);
    const uint32_t sbuf = __shfl_sync(~0u, sb + OFF_MISC + 1024 + (8 * wq + (lane >> 2)) * 32, lane);
    const uint32_t sown = __shfl_sync(~0u, sbuf + tile * 8, lane);
    const uint32_t peer = __shfl_sync(~0u, mapa(sb, r ^ 1) - sb, lane);
    const uint32_t meta = __shfl_sync(~0u, 0xEEEE4444u + p.zero, lane);
    cluster_wait();
    TS(56);
    float mean, msq;

#pragma unroll 1
    for (int ph = 0;; ph++) {
        uint4 o0, o1;
        {
            float s = 0.f, q = 0.f, s2 = 0.f, q2 = 0.f;
#pragma unroll
            for (int j = 0; j < 4; j++) {
                s += v[4 * j] + v[4 * j + 1]; s2 += v[4 * j + 2] + v[4 * j + 3];
                q += fmaf(v[4 * j], v[4 * j], v[4 * j + 1] * v[4 * j + 1]); q2 += fmaf(v[4 * j + 2], v[4 * j + 2], v[4 * j + 3] * v[4 * j + 3]);
            }
            s += s2; q += q2;
            const uint32_t xa = bars + (B_XA + ph) * 8;
            s += __shfl_xor_sync(~0u, s, 1); q += __shfl_xor_sync(~0u, q, 1);
            s += __shfl_xor_sync(~0u, s, 2); q += __shfl_xor_sync(~0u, q, 2);
            if (c4 == 0) st_async2f(sown + peer, s, q, xa + peer);
            if (c4 == 0) sts64f(sown, s, q);
#pragma unroll
            for (int j = 0; j < 8; j++) xr[j] = pack2(v[2 * j], v[2 * j + 1]);
            sts128(xown, xr[0], xr[1], xr[2], xr[3]);
            sts128(xown + 2048, xr[4], xr[5], xr[6], xr[7]);
            bar_sync(10, 256);
            o0 = lds128(xown ^ 4096); o1 = lds128((xown ^ 4096) + 2048);
            if (ph < 3) {
                st_async4(xown + peer, xr[0], xr[1], xr[2], xr[3], xa + (B_XB - B_XA) * 8 + peer);
                st_async4(xown + peer + 2048, xr[4], xr[5], xr[6], xr[7], xa + (B_XB - B_XA) * 8 + peer);
            }
            TS(57 + ph);
            if (ph == 0) acq(0);
            mbar_wait(xa, 0);
            const float4 u0 = lds128f(sbuf), u1 = lds128f(sbuf + 16);
            mean = ((u0.x + u0.z) + (u1.x + u1.z)) * (1.f / 256.f);
            msq = ((u0.y + u0.w) + (u1.y + u1.w)) * (1.f / 256.f);
        }
        if (ph == 3) break;
        uint32_t a[32];
        const uint32_t mean2 = pack2(mean, mean);
        auto centre = [&](int i, const uint4& u) {
            a[i] = hsub2(u.x, mean2); a[i + 1] = hsub2(u.y, mean2); a[i + 2] = hsub2(u.z, mean2); a[i + 3] = hsub2(u.w, mean2);
        };
#pragma unroll
        for (int j = 0; j < 8; j++) a[j] = hsub2(xr[j], mean2);
        centre(8, o0); centre(12, o1);
        const float rstd = rsq(fmaxf(fmaf(-mean, mean, msq), 0.f) + 1e-5f);
        auto gather_peer = [&]() {
            mbar_wait(bars + (B_XB + ph) * 8, 0);
#pragma unroll
            for (int i = 0; i < 4; i++) centre(16 + 4 * i, lds128(xrem + i * 2048));
        };
        auto sp = [&](float (&d)[32], int n, const uint32_t* af, int flip, int acc) {
            const uint32_t lo = rdesc + p.zero * (ph + n + 1) + (n % NSLOT) * (SLOT >> 4);
            const uint64_t b0 = mkdesc(lo + flip * 512), b1 = mkdesc(lo + (flip ^ 1) * 512);
            wg_fence();
            mma_sp(d, af, b0, meta, acc);
            mma_sp(d, af + 4, b0 + 256, meta, 1);
            mma_sp(d, af + 8, b1, meta, 1);
            mma_sp(d, af + 12, b1 + 256, meta, 1);
            wg_commit();
        };
        float d0[32], d1[32];

        if (ph != 1) {
            uint32_t h[32];
            const float rs = 0.5f * rstd;
            const uint32_t inb = bars + (B_INB + ph) * 8, box = H + wt * 16;
            bool ready = true;
            auto step = [&](float (&d)[32], int n, const uint32_t* af, int flip, int acc, auto work) {
                if (!ready) acq(n);
                if (((TURN >> n) & 1) && w == 1) bar_sync(7, 256);
                sp(d, n, af, flip, acc);
                if (n > 0 && ((TURN >> (n - 1)) & 1) && w == 0) bar_arrive(7, 256);
                if (n < 15) ready = mbar_test(fbar + ((n + 1) % NSLOT) * 8, ((n + 1) / NSLOT) & 1);
                wg_wait<1>();
                if (n > 0 && !((EAGER >> (n - 1)) & 1)) rel(n - 1);
                const uint32_t tie = work() & p.zero;
                if ((EAGER >> n) & 1) {
                    if (p.zero < n + ph + 1) wg_wait<0>();
                    if (lane == 0) mbar_arrive(fbar + (B_EMPTY - B_FULL + n % NSLOT) * 8 + tie);
                }
            };
            auto none = []() { return 0u; };
            auto act = [&](float (&d)[32], int i) {
                pin(d);
#pragma unroll
                for (int j = 0; j < 8; j++) {
                    const float u0 = (d[4 * j] + d[4 * j + 2]) * rs, u1 = (d[4 * j + 1] + d[4 * j + 3]) * rs;
                    h[8 * i + j] = pack2(fmaf(u0, tanh_fast(u0), u0), fmaf(u1, tanh_fast(u1), u1));
                }
                return h[8 * i] | h[8 * i + 1] | h[8 * i + 2] | h[8 * i + 3] | h[8 * i + 4] | h[8 * i + 5] | h[8 * i + 6] | h[8 * i + 7];
            };
            auto send = [&](float (&d)[32], int x) {
                pin(d);
                uint32_t pk[8];
#pragma unroll
                for (int j = 0; j < 8; j++) pk[j] = pack2(d[4 * j] + d[4 * j + 2], d[4 * j + 1] + d[4 * j + 3]);
                const uint32_t ow = w ^ (x & 1), dst = box + (ow * 3 + x - 1) * 4096;
                if (x & 2) {
                    st_async4(dst + peer, pk[0], pk[1], pk[2], pk[3], inb + ow * 8 + peer);
                    st_async4(dst + peer + 2048, pk[4], pk[5], pk[6], pk[7], inb + ow * 8 + peer);
                } else {
                    sts128(dst, pk[0], pk[1], pk[2], pk[3]);
                    sts128(dst + 2048, pk[4], pk[5], pk[6], pk[7]);
                }
            };
            TS(1 + ph * 10);
            step(d0, 0, a, w, 0, [&]() { gather_peer(); return 0u; });
            TS(32);
            step(d0, 1, a + 16, 0, 1, none);
            step(d1, 2, a, w, 0, [&]() { return act(d0, 0); });
            step(d1, 3, a + 16, 0, 1, none);
            step(d0, 4, a, w, 0, [&]() { return act(d1, 1); });
            TS(33);
            step(d0, 5, a + 16, 0, 1, none);
            step(d1, 6, a, w, 0, [&]() { return act(d0, 2); });
            step(d1, 7, a + 16, 0, 1, none);
            step(d0, 8, h, 0, 0, [&]() { return act(d1, 3); });
            TS(2 + ph * 10);
            step(d0, 9, h + 16, 0, 1, none);
            step(d1, 10, h, 0, 0, [&]() { send(d0, 3); return 0u; });
            step(d1, 11, h + 16, 0, 1, none);
            step(d0, 12, h, 0, 0, [&]() { send(d1, 2); return 0u; });
            TS(34);
            step(d0, 13, h + 16, 0, 1, none);
            step(d1, 14, h, 0, 0, [&]() { send(d0, 1); return 0u; });
            step(d1, 15, h + 16, 0, 1, none);
            if (ph == 0) acq(16);
            mbar_wait(inb + w * 8, 0);
            bar_sync(10, 256);
#pragma unroll
            for (int i = 0; i < 2; i++) {
                const uint32_t src = box + w * 12288 + i * 2048;
                const uint4 u0 = lds128(src), u1 = lds128(src + 4096), u2 = lds128(src + 8192);
                const uint32_t p0[4] = {u0.x, u0.y, u0.z, u0.w}, p1[4] = {u1.x, u1.y, u1.z, u1.w}, p2[4] = {u2.x, u2.y, u2.z, u2.w};
#pragma unroll
                for (int j = 0; j < 4; j++) {
                    v[8 * i + 2 * j] = fmaf(0.5f, blo(p0[j]) + blo(p1[j]) + blo(p2[j]), blo(xr[4 * i + j]));
                    v[8 * i + 2 * j + 1] = fmaf(0.5f, bhi(p0[j]) + bhi(p1[j]) + bhi(p2[j]), bhi(xr[4 * i + j]));
                }
            }
            wg_wait<0>();
            pin(d1);
            rel(15);
            TS(3 + ph * 10);
#pragma unroll
            for (int j = 0; j < 8; j++) {
                v[2 * j] = fmaf(0.5f, d1[4 * j] + d1[4 * j + 2], v[2 * j]);
                v[2 * j + 1] = fmaf(0.5f, d1[4 * j + 1] + d1[4 * j + 3], v[2 * j + 1]);
            }
            continue;
        }

        {
            TS(11);
            const uint32_t stg = H + warp * 2048;
            unsigned char* g = g_kvq + (size_t)((b * 4 + tile) * 1024 + trow) * 128 + lane * 16;
            auto put = [&](float (&d)[32], int i) {
                pin(d);
                uint32_t pk[8];
#pragma unroll
                for (int j = 0; j < 8; j++) pk[j] = pack2((d[4 * j] + d[4 * j + 2]) * rstd, (d[4 * j + 1] + d[4 * j + 3]) * rstd);
                if (i == 2) {
                    st_data(g + 2097152, pk[0], pk[1], pk[2], pk[3]);
                    st_data(g + 2097152 + 512, pk[4], pk[5], pk[6], pk[7]);
                    return;
                }
                stsm4(stg + i * 1024 + foff, pk[0], pk[1], pk[2], pk[3]);
                stsm4(stg + i * 1024 + (foff ^ 64), pk[4], pk[5], pk[6], pk[7]);
                __syncwarp();
                const uint4 u0 = lds128(stg + i * 1024 + lane * 16), u1 = lds128(stg + i * 1024 + 512 + lane * 16);
                stg128(g + i * 1048576, u0); stg128(g + i * 1048576 + 512, u1);
            };
            sp(d0, 16, a, w, 0);
            acq(17);
            sp(d1, 17, a, w, 0);
            gather_peer();
            acq(18);
            sp(d0, 18, a + 16, 0, 1);
            wg_wait<1>();
            rel(16); rel(17);
            acq(19);
            sp(d1, 19, a + 16, 0, 1);
            wg_wait<1>();
            rel(18);
            put(d0, 0);
            wg_wait<0>();
            rel(19);
            TS(37);
            put(d1, 1);
            bar_arrive(4, 288);
            TS(38);
            acq(20);
            sp(d0, 20, a, w, 0);
            acq(21);
            sp(d0, 21, a + 16, 0, 1);
            acq(22); acq(23);
            rel(22); rel(23);
            mbar_wait(bars + B_RST * 8, 0);
            wg_wait<0>();
            rel(20); rel(21);
            put(d0, 2);
            if (wq == 0 || wq == 3) {
                uint4* hp = &g_halo[((pair * 4 + tile) * 2 + (wq & 1)) * 64 + lane];
                st_data(hp, xr[0], xr[1], xr[2], xr[3]);
                st_data(hp + 32, xr[4], xr[5], xr[6], xr[7]);
            }
            TS(12);
        }

        const uint32_t xo = P + tile * XCH + wq * 1024, xt = P + tile * XCH + toff;
        {
            constexpr float CS = 0.125f * 1.4426950408889634f;
            float sa[32], sb2[32], o[36];
            uint32_t pa[16], pb[16], q[16];
            float n0 = INFINITY, n1 = INFINITY;
            zero(o); zero(pa); zero(pb); zero(sb2);
            const uint32_t ones = sb + OFF_MISC + 2048;
            { const uint32_t c = w ? 0u : 0x3F803F80u; sts128(ones + tid * 16, c, c, c, c); }
            fence_async_smem();
            bar_sync(10, 256);
            stsm4(xo + 1024 + foff, xr[0], xr[1], xr[2], xr[3]);
            stsm4(xo + 1024 + (foff ^ 64), xr[4], xr[5], xr[6], xr[7]);
            const uint32_t vdesc = rdesc + ((((ones - rbase) >> 4) - 1) << 16);
            auto qk_issue = [&](float (&s)[32], uint32_t lo) {
                const uint64_t kd = mkdesc(lo);
                wg_fence();
#pragma unroll
                for (int k = 0; k < 4; k++) mma_qk(s, q[4 * k], q[4 * k + 1], q[4 * k + 2], q[4 * k + 3], kd + 2 * k, k != 0);
                wg_commit();
            };
            auto both_issue = [&](float (&s)[32], uint32_t klo, uint32_t (&pp)[16], uint32_t vlo) {
                const uint64_t kd = mkdesc(klo), vd = mkdesc(vlo);
                wg_fence();
#pragma unroll
                for (int k = 0; k < 4; k++) {
                    mma_pv(o, pp[4 * k], pp[4 * k + 1], pp[4 * k + 2], pp[4 * k + 3], vd - k * (128 * 65535));
                    mma_qk(s, q[4 * k], q[4 * k + 1], q[4 * k + 2], q[4 * k + 3], kd + 2 * k, k != 0);
                }
                wg_commit();
            };
            auto new_max = [&](float (&s)[32], int nj, float& x0, float& x1) {
                x0 = s[0]; x1 = s[2];
#pragma unroll
                for (int j = 0; j < nj; j++) {
                    x0 = fmaxf(x0, fmaxf(s[4 * j], s[4 * j + 1]));
                    x1 = fmaxf(x1, fmaxf(s[4 * j + 2], s[4 * j + 3]));
                }
                x0 = fmaxf(x0, __shfl_xor_sync(~0u, x0, 1)); x1 = fmaxf(x1, __shfl_xor_sync(~0u, x1, 1));
                x0 = fmaxf(x0, __shfl_xor_sync(~0u, x0, 2)); x1 = fmaxf(x1, __shfl_xor_sync(~0u, x1, 2));
                x0 = fminf(n0, fmaf(x0, -CS, -20.f)); x1 = fminf(n1, fmaf(x1, -CS, -20.f));
            };
            auto probs = [&](float (&s)[32], uint32_t (&pp)[16], bool ready, bool tail, auto wait) {
                uint32_t any = 0;
#pragma unroll
                for (int i = 0; i < 16; i++) {
                    pp[i] = pack2(ex2(fmaf(s[2 * i], CS, (i & 1) ? n1 : n0)), ex2(fmaf(s[2 * i + 1], CS, (i & 1) ? n1 : n0)));
                    any |= pp[i];
                }
                wg_wait<0>();
                pin(sa); pin(sb2); pin(o); pin(pa); pin(pb);
                if (__any_sync(~0u, (any & 0x40004000u) || !ready)) {
                    wait();
                    if (__any_sync(~0u, any & 0x40004000u)) {
                        if (tail) {
#pragma unroll
                            for (int i = 20; i < 32; i++) s[i] = -INFINITY;
                        }
                        float x0, x1;
                        new_max(s, 8, x0, x1);
                        const float sc0 = ex2(x0 - n0), sc1 = ex2(x1 - n1);
                        n0 = x0; n1 = x1;
#pragma unroll
                        for (int j = 0; j < 9; j++) { o[4 * j] *= sc0; o[4 * j + 1] *= sc0; o[4 * j + 2] *= sc1; o[4 * j + 3] *= sc1; }
#pragma unroll
                        for (int i = 0; i < 16; i++)
                            pp[i] = pack2(ex2(fmaf(s[2 * i], CS, (i & 1) ? n1 : n0)), ex2(fmaf(s[2 * i + 1], CS, (i & 1) ? n1 : n0)));
                    }
                }
            };
            {
                uint4 u[4];
                const unsigned char* src = g_kvq + 2097152 + (size_t)(abh * 1024 + qt * 64 + wq * 16) * 128 + lane * 16;
                spin(QGATE);
                ld_data<512>(u, src);
#pragma unroll
                for (int k = 0; k < 2; k++) {
                    q[8 * k] = u[k].x; q[8 * k + 1] = u[k + 2].x; q[8 * k + 2] = u[k].y; q[8 * k + 3] = u[k + 2].y;
                    q[8 * k + 4] = u[k].z; q[8 * k + 5] = u[k + 2].z; q[8 * k + 6] = u[k].w; q[8 * k + 7] = u[k + 2].w;
                }
                pin(q);
            }
            TS(40);
            acq(24);
            TS(13);
            qk_issue(sa, rdesc + (24 % NSLOT) * (SLOT >> 4));
            wg_wait<0>();
            pin(sa);
            {
                float x0, x1;
                new_max(sa, NJ0, x0, x1);
                n0 = x0; n1 = x1;
            }
            bar_arrive(6, 384);
            uint32_t vd = vdesc - (SLOT >> 4) * 65535u, kd = rdesc, vb = fbar + 8, kb = fbar;
            uint32_t vlast = vdesc - 4 * (SLOT >> 4) * 65535u, klast = rdesc + 4 * (SLOT >> 4) + 512;
            uint32_t kprev = fbar + 32, vprev = bars + (B_SINK - (B_EMPTY - B_FULL)) * 8;
#pragma unroll 1
            for (int it = 0; it < 4; it++) {
                both_issue(sb2, klast, pb, vlast);
                probs(sa, pa, mbar_test(vb, it < 2) & mbar_test(kb, it < 3), false, [&]() { mbar_wait(vb, it < 2); mbar_wait(kb, it < 3); });
                TS(41 + it * 4);
                if (lane == 0) mbar_arrive(kprev + (B_EMPTY - B_FULL) * 8);
                if (lane == 0) mbar_arrive(vprev + (B_EMPTY - B_FULL) * 8);
                both_issue(sa, kd, pa, vd);
                const int dv = it == 0 ? 2 : (it == 1 ? -3 : 1);
                kprev = kb; vprev = vb; vlast = vd - 512 * 65535u; klast = kd + 512;
                vd -= dv * (SLOT >> 4) * 65535u; vb += dv * 8;
                kd += (it == 2 ? -3 : 2) * (SLOT >> 4); kb = it == 2 ? vb : kb + 16;
                probs(sb2, pb, true, it == 3 && w == 1, []() {});
                TS(43 + it * 4);
            }
            wg_fence();
#pragma unroll
            for (int k = 0; k < 4; k++)
                mma_pv(o, pb[4 * k], pb[4 * k + 1], pb[4 * k + 2], pb[4 * k + 3], mkdesc(vlast - k * (128 * 65535) + (k > 1 ? w * ((k - 1) << 22) : 0)));
            wg_commit();
            const int row = wq * 16 + (lane >> 2);
            const uint32_t ml = sb + OFF_MISC;
            mbar_wait(bars + (B_RST + 1) * 8, 0);
            wg_wait<0>();
            pin(o); pin(pb); pin(sa); pin(sb2);
            rel(31);
            const float l0 = o[32], l1 = o[34];
            if (c4 == 0) { sts64f(ml + w * 512 + row * 8, n0, l0); sts64f(ml + w * 512 + row * 8 + 64, n1, l1); }
            TS(14);
            float mine[16];
#pragma unroll
            for (int j = 0; j < 4; j++) {
                if (w == 0) sts128f(H + j * 2048 + wt * 16, o[16 + 4 * j], o[17 + 4 * j], o[18 + 4 * j], o[19 + 4 * j]);
                else sts128f(H + 8192 + j * 2048 + wt * 16, o[4 * j], o[4 * j + 1], o[4 * j + 2], o[4 * j + 3]);
            }
#pragma unroll
            for (int i = 0; i < 16; i++) mine[i] = w == 0 ? o[i] : o[16 + i];
            bar_sync(10, 256);
            const float2 u0 = lds64f(ml + (w ^ 1) * 512 + row * 8), u1 = lds64f(ml + (w ^ 1) * 512 + row * 8 + 64);
            const float x0 = fminf(n0, u0.x), x1 = fminf(n1, u1.x);
            float a0 = ex2(x0 - n0), b0 = ex2(x0 - u0.x), a1 = ex2(x1 - n1), b1 = ex2(x1 - u1.x);
            const float i0 = __fdividef(1.f, fmaf(a0, l0, b0 * u0.y)), i1 = __fdividef(1.f, fmaf(a1, l1, b1 * u1.y));
            a0 *= i0; b0 *= i0; a1 *= i1; b1 *= i1;
            uint32_t pk[8];
#pragma unroll
            for (int j = 0; j < 4; j++) {
                const float4 v = lds128f(H + (w ^ 1) * 8192 + j * 2048 + wt * 16);
                pk[2 * j] = pack2(fmaf(a0, mine[4 * j], b0 * v.x), fmaf(a0, mine[4 * j + 1], b0 * v.y));
                pk[2 * j + 1] = pack2(fmaf(a1, mine[4 * j + 2], b1 * v.z), fmaf(a1, mine[4 * j + 3], b1 * v.w));
            }
            unsigned char* dst = g_o + (size_t)(abh * PADROWS + 8 + qt * 64 + wq * 16) * 128 + w * 512 + lane * 16;
            st_data(dst, pk[0], pk[2], pk[4], pk[6]);
            st_data(dst + 1024, pk[1], pk[3], pk[5], pk[7]);
            if (tid == 0) asm volatile("red.relaxed.gpu.global.add.u32 [%0], 1;" ::"l"(&g_epoch[blockIdx.x * FS]) : "memory");
            TS(15);
        }

        auto mm = [&](float (&d)[24], int n, uint32_t act, int acc) {
            const uint32_t z = p.zero * (ph + n);
            const uint64_t ad = mkdesc(rdesc + z + (n % NSLOT) * (SLOT >> 4)), bd = mkdesc(desc_lo(act) + z);
            wg_fence();
#pragma unroll
            for (int k = 0; k < 8; k++) mma_t(d, ad + k * 128, bd + (k >> 2) * (XCH >> 4) + (k & 3) * 2, k == 0 ? acc : 1);
            wg_commit();
        };
        uint32_t dwr[15];
        {
#pragma unroll
            for (int i = 0; i < 15; i++) dwr[i] = hmul2(__ldg(reinterpret_cast<const uint32_t*>(p.dw + i * 256 + tile * 64) + lane), 0x3F003F00u);
            float d[24];
            uint32_t xw[12];
            bar_sync(9, 384);
#pragma unroll
            for (int j = 0; j < 3; j++) ldsm4t(xt + j * 2048, xw[4 * j], xw[4 * j + 1], xw[4 * j + 2], xw[4 * j + 3]);
            pin(xw);
            acq(32); acq(33); acq(34); acq(35);
            {
                if (ODELAY) spin(ODELAY);
                uint4 u[6];
                ld_data<1024>(u, g_o + (size_t)((b * 4 + (warp >> 1)) * PADROWS + pt * 32) * 128 + (warp & 1) * 512 + lane * 16);
                const uint32_t dst = H + (warp >> 1) * XCH + (foff ^ ((warp & 1) * 64));
#pragma unroll
                for (int i = 0; i < 6; i++) stsm4(dst + i * 1024, u[i].x, u[i].y, u[i].z, u[i].w);
            }
            fence_async_smem();
            bar_sync(10, 256);
            TS(16);
            if (WSTAG && w == 1) bar_sync(8, 256);
            mm(d, 32, H, 0);
            mm(d, 33, H + 2 * XCH, 1);
            if (WSTAG && w == 0) bar_arrive(8, 256);
            wg_wait<1>();
            rel(32);
            wg_wait<0>();
            pin(d);
#pragma unroll
            for (int i = 0; i < 12; i++) xw[i] = pack2(d[2 * i] + blo(xw[i]), d[2 * i + 1] + bhi(xw[i]));
            if (c4 == 0) { xw[0] = (xw[0] & 0xffff0000u) | 0x3F80u; xw[1] = (xw[1] & 0xffff0000u) | 0x3F80u; }
#pragma unroll
            for (int j = 0; j < 3; j++) stsm4t(xt + j * 2048, xw[4 * j], xw[4 * j + 1], xw[4 * j + 2], xw[4 * j + 3]);
            rel(33);
            publish(B_X2, P + tile * XCH, XCH, 352);
            TS(17);
        }
        {
            float da[24], db[24], st[24];
            bar_sync(5, 352);
            mm(da, 34, P + 2 * r * XCH, 0);
            mm(db, 35, P + 2 * r * XCH, 0);
            acq(36); acq(37);
            mbar_wait(bars + B_X2 * 8, 0);
            TS(39);
            if (PSTAG && w == 1) bar_sync(7, 256);
            mm(da, 36, P + 2 * (r ^ 1) * XCH, 1);
            mm(db, 37, P + 2 * (r ^ 1) * XCH, 1);
            if (PSTAG && w == 0) bar_arrive(7, 256);
            wg_wait<2>();
            rel(34); rel(35);
            mbar_wait(bars + B_ST * 8, 0);
#pragma unroll
            for (int j = 0; j < 6; j++) {
                const float4 u = lds128f(sb + OFF_STATS + (8 * j + 2 * c4) * 8);
                st[4 * j] = u.x; st[4 * j + 1] = u.y; st[4 * j + 2] = u.z; st[4 * j + 3] = u.w;
            }
            wg_wait<0>();
            pin(da); pin(db);
            rel(36); rel(37);
            TS(18);
            uint32_t pk[12];
#pragma unroll
            for (int hh = 0; hh < 2; hh++) {
                const float ca = __shfl_sync(~0u, da[2 * hh], lane & 28), cb = __shfl_sync(~0u, db[2 * hh], lane & 28);
#pragma unroll
                for (int j = 0; j < 6; j++) {
                    const float u0 = fmaf(-st[4 * j], ca, da[4 * j + 2 * hh] * st[4 * j + 1]);
                    const float u1 = fmaf(-st[4 * j + 2], ca, da[4 * j + 2 * hh + 1] * st[4 * j + 3]);
                    const float v0 = fmaf(-st[4 * j], cb, db[4 * j + 2 * hh] * st[4 * j + 1]);
                    const float v1 = fmaf(-st[4 * j + 2], cb, db[4 * j + 2 * hh + 1] * st[4 * j + 3]);
                    pk[2 * j + hh] = pack2(fmaf(u0, tanh_fast(v0), u0), fmaf(u1, tanh_fast(v1), u1));
                }
            }
            const uint32_t gs = H + 16384 + w * XCH;
#pragma unroll
            for (int j = 0; j < 3; j++) stsm4t(gs + toff + j * 2048, pk[4 * j], pk[4 * j + 1], pk[4 * j + 2], pk[4 * j + 3]);
            ldsm4(xo + 1024 + foff, xr[0], xr[1], xr[2], xr[3]);
            ldsm4(xo + 1024 + (foff ^ 64), xr[4], xr[5], xr[6], xr[7]);
            bar_sync(2 + w, 128);
            uint32_t ca[8], cb[8];
            const uint32_t grow = gs + 8 * wq * 128 + c4 * 4, srow = H + tile * HCH + 8 * wq * 128 + c4 * 4;
#pragma unroll
            for (int k = 0; k < 22; k++) {
                const uint32_t v = lds32(grow + (1 + k) * 128 + (((lane >> 2) ^ ((1 + k) & 7)) << 4));
#pragma unroll
                for (int i = 0; i < 8; i++) {
                    const int tap = k - i;
                    if (tap == 0) ca[i] = hmul2(v, dwr[0]);
                    else if (tap > 0 && tap < 8) ca[i] = hfma2(v, dwr[tap], ca[i]);
                    else if (tap == 8) cb[i] = hmul2(v, dwr[8]);
                    else if (tap > 8 && tap < 15) cb[i] = hfma2(v, dwr[tap], cb[i]);
                }
            }
#pragma unroll
            for (int i = 0; i < 8; i++) {
                const float h0 = blo(ca[i]) + blo(cb[i]), h1 = bhi(ca[i]) + bhi(cb[i]);
                sts32(srow + i * 128 + (((lane >> 2) ^ i) << 4), pack2(fmaf(h0, tanh_fast(h0), h0), fmaf(h1, tanh_fast(h1), h1)));
            }
            acq(38); acq(39);
            publish(B_SR, H + tile * HCH, HCH, 256);
            TS(19);
        }
        {
            auto frags = [&](int i, int half) {
                const uint32_t src = H + 2 * half * HCH + wq * 1024;
#pragma unroll
                for (int k = 0; k < 4; k++) ldsm4(src + (k >> 1) * HCH + (foff ^ ((k & 1) * 64)), a[i + 4 * k], a[i + 4 * k + 1], a[i + 4 * k + 2], a[i + 4 * k + 3]);
            };
            frags(0, r);
            sp(d0, 38, a, 0, 0);
            acq(40);
            mbar_wait(bars + B_SR * 8, 0);
            frags(16, r ^ 1);
            sp(d0, 39, a + 16, 0, 1);
            wg_wait<1>();
            rel(38);
            wg_wait<0>();
            pin(d0);
            rel(39);
#pragma unroll
            for (int j = 0; j < 8; j++) {
                v[2 * j] = d0[4 * j] + d0[4 * j + 2] + blo(xr[j]);
                v[2 * j + 1] = d0[4 * j + 1] + d0[4 * j + 3] + bhi(xr[j]);
            }
            TS(20);
        }
    }

    cluster_arrive();
    TS(24);
    {
        const float rstd = rsq(fmaxf(fmaf(-mean, mean, msq), 0.f) + 1e-5f), nb = -mean * rstd;
#pragma unroll
        for (int j = 0; j < 8; j++) xr[j] = pack2(fmaf(v[2 * j], rstd, nb), fmaf(v[2 * j + 1], rstd, nb));
        const uint32_t stg = P + 16384 + warp * 1024;
        stsm4(stg + foff, xr[0], xr[1], xr[2], xr[3]);
        stsm4(stg + (foff ^ 64), xr[4], xr[5], xr[6], xr[7]);
        __syncwarp();
        const uint32_t src = stg + (lane >> 3) * 128 + (((lane & 7) ^ (lane >> 3)) << 4);
        const uint4 u0 = lds128(src), u1 = lds128((src + 512) ^ 64);
        __nv_bfloat16* dst = p.out + (size_t)(b * T_ + trow + (lane >> 3)) * 256 + tile * 64 + (lane & 7) * 8;
        if (trow < T_) { stg128(dst, u0); stg128(dst + 4 * 256, u1); }
    }
    TS(25);
    TG(31);
    TSDUMP();
    cluster_wait();
}

typedef CUresult (*EncodeFn)(CUtensorMap*, CUtensorMapDataType, cuuint32_t, void*, const cuuint64_t*, const cuuint64_t*,
                             const cuuint32_t*, const cuuint32_t*, CUtensorMapInterleave, CUtensorMapSwizzle,
                             CUtensorMapL2promotion, CUtensorMapFloatOOBfill);

}

extern "C" void kernel_launch(void* const* d_in, const int* in_sizes, int n_in, void* d_out, int out_size) {
    static EncodeFn encode = nullptr;
    if (!encode) {
        void* fn = nullptr;
        cudaDriverEntryPointQueryResult qr;
        cudaGetDriverEntryPoint("cuTensorMapEncodeTiled", &fn, cudaEnableDefault, &qr);
        encode = (EncodeFn)fn;
        cudaFuncSetAttribute(conformer_kernel, cudaFuncAttributeMaxDynamicSharedMemorySize, SMEM_LAUNCH);
    }
    Params p;
    const cuuint32_t ones[5] = {1, 1, 1, 1, 1};
    const int idx[8] = {1, 2, 3, 4, 5, 7, 8, 9};
    const int rows[8] = {256, 1024, 256, 256, 256, 256, 256, 1024};
    const int cols[8] = {1024, 256, 768, 256, 512, 256, 1024, 256};
    for (int i = 0; i < 8; i++) {
        const bool perm = i != 3 && i != 4;
        const cuuint64_t pitch = (cuuint64_t)cols[i] * 2;
        const cuuint64_t dims[5] = {(cuuint64_t)cols[i], 2, 2, 4, (cuuint64_t)rows[i] / 16};
        const cuuint64_t strides[4] = {pitch, pitch * (perm ? 8 : 2), pitch * (perm ? 2 : 4), pitch * 16};
        const cuuint32_t box[5] = {64, 2, 2, 4, 8};
        encode(&p.tm[i], CU_TENSOR_MAP_DATA_TYPE_BFLOAT16, 5, d_in[idx[i]], dims, strides, box, ones, CU_TENSOR_MAP_INTERLEAVE_NONE,
               CU_TENSOR_MAP_SWIZZLE_128B, CU_TENSOR_MAP_L2_PROMOTION_L2_128B, CU_TENSOR_MAP_FLOAT_OOB_FILL_NONE);
        p.w[i] = (const char*)d_in[idx[i]];
    }
    {
        void* kv = nullptr;
        cudaGetSymbolAddress(&kv, g_kvq);
        const cuuint64_t dims[2] = {64, 16384};
        const cuuint64_t strides[1] = {128};
        const cuuint32_t box[2] = {64, 128};
        encode(&p.tm[8], CU_TENSOR_MAP_DATA_TYPE_BFLOAT16, 2, kv, dims, strides, box, ones, CU_TENSOR_MAP_INTERLEAVE_NONE,
               CU_TENSOR_MAP_SWIZZLE_NONE, CU_TENSOR_MAP_L2_PROMOTION_L2_128B, CU_TENSOR_MAP_FLOAT_OOB_FILL_NONE);
    }
    p.x = (const __nv_bfloat16*)d_in[0];
    p.dw = (const __nv_bfloat16*)d_in[6];
    p.out = (__nv_bfloat16*)d_out;
    p.zero = 0;
    conformer_kernel<<<NCTA, NTHREADS, SMEM_LAUNCH>>>(p);
}
```

```cpp
#include <cuda_runtime.h>
#include <cuda_bf16.h>
#include <cuda.h>
#include <stdint.h>

namespace {

constexpr int T_ = 1000;
constexpr int NCTA = 128;
constexpr int NTHREADS = 512;
constexpr int NSLOT = 5;
constexpr int SLOT = 16384;
constexpr int NLOADS = 56;

constexpr uint32_t OFF_RING = 0;
constexpr uint32_t OFF_P = 163840;
constexpr uint32_t OFF_H = 188416;
constexpr uint32_t OFF_MISC = 221184;
constexpr uint32_t OFF_BARS = 229888;
constexpr uint32_t SMEM_BYTES = 230400;
constexpr uint32_t GCH = 6144;
constexpr uint32_t HCH = 4096;

constexpr int B_FULL = 0, B_EMPTY = 10, B_XA = 20  , B_XB = 25  , B_INB = 29  , B_SR = 33,
              B_RST = 34  , B_RDY = 36  , B_SINK = 42, B_HALO = 43  , NBARS = 47;

#define KD2 300u
#define KD3 500u
#define QGATE 500u
#define BACKOFF 0u
#define KFS 8
#define KDELAY 300u
#define NJ0 2
#define HDELAY 300u
#define TURN 0
#define EAGER 0x4755
constexpr int FS = 8;

struct Params {
    CUtensorMap tm[9];
    const char* w[8];
    const __nv_bfloat16* x;
    const __nv_bfloat16* dw;
    __nv_bfloat16* out;
    uint32_t zero;
};

__device__ __align__(1024) unsigned char g_kvq[3 * 8 * 1024 * 128];
__device__ __align__(1024) unsigned char g_o[2 * 128 * 4096];
__device__ uint4 g_halo[64 * 4 * 2 * 64];
__device__ __align__(128) uint32_t g_flag_kv[8 * 32 * KFS];
__device__ uint32_t g_reset[4 * 32];
__device__ uint32_t g_epoch[NCTA * FS];

#define TS(i) do { } while (0)
#define TSW(i) do { } while (0)
#define TG(i) do { } while (0)
#define TSINIT() do { } while (0)
#define TSDUMP() do { } while (0)
constexpr uint32_t SMEM_LAUNCH = SMEM_BYTES;

__device__ __forceinline__ uint32_t smem_u32(const void* p) { return (uint32_t)__cvta_generic_to_shared(p); }
__device__ __forceinline__ void mbar_init(uint32_t b, uint32_t c) { asm volatile("mbarrier.init.shared::cta.b64 [%0], %1;" ::"r"(b), "r"(c) : "memory"); }
__device__ __forceinline__ void mbar_arrive(uint32_t b) { asm volatile("mbarrier.arrive.shared::cta.b64 _, [%0];" ::"r"(b) : "memory"); }
__device__ __forceinline__ void mbar_arrive_tx(uint32_t b, uint32_t tx) { asm volatile("mbarrier.arrive.expect_tx.shared::cta.b64 _, [%0], %1;" ::"r"(b), "r"(tx) : "memory"); }
__device__ __forceinline__ void mbar_wait(uint32_t b, uint32_t ph) {
    asm volatile("{\n.reg .pred p, q;\n.reg .u32 c;\nmov.u32 c, 0;\n"
                 "MW_LOOP:\n.pragma \"nounroll\";\n"
                 "mbarrier.try_wait.parity.shared::cta.b64 p, [%0], %1;\n"
                 "add.u32 c, c, 1;\nsetp.lt.u32 q, c, 65536;\nnot.pred p, p;\nand.pred p, p, q;\n@p bra MW_LOOP;\n}"
                 ::"r"(b), "r"(ph) : "memory");
}
__device__ __forceinline__ bool mbar_test(uint32_t b, uint32_t ph) {
    uint32_t ok;
    asm volatile("{\n.reg .pred p;\nmbarrier.test_wait.parity.shared::cta.b64 p, [%1], %2;\nselp.u32 %0, 1, 0, p;\n}" : "=r"(ok) : "r"(b), "r"(ph) : "memory");
    return ok;
}
__device__ __forceinline__ uint32_t mapa(uint32_t a, uint32_t r) { uint32_t o; asm("mapa.shared::cluster.u32 %0, %1, %2;" : "=r"(o) : "r"(a), "r"(r)); return o; }
__device__ __forceinline__ void fence_async_smem() { asm volatile("fence.proxy.async.shared::cta;" ::: "memory"); }
__device__ __forceinline__ void fence_async_global() { asm volatile("fence.proxy.async.global;" ::: "memory"); }
__device__ __forceinline__ void bar_sync(int id, int n) { asm volatile("bar.sync %0, %1;" ::"r"(id), "r"(n) : "memory"); }
__device__ __forceinline__ void bar_arrive(int id, int n) { asm volatile("bar.arrive %0, %1;" ::"r"(id), "r"(n) : "memory"); }
__device__ __forceinline__ void cluster_arrive() { asm volatile("barrier.cluster.arrive.relaxed.aligned;" ::: "memory"); }
__device__ __forceinline__ void cluster_wait() { asm volatile("barrier.cluster.wait.aligned;" ::: "memory"); }

__device__ __forceinline__ void ring_load(uint32_t dst, const CUtensorMap* tm, int col, int row16, uint32_t bar) {
    asm volatile("{\n.reg .pred p;\nelect.sync _|p, 0xffffffff;\n"
                 "@p mbarrier.arrive.expect_tx.shared::cta.b64 _, [%2], 16384;\n"
                 "@p cp.async.bulk.tensor.5d.shared::cluster.global.mbarrier::complete_tx::bytes [%0], [%1, {%3, 0, 0, 0, %4}], [%2];\n}"
                 ::"r"(dst), "l"(tm), "r"(bar), "r"(col), "r"(row16) : "memory");
}
__device__ __forceinline__ void ring_load_both(uint32_t dst, const CUtensorMap* tm, int c1, uint32_t bar) {
    asm volatile("{\n.reg .pred p;\nelect.sync _|p, 0xffffffff;\n"
                 "@p cp.async.bulk.tensor.2d.shared::cluster.global.mbarrier::complete_tx::bytes.multicast::cluster [%0], [%1, {0, %3}], [%2], %4;\n}"
                 ::"r"(dst), "l"(tm), "r"(bar), "r"(c1), "h"((uint16_t)3) : "memory");
}
__device__ __forceinline__ void mbar_arrive_peer(uint32_t b) { asm volatile("mbarrier.arrive.relaxed.cluster.shared::cluster.b64 _, [%0];" ::"r"(b) : "memory"); }
__device__ __forceinline__ void prefetch_l2(const void* src, uint32_t bytes) {
    asm volatile("cp.async.bulk.prefetch.L2.global [%0], %1;" ::"l"(src), "r"(bytes) : "memory");
}
__device__ __forceinline__ void peer_copy(uint32_t dst, uint32_t src, uint32_t bytes, uint32_t rbar) {
    asm volatile("{\n.reg .pred p;\nelect.sync _|p, 0xffffffff;\n"
                 "@p cp.async.bulk.shared::cluster.shared::cta.mbarrier::complete_tx::bytes [%0], [%1], %2, [%3];\n}"
                 ::"r"(dst), "r"(src), "r"(bytes), "r"(rbar) : "memory");
}
__device__ __forceinline__ void st_async4(uint32_t dst, uint32_t a, uint32_t b, uint32_t c, uint32_t d, uint32_t bar) {
    asm volatile("st.async.shared::cluster.mbarrier::complete_tx::bytes.v4.b32 [%0], {%1,%2,%3,%4}, [%5];" ::"r"(dst), "r"(a), "r"(b), "r"(c), "r"(d), "r"(bar) : "memory");
}
__device__ __forceinline__ void st_async2f(uint32_t dst, float a, float b, uint32_t bar) {
    asm volatile("st.async.shared::cluster.mbarrier::complete_tx::bytes.v2.f32 [%0], {%1,%2}, [%3];" ::"r"(dst), "f"(a), "f"(b), "r"(bar) : "memory");
}
__device__ __forceinline__ void stsm4(uint32_t a, uint32_t r0, uint32_t r1, uint32_t r2, uint32_t r3) {
    asm volatile("stmatrix.sync.aligned.m8n8.x4.shared.b16 [%0], {%1,%2,%3,%4};" ::"r"(a), "r"(r0), "r"(r1), "r"(r2), "r"(r3) : "memory");
}
__device__ __forceinline__ void ldsm4(uint32_t a, uint32_t& r0, uint32_t& r1, uint32_t& r2, uint32_t& r3) {
    asm volatile("ldmatrix.sync.aligned.m8n8.x4.shared.b16 {%0,%1,%2,%3}, [%4];" : "=r"(r0), "=r"(r1), "=r"(r2), "=r"(r3) : "r"(a) : "memory");
}
__device__ __forceinline__ uint4 lds128(uint32_t a) { uint4 v; asm volatile("ld.shared.v4.b32 {%0,%1,%2,%3}, [%4];" : "=r"(v.x), "=r"(v.y), "=r"(v.z), "=r"(v.w) : "r"(a) : "memory"); return v; }
__device__ __forceinline__ float4 lds128f(uint32_t a) { float4 v; asm volatile("ld.shared.v4.f32 {%0,%1,%2,%3}, [%4];" : "=f"(v.x), "=f"(v.y), "=f"(v.z), "=f"(v.w) : "r"(a) : "memory"); return v; }
__device__ __forceinline__ float2 lds64f(uint32_t a) { float2 v; asm volatile("ld.shared.v2.f32 {%0,%1}, [%2];" : "=f"(v.x), "=f"(v.y) : "r"(a) : "memory"); return v; }
__device__ __forceinline__ uint32_t lds32(uint32_t a) { uint32_t v; asm volatile("ld.shared.b32 %0, [%1];" : "=r"(v) : "r"(a) : "memory"); return v; }
__device__ __forceinline__ void sts128(uint32_t a, uint32_t x, uint32_t y, uint32_t z, uint32_t w) { asm volatile("st.shared.v4.b32 [%0], {%1,%2,%3,%4};" ::"r"(a), "r"(x), "r"(y), "r"(z), "r"(w) : "memory"); }
__device__ __forceinline__ void sts128f(uint32_t a, float x, float y, float z, float w) { asm volatile("st.shared.v4.f32 [%0], {%1,%2,%3,%4};" ::"r"(a), "f"(x), "f"(y), "f"(z), "f"(w) : "memory"); }
__device__ __forceinline__ void sts64f(uint32_t a, float x, float y) { asm volatile("st.shared.v2.f32 [%0], {%1,%2};" ::"r"(a), "f"(x), "f"(y) : "memory"); }
__device__ __forceinline__ void sts32(uint32_t a, uint32_t x) { asm volatile("st.shared.b32 [%0], %1;" ::"r"(a), "r"(x) : "memory"); }
__device__ __forceinline__ void stg128(void* p, uint4 v) { asm volatile("st.global.v4.b32 [%0], {%1,%2,%3,%4};" ::"l"(p), "r"(v.x), "r"(v.y), "r"(v.z), "r"(v.w) : "memory"); }

__device__ __forceinline__ uint32_t pack2(float lo, float hi) { uint32_t r; asm("cvt.rn.bf16x2.f32 %0, %1, %2;" : "=r"(r) : "f"(hi), "f"(lo)); return r; }
__device__ __forceinline__ float blo(uint32_t v) { return __uint_as_float(v << 16); }
__device__ __forceinline__ float bhi(uint32_t v) { return __uint_as_float(v & 0xffff0000u); }
__device__ __forceinline__ uint32_t hmul2(uint32_t a, uint32_t b) { uint32_t r; asm("mul.rn.bf16x2 %0, %1, %2;" : "=r"(r) : "r"(a), "r"(b)); return r; }
__device__ __forceinline__ uint32_t hsub2(uint32_t a, uint32_t b) { uint32_t r; asm("sub.rn.bf16x2 %0, %1, %2;" : "=r"(r) : "r"(a), "r"(b)); return r; }
__device__ __forceinline__ uint32_t hfma2(uint32_t a, uint32_t b, uint32_t c) { uint32_t r; asm("fma.rn.bf16x2 %0, %1, %2, %3;" : "=r"(r) : "r"(a), "r"(b), "r"(c)); return r; }
__device__ __forceinline__ float tanh_fast(float x) { float r; asm("tanh.approx.f32 %0, %1;" : "=f"(r) : "f"(x)); return r; }
__device__ __forceinline__ float rsq(float x) { float r; asm("rsqrt.approx.ftz.f32 %0, %1;" : "=f"(r) : "f"(x)); return r; }
__device__ __forceinline__ float ex2(float x) { float r; asm("ex2.approx.ftz.f32 %0, %1;" : "=f"(r) : "f"(x)); return r; }

__device__ __forceinline__ uint32_t ld_relaxed(const uint32_t* p) {
    uint32_t v;
    asm volatile("ld.relaxed.gpu.global.u32 %0, [%1];" : "=r"(v) : "l"(p) : "memory");
    return v;
}
__device__ __forceinline__ uint32_t clock32() { uint32_t c; asm volatile("mov.u32 %0, %%clock;" : "=r"(c)::"memory"); return c; }
__device__ __forceinline__ void spin(uint32_t clks) {
    const uint32_t t0 = clock32();
    while (clock32() - t0 < clks) {}
}
__device__ __forceinline__ void flag_wait(const uint32_t* p, uint32_t e, bool mine) {
#pragma unroll 1
    for (int i = 0; i < (1 << 19); i++) {
        if (mine) mine = ld_relaxed(p) != e;
        if (!__any_sync(~0u, mine)) break;
        if (BACKOFF) spin(BACKOFF);
    }
    asm volatile("fence.acquire.gpu;" ::: "memory");
    fence_async_global();
}
__device__ __forceinline__ void st_data(void* p, uint32_t x, uint32_t y, uint32_t z, uint32_t w) {
    asm volatile("st.relaxed.gpu.global.v4.b32 [%0], {%1,%2,%3,%4};" ::"l"(p), "r"(x), "r"(y), "r"(z), "r"(w) : "memory");
}
template <int STRIDE, int N>
__device__ __forceinline__ void ld_data(uint4 (&v)[N], const unsigned char* p) {
    int it = 0;
    bool again;
#pragma unroll 1
    do {
        uint32_t m = 0;
#pragma unroll
        for (int i = 0; i < N; i++)
            asm volatile("ld.relaxed.gpu.global.v4.b32 {%0,%1,%2,%3}, [%4];" : "=r"(v[i].x), "=r"(v[i].y), "=r"(v[i].z), "=r"(v[i].w) : "l"(p + i * STRIDE) : "memory");
#pragma unroll
        for (int i = 0; i < N; i++) m = __vimax3_u32(__vimax3_u32(v[i].x, v[i].y, v[i].z), v[i].w, m);
        again = __any_sync(~0u, m == ~0u) && ++it < (1 << 16);
    } while (again);
}
__device__ __forceinline__ uint32_t ld_epoch() { return ld_relaxed(&g_epoch[blockIdx.x * FS]) + 1; }
__device__ __forceinline__ void flag_set(uint32_t* p, uint32_t e) { asm volatile("st.release.gpu.global.u32 [%0], %1;" ::"l"(p), "r"(e) : "memory"); }

__device__ __forceinline__ uint32_t desc_lo(uint32_t addr) { return ((addr & 0x3FFFF) >> 4) | 0x10000u; }
__device__ __forceinline__ uint64_t mkdesc(uint32_t lo) { return (uint64_t)lo | (0x40000040ull << 32); }
__device__ __forceinline__ void wg_fence() { asm volatile("wgmma.fence.sync.aligned;" ::: "memory"); }
__device__ __forceinline__ void wg_commit() { asm volatile("wgmma.commit_group.sync.aligned;" ::: "memory"); }
template <int N> __device__ __forceinline__ void wg_wait() { asm volatile("wgmma.wait_group.sync.aligned %0;" ::"n"(N) : "memory"); }
template <int N> __device__ __forceinline__ void pin(float (&d)[N]) {
#pragma unroll
    for (int i = 0; i < N; i++) asm volatile("" : "+f"(d[i])::"memory");
}
template <int N> __device__ __forceinline__ void pin(uint32_t (&d)[N]) {
#pragma unroll
    for (int i = 0; i < N; i++) asm volatile("" : "+r"(d[i])::"memory");
}

template <typename Tp, int N> __device__ __forceinline__ void zero(Tp (&d)[N]) {
#pragma unroll
    for (int i = 0; i < N; i++) d[i] = 0;
    pin(d);
}

#define F4(d, i) "+f"(d[i]), "+f"(d[i + 1]), "+f"(d[i + 2]), "+f"(d[i + 3])
#define F16(d, i) F4(d, i), F4(d, i + 4), F4(d, i + 8), F4(d, i + 12)

__device__ __forceinline__ void mma_sp(float (&d)[32], const uint32_t* a, uint64_t b, uint32_t meta, int acc) {
    asm volatile("{.reg .pred p; setp.ne.b32 p, %38, 0;\n"
                 "wgmma.mma_async.sp.sync.aligned.m64n64k32.f32.bf16.bf16 {%0,%1,%2,%3,%4,%5,%6,%7,%8,%9,%10,%11,%12,%13,%14,%15,%16,%17,%18,%19,%20,%21,%22,%23,%24,%25,%26,%27,%28,%29,%30,%31}, "
                 "{%32,%33,%34,%35}, %36, %37, 0, p, 1, 1, 1;}\n"
                 : F16(d, 0), F16(d, 16) : "r"(a[0]), "r"(a[1]), "r"(a[2]), "r"(a[3]), "l"(b), "r"(meta), "r"(acc));
}
__device__ __forceinline__ void mma_qk(float (&d)[32], uint32_t a0, uint32_t a1, uint32_t a2, uint32_t a3, uint64_t b, int acc) {
    asm volatile("{.reg .pred p; setp.ne.b32 p, %37, 0;\n"
                 "wgmma.mma_async.sync.aligned.m64n64k16.f32.bf16.bf16 {%0,%1,%2,%3,%4,%5,%6,%7,%8,%9,%10,%11,%12,%13,%14,%15,%16,%17,%18,%19,%20,%21,%22,%23,%24,%25,%26,%27,%28,%29,%30,%31}, "
                 "{%32,%33,%34,%35}, %36, p, 1, 1, 0;}\n"
                 : F16(d, 0), F16(d, 16) : "r"(a0), "r"(a1), "r"(a2), "r"(a3), "l"(b), "r"(acc));
}
__device__ __forceinline__ void mma_pv(float (&d)[36], uint32_t a0, uint32_t a1, uint32_t a2, uint32_t a3, uint64_t b) {
    asm volatile("wgmma.mma_async.sync.aligned.m64n72k16.f32.bf16.bf16 {%0,%1,%2,%3,%4,%5,%6,%7,%8,%9,%10,%11,%12,%13,%14,%15,%16,%17,%18,%19,%20,%21,%22,%23,%24,%25,%26,%27,%28,%29,%30,%31,%32,%33,%34,%35}, "
                 "{%36,%37,%38,%39}, %40, 1, 1, 1, 1;\n"
                 : F16(d, 0), F16(d, 16), F4(d, 32) : "r"(a0), "r"(a1), "r"(a2), "r"(a3), "l"(b));
}

__device__ __forceinline__ uint32_t load_code(int n, int r, int w) {
    const int tile = 2 * r + w;
    int m, col, row;
    if (n < 16 || n >= 40) {
        const int k = n < 16 ? n : n - 40;
        m = n < 16 ? 0 : 6;
        if (k < 8) { col = 4 * tile + (k >> 1); row = (k & 1) ^ r; }
        else { m++; col = tile ^ (3 - ((k - 8) >> 1)); row = 2 * tile + (k & 1); }
    } else if (n < 32) {
        const int k = n - 16;
        m = 2;
        if (k < 4) { col = tile + ((k & 1) ? 8 : 4); row = (k >> 1) ^ r; }
        else { col = tile; row = (k & 1) ^ r; }
    } else if (n < 34) { m = 3; col = tile; row = n - 32; }
    else if (n < 38) { const int k = n - 34; m = 4; col = tile + 4 * (k & 1); row = (k >> 1) ^ r; }
    else { m = 5; col = tile; row = (n & 1) ^ r; }
    return m | (col << 4) | (row << 8);
}

__global__ void __cluster_dims__(2, 1, 1) __launch_bounds__(NTHREADS, 1)
conformer_kernel(const __grid_constant__ Params p) {
    extern __shared__ __align__(1024) unsigned char smem_raw[];
    const uint32_t sb = smem_u32(smem_raw);
    const uint32_t bars = sb + OFF_BARS;
    const int tid = threadIdx.x;
    const int lane = tid & 31;
    const int warp = __shfl_sync(~0u, tid >> 5, 0);
    const int r = blockIdx.x & 1;
    const int pair = blockIdx.x >> 1;
    const int b = pair >> 5, pt = pair & 31;
    const int ah = pt >> 3, qt = (pt & 7) * 2 + r;
    const int abh = b * 4 + ah;

    TG(30);
    TSINIT();
    TS(0);
    const uint32_t P = sb + OFF_P, H = sb + OFF_H;

    if (warp >= 8) {
        asm volatile("setmaxnreg.dec.sync.aligned.u32 48;");
        if (warp >= 12) {
            cluster_arrive();
            cluster_wait();
            const int ut = tid & 127;
            const uint32_t target = ld_epoch() * 64;
            auto reset_done = [&](int k) {
                bar_sync(11, 128);
                if (ut == 0) {
                    asm volatile("red.release.gpu.global.add.u32 [%0], 1;" ::"l"(&g_reset[(2 * b + k) * 32]) : "memory");
#pragma unroll 1
                    for (int i = 0; i < (1 << 20) && ld_relaxed(&g_reset[(2 * b + k) * 32]) != target; i++) __nanosleep(100);
                    asm volatile("fence.acquire.gpu;" ::: "memory");
                    mbar_arrive(bars + (B_RST + k) * 8);
                }
                __syncwarp();
                TS(13 + k);
            };
#pragma unroll
            for (int i = 0; i < 4; i++)
                st_data(g_kvq + 2097152 + (size_t)((b * 4 + 2 * r + (i >> 1)) * 1024 + pt * 32) * 128 + (i & 1) * 2048 + ut * 16, ~0u, ~0u, ~0u, ~0u);
            reset_done(0);
            bar_sync(6, 384);
#pragma unroll
            for (int i = 0; i < 4; i++) {
                st_data(g_o + (size_t)(b * 128 + qt * 8 + 2 * i + (ut >> 6)) * 4096 + ah * 1024 + (ut & 63) * 16, ~0u, ~0u, ~0u, ~0u);
                if (i < 2) st_data(&g_halo[(pair * 4 + 2 * r + i) * 128 + ut], ~0u, ~0u, ~0u, ~0u);
            }
            reset_done(1);
            const int side = warp & 1, wg = (warp >> 1) & 1, np = side ? pt + 1 : pt - 1;
            const unsigned char* src = reinterpret_cast<const unsigned char*>(&g_halo[(((b * 32 + np) * 4 + 2 * r + wg) * 2 + (side ^ 1)) * 64 + lane]);
            const uint32_t dst = H + 16384 + wg * GCH + side * 5120 + (lane & 7) * 128 + (((lane >> 3) ^ (lane & 7)) << 4);
            uint4 hv[2] = {make_uint4(0, 0, 0, 0), make_uint4(0, 0, 0, 0)};
            bar_sync(8 + wg, 192);
            if (np >= 0 && np < 32) {
                spin(HDELAY);
                ld_data<512>(hv, src);
            }
            stsm4(dst, hv[0].x, hv[0].y, hv[0].z, hv[0].w);
            stsm4(dst ^ 64, hv[1].x, hv[1].y, hv[1].z, hv[1].w);
            __syncwarp();
            if (lane == 0) mbar_arrive(bars + (B_HALO + (warp & 3)) * 8);
            TS(4);
        } else if (warp < 10) {
            const int w = warp - 8;
            const uint32_t ring = sb + OFF_RING + w * NSLOT * SLOT;
            const uint32_t full = bars + (B_FULL + w * NSLOT) * 8;
            if (lane == 0) {
#pragma unroll
                for (int i = 0; i < NSLOT; i++) { mbar_init(full + i * 8, 1); mbar_init(full + (B_EMPTY - B_FULL + i) * 8, 4); }
                asm volatile("fence.mbarrier_init.release.cluster;" ::: "memory");
                fence_async_smem();
            }
            __syncwarp();
            cluster_arrive();
            TS(1);
#pragma unroll
            for (int n = 0; n < NSLOT; n++) {
                if (n == 1 || n == 2) bar_sync(12, 64);
                ring_load(ring + n * SLOT, &p.tm[0], 64 * (8 * r + 4 * w + (n >> 1)), 8 * ((n & 1) ^ r), full + n * 8);
            }
            TS(2);
            const uint32_t code = load_code(lane, r, w) | (load_code(lane + 32, r, w) << 16);
            cluster_wait();
            uint32_t s = 0, ph = 0;
            int n = NSLOT;
#pragma unroll 1
            for (int seg = 0; seg < 2; seg++) {
#pragma unroll 1
                for (; n < (seg == 0 ? 22 : NLOADS); n++) {
                    const uint32_t c = __shfl_sync(~0u, code, n) >> (n & 32 ? 16 : 0);
                    const CUtensorMap* tm = &p.tm[c & 15];
                    const uint32_t col = (c & 0xf0) * 4, row = (c & 0xff00) >> 5, dst = ring + s * SLOT;
                    mbar_wait(full + (B_EMPTY - B_FULL) * 8 + s * 8, ph + (((uint32_t)(size_t)tm | col | row | dst) & p.zero));
                    ring_load(dst, tm, col, row, full + s * 8);
                    if (++s == NSLOT) { s = 0; ph ^= 1; }
                }
                if (seg == 1) break;
                const uint32_t epoch = ld_epoch();
                const uint32_t rdy = bars + (B_RDY + 3 * w) * 8, prdy = mapa(rdy, r ^ 1);
                const int odd = r ^ w;
                const uint32_t* flags = g_flag_kv + (abh * 32 + lane) * KFS;
                auto kv_load = [&](uint32_t sl, int isv, int i) {
                    ring_load_both(ring + sl * SLOT, &p.tm[8], (isv * 64 + abh * 8 + 2 * i + w) * 128, full + sl * 8);
                };
#pragma unroll 1
                for (int i = 0; i < 2; i++) {
                    if (lane < 3 + i) {
                        const uint32_t sl = i ? lane : lane + 2;
                        mbar_wait(full + (B_EMPTY - B_FULL + sl) * 8, i ^ 1);
                        mbar_arrive_tx(full + sl * 8, (i || lane == 2) ? SLOT : 0);
                    }
                    __syncwarp();
                }
                if (lane == 0) mbar_arrive_peer(prdy);
                bar_sync(14, 96);
                spin(KDELAY);
                mbar_wait(rdy, 0);
                flag_wait(flags, epoch, (lane >> 2) == 2 * odd + w);
                TSW(5 + 2 * odd);
                if (!odd) { kv_load(4, 0, 0); bar_arrive(12, 64); }
                else bar_sync(12, 64);
                spin(w ? KD3 : KD2);
                kv_load(odd ^ 1, odd ^ 1, odd);
                flag_wait(flags, epoch, (lane >> 2) == 2 * odd + w + 4);
                mbar_wait(full + (odd ^ 1) * 8, 1);
                kv_load(2 + odd, odd, 2 - odd);
#pragma unroll 1
                for (int i = 0; i < 3; i++) {
                    const uint32_t sl = i ? i - 1 : 4, bo = i == 2 ? 16 : 8;
                    mbar_wait(full + (B_EMPTY - B_FULL + sl) * 8, i != 0);
                    if (lane == 0) mbar_arrive_tx(full + sl * 8, SLOT);
                    if ((i & 1) != odd) {
                        mbar_wait(rdy + bo, 0);
                        kv_load(sl, i != 0, 2 + odd);
                    } else if (lane == 0) mbar_arrive_peer(prdy + bo);
                    __syncwarp();
                }
                n = 32; s = 2; ph = 1;
            }
        } else if (warp == 10) {
            if (lane == 0) {
#pragma unroll
                for (int i = B_XA; i < NBARS; i++) mbar_init(bars + i * 8, 1);
#pragma unroll
                for (int i = B_XA; i <= B_SR; i++) mbar_arrive_tx(bars + i * 8, i < B_XB ? 512 : 8192);
                asm volatile("fence.mbarrier_init.release.cluster;" ::: "memory");
                fence_async_smem();
            }
            __syncwarp();
            cluster_arrive();
            cluster_wait();
        } else {
            const uint32_t kb = (lane < 2 || lane > 5) ? 4096 : (lane == 2 ? 3072 : (lane == 4 ? 2048 : 1024));
            const char* pf = p.w[lane & 7] + blockIdx.x * kb;
            cluster_arrive();
            cluster_wait();
            if (lane < 2) prefetch_l2(pf, kb);
            mbar_wait(bars + B_XA * 8, 0);
            if (lane == 2) prefetch_l2(pf, kb);
            if (lane >= 1 && lane < 9) asm volatile("prefetch.tensormap [%0];" ::"l"(&p.tm[lane]) : "memory");
            mbar_wait(bars + (B_FULL + 1) * 8, 1);
            if (lane > 2 && lane < 8) prefetch_l2(pf, kb);
            if (lane == 8 && blockIdx.x < 15) prefetch_l2(p.dw + blockIdx.x * 256, 512);
            const uint32_t epoch = ld_epoch();
            bar_sync(4, 288);
            if (lane < 16) flag_set(&g_flag_kv[((b * 4 + 2 * r + (lane >> 3)) * 32 + pt) * KFS + (lane & 7)], epoch);
            __syncwarp();
            bar_arrive(14, 96);
            TSW(8);
        }
        TSDUMP();
        return;
    }

    const int w = warp >> 2, wq = warp & 3;
    const int tile = 2 * r + w;
    const int wt = tid & 127;
    const int c4 = lane & 3;
    const int trow = pt * 32 + 8 * wq;
    uint32_t xr[8];
    {
        const uint32_t* xp = reinterpret_cast<const uint32_t*>(p.x + (size_t)(b * T_ + trow + (lane >> 2)) * 256 + tile * 64) + c4;
#pragma unroll
        for (int j = 0; j < 8; j++) xr[j] = trow < T_ ? __ldg(xp + 4 * j) : 0u;
    }
    cluster_arrive();
    asm volatile("setmaxnreg.inc.sync.aligned.u32 208;");
    const uint32_t rbase = sb + OFF_RING + w * NSLOT * SLOT, fbar = bars + (B_FULL + w * NSLOT) * 8;
    const uint32_t rdesc = desc_lo(rbase);
    auto acq = [&](int n) { mbar_wait(fbar + (n % NSLOT) * 8, (n / NSLOT) & 1); };
    auto rel = [&](int n) { if (lane == 0) mbar_arrive(fbar + (B_EMPTY - B_FULL + n % NSLOT) * 8); };
    const uint32_t foff = (lane & 7) * 128 + (((lane >> 3) ^ (lane & 7)) << 4);
    float v[16];
#pragma unroll
    for (int j = 0; j < 8; j++) { v[2 * j] = blo(xr[j]); v[2 * j + 1] = bhi(xr[j]); }
    const uint32_t xown = __shfl_sync(~0u, P + wt * 16 + tile * 4096, lane), xrem = __shfl_sync(~0u, P + wt * 16 + (r ^ 1) * 8192, lane);
    const uint32_t sbuf = __shfl_sync(~0u, sb + OFF_MISC + 1024 + (8 * wq + (lane >> 2)) * 32, lane);
    const uint32_t sown = __shfl_sync(~0u, sbuf + tile * 8, lane);
    const uint32_t peer = __shfl_sync(~0u, mapa(sb, r ^ 1) - sb, lane);
    const uint32_t meta = __shfl_sync(~0u, 0xEEEE4444u + p.zero, lane);
    cluster_wait();
    TS(56);
    float mean, msq;

#pragma unroll 1
    for (int ph = 0;; ph++) {
        uint4 o0, o1;
        {
            float s = 0.f, q = 0.f, s2 = 0.f, q2 = 0.f;
#pragma unroll
            for (int j = 0; j < 4; j++) {
                s += v[4 * j] + v[4 * j + 1]; s2 += v[4 * j + 2] + v[4 * j + 3];
                q += fmaf(v[4 * j], v[4 * j], v[4 * j + 1] * v[4 * j + 1]); q2 += fmaf(v[4 * j + 2], v[4 * j + 2], v[4 * j + 3] * v[4 * j + 3]);
            }
            s += s2; q += q2;
            const uint32_t xa = bars + (B_XA + ph) * 8;
            s += __shfl_xor_sync(~0u, s, 1); q += __shfl_xor_sync(~0u, q, 1);
            s += __shfl_xor_sync(~0u, s, 2); q += __shfl_xor_sync(~0u, q, 2);
            if (c4 == 0) st_async2f(sown + peer, s, q, xa + peer);
            if (c4 == 0) sts64f(sown, s, q);
#pragma unroll
            for (int j = 0; j < 8; j++) xr[j] = pack2(v[2 * j], v[2 * j + 1]);
            sts128(xown, xr[0], xr[1], xr[2], xr[3]);
            sts128(xown + 2048, xr[4], xr[5], xr[6], xr[7]);
            bar_sync(10, 256);
            o0 = lds128(xown ^ 4096); o1 = lds128((xown ^ 4096) + 2048);
            if (ph < 4) {
                st_async4(xown + peer, xr[0], xr[1], xr[2], xr[3], xa + (B_XB - B_XA) * 8 + peer);
                st_async4(xown + peer + 2048, xr[4], xr[5], xr[6], xr[7], xa + (B_XB - B_XA) * 8 + peer);
            }
            TS(57 + ph);
            if (ph == 0) acq(0);
            mbar_wait(xa, 0);
            const float4 u0 = lds128f(sbuf), u1 = lds128f(sbuf + 16);
            mean = ((u0.x + u0.z) + (u1.x + u1.z)) * (1.f / 256.f);
            msq = ((u0.y + u0.w) + (u1.y + u1.w)) * (1.f / 256.f);
        }
        if (ph == 4) break;
        uint32_t a[32];
        const uint32_t mean2 = pack2(mean, mean);
        auto centre = [&](int i, const uint4& u) {
            a[i] = hsub2(u.x, mean2); a[i + 1] = hsub2(u.y, mean2); a[i + 2] = hsub2(u.z, mean2); a[i + 3] = hsub2(u.w, mean2);
        };
#pragma unroll
        for (int j = 0; j < 8; j++) a[j] = hsub2(xr[j], mean2);
        centre(8, o0); centre(12, o1);
        const float rstd = rsq(fmaxf(fmaf(-mean, mean, msq), 0.f) + 1e-5f);
        auto gather_peer = [&]() {
            mbar_wait(bars + (B_XB + ph) * 8, 0);
#pragma unroll
            for (int i = 0; i < 4; i++) centre(16 + 4 * i, lds128(xrem + i * 2048));
        };
        auto sp = [&](float (&d)[32], int n, const uint32_t* af, int flip, int acc) {
            const uint32_t lo = rdesc + p.zero * (ph + n + 1) + (n % NSLOT) * (SLOT >> 4);
            const uint64_t b0 = mkdesc(lo + flip * 512), b1 = mkdesc(lo + (flip ^ 1) * 512);
            wg_fence();
            mma_sp(d, af, b0, meta, acc);
            mma_sp(d, af + 4, b0 + 256, meta, 1);
            mma_sp(d, af + 8, b1, meta, 1);
            mma_sp(d, af + 12, b1 + 256, meta, 1);
            wg_commit();
        };
        float d0[32], d1[32];

        if (ph == 0 || ph == 3) {
            uint32_t h[32];
            const float rs = 0.5f * rstd;
            const uint32_t inb = bars + (B_INB + (ph & 2)) * 8, box = H + wt * 16;
            bool ready = true;
            auto step = [&](float (&d)[32], int n, const uint32_t* af, int flip, int acc, auto work) {
                if (!ready) acq(n);
                if (((TURN >> n) & 1) && w == 1) bar_sync(7, 256);
                sp(d, n, af, flip, acc);
                if (n > 0 && ((TURN >> (n - 1)) & 1) && w == 0) bar_arrive(7, 256);
                if (n < 15) ready = mbar_test(fbar + ((n + 1) % NSLOT) * 8, ((n + 1) / NSLOT) & 1);
                wg_wait<1>();
                if (n > 0 && !((EAGER >> (n - 1)) & 1)) rel(n - 1);
                const uint32_t tie = work() & p.zero;
                if ((EAGER >> n) & 1) {
                    if (p.zero < n + ph + 1) wg_wait<0>();
                    if (lane == 0) mbar_arrive(fbar + (B_EMPTY - B_FULL + n % NSLOT) * 8 + tie);
                }
            };
            auto none = []() { return 0u; };
            auto act = [&](float (&d)[32], int i) {
                pin(d);
#pragma unroll
                for (int j = 0; j < 8; j++) {
                    const float u0 = (d[4 * j] + d[4 * j + 2]) * rs, u1 = (d[4 * j + 1] + d[4 * j + 3]) * rs;
                    h[8 * i + j] = pack2(fmaf(u0, tanh_fast(u0), u0), fmaf(u1, tanh_fast(u1), u1));
                }
                return h[8 * i] | h[8 * i + 1] | h[8 * i + 2] | h[8 * i + 3] | h[8 * i + 4] | h[8 * i + 5] | h[8 * i + 6] | h[8 * i + 7];
            };
            auto send = [&](float (&d)[32], int x) {
                pin(d);
                uint32_t pk[8];
#pragma unroll
                for (int j = 0; j < 8; j++) pk[j] = pack2(d[4 * j] + d[4 * j + 2], d[4 * j + 1] + d[4 * j + 3]);
                const uint32_t ow = w ^ (x & 1), dst = box + (ow * 3 + x - 1) * 4096;
                if (x & 2) {
                    st_async4(dst + peer, pk[0], pk[1], pk[2], pk[3], inb + ow * 8 + peer);
                    st_async4(dst + peer + 2048, pk[4], pk[5], pk[6], pk[7], inb + ow * 8 + peer);
                } else {
                    sts128(dst, pk[0], pk[1], pk[2], pk[3]);
                    sts128(dst + 2048, pk[4], pk[5], pk[6], pk[7]);
                }
            };
            TS(1 + (ph & 2) * 10);
            step(d0, 0, a, w, 0, [&]() { gather_peer(); return 0u; });
            TS(32);
            step(d0, 1, a + 16, 0, 1, none);
            step(d1, 2, a, w, 0, [&]() { return act(d0, 0); });
            step(d1, 3, a + 16, 0, 1, none);
            step(d0, 4, a, w, 0, [&]() { return act(d1, 1); });
            TS(33);
            step(d0, 5, a + 16, 0, 1, none);
            step(d1, 6, a, w, 0, [&]() { return act(d0, 2); });
            step(d1, 7, a + 16, 0, 1, none);
            step(d0, 8, h, 0, 0, [&]() { return act(d1, 3); });
            TS(2 + (ph & 2) * 10);
            step(d0, 9, h + 16, 0, 1, none);
            step(d1, 10, h, 0, 0, [&]() { send(d0, 3); return 0u; });
            step(d1, 11, h + 16, 0, 1, none);
            step(d0, 12, h, 0, 0, [&]() { send(d1, 2); return 0u; });
            TS(34);
            step(d0, 13, h + 16, 0, 1, none);
            uint4 u[6];
            step(d1, 14, h, 0, 0, [&]() {
                send(d0, 1);
                mbar_wait(inb + w * 8, 0);
                bar_sync(10, 256);
#pragma unroll
                for (int i = 0; i < 6; i++) u[i] = lds128(box + w * 12288 + i * 2048);
                return u[0].x | u[1].x | u[2].x | u[3].x | u[4].x | u[5].x;
            });
            step(d1, 15, h + 16, 0, 1, none);
            mbar_wait(ph == 0 ? fbar + (16 % NSLOT) * 8 : inb + w * 8, ph == 0);
            uint32_t tie = 0;
#pragma unroll
            for (int i = 0; i < 2; i++) {
                const uint32_t p0[4] = {u[i].x, u[i].y, u[i].z, u[i].w}, p1[4] = {u[i + 2].x, u[i + 2].y, u[i + 2].z, u[i + 2].w}, p2[4] = {u[i + 4].x, u[i + 4].y, u[i + 4].z, u[i + 4].w};
#pragma unroll
                for (int j = 0; j < 4; j++) {
                    v[8 * i + 2 * j] = fmaf(0.5f, blo(p0[j]) + blo(p1[j]) + blo(p2[j]), blo(xr[4 * i + j]));
                    v[8 * i + 2 * j + 1] = fmaf(0.5f, bhi(p0[j]) + bhi(p1[j]) + bhi(p2[j]), bhi(xr[4 * i + j]));
                    tie |= __float_as_uint(v[8 * i + 2 * j]) | __float_as_uint(v[8 * i + 2 * j + 1]);
                }
            }
            if (__any_sync(~0u, tie & p.zero)) spin(1);
            wg_wait<0>();
            pin(d1);
            rel(15);
            TS(3 + (ph & 2) * 10);
#pragma unroll
            for (int j = 0; j < 8; j++) {
                v[2 * j] = fmaf(0.5f, d1[4 * j] + d1[4 * j + 2], v[2 * j]);
                v[2 * j + 1] = fmaf(0.5f, d1[4 * j + 1] + d1[4 * j + 3], v[2 * j + 1]);
            }
            continue;
        }

        auto residual = [&](int n) {
            wg_wait<1>();
            rel(n);
            wg_wait<0>();
            pin(d0);
            rel(n + 1);
#pragma unroll
            for (int j = 0; j < 8; j++) {
                v[2 * j] = d0[4 * j] + d0[4 * j + 2] + blo(xr[j]);
                v[2 * j + 1] = d0[4 * j + 1] + d0[4 * j + 3] + bhi(xr[j]);
            }
        };

        if (ph == 2) {
            TS(39);
            sp(d0, 34, a, w, 0);
            acq(35);
            sp(d1, 35, a, w, 0);
            const int mir = wq < 2 ? 7 : 0;
            uint32_t dwr[15];
#pragma unroll
            for (int i = 0; i < 15; i++)
                dwr[i] = __ldg(reinterpret_cast<const uint32_t*>(p.dw + (mir ? 14 - i : i) * 256 + tile * 64) + lane);
            acq(36);
            gather_peer();
            sp(d0, 36, a + 16, 0, 1);
            acq(37);
            sp(d1, 37, a + 16, 0, 1);
            wg_wait<2>();
            rel(34); rel(35);
#pragma unroll
            for (int i = 0; i < 15; i++) dwr[i] = hmul2(dwr[i], 0x3F003F00u);
            const float rs = trow < T_ ? 0.5f * rstd : 0.f;
            wg_wait<0>();
            pin(d0); pin(d1);
            rel(36); rel(37);
            TS(18);
            uint32_t pk[8];
#pragma unroll
            for (int j = 0; j < 8; j++) {
                const float u0 = (d0[4 * j] + d0[4 * j + 2]) * rs, u1 = (d0[4 * j + 1] + d0[4 * j + 3]) * rs;
                const float t0 = tanh_fast((d1[4 * j] + d1[4 * j + 2]) * rs), t1 = tanh_fast((d1[4 * j + 1] + d1[4 * j + 3]) * rs);
                pk[j] = pack2(fmaf(u0, t0, u0), fmaf(u1, t1, u1));
            }
            if (wq == 0 || wq == 3) {
                uint4* hp = &g_halo[((pair * 4 + tile) * 2 + (wq & 1)) * 64 + lane];
                st_data(hp, pk[0], pk[1], pk[2], pk[3]);
                st_data(hp + 32, pk[4], pk[5], pk[6], pk[7]);
            }
            const uint32_t gs = H + 16384 + w * GCH + wq * 1024;
            stsm4(gs + 1024 + foff, pk[0], pk[1], pk[2], pk[3]);
            stsm4(gs + 1024 + (foff ^ 64), pk[4], pk[5], pk[6], pk[7]);
            bar_sync(8 + w, 192);
            TS(26);
            uint32_t ca[8], cb[8];
            const uint32_t lo = (mir * 144) ^ (lane * 4);
#pragma unroll
            for (int k = 0; k < 22; k++) {
                if (k == 15) {
                    uint32_t tie = 0;
#pragma unroll
                    for (int i = 0; i < 7; i++) tie |= ca[i] | cb[i];
                    mbar_wait(bars + ((wq == 0 || wq == 3) ? B_HALO + 2 * w + (wq & 1) : B_RST) * 8, __shfl_sync(~0u, (tie | ca[7]) & p.zero, 0));
                    TS(27);
                }
                const int blk = (1 + k) >> 3;
                const uint32_t g = lds32((gs + (blk == 1 ? 1024 : ((blk == 0) == (mir != 0) ? 2048 : 0)) + lo) ^ (((1 + k) & 7) * 144));
#pragma unroll
                for (int i = 0; i < 8; i++) {
                    const int tap = k - i;
                    if (tap == 0) ca[i] = hmul2(g, dwr[0]);
                    else if (tap > 0 && tap < 8) ca[i] = hfma2(g, dwr[tap], ca[i]);
                    else if (tap == 8) cb[i] = hmul2(g, dwr[8]);
                    else if (tap > 8 && tap < 15) cb[i] = hfma2(g, dwr[tap], cb[i]);
                }
            }
            const uint32_t sown_ = H + tile * HCH;
#pragma unroll
            for (int i = 0; i < 8; i++) {
                const float h0 = blo(ca[i]) + blo(cb[i]), h1 = bhi(ca[i]) + bhi(cb[i]);
                sts32((sown_ + wq * 1024 + lo) ^ (i * 144), pack2(fmaf(h0, tanh_fast(h0), h0), fmaf(h1, tanh_fast(h1), h1)));
            }
            fence_async_smem();
            bar_sync(2 + w, 128);
            if (wq == 0) peer_copy(mapa(sown_, r ^ 1), sown_, HCH, mapa(bars + B_SR * 8, r ^ 1));
            acq(38);
            bar_sync(10, 256);
            TS(19);
            auto frags = [&](int i, int half) {
                const uint32_t src = H + 2 * half * HCH + wq * 1024;
#pragma unroll
                for (int k = 0; k < 4; k++) ldsm4(src + (k >> 1) * HCH + (foff ^ ((k & 1) * 64)), a[i + 4 * k], a[i + 4 * k + 1], a[i + 4 * k + 2], a[i + 4 * k + 3]);
            };
            frags(0, r);
            sp(d0, 38, a, 0, 0);
            acq(39); acq(40);
            mbar_wait(bars + B_SR * 8, 0);
            frags(16, r ^ 1);
            sp(d0, 39, a + 16, 0, 1);
            residual(38);
            TS(20);
            continue;
        }

        {
            TS(11);
            const uint32_t stg = H + warp * 2048;
            unsigned char* g = g_kvq + (size_t)((b * 4 + tile) * 1024 + trow) * 128 + lane * 16;
            auto put = [&](float (&d)[32], int i) {
                pin(d);
                uint32_t pk[8];
#pragma unroll
                for (int j = 0; j < 8; j++) pk[j] = pack2((d[4 * j] + d[4 * j + 2]) * rstd, (d[4 * j + 1] + d[4 * j + 3]) * rstd);
                if (i == 2) {
                    st_data(g + 2097152, pk[0], pk[1], pk[2], pk[3]);
                    st_data(g + 2097152 + 512, pk[4], pk[5], pk[6], pk[7]);
                    return;
                }
                stsm4(stg + i * 1024 + foff, pk[0], pk[1], pk[2], pk[3]);
                stsm4(stg + i * 1024 + (foff ^ 64), pk[4], pk[5], pk[6], pk[7]);
                __syncwarp();
                const uint4 u0 = lds128(stg + i * 1024 + lane * 16), u1 = lds128(stg + i * 1024 + 512 + lane * 16);
                stg128(g + i * 1048576, u0); stg128(g + i * 1048576 + 512, u1);
            };
            sp(d0, 16, a, w, 0);
            acq(17);
            sp(d1, 17, a, w, 0);
            gather_peer();
            acq(18);
            sp(d0, 18, a + 16, 0, 1);
            wg_wait<1>();
            rel(16); rel(17);
            acq(19);
            sp(d1, 19, a + 16, 0, 1);
            wg_wait<1>();
            rel(18);
            put(d0, 0);
            wg_wait<0>();
            rel(19);
            TS(37);
            put(d1, 1);
            bar_arrive(4, 288);
            TS(38);
            acq(20);
            sp(d0, 20, a, w, 0);
            acq(21);
            sp(d0, 21, a + 16, 0, 1);
            acq(22); acq(23);
            rel(22); rel(23);
            mbar_wait(bars + B_RST * 8, 0);
            wg_wait<0>();
            rel(20); rel(21);
            put(d0, 2);
            TS(12);
        }

        {
            constexpr float CS = 0.125f * 1.4426950408889634f;
            float sa[32], sb2[32], o[36];
            uint32_t pa[16], pb[16], q[16];
            float n0 = INFINITY, n1 = INFINITY;
            zero(o); zero(pa); zero(pb); zero(sb2);
            const uint32_t ones = sb + OFF_MISC + 2048;
            { const uint32_t c = w ? 0u : 0x3F803F80u; sts128(ones + tid * 16, c, c, c, c); }
            fence_async_smem();
            bar_sync(10, 256);
            const uint32_t vdesc = rdesc + ((((ones - rbase) >> 4) - 1) << 16);
            auto qk_issue = [&](float (&s)[32], uint32_t lo) {
                const uint64_t kd = mkdesc(lo);
                wg_fence();
#pragma unroll
                for (int k = 0; k < 4; k++) mma_qk(s, q[4 * k], q[4 * k + 1], q[4 * k + 2], q[4 * k + 3], kd + 2 * k, k != 0);
                wg_commit();
            };
            auto both_issue = [&](float (&s)[32], uint32_t klo, uint32_t (&pp)[16], uint32_t vlo) {
                const uint64_t kd = mkdesc(klo), vd = mkdesc(vlo);
                wg_fence();
#pragma unroll
                for (int k = 0; k < 4; k++) {
                    mma_pv(o, pp[4 * k], pp[4 * k + 1], pp[4 * k + 2], pp[4 * k + 3], vd - k * (128 * 65535));
                    mma_qk(s, q[4 * k], q[4 * k + 1], q[4 * k + 2], q[4 * k + 3], kd + 2 * k, k != 0);
                }
                wg_commit();
            };
            auto new_max = [&](float (&s)[32], int nj, float& x0, float& x1) {
                x0 = s[0]; x1 = s[2];
#pragma unroll
                for (int j = 0; j < nj; j++) {
                    x0 = fmaxf(x0, fmaxf(s[4 * j], s[4 * j + 1]));
                    x1 = fmaxf(x1, fmaxf(s[4 * j + 2], s[4 * j + 3]));
                }
                x0 = fmaxf(x0, __shfl_xor_sync(~0u, x0, 1)); x1 = fmaxf(x1, __shfl_xor_sync(~0u, x1, 1));
                x0 = fmaxf(x0, __shfl_xor_sync(~0u, x0, 2)); x1 = fmaxf(x1, __shfl_xor_sync(~0u, x1, 2));
                x0 = fminf(n0, fmaf(x0, -CS, -20.f)); x1 = fminf(n1, fmaf(x1, -CS, -20.f));
            };
            auto probs = [&](float (&s)[32], uint32_t (&pp)[16], bool ready, bool tail, auto wait) {
                uint32_t any = 0;
#pragma unroll
                for (int i = 0; i < 16; i++) {
                    pp[i] = pack2(ex2(fmaf(s[2 * i], CS, (i & 1) ? n1 : n0)), ex2(fmaf(s[2 * i + 1], CS, (i & 1) ? n1 : n0)));
                    any |= pp[i];
                }
                wg_wait<0>();
                pin(sa); pin(sb2); pin(o); pin(pa); pin(pb);
                if (__any_sync(~0u, (any & 0x40004000u) || !ready)) {
                    wait();
                    if (__any_sync(~0u, any & 0x40004000u)) {
                        if (tail) {
#pragma unroll
                            for (int i = 20; i < 32; i++) s[i] = -INFINITY;
                        }
                        float x0, x1;
                        new_max(s, 8, x0, x1);
                        const float sc0 = ex2(x0 - n0), sc1 = ex2(x1 - n1);
                        n0 = x0; n1 = x1;
#pragma unroll
                        for (int j = 0; j < 9; j++) { o[4 * j] *= sc0; o[4 * j + 1] *= sc0; o[4 * j + 2] *= sc1; o[4 * j + 3] *= sc1; }
#pragma unroll
                        for (int i = 0; i < 16; i++)
                            pp[i] = pack2(ex2(fmaf(s[2 * i], CS, (i & 1) ? n1 : n0)), ex2(fmaf(s[2 * i + 1], CS, (i & 1) ? n1 : n0)));
                    }
                }
            };
            {
                uint4 u[4];
                const unsigned char* src = g_kvq + 2097152 + (size_t)(abh * 1024 + qt * 64 + wq * 16) * 128 + lane * 16;
                spin(QGATE);
                ld_data<512>(u, src);
#pragma unroll
                for (int k = 0; k < 2; k++) {
                    q[8 * k] = u[k].x; q[8 * k + 1] = u[k + 2].x; q[8 * k + 2] = u[k].y; q[8 * k + 3] = u[k + 2].y;
                    q[8 * k + 4] = u[k].z; q[8 * k + 5] = u[k + 2].z; q[8 * k + 6] = u[k].w; q[8 * k + 7] = u[k + 2].w;
                }
                pin(q);
            }
            TS(40);
            acq(24);
            TS(13);
            qk_issue(sa, rdesc + (24 % NSLOT) * (SLOT >> 4));
            wg_wait<0>();
            pin(sa);
            {
                float x0, x1;
                new_max(sa, NJ0, x0, x1);
                n0 = x0; n1 = x1;
            }
            bar_arrive(6, 384);
            uint32_t vd = vdesc - (SLOT >> 4) * 65535u, kd = rdesc, vb = fbar + 8, kb = fbar;
            uint32_t vlast = vdesc - 4 * (SLOT >> 4) * 65535u, klast = rdesc + 4 * (SLOT >> 4) + 512;
            uint32_t kprev = fbar + 32, vprev = bars + (B_SINK - (B_EMPTY - B_FULL)) * 8;
#pragma unroll 1
            for (int it = 0; it < 4; it++) {
                both_issue(sb2, klast, pb, vlast);
                probs(sa, pa, mbar_test(vb, it < 2) & mbar_test(kb, it < 3), false, [&]() { mbar_wait(vb, it < 2); mbar_wait(kb, it < 3); });
                TS(41 + it * 4);
                if (lane == 0) mbar_arrive(kprev + (B_EMPTY - B_FULL) * 8);
                if (lane == 0) mbar_arrive(vprev + (B_EMPTY - B_FULL) * 8);
                both_issue(sa, kd, pa, vd);
                const int dv = it == 0 ? 2 : (it == 1 ? -3 : 1);
                kprev = kb; vprev = vb; vlast = vd - 512 * 65535u; klast = kd + 512;
                vd -= dv * (SLOT >> 4) * 65535u; vb += dv * 8;
                kd += (it == 2 ? -3 : 2) * (SLOT >> 4); kb = it == 2 ? vb : kb + 16;
                probs(sb2, pb, true, it == 3 && w == 1, []() {});
                TS(43 + it * 4);
            }
            wg_fence();
#pragma unroll
            for (int k = 0; k < 4; k++)
                mma_pv(o, pb[4 * k], pb[4 * k + 1], pb[4 * k + 2], pb[4 * k + 3], mkdesc(vlast - k * (128 * 65535) + (k > 1 ? w * ((k - 1) << 22) : 0)));
            wg_commit();
            const int row = wq * 16 + (lane >> 2);
            const uint32_t ml = sb + OFF_MISC;
            mbar_wait(bars + (B_RST + 1) * 8, 0);
            wg_wait<0>();
            pin(o); pin(pb); pin(sa); pin(sb2);
            rel(31);
            const float l0 = o[32], l1 = o[34];
            if (c4 == 0) { sts64f(ml + w * 512 + row * 8, n0, l0); sts64f(ml + w * 512 + row * 8 + 64, n1, l1); }
            TS(14);
            float mine[16];
#pragma unroll
            for (int j = 0; j < 4; j++) {
                if (w == 0) sts128f(H + j * 2048 + wt * 16, o[16 + 4 * j], o[17 + 4 * j], o[18 + 4 * j], o[19 + 4 * j]);
                else sts128f(H + 8192 + j * 2048 + wt * 16, o[4 * j], o[4 * j + 1], o[4 * j + 2], o[4 * j + 3]);
            }
#pragma unroll
            for (int i = 0; i < 16; i++) mine[i] = w == 0 ? o[i] : o[16 + i];
            bar_sync(10, 256);
            const float2 u0 = lds64f(ml + (w ^ 1) * 512 + row * 8), u1 = lds64f(ml + (w ^ 1) * 512 + row * 8 + 64);
            const float x0 = fminf(n0, u0.x), x1 = fminf(n1, u1.x);
            float a0 = ex2(x0 - n0), b0 = ex2(x0 - u0.x), a1 = ex2(x1 - n1), b1 = ex2(x1 - u1.x);
            const float i0 = __fdividef(1.f, fmaf(a0, l0, b0 * u0.y)), i1 = __fdividef(1.f, fmaf(a1, l1, b1 * u1.y));
            a0 *= i0; b0 *= i0; a1 *= i1; b1 *= i1;
            uint32_t pk[8];
#pragma unroll
            for (int j = 0; j < 4; j++) {
                const float4 v = lds128f(H + (w ^ 1) * 8192 + j * 2048 + wt * 16);
                pk[2 * j] = pack2(fmaf(a0, mine[4 * j], b0 * v.x), fmaf(a0, mine[4 * j + 1], b0 * v.y));
                pk[2 * j + 1] = pack2(fmaf(a1, mine[4 * j + 2], b1 * v.z), fmaf(a1, mine[4 * j + 3], b1 * v.w));
            }
            unsigned char* dst = g_o + (size_t)(b * 128 + qt * 8 + 2 * wq) * 4096 + ah * 1024 + w * 512 + lane * 16;
            st_data(dst, pk[0], pk[2], pk[4], pk[6]);
            st_data(dst + 4096, pk[1], pk[3], pk[5], pk[7]);
            if (tid == 0) asm volatile("red.relaxed.gpu.global.add.u32 [%0], 1;" ::"l"(&g_epoch[blockIdx.x * FS]) : "memory");
            TS(15);
        }

        {
            acq(32); acq(33); acq(34);
            uint4 u[8];
            ld_data<512>(u, g_o + (size_t)(b * 128 + pt * 4 + wq) * 4096 + lane * 16);
#pragma unroll
            for (int i = 0; i < 8; i++) { a[4 * i] = u[i].x; a[4 * i + 1] = u[i].y; a[4 * i + 2] = u[i].z; a[4 * i + 3] = u[i].w; }
            TS(16);
            sp(d0, 32, a, 0, 0);
            sp(d0, 33, a + 16, 0, 1);
            residual(32);
            TS(17);
        }
    }

    cluster_arrive();
    TS(24);
    {
        const float rstd = rsq(fmaxf(fmaf(-mean, mean, msq), 0.f) + 1e-5f), nb = -mean * rstd;
#pragma unroll
        for (int j = 0; j < 8; j++) xr[j] = pack2(fmaf(v[2 * j], rstd, nb), fmaf(v[2 * j + 1], rstd, nb));
        const uint32_t stg = P + 16384 + warp * 1024;
        stsm4(stg + foff, xr[0], xr[1], xr[2], xr[3]);
        stsm4(stg + (foff ^ 64), xr[4], xr[5], xr[6], xr[7]);
        __syncwarp();
        const uint32_t src = stg + (lane >> 3) * 128 + (((lane & 7) ^ (lane >> 3)) << 4);
        const uint4 u0 = lds128(src), u1 = lds128((src + 512) ^ 64);
        __nv_bfloat16* dst = p.out + (size_t)(b * T_ + trow + (lane >> 3)) * 256 + tile * 64 + (lane & 7) * 8;
        if (trow < T_) { stg128(dst, u0); stg128(dst + 4 * 256, u1); }
    }
    TS(25);
    TG(31);
    TSDUMP();
    cluster_wait();
}

typedef CUresult (*EncodeFn)(CUtensorMap*, CUtensorMapDataType, cuuint32_t, void*, const cuuint64_t*, const cuuint64_t*,
                             const cuuint32_t*, const cuuint32_t*, CUtensorMapInterleave, CUtensorMapSwizzle,
                             CUtensorMapL2promotion, CUtensorMapFloatOOBfill);

}

extern "C" void kernel_launch(void* const* d_in, const int* in_sizes, int n_in, void* d_out, int out_size) {
    static EncodeFn encode = nullptr;
    if (!encode) {
        void* fn = nullptr;
        cudaDriverEntryPointQueryResult qr;
        cudaGetDriverEntryPoint("cuTensorMapEncodeTiled", &fn, cudaEnableDefault, &qr);
        encode = (EncodeFn)fn;
        cudaFuncSetAttribute(conformer_kernel, cudaFuncAttributeMaxDynamicSharedMemorySize, SMEM_LAUNCH);
    }
    Params p;
    const cuuint32_t ones[5] = {1, 1, 1, 1, 1};
    const int idx[8] = {1, 2, 3, 4, 5, 7, 8, 9};
    const int rows[8] = {256, 1024, 256, 256, 256, 256, 256, 1024};
    const int cols[8] = {1024, 256, 768, 256, 512, 256, 1024, 256};
    for (int i = 0; i < 8; i++) {
        const cuuint64_t pitch = (cuuint64_t)cols[i] * 2;
        const cuuint64_t dims[5] = {(cuuint64_t)cols[i], 2, 2, 4, (cuuint64_t)rows[i] / 16};
        const cuuint64_t strides[4] = {pitch, pitch * 8, pitch * 2, pitch * 16};
        const cuuint32_t box[5] = {64, 2, 2, 4, 8};
        encode(&p.tm[i], CU_TENSOR_MAP_DATA_TYPE_BFLOAT16, 5, d_in[idx[i]], dims, strides, box, ones, CU_TENSOR_MAP_INTERLEAVE_NONE,
               CU_TENSOR_MAP_SWIZZLE_128B, CU_TENSOR_MAP_L2_PROMOTION_L2_128B, CU_TENSOR_MAP_FLOAT_OOB_FILL_NONE);
        p.w[i] = (const char*)d_in[idx[i]];
    }
    {
        void* kv = nullptr;
        cudaGetSymbolAddress(&kv, g_kvq);
        const cuuint64_t dims[2] = {64, 16384};
        const cuuint64_t strides[1] = {128};
        const cuuint32_t box[2] = {64, 128};
        encode(&p.tm[8], CU_TENSOR_MAP_DATA_TYPE_BFLOAT16, 2, kv, dims, strides, box, ones, CU_TENSOR_MAP_INTERLEAVE_NONE,
               CU_TENSOR_MAP_SWIZZLE_NONE, CU_TENSOR_MAP_L2_PROMOTION_L2_128B, CU_TENSOR_MAP_FLOAT_OOB_FILL_NONE);
    }
    p.x = (const __nv_bfloat16*)d_in[0];
    p.dw = (const __nv_bfloat16*)d_in[6];
    p.out = (__nv_bfloat16*)d_out;
    p.zero = 0;
    conformer_kernel<<<NCTA, NTHREADS, SMEM_LAUNCH>>>(p);
}
```

```cpp
#include <cuda_runtime.h>
#include <cuda_bf16.h>
#include <cuda.h>
#include <stdint.h>

namespace {

constexpr int T_ = 1000;
constexpr int NCTA = 128;
constexpr int NTHREADS = 512;
constexpr int NSLOT = 5;
constexpr int SLOT = 16384;
constexpr int NLOADS = 56;

constexpr uint32_t OFF_RING = 0;
constexpr uint32_t OFF_P = 163840;
constexpr uint32_t OFF_H = 188416;
constexpr uint32_t OFF_MISC = 221184;
constexpr uint32_t OFF_BARS = 229888;
constexpr uint32_t SMEM_BYTES = 230400;
constexpr uint32_t GCH = 6144;
constexpr uint32_t HCH = 4096;

constexpr int B_FULL = 0, B_EMPTY = 10, B_XA = 20  , B_XB = 25  , B_INB = 29  , B_SR = 33,
              B_RST = 34  , B_RDY = 36  , B_SINK = 42, B_HALO = 43  , NBARS = 47;

#define KD2 300u
#define KD3 500u
#define QGATE 500u
#define BACKOFF 0u
#define KFS 8
#define KDELAY 300u
#define NJ0 2
#define HDELAY 300u
#define TURN 0
#define EAGER 0x4755
constexpr int FS = 8;

struct Params {
    CUtensorMap tm[9];
    const char* w[8];
    const __nv_bfloat16* x;
    const __nv_bfloat16* dw;
    __nv_bfloat16* out;
    uint32_t zero;
};

__device__ __align__(1024) unsigned char g_kvq[3 * 8 * 1024 * 128];
__device__ __align__(1024) unsigned char g_o[2 * 128 * 4096];
__device__ uint4 g_halo[64 * 4 * 2 * 64];
__device__ __align__(128) uint32_t g_flag_kv[8 * 32 * KFS];
__device__ uint32_t g_reset[4 * 32];
__device__ uint32_t g_epoch[NCTA * FS];

#define TS(i) do { } while (0)
#define TSW(i) do { } while (0)
#define TG(i) do { } while (0)
#define TSINIT() do { } while (0)
#define TSDUMP() do { } while (0)
constexpr uint32_t SMEM_LAUNCH = SMEM_BYTES;

__device__ __forceinline__ uint32_t smem_u32(const void* p) { return (uint32_t)__cvta_generic_to_shared(p); }
__device__ __forceinline__ void mbar_init(uint32_t b, uint32_t c) { asm volatile("mbarrier.init.shared::cta.b64 [%0], %1;" ::"r"(b), "r"(c) : "memory"); }
__device__ __forceinline__ void mbar_arrive(uint32_t b) { asm volatile("mbarrier.arrive.shared::cta.b64 _, [%0];" ::"r"(b) : "memory"); }
__device__ __forceinline__ void mbar_arrive_tx(uint32_t b, uint32_t tx) { asm volatile("mbarrier.arrive.expect_tx.shared::cta.b64 _, [%0], %1;" ::"r"(b), "r"(tx) : "memory"); }
__device__ __forceinline__ void mbar_wait(uint32_t b, uint32_t ph) {
    asm volatile("{\n.reg .pred p, q;\n.reg .u32 c;\nmov.u32 c, 0;\n"
                 "MW_LOOP:\n.pragma \"nounroll\";\n"
                 "mbarrier.try_wait.parity.shared::cta.b64 p, [%0], %1;\n"
                 "add.u32 c, c, 1;\nsetp.lt.u32 q, c, 65536;\nnot.pred p, p;\nand.pred p, p, q;\n@p bra MW_LOOP;\n}"
                 ::"r"(b), "r"(ph) : "memory");
}
__device__ __forceinline__ bool mbar_test(uint32_t b, uint32_t ph) {
    uint32_t ok;
    asm volatile("{\n.reg .pred p;\nmbarrier.test_wait.parity.shared::cta.b64 p, [%1], %2;\nselp.u32 %0, 1, 0, p;\n}" : "=r"(ok) : "r"(b), "r"(ph) : "memory");
    return ok;
}
__device__ __forceinline__ uint32_t mapa(uint32_t a, uint32_t r) { uint32_t o; asm("mapa.shared::cluster.u32 %0, %1, %2;" : "=r"(o) : "r"(a), "r"(r)); return o; }
__device__ __forceinline__ void fence_async_smem() { asm volatile("fence.proxy.async.shared::cta;" ::: "memory"); }
__device__ __forceinline__ void fence_async_global() { asm volatile("fence.proxy.async.global;" ::: "memory"); }
__device__ __forceinline__ void bar_sync(int id, int n) { asm volatile("bar.sync %0, %1;" ::"r"(id), "r"(n) : "memory"); }
__device__ __forceinline__ void bar_arrive(int id, int n) { asm volatile("bar.arrive %0, %1;" ::"r"(id), "r"(n) : "memory"); }
__device__ __forceinline__ void cluster_arrive() { asm volatile("barrier.cluster.arrive.relaxed.aligned;" ::: "memory"); }
__device__ __forceinline__ void cluster_wait() { asm volatile("barrier.cluster.wait.aligned;" ::: "memory"); }

__device__ __forceinline__ void ring_load(uint32_t dst, const CUtensorMap* tm, int col, int row16, uint32_t bar) {
    asm volatile("{\n.reg .pred p;\nelect.sync _|p, 0xffffffff;\n"
                 "@p mbarrier.arrive.expect_tx.shared::cta.b64 _, [%2], 16384;\n"
                 "@p cp.async.bulk.tensor.5d.shared::cluster.global.mbarrier::complete_tx::bytes [%0], [%1, {%3, 0, 0, 0, %4}], [%2];\n}"
                 ::"r"(dst), "l"(tm), "r"(bar), "r"(col), "r"(row16) : "memory");
}
__device__ __forceinline__ void ring_load_both(uint32_t dst, const CUtensorMap* tm, int c1, uint32_t bar) {
    asm volatile("{\n.reg .pred p;\nelect.sync _|p, 0xffffffff;\n"
                 "@p cp.async.bulk.tensor.2d.shared::cluster.global.mbarrier::complete_tx::bytes.multicast::cluster [%0], [%1, {0, %3}], [%2], %4;\n}"
                 ::"r"(dst), "l"(tm), "r"(bar), "r"(c1), "h"((uint16_t)3) : "memory");
}
__device__ __forceinline__ void mbar_arrive_peer(uint32_t b) { asm volatile("mbarrier.arrive.relaxed.cluster.shared::cluster.b64 _, [%0];" ::"r"(b) : "memory"); }
__device__ __forceinline__ void prefetch_l2(const void* src, uint32_t bytes) {
    asm volatile("cp.async.bulk.prefetch.L2.global [%0], %1;" ::"l"(src), "r"(bytes) : "memory");
}
__device__ __forceinline__ void peer_copy(uint32_t dst, uint32_t src, uint32_t bytes, uint32_t rbar) {
    asm volatile("{\n.reg .pred p;\nelect.sync _|p, 0xffffffff;\n"
                 "@p cp.async.bulk.shared::cluster.shared::cta.mbarrier::complete_tx::bytes [%0], [%1], %2, [%3];\n}"
                 ::"r"(dst), "r"(src), "r"(bytes), "r"(rbar) : "memory");
}
__device__ __forceinline__ void st_async4(uint32_t dst, uint32_t a, uint32_t b, uint32_t c, uint32_t d, uint32_t bar) {
    asm volatile("st.async.shared::cluster.mbarrier::complete_tx::bytes.v4.b32 [%0], {%1,%2,%3,%4}, [%5];" ::"r"(dst), "r"(a), "r"(b), "r"(c), "r"(d), "r"(bar) : "memory");
}
__device__ __forceinline__ void st_async2f(uint32_t dst, float a, float b, uint32_t bar) {
    asm volatile("st.async.shared::cluster.mbarrier::complete_tx::bytes.v2.f32 [%0], {%1,%2}, [%3];" ::"r"(dst), "f"(a), "f"(b), "r"(bar) : "memory");
}
__device__ __forceinline__ void stsm4(uint32_t a, uint32_t r0, uint32_t r1, uint32_t r2, uint32_t r3) {
    asm volatile("stmatrix.sync.aligned.m8n8.x4.shared.b16 [%0], {%1,%2,%3,%4};" ::"r"(a), "r"(r0), "r"(r1), "r"(r2), "r"(r3) : "memory");
}
__device__ __forceinline__ void ldsm4(uint32_t a, uint32_t& r0, uint32_t& r1, uint32_t& r2, uint32_t& r3) {
    asm volatile("ldmatrix.sync.aligned.m8n8.x4.shared.b16 {%0,%1,%2,%3}, [%4];" : "=r"(r0), "=r"(r1), "=r"(r2), "=r"(r3) : "r"(a) : "memory");
}
__device__ __forceinline__ uint4 lds128(uint32_t a) { uint4 v; asm volatile("ld.shared.v4.b32 {%0,%1,%2,%3}, [%4];" : "=r"(v.x), "=r"(v.y), "=r"(v.z), "=r"(v.w) : "r"(a) : "memory"); return v; }
__device__ __forceinline__ float4 lds128f(uint32_t a) { float4 v; asm volatile("ld.shared.v4.f32 {%0,%1,%2,%3}, [%4];" : "=f"(v.x), "=f"(v.y), "=f"(v.z), "=f"(v.w) : "r"(a) : "memory"); return v; }
__device__ __forceinline__ float2 lds64f(uint32_t a) { float2 v; asm volatile("ld.shared.v2.f32 {%0,%1}, [%2];" : "=f"(v.x), "=f"(v.y) : "r"(a) : "memory"); return v; }
__device__ __forceinline__ uint32_t lds32(uint32_t a) { uint32_t v; asm volatile("ld.shared.b32 %0, [%1];" : "=r"(v) : "r"(a) : "memory"); return v; }
__device__ __forceinline__ void sts128(uint32_t a, uint32_t x, uint32_t y, uint32_t z, uint32_t w) { asm volatile("st.shared.v4.b32 [%0], {%1,%2,%3,%4};" ::"r"(a), "r"(x), "r"(y), "r"(z), "r"(w) : "memory"); }
__device__ __forceinline__ void sts128f(uint32_t a, float x, float y, float z, float w) { asm volatile("st.shared.v4.f32 [%0], {%1,%2,%3,%4};" ::"r"(a), "f"(x), "f"(y), "f"(z), "f"(w) : "memory"); }
__device__ __forceinline__ void sts64f(uint32_t a, float x, float y) { asm volatile("st.shared.v2.f32 [%0], {%1,%2};" ::"r"(a), "f"(x), "f"(y) : "memory"); }
__device__ __forceinline__ void sts32(uint32_t a, uint32_t x) { asm volatile("st.shared.b32 [%0], %1;" ::"r"(a), "r"(x) : "memory"); }
__device__ __forceinline__ void stg128(void* p, uint4 v) { asm volatile("st.global.v4.b32 [%0], {%1,%2,%3,%4};" ::"l"(p), "r"(v.x), "r"(v.y), "r"(v.z), "r"(v.w) : "memory"); }

__device__ __forceinline__ uint32_t pack2(float lo, float hi) { uint32_t r; asm("cvt.rn.bf16x2.f32 %0, %1, %2;" : "=r"(r) : "f"(hi), "f"(lo)); return r; }
__device__ __forceinline__ float blo(uint32_t v) { return __uint_as_float(v << 16); }
__device__ __forceinline__ float bhi(uint32_t v) { return __uint_as_float(v & 0xffff0000u); }
__device__ __forceinline__ uint32_t hmul2(uint32_t a, uint32_t b) { uint32_t r; asm("mul.rn.bf16x2 %0, %1, %2;" : "=r"(r) : "r"(a), "r"(b)); return r; }
__device__ __forceinline__ uint32_t hsub2(uint32_t a, uint32_t b) { uint32_t r; asm("sub.rn.bf16x2 %0, %1, %2;" : "=r"(r) : "r"(a), "r"(b)); return r; }
__device__ __forceinline__ uint32_t hfma2(uint32_t a, uint32_t b, uint32_t c) { uint32_t r; asm("fma.rn.bf16x2 %0, %1, %2, %3;" : "=r"(r) : "r"(a), "r"(b), "r"(c)); return r; }
__device__ __forceinline__ float tanh_fast(float x) { float r; asm("tanh.approx.f32 %0, %1;" : "=f"(r) : "f"(x)); return r; }
__device__ __forceinline__ float rsq(float x) { float r; asm("rsqrt.approx.ftz.f32 %0, %1;" : "=f"(r) : "f"(x)); return r; }
__device__ __forceinline__ float ex2(float x) { float r; asm("ex2.approx.ftz.f32 %0, %1;" : "=f"(r) : "f"(x)); return r; }

__device__ __forceinline__ uint32_t ld_relaxed(const uint32_t* p) {
    uint32_t v;
    asm volatile("ld.relaxed.gpu.global.u32 %0, [%1];" : "=r"(v) : "l"(p) : "memory");
    return v;
}
__device__ __forceinline__ uint32_t clock32() { uint32_t c; asm volatile("mov.u32 %0, %%clock;" : "=r"(c)::"memory"); return c; }
__device__ __forceinline__ void spin(uint32_t clks) {
    const uint32_t t0 = clock32();
    while (clock32() - t0 < clks) {}
}
__device__ __forceinline__ void flag_wait(const uint32_t* p, uint32_t e, bool mine) {
#pragma unroll 1
    for (int i = 0; i < (1 << 19); i++) {
        if (mine) mine = ld_relaxed(p) != e;
        if (!__any_sync(~0u, mine)) break;
        if (BACKOFF) spin(BACKOFF);
    }
    asm volatile("fence.acquire.gpu;" ::: "memory");
    fence_async_global();
}
__device__ __forceinline__ void st_data(void* p, uint32_t x, uint32_t y, uint32_t z, uint32_t w) {
    asm volatile("st.relaxed.gpu.global.v4.b32 [%0], {%1,%2,%3,%4};" ::"l"(p), "r"(x), "r"(y), "r"(z), "r"(w) : "memory");
}
template <int STRIDE, int N>
__device__ __forceinline__ void ld_data(uint4 (&v)[N], const unsigned char* p) {
    int it = 0;
    bool again;
#pragma unroll 1
    do {
        uint32_t m = 0;
#pragma unroll
        for (int i = 0; i < N; i++)
            asm volatile("ld.relaxed.gpu.global.v4.b32 {%0,%1,%2,%3}, [%4];" : "=r"(v[i].x), "=r"(v[i].y), "=r"(v[i].z), "=r"(v[i].w) : "l"(p + i * STRIDE) : "memory");
#pragma unroll
        for (int i = 0; i < N; i++) m = __vimax3_u32(__vimax3_u32(v[i].x, v[i].y, v[i].z), v[i].w, m);
        again = __any_sync(~0u, m == ~0u) && ++it < (1 << 16);
    } while (again);
}
__device__ __forceinline__ uint32_t ld_epoch() { return ld_relaxed(&g_epoch[blockIdx.x * FS]) + 1; }
__device__ __forceinline__ void flag_set(uint32_t* p, uint32_t e) { asm volatile("st.release.gpu.global.u32 [%0], %1;" ::"l"(p), "r"(e) : "memory"); }

__device__ __forceinline__ uint32_t desc_lo(uint32_t addr) { return ((addr & 0x3FFFF) >> 4) | 0x10000u; }
__device__ __forceinline__ uint64_t mkdesc(uint32_t lo) { return (uint64_t)lo | (0x40000040ull << 32); }
__device__ __forceinline__ void wg_fence() { asm volatile("wgmma.fence.sync.aligned;" ::: "memory"); }
__device__ __forceinline__ void wg_commit() { asm volatile("wgmma.commit_group.sync.aligned;" ::: "memory"); }
template <int N> __device__ __forceinline__ void wg_wait() { asm volatile("wgmma.wait_group.sync.aligned %0;" ::"n"(N) : "memory"); }
template <int N> __device__ __forceinline__ void pin(float (&d)[N]) {
#pragma unroll
    for (int i = 0; i < N; i++) asm volatile("" : "+f"(d[i])::"memory");
}
template <int N> __device__ __forceinline__ void pin(uint32_t (&d)[N]) {
#pragma unroll
    for (int i = 0; i < N; i++) asm volatile("" : "+r"(d[i])::"memory");
}

template <typename Tp, int N> __device__ __forceinline__ void zero(Tp (&d)[N]) {
#pragma unroll
    for (int i = 0; i < N; i++) d[i] = 0;
    pin(d);
}

#define F4(d, i) "+f"(d[i]), "+f"(d[i + 1]), "+f"(d[i + 2]), "+f"(d[i + 3])
#define F16(d, i) F4(d, i), F4(d, i + 4), F4(d, i + 8), F4(d, i + 12)

__device__ __forceinline__ void mma_sp(float (&d)[32], const uint32_t* a, uint64_t b, uint32_t meta, int acc) {
    asm volatile("{.reg .pred p; setp.ne.b32 p, %38, 0;\n"
                 "wgmma.mma_async.sp.sync.aligned.m64n64k32.f32.bf16.bf16 {%0,%1,%2,%3,%4,%5,%6,%7,%8,%9,%10,%11,%12,%13,%14,%15,%16,%17,%18,%19,%20,%21,%22,%23,%24,%25,%26,%27,%28,%29,%30,%31}, "
                 "{%32,%33,%34,%35}, %36, %37, 0, p, 1, 1, 1;}\n"
                 : F16(d, 0), F16(d, 16) : "r"(a[0]), "r"(a[1]), "r"(a[2]), "r"(a[3]), "l"(b), "r"(meta), "r"(acc));
}
__device__ __forceinline__ void mma_qk(float (&d)[32], uint32_t a0, uint32_t a1, uint32_t a2, uint32_t a3, uint64_t b, int acc) {
    asm volatile("{.reg .pred p; setp.ne.b32 p, %37, 0;\n"
                 "wgmma.mma_async.sync.aligned.m64n64k16.f32.bf16.bf16 {%0,%1,%2,%3,%4,%5,%6,%7,%8,%9,%10,%11,%12,%13,%14,%15,%16,%17,%18,%19,%20,%21,%22,%23,%24,%25,%26,%27,%28,%29,%30,%31}, "
                 "{%32,%33,%34,%35}, %36, p, 1, 1, 0;}\n"
                 : F16(d, 0), F16(d, 16) : "r"(a0), "r"(a1), "r"(a2), "r"(a3), "l"(b), "r"(acc));
}
__device__ __forceinline__ void mma_pv(float (&d)[36], uint32_t a0, uint32_t a1, uint32_t a2, uint32_t a3, uint64_t b) {
    asm volatile("wgmma.mma_async.sync.aligned.m64n72k16.f32.bf16.bf16 {%0,%1,%2,%3,%4,%5,%6,%7,%8,%9,%10,%11,%12,%13,%14,%15,%16,%17,%18,%19,%20,%21,%22,%23,%24,%25,%26,%27,%28,%29,%30,%31,%32,%33,%34,%35}, "
                 "{%36,%37,%38,%39}, %40, 1, 1, 1, 1;\n"
                 : F16(d, 0), F16(d, 16), F4(d, 32) : "r"(a0), "r"(a1), "r"(a2), "r"(a3), "l"(b));
}

__device__ __forceinline__ uint32_t load_code(int n, int r, int w) {
    const int tile = 2 * r + w;
    int m, col, row;
    if (n < 16 || n >= 40) {
        const int k = n < 16 ? n : n - 40;
        m = n < 16 ? 0 : 6;
        if (k < 8) { col = 4 * tile + (k >> 1); row = (k & 1) ^ r; }
        else { m++; col = tile ^ (3 - ((k - 8) >> 1)); row = 2 * tile + (k & 1); }
    } else if (n < 32) {
        const int k = n - 16;
        m = 2;
        if (k < 4) { col = tile + ((k & 1) ? 8 : 4); row = (k >> 1) ^ r; }
        else { col = tile; row = (k & 1) ^ r; }
    } else if (n < 34) { m = 3; col = tile; row = n - 32; }
    else if (n < 38) { const int k = n - 34; m = 4; col = tile + 4 * (k & 1); row = (k >> 1) ^ r; }
    else { m = 5; col = tile; row = (n & 1) ^ r; }
    return m | (col << 4) | (row << 8);
}

__global__ void __cluster_dims__(2, 1, 1) __launch_bounds__(NTHREADS, 1)
conformer_kernel(const __grid_constant__ Params p) {
    extern __shared__ __align__(1024) unsigned char smem_raw[];
    const uint32_t sb = smem_u32(smem_raw);
    const uint32_t bars = sb + OFF_BARS;
    const int tid = threadIdx.x;
    const int lane = tid & 31;
    const int warp = __shfl_sync(~0u, tid >> 5, 0);
    const int r = blockIdx.x & 1;
    const int pair = blockIdx.x >> 1;
    const int b = pair >> 5, pt = pair & 31;
    const int ah = pt >> 3, qt = (pt & 7) * 2 + r;
    const int abh = b * 4 + ah;

    TG(30);
    TSINIT();
    TS(0);
    const uint32_t P = sb + OFF_P, H = sb + OFF_H;

    if (warp >= 8) {
        asm volatile("setmaxnreg.dec.sync.aligned.u32 48;");
        if (warp >= 12) {
            cluster_arrive();
            cluster_wait();
            const int ut = tid & 127;
            const uint32_t target = ld_epoch() * 64;
            auto reset_done = [&](int k) {
                bar_sync(11, 128);
                if (ut == 0) {
                    asm volatile("red.release.gpu.global.add.u32 [%0], 1;" ::"l"(&g_reset[(2 * b + k) * 32]) : "memory");
#pragma unroll 1
                    for (int i = 0; i < (1 << 20) && ld_relaxed(&g_reset[(2 * b + k) * 32]) != target; i++) __nanosleep(100);
                    asm volatile("fence.acquire.gpu;" ::: "memory");
                    mbar_arrive(bars + (B_RST + k) * 8);
                }
                __syncwarp();
                TS(13 + k);
            };
#pragma unroll
            for (int i = 0; i < 4; i++)
                st_data(g_kvq + 2097152 + (size_t)((b * 4 + 2 * r + (i >> 1)) * 1024 + pt * 32) * 128 + (i & 1) * 2048 + ut * 16, ~0u, ~0u, ~0u, ~0u);
            reset_done(0);
            bar_sync(6, 384);
#pragma unroll
            for (int i = 0; i < 4; i++) {
                st_data(g_o + (size_t)(b * 128 + qt * 8 + 2 * i + (ut >> 6)) * 4096 + ah * 1024 + (ut & 63) * 16, ~0u, ~0u, ~0u, ~0u);
                if (i < 2) st_data(&g_halo[(pair * 4 + 2 * r + i) * 128 + ut], ~0u, ~0u, ~0u, ~0u);
            }
            reset_done(1);
            const int side = warp & 1, wg = (warp >> 1) & 1, np = side ? pt + 1 : pt - 1;
            const unsigned char* src = reinterpret_cast<const unsigned char*>(&g_halo[(((b * 32 + np) * 4 + 2 * r + wg) * 2 + (side ^ 1)) * 64 + lane]);
            const uint32_t dst = H + 16384 + wg * GCH + side * 5120 + (lane & 7) * 128 + (((lane >> 3) ^ (lane & 7)) << 4);
            uint4 hv[2] = {make_uint4(0, 0, 0, 0), make_uint4(0, 0, 0, 0)};
            bar_sync(8 + wg, 192);
            if (np >= 0 && np < 32) {
                spin(HDELAY);
                ld_data<512>(hv, src);
            }
            stsm4(dst, hv[0].x, hv[0].y, hv[0].z, hv[0].w);
            stsm4(dst ^ 64, hv[1].x, hv[1].y, hv[1].z, hv[1].w);
            __syncwarp();
            if (lane == 0) mbar_arrive(bars + (B_HALO + (warp & 3)) * 8);
            TS(4);
        } else if (warp < 10) {
            const int w = warp - 8;
            const uint32_t ring = sb + OFF_RING + w * NSLOT * SLOT;
            const uint32_t full = bars + (B_FULL + w * NSLOT) * 8;
            if (lane == 0) {
#pragma unroll
                for (int i = 0; i < NSLOT; i++) { mbar_init(full + i * 8, 1); mbar_init(full + (B_EMPTY - B_FULL + i) * 8, 4); }
                asm volatile("fence.mbarrier_init.release.cluster;" ::: "memory");
                fence_async_smem();
            }
            __syncwarp();
            cluster_arrive();
            TS(1);
#pragma unroll
            for (int n = 0; n < NSLOT; n++) {
                if (n == 1 || n == 2) bar_sync(12, 64);
                ring_load(ring + n * SLOT, &p.tm[0], 64 * (8 * r + 4 * w + (n >> 1)), 8 * ((n & 1) ^ r), full + n * 8);
            }
            TS(2);
            const uint32_t code = load_code(lane, r, w) | (load_code(lane + 32, r, w) << 16);
            cluster_wait();
            uint32_t s = 0, ph = 0;
            int n = NSLOT;
#pragma unroll 1
            for (int seg = 0; seg < 2; seg++) {
#pragma unroll 1
                for (; n < (seg == 0 ? 22 : NLOADS); n++) {
                    const uint32_t c = __shfl_sync(~0u, code, n) >> (n & 32 ? 16 : 0);
                    const CUtensorMap* tm = &p.tm[c & 15];
                    const uint32_t col = (c & 0xf0) * 4, row = (c & 0xff00) >> 5, dst = ring + s * SLOT;
                    mbar_wait(full + (B_EMPTY - B_FULL) * 8 + s * 8, ph + (((uint32_t)(size_t)tm | col | row | dst) & p.zero));
                    ring_load(dst, tm, col, row, full + s * 8);
                    if (++s == NSLOT) { s = 0; ph ^= 1; }
                }
                if (seg == 1) break;
                const uint32_t epoch = ld_epoch();
                const uint32_t rdy = bars + (B_RDY + 3 * w) * 8, prdy = mapa(rdy, r ^ 1);
                const int odd = r ^ w;
                const uint32_t* flags = g_flag_kv + (abh * 32 + lane) * KFS;
                auto kv_load = [&](uint32_t sl, int isv, int i) {
                    ring_load_both(ring + sl * SLOT, &p.tm[8], (isv * 64 + abh * 8 + 2 * i + w) * 128, full + sl * 8);
                };
#pragma unroll 1
                for (int i = 0; i < 2; i++) {
                    if (lane < 3 + i) {
                        const uint32_t sl = i ? lane : lane + 2;
                        mbar_wait(full + (B_EMPTY - B_FULL + sl) * 8, i ^ 1);
                        mbar_arrive_tx(full + sl * 8, (i || lane == 2) ? SLOT : 0);
                    }
                    __syncwarp();
                }
                if (lane == 0) mbar_arrive_peer(prdy);
                bar_sync(14, 96);
                spin(KDELAY);
                mbar_wait(rdy, 0);
                flag_wait(flags, epoch, (lane >> 2) == 2 * odd + w);
                TSW(5 + 2 * odd);
                if (!odd) { kv_load(4, 0, 0); bar_arrive(12, 64); }
                else bar_sync(12, 64);
                spin(w ? KD3 : KD2);
                kv_load(odd ^ 1, odd ^ 1, odd);
                flag_wait(flags, epoch, (lane >> 2) == 2 * odd + w + 4);
                mbar_wait(full + (odd ^ 1) * 8, 1);
                kv_load(2 + odd, odd, 2 - odd);
#pragma unroll 1
                for (int i = 0; i < 3; i++) {
                    const uint32_t sl = i ? i - 1 : 4, bo = i == 2 ? 16 : 8;
                    mbar_wait(full + (B_EMPTY - B_FULL + sl) * 8, i != 0);
                    if (lane == 0) mbar_arrive_tx(full + sl * 8, SLOT);
                    if ((i & 1) != odd) {
                        mbar_wait(rdy + bo, 0);
                        kv_load(sl, i != 0, 2 + odd);
                    } else if (lane == 0) mbar_arrive_peer(prdy + bo);
                    __syncwarp();
                }
                n = 32; s = 2; ph = 1;
            }
        } else if (warp == 10) {
            if (lane == 0) {
#pragma unroll
                for (int i = B_XA; i < NBARS; i++) mbar_init(bars + i * 8, 1);
#pragma unroll
                for (int i = B_XA; i <= B_SR; i++) mbar_arrive_tx(bars + i * 8, i < B_XB ? 512 : 8192);
                asm volatile("fence.mbarrier_init.release.cluster;" ::: "memory");
                fence_async_smem();
            }
            __syncwarp();
            cluster_arrive();
            cluster_wait();
        } else {
            const uint32_t kb = (lane < 2 || lane > 5) ? 4096 : (lane == 2 ? 3072 : (lane == 4 ? 2048 : 1024));
            const char* pf = p.w[lane & 7] + blockIdx.x * kb;
            cluster_arrive();
            cluster_wait();
            if (lane < 2) prefetch_l2(pf, kb);
            mbar_wait(bars + B_XA * 8, 0);
            if (lane == 2) prefetch_l2(pf, kb);
            if (lane >= 1 && lane < 9) asm volatile("prefetch.tensormap [%0];" ::"l"(&p.tm[lane]) : "memory");
            mbar_wait(bars + (B_FULL + 1) * 8, 1);
            if (lane > 2 && lane < 8) prefetch_l2(pf, kb);
            if (lane == 8 && blockIdx.x < 15) prefetch_l2(p.dw + blockIdx.x * 256, 512);
            const uint32_t epoch = ld_epoch();
            bar_sync(4, 288);
            if (lane < 16) flag_set(&g_flag_kv[((b * 4 + 2 * r + (lane >> 3)) * 32 + pt) * KFS + (lane & 7)], epoch);
            __syncwarp();
            bar_arrive(14, 96);
            TSW(8);
        }
        TSDUMP();
        return;
    }

    const int w = warp >> 2, wq = warp & 3;
    const int tile = 2 * r + w;
    const int wt = tid & 127;
    const int c4 = lane & 3;
    const int trow = pt * 32 + 8 * wq;
    uint32_t xr[8];
    {
        const uint32_t* xp = reinterpret_cast<const uint32_t*>(p.x + (size_t)(b * T_ + trow + (lane >> 2)) * 256 + tile * 64) + c4;
#pragma unroll
        for (int j = 0; j < 8; j++) xr[j] = trow < T_ ? __ldg(xp + 4 * j) : 0u;
    }
    cluster_arrive();
    asm volatile("setmaxnreg.inc.sync.aligned.u32 208;");
    const uint32_t rbase = sb + OFF_RING + w * NSLOT * SLOT, fbar = bars + (B_FULL + w * NSLOT) * 8;
    const uint32_t rdesc = desc_lo(rbase);
    auto acq = [&](int n) { mbar_wait(fbar + (n % NSLOT) * 8, (n / NSLOT) & 1); };
    auto rel = [&](int n) { if (lane == 0) mbar_arrive(fbar + (B_EMPTY - B_FULL + n % NSLOT) * 8); };
    const uint32_t foff = (lane & 7) * 128 + (((lane >> 3) ^ (lane & 7)) << 4);
    float v[16];
#pragma unroll
    for (int j = 0; j < 8; j++) { v[2 * j] = blo(xr[j]); v[2 * j + 1] = bhi(xr[j]); }
    const uint32_t xown = __shfl_sync(~0u, P + wt * 16 + tile * 4096, lane), xrem = __shfl_sync(~0u, P + wt * 16 + (r ^ 1) * 8192, lane);
    const uint32_t sbuf = __shfl_sync(~0u, sb + OFF_MISC + 1024 + (8 * wq + (lane >> 2)) * 32, lane);
    const uint32_t sown = __shfl_sync(~0u, sbuf + tile * 8, lane);
    const uint32_t peer = __shfl_sync(~0u, mapa(sb, r ^ 1) - sb, lane);
    const uint32_t meta = __shfl_sync(~0u, 0xEEEE4444u + p.zero, lane);
    cluster_wait();
    TS(56);
    float mean, msq;

#pragma unroll 1
    for (int ph = 0;; ph++) {
        uint4 o0, o1;
        {
            float s = 0.f, q = 0.f, s2 = 0.f, q2 = 0.f;
#pragma unroll
            for (int j = 0; j < 4; j++) {
                s += v[4 * j] + v[4 * j + 1]; s2 += v[4 * j + 2] + v[4 * j + 3];
                q += fmaf(v[4 * j], v[4 * j], v[4 * j + 1] * v[4 * j + 1]); q2 += fmaf(v[4 * j + 2], v[4 * j + 2], v[4 * j + 3] * v[4 * j + 3]);
            }
            s += s2; q += q2;
            const uint32_t xa = bars + (B_XA + ph) * 8;
            s += __shfl_xor_sync(~0u, s, 1); q += __shfl_xor_sync(~0u, q, 1);
            s += __shfl_xor_sync(~0u, s, 2); q += __shfl_xor_sync(~0u, q, 2);
            if (c4 == 0) st_async2f(sown + peer, s, q, xa + peer);
            if (c4 == 0) sts64f(sown, s, q);
#pragma unroll
            for (int j = 0; j < 8; j++) xr[j] = pack2(v[2 * j], v[2 * j + 1]);
            sts128(xown, xr[0], xr[1], xr[2], xr[3]);
            sts128(xown + 2048, xr[4], xr[5], xr[6], xr[7]);
            bar_sync(10, 256);
            o0 = lds128(xown ^ 4096); o1 = lds128((xown ^ 4096) + 2048);
            if (ph < 4) {
                st_async4(xown + peer, xr[0], xr[1], xr[2], xr[3], xa + (B_XB - B_XA) * 8 + peer);
                st_async4(xown + peer + 2048, xr[4], xr[5], xr[6], xr[7], xa + (B_XB - B_XA) * 8 + peer);
            }
            TS(57 + ph);
            if (ph == 0) acq(0);
            mbar_wait(xa, 0);
            const float4 u0 = lds128f(sbuf), u1 = lds128f(sbuf + 16);
            mean = ((u0.x + u0.z) + (u1.x + u1.z)) * (1.f / 256.f);
            msq = ((u0.y + u0.w) + (u1.y + u1.w)) * (1.f / 256.f);
        }
        if (ph == 4) break;
        uint32_t a[32];
        const uint32_t mean2 = pack2(mean, mean);
        auto centre = [&](int i, const uint4& u) {
            a[i] = hsub2(u.x, mean2); a[i + 1] = hsub2(u.y, mean2); a[i + 2] = hsub2(u.z, mean2); a[i + 3] = hsub2(u.w, mean2);
        };
#pragma unroll
        for (int j = 0; j < 8; j++) a[j] = hsub2(xr[j], mean2);
        centre(8, o0); centre(12, o1);
        const float rstd = rsq(fmaxf(fmaf(-mean, mean, msq), 0.f) + 1e-5f);
        auto gather_peer = [&]() {
            mbar_wait(bars + (B_XB + ph) * 8, 0);
#pragma unroll
            for (int i = 0; i < 4; i++) centre(16 + 4 * i, lds128(xrem + i * 2048));
        };
        auto sp = [&](float (&d)[32], int n, const uint32_t* af, int flip, int acc) {
            const uint32_t lo = rdesc + p.zero * (ph + n + 1) + (n % NSLOT) * (SLOT >> 4);
            const uint64_t b0 = mkdesc(lo + flip * 512), b1 = mkdesc(lo + (flip ^ 1) * 512);
            wg_fence();
            mma_sp(d, af, b0, meta, acc);
            mma_sp(d, af + 4, b0 + 256, meta, 1);
            mma_sp(d, af + 8, b1, meta, 1);
            mma_sp(d, af + 12, b1 + 256, meta, 1);
            wg_commit();
        };
        float d0[32], d1[32];

        if (ph == 0 || ph == 3) {
            uint32_t h[32];
            const float rs = 0.5f * rstd;
            const uint32_t inb = bars + (B_INB + (ph & 2)) * 8, box = H + wt * 16;
            bool ready = true;
            auto step = [&](float (&d)[32], int n, const uint32_t* af, int flip, int acc, auto work) {
                if (!ready) acq(n);
                if (((TURN >> n) & 1) && w == 1) bar_sync(7, 256);
                sp(d, n, af, flip, acc);
                if (n > 0 && ((TURN >> (n - 1)) & 1) && w == 0) bar_arrive(7, 256);
                if (n < 15) ready = mbar_test(fbar + ((n + 1) % NSLOT) * 8, ((n + 1) / NSLOT) & 1);
                wg_wait<1>();
                if (n > 0 && !((EAGER >> (n - 1)) & 1)) rel(n - 1);
                const uint32_t tie = work() & p.zero;
                if ((EAGER >> n) & 1) {
                    if (p.zero < n + ph + 1) wg_wait<0>();
                    if (lane == 0) mbar_arrive(fbar + (B_EMPTY - B_FULL + n % NSLOT) * 8 + tie);
                }
            };
            auto none = []() { return 0u; };
            auto act = [&](float (&d)[32], int i) {
                pin(d);
#pragma unroll
                for (int j = 0; j < 8; j++) {
                    const float u0 = (d[4 * j] + d[4 * j + 2]) * rs, u1 = (d[4 * j + 1] + d[4 * j + 3]) * rs;
                    h[8 * i + j] = pack2(fmaf(u0, tanh_fast(u0), u0), fmaf(u1, tanh_fast(u1), u1));
                }
                return h[8 * i] | h[8 * i + 1] | h[8 * i + 2] | h[8 * i + 3] | h[8 * i + 4] | h[8 * i + 5] | h[8 * i + 6] | h[8 * i + 7];
            };
            auto send = [&](float (&d)[32], int x) {
                pin(d);
                uint32_t pk[8];
#pragma unroll
                for (int j = 0; j < 8; j++) pk[j] = pack2(d[4 * j] + d[4 * j + 2], d[4 * j + 1] + d[4 * j + 3]);
                const uint32_t ow = w ^ (x & 1), dst = box + (ow * 3 + x - 1) * 4096;
                if (x & 2) {
                    st_async4(dst + peer, pk[0], pk[1], pk[2], pk[3], inb + ow * 8 + peer);
                    st_async4(dst + peer + 2048, pk[4], pk[5], pk[6], pk[7], inb + ow * 8 + peer);
                } else {
                    sts128(dst, pk[0], pk[1], pk[2], pk[3]);
                    sts128(dst + 2048, pk[4], pk[5], pk[6], pk[7]);
                }
            };
            TS(1 + (ph & 2) * 10);
            step(d0, 0, a, w, 0, [&]() { gather_peer(); return 0u; });
            TS(32);
            step(d0, 1, a + 16, 0, 1, none);
            step(d1, 2, a, w, 0, [&]() { return act(d0, 0); });
            step(d1, 3, a + 16, 0, 1, none);
            step(d0, 4, a, w, 0, [&]() { return act(d1, 1); });
            TS(33);
            step(d0, 5, a + 16, 0, 1, none);
            step(d1, 6, a, w, 0, [&]() { return act(d0, 2); });
            step(d1, 7, a + 16, 0, 1, none);
            step(d0, 8, h, 0, 0, [&]() { return act(d1, 3); });
            TS(2 + (ph & 2) * 10);
            step(d0, 9, h + 16, 0, 1, none);
            step(d1, 10, h, 0, 0, [&]() { send(d0, 3); return 0u; });
            step(d1, 11, h + 16, 0, 1, none);
            step(d0, 12, h, 0, 0, [&]() { send(d1, 2); return 0u; });
            TS(34);
            step(d0, 13, h + 16, 0, 1, none);
            uint4 u[6];
            step(d1, 14, h, 0, 0, [&]() {
                send(d0, 1);
                mbar_wait(inb + w * 8, 0);
                bar_sync(10, 256);
#pragma unroll
                for (int i = 0; i < 6; i++) u[i] = lds128(box + w * 12288 + i * 2048);
                return u[0].x | u[1].x | u[2].x | u[3].x | u[4].x | u[5].x;
            });
            step(d1, 15, h + 16, 0, 1, none);
            mbar_wait(ph == 0 ? fbar + (16 % NSLOT) * 8 : inb + w * 8, ph == 0);
            uint32_t tie = 0;
#pragma unroll
            for (int i = 0; i < 2; i++) {
                const uint32_t p0[4] = {u[i].x, u[i].y, u[i].z, u[i].w}, p1[4] = {u[i + 2].x, u[i + 2].y, u[i + 2].z, u[i + 2].w}, p2[4] = {u[i + 4].x, u[i + 4].y, u[i + 4].z, u[i + 4].w};
#pragma unroll
                for (int j = 0; j < 4; j++) {
                    v[8 * i + 2 * j] = fmaf(0.5f, blo(p0[j]) + blo(p1[j]) + blo(p2[j]), blo(xr[4 * i + j]));
                    v[8 * i + 2 * j + 1] = fmaf(0.5f, bhi(p0[j]) + bhi(p1[j]) + bhi(p2[j]), bhi(xr[4 * i + j]));
                    tie |= __float_as_uint(v[8 * i + 2 * j]) | __float_as_uint(v[8 * i + 2 * j + 1]);
                }
            }
            if (__any_sync(~0u, tie & p.zero)) spin(1);
            wg_wait<0>();
            pin(d1);
            rel(15);
            TS(3 + (ph & 2) * 10);
#pragma unroll
            for (int j = 0; j < 8; j++) {
                v[2 * j] = fmaf(0.5f, d1[4 * j] + d1[4 * j + 2], v[2 * j]);
                v[2 * j + 1] = fmaf(0.5f, d1[4 * j + 1] + d1[4 * j + 3], v[2 * j + 1]);
            }
            continue;
        }

        auto residual = [&](int n) {
            wg_wait<1>();
            rel(n);
            wg_wait<0>();
            pin(d0);
            rel(n + 1);
#pragma unroll
            for (int j = 0; j < 8; j++) {
                v[2 * j] = d0[4 * j] + d0[4 * j + 2] + blo(xr[j]);
                v[2 * j + 1] = d0[4 * j + 1] + d0[4 * j + 3] + bhi(xr[j]);
            }
        };

        if (ph == 2) {
            TS(39);
            sp(d0, 34, a, w, 0);
            acq(35);
            sp(d1, 35, a, w, 0);
            acq(36); acq(37);
            gather_peer();
            sp(d0, 36, a + 16, 0, 1);
            sp(d1, 37, a + 16, 0, 1);
            wg_wait<2>();
            rel(34); rel(35);
            const int mir = wq < 2 ? 7 : 0;
            uint32_t dwr[15];
            {
                const uint32_t* dp = reinterpret_cast<const uint32_t*>(p.dw + tile * 64) + lane;
#pragma unroll
                for (int i = 0; i < 15; i++) dwr[i] = __ldg(dp + i * 128);
            }
            const float rs = trow < T_ ? 0.5f * rstd : 0.f;
            wg_wait<0>();
            pin(d0); pin(d1);
            rel(36); rel(37);
            TS(18);
            uint32_t pk[8];
#pragma unroll
            for (int j = 0; j < 8; j++) {
                const float u0 = (d0[4 * j] + d0[4 * j + 2]) * rs, u1 = (d0[4 * j + 1] + d0[4 * j + 3]) * rs;
                const float t0 = tanh_fast((d1[4 * j] + d1[4 * j + 2]) * rs), t1 = tanh_fast((d1[4 * j + 1] + d1[4 * j + 3]) * rs);
                pk[j] = pack2(fmaf(u0, t0, u0), fmaf(u1, t1, u1));
            }
            if (wq == 0 || wq == 3) {
                uint4* hp = &g_halo[((pair * 4 + tile) * 2 + (wq & 1)) * 64 + lane];
                st_data(hp, pk[0], pk[1], pk[2], pk[3]);
                st_data(hp + 32, pk[4], pk[5], pk[6], pk[7]);
            }
            const uint32_t gs = H + 16384 + w * GCH + wq * 1024;
            stsm4(gs + 1024 + foff, pk[0], pk[1], pk[2], pk[3]);
            stsm4(gs + 1024 + (foff ^ 64), pk[4], pk[5], pk[6], pk[7]);
            bar_sync(8 + w, 192);
            TS(26);
#pragma unroll
            for (int i = 0; i < 7; i++) {
                const uint32_t x = dwr[i], y = dwr[14 - i];
                dwr[i] = hmul2(mir ? y : x, 0x3F003F00u); dwr[14 - i] = hmul2(mir ? x : y, 0x3F003F00u);
            }
            dwr[7] = hmul2(dwr[7], 0x3F003F00u);
            uint32_t ca[8], cb[8];
            const int e = (wq & 1) * 4;
            const uint32_t lo = ((mir ^ e) * 144) ^ (lane * 4);
            const int dir = mir ? -1024 : 1024;
            const uint32_t gb = H + 16384 + w * GCH + (mir ? 3072 : 2048) + lo, sown_ = H + tile * HCH, so = sown_ + (mir ? 1024 : 2048) + lo;
            auto finish = [&](int i) {
                const float h0 = blo(ca[i]) + blo(cb[i]), h1 = bhi(ca[i]) + bhi(cb[i]);
                sts32((so + (i >> 2) * dir) ^ ((i & 3) * 144), pack2(fmaf(h0, tanh_fast(h0), h0), fmaf(h1, tanh_fast(h1), h1)));
            };
#pragma unroll
            for (int k = 0; k < 26; k++) {
                if (k == 19) {
#pragma unroll
                    for (int i = 0; i < 4; i++) finish(i);
                    const uint32_t tie = ca[4] | ca[5] | ca[6] | ca[7] | cb[4] | cb[5] | cb[6];
                    mbar_wait(bars + (B_HALO + 2 * w + (wq >> 1)) * 8, __shfl_sync(~0u, tie & p.zero, 0));
                    TS(27);
                }
                const uint32_t g = lds32((gb + (((k + 1) & 4) ? ((k + 1) >> 3) + (wq & 1) : ((k + 1) >> 3)) * dir) ^ (((k + 1) & 7) * 144));
#pragma unroll
                for (int i = 0; i < 8; i++) {
                    const int tap = k - (i & 3) - 2 * (i & 4);
                    if (tap == 0) ca[i] = hmul2(g, dwr[0]);
                    else if (tap > 0 && tap < 8) ca[i] = hfma2(g, dwr[tap], ca[i]);
                    else if (tap == 8) cb[i] = hmul2(g, dwr[8]);
                    else if (tap > 8 && tap < 15) cb[i] = hfma2(g, dwr[tap], cb[i]);
                }
            }
#pragma unroll
            for (int i = 4; i < 8; i++) finish(i);
            fence_async_smem();
            bar_sync(2 + w, 128);
            if (wq == 0) peer_copy(mapa(sown_, r ^ 1), sown_, HCH, mapa(bars + B_SR * 8, r ^ 1));
            acq(38);
            bar_sync(10, 256);
            TS(19);
            auto frags = [&](int i, int half) {
                const uint32_t src = H + 2 * half * HCH + wq * 1024;
#pragma unroll
                for (int k = 0; k < 4; k++) ldsm4(src + (k >> 1) * HCH + (foff ^ ((k & 1) * 64)), a[i + 4 * k], a[i + 4 * k + 1], a[i + 4 * k + 2], a[i + 4 * k + 3]);
            };
            frags(0, r);
            sp(d0, 38, a, 0, 0);
            acq(39); acq(40);
            mbar_wait(bars + B_SR * 8, 0);
            frags(16, r ^ 1);
            sp(d0, 39, a + 16, 0, 1);
            residual(38);
            TS(20);
            continue;
        }

        {
            TS(11);
            const uint32_t stg = H + warp * 2048;
            unsigned char* g = g_kvq + (size_t)((b * 4 + tile) * 1024 + trow) * 128 + lane * 16;
            auto put = [&](float (&d)[32], int i) {
                pin(d);
                uint32_t pk[8];
#pragma unroll
                for (int j = 0; j < 8; j++) pk[j] = pack2((d[4 * j] + d[4 * j + 2]) * rstd, (d[4 * j + 1] + d[4 * j + 3]) * rstd);
                if (i == 2) {
                    st_data(g + 2097152, pk[0], pk[1], pk[2], pk[3]);
                    st_data(g + 2097152 + 512, pk[4], pk[5], pk[6], pk[7]);
                    return;
                }
                stsm4(stg + i * 1024 + foff, pk[0], pk[1], pk[2], pk[3]);
                stsm4(stg + i * 1024 + (foff ^ 64), pk[4], pk[5], pk[6], pk[7]);
                __syncwarp();
                const uint4 u0 = lds128(stg + i * 1024 + lane * 16), u1 = lds128(stg + i * 1024 + 512 + lane * 16);
                stg128(g + i * 1048576, u0); stg128(g + i * 1048576 + 512, u1);
            };
            sp(d0, 16, a, w, 0);
            acq(17);
            sp(d1, 17, a, w, 0);
            gather_peer();
            acq(18);
            sp(d0, 18, a + 16, 0, 1);
            wg_wait<1>();
            rel(16); rel(17);
            acq(19);
            sp(d1, 19, a + 16, 0, 1);
            wg_wait<1>();
            rel(18);
            put(d0, 0);
            wg_wait<0>();
            rel(19);
            TS(37);
            put(d1, 1);
            bar_arrive(4, 288);
            TS(38);
            acq(20);
            sp(d0, 20, a, w, 0);
            acq(21);
            sp(d0, 21, a + 16, 0, 1);
            acq(22); acq(23);
            rel(22); rel(23);
            mbar_wait(bars + B_RST * 8, 0);
            wg_wait<0>();
            rel(20); rel(21);
            put(d0, 2);
            TS(12);
        }

        {
            constexpr float CS = 0.125f * 1.4426950408889634f;
            float sa[32], sb2[32], o[36];
            uint32_t pa[16], pb[16], q[16];
            float n0 = INFINITY, n1 = INFINITY;
            zero(o); zero(pa); zero(pb); zero(sb2);
            const uint32_t ones = sb + OFF_MISC + 2048;
            { const uint32_t c = w ? 0u : 0x3F803F80u; sts128(ones + tid * 16, c, c, c, c); }
            fence_async_smem();
            bar_sync(10, 256);
            const uint32_t vdesc = rdesc + ((((ones - rbase) >> 4) - 1) << 16);
            auto qk_issue = [&](float (&s)[32], uint32_t lo) {
                const uint64_t kd = mkdesc(lo);
                wg_fence();
#pragma unroll
                for (int k = 0; k < 4; k++) mma_qk(s, q[4 * k], q[4 * k + 1], q[4 * k + 2], q[4 * k + 3], kd + 2 * k, k != 0);
                wg_commit();
            };
            auto both_issue = [&](float (&s)[32], uint32_t klo, uint32_t (&pp)[16], uint32_t vlo) {
                const uint64_t kd = mkdesc(klo), vd = mkdesc(vlo);
                wg_fence();
#pragma unroll
                for (int k = 0; k < 4; k++) {
                    mma_pv(o, pp[4 * k], pp[4 * k + 1], pp[4 * k + 2], pp[4 * k + 3], vd - k * (128 * 65535));
                    mma_qk(s, q[4 * k], q[4 * k + 1], q[4 * k + 2], q[4 * k + 3], kd + 2 * k, k != 0);
                }
                wg_commit();
            };
            auto new_max = [&](float (&s)[32], int nj, float& x0, float& x1) {
                x0 = s[0]; x1 = s[2];
#pragma unroll
                for (int j = 0; j < nj; j++) {
                    x0 = fmaxf(x0, fmaxf(s[4 * j], s[4 * j + 1]));
                    x1 = fmaxf(x1, fmaxf(s[4 * j + 2], s[4 * j + 3]));
                }
                x0 = fmaxf(x0, __shfl_xor_sync(~0u, x0, 1)); x1 = fmaxf(x1, __shfl_xor_sync(~0u, x1, 1));
                x0 = fmaxf(x0, __shfl_xor_sync(~0u, x0, 2)); x1 = fmaxf(x1, __shfl_xor_sync(~0u, x1, 2));
                x0 = fminf(n0, fmaf(x0, -CS, -20.f)); x1 = fminf(n1, fmaf(x1, -CS, -20.f));
            };
            auto probs = [&](float (&s)[32], uint32_t (&pp)[16], bool ready, bool tail, auto wait) {
                uint32_t any = 0;
#pragma unroll
                for (int i = 0; i < 16; i++) {
                    pp[i] = pack2(ex2(fmaf(s[2 * i], CS, (i & 1) ? n1 : n0)), ex2(fmaf(s[2 * i + 1], CS, (i & 1) ? n1 : n0)));
                    any |= pp[i];
                }
                wg_wait<0>();
                pin(sa); pin(sb2); pin(o); pin(pa); pin(pb);
                if (__any_sync(~0u, (any & 0x40004000u) || !ready)) {
                    wait();
                    if (__any_sync(~0u, any & 0x40004000u)) {
                        if (tail) {
#pragma unroll
                            for (int i = 20; i < 32; i++) s[i] = -INFINITY;
                        }
                        float x0, x1;
                        new_max(s, 8, x0, x1);
                        const float sc0 = ex2(x0 - n0), sc1 = ex2(x1 - n1);
                        n0 = x0; n1 = x1;
#pragma unroll
                        for (int j = 0; j < 9; j++) { o[4 * j] *= sc0; o[4 * j + 1] *= sc0; o[4 * j + 2] *= sc1; o[4 * j + 3] *= sc1; }
#pragma unroll
                        for (int i = 0; i < 16; i++)
                            pp[i] = pack2(ex2(fmaf(s[2 * i], CS, (i & 1) ? n1 : n0)), ex2(fmaf(s[2 * i + 1], CS, (i & 1) ? n1 : n0)));
                    }
                }
            };
            {
                uint4 u[4];
                const unsigned char* src = g_kvq + 2097152 + (size_t)(abh * 1024 + qt * 64 + wq * 16) * 128 + lane * 16;
                spin(QGATE);
                ld_data<512>(u, src);
#pragma unroll
                for (int k = 0; k < 2; k++) {
                    q[8 * k] = u[k].x; q[8 * k + 1] = u[k + 2].x; q[8 * k + 2] = u[k].y; q[8 * k + 3] = u[k + 2].y;
                    q[8 * k + 4] = u[k].z; q[8 * k + 5] = u[k + 2].z; q[8 * k + 6] = u[k].w; q[8 * k + 7] = u[k + 2].w;
                }
                pin(q);
            }
            TS(40);
            acq(24);
            TS(13);
            qk_issue(sa, rdesc + (24 % NSLOT) * (SLOT >> 4));
            wg_wait<0>();
            pin(sa);
            {
                float x0, x1;
                new_max(sa, NJ0, x0, x1);
                n0 = x0; n1 = x1;
            }
            bar_arrive(6, 384);
            uint32_t vd = vdesc - (SLOT >> 4) * 65535u, kd = rdesc, vb = fbar + 8, kb = fbar;
            uint32_t vlast = vdesc - 4 * (SLOT >> 4) * 65535u, klast = rdesc + 4 * (SLOT >> 4) + 512;
            uint32_t kprev = fbar + 32, vprev = bars + (B_SINK - (B_EMPTY - B_FULL)) * 8;
#pragma unroll 1
            for (int it = 0; it < 4; it++) {
                both_issue(sb2, klast, pb, vlast);
                probs(sa, pa, mbar_test(vb, it < 2) & mbar_test(kb, it < 3), false, [&]() { mbar_wait(vb, it < 2); mbar_wait(kb, it < 3); });
                TS(41 + it * 4);
                if (lane == 0) mbar_arrive(kprev + (B_EMPTY - B_FULL) * 8);
                if (lane == 0) mbar_arrive(vprev + (B_EMPTY - B_FULL) * 8);
                both_issue(sa, kd, pa, vd);
                const int dv = it == 0 ? 2 : (it == 1 ? -3 : 1);
                kprev = kb; vprev = vb; vlast = vd - 512 * 65535u; klast = kd + 512;
                vd -= dv * (SLOT >> 4) * 65535u; vb += dv * 8;
                kd += (it == 2 ? -3 : 2) * (SLOT >> 4); kb = it == 2 ? vb : kb + 16;
                probs(sb2, pb, true, it == 3 && w == 1, []() {});
                TS(43 + it * 4);
            }
            wg_fence();
#pragma unroll
            for (int k = 0; k < 4; k++)
                mma_pv(o, pb[4 * k], pb[4 * k + 1], pb[4 * k + 2], pb[4 * k + 3], mkdesc(vlast - k * (128 * 65535) + (k > 1 ? w * ((k - 1) << 22) : 0)));
            wg_commit();
            const int row = wq * 16 + (lane >> 2);
            const uint32_t ml = sb + OFF_MISC;
            mbar_wait(bars + (B_RST + 1) * 8, 0);
            wg_wait<0>();
            pin(o); pin(pb); pin(sa); pin(sb2);
            rel(31);
            const float l0 = o[32], l1 = o[34];
            if (c4 == 0) { sts64f(ml + w * 512 + row * 8, n0, l0); sts64f(ml + w * 512 + row * 8 + 64, n1, l1); }
            TS(14);
            float mine[16];
#pragma unroll
            for (int j = 0; j < 4; j++) {
                if (w == 0) sts128f(H + j * 2048 + wt * 16, o[16 + 4 * j], o[17 + 4 * j], o[18 + 4 * j], o[19 + 4 * j]);
                else sts128f(H + 8192 + j * 2048 + wt * 16, o[4 * j], o[4 * j + 1], o[4 * j + 2], o[4 * j + 3]);
            }
#pragma unroll
            for (int i = 0; i < 16; i++) mine[i] = w == 0 ? o[i] : o[16 + i];
            bar_sync(10, 256);
            const float2 u0 = lds64f(ml + (w ^ 1) * 512 + row * 8), u1 = lds64f(ml + (w ^ 1) * 512 + row * 8 + 64);
            const float x0 = fminf(n0, u0.x), x1 = fminf(n1, u1.x);
            float a0 = ex2(x0 - n0), b0 = ex2(x0 - u0.x), a1 = ex2(x1 - n1), b1 = ex2(x1 - u1.x);
            const float i0 = __fdividef(1.f, fmaf(a0, l0, b0 * u0.y)), i1 = __fdividef(1.f, fmaf(a1, l1, b1 * u1.y));
            a0 *= i0; b0 *= i0; a1 *= i1; b1 *= i1;
            uint32_t pk[8];
#pragma unroll
            for (int j = 0; j < 4; j++) {
                const float4 v = lds128f(H + (w ^ 1) * 8192 + j * 2048 + wt * 16);
                pk[2 * j] = pack2(fmaf(a0, mine[4 * j], b0 * v.x), fmaf(a0, mine[4 * j + 1], b0 * v.y));
                pk[2 * j + 1] = pack2(fmaf(a1, mine[4 * j + 2], b1 * v.z), fmaf(a1, mine[4 * j + 3], b1 * v.w));
            }
            unsigned char* dst = g_o + (size_t)(b * 128 + qt * 8 + 2 * wq) * 4096 + ah * 1024 + w * 512 + lane * 16;
            st_data(dst, pk[0], pk[2], pk[4], pk[6]);
            st_data(dst + 4096, pk[1], pk[3], pk[5], pk[7]);
            if (tid == 0) asm volatile("red.relaxed.gpu.global.add.u32 [%0], 1;" ::"l"(&g_epoch[blockIdx.x * FS]) : "memory");
            TS(15);
        }

        {
            acq(32); acq(33); acq(34);
            uint4 u[8];
            ld_data<512>(u, g_o + (size_t)(b * 128 + pt * 4 + wq) * 4096 + lane * 16);
#pragma unroll
            for (int i = 0; i < 8; i++) { a[4 * i] = u[i].x; a[4 * i + 1] = u[i].y; a[4 * i + 2] = u[i].z; a[4 * i + 3] = u[i].w; }
            TS(16);
            sp(d0, 32, a, 0, 0);
            sp(d0, 33, a + 16, 0, 1);
            residual(32);
            TS(17);
        }
    }

    cluster_arrive();
    TS(24);
    {
        const float rstd = rsq(fmaxf(fmaf(-mean, mean, msq), 0.f) + 1e-5f), nb = -mean * rstd;
#pragma unroll
        for (int j = 0; j < 8; j++) xr[j] = pack2(fmaf(v[2 * j], rstd, nb), fmaf(v[2 * j + 1], rstd, nb));
        const uint32_t stg = P + 16384 + warp * 1024;
        stsm4(stg + foff, xr[0], xr[1], xr[2], xr[3]);
        stsm4(stg + (foff ^ 64), xr[4], xr[5], xr[6], xr[7]);
        __syncwarp();
        const uint32_t src = stg + (lane >> 3) * 128 + (((lane & 7) ^ (lane >> 3)) << 4);
        const uint4 u0 = lds128(src), u1 = lds128((src + 512) ^ 64);
        __nv_bfloat16* dst = p.out + (size_t)(b * T_ + trow + (lane >> 3)) * 256 + tile * 64 + (lane & 7) * 8;
        if (trow < T_) { stg128(dst, u0); stg128(dst + 4 * 256, u1); }
    }
    TS(25);
    TG(31);
    TSDUMP();
    cluster_wait();
}

typedef CUresult (*EncodeFn)(CUtensorMap*, CUtensorMapDataType, cuuint32_t, void*, const cuuint64_t*, const cuuint64_t*,
                             const cuuint32_t*, const cuuint32_t*, CUtensorMapInterleave, CUtensorMapSwizzle,
                             CUtensorMapL2promotion, CUtensorMapFloatOOBfill);

}

extern "C" void kernel_launch(void* const* d_in, const int* in_sizes, int n_in, void* d_out, int out_size) {
    static EncodeFn encode = nullptr;
    if (!encode) {
        void* fn = nullptr;
        cudaDriverEntryPointQueryResult qr;
        cudaGetDriverEntryPoint("cuTensorMapEncodeTiled", &fn, cudaEnableDefault, &qr);
        encode = (EncodeFn)fn;
        cudaFuncSetAttribute(conformer_kernel, cudaFuncAttributeMaxDynamicSharedMemorySize, SMEM_LAUNCH);
    }
    Params p;
    const cuuint32_t ones[5] = {1, 1, 1, 1, 1};
    const int idx[8] = {1, 2, 3, 4, 5, 7, 8, 9};
    const int rows[8] = {256, 1024, 256, 256, 256, 256, 256, 1024};
    const int cols[8] = {1024, 256, 768, 256, 512, 256, 1024, 256};
    for (int i = 0; i < 8; i++) {
        const cuuint64_t pitch = (cuuint64_t)cols[i] * 2;
        const cuuint64_t dims[5] = {(cuuint64_t)cols[i], 2, 2, 4, (cuuint64_t)rows[i] / 16};
        const cuuint64_t strides[4] = {pitch, pitch * 8, pitch * 2, pitch * 16};
        const cuuint32_t box[5] = {64, 2, 2, 4, 8};
        encode(&p.tm[i], CU_TENSOR_MAP_DATA_TYPE_BFLOAT16, 5, d_in[idx[i]], dims, strides, box, ones, CU_TENSOR_MAP_INTERLEAVE_NONE,
               CU_TENSOR_MAP_SWIZZLE_128B, CU_TENSOR_MAP_L2_PROMOTION_L2_128B, CU_TENSOR_MAP_FLOAT_OOB_FILL_NONE);
        p.w[i] = (const char*)d_in[idx[i]];
    }
    {
        void* kv = nullptr;
        cudaGetSymbolAddress(&kv, g_kvq);
        const cuuint64_t dims[2] = {64, 16384};
        const cuuint64_t strides[1] = {128};
        const cuuint32_t box[2] = {64, 128};
        encode(&p.tm[8], CU_TENSOR_MAP_DATA_TYPE_BFLOAT16, 2, kv, dims, strides, box, ones, CU_TENSOR_MAP_INTERLEAVE_NONE,
               CU_TENSOR_MAP_SWIZZLE_NONE, CU_TENSOR_MAP_L2_PROMOTION_L2_128B, CU_TENSOR_MAP_FLOAT_OOB_FILL_NONE);
    }
    p.x = (const __nv_bfloat16*)d_in[0];
    p.dw = (const __nv_bfloat16*)d_in[6];
    p.out = (__nv_bfloat16*)d_out;
    p.zero = 0;
    conformer_kernel<<<NCTA, NTHREADS, SMEM_LAUNCH>>>(p);
}
```

```cpp
#include <cuda_runtime.h>
#include <cuda_bf16.h>
#include <cuda.h>
#include <stdint.h>

namespace {

constexpr int T_ = 1000;
constexpr int NCTA = 128;
constexpr int NTHREADS = 512;
constexpr int NSLOT = 5;
constexpr int SLOT = 16384;
constexpr int NLOADS = 56;

constexpr uint32_t OFF_RING = 0;
constexpr uint32_t OFF_P = 163840;
constexpr uint32_t OFF_H = 188416;
constexpr uint32_t OFF_MISC = 221184;
constexpr uint32_t OFF_BARS = 229888;
constexpr uint32_t SMEM_BYTES = 230400;
constexpr uint32_t GCH = 6144;
constexpr uint32_t HCH = 4096;

constexpr int B_FULL = 0, B_EMPTY = 10, B_XA = 20  , B_XB = 25  , B_INB = 29  , B_SR = 33,
              B_RST = 34  , B_RDY = 36  , B_SINK = 42, B_HALO = 43  , NBARS = 47;

#define KD2 300u
#define KD3 500u
#define QGATE 500u
#define BACKOFF 0u
#define KFS 8
#define KDELAY 300u
#define NJ0 2
#define HDELAY 200u
#define TURN 0
#define EAGER 0x4755
constexpr int FS = 8;

struct Params {
    CUtensorMap tm[9];
    const char* w[8];
    const __nv_bfloat16* x;
    const __nv_bfloat16* dw;
    __nv_bfloat16* out;
    uint32_t zero;
};

__device__ __align__(1024) unsigned char g_kvq[3 * 8 * 1024 * 128];
__device__ __align__(1024) unsigned char g_o[2 * 128 * 4096];
__device__ uint4 g_halo[64 * 4 * 2 * 64];
__device__ __align__(128) uint32_t g_flag_kv[8 * 32 * KFS];
__device__ uint32_t g_reset[4 * 32];
__device__ uint32_t g_epoch[NCTA * FS];

#define TS(i) do { } while (0)
#define TSW(i) do { } while (0)
#define TG(i) do { } while (0)
#define TSINIT() do { } while (0)
#define TSDUMP() do { } while (0)
constexpr uint32_t SMEM_LAUNCH = SMEM_BYTES;

__device__ __forceinline__ uint32_t smem_u32(const void* p) { return (uint32_t)__cvta_generic_to_shared(p); }
__device__ __forceinline__ void mbar_init(uint32_t b, uint32_t c) { asm volatile("mbarrier.init.shared::cta.b64 [%0], %1;" ::"r"(b), "r"(c) : "memory"); }
__device__ __forceinline__ void mbar_arrive(uint32_t b) { asm volatile("mbarrier.arrive.shared::cta.b64 _, [%0];" ::"r"(b) : "memory"); }
__device__ __forceinline__ void mbar_arrive_tx(uint32_t b, uint32_t tx) { asm volatile("mbarrier.arrive.expect_tx.shared::cta.b64 _, [%0], %1;" ::"r"(b), "r"(tx) : "memory"); }
__device__ __forceinline__ void mbar_wait(uint32_t b, uint32_t ph) {
    asm volatile("{\n.reg .pred p, q;\n.reg .u32 c;\nmov.u32 c, 0;\n"
                 "MW_LOOP:\n.pragma \"nounroll\";\n"
                 "mbarrier.try_wait.parity.shared::cta.b64 p, [%0], %1;\n"
                 "add.u32 c, c, 1;\nsetp.lt.u32 q, c, 65536;\nnot.pred p, p;\nand.pred p, p, q;\n@p bra MW_LOOP;\n}"
                 ::"r"(b), "r"(ph) : "memory");
}
__device__ __forceinline__ bool mbar_test(uint32_t b, uint32_t ph) {
    uint32_t ok;
    asm volatile("{\n.reg .pred p;\nmbarrier.test_wait.parity.shared::cta.b64 p, [%1], %2;\nselp.u32 %0, 1, 0, p;\n}" : "=r"(ok) : "r"(b), "r"(ph) : "memory");
    return ok;
}
__device__ __forceinline__ uint32_t mapa(uint32_t a, uint32_t r) { uint32_t o; asm("mapa.shared::cluster.u32 %0, %1, %2;" : "=r"(o) : "r"(a), "r"(r)); return o; }
__device__ __forceinline__ void fence_async_smem() { asm volatile("fence.proxy.async.shared::cta;" ::: "memory"); }
__device__ __forceinline__ void fence_async_global() { asm volatile("fence.proxy.async.global;" ::: "memory"); }
__device__ __forceinline__ void bar_sync(int id, int n) { asm volatile("bar.sync %0, %1;" ::"r"(id), "r"(n) : "memory"); }
__device__ __forceinline__ void bar_arrive(int id, int n) { asm volatile("bar.arrive %0, %1;" ::"r"(id), "r"(n) : "memory"); }
__device__ __forceinline__ void cluster_arrive() { asm volatile("barrier.cluster.arrive.relaxed.aligned;" ::: "memory"); }
__device__ __forceinline__ void cluster_wait() { asm volatile("barrier.cluster.wait.aligned;" ::: "memory"); }

__device__ __forceinline__ void ring_load(uint32_t dst, const CUtensorMap* tm, int col, int row16, uint32_t bar) {
    asm volatile("{\n.reg .pred p;\nelect.sync _|p, 0xffffffff;\n"
                 "@p mbarrier.arrive.expect_tx.shared::cta.b64 _, [%2], 16384;\n"
                 "@p cp.async.bulk.tensor.5d.shared::cluster.global.mbarrier::complete_tx::bytes [%0], [%1, {%3, 0, 0, 0, %4}], [%2];\n}"
                 ::"r"(dst), "l"(tm), "r"(bar), "r"(col), "r"(row16) : "memory");
}
__device__ __forceinline__ void ring_load_both(uint32_t dst, const CUtensorMap* tm, int c1, uint32_t bar) {
    asm volatile("{\n.reg .pred p;\nelect.sync _|p, 0xffffffff;\n"
                 "@p cp.async.bulk.tensor.2d.shared::cluster.global.mbarrier::complete_tx::bytes.multicast::cluster [%0], [%1, {0, %3}], [%2], %4;\n}"
                 ::"r"(dst), "l"(tm), "r"(bar), "r"(c1), "h"((uint16_t)3) : "memory");
}
__device__ __forceinline__ void mbar_arrive_peer(uint32_t b) { asm volatile("mbarrier.arrive.relaxed.cluster.shared::cluster.b64 _, [%0];" ::"r"(b) : "memory"); }
__device__ __forceinline__ void prefetch_l2(const void* src, uint32_t bytes) {
    asm volatile("cp.async.bulk.prefetch.L2.global [%0], %1;" ::"l"(src), "r"(bytes) : "memory");
}
__device__ __forceinline__ void peer_copy(uint32_t dst, uint32_t src, uint32_t bytes, uint32_t rbar) {
    asm volatile("{\n.reg .pred p;\nelect.sync _|p, 0xffffffff;\n"
                 "@p cp.async.bulk.shared::cluster.shared::cta.mbarrier::complete_tx::bytes [%0], [%1], %2, [%3];\n}"
                 ::"r"(dst), "r"(src), "r"(bytes), "r"(rbar) : "memory");
}
__device__ __forceinline__ void st_async4(uint32_t dst, uint32_t a, uint32_t b, uint32_t c, uint32_t d, uint32_t bar) {
    asm volatile("st.async.shared::cluster.mbarrier::complete_tx::bytes.v4.b32 [%0], {%1,%2,%3,%4}, [%5];" ::"r"(dst), "r"(a), "r"(b), "r"(c), "r"(d), "r"(bar) : "memory");
}
__device__ __forceinline__ void st_async2f(uint32_t dst, float a, float b, uint32_t bar) {
    asm volatile("st.async.shared::cluster.mbarrier::complete_tx::bytes.v2.f32 [%0], {%1,%2}, [%3];" ::"r"(dst), "f"(a), "f"(b), "r"(bar) : "memory");
}
__device__ __forceinline__ void stsm4(uint32_t a, uint32_t r0, uint32_t r1, uint32_t r2, uint32_t r3) {
    asm volatile("stmatrix.sync.aligned.m8n8.x4.shared.b16 [%0], {%1,%2,%3,%4};" ::"r"(a), "r"(r0), "r"(r1), "r"(r2), "r"(r3) : "memory");
}
__device__ __forceinline__ void ldsm4(uint32_t a, uint32_t& r0, uint32_t& r1, uint32_t& r2, uint32_t& r3) {
    asm volatile("ldmatrix.sync.aligned.m8n8.x4.shared.b16 {%0,%1,%2,%3}, [%4];" : "=r"(r0), "=r"(r1), "=r"(r2), "=r"(r3) : "r"(a) : "memory");
}
__device__ __forceinline__ uint4 lds128(uint32_t a) { uint4 v; asm volatile("ld.shared.v4.b32 {%0,%1,%2,%3}, [%4];" : "=r"(v.x), "=r"(v.y), "=r"(v.z), "=r"(v.w) : "r"(a) : "memory"); return v; }
__device__ __forceinline__ float4 lds128f(uint32_t a) { float4 v; asm volatile("ld.shared.v4.f32 {%0,%1,%2,%3}, [%4];" : "=f"(v.x), "=f"(v.y), "=f"(v.z), "=f"(v.w) : "r"(a) : "memory"); return v; }
__device__ __forceinline__ float2 lds64f(uint32_t a) { float2 v; asm volatile("ld.shared.v2.f32 {%0,%1}, [%2];" : "=f"(v.x), "=f"(v.y) : "r"(a) : "memory"); return v; }
__device__ __forceinline__ uint32_t lds32(uint32_t a) { uint32_t v; asm volatile("ld.shared.b32 %0, [%1];" : "=r"(v) : "r"(a) : "memory"); return v; }
__device__ __forceinline__ void sts128(uint32_t a, uint32_t x, uint32_t y, uint32_t z, uint32_t w) { asm volatile("st.shared.v4.b32 [%0], {%1,%2,%3,%4};" ::"r"(a), "r"(x), "r"(y), "r"(z), "r"(w) : "memory"); }
__device__ __forceinline__ void sts128f(uint32_t a, float x, float y, float z, float w) { asm volatile("st.shared.v4.f32 [%0], {%1,%2,%3,%4};" ::"r"(a), "f"(x), "f"(y), "f"(z), "f"(w) : "memory"); }
__device__ __forceinline__ void sts64f(uint32_t a, float x, float y) { asm volatile("st.shared.v2.f32 [%0], {%1,%2};" ::"r"(a), "f"(x), "f"(y) : "memory"); }
__device__ __forceinline__ void sts32(uint32_t a, uint32_t x) { asm volatile("st.shared.b32 [%0], %1;" ::"r"(a), "r"(x) : "memory"); }
__device__ __forceinline__ void stg128(void* p, uint4 v) { asm volatile("st.global.v4.b32 [%0], {%1,%2,%3,%4};" ::"l"(p), "r"(v.x), "r"(v.y), "r"(v.z), "r"(v.w) : "memory"); }

__device__ __forceinline__ uint32_t pack2(float lo, float hi) { uint32_t r; asm("cvt.rn.bf16x2.f32 %0, %1, %2;" : "=r"(r) : "f"(hi), "f"(lo)); return r; }
__device__ __forceinline__ float blo(uint32_t v) { return __uint_as_float(v << 16); }
__device__ __forceinline__ float bhi(uint32_t v) { return __uint_as_float(v & 0xffff0000u); }
__device__ __forceinline__ uint32_t hmul2(uint32_t a, uint32_t b) { uint32_t r; asm("mul.rn.bf16x2 %0, %1, %2;" : "=r"(r) : "r"(a), "r"(b)); return r; }
__device__ __forceinline__ uint32_t hsub2(uint32_t a, uint32_t b) { uint32_t r; asm("sub.rn.bf16x2 %0, %1, %2;" : "=r"(r) : "r"(a), "r"(b)); return r; }
__device__ __forceinline__ uint32_t hfma2(uint32_t a, uint32_t b, uint32_t c) { uint32_t r; asm("fma.rn.bf16x2 %0, %1, %2, %3;" : "=r"(r) : "r"(a), "r"(b), "r"(c)); return r; }
__device__ __forceinline__ float tanh_fast(float x) { float r; asm("tanh.approx.f32 %0, %1;" : "=f"(r) : "f"(x)); return r; }
__device__ __forceinline__ float rsq(float x) { float r; asm("rsqrt.approx.ftz.f32 %0, %1;" : "=f"(r) : "f"(x)); return r; }
__device__ __forceinline__ float ex2(float x) { float r; asm("ex2.approx.ftz.f32 %0, %1;" : "=f"(r) : "f"(x)); return r; }

__device__ __forceinline__ uint32_t ld_relaxed(const uint32_t* p) {
    uint32_t v;
    asm volatile("ld.relaxed.gpu.global.u32 %0, [%1];" : "=r"(v) : "l"(p) : "memory");
    return v;
}
__device__ __forceinline__ uint32_t clock32() { uint32_t c; asm volatile("mov.u32 %0, %%clock;" : "=r"(c)::"memory"); return c; }
__device__ __forceinline__ void spin(uint32_t clks) {
    const uint32_t t0 = clock32();
    while (clock32() - t0 < clks) {}
}
__device__ __forceinline__ void flag_wait(const uint32_t* p, uint32_t e, bool mine) {
#pragma unroll 1
    for (int i = 0; i < (1 << 19); i++) {
        if (mine) mine = ld_relaxed(p) != e;
        if (!__any_sync(~0u, mine)) break;
        if (BACKOFF) spin(BACKOFF);
    }
    asm volatile("fence.acquire.gpu;" ::: "memory");
    fence_async_global();
}
__device__ __forceinline__ void st_data(void* p, uint32_t x, uint32_t y, uint32_t z, uint32_t w) {
    asm volatile("st.relaxed.gpu.global.v4.b32 [%0], {%1,%2,%3,%4};" ::"l"(p), "r"(x), "r"(y), "r"(z), "r"(w) : "memory");
}
template <int STRIDE, int N>
__device__ __forceinline__ void ld_data(uint4 (&v)[N], const unsigned char* p) {
    int it = 0;
    bool again;
#pragma unroll 1
    do {
        uint32_t m = 0;
#pragma unroll
        for (int i = 0; i < N; i++)
            asm volatile("ld.relaxed.gpu.global.v4.b32 {%0,%1,%2,%3}, [%4];" : "=r"(v[i].x), "=r"(v[i].y), "=r"(v[i].z), "=r"(v[i].w) : "l"(p + i * STRIDE) : "memory");
#pragma unroll
        for (int i = 0; i < N; i++) m = __vimax3_u32(__vimax3_u32(v[i].x, v[i].y, v[i].z), v[i].w, m);
        again = __any_sync(~0u, m == ~0u) && ++it < (1 << 16);
    } while (again);
}
__device__ __forceinline__ uint32_t ld_epoch() { return ld_relaxed(&g_epoch[blockIdx.x * FS]) + 1; }
__device__ __forceinline__ void flag_set(uint32_t* p, uint32_t e) { asm volatile("st.release.gpu.global.u32 [%0], %1;" ::"l"(p), "r"(e) : "memory"); }

__device__ __forceinline__ uint32_t desc_lo(uint32_t addr) { return ((addr & 0x3FFFF) >> 4) | 0x10000u; }
__device__ __forceinline__ uint64_t mkdesc(uint32_t lo) { return (uint64_t)lo | (0x40000040ull << 32); }
__device__ __forceinline__ void wg_fence() { asm volatile("wgmma.fence.sync.aligned;" ::: "memory"); }
__device__ __forceinline__ void wg_commit() { asm volatile("wgmma.commit_group.sync.aligned;" ::: "memory"); }
template <int N> __device__ __forceinline__ void wg_wait() { asm volatile("wgmma.wait_group.sync.aligned %0;" ::"n"(N) : "memory"); }
template <int N> __device__ __forceinline__ void pin(float (&d)[N]) {
#pragma unroll
    for (int i = 0; i < N; i++) asm volatile("" : "+f"(d[i])::"memory");
}
template <int N> __device__ __forceinline__ void pin(uint32_t (&d)[N]) {
#pragma unroll
    for (int i = 0; i < N; i++) asm volatile("" : "+r"(d[i])::"memory");
}

template <typename Tp, int N> __device__ __forceinline__ void zero(Tp (&d)[N]) {
#pragma unroll
    for (int i = 0; i < N; i++) d[i] = 0;
    pin(d);
}

#define F4(d, i) "+f"(d[i]), "+f"(d[i + 1]), "+f"(d[i + 2]), "+f"(d[i + 3])
#define F16(d, i) F4(d, i), F4(d, i + 4), F4(d, i + 8), F4(d, i + 12)

__device__ __forceinline__ void mma_sp(float (&d)[32], const uint32_t* a, uint64_t b, uint32_t meta, int acc) {
    asm volatile("{.reg .pred p; setp.ne.b32 p, %38, 0;\n"
                 "wgmma.mma_async.sp.sync.aligned.m64n64k32.f32.bf16.bf16 {%0,%1,%2,%3,%4,%5,%6,%7,%8,%9,%10,%11,%12,%13,%14,%15,%16,%17,%18,%19,%20,%21,%22,%23,%24,%25,%26,%27,%28,%29,%30,%31}, "
                 "{%32,%33,%34,%35}, %36, %37, 0, p, 1, 1, 1;}\n"
                 : F16(d, 0), F16(d, 16) : "r"(a[0]), "r"(a[1]), "r"(a[2]), "r"(a[3]), "l"(b), "r"(meta), "r"(acc));
}
__device__ __forceinline__ void mma_qk(float (&d)[32], uint32_t a0, uint32_t a1, uint32_t a2, uint32_t a3, uint64_t b, int acc) {
    asm volatile("{.reg .pred p; setp.ne.b32 p, %37, 0;\n"
                 "wgmma.mma_async.sync.aligned.m64n64k16.f32.bf16.bf16 {%0,%1,%2,%3,%4,%5,%6,%7,%8,%9,%10,%11,%12,%13,%14,%15,%16,%17,%18,%19,%20,%21,%22,%23,%24,%25,%26,%27,%28,%29,%30,%31}, "
                 "{%32,%33,%34,%35}, %36, p, 1, 1, 0;}\n"
                 : F16(d, 0), F16(d, 16) : "r"(a0), "r"(a1), "r"(a2), "r"(a3), "l"(b), "r"(acc));
}
__device__ __forceinline__ void mma_pv(float (&d)[36], uint32_t a0, uint32_t a1, uint32_t a2, uint32_t a3, uint64_t b) {
    asm volatile("wgmma.mma_async.sync.aligned.m64n72k16.f32.bf16.bf16 {%0,%1,%2,%3,%4,%5,%6,%7,%8,%9,%10,%11,%12,%13,%14,%15,%16,%17,%18,%19,%20,%21,%22,%23,%24,%25,%26,%27,%28,%29,%30,%31,%32,%33,%34,%35}, "
                 "{%36,%37,%38,%39}, %40, 1, 1, 1, 1;\n"
                 : F16(d, 0), F16(d, 16), F4(d, 32) : "r"(a0), "r"(a1), "r"(a2), "r"(a3), "l"(b));
}

__device__ __forceinline__ uint32_t load_code(int n, int r, int w) {
    const int tile = 2 * r + w;
    int m, col, row;
    if (n < 16 || n >= 40) {
        const int k = n < 16 ? n : n - 40;
        m = n < 16 ? 0 : 6;
        if (k < 8) { col = 4 * tile + (k >> 1); row = (k & 1) ^ r; }
        else { m++; col = tile ^ (3 - ((k - 8) >> 1)); row = 2 * tile + (k & 1); }
    } else if (n < 32) {
        const int k = n - 16;
        m = 2;
        if (k < 4) { col = tile + ((k & 1) ? 8 : 4); row = (k >> 1) ^ r; }
        else { col = tile; row = (k & 1) ^ r; }
    } else if (n < 34) { m = 3; col = tile; row = n - 32; }
    else if (n < 38) { const int k = n - 34; m = 4; col = tile + 4 * (k & 1); row = (k >> 1) ^ r; }
    else { m = 5; col = tile; row = (n & 1) ^ r; }
    return m | (col << 4) | (row << 8);
}

__global__ void __cluster_dims__(2, 1, 1) __launch_bounds__(NTHREADS, 1)
conformer_kernel(const __grid_constant__ Params p) {
    extern __shared__ __align__(1024) unsigned char smem_raw[];
    const uint32_t sb = smem_u32(smem_raw);
    const uint32_t bars = sb + OFF_BARS;
    const int tid = threadIdx.x;
    const int lane = tid & 31;
    const int warp = __shfl_sync(~0u, tid >> 5, 0);
    const int r = blockIdx.x & 1;
    const int pair = blockIdx.x >> 1;
    const int b = pair >> 5, pt = pair & 31;
    const int ah = pt >> 3, qt = (pt & 7) * 2 + r;
    const int abh = b * 4 + ah;

    TG(30);
    TSINIT();
    TS(0);
    const uint32_t P = sb + OFF_P, H = sb + OFF_H;

    if (warp >= 8) {
        asm volatile("setmaxnreg.dec.sync.aligned.u32 48;");
        if (warp >= 12) {
            cluster_arrive();
            cluster_wait();
            const int ut = tid & 127;
            const uint32_t target = ld_epoch() * 64;
            auto reset_done = [&](int k) {
                bar_sync(11, 128);
                if (ut == 0) {
                    asm volatile("red.release.gpu.global.add.u32 [%0], 1;" ::"l"(&g_reset[(2 * b + k) * 32]) : "memory");
#pragma unroll 1
                    for (int i = 0; i < (1 << 20) && ld_relaxed(&g_reset[(2 * b + k) * 32]) != target; i++) __nanosleep(100);
                    asm volatile("fence.acquire.gpu;" ::: "memory");
                    mbar_arrive(bars + (B_RST + k) * 8);
                }
                __syncwarp();
                TS(13 + k);
            };
#pragma unroll
            for (int i = 0; i < 4; i++)
                st_data(g_kvq + 2097152 + (size_t)((b * 4 + 2 * r + (i >> 1)) * 1024 + pt * 32) * 128 + (i & 1) * 2048 + ut * 16, ~0u, ~0u, ~0u, ~0u);
            reset_done(0);
            bar_sync(6, 384);
#pragma unroll
            for (int i = 0; i < 4; i++) {
                st_data(g_o + (size_t)(b * 128 + qt * 8 + 2 * i + (ut >> 6)) * 4096 + ah * 1024 + (ut & 63) * 16, ~0u, ~0u, ~0u, ~0u);
                if (i < 2) st_data(&g_halo[(pair * 4 + 2 * r + i) * 128 + ut], ~0u, ~0u, ~0u, ~0u);
            }
            reset_done(1);
            const int side = warp & 1, wg = (warp >> 1) & 1, np = side ? pt + 1 : pt - 1;
            const unsigned char* src = reinterpret_cast<const unsigned char*>(&g_halo[(((b * 32 + np) * 4 + 2 * r + wg) * 2 + (side ^ 1)) * 64 + lane]);
            const uint32_t dst = H + 16384 + wg * GCH + side * 5120 + (lane & 7) * 128 + (((lane >> 3) ^ (lane & 7)) << 4);
            uint4 hv[2] = {make_uint4(0, 0, 0, 0), make_uint4(0, 0, 0, 0)};
            bar_sync(8 + wg, 192);
            if (np >= 0 && np < 32) {
                spin(HDELAY);
                ld_data<512>(hv, src);
            }
            stsm4(dst, hv[0].x, hv[0].y, hv[0].z, hv[0].w);
            stsm4(dst ^ 64, hv[1].x, hv[1].y, hv[1].z, hv[1].w);
            __syncwarp();
            if (lane == 0) mbar_arrive(bars + (B_HALO + (warp & 3)) * 8);
            TS(4);
        } else if (warp < 10) {
            const int w = warp - 8;
            const uint32_t ring = sb + OFF_RING + w * NSLOT * SLOT;
            const uint32_t full = bars + (B_FULL + w * NSLOT) * 8;
            if (lane == 0) {
#pragma unroll
                for (int i = 0; i < NSLOT; i++) { mbar_init(full + i * 8, 1); mbar_init(full + (B_EMPTY - B_FULL + i) * 8, 4); }
                asm volatile("fence.mbarrier_init.release.cluster;" ::: "memory");
                fence_async_smem();
            }
            __syncwarp();
            cluster_arrive();
            TS(1);
#pragma unroll
            for (int n = 0; n < NSLOT; n++) {
                if (n == 1 || n == 2) bar_sync(12, 64);
                ring_load(ring + n * SLOT, &p.tm[0], 64 * (8 * r + 4 * w + (n >> 1)), 8 * ((n & 1) ^ r), full + n * 8);
            }
            TS(2);
            const uint32_t code = load_code(lane, r, w) | (load_code(lane + 32, r, w) << 16);
            cluster_wait();
            uint32_t s = 0, ph = 0;
            int n = NSLOT;
#pragma unroll 1
            for (int seg = 0; seg < 2; seg++) {
#pragma unroll 1
                for (; n < (seg == 0 ? 22 : NLOADS); n++) {
                    const uint32_t c = __shfl_sync(~0u, code, n) >> (n & 32 ? 16 : 0);
                    const CUtensorMap* tm = &p.tm[c & 15];
                    const uint32_t col = (c & 0xf0) * 4, row = (c & 0xff00) >> 5, dst = ring + s * SLOT;
                    mbar_wait(full + (B_EMPTY - B_FULL) * 8 + s * 8, ph + (((uint32_t)(size_t)tm | col | row | dst) & p.zero));
                    ring_load(dst, tm, col, row, full + s * 8);
                    if (++s == NSLOT) { s = 0; ph ^= 1; }
                }
                if (seg == 1) break;
                const uint32_t epoch = ld_epoch();
                const uint32_t rdy = bars + (B_RDY + 3 * w) * 8, prdy = mapa(rdy, r ^ 1);
                const int odd = r ^ w;
                const uint32_t* flags = g_flag_kv + (abh * 32 + lane) * KFS;
                auto kv_load = [&](uint32_t sl, int isv, int i) {
                    ring_load_both(ring + sl * SLOT, &p.tm[8], (isv * 64 + abh * 8 + 2 * i + w) * 128, full + sl * 8);
                };
#pragma unroll 1
                for (int i = 0; i < 2; i++) {
                    if (lane < 3 + i) {
                        const uint32_t sl = i ? lane : lane + 2;
                        mbar_wait(full + (B_EMPTY - B_FULL + sl) * 8, i ^ 1);
                        mbar_arrive_tx(full + sl * 8, (i || lane == 2) ? SLOT : 0);
                    }
                    __syncwarp();
                }
                if (lane == 0) mbar_arrive_peer(prdy);
                bar_sync(14, 96);
                spin(KDELAY);
                mbar_wait(rdy, 0);
                flag_wait(flags, epoch, (lane >> 2) == 2 * odd + w);
                TSW(5 + 2 * odd);
                if (!odd) { kv_load(4, 0, 0); bar_arrive(12, 64); }
                else bar_sync(12, 64);
                spin(w ? KD3 : KD2);
                kv_load(odd ^ 1, odd ^ 1, odd);
                flag_wait(flags, epoch, (lane >> 2) == 2 * odd + w + 4);
                mbar_wait(full + (odd ^ 1) * 8, 1);
                kv_load(2 + odd, odd, 2 - odd);
#pragma unroll 1
                for (int i = 0; i < 3; i++) {
                    const uint32_t sl = i ? i - 1 : 4, bo = i == 2 ? 16 : 8;
                    mbar_wait(full + (B_EMPTY - B_FULL + sl) * 8, i != 0);
                    if (lane == 0) mbar_arrive_tx(full + sl * 8, SLOT);
                    if ((i & 1) != odd) {
                        mbar_wait(rdy + bo, 0);
                        kv_load(sl, i != 0, 2 + odd);
                    } else if (lane == 0) mbar_arrive_peer(prdy + bo);
                    __syncwarp();
                }
                n = 32; s = 2; ph = 1;
            }
        } else if (warp == 10) {
            if (lane == 0) {
#pragma unroll
                for (int i = B_XA; i < NBARS; i++) mbar_init(bars + i * 8, 1);
#pragma unroll
                for (int i = B_XA; i <= B_SR; i++) mbar_arrive_tx(bars + i * 8, i < B_XB ? 512 : 8192);
                asm volatile("fence.mbarrier_init.release.cluster;" ::: "memory");
                fence_async_smem();
            }
            __syncwarp();
            cluster_arrive();
            cluster_wait();
        } else {
            const uint32_t kb = (lane < 2 || lane > 5) ? 4096 : (lane == 2 ? 3072 : (lane == 4 ? 2048 : 1024));
            const char* pf = p.w[lane & 7] + blockIdx.x * kb;
            cluster_arrive();
            cluster_wait();
            if (lane < 2) prefetch_l2(pf, kb);
            mbar_wait(bars + B_XA * 8, 0);
            if (lane == 2) prefetch_l2(pf, kb);
            if (lane >= 1 && lane < 9) asm volatile("prefetch.tensormap [%0];" ::"l"(&p.tm[lane]) : "memory");
            mbar_wait(bars + (B_FULL + 1) * 8, 1);
            if (lane > 2 && lane < 8) prefetch_l2(pf, kb);
            if (lane == 8 && blockIdx.x < 15) prefetch_l2(p.dw + blockIdx.x * 256, 512);
            const uint32_t epoch = ld_epoch();
            bar_sync(4, 288);
            if (lane < 16) flag_set(&g_flag_kv[((b * 4 + 2 * r + (lane >> 3)) * 32 + pt) * KFS + (lane & 7)], epoch);
            __syncwarp();
            bar_arrive(14, 96);
            TSW(8);
        }
        TSDUMP();
        return;
    }

    const int w = warp >> 2, wq = warp & 3;
    const int tile = 2 * r + w;
    const int wt = tid & 127;
    const int c4 = lane & 3;
    const int trow = pt * 32 + 8 * wq;
    uint32_t xr[8];
    {
        const uint32_t* xp = reinterpret_cast<const uint32_t*>(p.x + (size_t)(b * T_ + trow + (lane >> 2)) * 256 + tile * 64) + c4;
#pragma unroll
        for (int j = 0; j < 8; j++) xr[j] = trow < T_ ? __ldg(xp + 4 * j) : 0u;
    }
    cluster_arrive();
    asm volatile("setmaxnreg.inc.sync.aligned.u32 208;");
    const uint32_t rbase = sb + OFF_RING + w * NSLOT * SLOT, fbar = bars + (B_FULL + w * NSLOT) * 8;
    const uint32_t rdesc = desc_lo(rbase);
    auto acq = [&](int n) { mbar_wait(fbar + (n % NSLOT) * 8, (n / NSLOT) & 1); };
    auto rel = [&](int n) { if (lane == 0) mbar_arrive(fbar + (B_EMPTY - B_FULL + n % NSLOT) * 8); };
    const uint32_t foff = (lane & 7) * 128 + (((lane >> 3) ^ (lane & 7)) << 4);
    float v[16];
#pragma unroll
    for (int j = 0; j < 8; j++) { v[2 * j] = blo(xr[j]); v[2 * j + 1] = bhi(xr[j]); }
    const uint32_t xown = __shfl_sync(~0u, P + wt * 16 + tile * 4096, lane), xrem = __shfl_sync(~0u, P + wt * 16 + (r ^ 1) * 8192, lane);
    const uint32_t sbuf = __shfl_sync(~0u, sb + OFF_MISC + 1024 + (8 * wq + (lane >> 2)) * 32, lane);
    const uint32_t sown = __shfl_sync(~0u, sbuf + tile * 8, lane);
    const uint32_t peer = __shfl_sync(~0u, mapa(sb, r ^ 1) - sb, lane);
    const uint32_t meta = __shfl_sync(~0u, 0xEEEE4444u + p.zero, lane);
    cluster_wait();
    TS(56);
    float mean, msq;

#pragma unroll 1
    for (int ph = 0;; ph++) {
        uint4 o0, o1;
        {
            float s = 0.f, q = 0.f, s2 = 0.f, q2 = 0.f;
#pragma unroll
            for (int j = 0; j < 4; j++) {
                s += v[4 * j] + v[4 * j + 1]; s2 += v[4 * j + 2] + v[4 * j + 3];
                q += fmaf(v[4 * j], v[4 * j], v[4 * j + 1] * v[4 * j + 1]); q2 += fmaf(v[4 * j + 2], v[4 * j + 2], v[4 * j + 3] * v[4 * j + 3]);
            }
            s += s2; q += q2;
            const uint32_t xa = bars + (B_XA + ph) * 8;
            s += __shfl_xor_sync(~0u, s, 1); q += __shfl_xor_sync(~0u, q, 1);
            s += __shfl_xor_sync(~0u, s, 2); q += __shfl_xor_sync(~0u, q, 2);
            if (c4 == 0) st_async2f(sown + peer, s, q, xa + peer);
            if (c4 == 0) sts64f(sown, s, q);
#pragma unroll
            for (int j = 0; j < 8; j++) xr[j] = pack2(v[2 * j], v[2 * j + 1]);
            sts128(xown, xr[0], xr[1], xr[2], xr[3]);
            sts128(xown + 2048, xr[4], xr[5], xr[6], xr[7]);
            bar_sync(10, 256);
            o0 = lds128(xown ^ 4096); o1 = lds128((xown ^ 4096) + 2048);
            if (ph < 4) {
                st_async4(xown + peer, xr[0], xr[1], xr[2], xr[3], xa + (B_XB - B_XA) * 8 + peer);
                st_async4(xown + peer + 2048, xr[4], xr[5], xr[6], xr[7], xa + (B_XB - B_XA) * 8 + peer);
            }
            TS(57 + ph);
            if (ph == 0) acq(0);
            mbar_wait(xa, 0);
            const float4 u0 = lds128f(sbuf), u1 = lds128f(sbuf + 16);
            mean = ((u0.x + u0.z) + (u1.x + u1.z)) * (1.f / 256.f);
            msq = ((u0.y + u0.w) + (u1.y + u1.w)) * (1.f / 256.f);
        }
        if (ph == 4) break;
        uint32_t a[32];
        const uint32_t mean2 = pack2(mean, mean);
        auto centre = [&](int i, const uint4& u) {
            a[i] = hsub2(u.x, mean2); a[i + 1] = hsub2(u.y, mean2); a[i + 2] = hsub2(u.z, mean2); a[i + 3] = hsub2(u.w, mean2);
        };
#pragma unroll
        for (int j = 0; j < 8; j++) a[j] = hsub2(xr[j], mean2);
        centre(8, o0); centre(12, o1);
        const float rstd = rsq(fmaxf(fmaf(-mean, mean, msq), 0.f) + 1e-5f);
        auto gather_peer = [&]() {
            mbar_wait(bars + (B_XB + ph) * 8, 0);
#pragma unroll
            for (int i = 0; i < 4; i++) centre(16 + 4 * i, lds128(xrem + i * 2048));
        };
        auto sp = [&](float (&d)[32], int n, const uint32_t* af, int flip, int acc) {
            const uint32_t lo = rdesc + p.zero * (ph + n + 1) + (n % NSLOT) * (SLOT >> 4);
            const uint64_t b0 = mkdesc(lo + flip * 512), b1 = mkdesc(lo + (flip ^ 1) * 512);
            wg_fence();
            mma_sp(d, af, b0, meta, acc);
            mma_sp(d, af + 4, b0 + 256, meta, 1);
            mma_sp(d, af + 8, b1, meta, 1);
            mma_sp(d, af + 12, b1 + 256, meta, 1);
            wg_commit();
        };
        float d0[32], d1[32];

        if (ph == 0 || ph == 3) {
            uint32_t h[32];
            const float rs = 0.5f * rstd;
            const uint32_t inb = bars + (B_INB + (ph & 2)) * 8, box = H + wt * 16;
            bool ready = true;
            auto step = [&](float (&d)[32], int n, const uint32_t* af, int flip, int acc, auto work) {
                if (!ready) acq(n);
                if (((TURN >> n) & 1) && w == 1) bar_sync(7, 256);
                sp(d, n, af, flip, acc);
                if (n > 0 && ((TURN >> (n - 1)) & 1) && w == 0) bar_arrive(7, 256);
                if (n < 15) ready = mbar_test(fbar + ((n + 1) % NSLOT) * 8, ((n + 1) / NSLOT) & 1);
                wg_wait<1>();
                if (n > 0 && !((EAGER >> (n - 1)) & 1)) rel(n - 1);
                const uint32_t tie = work() & p.zero;
                if ((EAGER >> n) & 1) {
                    if (p.zero < n + ph + 1) wg_wait<0>();
                    if (lane == 0) mbar_arrive(fbar + (B_EMPTY - B_FULL + n % NSLOT) * 8 + tie);
                }
            };
            auto none = []() { return 0u; };
            auto act = [&](float (&d)[32], int i) {
                pin(d);
#pragma unroll
                for (int j = 0; j < 8; j++) {
                    const float u0 = (d[4 * j] + d[4 * j + 2]) * rs, u1 = (d[4 * j + 1] + d[4 * j + 3]) * rs;
                    h[8 * i + j] = pack2(fmaf(u0, tanh_fast(u0), u0), fmaf(u1, tanh_fast(u1), u1));
                }
                return h[8 * i] | h[8 * i + 1] | h[8 * i + 2] | h[8 * i + 3] | h[8 * i + 4] | h[8 * i + 5] | h[8 * i + 6] | h[8 * i + 7];
            };
            auto send = [&](float (&d)[32], int x) {
                pin(d);
                uint32_t pk[8];
#pragma unroll
                for (int j = 0; j < 8; j++) pk[j] = pack2(d[4 * j] + d[4 * j + 2], d[4 * j + 1] + d[4 * j + 3]);
                const uint32_t ow = w ^ (x & 1), dst = box + (ow * 3 + x - 1) * 4096;
                if (x & 2) {
                    st_async4(dst + peer, pk[0], pk[1], pk[2], pk[3], inb + ow * 8 + peer);
                    st_async4(dst + peer + 2048, pk[4], pk[5], pk[6], pk[7], inb + ow * 8 + peer);
                } else {
                    sts128(dst, pk[0], pk[1], pk[2], pk[3]);
                    sts128(dst + 2048, pk[4], pk[5], pk[6], pk[7]);
                }
            };
            TS(1 + (ph & 2) * 10);
            step(d0, 0, a, w, 0, [&]() { gather_peer(); return 0u; });
            TS(32);
            step(d0, 1, a + 16, 0, 1, none);
            step(d1, 2, a, w, 0, [&]() { return act(d0, 0); });
            step(d1, 3, a + 16, 0, 1, none);
            step(d0, 4, a, w, 0, [&]() { return act(d1, 1); });
            TS(33);
            step(d0, 5, a + 16, 0, 1, none);
            step(d1, 6, a, w, 0, [&]() { return act(d0, 2); });
            step(d1, 7, a + 16, 0, 1, none);
            step(d0, 8, h, 0, 0, [&]() { return act(d1, 3); });
            TS(2 + (ph & 2) * 10);
            step(d0, 9, h + 16, 0, 1, none);
            step(d1, 10, h, 0, 0, [&]() { send(d0, 3); return 0u; });
            step(d1, 11, h + 16, 0, 1, none);
            step(d0, 12, h, 0, 0, [&]() { send(d1, 2); return 0u; });
            TS(34);
            step(d0, 13, h + 16, 0, 1, none);
            uint4 u[6];
            step(d1, 14, h, 0, 0, [&]() {
                send(d0, 1);
                mbar_wait(inb + w * 8, 0);
                bar_sync(10, 256);
#pragma unroll
                for (int i = 0; i < 6; i++) u[i] = lds128(box + w * 12288 + i * 2048);
                return u[0].x | u[1].x | u[2].x | u[3].x | u[4].x | u[5].x;
            });
            step(d1, 15, h + 16, 0, 1, none);
            mbar_wait(ph == 0 ? fbar + (16 % NSLOT) * 8 : inb + w * 8, ph == 0);
            uint32_t tie = 0;
#pragma unroll
            for (int i = 0; i < 2; i++) {
                const uint32_t p0[4] = {u[i].x, u[i].y, u[i].z, u[i].w}, p1[4] = {u[i + 2].x, u[i + 2].y, u[i + 2].z, u[i + 2].w}, p2[4] = {u[i + 4].x, u[i + 4].y, u[i + 4].z, u[i + 4].w};
#pragma unroll
                for (int j = 0; j < 4; j++) {
                    v[8 * i + 2 * j] = fmaf(0.5f, blo(p0[j]) + blo(p1[j]) + blo(p2[j]), blo(xr[4 * i + j]));
                    v[8 * i + 2 * j + 1] = fmaf(0.5f, bhi(p0[j]) + bhi(p1[j]) + bhi(p2[j]), bhi(xr[4 * i + j]));
                    tie |= __float_as_uint(v[8 * i + 2 * j]) | __float_as_uint(v[8 * i + 2 * j + 1]);
                }
            }
            if (__any_sync(~0u, tie & p.zero)) spin(1);
            wg_wait<0>();
            pin(d1);
            rel(15);
            TS(3 + (ph & 2) * 10);
#pragma unroll
            for (int j = 0; j < 8; j++) {
                v[2 * j] = fmaf(0.5f, d1[4 * j] + d1[4 * j + 2], v[2 * j]);
                v[2 * j + 1] = fmaf(0.5f, d1[4 * j + 1] + d1[4 * j + 3], v[2 * j + 1]);
            }
            continue;
        }

        auto residual = [&](int n) {
            wg_wait<1>();
            rel(n);
            wg_wait<0>();
            pin(d0);
            rel(n + 1);
#pragma unroll
            for (int j = 0; j < 8; j++) {
                v[2 * j] = d0[4 * j] + d0[4 * j + 2] + blo(xr[j]);
                v[2 * j + 1] = d0[4 * j + 1] + d0[4 * j + 3] + bhi(xr[j]);
            }
        };

        if (ph == 2) {
            TS(39);
            sp(d0, 34, a, w, 0);
            acq(35);
            sp(d1, 35, a, w, 0);
            acq(36); acq(37);
            gather_peer();
            sp(d0, 36, a + 16, 0, 1);
            sp(d1, 37, a + 16, 0, 1);
            wg_wait<2>();
            rel(34); rel(35);
            const int mir = wq < 2 ? 7 : 0;
            uint32_t dwr[15];
            {
                const uint32_t* dp = reinterpret_cast<const uint32_t*>(p.dw + tile * 64) + lane;
#pragma unroll
                for (int i = 0; i < 15; i++) dwr[i] = __ldg(dp + i * 128);
            }
            const float rs = trow < T_ ? 0.5f * rstd : 0.f;
            wg_wait<0>();
            pin(d0); pin(d1);
            rel(36); rel(37);
            TS(18);
            uint32_t pk[8];
#pragma unroll
            for (int j = 0; j < 8; j++) {
                const float u0 = (d0[4 * j] + d0[4 * j + 2]) * rs, u1 = (d0[4 * j + 1] + d0[4 * j + 3]) * rs;
                const float t0 = tanh_fast((d1[4 * j] + d1[4 * j + 2]) * rs), t1 = tanh_fast((d1[4 * j + 1] + d1[4 * j + 3]) * rs);
                pk[j] = pack2(fmaf(u0, t0, u0), fmaf(u1, t1, u1));
            }
            if (wq == 0 || wq == 3) {
                uint4* hp = &g_halo[((pair * 4 + tile) * 2 + (wq & 1)) * 64 + lane];
                st_data(hp, pk[0], pk[1], pk[2], pk[3]);
                st_data(hp + 32, pk[4], pk[5], pk[6], pk[7]);
            }
            const uint32_t gs = H + 16384 + w * GCH + wq * 1024;
            stsm4(gs + 1024 + foff, pk[0], pk[1], pk[2], pk[3]);
            stsm4(gs + 1024 + (foff ^ 64), pk[4], pk[5], pk[6], pk[7]);
            bar_sync(8 + w, 192);
            TS(26);
#pragma unroll
            for (int i = 0; i < 7; i++) {
                const uint32_t x = dwr[i], y = dwr[14 - i];
                dwr[i] = hmul2(mir ? y : x, 0x3F003F00u); dwr[14 - i] = hmul2(mir ? x : y, 0x3F003F00u);
            }
            dwr[7] = hmul2(dwr[7], 0x3F003F00u);
            uint32_t ca[8], cb[8];
            const int e = (wq & 1) * 4;
            const uint32_t lo = ((mir ^ e) * 144) ^ (lane * 4);
            const int dir = mir ? -1024 : 1024;
            const uint32_t gb = H + 16384 + w * GCH + (mir ? 3072 : 2048) + lo, sown_ = H + tile * HCH, so = sown_ + (mir ? 1024 : 2048) + lo;
            auto finish = [&](int i) {
                const float h0 = blo(ca[i]) + blo(cb[i]), h1 = bhi(ca[i]) + bhi(cb[i]);
                sts32((so + (i >> 2) * dir) ^ ((i & 3) * 144), pack2(fmaf(h0, tanh_fast(h0), h0), fmaf(h1, tanh_fast(h1), h1)));
            };
#pragma unroll
            for (int k = 0; k < 26; k++) {
                if (k == 19) {
#pragma unroll
                    for (int i = 0; i < 4; i++) finish(i);
                    fence_async_smem();
                    bar_sync(2 + w, 128);
                    if (wq == 0) peer_copy(mapa(sown_ + 1024, r ^ 1), sown_ + 1024, 2048, mapa(bars + B_SR * 8, r ^ 1));
                    acq(38); acq(39); acq(40);
                    const uint32_t tie = ca[4] | ca[5] | ca[6] | ca[7] | cb[4] | cb[5] | cb[6];
                    mbar_wait(bars + (B_HALO + 2 * w + (wq >> 1)) * 8, __shfl_sync(~0u, tie & p.zero, 0));
                    TS(27);
                }
                const uint32_t g = lds32((gb + (((k + 1) & 4) ? ((k + 1) >> 3) + (wq & 1) : ((k + 1) >> 3)) * dir) ^ (((k + 1) & 7) * 144));
#pragma unroll
                for (int i = 0; i < 8; i++) {
                    const int tap = k - (i & 3) - 2 * (i & 4);
                    if (tap == 0) ca[i] = hmul2(g, dwr[0]);
                    else if (tap > 0 && tap < 8) ca[i] = hfma2(g, dwr[tap], ca[i]);
                    else if (tap == 8) cb[i] = hmul2(g, dwr[8]);
                    else if (tap > 8 && tap < 15) cb[i] = hfma2(g, dwr[tap], cb[i]);
                }
            }
#pragma unroll
            for (int i = 4; i < 8; i++) finish(i);
            fence_async_smem();
            bar_sync(12 + (warp >> 1), 64);
            if (wq == 0 || wq == 3) peer_copy(mapa(sown_ + wq * 1024, r ^ 1), sown_ + wq * 1024, 1024, mapa(bars + B_SR * 8, r ^ 1));
            bar_sync(10, 256);
            TS(19);
            auto frags = [&](int i, int half) {
                const uint32_t src = H + 2 * half * HCH + wq * 1024;
#pragma unroll
                for (int k = 0; k < 4; k++) ldsm4(src + (k >> 1) * HCH + (foff ^ ((k & 1) * 64)), a[i + 4 * k], a[i + 4 * k + 1], a[i + 4 * k + 2], a[i + 4 * k + 3]);
            };
            frags(0, r);
            sp(d0, 38, a, 0, 0);
            mbar_wait(bars + B_SR * 8, 0);
            frags(16, r ^ 1);
            sp(d0, 39, a + 16, 0, 1);
            residual(38);
            TS(20);
            continue;
        }

        {
            TS(11);
            const uint32_t stg = H + warp * 2048;
            unsigned char* g = g_kvq + (size_t)((b * 4 + tile) * 1024 + trow) * 128 + lane * 16;
            auto put = [&](float (&d)[32], int i) {
                pin(d);
                uint32_t pk[8];
#pragma unroll
                for (int j = 0; j < 8; j++) pk[j] = pack2((d[4 * j] + d[4 * j + 2]) * rstd, (d[4 * j + 1] + d[4 * j + 3]) * rstd);
                if (i == 2) {
                    st_data(g + 2097152, pk[0], pk[1], pk[2], pk[3]);
                    st_data(g + 2097152 + 512, pk[4], pk[5], pk[6], pk[7]);
                    return;
                }
                stsm4(stg + i * 1024 + foff, pk[0], pk[1], pk[2], pk[3]);
                stsm4(stg + i * 1024 + (foff ^ 64), pk[4], pk[5], pk[6], pk[7]);
                __syncwarp();
                const uint4 u0 = lds128(stg + i * 1024 + lane * 16), u1 = lds128(stg + i * 1024 + 512 + lane * 16);
                stg128(g + i * 1048576, u0); stg128(g + i * 1048576 + 512, u1);
            };
            sp(d0, 16, a, w, 0);
            acq(17);
            sp(d1, 17, a, w, 0);
            gather_peer();
            acq(18);
            sp(d0, 18, a + 16, 0, 1);
            wg_wait<1>();
            rel(16); rel(17);
            acq(19);
            sp(d1, 19, a + 16, 0, 1);
            wg_wait<1>();
            rel(18);
            put(d0, 0);
            wg_wait<0>();
            rel(19);
            TS(37);
            put(d1, 1);
            bar_arrive(4, 288);
            TS(38);
            acq(20);
            sp(d0, 20, a, w, 0);
            acq(21);
            sp(d0, 21, a + 16, 0, 1);
            acq(22); acq(23);
            rel(22); rel(23);
            mbar_wait(bars + B_RST * 8, 0);
            wg_wait<0>();
            rel(20); rel(21);
            put(d0, 2);
            TS(12);
        }

        {
            constexpr float CS = 0.125f * 1.4426950408889634f;
            float sa[32], sb2[32], o[36];
            uint32_t pa[16], pb[16], q[16];
            float n0 = INFINITY, n1 = INFINITY;
            zero(o); zero(pa); zero(pb); zero(sb2);
            const uint32_t ones = sb + OFF_MISC + 2048;
            { const uint32_t c = w ? 0u : 0x3F803F80u; sts128(ones + tid * 16, c, c, c, c); }
            fence_async_smem();
            bar_sync(10, 256);
            const uint32_t vdesc = rdesc + ((((ones - rbase) >> 4) - 1) << 16);
            auto qk_issue = [&](float (&s)[32], uint32_t lo) {
                const uint64_t kd = mkdesc(lo);
                wg_fence();
#pragma unroll
                for (int k = 0; k < 4; k++) mma_qk(s, q[4 * k], q[4 * k + 1], q[4 * k + 2], q[4 * k + 3], kd + 2 * k, k != 0);
                wg_commit();
            };
            auto both_issue = [&](float (&s)[32], uint32_t klo, uint32_t (&pp)[16], uint32_t vlo) {
                const uint64_t kd = mkdesc(klo), vd = mkdesc(vlo);
                wg_fence();
#pragma unroll
                for (int k = 0; k < 4; k++) {
                    mma_pv(o, pp[4 * k], pp[4 * k + 1], pp[4 * k + 2], pp[4 * k + 3], vd - k * (128 * 65535));
                    mma_qk(s, q[4 * k], q[4 * k + 1], q[4 * k + 2], q[4 * k + 3], kd + 2 * k, k != 0);
                }
                wg_commit();
            };
            auto new_max = [&](float (&s)[32], int nj, float& x0, float& x1) {
                x0 = s[0]; x1 = s[2];
#pragma unroll
                for (int j = 0; j < nj; j++) {
                    x0 = fmaxf(x0, fmaxf(s[4 * j], s[4 * j + 1]));
                    x1 = fmaxf(x1, fmaxf(s[4 * j + 2], s[4 * j + 3]));
                }
                x0 = fmaxf(x0, __shfl_xor_sync(~0u, x0, 1)); x1 = fmaxf(x1, __shfl_xor_sync(~0u, x1, 1));
                x0 = fmaxf(x0, __shfl_xor_sync(~0u, x0, 2)); x1 = fmaxf(x1, __shfl_xor_sync(~0u, x1, 2));
                x0 = fminf(n0, fmaf(x0, -CS, -20.f)); x1 = fminf(n1, fmaf(x1, -CS, -20.f));
            };
            auto probs = [&](float (&s)[32], uint32_t (&pp)[16], bool ready, bool tail, auto wait) {
                uint32_t any = 0;
#pragma unroll
                for (int i = 0; i < 16; i++) {
                    pp[i] = pack2(ex2(fmaf(s[2 * i], CS, (i & 1) ? n1 : n0)), ex2(fmaf(s[2 * i + 1], CS, (i & 1) ? n1 : n0)));
                    any |= pp[i];
                }
                wg_wait<0>();
                pin(sa); pin(sb2); pin(o); pin(pa); pin(pb);
                if (__any_sync(~0u, (any & 0x40004000u) || !ready)) {
                    wait();
                    if (__any_sync(~0u, any & 0x40004000u)) {
                        if (tail) {
#pragma unroll
                            for (int i = 20; i < 32; i++) s[i] = -INFINITY;
                        }
                        float x0, x1;
                        new_max(s, 8, x0, x1);
                        const float sc0 = ex2(x0 - n0), sc1 = ex2(x1 - n1);
                        n0 = x0; n1 = x1;
#pragma unroll
                        for (int j = 0; j < 9; j++) { o[4 * j] *= sc0; o[4 * j + 1] *= sc0; o[4 * j + 2] *= sc1; o[4 * j + 3] *= sc1; }
#pragma unroll
                        for (int i = 0; i < 16; i++)
                            pp[i] = pack2(ex2(fmaf(s[2 * i], CS, (i & 1) ? n1 : n0)), ex2(fmaf(s[2 * i + 1], CS, (i & 1) ? n1 : n0)));
                    }
                }
            };
            {
                uint4 u[4];
                const unsigned char* src = g_kvq + 2097152 + (size_t)(abh * 1024 + qt * 64 + wq * 16) * 128 + lane * 16;
                spin(QGATE);
                ld_data<512>(u, src);
#pragma unroll
                for (int k = 0; k < 2; k++) {
                    q[8 * k] = u[k].x; q[8 * k + 1] = u[k + 2].x; q[8 * k + 2] = u[k].y; q[8 * k + 3] = u[k + 2].y;
                    q[8 * k + 4] = u[k].z; q[8 * k + 5] = u[k + 2].z; q[8 * k + 6] = u[k].w; q[8 * k + 7] = u[k + 2].w;
                }
                pin(q);
            }
            TS(40);
            acq(24);
            TS(13);
            qk_issue(sa, rdesc + (24 % NSLOT) * (SLOT >> 4));
            wg_wait<0>();
            pin(sa);
            {
                float x0, x1;
                new_max(sa, NJ0, x0, x1);
                n0 = x0; n1 = x1;
            }
            bar_arrive(6, 384);
            uint32_t vd = vdesc - (SLOT >> 4) * 65535u, kd = rdesc, vb = fbar + 8, kb = fbar;
            uint32_t vlast = vdesc - 4 * (SLOT >> 4) * 65535u, klast = rdesc + 4 * (SLOT >> 4) + 512;
            uint32_t kprev = fbar + 32, vprev = bars + (B_SINK - (B_EMPTY - B_FULL)) * 8;
#pragma unroll 1
            for (int it = 0; it < 4; it++) {
                both_issue(sb2, klast, pb, vlast);
                probs(sa, pa, mbar_test(vb, it < 2) & mbar_test(kb, it < 3), false, [&]() { mbar_wait(vb, it < 2); mbar_wait(kb, it < 3); });
                TS(41 + it * 4);
                if (lane == 0) mbar_arrive(kprev + (B_EMPTY - B_FULL) * 8);
                if (lane == 0) mbar_arrive(vprev + (B_EMPTY - B_FULL) * 8);
                both_issue(sa, kd, pa, vd);
                const int dv = it == 0 ? 2 : (it == 1 ? -3 : 1);
                kprev = kb; vprev = vb; vlast = vd - 512 * 65535u; klast = kd + 512;
                vd -= dv * (SLOT >> 4) * 65535u; vb += dv * 8;
                kd += (it == 2 ? -3 : 2) * (SLOT >> 4); kb = it == 2 ? vb : kb + 16;
                probs(sb2, pb, true, it == 3 && w == 1, []() {});
                TS(43 + it * 4);
            }
            wg_fence();
#pragma unroll
            for (int k = 0; k < 4; k++)
                mma_pv(o, pb[4 * k], pb[4 * k + 1], pb[4 * k + 2], pb[4 * k + 3], mkdesc(vlast - k * (128 * 65535) + (k > 1 ? w * ((k - 1) << 22) : 0)));
            wg_commit();
            const int row = wq * 16 + (lane >> 2);
            const uint32_t ml = sb + OFF_MISC;
            mbar_wait(bars + (B_RST + 1) * 8, 0);
            wg_wait<0>();
            pin(o); pin(pb); pin(sa); pin(sb2);
            rel(31);
            const float l0 = o[32], l1 = o[34];
            if (c4 == 0) { sts64f(ml + w * 512 + row * 8, n0, l0); sts64f(ml + w * 512 + row * 8 + 64, n1, l1); }
            TS(14);
            float mine[16];
#pragma unroll
            for (int j = 0; j < 4; j++) {
                if (w == 0) sts128f(H + j * 2048 + wt * 16, o[16 + 4 * j], o[17 + 4 * j], o[18 + 4 * j], o[19 + 4 * j]);
                else sts128f(H + 8192 + j * 2048 + wt * 16, o[4 * j], o[4 * j + 1], o[4 * j + 2], o[4 * j + 3]);
            }
#pragma unroll
            for (int i = 0; i < 16; i++) mine[i] = w == 0 ? o[i] : o[16 + i];
            bar_sync(10, 256);
            const float2 u0 = lds64f(ml + (w ^ 1) * 512 + row * 8), u1 = lds64f(ml + (w ^ 1) * 512 + row * 8 + 64);
            const float x0 = fminf(n0, u0.x), x1 = fminf(n1, u1.x);
            float a0 = ex2(x0 - n0), b0 = ex2(x0 - u0.x), a1 = ex2(x1 - n1), b1 = ex2(x1 - u1.x);
            const float i0 = __fdividef(1.f, fmaf(a0, l0, b0 * u0.y)), i1 = __fdividef(1.f, fmaf(a1, l1, b1 * u1.y));
            a0 *= i0; b0 *= i0; a1 *= i1; b1 *= i1;
            uint32_t pk[8];
#pragma unroll
            for (int j = 0; j < 4; j++) {
                const float4 v = lds128f(H + (w ^ 1) * 8192 + j * 2048 + wt * 16);
                pk[2 * j] = pack2(fmaf(a0, mine[4 * j], b0 * v.x), fmaf(a0, mine[4 * j + 1], b0 * v.y));
                pk[2 * j + 1] = pack2(fmaf(a1, mine[4 * j + 2], b1 * v.z), fmaf(a1, mine[4 * j + 3], b1 * v.w));
            }
            unsigned char* dst = g_o + (size_t)(b * 128 + qt * 8 + 2 * wq) * 4096 + ah * 1024 + w * 512 + lane * 16;
            st_data(dst, pk[0], pk[2], pk[4], pk[6]);
            st_data(dst + 4096, pk[1], pk[3], pk[5], pk[7]);
            if (tid == 0) asm volatile("red.relaxed.gpu.global.add.u32 [%0], 1;" ::"l"(&g_epoch[blockIdx.x * FS]) : "memory");
            TS(15);
        }

        {
            acq(32); acq(33); acq(34);
            uint4 u[8];
            ld_data<512>(u, g_o + (size_t)(b * 128 + pt * 4 + wq) * 4096 + lane * 16);
#pragma unroll
            for (int i = 0; i < 8; i++) { a[4 * i] = u[i].x; a[4 * i + 1] = u[i].y; a[4 * i + 2] = u[i].z; a[4 * i + 3] = u[i].w; }
            TS(16);
            sp(d0, 32, a, 0, 0);
            sp(d0, 33, a + 16, 0, 1);
            residual(32);
            TS(17);
        }
    }

    cluster_arrive();
    TS(24);
    {
        const float rstd = rsq(fmaxf(fmaf(-mean, mean, msq), 0.f) + 1e-5f), nb = -mean * rstd;
#pragma unroll
        for (int j = 0; j < 8; j++) xr[j] = pack2(fmaf(v[2 * j], rstd, nb), fmaf(v[2 * j + 1], rstd, nb));
        const uint32_t stg = P + 16384 + warp * 1024;
        stsm4(stg + foff, xr[0], xr[1], xr[2], xr[3]);
        stsm4(stg + (foff ^ 64), xr[4], xr[5], xr[6], xr[7]);
        __syncwarp();
        const uint32_t src = stg + (lane >> 3) * 128 + (((lane & 7) ^ (lane >> 3)) << 4);
        const uint4 u0 = lds128(src), u1 = lds128((src + 512) ^ 64);
        __nv_bfloat16* dst = p.out + (size_t)(b * T_ + trow + (lane >> 3)) * 256 + tile * 64 + (lane & 7) * 8;
        if (trow < T_) { stg128(dst, u0); stg128(dst + 4 * 256, u1); }
    }
    TS(25);
    TG(31);
    TSDUMP();
    cluster_wait();
}

typedef CUresult (*EncodeFn)(CUtensorMap*, CUtensorMapDataType, cuuint32_t, void*, const cuuint64_t*, const cuuint64_t*,
                             const cuuint32_t*, const cuuint32_t*, CUtensorMapInterleave, CUtensorMapSwizzle,
                             CUtensorMapL2promotion, CUtensorMapFloatOOBfill);

}

extern "C" void kernel_launch(void* const* d_in, const int* in_sizes, int n_in, void* d_out, int out_size) {
    static EncodeFn encode = nullptr;
    if (!encode) {
        void* fn = nullptr;
        cudaDriverEntryPointQueryResult qr;
        cudaGetDriverEntryPoint("cuTensorMapEncodeTiled", &fn, cudaEnableDefault, &qr);
        encode = (EncodeFn)fn;
        cudaFuncSetAttribute(conformer_kernel, cudaFuncAttributeMaxDynamicSharedMemorySize, SMEM_LAUNCH);
    }
    Params p;
    const cuuint32_t ones[5] = {1, 1, 1, 1, 1};
    const int idx[8] = {1, 2, 3, 4, 5, 7, 8, 9};
    const int rows[8] = {256, 1024, 256, 256, 256, 256, 256, 1024};
    const int cols[8] = {1024, 256, 768, 256, 512, 256, 1024, 256};
    for (int i = 0; i < 8; i++) {
        const cuuint64_t pitch = (cuuint64_t)cols[i] * 2;
        const cuuint64_t dims[5] = {(cuuint64_t)cols[i], 2, 2, 4, (cuuint64_t)rows[i] / 16};
        const cuuint64_t strides[4] = {pitch, pitch * 8, pitch * 2, pitch * 16};
        const cuuint32_t box[5] = {64, 2, 2, 4, 8};
        encode(&p.tm[i], CU_TENSOR_MAP_DATA_TYPE_BFLOAT16, 5, d_in[idx[i]], dims, strides, box, ones, CU_TENSOR_MAP_INTERLEAVE_NONE,
               CU_TENSOR_MAP_SWIZZLE_128B, CU_TENSOR_MAP_L2_PROMOTION_L2_128B, CU_TENSOR_MAP_FLOAT_OOB_FILL_NONE);
        p.w[i] = (const char*)d_in[idx[i]];
    }
    {
        void* kv = nullptr;
        cudaGetSymbolAddress(&kv, g_kvq);
        const cuuint64_t dims[2] = {64, 16384};
        const cuuint64_t strides[1] = {128};
        const cuuint32_t box[2] = {64, 128};
        encode(&p.tm[8], CU_TENSOR_MAP_DATA_TYPE_BFLOAT16, 2, kv, dims, strides, box, ones, CU_TENSOR_MAP_INTERLEAVE_NONE,
               CU_TENSOR_MAP_SWIZZLE_NONE, CU_TENSOR_MAP_L2_PROMOTION_L2_128B, CU_TENSOR_MAP_FLOAT_OOB_FILL_NONE);
    }
    p.x = (const __nv_bfloat16*)d_in[0];
    p.dw = (const __nv_bfloat16*)d_in[6];
    p.out = (__nv_bfloat16*)d_out;
    p.zero = 0;
    conformer_kernel<<<NCTA, NTHREADS, SMEM_LAUNCH>>>(p);
}
```

```cpp
#include <cuda_runtime.h>
#include <cuda_bf16.h>
#include <cuda.h>
#include <stdint.h>

namespace {

constexpr int T_ = 1000;
constexpr int NCTA = 128;
constexpr int NTHREADS = 512;
constexpr int NSLOT = 5;
constexpr int SLOT = 16384;
constexpr int NLOADS = 56;

constexpr uint32_t OFF_RING = 0;
constexpr uint32_t OFF_P = 163840;
constexpr uint32_t OFF_H = 188416;
constexpr uint32_t OFF_MISC = 221184;
constexpr uint32_t OFF_BARS = 229888;
constexpr uint32_t SMEM_BYTES = 230400;
constexpr uint32_t GCH = 6144;
constexpr uint32_t HCH = 4096;

constexpr int B_FULL = 0, B_EMPTY = 10, B_XA = 20  , B_XB = 25  , B_INB = 29  , B_SR = 33,
              B_RST = 34  , B_RDY = 36  , B_SINK = 42, B_HALO = 43  , NBARS = 47;

#define KD2 300u
#define KD3 500u
#define QGATE 500u
#define BACKOFF 0u
#define KFS 8
#define KDELAY 300u
#define NJ0 2
#define HDELAY 200u
#define LATE 7
#define TURN 0
#define EAGER 0x4755
constexpr int FS = 8;

struct Params {
    CUtensorMap tm[9];
    const char* w[8];
    const __nv_bfloat16* x;
    const __nv_bfloat16* dw;
    __nv_bfloat16* out;
    uint32_t zero;
};

__device__ __align__(1024) unsigned char g_kvq[3 * 8 * 1024 * 128];
__device__ __align__(1024) unsigned char g_o[2 * 128 * 4096];
__device__ uint4 g_halo[64 * 4 * 2 * 64];
__device__ __align__(128) uint32_t g_flag_kv[8 * 32 * KFS];
__device__ uint32_t g_reset[4 * 32];
__device__ uint32_t g_epoch[NCTA * FS];

#define TS(i) do { } while (0)
#define TSW(i) do { } while (0)
#define TG(i) do { } while (0)
#define TSINIT() do { } while (0)
#define TSDUMP() do { } while (0)
constexpr uint32_t SMEM_LAUNCH = SMEM_BYTES;

__device__ __forceinline__ uint32_t smem_u32(const void* p) { return (uint32_t)__cvta_generic_to_shared(p); }
__device__ __forceinline__ void mbar_init(uint32_t b, uint32_t c) { asm volatile("mbarrier.init.shared::cta.b64 [%0], %1;" ::"r"(b), "r"(c) : "memory"); }
__device__ __forceinline__ void mbar_arrive(uint32_t b) { asm volatile("mbarrier.arrive.shared::cta.b64 _, [%0];" ::"r"(b) : "memory"); }
__device__ __forceinline__ void mbar_arrive_tx(uint32_t b, uint32_t tx) { asm volatile("mbarrier.arrive.expect_tx.shared::cta.b64 _, [%0], %1;" ::"r"(b), "r"(tx) : "memory"); }
__device__ __forceinline__ void mbar_wait(uint32_t b, uint32_t ph) {
    asm volatile("{\n.reg .pred p, q;\n.reg .u32 c;\nmov.u32 c, 0;\n"
                 "MW_LOOP:\n.pragma \"nounroll\";\n"
                 "mbarrier.try_wait.parity.shared::cta.b64 p, [%0], %1;\n"
                 "add.u32 c, c, 1;\nsetp.lt.u32 q, c, 65536;\nnot.pred p, p;\nand.pred p, p, q;\n@p bra MW_LOOP;\n}"
                 ::"r"(b), "r"(ph) : "memory");
}
__device__ __forceinline__ bool mbar_test(uint32_t b, uint32_t ph) {
    uint32_t ok;
    asm volatile("{\n.reg .pred p;\nmbarrier.test_wait.parity.shared::cta.b64 p, [%1], %2;\nselp.u32 %0, 1, 0, p;\n}" : "=r"(ok) : "r"(b), "r"(ph) : "memory");
    return ok;
}
__device__ __forceinline__ uint32_t mapa(uint32_t a, uint32_t r) { uint32_t o; asm("mapa.shared::cluster.u32 %0, %1, %2;" : "=r"(o) : "r"(a), "r"(r)); return o; }
__device__ __forceinline__ void fence_async_smem() { asm volatile("fence.proxy.async.shared::cta;" ::: "memory"); }
__device__ __forceinline__ void fence_async_global() { asm volatile("fence.proxy.async.global;" ::: "memory"); }
__device__ __forceinline__ void bar_sync(int id, int n) { asm volatile("bar.sync %0, %1;" ::"r"(id), "r"(n) : "memory"); }
__device__ __forceinline__ void bar_arrive(int id, int n) { asm volatile("bar.arrive %0, %1;" ::"r"(id), "r"(n) : "memory"); }
__device__ __forceinline__ void cluster_arrive() { asm volatile("barrier.cluster.arrive.relaxed.aligned;" ::: "memory"); }
__device__ __forceinline__ void cluster_wait() { asm volatile("barrier.cluster.wait.aligned;" ::: "memory"); }

__device__ __forceinline__ void ring_load(uint32_t dst, const CUtensorMap* tm, int col, int row16, uint32_t bar) {
    asm volatile("{\n.reg .pred p;\nelect.sync _|p, 0xffffffff;\n"
                 "@p mbarrier.arrive.expect_tx.shared::cta.b64 _, [%2], 16384;\n"
                 "@p cp.async.bulk.tensor.5d.shared::cluster.global.mbarrier::complete_tx::bytes [%0], [%1, {%3, 0, 0, 0, %4}], [%2];\n}"
                 ::"r"(dst), "l"(tm), "r"(bar), "r"(col), "r"(row16) : "memory");
}
__device__ __forceinline__ void ring_load_both(uint32_t dst, const CUtensorMap* tm, int c1, uint32_t bar) {
    asm volatile("{\n.reg .pred p;\nelect.sync _|p, 0xffffffff;\n"
                 "@p cp.async.bulk.tensor.2d.shared::cluster.global.mbarrier::complete_tx::bytes.multicast::cluster [%0], [%1, {0, %3}], [%2], %4;\n}"
                 ::"r"(dst), "l"(tm), "r"(bar), "r"(c1), "h"((uint16_t)3) : "memory");
}
__device__ __forceinline__ void mbar_arrive_peer(uint32_t b) { asm volatile("mbarrier.arrive.relaxed.cluster.shared::cluster.b64 _, [%0];" ::"r"(b) : "memory"); }
__device__ __forceinline__ void prefetch_l2(const void* src, uint32_t bytes) {
    asm volatile("cp.async.bulk.prefetch.L2.global [%0], %1;" ::"l"(src), "r"(bytes) : "memory");
}
__device__ __forceinline__ void peer_copy(uint32_t dst, uint32_t src, uint32_t bytes, uint32_t rbar) {
    asm volatile("{\n.reg .pred p;\nelect.sync _|p, 0xffffffff;\n"
                 "@p cp.async.bulk.shared::cluster.shared::cta.mbarrier::complete_tx::bytes [%0], [%1], %2, [%3];\n}"
                 ::"r"(dst), "r"(src), "r"(bytes), "r"(rbar) : "memory");
}
__device__ __forceinline__ void st_async4(uint32_t dst, uint32_t a, uint32_t b, uint32_t c, uint32_t d, uint32_t bar) {
    asm volatile("st.async.shared::cluster.mbarrier::complete_tx::bytes.v4.b32 [%0], {%1,%2,%3,%4}, [%5];" ::"r"(dst), "r"(a), "r"(b), "r"(c), "r"(d), "r"(bar) : "memory");
}
__device__ __forceinline__ void st_async2f(uint32_t dst, float a, float b, uint32_t bar) {
    asm volatile("st.async.shared::cluster.mbarrier::complete_tx::bytes.v2.f32 [%0], {%1,%2}, [%3];" ::"r"(dst), "f"(a), "f"(b), "r"(bar) : "memory");
}
__device__ __forceinline__ void stsm4(uint32_t a, uint32_t r0, uint32_t r1, uint32_t r2, uint32_t r3) {
    asm volatile("stmatrix.sync.aligned.m8n8.x4.shared.b16 [%0], {%1,%2,%3,%4};" ::"r"(a), "r"(r0), "r"(r1), "r"(r2), "r"(r3) : "memory");
}
__device__ __forceinline__ void ldsm4(uint32_t a, uint32_t& r0, uint32_t& r1, uint32_t& r2, uint32_t& r3) {
    asm volatile("ldmatrix.sync.aligned.m8n8.x4.shared.b16 {%0,%1,%2,%3}, [%4];" : "=r"(r0), "=r"(r1), "=r"(r2), "=r"(r3) : "r"(a) : "memory");
}
__device__ __forceinline__ uint4 lds128(uint32_t a) { uint4 v; asm volatile("ld.shared.v4.b32 {%0,%1,%2,%3}, [%4];" : "=r"(v.x), "=r"(v.y), "=r"(v.z), "=r"(v.w) : "r"(a) : "memory"); return v; }
__device__ __forceinline__ float4 lds128f(uint32_t a) { float4 v; asm volatile("ld.shared.v4.f32 {%0,%1,%2,%3}, [%4];" : "=f"(v.x), "=f"(v.y), "=f"(v.z), "=f"(v.w) : "r"(a) : "memory"); return v; }
__device__ __forceinline__ float2 lds64f(uint32_t a) { float2 v; asm volatile("ld.shared.v2.f32 {%0,%1}, [%2];" : "=f"(v.x), "=f"(v.y) : "r"(a) : "memory"); return v; }
__device__ __forceinline__ uint32_t lds32(uint32_t a) { uint32_t v; asm volatile("ld.shared.b32 %0, [%1];" : "=r"(v) : "r"(a) : "memory"); return v; }
__device__ __forceinline__ void sts128(uint32_t a, uint32_t x, uint32_t y, uint32_t z, uint32_t w) { asm volatile("st.shared.v4.b32 [%0], {%1,%2,%3,%4};" ::"r"(a), "r"(x), "r"(y), "r"(z), "r"(w) : "memory"); }
__device__ __forceinline__ void sts128f(uint32_t a, float x, float y, float z, float w) { asm volatile("st.shared.v4.f32 [%0], {%1,%2,%3,%4};" ::"r"(a), "f"(x), "f"(y), "f"(z), "f"(w) : "memory"); }
__device__ __forceinline__ void sts64f(uint32_t a, float x, float y) { asm volatile("st.shared.v2.f32 [%0], {%1,%2};" ::"r"(a), "f"(x), "f"(y) : "memory"); }
__device__ __forceinline__ void sts32(uint32_t a, uint32_t x) { asm volatile("st.shared.b32 [%0], %1;" ::"r"(a), "r"(x) : "memory"); }
__device__ __forceinline__ void stg128(void* p, uint4 v) { asm volatile("st.global.v4.b32 [%0], {%1,%2,%3,%4};" ::"l"(p), "r"(v.x), "r"(v.y), "r"(v.z), "r"(v.w) : "memory"); }

__device__ __forceinline__ uint32_t pack2(float lo, float hi) { uint32_t r; asm("cvt.rn.bf16x2.f32 %0, %1, %2;" : "=r"(r) : "f"(hi), "f"(lo)); return r; }
__device__ __forceinline__ float blo(uint32_t v) { return __uint_as_float(v << 16); }
__device__ __forceinline__ float bhi(uint32_t v) { return __uint_as_float(v & 0xffff0000u); }
__device__ __forceinline__ uint32_t hmul2(uint32_t a, uint32_t b) { uint32_t r; asm("mul.rn.bf16x2 %0, %1, %2;" : "=r"(r) : "r"(a), "r"(b)); return r; }
__device__ __forceinline__ uint32_t hsub2(uint32_t a, uint32_t b) { uint32_t r; asm("sub.rn.bf16x2 %0, %1, %2;" : "=r"(r) : "r"(a), "r"(b)); return r; }
__device__ __forceinline__ uint32_t hfma2(uint32_t a, uint32_t b, uint32_t c) { uint32_t r; asm("fma.rn.bf16x2 %0, %1, %2, %3;" : "=r"(r) : "r"(a), "r"(b), "r"(c)); return r; }
__device__ __forceinline__ float tanh_fast(float x) { float r; asm("tanh.approx.f32 %0, %1;" : "=f"(r) : "f"(x)); return r; }
__device__ __forceinline__ float rsq(float x) { float r; asm("rsqrt.approx.ftz.f32 %0, %1;" : "=f"(r) : "f"(x)); return r; }
__device__ __forceinline__ float ex2(float x) { float r; asm("ex2.approx.ftz.f32 %0, %1;" : "=f"(r) : "f"(x)); return r; }

__device__ __forceinline__ uint32_t ld_relaxed(const uint32_t* p) {
    uint32_t v;
    asm volatile("ld.relaxed.gpu.global.u32 %0, [%1];" : "=r"(v) : "l"(p) : "memory");
    return v;
}
__device__ __forceinline__ uint32_t clock32() { uint32_t c; asm volatile("mov.u32 %0, %%clock;" : "=r"(c)::"memory"); return c; }
__device__ __forceinline__ void spin(uint32_t clks) {
    const uint32_t t0 = clock32();
    while (clock32() - t0 < clks) {}
}
__device__ __forceinline__ void flag_wait(const uint32_t* p, uint32_t e, bool mine) {
#pragma unroll 1
    for (int i = 0; i < (1 << 19); i++) {
        if (mine) mine = ld_relaxed(p) != e;
        if (!__any_sync(~0u, mine)) break;
        if (BACKOFF) spin(BACKOFF);
    }
    asm volatile("fence.acquire.gpu;" ::: "memory");
    fence_async_global();
}
__device__ __forceinline__ void st_data(void* p, uint32_t x, uint32_t y, uint32_t z, uint32_t w) {
    asm volatile("st.relaxed.gpu.global.v4.b32 [%0], {%1,%2,%3,%4};" ::"l"(p), "r"(x), "r"(y), "r"(z), "r"(w) : "memory");
}
template <int STRIDE, int N>
__device__ __forceinline__ void ld_data(uint4 (&v)[N], const unsigned char* p) {
    int it = 0;
    bool again;
#pragma unroll 1
    do {
        uint32_t m = 0;
#pragma unroll
        for (int i = 0; i < N; i++)
            asm volatile("ld.relaxed.gpu.global.v4.b32 {%0,%1,%2,%3}, [%4];" : "=r"(v[i].x), "=r"(v[i].y), "=r"(v[i].z), "=r"(v[i].w) : "l"(p + i * STRIDE) : "memory");
#pragma unroll
        for (int i = 0; i < N; i++) m = __vimax3_u32(__vimax3_u32(v[i].x, v[i].y, v[i].z), v[i].w, m);
        again = __any_sync(~0u, m == ~0u) && ++it < (1 << 16);
    } while (again);
}
__device__ __forceinline__ uint32_t ld_epoch() { return ld_relaxed(&g_epoch[blockIdx.x * FS]) + 1; }
__device__ __forceinline__ void flag_set(uint32_t* p, uint32_t e) { asm volatile("st.release.gpu.global.u32 [%0], %1;" ::"l"(p), "r"(e) : "memory"); }

__device__ __forceinline__ uint32_t desc_lo(uint32_t addr) { return ((addr & 0x3FFFF) >> 4) | 0x10000u; }
__device__ __forceinline__ uint64_t mkdesc(uint32_t lo) { return (uint64_t)lo | (0x40000040ull << 32); }
__device__ __forceinline__ void wg_fence() { asm volatile("wgmma.fence.sync.aligned;" ::: "memory"); }
__device__ __forceinline__ void wg_commit() { asm volatile("wgmma.commit_group.sync.aligned;" ::: "memory"); }
template <int N> __device__ __forceinline__ void wg_wait() { asm volatile("wgmma.wait_group.sync.aligned %0;" ::"n"(N) : "memory"); }
template <int N> __device__ __forceinline__ void pin(float (&d)[N]) {
#pragma unroll
    for (int i = 0; i < N; i++) asm volatile("" : "+f"(d[i])::"memory");
}
template <int N> __device__ __forceinline__ void pin(uint32_t (&d)[N]) {
#pragma unroll
    for (int i = 0; i < N; i++) asm volatile("" : "+r"(d[i])::"memory");
}

template <typename Tp, int N> __device__ __forceinline__ void zero(Tp (&d)[N]) {
#pragma unroll
    for (int i = 0; i < N; i++) d[i] = 0;
    pin(d);
}

#define F4(d, i) "+f"(d[i]), "+f"(d[i + 1]), "+f"(d[i + 2]), "+f"(d[i + 3])
#define F16(d, i) F4(d, i), F4(d, i + 4), F4(d, i + 8), F4(d, i + 12)

__device__ __forceinline__ void mma_sp(float (&d)[32], const uint32_t* a, uint64_t b, uint32_t meta, int acc) {
    asm volatile("{.reg .pred p; setp.ne.b32 p, %38, 0;\n"
                 "wgmma.mma_async.sp.sync.aligned.m64n64k32.f32.bf16.bf16 {%0,%1,%2,%3,%4,%5,%6,%7,%8,%9,%10,%11,%12,%13,%14,%15,%16,%17,%18,%19,%20,%21,%22,%23,%24,%25,%26,%27,%28,%29,%30,%31}, "
                 "{%32,%33,%34,%35}, %36, %37, 0, p, 1, 1, 1;}\n"
                 : F16(d, 0), F16(d, 16) : "r"(a[0]), "r"(a[1]), "r"(a[2]), "r"(a[3]), "l"(b), "r"(meta), "r"(acc));
}
__device__ __forceinline__ void mma_qk(float (&d)[32], uint32_t a0, uint32_t a1, uint32_t a2, uint32_t a3, uint64_t b, int acc) {
    asm volatile("{.reg .pred p; setp.ne.b32 p, %37, 0;\n"
                 "wgmma.mma_async.sync.aligned.m64n64k16.f32.bf16.bf16 {%0,%1,%2,%3,%4,%5,%6,%7,%8,%9,%10,%11,%12,%13,%14,%15,%16,%17,%18,%19,%20,%21,%22,%23,%24,%25,%26,%27,%28,%29,%30,%31}, "
                 "{%32,%33,%34,%35}, %36, p, 1, 1, 0;}\n"
                 : F16(d, 0), F16(d, 16) : "r"(a0), "r"(a1), "r"(a2), "r"(a3), "l"(b), "r"(acc));
}
__device__ __forceinline__ void mma_pv(float (&d)[36], uint32_t a0, uint32_t a1, uint32_t a2, uint32_t a3, uint64_t b) {
    asm volatile("wgmma.mma_async.sync.aligned.m64n72k16.f32.bf16.bf16 {%0,%1,%2,%3,%4,%5,%6,%7,%8,%9,%10,%11,%12,%13,%14,%15,%16,%17,%18,%19,%20,%21,%22,%23,%24,%25,%26,%27,%28,%29,%30,%31,%32,%33,%34,%35}, "
                 "{%36,%37,%38,%39}, %40, 1, 1, 1, 1;\n"
                 : F16(d, 0), F16(d, 16), F4(d, 32) : "r"(a0), "r"(a1), "r"(a2), "r"(a3), "l"(b));
}

__device__ __forceinline__ uint32_t load_code(int n, int r, int w) {
    const int tile = 2 * r + w;
    int m, col, row;
    if (n < 16 || n >= 40) {
        const int k = n < 16 ? n : n - 40;
        m = n < 16 ? 0 : 6;
        if (k < 8) { col = 4 * tile + (k >> 1); row = (k & 1) ^ r; }
        else { m++; col = tile ^ (3 - ((k - 8) >> 1)); row = 2 * tile + (k & 1); }
    } else if (n < 32) {
        const int k = n - 16;
        m = 2;
        if (k < 4) { col = tile + ((k & 1) ? 8 : 4); row = (k >> 1) ^ r; }
        else { col = tile; row = (k & 1) ^ r; }
    } else if (n < 34) { m = 3; col = tile; row = n - 32; }
    else if (n < 38) { const int k = n - 34; m = 4; col = tile + 4 * (k & 1); row = (k >> 1) ^ r; }
    else { m = 5; col = tile; row = (n & 1) ^ r; }
    return m | (col << 4) | (row << 8);
}

__global__ void __cluster_dims__(2, 1, 1) __launch_bounds__(NTHREADS, 1)
conformer_kernel(const __grid_constant__ Params p) {
    extern __shared__ __align__(1024) unsigned char smem_raw[];
    const uint32_t sb = smem_u32(smem_raw);
    const uint32_t bars = sb + OFF_BARS;
    const int tid = threadIdx.x;
    const int lane = tid & 31;
    const int warp = __shfl_sync(~0u, tid >> 5, 0);
    const int r = blockIdx.x & 1;
    const int pair = blockIdx.x >> 1;
    const int b = pair >> 5, pt = pair & 31;
    const int ah = pt >> 3, qt = (pt & 7) * 2 + r;
    const int abh = b * 4 + ah;

    TG(30);
    TSINIT();
    TS(0);
    const uint32_t P = sb + OFF_P, H = sb + OFF_H;

    if (warp >= 8) {
        asm volatile("setmaxnreg.dec.sync.aligned.u32 48;");
        if (warp >= 12) {
            cluster_arrive();
            cluster_wait();
            const int ut = tid & 127;
            const uint32_t target = ld_epoch() * 64;
            auto reset_done = [&](int k) {
                bar_sync(11, 128);
                if (ut == 0) {
                    asm volatile("red.release.gpu.global.add.u32 [%0], 1;" ::"l"(&g_reset[(2 * b + k) * 32]) : "memory");
#pragma unroll 1
                    for (int i = 0; i < (1 << 20) && ld_relaxed(&g_reset[(2 * b + k) * 32]) != target; i++) __nanosleep(100);
                    asm volatile("fence.acquire.gpu;" ::: "memory");
                    mbar_arrive(bars + (B_RST + k) * 8);
                }
                __syncwarp();
                TS(13 + k);
            };
#pragma unroll
            for (int i = 0; i < 4; i++)
                st_data(g_kvq + 2097152 + (size_t)((b * 4 + 2 * r + (i >> 1)) * 1024 + pt * 32) * 128 + (i & 1) * 2048 + ut * 16, ~0u, ~0u, ~0u, ~0u);
            reset_done(0);
            bar_sync(6, 384);
#pragma unroll
            for (int i = 0; i < 4; i++) {
                st_data(g_o + (size_t)(b * 128 + qt * 8 + 2 * i + (ut >> 6)) * 4096 + ah * 1024 + (ut & 63) * 16, ~0u, ~0u, ~0u, ~0u);
                if (i < 2) st_data(&g_halo[(pair * 4 + 2 * r + i) * 128 + ut], ~0u, ~0u, ~0u, ~0u);
            }
            reset_done(1);
            const int side = warp & 1, wg = (warp >> 1) & 1, np = side ? pt + 1 : pt - 1;
            const unsigned char* src = reinterpret_cast<const unsigned char*>(&g_halo[(((b * 32 + np) * 4 + 2 * r + wg) * 2 + (side ^ 1)) * 64 + lane]);
            const uint32_t dst = H + 16384 + wg * GCH + side * 5120 + (lane & 7) * 128 + (((lane >> 3) ^ (lane & 7)) << 4);
            uint4 hv[2] = {make_uint4(0, 0, 0, 0), make_uint4(0, 0, 0, 0)};
            bar_sync(8 + wg, 192);
            if (np >= 0 && np < 32) {
                spin(HDELAY);
                ld_data<512>(hv, src);
            }
            stsm4(dst, hv[0].x, hv[0].y, hv[0].z, hv[0].w);
            stsm4(dst ^ 64, hv[1].x, hv[1].y, hv[1].z, hv[1].w);
            __syncwarp();
            if (lane == 0) mbar_arrive(bars + (B_HALO + (warp & 3)) * 8);
            TS(4);
        } else if (warp < 10) {
            const int w = warp - 8;
            const uint32_t ring = sb + OFF_RING + w * NSLOT * SLOT;
            const uint32_t full = bars + (B_FULL + w * NSLOT) * 8;
            if (lane == 0) {
#pragma unroll
                for (int i = 0; i < NSLOT; i++) { mbar_init(full + i * 8, 1); mbar_init(full + (B_EMPTY - B_FULL + i) * 8, 4); }
                asm volatile("fence.mbarrier_init.release.cluster;" ::: "memory");
                fence_async_smem();
            }
            __syncwarp();
            cluster_arrive();
            TS(1);
#pragma unroll
            for (int n = 0; n < NSLOT; n++) {
                if (n == 1 || n == 2) bar_sync(12, 64);
                ring_load(ring + n * SLOT, &p.tm[0], 64 * (8 * r + 4 * w + (n >> 1)), 8 * ((n & 1) ^ r), full + n * 8);
            }
            TS(2);
            const uint32_t code = load_code(lane, r, w) | (load_code(lane + 32, r, w) << 16);
            cluster_wait();
            uint32_t s = 0, ph = 0;
            int n = NSLOT;
#pragma unroll 1
            for (int seg = 0; seg < 2; seg++) {
#pragma unroll 1
                for (; n < (seg == 0 ? 22 : NLOADS); n++) {
                    const uint32_t c = __shfl_sync(~0u, code, n) >> (n & 32 ? 16 : 0);
                    const CUtensorMap* tm = &p.tm[c & 15];
                    const uint32_t col = (c & 0xf0) * 4, row = (c & 0xff00) >> 5, dst = ring + s * SLOT;
                    mbar_wait(full + (B_EMPTY - B_FULL) * 8 + s * 8, ph + (((uint32_t)(size_t)tm | col | row | dst) & p.zero));
                    ring_load(dst, tm, col, row, full + s * 8);
                    if (++s == NSLOT) { s = 0; ph ^= 1; }
                }
                if (seg == 1) break;
                const uint32_t epoch = ld_epoch();
                const uint32_t rdy = bars + (B_RDY + 3 * w) * 8, prdy = mapa(rdy, r ^ 1);
                const int odd = r ^ w;
                const uint32_t* flags = g_flag_kv + (abh * 32 + lane) * KFS;
                auto kv_load = [&](uint32_t sl, int isv, int i) {
                    ring_load_both(ring + sl * SLOT, &p.tm[8], (isv * 64 + abh * 8 + 2 * i + w) * 128, full + sl * 8);
                };
#pragma unroll 1
                for (int i = 0; i < 2; i++) {
                    if (lane < 3 + i) {
                        const uint32_t sl = i ? lane : lane + 2;
                        mbar_wait(full + (B_EMPTY - B_FULL + sl) * 8, i ^ 1);
                        mbar_arrive_tx(full + sl * 8, (i || lane == 2) ? SLOT : 0);
                    }
                    __syncwarp();
                }
                if (lane == 0) mbar_arrive_peer(prdy);
                bar_sync(14, 96);
                spin(KDELAY);
                mbar_wait(rdy, 0);
                flag_wait(flags, epoch, (lane >> 2) == 2 * odd + w);
                TSW(5 + 2 * odd);
                if (!odd) { kv_load(4, 0, 0); bar_arrive(12, 64); }
                else bar_sync(12, 64);
                spin(w ? KD3 : KD2);
                kv_load(odd ^ 1, odd ^ 1, odd);
                flag_wait(flags, epoch, (lane >> 2) == 2 * odd + w + 4);
                mbar_wait(full + (odd ^ 1) * 8, 1);
                kv_load(2 + odd, odd, 2 - odd);
#pragma unroll 1
                for (int i = 0; i < 3; i++) {
                    const uint32_t sl = i ? i - 1 : 4, bo = i == 2 ? 16 : 8;
                    mbar_wait(full + (B_EMPTY - B_FULL + sl) * 8, i != 0);
                    if (lane == 0) mbar_arrive_tx(full + sl * 8, SLOT);
                    if ((i & 1) != odd) {
                        mbar_wait(rdy + bo, 0);
                        kv_load(sl, i != 0, 2 + odd);
                    } else if (lane == 0) mbar_arrive_peer(prdy + bo);
                    __syncwarp();
                }
                n = 32; s = 2; ph = 1;
            }
        } else if (warp == 10) {
            if (lane == 0) {
#pragma unroll
                for (int i = B_XA; i < NBARS; i++) mbar_init(bars + i * 8, 1);
#pragma unroll
                for (int i = B_XA; i <= B_SR; i++) mbar_arrive_tx(bars + i * 8, i < B_XB ? 512 : 8192);
                asm volatile("fence.mbarrier_init.release.cluster;" ::: "memory");
                fence_async_smem();
            }
            __syncwarp();
            cluster_arrive();
            cluster_wait();
        } else {
            const uint32_t kb = (lane < 2 || lane > 5) ? 4096 : (lane == 2 ? 3072 : (lane == 4 ? 2048 : 1024));
            const char* pf = p.w[lane & 7] + blockIdx.x * kb;
            cluster_arrive();
            cluster_wait();
            if (lane < 2) prefetch_l2(pf, kb);
            mbar_wait(bars + B_XA * 8, 0);
            if (lane == 2) prefetch_l2(pf, kb);
            if (lane >= 1 && lane < 9) asm volatile("prefetch.tensormap [%0];" ::"l"(&p.tm[lane]) : "memory");
            mbar_wait(bars + (B_FULL + 1) * 8, 1);
            if (lane > 2 && lane < 8) prefetch_l2(pf, kb);
            if (lane == 8 && blockIdx.x < 15) prefetch_l2(p.dw + blockIdx.x * 256, 512);
            const uint32_t epoch = ld_epoch();
            bar_sync(4, 288);
            if (lane < 16) flag_set(&g_flag_kv[((b * 4 + 2 * r + (lane >> 3)) * 32 + pt) * KFS + (lane & 7)], epoch);
            __syncwarp();
            bar_arrive(14, 96);
            TSW(8);
        }
        TSDUMP();
        return;
    }

    const int w = warp >> 2, wq = warp & 3;
    const int tile = 2 * r + w;
    const int wt = tid & 127;
    const int c4 = lane & 3;
    const int trow = pt * 32 + 8 * wq;
    uint32_t xr[8];
    {
        const uint32_t* xp = reinterpret_cast<const uint32_t*>(p.x + (size_t)(b * T_ + trow + (lane >> 2)) * 256 + tile * 64) + c4;
#pragma unroll
        for (int j = 0; j < 8; j++) xr[j] = trow < T_ ? __ldg(xp + 4 * j) : 0u;
    }
    cluster_arrive();
    asm volatile("setmaxnreg.inc.sync.aligned.u32 208;");
    const uint32_t rbase = sb + OFF_RING + w * NSLOT * SLOT, fbar = bars + (B_FULL + w * NSLOT) * 8;
    const uint32_t rdesc = desc_lo(rbase);
    auto acq = [&](int n) { mbar_wait(fbar + (n % NSLOT) * 8, (n / NSLOT) & 1); };
    auto rel = [&](int n) { if (lane == 0) mbar_arrive(fbar + (B_EMPTY - B_FULL + n % NSLOT) * 8); };
    const uint32_t foff = (lane & 7) * 128 + (((lane >> 3) ^ (lane & 7)) << 4);
    float v[16];
#pragma unroll
    for (int j = 0; j < 8; j++) { v[2 * j] = blo(xr[j]); v[2 * j + 1] = bhi(xr[j]); }
    const uint32_t xown = __shfl_sync(~0u, P + wt * 16 + tile * 4096, lane), xrem = __shfl_sync(~0u, P + wt * 16 + (r ^ 1) * 8192, lane);
    const uint32_t sbuf = __shfl_sync(~0u, sb + OFF_MISC + 1024 + (8 * wq + (lane >> 2)) * 32, lane);
    const uint32_t sown = __shfl_sync(~0u, sbuf + tile * 8, lane);
    const uint32_t peer = __shfl_sync(~0u, mapa(sb, r ^ 1) - sb, lane);
    const uint32_t meta = __shfl_sync(~0u, 0xEEEE4444u + p.zero, lane);
    cluster_wait();
    TS(56);
    float mean, msq;

#pragma unroll 1
    for (int ph = 0;; ph++) {
        uint4 o0, o1;
        {
            float s = 0.f, q = 0.f, s2 = 0.f, q2 = 0.f;
#pragma unroll
            for (int j = 0; j < 4; j++) {
                s += v[4 * j] + v[4 * j + 1]; s2 += v[4 * j + 2] + v[4 * j + 3];
                q += fmaf(v[4 * j], v[4 * j], v[4 * j + 1] * v[4 * j + 1]); q2 += fmaf(v[4 * j + 2], v[4 * j + 2], v[4 * j + 3] * v[4 * j + 3]);
            }
            s += s2; q += q2;
            const uint32_t xa = bars + (B_XA + ph) * 8;
            s += __shfl_xor_sync(~0u, s, 1); q += __shfl_xor_sync(~0u, q, 1);
            s += __shfl_xor_sync(~0u, s, 2); q += __shfl_xor_sync(~0u, q, 2);
            if (c4 == 0) st_async2f(sown + peer, s, q, xa + peer);
            if (c4 == 0) sts64f(sown, s, q);
#pragma unroll
            for (int j = 0; j < 8; j++) xr[j] = pack2(v[2 * j], v[2 * j + 1]);
            sts128(xown, xr[0], xr[1], xr[2], xr[3]);
            sts128(xown + 2048, xr[4], xr[5], xr[6], xr[7]);
            bar_sync(10, 256);
            o0 = lds128(xown ^ 4096); o1 = lds128((xown ^ 4096) + 2048);
            if (ph < 4) {
                st_async4(xown + peer, xr[0], xr[1], xr[2], xr[3], xa + (B_XB - B_XA) * 8 + peer);
                st_async4(xown + peer + 2048, xr[4], xr[5], xr[6], xr[7], xa + (B_XB - B_XA) * 8 + peer);
            }
            TS(57 + ph);
            if (ph == 0 || ph == 3) acq(0);
            mbar_wait(xa, 0);
            const float4 u0 = lds128f(sbuf), u1 = lds128f(sbuf + 16);
            mean = ((u0.x + u0.z) + (u1.x + u1.z)) * (1.f / 256.f);
            msq = ((u0.y + u0.w) + (u1.y + u1.w)) * (1.f / 256.f);
        }
        if (ph == 4) break;
        uint32_t a[32];
        const uint32_t mean2 = pack2(mean, mean);
        auto centre = [&](int i, const uint4& u) {
            a[i] = hsub2(u.x, mean2); a[i + 1] = hsub2(u.y, mean2); a[i + 2] = hsub2(u.z, mean2); a[i + 3] = hsub2(u.w, mean2);
        };
#pragma unroll
        for (int j = 0; j < 8; j++) a[j] = hsub2(xr[j], mean2);
        centre(8, o0); centre(12, o1);
        const float rstd = rsq(fmaxf(fmaf(-mean, mean, msq), 0.f) + 1e-5f);
        auto gather_peer = [&]() {
            mbar_wait(bars + (B_XB + ph) * 8, 0);
#pragma unroll
            for (int i = 0; i < 4; i++) centre(16 + 4 * i, lds128(xrem + i * 2048));
        };
        auto sp = [&](float (&d)[32], int n, const uint32_t* af, int flip, int acc) {
            const uint32_t lo = rdesc + p.zero * (ph + n + 1) + (n % NSLOT) * (SLOT >> 4);
            const uint64_t b0 = mkdesc(lo + flip * 512), b1 = mkdesc(lo + (flip ^ 1) * 512);
            wg_fence();
            mma_sp(d, af, b0, meta, acc);
            mma_sp(d, af + 4, b0 + 256, meta, 1);
            mma_sp(d, af + 8, b1, meta, 1);
            mma_sp(d, af + 12, b1 + 256, meta, 1);
            wg_commit();
        };
        float d0[32], d1[32];

        if (ph == 0 || ph == 3) {
            uint32_t h[32];
            const float rs = 0.5f * rstd;
            const uint32_t inb = bars + (B_INB + (ph & 2)) * 8, box = H + wt * 16;
            bool ready = true;
            auto step = [&](float (&d)[32], int n, const uint32_t* af, int flip, int acc, auto work) {
                if (!ready) acq(n);
                if (((TURN >> n) & 1) && w == 1) bar_sync(7, 256);
                sp(d, n, af, flip, acc);
                if (n > 0 && ((TURN >> (n - 1)) & 1) && w == 0) bar_arrive(7, 256);
                if (n < 15) ready = mbar_test(fbar + ((n + 1) % NSLOT) * 8, ((n + 1) / NSLOT) & 1);
                wg_wait<1>();
                if (n > 0 && !((EAGER >> (n - 1)) & 1)) rel(n - 1);
                const uint32_t tie = work() & p.zero;
                if ((EAGER >> n) & 1) {
                    if (p.zero < n + ph + 1) wg_wait<0>();
                    if (lane == 0) mbar_arrive(fbar + (B_EMPTY - B_FULL + n % NSLOT) * 8 + tie);
                }
            };
            auto none = []() { return 0u; };
            auto act = [&](float (&d)[32], int i) {
                pin(d);
#pragma unroll
                for (int j = 0; j < 8; j++) {
                    const float u0 = (d[4 * j] + d[4 * j + 2]) * rs, u1 = (d[4 * j + 1] + d[4 * j + 3]) * rs;
                    h[8 * i + j] = pack2(fmaf(u0, tanh_fast(u0), u0), fmaf(u1, tanh_fast(u1), u1));
                }
                return h[8 * i] | h[8 * i + 1] | h[8 * i + 2] | h[8 * i + 3] | h[8 * i + 4] | h[8 * i + 5] | h[8 * i + 6] | h[8 * i + 7];
            };
            auto send = [&](float (&d)[32], int x) {
                pin(d);
                uint32_t pk[8];
#pragma unroll
                for (int j = 0; j < 8; j++) pk[j] = pack2(d[4 * j] + d[4 * j + 2], d[4 * j + 1] + d[4 * j + 3]);
                const uint32_t ow = w ^ (x & 1), dst = box + (ow * 3 + x - 1) * 4096;
                if (x & 2) {
                    st_async4(dst + peer, pk[0], pk[1], pk[2], pk[3], inb + ow * 8 + peer);
                    st_async4(dst + peer + 2048, pk[4], pk[5], pk[6], pk[7], inb + ow * 8 + peer);
                } else {
                    sts128(dst, pk[0], pk[1], pk[2], pk[3]);
                    sts128(dst + 2048, pk[4], pk[5], pk[6], pk[7]);
                }
            };
            TS(1 + (ph & 2) * 10);
            step(d0, 0, a, w, 0, [&]() { gather_peer(); return 0u; });
            TS(32);
            step(d0, 1, a + 16, 0, 1, none);
            step(d1, 2, a, w, 0, [&]() { return act(d0, 0); });
            step(d1, 3, a + 16, 0, 1, none);
            step(d0, 4, a, w, 0, [&]() { return act(d1, 1); });
            TS(33);
            step(d0, 5, a + 16, 0, 1, none);
            step(d1, 6, a, w, 0, [&]() { return act(d0, 2); });
            step(d1, 7, a + 16, 0, 1, none);
            step(d0, 8, h, 0, 0, [&]() { return act(d1, 3); });
            TS(2 + (ph & 2) * 10);
            step(d0, 9, h + 16, 0, 1, none);
            step(d1, 10, h, 0, 0, [&]() { send(d0, 3); return 0u; });
            step(d1, 11, h + 16, 0, 1, none);
            step(d0, 12, h, 0, 0, [&]() { send(d1, 2); return 0u; });
            TS(34);
            step(d0, 13, h + 16, 0, 1, none);
            uint4 u[6];
            step(d1, 14, h, 0, 0, [&]() {
                send(d0, 1);
                mbar_wait(inb + w * 8, 0);
                bar_sync(10, 256);
#pragma unroll
                for (int i = 0; i < 6; i++) u[i] = lds128(box + w * 12288 + i * 2048);
                return u[0].x | u[1].x | u[2].x | u[3].x | u[4].x | u[5].x;
            });
            step(d1, 15, h + 16, 0, 1, none);
            mbar_wait(ph == 0 ? fbar + (16 % NSLOT) * 8 : inb + w * 8, ph == 0);
            uint32_t tie = 0;
#pragma unroll
            for (int i = 0; i < 2; i++) {
                const uint32_t p0[4] = {u[i].x, u[i].y, u[i].z, u[i].w}, p1[4] = {u[i + 2].x, u[i + 2].y, u[i + 2].z, u[i + 2].w}, p2[4] = {u[i + 4].x, u[i + 4].y, u[i + 4].z, u[i + 4].w};
#pragma unroll
                for (int j = 0; j < 4; j++) {
                    v[8 * i + 2 * j] = fmaf(0.5f, blo(p0[j]) + blo(p1[j]) + blo(p2[j]), blo(xr[4 * i + j]));
                    v[8 * i + 2 * j + 1] = fmaf(0.5f, bhi(p0[j]) + bhi(p1[j]) + bhi(p2[j]), bhi(xr[4 * i + j]));
                    tie |= __float_as_uint(v[8 * i + 2 * j]) | __float_as_uint(v[8 * i + 2 * j + 1]);
                }
            }
            if (__any_sync(~0u, tie & p.zero)) spin(1);
            wg_wait<0>();
            pin(d1);
            rel(15);
            TS(3 + (ph & 2) * 10);
#pragma unroll
            for (int j = 0; j < 8; j++) {
                v[2 * j] = fmaf(0.5f, d1[4 * j] + d1[4 * j + 2], v[2 * j]);
                v[2 * j + 1] = fmaf(0.5f, d1[4 * j + 1] + d1[4 * j + 3], v[2 * j + 1]);
            }
            continue;
        }

        auto residual = [&](int n) {
            wg_wait<1>();
            rel(n);
            wg_wait<0>();
            pin(d0);
            rel(n + 1);
#pragma unroll
            for (int j = 0; j < 8; j++) {
                v[2 * j] = d0[4 * j] + d0[4 * j + 2] + blo(xr[j]);
                v[2 * j + 1] = d0[4 * j + 1] + d0[4 * j + 3] + bhi(xr[j]);
            }
        };

        if (ph == 2) {
            TS(39);
            sp(d0, 34, a, w, 0);
            acq(35);
            sp(d1, 35, a, w, 0);
            acq(36); acq(37);
            gather_peer();
            sp(d0, 36, a + 16, 0, 1);
            sp(d1, 37, a + 16, 0, 1);
            wg_wait<2>();
            rel(34);
            if (!(LATE & 1)) rel(35);
            const int mir = wq < 2 ? 7 : 0;
            uint32_t dwr[15];
            {
                const uint32_t* dp = reinterpret_cast<const uint32_t*>(p.dw + tile * 64) + lane;
#pragma unroll
                for (int i = 0; i < 15; i++) dwr[i] = __ldg(dp + i * 128);
            }
            const float rs = trow < T_ ? 0.5f * rstd : 0.f;
            wg_wait<0>();
            pin(d0); pin(d1);
            if (!(LATE & 2)) { rel(36); rel(37); }
            TS(18);
            uint32_t pk[8];
#pragma unroll
            for (int j = 0; j < 8; j++) {
                const float u0 = (d0[4 * j] + d0[4 * j + 2]) * rs, u1 = (d0[4 * j + 1] + d0[4 * j + 3]) * rs;
                const float t0 = tanh_fast((d1[4 * j] + d1[4 * j + 2]) * rs), t1 = tanh_fast((d1[4 * j + 1] + d1[4 * j + 3]) * rs);
                pk[j] = pack2(fmaf(u0, t0, u0), fmaf(u1, t1, u1));
            }
            if (wq == 0 || wq == 3) {
                uint4* hp = &g_halo[((pair * 4 + tile) * 2 + (wq & 1)) * 64 + lane];
                st_data(hp, pk[0], pk[1], pk[2], pk[3]);
                st_data(hp + 32, pk[4], pk[5], pk[6], pk[7]);
            }
            const uint32_t gs = H + 16384 + w * GCH + wq * 1024;
            stsm4(gs + 1024 + foff, pk[0], pk[1], pk[2], pk[3]);
            stsm4(gs + 1024 + (foff ^ 64), pk[4], pk[5], pk[6], pk[7]);
            bar_sync(8 + w, 192);
            TS(26);
#pragma unroll
            for (int i = 0; i < 7; i++) {
                const uint32_t x = dwr[i], y = dwr[14 - i];
                dwr[i] = hmul2(mir ? y : x, 0x3F003F00u); dwr[14 - i] = hmul2(mir ? x : y, 0x3F003F00u);
            }
            dwr[7] = hmul2(dwr[7], 0x3F003F00u);
            uint32_t ca[8], cb[8];
            const int e = (wq & 1) * 4;
            const uint32_t lo = ((mir ^ e) * 144) ^ (lane * 4);
            const int dir = mir ? -1024 : 1024;
            const uint32_t gb = H + 16384 + w * GCH + (mir ? 3072 : 2048) + lo, sown_ = H + tile * HCH, so = sown_ + (mir ? 1024 : 2048) + lo;
            auto finish = [&](int i) {
                const float h0 = blo(ca[i]) + blo(cb[i]), h1 = bhi(ca[i]) + bhi(cb[i]);
                sts32((so + (i >> 2) * dir) ^ ((i & 3) * 144), pack2(fmaf(h0, tanh_fast(h0), h0), fmaf(h1, tanh_fast(h1), h1)));
            };
#pragma unroll
            for (int k = 0; k < 26; k++) {
                if (k == 19) {
#pragma unroll
                    for (int i = 0; i < 4; i++) finish(i);
                    fence_async_smem();
                    bar_sync(2 + w, 128);
                    if (wq == 0) peer_copy(mapa(sown_ + 1024, r ^ 1), sown_ + 1024, 2048, mapa(bars + B_SR * 8, r ^ 1));
                    acq(38); acq(39);
                    const uint32_t tie = ca[4] | ca[5] | ca[6] | ca[7] | cb[4] | cb[5] | cb[6];
                    mbar_wait(bars + (B_HALO + 2 * w + (wq >> 1)) * 8, __shfl_sync(~0u, tie & p.zero, 0));
                    if (LATE & 1) rel(35);
                    if (LATE & 2) { rel(36); rel(37); }
                    TS(27);
                }
                const uint32_t g = lds32((gb + (((k + 1) & 4) ? ((k + 1) >> 3) + (wq & 1) : ((k + 1) >> 3)) * dir) ^ (((k + 1) & 7) * 144));
#pragma unroll
                for (int i = 0; i < 8; i++) {
                    const int tap = k - (i & 3) - 2 * (i & 4);
                    if (tap == 0) ca[i] = hmul2(g, dwr[0]);
                    else if (tap > 0 && tap < 8) ca[i] = hfma2(g, dwr[tap], ca[i]);
                    else if (tap == 8) cb[i] = hmul2(g, dwr[8]);
                    else if (tap > 8 && tap < 15) cb[i] = hfma2(g, dwr[tap], cb[i]);
                }
            }
#pragma unroll
            for (int i = 4; i < 8; i++) finish(i);
            fence_async_smem();
            bar_sync(12 + (warp >> 1), 64);
            if (wq == 0 || wq == 3) peer_copy(mapa(sown_ + wq * 1024, r ^ 1), sown_ + wq * 1024, 1024, mapa(bars + B_SR * 8, r ^ 1));
            bar_sync(10, 256);
            TS(19);
            auto frags = [&](int i, int half) {
                const uint32_t src = H + 2 * half * HCH + wq * 1024;
#pragma unroll
                for (int k = 0; k < 4; k++) ldsm4(src + (k >> 1) * HCH + (foff ^ ((k & 1) * 64)), a[i + 4 * k], a[i + 4 * k + 1], a[i + 4 * k + 2], a[i + 4 * k + 3]);
            };
            frags(0, r);
            sp(d0, 38, a, 0, 0);
            mbar_wait(bars + B_SR * 8, 0);
            frags(16, r ^ 1);
            sp(d0, 39, a + 16, 0, 1);
            residual(38);
            TS(20);
            continue;
        }

        {
            TS(11);
            const uint32_t stg = H + warp * 2048;
            unsigned char* g = g_kvq + (size_t)((b * 4 + tile) * 1024 + trow) * 128 + lane * 16;
            auto put = [&](float (&d)[32], int i) {
                pin(d);
                uint32_t pk[8];
#pragma unroll
                for (int j = 0; j < 8; j++) pk[j] = pack2((d[4 * j] + d[4 * j + 2]) * rstd, (d[4 * j + 1] + d[4 * j + 3]) * rstd);
                if (i == 2) {
                    st_data(g + 2097152, pk[0], pk[1], pk[2], pk[3]);
                    st_data(g + 2097152 + 512, pk[4], pk[5], pk[6], pk[7]);
                    return;
                }
                stsm4(stg + i * 1024 + foff, pk[0], pk[1], pk[2], pk[3]);
                stsm4(stg + i * 1024 + (foff ^ 64), pk[4], pk[5], pk[6], pk[7]);
                __syncwarp();
                const uint4 u0 = lds128(stg + i * 1024 + lane * 16), u1 = lds128(stg + i * 1024 + 512 + lane * 16);
                stg128(g + i * 1048576, u0); stg128(g + i * 1048576 + 512, u1);
            };
            sp(d0, 16, a, w, 0);
            acq(17);
            sp(d1, 17, a, w, 0);
            gather_peer();
            acq(18);
            sp(d0, 18, a + 16, 0, 1);
            wg_wait<1>();
            rel(16); rel(17);
            acq(19);
            sp(d1, 19, a + 16, 0, 1);
            wg_wait<1>();
            rel(18);
            put(d0, 0);
            wg_wait<0>();
            rel(19);
            TS(37);
            put(d1, 1);
            bar_arrive(4, 288);
            TS(38);
            acq(20);
            sp(d0, 20, a, w, 0);
            acq(21);
            sp(d0, 21, a + 16, 0, 1);
            acq(22); acq(23);
            rel(22); rel(23);
            mbar_wait(bars + B_RST * 8, 0);
            wg_wait<0>();
            rel(20); rel(21);
            put(d0, 2);
            TS(12);
        }

        {
            constexpr float CS = 0.125f * 1.4426950408889634f;
            float sa[32], sb2[32], o[36];
            uint32_t pa[16], pb[16], q[16];
            float n0 = INFINITY, n1 = INFINITY;
            zero(o); zero(pa); zero(pb); zero(sb2);
            const uint32_t ones = sb + OFF_MISC + 2048;
            { const uint32_t c = w ? 0u : 0x3F803F80u; sts128(ones + tid * 16, c, c, c, c); }
            fence_async_smem();
            bar_sync(10, 256);
            const uint32_t vdesc = rdesc + ((((ones - rbase) >> 4) - 1) << 16);
            auto qk_issue = [&](float (&s)[32], uint32_t lo) {
                const uint64_t kd = mkdesc(lo);
                wg_fence();
#pragma unroll
                for (int k = 0; k < 4; k++) mma_qk(s, q[4 * k], q[4 * k + 1], q[4 * k + 2], q[4 * k + 3], kd + 2 * k, k != 0);
                wg_commit();
            };
            auto both_issue = [&](float (&s)[32], uint32_t klo, uint32_t (&pp)[16], uint32_t vlo) {
                const uint64_t kd = mkdesc(klo), vd = mkdesc(vlo);
                wg_fence();
#pragma unroll
                for (int k = 0; k < 4; k++) {
                    mma_pv(o, pp[4 * k], pp[4 * k + 1], pp[4 * k + 2], pp[4 * k + 3], vd - k * (128 * 65535));
                    mma_qk(s, q[4 * k], q[4 * k + 1], q[4 * k + 2], q[4 * k + 3], kd + 2 * k, k != 0);
                }
                wg_commit();
            };
            auto new_max = [&](float (&s)[32], int nj, float& x0, float& x1) {
                x0 = s[0]; x1 = s[2];
#pragma unroll
                for (int j = 0; j < nj; j++) {
                    x0 = fmaxf(x0, fmaxf(s[4 * j], s[4 * j + 1]));
                    x1 = fmaxf(x1, fmaxf(s[4 * j + 2], s[4 * j + 3]));
                }
                x0 = fmaxf(x0, __shfl_xor_sync(~0u, x0, 1)); x1 = fmaxf(x1, __shfl_xor_sync(~0u, x1, 1));
                x0 = fmaxf(x0, __shfl_xor_sync(~0u, x0, 2)); x1 = fmaxf(x1, __shfl_xor_sync(~0u, x1, 2));
                x0 = fminf(n0, fmaf(x0, -CS, -20.f)); x1 = fminf(n1, fmaf(x1, -CS, -20.f));
            };
            auto probs = [&](float (&s)[32], uint32_t (&pp)[16], bool ready, bool tail, auto wait) {
                uint32_t any = 0;
#pragma unroll
                for (int i = 0; i < 16; i++) {
                    pp[i] = pack2(ex2(fmaf(s[2 * i], CS, (i & 1) ? n1 : n0)), ex2(fmaf(s[2 * i + 1], CS, (i & 1) ? n1 : n0)));
                    any |= pp[i];
                }
                wg_wait<0>();
                pin(sa); pin(sb2); pin(o); pin(pa); pin(pb);
                if (__any_sync(~0u, (any & 0x40004000u) || !ready)) {
                    wait();
                    if (__any_sync(~0u, any & 0x40004000u)) {
                        if (tail) {
#pragma unroll
                            for (int i = 20; i < 32; i++) s[i] = -INFINITY;
                        }
                        float x0, x1;
                        new_max(s, 8, x0, x1);
                        const float sc0 = ex2(x0 - n0), sc1 = ex2(x1 - n1);
                        n0 = x0; n1 = x1;
#pragma unroll
                        for (int j = 0; j < 9; j++) { o[4 * j] *= sc0; o[4 * j + 1] *= sc0; o[4 * j + 2] *= sc1; o[4 * j + 3] *= sc1; }
#pragma unroll
                        for (int i = 0; i < 16; i++)
                            pp[i] = pack2(ex2(fmaf(s[2 * i], CS, (i & 1) ? n1 : n0)), ex2(fmaf(s[2 * i + 1], CS, (i & 1) ? n1 : n0)));
                    }
                }
            };
            {
                uint4 u[4];
                const unsigned char* src = g_kvq + 2097152 + (size_t)(abh * 1024 + qt * 64 + wq * 16) * 128 + lane * 16;
                spin(QGATE);
                ld_data<512>(u, src);
#pragma unroll
                for (int k = 0; k < 2; k++) {
                    q[8 * k] = u[k].x; q[8 * k + 1] = u[k + 2].x; q[8 * k + 2] = u[k].y; q[8 * k + 3] = u[k + 2].y;
                    q[8 * k + 4] = u[k].z; q[8 * k + 5] = u[k + 2].z; q[8 * k + 6] = u[k].w; q[8 * k + 7] = u[k + 2].w;
                }
                pin(q);
            }
            TS(40);
            acq(24);
            TS(13);
            qk_issue(sa, rdesc + (24 % NSLOT) * (SLOT >> 4));
            wg_wait<0>();
            pin(sa);
            {
                float x0, x1;
                new_max(sa, NJ0, x0, x1);
                n0 = x0; n1 = x1;
            }
            bar_arrive(6, 384);
            uint32_t vd = vdesc - (SLOT >> 4) * 65535u, kd = rdesc, vb = fbar + 8, kb = fbar;
            uint32_t vlast = vdesc - 4 * (SLOT >> 4) * 65535u, klast = rdesc + 4 * (SLOT >> 4) + 512;
            uint32_t kprev = fbar + 32, vprev = bars + (B_SINK - (B_EMPTY - B_FULL)) * 8;
#pragma unroll 1
            for (int it = 0; it < 4; it++) {
                both_issue(sb2, klast, pb, vlast);
                probs(sa, pa, mbar_test(vb, it < 2) & mbar_test(kb, it < 3), false, [&]() { mbar_wait(vb, it < 2); mbar_wait(kb, it < 3); });
                TS(41 + it * 4);
                if (lane == 0) mbar_arrive(kprev + (B_EMPTY - B_FULL) * 8);
                if (lane == 0) mbar_arrive(vprev + (B_EMPTY - B_FULL) * 8);
                both_issue(sa, kd, pa, vd);
                const int dv = it == 0 ? 2 : (it == 1 ? -3 : 1);
                kprev = kb; vprev = vb; vlast = vd - 512 * 65535u; klast = kd + 512;
                vd -= dv * (SLOT >> 4) * 65535u; vb += dv * 8;
                kd += (it == 2 ? -3 : 2) * (SLOT >> 4); kb = it == 2 ? vb : kb + 16;
                probs(sb2, pb, true, it == 3 && w == 1, []() {});
                TS(43 + it * 4);
            }
            wg_fence();
#pragma unroll
            for (int k = 0; k < 4; k++)
                mma_pv(o, pb[4 * k], pb[4 * k + 1], pb[4 * k + 2], pb[4 * k + 3], mkdesc(vlast - k * (128 * 65535) + (k > 1 ? w * ((k - 1) << 22) : 0)));
            wg_commit();
            const int row = wq * 16 + (lane >> 2);
            const uint32_t ml = sb + OFF_MISC;
            mbar_wait(bars + (B_RST + 1) * 8, 0);
            wg_wait<0>();
            pin(o); pin(pb); pin(sa); pin(sb2);
            if (!(LATE & 4)) rel(31);
            const float l0 = o[32], l1 = o[34];
            if (c4 == 0) { sts64f(ml + w * 512 + row * 8, n0, l0); sts64f(ml + w * 512 + row * 8 + 64, n1, l1); }
            TS(14);
            float mine[16];
#pragma unroll
            for (int j = 0; j < 4; j++) {
                if (w == 0) sts128f(H + j * 2048 + wt * 16, o[16 + 4 * j], o[17 + 4 * j], o[18 + 4 * j], o[19 + 4 * j]);
                else sts128f(H + 8192 + j * 2048 + wt * 16, o[4 * j], o[4 * j + 1], o[4 * j + 2], o[4 * j + 3]);
            }
#pragma unroll
            for (int i = 0; i < 16; i++) mine[i] = w == 0 ? o[i] : o[16 + i];
            bar_sync(10, 256);
            const float2 u0 = lds64f(ml + (w ^ 1) * 512 + row * 8), u1 = lds64f(ml + (w ^ 1) * 512 + row * 8 + 64);
            const float x0 = fminf(n0, u0.x), x1 = fminf(n1, u1.x);
            float a0 = ex2(x0 - n0), b0 = ex2(x0 - u0.x), a1 = ex2(x1 - n1), b1 = ex2(x1 - u1.x);
            const float i0 = __fdividef(1.f, fmaf(a0, l0, b0 * u0.y)), i1 = __fdividef(1.f, fmaf(a1, l1, b1 * u1.y));
            a0 *= i0; b0 *= i0; a1 *= i1; b1 *= i1;
            uint32_t pk[8];
#pragma unroll
            for (int j = 0; j < 4; j++) {
                const float4 v = lds128f(H + (w ^ 1) * 8192 + j * 2048 + wt * 16);
                pk[2 * j] = pack2(fmaf(a0, mine[4 * j], b0 * v.x), fmaf(a0, mine[4 * j + 1], b0 * v.y));
                pk[2 * j + 1] = pack2(fmaf(a1, mine[4 * j + 2], b1 * v.z), fmaf(a1, mine[4 * j + 3], b1 * v.w));
            }
            unsigned char* dst = g_o + (size_t)(b * 128 + qt * 8 + 2 * wq) * 4096 + ah * 1024 + w * 512 + lane * 16;
            st_data(dst, pk[0], pk[2], pk[4], pk[6]);
            st_data(dst + 4096, pk[1], pk[3], pk[5], pk[7]);
            if (tid == 0) asm volatile("red.relaxed.gpu.global.add.u32 [%0], 1;" ::"l"(&g_epoch[blockIdx.x * FS]) : "memory");
            TS(15);
        }

        {
            acq(32); acq(33); acq(34);
            uint4 u[8];
            ld_data<512>(u, g_o + (size_t)(b * 128 + pt * 4 + wq) * 4096 + lane * 16);
#pragma unroll
            for (int i = 0; i < 8; i++) { a[4 * i] = u[i].x; a[4 * i + 1] = u[i].y; a[4 * i + 2] = u[i].z; a[4 * i + 3] = u[i].w; }
            if (LATE & 4) rel(31);
            TS(16);
            sp(d0, 32, a, 0, 0);
            sp(d0, 33, a + 16, 0, 1);
            residual(32);
            TS(17);
        }
    }

    cluster_arrive();
    TS(24);
    {
        const float rstd = rsq(fmaxf(fmaf(-mean, mean, msq), 0.f) + 1e-5f), nb = -mean * rstd;
#pragma unroll
        for (int j = 0; j < 8; j++) xr[j] = pack2(fmaf(v[2 * j], rstd, nb), fmaf(v[2 * j + 1], rstd, nb));
        const uint32_t stg = P + 16384 + warp * 1024;
        stsm4(stg + foff, xr[0], xr[1], xr[2], xr[3]);
        stsm4(stg + (foff ^ 64), xr[4], xr[5], xr[6], xr[7]);
        __syncwarp();
        const uint32_t src = stg + (lane >> 3) * 128 + (((lane & 7) ^ (lane >> 3)) << 4);
        const uint4 u0 = lds128(src), u1 = lds128((src + 512) ^ 64);
        __nv_bfloat16* dst = p.out + (size_t)(b * T_ + trow + (lane >> 3)) * 256 + tile * 64 + (lane & 7) * 8;
        if (trow < T_) { stg128(dst, u0); stg128(dst + 4 * 256, u1); }
    }
    TS(25);
    TG(31);
    TSDUMP();
    cluster_wait();
}

typedef CUresult (*EncodeFn)(CUtensorMap*, CUtensorMapDataType, cuuint32_t, void*, const cuuint64_t*, const cuuint64_t*,
                             const cuuint32_t*, const cuuint32_t*, CUtensorMapInterleave, CUtensorMapSwizzle,
                             CUtensorMapL2promotion, CUtensorMapFloatOOBfill);

}

extern "C" void kernel_launch(void* const* d_in, const int* in_sizes, int n_in, void* d_out, int out_size) {
    static EncodeFn encode = nullptr;
    if (!encode) {
        void* fn = nullptr;
        cudaDriverEntryPointQueryResult qr;
        cudaGetDriverEntryPoint("cuTensorMapEncodeTiled", &fn, cudaEnableDefault, &qr);
        encode = (EncodeFn)fn;
        cudaFuncSetAttribute(conformer_kernel, cudaFuncAttributeMaxDynamicSharedMemorySize, SMEM_LAUNCH);
    }
    Params p;
    const cuuint32_t ones[5] = {1, 1, 1, 1, 1};
    const int idx[8] = {1, 2, 3, 4, 5, 7, 8, 9};
    const int rows[8] = {256, 1024, 256, 256, 256, 256, 256, 1024};
    const int cols[8] = {1024, 256, 768, 256, 512, 256, 1024, 256};
    for (int i = 0; i < 8; i++) {
        const cuuint64_t pitch = (cuuint64_t)cols[i] * 2;
        const cuuint64_t dims[5] = {(cuuint64_t)cols[i], 2, 2, 4, (cuuint64_t)rows[i] / 16};
        const cuuint64_t strides[4] = {pitch, pitch * 8, pitch * 2, pitch * 16};
        const cuuint32_t box[5] = {64, 2, 2, 4, 8};
        encode(&p.tm[i], CU_TENSOR_MAP_DATA_TYPE_BFLOAT16, 5, d_in[idx[i]], dims, strides, box, ones, CU_TENSOR_MAP_INTERLEAVE_NONE,
               CU_TENSOR_MAP_SWIZZLE_128B, CU_TENSOR_MAP_L2_PROMOTION_L2_128B, CU_TENSOR_MAP_FLOAT_OOB_FILL_NONE);
        p.w[i] = (const char*)d_in[idx[i]];
    }
    {
        void* kv = nullptr;
        cudaGetSymbolAddress(&kv, g_kvq);
        const cuuint64_t dims[2] = {64, 16384};
        const cuuint64_t strides[1] = {128};
        const cuuint32_t box[2] = {64, 128};
        encode(&p.tm[8], CU_TENSOR_MAP_DATA_TYPE_BFLOAT16, 2, kv, dims, strides, box, ones, CU_TENSOR_MAP_INTERLEAVE_NONE,
               CU_TENSOR_MAP_SWIZZLE_NONE, CU_TENSOR_MAP_L2_PROMOTION_L2_128B, CU_TENSOR_MAP_FLOAT_OOB_FILL_NONE);
    }
    p.x = (const __nv_bfloat16*)d_in[0];
    p.dw = (const __nv_bfloat16*)d_in[6];
    p.out = (__nv_bfloat16*)d_out;
    p.zero = 0;
    conformer_kernel<<<NCTA, NTHREADS, SMEM_LAUNCH>>>(p);
}
```

```cpp
#include <cuda_runtime.h>
#include <cuda_bf16.h>
#include <cuda.h>
#include <stdint.h>

namespace {

constexpr int T_ = 1000;
constexpr int NCTA = 128;
constexpr int NTHREADS = 512;
constexpr int NSLOT = 5;
constexpr int SLOT = 16384;
constexpr int NLOADS = 56;

constexpr uint32_t OFF_RING = 0;
constexpr uint32_t OFF_P = 163840;
constexpr uint32_t OFF_H = 188416;
constexpr uint32_t OFF_MISC = 221184;
constexpr uint32_t OFF_BARS = 229888;
constexpr uint32_t SMEM_BYTES = 230400;
constexpr uint32_t GCH = 6144;
constexpr uint32_t HCH = 4096;

constexpr int B_FULL = 0, B_EMPTY = 10, B_XA = 20  , B_XB = 25  , B_INB = 29  , B_SR = 33,
              B_RST = 34  , B_RDY = 36  , B_SINK = 42, B_HALO = 43  , NBARS = 47;

#define KD2 300u
#define KD3 500u
#define QGATE 500u
#define BACKOFF 0u
#define KFS 8
#define KDELAY 300u
#define NJ0 2
#define HDELAY 200u
#define LATE 3
#define TURN 0
#define EAGER 0x4755
constexpr int FS = 8;

struct Params {
    CUtensorMap tm[9];
    const char* w[8];
    const __nv_bfloat16* x;
    const __nv_bfloat16* dw;
    __nv_bfloat16* out;
    uint32_t zero;
};

__device__ __align__(1024) unsigned char g_kvq[3 * 8 * 1024 * 128];
__device__ __align__(1024) unsigned char g_o[2 * 128 * 4096];
__device__ uint4 g_halo[64 * 4 * 2 * 64];
__device__ __align__(128) uint32_t g_flag_kv[8 * 32 * KFS];
__device__ uint32_t g_reset[4 * 32];
__device__ uint32_t g_epoch[NCTA * FS];

#define TS(i) do { } while (0)
#define TSW(i) do { } while (0)
#define TG(i) do { } while (0)
#define TSINIT() do { } while (0)
#define TSDUMP() do { } while (0)
constexpr uint32_t SMEM_LAUNCH = SMEM_BYTES;

__device__ __forceinline__ uint32_t smem_u32(const void* p) { return (uint32_t)__cvta_generic_to_shared(p); }
__device__ __forceinline__ void mbar_init(uint32_t b, uint32_t c) { asm volatile("mbarrier.init.shared::cta.b64 [%0], %1;" ::"r"(b), "r"(c) : "memory"); }
__device__ __forceinline__ void mbar_arrive(uint32_t b) { asm volatile("mbarrier.arrive.shared::cta.b64 _, [%0];" ::"r"(b) : "memory"); }
__device__ __forceinline__ void mbar_arrive_tx(uint32_t b, uint32_t tx) { asm volatile("mbarrier.arrive.expect_tx.shared::cta.b64 _, [%0], %1;" ::"r"(b), "r"(tx) : "memory"); }
__device__ __forceinline__ void mbar_wait(uint32_t b, uint32_t ph) {
    asm volatile("{\n.reg .pred p, q;\n.reg .u32 c;\nmov.u32 c, 0;\n"
                 "MW_LOOP:\n.pragma \"nounroll\";\n"
                 "mbarrier.try_wait.parity.shared::cta.b64 p, [%0], %1;\n"
                 "add.u32 c, c, 1;\nsetp.lt.u32 q, c, 65536;\nnot.pred p, p;\nand.pred p, p, q;\n@p bra MW_LOOP;\n}"
                 ::"r"(b), "r"(ph) : "memory");
}
__device__ __forceinline__ bool mbar_test(uint32_t b, uint32_t ph) {
    uint32_t ok;
    asm volatile("{\n.reg .pred p;\nmbarrier.test_wait.parity.shared::cta.b64 p, [%1], %2;\nselp.u32 %0, 1, 0, p;\n}" : "=r"(ok) : "r"(b), "r"(ph) : "memory");
    return ok;
}
__device__ __forceinline__ uint32_t mapa(uint32_t a, uint32_t r) { uint32_t o; asm("mapa.shared::cluster.u32 %0, %1, %2;" : "=r"(o) : "r"(a), "r"(r)); return o; }
__device__ __forceinline__ void fence_async_smem() { asm volatile("fence.proxy.async.shared::cta;" ::: "memory"); }
__device__ __forceinline__ void fence_async_global() { asm volatile("fence.proxy.async.global;" ::: "memory"); }
__device__ __forceinline__ void bar_sync(int id, int n) { asm volatile("bar.sync %0, %1;" ::"r"(id), "r"(n) : "memory"); }
__device__ __forceinline__ void bar_arrive(int id, int n) { asm volatile("bar.arrive %0, %1;" ::"r"(id), "r"(n) : "memory"); }
__device__ __forceinline__ void cluster_arrive() { asm volatile("barrier.cluster.arrive.relaxed.aligned;" ::: "memory"); }
__device__ __forceinline__ void cluster_wait() { asm volatile("barrier.cluster.wait.aligned;" ::: "memory"); }

__device__ __forceinline__ void ring_load(uint32_t dst, const CUtensorMap* tm, int col, int row16, uint32_t bar) {
    asm volatile("{\n.reg .pred p;\nelect.sync _|p, 0xffffffff;\n"
                 "@p mbarrier.arrive.expect_tx.shared::cta.b64 _, [%2], 16384;\n"
                 "@p cp.async.bulk.tensor.5d.shared::cluster.global.mbarrier::complete_tx::bytes [%0], [%1, {%3, 0, 0, 0, %4}], [%2];\n}"
                 ::"r"(dst), "l"(tm), "r"(bar), "r"(col), "r"(row16) : "memory");
}
__device__ __forceinline__ void ring_load_both(uint32_t dst, const CUtensorMap* tm, int c1, uint32_t bar) {
    asm volatile("{\n.reg .pred p;\nelect.sync _|p, 0xffffffff;\n"
                 "@p cp.async.bulk.tensor.2d.shared::cluster.global.mbarrier::complete_tx::bytes.multicast::cluster [%0], [%1, {0, %3}], [%2], %4;\n}"
                 ::"r"(dst), "l"(tm), "r"(bar), "r"(c1), "h"((uint16_t)3) : "memory");
}
__device__ __forceinline__ void mbar_arrive_peer(uint32_t b) { asm volatile("mbarrier.arrive.relaxed.cluster.shared::cluster.b64 _, [%0];" ::"r"(b) : "memory"); }
__device__ __forceinline__ void prefetch_l2(const void* src, uint32_t bytes) {
    asm volatile("cp.async.bulk.prefetch.L2.global [%0], %1;" ::"l"(src), "r"(bytes) : "memory");
}
__device__ __forceinline__ void peer_copy(uint32_t dst, uint32_t src, uint32_t bytes, uint32_t rbar) {
    asm volatile("{\n.reg .pred p;\nelect.sync _|p, 0xffffffff;\n"
                 "@p cp.async.bulk.shared::cluster.shared::cta.mbarrier::complete_tx::bytes [%0], [%1], %2, [%3];\n}"
                 ::"r"(dst), "r"(src), "r"(bytes), "r"(rbar) : "memory");
}
__device__ __forceinline__ void st_async4(uint32_t dst, uint32_t a, uint32_t b, uint32_t c, uint32_t d, uint32_t bar) {
    asm volatile("st.async.shared::cluster.mbarrier::complete_tx::bytes.v4.b32 [%0], {%1,%2,%3,%4}, [%5];" ::"r"(dst), "r"(a), "r"(b), "r"(c), "r"(d), "r"(bar) : "memory");
}
__device__ __forceinline__ void st_async2f(uint32_t dst, float a, float b, uint32_t bar) {
    asm volatile("st.async.shared::cluster.mbarrier::complete_tx::bytes.v2.f32 [%0], {%1,%2}, [%3];" ::"r"(dst), "f"(a), "f"(b), "r"(bar) : "memory");
}
__device__ __forceinline__ void stsm4(uint32_t a, uint32_t r0, uint32_t r1, uint32_t r2, uint32_t r3) {
    asm volatile("stmatrix.sync.aligned.m8n8.x4.shared.b16 [%0], {%1,%2,%3,%4};" ::"r"(a), "r"(r0), "r"(r1), "r"(r2), "r"(r3) : "memory");
}
__device__ __forceinline__ void ldsm4(uint32_t a, uint32_t& r0, uint32_t& r1, uint32_t& r2, uint32_t& r3) {
    asm volatile("ldmatrix.sync.aligned.m8n8.x4.shared.b16 {%0,%1,%2,%3}, [%4];" : "=r"(r0), "=r"(r1), "=r"(r2), "=r"(r3) : "r"(a) : "memory");
}
__device__ __forceinline__ uint4 lds128(uint32_t a) { uint4 v; asm volatile("ld.shared.v4.b32 {%0,%1,%2,%3}, [%4];" : "=r"(v.x), "=r"(v.y), "=r"(v.z), "=r"(v.w) : "r"(a) : "memory"); return v; }
__device__ __forceinline__ float4 lds128f(uint32_t a) { float4 v; asm volatile("ld.shared.v4.f32 {%0,%1,%2,%3}, [%4];" : "=f"(v.x), "=f"(v.y), "=f"(v.z), "=f"(v.w) : "r"(a) : "memory"); return v; }
__device__ __forceinline__ float2 lds64f(uint32_t a) { float2 v; asm volatile("ld.shared.v2.f32 {%0,%1}, [%2];" : "=f"(v.x), "=f"(v.y) : "r"(a) : "memory"); return v; }
__device__ __forceinline__ uint32_t lds32(uint32_t a) { uint32_t v; asm volatile("ld.shared.b32 %0, [%1];" : "=r"(v) : "r"(a) : "memory"); return v; }
__device__ __forceinline__ void sts128(uint32_t a, uint32_t x, uint32_t y, uint32_t z, uint32_t w) { asm volatile("st.shared.v4.b32 [%0], {%1,%2,%3,%4};" ::"r"(a), "r"(x), "r"(y), "r"(z), "r"(w) : "memory"); }
__device__ __forceinline__ void sts128f(uint32_t a, float x, float y, float z, float w) { asm volatile("st.shared.v4.f32 [%0], {%1,%2,%3,%4};" ::"r"(a), "f"(x), "f"(y), "f"(z), "f"(w) : "memory"); }
__device__ __forceinline__ void sts64f(uint32_t a, float x, float y) { asm volatile("st.shared.v2.f32 [%0], {%1,%2};" ::"r"(a), "f"(x), "f"(y) : "memory"); }
__device__ __forceinline__ void sts32(uint32_t a, uint32_t x) { asm volatile("st.shared.b32 [%0], %1;" ::"r"(a), "r"(x) : "memory"); }
__device__ __forceinline__ void stg128(void* p, uint4 v) { asm volatile("st.global.v4.b32 [%0], {%1,%2,%3,%4};" ::"l"(p), "r"(v.x), "r"(v.y), "r"(v.z), "r"(v.w) : "memory"); }

__device__ __forceinline__ uint32_t pack2(float lo, float hi) { uint32_t r; asm("cvt.rn.bf16x2.f32 %0, %1, %2;" : "=r"(r) : "f"(hi), "f"(lo)); return r; }
__device__ __forceinline__ float blo(uint32_t v) { return __uint_as_float(v << 16); }
__device__ __forceinline__ float bhi(uint32_t v) { return __uint_as_float(v & 0xffff0000u); }
__device__ __forceinline__ uint32_t hmul2(uint32_t a, uint32_t b) { uint32_t r; asm("mul.rn.bf16x2 %0, %1, %2;" : "=r"(r) : "r"(a), "r"(b)); return r; }
__device__ __forceinline__ uint32_t hadd2(uint32_t a, uint32_t b) { uint32_t r; asm("add.rn.bf16x2 %0, %1, %2;" : "=r"(r) : "r"(a), "r"(b)); return r; }
__device__ __forceinline__ uint32_t hsub2(uint32_t a, uint32_t b) { uint32_t r; asm("sub.rn.bf16x2 %0, %1, %2;" : "=r"(r) : "r"(a), "r"(b)); return r; }
__device__ __forceinline__ uint32_t hfma2(uint32_t a, uint32_t b, uint32_t c) { uint32_t r; asm("fma.rn.bf16x2 %0, %1, %2, %3;" : "=r"(r) : "r"(a), "r"(b), "r"(c)); return r; }
__device__ __forceinline__ float tanh_fast(float x) { float r; asm("tanh.approx.f32 %0, %1;" : "=f"(r) : "f"(x)); return r; }
__device__ __forceinline__ float rsq(float x) { float r; asm("rsqrt.approx.ftz.f32 %0, %1;" : "=f"(r) : "f"(x)); return r; }
__device__ __forceinline__ float ex2(float x) { float r; asm("ex2.approx.ftz.f32 %0, %1;" : "=f"(r) : "f"(x)); return r; }

__device__ __forceinline__ uint32_t ld_relaxed(const uint32_t* p) {
    uint32_t v;
    asm volatile("ld.relaxed.gpu.global.u32 %0, [%1];" : "=r"(v) : "l"(p) : "memory");
    return v;
}
__device__ __forceinline__ uint32_t clock32() { uint32_t c; asm volatile("mov.u32 %0, %%clock;" : "=r"(c)::"memory"); return c; }
__device__ __forceinline__ void spin(uint32_t clks) {
    const uint32_t t0 = clock32();
    while (clock32() - t0 < clks) {}
}
__device__ __forceinline__ void flag_wait(const uint32_t* p, uint32_t e, bool mine) {
#pragma unroll 1
    for (int i = 0; i < (1 << 19); i++) {
        if (mine) mine = ld_relaxed(p) != e;
        if (!__any_sync(~0u, mine)) break;
        if (BACKOFF) spin(BACKOFF);
    }
    asm volatile("fence.acquire.gpu;" ::: "memory");
    fence_async_global();
}
__device__ __forceinline__ void st_data(void* p, uint32_t x, uint32_t y, uint32_t z, uint32_t w) {
    asm volatile("st.relaxed.gpu.global.v4.b32 [%0], {%1,%2,%3,%4};" ::"l"(p), "r"(x), "r"(y), "r"(z), "r"(w) : "memory");
}
template <int STRIDE, int N>
__device__ __forceinline__ void ld_data(uint4 (&v)[N], const unsigned char* p) {
    int it = 0;
    bool again;
#pragma unroll 1
    do {
        uint32_t m = 0;
#pragma unroll
        for (int i = 0; i < N; i++)
            asm volatile("ld.relaxed.gpu.global.v4.b32 {%0,%1,%2,%3}, [%4];" : "=r"(v[i].x), "=r"(v[i].y), "=r"(v[i].z), "=r"(v[i].w) : "l"(p + i * STRIDE) : "memory");
#pragma unroll
        for (int i = 0; i < N; i++) m = __vimax3_u32(__vimax3_u32(v[i].x, v[i].y, v[i].z), v[i].w, m);
        again = __any_sync(~0u, m == ~0u) && ++it < (1 << 16);
    } while (again);
}
__device__ __forceinline__ uint32_t ld_epoch() { return ld_relaxed(&g_epoch[blockIdx.x * FS]) + 1; }
__device__ __forceinline__ void flag_set(uint32_t* p, uint32_t e) { asm volatile("st.release.gpu.global.u32 [%0], %1;" ::"l"(p), "r"(e) : "memory"); }

__device__ __forceinline__ uint32_t desc_lo(uint32_t addr) { return ((addr & 0x3FFFF) >> 4) | 0x10000u; }
__device__ __forceinline__ uint64_t mkdesc(uint32_t lo) { return (uint64_t)lo | (0x40000040ull << 32); }
__device__ __forceinline__ void wg_fence() { asm volatile("wgmma.fence.sync.aligned;" ::: "memory"); }
__device__ __forceinline__ void wg_commit() { asm volatile("wgmma.commit_group.sync.aligned;" ::: "memory"); }
template <int N> __device__ __forceinline__ void wg_wait() { asm volatile("wgmma.wait_group.sync.aligned %0;" ::"n"(N) : "memory"); }
template <int N> __device__ __forceinline__ void pin(float (&d)[N]) {
#pragma unroll
    for (int i = 0; i < N; i++) asm volatile("" : "+f"(d[i])::"memory");
}
template <int N> __device__ __forceinline__ void pin(uint32_t (&d)[N]) {
#pragma unroll
    for (int i = 0; i < N; i++) asm volatile("" : "+r"(d[i])::"memory");
}

template <typename Tp, int N> __device__ __forceinline__ void zero(Tp (&d)[N]) {
#pragma unroll
    for (int i = 0; i < N; i++) d[i] = 0;
    pin(d);
}

#define F4(d, i) "+f"(d[i]), "+f"(d[i + 1]), "+f"(d[i + 2]), "+f"(d[i + 3])
#define F16(d, i) F4(d, i), F4(d, i + 4), F4(d, i + 8), F4(d, i + 12)

__device__ __forceinline__ void mma_sp(float (&d)[32], const uint32_t* a, uint64_t b, uint32_t meta, int acc) {
    asm volatile("{.reg .pred p; setp.ne.b32 p, %38, 0;\n"
                 "wgmma.mma_async.sp.sync.aligned.m64n64k32.f32.bf16.bf16 {%0,%1,%2,%3,%4,%5,%6,%7,%8,%9,%10,%11,%12,%13,%14,%15,%16,%17,%18,%19,%20,%21,%22,%23,%24,%25,%26,%27,%28,%29,%30,%31}, "
                 "{%32,%33,%34,%35}, %36, %37, 0, p, 1, 1, 1;}\n"
                 : F16(d, 0), F16(d, 16) : "r"(a[0]), "r"(a[1]), "r"(a[2]), "r"(a[3]), "l"(b), "r"(meta), "r"(acc));
}
__device__ __forceinline__ void mma_qk(float (&d)[32], uint32_t a0, uint32_t a1, uint32_t a2, uint32_t a3, uint64_t b, int acc) {
    asm volatile("{.reg .pred p; setp.ne.b32 p, %37, 0;\n"
                 "wgmma.mma_async.sync.aligned.m64n64k16.f32.bf16.bf16 {%0,%1,%2,%3,%4,%5,%6,%7,%8,%9,%10,%11,%12,%13,%14,%15,%16,%17,%18,%19,%20,%21,%22,%23,%24,%25,%26,%27,%28,%29,%30,%31}, "
                 "{%32,%33,%34,%35}, %36, p, 1, 1, 0;}\n"
                 : F16(d, 0), F16(d, 16) : "r"(a0), "r"(a1), "r"(a2), "r"(a3), "l"(b), "r"(acc));
}
__device__ __forceinline__ void mma_pv(float (&d)[36], uint32_t a0, uint32_t a1, uint32_t a2, uint32_t a3, uint64_t b) {
    asm volatile("wgmma.mma_async.sync.aligned.m64n72k16.f32.bf16.bf16 {%0,%1,%2,%3,%4,%5,%6,%7,%8,%9,%10,%11,%12,%13,%14,%15,%16,%17,%18,%19,%20,%21,%22,%23,%24,%25,%26,%27,%28,%29,%30,%31,%32,%33,%34,%35}, "
                 "{%36,%37,%38,%39}, %40, 1, 1, 1, 1;\n"
                 : F16(d, 0), F16(d, 16), F4(d, 32) : "r"(a0), "r"(a1), "r"(a2), "r"(a3), "l"(b));
}

__device__ __forceinline__ uint32_t load_code(int n, int r, int w) {
    const int tile = 2 * r + w;
    int m, col, row;
    if (n < 16 || n >= 40) {
        const int k = n < 16 ? n : n - 40;
        m = n < 16 ? 0 : 6;
        if (k < 8) { col = 4 * tile + (k >> 1); row = (k & 1) ^ r; }
        else { m++; col = tile ^ (3 - ((k - 8) >> 1)); row = 2 * tile + (k & 1); }
    } else if (n < 32) {
        const int k = n - 16;
        m = 2;
        if (k < 4) { col = tile + ((k & 1) ? 8 : 4); row = (k >> 1) ^ r; }
        else { col = tile; row = (k & 1) ^ r; }
    } else if (n < 34) { m = 3; col = tile; row = n - 32; }
    else if (n < 38) { const int k = n - 34; m = 4; col = tile + 4 * (k & 1); row = (k >> 1) ^ r; }
    else { m = 5; col = tile; row = (n & 1) ^ r; }
    return m | (col << 4) | (row << 8);
}

__global__ void __cluster_dims__(2, 1, 1) __launch_bounds__(NTHREADS, 1)
conformer_kernel(const __grid_constant__ Params p) {
    extern __shared__ __align__(1024) unsigned char smem_raw[];
    const uint32_t sb = smem_u32(smem_raw);
    const uint32_t bars = sb + OFF_BARS;
    const int tid = threadIdx.x;
    const int lane = tid & 31;
    const int warp = __shfl_sync(~0u, tid >> 5, 0);
    const int r = blockIdx.x & 1;
    const int pair = blockIdx.x >> 1;
    const int b = pair >> 5, pt = pair & 31;
    const int ah = pt >> 3, qt = (pt & 7) * 2 + r;
    const int abh = b * 4 + ah;

    TG(30);
    TSINIT();
    TS(0);
    const uint32_t P = sb + OFF_P, H = sb + OFF_H;

    if (warp >= 8) {
        asm volatile("setmaxnreg.dec.sync.aligned.u32 48;");
        if (warp >= 12) {
            cluster_arrive();
            cluster_wait();
            const int ut = tid & 127;
            const uint32_t target = ld_epoch() * 64;
            auto reset_done = [&](int k) {
                bar_sync(11, 128);
                if (ut == 0) {
                    asm volatile("red.release.gpu.global.add.u32 [%0], 1;" ::"l"(&g_reset[(2 * b + k) * 32]) : "memory");
#pragma unroll 1
                    for (int i = 0; i < (1 << 20) && ld_relaxed(&g_reset[(2 * b + k) * 32]) != target; i++) __nanosleep(100);
                    asm volatile("fence.acquire.gpu;" ::: "memory");
                    mbar_arrive(bars + (B_RST + k) * 8);
                }
                __syncwarp();
                TS(13 + k);
            };
#pragma unroll
            for (int i = 0; i < 4; i++)
                st_data(g_kvq + 2097152 + (size_t)((b * 4 + 2 * r + (i >> 1)) * 1024 + pt * 32) * 128 + (i & 1) * 2048 + ut * 16, ~0u, ~0u, ~0u, ~0u);
            reset_done(0);
            bar_sync(6, 384);
#pragma unroll
            for (int i = 0; i < 4; i++) {
                st_data(g_o + (size_t)(b * 128 + qt * 8 + 2 * i + (ut >> 6)) * 4096 + ah * 1024 + (ut & 63) * 16, ~0u, ~0u, ~0u, ~0u);
                if (i < 2) st_data(&g_halo[(pair * 4 + 2 * r + i) * 128 + ut], ~0u, ~0u, ~0u, ~0u);
            }
            reset_done(1);
            const int side = warp & 1, wg = (warp >> 1) & 1, np = side ? pt + 1 : pt - 1;
            const unsigned char* src = reinterpret_cast<const unsigned char*>(&g_halo[(((b * 32 + np) * 4 + 2 * r + wg) * 2 + (side ^ 1)) * 64 + lane]);
            const uint32_t dst = H + 16384 + wg * GCH + side * 5120 + (lane & 7) * 128 + (((lane >> 3) ^ (lane & 7)) << 4);
            uint4 hv[2] = {make_uint4(0, 0, 0, 0), make_uint4(0, 0, 0, 0)};
            bar_sync(8 + wg, 192);
            if (np >= 0 && np < 32) {
                spin(HDELAY);
                ld_data<512>(hv, src);
            }
            stsm4(dst, hv[0].x, hv[0].y, hv[0].z, hv[0].w);
            stsm4(dst ^ 64, hv[1].x, hv[1].y, hv[1].z, hv[1].w);
            __syncwarp();
            if (lane == 0) mbar_arrive(bars + (B_HALO + (warp & 3)) * 8);
            TS(4);
        } else if (warp < 10) {
            const int w = warp - 8;
            const uint32_t ring = sb + OFF_RING + w * NSLOT * SLOT;
            const uint32_t full = bars + (B_FULL + w * NSLOT) * 8;
            if (lane == 0) {
#pragma unroll
                for (int i = 0; i < NSLOT; i++) { mbar_init(full + i * 8, 1); mbar_init(full + (B_EMPTY - B_FULL + i) * 8, 4); }
                asm volatile("fence.mbarrier_init.release.cluster;" ::: "memory");
                fence_async_smem();
            }
            __syncwarp();
            cluster_arrive();
            TS(1);
#pragma unroll
            for (int n = 0; n < NSLOT; n++) {
                if (n == 1 || n == 2) bar_sync(12, 64);
                ring_load(ring + n * SLOT, &p.tm[0], 64 * (8 * r + 4 * w + (n >> 1)), 8 * ((n & 1) ^ r), full + n * 8);
            }
            TS(2);
            const uint32_t code = load_code(lane, r, w) | (load_code(lane + 32, r, w) << 16);
            cluster_wait();
            uint32_t s = 0, ph = 0;
            int n = NSLOT;
#pragma unroll 1
            for (int seg = 0; seg < 2; seg++) {
#pragma unroll 1
                for (; n < (seg == 0 ? 22 : NLOADS); n++) {
                    const uint32_t c = __shfl_sync(~0u, code, n) >> (n & 32 ? 16 : 0);
                    const CUtensorMap* tm = &p.tm[c & 15];
                    const uint32_t col = (c & 0xf0) * 4, row = (c & 0xff00) >> 5, dst = ring + s * SLOT;
                    mbar_wait(full + (B_EMPTY - B_FULL) * 8 + s * 8, ph + (((uint32_t)(size_t)tm | col | row | dst) & p.zero));
                    ring_load(dst, tm, col, row, full + s * 8);
                    if (++s == NSLOT) { s = 0; ph ^= 1; }
                }
                if (seg == 1) break;
                const uint32_t epoch = ld_epoch();
                const uint32_t rdy = bars + (B_RDY + 3 * w) * 8, prdy = mapa(rdy, r ^ 1);
                const int odd = r ^ w;
                const uint32_t* flags = g_flag_kv + (abh * 32 + lane) * KFS;
                auto kv_load = [&](uint32_t sl, int isv, int i) {
                    ring_load_both(ring + sl * SLOT, &p.tm[8], (isv * 64 + abh * 8 + 2 * i + w) * 128, full + sl * 8);
                };
#pragma unroll 1
                for (int i = 0; i < 2; i++) {
                    if (lane < 3 + i) {
                        const uint32_t sl = i ? lane : lane + 2;
                        mbar_wait(full + (B_EMPTY - B_FULL + sl) * 8, i ^ 1);
                        mbar_arrive_tx(full + sl * 8, (i || lane == 2) ? SLOT : 0);
                    }
                    __syncwarp();
                }
                if (lane == 0) mbar_arrive_peer(prdy);
                bar_sync(14, 96);
                spin(KDELAY);
                mbar_wait(rdy, 0);
                flag_wait(flags, epoch, (lane >> 2) == 2 * odd + w);
                TSW(5 + 2 * odd);
                if (!odd) { kv_load(4, 0, 0); bar_arrive(12, 64); }
                else bar_sync(12, 64);
                spin(w ? KD3 : KD2);
                kv_load(odd ^ 1, odd ^ 1, odd);
                flag_wait(flags, epoch, (lane >> 2) == 2 * odd + w + 4);
                mbar_wait(full + (odd ^ 1) * 8, 1);
                kv_load(2 + odd, odd, 2 - odd);
#pragma unroll 1
                for (int i = 0; i < 3; i++) {
                    const uint32_t sl = i ? i - 1 : 4, bo = i == 2 ? 16 : 8;
                    mbar_wait(full + (B_EMPTY - B_FULL + sl) * 8, i != 0);
                    if (lane == 0) mbar_arrive_tx(full + sl * 8, SLOT);
                    if ((i & 1) != odd) {
                        mbar_wait(rdy + bo, 0);
                        kv_load(sl, i != 0, 2 + odd);
                    } else if (lane == 0) mbar_arrive_peer(prdy + bo);
                    __syncwarp();
                }
                n = 32; s = 2; ph = 1;
            }
        } else if (warp == 10) {
            if (lane == 0) {
#pragma unroll
                for (int i = B_XA; i < NBARS; i++) mbar_init(bars + i * 8, 1);
#pragma unroll
                for (int i = B_XA; i <= B_SR; i++) mbar_arrive_tx(bars + i * 8, i < B_XB ? 512 : 8192);
                asm volatile("fence.mbarrier_init.release.cluster;" ::: "memory");
                fence_async_smem();
            }
            __syncwarp();
            cluster_arrive();
            cluster_wait();
        } else {
            const uint32_t kb = (lane < 2 || lane > 5) ? 4096 : (lane == 2 ? 3072 : (lane == 4 ? 2048 : 1024));
            const char* pf = p.w[lane & 7] + blockIdx.x * kb;
            cluster_arrive();
            cluster_wait();
            if (lane < 2) prefetch_l2(pf, kb);
            mbar_wait(bars + B_XA * 8, 0);
            if (lane == 2) prefetch_l2(pf, kb);
            if (lane >= 1 && lane < 9) asm volatile("prefetch.tensormap [%0];" ::"l"(&p.tm[lane]) : "memory");
            mbar_wait(bars + (B_FULL + 1) * 8, 1);
            if (lane > 2 && lane < 8) prefetch_l2(pf, kb);
            if (lane == 8 && blockIdx.x < 15) prefetch_l2(p.dw + blockIdx.x * 256, 512);
            const uint32_t epoch = ld_epoch();
            bar_sync(4, 288);
            if (lane < 16) flag_set(&g_flag_kv[((b * 4 + 2 * r + (lane >> 3)) * 32 + pt) * KFS + (lane & 7)], epoch);
            __syncwarp();
            bar_arrive(14, 96);
            TSW(8);
        }
        TSDUMP();
        return;
    }

    const int w = warp >> 2, wq = warp & 3;
    const int tile = 2 * r + w;
    const int wt = tid & 127;
    const int c4 = lane & 3;
    const int trow = pt * 32 + 8 * wq;
    uint32_t xr[8];
    {
        const uint32_t* xp = reinterpret_cast<const uint32_t*>(p.x + (size_t)(b * T_ + trow + (lane >> 2)) * 256 + tile * 64) + c4;
#pragma unroll
        for (int j = 0; j < 8; j++) xr[j] = trow < T_ ? __ldg(xp + 4 * j) : 0u;
    }
    cluster_arrive();
    asm volatile("setmaxnreg.inc.sync.aligned.u32 208;");
    const uint32_t rbase = sb + OFF_RING + w * NSLOT * SLOT, fbar = bars + (B_FULL + w * NSLOT) * 8;
    const uint32_t rdesc = desc_lo(rbase);
    auto acq = [&](int n) { mbar_wait(fbar + (n % NSLOT) * 8, (n / NSLOT) & 1); };
    auto rel = [&](int n) { if (lane == 0) mbar_arrive(fbar + (B_EMPTY - B_FULL + n % NSLOT) * 8); };
    const uint32_t foff = (lane & 7) * 128 + (((lane >> 3) ^ (lane & 7)) << 4);
    float v[16];
#pragma unroll
    for (int j = 0; j < 8; j++) { v[2 * j] = blo(xr[j]); v[2 * j + 1] = bhi(xr[j]); }
    const uint32_t xown = __shfl_sync(~0u, P + wt * 16 + tile * 4096, lane), xrem = __shfl_sync(~0u, P + wt * 16 + (r ^ 1) * 8192, lane);
    const uint32_t sbuf = __shfl_sync(~0u, sb + OFF_MISC + 1024 + (8 * wq + (lane >> 2)) * 32, lane);
    const uint32_t sown = __shfl_sync(~0u, sbuf + tile * 8, lane);
    const uint32_t peer = __shfl_sync(~0u, mapa(sb, r ^ 1) - sb, lane);
    const uint32_t meta = __shfl_sync(~0u, 0xEEEE4444u + p.zero, lane);
    cluster_wait();
    TS(56);
    float mean, msq;

#pragma unroll 1
    for (int ph = 0;; ph++) {
        uint4 o0, o1;
        {
            float s = 0.f, q = 0.f, s2 = 0.f, q2 = 0.f;
#pragma unroll
            for (int j = 0; j < 4; j++) {
                s += v[4 * j] + v[4 * j + 1]; s2 += v[4 * j + 2] + v[4 * j + 3];
                q += fmaf(v[4 * j], v[4 * j], v[4 * j + 1] * v[4 * j + 1]); q2 += fmaf(v[4 * j + 2], v[4 * j + 2], v[4 * j + 3] * v[4 * j + 3]);
            }
            s += s2; q += q2;
            const uint32_t xa = bars + (B_XA + ph) * 8;
            s += __shfl_xor_sync(~0u, s, 1); q += __shfl_xor_sync(~0u, q, 1);
            s += __shfl_xor_sync(~0u, s, 2); q += __shfl_xor_sync(~0u, q, 2);
            if (c4 == 0) st_async2f(sown + peer, s, q, xa + peer);
            if (c4 == 0) sts64f(sown, s, q);
#pragma unroll
            for (int j = 0; j < 8; j++) xr[j] = pack2(v[2 * j], v[2 * j + 1]);
            sts128(xown, xr[0], xr[1], xr[2], xr[3]);
            sts128(xown + 2048, xr[4], xr[5], xr[6], xr[7]);
            bar_sync(10, 256);
            o0 = lds128(xown ^ 4096); o1 = lds128((xown ^ 4096) + 2048);
            if (ph < 4) {
                st_async4(xown + peer, xr[0], xr[1], xr[2], xr[3], xa + (B_XB - B_XA) * 8 + peer);
                st_async4(xown + peer + 2048, xr[4], xr[5], xr[6], xr[7], xa + (B_XB - B_XA) * 8 + peer);
            }
            TS(57 + ph);
            if (ph == 0 || ph == 3) acq(0);
            mbar_wait(xa, 0);
            const float4 u0 = lds128f(sbuf), u1 = lds128f(sbuf + 16);
            mean = ((u0.x + u0.z) + (u1.x + u1.z)) * (1.f / 256.f);
            msq = ((u0.y + u0.w) + (u1.y + u1.w)) * (1.f / 256.f);
        }
        if (ph == 4) break;
        uint32_t a[32];
        const uint32_t mean2 = pack2(mean, mean);
        auto centre = [&](int i, const uint4& u) {
            a[i] = hsub2(u.x, mean2); a[i + 1] = hsub2(u.y, mean2); a[i + 2] = hsub2(u.z, mean2); a[i + 3] = hsub2(u.w, mean2);
        };
#pragma unroll
        for (int j = 0; j < 8; j++) a[j] = hsub2(xr[j], mean2);
        centre(8, o0); centre(12, o1);
        const float rstd = rsq(fmaxf(fmaf(-mean, mean, msq), 0.f) + 1e-5f);
        auto gather_peer = [&]() {
            mbar_wait(bars + (B_XB + ph) * 8, 0);
#pragma unroll
            for (int i = 0; i < 4; i++) centre(16 + 4 * i, lds128(xrem + i * 2048));
        };
        auto sp = [&](float (&d)[32], int n, const uint32_t* af, int flip, int acc) {
            const uint32_t lo = rdesc + p.zero * (ph + n + 1) + (n % NSLOT) * (SLOT >> 4);
            const uint64_t b0 = mkdesc(lo + flip * 512), b1 = mkdesc(lo + (flip ^ 1) * 512);
            wg_fence();
            mma_sp(d, af, b0, meta, acc);
            mma_sp(d, af + 4, b0 + 256, meta, 1);
            mma_sp(d, af + 8, b1, meta, 1);
            mma_sp(d, af + 12, b1 + 256, meta, 1);
            wg_commit();
        };
        float d0[32], d1[32];

        if (ph == 0 || ph == 3) {
            uint32_t h[32];
            const float rs = 0.5f * rstd;
            const uint32_t inb = bars + (B_INB + (ph & 2)) * 8, box = H + wt * 16;
            bool ready = true;
            auto step = [&](float (&d)[32], int n, const uint32_t* af, int flip, int acc, auto work) {
                if (!ready) acq(n);
                if (((TURN >> n) & 1) && w == 1) bar_sync(7, 256);
                sp(d, n, af, flip, acc);
                if (n > 0 && ((TURN >> (n - 1)) & 1) && w == 0) bar_arrive(7, 256);
                if (n < 15) ready = mbar_test(fbar + ((n + 1) % NSLOT) * 8, ((n + 1) / NSLOT) & 1);
                wg_wait<1>();
                if (n > 0 && !((EAGER >> (n - 1)) & 1)) rel(n - 1);
                const uint32_t tie = work() & p.zero;
                if ((EAGER >> n) & 1) {
                    if (p.zero < n + ph + 1) wg_wait<0>();
                    if (lane == 0) mbar_arrive(fbar + (B_EMPTY - B_FULL + n % NSLOT) * 8 + tie);
                }
            };
            auto none = []() { return 0u; };
            auto act = [&](float (&d)[32], int i) {
                pin(d);
#pragma unroll
                for (int j = 0; j < 8; j++) {
                    const float u0 = (d[4 * j] + d[4 * j + 2]) * rs, u1 = (d[4 * j + 1] + d[4 * j + 3]) * rs;
                    h[8 * i + j] = pack2(fmaf(u0, tanh_fast(u0), u0), fmaf(u1, tanh_fast(u1), u1));
                }
                return h[8 * i] | h[8 * i + 1] | h[8 * i + 2] | h[8 * i + 3] | h[8 * i + 4] | h[8 * i + 5] | h[8 * i + 6] | h[8 * i + 7];
            };
            auto send = [&](float (&d)[32], int x) {
                pin(d);
                uint32_t pk[8];
#pragma unroll
                for (int j = 0; j < 8; j++) pk[j] = pack2(d[4 * j] + d[4 * j + 2], d[4 * j + 1] + d[4 * j + 3]);
                const uint32_t ow = w ^ (x & 1), dst = box + (ow * 3 + x - 1) * 4096;
                if (x & 2) {
                    st_async4(dst + peer, pk[0], pk[1], pk[2], pk[3], inb + ow * 8 + peer);
                    st_async4(dst + peer + 2048, pk[4], pk[5], pk[6], pk[7], inb + ow * 8 + peer);
                } else {
                    sts128(dst, pk[0], pk[1], pk[2], pk[3]);
                    sts128(dst + 2048, pk[4], pk[5], pk[6], pk[7]);
                }
            };
            TS(1 + (ph & 2) * 10);
            step(d0, 0, a, w, 0, [&]() { gather_peer(); return 0u; });
            TS(32);
            step(d0, 1, a + 16, 0, 1, none);
            step(d1, 2, a, w, 0, [&]() { return act(d0, 0); });
            step(d1, 3, a + 16, 0, 1, none);
            step(d0, 4, a, w, 0, [&]() { return act(d1, 1); });
            TS(33);
            step(d0, 5, a + 16, 0, 1, none);
            step(d1, 6, a, w, 0, [&]() { return act(d0, 2); });
            step(d1, 7, a + 16, 0, 1, none);
            step(d0, 8, h, 0, 0, [&]() { return act(d1, 3); });
            TS(2 + (ph & 2) * 10);
            step(d0, 9, h + 16, 0, 1, none);
            step(d1, 10, h, 0, 0, [&]() { send(d0, 3); return 0u; });
            step(d1, 11, h + 16, 0, 1, none);
            step(d0, 12, h, 0, 0, [&]() { send(d1, 2); return 0u; });
            TS(34);
            step(d0, 13, h + 16, 0, 1, none);
            uint4 u[6];
            step(d1, 14, h, 0, 0, [&]() {
                send(d0, 1);
                mbar_wait(inb + w * 8, 0);
                bar_sync(10, 256);
#pragma unroll
                for (int i = 0; i < 6; i++) u[i] = lds128(box + w * 12288 + i * 2048);
                return u[0].x | u[1].x | u[2].x | u[3].x | u[4].x | u[5].x;
            });
            step(d1, 15, h + 16, 0, 1, none);
            mbar_wait(ph == 0 ? fbar + (16 % NSLOT) * 8 : inb + w * 8, ph == 0);
            uint32_t tie = 0;
#pragma unroll
            for (int i = 0; i < 2; i++) {
                const uint32_t p0[4] = {u[i].x, u[i].y, u[i].z, u[i].w}, p1[4] = {u[i + 2].x, u[i + 2].y, u[i + 2].z, u[i + 2].w}, p2[4] = {u[i + 4].x, u[i + 4].y, u[i + 4].z, u[i + 4].w};
#pragma unroll
                for (int j = 0; j < 4; j++) {
                    v[8 * i + 2 * j] = fmaf(0.5f, blo(p0[j]) + blo(p1[j]) + blo(p2[j]), blo(xr[4 * i + j]));
                    v[8 * i + 2 * j + 1] = fmaf(0.5f, bhi(p0[j]) + bhi(p1[j]) + bhi(p2[j]), bhi(xr[4 * i + j]));
                    tie |= __float_as_uint(v[8 * i + 2 * j]) | __float_as_uint(v[8 * i + 2 * j + 1]);
                }
            }
            if (__any_sync(~0u, tie & p.zero)) spin(1);
            wg_wait<0>();
            pin(d1);
            rel(15);
            TS(3 + (ph & 2) * 10);
#pragma unroll
            for (int j = 0; j < 8; j++) {
                v[2 * j] = fmaf(0.5f, d1[4 * j] + d1[4 * j + 2], v[2 * j]);
                v[2 * j + 1] = fmaf(0.5f, d1[4 * j + 1] + d1[4 * j + 3], v[2 * j + 1]);
            }
            continue;
        }

        auto residual = [&](int n) {
            wg_wait<1>();
            rel(n);
            wg_wait<0>();
            pin(d0);
            rel(n + 1);
#pragma unroll
            for (int j = 0; j < 8; j++) {
                v[2 * j] = d0[4 * j] + d0[4 * j + 2] + blo(xr[j]);
                v[2 * j + 1] = d0[4 * j + 1] + d0[4 * j + 3] + bhi(xr[j]);
            }
        };

        if (ph == 2) {
            TS(39);
            sp(d0, 34, a, w, 0);
            acq(35);
            sp(d1, 35, a, w, 0);
            uint32_t dwr[15];
            {
                const uint32_t* dp = reinterpret_cast<const uint32_t*>(p.dw + tile * 64) + lane;
#pragma unroll
                for (int i = 0; i < 15; i++) asm volatile("ld.global.nc.b32 %0, [%1];" : "=r"(dwr[i]) : "l"(dp + i * 128));
            }
            acq(36); acq(37);
            gather_peer();
            sp(d0, 36, a + 16, 0, 1);
            sp(d1, 37, a + 16, 0, 1);
            wg_wait<2>();
            rel(34);
            if (!(LATE & 1)) rel(35);
            acq(38);
            const int mir = wq < 2 ? 7 : 0;
            uint32_t tie = dwr[7] = hmul2(dwr[7], 0x3F003F00u);
#pragma unroll
            for (int i = 0; i < 7; i++) {
                const uint32_t x = dwr[i], y = dwr[14 - i];
                dwr[i] = hmul2(mir ? y : x, 0x3F003F00u); dwr[14 - i] = hmul2(mir ? x : y, 0x3F003F00u);
                tie |= dwr[i] | dwr[14 - i];
            }
            if (__any_sync(~0u, tie & p.zero)) spin(1);
            const float rs = trow < T_ ? 0.5f * rstd : 0.f;
            wg_wait<0>();
            pin(d0); pin(d1);
            if (!(LATE & 2)) { rel(36); rel(37); }
            TS(18);
            uint32_t pk[8];
#pragma unroll
            for (int j = 0; j < 8; j++) {
                const float u0 = (d0[4 * j] + d0[4 * j + 2]) * rs, u1 = (d0[4 * j + 1] + d0[4 * j + 3]) * rs;
                const float t0 = tanh_fast((d1[4 * j] + d1[4 * j + 2]) * rs), t1 = tanh_fast((d1[4 * j + 1] + d1[4 * j + 3]) * rs);
                pk[j] = pack2(fmaf(u0, t0, u0), fmaf(u1, t1, u1));
            }
            if (wq == 0 || wq == 3) {
                uint4* hp = &g_halo[((pair * 4 + tile) * 2 + (wq & 1)) * 64 + lane];
                st_data(hp, pk[0], pk[1], pk[2], pk[3]);
                st_data(hp + 32, pk[4], pk[5], pk[6], pk[7]);
            }
            const uint32_t gs = H + 16384 + w * GCH + wq * 1024;
            stsm4(gs + 1024 + foff, pk[0], pk[1], pk[2], pk[3]);
            stsm4(gs + 1024 + (foff ^ 64), pk[4], pk[5], pk[6], pk[7]);
            bar_sync(8 + w, 192);
            TS(26);
            uint32_t ca[8], cb[8];
            const int e = (wq & 1) * 4;
            const uint32_t lo = ((mir ^ e) * 144) ^ (lane * 4);
            const int dir = mir ? -1024 : 1024;
            const uint32_t gb = H + 16384 + w * GCH + (mir ? 3072 : 2048) + lo, sown_ = H + tile * HCH, so = sown_ + (mir ? 1024 : 2048) + lo;
            auto finish = [&](int i) {
                const uint32_t c = hadd2(ca[i], cb[i]);
                const float h0 = blo(c), h1 = bhi(c);
                sts32((so + (i >> 2) * dir) ^ ((i & 3) * 144), pack2(fmaf(h0, tanh_fast(h0), h0), fmaf(h1, tanh_fast(h1), h1)));
            };
#pragma unroll
            for (int k = 0; k < 26; k++) {
                if (k == 19) {
#pragma unroll
                    for (int i = 0; i < 4; i++) finish(i);
                    fence_async_smem();
                    bar_sync(2 + w, 128);
                    if (wq == 0) peer_copy(mapa(sown_ + 1024, r ^ 1), sown_ + 1024, 2048, mapa(bars + B_SR * 8, r ^ 1));
                    mbar_wait(bars + (B_HALO + 2 * w + (wq >> 1)) * 8, 0);
                    if (LATE & 1) rel(35);
                    if (LATE & 2) { rel(36); rel(37); }
                    TS(27);
                }
                const uint32_t g = lds32((gb + (((k + 1) & 4) ? ((k + 1) >> 3) + (wq & 1) : ((k + 1) >> 3)) * dir) ^ (((k + 1) & 7) * 144));
#pragma unroll
                for (int i = 0; i < 8; i++) {
                    const int tap = k - (i & 3) - 2 * (i & 4);
                    if (tap == 0) ca[i] = hmul2(g, dwr[0]);
                    else if (tap > 0 && tap < 8) ca[i] = hfma2(g, dwr[tap], ca[i]);
                    else if (tap == 8) cb[i] = hmul2(g, dwr[8]);
                    else if (tap > 8 && tap < 15) cb[i] = hfma2(g, dwr[tap], cb[i]);
                }
            }
#pragma unroll
            for (int i = 4; i < 8; i++) finish(i);
            fence_async_smem();
            bar_sync(12 + (warp >> 1), 64);
            if (wq == 0 || wq == 3) peer_copy(mapa(sown_ + wq * 1024, r ^ 1), sown_ + wq * 1024, 1024, mapa(bars + B_SR * 8, r ^ 1));
            bar_sync(10, 256);
            TS(19);
            auto frags = [&](int i, int half) {
                const uint32_t src = H + 2 * half * HCH + wq * 1024;
#pragma unroll
                for (int k = 0; k < 4; k++) ldsm4(src + (k >> 1) * HCH + (foff ^ ((k & 1) * 64)), a[i + 4 * k], a[i + 4 * k + 1], a[i + 4 * k + 2], a[i + 4 * k + 3]);
            };
            frags(0, r);
            sp(d0, 38, a, 0, 0);
            acq(39);
            mbar_wait(bars + B_SR * 8, 0);
            frags(16, r ^ 1);
            sp(d0, 39, a + 16, 0, 1);
            residual(38);
            TS(20);
            continue;
        }

        {
            TS(11);
            const uint32_t stg = H + warp * 2048;
            unsigned char* g = g_kvq + (size_t)((b * 4 + tile) * 1024 + trow) * 128 + lane * 16;
            auto put = [&](float (&d)[32], int i) {
                pin(d);
                uint32_t pk[8];
#pragma unroll
                for (int j = 0; j < 8; j++) pk[j] = pack2((d[4 * j] + d[4 * j + 2]) * rstd, (d[4 * j + 1] + d[4 * j + 3]) * rstd);
                if (i == 2) {
                    st_data(g + 2097152, pk[0], pk[1], pk[2], pk[3]);
                    st_data(g + 2097152 + 512, pk[4], pk[5], pk[6], pk[7]);
                    return;
                }
                stsm4(stg + i * 1024 + foff, pk[0], pk[1], pk[2], pk[3]);
                stsm4(stg + i * 1024 + (foff ^ 64), pk[4], pk[5], pk[6], pk[7]);
                __syncwarp();
                const uint4 u0 = lds128(stg + i * 1024 + lane * 16), u1 = lds128(stg + i * 1024 + 512 + lane * 16);
                stg128(g + i * 1048576, u0); stg128(g + i * 1048576 + 512, u1);
            };
            sp(d0, 16, a, w, 0);
            acq(17);
            sp(d1, 17, a, w, 0);
            gather_peer();
            acq(18);
            sp(d0, 18, a + 16, 0, 1);
            wg_wait<1>();
            rel(16); rel(17);
            acq(19);
            sp(d1, 19, a + 16, 0, 1);
            wg_wait<1>();
            rel(18);
            put(d0, 0);
            wg_wait<0>();
            rel(19);
            TS(37);
            put(d1, 1);
            bar_arrive(4, 288);
            TS(38);
            acq(20);
            sp(d0, 20, a, w, 0);
            acq(21);
            sp(d0, 21, a + 16, 0, 1);
            acq(22); acq(23);
            rel(22); rel(23);
            mbar_wait(bars + B_RST * 8, 0);
            wg_wait<0>();
            rel(20); rel(21);
            put(d0, 2);
            TS(12);
        }

        {
            constexpr float CS = 0.125f * 1.4426950408889634f;
            float sa[32], sb2[32], o[36];
            uint32_t pa[16], pb[16], q[16];
            float n0 = INFINITY, n1 = INFINITY;
            zero(o); zero(pa); zero(pb); zero(sb2);
            const uint32_t ones = sb + OFF_MISC + 2048;
            { const uint32_t c = w ? 0u : 0x3F803F80u; sts128(ones + tid * 16, c, c, c, c); }
            fence_async_smem();
            bar_sync(10, 256);
            const uint32_t vdesc = rdesc + ((((ones - rbase) >> 4) - 1) << 16);
            auto qk_issue = [&](float (&s)[32], uint32_t lo) {
                const uint64_t kd = mkdesc(lo);
                wg_fence();
#pragma unroll
                for (int k = 0; k < 4; k++) mma_qk(s, q[4 * k], q[4 * k + 1], q[4 * k + 2], q[4 * k + 3], kd + 2 * k, k != 0);
                wg_commit();
            };
            auto both_issue = [&](float (&s)[32], uint32_t klo, uint32_t (&pp)[16], uint32_t vlo) {
                const uint64_t kd = mkdesc(klo), vd = mkdesc(vlo);
                wg_fence();
#pragma unroll
                for (int k = 0; k < 4; k++) {
                    mma_pv(o, pp[4 * k], pp[4 * k + 1], pp[4 * k + 2], pp[4 * k + 3], vd - k * (128 * 65535));
                    mma_qk(s, q[4 * k], q[4 * k + 1], q[4 * k + 2], q[4 * k + 3], kd + 2 * k, k != 0);
                }
                wg_commit();
            };
            auto new_max = [&](float (&s)[32], int nj, float& x0, float& x1) {
                x0 = s[0]; x1 = s[2];
#pragma unroll
                for (int j = 0; j < nj; j++) {
                    x0 = fmaxf(x0, fmaxf(s[4 * j], s[4 * j + 1]));
                    x1 = fmaxf(x1, fmaxf(s[4 * j + 2], s[4 * j + 3]));
                }
                x0 = fmaxf(x0, __shfl_xor_sync(~0u, x0, 1)); x1 = fmaxf(x1, __shfl_xor_sync(~0u, x1, 1));
                x0 = fmaxf(x0, __shfl_xor_sync(~0u, x0, 2)); x1 = fmaxf(x1, __shfl_xor_sync(~0u, x1, 2));
                x0 = fminf(n0, fmaf(x0, -CS, -20.f)); x1 = fminf(n1, fmaf(x1, -CS, -20.f));
            };
            auto probs = [&](float (&s)[32], uint32_t (&pp)[16], bool ready, bool tail, auto wait) {
                uint32_t any = 0;
#pragma unroll
                for (int i = 0; i < 16; i++) {
                    pp[i] = pack2(ex2(fmaf(s[2 * i], CS, (i & 1) ? n1 : n0)), ex2(fmaf(s[2 * i + 1], CS, (i & 1) ? n1 : n0)));
                    any |= pp[i];
                }
                wg_wait<0>();
                pin(sa); pin(sb2); pin(o); pin(pa); pin(pb);
                if (__any_sync(~0u, (any & 0x40004000u) || !ready)) {
                    wait();
                    if (__any_sync(~0u, any & 0x40004000u)) {
                        if (tail) {
#pragma unroll
                            for (int i = 20; i < 32; i++) s[i] = -INFINITY;
                        }
                        float x0, x1;
                        new_max(s, 8, x0, x1);
                        const float sc0 = ex2(x0 - n0), sc1 = ex2(x1 - n1);
                        n0 = x0; n1 = x1;
#pragma unroll
                        for (int j = 0; j < 9; j++) { o[4 * j] *= sc0; o[4 * j + 1] *= sc0; o[4 * j + 2] *= sc1; o[4 * j + 3] *= sc1; }
#pragma unroll
                        for (int i = 0; i < 16; i++)
                            pp[i] = pack2(ex2(fmaf(s[2 * i], CS, (i & 1) ? n1 : n0)), ex2(fmaf(s[2 * i + 1], CS, (i & 1) ? n1 : n0)));
                    }
                }
            };
            {
                uint4 u[4];
                const unsigned char* src = g_kvq + 2097152 + (size_t)(abh * 1024 + qt * 64 + wq * 16) * 128 + lane * 16;
                spin(QGATE);
                ld_data<512>(u, src);
#pragma unroll
                for (int k = 0; k < 2; k++) {
                    q[8 * k] = u[k].x; q[8 * k + 1] = u[k + 2].x; q[8 * k + 2] = u[k].y; q[8 * k + 3] = u[k + 2].y;
                    q[8 * k + 4] = u[k].z; q[8 * k + 5] = u[k + 2].z; q[8 * k + 6] = u[k].w; q[8 * k + 7] = u[k + 2].w;
                }
                pin(q);
            }
            TS(40);
            acq(24);
            TS(13);
            qk_issue(sa, rdesc + (24 % NSLOT) * (SLOT >> 4));
            wg_wait<0>();
            pin(sa);
            {
                float x0, x1;
                new_max(sa, NJ0, x0, x1);
                n0 = x0; n1 = x1;
            }
            bar_arrive(6, 384);
            uint32_t vd = vdesc - (SLOT >> 4) * 65535u, kd = rdesc, vb = fbar + 8, kb = fbar;
            uint32_t vlast = vdesc - 4 * (SLOT >> 4) * 65535u, klast = rdesc + 4 * (SLOT >> 4) + 512;
            uint32_t kprev = fbar + 32, vprev = bars + (B_SINK - (B_EMPTY - B_FULL)) * 8;
#pragma unroll 1
            for (int it = 0; it < 4; it++) {
                both_issue(sb2, klast, pb, vlast);
                probs(sa, pa, mbar_test(vb, it < 2) & mbar_test(kb, it < 3), false, [&]() { mbar_wait(vb, it < 2); mbar_wait(kb, it < 3); });
                TS(41 + it * 4);
                if (lane == 0) mbar_arrive(kprev + (B_EMPTY - B_FULL) * 8);
                if (lane == 0) mbar_arrive(vprev + (B_EMPTY - B_FULL) * 8);
                both_issue(sa, kd, pa, vd);
                const int dv = it == 0 ? 2 : (it == 1 ? -3 : 1);
                kprev = kb; vprev = vb; vlast = vd - 512 * 65535u; klast = kd + 512;
                vd -= dv * (SLOT >> 4) * 65535u; vb += dv * 8;
                kd += (it == 2 ? -3 : 2) * (SLOT >> 4); kb = it == 2 ? vb : kb + 16;
                probs(sb2, pb, true, it == 3 && w == 1, []() {});
                TS(43 + it * 4);
            }
            wg_fence();
#pragma unroll
            for (int k = 0; k < 4; k++)
                mma_pv(o, pb[4 * k], pb[4 * k + 1], pb[4 * k + 2], pb[4 * k + 3], mkdesc(vlast - k * (128 * 65535) + (k > 1 ? w * ((k - 1) << 22) : 0)));
            wg_commit();
            const int row = wq * 16 + (lane >> 2);
            const uint32_t ml = sb + OFF_MISC;
            mbar_wait(bars + (B_RST + 1) * 8, 0);
            wg_wait<0>();
            pin(o); pin(pb); pin(sa); pin(sb2);
            if (!(LATE & 4)) rel(31);
            const float l0 = o[32], l1 = o[34];
            if (c4 == 0) { sts64f(ml + w * 512 + row * 8, n0, l0); sts64f(ml + w * 512 + row * 8 + 64, n1, l1); }
            TS(14);
            float mine[16];
#pragma unroll
            for (int j = 0; j < 4; j++) {
                if (w == 0) sts128f(H + j * 2048 + wt * 16, o[16 + 4 * j], o[17 + 4 * j], o[18 + 4 * j], o[19 + 4 * j]);
                else sts128f(H + 8192 + j * 2048 + wt * 16, o[4 * j], o[4 * j + 1], o[4 * j + 2], o[4 * j + 3]);
            }
#pragma unroll
            for (int i = 0; i < 16; i++) mine[i] = w == 0 ? o[i] : o[16 + i];
            bar_sync(10, 256);
            const float2 u0 = lds64f(ml + (w ^ 1) * 512 + row * 8), u1 = lds64f(ml + (w ^ 1) * 512 + row * 8 + 64);
            const float x0 = fminf(n0, u0.x), x1 = fminf(n1, u1.x);
            float a0 = ex2(x0 - n0), b0 = ex2(x0 - u0.x), a1 = ex2(x1 - n1), b1 = ex2(x1 - u1.x);
            const float i0 = __fdividef(1.f, fmaf(a0, l0, b0 * u0.y)), i1 = __fdividef(1.f, fmaf(a1, l1, b1 * u1.y));
            a0 *= i0; b0 *= i0; a1 *= i1; b1 *= i1;
            uint32_t pk[8];
#pragma unroll
            for (int j = 0; j < 4; j++) {
                const float4 v = lds128f(H + (w ^ 1) * 8192 + j * 2048 + wt * 16);
                pk[2 * j] = pack2(fmaf(a0, mine[4 * j], b0 * v.x), fmaf(a0, mine[4 * j + 1], b0 * v.y));
                pk[2 * j + 1] = pack2(fmaf(a1, mine[4 * j + 2], b1 * v.z), fmaf(a1, mine[4 * j + 3], b1 * v.w));
            }
            unsigned char* dst = g_o + (size_t)(b * 128 + qt * 8 + 2 * wq) * 4096 + ah * 1024 + w * 512 + lane * 16;
            st_data(dst, pk[0], pk[2], pk[4], pk[6]);
            st_data(dst + 4096, pk[1], pk[3], pk[5], pk[7]);
            if (tid == 0) asm volatile("red.relaxed.gpu.global.add.u32 [%0], 1;" ::"l"(&g_epoch[blockIdx.x * FS]) : "memory");
            TS(15);
        }

        {
            acq(32); acq(33); acq(34);
            uint4 u[8];
            ld_data<512>(u, g_o + (size_t)(b * 128 + pt * 4 + wq) * 4096 + lane * 16);
#pragma unroll
            for (int i = 0; i < 8; i++) { a[4 * i] = u[i].x; a[4 * i + 1] = u[i].y; a[4 * i + 2] = u[i].z; a[4 * i + 3] = u[i].w; }
            if (LATE & 4) rel(31);
            TS(16);
            sp(d0, 32, a, 0, 0);
            sp(d0, 33, a + 16, 0, 1);
            residual(32);
            TS(17);
        }
    }

    cluster_arrive();
    TS(24);
    {
        const float rstd = rsq(fmaxf(fmaf(-mean, mean, msq), 0.f) + 1e-5f), nb = -mean * rstd;
#pragma unroll
        for (int j = 0; j < 8; j++) xr[j] = pack2(fmaf(v[2 * j], rstd, nb), fmaf(v[2 * j + 1], rstd, nb));
        const uint32_t stg = P + 16384 + warp * 1024;
        stsm4(stg + foff, xr[0], xr[1], xr[2], xr[3]);
        stsm4(stg + (foff ^ 64), xr[4], xr[5], xr[6], xr[7]);
        __syncwarp();
        const uint32_t src = stg + (lane >> 3) * 128 + (((lane & 7) ^ (lane >> 3)) << 4);
        const uint4 u0 = lds128(src), u1 = lds128((src + 512) ^ 64);
        __nv_bfloat16* dst = p.out + (size_t)(b * T_ + trow + (lane >> 3)) * 256 + tile * 64 + (lane & 7) * 8;
        if (trow < T_) { stg128(dst, u0); stg128(dst + 4 * 256, u1); }
    }
    TS(25);
    TG(31);
    TSDUMP();
    cluster_wait();
}

typedef CUresult (*EncodeFn)(CUtensorMap*, CUtensorMapDataType, cuuint32_t, void*, const cuuint64_t*, const cuuint64_t*,
                             const cuuint32_t*, const cuuint32_t*, CUtensorMapInterleave, CUtensorMapSwizzle,
                             CUtensorMapL2promotion, CUtensorMapFloatOOBfill);

}

extern "C" void kernel_launch(void* const* d_in, const int* in_sizes, int n_in, void* d_out, int out_size) {
    static EncodeFn encode = nullptr;
    if (!encode) {
        void* fn = nullptr;
        cudaDriverEntryPointQueryResult qr;
        cudaGetDriverEntryPoint("cuTensorMapEncodeTiled", &fn, cudaEnableDefault, &qr);
        encode = (EncodeFn)fn;
        cudaFuncSetAttribute(conformer_kernel, cudaFuncAttributeMaxDynamicSharedMemorySize, SMEM_LAUNCH);
    }
    Params p;
    const cuuint32_t ones[5] = {1, 1, 1, 1, 1};
    const int idx[8] = {1, 2, 3, 4, 5, 7, 8, 9};
    const int rows[8] = {256, 1024, 256, 256, 256, 256, 256, 1024};
    const int cols[8] = {1024, 256, 768, 256, 512, 256, 1024, 256};
    for (int i = 0; i < 8; i++) {
        const cuuint64_t pitch = (cuuint64_t)cols[i] * 2;
        const cuuint64_t dims[5] = {(cuuint64_t)cols[i], 2, 2, 4, (cuuint64_t)rows[i] / 16};
        const cuuint64_t strides[4] = {pitch, pitch * 8, pitch * 2, pitch * 16};
        const cuuint32_t box[5] = {64, 2, 2, 4, 8};
        encode(&p.tm[i], CU_TENSOR_MAP_DATA_TYPE_BFLOAT16, 5, d_in[idx[i]], dims, strides, box, ones, CU_TENSOR_MAP_INTERLEAVE_NONE,
               CU_TENSOR_MAP_SWIZZLE_128B, CU_TENSOR_MAP_L2_PROMOTION_L2_128B, CU_TENSOR_MAP_FLOAT_OOB_FILL_NONE);
        p.w[i] = (const char*)d_in[idx[i]];
    }
    {
        void* kv = nullptr;
        cudaGetSymbolAddress(&kv, g_kvq);
        const cuuint64_t dims[2] = {64, 16384};
        const cuuint64_t strides[1] = {128};
        const cuuint32_t box[2] = {64, 128};
        encode(&p.tm[8], CU_TENSOR_MAP_DATA_TYPE_BFLOAT16, 2, kv, dims, strides, box, ones, CU_TENSOR_MAP_INTERLEAVE_NONE,
               CU_TENSOR_MAP_SWIZZLE_NONE, CU_TENSOR_MAP_L2_PROMOTION_L2_128B, CU_TENSOR_MAP_FLOAT_OOB_FILL_NONE);
    }
    p.x = (const __nv_bfloat16*)d_in[0];
    p.dw = (const __nv_bfloat16*)d_in[6];
    p.out = (__nv_bfloat16*)d_out;
    p.zero = 0;
    conformer_kernel<<<NCTA, NTHREADS, SMEM_LAUNCH>>>(p);
}
```

```cpp
#include <cuda_runtime.h>
#include <cuda_bf16.h>
#include <cuda.h>
#include <stdint.h>

namespace {

constexpr int T_ = 1000;
constexpr int NCTA = 128;
constexpr int NTHREADS = 512;
constexpr int NSLOT = 5;
constexpr int SLOT = 16384;
constexpr int NLOADS = 56;

constexpr uint32_t OFF_RING = 0;
constexpr uint32_t OFF_P = 163840;
constexpr uint32_t OFF_H = 188416;
constexpr uint32_t OFF_MISC = 221184;
constexpr uint32_t OFF_BARS = 229888;
constexpr uint32_t SMEM_BYTES = 230400;
constexpr uint32_t GCH = 6144;
constexpr uint32_t HCH = 4096;

constexpr int B_FULL = 0, B_EMPTY = 10, B_XA = 20  , B_XB = 25  , B_INB = 29  , B_SR = 33,
              B_RST = 34  , B_RDY = 36  , B_SINK = 42, B_HALO = 43  , NBARS = 47;

#define KD2 300u
#define KD3 500u
#define QGATE 500u
#define BACKOFF 0u
#define KFS 8
#define KDELAY 300u
#define NJ0 2
#define HDELAY 200u
#define LATE 2
#define TURN 0
#define EAGER 0x4755
constexpr int FS = 8;

struct Params {
    CUtensorMap tm[9];
    const char* w[8];
    const __nv_bfloat16* x;
    const __nv_bfloat16* dw;
    __nv_bfloat16* out;
    uint32_t zero;
};

__device__ __align__(1024) unsigned char g_kvq[3 * 8 * 1024 * 128];
__device__ __align__(1024) unsigned char g_o[2 * 128 * 4096];
__device__ uint4 g_halo[64 * 4 * 2 * 64];
__device__ __align__(128) uint32_t g_flag_kv[8 * 32 * KFS];
__device__ uint32_t g_reset[4 * 32];
__device__ uint32_t g_epoch[NCTA * FS];

#define TS(i) do { } while (0)
#define TSW(i) do { } while (0)
#define TG(i) do { } while (0)
#define TSINIT() do { } while (0)
#define TSDUMP() do { } while (0)
constexpr uint32_t SMEM_LAUNCH = SMEM_BYTES;

__device__ __forceinline__ uint32_t smem_u32(const void* p) { return (uint32_t)__cvta_generic_to_shared(p); }
__device__ __forceinline__ void mbar_init(uint32_t b, uint32_t c) { asm volatile("mbarrier.init.shared::cta.b64 [%0], %1;" ::"r"(b), "r"(c) : "memory"); }
__device__ __forceinline__ void mbar_arrive(uint32_t b) { asm volatile("mbarrier.arrive.shared::cta.b64 _, [%0];" ::"r"(b) : "memory"); }
__device__ __forceinline__ void mbar_arrive_tx(uint32_t b, uint32_t tx) { asm volatile("mbarrier.arrive.expect_tx.shared::cta.b64 _, [%0], %1;" ::"r"(b), "r"(tx) : "memory"); }
__device__ __forceinline__ void mbar_wait(uint32_t b, uint32_t ph) {
    asm volatile("{\n.reg .pred p, q;\n.reg .u32 c;\nmov.u32 c, 0;\n"
                 "MW_LOOP:\n.pragma \"nounroll\";\n"
                 "mbarrier.try_wait.parity.shared::cta.b64 p, [%0], %1;\n"
                 "add.u32 c, c, 1;\nsetp.lt.u32 q, c, 65536;\nnot.pred p, p;\nand.pred p, p, q;\n@p bra MW_LOOP;\n}"
                 ::"r"(b), "r"(ph) : "memory");
}
__device__ __forceinline__ bool mbar_test(uint32_t b, uint32_t ph) {
    uint32_t ok;
    asm volatile("{\n.reg .pred p;\nmbarrier.test_wait.parity.shared::cta.b64 p, [%1], %2;\nselp.u32 %0, 1, 0, p;\n}" : "=r"(ok) : "r"(b), "r"(ph) : "memory");
    return ok;
}
__device__ __forceinline__ uint32_t mapa(uint32_t a, uint32_t r) { uint32_t o; asm("mapa.shared::cluster.u32 %0, %1, %2;" : "=r"(o) : "r"(a), "r"(r)); return o; }
__device__ __forceinline__ void fence_async_smem() { asm volatile("fence.proxy.async.shared::cta;" ::: "memory"); }
__device__ __forceinline__ void fence_async_global() { asm volatile("fence.proxy.async.global;" ::: "memory"); }
__device__ __forceinline__ void bar_sync(int id, int n) { asm volatile("bar.sync %0, %1;" ::"r"(id), "r"(n) : "memory"); }
__device__ __forceinline__ void bar_arrive(int id, int n) { asm volatile("bar.arrive %0, %1;" ::"r"(id), "r"(n) : "memory"); }
__device__ __forceinline__ void cluster_arrive() { asm volatile("barrier.cluster.arrive.relaxed.aligned;" ::: "memory"); }
__device__ __forceinline__ void cluster_wait() { asm volatile("barrier.cluster.wait.aligned;" ::: "memory"); }

__device__ __forceinline__ void ring_load(uint32_t dst, const CUtensorMap* tm, int col, int row16, uint32_t bar) {
    asm volatile("{\n.reg .pred p;\nelect.sync _|p, 0xffffffff;\n"
                 "@p mbarrier.arrive.expect_tx.shared::cta.b64 _, [%2], 16384;\n"
                 "@p cp.async.bulk.tensor.5d.shared::cluster.global.mbarrier::complete_tx::bytes [%0], [%1, {%3, 0, 0, 0, %4}], [%2];\n}"
                 ::"r"(dst), "l"(tm), "r"(bar), "r"(col), "r"(row16) : "memory");
}
__device__ __forceinline__ void ring_load_both(uint32_t dst, const CUtensorMap* tm, int c1, uint32_t bar) {
    asm volatile("{\n.reg .pred p;\nelect.sync _|p, 0xffffffff;\n"
                 "@p cp.async.bulk.tensor.2d.shared::cluster.global.mbarrier::complete_tx::bytes.multicast::cluster [%0], [%1, {0, %3}], [%2], %4;\n}"
                 ::"r"(dst), "l"(tm), "r"(bar), "r"(c1), "h"((uint16_t)3) : "memory");
}
__device__ __forceinline__ void mbar_arrive_peer(uint32_t b) { asm volatile("mbarrier.arrive.relaxed.cluster.shared::cluster.b64 _, [%0];" ::"r"(b) : "memory"); }
__device__ __forceinline__ void prefetch_l2(const void* src, uint32_t bytes) {
    asm volatile("cp.async.bulk.prefetch.L2.global [%0], %1;" ::"l"(src), "r"(bytes) : "memory");
}
__device__ __forceinline__ void peer_copy(uint32_t dst, uint32_t src, uint32_t bytes, uint32_t rbar) {
    asm volatile("{\n.reg .pred p;\nelect.sync _|p, 0xffffffff;\n"
                 "@p cp.async.bulk.shared::cluster.shared::cta.mbarrier::complete_tx::bytes [%0], [%1], %2, [%3];\n}"
                 ::"r"(dst), "r"(src), "r"(bytes), "r"(rbar) : "memory");
}
__device__ __forceinline__ void st_async4(uint32_t dst, uint32_t a, uint32_t b, uint32_t c, uint32_t d, uint32_t bar) {
    asm volatile("st.async.shared::cluster.mbarrier::complete_tx::bytes.v4.b32 [%0], {%1,%2,%3,%4}, [%5];" ::"r"(dst), "r"(a), "r"(b), "r"(c), "r"(d), "r"(bar) : "memory");
}
__device__ __forceinline__ void st_async2f(uint32_t dst, float a, float b, uint32_t bar) {
    asm volatile("st.async.shared::cluster.mbarrier::complete_tx::bytes.v2.f32 [%0], {%1,%2}, [%3];" ::"r"(dst), "f"(a), "f"(b), "r"(bar) : "memory");
}
__device__ __forceinline__ void stsm4(uint32_t a, uint32_t r0, uint32_t r1, uint32_t r2, uint32_t r3) {
    asm volatile("stmatrix.sync.aligned.m8n8.x4.shared.b16 [%0], {%1,%2,%3,%4};" ::"r"(a), "r"(r0), "r"(r1), "r"(r2), "r"(r3) : "memory");
}
__device__ __forceinline__ void ldsm4(uint32_t a, uint32_t& r0, uint32_t& r1, uint32_t& r2, uint32_t& r3) {
    asm volatile("ldmatrix.sync.aligned.m8n8.x4.shared.b16 {%0,%1,%2,%3}, [%4];" : "=r"(r0), "=r"(r1), "=r"(r2), "=r"(r3) : "r"(a) : "memory");
}
__device__ __forceinline__ uint4 lds128(uint32_t a) { uint4 v; asm volatile("ld.shared.v4.b32 {%0,%1,%2,%3}, [%4];" : "=r"(v.x), "=r"(v.y), "=r"(v.z), "=r"(v.w) : "r"(a) : "memory"); return v; }
__device__ __forceinline__ float4 lds128f(uint32_t a) { float4 v; asm volatile("ld.shared.v4.f32 {%0,%1,%2,%3}, [%4];" : "=f"(v.x), "=f"(v.y), "=f"(v.z), "=f"(v.w) : "r"(a) : "memory"); return v; }
__device__ __forceinline__ float2 lds64f(uint32_t a) { float2 v; asm volatile("ld.shared.v2.f32 {%0,%1}, [%2];" : "=f"(v.x), "=f"(v.y) : "r"(a) : "memory"); return v; }
__device__ __forceinline__ uint32_t lds32(uint32_t a) { uint32_t v; asm volatile("ld.shared.b32 %0, [%1];" : "=r"(v) : "r"(a) : "memory"); return v; }
__device__ __forceinline__ void sts128(uint32_t a, uint32_t x, uint32_t y, uint32_t z, uint32_t w) { asm volatile("st.shared.v4.b32 [%0], {%1,%2,%3,%4};" ::"r"(a), "r"(x), "r"(y), "r"(z), "r"(w) : "memory"); }
__device__ __forceinline__ void sts128f(uint32_t a, float x, float y, float z, float w) { asm volatile("st.shared.v4.f32 [%0], {%1,%2,%3,%4};" ::"r"(a), "f"(x), "f"(y), "f"(z), "f"(w) : "memory"); }
__device__ __forceinline__ void sts64f(uint32_t a, float x, float y) { asm volatile("st.shared.v2.f32 [%0], {%1,%2};" ::"r"(a), "f"(x), "f"(y) : "memory"); }
__device__ __forceinline__ void sts32(uint32_t a, uint32_t x) { asm volatile("st.shared.b32 [%0], %1;" ::"r"(a), "r"(x) : "memory"); }
__device__ __forceinline__ void stg128(void* p, uint4 v) { asm volatile("st.global.v4.b32 [%0], {%1,%2,%3,%4};" ::"l"(p), "r"(v.x), "r"(v.y), "r"(v.z), "r"(v.w) : "memory"); }

__device__ __forceinline__ uint32_t pack2(float lo, float hi) { uint32_t r; asm("cvt.rn.bf16x2.f32 %0, %1, %2;" : "=r"(r) : "f"(hi), "f"(lo)); return r; }
__device__ __forceinline__ float blo(uint32_t v) { return __uint_as_float(v << 16); }
__device__ __forceinline__ float bhi(uint32_t v) { return __uint_as_float(v & 0xffff0000u); }
__device__ __forceinline__ uint32_t hmul2(uint32_t a, uint32_t b) { uint32_t r; asm("mul.rn.bf16x2 %0, %1, %2;" : "=r"(r) : "r"(a), "r"(b)); return r; }
__device__ __forceinline__ uint32_t hadd2(uint32_t a, uint32_t b) { uint32_t r; asm("add.rn.bf16x2 %0, %1, %2;" : "=r"(r) : "r"(a), "r"(b)); return r; }
__device__ __forceinline__ uint32_t hsub2(uint32_t a, uint32_t b) { uint32_t r; asm("sub.rn.bf16x2 %0, %1, %2;" : "=r"(r) : "r"(a), "r"(b)); return r; }
__device__ __forceinline__ uint32_t hfma2(uint32_t a, uint32_t b, uint32_t c) { uint32_t r; asm("fma.rn.bf16x2 %0, %1, %2, %3;" : "=r"(r) : "r"(a), "r"(b), "r"(c)); return r; }
__device__ __forceinline__ float tanh_fast(float x) { float r; asm("tanh.approx.f32 %0, %1;" : "=f"(r) : "f"(x)); return r; }
__device__ __forceinline__ float rsq(float x) { float r; asm("rsqrt.approx.ftz.f32 %0, %1;" : "=f"(r) : "f"(x)); return r; }
__device__ __forceinline__ float ex2(float x) { float r; asm("ex2.approx.ftz.f32 %0, %1;" : "=f"(r) : "f"(x)); return r; }

__device__ __forceinline__ uint32_t ld_relaxed(const uint32_t* p) {
    uint32_t v;
    asm volatile("ld.relaxed.gpu.global.u32 %0, [%1];" : "=r"(v) : "l"(p) : "memory");
    return v;
}
__device__ __forceinline__ uint32_t clock32() { uint32_t c; asm volatile("mov.u32 %0, %%clock;" : "=r"(c)::"memory"); return c; }
__device__ __forceinline__ void spin(uint32_t clks) {
    const uint32_t t0 = clock32();
    while (clock32() - t0 < clks) {}
}
__device__ __forceinline__ void flag_wait(const uint32_t* p, uint32_t e, bool mine) {
#pragma unroll 1
    for (int i = 0; i < (1 << 19); i++) {
        if (mine) mine = ld_relaxed(p) != e;
        if (!__any_sync(~0u, mine)) break;
        if (BACKOFF) spin(BACKOFF);
    }
    asm volatile("fence.acquire.gpu;" ::: "memory");
    fence_async_global();
}
__device__ __forceinline__ void st_data(void* p, uint32_t x, uint32_t y, uint32_t z, uint32_t w) {
    asm volatile("st.relaxed.gpu.global.v4.b32 [%0], {%1,%2,%3,%4};" ::"l"(p), "r"(x), "r"(y), "r"(z), "r"(w) : "memory");
}
template <int STRIDE, int N>
__device__ __forceinline__ void ld_data(uint4 (&v)[N], const unsigned char* p) {
    int it = 0;
    bool again;
#pragma unroll 1
    do {
        uint32_t m = 0;
#pragma unroll
        for (int i = 0; i < N; i++)
            asm volatile("ld.relaxed.gpu.global.v4.b32 {%0,%1,%2,%3}, [%4];" : "=r"(v[i].x), "=r"(v[i].y), "=r"(v[i].z), "=r"(v[i].w) : "l"(p + i * STRIDE) : "memory");
#pragma unroll
        for (int i = 0; i < N; i++) m = __vimax3_u32(__vimax3_u32(v[i].x, v[i].y, v[i].z), v[i].w, m);
        again = __any_sync(~0u, m == ~0u) && ++it < (1 << 16);
    } while (again);
}
__device__ __forceinline__ uint32_t ld_epoch() { return ld_relaxed(&g_epoch[blockIdx.x * FS]) + 1; }
__device__ __forceinline__ void flag_set(uint32_t* p, uint32_t e) { asm volatile("st.release.gpu.global.u32 [%0], %1;" ::"l"(p), "r"(e) : "memory"); }

__device__ __forceinline__ uint32_t desc_lo(uint32_t addr) { return ((addr & 0x3FFFF) >> 4) | 0x10000u; }
__device__ __forceinline__ uint64_t mkdesc(uint32_t lo) { return (uint64_t)lo | (0x40000040ull << 32); }
__device__ __forceinline__ void wg_fence() { asm volatile("wgmma.fence.sync.aligned;" ::: "memory"); }
__device__ __forceinline__ void wg_commit() { asm volatile("wgmma.commit_group.sync.aligned;" ::: "memory"); }
template <int N> __device__ __forceinline__ void wg_wait() { asm volatile("wgmma.wait_group.sync.aligned %0;" ::"n"(N) : "memory"); }
template <int N> __device__ __forceinline__ void pin(float (&d)[N]) {
#pragma unroll
    for (int i = 0; i < N; i++) asm volatile("" : "+f"(d[i])::"memory");
}
template <int N> __device__ __forceinline__ void pin(uint32_t (&d)[N]) {
#pragma unroll
    for (int i = 0; i < N; i++) asm volatile("" : "+r"(d[i])::"memory");
}

template <typename Tp, int N> __device__ __forceinline__ void zero(Tp (&d)[N]) {
#pragma unroll
    for (int i = 0; i < N; i++) d[i] = 0;
    pin(d);
}

#define F4(d, i) "+f"(d[i]), "+f"(d[i + 1]), "+f"(d[i + 2]), "+f"(d[i + 3])
#define F16(d, i) F4(d, i), F4(d, i + 4), F4(d, i + 8), F4(d, i + 12)

__device__ __forceinline__ void mma_sp(float (&d)[32], const uint32_t* a, uint64_t b, uint32_t meta, int acc) {
    asm volatile("{.reg .pred p; setp.ne.b32 p, %38, 0;\n"
                 "wgmma.mma_async.sp.sync.aligned.m64n64k32.f32.bf16.bf16 {%0,%1,%2,%3,%4,%5,%6,%7,%8,%9,%10,%11,%12,%13,%14,%15,%16,%17,%18,%19,%20,%21,%22,%23,%24,%25,%26,%27,%28,%29,%30,%31}, "
                 "{%32,%33,%34,%35}, %36, %37, 0, p, 1, 1, 1;}\n"
                 : F16(d, 0), F16(d, 16) : "r"(a[0]), "r"(a[1]), "r"(a[2]), "r"(a[3]), "l"(b), "r"(meta), "r"(acc));
}
__device__ __forceinline__ void mma_qk(float (&d)[32], uint32_t a0, uint32_t a1, uint32_t a2, uint32_t a3, uint64_t b, int acc) {
    asm volatile("{.reg .pred p; setp.ne.b32 p, %37, 0;\n"
                 "wgmma.mma_async.sync.aligned.m64n64k16.f32.bf16.bf16 {%0,%1,%2,%3,%4,%5,%6,%7,%8,%9,%10,%11,%12,%13,%14,%15,%16,%17,%18,%19,%20,%21,%22,%23,%24,%25,%26,%27,%28,%29,%30,%31}, "
                 "{%32,%33,%34,%35}, %36, p, 1, 1, 0;}\n"
                 : F16(d, 0), F16(d, 16) : "r"(a0), "r"(a1), "r"(a2), "r"(a3), "l"(b), "r"(acc));
}
__device__ __forceinline__ void mma_pv(float (&d)[36], uint32_t a0, uint32_t a1, uint32_t a2, uint32_t a3, uint64_t b) {
    asm volatile("wgmma.mma_async.sync.aligned.m64n72k16.f32.bf16.bf16 {%0,%1,%2,%3,%4,%5,%6,%7,%8,%9,%10,%11,%12,%13,%14,%15,%16,%17,%18,%19,%20,%21,%22,%23,%24,%25,%26,%27,%28,%29,%30,%31,%32,%33,%34,%35}, "
                 "{%36,%37,%38,%39}, %40, 1, 1, 1, 1;\n"
                 : F16(d, 0), F16(d, 16), F4(d, 32) : "r"(a0), "r"(a1), "r"(a2), "r"(a3), "l"(b));
}

__device__ __forceinline__ uint32_t load_code(int n, int r, int w) {
    const int tile = 2 * r + w;
    int m, col, row;
    if (n < 16 || n >= 40) {
        const int k = n < 16 ? n : n - 40;
        m = n < 16 ? 0 : 6;
        if (k < 8) { col = 4 * tile + (k >> 1); row = (k & 1) ^ r; }
        else { m++; col = tile ^ (3 - ((k - 8) >> 1)); row = 2 * tile + (k & 1); }
    } else if (n < 32) {
        const int k = n - 16;
        m = 2;
        if (k < 4) { col = tile + ((k & 1) ? 8 : 4); row = (k >> 1) ^ r; }
        else { col = tile; row = (k & 1) ^ r; }
    } else if (n < 34) { m = 3; col = tile; row = n - 32; }
    else if (n < 38) { const int k = n - 34; m = 4; col = tile + 4 * (k & 1); row = (k >> 1) ^ r; }
    else { m = 5; col = tile; row = (n & 1) ^ r; }
    return m | (col << 4) | (row << 8);
}

__global__ void __cluster_dims__(2, 1, 1) __launch_bounds__(NTHREADS, 1)
conformer_kernel(const __grid_constant__ Params p) {
    extern __shared__ __align__(1024) unsigned char smem_raw[];
    const uint32_t sb = smem_u32(smem_raw);
    const uint32_t bars = sb + OFF_BARS;
    const int tid = threadIdx.x;
    const int lane = tid & 31;
    const int warp = __shfl_sync(~0u, tid >> 5, 0);
    const int r = blockIdx.x & 1;
    const int pair = blockIdx.x >> 1;
    const int b = pair >> 5, pt = pair & 31;
    const int ah = pt >> 3, qt = (pt & 7) * 2 + r;
    const int abh = b * 4 + ah;

    TG(30);
    TSINIT();
    TS(0);
    const uint32_t P = sb + OFF_P, H = sb + OFF_H;

    if (warp >= 8) {
        asm volatile("setmaxnreg.dec.sync.aligned.u32 48;");
        if (warp >= 12) {
            cluster_arrive();
            cluster_wait();
            const int ut = tid & 127;
            const uint32_t target = ld_epoch() * 64;
            auto reset_done = [&](int k) {
                bar_sync(11, 128);
                if (ut == 0) {
                    asm volatile("red.release.gpu.global.add.u32 [%0], 1;" ::"l"(&g_reset[(2 * b + k) * 32]) : "memory");
#pragma unroll 1
                    for (int i = 0; i < (1 << 20) && ld_relaxed(&g_reset[(2 * b + k) * 32]) != target; i++) __nanosleep(100);
                    asm volatile("fence.acquire.gpu;" ::: "memory");
                    mbar_arrive(bars + (B_RST + k) * 8);
                }
                __syncwarp();
                TS(13 + k);
            };
#pragma unroll
            for (int i = 0; i < 4; i++)
                st_data(g_kvq + 2097152 + (size_t)((b * 4 + 2 * r + (i >> 1)) * 1024 + pt * 32) * 128 + (i & 1) * 2048 + ut * 16, ~0u, ~0u, ~0u, ~0u);
            reset_done(0);
            bar_sync(6, 384);
#pragma unroll
            for (int i = 0; i < 4; i++) {
                st_data(g_o + (size_t)(b * 128 + qt * 8 + 2 * i + (ut >> 6)) * 4096 + ah * 1024 + (ut & 63) * 16, ~0u, ~0u, ~0u, ~0u);
                if (i < 2) st_data(&g_halo[(pair * 4 + 2 * r + i) * 128 + ut], ~0u, ~0u, ~0u, ~0u);
            }
            reset_done(1);
            const int side = warp & 1, wg = (warp >> 1) & 1, np = side ? pt + 1 : pt - 1;
            const unsigned char* src = reinterpret_cast<const unsigned char*>(&g_halo[(((b * 32 + np) * 4 + 2 * r + wg) * 2 + (side ^ 1)) * 64 + lane]);
            const uint32_t dst = H + 16384 + wg * GCH + side * 5120 + (lane & 7) * 128 + (((lane >> 3) ^ (lane & 7)) << 4);
            uint4 hv[2] = {make_uint4(0, 0, 0, 0), make_uint4(0, 0, 0, 0)};
            bar_sync(8 + wg, 192);
            if (np >= 0 && np < 32) {
                spin(HDELAY);
                ld_data<512>(hv, src);
            }
            stsm4(dst, hv[0].x, hv[0].y, hv[0].z, hv[0].w);
            stsm4(dst ^ 64, hv[1].x, hv[1].y, hv[1].z, hv[1].w);
            __syncwarp();
            if (lane == 0) mbar_arrive(bars + (B_HALO + (warp & 3)) * 8);
            TS(4);
        } else if (warp < 10) {
            const int w = warp - 8;
            const uint32_t ring = sb + OFF_RING + w * NSLOT * SLOT;
            const uint32_t full = bars + (B_FULL + w * NSLOT) * 8;
            if (lane == 0) {
#pragma unroll
                for (int i = 0; i < NSLOT; i++) { mbar_init(full + i * 8, 1); mbar_init(full + (B_EMPTY - B_FULL + i) * 8, 4); }
                asm volatile("fence.mbarrier_init.release.cluster;" ::: "memory");
                fence_async_smem();
            }
            __syncwarp();
            cluster_arrive();
            TS(1);
#pragma unroll
            for (int n = 0; n < NSLOT; n++) {
                if (n == 1 || n == 2) bar_sync(12, 64);
                ring_load(ring + n * SLOT, &p.tm[0], 64 * (8 * r + 4 * w + (n >> 1)), 8 * ((n & 1) ^ r), full + n * 8);
            }
            TS(2);
            const uint32_t code = load_code(lane, r, w) | (load_code(lane + 32, r, w) << 16);
            cluster_wait();
            uint32_t s = 0, ph = 0;
            int n = NSLOT;
#pragma unroll 1
            for (int seg = 0; seg < 2; seg++) {
#pragma unroll 1
                for (; n < (seg == 0 ? 22 : NLOADS); n++) {
                    const uint32_t c = __shfl_sync(~0u, code, n) >> (n & 32 ? 16 : 0);
                    const CUtensorMap* tm = &p.tm[c & 15];
                    const uint32_t col = (c & 0xf0) * 4, row = (c & 0xff00) >> 5, dst = ring + s * SLOT;
                    mbar_wait(full + (B_EMPTY - B_FULL) * 8 + s * 8, ph + (((uint32_t)(size_t)tm | col | row | dst) & p.zero));
                    ring_load(dst, tm, col, row, full + s * 8);
                    if (++s == NSLOT) { s = 0; ph ^= 1; }
                }
                if (seg == 1) break;
                const uint32_t epoch = ld_epoch();
                const uint32_t rdy = bars + (B_RDY + 3 * w) * 8, prdy = mapa(rdy, r ^ 1);
                const int odd = r ^ w;
                const uint32_t* flags = g_flag_kv + (abh * 32 + lane) * KFS;
                auto kv_load = [&](uint32_t sl, int isv, int i) {
                    ring_load_both(ring + sl * SLOT, &p.tm[8], (isv * 64 + abh * 8 + 2 * i + w) * 128, full + sl * 8);
                };
#pragma unroll 1
                for (int i = 0; i < 2; i++) {
                    if (lane < 3 + i) {
                        const uint32_t sl = i ? lane : lane + 2;
                        mbar_wait(full + (B_EMPTY - B_FULL + sl) * 8, i ^ 1);
                        mbar_arrive_tx(full + sl * 8, (i || lane == 2) ? SLOT : 0);
                    }
                    __syncwarp();
                }
                if (lane == 0) mbar_arrive_peer(prdy);
                bar_sync(14, 96);
                spin(KDELAY);
                mbar_wait(rdy, 0);
                flag_wait(flags, epoch, (lane >> 2) == 2 * odd + w);
                TSW(5 + 2 * odd);
                if (!odd) { kv_load(4, 0, 0); bar_arrive(12, 64); }
                else bar_sync(12, 64);
                spin(w ? KD3 : KD2);
                kv_load(odd ^ 1, odd ^ 1, odd);
                flag_wait(flags, epoch, (lane >> 2) == 2 * odd + w + 4);
                mbar_wait(full + (odd ^ 1) * 8, 1);
                kv_load(2 + odd, odd, 2 - odd);
#pragma unroll 1
                for (int i = 0; i < 3; i++) {
                    const uint32_t sl = i ? i - 1 : 4, bo = i == 2 ? 16 : 8;
                    mbar_wait(full + (B_EMPTY - B_FULL + sl) * 8, i != 0);
                    if (lane == 0) mbar_arrive_tx(full + sl * 8, SLOT);
                    if ((i & 1) != odd) {
                        mbar_wait(rdy + bo, 0);
                        kv_load(sl, i != 0, 2 + odd);
                    } else if (lane == 0) mbar_arrive_peer(prdy + bo);
                    __syncwarp();
                }
                n = 32; s = 2; ph = 1;
            }
        } else if (warp == 10) {
            if (lane == 0) {
#pragma unroll
                for (int i = B_XA; i < NBARS; i++) mbar_init(bars + i * 8, 1);
#pragma unroll
                for (int i = B_XA; i <= B_SR; i++) mbar_arrive_tx(bars + i * 8, i < B_XB ? 512 : 8192);
                asm volatile("fence.mbarrier_init.release.cluster;" ::: "memory");
                fence_async_smem();
            }
            __syncwarp();
            cluster_arrive();
            cluster_wait();
        } else {
            const uint32_t kb = (lane < 2 || lane > 5) ? 4096 : (lane == 2 ? 3072 : (lane == 4 ? 2048 : 1024));
            const char* pf = p.w[lane & 7] + blockIdx.x * kb;
            cluster_arrive();
            cluster_wait();
            if (lane < 2) prefetch_l2(pf, kb);
            mbar_wait(bars + B_XA * 8, 0);
            if (lane == 2) prefetch_l2(pf, kb);
            if (lane >= 1 && lane < 9) asm volatile("prefetch.tensormap [%0];" ::"l"(&p.tm[lane]) : "memory");
            mbar_wait(bars + (B_FULL + 1) * 8, 1);
            if (lane > 2 && lane < 8) prefetch_l2(pf, kb);
            if (lane == 8 && blockIdx.x < 15) prefetch_l2(p.dw + blockIdx.x * 256, 512);
            const uint32_t epoch = ld_epoch();
            bar_sync(4, 288);
            if (lane < 16) flag_set(&g_flag_kv[((b * 4 + 2 * r + (lane >> 3)) * 32 + pt) * KFS + (lane & 7)], epoch);
            __syncwarp();
            bar_arrive(14, 96);
            TSW(8);
        }
        TSDUMP();
        return;
    }

    const int w = warp >> 2, wq = warp & 3;
    const int tile = 2 * r + w;
    const int wt = tid & 127;
    const int c4 = lane & 3;
    const int trow = pt * 32 + 8 * wq;
    uint32_t xr[8];
    {
        const uint32_t* xp = reinterpret_cast<const uint32_t*>(p.x + (size_t)(b * T_ + trow + (lane >> 2)) * 256 + tile * 64) + c4;
#pragma unroll
        for (int j = 0; j < 8; j++) xr[j] = trow < T_ ? __ldg(xp + 4 * j) : 0u;
    }
    cluster_arrive();
    asm volatile("setmaxnreg.inc.sync.aligned.u32 208;");
    const uint32_t rbase = sb + OFF_RING + w * NSLOT * SLOT, fbar = bars + (B_FULL + w * NSLOT) * 8;
    const uint32_t rdesc = desc_lo(rbase);
    auto acq = [&](int n) { mbar_wait(fbar + (n % NSLOT) * 8, (n / NSLOT) & 1); };
    auto rel = [&](int n) { if (lane == 0) mbar_arrive(fbar + (B_EMPTY - B_FULL + n % NSLOT) * 8); };
    const uint32_t foff = (lane & 7) * 128 + (((lane >> 3) ^ (lane & 7)) << 4);
    float v[16];
#pragma unroll
    for (int j = 0; j < 8; j++) { v[2 * j] = blo(xr[j]); v[2 * j + 1] = bhi(xr[j]); }
    const uint32_t xown = __shfl_sync(~0u, P + wt * 16 + tile * 4096, lane), xrem = __shfl_sync(~0u, P + wt * 16 + (r ^ 1) * 8192, lane);
    const uint32_t sbuf = __shfl_sync(~0u, sb + OFF_MISC + 1024 + (8 * wq + (lane >> 2)) * 32, lane);
    const uint32_t sown = __shfl_sync(~0u, sbuf + tile * 8, lane);
    const uint32_t peer = __shfl_sync(~0u, mapa(sb, r ^ 1) - sb, lane);
    const uint32_t meta = __shfl_sync(~0u, 0xEEEE4444u + p.zero, lane);
    cluster_wait();
    TS(56);
    float mean, msq;
    const int mir = wq < 2 ? 7 : 0;
    uint32_t dwr[15] = {};

#pragma unroll 1
    for (int ph = 0;; ph++) {
        uint4 o0, o1;
        {
            float s = 0.f, q = 0.f, s2 = 0.f, q2 = 0.f;
#pragma unroll
            for (int j = 0; j < 4; j++) {
                s += v[4 * j] + v[4 * j + 1]; s2 += v[4 * j + 2] + v[4 * j + 3];
                q += fmaf(v[4 * j], v[4 * j], v[4 * j + 1] * v[4 * j + 1]); q2 += fmaf(v[4 * j + 2], v[4 * j + 2], v[4 * j + 3] * v[4 * j + 3]);
            }
            s += s2; q += q2;
            const uint32_t xa = bars + (B_XA + ph) * 8;
            s += __shfl_xor_sync(~0u, s, 1); q += __shfl_xor_sync(~0u, q, 1);
            s += __shfl_xor_sync(~0u, s, 2); q += __shfl_xor_sync(~0u, q, 2);
            if (c4 == 0) st_async2f(sown + peer, s, q, xa + peer);
            if (c4 == 0) sts64f(sown, s, q);
#pragma unroll
            for (int j = 0; j < 8; j++) xr[j] = pack2(v[2 * j], v[2 * j + 1]);
            sts128(xown, xr[0], xr[1], xr[2], xr[3]);
            sts128(xown + 2048, xr[4], xr[5], xr[6], xr[7]);
            bar_sync(10, 256);
            o0 = lds128(xown ^ 4096); o1 = lds128((xown ^ 4096) + 2048);
            if (ph < 4) {
                st_async4(xown + peer, xr[0], xr[1], xr[2], xr[3], xa + (B_XB - B_XA) * 8 + peer);
                st_async4(xown + peer + 2048, xr[4], xr[5], xr[6], xr[7], xa + (B_XB - B_XA) * 8 + peer);
            }
            TS(57 + ph);
            if (ph == 0 || ph == 3) acq(0);
            mbar_wait(xa, 0);
            const float4 u0 = lds128f(sbuf), u1 = lds128f(sbuf + 16);
            mean = ((u0.x + u0.z) + (u1.x + u1.z)) * (1.f / 256.f);
            msq = ((u0.y + u0.w) + (u1.y + u1.w)) * (1.f / 256.f);
        }
        if (ph == 4) break;
        uint32_t a[32];
        const uint32_t mean2 = pack2(mean, mean);
        auto centre = [&](int i, const uint4& u) {
            a[i] = hsub2(u.x, mean2); a[i + 1] = hsub2(u.y, mean2); a[i + 2] = hsub2(u.z, mean2); a[i + 3] = hsub2(u.w, mean2);
        };
#pragma unroll
        for (int j = 0; j < 8; j++) a[j] = hsub2(xr[j], mean2);
        centre(8, o0); centre(12, o1);
        const float rstd = rsq(fmaxf(fmaf(-mean, mean, msq), 0.f) + 1e-5f);
        auto gather_peer = [&]() {
            mbar_wait(bars + (B_XB + ph) * 8, 0);
#pragma unroll
            for (int i = 0; i < 4; i++) centre(16 + 4 * i, lds128(xrem + i * 2048));
        };
        auto sp = [&](float (&d)[32], int n, const uint32_t* af, int flip, int acc) {
            const uint32_t lo = rdesc + p.zero * (ph + n + 1) + (n % NSLOT) * (SLOT >> 4);
            const uint64_t b0 = mkdesc(lo + flip * 512), b1 = mkdesc(lo + (flip ^ 1) * 512);
            wg_fence();
            mma_sp(d, af, b0, meta, acc);
            mma_sp(d, af + 4, b0 + 256, meta, 1);
            mma_sp(d, af + 8, b1, meta, 1);
            mma_sp(d, af + 12, b1 + 256, meta, 1);
            wg_commit();
        };
        float d0[32], d1[32];

        if (ph == 0 || ph == 3) {
            uint32_t h[32];
            const float rs = 0.5f * rstd;
            const uint32_t inb = bars + (B_INB + (ph & 2)) * 8, box = H + wt * 16;
            bool ready = true;
            auto step = [&](float (&d)[32], int n, const uint32_t* af, int flip, int acc, auto work) {
                if (!ready) acq(n);
                if (((TURN >> n) & 1) && w == 1) bar_sync(7, 256);
                sp(d, n, af, flip, acc);
                if (n > 0 && ((TURN >> (n - 1)) & 1) && w == 0) bar_arrive(7, 256);
                if (n < 15) ready = mbar_test(fbar + ((n + 1) % NSLOT) * 8, ((n + 1) / NSLOT) & 1);
                wg_wait<1>();
                if (n > 0 && !((EAGER >> (n - 1)) & 1)) rel(n - 1);
                const uint32_t tie = work() & p.zero;
                if ((EAGER >> n) & 1) {
                    if (p.zero < n + ph + 1) wg_wait<0>();
                    if (lane == 0) mbar_arrive(fbar + (B_EMPTY - B_FULL + n % NSLOT) * 8 + tie);
                }
            };
            auto none = []() { return 0u; };
            auto act = [&](float (&d)[32], int i) {
                pin(d);
#pragma unroll
                for (int j = 0; j < 8; j++) {
                    const float u0 = (d[4 * j] + d[4 * j + 2]) * rs, u1 = (d[4 * j + 1] + d[4 * j + 3]) * rs;
                    h[8 * i + j] = pack2(fmaf(u0, tanh_fast(u0), u0), fmaf(u1, tanh_fast(u1), u1));
                }
                return h[8 * i] | h[8 * i + 1] | h[8 * i + 2] | h[8 * i + 3] | h[8 * i + 4] | h[8 * i + 5] | h[8 * i + 6] | h[8 * i + 7];
            };
            auto send = [&](float (&d)[32], int x) {
                pin(d);
                uint32_t pk[8];
#pragma unroll
                for (int j = 0; j < 8; j++) pk[j] = pack2(d[4 * j] + d[4 * j + 2], d[4 * j + 1] + d[4 * j + 3]);
                const uint32_t ow = w ^ (x & 1), dst = box + (ow * 3 + x - 1) * 4096;
                if (x & 2) {
                    st_async4(dst + peer, pk[0], pk[1], pk[2], pk[3], inb + ow * 8 + peer);
                    st_async4(dst + peer + 2048, pk[4], pk[5], pk[6], pk[7], inb + ow * 8 + peer);
                } else {
                    sts128(dst, pk[0], pk[1], pk[2], pk[3]);
                    sts128(dst + 2048, pk[4], pk[5], pk[6], pk[7]);
                }
            };
            TS(1 + (ph & 2) * 10);
            step(d0, 0, a, w, 0, [&]() { gather_peer(); return 0u; });
            TS(32);
            step(d0, 1, a + 16, 0, 1, none);
            step(d1, 2, a, w, 0, [&]() { return act(d0, 0); });
            step(d1, 3, a + 16, 0, 1, none);
            step(d0, 4, a, w, 0, [&]() { return act(d1, 1); });
            TS(33);
            step(d0, 5, a + 16, 0, 1, none);
            step(d1, 6, a, w, 0, [&]() { return act(d0, 2); });
            step(d1, 7, a + 16, 0, 1, none);
            step(d0, 8, h, 0, 0, [&]() { return act(d1, 3); });
            TS(2 + (ph & 2) * 10);
            step(d0, 9, h + 16, 0, 1, none);
            step(d1, 10, h, 0, 0, [&]() { send(d0, 3); return 0u; });
            step(d1, 11, h + 16, 0, 1, none);
            step(d0, 12, h, 0, 0, [&]() { send(d1, 2); return 0u; });
            TS(34);
            step(d0, 13, h + 16, 0, 1, none);
            uint4 u[6];
            step(d1, 14, h, 0, 0, [&]() {
                send(d0, 1);
                mbar_wait(inb + w * 8, 0);
                bar_sync(10, 256);
#pragma unroll
                for (int i = 0; i < 6; i++) u[i] = lds128(box + w * 12288 + i * 2048);
                return u[0].x | u[1].x | u[2].x | u[3].x | u[4].x | u[5].x;
            });
            step(d1, 15, h + 16, 0, 1, none);
            mbar_wait(ph == 0 ? fbar + (16 % NSLOT) * 8 : inb + w * 8, ph == 0);
            uint32_t tie = 0;
#pragma unroll
            for (int i = 0; i < 2; i++) {
                const uint32_t p0[4] = {u[i].x, u[i].y, u[i].z, u[i].w}, p1[4] = {u[i + 2].x, u[i + 2].y, u[i + 2].z, u[i + 2].w}, p2[4] = {u[i + 4].x, u[i + 4].y, u[i + 4].z, u[i + 4].w};
#pragma unroll
                for (int j = 0; j < 4; j++) {
                    v[8 * i + 2 * j] = fmaf(0.5f, blo(p0[j]) + blo(p1[j]) + blo(p2[j]), blo(xr[4 * i + j]));
                    v[8 * i + 2 * j + 1] = fmaf(0.5f, bhi(p0[j]) + bhi(p1[j]) + bhi(p2[j]), bhi(xr[4 * i + j]));
                    tie |= __float_as_uint(v[8 * i + 2 * j]) | __float_as_uint(v[8 * i + 2 * j + 1]);
                }
            }
            if (__any_sync(~0u, tie & p.zero)) spin(1);
            wg_wait<0>();
            pin(d1);
            rel(15);
            TS(3 + (ph & 2) * 10);
#pragma unroll
            for (int j = 0; j < 8; j++) {
                v[2 * j] = fmaf(0.5f, d1[4 * j] + d1[4 * j + 2], v[2 * j]);
                v[2 * j + 1] = fmaf(0.5f, d1[4 * j + 1] + d1[4 * j + 3], v[2 * j + 1]);
            }
#pragma unroll
            for (int i = 0; i < 15; i++) dwr[i] = 0;
            continue;
        }

        auto residual = [&](int n) {
            wg_wait<1>();
            rel(n);
            wg_wait<0>();
            pin(d0);
            rel(n + 1);
#pragma unroll
            for (int j = 0; j < 8; j++) {
                v[2 * j] = d0[4 * j] + d0[4 * j + 2] + blo(xr[j]);
                v[2 * j + 1] = d0[4 * j + 1] + d0[4 * j + 3] + bhi(xr[j]);
            }
        };

        if (ph == 2) {
            TS(39);
            sp(d0, 34, a, w, 0);
            acq(35);
            sp(d1, 35, a, w, 0);
            acq(36); acq(37);
            gather_peer();
            sp(d0, 36, a + 16, 0, 1);
            sp(d1, 37, a + 16, 0, 1);
            wg_wait<2>();
            rel(34);
            if (!(LATE & 1)) rel(35);
            acq(38);
            const float rs = trow < T_ ? 0.5f * rstd : 0.f;
            wg_wait<0>();
            pin(d0); pin(d1);
            if (!(LATE & 2)) { rel(36); rel(37); }
            TS(18);
            uint32_t pk[8];
#pragma unroll
            for (int j = 0; j < 8; j++) {
                const float u0 = (d0[4 * j] + d0[4 * j + 2]) * rs, u1 = (d0[4 * j + 1] + d0[4 * j + 3]) * rs;
                const float t0 = tanh_fast((d1[4 * j] + d1[4 * j + 2]) * rs), t1 = tanh_fast((d1[4 * j + 1] + d1[4 * j + 3]) * rs);
                pk[j] = pack2(fmaf(u0, t0, u0), fmaf(u1, t1, u1));
            }
            if (wq == 0 || wq == 3) {
                uint4* hp = &g_halo[((pair * 4 + tile) * 2 + (wq & 1)) * 64 + lane];
                st_data(hp, pk[0], pk[1], pk[2], pk[3]);
                st_data(hp + 32, pk[4], pk[5], pk[6], pk[7]);
            }
            const uint32_t gs = H + 16384 + w * GCH + wq * 1024;
            stsm4(gs + 1024 + foff, pk[0], pk[1], pk[2], pk[3]);
            stsm4(gs + 1024 + (foff ^ 64), pk[4], pk[5], pk[6], pk[7]);
            bar_sync(8 + w, 192);
            TS(26);
            uint32_t ca[8], cb[8];
            const int e = (wq & 1) * 4;
            const uint32_t lo = ((mir ^ e) * 144) ^ (lane * 4);
            const int dir = mir ? -1024 : 1024;
            const uint32_t gb = H + 16384 + w * GCH + (mir ? 3072 : 2048) + lo, sown_ = H + tile * HCH, so = sown_ + (mir ? 1024 : 2048) + lo;
            auto finish = [&](int i) {
                const uint32_t c = hadd2(ca[i], cb[i]);
                const float h0 = blo(c), h1 = bhi(c);
                sts32((so + (i >> 2) * dir) ^ ((i & 3) * 144), pack2(fmaf(h0, tanh_fast(h0), h0), fmaf(h1, tanh_fast(h1), h1)));
            };
#pragma unroll
            for (int k = 0; k < 26; k++) {
                if (k == 19) {
#pragma unroll
                    for (int i = 0; i < 4; i++) finish(i);
                    fence_async_smem();
                    bar_sync(2 + w, 128);
                    if (wq == 0) peer_copy(mapa(sown_ + 1024, r ^ 1), sown_ + 1024, 2048, mapa(bars + B_SR * 8, r ^ 1));
                    mbar_wait(bars + (B_HALO + 2 * w + (wq >> 1)) * 8, 0);
                    if (LATE & 1) rel(35);
                    if (LATE & 2) { rel(36); rel(37); }
                    TS(27);
                }
                const uint32_t g = lds32((gb + (((k + 1) & 4) ? ((k + 1) >> 3) + (wq & 1) : ((k + 1) >> 3)) * dir) ^ (((k + 1) & 7) * 144));
#pragma unroll
                for (int i = 0; i < 8; i++) {
                    const int tap = k - (i & 3) - 2 * (i & 4);
                    if (tap == 0) ca[i] = hmul2(g, dwr[0]);
                    else if (tap > 0 && tap < 8) ca[i] = hfma2(g, dwr[tap], ca[i]);
                    else if (tap == 8) cb[i] = hmul2(g, dwr[8]);
                    else if (tap > 8 && tap < 15) cb[i] = hfma2(g, dwr[tap], cb[i]);
                }
            }
#pragma unroll
            for (int i = 4; i < 8; i++) finish(i);
            fence_async_smem();
            bar_sync(12 + (warp >> 1), 64);
            if (wq == 0 || wq == 3) peer_copy(mapa(sown_ + wq * 1024, r ^ 1), sown_ + wq * 1024, 1024, mapa(bars + B_SR * 8, r ^ 1));
            bar_sync(10, 256);
            TS(19);
            auto frags = [&](int i, int half) {
                const uint32_t src = H + 2 * half * HCH + wq * 1024;
#pragma unroll
                for (int k = 0; k < 4; k++) ldsm4(src + (k >> 1) * HCH + (foff ^ ((k & 1) * 64)), a[i + 4 * k], a[i + 4 * k + 1], a[i + 4 * k + 2], a[i + 4 * k + 3]);
            };
            frags(0, r);
            sp(d0, 38, a, 0, 0);
            acq(39);
            mbar_wait(bars + B_SR * 8, 0);
            frags(16, r ^ 1);
            sp(d0, 39, a + 16, 0, 1);
            residual(38);
            TS(20);
            continue;
        }

        {
            TS(11);
            const uint32_t stg = H + warp * 2048;
            unsigned char* g = g_kvq + (size_t)((b * 4 + tile) * 1024 + trow) * 128 + lane * 16;
            auto put = [&](float (&d)[32], int i) {
                pin(d);
                uint32_t pk[8];
#pragma unroll
                for (int j = 0; j < 8; j++) pk[j] = pack2((d[4 * j] + d[4 * j + 2]) * rstd, (d[4 * j + 1] + d[4 * j + 3]) * rstd);
                if (i == 2) {
                    st_data(g + 2097152, pk[0], pk[1], pk[2], pk[3]);
                    st_data(g + 2097152 + 512, pk[4], pk[5], pk[6], pk[7]);
                    return;
                }
                stsm4(stg + i * 1024 + foff, pk[0], pk[1], pk[2], pk[3]);
                stsm4(stg + i * 1024 + (foff ^ 64), pk[4], pk[5], pk[6], pk[7]);
                __syncwarp();
                const uint4 u0 = lds128(stg + i * 1024 + lane * 16), u1 = lds128(stg + i * 1024 + 512 + lane * 16);
                stg128(g + i * 1048576, u0); stg128(g + i * 1048576 + 512, u1);
            };
            sp(d0, 16, a, w, 0);
            acq(17);
            sp(d1, 17, a, w, 0);
            gather_peer();
            acq(18);
            sp(d0, 18, a + 16, 0, 1);
            wg_wait<1>();
            rel(16); rel(17);
            acq(19);
            sp(d1, 19, a + 16, 0, 1);
            wg_wait<1>();
            rel(18);
            put(d0, 0);
            wg_wait<0>();
            rel(19);
            TS(37);
            put(d1, 1);
            bar_arrive(4, 288);
            TS(38);
            acq(20);
            sp(d0, 20, a, w, 0);
            acq(21);
            sp(d0, 21, a + 16, 0, 1);
            acq(22); acq(23);
            rel(22); rel(23);
            mbar_wait(bars + B_RST * 8, 0);
            wg_wait<0>();
            rel(20); rel(21);
            put(d0, 2);
            TS(12);
        }

        {
            constexpr float CS = 0.125f * 1.4426950408889634f;
            float sa[32], sb2[32], o[36];
            uint32_t pa[16], pb[16], q[16];
            float n0 = INFINITY, n1 = INFINITY;
            zero(o); zero(pa); zero(pb); zero(sb2);
            const uint32_t ones = sb + OFF_MISC + 2048;
            { const uint32_t c = w ? 0u : 0x3F803F80u; sts128(ones + tid * 16, c, c, c, c); }
            fence_async_smem();
            bar_sync(10, 256);
            const uint32_t vdesc = rdesc + ((((ones - rbase) >> 4) - 1) << 16);
            auto qk_issue = [&](float (&s)[32], uint32_t lo) {
                const uint64_t kd = mkdesc(lo);
                wg_fence();
#pragma unroll
                for (int k = 0; k < 4; k++) mma_qk(s, q[4 * k], q[4 * k + 1], q[4 * k + 2], q[4 * k + 3], kd + 2 * k, k != 0);
                wg_commit();
            };
            auto both_issue = [&](float (&s)[32], uint32_t klo, uint32_t (&pp)[16], uint32_t vlo) {
                const uint64_t kd = mkdesc(klo), vd = mkdesc(vlo);
                wg_fence();
#pragma unroll
                for (int k = 0; k < 4; k++) {
                    mma_pv(o, pp[4 * k], pp[4 * k + 1], pp[4 * k + 2], pp[4 * k + 3], vd - k * (128 * 65535));
                    mma_qk(s, q[4 * k], q[4 * k + 1], q[4 * k + 2], q[4 * k + 3], kd + 2 * k, k != 0);
                }
                wg_commit();
            };
            auto new_max = [&](float (&s)[32], int nj, float& x0, float& x1) {
                x0 = s[0]; x1 = s[2];
#pragma unroll
                for (int j = 0; j < nj; j++) {
                    x0 = fmaxf(x0, fmaxf(s[4 * j], s[4 * j + 1]));
                    x1 = fmaxf(x1, fmaxf(s[4 * j + 2], s[4 * j + 3]));
                }
                x0 = fmaxf(x0, __shfl_xor_sync(~0u, x0, 1)); x1 = fmaxf(x1, __shfl_xor_sync(~0u, x1, 1));
                x0 = fmaxf(x0, __shfl_xor_sync(~0u, x0, 2)); x1 = fmaxf(x1, __shfl_xor_sync(~0u, x1, 2));
                x0 = fminf(n0, fmaf(x0, -CS, -20.f)); x1 = fminf(n1, fmaf(x1, -CS, -20.f));
            };
            auto probs = [&](float (&s)[32], uint32_t (&pp)[16], bool ready, bool tail, auto wait) {
                uint32_t any = 0;
#pragma unroll
                for (int i = 0; i < 16; i++) {
                    pp[i] = pack2(ex2(fmaf(s[2 * i], CS, (i & 1) ? n1 : n0)), ex2(fmaf(s[2 * i + 1], CS, (i & 1) ? n1 : n0)));
                    any |= pp[i];
                }
                wg_wait<0>();
                pin(sa); pin(sb2); pin(o); pin(pa); pin(pb);
                if (__any_sync(~0u, (any & 0x40004000u) || !ready)) {
                    wait();
                    if (__any_sync(~0u, any & 0x40004000u)) {
                        if (tail) {
#pragma unroll
                            for (int i = 20; i < 32; i++) s[i] = -INFINITY;
                        }
                        float x0, x1;
                        new_max(s, 8, x0, x1);
                        const float sc0 = ex2(x0 - n0), sc1 = ex2(x1 - n1);
                        n0 = x0; n1 = x1;
#pragma unroll
                        for (int j = 0; j < 9; j++) { o[4 * j] *= sc0; o[4 * j + 1] *= sc0; o[4 * j + 2] *= sc1; o[4 * j + 3] *= sc1; }
#pragma unroll
                        for (int i = 0; i < 16; i++)
                            pp[i] = pack2(ex2(fmaf(s[2 * i], CS, (i & 1) ? n1 : n0)), ex2(fmaf(s[2 * i + 1], CS, (i & 1) ? n1 : n0)));
                    }
                }
            };
            {
                uint4 u[4];
                const unsigned char* src = g_kvq + 2097152 + (size_t)(abh * 1024 + qt * 64 + wq * 16) * 128 + lane * 16;
                spin(QGATE);
                ld_data<512>(u, src);
#pragma unroll
                for (int k = 0; k < 2; k++) {
                    q[8 * k] = u[k].x; q[8 * k + 1] = u[k + 2].x; q[8 * k + 2] = u[k].y; q[8 * k + 3] = u[k + 2].y;
                    q[8 * k + 4] = u[k].z; q[8 * k + 5] = u[k + 2].z; q[8 * k + 6] = u[k].w; q[8 * k + 7] = u[k + 2].w;
                }
                pin(q);
            }
            TS(40);
            acq(24);
            TS(13);
            qk_issue(sa, rdesc + (24 % NSLOT) * (SLOT >> 4));
            wg_wait<0>();
            pin(sa);
            {
                float x0, x1;
                new_max(sa, NJ0, x0, x1);
                n0 = x0; n1 = x1;
            }
            bar_arrive(6, 384);
            uint32_t vd = vdesc - (SLOT >> 4) * 65535u, kd = rdesc, vb = fbar + 8, kb = fbar;
            uint32_t vlast = vdesc - 4 * (SLOT >> 4) * 65535u, klast = rdesc + 4 * (SLOT >> 4) + 512;
            uint32_t kprev = fbar + 32, vprev = bars + (B_SINK - (B_EMPTY - B_FULL)) * 8;
#pragma unroll 1
            for (int it = 0; it < 4; it++) {
                both_issue(sb2, klast, pb, vlast);
                probs(sa, pa, mbar_test(vb, it < 2) & mbar_test(kb, it < 3), false, [&]() { mbar_wait(vb, it < 2); mbar_wait(kb, it < 3); });
                TS(41 + it * 4);
                if (lane == 0) mbar_arrive(kprev + (B_EMPTY - B_FULL) * 8);
                if (lane == 0) mbar_arrive(vprev + (B_EMPTY - B_FULL) * 8);
                both_issue(sa, kd, pa, vd);
                const int dv = it == 0 ? 2 : (it == 1 ? -3 : 1);
                kprev = kb; vprev = vb; vlast = vd - 512 * 65535u; klast = kd + 512;
                vd -= dv * (SLOT >> 4) * 65535u; vb += dv * 8;
                kd += (it == 2 ? -3 : 2) * (SLOT >> 4); kb = it == 2 ? vb : kb + 16;
                probs(sb2, pb, true, it == 3 && w == 1, []() {});
                TS(43 + it * 4);
            }
            wg_fence();
#pragma unroll
            for (int k = 0; k < 4; k++)
                mma_pv(o, pb[4 * k], pb[4 * k + 1], pb[4 * k + 2], pb[4 * k + 3], mkdesc(vlast - k * (128 * 65535) + (k > 1 ? w * ((k - 1) << 22) : 0)));
            wg_commit();
            const int row = wq * 16 + (lane >> 2);
            const uint32_t ml = sb + OFF_MISC;
            mbar_wait(bars + (B_RST + 1) * 8, 0);
            wg_wait<0>();
            pin(o); pin(pb); pin(sa); pin(sb2);
            if (!(LATE & 4)) rel(31);
            const float l0 = o[32], l1 = o[34];
            if (c4 == 0) { sts64f(ml + w * 512 + row * 8, n0, l0); sts64f(ml + w * 512 + row * 8 + 64, n1, l1); }
            TS(14);
            float mine[16];
#pragma unroll
            for (int j = 0; j < 4; j++) {
                if (w == 0) sts128f(H + j * 2048 + wt * 16, o[16 + 4 * j], o[17 + 4 * j], o[18 + 4 * j], o[19 + 4 * j]);
                else sts128f(H + 8192 + j * 2048 + wt * 16, o[4 * j], o[4 * j + 1], o[4 * j + 2], o[4 * j + 3]);
            }
#pragma unroll
            for (int i = 0; i < 16; i++) mine[i] = w == 0 ? o[i] : o[16 + i];
            bar_sync(10, 256);
            const float2 u0 = lds64f(ml + (w ^ 1) * 512 + row * 8), u1 = lds64f(ml + (w ^ 1) * 512 + row * 8 + 64);
            const float x0 = fminf(n0, u0.x), x1 = fminf(n1, u1.x);
            float a0 = ex2(x0 - n0), b0 = ex2(x0 - u0.x), a1 = ex2(x1 - n1), b1 = ex2(x1 - u1.x);
            const float i0 = __fdividef(1.f, fmaf(a0, l0, b0 * u0.y)), i1 = __fdividef(1.f, fmaf(a1, l1, b1 * u1.y));
            a0 *= i0; b0 *= i0; a1 *= i1; b1 *= i1;
            uint32_t pk[8];
#pragma unroll
            for (int j = 0; j < 4; j++) {
                const float4 v = lds128f(H + (w ^ 1) * 8192 + j * 2048 + wt * 16);
                pk[2 * j] = pack2(fmaf(a0, mine[4 * j], b0 * v.x), fmaf(a0, mine[4 * j + 1], b0 * v.y));
                pk[2 * j + 1] = pack2(fmaf(a1, mine[4 * j + 2], b1 * v.z), fmaf(a1, mine[4 * j + 3], b1 * v.w));
            }
            unsigned char* dst = g_o + (size_t)(b * 128 + qt * 8 + 2 * wq) * 4096 + ah * 1024 + w * 512 + lane * 16;
            st_data(dst, pk[0], pk[2], pk[4], pk[6]);
            st_data(dst + 4096, pk[1], pk[3], pk[5], pk[7]);
            if (tid == 0) asm volatile("red.relaxed.gpu.global.add.u32 [%0], 1;" ::"l"(&g_epoch[blockIdx.x * FS]) : "memory");
            TS(15);
        }

        {
            const uint32_t* dp = reinterpret_cast<const uint32_t*>(p.dw + (mir ? 14 * 256 : 0) + tile * 64) + lane;
#pragma unroll
            for (int i = 0; i < 15; i++) asm volatile("ld.global.nc.b32 %0, [%1];" : "=r"(dwr[i]) : "l"(dp + i * (mir ? -128 : 128)));
            acq(32); acq(33); acq(34);
            uint4 u[8];
            ld_data<512>(u, g_o + (size_t)(b * 128 + pt * 4 + wq) * 4096 + lane * 16);
#pragma unroll
            for (int i = 0; i < 8; i++) { a[4 * i] = u[i].x; a[4 * i + 1] = u[i].y; a[4 * i + 2] = u[i].z; a[4 * i + 3] = u[i].w; }
            if (LATE & 4) rel(31);
            TS(16);
            sp(d0, 32, a, 0, 0);
            sp(d0, 33, a + 16, 0, 1);
#pragma unroll
            for (int i = 0; i < 15; i++) dwr[i] = hmul2(dwr[i], 0x3F003F00u);
            residual(32);
            TS(17);
        }
    }

    cluster_arrive();
    TS(24);
    {
        const float rstd = rsq(fmaxf(fmaf(-mean, mean, msq), 0.f) + 1e-5f), nb = -mean * rstd;
#pragma unroll
        for (int j = 0; j < 8; j++) xr[j] = pack2(fmaf(v[2 * j], rstd, nb), fmaf(v[2 * j + 1], rstd, nb));
        const uint32_t stg = P + 16384 + warp * 1024;
        stsm4(stg + foff, xr[0], xr[1], xr[2], xr[3]);
        stsm4(stg + (foff ^ 64), xr[4], xr[5], xr[6], xr[7]);
        __syncwarp();
        const uint32_t src = stg + (lane >> 3) * 128 + (((lane & 7) ^ (lane >> 3)) << 4);
        const uint4 u0 = lds128(src), u1 = lds128((src + 512) ^ 64);
        __nv_bfloat16* dst = p.out + (size_t)(b * T_ + trow + (lane >> 3)) * 256 + tile * 64 + (lane & 7) * 8;
        if (trow < T_) { stg128(dst, u0); stg128(dst + 4 * 256, u1); }
    }
    TS(25);
    TG(31);
    TSDUMP();
    cluster_wait();
}

typedef CUresult (*EncodeFn)(CUtensorMap*, CUtensorMapDataType, cuuint32_t, void*, const cuuint64_t*, const cuuint64_t*,
                             const cuuint32_t*, const cuuint32_t*, CUtensorMapInterleave, CUtensorMapSwizzle,
                             CUtensorMapL2promotion, CUtensorMapFloatOOBfill);

}

extern "C" void kernel_launch(void* const* d_in, const int* in_sizes, int n_in, void* d_out, int out_size) {
    static EncodeFn encode = nullptr;
    if (!encode) {
        void* fn = nullptr;
        cudaDriverEntryPointQueryResult qr;
        cudaGetDriverEntryPoint("cuTensorMapEncodeTiled", &fn, cudaEnableDefault, &qr);
        encode = (EncodeFn)fn;
        cudaFuncSetAttribute(conformer_kernel, cudaFuncAttributeMaxDynamicSharedMemorySize, SMEM_LAUNCH);
    }
    Params p;
    const cuuint32_t ones[5] = {1, 1, 1, 1, 1};
    const int idx[8] = {1, 2, 3, 4, 5, 7, 8, 9};
    const int rows[8] = {256, 1024, 256, 256, 256, 256, 256, 1024};
    const int cols[8] = {1024, 256, 768, 256, 512, 256, 1024, 256};
    for (int i = 0; i < 8; i++) {
        const cuuint64_t pitch = (cuuint64_t)cols[i] * 2;
        const cuuint64_t dims[5] = {(cuuint64_t)cols[i], 2, 2, 4, (cuuint64_t)rows[i] / 16};
        const cuuint64_t strides[4] = {pitch, pitch * 8, pitch * 2, pitch * 16};
        const cuuint32_t box[5] = {64, 2, 2, 4, 8};
        encode(&p.tm[i], CU_TENSOR_MAP_DATA_TYPE_BFLOAT16, 5, d_in[idx[i]], dims, strides, box, ones, CU_TENSOR_MAP_INTERLEAVE_NONE,
               CU_TENSOR_MAP_SWIZZLE_128B, CU_TENSOR_MAP_L2_PROMOTION_L2_128B, CU_TENSOR_MAP_FLOAT_OOB_FILL_NONE);
        p.w[i] = (const char*)d_in[idx[i]];
    }
    {
        void* kv = nullptr;
        cudaGetSymbolAddress(&kv, g_kvq);
        const cuuint64_t dims[2] = {64, 16384};
        const cuuint64_t strides[1] = {128};
        const cuuint32_t box[2] = {64, 128};
        encode(&p.tm[8], CU_TENSOR_MAP_DATA_TYPE_BFLOAT16, 2, kv, dims, strides, box, ones, CU_TENSOR_MAP_INTERLEAVE_NONE,
               CU_TENSOR_MAP_SWIZZLE_NONE, CU_TENSOR_MAP_L2_PROMOTION_L2_128B, CU_TENSOR_MAP_FLOAT_OOB_FILL_NONE);
    }
    p.x = (const __nv_bfloat16*)d_in[0];
    p.dw = (const __nv_bfloat16*)d_in[6];
    p.out = (__nv_bfloat16*)d_out;
    p.zero = 0;
    conformer_kernel<<<NCTA, NTHREADS, SMEM_LAUNCH>>>(p);
}
```

```cpp
#include <cuda_runtime.h>
#include <cuda_bf16.h>
#include <cuda.h>
#include <stdint.h>

namespace {

constexpr int T_ = 1000;
constexpr int NCTA = 128;
constexpr int NTHREADS = 512;
constexpr int NSLOT = 5;
constexpr int SLOT = 16384;
constexpr int NLOADS = 56;

constexpr uint32_t OFF_RING = 0;
constexpr uint32_t OFF_P = 163840;
constexpr uint32_t OFF_H = 188416;
constexpr uint32_t OFF_MISC = 221184;
constexpr uint32_t OFF_BARS = 229888;
constexpr uint32_t SMEM_BYTES = 230400;
constexpr uint32_t GCH = 6144;
constexpr uint32_t HCH = 4096;

constexpr int B_FULL = 0, B_EMPTY = 10, B_XA = 20  , B_XB = 25  , B_INB = 29  , B_SR = 33,
              B_RST = 34  , B_RDY = 36  , B_SINK = 42, B_HALO = 43  , NBARS = 47;

#define KD2 300u
#define KD3 500u
#define QGATE 500u
#define BACKOFF 0u
#define KFS 8
#define KDELAY 300u
#define NJ0 2
#define HDELAY 200u
#define LATE 2
#define UNRV 5
constexpr int UNR = UNRV;
#define F3 8
#define IB 14
#define TURN 0
#define EAGER 0x4155
constexpr int FS = 8;

struct Params {
    CUtensorMap tm[9];
    const char* w[8];
    const __nv_bfloat16* x;
    const __nv_bfloat16* dw;
    __nv_bfloat16* out;
    uint32_t zero;
};

__device__ __align__(1024) unsigned char g_kvq[3 * 8 * 1024 * 128];
__device__ __align__(1024) unsigned char g_o[2 * 128 * 4096];
__device__ uint4 g_halo[64 * 4 * 2 * 64];
__device__ __align__(128) uint32_t g_flag_kv[8 * 32 * KFS];
__device__ uint32_t g_reset[4 * 32];
__device__ uint32_t g_epoch[NCTA * FS];

#define TS(i) do { } while (0)
#define TSW(i) do { } while (0)
#define TG(i) do { } while (0)
#define TSINIT() do { } while (0)
#define TSDUMP() do { } while (0)
constexpr uint32_t SMEM_LAUNCH = SMEM_BYTES;

__device__ __forceinline__ uint32_t smem_u32(const void* p) { return (uint32_t)__cvta_generic_to_shared(p); }
__device__ __forceinline__ void mbar_init(uint32_t b, uint32_t c) { asm volatile("mbarrier.init.shared::cta.b64 [%0], %1;" ::"r"(b), "r"(c) : "memory"); }
__device__ __forceinline__ void mbar_arrive(uint32_t b) { asm volatile("mbarrier.arrive.shared::cta.b64 _, [%0];" ::"r"(b) : "memory"); }
__device__ __forceinline__ void mbar_arrive_tx(uint32_t b, uint32_t tx) { asm volatile("mbarrier.arrive.expect_tx.shared::cta.b64 _, [%0], %1;" ::"r"(b), "r"(tx) : "memory"); }
__device__ __forceinline__ void mbar_wait(uint32_t b, uint32_t ph) {
    asm volatile("{\n.reg .pred p, q;\n.reg .u32 c;\nmov.u32 c, 0;\n"
                 "MW_LOOP:\n.pragma \"nounroll\";\n"
                 "mbarrier.try_wait.parity.shared::cta.b64 p, [%0], %1;\n"
                 "add.u32 c, c, 1;\nsetp.lt.u32 q, c, 65536;\nnot.pred p, p;\nand.pred p, p, q;\n@p bra MW_LOOP;\n}"
                 ::"r"(b), "r"(ph) : "memory");
}
__device__ __forceinline__ bool mbar_test(uint32_t b, uint32_t ph) {
    uint32_t ok;
    asm volatile("{\n.reg .pred p;\nmbarrier.test_wait.parity.shared::cta.b64 p, [%1], %2;\nselp.u32 %0, 1, 0, p;\n}" : "=r"(ok) : "r"(b), "r"(ph) : "memory");
    return ok;
}
__device__ __forceinline__ uint32_t mapa(uint32_t a, uint32_t r) { uint32_t o; asm("mapa.shared::cluster.u32 %0, %1, %2;" : "=r"(o) : "r"(a), "r"(r)); return o; }
__device__ __forceinline__ void fence_async_smem() { asm volatile("fence.proxy.async.shared::cta;" ::: "memory"); }
__device__ __forceinline__ void fence_async_global() { asm volatile("fence.proxy.async.global;" ::: "memory"); }
__device__ __forceinline__ void bar_sync(int id, int n) { asm volatile("bar.sync %0, %1;" ::"r"(id), "r"(n) : "memory"); }
__device__ __forceinline__ void bar_arrive(int id, int n) { asm volatile("bar.arrive %0, %1;" ::"r"(id), "r"(n) : "memory"); }
__device__ __forceinline__ void cluster_arrive() { asm volatile("barrier.cluster.arrive.relaxed.aligned;" ::: "memory"); }
__device__ __forceinline__ void cluster_wait() { asm volatile("barrier.cluster.wait.aligned;" ::: "memory"); }

__device__ __forceinline__ void ring_load(uint32_t dst, const CUtensorMap* tm, int col, int row16, uint32_t bar) {
    asm volatile("{\n.reg .pred p;\nelect.sync _|p, 0xffffffff;\n"
                 "@p mbarrier.arrive.expect_tx.shared::cta.b64 _, [%2], 16384;\n"
                 "@p cp.async.bulk.tensor.5d.shared::cluster.global.mbarrier::complete_tx::bytes [%0], [%1, {%3, 0, 0, 0, %4}], [%2];\n}"
                 ::"r"(dst), "l"(tm), "r"(bar), "r"(col), "r"(row16) : "memory");
}
__device__ __forceinline__ void ring_load_both(uint32_t dst, const CUtensorMap* tm, int c1, uint32_t bar) {
    asm volatile("{\n.reg .pred p;\nelect.sync _|p, 0xffffffff;\n"
                 "@p cp.async.bulk.tensor.2d.shared::cluster.global.mbarrier::complete_tx::bytes.multicast::cluster [%0], [%1, {0, %3}], [%2], %4;\n}"
                 ::"r"(dst), "l"(tm), "r"(bar), "r"(c1), "h"((uint16_t)3) : "memory");
}
__device__ __forceinline__ void mbar_arrive_peer(uint32_t b) { asm volatile("mbarrier.arrive.relaxed.cluster.shared::cluster.b64 _, [%0];" ::"r"(b) : "memory"); }
__device__ __forceinline__ void prefetch_l2(const void* src, uint32_t bytes) {
    asm volatile("cp.async.bulk.prefetch.L2.global [%0], %1;" ::"l"(src), "r"(bytes) : "memory");
}
__device__ __forceinline__ void peer_copy(uint32_t dst, uint32_t src, uint32_t bytes, uint32_t rbar) {
    asm volatile("{\n.reg .pred p;\nelect.sync _|p, 0xffffffff;\n"
                 "@p cp.async.bulk.shared::cluster.shared::cta.mbarrier::complete_tx::bytes [%0], [%1], %2, [%3];\n}"
                 ::"r"(dst), "r"(src), "r"(bytes), "r"(rbar) : "memory");
}
__device__ __forceinline__ void st_async4(uint32_t dst, uint32_t a, uint32_t b, uint32_t c, uint32_t d, uint32_t bar) {
    asm volatile("st.async.shared::cluster.mbarrier::complete_tx::bytes.v4.b32 [%0], {%1,%2,%3,%4}, [%5];" ::"r"(dst), "r"(a), "r"(b), "r"(c), "r"(d), "r"(bar) : "memory");
}
__device__ __forceinline__ void st_async2f(uint32_t dst, float a, float b, uint32_t bar) {
    asm volatile("st.async.shared::cluster.mbarrier::complete_tx::bytes.v2.f32 [%0], {%1,%2}, [%3];" ::"r"(dst), "f"(a), "f"(b), "r"(bar) : "memory");
}
__device__ __forceinline__ void stsm4(uint32_t a, uint32_t r0, uint32_t r1, uint32_t r2, uint32_t r3) {
    asm volatile("stmatrix.sync.aligned.m8n8.x4.shared.b16 [%0], {%1,%2,%3,%4};" ::"r"(a), "r"(r0), "r"(r1), "r"(r2), "r"(r3) : "memory");
}
__device__ __forceinline__ void ldsm4(uint32_t a, uint32_t& r0, uint32_t& r1, uint32_t& r2, uint32_t& r3) {
    asm volatile("ldmatrix.sync.aligned.m8n8.x4.shared.b16 {%0,%1,%2,%3}, [%4];" : "=r"(r0), "=r"(r1), "=r"(r2), "=r"(r3) : "r"(a) : "memory");
}
__device__ __forceinline__ uint4 lds128(uint32_t a) { uint4 v; asm volatile("ld.shared.v4.b32 {%0,%1,%2,%3}, [%4];" : "=r"(v.x), "=r"(v.y), "=r"(v.z), "=r"(v.w) : "r"(a) : "memory"); return v; }
__device__ __forceinline__ float4 lds128f(uint32_t a) { float4 v; asm volatile("ld.shared.v4.f32 {%0,%1,%2,%3}, [%4];" : "=f"(v.x), "=f"(v.y), "=f"(v.z), "=f"(v.w) : "r"(a) : "memory"); return v; }
__device__ __forceinline__ float2 lds64f(uint32_t a) { float2 v; asm volatile("ld.shared.v2.f32 {%0,%1}, [%2];" : "=f"(v.x), "=f"(v.y) : "r"(a) : "memory"); return v; }
__device__ __forceinline__ uint32_t lds32(uint32_t a) { uint32_t v; asm volatile("ld.shared.b32 %0, [%1];" : "=r"(v) : "r"(a) : "memory"); return v; }
__device__ __forceinline__ void sts128(uint32_t a, uint32_t x, uint32_t y, uint32_t z, uint32_t w) { asm volatile("st.shared.v4.b32 [%0], {%1,%2,%3,%4};" ::"r"(a), "r"(x), "r"(y), "r"(z), "r"(w) : "memory"); }
__device__ __forceinline__ void sts128f(uint32_t a, float x, float y, float z, float w) { asm volatile("st.shared.v4.f32 [%0], {%1,%2,%3,%4};" ::"r"(a), "f"(x), "f"(y), "f"(z), "f"(w) : "memory"); }
__device__ __forceinline__ void sts64f(uint32_t a, float x, float y) { asm volatile("st.shared.v2.f32 [%0], {%1,%2};" ::"r"(a), "f"(x), "f"(y) : "memory"); }
__device__ __forceinline__ void sts32(uint32_t a, uint32_t x) { asm volatile("st.shared.b32 [%0], %1;" ::"r"(a), "r"(x) : "memory"); }
__device__ __forceinline__ void stg128(void* p, uint4 v) { asm volatile("st.global.v4.b32 [%0], {%1,%2,%3,%4};" ::"l"(p), "r"(v.x), "r"(v.y), "r"(v.z), "r"(v.w) : "memory"); }

__device__ __forceinline__ uint32_t pack2(float lo, float hi) { uint32_t r; asm("cvt.rn.bf16x2.f32 %0, %1, %2;" : "=r"(r) : "f"(hi), "f"(lo)); return r; }
__device__ __forceinline__ float blo(uint32_t v) { return __uint_as_float(v << 16); }
__device__ __forceinline__ float bhi(uint32_t v) { return __uint_as_float(v & 0xffff0000u); }
__device__ __forceinline__ uint32_t hmul2(uint32_t a, uint32_t b) { uint32_t r; asm("mul.rn.bf16x2 %0, %1, %2;" : "=r"(r) : "r"(a), "r"(b)); return r; }
__device__ __forceinline__ uint32_t hadd2(uint32_t a, uint32_t b) { uint32_t r; asm("add.rn.bf16x2 %0, %1, %2;" : "=r"(r) : "r"(a), "r"(b)); return r; }
__device__ __forceinline__ uint32_t hsub2(uint32_t a, uint32_t b) { uint32_t r; asm("sub.rn.bf16x2 %0, %1, %2;" : "=r"(r) : "r"(a), "r"(b)); return r; }
__device__ __forceinline__ uint32_t hfma2(uint32_t a, uint32_t b, uint32_t c) { uint32_t r; asm("fma.rn.bf16x2 %0, %1, %2, %3;" : "=r"(r) : "r"(a), "r"(b), "r"(c)); return r; }
__device__ __forceinline__ float tanh_fast(float x) { float r; asm("tanh.approx.f32 %0, %1;" : "=f"(r) : "f"(x)); return r; }
__device__ __forceinline__ float rsq(float x) { float r; asm("rsqrt.approx.ftz.f32 %0, %1;" : "=f"(r) : "f"(x)); return r; }
__device__ __forceinline__ float ex2(float x) { float r; asm("ex2.approx.ftz.f32 %0, %1;" : "=f"(r) : "f"(x)); return r; }

__device__ __forceinline__ uint32_t ld_relaxed(const uint32_t* p) {
    uint32_t v;
    asm volatile("ld.relaxed.gpu.global.u32 %0, [%1];" : "=r"(v) : "l"(p) : "memory");
    return v;
}
__device__ __forceinline__ uint32_t clock32() { uint32_t c; asm volatile("mov.u32 %0, %%clock;" : "=r"(c)::"memory"); return c; }
__device__ __forceinline__ void spin(uint32_t clks) {
    const uint32_t t0 = clock32();
    while (clock32() - t0 < clks) {}
}
__device__ __forceinline__ void flag_wait(const uint32_t* p, uint32_t e, bool mine) {
#pragma unroll 1
    for (int i = 0; i < (1 << 19); i++) {
        if (mine) mine = ld_relaxed(p) != e;
        if (!__any_sync(~0u, mine)) break;
        if (BACKOFF) spin(BACKOFF);
    }
    asm volatile("fence.acquire.gpu;" ::: "memory");
    fence_async_global();
}
__device__ __forceinline__ void st_data(void* p, uint32_t x, uint32_t y, uint32_t z, uint32_t w) {
    asm volatile("st.relaxed.gpu.global.v4.b32 [%0], {%1,%2,%3,%4};" ::"l"(p), "r"(x), "r"(y), "r"(z), "r"(w) : "memory");
}
template <int STRIDE, int N>
__device__ __forceinline__ void ld_data(uint4 (&v)[N], const unsigned char* p) {
    int it = 0;
    bool again;
#pragma unroll 1
    do {
        uint32_t m = 0;
#pragma unroll
        for (int i = 0; i < N; i++)
            asm volatile("ld.relaxed.gpu.global.v4.b32 {%0,%1,%2,%3}, [%4];" : "=r"(v[i].x), "=r"(v[i].y), "=r"(v[i].z), "=r"(v[i].w) : "l"(p + i * STRIDE) : "memory");
#pragma unroll
        for (int i = 0; i < N; i++) m = __vimax3_u32(__vimax3_u32(v[i].x, v[i].y, v[i].z), v[i].w, m);
        again = __any_sync(~0u, m == ~0u) && ++it < (1 << 16);
    } while (again);
}
__device__ __forceinline__ uint32_t ld_epoch() { return ld_relaxed(&g_epoch[blockIdx.x * FS]) + 1; }
__device__ __forceinline__ void flag_set(uint32_t* p, uint32_t e) { asm volatile("st.release.gpu.global.u32 [%0], %1;" ::"l"(p), "r"(e) : "memory"); }

__device__ __forceinline__ uint32_t desc_lo(uint32_t addr) { return ((addr & 0x3FFFF) >> 4) | 0x10000u; }
__device__ __forceinline__ uint64_t mkdesc(uint32_t lo) { return (uint64_t)lo | (0x40000040ull << 32); }
__device__ __forceinline__ void wg_fence() { asm volatile("wgmma.fence.sync.aligned;" ::: "memory"); }
__device__ __forceinline__ void wg_commit() { asm volatile("wgmma.commit_group.sync.aligned;" ::: "memory"); }
template <int N> __device__ __forceinline__ void wg_wait() { asm volatile("wgmma.wait_group.sync.aligned %0;" ::"n"(N) : "memory"); }
template <int N> __device__ __forceinline__ void pin(float (&d)[N]) {
#pragma unroll
    for (int i = 0; i < N; i++) asm volatile("" : "+f"(d[i])::"memory");
}
template <int N> __device__ __forceinline__ void pin(uint32_t (&d)[N]) {
#pragma unroll
    for (int i = 0; i < N; i++) asm volatile("" : "+r"(d[i])::"memory");
}

template <typename Tp, int N> __device__ __forceinline__ void zero(Tp (&d)[N]) {
#pragma unroll
    for (int i = 0; i < N; i++) d[i] = 0;
    pin(d);
}

#define F4(d, i) "+f"(d[i]), "+f"(d[i + 1]), "+f"(d[i + 2]), "+f"(d[i + 3])
#define F16(d, i) F4(d, i), F4(d, i + 4), F4(d, i + 8), F4(d, i + 12)

__device__ __forceinline__ void mma_sp(float (&d)[32], const uint32_t* a, uint64_t b, uint32_t meta, int acc) {
    asm volatile("{.reg .pred p; setp.ne.b32 p, %38, 0;\n"
                 "wgmma.mma_async.sp.sync.aligned.m64n64k32.f32.bf16.bf16 {%0,%1,%2,%3,%4,%5,%6,%7,%8,%9,%10,%11,%12,%13,%14,%15,%16,%17,%18,%19,%20,%21,%22,%23,%24,%25,%26,%27,%28,%29,%30,%31}, "
                 "{%32,%33,%34,%35}, %36, %37, 0, p, 1, 1, 1;}\n"
                 : F16(d, 0), F16(d, 16) : "r"(a[0]), "r"(a[1]), "r"(a[2]), "r"(a[3]), "l"(b), "r"(meta), "r"(acc));
}
__device__ __forceinline__ void mma_qk(float (&d)[32], uint32_t a0, uint32_t a1, uint32_t a2, uint32_t a3, uint64_t b, int acc) {
    asm volatile("{.reg .pred p; setp.ne.b32 p, %37, 0;\n"
                 "wgmma.mma_async.sync.aligned.m64n64k16.f32.bf16.bf16 {%0,%1,%2,%3,%4,%5,%6,%7,%8,%9,%10,%11,%12,%13,%14,%15,%16,%17,%18,%19,%20,%21,%22,%23,%24,%25,%26,%27,%28,%29,%30,%31}, "
                 "{%32,%33,%34,%35}, %36, p, 1, 1, 0;}\n"
                 : F16(d, 0), F16(d, 16) : "r"(a0), "r"(a1), "r"(a2), "r"(a3), "l"(b), "r"(acc));
}
__device__ __forceinline__ void mma_pv(float (&d)[36], uint32_t a0, uint32_t a1, uint32_t a2, uint32_t a3, uint64_t b) {
    asm volatile("wgmma.mma_async.sync.aligned.m64n72k16.f32.bf16.bf16 {%0,%1,%2,%3,%4,%5,%6,%7,%8,%9,%10,%11,%12,%13,%14,%15,%16,%17,%18,%19,%20,%21,%22,%23,%24,%25,%26,%27,%28,%29,%30,%31,%32,%33,%34,%35}, "
                 "{%36,%37,%38,%39}, %40, 1, 1, 1, 1;\n"
                 : F16(d, 0), F16(d, 16), F4(d, 32) : "r"(a0), "r"(a1), "r"(a2), "r"(a3), "l"(b));
}

__device__ __forceinline__ uint32_t load_code(int n, int r, int w) {
    const int tile = 2 * r + w;
    int m, col, row;
    if (n < 16 || n >= 40) {
        const int k = n < 16 ? n : n - 40;
        m = n < 16 ? 0 : 6;
        if (k < 8) { col = 4 * tile + (k >> 1); row = (k & 1) ^ r; }
        else { m++; col = k < 12 ? tile ^ 2 : tile; row = 2 * (tile ^ (k & 1)) + ((k >> 1) & 1); }
    } else if (n < 32) {
        const int k = n - 16;
        m = 2;
        if (k < 4) { col = tile + ((k & 1) ? 8 : 4); row = (k >> 1) ^ r; }
        else { col = tile; row = (k & 1) ^ r; }
    } else if (n < 34) { m = 3; col = tile; row = n - 32; }
    else if (n < 38) { const int k = n - 34; m = 4; col = tile + 4 * (k & 1); row = (k >> 1) ^ r; }
    else { m = 5; col = tile; row = (n & 1) ^ r; }
    return m | (col << 4) | (row << 8);
}

__global__ void __cluster_dims__(2, 1, 1) __launch_bounds__(NTHREADS, 1)
conformer_kernel(const __grid_constant__ Params p) {
    extern __shared__ __align__(1024) unsigned char smem_raw[];
    const uint32_t sb = smem_u32(smem_raw);
    const uint32_t bars = sb + OFF_BARS;
    const int tid = threadIdx.x;
    const int lane = tid & 31;
    const int warp = __shfl_sync(~0u, tid >> 5, 0);
    const int r = blockIdx.x & 1;
    const int pair = blockIdx.x >> 1;
    const int b = pair >> 5, pt = pair & 31;
    const int ah = pt >> 3, qt = (pt & 7) * 2 + r;
    const int abh = b * 4 + ah;

    TG(30);
    TSINIT();
    TS(0);
    const uint32_t P = sb + OFF_P, H = sb + OFF_H;

    if (warp >= 8) {
        asm volatile("setmaxnreg.dec.sync.aligned.u32 48;");
        if (warp >= 12) {
            cluster_arrive();
            cluster_wait();
            const int ut = tid & 127;
            const uint32_t target = ld_epoch() * 64;
            auto reset_done = [&](int k) {
                bar_sync(11, 128);
                if (ut == 0) {
                    asm volatile("red.release.gpu.global.add.u32 [%0], 1;" ::"l"(&g_reset[(2 * b + k) * 32]) : "memory");
#pragma unroll 1
                    for (int i = 0; i < (1 << 20) && ld_relaxed(&g_reset[(2 * b + k) * 32]) != target; i++) __nanosleep(100);
                    asm volatile("fence.acquire.gpu;" ::: "memory");
                    mbar_arrive(bars + (B_RST + k) * 8);
                }
                __syncwarp();
                TS(13 + k);
            };
#pragma unroll
            for (int i = 0; i < 4; i++)
                st_data(g_kvq + 2097152 + (size_t)((b * 4 + 2 * r + (i >> 1)) * 1024 + pt * 32) * 128 + (i & 1) * 2048 + ut * 16, ~0u, ~0u, ~0u, ~0u);
            reset_done(0);
            bar_sync(6, 384);
#pragma unroll
            for (int i = 0; i < 4; i++) {
                st_data(g_o + (size_t)(b * 128 + qt * 8 + 2 * i + (ut >> 6)) * 4096 + ah * 1024 + (ut & 63) * 16, ~0u, ~0u, ~0u, ~0u);
                if (i < 2) st_data(&g_halo[(pair * 4 + 2 * r + i) * 128 + ut], ~0u, ~0u, ~0u, ~0u);
            }
            reset_done(1);
            const int side = warp & 1, wg = (warp >> 1) & 1, np = side ? pt + 1 : pt - 1;
            const unsigned char* src = reinterpret_cast<const unsigned char*>(&g_halo[(((b * 32 + np) * 4 + 2 * r + wg) * 2 + (side ^ 1)) * 64 + lane]);
            const uint32_t dst = H + 16384 + wg * GCH + side * 5120 + (lane & 7) * 128 + (((lane >> 3) ^ (lane & 7)) << 4);
            uint4 hv[2] = {make_uint4(0, 0, 0, 0), make_uint4(0, 0, 0, 0)};
            bar_sync(8 + wg, 192);
            if (np >= 0 && np < 32) {
                spin(HDELAY);
                ld_data<512>(hv, src);
            }
            stsm4(dst, hv[0].x, hv[0].y, hv[0].z, hv[0].w);
            stsm4(dst ^ 64, hv[1].x, hv[1].y, hv[1].z, hv[1].w);
            __syncwarp();
            if (lane == 0) mbar_arrive(bars + (B_HALO + (warp & 3)) * 8);
            TS(4);
        } else if (warp < 10) {
            const int w = warp - 8;
            const uint32_t ring = sb + OFF_RING + w * NSLOT * SLOT;
            const uint32_t full = bars + (B_FULL + w * NSLOT) * 8;
            if (lane == 0) {
#pragma unroll
                for (int i = 0; i < NSLOT; i++) { mbar_init(full + i * 8, 1); mbar_init(full + (B_EMPTY - B_FULL + i) * 8, 4); }
                asm volatile("fence.mbarrier_init.release.cluster;" ::: "memory");
                fence_async_smem();
            }
            __syncwarp();
            cluster_arrive();
            TS(1);
#pragma unroll
            for (int n = 0; n < NSLOT; n++) {
                if (n == 1 || n == 2) bar_sync(12, 64);
                ring_load(ring + n * SLOT, &p.tm[0], 64 * (8 * r + 4 * w + (n >> 1)), 8 * ((n & 1) ^ r), full + n * 8);
            }
            TS(2);
            const uint32_t code = load_code(lane, r, w) | (load_code(lane + 32, r, w) << 16);
            cluster_wait();
            uint32_t s = 0, ph = 0;
            int n = NSLOT;
#pragma unroll 1
            for (int seg = 0; seg < 2; seg++) {
#pragma unroll 1
                for (; n < (seg == 0 ? 22 : NLOADS); n++) {
                    const uint32_t c = __shfl_sync(~0u, code, n) >> (n & 32 ? 16 : 0);
                    const CUtensorMap* tm = &p.tm[c & 15];
                    const uint32_t col = (c & 0xf0) * 4, row = (c & 0xff00) >> 5, dst = ring + s * SLOT;
                    mbar_wait(full + (B_EMPTY - B_FULL) * 8 + s * 8, ph + (((uint32_t)(size_t)tm | col | row | dst) & p.zero));
                    ring_load(dst, tm, col, row, full + s * 8);
                    if (++s == NSLOT) { s = 0; ph ^= 1; }
                }
                if (seg == 1) break;
                const uint32_t epoch = ld_epoch();
                const uint32_t rdy = bars + (B_RDY + 3 * w) * 8, prdy = mapa(rdy, r ^ 1);
                const int odd = r ^ w;
                const uint32_t* flags = g_flag_kv + (abh * 32 + lane) * KFS;
                auto kv_load = [&](uint32_t sl, int isv, int i) {
                    ring_load_both(ring + sl * SLOT, &p.tm[8], (isv * 64 + abh * 8 + 2 * i + w) * 128, full + sl * 8);
                };
#pragma unroll 1
                for (int i = 0; i < 2; i++) {
                    if (lane < 3 + i) {
                        const uint32_t sl = i ? lane : lane + 2;
                        mbar_wait(full + (B_EMPTY - B_FULL + sl) * 8, i ^ 1);
                        mbar_arrive_tx(full + sl * 8, (i || lane == 2) ? SLOT : 0);
                    }
                    __syncwarp();
                }
                if (lane == 0) mbar_arrive_peer(prdy);
                bar_sync(14, 96);
                spin(KDELAY);
                mbar_wait(rdy, 0);
                flag_wait(flags, epoch, (lane >> 2) == 2 * odd + w);
                TSW(5 + 2 * odd);
                if (!odd) { kv_load(4, 0, 0); bar_arrive(12, 64); }
                else bar_sync(12, 64);
                spin(w ? KD3 : KD2);
                kv_load(odd ^ 1, odd ^ 1, odd);
                flag_wait(flags, epoch, (lane >> 2) == 2 * odd + w + 4);
                mbar_wait(full + (odd ^ 1) * 8, 1);
                kv_load(2 + odd, odd, 2 - odd);
#pragma unroll 1
                for (int i = 0; i < 3; i++) {
                    const uint32_t sl = i ? i - 1 : 4, bo = i == 2 ? 16 : 8;
                    mbar_wait(full + (B_EMPTY - B_FULL + sl) * 8, i != 0);
                    if (lane == 0) mbar_arrive_tx(full + sl * 8, SLOT);
                    if ((i & 1) != odd) {
                        mbar_wait(rdy + bo, 0);
                        kv_load(sl, i != 0, 2 + odd);
                    } else if (lane == 0) mbar_arrive_peer(prdy + bo);
                    __syncwarp();
                }
                n = 32; s = 2; ph = 1;
            }
        } else if (warp == 10) {
            if (lane == 0) {
#pragma unroll
                for (int i = B_XA; i < NBARS; i++) mbar_init(bars + i * 8, 1);
#pragma unroll
                for (int i = B_XA; i <= B_SR; i++) mbar_arrive_tx(bars + i * 8, i < B_XB ? 512 : ((i >= B_INB && i < B_SR) ? 4096 : 8192));
                asm volatile("fence.mbarrier_init.release.cluster;" ::: "memory");
                fence_async_smem();
            }
            __syncwarp();
            cluster_arrive();
            cluster_wait();
        } else {
            const uint32_t kb = (lane < 2 || lane > 5) ? 4096 : (lane == 2 ? 3072 : (lane == 4 ? 2048 : 1024));
            const char* pf = p.w[lane & 7] + blockIdx.x * kb;
            cluster_arrive();
            cluster_wait();
            if (lane < 2) prefetch_l2(pf, kb);
            mbar_wait(bars + B_XA * 8, 0);
            if (lane == 2) prefetch_l2(pf, kb);
            if (lane >= 1 && lane < 9) asm volatile("prefetch.tensormap [%0];" ::"l"(&p.tm[lane]) : "memory");
            mbar_wait(bars + (B_FULL + 1) * 8, 1);
            if (lane > 2 && lane < 8) prefetch_l2(pf, kb);
            if (lane == 8 && blockIdx.x < 15) prefetch_l2(p.dw + blockIdx.x * 256, 512);
            const uint32_t epoch = ld_epoch();
            bar_sync(4, 288);
            if (lane < 16) flag_set(&g_flag_kv[((b * 4 + 2 * r + (lane >> 3)) * 32 + pt) * KFS + (lane & 7)], epoch);
            __syncwarp();
            bar_arrive(14, 96);
            TSW(8);
        }
        TSDUMP();
        return;
    }

    const int w = warp >> 2, wq = warp & 3;
    const int tile = 2 * r + w;
    const int wt = tid & 127;
    const int c4 = lane & 3;
    const int trow = pt * 32 + 8 * wq;
    uint32_t xr[8];
    {
        const uint32_t* xp = reinterpret_cast<const uint32_t*>(p.x + (size_t)(b * T_ + trow + (lane >> 2)) * 256 + tile * 64) + c4;
#pragma unroll
        for (int j = 0; j < 8; j++) xr[j] = trow < T_ ? __ldg(xp + 4 * j) : 0u;
    }
    cluster_arrive();
    asm volatile("setmaxnreg.inc.sync.aligned.u32 208;");
    const uint32_t rbase = sb + OFF_RING + w * NSLOT * SLOT, fbar = bars + (B_FULL + w * NSLOT) * 8;
    const uint32_t rdesc = desc_lo(rbase);
    auto acq = [&](int n) { mbar_wait(fbar + (n % NSLOT) * 8, (n / NSLOT) & 1); };
    auto rel = [&](int n) { if (lane == 0) mbar_arrive(fbar + (B_EMPTY - B_FULL + n % NSLOT) * 8); };
    const uint32_t foff = (lane & 7) * 128 + (((lane >> 3) ^ (lane & 7)) << 4);
    float v[16];
#pragma unroll
    for (int j = 0; j < 8; j++) { v[2 * j] = blo(xr[j]); v[2 * j + 1] = bhi(xr[j]); }
    const uint32_t xown = __shfl_sync(~0u, P + wt * 16 + tile * 4096, lane), xrem = __shfl_sync(~0u, P + wt * 16 + (r ^ 1) * 8192, lane);
    const uint32_t sbuf = __shfl_sync(~0u, sb + OFF_MISC + 1024 + (8 * wq + (lane >> 2)) * 32, lane);
    const uint32_t sown = __shfl_sync(~0u, sbuf + tile * 8, lane);
    const uint32_t peer = __shfl_sync(~0u, mapa(sb, r ^ 1) - sb, lane);
    const uint32_t hbuf = __shfl_sync(~0u, H + w * 4096 + wt * 16, lane);
    const uint32_t meta = __shfl_sync(~0u, 0xEEEE4444u + p.zero, lane);
    cluster_wait();
    TS(56);
    float mean, msq;
    const int mir = wq < 2 ? 7 : 0;
    uint32_t dwr[15] = {};

#pragma unroll UNR
    for (int ph = 0; ph < 5; ph++) {
        uint4 o0, o1;
        {
            float s = 0.f, q = 0.f, s2 = 0.f, q2 = 0.f;
#pragma unroll
            for (int j = 0; j < 4; j++) {
                s += v[4 * j] + v[4 * j + 1]; s2 += v[4 * j + 2] + v[4 * j + 3];
                q += fmaf(v[4 * j], v[4 * j], v[4 * j + 1] * v[4 * j + 1]); q2 += fmaf(v[4 * j + 2], v[4 * j + 2], v[4 * j + 3] * v[4 * j + 3]);
            }
            s += s2; q += q2;
            const uint32_t xa = bars + (B_XA + ph) * 8;
            s += __shfl_xor_sync(~0u, s, 1); q += __shfl_xor_sync(~0u, q, 1);
            s += __shfl_xor_sync(~0u, s, 2); q += __shfl_xor_sync(~0u, q, 2);
            if (c4 == 0) st_async2f(sown + peer, s, q, xa + peer);
            if (c4 == 0) sts64f(sown, s, q);
#pragma unroll
            for (int j = 0; j < 8; j++) xr[j] = pack2(v[2 * j], v[2 * j + 1]);
            sts128(xown, xr[0], xr[1], xr[2], xr[3]);
            sts128(xown + 2048, xr[4], xr[5], xr[6], xr[7]);
            bar_sync(10, 256);
            o0 = lds128(xown ^ 4096); o1 = lds128((xown ^ 4096) + 2048);
            if (ph < 4) {
                st_async4(xown + peer, xr[0], xr[1], xr[2], xr[3], xa + (B_XB - B_XA) * 8 + peer);
                st_async4(xown + peer + 2048, xr[4], xr[5], xr[6], xr[7], xa + (B_XB - B_XA) * 8 + peer);
            }
            TS(57 + ph);
            if (ph == 0 || ph == 3) acq(0);
            mbar_wait(xa, 0);
            const float4 u0 = lds128f(sbuf), u1 = lds128f(sbuf + 16);
            mean = ((u0.x + u0.z) + (u1.x + u1.z)) * (1.f / 256.f);
            msq = ((u0.y + u0.w) + (u1.y + u1.w)) * (1.f / 256.f);
        }
        if (ph == 4) break;
        uint32_t a[32];
        const uint32_t mean2 = pack2(mean, mean);
        auto centre = [&](int i, const uint4& u) {
            a[i] = hsub2(u.x, mean2); a[i + 1] = hsub2(u.y, mean2); a[i + 2] = hsub2(u.z, mean2); a[i + 3] = hsub2(u.w, mean2);
        };
#pragma unroll
        for (int j = 0; j < 8; j++) a[j] = hsub2(xr[j], mean2);
        centre(8, o0); centre(12, o1);
        const float rstd = rsq(fmaxf(fmaf(-mean, mean, msq), 0.f) + 1e-5f);
        auto gather_peer = [&]() {
            mbar_wait(bars + (B_XB + ph) * 8, 0);
#pragma unroll
            for (int i = 0; i < 4; i++) centre(16 + 4 * i, lds128(xrem + i * 2048));
        };
        auto sp = [&](float (&d)[32], int n, const uint32_t* af, int flip, int acc) {
            const uint32_t lo = rdesc + p.zero * (ph * 64 + n + 1) + (n % NSLOT) * (SLOT >> 4);
            const uint64_t b0 = mkdesc(lo + flip * 512), b1 = mkdesc(lo + (flip ^ 1) * 512);
            wg_fence();
            mma_sp(d, af, b0, meta, acc);
            mma_sp(d, af + 4, b0 + 256, meta, 1);
            mma_sp(d, af + 8, b1, meta, 1);
            mma_sp(d, af + 12, b1 + 256, meta, 1);
            wg_commit();
        };
        float d0[32], d1[32];

        if (ph == 0 || ph == 3) {
            uint32_t h[32], ho[32];
            const float rs = 0.5f * rstd;
            const uint32_t inb = bars + (B_INB + (ph & 2) + w) * 8;
            bool ready = true;
            auto step = [&](float (&d)[32], int n, const uint32_t* af, int flip, int acc, auto work) {
                if (!ready) acq(n);
                if (((TURN >> n) & 1) && w == 1) bar_sync(7, 256);
                sp(d, n, af, flip, acc);
                if (n > 0 && ((TURN >> (n - 1)) & 1) && w == 0) bar_arrive(7, 256);
                if (n < 15) ready = mbar_test(fbar + ((n + 1) % NSLOT) * 8, ((n + 1) / NSLOT) & 1);
                wg_wait<1>();
                if (n > 0 && !((EAGER >> (n - 1)) & 1)) rel(n - 1);
                const uint32_t tie = work() & p.zero;
                if ((EAGER >> n) & 1) {
                    if (p.zero < n + ph + 1) wg_wait<0>();
                    if (lane == 0) mbar_arrive(fbar + (B_EMPTY - B_FULL + n % NSLOT) * 8 + tie);
                }
            };
            auto none = []() { return 0u; };
            auto fetch = [&](int i) {
                bar_sync(10, 256);
                const uint4 u0 = lds128((hbuf ^ 4096) + (i & 1) * 8192), u1 = lds128((hbuf ^ 4096) + (i & 1) * 8192 + 2048);
                ho[8 * i] = u0.x; ho[8 * i + 1] = u0.y; ho[8 * i + 2] = u0.z; ho[8 * i + 3] = u0.w;
                ho[8 * i + 4] = u1.x; ho[8 * i + 5] = u1.y; ho[8 * i + 6] = u1.z; ho[8 * i + 7] = u1.w;
                return u0.x | u1.x;
            };
            auto act = [&](float (&d)[32], int i) {
                if (i > 0) fetch(i - 1);
                pin(d);
#pragma unroll
                for (int j = 0; j < 8; j++) {
                    const float u0 = (d[4 * j] + d[4 * j + 2]) * rs, u1 = (d[4 * j + 1] + d[4 * j + 3]) * rs;
                    h[8 * i + j] = pack2(fmaf(u0, tanh_fast(u0), u0), fmaf(u1, tanh_fast(u1), u1));
                }
                sts128(hbuf + (i & 1) * 8192, h[8 * i], h[8 * i + 1], h[8 * i + 2], h[8 * i + 3]);
                sts128(hbuf + (i & 1) * 8192 + 2048, h[8 * i + 4], h[8 * i + 5], h[8 * i + 6], h[8 * i + 7]);
                return 0u;
            };
            TS(1 + (ph & 2) * 10);
            step(d0, 0, a, w, 0, [&]() { gather_peer(); return 0u; });
            TS(32);
            step(d0, 1, a + 16, 0, 1, none);
            step(d1, 2, a, w, 0, [&]() { return act(d0, 0); });
            step(d1, 3, a + 16, 0, 1, none);
            step(d0, 4, a, w, 0, [&]() { return act(d1, 1); });
            TS(33);
            step(d0, 5, a + 16, 0, 1, none);
            step(d1, 6, a, w, 0, [&]() { return act(d0, 2); });
            step(d1, 7, a + 16, 0, 1, none);
            step(d0, 8, h, 0, 0, [&]() { act(d1, 3); return F3 == 8 ? fetch(3) : 0u; });
            TS(2 + (ph & 2) * 10);
            step(d0, 9, ho, 0, 1, [&]() { return F3 == 9 ? fetch(3) : 0u; });
            step(d0, 10, h + 16, 0, 1, [&]() { return F3 == 10 ? fetch(3) : 0u; });
            step(d0, 11, ho + 16, 0, 1, none);
            step(d1, 12, h, 0, 0, [&]() {
                pin(d0);
                uint32_t pk[8];
#pragma unroll
                for (int j = 0; j < 8; j++) pk[j] = pack2(d0[4 * j] + d0[4 * j + 2], d0[4 * j + 1] + d0[4 * j + 3]);
                st_async4(hbuf + 16384 + peer, pk[0], pk[1], pk[2], pk[3], inb + peer);
                st_async4(hbuf + 16384 + 2048 + peer, pk[4], pk[5], pk[6], pk[7], inb + peer);
                return 0u;
            });
            TS(34);
            step(d1, 13, ho, 0, 1, none);
            uint4 u[2];
            auto inbox = [&]() {
                mbar_wait(inb, 0);
                u[0] = lds128(hbuf + 16384); u[1] = lds128(hbuf + 16384 + 2048);
                return u[0].x | u[1].x;
            };
            step(d1, 14, h + 16, 0, 1, [&]() { return IB == 14 ? inbox() : 0u; });
            step(d1, 15, ho + 16, 0, 1, none);
            if (IB == 14 || ph == 0) mbar_wait(ph == 0 ? fbar + (16 % NSLOT) * 8 : inb, ph == 0);
            if (IB == 15) inbox();
            uint32_t tie = 0;
#pragma unroll
            for (int i = 0; i < 2; i++) {
                const uint32_t p0[4] = {u[i].x, u[i].y, u[i].z, u[i].w};
#pragma unroll
                for (int j = 0; j < 4; j++) {
                    v[8 * i + 2 * j] = fmaf(0.5f, blo(p0[j]), blo(xr[4 * i + j]));
                    v[8 * i + 2 * j + 1] = fmaf(0.5f, bhi(p0[j]), bhi(xr[4 * i + j]));
                    if (IB == 14) tie |= __float_as_uint(v[8 * i + 2 * j]) | __float_as_uint(v[8 * i + 2 * j + 1]);
                }
            }
            if (IB == 14 && __any_sync(~0u, tie & p.zero)) spin(1);
            wg_wait<0>();
            pin(d1);
            rel(15);
            TS(3 + (ph & 2) * 10);
#pragma unroll
            for (int j = 0; j < 8; j++) {
                v[2 * j] = fmaf(0.5f, d1[4 * j] + d1[4 * j + 2], v[2 * j]);
                v[2 * j + 1] = fmaf(0.5f, d1[4 * j + 1] + d1[4 * j + 3], v[2 * j + 1]);
            }
#pragma unroll
            for (int i = 0; i < 15; i++) dwr[i] = 0;
            continue;
        }

        auto residual = [&](int n) {
            wg_wait<1>();
            rel(n);
            wg_wait<0>();
            pin(d0);
            rel(n + 1);
#pragma unroll
            for (int j = 0; j < 8; j++) {
                v[2 * j] = d0[4 * j] + d0[4 * j + 2] + blo(xr[j]);
                v[2 * j + 1] = d0[4 * j + 1] + d0[4 * j + 3] + bhi(xr[j]);
            }
        };

        if (ph == 2) {
            TS(39);
            sp(d0, 34, a, w, 0);
            acq(35);
            sp(d1, 35, a, w, 0);
            acq(36); acq(37);
            gather_peer();
            sp(d0, 36, a + 16, 0, 1);
            sp(d1, 37, a + 16, 0, 1);
            wg_wait<2>();
            rel(34);
            if (!(LATE & 1)) rel(35);
            acq(38);
            const float rs = trow < T_ ? 0.5f * rstd : 0.f;
            wg_wait<0>();
            pin(d0); pin(d1);
            if (!(LATE & 2)) { rel(36); rel(37); }
            TS(18);
            uint32_t pk[8];
#pragma unroll
            for (int j = 0; j < 8; j++) {
                const float u0 = (d0[4 * j] + d0[4 * j + 2]) * rs, u1 = (d0[4 * j + 1] + d0[4 * j + 3]) * rs;
                const float t0 = tanh_fast((d1[4 * j] + d1[4 * j + 2]) * rs), t1 = tanh_fast((d1[4 * j + 1] + d1[4 * j + 3]) * rs);
                pk[j] = pack2(fmaf(u0, t0, u0), fmaf(u1, t1, u1));
            }
            if (wq == 0 || wq == 3) {
                uint4* hp = &g_halo[((pair * 4 + tile) * 2 + (wq & 1)) * 64 + lane];
                st_data(hp, pk[0], pk[1], pk[2], pk[3]);
                st_data(hp + 32, pk[4], pk[5], pk[6], pk[7]);
            }
            const uint32_t gs = H + 16384 + w * GCH + wq * 1024;
            stsm4(gs + 1024 + foff, pk[0], pk[1], pk[2], pk[3]);
            stsm4(gs + 1024 + (foff ^ 64), pk[4], pk[5], pk[6], pk[7]);
            bar_sync(8 + w, 192);
            TS(26);
            uint32_t ca[8], cb[8];
            const int e = (wq & 1) * 4;
            const uint32_t lo = ((mir ^ e) * 144) ^ (lane * 4);
            const int dir = mir ? -1024 : 1024;
            const uint32_t gb = H + 16384 + w * GCH + (mir ? 3072 : 2048) + lo, sown_ = H + tile * HCH, so = sown_ + (mir ? 1024 : 2048) + lo;
            auto finish = [&](int i) {
                const uint32_t c = hadd2(ca[i], cb[i]);
                const float h0 = blo(c), h1 = bhi(c);
                sts32((so + (i >> 2) * dir) ^ ((i & 3) * 144), pack2(fmaf(h0, tanh_fast(h0), h0), fmaf(h1, tanh_fast(h1), h1)));
            };
#pragma unroll
            for (int k = 0; k < 26; k++) {
                if (k == 19) {
#pragma unroll
                    for (int i = 0; i < 4; i++) finish(i);
                    fence_async_smem();
                    bar_sync(2 + w, 128);
                    if (wq == 0) peer_copy(mapa(sown_ + 1024, r ^ 1), sown_ + 1024, 2048, mapa(bars + B_SR * 8, r ^ 1));
                    mbar_wait(bars + (B_HALO + 2 * w + (wq >> 1)) * 8, 0);
                    if (LATE & 1) rel(35);
                    if (LATE & 2) { rel(36); rel(37); }
                    TS(27);
                }
                const uint32_t g = lds32((gb + (((k + 1) & 4) ? ((k + 1) >> 3) + (wq & 1) : ((k + 1) >> 3)) * dir) ^ (((k + 1) & 7) * 144));
#pragma unroll
                for (int i = 0; i < 8; i++) {
                    const int tap = k - (i & 3) - 2 * (i & 4);
                    if (tap == 0) ca[i] = hmul2(g, dwr[0]);
                    else if (tap > 0 && tap < 8) ca[i] = hfma2(g, dwr[tap], ca[i]);
                    else if (tap == 8) cb[i] = hmul2(g, dwr[8]);
                    else if (tap > 8 && tap < 15) cb[i] = hfma2(g, dwr[tap], cb[i]);
                }
            }
#pragma unroll
            for (int i = 4; i < 8; i++) finish(i);
            fence_async_smem();
            bar_sync(12 + (warp >> 1), 64);
            if (wq == 0 || wq == 3) peer_copy(mapa(sown_ + wq * 1024, r ^ 1), sown_ + wq * 1024, 1024, mapa(bars + B_SR * 8, r ^ 1));
            bar_sync(10, 256);
            TS(19);
            auto frags = [&](int i, int half) {
                const uint32_t src = H + 2 * half * HCH + wq * 1024;
#pragma unroll
                for (int k = 0; k < 4; k++) ldsm4(src + (k >> 1) * HCH + (foff ^ ((k & 1) * 64)), a[i + 4 * k], a[i + 4 * k + 1], a[i + 4 * k + 2], a[i + 4 * k + 3]);
            };
            frags(0, r);
            sp(d0, 38, a, 0, 0);
            acq(39);
            mbar_wait(bars + B_SR * 8, 0);
            frags(16, r ^ 1);
            sp(d0, 39, a + 16, 0, 1);
            residual(38);
            TS(20);
            continue;
        }

        {
            TS(11);
            const uint32_t stg = H + warp * 2048;
            unsigned char* g = g_kvq + (size_t)((b * 4 + tile) * 1024 + trow) * 128 + lane * 16;
            auto put = [&](float (&d)[32], int i) {
                pin(d);
                uint32_t pk[8];
#pragma unroll
                for (int j = 0; j < 8; j++) pk[j] = pack2((d[4 * j] + d[4 * j + 2]) * rstd, (d[4 * j + 1] + d[4 * j + 3]) * rstd);
                if (i == 2) {
                    st_data(g + 2097152, pk[0], pk[1], pk[2], pk[3]);
                    st_data(g + 2097152 + 512, pk[4], pk[5], pk[6], pk[7]);
                    return;
                }
                stsm4(stg + i * 1024 + foff, pk[0], pk[1], pk[2], pk[3]);
                stsm4(stg + i * 1024 + (foff ^ 64), pk[4], pk[5], pk[6], pk[7]);
                __syncwarp();
                const uint4 u0 = lds128(stg + i * 1024 + lane * 16), u1 = lds128(stg + i * 1024 + 512 + lane * 16);
                stg128(g + i * 1048576, u0); stg128(g + i * 1048576 + 512, u1);
            };
            sp(d0, 16, a, w, 0);
            acq(17);
            sp(d1, 17, a, w, 0);
            gather_peer();
            acq(18);
            sp(d0, 18, a + 16, 0, 1);
            wg_wait<1>();
            rel(16); rel(17);
            acq(19);
            sp(d1, 19, a + 16, 0, 1);
            wg_wait<1>();
            rel(18);
            put(d0, 0);
            wg_wait<0>();
            rel(19);
            TS(37);
            put(d1, 1);
            bar_arrive(4, 288);
            TS(38);
            acq(20);
            sp(d0, 20, a, w, 0);
            acq(21);
            sp(d0, 21, a + 16, 0, 1);
            acq(22); acq(23);
            rel(22); rel(23);
            mbar_wait(bars + B_RST * 8, 0);
            wg_wait<0>();
            rel(20); rel(21);
            put(d0, 2);
            TS(12);
        }

        {
            constexpr float CS = 0.125f * 1.4426950408889634f;
            float sa[32], sb2[32], o[36];
            uint32_t pa[16], pb[16], q[16];
            float n0 = INFINITY, n1 = INFINITY;
            zero(o); zero(pa); zero(pb); zero(sb2);
            const uint32_t ones = sb + OFF_MISC + 2048;
            { const uint32_t c = w ? 0u : 0x3F803F80u; sts128(ones + tid * 16, c, c, c, c); }
            fence_async_smem();
            bar_sync(10, 256);
            const uint32_t vdesc = rdesc + ((((ones - rbase) >> 4) - 1) << 16);
            auto qk_issue = [&](float (&s)[32], uint32_t lo) {
                const uint64_t kd = mkdesc(lo);
                wg_fence();
#pragma unroll
                for (int k = 0; k < 4; k++) mma_qk(s, q[4 * k], q[4 * k + 1], q[4 * k + 2], q[4 * k + 3], kd + 2 * k, k != 0);
                wg_commit();
            };
            auto both_issue = [&](float (&s)[32], uint32_t klo, uint32_t (&pp)[16], uint32_t vlo) {
                const uint64_t kd = mkdesc(klo), vd = mkdesc(vlo);
                wg_fence();
#pragma unroll
                for (int k = 0; k < 4; k++) {
                    mma_pv(o, pp[4 * k], pp[4 * k + 1], pp[4 * k + 2], pp[4 * k + 3], vd - k * (128 * 65535));
                    mma_qk(s, q[4 * k], q[4 * k + 1], q[4 * k + 2], q[4 * k + 3], kd + 2 * k, k != 0);
                }
                wg_commit();
            };
            auto new_max = [&](float (&s)[32], int nj, float& x0, float& x1) {
                x0 = s[0]; x1 = s[2];
#pragma unroll
                for (int j = 0; j < nj; j++) {
                    x0 = fmaxf(x0, fmaxf(s[4 * j], s[4 * j + 1]));
                    x1 = fmaxf(x1, fmaxf(s[4 * j + 2], s[4 * j + 3]));
                }
                x0 = fmaxf(x0, __shfl_xor_sync(~0u, x0, 1)); x1 = fmaxf(x1, __shfl_xor_sync(~0u, x1, 1));
                x0 = fmaxf(x0, __shfl_xor_sync(~0u, x0, 2)); x1 = fmaxf(x1, __shfl_xor_sync(~0u, x1, 2));
                x0 = fminf(n0, fmaf(x0, -CS, -20.f)); x1 = fminf(n1, fmaf(x1, -CS, -20.f));
            };
            auto probs = [&](float (&s)[32], uint32_t (&pp)[16], bool ready, bool tail, auto wait) {
                uint32_t any = 0;
#pragma unroll
                for (int i = 0; i < 16; i++) {
                    pp[i] = pack2(ex2(fmaf(s[2 * i], CS, (i & 1) ? n1 : n0)), ex2(fmaf(s[2 * i + 1], CS, (i & 1) ? n1 : n0)));
                    any |= pp[i];
                }
                wg_wait<0>();
                pin(sa); pin(sb2); pin(o); pin(pa); pin(pb);
                if (__any_sync(~0u, (any & 0x40004000u) || !ready)) {
                    wait();
                    if (__any_sync(~0u, any & 0x40004000u)) {
                        if (tail) {
#pragma unroll
                            for (int i = 20; i < 32; i++) s[i] = -INFINITY;
                        }
                        float x0, x1;
                        new_max(s, 8, x0, x1);
                        const float sc0 = ex2(x0 - n0), sc1 = ex2(x1 - n1);
                        n0 = x0; n1 = x1;
#pragma unroll
                        for (int j = 0; j < 9; j++) { o[4 * j] *= sc0; o[4 * j + 1] *= sc0; o[4 * j + 2] *= sc1; o[4 * j + 3] *= sc1; }
#pragma unroll
                        for (int i = 0; i < 16; i++)
                            pp[i] = pack2(ex2(fmaf(s[2 * i], CS, (i & 1) ? n1 : n0)), ex2(fmaf(s[2 * i + 1], CS, (i & 1) ? n1 : n0)));
                    }
                }
            };
            {
                uint4 u[4];
                const unsigned char* src = g_kvq + 2097152 + (size_t)(abh * 1024 + qt * 64 + wq * 16) * 128 + lane * 16;
                spin(QGATE);
                ld_data<512>(u, src);
#pragma unroll
                for (int k = 0; k < 2; k++) {
                    q[8 * k] = u[k].x; q[8 * k + 1] = u[k + 2].x; q[8 * k + 2] = u[k].y; q[8 * k + 3] = u[k + 2].y;
                    q[8 * k + 4] = u[k].z; q[8 * k + 5] = u[k + 2].z; q[8 * k + 6] = u[k].w; q[8 * k + 7] = u[k + 2].w;
                }
                pin(q);
            }
            TS(40);
            acq(24);
            TS(13);
            qk_issue(sa, rdesc + (24 % NSLOT) * (SLOT >> 4));
            wg_wait<0>();
            pin(sa);
            {
                float x0, x1;
                new_max(sa, NJ0, x0, x1);
                n0 = x0; n1 = x1;
            }
            bar_arrive(6, 384);
            uint32_t vd = vdesc - (SLOT >> 4) * 65535u, kd = rdesc, vb = fbar + 8, kb = fbar;
            uint32_t vlast = vdesc - 4 * (SLOT >> 4) * 65535u, klast = rdesc + 4 * (SLOT >> 4) + 512;
            uint32_t kprev = fbar + 32, vprev = bars + (B_SINK - (B_EMPTY - B_FULL)) * 8;
#pragma unroll 1
            for (int it = 0; it < 4; it++) {
                both_issue(sb2, klast, pb, vlast);
                probs(sa, pa, mbar_test(vb, it < 2) & mbar_test(kb, it < 3), false, [&]() { mbar_wait(vb, it < 2); mbar_wait(kb, it < 3); });
                TS(41 + it * 4);
                if (lane == 0) mbar_arrive(kprev + (B_EMPTY - B_FULL) * 8);
                if (lane == 0) mbar_arrive(vprev + (B_EMPTY - B_FULL) * 8);
                both_issue(sa, kd, pa, vd);
                const int dv = it == 0 ? 2 : (it == 1 ? -3 : 1);
                kprev = kb; vprev = vb; vlast = vd - 512 * 65535u; klast = kd + 512;
                vd -= dv * (SLOT >> 4) * 65535u; vb += dv * 8;
                kd += (it == 2 ? -3 : 2) * (SLOT >> 4); kb = it == 2 ? vb : kb + 16;
                probs(sb2, pb, true, it == 3 && w == 1, []() {});
                TS(43 + it * 4);
            }
            wg_fence();
#pragma unroll
            for (int k = 0; k < 4; k++)
                mma_pv(o, pb[4 * k], pb[4 * k + 1], pb[4 * k + 2], pb[4 * k + 3], mkdesc(vlast - k * (128 * 65535) + (k > 1 ? w * ((k - 1) << 22) : 0)));
            wg_commit();
            const int row = wq * 16 + (lane >> 2);
            const uint32_t ml = sb + OFF_MISC;
            mbar_wait(bars + (B_RST + 1) * 8, 0);
            wg_wait<0>();
            pin(o); pin(pb); pin(sa); pin(sb2);
            if (!(LATE & 4)) rel(31);
            const float l0 = o[32], l1 = o[34];
            if (c4 == 0) { sts64f(ml + w * 512 + row * 8, n0, l0); sts64f(ml + w * 512 + row * 8 + 64, n1, l1); }
            TS(14);
            float mine[16];
#pragma unroll
            for (int j = 0; j < 4; j++) {
                if (w == 0) sts128f(H + j * 2048 + wt * 16, o[16 + 4 * j], o[17 + 4 * j], o[18 + 4 * j], o[19 + 4 * j]);
                else sts128f(H + 8192 + j * 2048 + wt * 16, o[4 * j], o[4 * j + 1], o[4 * j + 2], o[4 * j + 3]);
            }
#pragma unroll
            for (int i = 0; i < 16; i++) mine[i] = w == 0 ? o[i] : o[16 + i];
            bar_sync(10, 256);
            const float2 u0 = lds64f(ml + (w ^ 1) * 512 + row * 8), u1 = lds64f(ml + (w ^ 1) * 512 + row * 8 + 64);
            const float x0 = fminf(n0, u0.x), x1 = fminf(n1, u1.x);
            float a0 = ex2(x0 - n0), b0 = ex2(x0 - u0.x), a1 = ex2(x1 - n1), b1 = ex2(x1 - u1.x);
            const float i0 = __fdividef(1.f, fmaf(a0, l0, b0 * u0.y)), i1 = __fdividef(1.f, fmaf(a1, l1, b1 * u1.y));
            a0 *= i0; b0 *= i0; a1 *= i1; b1 *= i1;
            uint32_t pk[8];
#pragma unroll
            for (int j = 0; j < 4; j++) {
                const float4 v = lds128f(H + (w ^ 1) * 8192 + j * 2048 + wt * 16);
                pk[2 * j] = pack2(fmaf(a0, mine[4 * j], b0 * v.x), fmaf(a0, mine[4 * j + 1], b0 * v.y));
                pk[2 * j + 1] = pack2(fmaf(a1, mine[4 * j + 2], b1 * v.z), fmaf(a1, mine[4 * j + 3], b1 * v.w));
            }
            unsigned char* dst = g_o + (size_t)(b * 128 + qt * 8 + 2 * wq) * 4096 + ah * 1024 + w * 512 + lane * 16;
            st_data(dst, pk[0], pk[2], pk[4], pk[6]);
            st_data(dst + 4096, pk[1], pk[3], pk[5], pk[7]);
            if (tid == 0) asm volatile("red.relaxed.gpu.global.add.u32 [%0], 1;" ::"l"(&g_epoch[blockIdx.x * FS]) : "memory");
            TS(15);
        }

        {
            const uint32_t* dp = reinterpret_cast<const uint32_t*>(p.dw + (mir ? 14 * 256 : 0) + tile * 64) + lane;
#pragma unroll
            for (int i = 0; i < 15; i++) asm volatile("ld.global.nc.b32 %0, [%1];" : "=r"(dwr[i]) : "l"(dp + i * (mir ? -128 : 128)));
            acq(32); acq(33); acq(34);
            uint4 u[8];
            ld_data<512>(u, g_o + (size_t)(b * 128 + pt * 4 + wq) * 4096 + lane * 16);
#pragma unroll
            for (int i = 0; i < 8; i++) { a[4 * i] = u[i].x; a[4 * i + 1] = u[i].y; a[4 * i + 2] = u[i].z; a[4 * i + 3] = u[i].w; }
            if (LATE & 4) rel(31);
            TS(16);
            sp(d0, 32, a, 0, 0);
            sp(d0, 33, a + 16, 0, 1);
#pragma unroll
            for (int i = 0; i < 15; i++) dwr[i] = hmul2(dwr[i], 0x3F003F00u);
            residual(32);
            TS(17);
        }
    }

    cluster_arrive();
    TS(24);
    {
        const float rstd = rsq(fmaxf(fmaf(-mean, mean, msq), 0.f) + 1e-5f), nb = -mean * rstd;
#pragma unroll
        for (int j = 0; j < 8; j++) xr[j] = pack2(fmaf(v[2 * j], rstd, nb), fmaf(v[2 * j + 1], rstd, nb));
        const uint32_t stg = P + 16384 + warp * 1024;
        stsm4(stg + foff, xr[0], xr[1], xr[2], xr[3]);
        stsm4(stg + (foff ^ 64), xr[4], xr[5], xr[6], xr[7]);
        __syncwarp();
        const uint32_t src = stg + (lane >> 3) * 128 + (((lane & 7) ^ (lane >> 3)) << 4);
        const uint4 u0 = lds128(src), u1 = lds128((src + 512) ^ 64);
        __nv_bfloat16* dst = p.out + (size_t)(b * T_ + trow + (lane >> 3)) * 256 + tile * 64 + (lane & 7) * 8;
        if (trow < T_) { stg128(dst, u0); stg128(dst + 4 * 256, u1); }
    }
    TS(25);
    TG(31);
    TSDUMP();
    cluster_wait();
}

typedef CUresult (*EncodeFn)(CUtensorMap*, CUtensorMapDataType, cuuint32_t, void*, const cuuint64_t*, const cuuint64_t*,
                             const cuuint32_t*, const cuuint32_t*, CUtensorMapInterleave, CUtensorMapSwizzle,
                             CUtensorMapL2promotion, CUtensorMapFloatOOBfill);

}

extern "C" void kernel_launch(void* const* d_in, const int* in_sizes, int n_in, void* d_out, int out_size) {
    static EncodeFn encode = nullptr;
    if (!encode) {
        void* fn = nullptr;
        cudaDriverEntryPointQueryResult qr;
        cudaGetDriverEntryPoint("cuTensorMapEncodeTiled", &fn, cudaEnableDefault, &qr);
        encode = (EncodeFn)fn;
        cudaFuncSetAttribute(conformer_kernel, cudaFuncAttributeMaxDynamicSharedMemorySize, SMEM_LAUNCH);
    }
    Params p;
    const cuuint32_t ones[5] = {1, 1, 1, 1, 1};
    const int idx[8] = {1, 2, 3, 4, 5, 7, 8, 9};
    const int rows[8] = {256, 1024, 256, 256, 256, 256, 256, 1024};
    const int cols[8] = {1024, 256, 768, 256, 512, 256, 1024, 256};
    for (int i = 0; i < 8; i++) {
        const cuuint64_t pitch = (cuuint64_t)cols[i] * 2;
        const cuuint64_t dims[5] = {(cuuint64_t)cols[i], 2, 2, 4, (cuuint64_t)rows[i] / 16};
        const cuuint64_t strides[4] = {pitch, pitch * 8, pitch * 2, pitch * 16};
        const cuuint32_t box[5] = {64, 2, 2, 4, 8};
        encode(&p.tm[i], CU_TENSOR_MAP_DATA_TYPE_BFLOAT16, 5, d_in[idx[i]], dims, strides, box, ones, CU_TENSOR_MAP_INTERLEAVE_NONE,
               CU_TENSOR_MAP_SWIZZLE_128B, CU_TENSOR_MAP_L2_PROMOTION_L2_128B, CU_TENSOR_MAP_FLOAT_OOB_FILL_NONE);
        p.w[i] = (const char*)d_in[idx[i]];
    }
    {
        void* kv = nullptr;
        cudaGetSymbolAddress(&kv, g_kvq);
        const cuuint64_t dims[2] = {64, 16384};
        const cuuint64_t strides[1] = {128};
        const cuuint32_t box[2] = {64, 128};
        encode(&p.tm[8], CU_TENSOR_MAP_DATA_TYPE_BFLOAT16, 2, kv, dims, strides, box, ones, CU_TENSOR_MAP_INTERLEAVE_NONE,
               CU_TENSOR_MAP_SWIZZLE_NONE, CU_TENSOR_MAP_L2_PROMOTION_L2_128B, CU_TENSOR_MAP_FLOAT_OOB_FILL_NONE);
    }
    p.x = (const __nv_bfloat16*)d_in[0];
    p.dw = (const __nv_bfloat16*)d_in[6];
    p.out = (__nv_bfloat16*)d_out;
    p.zero = 0;
    conformer_kernel<<<NCTA, NTHREADS, SMEM_LAUNCH>>>(p);
}
```

```cpp
#include <cuda_runtime.h>
#include <cuda_bf16.h>
#include <cuda.h>
#include <stdint.h>

namespace {

constexpr int T_ = 1000;
constexpr int NCTA = 128;
constexpr int NTHREADS = 512;
constexpr int NSLOT = 5;
constexpr int SLOT = 16384;
constexpr int NLOADS = 56;

constexpr uint32_t OFF_RING = 0;
constexpr uint32_t OFF_P = 163840;
constexpr uint32_t OFF_H = 188416;
constexpr uint32_t OFF_MISC = 221184;
constexpr uint32_t OFF_BARS = 229888;
constexpr uint32_t SMEM_BYTES = 230400;
constexpr uint32_t GCH = 6144;
constexpr uint32_t HCH = 4096;

constexpr int B_FULL = 0, B_EMPTY = 10, B_XA = 20  , B_XB = 25  , B_INB = 29  , B_SR = 33,
              B_RST = 34  , B_RDY = 36  , B_SINK = 42, B_HALO = 43  , NBARS = 47;

#define KD2 300u
#define KD3 500u
#define QGATE 500u
#define BACKOFF 0u
#define KFS 8
#define KDELAY 300u
#define NJ0 2
#define HDELAY 200u
#define LATE 2
#define UNRV 5
constexpr int UNR = UNRV;
#define SND 0
#define TURN 0x200
#define EAGER 0x0155
constexpr int FS = 8;

struct Params {
    CUtensorMap tm[9];
    const char* w[8];
    const __nv_bfloat16* x;
    const __nv_bfloat16* dw;
    __nv_bfloat16* out;
    uint32_t zero;
};

__device__ __align__(1024) unsigned char g_kvq[3 * 8 * 1024 * 128];
__device__ __align__(1024) unsigned char g_o[2 * 128 * 4096];
__device__ uint4 g_halo[64 * 4 * 2 * 64];
__device__ __align__(128) uint32_t g_flag_kv[8 * 32 * KFS];
__device__ uint32_t g_reset[4 * 32];
__device__ uint32_t g_epoch[NCTA * FS];

#define TS(i) do { } while (0)
#define TSW(i) do { } while (0)
#define TG(i) do { } while (0)
#define TSINIT() do { } while (0)
#define TSDUMP() do { } while (0)
constexpr uint32_t SMEM_LAUNCH = SMEM_BYTES;

__device__ __forceinline__ uint32_t smem_u32(const void* p) { return (uint32_t)__cvta_generic_to_shared(p); }
__device__ __forceinline__ void mbar_init(uint32_t b, uint32_t c) { asm volatile("mbarrier.init.shared::cta.b64 [%0], %1;" ::"r"(b), "r"(c) : "memory"); }
__device__ __forceinline__ void mbar_arrive(uint32_t b) { asm volatile("mbarrier.arrive.shared::cta.b64 _, [%0];" ::"r"(b) : "memory"); }
__device__ __forceinline__ void mbar_arrive_tx(uint32_t b, uint32_t tx) { asm volatile("mbarrier.arrive.expect_tx.shared::cta.b64 _, [%0], %1;" ::"r"(b), "r"(tx) : "memory"); }
__device__ __forceinline__ void mbar_wait(uint32_t b, uint32_t ph) {
    asm volatile("{\n.reg .pred p, q;\n.reg .u32 c;\nmov.u32 c, 0;\n"
                 "MW_LOOP:\n.pragma \"nounroll\";\n"
                 "mbarrier.try_wait.parity.shared::cta.b64 p, [%0], %1;\n"
                 "add.u32 c, c, 1;\nsetp.lt.u32 q, c, 65536;\nnot.pred p, p;\nand.pred p, p, q;\n@p bra MW_LOOP;\n}"
                 ::"r"(b), "r"(ph) : "memory");
}
__device__ __forceinline__ bool mbar_test(uint32_t b, uint32_t ph) {
    uint32_t ok;
    asm volatile("{\n.reg .pred p;\nmbarrier.test_wait.parity.shared::cta.b64 p, [%1], %2;\nselp.u32 %0, 1, 0, p;\n}" : "=r"(ok) : "r"(b), "r"(ph) : "memory");
    return ok;
}
__device__ __forceinline__ uint32_t mapa(uint32_t a, uint32_t r) { uint32_t o; asm("mapa.shared::cluster.u32 %0, %1, %2;" : "=r"(o) : "r"(a), "r"(r)); return o; }
__device__ __forceinline__ void fence_async_smem() { asm volatile("fence.proxy.async.shared::cta;" ::: "memory"); }
__device__ __forceinline__ void fence_async_global() { asm volatile("fence.proxy.async.global;" ::: "memory"); }
__device__ __forceinline__ void bar_sync(int id, int n) { asm volatile("bar.sync %0, %1;" ::"r"(id), "r"(n) : "memory"); }
__device__ __forceinline__ void bar_arrive(int id, int n) { asm volatile("bar.arrive %0, %1;" ::"r"(id), "r"(n) : "memory"); }
__device__ __forceinline__ void cluster_arrive() { asm volatile("barrier.cluster.arrive.relaxed.aligned;" ::: "memory"); }
__device__ __forceinline__ void cluster_wait() { asm volatile("barrier.cluster.wait.aligned;" ::: "memory"); }

__device__ __forceinline__ void ring_load(uint32_t dst, const CUtensorMap* tm, int col, int row16, uint32_t bar) {
    asm volatile("{\n.reg .pred p;\nelect.sync _|p, 0xffffffff;\n"
                 "@p mbarrier.arrive.expect_tx.shared::cta.b64 _, [%2], 16384;\n"
                 "@p cp.async.bulk.tensor.5d.shared::cluster.global.mbarrier::complete_tx::bytes [%0], [%1, {%3, 0, 0, 0, %4}], [%2];\n}"
                 ::"r"(dst), "l"(tm), "r"(bar), "r"(col), "r"(row16) : "memory");
}
__device__ __forceinline__ void ring_load_both(uint32_t dst, const CUtensorMap* tm, int c1, uint32_t bar) {
    asm volatile("{\n.reg .pred p;\nelect.sync _|p, 0xffffffff;\n"
                 "@p cp.async.bulk.tensor.2d.shared::cluster.global.mbarrier::complete_tx::bytes.multicast::cluster [%0], [%1, {0, %3}], [%2], %4;\n}"
                 ::"r"(dst), "l"(tm), "r"(bar), "r"(c1), "h"((uint16_t)3) : "memory");
}
__device__ __forceinline__ void mbar_arrive_peer(uint32_t b) { asm volatile("mbarrier.arrive.relaxed.cluster.shared::cluster.b64 _, [%0];" ::"r"(b) : "memory"); }
__device__ __forceinline__ void prefetch_l2(const void* src, uint32_t bytes) {
    asm volatile("cp.async.bulk.prefetch.L2.global [%0], %1;" ::"l"(src), "r"(bytes) : "memory");
}
__device__ __forceinline__ void peer_copy(uint32_t dst, uint32_t src, uint32_t bytes, uint32_t rbar) {
    asm volatile("{\n.reg .pred p;\nelect.sync _|p, 0xffffffff;\n"
                 "@p cp.async.bulk.shared::cluster.shared::cta.mbarrier::complete_tx::bytes [%0], [%1], %2, [%3];\n}"
                 ::"r"(dst), "r"(src), "r"(bytes), "r"(rbar) : "memory");
}
__device__ __forceinline__ void st_async4(uint32_t dst, uint32_t a, uint32_t b, uint32_t c, uint32_t d, uint32_t bar) {
    asm volatile("st.async.shared::cluster.mbarrier::complete_tx::bytes.v4.b32 [%0], {%1,%2,%3,%4}, [%5];" ::"r"(dst), "r"(a), "r"(b), "r"(c), "r"(d), "r"(bar) : "memory");
}
__device__ __forceinline__ void st_async2f(uint32_t dst, float a, float b, uint32_t bar) {
    asm volatile("st.async.shared::cluster.mbarrier::complete_tx::bytes.v2.f32 [%0], {%1,%2}, [%3];" ::"r"(dst), "f"(a), "f"(b), "r"(bar) : "memory");
}
__device__ __forceinline__ void stsm4(uint32_t a, uint32_t r0, uint32_t r1, uint32_t r2, uint32_t r3) {
    asm volatile("stmatrix.sync.aligned.m8n8.x4.shared.b16 [%0], {%1,%2,%3,%4};" ::"r"(a), "r"(r0), "r"(r1), "r"(r2), "r"(r3) : "memory");
}
__device__ __forceinline__ void ldsm4(uint32_t a, uint32_t& r0, uint32_t& r1, uint32_t& r2, uint32_t& r3) {
    asm volatile("ldmatrix.sync.aligned.m8n8.x4.shared.b16 {%0,%1,%2,%3}, [%4];" : "=r"(r0), "=r"(r1), "=r"(r2), "=r"(r3) : "r"(a) : "memory");
}
__device__ __forceinline__ uint4 lds128(uint32_t a) { uint4 v; asm volatile("ld.shared.v4.b32 {%0,%1,%2,%3}, [%4];" : "=r"(v.x), "=r"(v.y), "=r"(v.z), "=r"(v.w) : "r"(a) : "memory"); return v; }
__device__ __forceinline__ float4 lds128f(uint32_t a) { float4 v; asm volatile("ld.shared.v4.f32 {%0,%1,%2,%3}, [%4];" : "=f"(v.x), "=f"(v.y), "=f"(v.z), "=f"(v.w) : "r"(a) : "memory"); return v; }
__device__ __forceinline__ float2 lds64f(uint32_t a) { float2 v; asm volatile("ld.shared.v2.f32 {%0,%1}, [%2];" : "=f"(v.x), "=f"(v.y) : "r"(a) : "memory"); return v; }
__device__ __forceinline__ uint32_t lds32(uint32_t a) { uint32_t v; asm volatile("ld.shared.b32 %0, [%1];" : "=r"(v) : "r"(a) : "memory"); return v; }
__device__ __forceinline__ void sts128(uint32_t a, uint32_t x, uint32_t y, uint32_t z, uint32_t w) { asm volatile("st.shared.v4.b32 [%0], {%1,%2,%3,%4};" ::"r"(a), "r"(x), "r"(y), "r"(z), "r"(w) : "memory"); }
__device__ __forceinline__ void sts128f(uint32_t a, float x, float y, float z, float w) { asm volatile("st.shared.v4.f32 [%0], {%1,%2,%3,%4};" ::"r"(a), "f"(x), "f"(y), "f"(z), "f"(w) : "memory"); }
__device__ __forceinline__ void sts64f(uint32_t a, float x, float y) { asm volatile("st.shared.v2.f32 [%0], {%1,%2};" ::"r"(a), "f"(x), "f"(y) : "memory"); }
__device__ __forceinline__ void sts32(uint32_t a, uint32_t x) { asm volatile("st.shared.b32 [%0], %1;" ::"r"(a), "r"(x) : "memory"); }
__device__ __forceinline__ void stg128(void* p, uint4 v) { asm volatile("st.global.v4.b32 [%0], {%1,%2,%3,%4};" ::"l"(p), "r"(v.x), "r"(v.y), "r"(v.z), "r"(v.w) : "memory"); }

__device__ __forceinline__ uint32_t pack2(float lo, float hi) { uint32_t r; asm("cvt.rn.bf16x2.f32 %0, %1, %2;" : "=r"(r) : "f"(hi), "f"(lo)); return r; }
__device__ __forceinline__ float blo(uint32_t v) { return __uint_as_float(v << 16); }
__device__ __forceinline__ float bhi(uint32_t v) { return __uint_as_float(v & 0xffff0000u); }
__device__ __forceinline__ uint32_t hmul2(uint32_t a, uint32_t b) { uint32_t r; asm("mul.rn.bf16x2 %0, %1, %2;" : "=r"(r) : "r"(a), "r"(b)); return r; }
__device__ __forceinline__ uint32_t hadd2(uint32_t a, uint32_t b) { uint32_t r; asm("add.rn.bf16x2 %0, %1, %2;" : "=r"(r) : "r"(a), "r"(b)); return r; }
__device__ __forceinline__ uint32_t hsub2(uint32_t a, uint32_t b) { uint32_t r; asm("sub.rn.bf16x2 %0, %1, %2;" : "=r"(r) : "r"(a), "r"(b)); return r; }
__device__ __forceinline__ uint32_t hfma2(uint32_t a, uint32_t b, uint32_t c) { uint32_t r; asm("fma.rn.bf16x2 %0, %1, %2, %3;" : "=r"(r) : "r"(a), "r"(b), "r"(c)); return r; }
__device__ __forceinline__ float tanh_fast(float x) { float r; asm("tanh.approx.f32 %0, %1;" : "=f"(r) : "f"(x)); return r; }
__device__ __forceinline__ float rsq(float x) { float r; asm("rsqrt.approx.ftz.f32 %0, %1;" : "=f"(r) : "f"(x)); return r; }
__device__ __forceinline__ float ex2(float x) { float r; asm("ex2.approx.ftz.f32 %0, %1;" : "=f"(r) : "f"(x)); return r; }

__device__ __forceinline__ uint32_t ld_relaxed(const uint32_t* p) {
    uint32_t v;
    asm volatile("ld.relaxed.gpu.global.u32 %0, [%1];" : "=r"(v) : "l"(p) : "memory");
    return v;
}
__device__ __forceinline__ uint32_t clock32() { uint32_t c; asm volatile("mov.u32 %0, %%clock;" : "=r"(c)::"memory"); return c; }
__device__ __forceinline__ void spin(uint32_t clks) {
    const uint32_t t0 = clock32();
    while (clock32() - t0 < clks) {}
}
__device__ __forceinline__ void flag_wait(const uint32_t* p, uint32_t e, bool mine) {
#pragma unroll 1
    for (int i = 0; i < (1 << 19); i++) {
        if (mine) mine = ld_relaxed(p) != e;
        if (!__any_sync(~0u, mine)) break;
        if (BACKOFF) spin(BACKOFF);
    }
    asm volatile("fence.acquire.gpu;" ::: "memory");
    fence_async_global();
}
__device__ __forceinline__ void st_data(void* p, uint32_t x, uint32_t y, uint32_t z, uint32_t w) {
    asm volatile("st.relaxed.gpu.global.v4.b32 [%0], {%1,%2,%3,%4};" ::"l"(p), "r"(x), "r"(y), "r"(z), "r"(w) : "memory");
}
template <int STRIDE, int N>
__device__ __forceinline__ void ld_data(uint4 (&v)[N], const unsigned char* p) {
    int it = 0;
    bool again;
#pragma unroll 1
    do {
        uint32_t m = 0;
#pragma unroll
        for (int i = 0; i < N; i++)
            asm volatile("ld.relaxed.gpu.global.v4.b32 {%0,%1,%2,%3}, [%4];" : "=r"(v[i].x), "=r"(v[i].y), "=r"(v[i].z), "=r"(v[i].w) : "l"(p + i * STRIDE) : "memory");
#pragma unroll
        for (int i = 0; i < N; i++) m = __vimax3_u32(__vimax3_u32(v[i].x, v[i].y, v[i].z), v[i].w, m);
        again = __any_sync(~0u, m == ~0u) && ++it < (1 << 16);
    } while (again);
}
__device__ __forceinline__ uint32_t ld_epoch() { return ld_relaxed(&g_epoch[blockIdx.x * FS]) + 1; }
__device__ __forceinline__ void flag_set(uint32_t* p, uint32_t e) { asm volatile("st.release.gpu.global.u32 [%0], %1;" ::"l"(p), "r"(e) : "memory"); }

__device__ __forceinline__ uint32_t desc_lo(uint32_t addr) { return ((addr & 0x3FFFF) >> 4) | 0x10000u; }
__device__ __forceinline__ uint64_t mkdesc(uint32_t lo) { return (uint64_t)lo | (0x40000040ull << 32); }
__device__ __forceinline__ void wg_fence() { asm volatile("wgmma.fence.sync.aligned;" ::: "memory"); }
__device__ __forceinline__ void wg_commit() { asm volatile("wgmma.commit_group.sync.aligned;" ::: "memory"); }
template <int N> __device__ __forceinline__ void wg_wait() { asm volatile("wgmma.wait_group.sync.aligned %0;" ::"n"(N) : "memory"); }
template <int N> __device__ __forceinline__ void pin(float (&d)[N]) {
#pragma unroll
    for (int i = 0; i < N; i++) asm volatile("" : "+f"(d[i])::"memory");
}
template <int N> __device__ __forceinline__ void pin(uint32_t (&d)[N]) {
#pragma unroll
    for (int i = 0; i < N; i++) asm volatile("" : "+r"(d[i])::"memory");
}

template <typename Tp, int N> __device__ __forceinline__ void zero(Tp (&d)[N]) {
#pragma unroll
    for (int i = 0; i < N; i++) d[i] = 0;
    pin(d);
}

#define F4(d, i) "+f"(d[i]), "+f"(d[i + 1]), "+f"(d[i + 2]), "+f"(d[i + 3])
#define F16(d, i) F4(d, i), F4(d, i + 4), F4(d, i + 8), F4(d, i + 12)

__device__ __forceinline__ void mma16(float (&d)[4], const uint32_t* a, uint32_t b0, uint32_t b1) {
    asm("mma.sync.aligned.m16n8k16.row.col.f32.bf16.bf16.f32 {%0,%1,%2,%3}, {%4,%5,%6,%7}, {%8,%9}, {%0,%1,%2,%3};"
        : F4(d, 0) : "r"(a[0]), "r"(a[1]), "r"(a[2]), "r"(a[3]), "r"(b0), "r"(b1));
}
template <int N>
__device__ __forceinline__ void row_sums(const uint32_t* x, int lane, float& s, float& q) {
    float cs[4] = {}, c0[4] = {}, c1[4] = {};
#pragma unroll
    for (int i = 0; i < N; i += 4) {
        mma16(cs, x + i, 0x3F803F80u, 0x3F803F80u);
        mma16(c0, x + i, x[i], x[i + 2]);
        mma16(c1, x + i, x[i + 1], x[i + 3]);
    }
    s = cs[0] + cs[2];
    q = (lane & 4) ? c0[1] + c1[3] : c0[0] + c1[2];
}
__device__ __forceinline__ void mma_sp(float (&d)[32], const uint32_t* a, uint64_t b, uint32_t meta, int acc) {
    asm volatile("{.reg .pred p; setp.ne.b32 p, %38, 0;\n"
                 "wgmma.mma_async.sp.sync.aligned.m64n64k32.f32.bf16.bf16 {%0,%1,%2,%3,%4,%5,%6,%7,%8,%9,%10,%11,%12,%13,%14,%15,%16,%17,%18,%19,%20,%21,%22,%23,%24,%25,%26,%27,%28,%29,%30,%31}, "
                 "{%32,%33,%34,%35}, %36, %37, 0, p, 1, 1, 1;}\n"
                 : F16(d, 0), F16(d, 16) : "r"(a[0]), "r"(a[1]), "r"(a[2]), "r"(a[3]), "l"(b), "r"(meta), "r"(acc));
}
__device__ __forceinline__ void mma_qk(float (&d)[32], uint32_t a0, uint32_t a1, uint32_t a2, uint32_t a3, uint64_t b, int acc) {
    asm volatile("{.reg .pred p; setp.ne.b32 p, %37, 0;\n"
                 "wgmma.mma_async.sync.aligned.m64n64k16.f32.bf16.bf16 {%0,%1,%2,%3,%4,%5,%6,%7,%8,%9,%10,%11,%12,%13,%14,%15,%16,%17,%18,%19,%20,%21,%22,%23,%24,%25,%26,%27,%28,%29,%30,%31}, "
                 "{%32,%33,%34,%35}, %36, p, 1, 1, 0;}\n"
                 : F16(d, 0), F16(d, 16) : "r"(a0), "r"(a1), "r"(a2), "r"(a3), "l"(b), "r"(acc));
}
__device__ __forceinline__ void mma_pv(float (&d)[36], uint32_t a0, uint32_t a1, uint32_t a2, uint32_t a3, uint64_t b) {
    asm volatile("wgmma.mma_async.sync.aligned.m64n72k16.f32.bf16.bf16 {%0,%1,%2,%3,%4,%5,%6,%7,%8,%9,%10,%11,%12,%13,%14,%15,%16,%17,%18,%19,%20,%21,%22,%23,%24,%25,%26,%27,%28,%29,%30,%31,%32,%33,%34,%35}, "
                 "{%36,%37,%38,%39}, %40, 1, 1, 1, 1;\n"
                 : F16(d, 0), F16(d, 16), F4(d, 32) : "r"(a0), "r"(a1), "r"(a2), "r"(a3), "l"(b));
}

__device__ __forceinline__ uint32_t load_code(int n, int r, int w) {
    const int tile = 2 * r + w;
    int m, col, row;
    if (n < 16 || n >= 40) {
        const int k = n < 16 ? n : n - 40;
        m = n < 16 ? 0 : 6;
        if (k < 8) { col = 4 * tile + (k >> 1); row = (k & 1) ^ r; }
        else { m++; col = k < 12 ? tile ^ 2 : tile; row = 2 * (tile ^ (k & 1)) + ((k >> 1) & 1); }
    } else if (n < 32) {
        const int k = n - 16;
        m = 2;
        if (k < 4) { col = tile + ((k & 1) ? 8 : 4); row = (k >> 1) ^ r; }
        else { col = tile; row = (k & 1) ^ r; }
    } else if (n < 34) { m = 3; col = tile; row = n - 32; }
    else if (n < 38) { const int k = n - 34; m = 4; col = tile + 4 * (k & 1); row = (k >> 1) ^ r; }
    else { m = 5; col = tile; row = (n & 1) ^ r; }
    return m | (col << 4) | (row << 8);
}

__global__ void __cluster_dims__(2, 1, 1) __launch_bounds__(NTHREADS, 1)
conformer_kernel(const __grid_constant__ Params p) {
    extern __shared__ __align__(1024) unsigned char smem_raw[];
    const uint32_t sb = smem_u32(smem_raw);
    const uint32_t bars = sb + OFF_BARS;
    const int tid = threadIdx.x;
    const int lane = tid & 31;
    const int warp = __shfl_sync(~0u, tid >> 5, 0);
    const int r = blockIdx.x & 1;
    const int pair = blockIdx.x >> 1;
    const int b = pair >> 5, pt = pair & 31;
    const int ah = pt >> 3, qt = (pt & 7) * 2 + r;
    const int abh = b * 4 + ah;

    TG(30);
    TSINIT();
    TS(0);
    const uint32_t P = sb + OFF_P, H = sb + OFF_H;

    if (warp >= 8) {
        asm volatile("setmaxnreg.dec.sync.aligned.u32 48;");
        if (warp >= 12) {
            cluster_arrive();
            cluster_wait();
            const int ut = tid & 127;
            const uint32_t target = ld_epoch() * 64;
            auto reset_done = [&](int k) {
                bar_sync(11, 128);
                if (ut == 0) {
                    asm volatile("red.release.gpu.global.add.u32 [%0], 1;" ::"l"(&g_reset[(2 * b + k) * 32]) : "memory");
#pragma unroll 1
                    for (int i = 0; i < (1 << 20) && ld_relaxed(&g_reset[(2 * b + k) * 32]) != target; i++) __nanosleep(100);
                    asm volatile("fence.acquire.gpu;" ::: "memory");
                    mbar_arrive(bars + (B_RST + k) * 8);
                }
                __syncwarp();
                TS(13 + k);
            };
#pragma unroll
            for (int i = 0; i < 4; i++)
                st_data(g_kvq + 2097152 + (size_t)((b * 4 + 2 * r + (i >> 1)) * 1024 + pt * 32) * 128 + (i & 1) * 2048 + ut * 16, ~0u, ~0u, ~0u, ~0u);
            reset_done(0);
            bar_sync(6, 384);
#pragma unroll
            for (int i = 0; i < 4; i++) {
                st_data(g_o + (size_t)(b * 128 + qt * 8 + 2 * i + (ut >> 6)) * 4096 + ah * 1024 + (ut & 63) * 16, ~0u, ~0u, ~0u, ~0u);
                if (i < 2) st_data(&g_halo[(pair * 4 + 2 * r + i) * 128 + ut], ~0u, ~0u, ~0u, ~0u);
            }
            reset_done(1);
            const int side = warp & 1, wg = (warp >> 1) & 1, np = side ? pt + 1 : pt - 1;
            const unsigned char* src = reinterpret_cast<const unsigned char*>(&g_halo[(((b * 32 + np) * 4 + 2 * r + wg) * 2 + (side ^ 1)) * 64 + lane]);
            const uint32_t dst = H + 16384 + wg * GCH + side * 5120 + (lane & 7) * 128 + (((lane >> 3) ^ (lane & 7)) << 4);
            uint4 hv[2] = {make_uint4(0, 0, 0, 0), make_uint4(0, 0, 0, 0)};
            bar_sync(8 + wg, 192);
            if (np >= 0 && np < 32) {
                spin(HDELAY);
                ld_data<512>(hv, src);
            }
            stsm4(dst, hv[0].x, hv[0].y, hv[0].z, hv[0].w);
            stsm4(dst ^ 64, hv[1].x, hv[1].y, hv[1].z, hv[1].w);
            __syncwarp();
            if (lane == 0) mbar_arrive(bars + (B_HALO + (warp & 3)) * 8);
            TS(4);
        } else if (warp < 10) {
            const int w = warp - 8;
            const uint32_t ring = sb + OFF_RING + w * NSLOT * SLOT;
            const uint32_t full = bars + (B_FULL + w * NSLOT) * 8;
            if (lane == 0) {
#pragma unroll
                for (int i = 0; i < NSLOT; i++) { mbar_init(full + i * 8, 1); mbar_init(full + (B_EMPTY - B_FULL + i) * 8, 4); }
                asm volatile("fence.mbarrier_init.release.cluster;" ::: "memory");
                fence_async_smem();
            }
            __syncwarp();
            cluster_arrive();
            TS(1);
#pragma unroll
            for (int n = 0; n < NSLOT; n++) {
                if (n == 1 || n == 2) bar_sync(12, 64);
                ring_load(ring + n * SLOT, &p.tm[0], 64 * (8 * r + 4 * w + (n >> 1)), 8 * ((n & 1) ^ r), full + n * 8);
            }
            TS(2);
            const uint32_t code = load_code(lane, r, w) | (load_code(lane + 32, r, w) << 16);
            cluster_wait();
            uint32_t s = 0, ph = 0;
            int n = NSLOT;
#pragma unroll 1
            for (int seg = 0; seg < 2; seg++) {
#pragma unroll 1
                for (; n < (seg == 0 ? 22 : NLOADS); n++) {
                    const uint32_t c = __shfl_sync(~0u, code, n) >> (n & 32 ? 16 : 0);
                    const CUtensorMap* tm = &p.tm[c & 15];
                    const uint32_t col = (c & 0xf0) * 4, row = (c & 0xff00) >> 5, dst = ring + s * SLOT;
                    mbar_wait(full + (B_EMPTY - B_FULL) * 8 + s * 8, ph + (((uint32_t)(size_t)tm | col | row | dst) & p.zero));
                    ring_load(dst, tm, col, row, full + s * 8);
                    if (++s == NSLOT) { s = 0; ph ^= 1; }
                }
                if (seg == 1) break;
                const uint32_t epoch = ld_epoch();
                const uint32_t rdy = bars + (B_RDY + 3 * w) * 8, prdy = mapa(rdy, r ^ 1);
                const int odd = r ^ w;
                const uint32_t* flags = g_flag_kv + (abh * 32 + lane) * KFS;
                auto kv_load = [&](uint32_t sl, int isv, int i) {
                    ring_load_both(ring + sl * SLOT, &p.tm[8], (isv * 64 + abh * 8 + 2 * i + w) * 128, full + sl * 8);
                };
#pragma unroll 1
                for (int i = 0; i < 2; i++) {
                    if (lane < 3 + i) {
                        const uint32_t sl = i ? lane : lane + 2;
                        mbar_wait(full + (B_EMPTY - B_FULL + sl) * 8, i ^ 1);
                        mbar_arrive_tx(full + sl * 8, (i || lane == 2) ? SLOT : 0);
                    }
                    __syncwarp();
                }
                if (lane == 0) mbar_arrive_peer(prdy);
                bar_sync(14, 96);
                spin(KDELAY);
                mbar_wait(rdy, 0);
                flag_wait(flags, epoch, (lane >> 2) == 2 * odd + w);
                TSW(5 + 2 * odd);
                if (!odd) { kv_load(4, 0, 0); bar_arrive(12, 64); }
                else bar_sync(12, 64);
                spin(w ? KD3 : KD2);
                kv_load(odd ^ 1, odd ^ 1, odd);
                flag_wait(flags, epoch, (lane >> 2) == 2 * odd + w + 4);
                mbar_wait(full + (odd ^ 1) * 8, 1);
                kv_load(2 + odd, odd, 2 - odd);
#pragma unroll 1
                for (int i = 0; i < 3; i++) {
                    const uint32_t sl = i ? i - 1 : 4, bo = i == 2 ? 16 : 8;
                    mbar_wait(full + (B_EMPTY - B_FULL + sl) * 8, i != 0);
                    if (lane == 0) mbar_arrive_tx(full + sl * 8, SLOT);
                    if ((i & 1) != odd) {
                        mbar_wait(rdy + bo, 0);
                        kv_load(sl, i != 0, 2 + odd);
                    } else if (lane == 0) mbar_arrive_peer(prdy + bo);
                    __syncwarp();
                }
                n = 32; s = 2; ph = 1;
            }
        } else if (warp == 10) {
            if (lane == 0) {
#pragma unroll
                for (int i = B_XA; i < NBARS; i++) mbar_init(bars + i * 8, 1);
#pragma unroll
                for (int i = B_XA; i <= B_SR; i++) mbar_arrive_tx(bars + i * 8, i < B_XB ? 512 : ((i >= B_INB && i < B_SR) ? 4096 : 8192));
                asm volatile("fence.mbarrier_init.release.cluster;" ::: "memory");
                fence_async_smem();
            }
            __syncwarp();
            cluster_arrive();
            cluster_wait();
        } else {
            const uint32_t kb = (lane < 2 || lane > 5) ? 4096 : (lane == 2 ? 3072 : (lane == 4 ? 2048 : 1024));
            const char* pf = p.w[lane & 7] + blockIdx.x * kb;
            cluster_arrive();
            cluster_wait();
            if (lane < 2) prefetch_l2(pf, kb);
            mbar_wait(bars + B_XA * 8, 0);
            if (lane == 2) prefetch_l2(pf, kb);
            if (lane >= 1 && lane < 9) asm volatile("prefetch.tensormap [%0];" ::"l"(&p.tm[lane]) : "memory");
            mbar_wait(bars + (B_FULL + 1) * 8, 1);
            if (lane > 2 && lane < 8) prefetch_l2(pf, kb);
            if (lane == 8 && blockIdx.x < 15) prefetch_l2(p.dw + blockIdx.x * 256, 512);
            const uint32_t epoch = ld_epoch();
            bar_sync(4, 288);
            if (lane < 16) flag_set(&g_flag_kv[((b * 4 + 2 * r + (lane >> 3)) * 32 + pt) * KFS + (lane & 7)], epoch);
            __syncwarp();
            bar_arrive(14, 96);
            TSW(8);
        }
        TSDUMP();
        return;
    }

    const int w = warp >> 2, wq = warp & 3;
    const int tile = 2 * r + w;
    const int wt = tid & 127;
    const int c4 = lane & 3;
    const int trow = pt * 32 + 8 * wq;
    uint32_t xr[8];
    {
        const uint32_t* xp = reinterpret_cast<const uint32_t*>(p.x + (size_t)(b * T_ + trow + (lane >> 2)) * 256 + tile * 64) + c4;
#pragma unroll
        for (int j = 0; j < 8; j++) xr[j] = trow < T_ ? __ldg(xp + 4 * j) : 0u;
    }
    cluster_arrive();
    asm volatile("setmaxnreg.inc.sync.aligned.u32 208;");
    const uint32_t rbase = sb + OFF_RING + w * NSLOT * SLOT, fbar = bars + (B_FULL + w * NSLOT) * 8;
    const uint32_t rdesc = desc_lo(rbase);
    auto acq = [&](int n) { mbar_wait(fbar + (n % NSLOT) * 8, (n / NSLOT) & 1); };
    auto rel = [&](int n) { if (lane == 0) mbar_arrive(fbar + (B_EMPTY - B_FULL + n % NSLOT) * 8); };
    const uint32_t foff = (lane & 7) * 128 + (((lane >> 3) ^ (lane & 7)) << 4);
    float v[16];
#pragma unroll
    for (int j = 0; j < 8; j++) { v[2 * j] = blo(xr[j]); v[2 * j + 1] = bhi(xr[j]); }
    const uint32_t xown = __shfl_sync(~0u, P + wt * 16 + tile * 4096, lane), xrem = __shfl_sync(~0u, P + wt * 16 + (r ^ 1) * 8192, lane);
    const uint32_t sbuf = __shfl_sync(~0u, sb + OFF_MISC + 1024 + (8 * wq + (lane >> 2)) * 32, lane);
    const uint32_t sown = __shfl_sync(~0u, sbuf + tile * 8, lane);
    const uint32_t peer = __shfl_sync(~0u, mapa(sb, r ^ 1) - sb, lane);
    const uint32_t hbuf = __shfl_sync(~0u, H + w * 4096 + wt * 16, lane);
    const uint32_t meta = __shfl_sync(~0u, 0xEEEE4444u + p.zero, lane);
    cluster_wait();
    TS(56);
    float mean, msq;
    const int mir = wq < 2 ? 7 : 0;
    uint32_t dwr[15] = {};

#pragma unroll UNR
    for (int ph = 0; ph < 5; ph++) {
        uint4 o0, o1;
        {
            const uint32_t xa = bars + (B_XA + ph) * 8;
#pragma unroll
            for (int j = 0; j < 8; j++) xr[j] = pack2(v[2 * j], v[2 * j + 1]);
            float s, q;
            row_sums<8>(xr, lane, s, q);
            if (c4 == (lane >> 3)) st_async2f(sown + peer, s, q, xa + peer);
            if (c4 == (lane >> 3)) sts64f(sown, s, q);
            if (ph < 4) {
                sts128(xown, xr[0], xr[1], xr[2], xr[3]);
                sts128(xown + 2048, xr[4], xr[5], xr[6], xr[7]);
            }
            bar_sync(10, 256);
            if (ph < 4) {
                o0 = lds128(xown ^ 4096); o1 = lds128((xown ^ 4096) + 2048);
                st_async4(xown + peer, xr[0], xr[1], xr[2], xr[3], xa + (B_XB - B_XA) * 8 + peer);
                st_async4(xown + peer + 2048, xr[4], xr[5], xr[6], xr[7], xa + (B_XB - B_XA) * 8 + peer);
            }
            TS(57 + ph);
            if (ph == 0 || ph == 3) acq(0);
            if (ph == 1) acq(16);
            mbar_wait(xa, 0);
            const float4 u0 = lds128f(sbuf), u1 = lds128f(sbuf + 16);
            mean = ((u0.x + u0.z) + (u1.x + u1.z)) * (1.f / 256.f);
            msq = ((u0.y + u0.w) + (u1.y + u1.w)) * (1.f / 256.f);
        }
        if (ph == 4) break;
        uint32_t a[32];
        const uint32_t mean2 = pack2(mean, mean);
        auto centre = [&](int i, const uint4& u) {
            a[i] = hsub2(u.x, mean2); a[i + 1] = hsub2(u.y, mean2); a[i + 2] = hsub2(u.z, mean2); a[i + 3] = hsub2(u.w, mean2);
        };
#pragma unroll
        for (int j = 0; j < 8; j++) a[j] = hsub2(xr[j], mean2);
        centre(8, o0); centre(12, o1);
        const float rstd = rsq(fmaxf(fmaf(-mean, mean, msq), 0.f) + 1e-5f);
        auto gather_peer = [&]() {
            mbar_wait(bars + (B_XB + ph) * 8, 0);
#pragma unroll
            for (int i = 0; i < 4; i++) centre(16 + 4 * i, lds128(xrem + i * 2048));
        };
        auto sp = [&](float (&d)[32], int n, const uint32_t* af, int flip, int acc) {
            const uint32_t lo = rdesc + p.zero * (ph * 64 + n + 1) + (n % NSLOT) * (SLOT >> 4);
            const uint64_t b0 = mkdesc(lo + flip * 512), b1 = mkdesc(lo + (flip ^ 1) * 512);
            wg_fence();
            mma_sp(d, af, b0, meta, acc);
            mma_sp(d, af + 4, b0 + 256, meta, 1);
            mma_sp(d, af + 8, b1, meta, 1);
            mma_sp(d, af + 12, b1 + 256, meta, 1);
            wg_commit();
        };
        float d0[32], d1[32];

        if (ph == 0 || ph == 3) {
            uint32_t h[32], ho[32];
            const float rs = 0.5f * rstd;
            const uint32_t inb = bars + (B_INB + (ph & 2) + w) * 8;
            bool ready = true;
            auto step = [&](float (&d)[32], int n, const uint32_t* af, int flip, int acc, auto work) {
                if (!ready) acq(n);
                if (((TURN >> n) & 1) && w == 1) bar_sync(7, 256);
                sp(d, n, af, flip, acc);
                if (n > 0 && ((TURN >> (n - 1)) & 1) && w == 0) bar_arrive(7, 256);
                if (n < 15) ready = mbar_test(fbar + ((n + 1) % NSLOT) * 8, ((n + 1) / NSLOT) & 1);
                wg_wait<1>();
                if (n > 0 && !((EAGER >> (n - 1)) & 1)) rel(n - 1);
                const uint32_t tie = work() & p.zero;
                if ((EAGER >> n) & 1) {
                    if (p.zero < n + ph + 1) wg_wait<0>();
                    if (lane == 0) mbar_arrive(fbar + (B_EMPTY - B_FULL + n % NSLOT) * 8 + tie);
                }
            };
            auto none = []() { return 0u; };
            auto fetch = [&](int i) {
                bar_sync(10, 256);
                const uint4 u0 = lds128((hbuf ^ 4096) + (i & 1) * 8192), u1 = lds128((hbuf ^ 4096) + (i & 1) * 8192 + 2048);
                ho[8 * i] = u0.x; ho[8 * i + 1] = u0.y; ho[8 * i + 2] = u0.z; ho[8 * i + 3] = u0.w;
                ho[8 * i + 4] = u1.x; ho[8 * i + 5] = u1.y; ho[8 * i + 6] = u1.z; ho[8 * i + 7] = u1.w;
                return u0.x | u1.x;
            };
            auto act = [&](float (&d)[32], int i) {
                if (i > 0) fetch(i - 1);
                pin(d);
#pragma unroll
                for (int j = 0; j < 8; j++) {
                    const float u0 = (d[4 * j] + d[4 * j + 2]) * rs, u1 = (d[4 * j + 1] + d[4 * j + 3]) * rs;
                    h[8 * i + j] = pack2(fmaf(u0, tanh_fast(u0), u0), fmaf(u1, tanh_fast(u1), u1));
                }
                sts128(hbuf + (i & 1) * 8192, h[8 * i], h[8 * i + 1], h[8 * i + 2], h[8 * i + 3]);
                sts128(hbuf + (i & 1) * 8192 + 2048, h[8 * i + 4], h[8 * i + 5], h[8 * i + 6], h[8 * i + 7]);
                return 0u;
            };
            TS(1 + (ph & 2) * 10);
            step(d0, 0, a, w, 0, [&]() { gather_peer(); return 0u; });
            TS(32);
            step(d0, 1, a + 16, 0, 1, none);
            step(d1, 2, a, w, 0, [&]() { return act(d0, 0); });
            step(d1, 3, a + 16, 0, 1, none);
            step(d0, 4, a, w, 0, [&]() { return act(d1, 1); });
            TS(33);
            step(d0, 5, a + 16, 0, 1, none);
            step(d1, 6, a, w, 0, [&]() { return act(d0, 2); });
            step(d1, 7, a + 16, 0, 1, none);
            step(d0, 8, h, 0, 0, [&]() { act(d1, 3); return fetch(3); });
            TS(2 + (ph & 2) * 10);
            step(d0, 9, ho, 0, 1, none);
            step(d0, 10, h + 16, 0, 1, none);
            step(d0, 11, ho + 16, 0, 1, none);
            uint32_t pk[8];
            auto pack_out = [&]() {
                pin(d0);
#pragma unroll
                for (int j = 0; j < 8; j++) pk[j] = pack2(d0[4 * j] + d0[4 * j + 2], d0[4 * j + 1] + d0[4 * j + 3]);
            };
            auto send = [&](int i) { st_async4(hbuf + 16384 + i * 2048 + peer, pk[4 * i], pk[4 * i + 1], pk[4 * i + 2], pk[4 * i + 3], inb + peer); };
            step(d1, 12, h, 0, 0, [&]() { pack_out(); if (SND != 1) send(0); if (SND == 0) send(1); return 0u; });
            TS(34);
            step(d1, 13, ho, 0, 1, [&]() { if (SND == 1) send(0); if (SND) send(1); return 0u; });
            step(d1, 14, h + 16, 0, 1, none);
            step(d1, 15, ho + 16, 0, 1, none);
            mbar_wait(inb, 0);
#pragma unroll
            for (int i = 0; i < 2; i++) {
                const uint4 u = lds128(hbuf + 16384 + i * 2048);
                const uint32_t p0[4] = {u.x, u.y, u.z, u.w};
#pragma unroll
                for (int j = 0; j < 4; j++) {
                    v[8 * i + 2 * j] = fmaf(0.5f, blo(p0[j]), blo(xr[4 * i + j]));
                    v[8 * i + 2 * j + 1] = fmaf(0.5f, bhi(p0[j]), bhi(xr[4 * i + j]));
                }
            }
            wg_wait<0>();
            pin(d1);
            rel(15);
            TS(3 + (ph & 2) * 10);
#pragma unroll
            for (int j = 0; j < 8; j++) {
                v[2 * j] = fmaf(0.5f, d1[4 * j] + d1[4 * j + 2], v[2 * j]);
                v[2 * j + 1] = fmaf(0.5f, d1[4 * j + 1] + d1[4 * j + 3], v[2 * j + 1]);
            }
#pragma unroll
            for (int i = 0; i < 15; i++) dwr[i] = 0;
            continue;
        }

        auto residual = [&](int n) {
            wg_wait<1>();
            rel(n);
            wg_wait<0>();
            pin(d0);
            rel(n + 1);
#pragma unroll
            for (int j = 0; j < 8; j++) {
                v[2 * j] = d0[4 * j] + d0[4 * j + 2] + blo(xr[j]);
                v[2 * j + 1] = d0[4 * j + 1] + d0[4 * j + 3] + bhi(xr[j]);
            }
        };

        if (ph == 2) {
            TS(39);
            sp(d0, 34, a, w, 0);
            acq(35);
            sp(d1, 35, a, w, 0);
            acq(36); acq(37);
            gather_peer();
            sp(d0, 36, a + 16, 0, 1);
            sp(d1, 37, a + 16, 0, 1);
            wg_wait<2>();
            rel(34);
            if (!(LATE & 1)) rel(35);
            acq(38);
            const float rs = trow < T_ ? 0.5f * rstd : 0.f;
            wg_wait<0>();
            pin(d0); pin(d1);
            if (!(LATE & 2)) { rel(36); rel(37); }
            TS(18);
            uint32_t pk[8];
#pragma unroll
            for (int j = 0; j < 8; j++) {
                const float u0 = (d0[4 * j] + d0[4 * j + 2]) * rs, u1 = (d0[4 * j + 1] + d0[4 * j + 3]) * rs;
                const float t0 = tanh_fast((d1[4 * j] + d1[4 * j + 2]) * rs), t1 = tanh_fast((d1[4 * j + 1] + d1[4 * j + 3]) * rs);
                pk[j] = pack2(fmaf(u0, t0, u0), fmaf(u1, t1, u1));
            }
            if (wq == 0 || wq == 3) {
                uint4* hp = &g_halo[((pair * 4 + tile) * 2 + (wq & 1)) * 64 + lane];
                st_data(hp, pk[0], pk[1], pk[2], pk[3]);
                st_data(hp + 32, pk[4], pk[5], pk[6], pk[7]);
            }
            const uint32_t gs = H + 16384 + w * GCH + wq * 1024;
            stsm4(gs + 1024 + foff, pk[0], pk[1], pk[2], pk[3]);
            stsm4(gs + 1024 + (foff ^ 64), pk[4], pk[5], pk[6], pk[7]);
            bar_sync(8 + w, 192);
            TS(26);
            uint32_t ca[8], cb[8];
            const int e = (wq & 1) * 4;
            const uint32_t lo = ((mir ^ e) * 144) ^ (lane * 4);
            const int dir = mir ? -1024 : 1024;
            const uint32_t gb = H + 16384 + w * GCH + (mir ? 3072 : 2048) + lo, sown_ = H + tile * HCH, so = sown_ + (mir ? 1024 : 2048) + lo;
            auto finish = [&](int i) {
                const uint32_t c = hadd2(ca[i], cb[i]);
                const float h0 = blo(c), h1 = bhi(c);
                sts32((so + (i >> 2) * dir) ^ ((i & 3) * 144), pack2(fmaf(h0, tanh_fast(h0), h0), fmaf(h1, tanh_fast(h1), h1)));
            };
#pragma unroll
            for (int k = 0; k < 26; k++) {
                if (k == 19) {
#pragma unroll
                    for (int i = 0; i < 4; i++) finish(i);
                    fence_async_smem();
                    bar_sync(2 + w, 128);
                    if (wq == 0) peer_copy(mapa(sown_ + 1024, r ^ 1), sown_ + 1024, 2048, mapa(bars + B_SR * 8, r ^ 1));
                    mbar_wait(bars + (B_HALO + 2 * w + (wq >> 1)) * 8, 0);
                    if (LATE & 1) rel(35);
                    if (LATE & 2) { rel(36); rel(37); }
                    TS(27);
                }
                const uint32_t g = lds32((gb + (((k + 1) & 4) ? ((k + 1) >> 3) + (wq & 1) : ((k + 1) >> 3)) * dir) ^ (((k + 1) & 7) * 144));
#pragma unroll
                for (int i = 0; i < 8; i++) {
                    const int tap = k - (i & 3) - 2 * (i & 4);
                    if (tap == 0) ca[i] = hmul2(g, dwr[0]);
                    else if (tap > 0 && tap < 8) ca[i] = hfma2(g, dwr[tap], ca[i]);
                    else if (tap == 8) cb[i] = hmul2(g, dwr[8]);
                    else if (tap > 8 && tap < 15) cb[i] = hfma2(g, dwr[tap], cb[i]);
                }
            }
#pragma unroll
            for (int i = 4; i < 8; i++) finish(i);
            fence_async_smem();
            bar_sync(12 + (warp >> 1), 64);
            if (wq == 0 || wq == 3) peer_copy(mapa(sown_ + wq * 1024, r ^ 1), sown_ + wq * 1024, 1024, mapa(bars + B_SR * 8, r ^ 1));
            bar_sync(10, 256);
            TS(19);
            auto frags = [&](int i, int half) {
                const uint32_t src = H + 2 * half * HCH + wq * 1024;
#pragma unroll
                for (int k = 0; k < 4; k++) ldsm4(src + (k >> 1) * HCH + (foff ^ ((k & 1) * 64)), a[i + 4 * k], a[i + 4 * k + 1], a[i + 4 * k + 2], a[i + 4 * k + 3]);
            };
            frags(0, r);
            sp(d0, 38, a, 0, 0);
            acq(39);
            mbar_wait(bars + B_SR * 8, 0);
            frags(16, r ^ 1);
            sp(d0, 39, a + 16, 0, 1);
            residual(38);
            TS(20);
            continue;
        }

        {
            TS(11);
            const uint32_t stg = H + warp * 2048;
            unsigned char* g = g_kvq + (size_t)((b * 4 + tile) * 1024 + trow) * 128 + lane * 16;
            auto put = [&](float (&d)[32], int i) {
                pin(d);
                uint32_t pk[8];
#pragma unroll
                for (int j = 0; j < 8; j++) pk[j] = pack2((d[4 * j] + d[4 * j + 2]) * rstd, (d[4 * j + 1] + d[4 * j + 3]) * rstd);
                if (i == 2) {
                    st_data(g + 2097152, pk[0], pk[1], pk[2], pk[3]);
                    st_data(g + 2097152 + 512, pk[4], pk[5], pk[6], pk[7]);
                    return;
                }
                stsm4(stg + i * 1024 + foff, pk[0], pk[1], pk[2], pk[3]);
                stsm4(stg + i * 1024 + (foff ^ 64), pk[4], pk[5], pk[6], pk[7]);
                __syncwarp();
                const uint4 u0 = lds128(stg + i * 1024 + lane * 16), u1 = lds128(stg + i * 1024 + 512 + lane * 16);
                stg128(g + i * 1048576, u0); stg128(g + i * 1048576 + 512, u1);
            };
            sp(d0, 16, a, w, 0);
            acq(17);
            sp(d1, 17, a, w, 0);
            gather_peer();
            acq(18);
            sp(d0, 18, a + 16, 0, 1);
            wg_wait<1>();
            rel(16); rel(17);
            acq(19);
            sp(d1, 19, a + 16, 0, 1);
            wg_wait<1>();
            rel(18);
            put(d0, 0);
            wg_wait<0>();
            rel(19);
            TS(37);
            put(d1, 1);
            bar_arrive(4, 288);
            TS(38);
            acq(20);
            sp(d0, 20, a, w, 0);
            acq(21);
            sp(d0, 21, a + 16, 0, 1);
            acq(22); acq(23);
            rel(22); rel(23);
            mbar_wait(bars + B_RST * 8, 0);
            wg_wait<0>();
            rel(20); rel(21);
            put(d0, 2);
            TS(12);
        }

        {
            constexpr float CS = 0.125f * 1.4426950408889634f;
            float sa[32], sb2[32], o[36];
            uint32_t pa[16], pb[16], q[16];
            float n0 = INFINITY, n1 = INFINITY;
            zero(o); zero(pa); zero(pb); zero(sb2);
            const uint32_t ones = sb + OFF_MISC + 2048;
            { const uint32_t c = w ? 0u : 0x3F803F80u; sts128(ones + tid * 16, c, c, c, c); }
            fence_async_smem();
            bar_sync(10, 256);
            const uint32_t vdesc = rdesc + ((((ones - rbase) >> 4) - 1) << 16);
            auto qk_issue = [&](float (&s)[32], uint32_t lo) {
                const uint64_t kd = mkdesc(lo);
                wg_fence();
#pragma unroll
                for (int k = 0; k < 4; k++) mma_qk(s, q[4 * k], q[4 * k + 1], q[4 * k + 2], q[4 * k + 3], kd + 2 * k, k != 0);
                wg_commit();
            };
            auto both_issue = [&](float (&s)[32], uint32_t klo, uint32_t (&pp)[16], uint32_t vlo) {
                const uint64_t kd = mkdesc(klo), vd = mkdesc(vlo);
                wg_fence();
#pragma unroll
                for (int k = 0; k < 4; k++) {
                    mma_pv(o, pp[4 * k], pp[4 * k + 1], pp[4 * k + 2], pp[4 * k + 3], vd - k * (128 * 65535));
                    mma_qk(s, q[4 * k], q[4 * k + 1], q[4 * k + 2], q[4 * k + 3], kd + 2 * k, k != 0);
                }
                wg_commit();
            };
            auto new_max = [&](float (&s)[32], int nj, float& x0, float& x1) {
                x0 = s[0]; x1 = s[2];
#pragma unroll
                for (int j = 0; j < nj; j++) {
                    x0 = fmaxf(x0, fmaxf(s[4 * j], s[4 * j + 1]));
                    x1 = fmaxf(x1, fmaxf(s[4 * j + 2], s[4 * j + 3]));
                }
                x0 = fmaxf(x0, __shfl_xor_sync(~0u, x0, 1)); x1 = fmaxf(x1, __shfl_xor_sync(~0u, x1, 1));
                x0 = fmaxf(x0, __shfl_xor_sync(~0u, x0, 2)); x1 = fmaxf(x1, __shfl_xor_sync(~0u, x1, 2));
                x0 = fminf(n0, fmaf(x0, -CS, -20.f)); x1 = fminf(n1, fmaf(x1, -CS, -20.f));
            };
            auto probs = [&](float (&s)[32], uint32_t (&pp)[16], bool ready, bool tail, auto wait) {
                uint32_t any = 0;
#pragma unroll
                for (int i = 0; i < 16; i++) {
                    pp[i] = pack2(ex2(fmaf(s[2 * i], CS, (i & 1) ? n1 : n0)), ex2(fmaf(s[2 * i + 1], CS, (i & 1) ? n1 : n0)));
                    any |= pp[i];
                }
                wg_wait<0>();
                pin(sa); pin(sb2); pin(o); pin(pa); pin(pb);
                if (__any_sync(~0u, (any & 0x40004000u) || !ready)) {
                    wait();
                    if (__any_sync(~0u, any & 0x40004000u)) {
                        if (tail) {
#pragma unroll
                            for (int i = 20; i < 32; i++) s[i] = -INFINITY;
                        }
                        float x0, x1;
                        new_max(s, 8, x0, x1);
                        const float sc0 = ex2(x0 - n0), sc1 = ex2(x1 - n1);
                        n0 = x0; n1 = x1;
#pragma unroll
                        for (int j = 0; j < 9; j++) { o[4 * j] *= sc0; o[4 * j + 1] *= sc0; o[4 * j + 2] *= sc1; o[4 * j + 3] *= sc1; }
#pragma unroll
                        for (int i = 0; i < 16; i++)
                            pp[i] = pack2(ex2(fmaf(s[2 * i], CS, (i & 1) ? n1 : n0)), ex2(fmaf(s[2 * i + 1], CS, (i & 1) ? n1 : n0)));
                    }
                }
            };
            {
                uint4 u[4];
                const unsigned char* src = g_kvq + 2097152 + (size_t)(abh * 1024 + qt * 64 + wq * 16) * 128 + lane * 16;
                spin(QGATE);
                ld_data<512>(u, src);
#pragma unroll
                for (int k = 0; k < 2; k++) {
                    q[8 * k] = u[k].x; q[8 * k + 1] = u[k + 2].x; q[8 * k + 2] = u[k].y; q[8 * k + 3] = u[k + 2].y;
                    q[8 * k + 4] = u[k].z; q[8 * k + 5] = u[k + 2].z; q[8 * k + 6] = u[k].w; q[8 * k + 7] = u[k + 2].w;
                }
                pin(q);
            }
            TS(40);
            acq(24);
            TS(13);
            qk_issue(sa, rdesc + (24 % NSLOT) * (SLOT >> 4));
            wg_wait<0>();
            pin(sa);
            {
                float x0, x1;
                new_max(sa, NJ0, x0, x1);
                n0 = x0; n1 = x1;
            }
            bar_arrive(6, 384);
            uint32_t vd = vdesc - (SLOT >> 4) * 65535u, kd = rdesc, vb = fbar + 8, kb = fbar;
            uint32_t vlast = vdesc - 4 * (SLOT >> 4) * 65535u, klast = rdesc + 4 * (SLOT >> 4) + 512;
            uint32_t kprev = fbar + 32, vprev = bars + (B_SINK - (B_EMPTY - B_FULL)) * 8;
#pragma unroll 1
            for (int it = 0; it < 4; it++) {
                both_issue(sb2, klast, pb, vlast);
                probs(sa, pa, mbar_test(vb, it < 2) & mbar_test(kb, it < 3), false, [&]() { mbar_wait(vb, it < 2); mbar_wait(kb, it < 3); });
                TS(41 + it * 4);
                if (lane == 0) mbar_arrive(kprev + (B_EMPTY - B_FULL) * 8);
                if (lane == 0) mbar_arrive(vprev + (B_EMPTY - B_FULL) * 8);
                both_issue(sa, kd, pa, vd);
                const int dv = it == 0 ? 2 : (it == 1 ? -3 : 1);
                kprev = kb; vprev = vb; vlast = vd - 512 * 65535u; klast = kd + 512;
                vd -= dv * (SLOT >> 4) * 65535u; vb += dv * 8;
                kd += (it == 2 ? -3 : 2) * (SLOT >> 4); kb = it == 2 ? vb : kb + 16;
                probs(sb2, pb, true, it == 3 && w == 1, []() {});
                TS(43 + it * 4);
            }
            wg_fence();
#pragma unroll
            for (int k = 0; k < 4; k++)
                mma_pv(o, pb[4 * k], pb[4 * k + 1], pb[4 * k + 2], pb[4 * k + 3], mkdesc(vlast - k * (128 * 65535) + (k > 1 ? w * ((k - 1) << 22) : 0)));
            wg_commit();
            const int row = wq * 16 + (lane >> 2);
            const uint32_t ml = sb + OFF_MISC;
            mbar_wait(bars + (B_RST + 1) * 8, 0);
            wg_wait<0>();
            pin(o); pin(pb); pin(sa); pin(sb2);
            if (!(LATE & 4)) rel(31);
            const float l0 = o[32], l1 = o[34];
            if (c4 == 0) { sts64f(ml + w * 512 + row * 8, n0, l0); sts64f(ml + w * 512 + row * 8 + 64, n1, l1); }
            TS(14);
            float mine[16];
#pragma unroll
            for (int j = 0; j < 4; j++) {
                if (w == 0) sts128f(H + j * 2048 + wt * 16, o[16 + 4 * j], o[17 + 4 * j], o[18 + 4 * j], o[19 + 4 * j]);
                else sts128f(H + 8192 + j * 2048 + wt * 16, o[4 * j], o[4 * j + 1], o[4 * j + 2], o[4 * j + 3]);
            }
#pragma unroll
            for (int i = 0; i < 16; i++) mine[i] = w == 0 ? o[i] : o[16 + i];
            bar_sync(10, 256);
            const float2 u0 = lds64f(ml + (w ^ 1) * 512 + row * 8), u1 = lds64f(ml + (w ^ 1) * 512 + row * 8 + 64);
            const float x0 = fminf(n0, u0.x), x1 = fminf(n1, u1.x);
            float a0 = ex2(x0 - n0), b0 = ex2(x0 - u0.x), a1 = ex2(x1 - n1), b1 = ex2(x1 - u1.x);
            const float i0 = __fdividef(1.f, fmaf(a0, l0, b0 * u0.y)), i1 = __fdividef(1.f, fmaf(a1, l1, b1 * u1.y));
            a0 *= i0; b0 *= i0; a1 *= i1; b1 *= i1;
            uint32_t pk[8];
#pragma unroll
            for (int j = 0; j < 4; j++) {
                const float4 v = lds128f(H + (w ^ 1) * 8192 + j * 2048 + wt * 16);
                pk[2 * j] = pack2(fmaf(a0, mine[4 * j], b0 * v.x), fmaf(a0, mine[4 * j + 1], b0 * v.y));
                pk[2 * j + 1] = pack2(fmaf(a1, mine[4 * j + 2], b1 * v.z), fmaf(a1, mine[4 * j + 3], b1 * v.w));
            }
            unsigned char* dst = g_o + (size_t)(b * 128 + qt * 8 + 2 * wq) * 4096 + ah * 1024 + w * 512 + lane * 16;
            st_data(dst, pk[0], pk[2], pk[4], pk[6]);
            st_data(dst + 4096, pk[1], pk[3], pk[5], pk[7]);
            if (tid == 0) asm volatile("red.relaxed.gpu.global.add.u32 [%0], 1;" ::"l"(&g_epoch[blockIdx.x * FS]) : "memory");
            TS(15);
        }

        {
            const uint32_t* dp = reinterpret_cast<const uint32_t*>(p.dw + (mir ? 14 * 256 : 0) + tile * 64) + lane;
#pragma unroll
            for (int i = 0; i < 15; i++) asm volatile("ld.global.nc.b32 %0, [%1];" : "=r"(dwr[i]) : "l"(dp + i * (mir ? -128 : 128)));
            acq(32); acq(33); acq(34);
            uint4 u[8];
            ld_data<512>(u, g_o + (size_t)(b * 128 + pt * 4 + wq) * 4096 + lane * 16);
#pragma unroll
            for (int i = 0; i < 8; i++) { a[4 * i] = u[i].x; a[4 * i + 1] = u[i].y; a[4 * i + 2] = u[i].z; a[4 * i + 3] = u[i].w; }
            if (LATE & 4) rel(31);
            TS(16);
            sp(d0, 32, a, 0, 0);
            sp(d0, 33, a + 16, 0, 1);
#pragma unroll
            for (int i = 0; i < 15; i++) dwr[i] = hmul2(dwr[i], 0x3F003F00u);
            residual(32);
            TS(17);
        }
    }

    cluster_arrive();
    TS(24);
    {
        const float rstd = rsq(fmaxf(fmaf(-mean, mean, msq), 0.f) + 1e-5f), nb = -mean * rstd;
#pragma unroll
        for (int j = 0; j < 8; j++) xr[j] = pack2(fmaf(v[2 * j], rstd, nb), fmaf(v[2 * j + 1], rstd, nb));
        const uint32_t stg = P + 16384 + warp * 1024;
        stsm4(stg + foff, xr[0], xr[1], xr[2], xr[3]);
        stsm4(stg + (foff ^ 64), xr[4], xr[5], xr[6], xr[7]);
        __syncwarp();
        const uint32_t src = stg + (lane >> 3) * 128 + (((lane & 7) ^ (lane >> 3)) << 4);
        const uint4 u0 = lds128(src), u1 = lds128((src + 512) ^ 64);
        __nv_bfloat16* dst = p.out + (size_t)(b * T_ + trow + (lane >> 3)) * 256 + tile * 64 + (lane & 7) * 8;
        if (trow < T_) { stg128(dst, u0); stg128(dst + 4 * 256, u1); }
    }
    TS(25);
    TG(31);
    TSDUMP();
    cluster_wait();
}

typedef CUresult (*EncodeFn)(CUtensorMap*, CUtensorMapDataType, cuuint32_t, void*, const cuuint64_t*, const cuuint64_t*,
                             const cuuint32_t*, const cuuint32_t*, CUtensorMapInterleave, CUtensorMapSwizzle,
                             CUtensorMapL2promotion, CUtensorMapFloatOOBfill);

}

extern "C" void kernel_launch(void* const* d_in, const int* in_sizes, int n_in, void* d_out, int out_size) {
    static EncodeFn encode = nullptr;
    if (!encode) {
        void* fn = nullptr;
        cudaDriverEntryPointQueryResult qr;
        cudaGetDriverEntryPoint("cuTensorMapEncodeTiled", &fn, cudaEnableDefault, &qr);
        encode = (EncodeFn)fn;
        cudaFuncSetAttribute(conformer_kernel, cudaFuncAttributeMaxDynamicSharedMemorySize, SMEM_LAUNCH);
    }
    Params p;
    const cuuint32_t ones[5] = {1, 1, 1, 1, 1};
    const int idx[8] = {1, 2, 3, 4, 5, 7, 8, 9};
    const int rows[8] = {256, 1024, 256, 256, 256, 256, 256, 1024};
    const int cols[8] = {1024, 256, 768, 256, 512, 256, 1024, 256};
    for (int i = 0; i < 8; i++) {
        const cuuint64_t pitch = (cuuint64_t)cols[i] * 2;
        const cuuint64_t dims[5] = {(cuuint64_t)cols[i], 2, 2, 4, (cuuint64_t)rows[i] / 16};
        const cuuint64_t strides[4] = {pitch, pitch * 8, pitch * 2, pitch * 16};
        const cuuint32_t box[5] = {64, 2, 2, 4, 8};
        encode(&p.tm[i], CU_TENSOR_MAP_DATA_TYPE_BFLOAT16, 5, d_in[idx[i]], dims, strides, box, ones, CU_TENSOR_MAP_INTERLEAVE_NONE,
               CU_TENSOR_MAP_SWIZZLE_128B, CU_TENSOR_MAP_L2_PROMOTION_L2_128B, CU_TENSOR_MAP_FLOAT_OOB_FILL_NONE);
        p.w[i] = (const char*)d_in[idx[i]];
    }
    {
        void* kv = nullptr;
        cudaGetSymbolAddress(&kv, g_kvq);
        const cuuint64_t dims[2] = {64, 16384};
        const cuuint64_t strides[1] = {128};
        const cuuint32_t box[2] = {64, 128};
        encode(&p.tm[8], CU_TENSOR_MAP_DATA_TYPE_BFLOAT16, 2, kv, dims, strides, box, ones, CU_TENSOR_MAP_INTERLEAVE_NONE,
               CU_TENSOR_MAP_SWIZZLE_NONE, CU_TENSOR_MAP_L2_PROMOTION_L2_128B, CU_TENSOR_MAP_FLOAT_OOB_FILL_NONE);
    }
    p.x = (const __nv_bfloat16*)d_in[0];
    p.dw = (const __nv_bfloat16*)d_in[6];
    p.out = (__nv_bfloat16*)d_out;
    p.zero = 0;
    conformer_kernel<<<NCTA, NTHREADS, SMEM_LAUNCH>>>(p);
}
```

```cpp
#include <cuda_runtime.h>
#include <cuda_bf16.h>
#include <cuda.h>
#include <stdint.h>

namespace {

constexpr int T_ = 1000;
constexpr int NCTA = 128;
constexpr int NTHREADS = 512;
constexpr int NSLOT = 5;
constexpr int SLOT = 16384;
constexpr int NLOADS = 56;

constexpr uint32_t OFF_RING = 0;
constexpr uint32_t OFF_P = 163840;
constexpr uint32_t OFF_H = 188416;
constexpr uint32_t OFF_MISC = 221184;
constexpr uint32_t OFF_BARS = 229888;
constexpr uint32_t SMEM_BYTES = 230400;
constexpr uint32_t GCH = 6144;
constexpr uint32_t HCH = 4096;

constexpr int B_FULL = 0, B_EMPTY = 10, B_XA = 20  , B_XB = 25  , B_INB = 29  , B_SR = 33,
              B_RST = 34  , B_RDY = 36  , B_SINK = 42, B_HALO = 43  , NBARS = 47;

#define KD2 300u
#define KD3 500u
#define QGATE 500u
#define BACKOFF 0u
#define KFS 8
#define KDELAY 300u
#define NJ0 2
#define HDELAY 200u
#define LATE 2
#define UNRV 5
constexpr int UNR = UNRV;
#define SND 0
#define XBULK 2
#define TURN 0x200
#define EAGER 0x0155
constexpr int FS = 8;

struct Params {
    CUtensorMap tm[9];
    const char* w[8];
    const __nv_bfloat16* x;
    const __nv_bfloat16* dw;
    __nv_bfloat16* out;
    uint32_t zero;
};

__device__ __align__(1024) unsigned char g_kvq[3 * 8 * 1024 * 128];
__device__ __align__(1024) unsigned char g_o[2 * 128 * 4096];
__device__ uint4 g_halo[64 * 4 * 2 * 64];
__device__ __align__(128) uint32_t g_flag_kv[8 * 32 * KFS];
__device__ uint32_t g_reset[4 * 32];
__device__ uint32_t g_epoch[NCTA * FS];

#define TS(i) do { } while (0)
#define TSW(i) do { } while (0)
#define TG(i) do { } while (0)
#define TSINIT() do { } while (0)
#define TSDUMP() do { } while (0)
constexpr uint32_t SMEM_LAUNCH = SMEM_BYTES;

__device__ __forceinline__ uint32_t smem_u32(const void* p) { return (uint32_t)__cvta_generic_to_shared(p); }
__device__ __forceinline__ void mbar_init(uint32_t b, uint32_t c) { asm volatile("mbarrier.init.shared::cta.b64 [%0], %1;" ::"r"(b), "r"(c) : "memory"); }
__device__ __forceinline__ void mbar_arrive(uint32_t b) { asm volatile("mbarrier.arrive.shared::cta.b64 _, [%0];" ::"r"(b) : "memory"); }
__device__ __forceinline__ void mbar_arrive_tx(uint32_t b, uint32_t tx) { asm volatile("mbarrier.arrive.expect_tx.shared::cta.b64 _, [%0], %1;" ::"r"(b), "r"(tx) : "memory"); }
__device__ __forceinline__ void mbar_wait(uint32_t b, uint32_t ph) {
    asm volatile("{\n.reg .pred p, q;\n.reg .u32 c;\nmov.u32 c, 0;\n"
                 "MW_LOOP:\n.pragma \"nounroll\";\n"
                 "mbarrier.try_wait.parity.shared::cta.b64 p, [%0], %1;\n"
                 "add.u32 c, c, 1;\nsetp.lt.u32 q, c, 65536;\nnot.pred p, p;\nand.pred p, p, q;\n@p bra MW_LOOP;\n}"
                 ::"r"(b), "r"(ph) : "memory");
}
__device__ __forceinline__ bool mbar_test(uint32_t b, uint32_t ph) {
    uint32_t ok;
    asm volatile("{\n.reg .pred p;\nmbarrier.test_wait.parity.shared::cta.b64 p, [%1], %2;\nselp.u32 %0, 1, 0, p;\n}" : "=r"(ok) : "r"(b), "r"(ph) : "memory");
    return ok;
}
__device__ __forceinline__ uint32_t mapa(uint32_t a, uint32_t r) { uint32_t o; asm("mapa.shared::cluster.u32 %0, %1, %2;" : "=r"(o) : "r"(a), "r"(r)); return o; }
__device__ __forceinline__ void fence_async_smem() { asm volatile("fence.proxy.async.shared::cta;" ::: "memory"); }
__device__ __forceinline__ void fence_async_global() { asm volatile("fence.proxy.async.global;" ::: "memory"); }
__device__ __forceinline__ void bar_sync(int id, int n) { asm volatile("bar.sync %0, %1;" ::"r"(id), "r"(n) : "memory"); }
__device__ __forceinline__ void bar_arrive(int id, int n) { asm volatile("bar.arrive %0, %1;" ::"r"(id), "r"(n) : "memory"); }
__device__ __forceinline__ void cluster_arrive() { asm volatile("barrier.cluster.arrive.relaxed.aligned;" ::: "memory"); }
__device__ __forceinline__ void cluster_wait() { asm volatile("barrier.cluster.wait.aligned;" ::: "memory"); }

__device__ __forceinline__ void ring_load(uint32_t dst, const CUtensorMap* tm, int col, int row16, uint32_t bar) {
    asm volatile("{\n.reg .pred p;\nelect.sync _|p, 0xffffffff;\n"
                 "@p mbarrier.arrive.expect_tx.shared::cta.b64 _, [%2], 16384;\n"
                 "@p cp.async.bulk.tensor.5d.shared::cluster.global.mbarrier::complete_tx::bytes [%0], [%1, {%3, 0, 0, 0, %4}], [%2];\n}"
                 ::"r"(dst), "l"(tm), "r"(bar), "r"(col), "r"(row16) : "memory");
}
__device__ __forceinline__ void ring_load_both(uint32_t dst, const CUtensorMap* tm, int c1, uint32_t bar) {
    asm volatile("{\n.reg .pred p;\nelect.sync _|p, 0xffffffff;\n"
                 "@p cp.async.bulk.tensor.2d.shared::cluster.global.mbarrier::complete_tx::bytes.multicast::cluster [%0], [%1, {0, %3}], [%2], %4;\n}"
                 ::"r"(dst), "l"(tm), "r"(bar), "r"(c1), "h"((uint16_t)3) : "memory");
}
__device__ __forceinline__ void mbar_arrive_peer(uint32_t b) { asm volatile("mbarrier.arrive.relaxed.cluster.shared::cluster.b64 _, [%0];" ::"r"(b) : "memory"); }
__device__ __forceinline__ void prefetch_l2(const void* src, uint32_t bytes) {
    asm volatile("cp.async.bulk.prefetch.L2.global [%0], %1;" ::"l"(src), "r"(bytes) : "memory");
}
__device__ __forceinline__ void peer_copy(uint32_t dst, uint32_t src, uint32_t bytes, uint32_t rbar) {
    asm volatile("{\n.reg .pred p;\nelect.sync _|p, 0xffffffff;\n"
                 "@p cp.async.bulk.shared::cluster.shared::cta.mbarrier::complete_tx::bytes [%0], [%1], %2, [%3];\n}"
                 ::"r"(dst), "r"(src), "r"(bytes), "r"(rbar) : "memory");
}
__device__ __forceinline__ void st_async4(uint32_t dst, uint32_t a, uint32_t b, uint32_t c, uint32_t d, uint32_t bar) {
    asm volatile("st.async.shared::cluster.mbarrier::complete_tx::bytes.v4.b32 [%0], {%1,%2,%3,%4}, [%5];" ::"r"(dst), "r"(a), "r"(b), "r"(c), "r"(d), "r"(bar) : "memory");
}
__device__ __forceinline__ void put_sums(uint32_t dst, uint32_t rdst, float a, float b, uint32_t rbar, bool on) {
    asm volatile("{\n.reg .pred p;\nsetp.ne.u32 p, %5, 0;\n"
                 "@p st.async.shared::cluster.mbarrier::complete_tx::bytes.v2.f32 [%1], {%2,%3}, [%4];\n"
                 "@p st.shared.v2.f32 [%0], {%2,%3};\n}" ::"r"(dst), "r"(rdst), "f"(a), "f"(b), "r"(rbar), "r"((uint32_t)on) : "memory");
}
__device__ __forceinline__ void stsm4(uint32_t a, uint32_t r0, uint32_t r1, uint32_t r2, uint32_t r3) {
    asm volatile("stmatrix.sync.aligned.m8n8.x4.shared.b16 [%0], {%1,%2,%3,%4};" ::"r"(a), "r"(r0), "r"(r1), "r"(r2), "r"(r3) : "memory");
}
__device__ __forceinline__ void ldsm4(uint32_t a, uint32_t& r0, uint32_t& r1, uint32_t& r2, uint32_t& r3) {
    asm volatile("ldmatrix.sync.aligned.m8n8.x4.shared.b16 {%0,%1,%2,%3}, [%4];" : "=r"(r0), "=r"(r1), "=r"(r2), "=r"(r3) : "r"(a) : "memory");
}
__device__ __forceinline__ uint4 lds128(uint32_t a) { uint4 v; asm volatile("ld.shared.v4.b32 {%0,%1,%2,%3}, [%4];" : "=r"(v.x), "=r"(v.y), "=r"(v.z), "=r"(v.w) : "r"(a) : "memory"); return v; }
__device__ __forceinline__ float4 lds128f(uint32_t a) { float4 v; asm volatile("ld.shared.v4.f32 {%0,%1,%2,%3}, [%4];" : "=f"(v.x), "=f"(v.y), "=f"(v.z), "=f"(v.w) : "r"(a) : "memory"); return v; }
__device__ __forceinline__ float2 lds64f(uint32_t a) { float2 v; asm volatile("ld.shared.v2.f32 {%0,%1}, [%2];" : "=f"(v.x), "=f"(v.y) : "r"(a) : "memory"); return v; }
__device__ __forceinline__ uint32_t lds32(uint32_t a) { uint32_t v; asm volatile("ld.shared.b32 %0, [%1];" : "=r"(v) : "r"(a) : "memory"); return v; }
__device__ __forceinline__ void sts128(uint32_t a, uint32_t x, uint32_t y, uint32_t z, uint32_t w) { asm volatile("st.shared.v4.b32 [%0], {%1,%2,%3,%4};" ::"r"(a), "r"(x), "r"(y), "r"(z), "r"(w) : "memory"); }
__device__ __forceinline__ void sts128f(uint32_t a, float x, float y, float z, float w) { asm volatile("st.shared.v4.f32 [%0], {%1,%2,%3,%4};" ::"r"(a), "f"(x), "f"(y), "f"(z), "f"(w) : "memory"); }
__device__ __forceinline__ void sts64f(uint32_t a, float x, float y) { asm volatile("st.shared.v2.f32 [%0], {%1,%2};" ::"r"(a), "f"(x), "f"(y) : "memory"); }
__device__ __forceinline__ void sts32(uint32_t a, uint32_t x) { asm volatile("st.shared.b32 [%0], %1;" ::"r"(a), "r"(x) : "memory"); }
__device__ __forceinline__ void stg128(void* p, uint4 v) { asm volatile("st.global.v4.b32 [%0], {%1,%2,%3,%4};" ::"l"(p), "r"(v.x), "r"(v.y), "r"(v.z), "r"(v.w) : "memory"); }

__device__ __forceinline__ uint32_t pack2(float lo, float hi) { uint32_t r; asm("cvt.rn.bf16x2.f32 %0, %1, %2;" : "=r"(r) : "f"(hi), "f"(lo)); return r; }
__device__ __forceinline__ float blo(uint32_t v) { return __uint_as_float(v << 16); }
__device__ __forceinline__ float bhi(uint32_t v) { return __uint_as_float(v & 0xffff0000u); }
__device__ __forceinline__ uint32_t hmul2(uint32_t a, uint32_t b) { uint32_t r; asm("mul.rn.bf16x2 %0, %1, %2;" : "=r"(r) : "r"(a), "r"(b)); return r; }
__device__ __forceinline__ uint32_t hadd2(uint32_t a, uint32_t b) { uint32_t r; asm("add.rn.bf16x2 %0, %1, %2;" : "=r"(r) : "r"(a), "r"(b)); return r; }
__device__ __forceinline__ uint32_t hsub2(uint32_t a, uint32_t b) { uint32_t r; asm("sub.rn.bf16x2 %0, %1, %2;" : "=r"(r) : "r"(a), "r"(b)); return r; }
__device__ __forceinline__ uint32_t hfma2(uint32_t a, uint32_t b, uint32_t c) { uint32_t r; asm("fma.rn.bf16x2 %0, %1, %2, %3;" : "=r"(r) : "r"(a), "r"(b), "r"(c)); return r; }
__device__ __forceinline__ float tanh_fast(float x) { float r; asm("tanh.approx.f32 %0, %1;" : "=f"(r) : "f"(x)); return r; }
__device__ __forceinline__ float rsq(float x) { float r; asm("rsqrt.approx.ftz.f32 %0, %1;" : "=f"(r) : "f"(x)); return r; }
__device__ __forceinline__ float ex2(float x) { float r; asm("ex2.approx.ftz.f32 %0, %1;" : "=f"(r) : "f"(x)); return r; }

__device__ __forceinline__ uint32_t ld_relaxed(const uint32_t* p) {
    uint32_t v;
    asm volatile("ld.relaxed.gpu.global.u32 %0, [%1];" : "=r"(v) : "l"(p) : "memory");
    return v;
}
__device__ __forceinline__ uint32_t clock32() { uint32_t c; asm volatile("mov.u32 %0, %%clock;" : "=r"(c)::"memory"); return c; }
__device__ __forceinline__ void spin(uint32_t clks) {
    const uint32_t t0 = clock32();
    while (clock32() - t0 < clks) {}
}
__device__ __forceinline__ void flag_wait(const uint32_t* p, uint32_t e, bool mine) {
#pragma unroll 1
    for (int i = 0; i < (1 << 19); i++) {
        if (mine) mine = ld_relaxed(p) != e;
        if (!__any_sync(~0u, mine)) break;
        if (BACKOFF) spin(BACKOFF);
    }
    asm volatile("fence.acquire.gpu;" ::: "memory");
    fence_async_global();
}
__device__ __forceinline__ void st_data(void* p, uint32_t x, uint32_t y, uint32_t z, uint32_t w) {
    asm volatile("st.relaxed.gpu.global.v4.b32 [%0], {%1,%2,%3,%4};" ::"l"(p), "r"(x), "r"(y), "r"(z), "r"(w) : "memory");
}
template <int STRIDE, int N>
__device__ __forceinline__ void ld_data(uint4 (&v)[N], const unsigned char* p) {
    int it = 0;
    bool again;
#pragma unroll 1
    do {
        uint32_t m = 0;
#pragma unroll
        for (int i = 0; i < N; i++)
            asm volatile("ld.relaxed.gpu.global.v4.b32 {%0,%1,%2,%3}, [%4];" : "=r"(v[i].x), "=r"(v[i].y), "=r"(v[i].z), "=r"(v[i].w) : "l"(p + i * STRIDE) : "memory");
#pragma unroll
        for (int i = 0; i < N; i++) m = __vimax3_u32(__vimax3_u32(v[i].x, v[i].y, v[i].z), v[i].w, m);
        again = __any_sync(~0u, m == ~0u) && ++it < (1 << 16);
    } while (again);
}
__device__ __forceinline__ uint32_t ld_epoch() { return ld_relaxed(&g_epoch[blockIdx.x * FS]) + 1; }
__device__ __forceinline__ void flag_set(uint32_t* p, uint32_t e) { asm volatile("st.release.gpu.global.u32 [%0], %1;" ::"l"(p), "r"(e) : "memory"); }

__device__ __forceinline__ uint32_t desc_lo(uint32_t addr) { return ((addr & 0x3FFFF) >> 4) | 0x10000u; }
__device__ __forceinline__ uint64_t mkdesc(uint32_t lo) { return (uint64_t)lo | (0x40000040ull << 32); }
__device__ __forceinline__ void wg_fence() { asm volatile("wgmma.fence.sync.aligned;" ::: "memory"); }
__device__ __forceinline__ void wg_commit() { asm volatile("wgmma.commit_group.sync.aligned;" ::: "memory"); }
template <int N> __device__ __forceinline__ void wg_wait() { asm volatile("wgmma.wait_group.sync.aligned %0;" ::"n"(N) : "memory"); }
template <int N> __device__ __forceinline__ void pin(float (&d)[N]) {
#pragma unroll
    for (int i = 0; i < N; i++) asm volatile("" : "+f"(d[i])::"memory");
}
template <int N> __device__ __forceinline__ void pin(uint32_t (&d)[N]) {
#pragma unroll
    for (int i = 0; i < N; i++) asm volatile("" : "+r"(d[i])::"memory");
}

template <typename Tp, int N> __device__ __forceinline__ void zero(Tp (&d)[N]) {
#pragma unroll
    for (int i = 0; i < N; i++) d[i] = 0;
    pin(d);
}

#define F4(d, i) "+f"(d[i]), "+f"(d[i + 1]), "+f"(d[i + 2]), "+f"(d[i + 3])
#define F16(d, i) F4(d, i), F4(d, i + 4), F4(d, i + 8), F4(d, i + 12)

__device__ __forceinline__ void mma16(float (&d)[4], const uint32_t* a, uint32_t b0, uint32_t b1) {
    asm("mma.sync.aligned.m16n8k16.row.col.f32.bf16.bf16.f32 {%0,%1,%2,%3}, {%4,%5,%6,%7}, {%8,%9}, {%0,%1,%2,%3};"
        : F4(d, 0) : "r"(a[0]), "r"(a[1]), "r"(a[2]), "r"(a[3]), "r"(b0), "r"(b1));
}
template <int N>
__device__ __forceinline__ void row_sums(const uint32_t* x, int lane, float& s, float& q) {
    float cs[4] = {}, c0[4] = {}, c1[4] = {};
#pragma unroll
    for (int i = 0; i < N; i += 4) {
        mma16(cs, x + i, 0x3F803F80u, 0x3F803F80u);
        mma16(c0, x + i, x[i], x[i + 2]);
        mma16(c1, x + i, x[i + 1], x[i + 3]);
    }
    s = cs[0] + cs[2];
    q = (lane & 4) ? c0[1] + c1[3] : c0[0] + c1[2];
}
__device__ __forceinline__ void mma_sp(float (&d)[32], const uint32_t* a, uint64_t b, uint32_t meta, int acc) {
    asm volatile("{.reg .pred p; setp.ne.b32 p, %38, 0;\n"
                 "wgmma.mma_async.sp.sync.aligned.m64n64k32.f32.bf16.bf16 {%0,%1,%2,%3,%4,%5,%6,%7,%8,%9,%10,%11,%12,%13,%14,%15,%16,%17,%18,%19,%20,%21,%22,%23,%24,%25,%26,%27,%28,%29,%30,%31}, "
                 "{%32,%33,%34,%35}, %36, %37, 0, p, 1, 1, 1;}\n"
                 : F16(d, 0), F16(d, 16) : "r"(a[0]), "r"(a[1]), "r"(a[2]), "r"(a[3]), "l"(b), "r"(meta), "r"(acc));
}
__device__ __forceinline__ void mma_qk(float (&d)[32], uint32_t a0, uint32_t a1, uint32_t a2, uint32_t a3, uint64_t b, int acc) {
    asm volatile("{.reg .pred p; setp.ne.b32 p, %37, 0;\n"
                 "wgmma.mma_async.sync.aligned.m64n64k16.f32.bf16.bf16 {%0,%1,%2,%3,%4,%5,%6,%7,%8,%9,%10,%11,%12,%13,%14,%15,%16,%17,%18,%19,%20,%21,%22,%23,%24,%25,%26,%27,%28,%29,%30,%31}, "
                 "{%32,%33,%34,%35}, %36, p, 1, 1, 0;}\n"
                 : F16(d, 0), F16(d, 16) : "r"(a0), "r"(a1), "r"(a2), "r"(a3), "l"(b), "r"(acc));
}
__device__ __forceinline__ void mma_pv(float (&d)[36], uint32_t a0, uint32_t a1, uint32_t a2, uint32_t a3, uint64_t b) {
    asm volatile("wgmma.mma_async.sync.aligned.m64n72k16.f32.bf16.bf16 {%0,%1,%2,%3,%4,%5,%6,%7,%8,%9,%10,%11,%12,%13,%14,%15,%16,%17,%18,%19,%20,%21,%22,%23,%24,%25,%26,%27,%28,%29,%30,%31,%32,%33,%34,%35}, "
                 "{%36,%37,%38,%39}, %40, 1, 1, 1, 1;\n"
                 : F16(d, 0), F16(d, 16), F4(d, 32) : "r"(a0), "r"(a1), "r"(a2), "r"(a3), "l"(b));
}

__device__ __forceinline__ uint32_t load_code(int n, int r, int w) {
    const int tile = 2 * r + w;
    int m, col, row;
    if (n < 16 || n >= 40) {
        const int k = n < 16 ? n : n - 40;
        m = n < 16 ? 0 : 6;
        if (k < 8) { col = 4 * tile + (k >> 1); row = (k & 1) ^ r; }
        else { m++; col = k < 12 ? tile ^ 2 : tile; row = 2 * (tile ^ (k & 1)) + ((k >> 1) & 1); }
    } else if (n < 32) {
        const int k = n - 16;
        m = 2;
        if (k < 4) { col = tile + ((k & 1) ? 8 : 4); row = (k >> 1) ^ r; }
        else { col = tile; row = (k & 1) ^ r; }
    } else if (n < 34) { m = 3; col = tile; row = n - 32; }
    else if (n < 38) { const int k = n - 34; m = 4; col = tile + 4 * (k & 1); row = (k >> 1) ^ r; }
    else { m = 5; col = tile; row = (n & 1) ^ r; }
    return m | (col << 4) | (row << 8);
}

__global__ void __cluster_dims__(2, 1, 1) __launch_bounds__(NTHREADS, 1)
conformer_kernel(const __grid_constant__ Params p) {
    extern __shared__ __align__(1024) unsigned char smem_raw[];
    const uint32_t sb = smem_u32(smem_raw);
    const uint32_t bars = sb + OFF_BARS;
    const int tid = threadIdx.x;
    const int lane = tid & 31;
    const int warp = __shfl_sync(~0u, tid >> 5, 0);
    const int r = blockIdx.x & 1;
    const int pair = blockIdx.x >> 1;
    const int b = pair >> 5, pt = pair & 31;
    const int ah = pt >> 3, qt = (pt & 7) * 2 + r;
    const int abh = b * 4 + ah;

    TG(30);
    TSINIT();
    TS(0);
    const uint32_t P = sb + OFF_P, H = sb + OFF_H;

    if (warp >= 8) {
        asm volatile("setmaxnreg.dec.sync.aligned.u32 48;");
        if (warp >= 12) {
            cluster_arrive();
            cluster_wait();
            const int ut = tid & 127;
            const uint32_t target = ld_epoch() * 64;
            auto reset_done = [&](int k) {
                bar_sync(11, 128);
                if (ut == 0) {
                    asm volatile("red.release.gpu.global.add.u32 [%0], 1;" ::"l"(&g_reset[(2 * b + k) * 32]) : "memory");
#pragma unroll 1
                    for (int i = 0; i < (1 << 20) && ld_relaxed(&g_reset[(2 * b + k) * 32]) != target; i++) __nanosleep(100);
                    asm volatile("fence.acquire.gpu;" ::: "memory");
                    mbar_arrive(bars + (B_RST + k) * 8);
                }
                __syncwarp();
                TS(13 + k);
            };
#pragma unroll
            for (int i = 0; i < 4; i++)
                st_data(g_kvq + 2097152 + (size_t)((b * 4 + 2 * r + (i >> 1)) * 1024 + pt * 32) * 128 + (i & 1) * 2048 + ut * 16, ~0u, ~0u, ~0u, ~0u);
            reset_done(0);
            bar_sync(6, 384);
#pragma unroll
            for (int i = 0; i < 4; i++) {
                st_data(g_o + (size_t)(b * 128 + qt * 8 + 2 * i + (ut >> 6)) * 4096 + ah * 1024 + (ut & 63) * 16, ~0u, ~0u, ~0u, ~0u);
                if (i < 2) st_data(&g_halo[(pair * 4 + 2 * r + i) * 128 + ut], ~0u, ~0u, ~0u, ~0u);
            }
            reset_done(1);
            const int side = warp & 1, wg = (warp >> 1) & 1, np = side ? pt + 1 : pt - 1;
            const unsigned char* src = reinterpret_cast<const unsigned char*>(&g_halo[(((b * 32 + np) * 4 + 2 * r + wg) * 2 + (side ^ 1)) * 64 + lane]);
            const uint32_t dst = H + 16384 + wg * GCH + side * 5120 + (lane & 7) * 128 + (((lane >> 3) ^ (lane & 7)) << 4);
            uint4 hv[2] = {make_uint4(0, 0, 0, 0), make_uint4(0, 0, 0, 0)};
            bar_sync(8 + wg, 192);
            if (np >= 0 && np < 32) {
                spin(HDELAY);
                ld_data<512>(hv, src);
            }
            stsm4(dst, hv[0].x, hv[0].y, hv[0].z, hv[0].w);
            stsm4(dst ^ 64, hv[1].x, hv[1].y, hv[1].z, hv[1].w);
            __syncwarp();
            if (lane == 0) mbar_arrive(bars + (B_HALO + (warp & 3)) * 8);
            TS(4);
        } else if (warp < 10) {
            const int w = warp - 8;
            const uint32_t ring = sb + OFF_RING + w * NSLOT * SLOT;
            const uint32_t full = bars + (B_FULL + w * NSLOT) * 8;
            if (lane == 0) {
#pragma unroll
                for (int i = 0; i < NSLOT; i++) { mbar_init(full + i * 8, 1); mbar_init(full + (B_EMPTY - B_FULL + i) * 8, 4); }
                asm volatile("fence.mbarrier_init.release.cluster;" ::: "memory");
                fence_async_smem();
            }
            __syncwarp();
            cluster_arrive();
            TS(1);
#pragma unroll
            for (int n = 0; n < NSLOT; n++) {
                if (n == 1 || n == 2) bar_sync(12, 64);
                ring_load(ring + n * SLOT, &p.tm[0], 64 * (8 * r + 4 * w + (n >> 1)), 8 * ((n & 1) ^ r), full + n * 8);
            }
            TS(2);
            const uint32_t code = load_code(lane, r, w) | (load_code(lane + 32, r, w) << 16);
            cluster_wait();
            uint32_t s = 0, ph = 0;
            int n = NSLOT;
#pragma unroll 1
            for (int seg = 0; seg < 2; seg++) {
#pragma unroll 1
                for (; n < (seg == 0 ? 22 : NLOADS); n++) {
                    const uint32_t c = __shfl_sync(~0u, code, n) >> (n & 32 ? 16 : 0);
                    const CUtensorMap* tm = &p.tm[c & 15];
                    const uint32_t col = (c & 0xf0) * 4, row = (c & 0xff00) >> 5, dst = ring + s * SLOT;
                    mbar_wait(full + (B_EMPTY - B_FULL) * 8 + s * 8, ph + (((uint32_t)(size_t)tm | col | row | dst) & p.zero));
                    ring_load(dst, tm, col, row, full + s * 8);
                    if (++s == NSLOT) { s = 0; ph ^= 1; }
                }
                if (seg == 1) break;
                const uint32_t epoch = ld_epoch();
                const uint32_t rdy = bars + (B_RDY + 3 * w) * 8, prdy = mapa(rdy, r ^ 1);
                const int odd = r ^ w;
                const uint32_t* flags = g_flag_kv + (abh * 32 + lane) * KFS;
                auto kv_load = [&](uint32_t sl, int isv, int i) {
                    ring_load_both(ring + sl * SLOT, &p.tm[8], (isv * 64 + abh * 8 + 2 * i + w) * 128, full + sl * 8);
                };
#pragma unroll 1
                for (int i = 0; i < 2; i++) {
                    if (lane < 3 + i) {
                        const uint32_t sl = i ? lane : lane + 2;
                        mbar_wait(full + (B_EMPTY - B_FULL + sl) * 8, i ^ 1);
                        mbar_arrive_tx(full + sl * 8, (i || lane == 2) ? SLOT : 0);
                    }
                    __syncwarp();
                }
                if (lane == 0) mbar_arrive_peer(prdy);
                bar_sync(14, 96);
                spin(KDELAY);
                mbar_wait(rdy, 0);
                flag_wait(flags, epoch, (lane >> 2) == 2 * odd + w);
                TSW(5 + 2 * odd);
                if (!odd) { kv_load(4, 0, 0); bar_arrive(12, 64); }
                else bar_sync(12, 64);
                spin(w ? KD3 : KD2);
                kv_load(odd ^ 1, odd ^ 1, odd);
                flag_wait(flags, epoch, (lane >> 2) == 2 * odd + w + 4);
                mbar_wait(full + (odd ^ 1) * 8, 1);
                kv_load(2 + odd, odd, 2 - odd);
#pragma unroll 1
                for (int i = 0; i < 3; i++) {
                    const uint32_t sl = i ? i - 1 : 4, bo = i == 2 ? 16 : 8;
                    mbar_wait(full + (B_EMPTY - B_FULL + sl) * 8, i != 0);
                    if (lane == 0) mbar_arrive_tx(full + sl * 8, SLOT);
                    if ((i & 1) != odd) {
                        mbar_wait(rdy + bo, 0);
                        kv_load(sl, i != 0, 2 + odd);
                    } else if (lane == 0) mbar_arrive_peer(prdy + bo);
                    __syncwarp();
                }
                n = 32; s = 2; ph = 1;
            }
        } else if (warp == 10) {
            if (lane == 0) {
#pragma unroll
                for (int i = B_XA; i < NBARS; i++) mbar_init(bars + i * 8, 1);
#pragma unroll
                for (int i = B_XA; i <= B_SR; i++) mbar_arrive_tx(bars + i * 8, i < B_XB ? 512 : ((i >= B_INB && i < B_SR) ? 4096 : 8192));
                asm volatile("fence.mbarrier_init.release.cluster;" ::: "memory");
                fence_async_smem();
            }
            __syncwarp();
            cluster_arrive();
            cluster_wait();
            if (XBULK) {
#pragma unroll 1
                for (int ph = 0; ph < 4; ph++) {
                    const uint32_t bar = mapa(bars + (B_XB + ph) * 8, r ^ 1), dst = mapa(P + r * 8192, r ^ 1);
                    bar_sync(1, 288);
                    peer_copy(dst, P + r * 8192, 8192, bar);
                }
            }
        } else {
            const uint32_t kb = (lane < 2 || lane > 5) ? 4096 : (lane == 2 ? 3072 : (lane == 4 ? 2048 : 1024));
            const char* pf = p.w[lane & 7] + blockIdx.x * kb;
            cluster_arrive();
            cluster_wait();
            if (lane < 2) prefetch_l2(pf, kb);
            mbar_wait(bars + B_XA * 8, 0);
            if (lane == 2) prefetch_l2(pf, kb);
            if (lane >= 1 && lane < 9) asm volatile("prefetch.tensormap [%0];" ::"l"(&p.tm[lane]) : "memory");
            mbar_wait(bars + (B_FULL + 1) * 8, 1);
            if (lane > 2 && lane < 8) prefetch_l2(pf, kb);
            if (lane == 8 && blockIdx.x < 15) prefetch_l2(p.dw + blockIdx.x * 256, 512);
            const uint32_t epoch = ld_epoch();
            bar_sync(4, 288);
            if (lane < 16) flag_set(&g_flag_kv[((b * 4 + 2 * r + (lane >> 3)) * 32 + pt) * KFS + (lane & 7)], epoch);
            __syncwarp();
            bar_arrive(14, 96);
            TSW(8);
        }
        TSDUMP();
        return;
    }

    const int w = warp >> 2, wq = warp & 3;
    const int tile = 2 * r + w;
    const int wt = tid & 127;
    const int c4 = lane & 3;
    const int trow = pt * 32 + 8 * wq;
    uint32_t xr[8];
    {
        const uint32_t* xp = reinterpret_cast<const uint32_t*>(p.x + (size_t)(b * T_ + trow + (lane >> 2)) * 256 + tile * 64) + c4;
#pragma unroll
        for (int j = 0; j < 8; j++) xr[j] = trow < T_ ? __ldg(xp + 4 * j) : 0u;
    }
    cluster_arrive();
    asm volatile("setmaxnreg.inc.sync.aligned.u32 208;");
    const uint32_t rbase = sb + OFF_RING + w * NSLOT * SLOT, fbar = bars + (B_FULL + w * NSLOT) * 8;
    const uint32_t rdesc = desc_lo(rbase);
    auto acq = [&](int n) { mbar_wait(fbar + (n % NSLOT) * 8, (n / NSLOT) & 1); };
    auto rel = [&](int n) { if (lane == 0) mbar_arrive(fbar + (B_EMPTY - B_FULL + n % NSLOT) * 8); };
    const uint32_t foff = (lane & 7) * 128 + (((lane >> 3) ^ (lane & 7)) << 4);
    float v[16];
#pragma unroll
    for (int j = 0; j < 8; j++) { v[2 * j] = blo(xr[j]); v[2 * j + 1] = bhi(xr[j]); }
    const uint32_t xown = __shfl_sync(~0u, P + wt * 16 + tile * 4096, lane), xrem = __shfl_sync(~0u, P + wt * 16 + (r ^ 1) * 8192, lane);
    const uint32_t sbuf = __shfl_sync(~0u, sb + OFF_MISC + 1024 + (8 * wq + (lane >> 2)) * 32, lane);
    const uint32_t sown = __shfl_sync(~0u, sbuf + tile * 8, lane);
    const uint32_t peer = __shfl_sync(~0u, mapa(sb, r ^ 1) - sb, lane);
    const uint32_t hbuf = __shfl_sync(~0u, H + w * 4096 + wt * 16, lane);
    const uint32_t meta = __shfl_sync(~0u, 0xEEEE4444u + p.zero, lane);
    cluster_wait();
    TS(56);
    float mean, msq;
    const int mir = wq < 2 ? 7 : 0;
    uint32_t dwr[15] = {};

#pragma unroll UNR
    for (int ph = 0; ph < 5; ph++) {
        uint4 o0, o1;
        {
            const uint32_t xa = bars + (B_XA + ph) * 8;
#pragma unroll
            for (int j = 0; j < 8; j++) xr[j] = pack2(v[2 * j], v[2 * j + 1]);
            float s, q;
            row_sums<8>(xr, lane, s, q);
            if (ph < 4) {
                sts128(xown, xr[0], xr[1], xr[2], xr[3]);
                sts128(xown + 2048, xr[4], xr[5], xr[6], xr[7]);
                if (XBULK == 2) { fence_async_smem(); bar_arrive(1, 288); }
            }
            put_sums(sown, sown + peer, s, q, xa + peer, c4 == (lane >> 3));
            if (XBULK == 1 && ph < 4) { fence_async_smem(); bar_sync(1, 288); }
            else bar_sync(10, 256);
            if (ph < 4) {
                o0 = lds128(xown ^ 4096); o1 = lds128((xown ^ 4096) + 2048);
                if (!XBULK) {
                    st_async4(xown + peer, xr[0], xr[1], xr[2], xr[3], xa + (B_XB - B_XA) * 8 + peer);
                    st_async4(xown + peer + 2048, xr[4], xr[5], xr[6], xr[7], xa + (B_XB - B_XA) * 8 + peer);
                }
            }
            TS(57 + ph);
            if (ph == 0 || ph == 3) acq(0);
            if (ph == 1) acq(16);
            mbar_wait(xa, 0);
            const float4 u0 = lds128f(sbuf), u1 = lds128f(sbuf + 16);
            mean = ((u0.x + u0.z) + (u1.x + u1.z)) * (1.f / 256.f);
            msq = ((u0.y + u0.w) + (u1.y + u1.w)) * (1.f / 256.f);
        }
        if (ph == 4) break;
        uint32_t a[32];
        const uint32_t mean2 = pack2(mean, mean);
        auto centre = [&](int i, const uint4& u) {
            a[i] = hsub2(u.x, mean2); a[i + 1] = hsub2(u.y, mean2); a[i + 2] = hsub2(u.z, mean2); a[i + 3] = hsub2(u.w, mean2);
        };
#pragma unroll
        for (int j = 0; j < 8; j++) a[j] = hsub2(xr[j], mean2);
        centre(8, o0); centre(12, o1);
        const float rstd = rsq(fmaxf(fmaf(-mean, mean, msq), 0.f) + 1e-5f);
        auto gather_peer = [&]() {
            mbar_wait(bars + (B_XB + ph) * 8, 0);
#pragma unroll
            for (int i = 0; i < 4; i++) centre(16 + 4 * i, lds128(xrem + i * 2048));
        };
        auto sp = [&](float (&d)[32], int n, const uint32_t* af, int flip, int acc) {
            const uint32_t lo = rdesc + p.zero * (ph * 64 + n + 1) + (n % NSLOT) * (SLOT >> 4);
            const uint64_t b0 = mkdesc(lo + flip * 512), b1 = mkdesc(lo + (flip ^ 1) * 512);
            wg_fence();
            mma_sp(d, af, b0, meta, acc);
            mma_sp(d, af + 4, b0 + 256, meta, 1);
            mma_sp(d, af + 8, b1, meta, 1);
            mma_sp(d, af + 12, b1 + 256, meta, 1);
            wg_commit();
        };
        float d0[32], d1[32];

        if (ph == 0 || ph == 3) {
            uint32_t h[32], ho[32];
            const float rs = 0.5f * rstd;
            const uint32_t inb = bars + (B_INB + (ph & 2) + w) * 8;
            bool ready = true;
            auto step = [&](float (&d)[32], int n, const uint32_t* af, int flip, int acc, auto work) {
                if (!ready) acq(n);
                if (((TURN >> n) & 1) && w == 1) bar_sync(7, 256);
                sp(d, n, af, flip, acc);
                if (n > 0 && ((TURN >> (n - 1)) & 1) && w == 0) bar_arrive(7, 256);
                if (n < 15) ready = mbar_test(fbar + ((n + 1) % NSLOT) * 8, ((n + 1) / NSLOT) & 1);
                wg_wait<1>();
                if (n > 0 && !((EAGER >> (n - 1)) & 1)) rel(n - 1);
                const uint32_t tie = work() & p.zero;
                if ((EAGER >> n) & 1) {
                    if (p.zero < n + ph + 1) wg_wait<0>();
                    if (lane == 0) mbar_arrive(fbar + (B_EMPTY - B_FULL + n % NSLOT) * 8 + tie);
                }
            };
            auto none = []() { return 0u; };
            auto fetch = [&](int i) {
                bar_sync(10, 256);
                const uint4 u0 = lds128((hbuf ^ 4096) + (i & 1) * 8192), u1 = lds128((hbuf ^ 4096) + (i & 1) * 8192 + 2048);
                ho[8 * i] = u0.x; ho[8 * i + 1] = u0.y; ho[8 * i + 2] = u0.z; ho[8 * i + 3] = u0.w;
                ho[8 * i + 4] = u1.x; ho[8 * i + 5] = u1.y; ho[8 * i + 6] = u1.z; ho[8 * i + 7] = u1.w;
                return u0.x | u1.x;
            };
            auto act = [&](float (&d)[32], int i) {
                if (i > 0) fetch(i - 1);
                pin(d);
#pragma unroll
                for (int j = 0; j < 8; j++) {
                    const float u0 = (d[4 * j] + d[4 * j + 2]) * rs, u1 = (d[4 * j + 1] + d[4 * j + 3]) * rs;
                    h[8 * i + j] = pack2(fmaf(u0, tanh_fast(u0), u0), fmaf(u1, tanh_fast(u1), u1));
                }
                sts128(hbuf + (i & 1) * 8192, h[8 * i], h[8 * i + 1], h[8 * i + 2], h[8 * i + 3]);
                sts128(hbuf + (i & 1) * 8192 + 2048, h[8 * i + 4], h[8 * i + 5], h[8 * i + 6], h[8 * i + 7]);
                return 0u;
            };
            TS(1 + (ph & 2) * 10);
            step(d0, 0, a, w, 0, [&]() { gather_peer(); return 0u; });
            TS(32);
            step(d0, 1, a + 16, 0, 1, none);
            step(d1, 2, a, w, 0, [&]() { return act(d0, 0); });
            step(d1, 3, a + 16, 0, 1, none);
            step(d0, 4, a, w, 0, [&]() { return act(d1, 1); });
            TS(33);
            step(d0, 5, a + 16, 0, 1, none);
            step(d1, 6, a, w, 0, [&]() { return act(d0, 2); });
            step(d1, 7, a + 16, 0, 1, none);
            step(d0, 8, h, 0, 0, [&]() { act(d1, 3); return fetch(3); });
            TS(2 + (ph & 2) * 10);
            step(d0, 9, ho, 0, 1, none);
            step(d0, 10, h + 16, 0, 1, none);
            step(d0, 11, ho + 16, 0, 1, none);
            uint32_t pk[8];
            auto pack_out = [&]() {
                pin(d0);
#pragma unroll
                for (int j = 0; j < 8; j++) pk[j] = pack2(d0[4 * j] + d0[4 * j + 2], d0[4 * j + 1] + d0[4 * j + 3]);
            };
            auto send = [&](int i) { st_async4(hbuf + 16384 + i * 2048 + peer, pk[4 * i], pk[4 * i + 1], pk[4 * i + 2], pk[4 * i + 3], inb + peer); };
            step(d1, 12, h, 0, 0, [&]() { pack_out(); if (SND != 1) send(0); if (SND == 0) send(1); return 0u; });
            TS(34);
            step(d1, 13, ho, 0, 1, [&]() { if (SND == 1) send(0); if (SND) send(1); return 0u; });
            step(d1, 14, h + 16, 0, 1, none);
            step(d1, 15, ho + 16, 0, 1, none);
            mbar_wait(inb, 0);
#pragma unroll
            for (int i = 0; i < 2; i++) {
                const uint4 u = lds128(hbuf + 16384 + i * 2048);
                const uint32_t p0[4] = {u.x, u.y, u.z, u.w};
#pragma unroll
                for (int j = 0; j < 4; j++) {
                    v[8 * i + 2 * j] = fmaf(0.5f, blo(p0[j]), blo(xr[4 * i + j]));
                    v[8 * i + 2 * j + 1] = fmaf(0.5f, bhi(p0[j]), bhi(xr[4 * i + j]));
                }
            }
            wg_wait<0>();
            pin(d1);
            rel(15);
            TS(3 + (ph & 2) * 10);
#pragma unroll
            for (int j = 0; j < 8; j++) {
                v[2 * j] = fmaf(0.5f, d1[4 * j] + d1[4 * j + 2], v[2 * j]);
                v[2 * j + 1] = fmaf(0.5f, d1[4 * j + 1] + d1[4 * j + 3], v[2 * j + 1]);
            }
#pragma unroll
            for (int i = 0; i < 15; i++) dwr[i] = 0;
            continue;
        }

        auto residual = [&](int n) {
            wg_wait<1>();
            rel(n);
            wg_wait<0>();
            pin(d0);
            rel(n + 1);
#pragma unroll
            for (int j = 0; j < 8; j++) {
                v[2 * j] = d0[4 * j] + d0[4 * j + 2] + blo(xr[j]);
                v[2 * j + 1] = d0[4 * j + 1] + d0[4 * j + 3] + bhi(xr[j]);
            }
        };

        if (ph == 2) {
            TS(39);
            sp(d0, 34, a, w, 0);
            acq(35);
            sp(d1, 35, a, w, 0);
            acq(36); acq(37);
            gather_peer();
            sp(d0, 36, a + 16, 0, 1);
            sp(d1, 37, a + 16, 0, 1);
            wg_wait<2>();
            rel(34);
            if (!(LATE & 1)) rel(35);
            acq(38);
            const float rs = trow < T_ ? 0.5f * rstd : 0.f;
            wg_wait<0>();
            pin(d0); pin(d1);
            if (!(LATE & 2)) { rel(36); rel(37); }
            TS(18);
            uint32_t pk[8];
#pragma unroll
            for (int j = 0; j < 8; j++) {
                const float u0 = (d0[4 * j] + d0[4 * j + 2]) * rs, u1 = (d0[4 * j + 1] + d0[4 * j + 3]) * rs;
                const float t0 = tanh_fast((d1[4 * j] + d1[4 * j + 2]) * rs), t1 = tanh_fast((d1[4 * j + 1] + d1[4 * j + 3]) * rs);
                pk[j] = pack2(fmaf(u0, t0, u0), fmaf(u1, t1, u1));
            }
            if (wq == 0 || wq == 3) {
                uint4* hp = &g_halo[((pair * 4 + tile) * 2 + (wq & 1)) * 64 + lane];
                st_data(hp, pk[0], pk[1], pk[2], pk[3]);
                st_data(hp + 32, pk[4], pk[5], pk[6], pk[7]);
            }
            const uint32_t gs = H + 16384 + w * GCH + wq * 1024;
            stsm4(gs + 1024 + foff, pk[0], pk[1], pk[2], pk[3]);
            stsm4(gs + 1024 + (foff ^ 64), pk[4], pk[5], pk[6], pk[7]);
            bar_sync(8 + w, 192);
            TS(26);
            uint32_t ca[8], cb[8];
            const int e = (wq & 1) * 4;
            const uint32_t lo = ((mir ^ e) * 144) ^ (lane * 4);
            const int dir = mir ? -1024 : 1024;
            const uint32_t gb = H + 16384 + w * GCH + (mir ? 3072 : 2048) + lo, sown_ = H + tile * HCH, so = sown_ + (mir ? 1024 : 2048) + lo;
            auto finish = [&](int i) {
                const uint32_t c = hadd2(ca[i], cb[i]);
                const float h0 = blo(c), h1 = bhi(c);
                sts32((so + (i >> 2) * dir) ^ ((i & 3) * 144), pack2(fmaf(h0, tanh_fast(h0), h0), fmaf(h1, tanh_fast(h1), h1)));
            };
#pragma unroll
            for (int k = 0; k < 26; k++) {
                if (k == 19) {
#pragma unroll
                    for (int i = 0; i < 4; i++) finish(i);
                    fence_async_smem();
                    bar_sync(2 + w, 128);
                    if (wq == 0) peer_copy(mapa(sown_ + 1024, r ^ 1), sown_ + 1024, 2048, mapa(bars + B_SR * 8, r ^ 1));
                    mbar_wait(bars + (B_HALO + 2 * w + (wq >> 1)) * 8, 0);
                    if (LATE & 1) rel(35);
                    if (LATE & 2) { rel(36); rel(37); }
                    TS(27);
                }
                const uint32_t g = lds32((gb + (((k + 1) & 4) ? ((k + 1) >> 3) + (wq & 1) : ((k + 1) >> 3)) * dir) ^ (((k + 1) & 7) * 144));
#pragma unroll
                for (int i = 0; i < 8; i++) {
                    const int tap = k - (i & 3) - 2 * (i & 4);
                    if (tap == 0) ca[i] = hmul2(g, dwr[0]);
                    else if (tap > 0 && tap < 8) ca[i] = hfma2(g, dwr[tap], ca[i]);
                    else if (tap == 8) cb[i] = hmul2(g, dwr[8]);
                    else if (tap > 8 && tap < 15) cb[i] = hfma2(g, dwr[tap], cb[i]);
                }
            }
#pragma unroll
            for (int i = 4; i < 8; i++) finish(i);
            fence_async_smem();
            bar_sync(12 + (warp >> 1), 64);
            if (wq == 0 || wq == 3) peer_copy(mapa(sown_ + wq * 1024, r ^ 1), sown_ + wq * 1024, 1024, mapa(bars + B_SR * 8, r ^ 1));
            bar_sync(10, 256);
            TS(19);
            auto frags = [&](int i, int half) {
                const uint32_t src = H + 2 * half * HCH + wq * 1024;
#pragma unroll
                for (int k = 0; k < 4; k++) ldsm4(src + (k >> 1) * HCH + (foff ^ ((k & 1) * 64)), a[i + 4 * k], a[i + 4 * k + 1], a[i + 4 * k + 2], a[i + 4 * k + 3]);
            };
            frags(0, r);
            sp(d0, 38, a, 0, 0);
            acq(39);
            mbar_wait(bars + B_SR * 8, 0);
            frags(16, r ^ 1);
            sp(d0, 39, a + 16, 0, 1);
            residual(38);
            TS(20);
            continue;
        }

        {
            TS(11);
            const uint32_t stg = H + warp * 2048;
            unsigned char* g = g_kvq + (size_t)((b * 4 + tile) * 1024 + trow) * 128 + lane * 16;
            auto put = [&](float (&d)[32], int i) {
                pin(d);
                uint32_t pk[8];
#pragma unroll
                for (int j = 0; j < 8; j++) pk[j] = pack2((d[4 * j] + d[4 * j + 2]) * rstd, (d[4 * j + 1] + d[4 * j + 3]) * rstd);
                if (i == 2) {
                    st_data(g + 2097152, pk[0], pk[1], pk[2], pk[3]);
                    st_data(g + 2097152 + 512, pk[4], pk[5], pk[6], pk[7]);
                    return;
                }
                stsm4(stg + i * 1024 + foff, pk[0], pk[1], pk[2], pk[3]);
                stsm4(stg + i * 1024 + (foff ^ 64), pk[4], pk[5], pk[6], pk[7]);
                __syncwarp();
                const uint4 u0 = lds128(stg + i * 1024 + lane * 16), u1 = lds128(stg + i * 1024 + 512 + lane * 16);
                stg128(g + i * 1048576, u0); stg128(g + i * 1048576 + 512, u1);
            };
            sp(d0, 16, a, w, 0);
            acq(17);
            sp(d1, 17, a, w, 0);
            gather_peer();
            acq(18);
            sp(d0, 18, a + 16, 0, 1);
            wg_wait<1>();
            rel(16); rel(17);
            acq(19);
            sp(d1, 19, a + 16, 0, 1);
            wg_wait<1>();
            rel(18);
            put(d0, 0);
            wg_wait<0>();
            rel(19);
            TS(37);
            put(d1, 1);
            bar_arrive(4, 288);
            TS(38);
            acq(20);
            sp(d0, 20, a, w, 0);
            acq(21);
            sp(d0, 21, a + 16, 0, 1);
            acq(22); acq(23);
            rel(22); rel(23);
            mbar_wait(bars + B_RST * 8, 0);
            wg_wait<0>();
            rel(20); rel(21);
            put(d0, 2);
            TS(12);
        }

        {
            constexpr float CS = 0.125f * 1.4426950408889634f;
            float sa[32], sb2[32], o[36];
            uint32_t pa[16], pb[16], q[16];
            float n0 = INFINITY, n1 = INFINITY;
            zero(o); zero(pa); zero(pb); zero(sb2);
            const uint32_t ones = sb + OFF_MISC + 2048;
            { const uint32_t c = w ? 0u : 0x3F803F80u; sts128(ones + tid * 16, c, c, c, c); }
            fence_async_smem();
            bar_sync(10, 256);
            const uint32_t vdesc = rdesc + ((((ones - rbase) >> 4) - 1) << 16);
            auto qk_issue = [&](float (&s)[32], uint32_t lo) {
                const uint64_t kd = mkdesc(lo);
                wg_fence();
#pragma unroll
                for (int k = 0; k < 4; k++) mma_qk(s, q[4 * k], q[4 * k + 1], q[4 * k + 2], q[4 * k + 3], kd + 2 * k, k != 0);
                wg_commit();
            };
            auto both_issue = [&](float (&s)[32], uint32_t klo, uint32_t (&pp)[16], uint32_t vlo) {
                const uint64_t kd = mkdesc(klo), vd = mkdesc(vlo);
                wg_fence();
#pragma unroll
                for (int k = 0; k < 4; k++) {
                    mma_pv(o, pp[4 * k], pp[4 * k + 1], pp[4 * k + 2], pp[4 * k + 3], vd - k * (128 * 65535));
                    mma_qk(s, q[4 * k], q[4 * k + 1], q[4 * k + 2], q[4 * k + 3], kd + 2 * k, k != 0);
                }
                wg_commit();
            };
            auto new_max = [&](float (&s)[32], int nj, float& x0, float& x1) {
                x0 = s[0]; x1 = s[2];
#pragma unroll
                for (int j = 0; j < nj; j++) {
                    x0 = fmaxf(x0, fmaxf(s[4 * j], s[4 * j + 1]));
                    x1 = fmaxf(x1, fmaxf(s[4 * j + 2], s[4 * j + 3]));
                }
                x0 = fmaxf(x0, __shfl_xor_sync(~0u, x0, 1)); x1 = fmaxf(x1, __shfl_xor_sync(~0u, x1, 1));
                x0 = fmaxf(x0, __shfl_xor_sync(~0u, x0, 2)); x1 = fmaxf(x1, __shfl_xor_sync(~0u, x1, 2));
                x0 = fminf(n0, fmaf(x0, -CS, -20.f)); x1 = fminf(n1, fmaf(x1, -CS, -20.f));
            };
            auto probs = [&](float (&s)[32], uint32_t (&pp)[16], bool ready, bool tail, auto wait) {
                uint32_t any = 0;
#pragma unroll
                for (int i = 0; i < 16; i++) {
                    pp[i] = pack2(ex2(fmaf(s[2 * i], CS, (i & 1) ? n1 : n0)), ex2(fmaf(s[2 * i + 1], CS, (i & 1) ? n1 : n0)));
                    any |= pp[i];
                }
                wg_wait<0>();
                pin(sa); pin(sb2); pin(o); pin(pa); pin(pb);
                if (__any_sync(~0u, (any & 0x40004000u) || !ready)) {
                    wait();
                    if (__any_sync(~0u, any & 0x40004000u)) {
                        if (tail) {
#pragma unroll
                            for (int i = 20; i < 32; i++) s[i] = -INFINITY;
                        }
                        float x0, x1;
                        new_max(s, 8, x0, x1);
                        const float sc0 = ex2(x0 - n0), sc1 = ex2(x1 - n1);
                        n0 = x0; n1 = x1;
#pragma unroll
                        for (int j = 0; j < 9; j++) { o[4 * j] *= sc0; o[4 * j + 1] *= sc0; o[4 * j + 2] *= sc1; o[4 * j + 3] *= sc1; }
#pragma unroll
                        for (int i = 0; i < 16; i++)
                            pp[i] = pack2(ex2(fmaf(s[2 * i], CS, (i & 1) ? n1 : n0)), ex2(fmaf(s[2 * i + 1], CS, (i & 1) ? n1 : n0)));
                    }
                }
            };
            {
                uint4 u[4];
                const unsigned char* src = g_kvq + 2097152 + (size_t)(abh * 1024 + qt * 64 + wq * 16) * 128 + lane * 16;
                spin(QGATE);
                ld_data<512>(u, src);
#pragma unroll
                for (int k = 0; k < 2; k++) {
                    q[8 * k] = u[k].x; q[8 * k + 1] = u[k + 2].x; q[8 * k + 2] = u[k].y; q[8 * k + 3] = u[k + 2].y;
                    q[8 * k + 4] = u[k].z; q[8 * k + 5] = u[k + 2].z; q[8 * k + 6] = u[k].w; q[8 * k + 7] = u[k + 2].w;
                }
                pin(q);
            }
            TS(40);
            acq(24);
            TS(13);
            qk_issue(sa, rdesc + (24 % NSLOT) * (SLOT >> 4));
            wg_wait<0>();
            pin(sa);
            {
                float x0, x1;
                new_max(sa, NJ0, x0, x1);
                n0 = x0; n1 = x1;
            }
            bar_arrive(6, 384);
            uint32_t vd = vdesc - (SLOT >> 4) * 65535u, kd = rdesc, vb = fbar + 8, kb = fbar;
            uint32_t vlast = vdesc - 4 * (SLOT >> 4) * 65535u, klast = rdesc + 4 * (SLOT >> 4) + 512;
            uint32_t kprev = fbar + 32, vprev = bars + (B_SINK - (B_EMPTY - B_FULL)) * 8;
#pragma unroll 1
            for (int it = 0; it < 4; it++) {
                both_issue(sb2, klast, pb, vlast);
                probs(sa, pa, mbar_test(vb, it < 2) & mbar_test(kb, it < 3), false, [&]() { mbar_wait(vb, it < 2); mbar_wait(kb, it < 3); });
                TS(41 + it * 4);
                if (lane == 0) mbar_arrive(kprev + (B_EMPTY - B_FULL) * 8);
                if (lane == 0) mbar_arrive(vprev + (B_EMPTY - B_FULL) * 8);
                both_issue(sa, kd, pa, vd);
                const int dv = it == 0 ? 2 : (it == 1 ? -3 : 1);
                kprev = kb; vprev = vb; vlast = vd - 512 * 65535u; klast = kd + 512;
                vd -= dv * (SLOT >> 4) * 65535u; vb += dv * 8;
                kd += (it == 2 ? -3 : 2) * (SLOT >> 4); kb = it == 2 ? vb : kb + 16;
                probs(sb2, pb, true, it == 3 && w == 1, []() {});
                TS(43 + it * 4);
            }
            wg_fence();
#pragma unroll
            for (int k = 0; k < 4; k++)
                mma_pv(o, pb[4 * k], pb[4 * k + 1], pb[4 * k + 2], pb[4 * k + 3], mkdesc(vlast - k * (128 * 65535) + (k > 1 ? w * ((k - 1) << 22) : 0)));
            wg_commit();
            const int row = wq * 16 + (lane >> 2);
            const uint32_t ml = sb + OFF_MISC;
            mbar_wait(bars + (B_RST + 1) * 8, 0);
            wg_wait<0>();
            pin(o); pin(pb); pin(sa); pin(sb2);
            if (!(LATE & 4)) rel(31);
            const float l0 = o[32], l1 = o[34];
            if (c4 == 0) { sts64f(ml + w * 512 + row * 8, n0, l0); sts64f(ml + w * 512 + row * 8 + 64, n1, l1); }
            TS(14);
            float mine[16];
#pragma unroll
            for (int j = 0; j < 4; j++) {
                if (w == 0) sts128f(H + j * 2048 + wt * 16, o[16 + 4 * j], o[17 + 4 * j], o[18 + 4 * j], o[19 + 4 * j]);
                else sts128f(H + 8192 + j * 2048 + wt * 16, o[4 * j], o[4 * j + 1], o[4 * j + 2], o[4 * j + 3]);
            }
#pragma unroll
            for (int i = 0; i < 16; i++) mine[i] = w == 0 ? o[i] : o[16 + i];
            bar_sync(10, 256);
            const float2 u0 = lds64f(ml + (w ^ 1) * 512 + row * 8), u1 = lds64f(ml + (w ^ 1) * 512 + row * 8 + 64);
            const float x0 = fminf(n0, u0.x), x1 = fminf(n1, u1.x);
            float a0 = ex2(x0 - n0), b0 = ex2(x0 - u0.x), a1 = ex2(x1 - n1), b1 = ex2(x1 - u1.x);
            const float i0 = __fdividef(1.f, fmaf(a0, l0, b0 * u0.y)), i1 = __fdividef(1.f, fmaf(a1, l1, b1 * u1.y));
            a0 *= i0; b0 *= i0; a1 *= i1; b1 *= i1;
            uint32_t pk[8];
#pragma unroll
            for (int j = 0; j < 4; j++) {
                const float4 v = lds128f(H + (w ^ 1) * 8192 + j * 2048 + wt * 16);
                pk[2 * j] = pack2(fmaf(a0, mine[4 * j], b0 * v.x), fmaf(a0, mine[4 * j + 1], b0 * v.y));
                pk[2 * j + 1] = pack2(fmaf(a1, mine[4 * j + 2], b1 * v.z), fmaf(a1, mine[4 * j + 3], b1 * v.w));
            }
            unsigned char* dst = g_o + (size_t)(b * 128 + qt * 8 + 2 * wq) * 4096 + ah * 1024 + w * 512 + lane * 16;
            st_data(dst, pk[0], pk[2], pk[4], pk[6]);
            st_data(dst + 4096, pk[1], pk[3], pk[5], pk[7]);
            if (tid == 0) asm volatile("red.relaxed.gpu.global.add.u32 [%0], 1;" ::"l"(&g_epoch[blockIdx.x * FS]) : "memory");
            TS(15);
        }

        {
            const uint32_t* dp = reinterpret_cast<const uint32_t*>(p.dw + (mir ? 14 * 256 : 0) + tile * 64) + lane;
#pragma unroll
            for (int i = 0; i < 15; i++) asm volatile("ld.global.nc.b32 %0, [%1];" : "=r"(dwr[i]) : "l"(dp + i * (mir ? -128 : 128)));
            acq(32); acq(33); acq(34);
            uint4 u[8];
            ld_data<512>(u, g_o + (size_t)(b * 128 + pt * 4 + wq) * 4096 + lane * 16);
#pragma unroll
            for (int i = 0; i < 8; i++) { a[4 * i] = u[i].x; a[4 * i + 1] = u[i].y; a[4 * i + 2] = u[i].z; a[4 * i + 3] = u[i].w; }
            if (LATE & 4) rel(31);
            TS(16);
            sp(d0, 32, a, 0, 0);
            sp(d0, 33, a + 16, 0, 1);
#pragma unroll
            for (int i = 0; i < 15; i++) dwr[i] = hmul2(dwr[i], 0x3F003F00u);
            residual(32);
            TS(17);
        }
    }

    cluster_arrive();
    TS(24);
    {
        const float rstd = rsq(fmaxf(fmaf(-mean, mean, msq), 0.f) + 1e-5f), nb = -mean * rstd;
#pragma unroll
        for (int j = 0; j < 8; j++) xr[j] = pack2(fmaf(v[2 * j], rstd, nb), fmaf(v[2 * j + 1], rstd, nb));
        const uint32_t stg = P + 16384 + warp * 1024;
        stsm4(stg + foff, xr[0], xr[1], xr[2], xr[3]);
        stsm4(stg + (foff ^ 64), xr[4], xr[5], xr[6], xr[7]);
        __syncwarp();
        const uint32_t src = stg + (lane >> 3) * 128 + (((lane & 7) ^ (lane >> 3)) << 4);
        const uint4 u0 = lds128(src), u1 = lds128((src + 512) ^ 64);
        __nv_bfloat16* dst = p.out + (size_t)(b * T_ + trow + (lane >> 3)) * 256 + tile * 64 + (lane & 7) * 8;
        if (trow < T_) { stg128(dst, u0); stg128(dst + 4 * 256, u1); }
    }
    TS(25);
    TG(31);
    TSDUMP();
    cluster_wait();
}

typedef CUresult (*EncodeFn)(CUtensorMap*, CUtensorMapDataType, cuuint32_t, void*, const cuuint64_t*, const cuuint64_t*,
                             const cuuint32_t*, const cuuint32_t*, CUtensorMapInterleave, CUtensorMapSwizzle,
                             CUtensorMapL2promotion, CUtensorMapFloatOOBfill);

}

extern "C" void kernel_launch(void* const* d_in, const int* in_sizes, int n_in, void* d_out, int out_size) {
    static EncodeFn encode = nullptr;
    if (!encode) {
        void* fn = nullptr;
        cudaDriverEntryPointQueryResult qr;
        cudaGetDriverEntryPoint("cuTensorMapEncodeTiled", &fn, cudaEnableDefault, &qr);
        encode = (EncodeFn)fn;
        cudaFuncSetAttribute(conformer_kernel, cudaFuncAttributeMaxDynamicSharedMemorySize, SMEM_LAUNCH);
    }
    Params p;
    const cuuint32_t ones[5] = {1, 1, 1, 1, 1};
    const int idx[8] = {1, 2, 3, 4, 5, 7, 8, 9};
    const int rows[8] = {256, 1024, 256, 256, 256, 256, 256, 1024};
    const int cols[8] = {1024, 256, 768, 256, 512, 256, 1024, 256};
    for (int i = 0; i < 8; i++) {
        const cuuint64_t pitch = (cuuint64_t)cols[i] * 2;
        const cuuint64_t dims[5] = {(cuuint64_t)cols[i], 2, 2, 4, (cuuint64_t)rows[i] / 16};
        const cuuint64_t strides[4] = {pitch, pitch * 8, pitch * 2, pitch * 16};
        const cuuint32_t box[5] = {64, 2, 2, 4, 8};
        encode(&p.tm[i], CU_TENSOR_MAP_DATA_TYPE_BFLOAT16, 5, d_in[idx[i]], dims, strides, box, ones, CU_TENSOR_MAP_INTERLEAVE_NONE,
               CU_TENSOR_MAP_SWIZZLE_128B, CU_TENSOR_MAP_L2_PROMOTION_L2_128B, CU_TENSOR_MAP_FLOAT_OOB_FILL_NONE);
        p.w[i] = (const char*)d_in[idx[i]];
    }
    {
        void* kv = nullptr;
        cudaGetSymbolAddress(&kv, g_kvq);
        const cuuint64_t dims[2] = {64, 16384};
        const cuuint64_t strides[1] = {128};
        const cuuint32_t box[2] = {64, 128};
        encode(&p.tm[8], CU_TENSOR_MAP_DATA_TYPE_BFLOAT16, 2, kv, dims, strides, box, ones, CU_TENSOR_MAP_INTERLEAVE_NONE,
               CU_TENSOR_MAP_SWIZZLE_NONE, CU_TENSOR_MAP_L2_PROMOTION_L2_128B, CU_TENSOR_MAP_FLOAT_OOB_FILL_NONE);
    }
    p.x = (const __nv_bfloat16*)d_in[0];
    p.dw = (const __nv_bfloat16*)d_in[6];
    p.out = (__nv_bfloat16*)d_out;
    p.zero = 0;
    conformer_kernel<<<NCTA, NTHREADS, SMEM_LAUNCH>>>(p);
}
```

```cpp
#include <cuda_runtime.h>
#include <cuda_bf16.h>
#include <cuda.h>
#include <stdint.h>

namespace {

constexpr int T_ = 1000;
constexpr int NCTA = 128;
constexpr int NTHREADS = 512;
constexpr int NSLOT = 5;
constexpr int SLOT = 16384;
constexpr int NLOADS = 56;

constexpr uint32_t OFF_RING = 0;
constexpr uint32_t OFF_P = 163840;
constexpr uint32_t OFF_H = 188416;
constexpr uint32_t OFF_MISC = 221184;
constexpr uint32_t OFF_BARS = 229888;
constexpr uint32_t SMEM_BYTES = 230400;
constexpr uint32_t GCH = 6144;
constexpr uint32_t HCH = 4096;

constexpr int B_FULL = 0, B_EMPTY = 10, B_XA = 20  , B_XB = 25  , B_INB = 29  , B_SR = 33,
              B_RST = 34  , B_RDY = 36  , B_SINK = 42, B_HALO = 43  , NBARS = 47;

#define KD2 300u
#define KD3 500u
#define QGATE 500u
#define BACKOFF 0u
#define KFS 8
#define KDELAY 300u
#define NJ0 2
#define HDELAY 200u
#define LATE 2
#define SND 0
#define TURN 0x200
#define EAGER 0x0155
constexpr int FS = 8;

struct Params {
    CUtensorMap tm[9];
    const char* w[8];
    const __nv_bfloat16* x;
    const __nv_bfloat16* dw;
    __nv_bfloat16* out;
    uint32_t zero;
};

__device__ __align__(1024) unsigned char g_kvq[3 * 8 * 1024 * 128];
__device__ __align__(1024) unsigned char g_o[2 * 128 * 4096];
__device__ uint4 g_halo[64 * 4 * 2 * 64];
__device__ __align__(128) uint32_t g_flag_kv[8 * 32 * KFS];
__device__ uint32_t g_reset[4 * 32];
__device__ uint32_t g_epoch[NCTA * FS];

#define TS(i) do { } while (0)
#define TSW(i) do { } while (0)
#define TG(i) do { } while (0)
#define TSINIT() do { } while (0)
#define TSDUMP() do { } while (0)
constexpr uint32_t SMEM_LAUNCH = SMEM_BYTES;

__device__ __forceinline__ uint32_t smem_u32(const void* p) { return (uint32_t)__cvta_generic_to_shared(p); }
__device__ __forceinline__ void mbar_init(uint32_t b, uint32_t c) { asm volatile("mbarrier.init.shared::cta.b64 [%0], %1;" ::"r"(b), "r"(c) : "memory"); }
__device__ __forceinline__ void mbar_arrive(uint32_t b) { asm volatile("mbarrier.arrive.shared::cta.b64 _, [%0];" ::"r"(b) : "memory"); }
__device__ __forceinline__ void mbar_arrive_tx(uint32_t b, uint32_t tx) { asm volatile("mbarrier.arrive.expect_tx.shared::cta.b64 _, [%0], %1;" ::"r"(b), "r"(tx) : "memory"); }
__device__ __forceinline__ void mbar_wait(uint32_t b, uint32_t ph) {
    asm volatile("{\n.reg .pred p, q;\n.reg .u32 c;\nmov.u32 c, 0;\n"
                 "MW_LOOP:\n.pragma \"nounroll\";\n"
                 "mbarrier.try_wait.parity.shared::cta.b64 p, [%0], %1;\n"
                 "add.u32 c, c, 1;\nsetp.lt.u32 q, c, 65536;\nnot.pred p, p;\nand.pred p, p, q;\n@p bra MW_LOOP;\n}"
                 ::"r"(b), "r"(ph) : "memory");
}
__device__ __forceinline__ bool mbar_test(uint32_t b, uint32_t ph) {
    uint32_t ok;
    asm volatile("{\n.reg .pred p;\nmbarrier.test_wait.parity.shared::cta.b64 p, [%1], %2;\nselp.u32 %0, 1, 0, p;\n}" : "=r"(ok) : "r"(b), "r"(ph) : "memory");
    return ok;
}
__device__ __forceinline__ uint32_t mapa(uint32_t a, uint32_t r) { uint32_t o; asm("mapa.shared::cluster.u32 %0, %1, %2;" : "=r"(o) : "r"(a), "r"(r)); return o; }
__device__ __forceinline__ void fence_async_smem() { asm volatile("fence.proxy.async.shared::cta;" ::: "memory"); }
__device__ __forceinline__ void fence_async_global() { asm volatile("fence.proxy.async.global;" ::: "memory"); }
__device__ __forceinline__ void bar_sync(int id, int n) { asm volatile("bar.sync %0, %1;" ::"r"(id), "r"(n) : "memory"); }
__device__ __forceinline__ void bar_arrive(int id, int n) { asm volatile("bar.arrive %0, %1;" ::"r"(id), "r"(n) : "memory"); }
__device__ __forceinline__ void cluster_arrive() { asm volatile("barrier.cluster.arrive.relaxed.aligned;" ::: "memory"); }
__device__ __forceinline__ void cluster_wait() { asm volatile("barrier.cluster.wait.aligned;" ::: "memory"); }

__device__ __forceinline__ void ring_load(uint32_t dst, const CUtensorMap* tm, int col, int row16, uint32_t bar) {
    asm volatile("{\n.reg .pred p;\nelect.sync _|p, 0xffffffff;\n"
                 "@p mbarrier.arrive.expect_tx.shared::cta.b64 _, [%2], 16384;\n"
                 "@p cp.async.bulk.tensor.5d.shared::cluster.global.mbarrier::complete_tx::bytes [%0], [%1, {%3, 0, 0, 0, %4}], [%2];\n}"
                 ::"r"(dst), "l"(tm), "r"(bar), "r"(col), "r"(row16) : "memory");
}
__device__ __forceinline__ void ring_load_both(uint32_t dst, const CUtensorMap* tm, int c1, uint32_t bar) {
    asm volatile("{\n.reg .pred p;\nelect.sync _|p, 0xffffffff;\n"
                 "@p cp.async.bulk.tensor.2d.shared::cluster.global.mbarrier::complete_tx::bytes.multicast::cluster [%0], [%1, {0, %3}], [%2], %4;\n}"
                 ::"r"(dst), "l"(tm), "r"(bar), "r"(c1), "h"((uint16_t)3) : "memory");
}
__device__ __forceinline__ void mbar_arrive_peer(uint32_t b) { asm volatile("mbarrier.arrive.relaxed.cluster.shared::cluster.b64 _, [%0];" ::"r"(b) : "memory"); }
__device__ __forceinline__ void prefetch_l2(const void* src, uint32_t bytes) {
    asm volatile("cp.async.bulk.prefetch.L2.global [%0], %1;" ::"l"(src), "r"(bytes) : "memory");
}
__device__ __forceinline__ void peer_copy(uint32_t dst, uint32_t src, uint32_t bytes, uint32_t rbar) {
    asm volatile("{\n.reg .pred p;\nelect.sync _|p, 0xffffffff;\n"
                 "@p cp.async.bulk.shared::cluster.shared::cta.mbarrier::complete_tx::bytes [%0], [%1], %2, [%3];\n}"
                 ::"r"(dst), "r"(src), "r"(bytes), "r"(rbar) : "memory");
}
__device__ __forceinline__ void st_async4(uint32_t dst, uint32_t a, uint32_t b, uint32_t c, uint32_t d, uint32_t bar) {
    asm volatile("st.async.shared::cluster.mbarrier::complete_tx::bytes.v4.b32 [%0], {%1,%2,%3,%4}, [%5];" ::"r"(dst), "r"(a), "r"(b), "r"(c), "r"(d), "r"(bar) : "memory");
}
__device__ __forceinline__ void put_sums(uint32_t dst, uint32_t rdst, float a, float b, uint32_t rbar, bool on) {
    asm volatile("{\n.reg .pred p;\nsetp.ne.u32 p, %5, 0;\n"
                 "@p st.async.shared::cluster.mbarrier::complete_tx::bytes.v2.f32 [%1], {%2,%3}, [%4];\n"
                 "@p st.shared.v2.f32 [%0], {%2,%3};\n}" ::"r"(dst), "r"(rdst), "f"(a), "f"(b), "r"(rbar), "r"((uint32_t)on) : "memory");
}
__device__ __forceinline__ void stsm4(uint32_t a, uint32_t r0, uint32_t r1, uint32_t r2, uint32_t r3) {
    asm volatile("stmatrix.sync.aligned.m8n8.x4.shared.b16 [%0], {%1,%2,%3,%4};" ::"r"(a), "r"(r0), "r"(r1), "r"(r2), "r"(r3) : "memory");
}
__device__ __forceinline__ void ldsm4(uint32_t a, uint32_t& r0, uint32_t& r1, uint32_t& r2, uint32_t& r3) {
    asm volatile("ldmatrix.sync.aligned.m8n8.x4.shared.b16 {%0,%1,%2,%3}, [%4];" : "=r"(r0), "=r"(r1), "=r"(r2), "=r"(r3) : "r"(a) : "memory");
}
__device__ __forceinline__ uint4 lds128(uint32_t a) { uint4 v; asm volatile("ld.shared.v4.b32 {%0,%1,%2,%3}, [%4];" : "=r"(v.x), "=r"(v.y), "=r"(v.z), "=r"(v.w) : "r"(a) : "memory"); return v; }
__device__ __forceinline__ float4 lds128f(uint32_t a) { float4 v; asm volatile("ld.shared.v4.f32 {%0,%1,%2,%3}, [%4];" : "=f"(v.x), "=f"(v.y), "=f"(v.z), "=f"(v.w) : "r"(a) : "memory"); return v; }
__device__ __forceinline__ float2 lds64f(uint32_t a) { float2 v; asm volatile("ld.shared.v2.f32 {%0,%1}, [%2];" : "=f"(v.x), "=f"(v.y) : "r"(a) : "memory"); return v; }
__device__ __forceinline__ uint32_t lds32(uint32_t a) { uint32_t v; asm volatile("ld.shared.b32 %0, [%1];" : "=r"(v) : "r"(a) : "memory"); return v; }
__device__ __forceinline__ void sts128(uint32_t a, uint32_t x, uint32_t y, uint32_t z, uint32_t w) { asm volatile("st.shared.v4.b32 [%0], {%1,%2,%3,%4};" ::"r"(a), "r"(x), "r"(y), "r"(z), "r"(w) : "memory"); }
__device__ __forceinline__ void sts128f(uint32_t a, float x, float y, float z, float w) { asm volatile("st.shared.v4.f32 [%0], {%1,%2,%3,%4};" ::"r"(a), "f"(x), "f"(y), "f"(z), "f"(w) : "memory"); }
__device__ __forceinline__ void sts64f(uint32_t a, float x, float y) { asm volatile("st.shared.v2.f32 [%0], {%1,%2};" ::"r"(a), "f"(x), "f"(y) : "memory"); }
__device__ __forceinline__ void sts32(uint32_t a, uint32_t x) { asm volatile("st.shared.b32 [%0], %1;" ::"r"(a), "r"(x) : "memory"); }
__device__ __forceinline__ void stg128(void* p, uint4 v) { asm volatile("st.global.v4.b32 [%0], {%1,%2,%3,%4};" ::"l"(p), "r"(v.x), "r"(v.y), "r"(v.z), "r"(v.w) : "memory"); }

__device__ __forceinline__ uint32_t pack2(float lo, float hi) { uint32_t r; asm("cvt.rn.bf16x2.f32 %0, %1, %2;" : "=r"(r) : "f"(hi), "f"(lo)); return r; }
__device__ __forceinline__ float blo(uint32_t v) { return __uint_as_float(v << 16); }
__device__ __forceinline__ float bhi(uint32_t v) { return __uint_as_float(v & 0xffff0000u); }
__device__ __forceinline__ uint32_t hmul2(uint32_t a, uint32_t b) { uint32_t r; asm("mul.rn.bf16x2 %0, %1, %2;" : "=r"(r) : "r"(a), "r"(b)); return r; }
__device__ __forceinline__ uint32_t hadd2(uint32_t a, uint32_t b) { uint32_t r; asm("add.rn.bf16x2 %0, %1, %2;" : "=r"(r) : "r"(a), "r"(b)); return r; }
__device__ __forceinline__ uint32_t hsub2(uint32_t a, uint32_t b) { uint32_t r; asm("sub.rn.bf16x2 %0, %1, %2;" : "=r"(r) : "r"(a), "r"(b)); return r; }
__device__ __forceinline__ uint32_t hfma2(uint32_t a, uint32_t b, uint32_t c) { uint32_t r; asm("fma.rn.bf16x2 %0, %1, %2, %3;" : "=r"(r) : "r"(a), "r"(b), "r"(c)); return r; }
__device__ __forceinline__ float tanh_fast(float x) { float r; asm("tanh.approx.f32 %0, %1;" : "=f"(r) : "f"(x)); return r; }
__device__ __forceinline__ float rsq(float x) { float r; asm("rsqrt.approx.ftz.f32 %0, %1;" : "=f"(r) : "f"(x)); return r; }
__device__ __forceinline__ float ex2(float x) { float r; asm("ex2.approx.ftz.f32 %0, %1;" : "=f"(r) : "f"(x)); return r; }

__device__ __forceinline__ uint32_t ld_relaxed(const uint32_t* p) {
    uint32_t v;
    asm volatile("ld.relaxed.gpu.global.u32 %0, [%1];" : "=r"(v) : "l"(p) : "memory");
    return v;
}
__device__ __forceinline__ uint32_t clock32() { uint32_t c; asm volatile("mov.u32 %0, %%clock;" : "=r"(c)::"memory"); return c; }
__device__ __forceinline__ void spin(uint32_t clks) {
    const uint32_t t0 = clock32();
    while (clock32() - t0 < clks) {}
}
__device__ __forceinline__ void flag_wait(const uint32_t* p, uint32_t e, bool mine) {
#pragma unroll 1
    for (int i = 0; i < (1 << 19); i++) {
        if (mine) mine = ld_relaxed(p) != e;
        if (!__any_sync(~0u, mine)) break;
        if (BACKOFF) spin(BACKOFF);
    }
    asm volatile("fence.acquire.gpu;" ::: "memory");
    fence_async_global();
}
__device__ __forceinline__ void st_data(void* p, uint32_t x, uint32_t y, uint32_t z, uint32_t w) {
    asm volatile("st.relaxed.gpu.global.v4.b32 [%0], {%1,%2,%3,%4};" ::"l"(p), "r"(x), "r"(y), "r"(z), "r"(w) : "memory");
}
template <int STRIDE, int N>
__device__ __forceinline__ void ld_data(uint4 (&v)[N], const unsigned char* p) {
    int it = 0;
    bool again;
#pragma unroll 1
    do {
        uint32_t m = 0;
#pragma unroll
        for (int i = 0; i < N; i++)
            asm volatile("ld.relaxed.gpu.global.v4.b32 {%0,%1,%2,%3}, [%4];" : "=r"(v[i].x), "=r"(v[i].y), "=r"(v[i].z), "=r"(v[i].w) : "l"(p + i * STRIDE) : "memory");
#pragma unroll
        for (int i = 0; i < N; i++) m = __vimax3_u32(__vimax3_u32(v[i].x, v[i].y, v[i].z), v[i].w, m);
        again = __any_sync(~0u, m == ~0u) && ++it < (1 << 16);
    } while (again);
}
__device__ __forceinline__ uint32_t ld_epoch() { return ld_relaxed(&g_epoch[blockIdx.x * FS]) + 1; }
__device__ __forceinline__ void flag_set(uint32_t* p, uint32_t e) { asm volatile("st.release.gpu.global.u32 [%0], %1;" ::"l"(p), "r"(e) : "memory"); }

__device__ __forceinline__ uint32_t desc_lo(uint32_t addr) { return ((addr & 0x3FFFF) >> 4) | 0x10000u; }
__device__ __forceinline__ uint64_t mkdesc(uint32_t lo) { return (uint64_t)lo | (0x40000040ull << 32); }
__device__ __forceinline__ void wg_fence() { asm volatile("wgmma.fence.sync.aligned;" ::: "memory"); }
__device__ __forceinline__ void wg_commit() { asm volatile("wgmma.commit_group.sync.aligned;" ::: "memory"); }
template <int N> __device__ __forceinline__ void wg_wait() { asm volatile("wgmma.wait_group.sync.aligned %0;" ::"n"(N) : "memory"); }
template <int N> __device__ __forceinline__ void pin(float (&d)[N]) {
#pragma unroll
    for (int i = 0; i < N; i++) asm volatile("" : "+f"(d[i])::"memory");
}
template <int N> __device__ __forceinline__ void pin(uint32_t (&d)[N]) {
#pragma unroll
    for (int i = 0; i < N; i++) asm volatile("" : "+r"(d[i])::"memory");
}

template <typename Tp, int N> __device__ __forceinline__ void zero(Tp (&d)[N]) {
#pragma unroll
    for (int i = 0; i < N; i++) d[i] = 0;
    pin(d);
}

#define F4(d, i) "+f"(d[i]), "+f"(d[i + 1]), "+f"(d[i + 2]), "+f"(d[i + 3])
#define F16(d, i) F4(d, i), F4(d, i + 4), F4(d, i + 8), F4(d, i + 12)

__device__ __forceinline__ void mma16(float (&d)[4], const uint32_t* a, uint32_t b0, uint32_t b1) {
    asm("mma.sync.aligned.m16n8k16.row.col.f32.bf16.bf16.f32 {%0,%1,%2,%3}, {%4,%5,%6,%7}, {%8,%9}, {%0,%1,%2,%3};"
        : F4(d, 0) : "r"(a[0]), "r"(a[1]), "r"(a[2]), "r"(a[3]), "r"(b0), "r"(b1));
}
template <int N>
__device__ __forceinline__ void row_sums(const uint32_t* x, int lane, float& s, float& q) {
    float cs[4] = {}, c0[4] = {}, c1[4] = {};
#pragma unroll
    for (int i = 0; i < N; i += 4) {
        mma16(cs, x + i, 0x3F803F80u, 0x3F803F80u);
        mma16(c0, x + i, x[i], x[i + 2]);
        mma16(c1, x + i, x[i + 1], x[i + 3]);
    }
    s = cs[0] + cs[2];
    q = (lane & 4) ? c0[1] + c1[3] : c0[0] + c1[2];
}
__device__ __forceinline__ void mma_sp(float (&d)[32], const uint32_t* a, uint64_t b, uint32_t meta, int acc) {
    asm volatile("{.reg .pred p; setp.ne.b32 p, %38, 0;\n"
                 "wgmma.mma_async.sp.sync.aligned.m64n64k32.f32.bf16.bf16 {%0,%1,%2,%3,%4,%5,%6,%7,%8,%9,%10,%11,%12,%13,%14,%15,%16,%17,%18,%19,%20,%21,%22,%23,%24,%25,%26,%27,%28,%29,%30,%31}, "
                 "{%32,%33,%34,%35}, %36, %37, 0, p, 1, 1, 1;}\n"
                 : F16(d, 0), F16(d, 16) : "r"(a[0]), "r"(a[1]), "r"(a[2]), "r"(a[3]), "l"(b), "r"(meta), "r"(acc));
}
__device__ __forceinline__ void mma_qk(float (&d)[32], uint32_t a0, uint32_t a1, uint32_t a2, uint32_t a3, uint64_t b, int acc) {
    asm volatile("{.reg .pred p; setp.ne.b32 p, %37, 0;\n"
                 "wgmma.mma_async.sync.aligned.m64n64k16.f32.bf16.bf16 {%0,%1,%2,%3,%4,%5,%6,%7,%8,%9,%10,%11,%12,%13,%14,%15,%16,%17,%18,%19,%20,%21,%22,%23,%24,%25,%26,%27,%28,%29,%30,%31}, "
                 "{%32,%33,%34,%35}, %36, p, 1, 1, 0;}\n"
                 : F16(d, 0), F16(d, 16) : "r"(a0), "r"(a1), "r"(a2), "r"(a3), "l"(b), "r"(acc));
}
__device__ __forceinline__ void mma_pv(float (&d)[36], uint32_t a0, uint32_t a1, uint32_t a2, uint32_t a3, uint64_t b) {
    asm volatile("wgmma.mma_async.sync.aligned.m64n72k16.f32.bf16.bf16 {%0,%1,%2,%3,%4,%5,%6,%7,%8,%9,%10,%11,%12,%13,%14,%15,%16,%17,%18,%19,%20,%21,%22,%23,%24,%25,%26,%27,%28,%29,%30,%31,%32,%33,%34,%35}, "
                 "{%36,%37,%38,%39}, %40, 1, 1, 1, 1;\n"
                 : F16(d, 0), F16(d, 16), F4(d, 32) : "r"(a0), "r"(a1), "r"(a2), "r"(a3), "l"(b));
}

__device__ __forceinline__ uint32_t load_code(int n, int r, int w) {
    const int tile = 2 * r + w;
    int m, col, row;
    if (n < 16 || n >= 40) {
        const int k = n < 16 ? n : n - 40;
        m = n < 16 ? 0 : 6;
        if (k < 8) { col = 4 * tile + (k >> 1); row = n < 16 ? (k & 1) : (k & 1) ^ r; }
        else { m++; col = k < 12 ? tile ^ 2 : tile; row = 2 * (tile ^ (k & 1)) + ((k >> 1) & 1); }
    } else if (n < 32) {
        const int k = n - 16;
        m = 2;
        if (k < 4) { col = tile + ((k & 1) ? 8 : 4); row = (k >> 1) ^ r; }
        else { col = tile; row = (k & 1) ^ r; }
    } else if (n < 34) { m = 3; col = tile; row = n - 32; }
    else if (n < 38) { const int k = n - 34; m = 4; col = tile + 4 * (k & 1); row = (k >> 1) ^ r; }
    else { m = 5; col = tile; row = (n & 1) ^ r; }
    return m | (col << 4) | (row << (m ? 11 : 10));
}

__global__ void __cluster_dims__(2, 1, 1) __launch_bounds__(NTHREADS, 1)
conformer_kernel(const __grid_constant__ Params p) {
    extern __shared__ __align__(1024) unsigned char smem_raw[];
    const uint32_t sb = smem_u32(smem_raw);
    const uint32_t bars = sb + OFF_BARS;
    const int tid = threadIdx.x;
    const int lane = tid & 31;
    const int warp = __shfl_sync(~0u, tid >> 5, 0);
    const int r = blockIdx.x & 1;
    const int pair = blockIdx.x >> 1;
    const int b = pair >> 5, pt = pair & 31;
    const int ah = pt >> 3, qt = (pt & 7) * 2 + r;
    const int abh = b * 4 + ah;

    TG(30);
    TSINIT();
    TS(0);
    const uint32_t P = sb + OFF_P, H = sb + OFF_H;
    if ((warp >> 1) == 4) {
        const uint32_t full = bars + (B_FULL + (warp & 1) * NSLOT) * 8;
        if (lane == 0) {
#pragma unroll
            for (int i = 0; i < NSLOT; i++) { mbar_init(full + i * 8, 1); mbar_init(full + (B_EMPTY - B_FULL + i) * 8, 4); }
            asm volatile("fence.mbarrier_init.release.cluster;" ::: "memory");
            fence_async_smem();
        }
        __syncwarp();
#pragma unroll
        for (int n = 0; n < 2; n++)
            ring_load(sb + OFF_RING + ((warp & 1) * NSLOT + n) * SLOT, &p.tm[0], 64 * (8 * r + 4 * (warp & 1)), 4 * n, full + n * 8);
        cluster_arrive();
        TS(1);
    }

    if (warp >= 8) {
        asm volatile("setmaxnreg.dec.sync.aligned.u32 48;");
        if (warp >= 12) {
            cluster_arrive();
            cluster_wait();
            const int ut = tid & 127;
            const uint32_t target = ld_epoch() * 64;
            auto reset_done = [&](int k) {
                bar_sync(11, 128);
                if (ut == 0) {
                    asm volatile("red.release.gpu.global.add.u32 [%0], 1;" ::"l"(&g_reset[(2 * b + k) * 32]) : "memory");
#pragma unroll 1
                    for (int i = 0; i < (1 << 20) && ld_relaxed(&g_reset[(2 * b + k) * 32]) != target; i++) __nanosleep(100);
                    asm volatile("fence.acquire.gpu;" ::: "memory");
                    mbar_arrive(bars + (B_RST + k) * 8);
                }
                __syncwarp();
                TS(13 + k);
            };
#pragma unroll
            for (int i = 0; i < 4; i++)
                st_data(g_kvq + 2097152 + (size_t)((b * 4 + 2 * r + (i >> 1)) * 1024 + pt * 32) * 128 + (i & 1) * 2048 + ut * 16, ~0u, ~0u, ~0u, ~0u);
            reset_done(0);
            bar_sync(6, 384);
#pragma unroll
            for (int i = 0; i < 4; i++) {
                st_data(g_o + (size_t)(b * 128 + qt * 8 + 2 * i + (ut >> 6)) * 4096 + ah * 1024 + (ut & 63) * 16, ~0u, ~0u, ~0u, ~0u);
                if (i < 2) st_data(&g_halo[(pair * 4 + 2 * r + i) * 128 + ut], ~0u, ~0u, ~0u, ~0u);
            }
            reset_done(1);
            const int side = warp & 1, wg = (warp >> 1) & 1, np = side ? pt + 1 : pt - 1;
            const unsigned char* src = reinterpret_cast<const unsigned char*>(&g_halo[(((b * 32 + np) * 4 + 2 * r + wg) * 2 + (side ^ 1)) * 64 + lane]);
            const uint32_t dst = H + 16384 + wg * GCH + side * 5120 + (lane & 7) * 128 + (((lane >> 3) ^ (lane & 7)) << 4);
            uint4 hv[2] = {make_uint4(0, 0, 0, 0), make_uint4(0, 0, 0, 0)};
            bar_sync(8 + wg, 192);
            if (np >= 0 && np < 32) {
                spin(HDELAY);
                ld_data<512>(hv, src);
            }
            stsm4(dst, hv[0].x, hv[0].y, hv[0].z, hv[0].w);
            stsm4(dst ^ 64, hv[1].x, hv[1].y, hv[1].z, hv[1].w);
            __syncwarp();
            if (lane == 0) mbar_arrive(bars + (B_HALO + (warp & 3)) * 8);
            TS(4);
        } else if (warp < 10) {
            const int w = warp - 8;
            const uint32_t ring = sb + OFF_RING + w * NSLOT * SLOT;
            const uint32_t full = bars + (B_FULL + w * NSLOT) * 8;
            bar_sync(12, 64);
#pragma unroll
            for (int n = 2; n < NSLOT; n++) ring_load(ring + n * SLOT, &p.tm[0], 64 * (8 * r + 4 * w + (n >> 1)), 4 * (n & 1), full + n * 8);
            TS(2);
            const uint32_t code = load_code(lane, r, w) | (load_code(lane + 32, r, w) << 16);
            cluster_wait();
            uint32_t s = 0, ph = 0;
            int n = NSLOT;
#pragma unroll 1
            for (int seg = 0; seg < 2; seg++) {
#pragma unroll 1
                for (; n < (seg == 0 ? 22 : NLOADS); n++) {
                    const uint32_t c = __shfl_sync(~0u, code, n) >> (n & 32 ? 16 : 0);
                    const CUtensorMap* tm = &p.tm[c & 15];
                    const uint32_t col = (c & 0xf0) * 4, row = (c & 0xff00) >> 8, dst = ring + s * SLOT;
                    mbar_wait(full + (B_EMPTY - B_FULL) * 8 + s * 8, ph + (((uint32_t)(size_t)tm | col | row | dst) & p.zero));
                    ring_load(dst, tm, col, row, full + s * 8);
                    if (++s == NSLOT) { s = 0; ph ^= 1; }
                }
                if (seg == 1) break;
                const uint32_t epoch = ld_epoch();
                const uint32_t rdy = bars + (B_RDY + 3 * w) * 8, prdy = mapa(rdy, r ^ 1);
                const int odd = r ^ w;
                const uint32_t* flags = g_flag_kv + (abh * 32 + lane) * KFS;
                auto kv_load = [&](uint32_t sl, int isv, int i) {
                    ring_load_both(ring + sl * SLOT, &p.tm[8], (isv * 64 + abh * 8 + 2 * i + w) * 128, full + sl * 8);
                };
#pragma unroll 1
                for (int i = 0; i < 2; i++) {
                    if (lane < 3 + i) {
                        const uint32_t sl = i ? lane : lane + 2;
                        mbar_wait(full + (B_EMPTY - B_FULL + sl) * 8, i ^ 1);
                        mbar_arrive_tx(full + sl * 8, (i || lane == 2) ? SLOT : 0);
                    }
                    __syncwarp();
                }
                if (lane == 0) mbar_arrive_peer(prdy);
                bar_sync(14, 96);
                spin(KDELAY);
                mbar_wait(rdy, 0);
                flag_wait(flags, epoch, (lane >> 2) == 2 * odd + w);
                TSW(5 + 2 * odd);
                if (!odd) { kv_load(4, 0, 0); bar_arrive(12, 64); }
                else bar_sync(12, 64);
                spin(w ? KD3 : KD2);
                kv_load(odd ^ 1, odd ^ 1, odd);
                flag_wait(flags, epoch, (lane >> 2) == 2 * odd + w + 4);
                mbar_wait(full + (odd ^ 1) * 8, 1);
                kv_load(2 + odd, odd, 2 - odd);
#pragma unroll 1
                for (int i = 0; i < 3; i++) {
                    const uint32_t sl = i ? i - 1 : 4, bo = i == 2 ? 16 : 8;
                    mbar_wait(full + (B_EMPTY - B_FULL + sl) * 8, i != 0);
                    if (lane == 0) mbar_arrive_tx(full + sl * 8, SLOT);
                    if ((i & 1) != odd) {
                        mbar_wait(rdy + bo, 0);
                        kv_load(sl, i != 0, 2 + odd);
                    } else if (lane == 0) mbar_arrive_peer(prdy + bo);
                    __syncwarp();
                }
                n = 32; s = 2; ph = 1;
            }
        } else if (warp == 10) {
            if (lane == 0) {
#pragma unroll
                for (int i = B_XA; i < NBARS; i++) mbar_init(bars + i * 8, 1);
#pragma unroll
                for (int i = B_XA; i <= B_SR; i++) mbar_arrive_tx(bars + i * 8, i < B_XB ? 512 : ((i >= B_INB && i < B_SR) ? 4096 : 8192));
                asm volatile("fence.mbarrier_init.release.cluster;" ::: "memory");
                fence_async_smem();
            }
            __syncwarp();
            cluster_arrive();
            cluster_wait();
        } else {
            const uint32_t kb = (lane < 2 || lane > 5) ? 4096 : (lane == 2 ? 3072 : (lane == 4 ? 2048 : 1024));
            const char* pf = p.w[lane & 7] + blockIdx.x * kb;
            cluster_arrive();
            cluster_wait();
            if (lane < 2) prefetch_l2(pf, kb);
            mbar_wait(bars + B_FULL * 8, 0);
            if (lane == 2) prefetch_l2(pf, kb);
            if (lane >= 1 && lane < 9) asm volatile("prefetch.tensormap [%0];" ::"l"(&p.tm[lane]) : "memory");
            mbar_wait(bars + (B_FULL + 1) * 8, 1);
            if (lane > 2 && lane < 8) prefetch_l2(pf, kb);
            if (lane == 8 && blockIdx.x < 15) prefetch_l2(p.dw + blockIdx.x * 256, 512);
            const uint32_t epoch = ld_epoch();
            bar_sync(4, 288);
            if (lane < 16) flag_set(&g_flag_kv[((b * 4 + 2 * r + (lane >> 3)) * 32 + pt) * KFS + (lane & 7)], epoch);
            __syncwarp();
            bar_arrive(14, 96);
            TSW(8);
        }
        TSDUMP();
        return;
    }

    const int w = warp >> 2, wq = warp & 3;
    const int tile = 2 * r + w;
    const int wt = tid & 127;
    const int c4 = lane & 3;
    const int trow = pt * 32 + 8 * wq;
    uint32_t xr[8];
    uint32_t a[32];
    {
        const __nv_bfloat16* xrow = p.x + (size_t)(b * T_ + trow + (lane >> 2)) * 256;
#pragma unroll
        for (int i = 0; i < 8; i++) {
            const uint4 u = trow < T_ ? __ldg(reinterpret_cast<const uint4*>(xrow) + 4 * i + c4) : make_uint4(0, 0, 0, 0);
            a[4 * i] = u.x; a[4 * i + 1] = u.y; a[4 * i + 2] = u.z; a[4 * i + 3] = u.w;
        }
#pragma unroll
        for (int j = 0; j < 8; j++) xr[j] = trow < T_ ? __ldg(reinterpret_cast<const uint32_t*>(xrow + tile * 64) + 4 * j + c4) : 0u;
    }
    cluster_arrive();
    asm volatile("setmaxnreg.inc.sync.aligned.u32 208;");
    const uint32_t rbase = sb + OFF_RING + w * NSLOT * SLOT, fbar = bars + (B_FULL + w * NSLOT) * 8;
    const uint32_t rdesc = desc_lo(rbase);
    auto acq = [&](int n) { mbar_wait(fbar + (n % NSLOT) * 8, (n / NSLOT) & 1); };
    auto rel = [&](int n) { if (lane == 0) mbar_arrive(fbar + (B_EMPTY - B_FULL + n % NSLOT) * 8); };
    const uint32_t foff = (lane & 7) * 128 + (((lane >> 3) ^ (lane & 7)) << 4);
    float v[16];
    const uint32_t xown = __shfl_sync(~0u, P + wt * 16 + tile * 4096, lane), xrem = __shfl_sync(~0u, P + wt * 16 + (r ^ 1) * 8192, lane);
    const uint32_t sbuf = __shfl_sync(~0u, sb + OFF_MISC + 1024 + (8 * wq + (lane >> 2)) * 32, lane);
    const uint32_t sown = __shfl_sync(~0u, sbuf + tile * 8, lane);
    const uint32_t peer = __shfl_sync(~0u, mapa(sb, r ^ 1) - sb, lane);
    const uint32_t hbuf = __shfl_sync(~0u, H + w * 4096 + wt * 16, lane);
    const uint32_t meta = __shfl_sync(~0u, 0xEEEE4444u + p.zero, lane);
    cluster_wait();
    TS(56);
    float mean, msq;
    const int mir = wq < 2 ? 7 : 0;
    uint32_t dwr[15] = {};

#pragma unroll
    for (int ph = 0; ph < 5; ph++) {
        uint4 o0, o1;
        if (ph == 0) {
            float s, q, s2, q2;
            row_sums<16>(a, lane, s, q);
            row_sums<16>(a + 16, lane, s2, q2);
            mean = (s + s2) * (1.f / 256.f);
            msq = __shfl_sync(~0u, q + q2, (lane & 28) + (lane >> 3)) * (1.f / 256.f);
            TS(57);
        } else {
            const uint32_t xa = bars + (B_XA + ph) * 8;
#pragma unroll
            for (int j = 0; j < 8; j++) xr[j] = pack2(v[2 * j], v[2 * j + 1]);
            float s, q;
            row_sums<8>(xr, lane, s, q);
            if (ph < 4) {
                sts128(xown, xr[0], xr[1], xr[2], xr[3]);
                sts128(xown + 2048, xr[4], xr[5], xr[6], xr[7]);
            }
            put_sums(sown, sown + peer, s, q, xa + peer, c4 == (lane >> 3));
            bar_sync(10, 256);
            if (ph < 4) {
                o0 = lds128(xown ^ 4096); o1 = lds128((xown ^ 4096) + 2048);
                st_async4(xown + peer, xr[0], xr[1], xr[2], xr[3], xa + (B_XB - B_XA) * 8 + peer);
                st_async4(xown + peer + 2048, xr[4], xr[5], xr[6], xr[7], xa + (B_XB - B_XA) * 8 + peer);
            }
            TS(57 + ph);
            if (ph == 3) acq(0);
            if (ph == 1) acq(16);
            mbar_wait(xa, 0);
            const float4 u0 = lds128f(sbuf), u1 = lds128f(sbuf + 16);
            mean = ((u0.x + u0.z) + (u1.x + u1.z)) * (1.f / 256.f);
            msq = ((u0.y + u0.w) + (u1.y + u1.w)) * (1.f / 256.f);
        }
        if (ph == 4) break;
        const uint32_t mean2 = pack2(mean, mean);
        auto centre = [&](int i, const uint4& u) {
            a[i] = hsub2(u.x, mean2); a[i + 1] = hsub2(u.y, mean2); a[i + 2] = hsub2(u.z, mean2); a[i + 3] = hsub2(u.w, mean2);
        };
        if (ph == 0) {
#pragma unroll
            for (int j = 0; j < 32; j++) a[j] = hsub2(a[j], mean2);
            pin(a);
            acq(0);
        } else {
#pragma unroll
            for (int j = 0; j < 8; j++) a[j] = hsub2(xr[j], mean2);
            centre(8, o0); centre(12, o1);
        }
        const float rstd = rsq(fmaxf(fmaf(-mean, mean, msq), 0.f) + 1e-5f);
        auto gather_peer = [&]() {
            mbar_wait(bars + (B_XB + ph) * 8, 0);
#pragma unroll
            for (int i = 0; i < 4; i++) centre(16 + 4 * i, lds128(xrem + i * 2048));
        };
        auto sp = [&](float (&d)[32], int n, const uint32_t* af, int flip, int acc) {
            const uint32_t lo = rdesc + p.zero * (ph * 64 + n + 1) + (n % NSLOT) * (SLOT >> 4);
            const uint64_t b0 = mkdesc(lo + flip * 512), b1 = mkdesc(lo + (flip ^ 1) * 512);
            wg_fence();
            mma_sp(d, af, b0, meta, acc);
            mma_sp(d, af + 4, b0 + 256, meta, 1);
            mma_sp(d, af + 8, b1, meta, 1);
            mma_sp(d, af + 12, b1 + 256, meta, 1);
            wg_commit();
        };
        float d0[32], d1[32];

        if (ph == 0 || ph == 3) {
            uint32_t h[32], ho[32];
            const float rs = 0.5f * rstd;
            const uint32_t inb = bars + (B_INB + (ph & 2) + w) * 8;
            bool ready = true;
            const int eager = ph ? EAGER : EAGER - 1;
            auto step = [&](float (&d)[32], int n, const uint32_t* af, int flip, int acc, auto work) {
                if (!ready) acq(n);
                if (((TURN >> n) & 1) && w == 1) bar_sync(7, 256);
                sp(d, n, af, flip, acc);
                if (n > 0 && ((TURN >> (n - 1)) & 1) && w == 0) bar_arrive(7, 256);
                if (n < 15) ready = mbar_test(fbar + ((n + 1) % NSLOT) * 8, ((n + 1) / NSLOT) & 1);
                wg_wait<1>();
                if (n > 0 && !((eager >> (n - 1)) & 1)) rel(n - 1);
                const uint32_t tie = work() & p.zero;
                if ((eager >> n) & 1) {
                    if (p.zero < n + ph + 1) wg_wait<0>();
                    if (lane == 0) mbar_arrive(fbar + (B_EMPTY - B_FULL + n % NSLOT) * 8 + tie);
                }
            };
            auto none = []() { return 0u; };
            const int fl = ph ? w : 0;
            auto fetch = [&](int i) {
                bar_sync(10, 256);
                const uint4 u0 = lds128((hbuf ^ 4096) + (i & 1) * 8192), u1 = lds128((hbuf ^ 4096) + (i & 1) * 8192 + 2048);
                ho[8 * i] = u0.x; ho[8 * i + 1] = u0.y; ho[8 * i + 2] = u0.z; ho[8 * i + 3] = u0.w;
                ho[8 * i + 4] = u1.x; ho[8 * i + 5] = u1.y; ho[8 * i + 6] = u1.z; ho[8 * i + 7] = u1.w;
                return u0.x | u1.x;
            };
            auto act = [&](float (&d)[32], int i) {
                if (i > 0) fetch(i - 1);
                pin(d);
#pragma unroll
                for (int j = 0; j < 8; j++) {
                    const float u0 = (d[4 * j] + d[4 * j + 2]) * rs, u1 = (d[4 * j + 1] + d[4 * j + 3]) * rs;
                    h[8 * i + j] = pack2(fmaf(u0, tanh_fast(u0), u0), fmaf(u1, tanh_fast(u1), u1));
                }
                sts128(hbuf + (i & 1) * 8192, h[8 * i], h[8 * i + 1], h[8 * i + 2], h[8 * i + 3]);
                sts128(hbuf + (i & 1) * 8192 + 2048, h[8 * i + 4], h[8 * i + 5], h[8 * i + 6], h[8 * i + 7]);
                return 0u;
            };
            TS(1 + (ph & 2) * 10);
            step(d0, 0, a, fl, 0, [&]() { if (ph) gather_peer(); return 0u; });
            TS(32);
            step(d0, 1, a + 16, 0, 1, none);
            step(d1, 2, a, fl, 0, [&]() { return act(d0, 0); });
            step(d1, 3, a + 16, 0, 1, none);
            step(d0, 4, a, fl, 0, [&]() { return act(d1, 1); });
            TS(33);
            step(d0, 5, a + 16, 0, 1, none);
            step(d1, 6, a, fl, 0, [&]() { return act(d0, 2); });
            step(d1, 7, a + 16, 0, 1, none);
            step(d0, 8, h, 0, 0, [&]() { act(d1, 3); return fetch(3); });
            TS(2 + (ph & 2) * 10);
            step(d0, 9, ho, 0, 1, none);
            step(d0, 10, h + 16, 0, 1, none);
            step(d0, 11, ho + 16, 0, 1, none);
            uint32_t pk[8];
            auto pack_out = [&]() {
                pin(d0);
#pragma unroll
                for (int j = 0; j < 8; j++) pk[j] = pack2(d0[4 * j] + d0[4 * j + 2], d0[4 * j + 1] + d0[4 * j + 3]);
            };
            auto send = [&](int i) { st_async4(hbuf + 16384 + i * 2048 + peer, pk[4 * i], pk[4 * i + 1], pk[4 * i + 2], pk[4 * i + 3], inb + peer); };
            step(d1, 12, h, 0, 0, [&]() { pack_out(); if (SND != 1) send(0); if (SND == 0) send(1); return 0u; });
            TS(34);
            step(d1, 13, ho, 0, 1, [&]() { if (SND == 1) send(0); if (SND) send(1); return 0u; });
            step(d1, 14, h + 16, 0, 1, none);
            step(d1, 15, ho + 16, 0, 1, none);
            mbar_wait(inb, 0);
#pragma unroll
            for (int i = 0; i < 2; i++) {
                const uint4 u = lds128(hbuf + 16384 + i * 2048);
                const uint32_t p0[4] = {u.x, u.y, u.z, u.w};
#pragma unroll
                for (int j = 0; j < 4; j++) {
                    v[8 * i + 2 * j] = fmaf(0.5f, blo(p0[j]), blo(xr[4 * i + j]));
                    v[8 * i + 2 * j + 1] = fmaf(0.5f, bhi(p0[j]), bhi(xr[4 * i + j]));
                }
            }
            wg_wait<0>();
            pin(d1);
            rel(15);
            TS(3 + (ph & 2) * 10);
#pragma unroll
            for (int j = 0; j < 8; j++) {
                v[2 * j] = fmaf(0.5f, d1[4 * j] + d1[4 * j + 2], v[2 * j]);
                v[2 * j + 1] = fmaf(0.5f, d1[4 * j + 1] + d1[4 * j + 3], v[2 * j + 1]);
            }
#pragma unroll
            for (int i = 0; i < 15; i++) dwr[i] = 0;
            continue;
        }

        auto residual = [&](int n) {
            wg_wait<1>();
            rel(n);
            wg_wait<0>();
            pin(d0);
            rel(n + 1);
#pragma unroll
            for (int j = 0; j < 8; j++) {
                v[2 * j] = d0[4 * j] + d0[4 * j + 2] + blo(xr[j]);
                v[2 * j + 1] = d0[4 * j + 1] + d0[4 * j + 3] + bhi(xr[j]);
            }
        };

        if (ph == 2) {
            TS(39);
            sp(d0, 34, a, w, 0);
            acq(35);
            sp(d1, 35, a, w, 0);
            acq(36); acq(37);
            gather_peer();
            sp(d0, 36, a + 16, 0, 1);
            sp(d1, 37, a + 16, 0, 1);
            wg_wait<2>();
            rel(34);
            if (!(LATE & 1)) rel(35);
            acq(38);
            const float rs = trow < T_ ? 0.5f * rstd : 0.f;
            wg_wait<0>();
            pin(d0); pin(d1);
            if (!(LATE & 2)) { rel(36); rel(37); }
            TS(18);
            uint32_t pk[8];
#pragma unroll
            for (int j = 0; j < 8; j++) {
                const float u0 = (d0[4 * j] + d0[4 * j + 2]) * rs, u1 = (d0[4 * j + 1] + d0[4 * j + 3]) * rs;
                const float t0 = tanh_fast((d1[4 * j] + d1[4 * j + 2]) * rs), t1 = tanh_fast((d1[4 * j + 1] + d1[4 * j + 3]) * rs);
                pk[j] = pack2(fmaf(u0, t0, u0), fmaf(u1, t1, u1));
            }
            if (wq == 0 || wq == 3) {
                uint4* hp = &g_halo[((pair * 4 + tile) * 2 + (wq & 1)) * 64 + lane];
                st_data(hp, pk[0], pk[1], pk[2], pk[3]);
                st_data(hp + 32, pk[4], pk[5], pk[6], pk[7]);
            }
            const uint32_t gs = H + 16384 + w * GCH + wq * 1024;
            stsm4(gs + 1024 + foff, pk[0], pk[1], pk[2], pk[3]);
            stsm4(gs + 1024 + (foff ^ 64), pk[4], pk[5], pk[6], pk[7]);
            bar_sync(8 + w, 192);
            TS(26);
            uint32_t ca[8], cb[8];
            const int e = (wq & 1) * 4;
            const uint32_t lo = ((mir ^ e) * 144) ^ (lane * 4);
            const int dir = mir ? -1024 : 1024;
            const uint32_t gb = H + 16384 + w * GCH + (mir ? 3072 : 2048) + lo, sown_ = H + tile * HCH, so = sown_ + (mir ? 1024 : 2048) + lo;
            auto finish = [&](int i) {
                const uint32_t c = hadd2(ca[i], cb[i]);
                const float h0 = blo(c), h1 = bhi(c);
                sts32((so + (i >> 2) * dir) ^ ((i & 3) * 144), pack2(fmaf(h0, tanh_fast(h0), h0), fmaf(h1, tanh_fast(h1), h1)));
            };
#pragma unroll
            for (int k = 0; k < 26; k++) {
                if (k == 19) {
#pragma unroll
                    for (int i = 0; i < 4; i++) finish(i);
                    fence_async_smem();
                    bar_sync(2 + w, 128);
                    if (wq == 0) peer_copy(mapa(sown_ + 1024, r ^ 1), sown_ + 1024, 2048, mapa(bars + B_SR * 8, r ^ 1));
                    mbar_wait(bars + (B_HALO + 2 * w + (wq >> 1)) * 8, 0);
                    if (LATE & 1) rel(35);
                    if (LATE & 2) { rel(36); rel(37); }
                    TS(27);
                }
                const uint32_t g = lds32((gb + (((k + 1) & 4) ? ((k + 1) >> 3) + (wq & 1) : ((k + 1) >> 3)) * dir) ^ (((k + 1) & 7) * 144));
#pragma unroll
                for (int i = 0; i < 8; i++) {
                    const int tap = k - (i & 3) - 2 * (i & 4);
                    if (tap == 0) ca[i] = hmul2(g, dwr[0]);
                    else if (tap > 0 && tap < 8) ca[i] = hfma2(g, dwr[tap], ca[i]);
                    else if (tap == 8) cb[i] = hmul2(g, dwr[8]);
                    else if (tap > 8 && tap < 15) cb[i] = hfma2(g, dwr[tap], cb[i]);
                }
            }
#pragma unroll
            for (int i = 4; i < 8; i++) finish(i);
            fence_async_smem();
            bar_sync(12 + (warp >> 1), 64);
            if (wq == 0 || wq == 3) peer_copy(mapa(sown_ + wq * 1024, r ^ 1), sown_ + wq * 1024, 1024, mapa(bars + B_SR * 8, r ^ 1));
            bar_sync(10, 256);
            TS(19);
            auto frags = [&](int i, int half) {
                const uint32_t src = H + 2 * half * HCH + wq * 1024;
#pragma unroll
                for (int k = 0; k < 4; k++) ldsm4(src + (k >> 1) * HCH + (foff ^ ((k & 1) * 64)), a[i + 4 * k], a[i + 4 * k + 1], a[i + 4 * k + 2], a[i + 4 * k + 3]);
            };
            frags(0, r);
            sp(d0, 38, a, 0, 0);
            acq(39);
            mbar_wait(bars + B_SR * 8, 0);
            frags(16, r ^ 1);
            sp(d0, 39, a + 16, 0, 1);
            residual(38);
            TS(20);
            continue;
        }

        {
            TS(11);
            const uint32_t stg = H + warp * 2048;
            unsigned char* g = g_kvq + (size_t)((b * 4 + tile) * 1024 + trow) * 128 + lane * 16;
            auto put = [&](float (&d)[32], int i) {
                pin(d);
                uint32_t pk[8];
#pragma unroll
                for (int j = 0; j < 8; j++) pk[j] = pack2((d[4 * j] + d[4 * j + 2]) * rstd, (d[4 * j + 1] + d[4 * j + 3]) * rstd);
                if (i == 2) {
                    st_data(g + 2097152, pk[0], pk[1], pk[2], pk[3]);
                    st_data(g + 2097152 + 512, pk[4], pk[5], pk[6], pk[7]);
                    return;
                }
                stsm4(stg + i * 1024 + foff, pk[0], pk[1], pk[2], pk[3]);
                stsm4(stg + i * 1024 + (foff ^ 64), pk[4], pk[5], pk[6], pk[7]);
                __syncwarp();
                const uint4 u0 = lds128(stg + i * 1024 + lane * 16), u1 = lds128(stg + i * 1024 + 512 + lane * 16);
                stg128(g + i * 1048576, u0); stg128(g + i * 1048576 + 512, u1);
            };
            sp(d0, 16, a, w, 0);
            acq(17);
            sp(d1, 17, a, w, 0);
            gather_peer();
            acq(18);
            sp(d0, 18, a + 16, 0, 1);
            wg_wait<1>();
            rel(16); rel(17);
            acq(19);
            sp(d1, 19, a + 16, 0, 1);
            wg_wait<1>();
            rel(18);
            put(d0, 0);
            wg_wait<0>();
            rel(19);
            TS(37);
            put(d1, 1);
            bar_arrive(4, 288);
            TS(38);
            acq(20);
            sp(d0, 20, a, w, 0);
            acq(21);
            sp(d0, 21, a + 16, 0, 1);
            acq(22); acq(23);
            rel(22); rel(23);
            mbar_wait(bars + B_RST * 8, 0);
            wg_wait<0>();
            rel(20); rel(21);
            put(d0, 2);
            TS(12);
        }

        {
            constexpr float CS = 0.125f * 1.4426950408889634f;
            float sa[32], sb2[32], o[36];
            uint32_t pa[16], pb[16], q[16];
            float n0 = INFINITY, n1 = INFINITY;
            zero(o); zero(pa); zero(pb); zero(sb2);
            const uint32_t ones = sb + OFF_MISC + 2048;
            { const uint32_t c = w ? 0u : 0x3F803F80u; sts128(ones + tid * 16, c, c, c, c); }
            fence_async_smem();
            bar_sync(10, 256);
            const uint32_t vdesc = rdesc + ((((ones - rbase) >> 4) - 1) << 16);
            auto qk_issue = [&](float (&s)[32], uint32_t lo) {
                const uint64_t kd = mkdesc(lo);
                wg_fence();
#pragma unroll
                for (int k = 0; k < 4; k++) mma_qk(s, q[4 * k], q[4 * k + 1], q[4 * k + 2], q[4 * k + 3], kd + 2 * k, k != 0);
                wg_commit();
            };
            auto both_issue = [&](float (&s)[32], uint32_t klo, uint32_t (&pp)[16], uint32_t vlo) {
                const uint64_t kd = mkdesc(klo), vd = mkdesc(vlo);
                wg_fence();
#pragma unroll
                for (int k = 0; k < 4; k++) {
                    mma_pv(o, pp[4 * k], pp[4 * k + 1], pp[4 * k + 2], pp[4 * k + 3], vd - k * (128 * 65535));
                    mma_qk(s, q[4 * k], q[4 * k + 1], q[4 * k + 2], q[4 * k + 3], kd + 2 * k, k != 0);
                }
                wg_commit();
            };
            auto new_max = [&](float (&s)[32], int nj, float& x0, float& x1) {
                x0 = s[0]; x1 = s[2];
#pragma unroll
                for (int j = 0; j < nj; j++) {
                    x0 = fmaxf(x0, fmaxf(s[4 * j], s[4 * j + 1]));
                    x1 = fmaxf(x1, fmaxf(s[4 * j + 2], s[4 * j + 3]));
                }
                x0 = fmaxf(x0, __shfl_xor_sync(~0u, x0, 1)); x1 = fmaxf(x1, __shfl_xor_sync(~0u, x1, 1));
                x0 = fmaxf(x0, __shfl_xor_sync(~0u, x0, 2)); x1 = fmaxf(x1, __shfl_xor_sync(~0u, x1, 2));
                x0 = fminf(n0, fmaf(x0, -CS, -20.f)); x1 = fminf(n1, fmaf(x1, -CS, -20.f));
            };
            auto probs = [&](float (&s)[32], uint32_t (&pp)[16], bool ready, bool tail, auto wait) {
                uint32_t any = 0;
#pragma unroll
                for (int i = 0; i < 16; i++) {
                    pp[i] = pack2(ex2(fmaf(s[2 * i], CS, (i & 1) ? n1 : n0)), ex2(fmaf(s[2 * i + 1], CS, (i & 1) ? n1 : n0)));
                    any |= pp[i];
                }
                wg_wait<0>();
                pin(sa); pin(sb2); pin(o); pin(pa); pin(pb);
                if (__builtin_expect(__any_sync(~0u, (any & 0x40004000u) || !ready), 0)) {
                    wait();
                    if (__any_sync(~0u, any & 0x40004000u)) {
                        if (tail) {
#pragma unroll
                            for (int i = 20; i < 32; i++) s[i] = -INFINITY;
                        }
                        float x0, x1;
                        new_max(s, 8, x0, x1);
                        const float sc0 = ex2(x0 - n0), sc1 = ex2(x1 - n1);
                        n0 = x0; n1 = x1;
#pragma unroll
                        for (int j = 0; j < 9; j++) { o[4 * j] *= sc0; o[4 * j + 1] *= sc0; o[4 * j + 2] *= sc1; o[4 * j + 3] *= sc1; }
#pragma unroll
                        for (int i = 0; i < 16; i++)
                            pp[i] = pack2(ex2(fmaf(s[2 * i], CS, (i & 1) ? n1 : n0)), ex2(fmaf(s[2 * i + 1], CS, (i & 1) ? n1 : n0)));
                    }
                }
            };
            {
                uint4 u[4];
                const unsigned char* src = g_kvq + 2097152 + (size_t)(abh * 1024 + qt * 64 + wq * 16) * 128 + lane * 16;
                spin(QGATE);
                ld_data<512>(u, src);
#pragma unroll
                for (int k = 0; k < 2; k++) {
                    q[8 * k] = u[k].x; q[8 * k + 1] = u[k + 2].x; q[8 * k + 2] = u[k].y; q[8 * k + 3] = u[k + 2].y;
                    q[8 * k + 4] = u[k].z; q[8 * k + 5] = u[k + 2].z; q[8 * k + 6] = u[k].w; q[8 * k + 7] = u[k + 2].w;
                }
                pin(q);
            }
            TS(40);
            acq(24);
            TS(13);
            qk_issue(sa, rdesc + (24 % NSLOT) * (SLOT >> 4));
            wg_wait<0>();
            pin(sa);
            {
                float x0, x1;
                new_max(sa, NJ0, x0, x1);
                n0 = x0; n1 = x1;
            }
            bar_arrive(6, 384);
            uint32_t vd = vdesc - (SLOT >> 4) * 65535u, kd = rdesc, vb = fbar + 8, kb = fbar;
            uint32_t vlast = vdesc - 4 * (SLOT >> 4) * 65535u, klast = rdesc + 4 * (SLOT >> 4) + 512;
            uint32_t kprev = fbar + 32, vprev = bars + (B_SINK - (B_EMPTY - B_FULL)) * 8;
#pragma unroll 1
            for (int it = 0; it < 4; it++) {
                both_issue(sb2, klast, pb, vlast);
                probs(sa, pa, mbar_test(vb, it < 2) & mbar_test(kb, it < 3), false, [&]() { mbar_wait(vb, it < 2); mbar_wait(kb, it < 3); });
                TS(41 + it * 4);
                if (lane == 0) mbar_arrive(kprev + (B_EMPTY - B_FULL) * 8);
                if (lane == 0) mbar_arrive(vprev + (B_EMPTY - B_FULL) * 8);
                both_issue(sa, kd, pa, vd);
                const int dv = it == 0 ? 2 : (it == 1 ? -3 : 1);
                kprev = kb; vprev = vb; vlast = vd - 512 * 65535u; klast = kd + 512;
                vd -= dv * (SLOT >> 4) * 65535u; vb += dv * 8;
                kd += (it == 2 ? -3 : 2) * (SLOT >> 4); kb = it == 2 ? vb : kb + 16;
                probs(sb2, pb, true, it == 3 && w == 1, []() {});
                TS(43 + it * 4);
            }
            wg_fence();
#pragma unroll
            for (int k = 0; k < 4; k++)
                mma_pv(o, pb[4 * k], pb[4 * k + 1], pb[4 * k + 2], pb[4 * k + 3], mkdesc(vlast - k * (128 * 65535) + (k > 1 ? w * ((k - 1) << 22) : 0)));
            wg_commit();
            const int row = wq * 16 + (lane >> 2);
            const uint32_t ml = sb + OFF_MISC;
            mbar_wait(bars + (B_RST + 1) * 8, 0);
            wg_wait<0>();
            pin(o); pin(pb); pin(sa); pin(sb2);
            if (!(LATE & 4)) rel(31);
            const float l0 = o[32], l1 = o[34];
            if (c4 == 0) { sts64f(ml + w * 512 + row * 8, n0, l0); sts64f(ml + w * 512 + row * 8 + 64, n1, l1); }
            TS(14);
            float mine[16];
#pragma unroll
            for (int j = 0; j < 4; j++) {
                if (w == 0) sts128f(H + j * 2048 + wt * 16, o[16 + 4 * j], o[17 + 4 * j], o[18 + 4 * j], o[19 + 4 * j]);
                else sts128f(H + 8192 + j * 2048 + wt * 16, o[4 * j], o[4 * j + 1], o[4 * j + 2], o[4 * j + 3]);
            }
#pragma unroll
            for (int i = 0; i < 16; i++) mine[i] = w == 0 ? o[i] : o[16 + i];
            bar_sync(10, 256);
            const float2 u0 = lds64f(ml + (w ^ 1) * 512 + row * 8), u1 = lds64f(ml + (w ^ 1) * 512 + row * 8 + 64);
            const float x0 = fminf(n0, u0.x), x1 = fminf(n1, u1.x);
            float a0 = ex2(x0 - n0), b0 = ex2(x0 - u0.x), a1 = ex2(x1 - n1), b1 = ex2(x1 - u1.x);
            const float i0 = __fdividef(1.f, fmaf(a0, l0, b0 * u0.y)), i1 = __fdividef(1.f, fmaf(a1, l1, b1 * u1.y));
            a0 *= i0; b0 *= i0; a1 *= i1; b1 *= i1;
            uint32_t pk[8];
#pragma unroll
            for (int j = 0; j < 4; j++) {
                const float4 v = lds128f(H + (w ^ 1) * 8192 + j * 2048 + wt * 16);
                pk[2 * j] = pack2(fmaf(a0, mine[4 * j], b0 * v.x), fmaf(a0, mine[4 * j + 1], b0 * v.y));
                pk[2 * j + 1] = pack2(fmaf(a1, mine[4 * j + 2], b1 * v.z), fmaf(a1, mine[4 * j + 3], b1 * v.w));
            }
            unsigned char* dst = g_o + (size_t)(b * 128 + qt * 8 + 2 * wq) * 4096 + ah * 1024 + w * 512 + lane * 16;
            st_data(dst, pk[0], pk[2], pk[4], pk[6]);
            st_data(dst + 4096, pk[1], pk[3], pk[5], pk[7]);
            if (tid == 0) asm volatile("red.relaxed.gpu.global.add.u32 [%0], 1;" ::"l"(&g_epoch[blockIdx.x * FS]) : "memory");
            TS(15);
        }

        {
            const uint32_t* dp = reinterpret_cast<const uint32_t*>(p.dw + (mir ? 14 * 256 : 0) + tile * 64) + lane;
#pragma unroll
            for (int i = 0; i < 15; i++) asm volatile("ld.global.nc.b32 %0, [%1];" : "=r"(dwr[i]) : "l"(dp + i * (mir ? -128 : 128)));
            acq(32); acq(33); acq(34);
            uint4 u[8];
            ld_data<512>(u, g_o + (size_t)(b * 128 + pt * 4 + wq) * 4096 + lane * 16);
#pragma unroll
            for (int i = 0; i < 8; i++) { a[4 * i] = u[i].x; a[4 * i + 1] = u[i].y; a[4 * i + 2] = u[i].z; a[4 * i + 3] = u[i].w; }
            if (LATE & 4) rel(31);
            TS(16);
            sp(d0, 32, a, 0, 0);
            sp(d0, 33, a + 16, 0, 1);
#pragma unroll
            for (int i = 0; i < 15; i++) dwr[i] = hmul2(dwr[i], 0x3F003F00u);
            residual(32);
            TS(17);
        }
    }

    cluster_arrive();
    TS(24);
    {
        const float rstd = rsq(fmaxf(fmaf(-mean, mean, msq), 0.f) + 1e-5f), nb = -mean * rstd;
#pragma unroll
        for (int j = 0; j < 8; j++) xr[j] = pack2(fmaf(v[2 * j], rstd, nb), fmaf(v[2 * j + 1], rstd, nb));
        const uint32_t stg = P + 16384 + warp * 1024;
        stsm4(stg + foff, xr[0], xr[1], xr[2], xr[3]);
        stsm4(stg + (foff ^ 64), xr[4], xr[5], xr[6], xr[7]);
        __syncwarp();
        const uint32_t src = stg + (lane >> 3) * 128 + (((lane & 7) ^ (lane >> 3)) << 4);
        const uint4 u0 = lds128(src), u1 = lds128((src + 512) ^ 64);
        __nv_bfloat16* dst = p.out + (size_t)(b * T_ + trow + (lane >> 3)) * 256 + tile * 64 + (lane & 7) * 8;
        if (trow < T_) { stg128(dst, u0); stg128(dst + 4 * 256, u1); }
    }
    TS(25);
    TG(31);
    TSDUMP();
    cluster_wait();
}

typedef CUresult (*EncodeFn)(CUtensorMap*, CUtensorMapDataType, cuuint32_t, void*, const cuuint64_t*, const cuuint64_t*,
                             const cuuint32_t*, const cuuint32_t*, CUtensorMapInterleave, CUtensorMapSwizzle,
                             CUtensorMapL2promotion, CUtensorMapFloatOOBfill);

}

extern "C" void kernel_launch(void* const* d_in, const int* in_sizes, int n_in, void* d_out, int out_size) {
    static EncodeFn encode = nullptr;
    if (!encode) {
        void* fn = nullptr;
        cudaDriverEntryPointQueryResult qr;
        cudaGetDriverEntryPoint("cuTensorMapEncodeTiled", &fn, cudaEnableDefault, &qr);
        encode = (EncodeFn)fn;
        cudaFuncSetAttribute(conformer_kernel, cudaFuncAttributeMaxDynamicSharedMemorySize, SMEM_LAUNCH);
    }
    Params p;
    const cuuint32_t ones[5] = {1, 1, 1, 1, 1};
    const int idx[8] = {1, 2, 3, 4, 5, 7, 8, 9};
    const int rows[8] = {256, 1024, 256, 256, 256, 256, 256, 1024};
    const int cols[8] = {1024, 256, 768, 256, 512, 256, 1024, 256};
    for (int i = 0; i < 8; i++) {
        const cuuint64_t pitch = (cuuint64_t)cols[i] * 2;
        const cuuint64_t dims[5] = {(cuuint64_t)cols[i], i ? 2u : 4u, i ? 2u : 4u, i ? 4u : 2u, (cuuint64_t)rows[i] / (i ? 16 : 32)};
        const cuuint64_t strides[4] = {pitch, pitch * 8, pitch * (i ? 2 : 4), pitch * (i ? 16 : 32)};
        const cuuint32_t box[5] = {64, i ? 2u : 4u, i ? 2u : 4u, i ? 4u : 2u, i ? 8u : 4u};
        encode(&p.tm[i], CU_TENSOR_MAP_DATA_TYPE_BFLOAT16, 5, d_in[idx[i]], dims, strides, box, ones, CU_TENSOR_MAP_INTERLEAVE_NONE,
               CU_TENSOR_MAP_SWIZZLE_128B, CU_TENSOR_MAP_L2_PROMOTION_L2_128B, CU_TENSOR_MAP_FLOAT_OOB_FILL_NONE);
        p.w[i] = (const char*)d_in[idx[i]];
    }
    {
        void* kv = nullptr;
        cudaGetSymbolAddress(&kv, g_kvq);
        const cuuint64_t dims[2] = {64, 16384};
        const cuuint64_t strides[1] = {128};
        const cuuint32_t box[2] = {64, 128};
        encode(&p.tm[8], CU_TENSOR_MAP_DATA_TYPE_BFLOAT16, 2, kv, dims, strides, box, ones, CU_TENSOR_MAP_INTERLEAVE_NONE,
               CU_TENSOR_MAP_SWIZZLE_NONE, CU_TENSOR_MAP_L2_PROMOTION_L2_128B, CU_TENSOR_MAP_FLOAT_OOB_FILL_NONE);
    }
    p.x = (const __nv_bfloat16*)d_in[0];
    p.dw = (const __nv_bfloat16*)d_in[6];
    p.out = (__nv_bfloat16*)d_out;
    p.zero = 0;
    conformer_kernel<<<NCTA, NTHREADS, SMEM_LAUNCH>>>(p);
}
```

```cpp
#include <cuda_runtime.h>
#include <cuda_bf16.h>
#include <cuda.h>
#include <stdint.h>

namespace {

constexpr int T_ = 1000;
constexpr int NCTA = 128;
constexpr int NTHREADS = 512;
constexpr int NSLOT = 5;
constexpr int SLOT = 16384;
constexpr int NLOADS = 56;

constexpr uint32_t OFF_RING = 0;
constexpr uint32_t OFF_P = 163840;
constexpr uint32_t OFF_H = 188416;
constexpr uint32_t OFF_MISC = 221184;
constexpr uint32_t OFF_BARS = 229888;
constexpr uint32_t SMEM_BYTES = 230400;
constexpr uint32_t GCH = 6144;
constexpr uint32_t HCH = 4096;

constexpr int B_FULL = 0, B_EMPTY = 10, B_XA = 20  , B_XB = 25  , B_INB = 29  , B_SR = 33,
              B_RST = 34  , B_RDY = 36  , B_SINK = 42, B_HALO = 43  , NBARS = 47;

#define KD2 300u
#define KD3 500u
#define QGATE 500u
#define BACKOFF 0u
#define KFS 8
#define KDELAY 300u
#define NJ0 2
#define HDELAY 200u
#define LATE 2
#define SND 0
#define PF0 1
#define TURN 0x200
#define EAGER 0x0155
constexpr int FS = 8;

struct Params {
    CUtensorMap tm[9];
    const char* w[8];
    const __nv_bfloat16* x;
    const __nv_bfloat16* dw;
    __nv_bfloat16* out;
    uint32_t zero;
};

__device__ __align__(1024) unsigned char g_kvq[3 * 8 * 1024 * 128];
__device__ __align__(1024) unsigned char g_o[2 * 128 * 4096];
__device__ uint4 g_halo[64 * 4 * 2 * 64];
__device__ __align__(128) uint32_t g_flag_kv[8 * 32 * KFS];
__device__ uint32_t g_reset[4 * 32];
__device__ uint32_t g_epoch[NCTA * FS];

#define TS(i) do { } while (0)
#define TSW(i) do { } while (0)
#define TG(i) do { } while (0)
#define TSINIT() do { } while (0)
#define TSDUMP() do { } while (0)
constexpr uint32_t SMEM_LAUNCH = SMEM_BYTES;

__device__ __forceinline__ uint32_t smem_u32(const void* p) { return (uint32_t)__cvta_generic_to_shared(p); }
__device__ __forceinline__ void mbar_init(uint32_t b, uint32_t c) { asm volatile("mbarrier.init.shared::cta.b64 [%0], %1;" ::"r"(b), "r"(c) : "memory"); }
__device__ __forceinline__ void mbar_arrive(uint32_t b) { asm volatile("mbarrier.arrive.shared::cta.b64 _, [%0];" ::"r"(b) : "memory"); }
__device__ __forceinline__ void mbar_arrive_tx(uint32_t b, uint32_t tx) { asm volatile("mbarrier.arrive.expect_tx.shared::cta.b64 _, [%0], %1;" ::"r"(b), "r"(tx) : "memory"); }
__device__ __forceinline__ void mbar_wait(uint32_t b, uint32_t ph) {
    asm volatile("{\n.reg .pred p, q;\n.reg .u32 c;\nmov.u32 c, 0;\n"
                 "MW_LOOP:\n.pragma \"nounroll\";\n"
                 "mbarrier.try_wait.parity.shared::cta.b64 p, [%0], %1;\n"
                 "add.u32 c, c, 1;\nsetp.lt.u32 q, c, 65536;\nnot.pred p, p;\nand.pred p, p, q;\n@p bra MW_LOOP;\n}"
                 ::"r"(b), "r"(ph) : "memory");
}
__device__ __forceinline__ bool mbar_test(uint32_t b, uint32_t ph) {
    uint32_t ok;
    asm volatile("{\n.reg .pred p;\nmbarrier.test_wait.parity.shared::cta.b64 p, [%1], %2;\nselp.u32 %0, 1, 0, p;\n}" : "=r"(ok) : "r"(b), "r"(ph) : "memory");
    return ok;
}
__device__ __forceinline__ uint32_t mapa(uint32_t a, uint32_t r) { uint32_t o; asm("mapa.shared::cluster.u32 %0, %1, %2;" : "=r"(o) : "r"(a), "r"(r)); return o; }
__device__ __forceinline__ void fence_async_smem() { asm volatile("fence.proxy.async.shared::cta;" ::: "memory"); }
__device__ __forceinline__ void fence_async_global() { asm volatile("fence.proxy.async.global;" ::: "memory"); }
__device__ __forceinline__ void bar_sync(int id, int n) { asm volatile("bar.sync %0, %1;" ::"r"(id), "r"(n) : "memory"); }
__device__ __forceinline__ void bar_arrive(int id, int n) { asm volatile("bar.arrive %0, %1;" ::"r"(id), "r"(n) : "memory"); }
__device__ __forceinline__ void cluster_arrive() { asm volatile("barrier.cluster.arrive.relaxed.aligned;" ::: "memory"); }
__device__ __forceinline__ void cluster_wait() { asm volatile("barrier.cluster.wait.aligned;" ::: "memory"); }

__device__ __forceinline__ void ring_load(uint32_t dst, const CUtensorMap* tm, int col, int row16, uint32_t bar) {
    asm volatile("{\n.reg .pred p;\nelect.sync _|p, 0xffffffff;\n"
                 "@p mbarrier.arrive.expect_tx.shared::cta.b64 _, [%2], 16384;\n"
                 "@p cp.async.bulk.tensor.5d.shared::cluster.global.mbarrier::complete_tx::bytes [%0], [%1, {%3, 0, 0, 0, %4}], [%2];\n}"
                 ::"r"(dst), "l"(tm), "r"(bar), "r"(col), "r"(row16) : "memory");
}
__device__ __forceinline__ void ring_load_both(uint32_t dst, const CUtensorMap* tm, int c1, uint32_t bar) {
    asm volatile("{\n.reg .pred p;\nelect.sync _|p, 0xffffffff;\n"
                 "@p cp.async.bulk.tensor.2d.shared::cluster.global.mbarrier::complete_tx::bytes.multicast::cluster [%0], [%1, {0, %3}], [%2], %4;\n}"
                 ::"r"(dst), "l"(tm), "r"(bar), "r"(c1), "h"((uint16_t)3) : "memory");
}
__device__ __forceinline__ void mbar_arrive_peer(uint32_t b) { asm volatile("mbarrier.arrive.relaxed.cluster.shared::cluster.b64 _, [%0];" ::"r"(b) : "memory"); }
__device__ __forceinline__ void prefetch_l2(const void* src, uint32_t bytes) {
    asm volatile("cp.async.bulk.prefetch.L2.global [%0], %1;" ::"l"(src), "r"(bytes) : "memory");
}
__device__ __forceinline__ void peer_copy(uint32_t dst, uint32_t src, uint32_t bytes, uint32_t rbar) {
    asm volatile("{\n.reg .pred p;\nelect.sync _|p, 0xffffffff;\n"
                 "@p cp.async.bulk.shared::cluster.shared::cta.mbarrier::complete_tx::bytes [%0], [%1], %2, [%3];\n}"
                 ::"r"(dst), "r"(src), "r"(bytes), "r"(rbar) : "memory");
}
__device__ __forceinline__ void st_async4(uint32_t dst, uint32_t a, uint32_t b, uint32_t c, uint32_t d, uint32_t bar) {
    asm volatile("st.async.shared::cluster.mbarrier::complete_tx::bytes.v4.b32 [%0], {%1,%2,%3,%4}, [%5];" ::"r"(dst), "r"(a), "r"(b), "r"(c), "r"(d), "r"(bar) : "memory");
}
__device__ __forceinline__ void put_sums(uint32_t dst, uint32_t rdst, float a, float b, uint32_t rbar, bool on) {
    asm volatile("{\n.reg .pred p;\nsetp.ne.u32 p, %5, 0;\n"
                 "@p st.async.shared::cluster.mbarrier::complete_tx::bytes.v2.f32 [%1], {%2,%3}, [%4];\n"
                 "@p st.shared.v2.f32 [%0], {%2,%3};\n}" ::"r"(dst), "r"(rdst), "f"(a), "f"(b), "r"(rbar), "r"((uint32_t)on) : "memory");
}
__device__ __forceinline__ void stsm4(uint32_t a, uint32_t r0, uint32_t r1, uint32_t r2, uint32_t r3) {
    asm volatile("stmatrix.sync.aligned.m8n8.x4.shared.b16 [%0], {%1,%2,%3,%4};" ::"r"(a), "r"(r0), "r"(r1), "r"(r2), "r"(r3) : "memory");
}
__device__ __forceinline__ void ldsm4(uint32_t a, uint32_t& r0, uint32_t& r1, uint32_t& r2, uint32_t& r3) {
    asm volatile("ldmatrix.sync.aligned.m8n8.x4.shared.b16 {%0,%1,%2,%3}, [%4];" : "=r"(r0), "=r"(r1), "=r"(r2), "=r"(r3) : "r"(a) : "memory");
}
__device__ __forceinline__ uint4 lds128(uint32_t a) { uint4 v; asm volatile("ld.shared.v4.b32 {%0,%1,%2,%3}, [%4];" : "=r"(v.x), "=r"(v.y), "=r"(v.z), "=r"(v.w) : "r"(a) : "memory"); return v; }
__device__ __forceinline__ float4 lds128f(uint32_t a) { float4 v; asm volatile("ld.shared.v4.f32 {%0,%1,%2,%3}, [%4];" : "=f"(v.x), "=f"(v.y), "=f"(v.z), "=f"(v.w) : "r"(a) : "memory"); return v; }
__device__ __forceinline__ float2 lds64f(uint32_t a) { float2 v; asm volatile("ld.shared.v2.f32 {%0,%1}, [%2];" : "=f"(v.x), "=f"(v.y) : "r"(a) : "memory"); return v; }
__device__ __forceinline__ uint32_t lds32(uint32_t a) { uint32_t v; asm volatile("ld.shared.b32 %0, [%1];" : "=r"(v) : "r"(a) : "memory"); return v; }
__device__ __forceinline__ void sts128(uint32_t a, uint32_t x, uint32_t y, uint32_t z, uint32_t w) { asm volatile("st.shared.v4.b32 [%0], {%1,%2,%3,%4};" ::"r"(a), "r"(x), "r"(y), "r"(z), "r"(w) : "memory"); }
__device__ __forceinline__ void sts128f(uint32_t a, float x, float y, float z, float w) { asm volatile("st.shared.v4.f32 [%0], {%1,%2,%3,%4};" ::"r"(a), "f"(x), "f"(y), "f"(z), "f"(w) : "memory"); }
__device__ __forceinline__ void sts64f(uint32_t a, float x, float y) { asm volatile("st.shared.v2.f32 [%0], {%1,%2};" ::"r"(a), "f"(x), "f"(y) : "memory"); }
__device__ __forceinline__ void sts32(uint32_t a, uint32_t x) { asm volatile("st.shared.b32 [%0], %1;" ::"r"(a), "r"(x) : "memory"); }
__device__ __forceinline__ void stg128(void* p, uint4 v) { asm volatile("st.global.v4.b32 [%0], {%1,%2,%3,%4};" ::"l"(p), "r"(v.x), "r"(v.y), "r"(v.z), "r"(v.w) : "memory"); }

__device__ __forceinline__ uint32_t pack2(float lo, float hi) { uint32_t r; asm("cvt.rn.bf16x2.f32 %0, %1, %2;" : "=r"(r) : "f"(hi), "f"(lo)); return r; }
__device__ __forceinline__ float blo(uint32_t v) { return __uint_as_float(v << 16); }
__device__ __forceinline__ float bhi(uint32_t v) { return __uint_as_float(v & 0xffff0000u); }
__device__ __forceinline__ uint32_t hmul2(uint32_t a, uint32_t b) { uint32_t r; asm("mul.rn.bf16x2 %0, %1, %2;" : "=r"(r) : "r"(a), "r"(b)); return r; }
__device__ __forceinline__ uint32_t hadd2(uint32_t a, uint32_t b) { uint32_t r; asm("add.rn.bf16x2 %0, %1, %2;" : "=r"(r) : "r"(a), "r"(b)); return r; }
__device__ __forceinline__ uint32_t hsub2(uint32_t a, uint32_t b) { uint32_t r; asm("sub.rn.bf16x2 %0, %1, %2;" : "=r"(r) : "r"(a), "r"(b)); return r; }
__device__ __forceinline__ uint32_t hfma2(uint32_t a, uint32_t b, uint32_t c) { uint32_t r; asm("fma.rn.bf16x2 %0, %1, %2, %3;" : "=r"(r) : "r"(a), "r"(b), "r"(c)); return r; }
__device__ __forceinline__ float tanh_fast(float x) { float r; asm("tanh.approx.f32 %0, %1;" : "=f"(r) : "f"(x)); return r; }
__device__ __forceinline__ float rsq(float x) { float r; asm("rsqrt.approx.ftz.f32 %0, %1;" : "=f"(r) : "f"(x)); return r; }
__device__ __forceinline__ float ex2(float x) { float r; asm("ex2.approx.ftz.f32 %0, %1;" : "=f"(r) : "f"(x)); return r; }

__device__ __forceinline__ uint32_t ld_relaxed(const uint32_t* p) {
    uint32_t v;
    asm volatile("ld.relaxed.gpu.global.u32 %0, [%1];" : "=r"(v) : "l"(p) : "memory");
    return v;
}
__device__ __forceinline__ uint32_t clock32() { uint32_t c; asm volatile("mov.u32 %0, %%clock;" : "=r"(c)::"memory"); return c; }
__device__ __forceinline__ void spin(uint32_t clks) {
    const uint32_t t0 = clock32();
    while (clock32() - t0 < clks) {}
}
__device__ __forceinline__ void flag_wait(const uint32_t* p, uint32_t e, bool mine) {
#pragma unroll 1
    for (int i = 0; i < (1 << 19); i++) {
        if (mine) mine = ld_relaxed(p) != e;
        if (!__any_sync(~0u, mine)) break;
        if (BACKOFF) spin(BACKOFF);
    }
    asm volatile("fence.acquire.gpu;" ::: "memory");
    fence_async_global();
}
__device__ __forceinline__ void st_data(void* p, uint32_t x, uint32_t y, uint32_t z, uint32_t w) {
    asm volatile("st.relaxed.gpu.global.v4.b32 [%0], {%1,%2,%3,%4};" ::"l"(p), "r"(x), "r"(y), "r"(z), "r"(w) : "memory");
}
template <int STRIDE, int N>
__device__ __forceinline__ void ld_data(uint4 (&v)[N], const unsigned char* p) {
    int it = 0;
    bool again;
#pragma unroll 1
    do {
        uint32_t m = 0;
#pragma unroll
        for (int i = 0; i < N; i++)
            asm volatile("ld.relaxed.gpu.global.v4.b32 {%0,%1,%2,%3}, [%4];" : "=r"(v[i].x), "=r"(v[i].y), "=r"(v[i].z), "=r"(v[i].w) : "l"(p + i * STRIDE) : "memory");
#pragma unroll
        for (int i = 0; i < N; i++) m = __vimax3_u32(__vimax3_u32(v[i].x, v[i].y, v[i].z), v[i].w, m);
        again = __any_sync(~0u, m == ~0u) && ++it < (1 << 16);
    } while (again);
}
__device__ __forceinline__ uint32_t ld_epoch() { return ld_relaxed(&g_epoch[blockIdx.x * FS]) + 1; }
__device__ __forceinline__ void flag_set(uint32_t* p, uint32_t e) { asm volatile("st.release.gpu.global.u32 [%0], %1;" ::"l"(p), "r"(e) : "memory"); }

__device__ __forceinline__ uint32_t desc_lo(uint32_t addr) { return ((addr & 0x3FFFF) >> 4) | 0x10000u; }
__device__ __forceinline__ uint64_t mkdesc(uint32_t lo) { return (uint64_t)lo | (0x40000040ull << 32); }
__device__ __forceinline__ void wg_fence() { asm volatile("wgmma.fence.sync.aligned;" ::: "memory"); }
__device__ __forceinline__ void wg_commit() { asm volatile("wgmma.commit_group.sync.aligned;" ::: "memory"); }
template <int N> __device__ __forceinline__ void wg_wait() { asm volatile("wgmma.wait_group.sync.aligned %0;" ::"n"(N) : "memory"); }
template <int N> __device__ __forceinline__ void pin(float (&d)[N]) {
#pragma unroll
    for (int i = 0; i < N; i++) asm volatile("" : "+f"(d[i])::"memory");
}
template <int N> __device__ __forceinline__ void pin(uint32_t (&d)[N]) {
#pragma unroll
    for (int i = 0; i < N; i++) asm volatile("" : "+r"(d[i])::"memory");
}

template <typename Tp, int N> __device__ __forceinline__ void zero(Tp (&d)[N]) {
#pragma unroll
    for (int i = 0; i < N; i++) d[i] = 0;
    pin(d);
}

#define F4(d, i) "+f"(d[i]), "+f"(d[i + 1]), "+f"(d[i + 2]), "+f"(d[i + 3])
#define F16(d, i) F4(d, i), F4(d, i + 4), F4(d, i + 8), F4(d, i + 12)

__device__ __forceinline__ void mma16(float (&d)[4], const uint32_t* a, uint32_t b0, uint32_t b1) {
    asm("mma.sync.aligned.m16n8k16.row.col.f32.bf16.bf16.f32 {%0,%1,%2,%3}, {%4,%5,%6,%7}, {%8,%9}, {%0,%1,%2,%3};"
        : F4(d, 0) : "r"(a[0]), "r"(a[1]), "r"(a[2]), "r"(a[3]), "r"(b0), "r"(b1));
}
template <int N>
__device__ __forceinline__ float row_sum(const uint32_t* x) {
    float c[4] = {};
#pragma unroll
    for (int i = 0; i < N; i += 4) mma16(c, x + i, 0x3F803F80u, 0x3F803F80u);
    return c[0] + c[2];
}
template <int N>
__device__ __forceinline__ float row_sumsq(const uint32_t* x, int lane) {
    float c0[4] = {}, c1[4] = {};
#pragma unroll
    for (int i = 0; i < N; i += 4) {
        mma16(c0, x + i, x[i], x[i + 2]);
        mma16(c1, x + i, x[i + 1], x[i + 3]);
    }
    return (lane & 4) ? c0[1] + c1[3] : c0[0] + c1[2];
}
__device__ __forceinline__ void mma_sp(float (&d)[32], const uint32_t* a, uint64_t b, uint32_t meta, int acc) {
    asm volatile("{.reg .pred p; setp.ne.b32 p, %38, 0;\n"
                 "wgmma.mma_async.sp.sync.aligned.m64n64k32.f32.bf16.bf16 {%0,%1,%2,%3,%4,%5,%6,%7,%8,%9,%10,%11,%12,%13,%14,%15,%16,%17,%18,%19,%20,%21,%22,%23,%24,%25,%26,%27,%28,%29,%30,%31}, "
                 "{%32,%33,%34,%35}, %36, %37, 0, p, 1, 1, 1;}\n"
                 : F16(d, 0), F16(d, 16) : "r"(a[0]), "r"(a[1]), "r"(a[2]), "r"(a[3]), "l"(b), "r"(meta), "r"(acc));
}
__device__ __forceinline__ void mma_qk(float (&d)[32], uint32_t a0, uint32_t a1, uint32_t a2, uint32_t a3, uint64_t b, int acc) {
    asm volatile("{.reg .pred p; setp.ne.b32 p, %37, 0;\n"
                 "wgmma.mma_async.sync.aligned.m64n64k16.f32.bf16.bf16 {%0,%1,%2,%3,%4,%5,%6,%7,%8,%9,%10,%11,%12,%13,%14,%15,%16,%17,%18,%19,%20,%21,%22,%23,%24,%25,%26,%27,%28,%29,%30,%31}, "
                 "{%32,%33,%34,%35}, %36, p, 1, 1, 0;}\n"
                 : F16(d, 0), F16(d, 16) : "r"(a0), "r"(a1), "r"(a2), "r"(a3), "l"(b), "r"(acc));
}
__device__ __forceinline__ void mma_pv(float (&d)[36], uint32_t a0, uint32_t a1, uint32_t a2, uint32_t a3, uint64_t b) {
    asm volatile("wgmma.mma_async.sync.aligned.m64n72k16.f32.bf16.bf16 {%0,%1,%2,%3,%4,%5,%6,%7,%8,%9,%10,%11,%12,%13,%14,%15,%16,%17,%18,%19,%20,%21,%22,%23,%24,%25,%26,%27,%28,%29,%30,%31,%32,%33,%34,%35}, "
                 "{%36,%37,%38,%39}, %40, 1, 1, 1, 1;\n"
                 : F16(d, 0), F16(d, 16), F4(d, 32) : "r"(a0), "r"(a1), "r"(a2), "r"(a3), "l"(b));
}

__device__ __forceinline__ uint32_t load_code(int n, int r, int w) {
    const int tile = 2 * r + w;
    int m, col, row;
    if (n < 16 || n >= 40) {
        const int k = n < 16 ? n : n - 40;
        m = n < 16 ? 0 : 6;
        if (k < 8) { col = 4 * tile + (k >> 1); row = n < 16 ? (k & 1) : (k & 1) ^ r; }
        else { m++; col = k < 12 ? tile ^ 2 : tile; row = 2 * (tile ^ (k & 1)) + ((k >> 1) & 1); }
    } else if (n < 32) {
        const int k = n - 16;
        m = 2;
        if (k < 4) { col = tile + ((k & 1) ? 8 : 4); row = (k >> 1) ^ r; }
        else { col = tile; row = (k & 1) ^ r; }
    } else if (n < 34) { m = 3; col = tile; row = n - 32; }
    else if (n < 38) { const int k = n - 34; m = 4; col = tile + 4 * (k & 1); row = (k >> 1) ^ r; }
    else { m = 5; col = tile; row = (n & 1) ^ r; }
    return m | (col << 4) | (row << (m ? 11 : 10));
}

__global__ void __cluster_dims__(2, 1, 1) __launch_bounds__(NTHREADS, 1)
conformer_kernel(const __grid_constant__ Params p) {
    extern __shared__ __align__(1024) unsigned char smem_raw[];
    const uint32_t sb = smem_u32(smem_raw);
    const uint32_t bars = sb + OFF_BARS;
    const int tid = threadIdx.x;
    const int lane = tid & 31;
    const int warp = __shfl_sync(~0u, tid >> 5, 0);
    const int r = blockIdx.x & 1;
    const int pair = blockIdx.x >> 1;
    const int b = pair >> 5, pt = pair & 31;
    const int ah = pt >> 3, qt = (pt & 7) * 2 + r;
    const int abh = b * 4 + ah;

    TG(30);
    TSINIT();
    TS(0);
    const uint32_t P = sb + OFF_P, H = sb + OFF_H;
    if ((warp >> 1) == 4) {
        const uint32_t full = bars + (B_FULL + (warp & 1) * NSLOT) * 8;
        if (lane == 0) {
#pragma unroll
            for (int i = 0; i < NSLOT; i++) { mbar_init(full + i * 8, 1); mbar_init(full + (B_EMPTY - B_FULL + i) * 8, 4); }
            asm volatile("fence.mbarrier_init.release.cluster;" ::: "memory");
            fence_async_smem();
        }
        __syncwarp();
#pragma unroll
        for (int n = 0; n < 2; n++)
            ring_load(sb + OFF_RING + ((warp & 1) * NSLOT + n) * SLOT, &p.tm[0], 64 * (8 * r + 4 * (warp & 1)), 4 * n, full + n * 8);
        cluster_arrive();
        TS(1);
    }

    if (warp >= 8) {
        asm volatile("setmaxnreg.dec.sync.aligned.u32 48;");
        if (warp >= 12) {
            cluster_arrive();
            cluster_wait();
            const int ut = tid & 127;
            const uint32_t target = ld_epoch() * 64;
            auto reset_done = [&](int k) {
                bar_sync(11, 128);
                if (ut == 0) {
                    asm volatile("red.release.gpu.global.add.u32 [%0], 1;" ::"l"(&g_reset[(2 * b + k) * 32]) : "memory");
#pragma unroll 1
                    for (int i = 0; i < (1 << 20) && ld_relaxed(&g_reset[(2 * b + k) * 32]) != target; i++) __nanosleep(100);
                    asm volatile("fence.acquire.gpu;" ::: "memory");
                    mbar_arrive(bars + (B_RST + k) * 8);
                }
                __syncwarp();
                TS(13 + k);
            };
#pragma unroll
            for (int i = 0; i < 4; i++)
                st_data(g_kvq + 2097152 + (size_t)((b * 4 + 2 * r + (i >> 1)) * 1024 + pt * 32) * 128 + (i & 1) * 2048 + ut * 16, ~0u, ~0u, ~0u, ~0u);
            reset_done(0);
            bar_sync(6, 384);
#pragma unroll
            for (int i = 0; i < 4; i++) {
                st_data(g_o + (size_t)(b * 128 + qt * 8 + 2 * i + (ut >> 6)) * 4096 + ah * 1024 + (ut & 63) * 16, ~0u, ~0u, ~0u, ~0u);
                if (i < 2) st_data(&g_halo[(pair * 4 + 2 * r + i) * 128 + ut], ~0u, ~0u, ~0u, ~0u);
            }
            reset_done(1);
            const int side = warp & 1, wg = (warp >> 1) & 1, np = side ? pt + 1 : pt - 1;
            const unsigned char* src = reinterpret_cast<const unsigned char*>(&g_halo[(((b * 32 + np) * 4 + 2 * r + wg) * 2 + (side ^ 1)) * 64 + lane]);
            const uint32_t dst = H + 16384 + wg * GCH + side * 5120 + (lane & 7) * 128 + (((lane >> 3) ^ (lane & 7)) << 4);
            uint4 hv[2] = {make_uint4(0, 0, 0, 0), make_uint4(0, 0, 0, 0)};
            bar_sync(8 + wg, 192);
            if (np >= 0 && np < 32) {
                spin(HDELAY);
                ld_data<512>(hv, src);
            }
            stsm4(dst, hv[0].x, hv[0].y, hv[0].z, hv[0].w);
            stsm4(dst ^ 64, hv[1].x, hv[1].y, hv[1].z, hv[1].w);
            __syncwarp();
            if (lane == 0) mbar_arrive(bars + (B_HALO + (warp & 3)) * 8);
            TS(4);
        } else if (warp < 10) {
            const int w = warp - 8;
            const uint32_t ring = sb + OFF_RING + w * NSLOT * SLOT;
            const uint32_t full = bars + (B_FULL + w * NSLOT) * 8;
            bar_sync(12, 64);
#pragma unroll
            for (int n = 2; n < NSLOT; n++) ring_load(ring + n * SLOT, &p.tm[0], 64 * (8 * r + 4 * w + (n >> 1)), 4 * (n & 1), full + n * 8);
            TS(2);
            const uint32_t code = load_code(lane, r, w) | (load_code(lane + 32, r, w) << 16);
            cluster_wait();
            uint32_t s = 0, ph = 0;
            int n = NSLOT;
#pragma unroll 1
            for (int seg = 0; seg < 2; seg++) {
#pragma unroll 1
                for (; n < (seg == 0 ? 22 : NLOADS); n++) {
                    const uint32_t c = __shfl_sync(~0u, code, n) >> (n & 32 ? 16 : 0);
                    const CUtensorMap* tm = &p.tm[c & 15];
                    const uint32_t col = (c & 0xf0) * 4, row = (c & 0xff00) >> 8, dst = ring + s * SLOT;
                    mbar_wait(full + (B_EMPTY - B_FULL) * 8 + s * 8, ph + (((uint32_t)(size_t)tm | col | row | dst) & p.zero));
                    ring_load(dst, tm, col, row, full + s * 8);
                    if (++s == NSLOT) { s = 0; ph ^= 1; }
                }
                if (seg == 1) break;
                const uint32_t epoch = ld_epoch();
                const uint32_t rdy = bars + (B_RDY + 3 * w) * 8, prdy = mapa(rdy, r ^ 1);
                const int odd = r ^ w;
                const uint32_t* flags = g_flag_kv + (abh * 32 + lane) * KFS;
                auto kv_load = [&](uint32_t sl, int isv, int i) {
                    ring_load_both(ring + sl * SLOT, &p.tm[8], (isv * 64 + abh * 8 + 2 * i + w) * 128, full + sl * 8);
                };
#pragma unroll 1
                for (int i = 0; i < 2; i++) {
                    if (lane < 3 + i) {
                        const uint32_t sl = i ? lane : lane + 2;
                        mbar_wait(full + (B_EMPTY - B_FULL + sl) * 8, i ^ 1);
                        mbar_arrive_tx(full + sl * 8, (i || lane == 2) ? SLOT : 0);
                    }
                    __syncwarp();
                }
                if (lane == 0) mbar_arrive_peer(prdy);
                bar_sync(14, 96);
                spin(KDELAY);
                mbar_wait(rdy, 0);
                flag_wait(flags, epoch, (lane >> 2) == 2 * odd + w);
                TSW(5 + 2 * odd);
                if (!odd) { kv_load(4, 0, 0); bar_arrive(12, 64); }
                else bar_sync(12, 64);
                spin(w ? KD3 : KD2);
                kv_load(odd ^ 1, odd ^ 1, odd);
                flag_wait(flags, epoch, (lane >> 2) == 2 * odd + w + 4);
                mbar_wait(full + (odd ^ 1) * 8, 1);
                kv_load(2 + odd, odd, 2 - odd);
#pragma unroll 1
                for (int i = 0; i < 3; i++) {
                    const uint32_t sl = i ? i - 1 : 4, bo = i == 2 ? 16 : 8;
                    mbar_wait(full + (B_EMPTY - B_FULL + sl) * 8, i != 0);
                    if (lane == 0) mbar_arrive_tx(full + sl * 8, SLOT);
                    if ((i & 1) != odd) {
                        mbar_wait(rdy + bo, 0);
                        kv_load(sl, i != 0, 2 + odd);
                    } else if (lane == 0) mbar_arrive_peer(prdy + bo);
                    __syncwarp();
                }
                n = 32; s = 2; ph = 1;
            }
        } else if (warp == 10) {
            if (lane == 0) {
#pragma unroll
                for (int i = B_XA; i < NBARS; i++) mbar_init(bars + i * 8, 1);
#pragma unroll
                for (int i = B_XA; i <= B_SR; i++) mbar_arrive_tx(bars + i * 8, i < B_XB ? 512 : ((i >= B_INB && i < B_SR) ? 4096 : 8192));
                asm volatile("fence.mbarrier_init.release.cluster;" ::: "memory");
                fence_async_smem();
            }
            __syncwarp();
            cluster_arrive();
            cluster_wait();
        } else {
            const uint32_t kb = (lane < 2 || lane > 5) ? 4096 : (lane == 2 ? 3072 : (lane == 4 ? 2048 : 1024));
            const char* pf = p.w[lane & 7] + blockIdx.x * kb;
            cluster_arrive();
            cluster_wait();
            if (lane < PF0) prefetch_l2(pf, kb);
            mbar_wait(bars + B_FULL * 8, 0);
            if (lane >= PF0 && lane < 3) prefetch_l2(pf, kb);
            if (lane >= 1 && lane < 9) asm volatile("prefetch.tensormap [%0];" ::"l"(&p.tm[lane]) : "memory");
            mbar_wait(bars + (B_FULL + 1) * 8, 1);
            if (lane > 2 && lane < 8) prefetch_l2(pf, kb);
            if (lane == 8 && blockIdx.x < 15) prefetch_l2(p.dw + blockIdx.x * 256, 512);
            const uint32_t epoch = ld_epoch();
            bar_sync(4, 288);
            if (lane < 16) flag_set(&g_flag_kv[((b * 4 + 2 * r + (lane >> 3)) * 32 + pt) * KFS + (lane & 7)], epoch);
            __syncwarp();
            bar_arrive(14, 96);
            TSW(8);
        }
        TSDUMP();
        return;
    }

    const int w = warp >> 2, wq = warp & 3;
    const int tile = 2 * r + w;
    const int wt = tid & 127;
    const int c4 = lane & 3;
    const int trow = pt * 32 + 8 * wq;
    uint32_t xr[8];
    uint32_t a[32];
    const char* xrow = reinterpret_cast<const char*>(p.x) + (b * T_ + trow + (lane >> 2)) * 512;
    zero(a);
    if (trow < T_) {
        const char* src = xrow + c4 * 16 + p.zero;
#pragma unroll
        for (int i = 0; i < 8; i++)
            asm volatile("ld.global.nc.v4.b32 {%0,%1,%2,%3}, [%4];" : "=r"(a[4 * i]), "=r"(a[4 * i + 1]), "=r"(a[4 * i + 2]), "=r"(a[4 * i + 3]) : "l"(src + 64 * i));
    }
    cluster_arrive();
    asm volatile("setmaxnreg.inc.sync.aligned.u32 208;");
    const uint32_t rbase = sb + OFF_RING + w * NSLOT * SLOT, fbar = bars + (B_FULL + w * NSLOT) * 8;
    const uint32_t rdesc = desc_lo(rbase);
    auto acq = [&](int n) { mbar_wait(fbar + (n % NSLOT) * 8, (n / NSLOT) & 1); };
    auto rel = [&](int n) { if (lane == 0) mbar_arrive(fbar + (B_EMPTY - B_FULL + n % NSLOT) * 8); };
    const uint32_t foff = (lane & 7) * 128 + (((lane >> 3) ^ (lane & 7)) << 4);
    float v[16];
    const uint32_t xown = __shfl_sync(~0u, P + wt * 16 + tile * 4096, lane), xrem = __shfl_sync(~0u, P + wt * 16 + (r ^ 1) * 8192, lane);
    const uint32_t sbuf = __shfl_sync(~0u, sb + OFF_MISC + 1024 + (8 * wq + (lane >> 2)) * 32, lane);
    const uint32_t sown = __shfl_sync(~0u, sbuf + tile * 8, lane);
    const uint32_t peer = __shfl_sync(~0u, mapa(sb, r ^ 1) - sb, lane);
    const uint32_t hbuf = __shfl_sync(~0u, H + w * 4096 + wt * 16, lane);
    const uint32_t meta = __shfl_sync(~0u, 0xEEEE4444u + p.zero, lane);
    cluster_wait();
    TS(56);
    float mean, msq;
    const int mir = wq < 2 ? 7 : 0;
    uint32_t dwr[15] = {};

#pragma unroll
    for (int ph = 0; ph < 5; ph++) {
        uint4 o0, o1;
        if (ph == 0) {
            mean = ((row_sum<8>(a) + row_sum<8>(a + 8)) + (row_sum<8>(a + 16) + row_sum<8>(a + 24))) * (1.f / 256.f);
            TS(57);
        } else {
            const uint32_t xa = bars + (B_XA + ph) * 8;
#pragma unroll
            for (int j = 0; j < 8; j++) xr[j] = pack2(v[2 * j], v[2 * j + 1]);
            const float s = row_sum<8>(xr), q = row_sumsq<8>(xr, lane);
            if (ph < 4) {
                sts128(xown, xr[0], xr[1], xr[2], xr[3]);
                sts128(xown + 2048, xr[4], xr[5], xr[6], xr[7]);
            }
            put_sums(sown, sown + peer, s, q, xa + peer, c4 == (lane >> 3));
            bar_sync(10, 256);
            if (ph < 4) {
                o0 = lds128(xown ^ 4096); o1 = lds128((xown ^ 4096) + 2048);
                st_async4(xown + peer, xr[0], xr[1], xr[2], xr[3], xa + (B_XB - B_XA) * 8 + peer);
                st_async4(xown + peer + 2048, xr[4], xr[5], xr[6], xr[7], xa + (B_XB - B_XA) * 8 + peer);
            }
            TS(57 + ph);
            if (ph == 3) acq(0);
            if (ph == 1) acq(16);
            mbar_wait(xa, 0);
            const float4 u0 = lds128f(sbuf), u1 = lds128f(sbuf + 16);
            mean = ((u0.x + u0.z) + (u1.x + u1.z)) * (1.f / 256.f);
            msq = ((u0.y + u0.w) + (u1.y + u1.w)) * (1.f / 256.f);
        }
        if (ph == 4) break;
        const uint32_t mean2 = pack2(mean, mean);
        auto centre = [&](int i, const uint4& u) {
            a[i] = hsub2(u.x, mean2); a[i + 1] = hsub2(u.y, mean2); a[i + 2] = hsub2(u.z, mean2); a[i + 3] = hsub2(u.w, mean2);
        };
        if (ph == 0) {
#pragma unroll
            for (int j = 0; j < 32; j++) a[j] = hsub2(a[j], mean2);
            pin(a);
            acq(0);
        } else {
#pragma unroll
            for (int j = 0; j < 8; j++) a[j] = hsub2(xr[j], mean2);
            centre(8, o0); centre(12, o1);
        }
        float rstd = ph ? rsq(fmaxf(fmaf(-mean, mean, msq), 0.f) + 1e-5f) : 0.f;
        auto gather_peer = [&]() {
            mbar_wait(bars + (B_XB + ph) * 8, 0);
#pragma unroll
            for (int i = 0; i < 4; i++) centre(16 + 4 * i, lds128(xrem + i * 2048));
        };
        auto sp = [&](float (&d)[32], int n, const uint32_t* af, int flip, int acc) {
            const uint32_t lo = rdesc + p.zero * (ph * 64 + n + 1) + (n % NSLOT) * (SLOT >> 4);
            const uint64_t b0 = mkdesc(lo + flip * 512), b1 = mkdesc(lo + (flip ^ 1) * 512);
            wg_fence();
            mma_sp(d, af, b0, meta, acc);
            mma_sp(d, af + 4, b0 + 256, meta, 1);
            mma_sp(d, af + 8, b1, meta, 1);
            mma_sp(d, af + 12, b1 + 256, meta, 1);
            wg_commit();
        };
        float d0[32], d1[32];

        if (ph == 0 || ph == 3) {
            uint32_t h[32], ho[32];
            float rs = 0.5f * rstd;
            const uint32_t inb = bars + (B_INB + (ph & 2) + w) * 8;
            bool ready = true;
            const int eager = ph ? EAGER : EAGER - 1;
            auto step = [&](float (&d)[32], int n, const uint32_t* af, int flip, int acc, auto work) {
                if (!ready) acq(n);
                if (((TURN >> n) & 1) && w == 1) bar_sync(7, 256);
                sp(d, n, af, flip, acc);
                if (n > 0 && ((TURN >> (n - 1)) & 1) && w == 0) bar_arrive(7, 256);
                if (n < 15) ready = mbar_test(fbar + ((n + 1) % NSLOT) * 8, ((n + 1) / NSLOT) & 1);
                wg_wait<1>();
                if (n > 0 && !((eager >> (n - 1)) & 1)) rel(n - 1);
                const uint32_t tie = work() & p.zero;
                if ((eager >> n) & 1) {
                    if (p.zero < n + ph + 1) wg_wait<0>();
                    if (lane == 0) mbar_arrive(fbar + (B_EMPTY - B_FULL + n % NSLOT) * 8 + tie);
                }
            };
            auto none = []() { return 0u; };
            const int fl = ph ? w : 0;
            auto fetch = [&](int i) {
                bar_sync(10, 256);
                const uint4 u0 = lds128((hbuf ^ 4096) + (i & 1) * 8192), u1 = lds128((hbuf ^ 4096) + (i & 1) * 8192 + 2048);
                ho[8 * i] = u0.x; ho[8 * i + 1] = u0.y; ho[8 * i + 2] = u0.z; ho[8 * i + 3] = u0.w;
                ho[8 * i + 4] = u1.x; ho[8 * i + 5] = u1.y; ho[8 * i + 6] = u1.z; ho[8 * i + 7] = u1.w;
                return u0.x | u1.x;
            };
            auto act = [&](float (&d)[32], int i) {
                if (i > 0) fetch(i - 1);
                pin(d);
#pragma unroll
                for (int j = 0; j < 8; j++) {
                    const float u0 = (d[4 * j] + d[4 * j + 2]) * rs, u1 = (d[4 * j + 1] + d[4 * j + 3]) * rs;
                    h[8 * i + j] = pack2(fmaf(u0, tanh_fast(u0), u0), fmaf(u1, tanh_fast(u1), u1));
                }
                sts128(hbuf + (i & 1) * 8192, h[8 * i], h[8 * i + 1], h[8 * i + 2], h[8 * i + 3]);
                sts128(hbuf + (i & 1) * 8192 + 2048, h[8 * i + 4], h[8 * i + 5], h[8 * i + 6], h[8 * i + 7]);
                return 0u;
            };
            TS(1 + (ph & 2) * 10);
            step(d0, 0, a, fl, 0, [&]() {
                if (ph) gather_peer();
                else {
                    const float dm = mean - blo(mean2);
                    const float ms = __shfl_sync(~0u, row_sumsq<32>(a, lane), (lane & 28) + (lane >> 3)) * (1.f / 256.f);
                    rs = 0.5f * rsq(fmaxf(fmaf(-dm, dm, ms), 0.f) + 1e-5f);
                    zero(xr);
                    if (trow < T_) {
                        const char* src = xrow + tile * 128 + c4 * 4 + p.zero;
#pragma unroll
                        for (int j = 0; j < 8; j++) asm volatile("ld.global.nc.b32 %0, [%1];" : "=r"(xr[j]) : "l"(src + 16 * j));
                    }
                }
                return 0u;
            });
            TS(32);
            step(d0, 1, a + 16, 0, 1, none);
            step(d1, 2, a, fl, 0, [&]() { return act(d0, 0); });
            step(d1, 3, a + 16, 0, 1, none);
            step(d0, 4, a, fl, 0, [&]() { return act(d1, 1); });
            TS(33);
            step(d0, 5, a + 16, 0, 1, none);
            step(d1, 6, a, fl, 0, [&]() { return act(d0, 2); });
            step(d1, 7, a + 16, 0, 1, none);
            step(d0, 8, h, 0, 0, [&]() { act(d1, 3); return fetch(3); });
            TS(2 + (ph & 2) * 10);
            step(d0, 9, ho, 0, 1, none);
            step(d0, 10, h + 16, 0, 1, none);
            step(d0, 11, ho + 16, 0, 1, none);
            uint32_t pk[8];
            auto pack_out = [&]() {
                pin(d0);
#pragma unroll
                for (int j = 0; j < 8; j++) pk[j] = pack2(d0[4 * j] + d0[4 * j + 2], d0[4 * j + 1] + d0[4 * j + 3]);
            };
            auto send = [&](int i) { st_async4(hbuf + 16384 + i * 2048 + peer, pk[4 * i], pk[4 * i + 1], pk[4 * i + 2], pk[4 * i + 3], inb + peer); };
            step(d1, 12, h, 0, 0, [&]() { pack_out(); if (SND != 1) send(0); if (SND == 0) send(1); return 0u; });
            TS(34);
            step(d1, 13, ho, 0, 1, [&]() { if (SND == 1) send(0); if (SND) send(1); return 0u; });
            step(d1, 14, h + 16, 0, 1, none);
            step(d1, 15, ho + 16, 0, 1, none);
            mbar_wait(inb, 0);
#pragma unroll
            for (int i = 0; i < 2; i++) {
                const uint4 u = lds128(hbuf + 16384 + i * 2048);
                const uint32_t p0[4] = {u.x, u.y, u.z, u.w};
#pragma unroll
                for (int j = 0; j < 4; j++) {
                    v[8 * i + 2 * j] = fmaf(0.5f, blo(p0[j]), blo(xr[4 * i + j]));
                    v[8 * i + 2 * j + 1] = fmaf(0.5f, bhi(p0[j]), bhi(xr[4 * i + j]));
                }
            }
            wg_wait<0>();
            pin(d1);
            rel(15);
            TS(3 + (ph & 2) * 10);
#pragma unroll
            for (int j = 0; j < 8; j++) {
                v[2 * j] = fmaf(0.5f, d1[4 * j] + d1[4 * j + 2], v[2 * j]);
                v[2 * j + 1] = fmaf(0.5f, d1[4 * j + 1] + d1[4 * j + 3], v[2 * j + 1]);
            }
#pragma unroll
            for (int i = 0; i < 15; i++) dwr[i] = 0;
            continue;
        }

        auto residual = [&](int n) {
            wg_wait<1>();
            rel(n);
            wg_wait<0>();
            pin(d0);
            rel(n + 1);
#pragma unroll
            for (int j = 0; j < 8; j++) {
                v[2 * j] = d0[4 * j] + d0[4 * j + 2] + blo(xr[j]);
                v[2 * j + 1] = d0[4 * j + 1] + d0[4 * j + 3] + bhi(xr[j]);
            }
        };

        if (ph == 2) {
            TS(39);
            sp(d0, 34, a, w, 0);
            acq(35);
            sp(d1, 35, a, w, 0);
            acq(36); acq(37);
            gather_peer();
            sp(d0, 36, a + 16, 0, 1);
            sp(d1, 37, a + 16, 0, 1);
            wg_wait<2>();
            rel(34);
            if (!(LATE & 1)) rel(35);
            acq(38);
            const float rs = trow < T_ ? 0.5f * rstd : 0.f;
            wg_wait<0>();
            pin(d0); pin(d1);
            if (!(LATE & 2)) { rel(36); rel(37); }
            TS(18);
            uint32_t pk[8];
#pragma unroll
            for (int j = 0; j < 8; j++) {
                const float u0 = (d0[4 * j] + d0[4 * j + 2]) * rs, u1 = (d0[4 * j + 1] + d0[4 * j + 3]) * rs;
                const float t0 = tanh_fast((d1[4 * j] + d1[4 * j + 2]) * rs), t1 = tanh_fast((d1[4 * j + 1] + d1[4 * j + 3]) * rs);
                pk[j] = pack2(fmaf(u0, t0, u0), fmaf(u1, t1, u1));
            }
            if (wq == 0 || wq == 3) {
                uint4* hp = &g_halo[((pair * 4 + tile) * 2 + (wq & 1)) * 64 + lane];
                st_data(hp, pk[0], pk[1], pk[2], pk[3]);
                st_data(hp + 32, pk[4], pk[5], pk[6], pk[7]);
            }
            const uint32_t gs = H + 16384 + w * GCH + wq * 1024;
            stsm4(gs + 1024 + foff, pk[0], pk[1], pk[2], pk[3]);
            stsm4(gs + 1024 + (foff ^ 64), pk[4], pk[5], pk[6], pk[7]);
            bar_sync(8 + w, 192);
            TS(26);
            uint32_t ca[8], cb[8];
            const int e = (wq & 1) * 4;
            const uint32_t lo = ((mir ^ e) * 144) ^ (lane * 4);
            const int dir = mir ? -1024 : 1024;
            const uint32_t gb = H + 16384 + w * GCH + (mir ? 3072 : 2048) + lo, sown_ = H + tile * HCH, so = sown_ + (mir ? 1024 : 2048) + lo;
            auto finish = [&](int i) {
                const uint32_t c = hadd2(ca[i], cb[i]);
                const float h0 = blo(c), h1 = bhi(c);
                sts32((so + (i >> 2) * dir) ^ ((i & 3) * 144), pack2(fmaf(h0, tanh_fast(h0), h0), fmaf(h1, tanh_fast(h1), h1)));
            };
#pragma unroll
            for (int k = 0; k < 26; k++) {
                if (k == 19) {
#pragma unroll
                    for (int i = 0; i < 4; i++) finish(i);
                    fence_async_smem();
                    bar_sync(2 + w, 128);
                    if (wq == 0) peer_copy(mapa(sown_ + 1024, r ^ 1), sown_ + 1024, 2048, mapa(bars + B_SR * 8, r ^ 1));
                    mbar_wait(bars + (B_HALO + 2 * w + (wq >> 1)) * 8, 0);
                    if (LATE & 1) rel(35);
                    if (LATE & 2) { rel(36); rel(37); }
                    TS(27);
                }
                const uint32_t g = lds32((gb + (((k + 1) & 4) ? ((k + 1) >> 3) + (wq & 1) : ((k + 1) >> 3)) * dir) ^ (((k + 1) & 7) * 144));
#pragma unroll
                for (int i = 0; i < 8; i++) {
                    const int tap = k - (i & 3) - 2 * (i & 4);
                    if (tap == 0) ca[i] = hmul2(g, dwr[0]);
                    else if (tap > 0 && tap < 8) ca[i] = hfma2(g, dwr[tap], ca[i]);
                    else if (tap == 8) cb[i] = hmul2(g, dwr[8]);
                    else if (tap > 8 && tap < 15) cb[i] = hfma2(g, dwr[tap], cb[i]);
                }
            }
#pragma unroll
            for (int i = 4; i < 8; i++) finish(i);
            fence_async_smem();
            bar_sync(12 + (warp >> 1), 64);
            if (wq == 0 || wq == 3) peer_copy(mapa(sown_ + wq * 1024, r ^ 1), sown_ + wq * 1024, 1024, mapa(bars + B_SR * 8, r ^ 1));
            bar_sync(10, 256);
            TS(19);
            auto frags = [&](int i, int half) {
                const uint32_t src = H + 2 * half * HCH + wq * 1024;
#pragma unroll
                for (int k = 0; k < 4; k++) ldsm4(src + (k >> 1) * HCH + (foff ^ ((k & 1) * 64)), a[i + 4 * k], a[i + 4 * k + 1], a[i + 4 * k + 2], a[i + 4 * k + 3]);
            };
            frags(0, r);
            sp(d0, 38, a, 0, 0);
            acq(39);
            mbar_wait(bars + B_SR * 8, 0);
            frags(16, r ^ 1);
            sp(d0, 39, a + 16, 0, 1);
            residual(38);
            TS(20);
            continue;
        }

        {
            TS(11);
            const uint32_t stg = H + warp * 2048;
            unsigned char* g = g_kvq + (size_t)((b * 4 + tile) * 1024 + trow) * 128 + lane * 16;
            auto put = [&](float (&d)[32], int i) {
                pin(d);
                uint32_t pk[8];
#pragma unroll
                for (int j = 0; j < 8; j++) pk[j] = pack2((d[4 * j] + d[4 * j + 2]) * rstd, (d[4 * j + 1] + d[4 * j + 3]) * rstd);
                if (i == 2) {
                    st_data(g + 2097152, pk[0], pk[1], pk[2], pk[3]);
                    st_data(g + 2097152 + 512, pk[4], pk[5], pk[6], pk[7]);
                    return;
                }
                stsm4(stg + i * 1024 + foff, pk[0], pk[1], pk[2], pk[3]);
                stsm4(stg + i * 1024 + (foff ^ 64), pk[4], pk[5], pk[6], pk[7]);
                __syncwarp();
                const uint4 u0 = lds128(stg + i * 1024 + lane * 16), u1 = lds128(stg + i * 1024 + 512 + lane * 16);
                stg128(g + i * 1048576, u0); stg128(g + i * 1048576 + 512, u1);
            };
            sp(d0, 16, a, w, 0);
            acq(17);
            sp(d1, 17, a, w, 0);
            gather_peer();
            acq(18);
            sp(d0, 18, a + 16, 0, 1);
            wg_wait<1>();
            rel(16); rel(17);
            acq(19);
            sp(d1, 19, a + 16, 0, 1);
            wg_wait<1>();
            rel(18);
            put(d0, 0);
            wg_wait<0>();
            rel(19);
            TS(37);
            put(d1, 1);
            bar_arrive(4, 288);
            TS(38);
            acq(20);
            sp(d0, 20, a, w, 0);
            acq(21);
            sp(d0, 21, a + 16, 0, 1);
            acq(22); acq(23);
            rel(22); rel(23);
            mbar_wait(bars + B_RST * 8, 0);
            wg_wait<0>();
            rel(20); rel(21);
            put(d0, 2);
            TS(12);
        }

        {
            constexpr float CS = 0.125f * 1.4426950408889634f;
            float sa[32], sb2[32], o[36];
            uint32_t pa[16], pb[16], q[16];
            float n0 = INFINITY, n1 = INFINITY;
            zero(o); zero(pa); zero(pb); zero(sb2);
            const uint32_t ones = sb + OFF_MISC + 2048;
            { const uint32_t c = w ? 0u : 0x3F803F80u; sts128(ones + tid * 16, c, c, c, c); }
            fence_async_smem();
            bar_sync(10, 256);
            const uint32_t vdesc = rdesc + ((((ones - rbase) >> 4) - 1) << 16);
            auto qk_issue = [&](float (&s)[32], uint32_t lo) {
                const uint64_t kd = mkdesc(lo);
                wg_fence();
#pragma unroll
                for (int k = 0; k < 4; k++) mma_qk(s, q[4 * k], q[4 * k + 1], q[4 * k + 2], q[4 * k + 3], kd + 2 * k, k != 0);
                wg_commit();
            };
            auto both_issue = [&](float (&s)[32], uint32_t klo, uint32_t (&pp)[16], uint32_t vlo) {
                const uint64_t kd = mkdesc(klo), vd = mkdesc(vlo);
                wg_fence();
#pragma unroll
                for (int k = 0; k < 4; k++) {
                    mma_pv(o, pp[4 * k], pp[4 * k + 1], pp[4 * k + 2], pp[4 * k + 3], vd - k * (128 * 65535));
                    mma_qk(s, q[4 * k], q[4 * k + 1], q[4 * k + 2], q[4 * k + 3], kd + 2 * k, k != 0);
                }
                wg_commit();
            };
            auto new_max = [&](float (&s)[32], int nj, float& x0, float& x1) {
                x0 = s[0]; x1 = s[2];
#pragma unroll
                for (int j = 0; j < nj; j++) {
                    x0 = fmaxf(x0, fmaxf(s[4 * j], s[4 * j + 1]));
                    x1 = fmaxf(x1, fmaxf(s[4 * j + 2], s[4 * j + 3]));
                }
                x0 = fmaxf(x0, __shfl_xor_sync(~0u, x0, 1)); x1 = fmaxf(x1, __shfl_xor_sync(~0u, x1, 1));
                x0 = fmaxf(x0, __shfl_xor_sync(~0u, x0, 2)); x1 = fmaxf(x1, __shfl_xor_sync(~0u, x1, 2));
                x0 = fminf(n0, fmaf(x0, -CS, -20.f)); x1 = fminf(n1, fmaf(x1, -CS, -20.f));
            };
            auto probs = [&](float (&s)[32], uint32_t (&pp)[16], bool ready, bool tail, auto wait) {
                uint32_t any = 0;
#pragma unroll
                for (int i = 0; i < 16; i++) {
                    pp[i] = pack2(ex2(fmaf(s[2 * i], CS, (i & 1) ? n1 : n0)), ex2(fmaf(s[2 * i + 1], CS, (i & 1) ? n1 : n0)));
                    any |= pp[i];
                }
                wg_wait<0>();
                pin(sa); pin(sb2); pin(o); pin(pa); pin(pb);
                if (__builtin_expect(__any_sync(~0u, (any & 0x40004000u) || !ready), 0)) {
                    wait();
                    if (__any_sync(~0u, any & 0x40004000u)) {
                        if (tail) {
#pragma unroll
                            for (int i = 20; i < 32; i++) s[i] = -INFINITY;
                        }
                        float x0, x1;
                        new_max(s, 8, x0, x1);
                        const float sc0 = ex2(x0 - n0), sc1 = ex2(x1 - n1);
                        n0 = x0; n1 = x1;
#pragma unroll
                        for (int j = 0; j < 9; j++) { o[4 * j] *= sc0; o[4 * j + 1] *= sc0; o[4 * j + 2] *= sc1; o[4 * j + 3] *= sc1; }
#pragma unroll
                        for (int i = 0; i < 16; i++)
                            pp[i] = pack2(ex2(fmaf(s[2 * i], CS, (i & 1) ? n1 : n0)), ex2(fmaf(s[2 * i + 1], CS, (i & 1) ? n1 : n0)));
                    }
                }
            };
            {
                uint4 u[4];
                const unsigned char* src = g_kvq + 2097152 + (size_t)(abh * 1024 + qt * 64 + wq * 16) * 128 + lane * 16;
                spin(QGATE);
                ld_data<512>(u, src);
#pragma unroll
                for (int k = 0; k < 2; k++) {
                    q[8 * k] = u[k].x; q[8 * k + 1] = u[k + 2].x; q[8 * k + 2] = u[k].y; q[8 * k + 3] = u[k + 2].y;
                    q[8 * k + 4] = u[k].z; q[8 * k + 5] = u[k + 2].z; q[8 * k + 6] = u[k].w; q[8 * k + 7] = u[k + 2].w;
                }
                pin(q);
            }
            TS(40);
            acq(24);
            TS(13);
            qk_issue(sa, rdesc + (24 % NSLOT) * (SLOT >> 4));
            wg_wait<0>();
            pin(sa);
            {
                float x0, x1;
                new_max(sa, NJ0, x0, x1);
                n0 = x0; n1 = x1;
            }
            bar_arrive(6, 384);
            uint32_t vd = vdesc - (SLOT >> 4) * 65535u, kd = rdesc, vb = fbar + 8, kb = fbar;
            uint32_t vlast = vdesc - 4 * (SLOT >> 4) * 65535u, klast = rdesc + 4 * (SLOT >> 4) + 512;
            uint32_t kprev = fbar + 32, vprev = bars + (B_SINK - (B_EMPTY - B_FULL)) * 8;
#pragma unroll 1
            for (int it = 0; it < 4; it++) {
                both_issue(sb2, klast, pb, vlast);
                probs(sa, pa, mbar_test(vb, it < 2) & mbar_test(kb, it < 3), false, [&]() { mbar_wait(vb, it < 2); mbar_wait(kb, it < 3); });
                TS(41 + it * 4);
                if (lane == 0) mbar_arrive(kprev + (B_EMPTY - B_FULL) * 8);
                if (lane == 0) mbar_arrive(vprev + (B_EMPTY - B_FULL) * 8);
                both_issue(sa, kd, pa, vd);
                const int dv = it == 0 ? 2 : (it == 1 ? -3 : 1);
                kprev = kb; vprev = vb; vlast = vd - 512 * 65535u; klast = kd + 512;
                vd -= dv * (SLOT >> 4) * 65535u; vb += dv * 8;
                kd += (it == 2 ? -3 : 2) * (SLOT >> 4); kb = it == 2 ? vb : kb + 16;
                probs(sb2, pb, true, it == 3 && w == 1, []() {});
                TS(43 + it * 4);
            }
            wg_fence();
#pragma unroll
            for (int k = 0; k < 4; k++)
                mma_pv(o, pb[4 * k], pb[4 * k + 1], pb[4 * k + 2], pb[4 * k + 3], mkdesc(vlast - k * (128 * 65535) + (k > 1 ? w * ((k - 1) << 22) : 0)));
            wg_commit();
            const int row = wq * 16 + (lane >> 2);
            const uint32_t ml = sb + OFF_MISC;
            mbar_wait(bars + (B_RST + 1) * 8, 0);
            wg_wait<0>();
            pin(o); pin(pb); pin(sa); pin(sb2);
            if (!(LATE & 4)) rel(31);
            const float l0 = o[32], l1 = o[34];
            if (c4 == 0) { sts64f(ml + w * 512 + row * 8, n0, l0); sts64f(ml + w * 512 + row * 8 + 64, n1, l1); }
            TS(14);
            float mine[16];
#pragma unroll
            for (int j = 0; j < 4; j++) {
                if (w == 0) sts128f(H + j * 2048 + wt * 16, o[16 + 4 * j], o[17 + 4 * j], o[18 + 4 * j], o[19 + 4 * j]);
                else sts128f(H + 8192 + j * 2048 + wt * 16, o[4 * j], o[4 * j + 1], o[4 * j + 2], o[4 * j + 3]);
            }
#pragma unroll
            for (int i = 0; i < 16; i++) mine[i] = w == 0 ? o[i] : o[16 + i];
            bar_sync(10, 256);
            const float2 u0 = lds64f(ml + (w ^ 1) * 512 + row * 8), u1 = lds64f(ml + (w ^ 1) * 512 + row * 8 + 64);
            const float x0 = fminf(n0, u0.x), x1 = fminf(n1, u1.x);
            float a0 = ex2(x0 - n0), b0 = ex2(x0 - u0.x), a1 = ex2(x1 - n1), b1 = ex2(x1 - u1.x);
            const float i0 = __fdividef(1.f, fmaf(a0, l0, b0 * u0.y)), i1 = __fdividef(1.f, fmaf(a1, l1, b1 * u1.y));
            a0 *= i0; b0 *= i0; a1 *= i1; b1 *= i1;
            uint32_t pk[8];
#pragma unroll
            for (int j = 0; j < 4; j++) {
                const float4 v = lds128f(H + (w ^ 1) * 8192 + j * 2048 + wt * 16);
                pk[2 * j] = pack2(fmaf(a0, mine[4 * j], b0 * v.x), fmaf(a0, mine[4 * j + 1], b0 * v.y));
                pk[2 * j + 1] = pack2(fmaf(a1, mine[4 * j + 2], b1 * v.z), fmaf(a1, mine[4 * j + 3], b1 * v.w));
            }
            unsigned char* dst = g_o + (size_t)(b * 128 + qt * 8 + 2 * wq) * 4096 + ah * 1024 + w * 512 + lane * 16;
            st_data(dst, pk[0], pk[2], pk[4], pk[6]);
            st_data(dst + 4096, pk[1], pk[3], pk[5], pk[7]);
            if (tid == 0) asm volatile("red.relaxed.gpu.global.add.u32 [%0], 1;" ::"l"(&g_epoch[blockIdx.x * FS]) : "memory");
            TS(15);
        }

        {
            const uint32_t* dp = reinterpret_cast<const uint32_t*>(p.dw + (mir ? 14 * 256 : 0) + tile * 64) + lane;
#pragma unroll
            for (int i = 0; i < 15; i++) asm volatile("ld.global.nc.b32 %0, [%1];" : "=r"(dwr[i]) : "l"(dp + i * (mir ? -128 : 128)));
            acq(32); acq(33); acq(34);
            uint4 u[8];
            ld_data<512>(u, g_o + (size_t)(b * 128 + pt * 4 + wq) * 4096 + lane * 16);
#pragma unroll
            for (int i = 0; i < 8; i++) { a[4 * i] = u[i].x; a[4 * i + 1] = u[i].y; a[4 * i + 2] = u[i].z; a[4 * i + 3] = u[i].w; }
            if (LATE & 4) rel(31);
            TS(16);
            sp(d0, 32, a, 0, 0);
            sp(d0, 33, a + 16, 0, 1);
#pragma unroll
            for (int i = 0; i < 15; i++) dwr[i] = hmul2(dwr[i], 0x3F003F00u);
            residual(32);
            TS(17);
        }
    }

    cluster_arrive();
    TS(24);
    {
        const float rstd = rsq(fmaxf(fmaf(-mean, mean, msq), 0.f) + 1e-5f), nb = -mean * rstd;
#pragma unroll
        for (int j = 0; j < 8; j++) xr[j] = pack2(fmaf(v[2 * j], rstd, nb), fmaf(v[2 * j + 1], rstd, nb));
        const uint32_t stg = P + 16384 + warp * 1024;
        stsm4(stg + foff, xr[0], xr[1], xr[2], xr[3]);
        stsm4(stg + (foff ^ 64), xr[4], xr[5], xr[6], xr[7]);
        __syncwarp();
        const uint32_t src = stg + (lane >> 3) * 128 + (((lane & 7) ^ (lane >> 3)) << 4);
        const uint4 u0 = lds128(src), u1 = lds128((src + 512) ^ 64);
        __nv_bfloat16* dst = p.out + (size_t)(b * T_ + trow + (lane >> 3)) * 256 + tile * 64 + (lane & 7) * 8;
        if (trow < T_) { stg128(dst, u0); stg128(dst + 4 * 256, u1); }
    }
    TS(25);
    TG(31);
    TSDUMP();
    cluster_wait();
}

typedef CUresult (*EncodeFn)(CUtensorMap*, CUtensorMapDataType, cuuint32_t, void*, const cuuint64_t*, const cuuint64_t*,
                             const cuuint32_t*, const cuuint32_t*, CUtensorMapInterleave, CUtensorMapSwizzle,
                             CUtensorMapL2promotion, CUtensorMapFloatOOBfill);

}

extern "C" void kernel_launch(void* const* d_in, const int* in_sizes, int n_in, void* d_out, int out_size) {
    static EncodeFn encode = nullptr;
    if (!encode) {
        void* fn = nullptr;
        cudaDriverEntryPointQueryResult qr;
        cudaGetDriverEntryPoint("cuTensorMapEncodeTiled", &fn, cudaEnableDefault, &qr);
        encode = (EncodeFn)fn;
        cudaFuncSetAttribute(conformer_kernel, cudaFuncAttributeMaxDynamicSharedMemorySize, SMEM_LAUNCH);
    }
    Params p;
    const cuuint32_t ones[5] = {1, 1, 1, 1, 1};
    const int idx[8] = {1, 2, 3, 4, 5, 7, 8, 9};
    const int rows[8] = {256, 1024, 256, 256, 256, 256, 256, 1024};
    const int cols[8] = {1024, 256, 768, 256, 512, 256, 1024, 256};
    for (int i = 0; i < 8; i++) {
        const cuuint64_t pitch = (cuuint64_t)cols[i] * 2;
        const cuuint64_t dims[5] = {(cuuint64_t)cols[i], i ? 2u : 4u, i ? 2u : 4u, i ? 4u : 2u, (cuuint64_t)rows[i] / (i ? 16 : 32)};
        const cuuint64_t strides[4] = {pitch, pitch * 8, pitch * (i ? 2 : 4), pitch * (i ? 16 : 32)};
        const cuuint32_t box[5] = {64, i ? 2u : 4u, i ? 2u : 4u, i ? 4u : 2u, i ? 8u : 4u};
        encode(&p.tm[i], CU_TENSOR_MAP_DATA_TYPE_BFLOAT16, 5, d_in[idx[i]], dims, strides, box, ones, CU_TENSOR_MAP_INTERLEAVE_NONE,
               CU_TENSOR_MAP_SWIZZLE_128B, CU_TENSOR_MAP_L2_PROMOTION_L2_128B, CU_TENSOR_MAP_FLOAT_OOB_FILL_NONE);
        p.w[i] = (const char*)d_in[idx[i]];
    }
    {
        void* kv = nullptr;
        cudaGetSymbolAddress(&kv, g_kvq);
        const cuuint64_t dims[2] = {64, 16384};
        const cuuint64_t strides[1] = {128};
        const cuuint32_t box[2] = {64, 128};
        encode(&p.tm[8], CU_TENSOR_MAP_DATA_TYPE_BFLOAT16, 2, kv, dims, strides, box, ones, CU_TENSOR_MAP_INTERLEAVE_NONE,
               CU_TENSOR_MAP_SWIZZLE_NONE, CU_TENSOR_MAP_L2_PROMOTION_L2_128B, CU_TENSOR_MAP_FLOAT_OOB_FILL_NONE);
    }
    p.x = (const __nv_bfloat16*)d_in[0];
    p.dw = (const __nv_bfloat16*)d_in[6];
    p.out = (__nv_bfloat16*)d_out;
    p.zero = 0;
    conformer_kernel<<<NCTA, NTHREADS, SMEM_LAUNCH>>>(p);
}
```

```cpp
#include <cuda_runtime.h>
#include <cuda_bf16.h>
#include <cuda.h>
#include <stdint.h>

namespace {

constexpr int T_ = 1000;
constexpr int NCTA = 128;
constexpr int NTHREADS = 512;
constexpr int NSLOT = 5;
constexpr int SLOT = 16384;
constexpr int NLOADS = 56;

constexpr uint32_t OFF_RING = 0;
constexpr uint32_t OFF_P = 163840;
constexpr uint32_t OFF_H = 188416;
constexpr uint32_t OFF_MISC = 221184;
constexpr uint32_t OFF_BARS = 229888;
constexpr uint32_t SMEM_BYTES = 230400;
constexpr uint32_t GCH = 6144;
constexpr uint32_t HCH = 4096;

constexpr int B_FULL = 0, B_EMPTY = 10, B_XA = 20  , B_XB = 25  , B_INB = 29  , B_SR = 33,
              B_RST = 34  , B_RDY = 36  , B_SINK = 42, B_HALO = 43  , NBARS = 47;

#define KD2 300u
#define KD3 500u
#define QGATE 500u
#define BACKOFF 0u
#define KFS 8
#define KDELAY 300u
#define NJ0 2
#define HDELAY 200u
#define LATE 2
#define SND 0
#define PF0 1
#define TURN 0x200
#define EAGER 0x0155
constexpr int FS = 8;

struct Params {
    CUtensorMap tm[9];
    const char* w[8];
    const __nv_bfloat16* x;
    const __nv_bfloat16* dw;
    __nv_bfloat16* out;
    uint32_t zero;
};

__device__ __align__(1024) unsigned char g_kvq[3 * 8 * 1024 * 128];
__device__ __align__(1024) unsigned char g_o[2 * 128 * 4096];
__device__ uint4 g_halo[64 * 4 * 2 * 64];
__device__ __align__(128) uint32_t g_flag_kv[8 * 32 * KFS];
__device__ uint32_t g_reset[4 * 32];
__device__ uint32_t g_epoch[NCTA * FS];

#define TS(i) do { } while (0)
#define TSW(i) do { } while (0)
#define TG(i) do { } while (0)
#define TSINIT() do { } while (0)
#define TSDUMP() do { } while (0)
constexpr uint32_t SMEM_LAUNCH = SMEM_BYTES;

__device__ __forceinline__ uint32_t smem_u32(const void* p) { return (uint32_t)__cvta_generic_to_shared(p); }
__device__ __forceinline__ void mbar_init(uint32_t b, uint32_t c) { asm volatile("mbarrier.init.shared::cta.b64 [%0], %1;" ::"r"(b), "r"(c) : "memory"); }
__device__ __forceinline__ void mbar_arrive(uint32_t b) { asm volatile("mbarrier.arrive.shared::cta.b64 _, [%0];" ::"r"(b) : "memory"); }
__device__ __forceinline__ void mbar_arrive_tx(uint32_t b, uint32_t tx) { asm volatile("mbarrier.arrive.expect_tx.shared::cta.b64 _, [%0], %1;" ::"r"(b), "r"(tx) : "memory"); }
__device__ __forceinline__ void mbar_wait(uint32_t b, uint32_t ph) {
    asm volatile("{\n.reg .pred p, q;\n.reg .u32 c;\nmov.u32 c, 0;\n"
                 "MW_LOOP:\n.pragma \"nounroll\";\n"
                 "mbarrier.try_wait.parity.shared::cta.b64 p, [%0], %1;\n"
                 "add.u32 c, c, 1;\nsetp.lt.u32 q, c, 65536;\nnot.pred p, p;\nand.pred p, p, q;\n@p bra MW_LOOP;\n}"
                 ::"r"(b), "r"(ph) : "memory");
}
__device__ __forceinline__ bool mbar_test(uint32_t b, uint32_t ph) {
    uint32_t ok;
    asm volatile("{\n.reg .pred p;\nmbarrier.test_wait.parity.shared::cta.b64 p, [%1], %2;\nselp.u32 %0, 1, 0, p;\n}" : "=r"(ok) : "r"(b), "r"(ph) : "memory");
    return ok;
}
__device__ __forceinline__ uint32_t mapa(uint32_t a, uint32_t r) { uint32_t o; asm("mapa.shared::cluster.u32 %0, %1, %2;" : "=r"(o) : "r"(a), "r"(r)); return o; }
__device__ __forceinline__ void fence_async_smem() { asm volatile("fence.proxy.async.shared::cta;" ::: "memory"); }
__device__ __forceinline__ void fence_async_global() { asm volatile("fence.proxy.async.global;" ::: "memory"); }
__device__ __forceinline__ void bar_sync(int id, int n) { asm volatile("bar.sync %0, %1;" ::"r"(id), "r"(n) : "memory"); }
__device__ __forceinline__ void bar_arrive(int id, int n) { asm volatile("bar.arrive %0, %1;" ::"r"(id), "r"(n) : "memory"); }
__device__ __forceinline__ void cluster_arrive() { asm volatile("barrier.cluster.arrive.relaxed.aligned;" ::: "memory"); }
__device__ __forceinline__ void cluster_wait() { asm volatile("barrier.cluster.wait.aligned;" ::: "memory"); }

__device__ __forceinline__ void ring_load(uint32_t dst, const CUtensorMap* tm, int col, int row16, uint32_t bar) {
    asm volatile("{\n.reg .pred p;\nelect.sync _|p, 0xffffffff;\n"
                 "@p mbarrier.arrive.expect_tx.shared::cta.b64 _, [%2], 16384;\n"
                 "@p cp.async.bulk.tensor.5d.shared::cluster.global.mbarrier::complete_tx::bytes [%0], [%1, {%3, 0, 0, 0, %4}], [%2];\n}"
                 ::"r"(dst), "l"(tm), "r"(bar), "r"(col), "r"(row16) : "memory");
}
__device__ __forceinline__ void ring_load_both(uint32_t dst, const CUtensorMap* tm, int c1, uint32_t bar) {
    asm volatile("{\n.reg .pred p;\nelect.sync _|p, 0xffffffff;\n"
                 "@p cp.async.bulk.tensor.2d.shared::cluster.global.mbarrier::complete_tx::bytes.multicast::cluster [%0], [%1, {0, %3}], [%2], %4;\n}"
                 ::"r"(dst), "l"(tm), "r"(bar), "r"(c1), "h"((uint16_t)3) : "memory");
}
__device__ __forceinline__ void mbar_arrive_peer(uint32_t b) { asm volatile("mbarrier.arrive.relaxed.cluster.shared::cluster.b64 _, [%0];" ::"r"(b) : "memory"); }
__device__ __forceinline__ void prefetch_l2(const void* src, uint32_t bytes) {
    asm volatile("cp.async.bulk.prefetch.L2.global [%0], %1;" ::"l"(src), "r"(bytes) : "memory");
}
__device__ __forceinline__ void peer_copy(uint32_t dst, uint32_t src, uint32_t bytes, uint32_t rbar) {
    asm volatile("{\n.reg .pred p;\nelect.sync _|p, 0xffffffff;\n"
                 "@p cp.async.bulk.shared::cluster.shared::cta.mbarrier::complete_tx::bytes [%0], [%1], %2, [%3];\n}"
                 ::"r"(dst), "r"(src), "r"(bytes), "r"(rbar) : "memory");
}
__device__ __forceinline__ void st_async4(uint32_t dst, uint32_t a, uint32_t b, uint32_t c, uint32_t d, uint32_t bar) {
    asm volatile("st.async.shared::cluster.mbarrier::complete_tx::bytes.v4.b32 [%0], {%1,%2,%3,%4}, [%5];" ::"r"(dst), "r"(a), "r"(b), "r"(c), "r"(d), "r"(bar) : "memory");
}
__device__ __forceinline__ void put_sums(uint32_t dst, uint32_t rdst, float a, float b, uint32_t rbar, bool on) {
    asm volatile("{\n.reg .pred p;\nsetp.ne.u32 p, %5, 0;\n"
                 "@p st.async.shared::cluster.mbarrier::complete_tx::bytes.v2.f32 [%1], {%2,%3}, [%4];\n"
                 "@p st.shared.v2.f32 [%0], {%2,%3};\n}" ::"r"(dst), "r"(rdst), "f"(a), "f"(b), "r"(rbar), "r"((uint32_t)on) : "memory");
}
__device__ __forceinline__ void stsm4(uint32_t a, uint32_t r0, uint32_t r1, uint32_t r2, uint32_t r3) {
    asm volatile("stmatrix.sync.aligned.m8n8.x4.shared.b16 [%0], {%1,%2,%3,%4};" ::"r"(a), "r"(r0), "r"(r1), "r"(r2), "r"(r3) : "memory");
}
__device__ __forceinline__ void ldsm4(uint32_t a, uint32_t& r0, uint32_t& r1, uint32_t& r2, uint32_t& r3) {
    asm volatile("ldmatrix.sync.aligned.m8n8.x4.shared.b16 {%0,%1,%2,%3}, [%4];" : "=r"(r0), "=r"(r1), "=r"(r2), "=r"(r3) : "r"(a) : "memory");
}
__device__ __forceinline__ uint4 lds128(uint32_t a) { uint4 v; asm volatile("ld.shared.v4.b32 {%0,%1,%2,%3}, [%4];" : "=r"(v.x), "=r"(v.y), "=r"(v.z), "=r"(v.w) : "r"(a) : "memory"); return v; }
__device__ __forceinline__ float4 lds128f(uint32_t a) { float4 v; asm volatile("ld.shared.v4.f32 {%0,%1,%2,%3}, [%4];" : "=f"(v.x), "=f"(v.y), "=f"(v.z), "=f"(v.w) : "r"(a) : "memory"); return v; }
__device__ __forceinline__ float2 lds64f(uint32_t a) { float2 v; asm volatile("ld.shared.v2.f32 {%0,%1}, [%2];" : "=f"(v.x), "=f"(v.y) : "r"(a) : "memory"); return v; }
__device__ __forceinline__ uint32_t lds32(uint32_t a) { uint32_t v; asm volatile("ld.shared.b32 %0, [%1];" : "=r"(v) : "r"(a) : "memory"); return v; }
__device__ __forceinline__ void sts128(uint32_t a, uint32_t x, uint32_t y, uint32_t z, uint32_t w) { asm volatile("st.shared.v4.b32 [%0], {%1,%2,%3,%4};" ::"r"(a), "r"(x), "r"(y), "r"(z), "r"(w) : "memory"); }
__device__ __forceinline__ void sts128f(uint32_t a, float x, float y, float z, float w) { asm volatile("st.shared.v4.f32 [%0], {%1,%2,%3,%4};" ::"r"(a), "f"(x), "f"(y), "f"(z), "f"(w) : "memory"); }
__device__ __forceinline__ void sts64f(uint32_t a, float x, float y) { asm volatile("st.shared.v2.f32 [%0], {%1,%2};" ::"r"(a), "f"(x), "f"(y) : "memory"); }
__device__ __forceinline__ void sts32(uint32_t a, uint32_t x) { asm volatile("st.shared.b32 [%0], %1;" ::"r"(a), "r"(x) : "memory"); }
__device__ __forceinline__ void stg128(void* p, uint4 v) { asm volatile("st.global.v4.b32 [%0], {%1,%2,%3,%4};" ::"l"(p), "r"(v.x), "r"(v.y), "r"(v.z), "r"(v.w) : "memory"); }

__device__ __forceinline__ uint32_t pack2(float lo, float hi) { uint32_t r; asm("cvt.rn.bf16x2.f32 %0, %1, %2;" : "=r"(r) : "f"(hi), "f"(lo)); return r; }
__device__ __forceinline__ float blo(uint32_t v) { return __uint_as_float(v << 16); }
__device__ __forceinline__ float bhi(uint32_t v) { return __uint_as_float(v & 0xffff0000u); }
__device__ __forceinline__ uint32_t hmul2(uint32_t a, uint32_t b) { uint32_t r; asm("mul.rn.bf16x2 %0, %1, %2;" : "=r"(r) : "r"(a), "r"(b)); return r; }
__device__ __forceinline__ uint32_t hadd2(uint32_t a, uint32_t b) { uint32_t r; asm("add.rn.bf16x2 %0, %1, %2;" : "=r"(r) : "r"(a), "r"(b)); return r; }
__device__ __forceinline__ uint32_t hsub2(uint32_t a, uint32_t b) { uint32_t r; asm("sub.rn.bf16x2 %0, %1, %2;" : "=r"(r) : "r"(a), "r"(b)); return r; }
__device__ __forceinline__ uint32_t hfma2(uint32_t a, uint32_t b, uint32_t c) { uint32_t r; asm("fma.rn.bf16x2 %0, %1, %2, %3;" : "=r"(r) : "r"(a), "r"(b), "r"(c)); return r; }
__device__ __forceinline__ float tanh_fast(float x) { float r; asm("tanh.approx.f32 %0, %1;" : "=f"(r) : "f"(x)); return r; }
__device__ __forceinline__ float rsq(float x) { float r; asm("rsqrt.approx.ftz.f32 %0, %1;" : "=f"(r) : "f"(x)); return r; }
__device__ __forceinline__ float ex2(float x) { float r; asm("ex2.approx.ftz.f32 %0, %1;" : "=f"(r) : "f"(x)); return r; }

__device__ __forceinline__ uint32_t ld_relaxed(const uint32_t* p) {
    uint32_t v;
    asm volatile("ld.relaxed.gpu.global.u32 %0, [%1];" : "=r"(v) : "l"(p) : "memory");
    return v;
}
__device__ __forceinline__ uint32_t clock32() { uint32_t c; asm volatile("mov.u32 %0, %%clock;" : "=r"(c)::"memory"); return c; }
__device__ __forceinline__ void spin(uint32_t clks) {
    const uint32_t t0 = clock32();
    while (clock32() - t0 < clks) {}
}
__device__ __forceinline__ void flag_wait(const uint32_t* p, uint32_t e, bool mine) {
#pragma unroll 1
    for (int i = 0; i < (1 << 19); i++) {
        if (mine) mine = ld_relaxed(p) != e;
        if (!__any_sync(~0u, mine)) break;
        if (BACKOFF) spin(BACKOFF);
    }
    asm volatile("fence.acquire.gpu;" ::: "memory");
    fence_async_global();
}
__device__ __forceinline__ void st_data(void* p, uint32_t x, uint32_t y, uint32_t z, uint32_t w) {
    asm volatile("st.relaxed.gpu.global.v4.b32 [%0], {%1,%2,%3,%4};" ::"l"(p), "r"(x), "r"(y), "r"(z), "r"(w) : "memory");
}
template <int STRIDE, int N>
__device__ __forceinline__ void ld_data(uint4 (&v)[N], const unsigned char* p) {
    int it = 0;
    bool again;
#pragma unroll 1
    do {
        uint32_t m = 0;
#pragma unroll
        for (int i = 0; i < N; i++)
            asm volatile("ld.relaxed.gpu.global.v4.b32 {%0,%1,%2,%3}, [%4];" : "=r"(v[i].x), "=r"(v[i].y), "=r"(v[i].z), "=r"(v[i].w) : "l"(p + i * STRIDE) : "memory");
#pragma unroll
        for (int i = 0; i < N; i++) m = __vimax3_u32(__vimax3_u32(v[i].x, v[i].y, v[i].z), v[i].w, m);
        again = __any_sync(~0u, m == ~0u) && ++it < (1 << 16);
    } while (again);
}
__device__ __forceinline__ uint32_t ld_epoch() { return ld_relaxed(&g_epoch[blockIdx.x * FS]) + 1; }
__device__ __forceinline__ void flag_set(uint32_t* p, uint32_t e) { asm volatile("st.release.gpu.global.u32 [%0], %1;" ::"l"(p), "r"(e) : "memory"); }

__device__ __forceinline__ uint32_t desc_lo(uint32_t addr) { return ((addr & 0x3FFFF) >> 4) | 0x10000u; }
__device__ __forceinline__ uint64_t mkdesc(uint32_t lo) { return (uint64_t)lo | (0x40000040ull << 32); }
__device__ __forceinline__ void wg_fence() { asm volatile("wgmma.fence.sync.aligned;" ::: "memory"); }
__device__ __forceinline__ void wg_commit() { asm volatile("wgmma.commit_group.sync.aligned;" ::: "memory"); }
template <int N> __device__ __forceinline__ void wg_wait() { asm volatile("wgmma.wait_group.sync.aligned %0;" ::"n"(N) : "memory"); }
template <int N> __device__ __forceinline__ void pin(float (&d)[N]) {
#pragma unroll
    for (int i = 0; i < N; i++) asm volatile("" : "+f"(d[i])::"memory");
}
template <int N> __device__ __forceinline__ void pin(uint32_t (&d)[N]) {
#pragma unroll
    for (int i = 0; i < N; i++) asm volatile("" : "+r"(d[i])::"memory");
}

template <typename Tp, int N> __device__ __forceinline__ void zero(Tp (&d)[N]) {
#pragma unroll
    for (int i = 0; i < N; i++) d[i] = 0;
    pin(d);
}

#define F4(d, i) "+f"(d[i]), "+f"(d[i + 1]), "+f"(d[i + 2]), "+f"(d[i + 3])
#define F16(d, i) F4(d, i), F4(d, i + 4), F4(d, i + 8), F4(d, i + 12)

__device__ __forceinline__ void mma16(float (&d)[4], const uint32_t* a, uint32_t b0, uint32_t b1) {
    asm("mma.sync.aligned.m16n8k16.row.col.f32.bf16.bf16.f32 {%0,%1,%2,%3}, {%4,%5,%6,%7}, {%8,%9}, {%0,%1,%2,%3};"
        : F4(d, 0) : "r"(a[0]), "r"(a[1]), "r"(a[2]), "r"(a[3]), "r"(b0), "r"(b1));
}
template <int N>
__device__ __forceinline__ float row_sum(const uint32_t* x) {
    float c[4] = {};
#pragma unroll
    for (int i = 0; i < N; i += 4) mma16(c, x + i, 0x3F803F80u, 0x3F803F80u);
    return c[0] + c[2];
}
template <int N>
__device__ __forceinline__ float row_sumsq(const uint32_t* x, int lane) {
    float c0[4] = {}, c1[4] = {};
#pragma unroll
    for (int i = 0; i < N; i += 4) {
        mma16(c0, x + i, x[i], x[i + 2]);
        mma16(c1, x + i, x[i + 1], x[i + 3]);
    }
    return (lane & 4) ? c0[1] + c1[3] : c0[0] + c1[2];
}
__device__ __forceinline__ void mma_sp(float (&d)[32], const uint32_t* a, uint64_t b, uint32_t meta, int acc) {
    asm volatile("{.reg .pred p; setp.ne.b32 p, %38, 0;\n"
                 "wgmma.mma_async.sp.sync.aligned.m64n64k32.f32.bf16.bf16 {%0,%1,%2,%3,%4,%5,%6,%7,%8,%9,%10,%11,%12,%13,%14,%15,%16,%17,%18,%19,%20,%21,%22,%23,%24,%25,%26,%27,%28,%29,%30,%31}, "
                 "{%32,%33,%34,%35}, %36, %37, 0, p, 1, 1, 1;}\n"
                 : F16(d, 0), F16(d, 16) : "r"(a[0]), "r"(a[1]), "r"(a[2]), "r"(a[3]), "l"(b), "r"(meta), "r"(acc));
}
__device__ __forceinline__ void mma_qk(float (&d)[32], uint32_t a0, uint32_t a1, uint32_t a2, uint32_t a3, uint64_t b, int acc) {
    asm volatile("{.reg .pred p; setp.ne.b32 p, %37, 0;\n"
                 "wgmma.mma_async.sync.aligned.m64n64k16.f32.bf16.bf16 {%0,%1,%2,%3,%4,%5,%6,%7,%8,%9,%10,%11,%12,%13,%14,%15,%16,%17,%18,%19,%20,%21,%22,%23,%24,%25,%26,%27,%28,%29,%30,%31}, "
                 "{%32,%33,%34,%35}, %36, p, 1, 1, 0;}\n"
                 : F16(d, 0), F16(d, 16) : "r"(a0), "r"(a1), "r"(a2), "r"(a3), "l"(b), "r"(acc));
}
__device__ __forceinline__ void mma_pv(float (&d)[36], uint32_t a0, uint32_t a1, uint32_t a2, uint32_t a3, uint64_t b) {
    asm volatile("wgmma.mma_async.sync.aligned.m64n72k16.f32.bf16.bf16 {%0,%1,%2,%3,%4,%5,%6,%7,%8,%9,%10,%11,%12,%13,%14,%15,%16,%17,%18,%19,%20,%21,%22,%23,%24,%25,%26,%27,%28,%29,%30,%31,%32,%33,%34,%35}, "
                 "{%36,%37,%38,%39}, %40, 1, 1, 1, 1;\n"
                 : F16(d, 0), F16(d, 16), F4(d, 32) : "r"(a0), "r"(a1), "r"(a2), "r"(a3), "l"(b));
}

__device__ __forceinline__ uint32_t load_code(int n, int r, int w) {
    const int tile = 2 * r + w;
    int m, col, row;
    if (n < 16 || n >= 40) {
        const int k = n < 16 ? n : n - 40;
        m = n < 16 ? 0 : 6;
        if (k < 8) { col = 4 * tile + (k >> 1); row = n < 16 ? (k & 1) : (k & 1) ^ r; }
        else { m++; col = k < 12 ? tile ^ 2 : tile; row = 2 * (tile ^ (k & 1)) + ((k >> 1) & 1); }
    } else if (n < 32) {
        const int k = n - 16;
        m = 2;
        if (k < 4) { col = tile + ((k & 1) ? 8 : 4); row = (k >> 1) ^ r; }
        else { col = tile; row = (k & 1) ^ r; }
    } else if (n < 34) { m = 3; col = tile; row = n - 32; }
    else if (n < 38) { const int k = n - 34; m = 4; col = tile + 4 * (k & 1); row = (k >> 1) ^ r; }
    else { m = 5; col = tile; row = (n & 1) ^ r; }
    return m | (col << 4) | (row << (m ? 11 : 10));
}

__global__ void __cluster_dims__(2, 1, 1) __launch_bounds__(NTHREADS, 1)
conformer_kernel(const __grid_constant__ Params p) {
    extern __shared__ __align__(1024) unsigned char smem_raw[];
    const uint32_t sb = smem_u32(smem_raw);
    const uint32_t bars = sb + OFF_BARS;
    const int tid = threadIdx.x;
    const int lane = tid & 31;
    const int warp = __shfl_sync(~0u, tid >> 5, 0);
    const int r = blockIdx.x & 1;
    const int pair = blockIdx.x >> 1;
    const int b = pair >> 5, pt = pair & 31;
    const int ah = pt >> 3, qt = (pt & 7) * 2 + r;
    const int abh = b * 4 + ah;

    TG(30);
    TSINIT();
    TS(0);
    const uint32_t P = sb + OFF_P, H = sb + OFF_H;
    if ((warp >> 1) == 4) {
        const uint32_t full = bars + (B_FULL + (warp & 1) * NSLOT) * 8;
        if (lane == 0) {
#pragma unroll
            for (int i = 0; i < NSLOT; i++) { mbar_init(full + i * 8, 1); mbar_init(full + (B_EMPTY - B_FULL + i) * 8, 4); }
            asm volatile("fence.mbarrier_init.release.cluster;" ::: "memory");
            fence_async_smem();
        }
        __syncwarp();
        cluster_arrive();
#pragma unroll
        for (int n = 0; n < NSLOT; n++) {
            if (n == 1 || n == 2) bar_sync(12, 64);
            ring_load(sb + OFF_RING + ((warp & 1) * NSLOT + n) * SLOT, &p.tm[0], 64 * (8 * r + 4 * (warp & 1) + (n >> 1)), 4 * (n & 1), full + n * 8);
        }
        TS(1);
    }

    if (warp >= 8) {
        asm volatile("setmaxnreg.dec.sync.aligned.u32 48;");
        if (warp >= 12) {
            cluster_arrive();
            cluster_wait();
            const int ut = tid & 127;
            const uint32_t target = ld_epoch() * 64;
            auto reset_done = [&](int k) {
                bar_sync(11, 128);
                if (ut == 0) {
                    asm volatile("red.release.gpu.global.add.u32 [%0], 1;" ::"l"(&g_reset[(2 * b + k) * 32]) : "memory");
#pragma unroll 1
                    for (int i = 0; i < (1 << 20) && ld_relaxed(&g_reset[(2 * b + k) * 32]) != target; i++) __nanosleep(100);
                    asm volatile("fence.acquire.gpu;" ::: "memory");
                    mbar_arrive(bars + (B_RST + k) * 8);
                }
                __syncwarp();
                TS(13 + k);
            };
#pragma unroll
            for (int i = 0; i < 4; i++)
                st_data(g_kvq + 2097152 + (size_t)((b * 4 + 2 * r + (i >> 1)) * 1024 + pt * 32) * 128 + (i & 1) * 2048 + ut * 16, ~0u, ~0u, ~0u, ~0u);
            reset_done(0);
            bar_sync(6, 384);
#pragma unroll
            for (int i = 0; i < 4; i++) {
                st_data(g_o + (size_t)(b * 128 + qt * 8 + 2 * i + (ut >> 6)) * 4096 + ah * 1024 + (ut & 63) * 16, ~0u, ~0u, ~0u, ~0u);
                if (i < 2) st_data(&g_halo[(pair * 4 + 2 * r + i) * 128 + ut], ~0u, ~0u, ~0u, ~0u);
            }
            reset_done(1);
            const int side = warp & 1, wg = (warp >> 1) & 1, np = side ? pt + 1 : pt - 1;
            const unsigned char* src = reinterpret_cast<const unsigned char*>(&g_halo[(((b * 32 + np) * 4 + 2 * r + wg) * 2 + (side ^ 1)) * 64 + lane]);
            const uint32_t dst = H + 16384 + wg * GCH + side * 5120 + (lane & 7) * 128 + (((lane >> 3) ^ (lane & 7)) << 4);
            uint4 hv[2] = {make_uint4(0, 0, 0, 0), make_uint4(0, 0, 0, 0)};
            bar_sync(8 + wg, 192);
            if (np >= 0 && np < 32) {
                spin(HDELAY);
                ld_data<512>(hv, src);
            }
            stsm4(dst, hv[0].x, hv[0].y, hv[0].z, hv[0].w);
            stsm4(dst ^ 64, hv[1].x, hv[1].y, hv[1].z, hv[1].w);
            __syncwarp();
            if (lane == 0) mbar_arrive(bars + (B_HALO + (warp & 3)) * 8);
            TS(4);
        } else if (warp < 10) {
            const int w = warp - 8;
            const uint32_t ring = sb + OFF_RING + w * NSLOT * SLOT;
            const uint32_t full = bars + (B_FULL + w * NSLOT) * 8;
            TS(2);
            const uint32_t code = load_code(lane, r, w) | (load_code(lane + 32, r, w) << 16);
            cluster_wait();
            uint32_t s = 0, ph = 0;
            int n = NSLOT;
#pragma unroll 1
            for (int seg = 0; seg < 2; seg++) {
#pragma unroll 1
                for (; n < (seg == 0 ? 22 : NLOADS); n++) {
                    const uint32_t c = __shfl_sync(~0u, code, n) >> (n & 32 ? 16 : 0);
                    const CUtensorMap* tm = &p.tm[c & 15];
                    const uint32_t col = (c & 0xf0) * 4, row = (c & 0xff00) >> 8, dst = ring + s * SLOT;
                    mbar_wait(full + (B_EMPTY - B_FULL) * 8 + s * 8, ph + (((uint32_t)(size_t)tm | col | row | dst) & p.zero));
                    ring_load(dst, tm, col, row, full + s * 8);
                    if (++s == NSLOT) { s = 0; ph ^= 1; }
                }
                if (seg == 1) break;
                const uint32_t epoch = ld_epoch();
                const uint32_t rdy = bars + (B_RDY + 3 * w) * 8, prdy = mapa(rdy, r ^ 1);
                const int odd = r ^ w;
                const uint32_t* flags = g_flag_kv + (abh * 32 + lane) * KFS;
                auto kv_load = [&](uint32_t sl, int isv, int i) {
                    ring_load_both(ring + sl * SLOT, &p.tm[8], (isv * 64 + abh * 8 + 2 * i + w) * 128, full + sl * 8);
                };
#pragma unroll 1
                for (int i = 0; i < 2; i++) {
                    if (lane < 3 + i) {
                        const uint32_t sl = i ? lane : lane + 2;
                        mbar_wait(full + (B_EMPTY - B_FULL + sl) * 8, i ^ 1);
                        mbar_arrive_tx(full + sl * 8, (i || lane == 2) ? SLOT : 0);
                    }
                    __syncwarp();
                }
                if (lane == 0) mbar_arrive_peer(prdy);
                bar_sync(14, 96);
                spin(KDELAY);
                mbar_wait(rdy, 0);
                flag_wait(flags, epoch, (lane >> 2) == 2 * odd + w);
                TSW(5 + 2 * odd);
                if (!odd) { kv_load(4, 0, 0); bar_arrive(12, 64); }
                else bar_sync(12, 64);
                spin(w ? KD3 : KD2);
                kv_load(odd ^ 1, odd ^ 1, odd);
                flag_wait(flags, epoch, (lane >> 2) == 2 * odd + w + 4);
                mbar_wait(full + (odd ^ 1) * 8, 1);
                kv_load(2 + odd, odd, 2 - odd);
#pragma unroll 1
                for (int i = 0; i < 3; i++) {
                    const uint32_t sl = i ? i - 1 : 4, bo = i == 2 ? 16 : 8;
                    mbar_wait(full + (B_EMPTY - B_FULL + sl) * 8, i != 0);
                    if (lane == 0) mbar_arrive_tx(full + sl * 8, SLOT);
                    if ((i & 1) != odd) {
                        mbar_wait(rdy + bo, 0);
                        kv_load(sl, i != 0, 2 + odd);
                    } else if (lane == 0) mbar_arrive_peer(prdy + bo);
                    __syncwarp();
                }
                n = 32; s = 2; ph = 1;
            }
        } else if (warp == 10) {
            if (lane == 0) {
#pragma unroll
                for (int i = B_XA; i < NBARS; i++) mbar_init(bars + i * 8, 1);
#pragma unroll
                for (int i = B_XA; i <= B_SR; i++) mbar_arrive_tx(bars + i * 8, i < B_XB ? 512 : ((i >= B_INB && i < B_SR) ? 4096 : 8192));
                asm volatile("fence.mbarrier_init.release.cluster;" ::: "memory");
                fence_async_smem();
            }
            __syncwarp();
            cluster_arrive();
            cluster_wait();
        } else {
            const uint32_t kb = (lane < 2 || lane > 5) ? 4096 : (lane == 2 ? 3072 : (lane == 4 ? 2048 : 1024));
            const char* pf = p.w[lane & 7] + blockIdx.x * kb;
            cluster_arrive();
            cluster_wait();
            if (lane < PF0) prefetch_l2(pf, kb);
            mbar_wait(bars + B_FULL * 8, 0);
            if (lane >= PF0 && lane < 3) prefetch_l2(pf, kb);
            if (lane >= 1 && lane < 9) asm volatile("prefetch.tensormap [%0];" ::"l"(&p.tm[lane]) : "memory");
            mbar_wait(bars + (B_FULL + 1) * 8, 1);
            if (lane > 2 && lane < 8) prefetch_l2(pf, kb);
            if (lane == 8 && blockIdx.x < 15) prefetch_l2(p.dw + blockIdx.x * 256, 512);
            const uint32_t epoch = ld_epoch();
            bar_sync(4, 288);
            if (lane < 16) flag_set(&g_flag_kv[((b * 4 + 2 * r + (lane >> 3)) * 32 + pt) * KFS + (lane & 7)], epoch);
            __syncwarp();
            bar_arrive(14, 96);
            TSW(8);
        }
        TSDUMP();
        return;
    }

    const int w = warp >> 2, wq = warp & 3;
    const int tile = 2 * r + w;
    const int wt = tid & 127;
    const int c4 = lane & 3;
    const int trow = pt * 32 + 8 * wq;
    uint32_t xr[8];
    uint32_t a[32];
    const char* xrow = reinterpret_cast<const char*>(p.x) + (b * T_ + trow + (lane >> 2)) * 512;
    zero(a);
    if (trow < T_) {
        const char* src = xrow + c4 * 16 + p.zero;
#pragma unroll
        for (int i = 0; i < 8; i++)
            asm volatile("ld.global.nc.v4.b32 {%0,%1,%2,%3}, [%4];" : "=r"(a[4 * i]), "=r"(a[4 * i + 1]), "=r"(a[4 * i + 2]), "=r"(a[4 * i + 3]) : "l"(src + 64 * i));
    }
    cluster_arrive();
    const uint32_t rbase = sb + OFF_RING + w * NSLOT * SLOT, fbar = bars + (B_FULL + w * NSLOT) * 8;
    const uint32_t rdesc = desc_lo(rbase);
    auto acq = [&](int n) { mbar_wait(fbar + (n % NSLOT) * 8, (n / NSLOT) & 1); };
    auto rel = [&](int n) { if (lane == 0) mbar_arrive(fbar + (B_EMPTY - B_FULL + n % NSLOT) * 8); };
    const uint32_t foff = (lane & 7) * 128 + (((lane >> 3) ^ (lane & 7)) << 4);
    float v[16];
    const uint32_t xown = __shfl_sync(~0u, P + wt * 16 + tile * 4096, lane), xrem = __shfl_sync(~0u, P + wt * 16 + (r ^ 1) * 8192, lane);
    const uint32_t sbuf = __shfl_sync(~0u, sb + OFF_MISC + 1024 + (8 * wq + (lane >> 2)) * 32, lane);
    const uint32_t sown = __shfl_sync(~0u, sbuf + tile * 8, lane);
    const uint32_t peer = __shfl_sync(~0u, mapa(sb, r ^ 1) - sb, lane);
    const uint32_t hbuf = __shfl_sync(~0u, H + w * 4096 + wt * 16, lane);
    const uint32_t meta = __shfl_sync(~0u, 0xEEEE4444u + p.zero, lane);
    cluster_wait();
    TS(56);
    float mean, msq;
    const int mir = wq < 2 ? 7 : 0;
    uint32_t dwr[15] = {};

#pragma unroll
    for (int ph = 0; ph < 5; ph++) {
        uint4 o0, o1;
        if (ph == 0) {
            mean = ((row_sum<8>(a) + row_sum<8>(a + 8)) + (row_sum<8>(a + 16) + row_sum<8>(a + 24))) * (1.f / 256.f);
            TS(57);
        } else {
            const uint32_t xa = bars + (B_XA + ph) * 8;
#pragma unroll
            for (int j = 0; j < 8; j++) xr[j] = pack2(v[2 * j], v[2 * j + 1]);
            const float s = row_sum<8>(xr), q = row_sumsq<8>(xr, lane);
            if (ph < 4) {
                sts128(xown, xr[0], xr[1], xr[2], xr[3]);
                sts128(xown + 2048, xr[4], xr[5], xr[6], xr[7]);
            }
            put_sums(sown, sown + peer, s, q, xa + peer, c4 == (lane >> 3));
            bar_sync(10, 256);
            if (ph < 4) {
                o0 = lds128(xown ^ 4096); o1 = lds128((xown ^ 4096) + 2048);
                st_async4(xown + peer, xr[0], xr[1], xr[2], xr[3], xa + (B_XB - B_XA) * 8 + peer);
                st_async4(xown + peer + 2048, xr[4], xr[5], xr[6], xr[7], xa + (B_XB - B_XA) * 8 + peer);
            }
            TS(57 + ph);
            if (ph == 3) acq(0);
            if (ph == 1) acq(16);
            mbar_wait(xa, 0);
            const float4 u0 = lds128f(sbuf), u1 = lds128f(sbuf + 16);
            mean = ((u0.x + u0.z) + (u1.x + u1.z)) * (1.f / 256.f);
            msq = ((u0.y + u0.w) + (u1.y + u1.w)) * (1.f / 256.f);
        }
        if (ph == 4) break;
        const uint32_t mean2 = pack2(mean, mean);
        auto centre = [&](int i, const uint4& u) {
            a[i] = hsub2(u.x, mean2); a[i + 1] = hsub2(u.y, mean2); a[i + 2] = hsub2(u.z, mean2); a[i + 3] = hsub2(u.w, mean2);
        };
        if (ph == 0) {
#pragma unroll
            for (int j = 0; j < 32; j++) a[j] = hsub2(a[j], mean2);
            pin(a);
            asm volatile("setmaxnreg.inc.sync.aligned.u32 208;");
            acq(0);
        } else {
#pragma unroll
            for (int j = 0; j < 8; j++) a[j] = hsub2(xr[j], mean2);
            centre(8, o0); centre(12, o1);
        }
        float rstd = ph ? rsq(fmaxf(fmaf(-mean, mean, msq), 0.f) + 1e-5f) : 0.f;
        auto gather_peer = [&]() {
            mbar_wait(bars + (B_XB + ph) * 8, 0);
#pragma unroll
            for (int i = 0; i < 4; i++) centre(16 + 4 * i, lds128(xrem + i * 2048));
        };
        auto sp = [&](float (&d)[32], int n, const uint32_t* af, int flip, int acc) {
            const uint32_t lo = rdesc + p.zero * (ph * 64 + n + 1) + (n % NSLOT) * (SLOT >> 4);
            const uint64_t b0 = mkdesc(lo + flip * 512), b1 = mkdesc(lo + (flip ^ 1) * 512);
            wg_fence();
            mma_sp(d, af, b0, meta, acc);
            mma_sp(d, af + 4, b0 + 256, meta, 1);
            mma_sp(d, af + 8, b1, meta, 1);
            mma_sp(d, af + 12, b1 + 256, meta, 1);
            wg_commit();
        };
        float d0[32], d1[32];

        if (ph == 0 || ph == 3) {
            uint32_t h[32], ho[32];
            float rs = 0.5f * rstd;
            const uint32_t inb = bars + (B_INB + (ph & 2) + w) * 8;
            bool ready = true;
            const int eager = ph ? EAGER : EAGER - 1;
            auto step = [&](float (&d)[32], int n, const uint32_t* af, int flip, int acc, auto work) {
                if (!ready) acq(n);
                if (((TURN >> n) & 1) && w == 1) bar_sync(7, 256);
                sp(d, n, af, flip, acc);
                if (n > 0 && ((TURN >> (n - 1)) & 1) && w == 0) bar_arrive(7, 256);
                if (n < 15) ready = mbar_test(fbar + ((n + 1) % NSLOT) * 8, ((n + 1) / NSLOT) & 1);
                wg_wait<1>();
                if (n > 0 && !((eager >> (n - 1)) & 1)) rel(n - 1);
                const uint32_t tie = work() & p.zero;
                if ((eager >> n) & 1) {
                    if (p.zero < n + ph + 1) wg_wait<0>();
                    if (lane == 0) mbar_arrive(fbar + (B_EMPTY - B_FULL + n % NSLOT) * 8 + tie);
                }
            };
            auto none = []() { return 0u; };
            const int fl = ph ? w : 0;
            auto fetch = [&](int i) {
                bar_sync(10, 256);
                const uint4 u0 = lds128((hbuf ^ 4096) + (i & 1) * 8192), u1 = lds128((hbuf ^ 4096) + (i & 1) * 8192 + 2048);
                ho[8 * i] = u0.x; ho[8 * i + 1] = u0.y; ho[8 * i + 2] = u0.z; ho[8 * i + 3] = u0.w;
                ho[8 * i + 4] = u1.x; ho[8 * i + 5] = u1.y; ho[8 * i + 6] = u1.z; ho[8 * i + 7] = u1.w;
                return u0.x | u1.x;
            };
            auto act = [&](float (&d)[32], int i) {
                if (i > 0) fetch(i - 1);
                pin(d);
#pragma unroll
                for (int j = 0; j < 8; j++) {
                    const float u0 = (d[4 * j] + d[4 * j + 2]) * rs, u1 = (d[4 * j + 1] + d[4 * j + 3]) * rs;
                    h[8 * i + j] = pack2(fmaf(u0, tanh_fast(u0), u0), fmaf(u1, tanh_fast(u1), u1));
                }
                sts128(hbuf + (i & 1) * 8192, h[8 * i], h[8 * i + 1], h[8 * i + 2], h[8 * i + 3]);
                sts128(hbuf + (i & 1) * 8192 + 2048, h[8 * i + 4], h[8 * i + 5], h[8 * i + 6], h[8 * i + 7]);
                return 0u;
            };
            TS(1 + (ph & 2) * 10);
            step(d0, 0, a, fl, 0, [&]() {
                if (ph) gather_peer();
                else {
                    const float dm = mean - blo(mean2);
                    const float ms = __shfl_sync(~0u, row_sumsq<32>(a, lane), (lane & 28) + (lane >> 3)) * (1.f / 256.f);
                    rs = 0.5f * rsq(fmaxf(fmaf(-dm, dm, ms), 0.f) + 1e-5f);
                    zero(xr);
                    if (trow < T_) {
                        const char* src = xrow + tile * 128 + c4 * 4 + p.zero;
#pragma unroll
                        for (int j = 0; j < 8; j++) asm volatile("ld.global.nc.b32 %0, [%1];" : "=r"(xr[j]) : "l"(src + 16 * j));
                    }
                }
                return 0u;
            });
            TS(32);
            step(d0, 1, a + 16, 0, 1, none);
            step(d1, 2, a, fl, 0, [&]() { return act(d0, 0); });
            step(d1, 3, a + 16, 0, 1, none);
            step(d0, 4, a, fl, 0, [&]() { return act(d1, 1); });
            TS(33);
            step(d0, 5, a + 16, 0, 1, none);
            step(d1, 6, a, fl, 0, [&]() { return act(d0, 2); });
            step(d1, 7, a + 16, 0, 1, none);
            step(d0, 8, h, 0, 0, [&]() { act(d1, 3); return fetch(3); });
            TS(2 + (ph & 2) * 10);
            step(d0, 9, ho, 0, 1, none);
            step(d0, 10, h + 16, 0, 1, none);
            step(d0, 11, ho + 16, 0, 1, none);
            uint32_t pk[8];
            auto pack_out = [&]() {
                pin(d0);
#pragma unroll
                for (int j = 0; j < 8; j++) pk[j] = pack2(d0[4 * j] + d0[4 * j + 2], d0[4 * j + 1] + d0[4 * j + 3]);
            };
            auto send = [&](int i) { st_async4(hbuf + 16384 + i * 2048 + peer, pk[4 * i], pk[4 * i + 1], pk[4 * i + 2], pk[4 * i + 3], inb + peer); };
            step(d1, 12, h, 0, 0, [&]() { pack_out(); if (SND != 1) send(0); if (SND == 0) send(1); return 0u; });
            TS(34);
            step(d1, 13, ho, 0, 1, [&]() { if (SND == 1) send(0); if (SND) send(1); return 0u; });
            step(d1, 14, h + 16, 0, 1, none);
            step(d1, 15, ho + 16, 0, 1, none);
            mbar_wait(inb, 0);
#pragma unroll
            for (int i = 0; i < 2; i++) {
                const uint4 u = lds128(hbuf + 16384 + i * 2048);
                const uint32_t p0[4] = {u.x, u.y, u.z, u.w};
#pragma unroll
                for (int j = 0; j < 4; j++) {
                    v[8 * i + 2 * j] = fmaf(0.5f, blo(p0[j]), blo(xr[4 * i + j]));
                    v[8 * i + 2 * j + 1] = fmaf(0.5f, bhi(p0[j]), bhi(xr[4 * i + j]));
                }
            }
            wg_wait<0>();
            pin(d1);
            rel(15);
            TS(3 + (ph & 2) * 10);
#pragma unroll
            for (int j = 0; j < 8; j++) {
                v[2 * j] = fmaf(0.5f, d1[4 * j] + d1[4 * j + 2], v[2 * j]);
                v[2 * j + 1] = fmaf(0.5f, d1[4 * j + 1] + d1[4 * j + 3], v[2 * j + 1]);
            }
#pragma unroll
            for (int i = 0; i < 15; i++) dwr[i] = 0;
            continue;
        }

        auto residual = [&](int n) {
            wg_wait<1>();
            rel(n);
            wg_wait<0>();
            pin(d0);
            rel(n + 1);
#pragma unroll
            for (int j = 0; j < 8; j++) {
                v[2 * j] = d0[4 * j] + d0[4 * j + 2] + blo(xr[j]);
                v[2 * j + 1] = d0[4 * j + 1] + d0[4 * j + 3] + bhi(xr[j]);
            }
        };

        if (ph == 2) {
            TS(39);
            sp(d0, 34, a, w, 0);
            acq(35);
            sp(d1, 35, a, w, 0);
            acq(36); acq(37);
            gather_peer();
            sp(d0, 36, a + 16, 0, 1);
            sp(d1, 37, a + 16, 0, 1);
            wg_wait<2>();
            rel(34);
            if (!(LATE & 1)) rel(35);
            acq(38);
            const float rs = trow < T_ ? 0.5f * rstd : 0.f;
            wg_wait<0>();
            pin(d0); pin(d1);
            if (!(LATE & 2)) { rel(36); rel(37); }
            TS(18);
            uint32_t pk[8];
#pragma unroll
            for (int j = 0; j < 8; j++) {
                const float u0 = (d0[4 * j] + d0[4 * j + 2]) * rs, u1 = (d0[4 * j + 1] + d0[4 * j + 3]) * rs;
                const float t0 = tanh_fast((d1[4 * j] + d1[4 * j + 2]) * rs), t1 = tanh_fast((d1[4 * j + 1] + d1[4 * j + 3]) * rs);
                pk[j] = pack2(fmaf(u0, t0, u0), fmaf(u1, t1, u1));
            }
            if (wq == 0 || wq == 3) {
                uint4* hp = &g_halo[((pair * 4 + tile) * 2 + (wq & 1)) * 64 + lane];
                st_data(hp, pk[0], pk[1], pk[2], pk[3]);
                st_data(hp + 32, pk[4], pk[5], pk[6], pk[7]);
            }
            const uint32_t gs = H + 16384 + w * GCH + wq * 1024;
            stsm4(gs + 1024 + foff, pk[0], pk[1], pk[2], pk[3]);
            stsm4(gs + 1024 + (foff ^ 64), pk[4], pk[5], pk[6], pk[7]);
            bar_sync(8 + w, 192);
            TS(26);
            uint32_t ca[8], cb[8];
            const int e = (wq & 1) * 4;
            const uint32_t lo = ((mir ^ e) * 144) ^ (lane * 4);
            const int dir = mir ? -1024 : 1024;
            const uint32_t gb = H + 16384 + w * GCH + (mir ? 3072 : 2048) + lo, sown_ = H + tile * HCH, so = sown_ + (mir ? 1024 : 2048) + lo;
            auto finish = [&](int i) {
                const uint32_t c = hadd2(ca[i], cb[i]);
                const float h0 = blo(c), h1 = bhi(c);
                sts32((so + (i >> 2) * dir) ^ ((i & 3) * 144), pack2(fmaf(h0, tanh_fast(h0), h0), fmaf(h1, tanh_fast(h1), h1)));
            };
#pragma unroll
            for (int k = 0; k < 26; k++) {
                if (k == 19) {
#pragma unroll
                    for (int i = 0; i < 4; i++) finish(i);
                    fence_async_smem();
                    bar_sync(2 + w, 128);
                    if (wq == 0) peer_copy(mapa(sown_ + 1024, r ^ 1), sown_ + 1024, 2048, mapa(bars + B_SR * 8, r ^ 1));
                    mbar_wait(bars + (B_HALO + 2 * w + (wq >> 1)) * 8, 0);
                    if (LATE & 1) rel(35);
                    if (LATE & 2) { rel(36); rel(37); }
                    TS(27);
                }
                const uint32_t g = lds32((gb + (((k + 1) & 4) ? ((k + 1) >> 3) + (wq & 1) : ((k + 1) >> 3)) * dir) ^ (((k + 1) & 7) * 144));
#pragma unroll
                for (int i = 0; i < 8; i++) {
                    const int tap = k - (i & 3) - 2 * (i & 4);
                    if (tap == 0) ca[i] = hmul2(g, dwr[0]);
                    else if (tap > 0 && tap < 8) ca[i] = hfma2(g, dwr[tap], ca[i]);
                    else if (tap == 8) cb[i] = hmul2(g, dwr[8]);
                    else if (tap > 8 && tap < 15) cb[i] = hfma2(g, dwr[tap], cb[i]);
                }
            }
#pragma unroll
            for (int i = 4; i < 8; i++) finish(i);
            fence_async_smem();
            bar_sync(12 + (warp >> 1), 64);
            if (wq == 0 || wq == 3) peer_copy(mapa(sown_ + wq * 1024, r ^ 1), sown_ + wq * 1024, 1024, mapa(bars + B_SR * 8, r ^ 1));
            bar_sync(10, 256);
            TS(19);
            auto frags = [&](int i, int half) {
                const uint32_t src = H + 2 * half * HCH + wq * 1024;
#pragma unroll
                for (int k = 0; k < 4; k++) ldsm4(src + (k >> 1) * HCH + (foff ^ ((k & 1) * 64)), a[i + 4 * k], a[i + 4 * k + 1], a[i + 4 * k + 2], a[i + 4 * k + 3]);
            };
            frags(0, r);
            sp(d0, 38, a, 0, 0);
            acq(39);
            mbar_wait(bars + B_SR * 8, 0);
            frags(16, r ^ 1);
            sp(d0, 39, a + 16, 0, 1);
            residual(38);
            TS(20);
            continue;
        }

        {
            TS(11);
            const uint32_t stg = H + warp * 2048;
            unsigned char* g = g_kvq + (size_t)((b * 4 + tile) * 1024 + trow) * 128 + lane * 16;
            auto put = [&](float (&d)[32], int i) {
                pin(d);
                uint32_t pk[8];
#pragma unroll
                for (int j = 0; j < 8; j++) pk[j] = pack2((d[4 * j] + d[4 * j + 2]) * rstd, (d[4 * j + 1] + d[4 * j + 3]) * rstd);
                if (i == 2) {
                    st_data(g + 2097152, pk[0], pk[1], pk[2], pk[3]);
                    st_data(g + 2097152 + 512, pk[4], pk[5], pk[6], pk[7]);
                    return;
                }
                stsm4(stg + i * 1024 + foff, pk[0], pk[1], pk[2], pk[3]);
                stsm4(stg + i * 1024 + (foff ^ 64), pk[4], pk[5], pk[6], pk[7]);
                __syncwarp();
                const uint4 u0 = lds128(stg + i * 1024 + lane * 16), u1 = lds128(stg + i * 1024 + 512 + lane * 16);
                stg128(g + i * 1048576, u0); stg128(g + i * 1048576 + 512, u1);
            };
            sp(d0, 16, a, w, 0);
            acq(17);
            sp(d1, 17, a, w, 0);
            gather_peer();
            acq(18);
            sp(d0, 18, a + 16, 0, 1);
            wg_wait<1>();
            rel(16); rel(17);
            acq(19);
            sp(d1, 19, a + 16, 0, 1);
            wg_wait<1>();
            rel(18);
            put(d0, 0);
            wg_wait<0>();
            rel(19);
            TS(37);
            put(d1, 1);
            bar_arrive(4, 288);
            TS(38);
            acq(20);
            sp(d0, 20, a, w, 0);
            acq(21);
            sp(d0, 21, a + 16, 0, 1);
            acq(22); acq(23);
            rel(22); rel(23);
            mbar_wait(bars + B_RST * 8, 0);
            wg_wait<0>();
            rel(20); rel(21);
            put(d0, 2);
            TS(12);
        }

        {
            constexpr float CS = 0.125f * 1.4426950408889634f;
            float sa[32], sb2[32], o[36];
            uint32_t pa[16], pb[16], q[16];
            float n0 = INFINITY, n1 = INFINITY;
            zero(o); zero(pa); zero(pb); zero(sb2);
            const uint32_t ones = sb + OFF_MISC + 2048;
            { const uint32_t c = w ? 0u : 0x3F803F80u; sts128(ones + tid * 16, c, c, c, c); }
            fence_async_smem();
            bar_sync(10, 256);
            const uint32_t vdesc = rdesc + ((((ones - rbase) >> 4) - 1) << 16);
            auto qk_issue = [&](float (&s)[32], uint32_t lo) {
                const uint64_t kd = mkdesc(lo);
                wg_fence();
#pragma unroll
                for (int k = 0; k < 4; k++) mma_qk(s, q[4 * k], q[4 * k + 1], q[4 * k + 2], q[4 * k + 3], kd + 2 * k, k != 0);
                wg_commit();
            };
            auto both_issue = [&](float (&s)[32], uint32_t klo, uint32_t (&pp)[16], uint32_t vlo) {
                const uint64_t kd = mkdesc(klo), vd = mkdesc(vlo);
                wg_fence();
#pragma unroll
                for (int k = 0; k < 4; k++) {
                    mma_pv(o, pp[4 * k], pp[4 * k + 1], pp[4 * k + 2], pp[4 * k + 3], vd - k * (128 * 65535));
                    mma_qk(s, q[4 * k], q[4 * k + 1], q[4 * k + 2], q[4 * k + 3], kd + 2 * k, k != 0);
                }
                wg_commit();
            };
            auto new_max = [&](float (&s)[32], int nj, float& x0, float& x1) {
                x0 = s[0]; x1 = s[2];
#pragma unroll
                for (int j = 0; j < nj; j++) {
                    x0 = fmaxf(x0, fmaxf(s[4 * j], s[4 * j + 1]));
                    x1 = fmaxf(x1, fmaxf(s[4 * j + 2], s[4 * j + 3]));
                }
                x0 = fmaxf(x0, __shfl_xor_sync(~0u, x0, 1)); x1 = fmaxf(x1, __shfl_xor_sync(~0u, x1, 1));
                x0 = fmaxf(x0, __shfl_xor_sync(~0u, x0, 2)); x1 = fmaxf(x1, __shfl_xor_sync(~0u, x1, 2));
                x0 = fminf(n0, fmaf(x0, -CS, -20.f)); x1 = fminf(n1, fmaf(x1, -CS, -20.f));
            };
            auto probs = [&](float (&s)[32], uint32_t (&pp)[16], bool ready, bool tail, auto wait) {
                uint32_t any = 0;
#pragma unroll
                for (int i = 0; i < 16; i++) {
                    pp[i] = pack2(ex2(fmaf(s[2 * i], CS, (i & 1) ? n1 : n0)), ex2(fmaf(s[2 * i + 1], CS, (i & 1) ? n1 : n0)));
                    any |= pp[i];
                }
                wg_wait<0>();
                pin(sa); pin(sb2); pin(o); pin(pa); pin(pb);
                if (__builtin_expect(__any_sync(~0u, (any & 0x40004000u) || !ready), 0)) {
                    wait();
                    if (__any_sync(~0u, any & 0x40004000u)) {
                        if (tail) {
#pragma unroll
                            for (int i = 20; i < 32; i++) s[i] = -INFINITY;
                        }
                        float x0, x1;
                        new_max(s, 8, x0, x1);
                        const float sc0 = ex2(x0 - n0), sc1 = ex2(x1 - n1);
                        n0 = x0; n1 = x1;
#pragma unroll
                        for (int j = 0; j < 9; j++) { o[4 * j] *= sc0; o[4 * j + 1] *= sc0; o[4 * j + 2] *= sc1; o[4 * j + 3] *= sc1; }
#pragma unroll
                        for (int i = 0; i < 16; i++)
                            pp[i] = pack2(ex2(fmaf(s[2 * i], CS, (i & 1) ? n1 : n0)), ex2(fmaf(s[2 * i + 1], CS, (i & 1) ? n1 : n0)));
                    }
                }
            };
            {
                uint4 u[4];
                const unsigned char* src = g_kvq + 2097152 + (size_t)(abh * 1024 + qt * 64 + wq * 16) * 128 + lane * 16;
                spin(QGATE);
                ld_data<512>(u, src);
#pragma unroll
                for (int k = 0; k < 2; k++) {
                    q[8 * k] = u[k].x; q[8 * k + 1] = u[k + 2].x; q[8 * k + 2] = u[k].y; q[8 * k + 3] = u[k + 2].y;
                    q[8 * k + 4] = u[k].z; q[8 * k + 5] = u[k + 2].z; q[8 * k + 6] = u[k].w; q[8 * k + 7] = u[k + 2].w;
                }
                pin(q);
            }
            TS(40);
            acq(24);
            TS(13);
            qk_issue(sa, rdesc + (24 % NSLOT) * (SLOT >> 4));
            wg_wait<0>();
            pin(sa);
            {
                float x0, x1;
                new_max(sa, NJ0, x0, x1);
                n0 = x0; n1 = x1;
            }
            bar_arrive(6, 384);
            uint32_t vd = vdesc - (SLOT >> 4) * 65535u, kd = rdesc, vb = fbar + 8, kb = fbar;
            uint32_t vlast = vdesc - 4 * (SLOT >> 4) * 65535u, klast = rdesc + 4 * (SLOT >> 4) + 512;
            uint32_t kprev = fbar + 32, vprev = bars + (B_SINK - (B_EMPTY - B_FULL)) * 8;
#pragma unroll 1
            for (int it = 0; it < 4; it++) {
                both_issue(sb2, klast, pb, vlast);
                probs(sa, pa, mbar_test(vb, it < 2) & mbar_test(kb, it < 3), false, [&]() { mbar_wait(vb, it < 2); mbar_wait(kb, it < 3); });
                TS(41 + it * 4);
                if (lane == 0) mbar_arrive(kprev + (B_EMPTY - B_FULL) * 8);
                if (lane == 0) mbar_arrive(vprev + (B_EMPTY - B_FULL) * 8);
                both_issue(sa, kd, pa, vd);
                const int dv = it == 0 ? 2 : (it == 1 ? -3 : 1);
                kprev = kb; vprev = vb; vlast = vd - 512 * 65535u; klast = kd + 512;
                vd -= dv * (SLOT >> 4) * 65535u; vb += dv * 8;
                kd += (it == 2 ? -3 : 2) * (SLOT >> 4); kb = it == 2 ? vb : kb + 16;
                probs(sb2, pb, true, it == 3 && w == 1, []() {});
                TS(43 + it * 4);
            }
            wg_fence();
#pragma unroll
            for (int k = 0; k < 4; k++)
                mma_pv(o, pb[4 * k], pb[4 * k + 1], pb[4 * k + 2], pb[4 * k + 3], mkdesc(vlast - k * (128 * 65535) + (k > 1 ? w * ((k - 1) << 22) : 0)));
            wg_commit();
            const int row = wq * 16 + (lane >> 2);
            const uint32_t ml = sb + OFF_MISC;
            mbar_wait(bars + (B_RST + 1) * 8, 0);
            wg_wait<0>();
            pin(o); pin(pb); pin(sa); pin(sb2);
            if (!(LATE & 4)) rel(31);
            const float l0 = o[32], l1 = o[34];
            if (c4 == 0) { sts64f(ml + w * 512 + row * 8, n0, l0); sts64f(ml + w * 512 + row * 8 + 64, n1, l1); }
            TS(14);
            float mine[16];
#pragma unroll
            for (int j = 0; j < 4; j++) {
                if (w == 0) sts128f(H + j * 2048 + wt * 16, o[16 + 4 * j], o[17 + 4 * j], o[18 + 4 * j], o[19 + 4 * j]);
                else sts128f(H + 8192 + j * 2048 + wt * 16, o[4 * j], o[4 * j + 1], o[4 * j + 2], o[4 * j + 3]);
            }
#pragma unroll
            for (int i = 0; i < 16; i++) mine[i] = w == 0 ? o[i] : o[16 + i];
            bar_sync(10, 256);
            const float2 u0 = lds64f(ml + (w ^ 1) * 512 + row * 8), u1 = lds64f(ml + (w ^ 1) * 512 + row * 8 + 64);
            const float x0 = fminf(n0, u0.x), x1 = fminf(n1, u1.x);
            float a0 = ex2(x0 - n0), b0 = ex2(x0 - u0.x), a1 = ex2(x1 - n1), b1 = ex2(x1 - u1.x);
            const float i0 = __fdividef(1.f, fmaf(a0, l0, b0 * u0.y)), i1 = __fdividef(1.f, fmaf(a1, l1, b1 * u1.y));
            a0 *= i0; b0 *= i0; a1 *= i1; b1 *= i1;
            uint32_t pk[8];
#pragma unroll
            for (int j = 0; j < 4; j++) {
                const float4 v = lds128f(H + (w ^ 1) * 8192 + j * 2048 + wt * 16);
                pk[2 * j] = pack2(fmaf(a0, mine[4 * j], b0 * v.x), fmaf(a0, mine[4 * j + 1], b0 * v.y));
                pk[2 * j + 1] = pack2(fmaf(a1, mine[4 * j + 2], b1 * v.z), fmaf(a1, mine[4 * j + 3], b1 * v.w));
            }
            unsigned char* dst = g_o + (size_t)(b * 128 + qt * 8 + 2 * wq) * 4096 + ah * 1024 + w * 512 + lane * 16;
            st_data(dst, pk[0], pk[2], pk[4], pk[6]);
            st_data(dst + 4096, pk[1], pk[3], pk[5], pk[7]);
            if (tid == 0) asm volatile("red.relaxed.gpu.global.add.u32 [%0], 1;" ::"l"(&g_epoch[blockIdx.x * FS]) : "memory");
            TS(15);
        }

        {
            const uint32_t* dp = reinterpret_cast<const uint32_t*>(p.dw + (mir ? 14 * 256 : 0) + tile * 64) + lane;
#pragma unroll
            for (int i = 0; i < 15; i++) asm volatile("ld.global.nc.b32 %0, [%1];" : "=r"(dwr[i]) : "l"(dp + i * (mir ? -128 : 128)));
            acq(32); acq(33); acq(34);
            uint4 u[8];
            ld_data<512>(u, g_o + (size_t)(b * 128 + pt * 4 + wq) * 4096 + lane * 16);
#pragma unroll
            for (int i = 0; i < 8; i++) { a[4 * i] = u[i].x; a[4 * i + 1] = u[i].y; a[4 * i + 2] = u[i].z; a[4 * i + 3] = u[i].w; }
            if (LATE & 4) rel(31);
            TS(16);
            sp(d0, 32, a, 0, 0);
            sp(d0, 33, a + 16, 0, 1);
#pragma unroll
            for (int i = 0; i < 15; i++) dwr[i] = hmul2(dwr[i], 0x3F003F00u);
            residual(32);
            TS(17);
        }
    }

    cluster_arrive();
    TS(24);
    {
        const float rstd = rsq(fmaxf(fmaf(-mean, mean, msq), 0.f) + 1e-5f), nb = -mean * rstd;
#pragma unroll
        for (int j = 0; j < 8; j++) xr[j] = pack2(fmaf(v[2 * j], rstd, nb), fmaf(v[2 * j + 1], rstd, nb));
        const uint32_t stg = P + 16384 + warp * 1024;
        stsm4(stg + foff, xr[0], xr[1], xr[2], xr[3]);
        stsm4(stg + (foff ^ 64), xr[4], xr[5], xr[6], xr[7]);
        __syncwarp();
        const uint32_t src = stg + (lane >> 3) * 128 + (((lane & 7) ^ (lane >> 3)) << 4);
        const uint4 u0 = lds128(src), u1 = lds128((src + 512) ^ 64);
        __nv_bfloat16* dst = p.out + (size_t)(b * T_ + trow + (lane >> 3)) * 256 + tile * 64 + (lane & 7) * 8;
        if (trow < T_) { stg128(dst, u0); stg128(dst + 4 * 256, u1); }
    }
    TS(25);
    TG(31);
    TSDUMP();
    cluster_wait();
}

typedef CUresult (*EncodeFn)(CUtensorMap*, CUtensorMapDataType, cuuint32_t, void*, const cuuint64_t*, const cuuint64_t*,
                             const cuuint32_t*, const cuuint32_t*, CUtensorMapInterleave, CUtensorMapSwizzle,
                             CUtensorMapL2promotion, CUtensorMapFloatOOBfill);

}

extern "C" void kernel_launch(void* const* d_in, const int* in_sizes, int n_in, void* d_out, int out_size) {
    static EncodeFn encode = nullptr;
    if (!encode) {
        void* fn = nullptr;
        cudaDriverEntryPointQueryResult qr;
        cudaGetDriverEntryPoint("cuTensorMapEncodeTiled", &fn, cudaEnableDefault, &qr);
        encode = (EncodeFn)fn;
        cudaFuncSetAttribute(conformer_kernel, cudaFuncAttributeMaxDynamicSharedMemorySize, SMEM_LAUNCH);
    }
    Params p;
    const cuuint32_t ones[5] = {1, 1, 1, 1, 1};
    const int idx[8] = {1, 2, 3, 4, 5, 7, 8, 9};
    const int rows[8] = {256, 1024, 256, 256, 256, 256, 256, 1024};
    const int cols[8] = {1024, 256, 768, 256, 512, 256, 1024, 256};
    for (int i = 0; i < 8; i++) {
        const cuuint64_t pitch = (cuuint64_t)cols[i] * 2;
        const cuuint64_t dims[5] = {(cuuint64_t)cols[i], i ? 2u : 4u, i ? 2u : 4u, i ? 4u : 2u, (cuuint64_t)rows[i] / (i ? 16 : 32)};
        const cuuint64_t strides[4] = {pitch, pitch * 8, pitch * (i ? 2 : 4), pitch * (i ? 16 : 32)};
        const cuuint32_t box[5] = {64, i ? 2u : 4u, i ? 2u : 4u, i ? 4u : 2u, i ? 8u : 4u};
        encode(&p.tm[i], CU_TENSOR_MAP_DATA_TYPE_BFLOAT16, 5, d_in[idx[i]], dims, strides, box, ones, CU_TENSOR_MAP_INTERLEAVE_NONE,
               CU_TENSOR_MAP_SWIZZLE_128B, CU_TENSOR_MAP_L2_PROMOTION_L2_128B, CU_TENSOR_MAP_FLOAT_OOB_FILL_NONE);
        p.w[i] = (const char*)d_in[idx[i]];
    }
    {
        void* kv = nullptr;
        cudaGetSymbolAddress(&kv, g_kvq);
        const cuuint64_t dims[2] = {64, 16384};
        const cuuint64_t strides[1] = {128};
        const cuuint32_t box[2] = {64, 128};
        encode(&p.tm[8], CU_TENSOR_MAP_DATA_TYPE_BFLOAT16, 2, kv, dims, strides, box, ones, CU_TENSOR_MAP_INTERLEAVE_NONE,
               CU_TENSOR_MAP_SWIZZLE_NONE, CU_TENSOR_MAP_L2_PROMOTION_L2_128B, CU_TENSOR_MAP_FLOAT_OOB_FILL_NONE);
    }
    p.x = (const __nv_bfloat16*)d_in[0];
    p.dw = (const __nv_bfloat16*)d_in[6];
    p.out = (__nv_bfloat16*)d_out;
    p.zero = 0;
    conformer_kernel<<<NCTA, NTHREADS, SMEM_LAUNCH>>>(p);
}
```

```cpp
#include <cuda_runtime.h>
#include <cuda_bf16.h>
#include <cuda.h>
#include <stdint.h>

namespace {

constexpr int T_ = 1000;
constexpr int NCTA = 128;
constexpr int NTHREADS = 512;
constexpr int NSLOT = 5;
constexpr int SLOT = 16384;
constexpr int NLOADS = 56;

constexpr uint32_t OFF_RING = 0;
constexpr uint32_t OFF_P = 163840;
constexpr uint32_t OFF_H = 188416;
constexpr uint32_t OFF_MISC = 221184;
constexpr uint32_t OFF_BARS = 229888;
constexpr uint32_t SMEM_BYTES = 230400;
constexpr uint32_t GCH = 6144;
constexpr uint32_t HCH = 4096;

constexpr int B_FULL = 0, B_EMPTY = 10, B_XA = 20  , B_XB = 25  , B_INB = 29  , B_SR = 33,
              B_RST = 34  , B_RDY = 36  , B_SINK = 42, B_HALO = 43  , NBARS = 47;

#define KD2 300u
#define KD3 500u
#define QGATE 500u
#define BACKOFF 0u
#define KFS 8
#define KDELAY 300u
#define NJ0 2
#define HDELAY 200u
#define LATE 2
#define SND 0
#define PF0 1
#define TURN 0x200
#define EAGER 0x0155
constexpr int FS = 8;

struct Params {
    CUtensorMap tm[9];
    const char* w[8];
    const __nv_bfloat16* x;
    const __nv_bfloat16* dw;
    __nv_bfloat16* out;
    uint32_t zero;
};

__device__ __align__(1024) unsigned char g_kvq[3 * 8 * 1024 * 128];
__device__ __align__(1024) unsigned char g_o[2 * 128 * 4096];
__device__ uint4 g_halo[64 * 4 * 2 * 64];
__device__ __align__(128) uint32_t g_flag_kv[8 * 32 * KFS];
__device__ uint32_t g_reset[4 * 32];
__device__ uint32_t g_epoch[NCTA * FS];

#define TS(i) do { } while (0)
#define TSW(i) do { } while (0)
#define TG(i) do { } while (0)
#define TSINIT() do { } while (0)
#define TSDUMP() do { } while (0)
constexpr uint32_t SMEM_LAUNCH = SMEM_BYTES;

__device__ __forceinline__ uint32_t smem_u32(const void* p) { return (uint32_t)__cvta_generic_to_shared(p); }
__device__ __forceinline__ void mbar_init(uint32_t b, uint32_t c) { asm volatile("mbarrier.init.shared::cta.b64 [%0], %1;" ::"r"(b), "r"(c) : "memory"); }
__device__ __forceinline__ void mbar_arrive(uint32_t b) { asm volatile("mbarrier.arrive.shared::cta.b64 _, [%0];" ::"r"(b) : "memory"); }
__device__ __forceinline__ void mbar_arrive_tx(uint32_t b, uint32_t tx) { asm volatile("mbarrier.arrive.expect_tx.shared::cta.b64 _, [%0], %1;" ::"r"(b), "r"(tx) : "memory"); }
__device__ __forceinline__ void mbar_wait(uint32_t b, uint32_t ph) {
    asm volatile("{\n.reg .pred p, q;\n.reg .u32 c;\nmov.u32 c, 0;\n"
                 "MW_LOOP:\n.pragma \"nounroll\";\n"
                 "mbarrier.try_wait.parity.shared::cta.b64 p, [%0], %1;\n"
                 "add.u32 c, c, 1;\nsetp.lt.u32 q, c, 65536;\nnot.pred p, p;\nand.pred p, p, q;\n@p bra MW_LOOP;\n}"
                 ::"r"(b), "r"(ph) : "memory");
}
__device__ __forceinline__ bool mbar_test(uint32_t b, uint32_t ph) {
    uint32_t ok;
    asm volatile("{\n.reg .pred p;\nmbarrier.test_wait.parity.shared::cta.b64 p, [%1], %2;\nselp.u32 %0, 1, 0, p;\n}" : "=r"(ok) : "r"(b), "r"(ph) : "memory");
    return ok;
}
__device__ __forceinline__ uint32_t mapa(uint32_t a, uint32_t r) { uint32_t o; asm("mapa.shared::cluster.u32 %0, %1, %2;" : "=r"(o) : "r"(a), "r"(r)); return o; }
__device__ __forceinline__ void fence_async_smem() { asm volatile("fence.proxy.async.shared::cta;" ::: "memory"); }
__device__ __forceinline__ void fence_async_global() { asm volatile("fence.proxy.async.global;" ::: "memory"); }
__device__ __forceinline__ void bar_sync(int id, int n) { asm volatile("bar.sync %0, %1;" ::"r"(id), "r"(n) : "memory"); }
__device__ __forceinline__ void bar_arrive(int id, int n) { asm volatile("bar.arrive %0, %1;" ::"r"(id), "r"(n) : "memory"); }
__device__ __forceinline__ void cluster_arrive() { asm volatile("barrier.cluster.arrive.relaxed.aligned;" ::: "memory"); }
__device__ __forceinline__ void cluster_wait() { asm volatile("barrier.cluster.wait.aligned;" ::: "memory"); }

__device__ __forceinline__ void ring_load(uint32_t dst, const CUtensorMap* tm, int col, int row16, uint32_t bar) {
    asm volatile("{\n.reg .pred p;\nelect.sync _|p, 0xffffffff;\n"
                 "@p mbarrier.arrive.expect_tx.shared::cta.b64 _, [%2], 16384;\n"
                 "@p cp.async.bulk.tensor.5d.shared::cluster.global.mbarrier::complete_tx::bytes [%0], [%1, {%3, 0, 0, 0, %4}], [%2];\n}"
                 ::"r"(dst), "l"(tm), "r"(bar), "r"(col), "r"(row16) : "memory");
}
__device__ __forceinline__ void ring_load_both(uint32_t dst, const CUtensorMap* tm, int c1, uint32_t bar) {
    asm volatile("{\n.reg .pred p;\nelect.sync _|p, 0xffffffff;\n"
                 "@p cp.async.bulk.tensor.2d.shared::cluster.global.mbarrier::complete_tx::bytes.multicast::cluster [%0], [%1, {0, %3}], [%2], %4;\n}"
                 ::"r"(dst), "l"(tm), "r"(bar), "r"(c1), "h"((uint16_t)3) : "memory");
}
__device__ __forceinline__ void mbar_arrive_peer(uint32_t b) { asm volatile("mbarrier.arrive.relaxed.cluster.shared::cluster.b64 _, [%0];" ::"r"(b) : "memory"); }
__device__ __forceinline__ void prefetch_l2(const void* src, uint32_t bytes) {
    asm volatile("cp.async.bulk.prefetch.L2.global [%0], %1;" ::"l"(src), "r"(bytes) : "memory");
}
__device__ __forceinline__ void peer_copy(uint32_t dst, uint32_t src, uint32_t bytes, uint32_t rbar) {
    asm volatile("{\n.reg .pred p;\nelect.sync _|p, 0xffffffff;\n"
                 "@p cp.async.bulk.shared::cluster.shared::cta.mbarrier::complete_tx::bytes [%0], [%1], %2, [%3];\n}"
                 ::"r"(dst), "r"(src), "r"(bytes), "r"(rbar) : "memory");
}
__device__ __forceinline__ void st_async4(uint32_t dst, uint32_t a, uint32_t b, uint32_t c, uint32_t d, uint32_t bar) {
    asm volatile("st.async.shared::cluster.mbarrier::complete_tx::bytes.v4.b32 [%0], {%1,%2,%3,%4}, [%5];" ::"r"(dst), "r"(a), "r"(b), "r"(c), "r"(d), "r"(bar) : "memory");
}
__device__ __forceinline__ void put_sums(uint32_t dst, uint32_t rdst, float a, float b, uint32_t rbar, bool on) {
    asm volatile("{\n.reg .pred p;\nsetp.ne.u32 p, %5, 0;\n"
                 "@p st.async.shared::cluster.mbarrier::complete_tx::bytes.v2.f32 [%1], {%2,%3}, [%4];\n"
                 "@p st.shared.v2.f32 [%0], {%2,%3};\n}" ::"r"(dst), "r"(rdst), "f"(a), "f"(b), "r"(rbar), "r"((uint32_t)on) : "memory");
}
__device__ __forceinline__ void stsm4(uint32_t a, uint32_t r0, uint32_t r1, uint32_t r2, uint32_t r3) {
    asm volatile("stmatrix.sync.aligned.m8n8.x4.shared.b16 [%0], {%1,%2,%3,%4};" ::"r"(a), "r"(r0), "r"(r1), "r"(r2), "r"(r3) : "memory");
}
__device__ __forceinline__ void ldsm4(uint32_t a, uint32_t& r0, uint32_t& r1, uint32_t& r2, uint32_t& r3) {
    asm volatile("ldmatrix.sync.aligned.m8n8.x4.shared.b16 {%0,%1,%2,%3}, [%4];" : "=r"(r0), "=r"(r1), "=r"(r2), "=r"(r3) : "r"(a) : "memory");
}
__device__ __forceinline__ uint4 lds128(uint32_t a) { uint4 v; asm volatile("ld.shared.v4.b32 {%0,%1,%2,%3}, [%4];" : "=r"(v.x), "=r"(v.y), "=r"(v.z), "=r"(v.w) : "r"(a) : "memory"); return v; }
__device__ __forceinline__ float4 lds128f(uint32_t a) { float4 v; asm volatile("ld.shared.v4.f32 {%0,%1,%2,%3}, [%4];" : "=f"(v.x), "=f"(v.y), "=f"(v.z), "=f"(v.w) : "r"(a) : "memory"); return v; }
__device__ __forceinline__ float2 lds64f(uint32_t a) { float2 v; asm volatile("ld.shared.v2.f32 {%0,%1}, [%2];" : "=f"(v.x), "=f"(v.y) : "r"(a) : "memory"); return v; }
__device__ __forceinline__ uint32_t lds32(uint32_t a) { uint32_t v; asm volatile("ld.shared.b32 %0, [%1];" : "=r"(v) : "r"(a) : "memory"); return v; }
__device__ __forceinline__ void sts128(uint32_t a, uint32_t x, uint32_t y, uint32_t z, uint32_t w) { asm volatile("st.shared.v4.b32 [%0], {%1,%2,%3,%4};" ::"r"(a), "r"(x), "r"(y), "r"(z), "r"(w) : "memory"); }
__device__ __forceinline__ void sts128f(uint32_t a, float x, float y, float z, float w) { asm volatile("st.shared.v4.f32 [%0], {%1,%2,%3,%4};" ::"r"(a), "f"(x), "f"(y), "f"(z), "f"(w) : "memory"); }
__device__ __forceinline__ void sts64f(uint32_t a, float x, float y) { asm volatile("st.shared.v2.f32 [%0], {%1,%2};" ::"r"(a), "f"(x), "f"(y) : "memory"); }
__device__ __forceinline__ void sts32(uint32_t a, uint32_t x) { asm volatile("st.shared.b32 [%0], %1;" ::"r"(a), "r"(x) : "memory"); }
__device__ __forceinline__ void stg128(void* p, uint4 v) { asm volatile("st.global.v4.b32 [%0], {%1,%2,%3,%4};" ::"l"(p), "r"(v.x), "r"(v.y), "r"(v.z), "r"(v.w) : "memory"); }

__device__ __forceinline__ uint32_t pack2(float lo, float hi) { uint32_t r; asm("cvt.rn.bf16x2.f32 %0, %1, %2;" : "=r"(r) : "f"(hi), "f"(lo)); return r; }
__device__ __forceinline__ float blo(uint32_t v) { return __uint_as_float(v << 16); }
__device__ __forceinline__ float bhi(uint32_t v) { return __uint_as_float(v & 0xffff0000u); }
__device__ __forceinline__ uint32_t hmul2(uint32_t a, uint32_t b) { uint32_t r; asm("mul.rn.bf16x2 %0, %1, %2;" : "=r"(r) : "r"(a), "r"(b)); return r; }
__device__ __forceinline__ uint32_t hadd2(uint32_t a, uint32_t b) { uint32_t r; asm("add.rn.bf16x2 %0, %1, %2;" : "=r"(r) : "r"(a), "r"(b)); return r; }
__device__ __forceinline__ uint32_t hsub2(uint32_t a, uint32_t b) { uint32_t r; asm("sub.rn.bf16x2 %0, %1, %2;" : "=r"(r) : "r"(a), "r"(b)); return r; }
__device__ __forceinline__ uint32_t hfma2(uint32_t a, uint32_t b, uint32_t c) { uint32_t r; asm("fma.rn.bf16x2 %0, %1, %2, %3;" : "=r"(r) : "r"(a), "r"(b), "r"(c)); return r; }
__device__ __forceinline__ float tanh_fast(float x) { float r; asm("tanh.approx.f32 %0, %1;" : "=f"(r) : "f"(x)); return r; }
__device__ __forceinline__ float rsq(float x) { float r; asm("rsqrt.approx.ftz.f32 %0, %1;" : "=f"(r) : "f"(x)); return r; }
__device__ __forceinline__ float ex2(float x) { float r; asm("ex2.approx.ftz.f32 %0, %1;" : "=f"(r) : "f"(x)); return r; }

__device__ __forceinline__ uint32_t ld_relaxed(const uint32_t* p) {
    uint32_t v;
    asm volatile("ld.relaxed.gpu.global.u32 %0, [%1];" : "=r"(v) : "l"(p) : "memory");
    return v;
}
__device__ __forceinline__ uint32_t clock32() { uint32_t c; asm volatile("mov.u32 %0, %%clock;" : "=r"(c)::"memory"); return c; }
__device__ __forceinline__ void spin(uint32_t clks) {
    const uint32_t t0 = clock32();
    while (clock32() - t0 < clks) {}
}
__device__ __forceinline__ void flag_wait(const uint32_t* p, uint32_t e, bool mine) {
#pragma unroll 1
    for (int i = 0; i < (1 << 19); i++) {
        if (mine) mine = ld_relaxed(p) != e;
        if (!__any_sync(~0u, mine)) break;
        if (BACKOFF) spin(BACKOFF);
    }
    asm volatile("fence.acquire.gpu;" ::: "memory");
    fence_async_global();
}
__device__ __forceinline__ void st_data(void* p, uint32_t x, uint32_t y, uint32_t z, uint32_t w) {
    asm volatile("st.relaxed.gpu.global.v4.b32 [%0], {%1,%2,%3,%4};" ::"l"(p), "r"(x), "r"(y), "r"(z), "r"(w) : "memory");
}
template <int STRIDE, int N>
__device__ __forceinline__ void ld_data(uint4 (&v)[N], const unsigned char* p) {
    int it = 0;
    bool again;
#pragma unroll 1
    do {
        uint32_t m = 0;
#pragma unroll
        for (int i = 0; i < N; i++)
            asm volatile("ld.relaxed.gpu.global.v4.b32 {%0,%1,%2,%3}, [%4];" : "=r"(v[i].x), "=r"(v[i].y), "=r"(v[i].z), "=r"(v[i].w) : "l"(p + i * STRIDE) : "memory");
#pragma unroll
        for (int i = 0; i < N; i++) m = __vimax3_u32(__vimax3_u32(v[i].x, v[i].y, v[i].z), v[i].w, m);
        again = __any_sync(~0u, m == ~0u) && ++it < (1 << 16);
    } while (again);
}
__device__ __forceinline__ uint32_t ld_epoch() { return ld_relaxed(&g_epoch[blockIdx.x * FS]) + 1; }
__device__ __forceinline__ void flag_set(uint32_t* p, uint32_t e) { asm volatile("st.release.gpu.global.u32 [%0], %1;" ::"l"(p), "r"(e) : "memory"); }

__device__ __forceinline__ uint32_t desc_lo(uint32_t addr) { return ((addr & 0x3FFFF) >> 4) | 0x10000u; }
__device__ __forceinline__ uint64_t mkdesc(uint32_t lo) { return (uint64_t)lo | (0x40000040ull << 32); }
__device__ __forceinline__ void wg_fence() { asm volatile("wgmma.fence.sync.aligned;" ::: "memory"); }
__device__ __forceinline__ void wg_commit() { asm volatile("wgmma.commit_group.sync.aligned;" ::: "memory"); }
template <int N> __device__ __forceinline__ void wg_wait() { asm volatile("wgmma.wait_group.sync.aligned %0;" ::"n"(N) : "memory"); }
template <int N> __device__ __forceinline__ void pin(float (&d)[N]) {
#pragma unroll
    for (int i = 0; i < N; i++) asm volatile("" : "+f"(d[i])::"memory");
}
template <int N> __device__ __forceinline__ void pin(uint32_t (&d)[N]) {
#pragma unroll
    for (int i = 0; i < N; i++) asm volatile("" : "+r"(d[i])::"memory");
}

template <typename Tp, int N> __device__ __forceinline__ void zero(Tp (&d)[N]) {
#pragma unroll
    for (int i = 0; i < N; i++) d[i] = 0;
    pin(d);
}

#define F4(d, i) "+f"(d[i]), "+f"(d[i + 1]), "+f"(d[i + 2]), "+f"(d[i + 3])
#define F16(d, i) F4(d, i), F4(d, i + 4), F4(d, i + 8), F4(d, i + 12)

__device__ __forceinline__ void mma16(float (&d)[4], const uint32_t* a, uint32_t b0, uint32_t b1) {
    asm("mma.sync.aligned.m16n8k16.row.col.f32.bf16.bf16.f32 {%0,%1,%2,%3}, {%4,%5,%6,%7}, {%8,%9}, {%0,%1,%2,%3};"
        : F4(d, 0) : "r"(a[0]), "r"(a[1]), "r"(a[2]), "r"(a[3]), "r"(b0), "r"(b1));
}
template <int N>
__device__ __forceinline__ float row_sum(const uint32_t* x) {
    float c[4] = {};
#pragma unroll
    for (int i = 0; i < N; i += 4) mma16(c, x + i, 0x3F803F80u, 0x3F803F80u);
    return c[0] + c[2];
}
template <int N>
__device__ __forceinline__ float row_sumsq(const uint32_t* x, int lane) {
    float c0[4] = {}, c1[4] = {};
#pragma unroll
    for (int i = 0; i < N; i += 4) {
        mma16(c0, x + i, x[i], x[i + 2]);
        mma16(c1, x + i, x[i + 1], x[i + 3]);
    }
    return (lane & 4) ? c0[1] + c1[3] : c0[0] + c1[2];
}
__device__ __forceinline__ void mma_sp(float (&d)[32], const uint32_t* a, uint64_t b, uint32_t meta, int acc) {
    asm volatile("{.reg .pred p; setp.ne.b32 p, %38, 0;\n"
                 "wgmma.mma_async.sp.sync.aligned.m64n64k32.f32.bf16.bf16 {%0,%1,%2,%3,%4,%5,%6,%7,%8,%9,%10,%11,%12,%13,%14,%15,%16,%17,%18,%19,%20,%21,%22,%23,%24,%25,%26,%27,%28,%29,%30,%31}, "
                 "{%32,%33,%34,%35}, %36, %37, 0, p, 1, 1, 1;}\n"
                 : F16(d, 0), F16(d, 16) : "r"(a[0]), "r"(a[1]), "r"(a[2]), "r"(a[3]), "l"(b), "r"(meta), "r"(acc));
}
__device__ __forceinline__ void mma_qk(float (&d)[32], uint32_t a0, uint32_t a1, uint32_t a2, uint32_t a3, uint64_t b, int acc) {
    asm volatile("{.reg .pred p; setp.ne.b32 p, %37, 0;\n"
                 "wgmma.mma_async.sync.aligned.m64n64k16.f32.bf16.bf16 {%0,%1,%2,%3,%4,%5,%6,%7,%8,%9,%10,%11,%12,%13,%14,%15,%16,%17,%18,%19,%20,%21,%22,%23,%24,%25,%26,%27,%28,%29,%30,%31}, "
                 "{%32,%33,%34,%35}, %36, p, 1, 1, 0;}\n"
                 : F16(d, 0), F16(d, 16) : "r"(a0), "r"(a1), "r"(a2), "r"(a3), "l"(b), "r"(acc));
}
__device__ __forceinline__ void mma_pv(float (&d)[36], uint32_t a0, uint32_t a1, uint32_t a2, uint32_t a3, uint64_t b) {
    asm volatile("wgmma.mma_async.sync.aligned.m64n72k16.f32.bf16.bf16 {%0,%1,%2,%3,%4,%5,%6,%7,%8,%9,%10,%11,%12,%13,%14,%15,%16,%17,%18,%19,%20,%21,%22,%23,%24,%25,%26,%27,%28,%29,%30,%31,%32,%33,%34,%35}, "
                 "{%36,%37,%38,%39}, %40, 1, 1, 1, 1;\n"
                 : F16(d, 0), F16(d, 16), F4(d, 32) : "r"(a0), "r"(a1), "r"(a2), "r"(a3), "l"(b));
}

__device__ __forceinline__ uint32_t load_code(int n, int r, int w) {
    const int tile = 2 * r + w;
    int m, col, row;
    if (n < 16 || n >= 40) {
        const int k = n < 16 ? n : n - 40;
        m = n < 16 ? 0 : 6;
        if (k < 8) { col = 4 * tile + (k >> 1); row = n < 16 ? (k & 1) : (k & 1) ^ r; }
        else { m++; col = k < 12 ? tile ^ 2 : tile; row = 2 * (tile ^ (k & 1)) + ((k >> 1) & 1); }
    } else if (n < 32) {
        const int k = n - 16;
        m = 2;
        if (k < 4) { col = tile + ((k & 1) ? 8 : 4); row = (k >> 1) ^ r; }
        else { col = tile; row = (k & 1) ^ r; }
    } else if (n < 34) { m = 3; col = tile; row = n - 32; }
    else if (n < 38) { const int k = n - 34; m = 4; col = tile + 4 * (k & 1); row = (k >> 1) ^ r; }
    else { m = 5; col = tile; row = (n & 1) ^ r; }
    return m | (col << 4) | (row << (m ? 11 : 10));
}

__global__ void __cluster_dims__(2, 1, 1) __launch_bounds__(NTHREADS, 1)
conformer_kernel(const __grid_constant__ Params p) {
    extern __shared__ __align__(1024) unsigned char smem_raw[];
    const uint32_t sb = smem_u32(smem_raw);
    const uint32_t bars = sb + OFF_BARS;
    const int tid = threadIdx.x;
    const int lane = tid & 31;
    const int warp = __shfl_sync(~0u, tid >> 5, 0);
    const int r = blockIdx.x & 1;
    const int pair = blockIdx.x >> 1;
    const int b = pair >> 5, pt = pair & 31;
    const int ah = pt >> 3, qt = (pt & 7) * 2 + r;
    const int abh = b * 4 + ah;

    TG(30);
    TSINIT();
    TS(0);
    const uint32_t P = sb + OFF_P, H = sb + OFF_H;

    if (warp >= 8) {
        asm volatile("setmaxnreg.dec.sync.aligned.u32 48;");
        if (warp >= 12) {
            cluster_arrive();
            cluster_wait();
            const int ut = tid & 127;
            const uint32_t target = ld_epoch() * 64;
            auto reset_done = [&](int k) {
                bar_sync(11, 128);
                if (ut == 0) {
                    asm volatile("red.release.gpu.global.add.u32 [%0], 1;" ::"l"(&g_reset[(2 * b + k) * 32]) : "memory");
#pragma unroll 1
                    for (int i = 0; i < (1 << 20) && ld_relaxed(&g_reset[(2 * b + k) * 32]) != target; i++) __nanosleep(100);
                    asm volatile("fence.acquire.gpu;" ::: "memory");
                    mbar_arrive(bars + (B_RST + k) * 8);
                }
                __syncwarp();
                TS(13 + k);
            };
#pragma unroll
            for (int i = 0; i < 4; i++)
                st_data(g_kvq + 2097152 + (size_t)((b * 4 + 2 * r + (i >> 1)) * 1024 + pt * 32) * 128 + (i & 1) * 2048 + ut * 16, ~0u, ~0u, ~0u, ~0u);
            reset_done(0);
            bar_sync(6, 384);
#pragma unroll
            for (int i = 0; i < 4; i++) {
                st_data(g_o + (size_t)(b * 128 + qt * 8 + 2 * i + (ut >> 6)) * 4096 + ah * 1024 + (ut & 63) * 16, ~0u, ~0u, ~0u, ~0u);
                if (i < 2) st_data(&g_halo[(pair * 4 + 2 * r + i) * 128 + ut], ~0u, ~0u, ~0u, ~0u);
            }
            reset_done(1);
            const int side = warp & 1, wg = (warp >> 1) & 1, np = side ? pt + 1 : pt - 1;
            const unsigned char* src = reinterpret_cast<const unsigned char*>(&g_halo[(((b * 32 + np) * 4 + 2 * r + wg) * 2 + (side ^ 1)) * 64 + lane]);
            const uint32_t dst = H + 16384 + wg * GCH + side * 5120 + (lane & 7) * 128 + (((lane >> 3) ^ (lane & 7)) << 4);
            uint4 hv[2] = {make_uint4(0, 0, 0, 0), make_uint4(0, 0, 0, 0)};
            bar_sync(8 + wg, 192);
            if (np >= 0 && np < 32) {
                spin(HDELAY);
                ld_data<512>(hv, src);
            }
            stsm4(dst, hv[0].x, hv[0].y, hv[0].z, hv[0].w);
            stsm4(dst ^ 64, hv[1].x, hv[1].y, hv[1].z, hv[1].w);
            __syncwarp();
            if (lane == 0) mbar_arrive(bars + (B_HALO + (warp & 3)) * 8);
            TS(4);
        } else if (warp < 10) {
            const int w = warp - 8;
            const uint32_t ring = sb + OFF_RING + w * NSLOT * SLOT;
            const uint32_t full = bars + (B_FULL + w * NSLOT) * 8;
            if (lane == 0) {
#pragma unroll
                for (int i = 0; i < NSLOT; i++) { mbar_init(full + i * 8, 1); mbar_init(full + (B_EMPTY - B_FULL + i) * 8, 4); }
                asm volatile("fence.mbarrier_init.release.cluster;" ::: "memory");
                fence_async_smem();
            }
            __syncwarp();
            cluster_arrive();
            TS(1);
#pragma unroll
            for (int n = 0; n < NSLOT; n++) {
                if (n == 1 || n == 2) bar_sync(12, 64);
                ring_load(ring + n * SLOT, &p.tm[0], 64 * (8 * r + 4 * w + (n >> 1)), 4 * (n & 1), full + n * 8);
            }
            TS(2);
            const uint32_t code = load_code(lane, r, w) | (load_code(lane + 32, r, w) << 16);
            cluster_wait();
            uint32_t s = 0, ph = 0;
            int n = NSLOT;
#pragma unroll 1
            for (int seg = 0; seg < 2; seg++) {
#pragma unroll 1
                for (; n < (seg == 0 ? 22 : NLOADS); n++) {
                    const uint32_t c = __shfl_sync(~0u, code, n) >> (n & 32 ? 16 : 0);
                    const CUtensorMap* tm = &p.tm[c & 15];
                    const uint32_t col = (c & 0xf0) * 4, row = (c & 0xff00) >> 8, dst = ring + s * SLOT;
                    mbar_wait(full + (B_EMPTY - B_FULL) * 8 + s * 8, ph + (((uint32_t)(size_t)tm | col | row | dst) & p.zero));
                    ring_load(dst, tm, col, row, full + s * 8);
                    if (++s == NSLOT) { s = 0; ph ^= 1; }
                }
                if (seg == 1) break;
                const uint32_t epoch = ld_epoch();
                const uint32_t rdy = bars + (B_RDY + 3 * w) * 8, prdy = mapa(rdy, r ^ 1);
                const int odd = r ^ w;
                const uint32_t* flags = g_flag_kv + (abh * 32 + lane) * KFS;
                auto kv_load = [&](uint32_t sl, int isv, int i) {
                    ring_load_both(ring + sl * SLOT, &p.tm[8], (isv * 64 + abh * 8 + 2 * i + w) * 128, full + sl * 8);
                };
#pragma unroll 1
                for (int i = 0; i < 2; i++) {
                    if (lane < 3 + i) {
                        const uint32_t sl = i ? lane : lane + 2;
                        mbar_wait(full + (B_EMPTY - B_FULL + sl) * 8, i ^ 1);
                        mbar_arrive_tx(full + sl * 8, (i || lane == 2) ? SLOT : 0);
                    }
                    __syncwarp();
                }
                if (lane == 0) mbar_arrive_peer(prdy);
                bar_sync(14, 96);
                spin(KDELAY);
                mbar_wait(rdy, 0);
                flag_wait(flags, epoch, (lane >> 2) == 2 * odd + w);
                TSW(5 + 2 * odd);
                if (!odd) { kv_load(4, 0, 0); bar_arrive(12, 64); }
                else bar_sync(12, 64);
                spin(w ? KD3 : KD2);
                kv_load(odd ^ 1, odd ^ 1, odd);
                flag_wait(flags, epoch, (lane >> 2) == 2 * odd + w + 4);
                mbar_wait(full + (odd ^ 1) * 8, 1);
                kv_load(2 + odd, odd, 2 - odd);
#pragma unroll 1
                for (int i = 0; i < 3; i++) {
                    const uint32_t sl = i ? i - 1 : 4, bo = i == 2 ? 16 : 8;
                    mbar_wait(full + (B_EMPTY - B_FULL + sl) * 8, i != 0);
                    if (lane == 0) mbar_arrive_tx(full + sl * 8, SLOT);
                    if ((i & 1) != odd) {
                        mbar_wait(rdy + bo, 0);
                        kv_load(sl, i != 0, 2 + odd);
                    } else if (lane == 0) mbar_arrive_peer(prdy + bo);
                    __syncwarp();
                }
                n = 32; s = 2; ph = 1;
            }
        } else if (warp == 10) {
            if (lane == 0) {
#pragma unroll
                for (int i = B_XA; i < NBARS; i++) mbar_init(bars + i * 8, 1);
#pragma unroll
                for (int i = B_XA; i <= B_SR; i++) mbar_arrive_tx(bars + i * 8, i < B_XB ? 512 : ((i >= B_INB && i < B_SR) ? 4096 : 8192));
                asm volatile("fence.mbarrier_init.release.cluster;" ::: "memory");
                fence_async_smem();
            }
            __syncwarp();
            cluster_arrive();
            cluster_wait();
        } else {
            const uint32_t kb = (lane < 2 || lane > 5) ? 4096 : (lane == 2 ? 3072 : (lane == 4 ? 2048 : 1024));
            const char* pf = p.w[lane & 7] + blockIdx.x * kb;
            cluster_arrive();
            cluster_wait();
            if (lane < PF0) prefetch_l2(pf, kb);
            mbar_wait(bars + B_FULL * 8, 0);
            if (lane >= PF0 && lane < 3) prefetch_l2(pf, kb);
            if (lane >= 1 && lane < 9) asm volatile("prefetch.tensormap [%0];" ::"l"(&p.tm[lane]) : "memory");
            mbar_wait(bars + (B_FULL + 1) * 8, 1);
            if (lane > 2 && lane < 8) prefetch_l2(pf, kb);
            if (lane == 8 && blockIdx.x < 15) prefetch_l2(p.dw + blockIdx.x * 256, 512);
            const uint32_t epoch = ld_epoch();
            bar_sync(4, 288);
            if (lane < 16) flag_set(&g_flag_kv[((b * 4 + 2 * r + (lane >> 3)) * 32 + pt) * KFS + (lane & 7)], epoch);
            __syncwarp();
            bar_arrive(14, 96);
            TSW(8);
        }
        TSDUMP();
        return;
    }

    const int w = warp >> 2, wq = warp & 3;
    const int tile = 2 * r + w;
    const int wt = tid & 127;
    const int c4 = lane & 3;
    const int trow = pt * 32 + 8 * wq;
    uint32_t xr[8];
    uint32_t a[32];
    const char* xrow = reinterpret_cast<const char*>(p.x) + (b * T_ + trow + (lane >> 2)) * 512;
    zero(a);
    if (trow < T_) {
        const char* src = xrow + c4 * 16 + p.zero;
#pragma unroll
        for (int i = 0; i < 8; i++)
            asm volatile("ld.global.nc.v4.b32 {%0,%1,%2,%3}, [%4];" : "=r"(a[4 * i]), "=r"(a[4 * i + 1]), "=r"(a[4 * i + 2]), "=r"(a[4 * i + 3]) : "l"(src + 64 * i));
    }
    cluster_arrive();
    asm volatile("setmaxnreg.inc.sync.aligned.u32 208;");
    const uint32_t rbase = sb + OFF_RING + w * NSLOT * SLOT, fbar = bars + (B_FULL + w * NSLOT) * 8;
    const uint32_t rdesc = desc_lo(rbase);
    auto acq = [&](int n) { mbar_wait(fbar + (n % NSLOT) * 8, (n / NSLOT) & 1); };
    auto rel = [&](int n) { if (lane == 0) mbar_arrive(fbar + (B_EMPTY - B_FULL + n % NSLOT) * 8); };
    const uint32_t foff = (lane & 7) * 128 + (((lane >> 3) ^ (lane & 7)) << 4);
    float v[16];
    const uint32_t xown = __shfl_sync(~0u, P + wt * 16 + tile * 4096, lane), xrem = __shfl_sync(~0u, P + wt * 16 + (r ^ 1) * 8192, lane);
    const uint32_t sbuf = __shfl_sync(~0u, sb + OFF_MISC + 1024 + (8 * wq + (lane >> 2)) * 32, lane);
    const uint32_t sown = __shfl_sync(~0u, sbuf + tile * 8, lane);
    const uint32_t peer = __shfl_sync(~0u, mapa(sb, r ^ 1) - sb, lane);
    const uint32_t hbuf = __shfl_sync(~0u, H + w * 4096 + wt * 16, lane);
    const uint32_t meta = __shfl_sync(~0u, 0xEEEE4444u + p.zero, lane);
    cluster_wait();
    TS(56);
    float mean, msq;
    const int mir = wq < 2 ? 7 : 0;
    uint32_t dwr[15] = {};

#pragma unroll
    for (int ph = 0; ph < 5; ph++) {
        uint4 o0, o1;
        if (ph == 0) {
            mean = ((row_sum<8>(a) + row_sum<8>(a + 8)) + (row_sum<8>(a + 16) + row_sum<8>(a + 24))) * (1.f / 256.f);
            TS(57);
        } else {
            const uint32_t xa = bars + (B_XA + ph) * 8;
#pragma unroll
            for (int j = 0; j < 8; j++) xr[j] = pack2(v[2 * j], v[2 * j + 1]);
            const float s = row_sum<8>(xr), q = row_sumsq<8>(xr, lane);
            if (ph < 4) {
                sts128(xown, xr[0], xr[1], xr[2], xr[3]);
                sts128(xown + 2048, xr[4], xr[5], xr[6], xr[7]);
            }
            put_sums(sown, sown + peer, s, q, xa + peer, c4 == (lane >> 3));
            bar_sync(10, 256);
            if (ph < 4) {
                o0 = lds128(xown ^ 4096); o1 = lds128((xown ^ 4096) + 2048);
                st_async4(xown + peer, xr[0], xr[1], xr[2], xr[3], xa + (B_XB - B_XA) * 8 + peer);
                st_async4(xown + peer + 2048, xr[4], xr[5], xr[6], xr[7], xa + (B_XB - B_XA) * 8 + peer);
            }
            TS(57 + ph);
            if (ph == 3) acq(0);
            if (ph == 1) acq(16);
            mbar_wait(xa, 0);
            const float4 u0 = lds128f(sbuf), u1 = lds128f(sbuf + 16);
            mean = ((u0.x + u0.z) + (u1.x + u1.z)) * (1.f / 256.f);
            msq = ((u0.y + u0.w) + (u1.y + u1.w)) * (1.f / 256.f);
        }
        if (ph == 4) break;
        const uint32_t mean2 = pack2(mean, mean);
        auto centre = [&](int i, const uint4& u) {
            a[i] = hsub2(u.x, mean2); a[i + 1] = hsub2(u.y, mean2); a[i + 2] = hsub2(u.z, mean2); a[i + 3] = hsub2(u.w, mean2);
        };
        if (ph == 0) {
#pragma unroll
            for (int j = 0; j < 32; j++) a[j] = hsub2(a[j], mean2);
            zero(xr);
            if (trow < T_) {
                const char* src = xrow + tile * 128 + c4 * 4 + (mean2 & p.zero);
#pragma unroll
                for (int j = 0; j < 8; j++) asm volatile("ld.global.nc.b32 %0, [%1];" : "=r"(xr[j]) : "l"(src + 16 * j));
            }
            mean -= blo(mean2);
            msq = __shfl_sync(~0u, row_sumsq<16>(a, lane) + row_sumsq<16>(a + 16, lane), (lane & 28) + (lane >> 3)) * (1.f / 256.f);
            acq(0);
        } else {
#pragma unroll
            for (int j = 0; j < 8; j++) a[j] = hsub2(xr[j], mean2);
            centre(8, o0); centre(12, o1);
        }
        const float rstd = rsq(fmaxf(fmaf(-mean, mean, msq), 0.f) + 1e-5f);
        auto gather_peer = [&]() {
            mbar_wait(bars + (B_XB + ph) * 8, 0);
#pragma unroll
            for (int i = 0; i < 4; i++) centre(16 + 4 * i, lds128(xrem + i * 2048));
        };
        auto sp = [&](float (&d)[32], int n, const uint32_t* af, int flip, int acc) {
            const uint32_t lo = rdesc + p.zero * (ph * 64 + n + 1) + (n % NSLOT) * (SLOT >> 4);
            const uint64_t b0 = mkdesc(lo + flip * 512), b1 = mkdesc(lo + (flip ^ 1) * 512);
            wg_fence();
            mma_sp(d, af, b0, meta, acc);
            mma_sp(d, af + 4, b0 + 256, meta, 1);
            mma_sp(d, af + 8, b1, meta, 1);
            mma_sp(d, af + 12, b1 + 256, meta, 1);
            wg_commit();
        };
        float d0[32], d1[32];

        if (ph == 0 || ph == 3) {
            uint32_t h[32], ho[32];
            const float rs = 0.5f * rstd;
            const uint32_t inb = bars + (B_INB + (ph & 2) + w) * 8;
            bool ready = true;
            const int eager = ph ? EAGER : EAGER - 1;
            auto step = [&](float (&d)[32], int n, const uint32_t* af, int flip, int acc, auto work) {
                if (!ready) acq(n);
                if (((TURN >> n) & 1) && w == 1) bar_sync(7, 256);
                sp(d, n, af, flip, acc);
                if (n > 0 && ((TURN >> (n - 1)) & 1) && w == 0) bar_arrive(7, 256);
                if (n < 15) ready = mbar_test(fbar + ((n + 1) % NSLOT) * 8, ((n + 1) / NSLOT) & 1);
                wg_wait<1>();
                if (n > 0 && !((eager >> (n - 1)) & 1)) rel(n - 1);
                const uint32_t tie = work() & p.zero;
                if ((eager >> n) & 1) {
                    if (p.zero < n + ph + 1) wg_wait<0>();
                    if (lane == 0) mbar_arrive(fbar + (B_EMPTY - B_FULL + n % NSLOT) * 8 + tie);
                }
            };
            auto none = []() { return 0u; };
            const int fl = ph ? w : 0;
            auto fetch = [&](int i) {
                bar_sync(10, 256);
                const uint4 u0 = lds128((hbuf ^ 4096) + (i & 1) * 8192), u1 = lds128((hbuf ^ 4096) + (i & 1) * 8192 + 2048);
                ho[8 * i] = u0.x; ho[8 * i + 1] = u0.y; ho[8 * i + 2] = u0.z; ho[8 * i + 3] = u0.w;
                ho[8 * i + 4] = u1.x; ho[8 * i + 5] = u1.y; ho[8 * i + 6] = u1.z; ho[8 * i + 7] = u1.w;
                return u0.x | u1.x;
            };
            auto act = [&](float (&d)[32], int i) {
                if (i > 0) fetch(i - 1);
                pin(d);
#pragma unroll
                for (int j = 0; j < 8; j++) {
                    const float u0 = (d[4 * j] + d[4 * j + 2]) * rs, u1 = (d[4 * j + 1] + d[4 * j + 3]) * rs;
                    h[8 * i + j] = pack2(fmaf(u0, tanh_fast(u0), u0), fmaf(u1, tanh_fast(u1), u1));
                }
                sts128(hbuf + (i & 1) * 8192, h[8 * i], h[8 * i + 1], h[8 * i + 2], h[8 * i + 3]);
                sts128(hbuf + (i & 1) * 8192 + 2048, h[8 * i + 4], h[8 * i + 5], h[8 * i + 6], h[8 * i + 7]);
                return 0u;
            };
            TS(1 + (ph & 2) * 10);
            step(d0, 0, a, fl, 0, [&]() { if (ph) gather_peer(); return 0u; });
            TS(32);
            step(d0, 1, a + 16, 0, 1, none);
            step(d1, 2, a, fl, 0, [&]() { return act(d0, 0); });
            step(d1, 3, a + 16, 0, 1, none);
            step(d0, 4, a, fl, 0, [&]() { return act(d1, 1); });
            TS(33);
            step(d0, 5, a + 16, 0, 1, none);
            step(d1, 6, a, fl, 0, [&]() { return act(d0, 2); });
            step(d1, 7, a + 16, 0, 1, none);
            step(d0, 8, h, 0, 0, [&]() { act(d1, 3); return fetch(3); });
            TS(2 + (ph & 2) * 10);
            step(d0, 9, ho, 0, 1, none);
            step(d0, 10, h + 16, 0, 1, none);
            step(d0, 11, ho + 16, 0, 1, none);
            uint32_t pk[8];
            auto pack_out = [&]() {
                pin(d0);
#pragma unroll
                for (int j = 0; j < 8; j++) pk[j] = pack2(d0[4 * j] + d0[4 * j + 2], d0[4 * j + 1] + d0[4 * j + 3]);
            };
            auto send = [&](int i) { st_async4(hbuf + 16384 + i * 2048 + peer, pk[4 * i], pk[4 * i + 1], pk[4 * i + 2], pk[4 * i + 3], inb + peer); };
            step(d1, 12, h, 0, 0, [&]() { pack_out(); if (SND != 1) send(0); if (SND == 0) send(1); return 0u; });
            TS(34);
            step(d1, 13, ho, 0, 1, [&]() { if (SND == 1) send(0); if (SND) send(1); return 0u; });
            step(d1, 14, h + 16, 0, 1, none);
            step(d1, 15, ho + 16, 0, 1, none);
            mbar_wait(inb, 0);
#pragma unroll
            for (int i = 0; i < 2; i++) {
                const uint4 u = lds128(hbuf + 16384 + i * 2048);
                const uint32_t p0[4] = {u.x, u.y, u.z, u.w};
#pragma unroll
                for (int j = 0; j < 4; j++) {
                    v[8 * i + 2 * j] = fmaf(0.5f, blo(p0[j]), blo(xr[4 * i + j]));
                    v[8 * i + 2 * j + 1] = fmaf(0.5f, bhi(p0[j]), bhi(xr[4 * i + j]));
                }
            }
            wg_wait<0>();
            pin(d1);
            rel(15);
            TS(3 + (ph & 2) * 10);
#pragma unroll
            for (int j = 0; j < 8; j++) {
                v[2 * j] = fmaf(0.5f, d1[4 * j] + d1[4 * j + 2], v[2 * j]);
                v[2 * j + 1] = fmaf(0.5f, d1[4 * j + 1] + d1[4 * j + 3], v[2 * j + 1]);
            }
#pragma unroll
            for (int i = 0; i < 15; i++) dwr[i] = 0;
            continue;
        }

        auto residual = [&](int n) {
            wg_wait<1>();
            rel(n);
            wg_wait<0>();
            pin(d0);
            rel(n + 1);
#pragma unroll
            for (int j = 0; j < 8; j++) {
                v[2 * j] = d0[4 * j] + d0[4 * j + 2] + blo(xr[j]);
                v[2 * j + 1] = d0[4 * j + 1] + d0[4 * j + 3] + bhi(xr[j]);
            }
        };

        if (ph == 2) {
            TS(39);
            sp(d0, 34, a, w, 0);
            acq(35);
            sp(d1, 35, a, w, 0);
            acq(36); acq(37);
            gather_peer();
            sp(d0, 36, a + 16, 0, 1);
            sp(d1, 37, a + 16, 0, 1);
            wg_wait<2>();
            rel(34);
            if (!(LATE & 1)) rel(35);
            acq(38);
            const float rs = trow < T_ ? 0.5f * rstd : 0.f;
            wg_wait<0>();
            pin(d0); pin(d1);
            if (!(LATE & 2)) { rel(36); rel(37); }
            TS(18);
            uint32_t pk[8];
#pragma unroll
            for (int j = 0; j < 8; j++) {
                const float u0 = (d0[4 * j] + d0[4 * j + 2]) * rs, u1 = (d0[4 * j + 1] + d0[4 * j + 3]) * rs;
                const float t0 = tanh_fast((d1[4 * j] + d1[4 * j + 2]) * rs), t1 = tanh_fast((d1[4 * j + 1] + d1[4 * j + 3]) * rs);
                pk[j] = pack2(fmaf(u0, t0, u0), fmaf(u1, t1, u1));
            }
            if (wq == 0 || wq == 3) {
                uint4* hp = &g_halo[((pair * 4 + tile) * 2 + (wq & 1)) * 64 + lane];
                st_data(hp, pk[0], pk[1], pk[2], pk[3]);
                st_data(hp + 32, pk[4], pk[5], pk[6], pk[7]);
            }
            const uint32_t gs = H + 16384 + w * GCH + wq * 1024;
            stsm4(gs + 1024 + foff, pk[0], pk[1], pk[2], pk[3]);
            stsm4(gs + 1024 + (foff ^ 64), pk[4], pk[5], pk[6], pk[7]);
            bar_sync(8 + w, 192);
            TS(26);
            uint32_t ca[8], cb[8];
            const int e = (wq & 1) * 4;
            const uint32_t lo = ((mir ^ e) * 144) ^ (lane * 4);
            const int dir = mir ? -1024 : 1024;
            const uint32_t gb = H + 16384 + w * GCH + (mir ? 3072 : 2048) + lo, sown_ = H + tile * HCH, so = sown_ + (mir ? 1024 : 2048) + lo;
            auto finish = [&](int i) {
                const uint32_t c = hadd2(ca[i], cb[i]);
                const float h0 = blo(c), h1 = bhi(c);
                sts32((so + (i >> 2) * dir) ^ ((i & 3) * 144), pack2(fmaf(h0, tanh_fast(h0), h0), fmaf(h1, tanh_fast(h1), h1)));
            };
#pragma unroll
            for (int k = 0; k < 26; k++) {
                if (k == 19) {
#pragma unroll
                    for (int i = 0; i < 4; i++) finish(i);
                    fence_async_smem();
                    bar_sync(2 + w, 128);
                    if (wq == 0) peer_copy(mapa(sown_ + 1024, r ^ 1), sown_ + 1024, 2048, mapa(bars + B_SR * 8, r ^ 1));
                    mbar_wait(bars + (B_HALO + 2 * w + (wq >> 1)) * 8, 0);
                    if (LATE & 1) rel(35);
                    if (LATE & 2) { rel(36); rel(37); }
                    TS(27);
                }
                const uint32_t g = lds32((gb + (((k + 1) & 4) ? ((k + 1) >> 3) + (wq & 1) : ((k + 1) >> 3)) * dir) ^ (((k + 1) & 7) * 144));
#pragma unroll
                for (int i = 0; i < 8; i++) {
                    const int tap = k - (i & 3) - 2 * (i & 4);
                    if (tap == 0) ca[i] = hmul2(g, dwr[0]);
                    else if (tap > 0 && tap < 8) ca[i] = hfma2(g, dwr[tap], ca[i]);
                    else if (tap == 8) cb[i] = hmul2(g, dwr[8]);
                    else if (tap > 8 && tap < 15) cb[i] = hfma2(g, dwr[tap], cb[i]);
                }
            }
#pragma unroll
            for (int i = 4; i < 8; i++) finish(i);
            fence_async_smem();
            bar_sync(12 + (warp >> 1), 64);
            if (wq == 0 || wq == 3) peer_copy(mapa(sown_ + wq * 1024, r ^ 1), sown_ + wq * 1024, 1024, mapa(bars + B_SR * 8, r ^ 1));
            bar_sync(10, 256);
            TS(19);
            auto frags = [&](int i, int half) {
                const uint32_t src = H + 2 * half * HCH + wq * 1024;
#pragma unroll
                for (int k = 0; k < 4; k++) ldsm4(src + (k >> 1) * HCH + (foff ^ ((k & 1) * 64)), a[i + 4 * k], a[i + 4 * k + 1], a[i + 4 * k + 2], a[i + 4 * k + 3]);
            };
            frags(0, r);
            sp(d0, 38, a, 0, 0);
            acq(39);
            mbar_wait(bars + B_SR * 8, 0);
            frags(16, r ^ 1);
            sp(d0, 39, a + 16, 0, 1);
            residual(38);
            TS(20);
            continue;
        }

        {
            TS(11);
            const uint32_t stg = H + warp * 2048;
            unsigned char* g = g_kvq + (size_t)((b * 4 + tile) * 1024 + trow) * 128 + lane * 16;
            auto put = [&](float (&d)[32], int i) {
                pin(d);
                uint32_t pk[8];
#pragma unroll
                for (int j = 0; j < 8; j++) pk[j] = pack2((d[4 * j] + d[4 * j + 2]) * rstd, (d[4 * j + 1] + d[4 * j + 3]) * rstd);
                if (i == 2) {
                    st_data(g + 2097152, pk[0], pk[1], pk[2], pk[3]);
                    st_data(g + 2097152 + 512, pk[4], pk[5], pk[6], pk[7]);
                    return;
                }
                stsm4(stg + i * 1024 + foff, pk[0], pk[1], pk[2], pk[3]);
                stsm4(stg + i * 1024 + (foff ^ 64), pk[4], pk[5], pk[6], pk[7]);
                __syncwarp();
                const uint4 u0 = lds128(stg + i * 1024 + lane * 16), u1 = lds128(stg + i * 1024 + 512 + lane * 16);
                stg128(g + i * 1048576, u0); stg128(g + i * 1048576 + 512, u1);
            };
            sp(d0, 16, a, w, 0);
            acq(17);
            sp(d1, 17, a, w, 0);
            gather_peer();
            acq(18);
            sp(d0, 18, a + 16, 0, 1);
            wg_wait<1>();
            rel(16); rel(17);
            acq(19);
            sp(d1, 19, a + 16, 0, 1);
            wg_wait<1>();
            rel(18);
            put(d0, 0);
            wg_wait<0>();
            rel(19);
            TS(37);
            put(d1, 1);
            bar_arrive(4, 288);
            TS(38);
            acq(20);
            sp(d0, 20, a, w, 0);
            acq(21);
            sp(d0, 21, a + 16, 0, 1);
            acq(22); acq(23);
            rel(22); rel(23);
            mbar_wait(bars + B_RST * 8, 0);
            wg_wait<0>();
            rel(20); rel(21);
            put(d0, 2);
            TS(12);
        }

        {
            constexpr float CS = 0.125f * 1.4426950408889634f;
            float sa[32], sb2[32], o[36];
            uint32_t pa[16], pb[16], q[16];
            float n0 = INFINITY, n1 = INFINITY;
            zero(o); zero(pa); zero(pb); zero(sb2);
            const uint32_t ones = sb + OFF_MISC + 2048;
            { const uint32_t c = w ? 0u : 0x3F803F80u; sts128(ones + tid * 16, c, c, c, c); }
            fence_async_smem();
            bar_sync(10, 256);
            const uint32_t vdesc = rdesc + ((((ones - rbase) >> 4) - 1) << 16);
            auto qk_issue = [&](float (&s)[32], uint32_t lo) {
                const uint64_t kd = mkdesc(lo);
                wg_fence();
#pragma unroll
                for (int k = 0; k < 4; k++) mma_qk(s, q[4 * k], q[4 * k + 1], q[4 * k + 2], q[4 * k + 3], kd + 2 * k, k != 0);
                wg_commit();
            };
            auto both_issue = [&](float (&s)[32], uint32_t klo, uint32_t (&pp)[16], uint32_t vlo) {
                const uint64_t kd = mkdesc(klo), vd = mkdesc(vlo);
                wg_fence();
#pragma unroll
                for (int k = 0; k < 4; k++) {
                    mma_pv(o, pp[4 * k], pp[4 * k + 1], pp[4 * k + 2], pp[4 * k + 3], vd - k * (128 * 65535));
                    mma_qk(s, q[4 * k], q[4 * k + 1], q[4 * k + 2], q[4 * k + 3], kd + 2 * k, k != 0);
                }
                wg_commit();
            };
            auto new_max = [&](float (&s)[32], int nj, float& x0, float& x1) {
                x0 = s[0]; x1 = s[2];
#pragma unroll
                for (int j = 0; j < nj; j++) {
                    x0 = fmaxf(x0, fmaxf(s[4 * j], s[4 * j + 1]));
                    x1 = fmaxf(x1, fmaxf(s[4 * j + 2], s[4 * j + 3]));
                }
                x0 = fmaxf(x0, __shfl_xor_sync(~0u, x0, 1)); x1 = fmaxf(x1, __shfl_xor_sync(~0u, x1, 1));
                x0 = fmaxf(x0, __shfl_xor_sync(~0u, x0, 2)); x1 = fmaxf(x1, __shfl_xor_sync(~0u, x1, 2));
                x0 = fminf(n0, fmaf(x0, -CS, -20.f)); x1 = fminf(n1, fmaf(x1, -CS, -20.f));
            };
            auto probs = [&](float (&s)[32], uint32_t (&pp)[16], bool ready, bool tail, auto wait) {
                uint32_t any = 0;
#pragma unroll
                for (int i = 0; i < 16; i++) {
                    pp[i] = pack2(ex2(fmaf(s[2 * i], CS, (i & 1) ? n1 : n0)), ex2(fmaf(s[2 * i + 1], CS, (i & 1) ? n1 : n0)));
                    any |= pp[i];
                }
                wg_wait<0>();
                pin(sa); pin(sb2); pin(o); pin(pa); pin(pb);
                if (__builtin_expect(__any_sync(~0u, (any & 0x40004000u) || !ready), 0)) {
                    wait();
                    if (__any_sync(~0u, any & 0x40004000u)) {
                        if (tail) {
#pragma unroll
                            for (int i = 20; i < 32; i++) s[i] = -INFINITY;
                        }
                        float x0, x1;
                        new_max(s, 8, x0, x1);
                        const float sc0 = ex2(x0 - n0), sc1 = ex2(x1 - n1);
                        n0 = x0; n1 = x1;
#pragma unroll
                        for (int j = 0; j < 9; j++) { o[4 * j] *= sc0; o[4 * j + 1] *= sc0; o[4 * j + 2] *= sc1; o[4 * j + 3] *= sc1; }
#pragma unroll
                        for (int i = 0; i < 16; i++)
                            pp[i] = pack2(ex2(fmaf(s[2 * i], CS, (i & 1) ? n1 : n0)), ex2(fmaf(s[2 * i + 1], CS, (i & 1) ? n1 : n0)));
                    }
                }
            };
            {
                uint4 u[4];
                const unsigned char* src = g_kvq + 2097152 + (size_t)(abh * 1024 + qt * 64 + wq * 16) * 128 + lane * 16;
                spin(QGATE);
                ld_data<512>(u, src);
#pragma unroll
                for (int k = 0; k < 2; k++) {
                    q[8 * k] = u[k].x; q[8 * k + 1] = u[k + 2].x; q[8 * k + 2] = u[k].y; q[8 * k + 3] = u[k + 2].y;
                    q[8 * k + 4] = u[k].z; q[8 * k + 5] = u[k + 2].z; q[8 * k + 6] = u[k].w; q[8 * k + 7] = u[k + 2].w;
                }
                pin(q);
            }
            TS(40);
            acq(24);
            TS(13);
            qk_issue(sa, rdesc + (24 % NSLOT) * (SLOT >> 4));
            wg_wait<0>();
            pin(sa);
            {
                float x0, x1;
                new_max(sa, NJ0, x0, x1);
                n0 = x0; n1 = x1;
            }
            bar_arrive(6, 384);
            uint32_t vd = vdesc - (SLOT >> 4) * 65535u, kd = rdesc, vb = fbar + 8, kb = fbar;
            uint32_t vlast = vdesc - 4 * (SLOT >> 4) * 65535u, klast = rdesc + 4 * (SLOT >> 4) + 512;
            uint32_t kprev = fbar + 32, vprev = bars + (B_SINK - (B_EMPTY - B_FULL)) * 8;
#pragma unroll 1
            for (int it = 0; it < 4; it++) {
                both_issue(sb2, klast, pb, vlast);
                probs(sa, pa, mbar_test(vb, it < 2) & mbar_test(kb, it < 3), false, [&]() { mbar_wait(vb, it < 2); mbar_wait(kb, it < 3); });
                TS(41 + it * 4);
                if (lane == 0) mbar_arrive(kprev + (B_EMPTY - B_FULL) * 8);
                if (lane == 0) mbar_arrive(vprev + (B_EMPTY - B_FULL) * 8);
                both_issue(sa, kd, pa, vd);
                const int dv = it == 0 ? 2 : (it == 1 ? -3 : 1);
                kprev = kb; vprev = vb; vlast = vd - 512 * 65535u; klast = kd + 512;
                vd -= dv * (SLOT >> 4) * 65535u; vb += dv * 8;
                kd += (it == 2 ? -3 : 2) * (SLOT >> 4); kb = it == 2 ? vb : kb + 16;
                probs(sb2, pb, true, it == 3 && w == 1, []() {});
                TS(43 + it * 4);
            }
            wg_fence();
#pragma unroll
            for (int k = 0; k < 4; k++)
                mma_pv(o, pb[4 * k], pb[4 * k + 1], pb[4 * k + 2], pb[4 * k + 3], mkdesc(vlast - k * (128 * 65535) + (k > 1 ? w * ((k - 1) << 22) : 0)));
            wg_commit();
            const int row = wq * 16 + (lane >> 2);
            const uint32_t ml = sb + OFF_MISC;
            mbar_wait(bars + (B_RST + 1) * 8, 0);
            wg_wait<0>();
            pin(o); pin(pb); pin(sa); pin(sb2);
            if (!(LATE & 4)) rel(31);
            const float l0 = o[32], l1 = o[34];
            if (c4 == 0) { sts64f(ml + w * 512 + row * 8, n0, l0); sts64f(ml + w * 512 + row * 8 + 64, n1, l1); }
            TS(14);
            float mine[16];
#pragma unroll
            for (int j = 0; j < 4; j++) {
                if (w == 0) sts128f(H + j * 2048 + wt * 16, o[16 + 4 * j], o[17 + 4 * j], o[18 + 4 * j], o[19 + 4 * j]);
                else sts128f(H + 8192 + j * 2048 + wt * 16, o[4 * j], o[4 * j + 1], o[4 * j + 2], o[4 * j + 3]);
            }
#pragma unroll
            for (int i = 0; i < 16; i++) mine[i] = w == 0 ? o[i] : o[16 + i];
            bar_sync(10, 256);
            const float2 u0 = lds64f(ml + (w ^ 1) * 512 + row * 8), u1 = lds64f(ml + (w ^ 1) * 512 + row * 8 + 64);
            const float x0 = fminf(n0, u0.x), x1 = fminf(n1, u1.x);
            float a0 = ex2(x0 - n0), b0 = ex2(x0 - u0.x), a1 = ex2(x1 - n1), b1 = ex2(x1 - u1.x);
            const float i0 = __fdividef(1.f, fmaf(a0, l0, b0 * u0.y)), i1 = __fdividef(1.f, fmaf(a1, l1, b1 * u1.y));
            a0 *= i0; b0 *= i0; a1 *= i1; b1 *= i1;
            uint32_t pk[8];
#pragma unroll
            for (int j = 0; j < 4; j++) {
                const float4 v = lds128f(H + (w ^ 1) * 8192 + j * 2048 + wt * 16);
                pk[2 * j] = pack2(fmaf(a0, mine[4 * j], b0 * v.x), fmaf(a0, mine[4 * j + 1], b0 * v.y));
                pk[2 * j + 1] = pack2(fmaf(a1, mine[4 * j + 2], b1 * v.z), fmaf(a1, mine[4 * j + 3], b1 * v.w));
            }
            unsigned char* dst = g_o + (size_t)(b * 128 + qt * 8 + 2 * wq) * 4096 + ah * 1024 + w * 512 + lane * 16;
            st_data(dst, pk[0], pk[2], pk[4], pk[6]);
            st_data(dst + 4096, pk[1], pk[3], pk[5], pk[7]);
            if (tid == 0) asm volatile("red.relaxed.gpu.global.add.u32 [%0], 1;" ::"l"(&g_epoch[blockIdx.x * FS]) : "memory");
            TS(15);
        }

        {
            const uint32_t* dp = reinterpret_cast<const uint32_t*>(p.dw + (mir ? 14 * 256 : 0) + tile * 64) + lane;
#pragma unroll
            for (int i = 0; i < 15; i++) asm volatile("ld.global.nc.b32 %0, [%1];" : "=r"(dwr[i]) : "l"(dp + i * (mir ? -128 : 128)));
            acq(32); acq(33); acq(34);
            uint4 u[8];
            ld_data<512>(u, g_o + (size_t)(b * 128 + pt * 4 + wq) * 4096 + lane * 16);
#pragma unroll
            for (int i = 0; i < 8; i++) { a[4 * i] = u[i].x; a[4 * i + 1] = u[i].y; a[4 * i + 2] = u[i].z; a[4 * i + 3] = u[i].w; }
            if (LATE & 4) rel(31);
            TS(16);
            sp(d0, 32, a, 0, 0);
            sp(d0, 33, a + 16, 0, 1);
#pragma unroll
            for (int i = 0; i < 15; i++) dwr[i] = hmul2(dwr[i], 0x3F003F00u);
            residual(32);
            TS(17);
        }
    }

    cluster_arrive();
    TS(24);
    {
        const float rstd = rsq(fmaxf(fmaf(-mean, mean, msq), 0.f) + 1e-5f), nb = -mean * rstd;
#pragma unroll
        for (int j = 0; j < 8; j++) xr[j] = pack2(fmaf(v[2 * j], rstd, nb), fmaf(v[2 * j + 1], rstd, nb));
        const uint32_t stg = P + 16384 + warp * 1024;
        stsm4(stg + foff, xr[0], xr[1], xr[2], xr[3]);
        stsm4(stg + (foff ^ 64), xr[4], xr[5], xr[6], xr[7]);
        __syncwarp();
        const uint32_t src = stg + (lane >> 3) * 128 + (((lane & 7) ^ (lane >> 3)) << 4);
        const uint4 u0 = lds128(src), u1 = lds128((src + 512) ^ 64);
        __nv_bfloat16* dst = p.out + (size_t)(b * T_ + trow + (lane >> 3)) * 256 + tile * 64 + (lane & 7) * 8;
        if (trow < T_) { stg128(dst, u0); stg128(dst + 4 * 256, u1); }
    }
    TS(25);
    TG(31);
    TSDUMP();
    cluster_wait();
}

typedef CUresult (*EncodeFn)(CUtensorMap*, CUtensorMapDataType, cuuint32_t, void*, const cuuint64_t*, const cuuint64_t*,
                             const cuuint32_t*, const cuuint32_t*, CUtensorMapInterleave, CUtensorMapSwizzle,
                             CUtensorMapL2promotion, CUtensorMapFloatOOBfill);

}

extern "C" void kernel_launch(void* const* d_in, const int* in_sizes, int n_in, void* d_out, int out_size) {
    static EncodeFn encode = nullptr;
    if (!encode) {
        void* fn = nullptr;
        cudaDriverEntryPointQueryResult qr;
        cudaGetDriverEntryPoint("cuTensorMapEncodeTiled", &fn, cudaEnableDefault, &qr);
        encode = (EncodeFn)fn;
        cudaFuncSetAttribute(conformer_kernel, cudaFuncAttributeMaxDynamicSharedMemorySize, SMEM_LAUNCH);
    }
    Params p;
    const cuuint32_t ones[5] = {1, 1, 1, 1, 1};
    const int idx[8] = {1, 2, 3, 4, 5, 7, 8, 9};
    const int rows[8] = {256, 1024, 256, 256, 256, 256, 256, 1024};
    const int cols[8] = {1024, 256, 768, 256, 512, 256, 1024, 256};
    for (int i = 0; i < 8; i++) {
        const cuuint64_t pitch = (cuuint64_t)cols[i] * 2;
        const cuuint64_t dims[5] = {(cuuint64_t)cols[i], i ? 2u : 4u, i ? 2u : 4u, i ? 4u : 2u, (cuuint64_t)rows[i] / (i ? 16 : 32)};
        const cuuint64_t strides[4] = {pitch, pitch * 8, pitch * (i ? 2 : 4), pitch * (i ? 16 : 32)};
        const cuuint32_t box[5] = {64, i ? 2u : 4u, i ? 2u : 4u, i ? 4u : 2u, i ? 8u : 4u};
        encode(&p.tm[i], CU_TENSOR_MAP_DATA_TYPE_BFLOAT16, 5, d_in[idx[i]], dims, strides, box, ones, CU_TENSOR_MAP_INTERLEAVE_NONE,
               CU_TENSOR_MAP_SWIZZLE_128B, CU_TENSOR_MAP_L2_PROMOTION_L2_128B, CU_TENSOR_MAP_FLOAT_OOB_FILL_NONE);
        p.w[i] = (const char*)d_in[idx[i]];
    }
    {
        void* kv = nullptr;
        cudaGetSymbolAddress(&kv, g_kvq);
        const cuuint64_t dims[2] = {64, 16384};
        const cuuint64_t strides[1] = {128};
        const cuuint32_t box[2] = {64, 128};
        encode(&p.tm[8], CU_TENSOR_MAP_DATA_TYPE_BFLOAT16, 2, kv, dims, strides, box, ones, CU_TENSOR_MAP_INTERLEAVE_NONE,
               CU_TENSOR_MAP_SWIZZLE_NONE, CU_TENSOR_MAP_L2_PROMOTION_L2_128B, CU_TENSOR_MAP_FLOAT_OOB_FILL_NONE);
    }
    p.x = (const __nv_bfloat16*)d_in[0];
    p.dw = (const __nv_bfloat16*)d_in[6];
    p.out = (__nv_bfloat16*)d_out;
    p.zero = 0;
    conformer_kernel<<<NCTA, NTHREADS, SMEM_LAUNCH>>>(p);
}
```

```cpp
#include <cuda_runtime.h>
#include <cuda_bf16.h>
#include <cuda.h>
#include <stdint.h>

namespace {

constexpr int T_ = 1000;
constexpr int NCTA = 128;
constexpr int NTHREADS = 512;
constexpr int NSLOT = 5;
constexpr int SLOT = 16384;
constexpr int NLOADS = 56;

constexpr uint32_t OFF_RING = 0;
constexpr uint32_t OFF_P = 163840;
constexpr uint32_t OFF_H = 188416;
constexpr uint32_t OFF_MISC = 221184;
constexpr uint32_t OFF_BARS = 229888;
constexpr uint32_t SMEM_BYTES = 230400;
constexpr uint32_t GCH = 6144;
constexpr uint32_t HCH = 4096;

constexpr int B_FULL = 0, B_EMPTY = 10, B_XA = 20  , B_XB = 25  , B_INB = 29  , B_SR = 33,
              B_RST = 34  , B_RDY = 36  , B_SINK = 42, B_HALO = 43  , NBARS = 47;

#define KD2 300u
#define KD3 500u
#define QGATE 500u
#define BACKOFF 0u
#define KFS 8
#define KDELAY 300u
#define NJ0 2
#define HDELAY 200u
#define LATE 2
#define SND 0
#define PF0 1
#define NFIRST 2
#define TURN 0x200
#define EAGER 0x0155
constexpr int FS = 8;

struct Params {
    CUtensorMap tm[9];
    const char* w[8];
    const __nv_bfloat16* x;
    const __nv_bfloat16* dw;
    __nv_bfloat16* out;
    uint32_t zero;
};

__device__ __align__(1024) unsigned char g_kvq[3 * 8 * 1024 * 128];
__device__ __align__(1024) unsigned char g_o[2 * 128 * 4096];
__device__ uint4 g_halo[64 * 4 * 2 * 64];
__device__ __align__(128) uint32_t g_flag_kv[8 * 32 * KFS];
__device__ uint32_t g_reset[4 * 32];
__device__ uint32_t g_epoch[NCTA * FS];

#define TS(i) do { } while (0)
#define TSW(i) do { } while (0)
#define TG(i) do { } while (0)
#define TSINIT() do { } while (0)
#define TSDUMP() do { } while (0)
constexpr uint32_t SMEM_LAUNCH = SMEM_BYTES;

__device__ __forceinline__ uint32_t smem_u32(const void* p) { return (uint32_t)__cvta_generic_to_shared(p); }
__device__ __forceinline__ void mbar_init(uint32_t b, uint32_t c) { asm volatile("mbarrier.init.shared::cta.b64 [%0], %1;" ::"r"(b), "r"(c) : "memory"); }
__device__ __forceinline__ void mbar_arrive(uint32_t b) { asm volatile("mbarrier.arrive.shared::cta.b64 _, [%0];" ::"r"(b) : "memory"); }
__device__ __forceinline__ void mbar_arrive_tx(uint32_t b, uint32_t tx) { asm volatile("mbarrier.arrive.expect_tx.shared::cta.b64 _, [%0], %1;" ::"r"(b), "r"(tx) : "memory"); }
__device__ __forceinline__ void mbar_wait(uint32_t b, uint32_t ph) {
    asm volatile("{\n.reg .pred p, q;\n.reg .u32 c;\nmov.u32 c, 0;\n"
                 "MW_LOOP:\n.pragma \"nounroll\";\n"
                 "mbarrier.try_wait.parity.shared::cta.b64 p, [%0], %1;\n"
                 "add.u32 c, c, 1;\nsetp.lt.u32 q, c, 65536;\nnot.pred p, p;\nand.pred p, p, q;\n@p bra MW_LOOP;\n}"
                 ::"r"(b), "r"(ph) : "memory");
}
__device__ __forceinline__ bool mbar_test(uint32_t b, uint32_t ph) {
    uint32_t ok;
    asm volatile("{\n.reg .pred p;\nmbarrier.test_wait.parity.shared::cta.b64 p, [%1], %2;\nselp.u32 %0, 1, 0, p;\n}" : "=r"(ok) : "r"(b), "r"(ph) : "memory");
    return ok;
}
__device__ __forceinline__ uint32_t mapa(uint32_t a, uint32_t r) { uint32_t o; asm("mapa.shared::cluster.u32 %0, %1, %2;" : "=r"(o) : "r"(a), "r"(r)); return o; }
__device__ __forceinline__ void fence_async_smem() { asm volatile("fence.proxy.async.shared::cta;" ::: "memory"); }
__device__ __forceinline__ void fence_async_global() { asm volatile("fence.proxy.async.global;" ::: "memory"); }
__device__ __forceinline__ void bar_sync(int id, int n) { asm volatile("bar.sync %0, %1;" ::"r"(id), "r"(n) : "memory"); }
__device__ __forceinline__ void bar_arrive(int id, int n) { asm volatile("bar.arrive %0, %1;" ::"r"(id), "r"(n) : "memory"); }
__device__ __forceinline__ void cluster_arrive() { asm volatile("barrier.cluster.arrive.relaxed.aligned;" ::: "memory"); }
__device__ __forceinline__ void cluster_wait() { asm volatile("barrier.cluster.wait.aligned;" ::: "memory"); }

__device__ __forceinline__ void ring_load(uint32_t dst, const CUtensorMap* tm, int col, int row16, uint32_t bar) {
    asm volatile("{\n.reg .pred p;\nelect.sync _|p, 0xffffffff;\n"
                 "@p mbarrier.arrive.expect_tx.shared::cta.b64 _, [%2], 16384;\n"
                 "@p cp.async.bulk.tensor.5d.shared::cluster.global.mbarrier::complete_tx::bytes [%0], [%1, {%3, 0, 0, 0, %4}], [%2];\n}"
                 ::"r"(dst), "l"(tm), "r"(bar), "r"(col), "r"(row16) : "memory");
}
__device__ __forceinline__ void ring_load_both(uint32_t dst, const CUtensorMap* tm, int c1, uint32_t bar) {
    asm volatile("{\n.reg .pred p;\nelect.sync _|p, 0xffffffff;\n"
                 "@p cp.async.bulk.tensor.2d.shared::cluster.global.mbarrier::complete_tx::bytes.multicast::cluster [%0], [%1, {0, %3}], [%2], %4;\n}"
                 ::"r"(dst), "l"(tm), "r"(bar), "r"(c1), "h"((uint16_t)3) : "memory");
}
__device__ __forceinline__ void mbar_arrive_peer(uint32_t b) { asm volatile("mbarrier.arrive.relaxed.cluster.shared::cluster.b64 _, [%0];" ::"r"(b) : "memory"); }
__device__ __forceinline__ void prefetch_l2(const void* src, uint32_t bytes) {
    asm volatile("cp.async.bulk.prefetch.L2.global [%0], %1;" ::"l"(src), "r"(bytes) : "memory");
}
__device__ __forceinline__ void peer_copy(uint32_t dst, uint32_t src, uint32_t bytes, uint32_t rbar) {
    asm volatile("{\n.reg .pred p;\nelect.sync _|p, 0xffffffff;\n"
                 "@p cp.async.bulk.shared::cluster.shared::cta.mbarrier::complete_tx::bytes [%0], [%1], %2, [%3];\n}"
                 ::"r"(dst), "r"(src), "r"(bytes), "r"(rbar) : "memory");
}
__device__ __forceinline__ void st_async4(uint32_t dst, uint32_t a, uint32_t b, uint32_t c, uint32_t d, uint32_t bar) {
    asm volatile("st.async.shared::cluster.mbarrier::complete_tx::bytes.v4.b32 [%0], {%1,%2,%3,%4}, [%5];" ::"r"(dst), "r"(a), "r"(b), "r"(c), "r"(d), "r"(bar) : "memory");
}
__device__ __forceinline__ void put_sums(uint32_t dst, uint32_t rdst, float a, float b, uint32_t rbar, bool on) {
    asm volatile("{\n.reg .pred p;\nsetp.ne.u32 p, %5, 0;\n"
                 "@p st.async.shared::cluster.mbarrier::complete_tx::bytes.v2.f32 [%1], {%2,%3}, [%4];\n"
                 "@p st.shared.v2.f32 [%0], {%2,%3};\n}" ::"r"(dst), "r"(rdst), "f"(a), "f"(b), "r"(rbar), "r"((uint32_t)on) : "memory");
}
__device__ __forceinline__ void stsm4(uint32_t a, uint32_t r0, uint32_t r1, uint32_t r2, uint32_t r3) {
    asm volatile("stmatrix.sync.aligned.m8n8.x4.shared.b16 [%0], {%1,%2,%3,%4};" ::"r"(a), "r"(r0), "r"(r1), "r"(r2), "r"(r3) : "memory");
}
__device__ __forceinline__ void ldsm4(uint32_t a, uint32_t& r0, uint32_t& r1, uint32_t& r2, uint32_t& r3) {
    asm volatile("ldmatrix.sync.aligned.m8n8.x4.shared.b16 {%0,%1,%2,%3}, [%4];" : "=r"(r0), "=r"(r1), "=r"(r2), "=r"(r3) : "r"(a) : "memory");
}
__device__ __forceinline__ uint4 lds128(uint32_t a) { uint4 v; asm volatile("ld.shared.v4.b32 {%0,%1,%2,%3}, [%4];" : "=r"(v.x), "=r"(v.y), "=r"(v.z), "=r"(v.w) : "r"(a) : "memory"); return v; }
__device__ __forceinline__ float4 lds128f(uint32_t a) { float4 v; asm volatile("ld.shared.v4.f32 {%0,%1,%2,%3}, [%4];" : "=f"(v.x), "=f"(v.y), "=f"(v.z), "=f"(v.w) : "r"(a) : "memory"); return v; }
__device__ __forceinline__ float2 lds64f(uint32_t a) { float2 v; asm volatile("ld.shared.v2.f32 {%0,%1}, [%2];" : "=f"(v.x), "=f"(v.y) : "r"(a) : "memory"); return v; }
__device__ __forceinline__ uint32_t lds32(uint32_t a) { uint32_t v; asm volatile("ld.shared.b32 %0, [%1];" : "=r"(v) : "r"(a) : "memory"); return v; }
__device__ __forceinline__ void sts128(uint32_t a, uint32_t x, uint32_t y, uint32_t z, uint32_t w) { asm volatile("st.shared.v4.b32 [%0], {%1,%2,%3,%4};" ::"r"(a), "r"(x), "r"(y), "r"(z), "r"(w) : "memory"); }
__device__ __forceinline__ void sts128f(uint32_t a, float x, float y, float z, float w) { asm volatile("st.shared.v4.f32 [%0], {%1,%2,%3,%4};" ::"r"(a), "f"(x), "f"(y), "f"(z), "f"(w) : "memory"); }
__device__ __forceinline__ void sts64f(uint32_t a, float x, float y) { asm volatile("st.shared.v2.f32 [%0], {%1,%2};" ::"r"(a), "f"(x), "f"(y) : "memory"); }
__device__ __forceinline__ void sts32(uint32_t a, uint32_t x) { asm volatile("st.shared.b32 [%0], %1;" ::"r"(a), "r"(x) : "memory"); }
__device__ __forceinline__ void stg128(void* p, uint4 v) { asm volatile("st.global.v4.b32 [%0], {%1,%2,%3,%4};" ::"l"(p), "r"(v.x), "r"(v.y), "r"(v.z), "r"(v.w) : "memory"); }

__device__ __forceinline__ uint32_t pack2(float lo, float hi) { uint32_t r; asm("cvt.rn.bf16x2.f32 %0, %1, %2;" : "=r"(r) : "f"(hi), "f"(lo)); return r; }
__device__ __forceinline__ float blo(uint32_t v) { return __uint_as_float(v << 16); }
__device__ __forceinline__ float bhi(uint32_t v) { return __uint_as_float(v & 0xffff0000u); }
__device__ __forceinline__ uint32_t hmul2(uint32_t a, uint32_t b) { uint32_t r; asm("mul.rn.bf16x2 %0, %1, %2;" : "=r"(r) : "r"(a), "r"(b)); return r; }
__device__ __forceinline__ uint32_t hadd2(uint32_t a, uint32_t b) { uint32_t r; asm("add.rn.bf16x2 %0, %1, %2;" : "=r"(r) : "r"(a), "r"(b)); return r; }
__device__ __forceinline__ uint32_t hsub2(uint32_t a, uint32_t b) { uint32_t r; asm("sub.rn.bf16x2 %0, %1, %2;" : "=r"(r) : "r"(a), "r"(b)); return r; }
__device__ __forceinline__ uint32_t hfma2(uint32_t a, uint32_t b, uint32_t c) { uint32_t r; asm("fma.rn.bf16x2 %0, %1, %2, %3;" : "=r"(r) : "r"(a), "r"(b), "r"(c)); return r; }
__device__ __forceinline__ float tanh_fast(float x) { float r; asm("tanh.approx.f32 %0, %1;" : "=f"(r) : "f"(x)); return r; }
__device__ __forceinline__ float rsq(float x) { float r; asm("rsqrt.approx.ftz.f32 %0, %1;" : "=f"(r) : "f"(x)); return r; }
__device__ __forceinline__ float ex2(float x) { float r; asm("ex2.approx.ftz.f32 %0, %1;" : "=f"(r) : "f"(x)); return r; }

__device__ __forceinline__ uint32_t ld_relaxed(const uint32_t* p) {
    uint32_t v;
    asm volatile("ld.relaxed.gpu.global.u32 %0, [%1];" : "=r"(v) : "l"(p) : "memory");
    return v;
}
__device__ __forceinline__ uint32_t clock32() { uint32_t c; asm volatile("mov.u32 %0, %%clock;" : "=r"(c)::"memory"); return c; }
__device__ __forceinline__ void spin(uint32_t clks) {
    const uint32_t t0 = clock32();
    while (clock32() - t0 < clks) {}
}
__device__ __forceinline__ void flag_wait(const uint32_t* p, uint32_t e, bool mine) {
#pragma unroll 1
    for (int i = 0; i < (1 << 19); i++) {
        if (mine) mine = ld_relaxed(p) != e;
        if (!__any_sync(~0u, mine)) break;
        if (BACKOFF) spin(BACKOFF);
    }
    asm volatile("fence.acquire.gpu;" ::: "memory");
    fence_async_global();
}
__device__ __forceinline__ void st_data(void* p, uint32_t x, uint32_t y, uint32_t z, uint32_t w) {
    asm volatile("st.relaxed.gpu.global.v4.b32 [%0], {%1,%2,%3,%4};" ::"l"(p), "r"(x), "r"(y), "r"(z), "r"(w) : "memory");
}
template <int STRIDE, int N>
__device__ __forceinline__ void ld_data(uint4 (&v)[N], const unsigned char* p) {
    int it = 0;
    bool again;
#pragma unroll 1
    do {
        uint32_t m = 0;
#pragma unroll
        for (int i = 0; i < N; i++)
            asm volatile("ld.relaxed.gpu.global.v4.b32 {%0,%1,%2,%3}, [%4];" : "=r"(v[i].x), "=r"(v[i].y), "=r"(v[i].z), "=r"(v[i].w) : "l"(p + i * STRIDE) : "memory");
#pragma unroll
        for (int i = 0; i < N; i++) m = __vimax3_u32(__vimax3_u32(v[i].x, v[i].y, v[i].z), v[i].w, m);
        again = __any_sync(~0u, m == ~0u) && ++it < (1 << 16);
    } while (again);
}
__device__ __forceinline__ uint32_t ld_epoch() { return ld_relaxed(&g_epoch[blockIdx.x * FS]) + 1; }
__device__ __forceinline__ void flag_set(uint32_t* p, uint32_t e) { asm volatile("st.release.gpu.global.u32 [%0], %1;" ::"l"(p), "r"(e) : "memory"); }

__device__ __forceinline__ uint32_t desc_lo(uint32_t addr) { return ((addr & 0x3FFFF) >> 4) | 0x10000u; }
__device__ __forceinline__ uint64_t mkdesc(uint32_t lo) { return (uint64_t)lo | (0x40000040ull << 32); }
__device__ __forceinline__ void wg_fence() { asm volatile("wgmma.fence.sync.aligned;" ::: "memory"); }
__device__ __forceinline__ void wg_commit() { asm volatile("wgmma.commit_group.sync.aligned;" ::: "memory"); }
template <int N> __device__ __forceinline__ void wg_wait() { asm volatile("wgmma.wait_group.sync.aligned %0;" ::"n"(N) : "memory"); }
template <int N> __device__ __forceinline__ void pin(float (&d)[N]) {
#pragma unroll
    for (int i = 0; i < N; i++) asm volatile("" : "+f"(d[i])::"memory");
}
template <int N> __device__ __forceinline__ void pin(uint32_t (&d)[N]) {
#pragma unroll
    for (int i = 0; i < N; i++) asm volatile("" : "+r"(d[i])::"memory");
}

template <typename Tp, int N> __device__ __forceinline__ void zero(Tp (&d)[N]) {
#pragma unroll
    for (int i = 0; i < N; i++) d[i] = 0;
    pin(d);
}

#define F4(d, i) "+f"(d[i]), "+f"(d[i + 1]), "+f"(d[i + 2]), "+f"(d[i + 3])
#define F16(d, i) F4(d, i), F4(d, i + 4), F4(d, i + 8), F4(d, i + 12)

__device__ __forceinline__ void mma16(float (&d)[4], const uint32_t* a, uint32_t b0, uint32_t b1) {
    asm("mma.sync.aligned.m16n8k16.row.col.f32.bf16.bf16.f32 {%0,%1,%2,%3}, {%4,%5,%6,%7}, {%8,%9}, {%0,%1,%2,%3};"
        : F4(d, 0) : "r"(a[0]), "r"(a[1]), "r"(a[2]), "r"(a[3]), "r"(b0), "r"(b1));
}
template <int N>
__device__ __forceinline__ float row_sum(const uint32_t* x, uint32_t ones = 0x3F803F80u) {
    float c[4] = {};
#pragma unroll
    for (int i = 0; i < N; i += 4) mma16(c, x + i, ones, ones);
    return c[0] + c[2];
}
template <int N>
__device__ __forceinline__ float row_sumsq(const uint32_t* x, int lane) {
    float c0[4] = {}, c1[4] = {};
#pragma unroll
    for (int i = 0; i < N; i += 4) {
        mma16(c0, x + i, x[i], x[i + 2]);
        mma16(c1, x + i, x[i + 1], x[i + 3]);
    }
    return (lane & 4) ? c0[1] + c1[3] : c0[0] + c1[2];
}
__device__ __forceinline__ void mma_sp(float (&d)[32], const uint32_t* a, uint64_t b, uint32_t meta, int acc) {
    asm volatile("{.reg .pred p; setp.ne.b32 p, %38, 0;\n"
                 "wgmma.mma_async.sp.sync.aligned.m64n64k32.f32.bf16.bf16 {%0,%1,%2,%3,%4,%5,%6,%7,%8,%9,%10,%11,%12,%13,%14,%15,%16,%17,%18,%19,%20,%21,%22,%23,%24,%25,%26,%27,%28,%29,%30,%31}, "
                 "{%32,%33,%34,%35}, %36, %37, 0, p, 1, 1, 1;}\n"
                 : F16(d, 0), F16(d, 16) : "r"(a[0]), "r"(a[1]), "r"(a[2]), "r"(a[3]), "l"(b), "r"(meta), "r"(acc));
}
__device__ __forceinline__ void mma_qk(float (&d)[32], uint32_t a0, uint32_t a1, uint32_t a2, uint32_t a3, uint64_t b, int acc) {
    asm volatile("{.reg .pred p; setp.ne.b32 p, %37, 0;\n"
                 "wgmma.mma_async.sync.aligned.m64n64k16.f32.bf16.bf16 {%0,%1,%2,%3,%4,%5,%6,%7,%8,%9,%10,%11,%12,%13,%14,%15,%16,%17,%18,%19,%20,%21,%22,%23,%24,%25,%26,%27,%28,%29,%30,%31}, "
                 "{%32,%33,%34,%35}, %36, p, 1, 1, 0;}\n"
                 : F16(d, 0), F16(d, 16) : "r"(a0), "r"(a1), "r"(a2), "r"(a3), "l"(b), "r"(acc));
}
__device__ __forceinline__ void mma_pv(float (&d)[36], uint32_t a0, uint32_t a1, uint32_t a2, uint32_t a3, uint64_t b) {
    asm volatile("wgmma.mma_async.sync.aligned.m64n72k16.f32.bf16.bf16 {%0,%1,%2,%3,%4,%5,%6,%7,%8,%9,%10,%11,%12,%13,%14,%15,%16,%17,%18,%19,%20,%21,%22,%23,%24,%25,%26,%27,%28,%29,%30,%31,%32,%33,%34,%35}, "
                 "{%36,%37,%38,%39}, %40, 1, 1, 1, 1;\n"
                 : F16(d, 0), F16(d, 16), F4(d, 32) : "r"(a0), "r"(a1), "r"(a2), "r"(a3), "l"(b));
}

__device__ __forceinline__ uint32_t load_code(int n, int r, int w) {
    const int tile = 2 * r + w;
    int m, col, row;
    if (n < 16 || n >= 40) {
        const int k = n < 16 ? n : n - 40;
        m = n < 16 ? 0 : 6;
        if (k < 8) { col = 4 * tile + (k >> 1); row = n < 16 ? (k & 1) : (k & 1) ^ r; }
        else { m++; col = k < 12 ? tile ^ 2 : tile; row = 2 * (tile ^ (k & 1)) + ((k >> 1) & 1); }
    } else if (n < 32) {
        const int k = n - 16;
        m = 2;
        if (k < 4) { col = tile + ((k & 1) ? 8 : 4); row = (k >> 1) ^ r; }
        else { col = tile; row = (k & 1) ^ r; }
    } else if (n < 34) { m = 3; col = tile; row = n - 32; }
    else if (n < 38) { const int k = n - 34; m = 4; col = tile + 4 * (k & 1); row = (k >> 1) ^ r; }
    else { m = 5; col = tile; row = (n & 1) ^ r; }
    return m | (col << 4) | (row << (m ? 11 : 10));
}

__global__ void __cluster_dims__(2, 1, 1) __launch_bounds__(NTHREADS, 1)
conformer_kernel(const __grid_constant__ Params p) {
    extern __shared__ __align__(1024) unsigned char smem_raw[];
    const uint32_t sb = smem_u32(smem_raw);
    const uint32_t bars = sb + OFF_BARS;
    const int tid = threadIdx.x;
    const int lane = tid & 31;
    const int warp = __shfl_sync(~0u, tid >> 5, 0);
    const int r = blockIdx.x & 1;
    const int pair = blockIdx.x >> 1;
    const int b = pair >> 5, pt = pair & 31;
    const int ah = pt >> 3, qt = (pt & 7) * 2 + r;
    const int abh = b * 4 + ah;

    TG(30);
    TSINIT();
    TS(0);
    const uint32_t P = sb + OFF_P, H = sb + OFF_H;
    if (warp == 11) {
        if (lane == 0) {
#pragma unroll
            for (int i = 0; i < 2 * NSLOT; i++) mbar_init(bars + (B_FULL + i) * 8, 1);
            asm volatile("fence.mbarrier_init.release.cluster;" ::: "memory");
            fence_async_smem();
        }
        __syncwarp();
#pragma unroll
        for (int i = 0; i < 2 * NFIRST; i++)
            ring_load(sb + OFF_RING + ((i & 1) * NSLOT + (i >> 1)) * SLOT, &p.tm[0], 64 * (8 * r + 4 * (i & 1) + (i >> 2)), 4 * ((i >> 1) & 1),
                      bars + (B_FULL + (i & 1) * NSLOT + (i >> 1)) * 8);
        bar_arrive(13, 96);
        cluster_arrive();
    }

    if (warp >= 8) {
        asm volatile("setmaxnreg.dec.sync.aligned.u32 48;");
        if (warp >= 12) {
            cluster_arrive();
            cluster_wait();
            const int ut = tid & 127;
            const uint32_t target = ld_epoch() * 64;
            auto reset_done = [&](int k) {
                bar_sync(11, 128);
                if (ut == 0) {
                    asm volatile("red.release.gpu.global.add.u32 [%0], 1;" ::"l"(&g_reset[(2 * b + k) * 32]) : "memory");
#pragma unroll 1
                    for (int i = 0; i < (1 << 20) && ld_relaxed(&g_reset[(2 * b + k) * 32]) != target; i++) __nanosleep(100);
                    asm volatile("fence.acquire.gpu;" ::: "memory");
                    mbar_arrive(bars + (B_RST + k) * 8);
                }
                __syncwarp();
                TS(13 + k);
            };
#pragma unroll
            for (int i = 0; i < 4; i++)
                st_data(g_kvq + 2097152 + (size_t)((b * 4 + 2 * r + (i >> 1)) * 1024 + pt * 32) * 128 + (i & 1) * 2048 + ut * 16, ~0u, ~0u, ~0u, ~0u);
            reset_done(0);
            bar_sync(6, 384);
#pragma unroll
            for (int i = 0; i < 4; i++) {
                st_data(g_o + (size_t)(b * 128 + qt * 8 + 2 * i + (ut >> 6)) * 4096 + ah * 1024 + (ut & 63) * 16, ~0u, ~0u, ~0u, ~0u);
                if (i < 2) st_data(&g_halo[(pair * 4 + 2 * r + i) * 128 + ut], ~0u, ~0u, ~0u, ~0u);
            }
            reset_done(1);
            const int side = warp & 1, wg = (warp >> 1) & 1, np = side ? pt + 1 : pt - 1;
            const unsigned char* src = reinterpret_cast<const unsigned char*>(&g_halo[(((b * 32 + np) * 4 + 2 * r + wg) * 2 + (side ^ 1)) * 64 + lane]);
            const uint32_t dst = H + 16384 + wg * GCH + side * 5120 + (lane & 7) * 128 + (((lane >> 3) ^ (lane & 7)) << 4);
            uint4 hv[2] = {make_uint4(0, 0, 0, 0), make_uint4(0, 0, 0, 0)};
            bar_sync(8 + wg, 192);
            if (np >= 0 && np < 32) {
                spin(HDELAY);
                ld_data<512>(hv, src);
            }
            stsm4(dst, hv[0].x, hv[0].y, hv[0].z, hv[0].w);
            stsm4(dst ^ 64, hv[1].x, hv[1].y, hv[1].z, hv[1].w);
            __syncwarp();
            if (lane == 0) mbar_arrive(bars + (B_HALO + (warp & 3)) * 8);
            TS(4);
        } else if (warp < 10) {
            const int w = warp - 8;
            const uint32_t ring = sb + OFF_RING + w * NSLOT * SLOT;
            const uint32_t full = bars + (B_FULL + w * NSLOT) * 8;
            cluster_arrive();
            bar_sync(13, 96);
            TS(1);
#pragma unroll
            for (int n = NFIRST; n < NSLOT; n++) {
                if (n == NFIRST + 1) bar_sync(12, 64);
                ring_load(ring + n * SLOT, &p.tm[0], 64 * (8 * r + 4 * w + (n >> 1)), 4 * (n & 1), full + n * 8);
            }
            TS(2);
            const uint32_t code = load_code(lane, r, w) | (load_code(lane + 32, r, w) << 16);
            cluster_wait();
            uint32_t s = 0, ph = 0;
            int n = NSLOT;
#pragma unroll 1
            for (int seg = 0; seg < 2; seg++) {
#pragma unroll 1
                for (; n < (seg == 0 ? 22 : NLOADS); n++) {
                    const uint32_t c = __shfl_sync(~0u, code, n) >> (n & 32 ? 16 : 0);
                    const CUtensorMap* tm = &p.tm[c & 15];
                    const uint32_t col = (c & 0xf0) * 4, row = (c & 0xff00) >> 8, dst = ring + s * SLOT;
                    mbar_wait(full + (B_EMPTY - B_FULL) * 8 + s * 8, ph + (((uint32_t)(size_t)tm | col | row | dst) & p.zero));
                    ring_load(dst, tm, col, row, full + s * 8);
                    if (++s == NSLOT) { s = 0; ph ^= 1; }
                }
                if (seg == 1) break;
                const uint32_t epoch = ld_epoch();
                const uint32_t rdy = bars + (B_RDY + 3 * w) * 8, prdy = mapa(rdy, r ^ 1);
                const int odd = r ^ w;
                const uint32_t* flags = g_flag_kv + (abh * 32 + lane) * KFS;
                auto kv_load = [&](uint32_t sl, int isv, int i) {
                    ring_load_both(ring + sl * SLOT, &p.tm[8], (isv * 64 + abh * 8 + 2 * i + w) * 128, full + sl * 8);
                };
#pragma unroll 1
                for (int i = 0; i < 2; i++) {
                    if (lane < 3 + i) {
                        const uint32_t sl = i ? lane : lane + 2;
                        mbar_wait(full + (B_EMPTY - B_FULL + sl) * 8, i ^ 1);
                        mbar_arrive_tx(full + sl * 8, (i || lane == 2) ? SLOT : 0);
                    }
                    __syncwarp();
                }
                if (lane == 0) mbar_arrive_peer(prdy);
                bar_sync(14, 96);
                spin(KDELAY);
                mbar_wait(rdy, 0);
                flag_wait(flags, epoch, (lane >> 2) == 2 * odd + w);
                TSW(5 + 2 * odd);
                if (!odd) { kv_load(4, 0, 0); bar_arrive(12, 64); }
                else bar_sync(12, 64);
                spin(w ? KD3 : KD2);
                kv_load(odd ^ 1, odd ^ 1, odd);
                flag_wait(flags, epoch, (lane >> 2) == 2 * odd + w + 4);
                mbar_wait(full + (odd ^ 1) * 8, 1);
                kv_load(2 + odd, odd, 2 - odd);
#pragma unroll 1
                for (int i = 0; i < 3; i++) {
                    const uint32_t sl = i ? i - 1 : 4, bo = i == 2 ? 16 : 8;
                    mbar_wait(full + (B_EMPTY - B_FULL + sl) * 8, i != 0);
                    if (lane == 0) mbar_arrive_tx(full + sl * 8, SLOT);
                    if ((i & 1) != odd) {
                        mbar_wait(rdy + bo, 0);
                        kv_load(sl, i != 0, 2 + odd);
                    } else if (lane == 0) mbar_arrive_peer(prdy + bo);
                    __syncwarp();
                }
                n = 32; s = 2; ph = 1;
            }
        } else if (warp == 10) {
            if (lane == 0) {
#pragma unroll
                for (int i = B_EMPTY; i < NBARS; i++) mbar_init(bars + i * 8, i < B_XA ? 4 : 1);
#pragma unroll
                for (int i = B_XA; i <= B_SR; i++) mbar_arrive_tx(bars + i * 8, i < B_XB ? 512 : ((i >= B_INB && i < B_SR) ? 4096 : 8192));
                asm volatile("fence.mbarrier_init.release.cluster;" ::: "memory");
                fence_async_smem();
            }
            __syncwarp();
            cluster_arrive();
            cluster_wait();
        } else {
            const uint32_t kb = (lane < 2 || lane > 5) ? 4096 : (lane == 2 ? 3072 : (lane == 4 ? 2048 : 1024));
            const char* pf = p.w[lane & 7] + blockIdx.x * kb;
            cluster_wait();
            if (lane < PF0) prefetch_l2(pf, kb);
            mbar_wait(bars + B_FULL * 8, 0);
            if (lane >= PF0 && lane < 3) prefetch_l2(pf, kb);
            if (lane >= 1 && lane < 9) asm volatile("prefetch.tensormap [%0];" ::"l"(&p.tm[lane]) : "memory");
            mbar_wait(bars + (B_FULL + 1) * 8, 1);
            if (lane > 2 && lane < 8) prefetch_l2(pf, kb);
            if (lane == 8 && blockIdx.x < 15) prefetch_l2(p.dw + blockIdx.x * 256, 512);
            const uint32_t epoch = ld_epoch();
            bar_sync(4, 288);
            if (lane < 16) flag_set(&g_flag_kv[((b * 4 + 2 * r + (lane >> 3)) * 32 + pt) * KFS + (lane & 7)], epoch);
            __syncwarp();
            bar_arrive(14, 96);
            TSW(8);
        }
        TSDUMP();
        return;
    }

    const int w = warp >> 2, wq = warp & 3;
    const int tile = 2 * r + w;
    const int wt = tid & 127;
    const int c4 = lane & 3;
    const int trow = pt * 32 + 8 * wq;
    uint32_t xr[8];
    uint32_t a[32];
    const char* xrow = reinterpret_cast<const char*>(p.x) + (b * T_ + trow + (lane >> 2)) * 512;
    zero(a);
    if (trow < T_) {
        const char* src = xrow + c4 * 16 + p.zero;
#pragma unroll
        for (int i = 0; i < 8; i++)
            asm volatile("ld.global.nc.v4.b32 {%0,%1,%2,%3}, [%4];" : "=r"(a[4 * i]), "=r"(a[4 * i + 1]), "=r"(a[4 * i + 2]), "=r"(a[4 * i + 3]) : "l"(src + 64 * i));
    }
    cluster_arrive();
    asm volatile("setmaxnreg.inc.sync.aligned.u32 208;");
    const uint32_t rbase = sb + OFF_RING + w * NSLOT * SLOT, fbar = bars + (B_FULL + w * NSLOT) * 8;
    const uint32_t rdesc = desc_lo(rbase);
    auto acq = [&](int n) { mbar_wait(fbar + (n % NSLOT) * 8, (n / NSLOT) & 1); };
    auto rel = [&](int n) { if (lane == 0) mbar_arrive(fbar + (B_EMPTY - B_FULL + n % NSLOT) * 8); };
    const uint32_t foff = (lane & 7) * 128 + (((lane >> 3) ^ (lane & 7)) << 4);
    float v[16];
    const uint32_t xown = __shfl_sync(~0u, P + wt * 16 + tile * 4096, lane), xrem = __shfl_sync(~0u, P + wt * 16 + (r ^ 1) * 8192, lane);
    const uint32_t sbuf = __shfl_sync(~0u, sb + OFF_MISC + 1024 + (8 * wq + (lane >> 2)) * 32, lane);
    const uint32_t sown = __shfl_sync(~0u, sbuf + tile * 8, lane);
    const uint32_t peer = __shfl_sync(~0u, mapa(sb, r ^ 1) - sb, lane);
    const uint32_t hbuf = __shfl_sync(~0u, H + w * 4096 + wt * 16, lane);
    const uint32_t meta = __shfl_sync(~0u, 0xEEEE4444u + p.zero, lane);
    cluster_wait();
    TS(56);
    float mean, msq;
    const int mir = wq < 2 ? 7 : 0;
    uint32_t dwr[15] = {};

#pragma unroll
    for (int ph = 0; ph < 5; ph++) {
        uint4 o0, o1;
        if (ph == 0) {
            const uint32_t one = 0x3F803F80u + ((xown | xrem | sbuf | sown | hbuf | foff | rdesc | fbar) & p.zero);
            mean = ((row_sum<8>(a, one) + row_sum<8>(a + 8, one)) + (row_sum<8>(a + 16, one) + row_sum<8>(a + 24, one))) * (1.f / 256.f);
            TS(57);
        } else {
            const uint32_t xa = bars + (B_XA + ph) * 8;
#pragma unroll
            for (int j = 0; j < 8; j++) xr[j] = pack2(v[2 * j], v[2 * j + 1]);
            const float s = row_sum<8>(xr), q = row_sumsq<8>(xr, lane);
            if (ph < 4) {
                sts128(xown, xr[0], xr[1], xr[2], xr[3]);
                sts128(xown + 2048, xr[4], xr[5], xr[6], xr[7]);
            }
            put_sums(sown, sown + peer, s, q, xa + peer, c4 == (lane >> 3));
            bar_sync(10, 256);
            if (ph < 4) {
                o0 = lds128(xown ^ 4096); o1 = lds128((xown ^ 4096) + 2048);
                st_async4(xown + peer, xr[0], xr[1], xr[2], xr[3], xa + (B_XB - B_XA) * 8 + peer);
                st_async4(xown + peer + 2048, xr[4], xr[5], xr[6], xr[7], xa + (B_XB - B_XA) * 8 + peer);
            }
            TS(57 + ph);
            if (ph == 3) acq(0);
            if (ph == 1) acq(16);
            mbar_wait(xa, 0);
            const float4 u0 = lds128f(sbuf), u1 = lds128f(sbuf + 16);
            mean = ((u0.x + u0.z) + (u1.x + u1.z)) * (1.f / 256.f);
            msq = ((u0.y + u0.w) + (u1.y + u1.w)) * (1.f / 256.f);
        }
        if (ph == 4) break;
        const uint32_t mean2 = pack2(mean, mean);
        auto centre = [&](int i, const uint4& u) {
            a[i] = hsub2(u.x, mean2); a[i + 1] = hsub2(u.y, mean2); a[i + 2] = hsub2(u.z, mean2); a[i + 3] = hsub2(u.w, mean2);
        };
        if (ph == 0) {
#pragma unroll
            for (int j = 0; j < 32; j++) a[j] = hsub2(a[j], mean2);
            zero(xr);
            if (trow < T_) {
                const char* src = xrow + tile * 128 + c4 * 4 + (mean2 & p.zero);
#pragma unroll
                for (int j = 0; j < 8; j++) asm volatile("ld.global.nc.b32 %0, [%1];" : "=r"(xr[j]) : "l"(src + 16 * j));
            }
            mean -= blo(mean2);
            msq = __shfl_sync(~0u, row_sumsq<16>(a, lane) + row_sumsq<16>(a + 16, lane), (lane & 28) + (lane >> 3)) * (1.f / 256.f);
            acq(0);
        } else {
#pragma unroll
            for (int j = 0; j < 8; j++) a[j] = hsub2(xr[j], mean2);
            centre(8, o0); centre(12, o1);
        }
        const float rstd = rsq(fmaxf(fmaf(-mean, mean, msq), 0.f) + 1e-5f);
        auto gather_peer = [&]() {
            mbar_wait(bars + (B_XB + ph) * 8, 0);
#pragma unroll
            for (int i = 0; i < 4; i++) centre(16 + 4 * i, lds128(xrem + i * 2048));
        };
        auto sp = [&](float (&d)[32], int n, const uint32_t* af, int flip, int acc) {
            const uint32_t lo = rdesc + p.zero * (ph * 64 + n + 1) + (n % NSLOT) * (SLOT >> 4);
            const uint64_t b0 = mkdesc(lo + flip * 512), b1 = mkdesc(lo + (flip ^ 1) * 512);
            wg_fence();
            mma_sp(d, af, b0, meta, acc);
            mma_sp(d, af + 4, b0 + 256, meta, 1);
            mma_sp(d, af + 8, b1, meta, 1);
            mma_sp(d, af + 12, b1 + 256, meta, 1);
            wg_commit();
        };
        float d0[32], d1[32];

        if (ph == 0 || ph == 3) {
            uint32_t h[32], ho[32];
            const float rs = 0.5f * rstd;
            const uint32_t inb = bars + (B_INB + (ph & 2) + w) * 8;
            bool ready = true;
            const int eager = ph ? EAGER : EAGER - 1;
            auto step = [&](float (&d)[32], int n, const uint32_t* af, int flip, int acc, auto work) {
                if (!ready) acq(n);
                if (((TURN >> n) & 1) && w == 1) bar_sync(7, 256);
                sp(d, n, af, flip, acc);
                if (n > 0 && ((TURN >> (n - 1)) & 1) && w == 0) bar_arrive(7, 256);
                if (n < 15) ready = mbar_test(fbar + ((n + 1) % NSLOT) * 8, ((n + 1) / NSLOT) & 1);
                wg_wait<1>();
                if (n > 0 && !((eager >> (n - 1)) & 1)) rel(n - 1);
                const uint32_t tie = work() & p.zero;
                if ((eager >> n) & 1) {
                    if (p.zero < n + ph + 1) wg_wait<0>();
                    if (lane == 0) mbar_arrive(fbar + (B_EMPTY - B_FULL + n % NSLOT) * 8 + tie);
                }
            };
            auto none = []() { return 0u; };
            const int fl = ph ? w : 0;
            auto fetch = [&](int i) {
                bar_sync(10, 256);
                const uint4 u0 = lds128((hbuf ^ 4096) + (i & 1) * 8192), u1 = lds128((hbuf ^ 4096) + (i & 1) * 8192 + 2048);
                ho[8 * i] = u0.x; ho[8 * i + 1] = u0.y; ho[8 * i + 2] = u0.z; ho[8 * i + 3] = u0.w;
                ho[8 * i + 4] = u1.x; ho[8 * i + 5] = u1.y; ho[8 * i + 6] = u1.z; ho[8 * i + 7] = u1.w;
                return u0.x | u1.x;
            };
            auto act = [&](float (&d)[32], int i) {
                if (i > 0) fetch(i - 1);
                pin(d);
#pragma unroll
                for (int j = 0; j < 8; j++) {
                    const float u0 = (d[4 * j] + d[4 * j + 2]) * rs, u1 = (d[4 * j + 1] + d[4 * j + 3]) * rs;
                    h[8 * i + j] = pack2(fmaf(u0, tanh_fast(u0), u0), fmaf(u1, tanh_fast(u1), u1));
                }
                sts128(hbuf + (i & 1) * 8192, h[8 * i], h[8 * i + 1], h[8 * i + 2], h[8 * i + 3]);
                sts128(hbuf + (i & 1) * 8192 + 2048, h[8 * i + 4], h[8 * i + 5], h[8 * i + 6], h[8 * i + 7]);
                return 0u;
            };
            TS(1 + (ph & 2) * 10);
            step(d0, 0, a, fl, 0, [&]() { if (ph) gather_peer(); return 0u; });
            TS(32);
            step(d0, 1, a + 16, 0, 1, none);
            step(d1, 2, a, fl, 0, [&]() { return act(d0, 0); });
            step(d1, 3, a + 16, 0, 1, none);
            step(d0, 4, a, fl, 0, [&]() { return act(d1, 1); });
            TS(33);
            step(d0, 5, a + 16, 0, 1, none);
            step(d1, 6, a, fl, 0, [&]() { return act(d0, 2); });
            step(d1, 7, a + 16, 0, 1, none);
            step(d0, 8, h, 0, 0, [&]() { act(d1, 3); return fetch(3); });
            TS(2 + (ph & 2) * 10);
            step(d0, 9, ho, 0, 1, none);
            step(d0, 10, h + 16, 0, 1, none);
            step(d0, 11, ho + 16, 0, 1, none);
            uint32_t pk[8];
            auto pack_out = [&]() {
                pin(d0);
#pragma unroll
                for (int j = 0; j < 8; j++) pk[j] = pack2(d0[4 * j] + d0[4 * j + 2], d0[4 * j + 1] + d0[4 * j + 3]);
            };
            auto send = [&](int i) { st_async4(hbuf + 16384 + i * 2048 + peer, pk[4 * i], pk[4 * i + 1], pk[4 * i + 2], pk[4 * i + 3], inb + peer); };
            step(d1, 12, h, 0, 0, [&]() { pack_out(); if (SND != 1) send(0); if (SND == 0) send(1); return 0u; });
            TS(34);
            step(d1, 13, ho, 0, 1, [&]() { if (SND == 1) send(0); if (SND) send(1); return 0u; });
            step(d1, 14, h + 16, 0, 1, none);
            step(d1, 15, ho + 16, 0, 1, none);
            mbar_wait(inb, 0);
#pragma unroll
            for (int i = 0; i < 2; i++) {
                const uint4 u = lds128(hbuf + 16384 + i * 2048);
                const uint32_t p0[4] = {u.x, u.y, u.z, u.w};
#pragma unroll
                for (int j = 0; j < 4; j++) {
                    v[8 * i + 2 * j] = fmaf(0.5f, blo(p0[j]), blo(xr[4 * i + j]));
                    v[8 * i + 2 * j + 1] = fmaf(0.5f, bhi(p0[j]), bhi(xr[4 * i + j]));
                }
            }
            wg_wait<0>();
            pin(d1);
            rel(15);
            TS(3 + (ph & 2) * 10);
#pragma unroll
            for (int j = 0; j < 8; j++) {
                v[2 * j] = fmaf(0.5f, d1[4 * j] + d1[4 * j + 2], v[2 * j]);
                v[2 * j + 1] = fmaf(0.5f, d1[4 * j + 1] + d1[4 * j + 3], v[2 * j + 1]);
            }
#pragma unroll
            for (int i = 0; i < 15; i++) dwr[i] = 0;
            continue;
        }

        auto residual = [&](int n) {
            wg_wait<1>();
            rel(n);
            wg_wait<0>();
            pin(d0);
            rel(n + 1);
#pragma unroll
            for (int j = 0; j < 8; j++) {
                v[2 * j] = d0[4 * j] + d0[4 * j + 2] + blo(xr[j]);
                v[2 * j + 1] = d0[4 * j + 1] + d0[4 * j + 3] + bhi(xr[j]);
            }
        };

        if (ph == 2) {
            TS(39);
            sp(d0, 34, a, w, 0);
            acq(35);
            sp(d1, 35, a, w, 0);
            acq(36); acq(37);
            gather_peer();
            sp(d0, 36, a + 16, 0, 1);
            sp(d1, 37, a + 16, 0, 1);
            wg_wait<2>();
            rel(34);
            if (!(LATE & 1)) rel(35);
            acq(38);
            const float rs = trow < T_ ? 0.5f * rstd : 0.f;
            wg_wait<0>();
            pin(d0); pin(d1);
            if (!(LATE & 2)) { rel(36); rel(37); }
            TS(18);
            uint32_t pk[8];
#pragma unroll
            for (int j = 0; j < 8; j++) {
                const float u0 = (d0[4 * j] + d0[4 * j + 2]) * rs, u1 = (d0[4 * j + 1] + d0[4 * j + 3]) * rs;
                const float t0 = tanh_fast((d1[4 * j] + d1[4 * j + 2]) * rs), t1 = tanh_fast((d1[4 * j + 1] + d1[4 * j + 3]) * rs);
                pk[j] = pack2(fmaf(u0, t0, u0), fmaf(u1, t1, u1));
            }
            if (wq == 0 || wq == 3) {
                uint4* hp = &g_halo[((pair * 4 + tile) * 2 + (wq & 1)) * 64 + lane];
                st_data(hp, pk[0], pk[1], pk[2], pk[3]);
                st_data(hp + 32, pk[4], pk[5], pk[6], pk[7]);
            }
            const uint32_t gs = H + 16384 + w * GCH + wq * 1024;
            stsm4(gs + 1024 + foff, pk[0], pk[1], pk[2], pk[3]);
            stsm4(gs + 1024 + (foff ^ 64), pk[4], pk[5], pk[6], pk[7]);
            bar_sync(8 + w, 192);
            TS(26);
            uint32_t ca[8], cb[8];
            const int e = (wq & 1) * 4;
            const uint32_t lo = ((mir ^ e) * 144) ^ (lane * 4);
            const int dir = mir ? -1024 : 1024;
            const uint32_t gb = H + 16384 + w * GCH + (mir ? 3072 : 2048) + lo, sown_ = H + tile * HCH, so = sown_ + (mir ? 1024 : 2048) + lo;
            auto finish = [&](int i) {
                const uint32_t c = hadd2(ca[i], cb[i]);
                const float h0 = blo(c), h1 = bhi(c);
                sts32((so + (i >> 2) * dir) ^ ((i & 3) * 144), pack2(fmaf(h0, tanh_fast(h0), h0), fmaf(h1, tanh_fast(h1), h1)));
            };
#pragma unroll
            for (int k = 0; k < 26; k++) {
                if (k == 19) {
#pragma unroll
                    for (int i = 0; i < 4; i++) finish(i);
                    fence_async_smem();
                    bar_sync(2 + w, 128);
                    if (wq == 0) peer_copy(mapa(sown_ + 1024, r ^ 1), sown_ + 1024, 2048, mapa(bars + B_SR * 8, r ^ 1));
                    mbar_wait(bars + (B_HALO + 2 * w + (wq >> 1)) * 8, 0);
                    if (LATE & 1) rel(35);
                    if (LATE & 2) { rel(36); rel(37); }
                    TS(27);
                }
                const uint32_t g = lds32((gb + (((k + 1) & 4) ? ((k + 1) >> 3) + (wq & 1) : ((k + 1) >> 3)) * dir) ^ (((k + 1) & 7) * 144));
#pragma unroll
                for (int i = 0; i < 8; i++) {
                    const int tap = k - (i & 3) - 2 * (i & 4);
                    if (tap == 0) ca[i] = hmul2(g, dwr[0]);
                    else if (tap > 0 && tap < 8) ca[i] = hfma2(g, dwr[tap], ca[i]);
                    else if (tap == 8) cb[i] = hmul2(g, dwr[8]);
                    else if (tap > 8 && tap < 15) cb[i] = hfma2(g, dwr[tap], cb[i]);
                }
            }
#pragma unroll
            for (int i = 4; i < 8; i++) finish(i);
            fence_async_smem();
            bar_sync(12 + (warp >> 1), 64);
            if (wq == 0 || wq == 3) peer_copy(mapa(sown_ + wq * 1024, r ^ 1), sown_ + wq * 1024, 1024, mapa(bars + B_SR * 8, r ^ 1));
            bar_sync(10, 256);
            TS(19);
            auto frags = [&](int i, int half) {
                const uint32_t src = H + 2 * half * HCH + wq * 1024;
#pragma unroll
                for (int k = 0; k < 4; k++) ldsm4(src + (k >> 1) * HCH + (foff ^ ((k & 1) * 64)), a[i + 4 * k], a[i + 4 * k + 1], a[i + 4 * k + 2], a[i + 4 * k + 3]);
            };
            frags(0, r);
            sp(d0, 38, a, 0, 0);
            acq(39);
            mbar_wait(bars + B_SR * 8, 0);
            frags(16, r ^ 1);
            sp(d0, 39, a + 16, 0, 1);
            residual(38);
            TS(20);
            continue;
        }

        {
            TS(11);
            const uint32_t stg = H + warp * 2048;
            unsigned char* g = g_kvq + (size_t)((b * 4 + tile) * 1024 + trow) * 128 + lane * 16;
            auto put = [&](float (&d)[32], int i) {
                pin(d);
                uint32_t pk[8];
#pragma unroll
                for (int j = 0; j < 8; j++) pk[j] = pack2((d[4 * j] + d[4 * j + 2]) * rstd, (d[4 * j + 1] + d[4 * j + 3]) * rstd);
                if (i == 2) {
                    st_data(g + 2097152, pk[0], pk[1], pk[2], pk[3]);
                    st_data(g + 2097152 + 512, pk[4], pk[5], pk[6], pk[7]);
                    return;
                }
                stsm4(stg + i * 1024 + foff, pk[0], pk[1], pk[2], pk[3]);
                stsm4(stg + i * 1024 + (foff ^ 64), pk[4], pk[5], pk[6], pk[7]);
                __syncwarp();
                const uint4 u0 = lds128(stg + i * 1024 + lane * 16), u1 = lds128(stg + i * 1024 + 512 + lane * 16);
                stg128(g + i * 1048576, u0); stg128(g + i * 1048576 + 512, u1);
            };
            sp(d0, 16, a, w, 0);
            acq(17);
            sp(d1, 17, a, w, 0);
            gather_peer();
            acq(18);
            sp(d0, 18, a + 16, 0, 1);
            wg_wait<1>();
            rel(16); rel(17);
            acq(19);
            sp(d1, 19, a + 16, 0, 1);
            wg_wait<1>();
            rel(18);
            put(d0, 0);
            wg_wait<0>();
            rel(19);
            TS(37);
            put(d1, 1);
            bar_arrive(4, 288);
            TS(38);
            acq(20);
            sp(d0, 20, a, w, 0);
            acq(21);
            sp(d0, 21, a + 16, 0, 1);
            acq(22); acq(23);
            rel(22); rel(23);
            mbar_wait(bars + B_RST * 8, 0);
            wg_wait<0>();
            rel(20); rel(21);
            put(d0, 2);
            TS(12);
        }

        {
            constexpr float CS = 0.125f * 1.4426950408889634f;
            float sa[32], sb2[32], o[36];
            uint32_t pa[16], pb[16], q[16];
            float n0 = INFINITY, n1 = INFINITY;
            zero(o); zero(pa); zero(pb); zero(sb2);
            const uint32_t ones = sb + OFF_MISC + 2048;
            { const uint32_t c = w ? 0u : 0x3F803F80u; sts128(ones + tid * 16, c, c, c, c); }
            fence_async_smem();
            bar_sync(10, 256);
            const uint32_t vdesc = rdesc + ((((ones - rbase) >> 4) - 1) << 16);
            auto qk_issue = [&](float (&s)[32], uint32_t lo) {
                const uint64_t kd = mkdesc(lo);
                wg_fence();
#pragma unroll
                for (int k = 0; k < 4; k++) mma_qk(s, q[4 * k], q[4 * k + 1], q[4 * k + 2], q[4 * k + 3], kd + 2 * k, k != 0);
                wg_commit();
            };
            auto both_issue = [&](float (&s)[32], uint32_t klo, uint32_t (&pp)[16], uint32_t vlo) {
                const uint64_t kd = mkdesc(klo), vd = mkdesc(vlo);
                wg_fence();
#pragma unroll
                for (int k = 0; k < 4; k++) {
                    mma_pv(o, pp[4 * k], pp[4 * k + 1], pp[4 * k + 2], pp[4 * k + 3], vd - k * (128 * 65535));
                    mma_qk(s, q[4 * k], q[4 * k + 1], q[4 * k + 2], q[4 * k + 3], kd + 2 * k, k != 0);
                }
                wg_commit();
            };
            auto new_max = [&](float (&s)[32], int nj, float& x0, float& x1) {
                x0 = s[0]; x1 = s[2];
#pragma unroll
                for (int j = 0; j < nj; j++) {
                    x0 = fmaxf(x0, fmaxf(s[4 * j], s[4 * j + 1]));
                    x1 = fmaxf(x1, fmaxf(s[4 * j + 2], s[4 * j + 3]));
                }
                x0 = fmaxf(x0, __shfl_xor_sync(~0u, x0, 1)); x1 = fmaxf(x1, __shfl_xor_sync(~0u, x1, 1));
                x0 = fmaxf(x0, __shfl_xor_sync(~0u, x0, 2)); x1 = fmaxf(x1, __shfl_xor_sync(~0u, x1, 2));
                x0 = fminf(n0, fmaf(x0, -CS, -20.f)); x1 = fminf(n1, fmaf(x1, -CS, -20.f));
            };
            auto probs = [&](float (&s)[32], uint32_t (&pp)[16], bool ready, bool tail, auto wait) {
                uint32_t any = 0;
#pragma unroll
                for (int i = 0; i < 16; i++) {
                    pp[i] = pack2(ex2(fmaf(s[2 * i], CS, (i & 1) ? n1 : n0)), ex2(fmaf(s[2 * i + 1], CS, (i & 1) ? n1 : n0)));
                    any |= pp[i];
                }
                wg_wait<0>();
                pin(sa); pin(sb2); pin(o); pin(pa); pin(pb);
                if (__builtin_expect(__any_sync(~0u, (any & 0x40004000u) || !ready), 0)) {
                    wait();
                    if (__any_sync(~0u, any & 0x40004000u)) {
                        if (tail) {
#pragma unroll
                            for (int i = 20; i < 32; i++) s[i] = -INFINITY;
                        }
                        float x0, x1;
                        new_max(s, 8, x0, x1);
                        const float sc0 = ex2(x0 - n0), sc1 = ex2(x1 - n1);
                        n0 = x0; n1 = x1;
#pragma unroll
                        for (int j = 0; j < 9; j++) { o[4 * j] *= sc0; o[4 * j + 1] *= sc0; o[4 * j + 2] *= sc1; o[4 * j + 3] *= sc1; }
#pragma unroll
                        for (int i = 0; i < 16; i++)
                            pp[i] = pack2(ex2(fmaf(s[2 * i], CS, (i & 1) ? n1 : n0)), ex2(fmaf(s[2 * i + 1], CS, (i & 1) ? n1 : n0)));
                    }
                }
            };
            {
                uint4 u[4];
                const unsigned char* src = g_kvq + 2097152 + (size_t)(abh * 1024 + qt * 64 + wq * 16) * 128 + lane * 16;
                spin(QGATE);
                ld_data<512>(u, src);
#pragma unroll
                for (int k = 0; k < 2; k++) {
                    q[8 * k] = u[k].x; q[8 * k + 1] = u[k + 2].x; q[8 * k + 2] = u[k].y; q[8 * k + 3] = u[k + 2].y;
                    q[8 * k + 4] = u[k].z; q[8 * k + 5] = u[k + 2].z; q[8 * k + 6] = u[k].w; q[8 * k + 7] = u[k + 2].w;
                }
                pin(q);
            }
            TS(40);
            acq(24);
            TS(13);
            qk_issue(sa, rdesc + (24 % NSLOT) * (SLOT >> 4));
            wg_wait<0>();
            pin(sa);
            {
                float x0, x1;
                new_max(sa, NJ0, x0, x1);
                n0 = x0; n1 = x1;
            }
            bar_arrive(6, 384);
            uint32_t vd = vdesc - (SLOT >> 4) * 65535u, kd = rdesc, vb = fbar + 8, kb = fbar;
            uint32_t vlast = vdesc - 4 * (SLOT >> 4) * 65535u, klast = rdesc + 4 * (SLOT >> 4) + 512;
            uint32_t kprev = fbar + 32, vprev = bars + (B_SINK - (B_EMPTY - B_FULL)) * 8;
#pragma unroll 1
            for (int it = 0; it < 4; it++) {
                both_issue(sb2, klast, pb, vlast);
                probs(sa, pa, mbar_test(vb, it < 2) & mbar_test(kb, it < 3), false, [&]() { mbar_wait(vb, it < 2); mbar_wait(kb, it < 3); });
                TS(41 + it * 4);
                if (lane == 0) mbar_arrive(kprev + (B_EMPTY - B_FULL) * 8);
                if (lane == 0) mbar_arrive(vprev + (B_EMPTY - B_FULL) * 8);
                both_issue(sa, kd, pa, vd);
                const int dv = it == 0 ? 2 : (it == 1 ? -3 : 1);
                kprev = kb; vprev = vb; vlast = vd - 512 * 65535u; klast = kd + 512;
                vd -= dv * (SLOT >> 4) * 65535u; vb += dv * 8;
                kd += (it == 2 ? -3 : 2) * (SLOT >> 4); kb = it == 2 ? vb : kb + 16;
                probs(sb2, pb, true, it == 3 && w == 1, []() {});
                TS(43 + it * 4);
            }
            wg_fence();
#pragma unroll
            for (int k = 0; k < 4; k++)
                mma_pv(o, pb[4 * k], pb[4 * k + 1], pb[4 * k + 2], pb[4 * k + 3], mkdesc(vlast - k * (128 * 65535) + (k > 1 ? w * ((k - 1) << 22) : 0)));
            wg_commit();
            const int row = wq * 16 + (lane >> 2);
            const uint32_t ml = sb + OFF_MISC;
            mbar_wait(bars + (B_RST + 1) * 8, 0);
            wg_wait<0>();
            pin(o); pin(pb); pin(sa); pin(sb2);
            if (!(LATE & 4)) rel(31);
            const float l0 = o[32], l1 = o[34];
            if (c4 == 0) { sts64f(ml + w * 512 + row * 8, n0, l0); sts64f(ml + w * 512 + row * 8 + 64, n1, l1); }
            TS(14);
            float mine[16];
#pragma unroll
            for (int j = 0; j < 4; j++) {
                if (w == 0) sts128f(H + j * 2048 + wt * 16, o[16 + 4 * j], o[17 + 4 * j], o[18 + 4 * j], o[19 + 4 * j]);
                else sts128f(H + 8192 + j * 2048 + wt * 16, o[4 * j], o[4 * j + 1], o[4 * j + 2], o[4 * j + 3]);
            }
#pragma unroll
            for (int i = 0; i < 16; i++) mine[i] = w == 0 ? o[i] : o[16 + i];
            bar_sync(10, 256);
            const float2 u0 = lds64f(ml + (w ^ 1) * 512 + row * 8), u1 = lds64f(ml + (w ^ 1) * 512 + row * 8 + 64);
            const float x0 = fminf(n0, u0.x), x1 = fminf(n1, u1.x);
            float a0 = ex2(x0 - n0), b0 = ex2(x0 - u0.x), a1 = ex2(x1 - n1), b1 = ex2(x1 - u1.x);
            const float i0 = __fdividef(1.f, fmaf(a0, l0, b0 * u0.y)), i1 = __fdividef(1.f, fmaf(a1, l1, b1 * u1.y));
            a0 *= i0; b0 *= i0; a1 *= i1; b1 *= i1;
            uint32_t pk[8];
#pragma unroll
            for (int j = 0; j < 4; j++) {
                const float4 v = lds128f(H + (w ^ 1) * 8192 + j * 2048 + wt * 16);
                pk[2 * j] = pack2(fmaf(a0, mine[4 * j], b0 * v.x), fmaf(a0, mine[4 * j + 1], b0 * v.y));
                pk[2 * j + 1] = pack2(fmaf(a1, mine[4 * j + 2], b1 * v.z), fmaf(a1, mine[4 * j + 3], b1 * v.w));
            }
            unsigned char* dst = g_o + (size_t)(b * 128 + qt * 8 + 2 * wq) * 4096 + ah * 1024 + w * 512 + lane * 16;
            st_data(dst, pk[0], pk[2], pk[4], pk[6]);
            st_data(dst + 4096, pk[1], pk[3], pk[5], pk[7]);
            if (tid == 0) asm volatile("red.relaxed.gpu.global.add.u32 [%0], 1;" ::"l"(&g_epoch[blockIdx.x * FS]) : "memory");
            TS(15);
        }

        {
            const uint32_t* dp = reinterpret_cast<const uint32_t*>(p.dw + (mir ? 14 * 256 : 0) + tile * 64) + lane;
#pragma unroll
            for (int i = 0; i < 15; i++) asm volatile("ld.global.nc.b32 %0, [%1];" : "=r"(dwr[i]) : "l"(dp + i * (mir ? -128 : 128)));
            acq(32); acq(33); acq(34);
            uint4 u[8];
            ld_data<512>(u, g_o + (size_t)(b * 128 + pt * 4 + wq) * 4096 + lane * 16);
#pragma unroll
            for (int i = 0; i < 8; i++) { a[4 * i] = u[i].x; a[4 * i + 1] = u[i].y; a[4 * i + 2] = u[i].z; a[4 * i + 3] = u[i].w; }
            if (LATE & 4) rel(31);
            TS(16);
            sp(d0, 32, a, 0, 0);
            sp(d0, 33, a + 16, 0, 1);
#pragma unroll
            for (int i = 0; i < 15; i++) dwr[i] = hmul2(dwr[i], 0x3F003F00u);
            residual(32);
            TS(17);
        }
    }

    cluster_arrive();
    TS(24);
    {
        const float rstd = rsq(fmaxf(fmaf(-mean, mean, msq), 0.f) + 1e-5f), nb = -mean * rstd;
#pragma unroll
        for (int j = 0; j < 8; j++) xr[j] = pack2(fmaf(v[2 * j], rstd, nb), fmaf(v[2 * j + 1], rstd, nb));
        const uint32_t stg = P + 16384 + warp * 1024;
        stsm4(stg + foff, xr[0], xr[1], xr[2], xr[3]);
        stsm4(stg + (foff ^ 64), xr[4], xr[5], xr[6], xr[7]);
        __syncwarp();
        const uint32_t src = stg + (lane >> 3) * 128 + (((lane & 7) ^ (lane >> 3)) << 4);
        const uint4 u0 = lds128(src), u1 = lds128((src + 512) ^ 64);
        __nv_bfloat16* dst = p.out + (size_t)(b * T_ + trow + (lane >> 3)) * 256 + tile * 64 + (lane & 7) * 8;
        if (trow < T_) { stg128(dst, u0); stg128(dst + 4 * 256, u1); }
    }
    TS(25);
    TG(31);
    TSDUMP();
    cluster_wait();
}

typedef CUresult (*EncodeFn)(CUtensorMap*, CUtensorMapDataType, cuuint32_t, void*, const cuuint64_t*, const cuuint64_t*,
                             const cuuint32_t*, const cuuint32_t*, CUtensorMapInterleave, CUtensorMapSwizzle,
                             CUtensorMapL2promotion, CUtensorMapFloatOOBfill);

}

extern "C" void kernel_launch(void* const* d_in, const int* in_sizes, int n_in, void* d_out, int out_size) {
    static EncodeFn encode = nullptr;
    if (!encode) {
        void* fn = nullptr;
        cudaDriverEntryPointQueryResult qr;
        cudaGetDriverEntryPoint("cuTensorMapEncodeTiled", &fn, cudaEnableDefault, &qr);
        encode = (EncodeFn)fn;
        cudaFuncSetAttribute(conformer_kernel, cudaFuncAttributeMaxDynamicSharedMemorySize, SMEM_LAUNCH);
    }
    Params p;
    const cuuint32_t ones[5] = {1, 1, 1, 1, 1};
    const int idx[8] = {1, 2, 3, 4, 5, 7, 8, 9};
    const int rows[8] = {256, 1024, 256, 256, 256, 256, 256, 1024};
    const int cols[8] = {1024, 256, 768, 256, 512, 256, 1024, 256};
    for (int i = 0; i < 8; i++) {
        const cuuint64_t pitch = (cuuint64_t)cols[i] * 2;
        const cuuint64_t dims[5] = {(cuuint64_t)cols[i], i ? 2u : 4u, i ? 2u : 4u, i ? 4u : 2u, (cuuint64_t)rows[i] / (i ? 16 : 32)};
        const cuuint64_t strides[4] = {pitch, pitch * 8, pitch * (i ? 2 : 4), pitch * (i ? 16 : 32)};
        const cuuint32_t box[5] = {64, i ? 2u : 4u, i ? 2u : 4u, i ? 4u : 2u, i ? 8u : 4u};
        encode(&p.tm[i], CU_TENSOR_MAP_DATA_TYPE_BFLOAT16, 5, d_in[idx[i]], dims, strides, box, ones, CU_TENSOR_MAP_INTERLEAVE_NONE,
               CU_TENSOR_MAP_SWIZZLE_128B, CU_TENSOR_MAP_L2_PROMOTION_L2_128B, CU_TENSOR_MAP_FLOAT_OOB_FILL_NONE);
        p.w[i] = (const char*)d_in[idx[i]];
    }
    {
        void* kv = nullptr;
        cudaGetSymbolAddress(&kv, g_kvq);
        const cuuint64_t dims[2] = {64, 16384};
        const cuuint64_t strides[1] = {128};
        const cuuint32_t box[2] = {64, 128};
        encode(&p.tm[8], CU_TENSOR_MAP_DATA_TYPE_BFLOAT16, 2, kv, dims, strides, box, ones, CU_TENSOR_MAP_INTERLEAVE_NONE,
               CU_TENSOR_MAP_SWIZZLE_NONE, CU_TENSOR_MAP_L2_PROMOTION_L2_128B, CU_TENSOR_MAP_FLOAT_OOB_FILL_NONE);
    }
    p.x = (const __nv_bfloat16*)d_in[0];
    p.dw = (const __nv_bfloat16*)d_in[6];
    p.out = (__nv_bfloat16*)d_out;
    p.zero = 0;
    conformer_kernel<<<NCTA, NTHREADS, SMEM_LAUNCH>>>(p);
}
```

```cpp
#include <cuda_runtime.h>
#include <cuda_bf16.h>
#include <cuda.h>
#include <stdint.h>

namespace {

constexpr int T_ = 1000;
constexpr int NCTA = 128;
constexpr int NTHREADS = 512;
constexpr int NSLOT = 5;
constexpr int SLOT = 16384;
constexpr int NLOADS = 56;

constexpr uint32_t OFF_RING = 0;
constexpr uint32_t OFF_P = 163840;
constexpr uint32_t OFF_H = 188416;
constexpr uint32_t OFF_MISC = 221184;
constexpr uint32_t OFF_BARS = 229888;
constexpr uint32_t SMEM_BYTES = 230400;
constexpr uint32_t GCH = 6144;
constexpr uint32_t HCH = 4096;

constexpr int B_FULL = 0, B_EMPTY = 10, B_XA = 20  , B_XB = 25  , B_INB = 29  , B_SR = 33,
              B_RST = 34  , B_RDY = 36  , B_SINK = 42, B_HALO = 43  , NBARS = 47;

#define KD2 300u
#define QGATE 500u
#define BACKOFF 0u
#define KFS 8
#define KDELAY 300u
#define NJ0 2
#define HDELAY 200u
#define LATE 2
#define SND 0
#define PF0 1
#define NFIRST 2
#define QEARLY 0
#define TURN 0x200
#define EAGER 0x0155
constexpr int FS = 8;

struct Params {
    CUtensorMap tm[9];
    const char* w[8];
    const __nv_bfloat16* x;
    const __nv_bfloat16* dw;
    __nv_bfloat16* out;
    uint32_t zero;
};

__device__ __align__(1024) unsigned char g_kvq[3 * 8 * 1024 * 128];
__device__ __align__(1024) unsigned char g_o[2 * 128 * 4096];
__device__ uint4 g_halo[64 * 4 * 2 * 64];
__device__ __align__(128) uint32_t g_flag_kv[2 * 8 * 32 * KFS];
__device__ uint32_t g_reset[4 * 32];
__device__ uint32_t g_epoch[NCTA * FS];

#define TS(i) do { } while (0)
#define TSW(i) do { } while (0)
#define TG(i) do { } while (0)
#define TSINIT() do { } while (0)
#define TSDUMP() do { } while (0)
constexpr uint32_t SMEM_LAUNCH = SMEM_BYTES;

__device__ __forceinline__ uint32_t smem_u32(const void* p) { return (uint32_t)__cvta_generic_to_shared(p); }
__device__ __forceinline__ void mbar_init(uint32_t b, uint32_t c) { asm volatile("mbarrier.init.shared::cta.b64 [%0], %1;" ::"r"(b), "r"(c) : "memory"); }
__device__ __forceinline__ void mbar_arrive(uint32_t b) { asm volatile("mbarrier.arrive.shared::cta.b64 _, [%0];" ::"r"(b) : "memory"); }
__device__ __forceinline__ void mbar_arrive_tx(uint32_t b, uint32_t tx) { asm volatile("mbarrier.arrive.expect_tx.shared::cta.b64 _, [%0], %1;" ::"r"(b), "r"(tx) : "memory"); }
__device__ __forceinline__ void mbar_wait(uint32_t b, uint32_t ph) {
    asm volatile("{\n.reg .pred p, q;\n.reg .u32 c;\nmov.u32 c, 0;\n"
                 "MW_LOOP:\n.pragma \"nounroll\";\n"
                 "mbarrier.try_wait.parity.shared::cta.b64 p, [%0], %1;\n"
                 "add.u32 c, c, 1;\nsetp.lt.u32 q, c, 65536;\nnot.pred p, p;\nand.pred p, p, q;\n@p bra MW_LOOP;\n}"
                 ::"r"(b), "r"(ph) : "memory");
}
__device__ __forceinline__ bool mbar_test(uint32_t b, uint32_t ph) {
    uint32_t ok;
    asm volatile("{\n.reg .pred p;\nmbarrier.test_wait.parity.shared::cta.b64 p, [%1], %2;\nselp.u32 %0, 1, 0, p;\n}" : "=r"(ok) : "r"(b), "r"(ph) : "memory");
    return ok;
}
__device__ __forceinline__ uint32_t mapa(uint32_t a, uint32_t r) { uint32_t o; asm("mapa.shared::cluster.u32 %0, %1, %2;" : "=r"(o) : "r"(a), "r"(r)); return o; }
__device__ __forceinline__ void fence_async_smem() { asm volatile("fence.proxy.async.shared::cta;" ::: "memory"); }
__device__ __forceinline__ void fence_async_global() { asm volatile("fence.proxy.async.global;" ::: "memory"); }
__device__ __forceinline__ void bar_sync(int id, int n) { asm volatile("bar.sync %0, %1;" ::"r"(id), "r"(n) : "memory"); }
__device__ __forceinline__ void bar_arrive(int id, int n) { asm volatile("bar.arrive %0, %1;" ::"r"(id), "r"(n) : "memory"); }
__device__ __forceinline__ void cluster_arrive() { asm volatile("barrier.cluster.arrive.relaxed.aligned;" ::: "memory"); }
__device__ __forceinline__ void cluster_wait() { asm volatile("barrier.cluster.wait.aligned;" ::: "memory"); }

__device__ __forceinline__ void ring_load(uint32_t dst, const CUtensorMap* tm, int col, int row16, uint32_t bar) {
    asm volatile("{\n.reg .pred p;\nelect.sync _|p, 0xffffffff;\n"
                 "@p mbarrier.arrive.expect_tx.shared::cta.b64 _, [%2], 16384;\n"
                 "@p cp.async.bulk.tensor.5d.shared::cluster.global.mbarrier::complete_tx::bytes [%0], [%1, {%3, 0, 0, 0, %4}], [%2];\n}"
                 ::"r"(dst), "l"(tm), "r"(bar), "r"(col), "r"(row16) : "memory");
}
__device__ __forceinline__ void ring_load_both(uint32_t dst, const CUtensorMap* tm, int c1, uint32_t bar) {
    asm volatile("{\n.reg .pred p;\nelect.sync _|p, 0xffffffff;\n"
                 "@p cp.async.bulk.tensor.2d.shared::cluster.global.mbarrier::complete_tx::bytes.multicast::cluster [%0], [%1, {0, %3}], [%2], %4;\n}"
                 ::"r"(dst), "l"(tm), "r"(bar), "r"(c1), "h"((uint16_t)3) : "memory");
}
__device__ __forceinline__ void mbar_arrive_peer(uint32_t b) { asm volatile("mbarrier.arrive.relaxed.cluster.shared::cluster.b64 _, [%0];" ::"r"(b) : "memory"); }
__device__ __forceinline__ void prefetch_l2(const void* src, uint32_t bytes) {
    asm volatile("cp.async.bulk.prefetch.L2.global [%0], %1;" ::"l"(src), "r"(bytes) : "memory");
}
__device__ __forceinline__ void peer_copy(uint32_t dst, uint32_t src, uint32_t bytes, uint32_t rbar) {
    asm volatile("{\n.reg .pred p;\nelect.sync _|p, 0xffffffff;\n"
                 "@p cp.async.bulk.shared::cluster.shared::cta.mbarrier::complete_tx::bytes [%0], [%1], %2, [%3];\n}"
                 ::"r"(dst), "r"(src), "r"(bytes), "r"(rbar) : "memory");
}
__device__ __forceinline__ void st_async4(uint32_t dst, uint32_t a, uint32_t b, uint32_t c, uint32_t d, uint32_t bar) {
    asm volatile("st.async.shared::cluster.mbarrier::complete_tx::bytes.v4.b32 [%0], {%1,%2,%3,%4}, [%5];" ::"r"(dst), "r"(a), "r"(b), "r"(c), "r"(d), "r"(bar) : "memory");
}
__device__ __forceinline__ void put_sums(uint32_t dst, uint32_t rdst, float a, float b, uint32_t rbar, bool on) {
    asm volatile("{\n.reg .pred p;\nsetp.ne.u32 p, %5, 0;\n"
                 "@p st.async.shared::cluster.mbarrier::complete_tx::bytes.v2.f32 [%1], {%2,%3}, [%4];\n"
                 "@p st.shared.v2.f32 [%0], {%2,%3};\n}" ::"r"(dst), "r"(rdst), "f"(a), "f"(b), "r"(rbar), "r"((uint32_t)on) : "memory");
}
__device__ __forceinline__ void stsm4(uint32_t a, uint32_t r0, uint32_t r1, uint32_t r2, uint32_t r3) {
    asm volatile("stmatrix.sync.aligned.m8n8.x4.shared.b16 [%0], {%1,%2,%3,%4};" ::"r"(a), "r"(r0), "r"(r1), "r"(r2), "r"(r3) : "memory");
}
__device__ __forceinline__ void ldsm4(uint32_t a, uint32_t& r0, uint32_t& r1, uint32_t& r2, uint32_t& r3) {
    asm volatile("ldmatrix.sync.aligned.m8n8.x4.shared.b16 {%0,%1,%2,%3}, [%4];" : "=r"(r0), "=r"(r1), "=r"(r2), "=r"(r3) : "r"(a) : "memory");
}
__device__ __forceinline__ uint4 lds128(uint32_t a) { uint4 v; asm volatile("ld.shared.v4.b32 {%0,%1,%2,%3}, [%4];" : "=r"(v.x), "=r"(v.y), "=r"(v.z), "=r"(v.w) : "r"(a) : "memory"); return v; }
__device__ __forceinline__ float4 lds128f(uint32_t a) { float4 v; asm volatile("ld.shared.v4.f32 {%0,%1,%2,%3}, [%4];" : "=f"(v.x), "=f"(v.y), "=f"(v.z), "=f"(v.w) : "r"(a) : "memory"); return v; }
__device__ __forceinline__ float2 lds64f(uint32_t a) { float2 v; asm volatile("ld.shared.v2.f32 {%0,%1}, [%2];" : "=f"(v.x), "=f"(v.y) : "r"(a) : "memory"); return v; }
__device__ __forceinline__ uint32_t lds32(uint32_t a) { uint32_t v; asm volatile("ld.shared.b32 %0, [%1];" : "=r"(v) : "r"(a) : "memory"); return v; }
__device__ __forceinline__ void sts128(uint32_t a, uint32_t x, uint32_t y, uint32_t z, uint32_t w) { asm volatile("st.shared.v4.b32 [%0], {%1,%2,%3,%4};" ::"r"(a), "r"(x), "r"(y), "r"(z), "r"(w) : "memory"); }
__device__ __forceinline__ void sts128f(uint32_t a, float x, float y, float z, float w) { asm volatile("st.shared.v4.f32 [%0], {%1,%2,%3,%4};" ::"r"(a), "f"(x), "f"(y), "f"(z), "f"(w) : "memory"); }
__device__ __forceinline__ void sts64f(uint32_t a, float x, float y) { asm volatile("st.shared.v2.f32 [%0], {%1,%2};" ::"r"(a), "f"(x), "f"(y) : "memory"); }
__device__ __forceinline__ void sts32(uint32_t a, uint32_t x) { asm volatile("st.shared.b32 [%0], %1;" ::"r"(a), "r"(x) : "memory"); }
__device__ __forceinline__ void stg128(void* p, uint4 v) { asm volatile("st.global.v4.b32 [%0], {%1,%2,%3,%4};" ::"l"(p), "r"(v.x), "r"(v.y), "r"(v.z), "r"(v.w) : "memory"); }

__device__ __forceinline__ uint32_t pack2(float lo, float hi) { uint32_t r; asm("cvt.rn.bf16x2.f32 %0, %1, %2;" : "=r"(r) : "f"(hi), "f"(lo)); return r; }
__device__ __forceinline__ float blo(uint32_t v) { return __uint_as_float(v << 16); }
__device__ __forceinline__ float bhi(uint32_t v) { return __uint_as_float(v & 0xffff0000u); }
__device__ __forceinline__ uint32_t hmul2(uint32_t a, uint32_t b) { uint32_t r; asm("mul.rn.bf16x2 %0, %1, %2;" : "=r"(r) : "r"(a), "r"(b)); return r; }
__device__ __forceinline__ uint32_t hadd2(uint32_t a, uint32_t b) { uint32_t r; asm("add.rn.bf16x2 %0, %1, %2;" : "=r"(r) : "r"(a), "r"(b)); return r; }
__device__ __forceinline__ uint32_t hsub2(uint32_t a, uint32_t b) { uint32_t r; asm("sub.rn.bf16x2 %0, %1, %2;" : "=r"(r) : "r"(a), "r"(b)); return r; }
__device__ __forceinline__ uint32_t hfma2(uint32_t a, uint32_t b, uint32_t c) { uint32_t r; asm("fma.rn.bf16x2 %0, %1, %2, %3;" : "=r"(r) : "r"(a), "r"(b), "r"(c)); return r; }
__device__ __forceinline__ float tanh_fast(float x) { float r; asm("tanh.approx.f32 %0, %1;" : "=f"(r) : "f"(x)); return r; }
__device__ __forceinline__ float rsq(float x) { float r; asm("rsqrt.approx.ftz.f32 %0, %1;" : "=f"(r) : "f"(x)); return r; }
__device__ __forceinline__ float ex2(float x) { float r; asm("ex2.approx.ftz.f32 %0, %1;" : "=f"(r) : "f"(x)); return r; }

__device__ __forceinline__ uint32_t ld_relaxed(const uint32_t* p) {
    uint32_t v;
    asm volatile("ld.relaxed.gpu.global.u32 %0, [%1];" : "=r"(v) : "l"(p) : "memory");
    return v;
}
__device__ __forceinline__ uint32_t clock32() { uint32_t c; asm volatile("mov.u32 %0, %%clock;" : "=r"(c)::"memory"); return c; }
__device__ __forceinline__ void spin(uint32_t clks) {
    const uint32_t t0 = clock32();
    while (clock32() - t0 < clks) {}
}
__device__ __forceinline__ void flag_wait(const uint32_t* p, uint32_t e, bool mine) {
#pragma unroll 1
    for (int i = 0; i < (1 << 19); i++) {
        if (mine) mine = ld_relaxed(p) != e;
        if (!__any_sync(~0u, mine)) break;
        if (BACKOFF) spin(BACKOFF);
    }
    asm volatile("fence.acquire.gpu;" ::: "memory");
    fence_async_global();
}
__device__ __forceinline__ void st_data(void* p, uint32_t x, uint32_t y, uint32_t z, uint32_t w) {
    asm volatile("st.relaxed.gpu.global.v4.b32 [%0], {%1,%2,%3,%4};" ::"l"(p), "r"(x), "r"(y), "r"(z), "r"(w) : "memory");
}
template <int STRIDE, int N>
__device__ __forceinline__ void ld_data(uint4 (&v)[N], const unsigned char* p) {
    int it = 0;
    bool again;
#pragma unroll 1
    do {
        uint32_t m = 0;
#pragma unroll
        for (int i = 0; i < N; i++)
            asm volatile("ld.relaxed.gpu.global.v4.b32 {%0,%1,%2,%3}, [%4];" : "=r"(v[i].x), "=r"(v[i].y), "=r"(v[i].z), "=r"(v[i].w) : "l"(p + i * STRIDE) : "memory");
#pragma unroll
        for (int i = 0; i < N; i++) m = __vimax3_u32(__vimax3_u32(v[i].x, v[i].y, v[i].z), v[i].w, m);
        again = __any_sync(~0u, m == ~0u) && ++it < (1 << 16);
    } while (again);
}
__device__ __forceinline__ uint32_t ld_epoch() { return ld_relaxed(&g_epoch[blockIdx.x * FS]) + 1; }
__device__ __forceinline__ void flag_set(uint32_t* p, uint32_t e) { asm volatile("st.release.gpu.global.u32 [%0], %1;" ::"l"(p), "r"(e) : "memory"); }

__device__ __forceinline__ uint32_t desc_lo(uint32_t addr) { return ((addr & 0x3FFFF) >> 4) | 0x10000u; }
__device__ __forceinline__ uint64_t mkdesc(uint32_t lo) { return (uint64_t)lo | (0x40000040ull << 32); }
__device__ __forceinline__ void wg_fence() { asm volatile("wgmma.fence.sync.aligned;" ::: "memory"); }
__device__ __forceinline__ void wg_commit() { asm volatile("wgmma.commit_group.sync.aligned;" ::: "memory"); }
template <int N> __device__ __forceinline__ void wg_wait() { asm volatile("wgmma.wait_group.sync.aligned %0;" ::"n"(N) : "memory"); }
template <int N> __device__ __forceinline__ void pin(float (&d)[N]) {
#pragma unroll
    for (int i = 0; i < N; i++) asm volatile("" : "+f"(d[i])::"memory");
}
template <int N> __device__ __forceinline__ void pin(uint32_t (&d)[N]) {
#pragma unroll
    for (int i = 0; i < N; i++) asm volatile("" : "+r"(d[i])::"memory");
}

template <typename Tp, int N> __device__ __forceinline__ void zero(Tp (&d)[N]) {
#pragma unroll
    for (int i = 0; i < N; i++) d[i] = 0;
    pin(d);
}

#define F4(d, i) "+f"(d[i]), "+f"(d[i + 1]), "+f"(d[i + 2]), "+f"(d[i + 3])
#define F16(d, i) F4(d, i), F4(d, i + 4), F4(d, i + 8), F4(d, i + 12)

__device__ __forceinline__ void mma16(float (&d)[4], const uint32_t* a, uint32_t b0, uint32_t b1) {
    asm("mma.sync.aligned.m16n8k16.row.col.f32.bf16.bf16.f32 {%0,%1,%2,%3}, {%4,%5,%6,%7}, {%8,%9}, {%0,%1,%2,%3};"
        : F4(d, 0) : "r"(a[0]), "r"(a[1]), "r"(a[2]), "r"(a[3]), "r"(b0), "r"(b1));
}
template <int N>
__device__ __forceinline__ float row_sum(const uint32_t* x, uint32_t ones = 0x3F803F80u) {
    float c[4] = {};
#pragma unroll
    for (int i = 0; i < N; i += 4) mma16(c, x + i, ones, ones);
    return c[0] + c[2];
}
template <int N>
__device__ __forceinline__ float row_sumsq(const uint32_t* x, int lane) {
    float c0[4] = {}, c1[4] = {};
#pragma unroll
    for (int i = 0; i < N; i += 4) {
        mma16(c0, x + i, x[i], x[i + 2]);
        mma16(c1, x + i, x[i + 1], x[i + 3]);
    }
    return (lane & 4) ? c0[1] + c1[3] : c0[0] + c1[2];
}
__device__ __forceinline__ void mma_sp(float (&d)[32], const uint32_t* a, uint64_t b, uint32_t meta, int acc) {
    asm volatile("{.reg .pred p; setp.ne.b32 p, %38, 0;\n"
                 "wgmma.mma_async.sp.sync.aligned.m64n64k32.f32.bf16.bf16 {%0,%1,%2,%3,%4,%5,%6,%7,%8,%9,%10,%11,%12,%13,%14,%15,%16,%17,%18,%19,%20,%21,%22,%23,%24,%25,%26,%27,%28,%29,%30,%31}, "
                 "{%32,%33,%34,%35}, %36, %37, 0, p, 1, 1, 1;}\n"
                 : F16(d, 0), F16(d, 16) : "r"(a[0]), "r"(a[1]), "r"(a[2]), "r"(a[3]), "l"(b), "r"(meta), "r"(acc));
}
__device__ __forceinline__ void mma_qk(float (&d)[32], uint32_t a0, uint32_t a1, uint32_t a2, uint32_t a3, uint64_t b, int acc) {
    asm volatile("{.reg .pred p; setp.ne.b32 p, %37, 0;\n"
                 "wgmma.mma_async.sync.aligned.m64n64k16.f32.bf16.bf16 {%0,%1,%2,%3,%4,%5,%6,%7,%8,%9,%10,%11,%12,%13,%14,%15,%16,%17,%18,%19,%20,%21,%22,%23,%24,%25,%26,%27,%28,%29,%30,%31}, "
                 "{%32,%33,%34,%35}, %36, p, 1, 1, 0;}\n"
                 : F16(d, 0), F16(d, 16) : "r"(a0), "r"(a1), "r"(a2), "r"(a3), "l"(b), "r"(acc));
}
__device__ __forceinline__ void mma_pv(float (&d)[36], uint32_t a0, uint32_t a1, uint32_t a2, uint32_t a3, uint64_t b) {
    asm volatile("wgmma.mma_async.sync.aligned.m64n72k16.f32.bf16.bf16 {%0,%1,%2,%3,%4,%5,%6,%7,%8,%9,%10,%11,%12,%13,%14,%15,%16,%17,%18,%19,%20,%21,%22,%23,%24,%25,%26,%27,%28,%29,%30,%31,%32,%33,%34,%35}, "
                 "{%36,%37,%38,%39}, %40, 1, 1, 1, 1;\n"
                 : F16(d, 0), F16(d, 16), F4(d, 32) : "r"(a0), "r"(a1), "r"(a2), "r"(a3), "l"(b));
}

__device__ __forceinline__ uint32_t load_code(int n, int r, int w) {
    const int tile = 2 * r + w;
    int m, col, row;
    if (n < 16 || n >= 40) {
        const int k = n < 16 ? n : n - 40;
        m = n < 16 ? 0 : 6;
        if (k < 8) { col = 4 * tile + (k >> 1); row = n < 16 ? (k & 1) : (k & 1) ^ r; }
        else { m++; col = k < 12 ? tile ^ 2 : tile; row = 2 * (tile ^ (k & 1)) + ((k >> 1) & 1); }
    } else if (n < 32) {
        const int k = n - 16;
        m = 2;
        col = tile + (k < 2 ? 4 : (k < 4 ? 0 : 8)); row = (k & 1) ^ r;
    } else if (n < 34) { m = 3; col = tile; row = n - 32; }
    else if (n < 38) { const int k = n - 34; m = 4; col = tile + 4 * (k & 1); row = (k >> 1) ^ r; }
    else { m = 5; col = tile; row = (n & 1) ^ r; }
    return m | (col << 4) | (row << (m ? 11 : 10));
}

__global__ void __cluster_dims__(2, 1, 1) __launch_bounds__(NTHREADS, 1)
conformer_kernel(const __grid_constant__ Params p) {
    extern __shared__ __align__(1024) unsigned char smem_raw[];
    const uint32_t sb = smem_u32(smem_raw);
    const uint32_t bars = sb + OFF_BARS;
    const int tid = threadIdx.x;
    const int lane = tid & 31;
    const int warp = __shfl_sync(~0u, tid >> 5, 0);
    const int r = blockIdx.x & 1;
    const int pair = blockIdx.x >> 1;
    const int b = pair >> 5, pt = pair & 31;
    const int ah = pt >> 3, qt = (pt & 7) * 2 + r;
    const int abh = b * 4 + ah;

    TG(30);
    TSINIT();
    TS(0);
    const uint32_t P = sb + OFF_P, H = sb + OFF_H;
    if (warp == 11) {
        if (lane == 0) {
#pragma unroll
            for (int i = 0; i < 2 * NSLOT; i++) mbar_init(bars + (B_FULL + i) * 8, 1);
            asm volatile("fence.mbarrier_init.release.cluster;" ::: "memory");
            fence_async_smem();
        }
        __syncwarp();
#pragma unroll
        for (int i = 0; i < 2 * NFIRST; i++)
            ring_load(sb + OFF_RING + ((i & 1) * NSLOT + (i >> 1)) * SLOT, &p.tm[0], 64 * (8 * r + 4 * (i & 1) + (i >> 2)), 4 * ((i >> 1) & 1),
                      bars + (B_FULL + (i & 1) * NSLOT + (i >> 1)) * 8);
        bar_arrive(13, 96);
        cluster_arrive();
    }

    if (warp >= 8) {
        asm volatile("setmaxnreg.dec.sync.aligned.u32 48;");
        if (warp >= 12) {
            cluster_arrive();
            cluster_wait();
            const int ut = tid & 127;
            const uint32_t target = ld_epoch() * 64;
            auto reset_done = [&](int k) {
                bar_sync(11, 128);
                if (ut == 0) {
                    asm volatile("red.release.gpu.global.add.u32 [%0], 1;" ::"l"(&g_reset[(2 * b + k) * 32]) : "memory");
#pragma unroll 1
                    for (int i = 0; i < (1 << 20) && ld_relaxed(&g_reset[(2 * b + k) * 32]) != target; i++) __nanosleep(100);
                    asm volatile("fence.acquire.gpu;" ::: "memory");
                    mbar_arrive(bars + (B_RST + k) * 8);
                }
                __syncwarp();
                TS(13 + k);
            };
#pragma unroll
            for (int i = 0; i < 4; i++)
                st_data(g_kvq + 2097152 + (size_t)((b * 4 + 2 * r + (i >> 1)) * 1024 + pt * 32) * 128 + (i & 1) * 2048 + ut * 16, ~0u, ~0u, ~0u, ~0u);
            reset_done(0);
            bar_sync(6, 384);
#pragma unroll
            for (int i = 0; i < 4; i++) {
                st_data(g_o + (size_t)(b * 128 + qt * 8 + 2 * i + (ut >> 6)) * 4096 + ah * 1024 + (ut & 63) * 16, ~0u, ~0u, ~0u, ~0u);
                if (i < 2) st_data(&g_halo[(pair * 4 + 2 * r + i) * 128 + ut], ~0u, ~0u, ~0u, ~0u);
            }
            reset_done(1);
            const int side = warp & 1, wg = (warp >> 1) & 1, np = side ? pt + 1 : pt - 1;
            const unsigned char* src = reinterpret_cast<const unsigned char*>(&g_halo[(((b * 32 + np) * 4 + 2 * r + wg) * 2 + (side ^ 1)) * 64 + lane]);
            const uint32_t dst = H + 16384 + wg * GCH + side * 5120 + (lane & 7) * 128 + (((lane >> 3) ^ (lane & 7)) << 4);
            uint4 hv[2] = {make_uint4(0, 0, 0, 0), make_uint4(0, 0, 0, 0)};
            bar_sync(8 + wg, 192);
            if (np >= 0 && np < 32) {
                spin(HDELAY);
                ld_data<512>(hv, src);
            }
            stsm4(dst, hv[0].x, hv[0].y, hv[0].z, hv[0].w);
            stsm4(dst ^ 64, hv[1].x, hv[1].y, hv[1].z, hv[1].w);
            __syncwarp();
            if (lane == 0) mbar_arrive(bars + (B_HALO + (warp & 3)) * 8);
            TS(4);
        } else if (warp < 10) {
            const int w = warp - 8;
            const uint32_t ring = sb + OFF_RING + w * NSLOT * SLOT;
            const uint32_t full = bars + (B_FULL + w * NSLOT) * 8;
            cluster_arrive();
            bar_sync(13, 96);
            TS(1);
#pragma unroll
            for (int n = NFIRST; n < NSLOT; n++) {
                if (n == NFIRST + 1) bar_sync(12, 64);
                ring_load(ring + n * SLOT, &p.tm[0], 64 * (8 * r + 4 * w + (n >> 1)), 4 * (n & 1), full + n * 8);
            }
            TS(2);
            const uint32_t code = load_code(lane, r, w) | (load_code(lane + 32, r, w) << 16);
            cluster_wait();
            uint32_t s = 0, ph = 0;
            int n = NSLOT;
#pragma unroll 1
            for (int seg = 0; seg < 2; seg++) {
#pragma unroll 1
                for (; n < (seg == 0 ? 22 : NLOADS); n++) {
                    const uint32_t c = __shfl_sync(~0u, code, n) >> (n & 32 ? 16 : 0);
                    const CUtensorMap* tm = &p.tm[c & 15];
                    const uint32_t col = (c & 0xf0) * 4, row = (c & 0xff00) >> 8, dst = ring + s * SLOT;
                    mbar_wait(full + (B_EMPTY - B_FULL) * 8 + s * 8, ph + (((uint32_t)(size_t)tm | col | row | dst) & p.zero));
                    ring_load(dst, tm, col, row, full + s * 8);
                    if (++s == NSLOT) { s = 0; ph ^= 1; }
                }
                if (seg == 1) break;
                const uint32_t epoch = ld_epoch();
                const uint32_t rdy = bars + (B_RDY + 3 * w) * 8, prdy = mapa(rdy, r ^ 1);
                const int odd = r ^ w;
                const uint32_t* flags = g_flag_kv + (abh * 32 + lane) * KFS;
                auto kv_load = [&](uint32_t sl, int isv, int i) {
                    ring_load_both(ring + sl * SLOT, &p.tm[8], (isv * 64 + abh * 8 + 2 * i + w) * 128, full + sl * 8);
                };
#pragma unroll 1
                for (int i = 0; i < 2; i++) {
                    if (lane < 3 + i) {
                        const uint32_t sl = i ? lane : lane + 2;
                        mbar_wait(full + (B_EMPTY - B_FULL + sl) * 8, i ^ 1);
                        mbar_arrive_tx(full + sl * 8, (i || lane == 2) ? SLOT : 0);
                    }
                    __syncwarp();
                }
                if (lane == 0) mbar_arrive_peer(prdy);
                bar_sync(14, 96);
                spin(KDELAY);
                mbar_wait(rdy, 0);
                flag_wait(flags, epoch, (lane >> 2) == 2 * odd + w);
                if (!odd) TSW(5);
                if (!odd) { kv_load(4, 0, 0); bar_arrive(12, 64); }
                else { bar_sync(12, 64); spin(KD2); kv_load(0, 0, 1); }
                bar_sync(15, 96);
                flag_wait(flags + 256 * KFS, epoch, (lane >> 2) == 2 * odd + w);
                if (!odd) TSW(7);
                if (odd) mbar_wait(full + 8, 1);
                kv_load(1 + 2 * odd, 1, odd);
                flag_wait(flags + 256 * KFS, epoch, (lane >> 2) == 2 * odd + w + 4);
                if (!odd) kv_load(2, 0, 2);
#pragma unroll 1
                for (int i = 0; i < 3; i++) {
                    const uint32_t sl = i ? i - 1 : 4, bo = i == 2 ? 16 : 8;
                    mbar_wait(full + (B_EMPTY - B_FULL + sl) * 8, i != 0);
                    if (lane == 0) mbar_arrive_tx(full + sl * 8, SLOT);
                    if ((i & 1) != odd) {
                        mbar_wait(rdy + bo, 0);
                        kv_load(sl, i != 0, 2 + odd);
                    } else if (lane == 0) mbar_arrive_peer(prdy + bo);
                    __syncwarp();
                }
                n = 32; s = 2; ph = 1;
            }
        } else if (warp == 10) {
            if (lane == 0) {
#pragma unroll
                for (int i = B_EMPTY; i < NBARS; i++) mbar_init(bars + i * 8, i < B_XA ? 4 : 1);
#pragma unroll
                for (int i = B_XA; i <= B_SR; i++) mbar_arrive_tx(bars + i * 8, i < B_XB ? 512 : ((i >= B_INB && i < B_SR) ? 4096 : 8192));
                asm volatile("fence.mbarrier_init.release.cluster;" ::: "memory");
                fence_async_smem();
            }
            __syncwarp();
            cluster_arrive();
            cluster_wait();
        } else {
            const uint32_t kb = (lane < 2 || lane > 5) ? 4096 : (lane == 2 ? 3072 : (lane == 4 ? 2048 : 1024));
            const char* pf = p.w[lane & 7] + blockIdx.x * kb;
            cluster_wait();
            if (lane < PF0) prefetch_l2(pf, kb);
            mbar_wait(bars + B_FULL * 8, 0);
            if (lane >= PF0 && lane < 3) prefetch_l2(pf, kb);
            if (lane >= 1 && lane < 9) asm volatile("prefetch.tensormap [%0];" ::"l"(&p.tm[lane]) : "memory");
            mbar_wait(bars + (B_FULL + 1) * 8, 1);
            if (lane > 2 && lane < 8) prefetch_l2(pf, kb);
            if (lane == 8 && blockIdx.x < 15) prefetch_l2(p.dw + blockIdx.x * 256, 512);
            const uint32_t epoch = ld_epoch();
#pragma unroll 1
            for (int k = 0; k < 2; k++) {
                bar_sync(4, 288);
                if (lane < 16) flag_set(&g_flag_kv[(k * 256 + (b * 4 + 2 * r + (lane >> 3)) * 32 + pt) * KFS + (lane & 7)], epoch);
                __syncwarp();
                if (k == 0) bar_arrive(5, 288);
                else spin(KDELAY);
                bar_arrive(14 + k, 96);
                TSW(8 + k);
            }
        }
        TSDUMP();
        return;
    }

    const int w = warp >> 2, wq = warp & 3;
    const int tile = 2 * r + w;
    const int wt = tid & 127;
    const int c4 = lane & 3;
    const int trow = pt * 32 + 8 * wq;
    uint32_t xr[8];
    uint32_t a[32];
    const char* xrow = reinterpret_cast<const char*>(p.x) + (b * T_ + trow + (lane >> 2)) * 512;
    zero(a);
    if (trow < T_) {
        const char* src = xrow + c4 * 16 + p.zero;
#pragma unroll
        for (int i = 0; i < 8; i++)
            asm volatile("ld.global.nc.v4.b32 {%0,%1,%2,%3}, [%4];" : "=r"(a[4 * i]), "=r"(a[4 * i + 1]), "=r"(a[4 * i + 2]), "=r"(a[4 * i + 3]) : "l"(src + 64 * i));
    }
    cluster_arrive();
    asm volatile("setmaxnreg.inc.sync.aligned.u32 208;");
    const uint32_t rbase = sb + OFF_RING + w * NSLOT * SLOT, fbar = bars + (B_FULL + w * NSLOT) * 8;
    const uint32_t rdesc = desc_lo(rbase);
    auto acq = [&](int n) { mbar_wait(fbar + (n % NSLOT) * 8, (n / NSLOT) & 1); };
    auto rel = [&](int n) { if (lane == 0) mbar_arrive(fbar + (B_EMPTY - B_FULL + n % NSLOT) * 8); };
    const uint32_t foff = (lane & 7) * 128 + (((lane >> 3) ^ (lane & 7)) << 4);
    float v[16];
    const uint32_t xown = __shfl_sync(~0u, P + wt * 16 + tile * 4096, lane), xrem = __shfl_sync(~0u, P + wt * 16 + (r ^ 1) * 8192, lane);
    const uint32_t sbuf = __shfl_sync(~0u, sb + OFF_MISC + 1024 + (8 * wq + (lane >> 2)) * 32, lane);
    const uint32_t sown = __shfl_sync(~0u, sbuf + tile * 8, lane);
    const uint32_t peer = __shfl_sync(~0u, mapa(sb, r ^ 1) - sb, lane);
    const uint32_t hbuf = __shfl_sync(~0u, H + w * 4096 + wt * 16, lane);
    const uint32_t meta = __shfl_sync(~0u, 0xEEEE4444u + p.zero, lane);
    cluster_wait();
    TS(56);
    float mean, msq;
    const int mir = wq < 2 ? 7 : 0;
    uint32_t dwr[15] = {};

#pragma unroll
    for (int ph = 0; ph < 5; ph++) {
        uint4 o0, o1;
        if (ph == 0) {
            const uint32_t one = 0x3F803F80u + ((xown | xrem | sbuf | sown | hbuf | foff | rdesc | fbar) & p.zero);
            mean = ((row_sum<8>(a, one) + row_sum<8>(a + 8, one)) + (row_sum<8>(a + 16, one) + row_sum<8>(a + 24, one))) * (1.f / 256.f);
            TS(57);
        } else {
            const uint32_t xa = bars + (B_XA + ph) * 8;
#pragma unroll
            for (int j = 0; j < 8; j++) xr[j] = pack2(v[2 * j], v[2 * j + 1]);
            const float s = row_sum<8>(xr), q = row_sumsq<8>(xr, lane);
            if (ph < 4) {
                sts128(xown, xr[0], xr[1], xr[2], xr[3]);
                sts128(xown + 2048, xr[4], xr[5], xr[6], xr[7]);
            }
            put_sums(sown, sown + peer, s, q, xa + peer, c4 == (lane >> 3));
            bar_sync(10, 256);
            if (ph < 4) {
                o0 = lds128(xown ^ 4096); o1 = lds128((xown ^ 4096) + 2048);
                st_async4(xown + peer, xr[0], xr[1], xr[2], xr[3], xa + (B_XB - B_XA) * 8 + peer);
                st_async4(xown + peer + 2048, xr[4], xr[5], xr[6], xr[7], xa + (B_XB - B_XA) * 8 + peer);
            }
            TS(57 + ph);
            if (ph == 3) acq(0);
            if (ph == 1) acq(16);
            mbar_wait(xa, 0);
            const float4 u0 = lds128f(sbuf), u1 = lds128f(sbuf + 16);
            mean = ((u0.x + u0.z) + (u1.x + u1.z)) * (1.f / 256.f);
            msq = ((u0.y + u0.w) + (u1.y + u1.w)) * (1.f / 256.f);
        }
        if (ph == 4) break;
        const uint32_t mean2 = pack2(mean, mean);
        auto centre = [&](int i, const uint4& u) {
            a[i] = hsub2(u.x, mean2); a[i + 1] = hsub2(u.y, mean2); a[i + 2] = hsub2(u.z, mean2); a[i + 3] = hsub2(u.w, mean2);
        };
        if (ph == 0) {
#pragma unroll
            for (int j = 0; j < 32; j++) a[j] = hsub2(a[j], mean2);
            zero(xr);
            if (trow < T_) {
                const char* src = xrow + tile * 128 + c4 * 4 + (mean2 & p.zero);
#pragma unroll
                for (int j = 0; j < 8; j++) asm volatile("ld.global.nc.b32 %0, [%1];" : "=r"(xr[j]) : "l"(src + 16 * j));
            }
            mean -= blo(mean2);
            msq = __shfl_sync(~0u, row_sumsq<16>(a, lane) + row_sumsq<16>(a + 16, lane), (lane & 28) + (lane >> 3)) * (1.f / 256.f);
            acq(0);
        } else {
#pragma unroll
            for (int j = 0; j < 8; j++) a[j] = hsub2(xr[j], mean2);
            centre(8, o0); centre(12, o1);
        }
        const float rstd = rsq(fmaxf(fmaf(-mean, mean, msq), 0.f) + 1e-5f);
        auto gather_peer = [&]() {
            mbar_wait(bars + (B_XB + ph) * 8, 0);
#pragma unroll
            for (int i = 0; i < 4; i++) centre(16 + 4 * i, lds128(xrem + i * 2048));
        };
        auto sp = [&](float (&d)[32], int n, const uint32_t* af, int flip, int acc) {
            const uint32_t lo = rdesc + p.zero * (ph * 64 + n + 1) + (n % NSLOT) * (SLOT >> 4);
            const uint64_t b0 = mkdesc(lo + flip * 512), b1 = mkdesc(lo + (flip ^ 1) * 512);
            wg_fence();
            mma_sp(d, af, b0, meta, acc);
            mma_sp(d, af + 4, b0 + 256, meta, 1);
            mma_sp(d, af + 8, b1, meta, 1);
            mma_sp(d, af + 12, b1 + 256, meta, 1);
            wg_commit();
        };
        float d0[32], d1[32];

        if (ph == 0 || ph == 3) {
            uint32_t h[32], ho[32];
            const float rs = 0.5f * rstd;
            const uint32_t inb = bars + (B_INB + (ph & 2) + w) * 8;
            bool ready = true;
            const int eager = ph ? EAGER : EAGER - 1;
            auto step = [&](float (&d)[32], int n, const uint32_t* af, int flip, int acc, auto work) {
                if (!ready) acq(n);
                if (((TURN >> n) & 1) && w == 1) bar_sync(7, 256);
                sp(d, n, af, flip, acc);
                if (n > 0 && ((TURN >> (n - 1)) & 1) && w == 0) bar_arrive(7, 256);
                if (n < 15) ready = mbar_test(fbar + ((n + 1) % NSLOT) * 8, ((n + 1) / NSLOT) & 1);
                wg_wait<1>();
                if (n > 0 && !((eager >> (n - 1)) & 1)) rel(n - 1);
                const uint32_t tie = work() & p.zero;
                if ((eager >> n) & 1) {
                    if (p.zero < n + ph + 1) wg_wait<0>();
                    if (lane == 0) mbar_arrive(fbar + (B_EMPTY - B_FULL + n % NSLOT) * 8 + tie);
                }
            };
            auto none = []() { return 0u; };
            const int fl = ph ? w : 0;
            auto fetch = [&](int i) {
                bar_sync(10, 256);
                const uint4 u0 = lds128((hbuf ^ 4096) + (i & 1) * 8192), u1 = lds128((hbuf ^ 4096) + (i & 1) * 8192 + 2048);
                ho[8 * i] = u0.x; ho[8 * i + 1] = u0.y; ho[8 * i + 2] = u0.z; ho[8 * i + 3] = u0.w;
                ho[8 * i + 4] = u1.x; ho[8 * i + 5] = u1.y; ho[8 * i + 6] = u1.z; ho[8 * i + 7] = u1.w;
                return u0.x | u1.x;
            };
            auto act = [&](float (&d)[32], int i) {
                if (i > 0) fetch(i - 1);
                pin(d);
#pragma unroll
                for (int j = 0; j < 8; j++) {
                    const float u0 = (d[4 * j] + d[4 * j + 2]) * rs, u1 = (d[4 * j + 1] + d[4 * j + 3]) * rs;
                    h[8 * i + j] = pack2(fmaf(u0, tanh_fast(u0), u0), fmaf(u1, tanh_fast(u1), u1));
                }
                sts128(hbuf + (i & 1) * 8192, h[8 * i], h[8 * i + 1], h[8 * i + 2], h[8 * i + 3]);
                sts128(hbuf + (i & 1) * 8192 + 2048, h[8 * i + 4], h[8 * i + 5], h[8 * i + 6], h[8 * i + 7]);
                return 0u;
            };
            TS(1 + (ph & 2) * 10);
            step(d0, 0, a, fl, 0, [&]() { if (ph) gather_peer(); return 0u; });
            TS(32);
            step(d0, 1, a + 16, 0, 1, none);
            step(d1, 2, a, fl, 0, [&]() { return act(d0, 0); });
            step(d1, 3, a + 16, 0, 1, none);
            step(d0, 4, a, fl, 0, [&]() { return act(d1, 1); });
            TS(33);
            step(d0, 5, a + 16, 0, 1, none);
            step(d1, 6, a, fl, 0, [&]() { return act(d0, 2); });
            step(d1, 7, a + 16, 0, 1, none);
            step(d0, 8, h, 0, 0, [&]() { act(d1, 3); return fetch(3); });
            TS(2 + (ph & 2) * 10);
            step(d0, 9, ho, 0, 1, none);
            step(d0, 10, h + 16, 0, 1, none);
            step(d0, 11, ho + 16, 0, 1, none);
            uint32_t pk[8];
            auto pack_out = [&]() {
                pin(d0);
#pragma unroll
                for (int j = 0; j < 8; j++) pk[j] = pack2(d0[4 * j] + d0[4 * j + 2], d0[4 * j + 1] + d0[4 * j + 3]);
            };
            auto send = [&](int i) { st_async4(hbuf + 16384 + i * 2048 + peer, pk[4 * i], pk[4 * i + 1], pk[4 * i + 2], pk[4 * i + 3], inb + peer); };
            step(d1, 12, h, 0, 0, [&]() { pack_out(); if (SND != 1) send(0); if (SND == 0) send(1); return 0u; });
            TS(34);
            step(d1, 13, ho, 0, 1, [&]() { if (SND == 1) send(0); if (SND) send(1); return 0u; });
            step(d1, 14, h + 16, 0, 1, none);
            step(d1, 15, ho + 16, 0, 1, none);
            mbar_wait(inb, 0);
#pragma unroll
            for (int i = 0; i < 2; i++) {
                const uint4 u = lds128(hbuf + 16384 + i * 2048);
                const uint32_t p0[4] = {u.x, u.y, u.z, u.w};
#pragma unroll
                for (int j = 0; j < 4; j++) {
                    v[8 * i + 2 * j] = fmaf(0.5f, blo(p0[j]), blo(xr[4 * i + j]));
                    v[8 * i + 2 * j + 1] = fmaf(0.5f, bhi(p0[j]), bhi(xr[4 * i + j]));
                }
            }
            wg_wait<0>();
            pin(d1);
            rel(15);
            TS(3 + (ph & 2) * 10);
#pragma unroll
            for (int j = 0; j < 8; j++) {
                v[2 * j] = fmaf(0.5f, d1[4 * j] + d1[4 * j + 2], v[2 * j]);
                v[2 * j + 1] = fmaf(0.5f, d1[4 * j + 1] + d1[4 * j + 3], v[2 * j + 1]);
            }
#pragma unroll
            for (int i = 0; i < 15; i++) dwr[i] = 0;
            continue;
        }

        auto residual = [&](int n) {
            wg_wait<1>();
            rel(n);
            wg_wait<0>();
            pin(d0);
            rel(n + 1);
#pragma unroll
            for (int j = 0; j < 8; j++) {
                v[2 * j] = d0[4 * j] + d0[4 * j + 2] + blo(xr[j]);
                v[2 * j + 1] = d0[4 * j + 1] + d0[4 * j + 3] + bhi(xr[j]);
            }
        };

        if (ph == 2) {
            TS(39);
            sp(d0, 34, a, w, 0);
            acq(35);
            sp(d1, 35, a, w, 0);
            acq(36); acq(37);
            gather_peer();
            sp(d0, 36, a + 16, 0, 1);
            sp(d1, 37, a + 16, 0, 1);
            wg_wait<2>();
            rel(34);
            if (!(LATE & 1)) rel(35);
            acq(38);
            const float rs = trow < T_ ? 0.5f * rstd : 0.f;
            wg_wait<0>();
            pin(d0); pin(d1);
            if (!(LATE & 2)) { rel(36); rel(37); }
            TS(18);
            uint32_t pk[8];
#pragma unroll
            for (int j = 0; j < 8; j++) {
                const float u0 = (d0[4 * j] + d0[4 * j + 2]) * rs, u1 = (d0[4 * j + 1] + d0[4 * j + 3]) * rs;
                const float t0 = tanh_fast((d1[4 * j] + d1[4 * j + 2]) * rs), t1 = tanh_fast((d1[4 * j + 1] + d1[4 * j + 3]) * rs);
                pk[j] = pack2(fmaf(u0, t0, u0), fmaf(u1, t1, u1));
            }
            if (wq == 0 || wq == 3) {
                uint4* hp = &g_halo[((pair * 4 + tile) * 2 + (wq & 1)) * 64 + lane];
                st_data(hp, pk[0], pk[1], pk[2], pk[3]);
                st_data(hp + 32, pk[4], pk[5], pk[6], pk[7]);
            }
            const uint32_t gs = H + 16384 + w * GCH + wq * 1024;
            stsm4(gs + 1024 + foff, pk[0], pk[1], pk[2], pk[3]);
            stsm4(gs + 1024 + (foff ^ 64), pk[4], pk[5], pk[6], pk[7]);
            bar_sync(8 + w, 192);
            TS(26);
            uint32_t ca[8], cb[8];
            const int e = (wq & 1) * 4;
            const uint32_t lo = ((mir ^ e) * 144) ^ (lane * 4);
            const int dir = mir ? -1024 : 1024;
            const uint32_t gb = H + 16384 + w * GCH + (mir ? 3072 : 2048) + lo, sown_ = H + tile * HCH, so = sown_ + (mir ? 1024 : 2048) + lo;
            auto finish = [&](int i) {
                const uint32_t c = hadd2(ca[i], cb[i]);
                const float h0 = blo(c), h1 = bhi(c);
                sts32((so + (i >> 2) * dir) ^ ((i & 3) * 144), pack2(fmaf(h0, tanh_fast(h0), h0), fmaf(h1, tanh_fast(h1), h1)));
            };
#pragma unroll
            for (int k = 0; k < 26; k++) {
                if (k == 19) {
#pragma unroll
                    for (int i = 0; i < 4; i++) finish(i);
                    fence_async_smem();
                    bar_sync(2 + w, 128);
                    if (wq == 0) peer_copy(mapa(sown_ + 1024, r ^ 1), sown_ + 1024, 2048, mapa(bars + B_SR * 8, r ^ 1));
                    mbar_wait(bars + (B_HALO + 2 * w + (wq >> 1)) * 8, 0);
                    if (LATE & 1) rel(35);
                    if (LATE & 2) { rel(36); rel(37); }
                    TS(27);
                }
                const uint32_t g = lds32((gb + (((k + 1) & 4) ? ((k + 1) >> 3) + (wq & 1) : ((k + 1) >> 3)) * dir) ^ (((k + 1) & 7) * 144));
#pragma unroll
                for (int i = 0; i < 8; i++) {
                    const int tap = k - (i & 3) - 2 * (i & 4);
                    if (tap == 0) ca[i] = hmul2(g, dwr[0]);
                    else if (tap > 0 && tap < 8) ca[i] = hfma2(g, dwr[tap], ca[i]);
                    else if (tap == 8) cb[i] = hmul2(g, dwr[8]);
                    else if (tap > 8 && tap < 15) cb[i] = hfma2(g, dwr[tap], cb[i]);
                }
            }
#pragma unroll
            for (int i = 4; i < 8; i++) finish(i);
            fence_async_smem();
            bar_sync(12 + (warp >> 1), 64);
            if (wq == 0 || wq == 3) peer_copy(mapa(sown_ + wq * 1024, r ^ 1), sown_ + wq * 1024, 1024, mapa(bars + B_SR * 8, r ^ 1));
            bar_sync(10, 256);
            TS(19);
            auto frags = [&](int i, int half) {
                const uint32_t src = H + 2 * half * HCH + wq * 1024;
#pragma unroll
                for (int k = 0; k < 4; k++) ldsm4(src + (k >> 1) * HCH + (foff ^ ((k & 1) * 64)), a[i + 4 * k], a[i + 4 * k + 1], a[i + 4 * k + 2], a[i + 4 * k + 3]);
            };
            frags(0, r);
            sp(d0, 38, a, 0, 0);
            acq(39);
            mbar_wait(bars + B_SR * 8, 0);
            frags(16, r ^ 1);
            sp(d0, 39, a + 16, 0, 1);
            residual(38);
            TS(20);
            continue;
        }

        {
            TS(11);
            const uint32_t stg = H + warp * 1024;
            unsigned char* g = g_kvq + (size_t)((b * 4 + tile) * 1024 + trow) * 128 + lane * 16;
            auto vecs = [&](float (&d)[32], bool image, uint4& u0, uint4& u1) {
                pin(d);
                uint32_t pk[8];
#pragma unroll
                for (int j = 0; j < 8; j++) pk[j] = pack2((d[4 * j] + d[4 * j + 2]) * rstd, (d[4 * j + 1] + d[4 * j + 3]) * rstd);
                u0 = make_uint4(pk[0], pk[1], pk[2], pk[3]); u1 = make_uint4(pk[4], pk[5], pk[6], pk[7]);
                if (image) {
                    stsm4(stg + foff, pk[0], pk[1], pk[2], pk[3]);
                    stsm4(stg + (foff ^ 64), pk[4], pk[5], pk[6], pk[7]);
                    __syncwarp();
                    u0 = lds128(stg + lane * 16); u1 = lds128(stg + 512 + lane * 16);
                    __syncwarp();
                }
            };
            uint4 u0, u1, q0, q1;
            sp(d0, 16, a, w, 0);
            acq(17);
            gather_peer();
            sp(d0, 17, a + 16, 0, 1);
            acq(18); acq(19);
            wg_wait<0>();
            rel(16); rel(17);
            TS(37);
            vecs(d0, true, u0, u1);
            stg128(g, u0); stg128(g + 512, u1);
            bar_arrive(4, 288);
            TS(38);
            sp(d1, 18, a, w, 0);
            sp(d1, 19, a + 16, 0, 1);
            acq(20);
            sp(d0, 20, a, w, 0);
            wg_wait<1>();
            rel(18); rel(19);
            acq(21);
            sp(d0, 21, a + 16, 0, 1);
            vecs(d1, false, q0, q1);
            acq(22); acq(23);
            rel(22); rel(23);
            mbar_wait(bars + B_RST * 8, 0);
            if (QEARLY) {
                bar_sync(5, 288);
                st_data(g + 2097152, q0.x, q0.y, q0.z, q0.w); st_data(g + 2097152 + 512, q1.x, q1.y, q1.z, q1.w);
            }
            wg_wait<0>();
            rel(20); rel(21);
            vecs(d0, true, u0, u1);
            if (!QEARLY) {
                bar_sync(5, 288);
                st_data(g + 2097152, q0.x, q0.y, q0.z, q0.w); st_data(g + 2097152 + 512, q1.x, q1.y, q1.z, q1.w);
            }
            stg128(g + 1048576, u0); stg128(g + 1048576 + 512, u1);
            bar_arrive(4, 288);
            TS(12);
        }

        {
            constexpr float CS = 0.125f * 1.4426950408889634f;
            float sa[32], sb2[32], o[36];
            uint32_t pa[16], pb[16], q[16];
            float n0 = INFINITY, n1 = INFINITY;
            zero(o); zero(pa); zero(pb); zero(sb2);
            const uint32_t ones = sb + OFF_MISC + 2048;
            { const uint32_t c = w ? 0u : 0x3F803F80u; sts128(ones + tid * 16, c, c, c, c); }
            sts128(H + 16384 + tid * 16, 0, 0, 0, 0); sts128(H + 20480 + tid * 16, 0, 0, 0, 0);
            fence_async_smem();
            bar_sync(10, 256);
            const uint32_t vdesc = rdesc + ((((ones - rbase) >> 4) - 1) << 16);
            auto qk_issue = [&](float (&s)[32], uint32_t lo) {
                const uint64_t kd = mkdesc(lo);
                wg_fence();
#pragma unroll
                for (int k = 0; k < 4; k++) mma_qk(s, q[4 * k], q[4 * k + 1], q[4 * k + 2], q[4 * k + 3], kd + 2 * k, k != 0);
                wg_commit();
            };
            auto both_issue = [&](float (&s)[32], uint32_t klo, uint32_t (&pp)[16], uint32_t vlo) {
                const uint64_t kd = mkdesc(klo), vd = mkdesc(vlo);
                wg_fence();
#pragma unroll
                for (int k = 0; k < 4; k++) {
                    mma_pv(o, pp[4 * k], pp[4 * k + 1], pp[4 * k + 2], pp[4 * k + 3], vd - k * (128 * 65535));
                    mma_qk(s, q[4 * k], q[4 * k + 1], q[4 * k + 2], q[4 * k + 3], kd + 2 * k, k != 0);
                }
                wg_commit();
            };
            auto new_max = [&](float (&s)[32], int nj, float& x0, float& x1) {
                x0 = s[0]; x1 = s[2];
#pragma unroll
                for (int j = 0; j < nj; j++) {
                    x0 = fmaxf(x0, fmaxf(s[4 * j], s[4 * j + 1]));
                    x1 = fmaxf(x1, fmaxf(s[4 * j + 2], s[4 * j + 3]));
                }
                x0 = fmaxf(x0, __shfl_xor_sync(~0u, x0, 1)); x1 = fmaxf(x1, __shfl_xor_sync(~0u, x1, 1));
                x0 = fmaxf(x0, __shfl_xor_sync(~0u, x0, 2)); x1 = fmaxf(x1, __shfl_xor_sync(~0u, x1, 2));
                x0 = fminf(n0, fmaf(x0, -CS, -20.f)); x1 = fminf(n1, fmaf(x1, -CS, -20.f));
            };
            auto probs = [&](float (&s)[32], uint32_t (&pp)[16], bool ready, bool tail, auto wait) {
                uint32_t any = 0;
#pragma unroll
                for (int i = 0; i < 16; i++) {
                    pp[i] = pack2(ex2(fmaf(s[2 * i], CS, (i & 1) ? n1 : n0)), ex2(fmaf(s[2 * i + 1], CS, (i & 1) ? n1 : n0)));
                    any |= pp[i];
                }
                wg_wait<0>();
                pin(sa); pin(sb2); pin(o); pin(pa); pin(pb);
                if (__builtin_expect(__any_sync(~0u, (any & 0x40004000u) || !ready), 0)) {
                    wait();
                    if (__any_sync(~0u, any & 0x40004000u)) {
                        if (tail) {
#pragma unroll
                            for (int i = 20; i < 32; i++) s[i] = -INFINITY;
                        }
                        float x0, x1;
                        new_max(s, 8, x0, x1);
                        const float sc0 = ex2(x0 - n0), sc1 = ex2(x1 - n1);
                        n0 = x0; n1 = x1;
#pragma unroll
                        for (int j = 0; j < 9; j++) { o[4 * j] *= sc0; o[4 * j + 1] *= sc0; o[4 * j + 2] *= sc1; o[4 * j + 3] *= sc1; }
#pragma unroll
                        for (int i = 0; i < 16; i++)
                            pp[i] = pack2(ex2(fmaf(s[2 * i], CS, (i & 1) ? n1 : n0)), ex2(fmaf(s[2 * i + 1], CS, (i & 1) ? n1 : n0)));
                    }
                }
            };
            {
                uint4 u[4];
                const unsigned char* src = g_kvq + 2097152 + (size_t)(abh * 1024 + qt * 64 + wq * 16) * 128 + lane * 16;
                spin(QGATE);
                ld_data<512>(u, src);
#pragma unroll
                for (int k = 0; k < 2; k++) {
                    q[8 * k] = u[k].x; q[8 * k + 1] = u[k + 2].x; q[8 * k + 2] = u[k].y; q[8 * k + 3] = u[k + 2].y;
                    q[8 * k + 4] = u[k].z; q[8 * k + 5] = u[k + 2].z; q[8 * k + 6] = u[k].w; q[8 * k + 7] = u[k + 2].w;
                }
                pin(q);
            }
            TS(40);
            acq(24);
            TS(13);
            qk_issue(sa, rdesc + (24 % NSLOT) * (SLOT >> 4));
            wg_wait<0>();
            pin(sa);
            {
                float x0, x1;
                new_max(sa, NJ0, x0, x1);
                n0 = x0; n1 = x1;
            }
            bar_arrive(6, 384);
            uint32_t vd = vdesc - (SLOT >> 4) * 65535u, kd = rdesc, vb = fbar + 8, kb = fbar;
            uint32_t vlast = vdesc - 4 * (SLOT >> 4) * 65535u, klast = rdesc + 4 * (SLOT >> 4) + 512;
            uint32_t kprev = fbar + 32, vprev = bars + (B_SINK - (B_EMPTY - B_FULL)) * 8;
#pragma unroll 1
            for (int it = 0; it < 4; it++) {
                both_issue(sb2, klast, pb, vlast);
                const uint32_t vt = it ? vb : kb;
                probs(sa, pa, mbar_test(vt, it < 2) & mbar_test(kb, it < 3), false, [&]() { mbar_wait(vt, it < 2); mbar_wait(kb, it < 3); });
                TS(41 + it * 4);
                if (lane == 0) mbar_arrive(kprev + (B_EMPTY - B_FULL) * 8);
                if (lane == 0) mbar_arrive(vprev + (B_EMPTY - B_FULL) * 8);
                both_issue(sa, kd, pa, it ? vd : desc_lo(H + 16384) + ((((ones + 2048 - H - 16384) >> 4) - 1) << 16));
                const float m0 = n0, m1 = n1;
                const int dv = it == 0 ? 2 : (it == 1 ? -3 : 1);
                kprev = kb; vprev = vb; vlast = vd - 512 * 65535u; klast = kd + 512;
                vd -= dv * (SLOT >> 4) * 65535u; vb += dv * 8;
                kd += (it == 2 ? -3 : 2) * (SLOT >> 4); kb = it == 2 ? vb : kb + 16;
                probs(sb2, pb, true, it == 3 && w == 1, []() {});
                if (it == 0) {
                    acq(26);
                    wg_fence();
#pragma unroll
                    for (int k = 0; k < 4; k++)
                        mma_pv(o, pa[4 * k], pa[4 * k + 1], pa[4 * k + 2], pa[4 * k + 3], mkdesc(vdesc - ((SLOT >> 4) + k * 128) * 65535u));
                    wg_commit();
                    wg_wait<0>();
                    pin(o); pin(pa);
                    if (__any_sync(~0u, m0 != n0 || m1 != n1)) {
                        const float sc0 = ex2(n0 - m0), sc1 = ex2(n1 - m1);
#pragma unroll
                        for (int j = 0; j < 9; j++) { o[4 * j] *= sc0; o[4 * j + 1] *= sc0; o[4 * j + 2] *= sc1; o[4 * j + 3] *= sc1; }
                    }
                }
                TS(43 + it * 4);
            }
            wg_fence();
#pragma unroll
            for (int k = 0; k < 4; k++)
                mma_pv(o, pb[4 * k], pb[4 * k + 1], pb[4 * k + 2], pb[4 * k + 3], mkdesc(vlast - k * (128 * 65535) + (k > 1 ? w * ((k - 1) << 22) : 0)));
            wg_commit();
            const int row = wq * 16 + (lane >> 2);
            const uint32_t ml = sb + OFF_MISC;
            mbar_wait(bars + (B_RST + 1) * 8, 0);
            wg_wait<0>();
            pin(o); pin(pb); pin(sa); pin(sb2);
            if (!(LATE & 4)) rel(31);
            const float l0 = o[32], l1 = o[34];
            if (c4 == 0) { sts64f(ml + w * 512 + row * 8, n0, l0); sts64f(ml + w * 512 + row * 8 + 64, n1, l1); }
            TS(14);
            float mine[16];
#pragma unroll
            for (int j = 0; j < 4; j++) {
                if (w == 0) sts128f(H + j * 2048 + wt * 16, o[16 + 4 * j], o[17 + 4 * j], o[18 + 4 * j], o[19 + 4 * j]);
                else sts128f(H + 8192 + j * 2048 + wt * 16, o[4 * j], o[4 * j + 1], o[4 * j + 2], o[4 * j + 3]);
            }
#pragma unroll
            for (int i = 0; i < 16; i++) mine[i] = w == 0 ? o[i] : o[16 + i];
            bar_sync(10, 256);
            const float2 u0 = lds64f(ml + (w ^ 1) * 512 + row * 8), u1 = lds64f(ml + (w ^ 1) * 512 + row * 8 + 64);
            const float x0 = fminf(n0, u0.x), x1 = fminf(n1, u1.x);
            float a0 = ex2(x0 - n0), b0 = ex2(x0 - u0.x), a1 = ex2(x1 - n1), b1 = ex2(x1 - u1.x);
            const float i0 = __fdividef(1.f, fmaf(a0, l0, b0 * u0.y)), i1 = __fdividef(1.f, fmaf(a1, l1, b1 * u1.y));
            a0 *= i0; b0 *= i0; a1 *= i1; b1 *= i1;
            uint32_t pk[8];
#pragma unroll
            for (int j = 0; j < 4; j++) {
                const float4 v = lds128f(H + (w ^ 1) * 8192 + j * 2048 + wt * 16);
                pk[2 * j] = pack2(fmaf(a0, mine[4 * j], b0 * v.x), fmaf(a0, mine[4 * j + 1], b0 * v.y));
                pk[2 * j + 1] = pack2(fmaf(a1, mine[4 * j + 2], b1 * v.z), fmaf(a1, mine[4 * j + 3], b1 * v.w));
            }
            unsigned char* dst = g_o + (size_t)(b * 128 + qt * 8 + 2 * wq) * 4096 + ah * 1024 + w * 512 + lane * 16;
            st_data(dst, pk[0], pk[2], pk[4], pk[6]);
            st_data(dst + 4096, pk[1], pk[3], pk[5], pk[7]);
            if (tid == 0) asm volatile("red.relaxed.gpu.global.add.u32 [%0], 1;" ::"l"(&g_epoch[blockIdx.x * FS]) : "memory");
            TS(15);
        }

        {
            const uint32_t* dp = reinterpret_cast<const uint32_t*>(p.dw + (mir ? 14 * 256 : 0) + tile * 64) + lane;
#pragma unroll
            for (int i = 0; i < 15; i++) asm volatile("ld.global.nc.b32 %0, [%1];" : "=r"(dwr[i]) : "l"(dp + i * (mir ? -128 : 128)));
            acq(32); acq(33); acq(34);
            uint4 u[8];
            ld_data<512>(u, g_o + (size_t)(b * 128 + pt * 4 + wq) * 4096 + lane * 16);
#pragma unroll
            for (int i = 0; i < 8; i++) { a[4 * i] = u[i].x; a[4 * i + 1] = u[i].y; a[4 * i + 2] = u[i].z; a[4 * i + 3] = u[i].w; }
            if (LATE & 4) rel(31);
            TS(16);
            sp(d0, 32, a, 0, 0);
            sp(d0, 33, a + 16, 0, 1);
#pragma unroll
            for (int i = 0; i < 15; i++) dwr[i] = hmul2(dwr[i], 0x3F003F00u);
            residual(32);
            TS(17);
        }
    }

    cluster_arrive();
    TS(24);
    {
        const float rstd = rsq(fmaxf(fmaf(-mean, mean, msq), 0.f) + 1e-5f), nb = -mean * rstd;
#pragma unroll
        for (int j = 0; j < 8; j++) xr[j] = pack2(fmaf(v[2 * j], rstd, nb), fmaf(v[2 * j + 1], rstd, nb));
        const uint32_t stg = P + 16384 + warp * 1024;
        stsm4(stg + foff, xr[0], xr[1], xr[2], xr[3]);
        stsm4(stg + (foff ^ 64), xr[4], xr[5], xr[6], xr[7]);
        __syncwarp();
        const uint32_t src = stg + (lane >> 3) * 128 + (((lane & 7) ^ (lane >> 3)) << 4);
        const uint4 u0 = lds128(src), u1 = lds128((src + 512) ^ 64);
        __nv_bfloat16* dst = p.out + (size_t)(b * T_ + trow + (lane >> 3)) * 256 + tile * 64 + (lane & 7) * 8;
        if (trow < T_) { stg128(dst, u0); stg128(dst + 4 * 256, u1); }
    }
    TS(25);
    TG(31);
    TSDUMP();
    cluster_wait();
}

typedef CUresult (*EncodeFn)(CUtensorMap*, CUtensorMapDataType, cuuint32_t, void*, const cuuint64_t*, const cuuint64_t*,
                             const cuuint32_t*, const cuuint32_t*, CUtensorMapInterleave, CUtensorMapSwizzle,
                             CUtensorMapL2promotion, CUtensorMapFloatOOBfill);

}

extern "C" void kernel_launch(void* const* d_in, const int* in_sizes, int n_in, void* d_out, int out_size) {
    static EncodeFn encode = nullptr;
    if (!encode) {
        void* fn = nullptr;
        cudaDriverEntryPointQueryResult qr;
        cudaGetDriverEntryPoint("cuTensorMapEncodeTiled", &fn, cudaEnableDefault, &qr);
        encode = (EncodeFn)fn;
        cudaFuncSetAttribute(conformer_kernel, cudaFuncAttributeMaxDynamicSharedMemorySize, SMEM_LAUNCH);
    }
    Params p;
    const cuuint32_t ones[5] = {1, 1, 1, 1, 1};
    const int idx[8] = {1, 2, 3, 4, 5, 7, 8, 9};
    const int rows[8] = {256, 1024, 256, 256, 256, 256, 256, 1024};
    const int cols[8] = {1024, 256, 768, 256, 512, 256, 1024, 256};
    for (int i = 0; i < 8; i++) {
        const cuuint64_t pitch = (cuuint64_t)cols[i] * 2;
        const cuuint64_t dims[5] = {(cuuint64_t)cols[i], i ? 2u : 4u, i ? 2u : 4u, i ? 4u : 2u, (cuuint64_t)rows[i] / (i ? 16 : 32)};
        const cuuint64_t strides[4] = {pitch, pitch * 8, pitch * (i ? 2 : 4), pitch * (i ? 16 : 32)};
        const cuuint32_t box[5] = {64, i ? 2u : 4u, i ? 2u : 4u, i ? 4u : 2u, i ? 8u : 4u};
        encode(&p.tm[i], CU_TENSOR_MAP_DATA_TYPE_BFLOAT16, 5, d_in[idx[i]], dims, strides, box, ones, CU_TENSOR_MAP_INTERLEAVE_NONE,
               CU_TENSOR_MAP_SWIZZLE_128B, CU_TENSOR_MAP_L2_PROMOTION_L2_128B, CU_TENSOR_MAP_FLOAT_OOB_FILL_NONE);
        p.w[i] = (const char*)d_in[idx[i]];
    }
    {
        void* kv = nullptr;
        cudaGetSymbolAddress(&kv, g_kvq);
        const cuuint64_t dims[2] = {64, 16384};
        const cuuint64_t strides[1] = {128};
        const cuuint32_t box[2] = {64, 128};
        encode(&p.tm[8], CU_TENSOR_MAP_DATA_TYPE_BFLOAT16, 2, kv, dims, strides, box, ones, CU_TENSOR_MAP_INTERLEAVE_NONE,
               CU_TENSOR_MAP_SWIZZLE_NONE, CU_TENSOR_MAP_L2_PROMOTION_L2_128B, CU_TENSOR_MAP_FLOAT_OOB_FILL_NONE);
    }
    p.x = (const __nv_bfloat16*)d_in[0];
    p.dw = (const __nv_bfloat16*)d_in[6];
    p.out = (__nv_bfloat16*)d_out;
    p.zero = 0;
    conformer_kernel<<<NCTA, NTHREADS, SMEM_LAUNCH>>>(p);
}
```

```cpp
#include <cuda_runtime.h>
#include <cuda_bf16.h>
#include <cuda.h>
#include <stdint.h>

namespace {

constexpr int T_ = 1000;
constexpr int NCTA = 128;
constexpr int NTHREADS = 512;
constexpr int NSLOT = 5;
constexpr int SLOT = 16384;
constexpr int NLOADS = 56;

constexpr uint32_t OFF_RING = 0;
constexpr uint32_t OFF_P = 163840;
constexpr uint32_t OFF_H = 188416;
constexpr uint32_t OFF_MISC = 221184;
constexpr uint32_t OFF_BARS = 229888;
constexpr uint32_t SMEM_BYTES = 230400;
constexpr uint32_t GCH = 6144;
constexpr uint32_t HCH = 4096;

constexpr int B_FULL = 0, B_EMPTY = 10, B_XA = 20  , B_XB = 25  , B_INB = 29  , B_SR = 33,
              B_RST = 34  , B_RDY = 36  , B_SINK = 42, B_HALO = 43  , NBARS = 47;

#define QGATE 1u
#define BACKOFF 0u
#define KFS 8
#define KDELAY 300u
#define NJ0 2
#define HDELAY 200u
#define LATE 2
#define SND 0
#define PF0 1
#define NFIRST 2
#define TURN 0x200
#define EAGER 0x0155
constexpr int FS = 8;

struct Params {
    CUtensorMap tm[9];
    const char* w[8];
    const __nv_bfloat16* x;
    const __nv_bfloat16* dw;
    __nv_bfloat16* out;
    uint32_t zero;
};

__device__ __align__(1024) unsigned char g_kvq[3 * 8 * 1024 * 128];
__device__ __align__(1024) unsigned char g_o[2 * 128 * 4096];
__device__ uint4 g_halo[64 * 4 * 2 * 64];
__device__ __align__(128) uint32_t g_flag_kv[8 * 32 * KFS];
__device__ uint32_t g_reset[4 * 32];
__device__ uint32_t g_epoch[NCTA * FS];

#define TS(i) do { } while (0)
#define TSW(i) do { } while (0)
#define TG(i) do { } while (0)
#define TSINIT() do { } while (0)
#define TSDUMP() do { } while (0)
constexpr uint32_t SMEM_LAUNCH = SMEM_BYTES;

__device__ __forceinline__ uint32_t smem_u32(const void* p) { return (uint32_t)__cvta_generic_to_shared(p); }
__device__ __forceinline__ void mbar_init(uint32_t b, uint32_t c) { asm volatile("mbarrier.init.shared::cta.b64 [%0], %1;" ::"r"(b), "r"(c) : "memory"); }
__device__ __forceinline__ void mbar_arrive(uint32_t b) { asm volatile("mbarrier.arrive.shared::cta.b64 _, [%0];" ::"r"(b) : "memory"); }
__device__ __forceinline__ void mbar_arrive_tx(uint32_t b, uint32_t tx) { asm volatile("mbarrier.arrive.expect_tx.shared::cta.b64 _, [%0], %1;" ::"r"(b), "r"(tx) : "memory"); }
__device__ __forceinline__ void mbar_wait(uint32_t b, uint32_t ph) {
    asm volatile("{\n.reg .pred p, q;\n.reg .u32 c;\nmov.u32 c, 0;\n"
                 "MW_LOOP:\n.pragma \"nounroll\";\n"
                 "mbarrier.try_wait.parity.shared::cta.b64 p, [%0], %1;\n"
                 "add.u32 c, c, 1;\nsetp.lt.u32 q, c, 65536;\nnot.pred p, p;\nand.pred p, p, q;\n@p bra MW_LOOP;\n}"
                 ::"r"(b), "r"(ph) : "memory");
}
__device__ __forceinline__ bool mbar_test(uint32_t b, uint32_t ph) {
    uint32_t ok;
    asm volatile("{\n.reg .pred p;\nmbarrier.test_wait.parity.shared::cta.b64 p, [%1], %2;\nselp.u32 %0, 1, 0, p;\n}" : "=r"(ok) : "r"(b), "r"(ph) : "memory");
    return ok;
}
__device__ __forceinline__ uint32_t mapa(uint32_t a, uint32_t r) { uint32_t o; asm("mapa.shared::cluster.u32 %0, %1, %2;" : "=r"(o) : "r"(a), "r"(r)); return o; }
__device__ __forceinline__ void fence_async_smem() { asm volatile("fence.proxy.async.shared::cta;" ::: "memory"); }
__device__ __forceinline__ void fence_async_global() { asm volatile("fence.proxy.async.global;" ::: "memory"); }
__device__ __forceinline__ void bar_sync(int id, int n) { asm volatile("bar.sync %0, %1;" ::"r"(id), "r"(n) : "memory"); }
__device__ __forceinline__ void bar_arrive(int id, int n) { asm volatile("bar.arrive %0, %1;" ::"r"(id), "r"(n) : "memory"); }
__device__ __forceinline__ void cluster_arrive() { asm volatile("barrier.cluster.arrive.relaxed.aligned;" ::: "memory"); }
__device__ __forceinline__ void cluster_wait() { asm volatile("barrier.cluster.wait.aligned;" ::: "memory"); }

__device__ __forceinline__ void ring_load(uint32_t dst, const CUtensorMap* tm, int col, int row16, uint32_t bar) {
    asm volatile("{\n.reg .pred p;\nelect.sync _|p, 0xffffffff;\n"
                 "@p mbarrier.arrive.expect_tx.shared::cta.b64 _, [%2], 16384;\n"
                 "@p cp.async.bulk.tensor.5d.shared::cluster.global.mbarrier::complete_tx::bytes [%0], [%1, {%3, 0, 0, 0, %4}], [%2];\n}"
                 ::"r"(dst), "l"(tm), "r"(bar), "r"(col), "r"(row16) : "memory");
}
__device__ __forceinline__ void ring_load_both(uint32_t dst, const CUtensorMap* tm, int c1, uint32_t bar) {
    asm volatile("{\n.reg .pred p;\nelect.sync _|p, 0xffffffff;\n"
                 "@p cp.async.bulk.tensor.2d.shared::cluster.global.mbarrier::complete_tx::bytes.multicast::cluster [%0], [%1, {0, %3}], [%2], %4;\n}"
                 ::"r"(dst), "l"(tm), "r"(bar), "r"(c1), "h"((uint16_t)3) : "memory");
}
__device__ __forceinline__ void mbar_arrive_peer(uint32_t b) { asm volatile("mbarrier.arrive.relaxed.cluster.shared::cluster.b64 _, [%0];" ::"r"(b) : "memory"); }
__device__ __forceinline__ void prefetch_l2(const void* src, uint32_t bytes) {
    asm volatile("cp.async.bulk.prefetch.L2.global [%0], %1;" ::"l"(src), "r"(bytes) : "memory");
}
__device__ __forceinline__ void peer_copy(uint32_t dst, uint32_t src, uint32_t bytes, uint32_t rbar) {
    asm volatile("{\n.reg .pred p;\nelect.sync _|p, 0xffffffff;\n"
                 "@p cp.async.bulk.shared::cluster.shared::cta.mbarrier::complete_tx::bytes [%0], [%1], %2, [%3];\n}"
                 ::"r"(dst), "r"(src), "r"(bytes), "r"(rbar) : "memory");
}
__device__ __forceinline__ void st_async4(uint32_t dst, uint32_t a, uint32_t b, uint32_t c, uint32_t d, uint32_t bar) {
    asm volatile("st.async.shared::cluster.mbarrier::complete_tx::bytes.v4.b32 [%0], {%1,%2,%3,%4}, [%5];" ::"r"(dst), "r"(a), "r"(b), "r"(c), "r"(d), "r"(bar) : "memory");
}
__device__ __forceinline__ void put_sums(uint32_t dst, uint32_t rdst, float a, float b, uint32_t rbar, bool on) {
    asm volatile("{\n.reg .pred p;\nsetp.ne.u32 p, %5, 0;\n"
                 "@p st.async.shared::cluster.mbarrier::complete_tx::bytes.v2.f32 [%1], {%2,%3}, [%4];\n"
                 "@p st.shared.v2.f32 [%0], {%2,%3};\n}" ::"r"(dst), "r"(rdst), "f"(a), "f"(b), "r"(rbar), "r"((uint32_t)on) : "memory");
}
__device__ __forceinline__ void stsm4(uint32_t a, uint32_t r0, uint32_t r1, uint32_t r2, uint32_t r3) {
    asm volatile("stmatrix.sync.aligned.m8n8.x4.shared.b16 [%0], {%1,%2,%3,%4};" ::"r"(a), "r"(r0), "r"(r1), "r"(r2), "r"(r3) : "memory");
}
__device__ __forceinline__ void ldsm4(uint32_t a, uint32_t& r0, uint32_t& r1, uint32_t& r2, uint32_t& r3) {
    asm volatile("ldmatrix.sync.aligned.m8n8.x4.shared.b16 {%0,%1,%2,%3}, [%4];" : "=r"(r0), "=r"(r1), "=r"(r2), "=r"(r3) : "r"(a) : "memory");
}
__device__ __forceinline__ uint4 lds128(uint32_t a) { uint4 v; asm volatile("ld.shared.v4.b32 {%0,%1,%2,%3}, [%4];" : "=r"(v.x), "=r"(v.y), "=r"(v.z), "=r"(v.w) : "r"(a) : "memory"); return v; }
__device__ __forceinline__ float4 lds128f(uint32_t a) { float4 v; asm volatile("ld.shared.v4.f32 {%0,%1,%2,%3}, [%4];" : "=f"(v.x), "=f"(v.y), "=f"(v.z), "=f"(v.w) : "r"(a) : "memory"); return v; }
__device__ __forceinline__ float2 lds64f(uint32_t a) { float2 v; asm volatile("ld.shared.v2.f32 {%0,%1}, [%2];" : "=f"(v.x), "=f"(v.y) : "r"(a) : "memory"); return v; }
__device__ __forceinline__ uint32_t lds32(uint32_t a) { uint32_t v; asm volatile("ld.shared.b32 %0, [%1];" : "=r"(v) : "r"(a) : "memory"); return v; }
__device__ __forceinline__ void sts128(uint32_t a, uint32_t x, uint32_t y, uint32_t z, uint32_t w) { asm volatile("st.shared.v4.b32 [%0], {%1,%2,%3,%4};" ::"r"(a), "r"(x), "r"(y), "r"(z), "r"(w) : "memory"); }
__device__ __forceinline__ void sts128f(uint32_t a, float x, float y, float z, float w) { asm volatile("st.shared.v4.f32 [%0], {%1,%2,%3,%4};" ::"r"(a), "f"(x), "f"(y), "f"(z), "f"(w) : "memory"); }
__device__ __forceinline__ void sts64f(uint32_t a, float x, float y) { asm volatile("st.shared.v2.f32 [%0], {%1,%2};" ::"r"(a), "f"(x), "f"(y) : "memory"); }
__device__ __forceinline__ void sts32(uint32_t a, uint32_t x) { asm volatile("st.shared.b32 [%0], %1;" ::"r"(a), "r"(x) : "memory"); }
__device__ __forceinline__ void stg128(void* p, uint4 v) { asm volatile("st.global.v4.b32 [%0], {%1,%2,%3,%4};" ::"l"(p), "r"(v.x), "r"(v.y), "r"(v.z), "r"(v.w) : "memory"); }

__device__ __forceinline__ uint32_t pack2(float lo, float hi) { uint32_t r; asm("cvt.rn.bf16x2.f32 %0, %1, %2;" : "=r"(r) : "f"(hi), "f"(lo)); return r; }
__device__ __forceinline__ float blo(uint32_t v) { return __uint_as_float(v << 16); }
__device__ __forceinline__ float bhi(uint32_t v) { return __uint_as_float(v & 0xffff0000u); }
__device__ __forceinline__ uint32_t hmul2(uint32_t a, uint32_t b) { uint32_t r; asm("mul.rn.bf16x2 %0, %1, %2;" : "=r"(r) : "r"(a), "r"(b)); return r; }
__device__ __forceinline__ uint32_t hadd2(uint32_t a, uint32_t b) { uint32_t r; asm("add.rn.bf16x2 %0, %1, %2;" : "=r"(r) : "r"(a), "r"(b)); return r; }
__device__ __forceinline__ uint32_t hsub2(uint32_t a, uint32_t b) { uint32_t r; asm("sub.rn.bf16x2 %0, %1, %2;" : "=r"(r) : "r"(a), "r"(b)); return r; }
__device__ __forceinline__ uint32_t hfma2(uint32_t a, uint32_t b, uint32_t c) { uint32_t r; asm("fma.rn.bf16x2 %0, %1, %2, %3;" : "=r"(r) : "r"(a), "r"(b), "r"(c)); return r; }
__device__ __forceinline__ float tanh_fast(float x) { float r; asm("tanh.approx.f32 %0, %1;" : "=f"(r) : "f"(x)); return r; }
__device__ __forceinline__ float rsq(float x) { float r; asm("rsqrt.approx.ftz.f32 %0, %1;" : "=f"(r) : "f"(x)); return r; }
__device__ __forceinline__ float ex2(float x) { float r; asm("ex2.approx.ftz.f32 %0, %1;" : "=f"(r) : "f"(x)); return r; }

__device__ __forceinline__ uint32_t ld_relaxed(const uint32_t* p) {
    uint32_t v;
    asm volatile("ld.relaxed.gpu.global.u32 %0, [%1];" : "=r"(v) : "l"(p) : "memory");
    return v;
}
__device__ __forceinline__ uint32_t clock32() { uint32_t c; asm volatile("mov.u32 %0, %%clock;" : "=r"(c)::"memory"); return c; }
__device__ __forceinline__ void spin(uint32_t clks) {
    const uint32_t t0 = clock32();
    while (clock32() - t0 < clks) {}
}
__device__ __forceinline__ void flag_wait(const uint32_t* p, uint32_t e, bool mine) {
#pragma unroll 1
    for (int i = 0; i < (1 << 19); i++) {
        if (mine) mine = ld_relaxed(p) != e;
        if (!__any_sync(~0u, mine)) break;
        if (BACKOFF) spin(BACKOFF);
    }
    asm volatile("fence.acquire.gpu;" ::: "memory");
    fence_async_global();
}
__device__ __forceinline__ void st_data(void* p, uint32_t x, uint32_t y, uint32_t z, uint32_t w) {
    asm volatile("st.relaxed.gpu.global.v4.b32 [%0], {%1,%2,%3,%4};" ::"l"(p), "r"(x), "r"(y), "r"(z), "r"(w) : "memory");
}
template <int STRIDE, int N>
__device__ __forceinline__ void ld_data(uint4 (&v)[N], const unsigned char* p) {
    int it = 0;
    bool again;
#pragma unroll 1
    do {
        uint32_t m = 0;
#pragma unroll
        for (int i = 0; i < N; i++)
            asm volatile("ld.relaxed.gpu.global.v4.b32 {%0,%1,%2,%3}, [%4];" : "=r"(v[i].x), "=r"(v[i].y), "=r"(v[i].z), "=r"(v[i].w) : "l"(p + i * STRIDE) : "memory");
#pragma unroll
        for (int i = 0; i < N; i++) m = __vimax3_u32(__vimax3_u32(v[i].x, v[i].y, v[i].z), v[i].w, m);
        again = __any_sync(~0u, m == ~0u) && ++it < (1 << 16);
    } while (again);
}
__device__ __forceinline__ uint32_t ld_epoch() { return ld_relaxed(&g_epoch[blockIdx.x * FS]) + 1; }
__device__ __forceinline__ void flag_set(uint32_t* p, uint32_t e) { asm volatile("st.release.gpu.global.u32 [%0], %1;" ::"l"(p), "r"(e) : "memory"); }

__device__ __forceinline__ uint32_t desc_lo(uint32_t addr) { return ((addr & 0x3FFFF) >> 4) | 0x10000u; }
__device__ __forceinline__ uint64_t mkdesc(uint32_t lo) { return (uint64_t)lo | (0x40000040ull << 32); }
__device__ __forceinline__ void wg_fence() { asm volatile("wgmma.fence.sync.aligned;" ::: "memory"); }
__device__ __forceinline__ void wg_commit() { asm volatile("wgmma.commit_group.sync.aligned;" ::: "memory"); }
template <int N> __device__ __forceinline__ void wg_wait() { asm volatile("wgmma.wait_group.sync.aligned %0;" ::"n"(N) : "memory"); }
template <int N> __device__ __forceinline__ void pin(float (&d)[N]) {
#pragma unroll
    for (int i = 0; i < N; i++) asm volatile("" : "+f"(d[i])::"memory");
}
template <int N> __device__ __forceinline__ void pin(uint32_t (&d)[N]) {
#pragma unroll
    for (int i = 0; i < N; i++) asm volatile("" : "+r"(d[i])::"memory");
}

template <typename Tp, int N> __device__ __forceinline__ void zero(Tp (&d)[N]) {
#pragma unroll
    for (int i = 0; i < N; i++) d[i] = 0;
    pin(d);
}

#define F4(d, i) "+f"(d[i]), "+f"(d[i + 1]), "+f"(d[i + 2]), "+f"(d[i + 3])
#define F16(d, i) F4(d, i), F4(d, i + 4), F4(d, i + 8), F4(d, i + 12)

__device__ __forceinline__ void mma16(float (&d)[4], const uint32_t* a, uint32_t b0, uint32_t b1) {
    asm("mma.sync.aligned.m16n8k16.row.col.f32.bf16.bf16.f32 {%0,%1,%2,%3}, {%4,%5,%6,%7}, {%8,%9}, {%0,%1,%2,%3};"
        : F4(d, 0) : "r"(a[0]), "r"(a[1]), "r"(a[2]), "r"(a[3]), "r"(b0), "r"(b1));
}
template <int N>
__device__ __forceinline__ float row_sum(const uint32_t* x, uint32_t ones = 0x3F803F80u) {
    float c[4] = {};
#pragma unroll
    for (int i = 0; i < N; i += 4) mma16(c, x + i, ones, ones);
    return c[0] + c[2];
}
template <int N>
__device__ __forceinline__ float row_sumsq(const uint32_t* x, int lane) {
    float c0[4] = {}, c1[4] = {};
#pragma unroll
    for (int i = 0; i < N; i += 4) {
        mma16(c0, x + i, x[i], x[i + 2]);
        mma16(c1, x + i, x[i + 1], x[i + 3]);
    }
    return (lane & 4) ? c0[1] + c1[3] : c0[0] + c1[2];
}
__device__ __forceinline__ void mma_sp(float (&d)[32], const uint32_t* a, uint64_t b, uint32_t meta, int acc) {
    asm volatile("{.reg .pred p; setp.ne.b32 p, %38, 0;\n"
                 "wgmma.mma_async.sp.sync.aligned.m64n64k32.f32.bf16.bf16 {%0,%1,%2,%3,%4,%5,%6,%7,%8,%9,%10,%11,%12,%13,%14,%15,%16,%17,%18,%19,%20,%21,%22,%23,%24,%25,%26,%27,%28,%29,%30,%31}, "
                 "{%32,%33,%34,%35}, %36, %37, 0, p, 1, 1, 1;}\n"
                 : F16(d, 0), F16(d, 16) : "r"(a[0]), "r"(a[1]), "r"(a[2]), "r"(a[3]), "l"(b), "r"(meta), "r"(acc));
}
__device__ __forceinline__ void mma_qk(float (&d)[32], uint32_t a0, uint32_t a1, uint32_t a2, uint32_t a3, uint64_t b, int acc) {
    asm volatile("{.reg .pred p; setp.ne.b32 p, %37, 0;\n"
                 "wgmma.mma_async.sync.aligned.m64n64k16.f32.bf16.bf16 {%0,%1,%2,%3,%4,%5,%6,%7,%8,%9,%10,%11,%12,%13,%14,%15,%16,%17,%18,%19,%20,%21,%22,%23,%24,%25,%26,%27,%28,%29,%30,%31}, "
                 "{%32,%33,%34,%35}, %36, p, 1, 1, 0;}\n"
                 : F16(d, 0), F16(d, 16) : "r"(a0), "r"(a1), "r"(a2), "r"(a3), "l"(b), "r"(acc));
}
__device__ __forceinline__ void mma_pv(float (&d)[36], uint32_t a0, uint32_t a1, uint32_t a2, uint32_t a3, uint64_t b) {
    asm volatile("wgmma.mma_async.sync.aligned.m64n72k16.f32.bf16.bf16 {%0,%1,%2,%3,%4,%5,%6,%7,%8,%9,%10,%11,%12,%13,%14,%15,%16,%17,%18,%19,%20,%21,%22,%23,%24,%25,%26,%27,%28,%29,%30,%31,%32,%33,%34,%35}, "
                 "{%36,%37,%38,%39}, %40, 1, 1, 1, 1;\n"
                 : F16(d, 0), F16(d, 16), F4(d, 32) : "r"(a0), "r"(a1), "r"(a2), "r"(a3), "l"(b));
}

__device__ __forceinline__ uint32_t load_code(int n, int r, int w) {
    const int tile = 2 * r + w;
    int m, col, row;
    if (n < 16 || n >= 40) {
        const int k = n < 16 ? n : n - 40;
        m = n < 16 ? 0 : 6;
        if (k < 8) { col = 4 * tile + (k >> 1); row = n < 16 ? (k & 1) : (k & 1) ^ r; }
        else { m++; col = k < 12 ? tile ^ 2 : tile; row = 2 * (tile ^ (k & 1)) + ((k >> 1) & 1); }
    } else if (n < 32) {
        const int k = n - 16;
        m = 2;
        if (k < 4) { col = tile + ((k & 1) ? 8 : 4); row = (k >> 1) ^ r; }
        else { col = tile; row = (k & 1) ^ r; }
    } else if (n < 34) { m = 3; col = tile; row = n - 32; }
    else if (n < 38) { const int k = n - 34; m = 4; col = tile + 4 * (k & 1); row = (k >> 1) ^ r; }
    else { m = 5; col = tile; row = (n & 1) ^ r; }
    return m | (col << 4) | (row << (m ? 11 : 10));
}

__global__ void __cluster_dims__(2, 1, 1) __launch_bounds__(NTHREADS, 1)
conformer_kernel(const __grid_constant__ Params p) {
    extern __shared__ __align__(1024) unsigned char smem_raw[];
    const uint32_t sb = smem_u32(smem_raw);
    const uint32_t bars = sb + OFF_BARS;
    const int tid = threadIdx.x;
    const int lane = tid & 31;
    const int warp = __shfl_sync(~0u, tid >> 5, 0);
    const int r = blockIdx.x & 1;
    const int pair = blockIdx.x >> 1;
    const int b = pair >> 5, pt = pair & 31;
    const int ah = pt >> 3, qt = (pt & 7) * 2 + r;
    const int abh = b * 4 + ah;

    TG(30);
    TSINIT();
    TS(0);
    const uint32_t P = sb + OFF_P, H = sb + OFF_H;
    if (warp == 11) {
        if (lane == 0) {
#pragma unroll
            for (int i = 0; i < 2 * NSLOT; i++) mbar_init(bars + (B_FULL + i) * 8, 1);
            asm volatile("fence.mbarrier_init.release.cluster;" ::: "memory");
            fence_async_smem();
        }
        __syncwarp();
#pragma unroll
        for (int i = 0; i < 2 * NFIRST; i++)
            ring_load(sb + OFF_RING + ((i & 1) * NSLOT + (i >> 1)) * SLOT, &p.tm[0], 64 * (8 * r + 4 * (i & 1) + (i >> 2)), 4 * ((i >> 1) & 1),
                      bars + (B_FULL + (i & 1) * NSLOT + (i >> 1)) * 8);
        bar_arrive(13, 96);
        cluster_arrive();
    }

    if (warp >= 8) {
        asm volatile("setmaxnreg.dec.sync.aligned.u32 48;");
        if (warp >= 12) {
            cluster_arrive();
            cluster_wait();
            const int ut = tid & 127;
            const uint32_t target = ld_epoch() * 64;
            auto reset_done = [&](int k) {
                bar_sync(11, 128);
                if (ut == 0) {
                    asm volatile("red.release.gpu.global.add.u32 [%0], 1;" ::"l"(&g_reset[(2 * b + k) * 32]) : "memory");
#pragma unroll 1
                    for (int i = 0; i < (1 << 20) && ld_relaxed(&g_reset[(2 * b + k) * 32]) != target; i++) __nanosleep(100);
                    asm volatile("fence.acquire.gpu;" ::: "memory");
                    mbar_arrive(bars + (B_RST + k) * 8);
                }
                __syncwarp();
                TS(13 + k);
            };
#pragma unroll
            for (int i = 0; i < 4; i++) {
                unsigned char* g = g_kvq + (size_t)((b * 4 + 2 * r + (i >> 1)) * 1024 + pt * 32) * 128 + (i & 1) * 2048 + ut * 16;
                st_data(g + 2097152, ~0u, ~0u, ~0u, ~0u);
                if (pt < 8) st_data(g, ~0u, ~0u, ~0u, ~0u);
            }
            reset_done(0);
            bar_sync(6, 384);
#pragma unroll
            for (int i = 0; i < 4; i++) {
                st_data(g_o + (size_t)(b * 128 + qt * 8 + 2 * i + (ut >> 6)) * 4096 + ah * 1024 + (ut & 63) * 16, ~0u, ~0u, ~0u, ~0u);
                if (i < 2) st_data(&g_halo[(pair * 4 + 2 * r + i) * 128 + ut], ~0u, ~0u, ~0u, ~0u);
            }
            reset_done(1);
            const int side = warp & 1, wg = (warp >> 1) & 1, np = side ? pt + 1 : pt - 1;
            const unsigned char* src = reinterpret_cast<const unsigned char*>(&g_halo[(((b * 32 + np) * 4 + 2 * r + wg) * 2 + (side ^ 1)) * 64 + lane]);
            const uint32_t dst = H + 16384 + wg * GCH + side * 5120 + (lane & 7) * 128 + (((lane >> 3) ^ (lane & 7)) << 4);
            uint4 hv[2] = {make_uint4(0, 0, 0, 0), make_uint4(0, 0, 0, 0)};
            bar_sync(8 + wg, 192);
            if (np >= 0 && np < 32) {
                spin(HDELAY);
                ld_data<512>(hv, src);
            }
            stsm4(dst, hv[0].x, hv[0].y, hv[0].z, hv[0].w);
            stsm4(dst ^ 64, hv[1].x, hv[1].y, hv[1].z, hv[1].w);
            __syncwarp();
            if (lane == 0) mbar_arrive(bars + (B_HALO + (warp & 3)) * 8);
            TS(4);
        } else if (warp < 10) {
            const int w = warp - 8;
            const uint32_t ring = sb + OFF_RING + w * NSLOT * SLOT;
            const uint32_t full = bars + (B_FULL + w * NSLOT) * 8;
            cluster_arrive();
            bar_sync(13, 96);
            TS(1);
#pragma unroll
            for (int n = NFIRST; n < NSLOT; n++) {
                if (n == NFIRST + 1) bar_sync(12, 64);
                ring_load(ring + n * SLOT, &p.tm[0], 64 * (8 * r + 4 * w + (n >> 1)), 4 * (n & 1), full + n * 8);
            }
            TS(2);
            const uint32_t code = load_code(lane, r, w) | (load_code(lane + 32, r, w) << 16);
            cluster_wait();
            uint32_t s = 0, ph = 0;
            int n = NSLOT;
#pragma unroll 1
            for (int seg = 0; seg < 2; seg++) {
#pragma unroll 1
                for (; n < (seg == 0 ? 22 : NLOADS); n++) {
                    const uint32_t c = __shfl_sync(~0u, code, n) >> (n & 32 ? 16 : 0);
                    const CUtensorMap* tm = &p.tm[c & 15];
                    const uint32_t col = (c & 0xf0) * 4, row = (c & 0xff00) >> 8, dst = ring + s * SLOT;
                    mbar_wait(full + (B_EMPTY - B_FULL) * 8 + s * 8, ph + (((uint32_t)(size_t)tm | col | row | dst) & p.zero));
                    ring_load(dst, tm, col, row, full + s * 8);
                    if (++s == NSLOT) { s = 0; ph ^= 1; }
                }
                if (seg == 1) break;
                const uint32_t epoch = ld_epoch();
                const uint32_t rdy = bars + (B_RDY + 3 * w) * 8, prdy = mapa(rdy, r ^ 1);
                const int odd = r ^ w;
                const uint32_t* flags = g_flag_kv + (abh * 32 + lane) * KFS;
                auto kv_load = [&](uint32_t sl, int isv, int i) {
                    ring_load_both(ring + sl * SLOT, &p.tm[8], (isv * 64 + abh * 8 + 2 * i + w) * 128, full + sl * 8);
                };
#pragma unroll 1
                for (int i = 0; i < 2; i++) {
                    if (lane < 3 + i) {
                        const uint32_t sl = i ? lane : lane + 2;
                        mbar_wait(full + (B_EMPTY - B_FULL + sl) * 8, i ^ 1);
                        mbar_arrive_tx(full + sl * 8, i ? SLOT : 0);
                    }
                    __syncwarp();
                }
                if (lane == 0) mbar_arrive_peer(prdy);
                bar_sync(14, 96);
                spin(KDELAY);
                mbar_wait(rdy, 0);
                flag_wait(flags, epoch, (lane >> 2) == 2 * odd + w);
                TSW(5 + 2 * odd);
                kv_load(odd ^ 1, odd ^ 1, odd);
                flag_wait(flags, epoch, (lane >> 2) == 2 * odd + w + 4);
                mbar_wait(full + (odd ^ 1) * 8, 1);
                kv_load(2 + odd, odd, 2 - odd);
#pragma unroll 1
                for (int i = 0; i < 3; i++) {
                    const uint32_t sl = i ? i - 1 : 4, bo = i == 2 ? 16 : 8;
                    mbar_wait(full + (B_EMPTY - B_FULL + sl) * 8, i != 0);
                    if (lane == 0) mbar_arrive_tx(full + sl * 8, SLOT);
                    if ((i & 1) != odd) {
                        mbar_wait(rdy + bo, 0);
                        kv_load(sl, i != 0, 2 + odd);
                    } else if (lane == 0) mbar_arrive_peer(prdy + bo);
                    __syncwarp();
                }
                n = 32; s = 2; ph = 1;
            }
        } else if (warp == 10) {
            if (lane == 0) {
#pragma unroll
                for (int i = B_EMPTY; i < NBARS; i++) mbar_init(bars + i * 8, i < B_XA ? 4 : 1);
#pragma unroll
                for (int i = B_XA; i <= B_SR; i++) mbar_arrive_tx(bars + i * 8, i < B_XB ? 512 : ((i >= B_INB && i < B_SR) ? 4096 : 8192));
                asm volatile("fence.mbarrier_init.release.cluster;" ::: "memory");
                fence_async_smem();
            }
            __syncwarp();
            cluster_arrive();
            cluster_wait();
        } else {
            const uint32_t kb = (lane < 2 || lane > 5) ? 4096 : (lane == 2 ? 3072 : (lane == 4 ? 2048 : 1024));
            const char* pf = p.w[lane & 7] + blockIdx.x * kb;
            cluster_wait();
            if (lane < PF0) prefetch_l2(pf, kb);
            mbar_wait(bars + B_FULL * 8, 0);
            if (lane >= PF0 && lane < 3) prefetch_l2(pf, kb);
            if (lane >= 1 && lane < 9) asm volatile("prefetch.tensormap [%0];" ::"l"(&p.tm[lane]) : "memory");
            mbar_wait(bars + (B_FULL + 1) * 8, 1);
            if (lane > 2 && lane < 8) prefetch_l2(pf, kb);
            if (lane == 8 && blockIdx.x < 15) prefetch_l2(p.dw + blockIdx.x * 256, 512);
            const uint32_t epoch = ld_epoch();
            bar_sync(4, 288);
            if (lane < 16) flag_set(&g_flag_kv[((b * 4 + 2 * r + (lane >> 3)) * 32 + pt) * KFS + (lane & 7)], epoch);
            __syncwarp();
            bar_arrive(14, 96);
            TSW(8);
        }
        TSDUMP();
        return;
    }

    const int w = warp >> 2, wq = warp & 3;
    const int tile = 2 * r + w;
    const int wt = tid & 127;
    const int c4 = lane & 3;
    const int trow = pt * 32 + 8 * wq;
    uint32_t xr[8];
    uint32_t a[32];
    const char* xrow = reinterpret_cast<const char*>(p.x) + (b * T_ + trow + (lane >> 2)) * 512;
    zero(a);
    if (trow < T_) {
        const char* src = xrow + c4 * 16 + p.zero;
#pragma unroll
        for (int i = 0; i < 8; i++)
            asm volatile("ld.global.nc.v4.b32 {%0,%1,%2,%3}, [%4];" : "=r"(a[4 * i]), "=r"(a[4 * i + 1]), "=r"(a[4 * i + 2]), "=r"(a[4 * i + 3]) : "l"(src + 64 * i));
    }
    cluster_arrive();
    asm volatile("setmaxnreg.inc.sync.aligned.u32 208;");
    const uint32_t rbase = sb + OFF_RING + w * NSLOT * SLOT, fbar = bars + (B_FULL + w * NSLOT) * 8;
    const uint32_t rdesc = desc_lo(rbase);
    auto acq = [&](int n) { mbar_wait(fbar + (n % NSLOT) * 8, (n / NSLOT) & 1); };
    auto rel = [&](int n) { if (lane == 0) mbar_arrive(fbar + (B_EMPTY - B_FULL + n % NSLOT) * 8); };
    const uint32_t foff = (lane & 7) * 128 + (((lane >> 3) ^ (lane & 7)) << 4);
    float v[16];
    const uint32_t xown = __shfl_sync(~0u, P + wt * 16 + tile * 4096, lane), xrem = __shfl_sync(~0u, P + wt * 16 + (r ^ 1) * 8192, lane);
    const uint32_t sbuf = __shfl_sync(~0u, sb + OFF_MISC + 1024 + (8 * wq + (lane >> 2)) * 32, lane);
    const uint32_t sown = __shfl_sync(~0u, sbuf + tile * 8, lane);
    const uint32_t peer = __shfl_sync(~0u, mapa(sb, r ^ 1) - sb, lane);
    const uint32_t hbuf = __shfl_sync(~0u, H + w * 4096 + wt * 16, lane);
    const uint32_t meta = __shfl_sync(~0u, 0xEEEE4444u + p.zero, lane);
    cluster_wait();
    TS(56);
    float mean, msq;
    const int mir = wq < 2 ? 7 : 0;
    uint32_t dwr[15] = {};

#pragma unroll
    for (int ph = 0; ph < 5; ph++) {
        uint4 o0, o1;
        if (ph == 0) {
            const uint32_t one = 0x3F803F80u + ((xown | xrem | sbuf | sown | hbuf | foff | rdesc | fbar) & p.zero);
            mean = ((row_sum<8>(a, one) + row_sum<8>(a + 8, one)) + (row_sum<8>(a + 16, one) + row_sum<8>(a + 24, one))) * (1.f / 256.f);
            TS(57);
        } else {
            const uint32_t xa = bars + (B_XA + ph) * 8;
#pragma unroll
            for (int j = 0; j < 8; j++) xr[j] = pack2(v[2 * j], v[2 * j + 1]);
            const float s = row_sum<8>(xr), q = row_sumsq<8>(xr, lane);
            if (ph < 4) {
                sts128(xown, xr[0], xr[1], xr[2], xr[3]);
                sts128(xown + 2048, xr[4], xr[5], xr[6], xr[7]);
            }
            put_sums(sown, sown + peer, s, q, xa + peer, c4 == (lane >> 3));
            bar_sync(10, 256);
            if (ph < 4) {
                o0 = lds128(xown ^ 4096); o1 = lds128((xown ^ 4096) + 2048);
                st_async4(xown + peer, xr[0], xr[1], xr[2], xr[3], xa + (B_XB - B_XA) * 8 + peer);
                st_async4(xown + peer + 2048, xr[4], xr[5], xr[6], xr[7], xa + (B_XB - B_XA) * 8 + peer);
            }
            TS(57 + ph);
            if (ph == 3) acq(0);
            if (ph == 1) acq(16);
            mbar_wait(xa, 0);
            const float4 u0 = lds128f(sbuf), u1 = lds128f(sbuf + 16);
            mean = ((u0.x + u0.z) + (u1.x + u1.z)) * (1.f / 256.f);
            msq = ((u0.y + u0.w) + (u1.y + u1.w)) * (1.f / 256.f);
        }
        if (ph == 4) break;
        const uint32_t mean2 = pack2(mean, mean);
        auto centre = [&](int i, const uint4& u) {
            a[i] = hsub2(u.x, mean2); a[i + 1] = hsub2(u.y, mean2); a[i + 2] = hsub2(u.z, mean2); a[i + 3] = hsub2(u.w, mean2);
        };
        if (ph == 0) {
#pragma unroll
            for (int j = 0; j < 32; j++) a[j] = hsub2(a[j], mean2);
            zero(xr);
            if (trow < T_) {
                const char* src = xrow + tile * 128 + c4 * 4 + (mean2 & p.zero);
#pragma unroll
                for (int j = 0; j < 8; j++) asm volatile("ld.global.nc.b32 %0, [%1];" : "=r"(xr[j]) : "l"(src + 16 * j));
            }
            mean -= blo(mean2);
            msq = __shfl_sync(~0u, row_sumsq<16>(a, lane) + row_sumsq<16>(a + 16, lane), (lane & 28) + (lane >> 3)) * (1.f / 256.f);
            acq(0);
        } else {
#pragma unroll
            for (int j = 0; j < 8; j++) a[j] = hsub2(xr[j], mean2);
            centre(8, o0); centre(12, o1);
        }
        const float rstd = rsq(fmaxf(fmaf(-mean, mean, msq), 0.f) + 1e-5f);
        auto gather_peer = [&]() {
            mbar_wait(bars + (B_XB + ph) * 8, 0);
#pragma unroll
            for (int i = 0; i < 4; i++) centre(16 + 4 * i, lds128(xrem + i * 2048));
        };
        auto sp = [&](float (&d)[32], int n, const uint32_t* af, int flip, int acc) {
            const uint32_t lo = rdesc + p.zero * (ph * 64 + n + 1) + (n % NSLOT) * (SLOT >> 4);
            const uint64_t b0 = mkdesc(lo + flip * 512), b1 = mkdesc(lo + (flip ^ 1) * 512);
            wg_fence();
            mma_sp(d, af, b0, meta, acc);
            mma_sp(d, af + 4, b0 + 256, meta, 1);
            mma_sp(d, af + 8, b1, meta, 1);
            mma_sp(d, af + 12, b1 + 256, meta, 1);
            wg_commit();
        };
        float d0[32], d1[32];

        if (ph == 0 || ph == 3) {
            uint32_t h[32], ho[32];
            const float rs = 0.5f * rstd;
            const uint32_t inb = bars + (B_INB + (ph & 2) + w) * 8;
            bool ready = true;
            const int eager = ph ? EAGER : EAGER - 1;
            auto step = [&](float (&d)[32], int n, const uint32_t* af, int flip, int acc, auto work) {
                if (!ready) acq(n);
                if (((TURN >> n) & 1) && w == 1) bar_sync(7, 256);
                sp(d, n, af, flip, acc);
                if (n > 0 && ((TURN >> (n - 1)) & 1) && w == 0) bar_arrive(7, 256);
                if (n < 15) ready = mbar_test(fbar + ((n + 1) % NSLOT) * 8, ((n + 1) / NSLOT) & 1);
                wg_wait<1>();
                if (n > 0 && !((eager >> (n - 1)) & 1)) rel(n - 1);
                const uint32_t tie = work() & p.zero;
                if ((eager >> n) & 1) {
                    if (p.zero < n + ph + 1) wg_wait<0>();
                    if (lane == 0) mbar_arrive(fbar + (B_EMPTY - B_FULL + n % NSLOT) * 8 + tie);
                }
            };
            auto none = []() { return 0u; };
            const int fl = ph ? w : 0;
            auto fetch = [&](int i) {
                bar_sync(10, 256);
                const uint4 u0 = lds128((hbuf ^ 4096) + (i & 1) * 8192), u1 = lds128((hbuf ^ 4096) + (i & 1) * 8192 + 2048);
                ho[8 * i] = u0.x; ho[8 * i + 1] = u0.y; ho[8 * i + 2] = u0.z; ho[8 * i + 3] = u0.w;
                ho[8 * i + 4] = u1.x; ho[8 * i + 5] = u1.y; ho[8 * i + 6] = u1.z; ho[8 * i + 7] = u1.w;
                return u0.x | u1.x;
            };
            auto act = [&](float (&d)[32], int i) {
                if (i > 0) fetch(i - 1);
                pin(d);
#pragma unroll
                for (int j = 0; j < 8; j++) {
                    const float u0 = (d[4 * j] + d[4 * j + 2]) * rs, u1 = (d[4 * j + 1] + d[4 * j + 3]) * rs;
                    h[8 * i + j] = pack2(fmaf(u0, tanh_fast(u0), u0), fmaf(u1, tanh_fast(u1), u1));
                }
                sts128(hbuf + (i & 1) * 8192, h[8 * i], h[8 * i + 1], h[8 * i + 2], h[8 * i + 3]);
                sts128(hbuf + (i & 1) * 8192 + 2048, h[8 * i + 4], h[8 * i + 5], h[8 * i + 6], h[8 * i + 7]);
                return 0u;
            };
            TS(1 + (ph & 2) * 10);
            step(d0, 0, a, fl, 0, [&]() { if (ph) gather_peer(); return 0u; });
            TS(32);
            step(d0, 1, a + 16, 0, 1, none);
            step(d1, 2, a, fl, 0, [&]() { return act(d0, 0); });
            step(d1, 3, a + 16, 0, 1, none);
            step(d0, 4, a, fl, 0, [&]() { return act(d1, 1); });
            TS(33);
            step(d0, 5, a + 16, 0, 1, none);
            step(d1, 6, a, fl, 0, [&]() { return act(d0, 2); });
            step(d1, 7, a + 16, 0, 1, none);
            step(d0, 8, h, 0, 0, [&]() { act(d1, 3); return fetch(3); });
            TS(2 + (ph & 2) * 10);
            step(d0, 9, ho, 0, 1, none);
            step(d0, 10, h + 16, 0, 1, none);
            step(d0, 11, ho + 16, 0, 1, none);
            uint32_t pk[8];
            auto pack_out = [&]() {
                pin(d0);
#pragma unroll
                for (int j = 0; j < 8; j++) pk[j] = pack2(d0[4 * j] + d0[4 * j + 2], d0[4 * j + 1] + d0[4 * j + 3]);
            };
            auto send = [&](int i) { st_async4(hbuf + 16384 + i * 2048 + peer, pk[4 * i], pk[4 * i + 1], pk[4 * i + 2], pk[4 * i + 3], inb + peer); };
            step(d1, 12, h, 0, 0, [&]() { pack_out(); if (SND != 1) send(0); if (SND == 0) send(1); return 0u; });
            TS(34);
            step(d1, 13, ho, 0, 1, [&]() { if (SND == 1) send(0); if (SND) send(1); return 0u; });
            step(d1, 14, h + 16, 0, 1, none);
            step(d1, 15, ho + 16, 0, 1, none);
            mbar_wait(inb, 0);
#pragma unroll
            for (int i = 0; i < 2; i++) {
                const uint4 u = lds128(hbuf + 16384 + i * 2048);
                const uint32_t p0[4] = {u.x, u.y, u.z, u.w};
#pragma unroll
                for (int j = 0; j < 4; j++) {
                    v[8 * i + 2 * j] = fmaf(0.5f, blo(p0[j]), blo(xr[4 * i + j]));
                    v[8 * i + 2 * j + 1] = fmaf(0.5f, bhi(p0[j]), bhi(xr[4 * i + j]));
                }
            }
            wg_wait<0>();
            pin(d1);
            rel(15);
            TS(3 + (ph & 2) * 10);
#pragma unroll
            for (int j = 0; j < 8; j++) {
                v[2 * j] = fmaf(0.5f, d1[4 * j] + d1[4 * j + 2], v[2 * j]);
                v[2 * j + 1] = fmaf(0.5f, d1[4 * j + 1] + d1[4 * j + 3], v[2 * j + 1]);
            }
#pragma unroll
            for (int i = 0; i < 15; i++) dwr[i] = 0;
            continue;
        }

        auto residual = [&](int n) {
            wg_wait<1>();
            rel(n);
            wg_wait<0>();
            pin(d0);
            rel(n + 1);
#pragma unroll
            for (int j = 0; j < 8; j++) {
                v[2 * j] = d0[4 * j] + d0[4 * j + 2] + blo(xr[j]);
                v[2 * j + 1] = d0[4 * j + 1] + d0[4 * j + 3] + bhi(xr[j]);
            }
        };

        if (ph == 2) {
            TS(39);
            sp(d0, 34, a, w, 0);
            acq(35);
            sp(d1, 35, a, w, 0);
            acq(36); acq(37);
            gather_peer();
            sp(d0, 36, a + 16, 0, 1);
            sp(d1, 37, a + 16, 0, 1);
            wg_wait<2>();
            rel(34);
            if (!(LATE & 1)) rel(35);
            acq(38);
            const float rs = trow < T_ ? 0.5f * rstd : 0.f;
            wg_wait<0>();
            pin(d0); pin(d1);
            if (!(LATE & 2)) { rel(36); rel(37); }
            TS(18);
            uint32_t pk[8];
#pragma unroll
            for (int j = 0; j < 8; j++) {
                const float u0 = (d0[4 * j] + d0[4 * j + 2]) * rs, u1 = (d0[4 * j + 1] + d0[4 * j + 3]) * rs;
                const float t0 = tanh_fast((d1[4 * j] + d1[4 * j + 2]) * rs), t1 = tanh_fast((d1[4 * j + 1] + d1[4 * j + 3]) * rs);
                pk[j] = pack2(fmaf(u0, t0, u0), fmaf(u1, t1, u1));
            }
            if (wq == 0 || wq == 3) {
                uint4* hp = &g_halo[((pair * 4 + tile) * 2 + (wq & 1)) * 64 + lane];
                st_data(hp, pk[0], pk[1], pk[2], pk[3]);
                st_data(hp + 32, pk[4], pk[5], pk[6], pk[7]);
            }
            const uint32_t gs = H + 16384 + w * GCH + wq * 1024;
            stsm4(gs + 1024 + foff, pk[0], pk[1], pk[2], pk[3]);
            stsm4(gs + 1024 + (foff ^ 64), pk[4], pk[5], pk[6], pk[7]);
            bar_sync(8 + w, 192);
            TS(26);
            uint32_t ca[8], cb[8];
            const int e = (wq & 1) * 4;
            const uint32_t lo = ((mir ^ e) * 144) ^ (lane * 4);
            const int dir = mir ? -1024 : 1024;
            const uint32_t gb = H + 16384 + w * GCH + (mir ? 3072 : 2048) + lo, sown_ = H + tile * HCH, so = sown_ + (mir ? 1024 : 2048) + lo;
            auto finish = [&](int i) {
                const uint32_t c = hadd2(ca[i], cb[i]);
                const float h0 = blo(c), h1 = bhi(c);
                sts32((so + (i >> 2) * dir) ^ ((i & 3) * 144), pack2(fmaf(h0, tanh_fast(h0), h0), fmaf(h1, tanh_fast(h1), h1)));
            };
#pragma unroll
            for (int k = 0; k < 26; k++) {
                if (k == 19) {
#pragma unroll
                    for (int i = 0; i < 4; i++) finish(i);
                    fence_async_smem();
                    bar_sync(2 + w, 128);
                    if (wq == 0) peer_copy(mapa(sown_ + 1024, r ^ 1), sown_ + 1024, 2048, mapa(bars + B_SR * 8, r ^ 1));
                    mbar_wait(bars + (B_HALO + 2 * w + (wq >> 1)) * 8, 0);
                    if (LATE & 1) rel(35);
                    if (LATE & 2) { rel(36); rel(37); }
                    TS(27);
                }
                const uint32_t g = lds32((gb + (((k + 1) & 4) ? ((k + 1) >> 3) + (wq & 1) : ((k + 1) >> 3)) * dir) ^ (((k + 1) & 7) * 144));
#pragma unroll
                for (int i = 0; i < 8; i++) {
                    const int tap = k - (i & 3) - 2 * (i & 4);
                    if (tap == 0) ca[i] = hmul2(g, dwr[0]);
                    else if (tap > 0 && tap < 8) ca[i] = hfma2(g, dwr[tap], ca[i]);
                    else if (tap == 8) cb[i] = hmul2(g, dwr[8]);
                    else if (tap > 8 && tap < 15) cb[i] = hfma2(g, dwr[tap], cb[i]);
                }
            }
#pragma unroll
            for (int i = 4; i < 8; i++) finish(i);
            fence_async_smem();
            bar_sync(12 + (warp >> 1), 64);
            if (wq == 0 || wq == 3) peer_copy(mapa(sown_ + wq * 1024, r ^ 1), sown_ + wq * 1024, 1024, mapa(bars + B_SR * 8, r ^ 1));
            bar_sync(10, 256);
            TS(19);
            auto frags = [&](int i, int half) {
                const uint32_t src = H + 2 * half * HCH + wq * 1024;
#pragma unroll
                for (int k = 0; k < 4; k++) ldsm4(src + (k >> 1) * HCH + (foff ^ ((k & 1) * 64)), a[i + 4 * k], a[i + 4 * k + 1], a[i + 4 * k + 2], a[i + 4 * k + 3]);
            };
            frags(0, r);
            sp(d0, 38, a, 0, 0);
            acq(39);
            mbar_wait(bars + B_SR * 8, 0);
            frags(16, r ^ 1);
            sp(d0, 39, a + 16, 0, 1);
            residual(38);
            TS(20);
            continue;
        }

        {
            TS(11);
            const uint32_t stg = H + warp * 2048;
            unsigned char* g = g_kvq + (size_t)((b * 4 + tile) * 1024 + trow) * 128 + lane * 16;
            auto put = [&](float (&d)[32], int i) {
                pin(d);
                uint32_t pk[8];
#pragma unroll
                for (int j = 0; j < 8; j++) pk[j] = pack2((d[4 * j] + d[4 * j + 2]) * rstd, (d[4 * j + 1] + d[4 * j + 3]) * rstd);
                if (i == 2) {
                    st_data(g + 2097152, pk[0], pk[1], pk[2], pk[3]);
                    st_data(g + 2097152 + 512, pk[4], pk[5], pk[6], pk[7]);
                    return;
                }
                stsm4(stg + i * 1024 + foff, pk[0], pk[1], pk[2], pk[3]);
                stsm4(stg + i * 1024 + (foff ^ 64), pk[4], pk[5], pk[6], pk[7]);
                __syncwarp();
                const uint4 u0 = lds128(stg + i * 1024 + lane * 16), u1 = lds128(stg + i * 1024 + 512 + lane * 16);
                st_data(g + i * 1048576, u0.x, u0.y, u0.z, u0.w); st_data(g + i * 1048576 + 512, u1.x, u1.y, u1.z, u1.w);
            };
            sp(d0, 16, a, w, 0);
            acq(17);
            sp(d1, 17, a, w, 0);
            mbar_wait(bars + B_RST * 8, 0);
            gather_peer();
            acq(18);
            sp(d0, 18, a + 16, 0, 1);
            wg_wait<1>();
            rel(16); rel(17);
            acq(19);
            sp(d1, 19, a + 16, 0, 1);
            wg_wait<1>();
            rel(18);
            put(d0, 0);
            wg_wait<0>();
            rel(19);
            TS(37);
            put(d1, 1);
            bar_arrive(4, 288);
            TS(38);
            acq(20);
            sp(d0, 20, a, w, 0);
            acq(21);
            sp(d0, 21, a + 16, 0, 1);
            acq(22); acq(23);
            rel(22); rel(23);
            wg_wait<0>();
            rel(20); rel(21);
            put(d0, 2);
            TS(12);
        }

        {
            constexpr float CS = 0.125f * 1.4426950408889634f;
            float sa[32], sb2[32], o[36];
            uint32_t pa[16], pb[16], q[16];
            float n0 = INFINITY, n1 = INFINITY;
            zero(o); zero(pa); zero(pb); zero(sb2);
            const uint32_t ones = sb + OFF_MISC + 2048;
            { const uint32_t c = w ? 0u : 0x3F803F80u; sts128(ones + tid * 16, c, c, c, c); }
            fence_async_smem();
            bar_sync(10, 256);
            const uint32_t vdesc = rdesc + ((((ones - rbase) >> 4) - 1) << 16);
            auto qk_issue = [&](float (&s)[32], uint32_t lo) {
                const uint64_t kd = mkdesc(lo);
                wg_fence();
#pragma unroll
                for (int k = 0; k < 4; k++) mma_qk(s, q[4 * k], q[4 * k + 1], q[4 * k + 2], q[4 * k + 3], kd + 2 * k, k != 0);
                wg_commit();
            };
            auto both_issue = [&](float (&s)[32], uint32_t klo, uint32_t (&pp)[16], uint32_t vlo) {
                const uint64_t kd = mkdesc(klo), vd = mkdesc(vlo);
                wg_fence();
#pragma unroll
                for (int k = 0; k < 4; k++) {
                    mma_pv(o, pp[4 * k], pp[4 * k + 1], pp[4 * k + 2], pp[4 * k + 3], vd - k * (128 * 65535));
                    mma_qk(s, q[4 * k], q[4 * k + 1], q[4 * k + 2], q[4 * k + 3], kd + 2 * k, k != 0);
                }
                wg_commit();
            };
            auto new_max = [&](float (&s)[32], int nj, float& x0, float& x1) {
                x0 = s[0]; x1 = s[2];
#pragma unroll
                for (int j = 0; j < nj; j++) {
                    x0 = fmaxf(x0, fmaxf(s[4 * j], s[4 * j + 1]));
                    x1 = fmaxf(x1, fmaxf(s[4 * j + 2], s[4 * j + 3]));
                }
                x0 = fmaxf(x0, __shfl_xor_sync(~0u, x0, 1)); x1 = fmaxf(x1, __shfl_xor_sync(~0u, x1, 1));
                x0 = fmaxf(x0, __shfl_xor_sync(~0u, x0, 2)); x1 = fmaxf(x1, __shfl_xor_sync(~0u, x1, 2));
                x0 = fminf(n0, fmaf(x0, -CS, -20.f)); x1 = fminf(n1, fmaf(x1, -CS, -20.f));
            };
            auto probs = [&](float (&s)[32], uint32_t (&pp)[16], bool ready, bool tail, auto wait) {
                uint32_t any = 0;
#pragma unroll
                for (int i = 0; i < 16; i++) {
                    pp[i] = pack2(ex2(fmaf(s[2 * i], CS, (i & 1) ? n1 : n0)), ex2(fmaf(s[2 * i + 1], CS, (i & 1) ? n1 : n0)));
                    any |= pp[i];
                }
                wg_wait<0>();
                pin(sa); pin(sb2); pin(o); pin(pa); pin(pb);
                if (__builtin_expect(__any_sync(~0u, (any & 0x40004000u) || !ready), 0)) {
                    wait();
                    if (__any_sync(~0u, any & 0x40004000u)) {
                        if (tail) {
#pragma unroll
                            for (int i = 20; i < 32; i++) s[i] = -INFINITY;
                        }
                        float x0, x1;
                        new_max(s, 8, x0, x1);
                        const float sc0 = ex2(x0 - n0), sc1 = ex2(x1 - n1);
                        n0 = x0; n1 = x1;
#pragma unroll
                        for (int j = 0; j < 9; j++) { o[4 * j] *= sc0; o[4 * j + 1] *= sc0; o[4 * j + 2] *= sc1; o[4 * j + 3] *= sc1; }
#pragma unroll
                        for (int i = 0; i < 16; i++)
                            pp[i] = pack2(ex2(fmaf(s[2 * i], CS, (i & 1) ? n1 : n0)), ex2(fmaf(s[2 * i + 1], CS, (i & 1) ? n1 : n0)));
                    }
                }
            };
            {
                uint4 u[4];
                const unsigned char* src = g_kvq + 2097152 + (size_t)(abh * 1024 + qt * 64 + wq * 16) * 128 + lane * 16;
                uint4 kv[8];
                acq(24);
                spin(QGATE);
                ld_data<2048>(kv, g_kvq + (size_t)(abh * 1024 + w * 128) * 128 + wt * 16);
#pragma unroll
                for (int i = 0; i < 8; i++) sts128(rbase + (24 % NSLOT) * SLOT + i * 2048 + wt * 16, kv[i].x, kv[i].y, kv[i].z, kv[i].w);
                TS(42);
                ld_data<512>(u, src);
                fence_async_smem();
#pragma unroll
                for (int k = 0; k < 2; k++) {
                    q[8 * k] = u[k].x; q[8 * k + 1] = u[k + 2].x; q[8 * k + 2] = u[k].y; q[8 * k + 3] = u[k + 2].y;
                    q[8 * k + 4] = u[k].z; q[8 * k + 5] = u[k + 2].z; q[8 * k + 6] = u[k].w; q[8 * k + 7] = u[k + 2].w;
                }
                pin(q);
            }
            TS(40);
            bar_sync(2 + w, 128);
            TS(13);
            qk_issue(sa, rdesc + (24 % NSLOT) * (SLOT >> 4));
            wg_wait<0>();
            pin(sa);
            {
                float x0, x1;
                new_max(sa, NJ0, x0, x1);
                n0 = x0; n1 = x1;
            }
            bar_arrive(6, 384);
            uint32_t vd = vdesc - (SLOT >> 4) * 65535u, kd = rdesc, vb = fbar + 8, kb = fbar;
            uint32_t vlast = vdesc - 4 * (SLOT >> 4) * 65535u, klast = rdesc + 4 * (SLOT >> 4) + 512;
            uint32_t kprev = fbar + 32, vprev = bars + (B_SINK - (B_EMPTY - B_FULL)) * 8;
#pragma unroll 1
            for (int it = 0; it < 4; it++) {
                both_issue(sb2, klast, pb, vlast);
                probs(sa, pa, mbar_test(vb, it < 2) & mbar_test(kb, it < 3), false, [&]() { mbar_wait(vb, it < 2); mbar_wait(kb, it < 3); });
                TS(41 + it * 4);
                if (lane == 0) mbar_arrive(kprev + (B_EMPTY - B_FULL) * 8);
                if (lane == 0) mbar_arrive(vprev + (B_EMPTY - B_FULL) * 8);
                both_issue(sa, kd, pa, vd);
                const int dv = it == 0 ? 2 : (it == 1 ? -3 : 1);
                kprev = kb; vprev = vb; vlast = vd - 512 * 65535u; klast = kd + 512;
                vd -= dv * (SLOT >> 4) * 65535u; vb += dv * 8;
                kd += (it == 2 ? -3 : 2) * (SLOT >> 4); kb = it == 2 ? vb : kb + 16;
                probs(sb2, pb, true, it == 3 && w == 1, []() {});
                TS(43 + it * 4);
            }
            wg_fence();
#pragma unroll
            for (int k = 0; k < 4; k++)
                mma_pv(o, pb[4 * k], pb[4 * k + 1], pb[4 * k + 2], pb[4 * k + 3], mkdesc(vlast - k * (128 * 65535) + (k > 1 ? w * ((k - 1) << 22) : 0)));
            wg_commit();
            const int row = wq * 16 + (lane >> 2);
            const uint32_t ml = sb + OFF_MISC;
            mbar_wait(bars + (B_RST + 1) * 8, 0);
            wg_wait<0>();
            pin(o); pin(pb); pin(sa); pin(sb2);
            if (!(LATE & 4)) rel(31);
            const float l0 = o[32], l1 = o[34];
            if (c4 == 0) { sts64f(ml + w * 512 + row * 8, n0, l0); sts64f(ml + w * 512 + row * 8 + 64, n1, l1); }
            TS(14);
            float mine[16];
#pragma unroll
            for (int j = 0; j < 4; j++) {
                if (w == 0) sts128f(H + j * 2048 + wt * 16, o[16 + 4 * j], o[17 + 4 * j], o[18 + 4 * j], o[19 + 4 * j]);
                else sts128f(H + 8192 + j * 2048 + wt * 16, o[4 * j], o[4 * j + 1], o[4 * j + 2], o[4 * j + 3]);
            }
#pragma unroll
            for (int i = 0; i < 16; i++) mine[i] = w == 0 ? o[i] : o[16 + i];
            bar_sync(10, 256);
            const float2 u0 = lds64f(ml + (w ^ 1) * 512 + row * 8), u1 = lds64f(ml + (w ^ 1) * 512 + row * 8 + 64);
            const float x0 = fminf(n0, u0.x), x1 = fminf(n1, u1.x);
            float a0 = ex2(x0 - n0), b0 = ex2(x0 - u0.x), a1 = ex2(x1 - n1), b1 = ex2(x1 - u1.x);
            const float i0 = __fdividef(1.f, fmaf(a0, l0, b0 * u0.y)), i1 = __fdividef(1.f, fmaf(a1, l1, b1 * u1.y));
            a0 *= i0; b0 *= i0; a1 *= i1; b1 *= i1;
            uint32_t pk[8];
#pragma unroll
            for (int j = 0; j < 4; j++) {
                const float4 v = lds128f(H + (w ^ 1) * 8192 + j * 2048 + wt * 16);
                pk[2 * j] = pack2(fmaf(a0, mine[4 * j], b0 * v.x), fmaf(a0, mine[4 * j + 1], b0 * v.y));
                pk[2 * j + 1] = pack2(fmaf(a1, mine[4 * j + 2], b1 * v.z), fmaf(a1, mine[4 * j + 3], b1 * v.w));
            }
            unsigned char* dst = g_o + (size_t)(b * 128 + qt * 8 + 2 * wq) * 4096 + ah * 1024 + w * 512 + lane * 16;
            st_data(dst, pk[0], pk[2], pk[4], pk[6]);
            st_data(dst + 4096, pk[1], pk[3], pk[5], pk[7]);
            if (tid == 0) asm volatile("red.relaxed.gpu.global.add.u32 [%0], 1;" ::"l"(&g_epoch[blockIdx.x * FS]) : "memory");
            TS(15);
        }

        {
            const uint32_t* dp = reinterpret_cast<const uint32_t*>(p.dw + (mir ? 14 * 256 : 0) + tile * 64) + lane;
#pragma unroll
            for (int i = 0; i < 15; i++) asm volatile("ld.global.nc.b32 %0, [%1];" : "=r"(dwr[i]) : "l"(dp + i * (mir ? -128 : 128)));
            acq(32); acq(33); acq(34);
            uint4 u[8];
            ld_data<512>(u, g_o + (size_t)(b * 128 + pt * 4 + wq) * 4096 + lane * 16);
#pragma unroll
            for (int i = 0; i < 8; i++) { a[4 * i] = u[i].x; a[4 * i + 1] = u[i].y; a[4 * i + 2] = u[i].z; a[4 * i + 3] = u[i].w; }
            if (LATE & 4) rel(31);
            TS(16);
            sp(d0, 32, a, 0, 0);
            sp(d0, 33, a + 16, 0, 1);
#pragma unroll
            for (int i = 0; i < 15; i++) dwr[i] = hmul2(dwr[i], 0x3F003F00u);
            residual(32);
            TS(17);
        }
    }

    cluster_arrive();
    TS(24);
    {
        const float rstd = rsq(fmaxf(fmaf(-mean, mean, msq), 0.f) + 1e-5f), nb = -mean * rstd;
#pragma unroll
        for (int j = 0; j < 8; j++) xr[j] = pack2(fmaf(v[2 * j], rstd, nb), fmaf(v[2 * j + 1], rstd, nb));
        const uint32_t stg = P + 16384 + warp * 1024;
        stsm4(stg + foff, xr[0], xr[1], xr[2], xr[3]);
        stsm4(stg + (foff ^ 64), xr[4], xr[5], xr[6], xr[7]);
        __syncwarp();
        const uint32_t src = stg + (lane >> 3) * 128 + (((lane & 7) ^ (lane >> 3)) << 4);
        const uint4 u0 = lds128(src), u1 = lds128((src + 512) ^ 64);
        __nv_bfloat16* dst = p.out + (size_t)(b * T_ + trow + (lane >> 3)) * 256 + tile * 64 + (lane & 7) * 8;
        if (trow < T_) { stg128(dst, u0); stg128(dst + 4 * 256, u1); }
    }
    TS(25);
    TG(31);
    TSDUMP();
    cluster_wait();
}

typedef CUresult (*EncodeFn)(CUtensorMap*, CUtensorMapDataType, cuuint32_t, void*, const cuuint64_t*, const cuuint64_t*,
                             const cuuint32_t*, const cuuint32_t*, CUtensorMapInterleave, CUtensorMapSwizzle,
                             CUtensorMapL2promotion, CUtensorMapFloatOOBfill);

}

extern "C" void kernel_launch(void* const* d_in, const int* in_sizes, int n_in, void* d_out, int out_size) {
    static EncodeFn encode = nullptr;
    if (!encode) {
        void* fn = nullptr;
        cudaDriverEntryPointQueryResult qr;
        cudaGetDriverEntryPoint("cuTensorMapEncodeTiled", &fn, cudaEnableDefault, &qr);
        encode = (EncodeFn)fn;
        cudaFuncSetAttribute(conformer_kernel, cudaFuncAttributeMaxDynamicSharedMemorySize, SMEM_LAUNCH);
    }
    Params p;
    const cuuint32_t ones[5] = {1, 1, 1, 1, 1};
    const int idx[8] = {1, 2, 3, 4, 5, 7, 8, 9};
    const int rows[8] = {256, 1024, 256, 256, 256, 256, 256, 1024};
    const int cols[8] = {1024, 256, 768, 256, 512, 256, 1024, 256};
    for (int i = 0; i < 8; i++) {
        const cuuint64_t pitch = (cuuint64_t)cols[i] * 2;
        const cuuint64_t dims[5] = {(cuuint64_t)cols[i], i ? 2u : 4u, i ? 2u : 4u, i ? 4u : 2u, (cuuint64_t)rows[i] / (i ? 16 : 32)};
        const cuuint64_t strides[4] = {pitch, pitch * 8, pitch * (i ? 2 : 4), pitch * (i ? 16 : 32)};
        const cuuint32_t box[5] = {64, i ? 2u : 4u, i ? 2u : 4u, i ? 4u : 2u, i ? 8u : 4u};
        encode(&p.tm[i], CU_TENSOR_MAP_DATA_TYPE_BFLOAT16, 5, d_in[idx[i]], dims, strides, box, ones, CU_TENSOR_MAP_INTERLEAVE_NONE,
               CU_TENSOR_MAP_SWIZZLE_128B, CU_TENSOR_MAP_L2_PROMOTION_L2_128B, CU_TENSOR_MAP_FLOAT_OOB_FILL_NONE);
        p.w[i] = (const char*)d_in[idx[i]];
    }
    {
        void* kv = nullptr;
        cudaGetSymbolAddress(&kv, g_kvq);
        const cuuint64_t dims[2] = {64, 16384};
        const cuuint64_t strides[1] = {128};
        const cuuint32_t box[2] = {64, 128};
        encode(&p.tm[8], CU_TENSOR_MAP_DATA_TYPE_BFLOAT16, 2, kv, dims, strides, box, ones, CU_TENSOR_MAP_INTERLEAVE_NONE,
               CU_TENSOR_MAP_SWIZZLE_NONE, CU_TENSOR_MAP_L2_PROMOTION_L2_128B, CU_TENSOR_MAP_FLOAT_OOB_FILL_NONE);
    }
    p.x = (const __nv_bfloat16*)d_in[0];
    p.dw = (const __nv_bfloat16*)d_in[6];
    p.out = (__nv_bfloat16*)d_out;
    p.zero = 0;
    conformer_kernel<<<NCTA, NTHREADS, SMEM_LAUNCH>>>(p);
}
```

```cpp
#include <cuda_runtime.h>
#include <cuda_bf16.h>
#include <cuda.h>
#include <stdint.h>

namespace {

constexpr int T_ = 1000;
constexpr int NCTA = 128;
constexpr int NTHREADS = 512;
constexpr int NSLOT = 5;
constexpr int SLOT = 16384;
constexpr int NLOADS = 56;

constexpr uint32_t OFF_RING = 0;
constexpr uint32_t OFF_P = 163840;
constexpr uint32_t OFF_H = 188416;
constexpr uint32_t OFF_MISC = 221184;
constexpr uint32_t OFF_BARS = 229888;
constexpr uint32_t SMEM_BYTES = 230400;
constexpr uint32_t GCH = 6144;
constexpr uint32_t HCH = 4096;

constexpr int B_FULL = 0, B_EMPTY = 10, B_XA = 20  , B_XB = 25  , B_INB = 29  , B_SR = 33,
              B_RST = 34  , B_RDY = 36  , B_SINK = 42, B_HALO = 43  , NBARS = 47;

#define KD2 300u
#define KD3 500u
#define QGATE 500u
#define BACKOFF 0u
#define KFS 8
#define KDELAY 300u
#define NJ0 2
#define HDELAY 200u
#define LATE 2
#define SND 0
#define PF0 1
#define NFIRST 2
#define TWO 1
#define TURN 0x200
#define EAGER 0x0155
constexpr int FS = 8;

struct Scalars {
    const __nv_bfloat16* x;
    const __nv_bfloat16* dw;
    __nv_bfloat16* out;
    uint32_t zero;
};
struct Maps {
    CUtensorMap tm[9];
    const char* w[8];
};

__device__ __align__(1024) unsigned char g_kvq[3 * 8 * 1024 * 128];
__device__ __align__(1024) unsigned char g_o[2 * 128 * 4096];
__device__ uint4 g_halo[64 * 4 * 2 * 64];
__device__ __align__(128) uint32_t g_flag_kv[8 * 32 * KFS];
__device__ uint32_t g_reset[4 * 32];
__device__ uint32_t g_epoch[NCTA * FS];

#define TS(i) do { } while (0)
#define TSW(i) do { } while (0)
#define TG(i) do { } while (0)
#define TSINIT() do { } while (0)
#define TSDUMP() do { } while (0)
constexpr uint32_t SMEM_LAUNCH = SMEM_BYTES;

__device__ __forceinline__ uint32_t smem_u32(const void* p) { return (uint32_t)__cvta_generic_to_shared(p); }
__device__ __forceinline__ void mbar_init(uint32_t b, uint32_t c) { asm volatile("mbarrier.init.shared::cta.b64 [%0], %1;" ::"r"(b), "r"(c) : "memory"); }
__device__ __forceinline__ void mbar_arrive(uint32_t b) { asm volatile("mbarrier.arrive.shared::cta.b64 _, [%0];" ::"r"(b) : "memory"); }
__device__ __forceinline__ void mbar_arrive_tx(uint32_t b, uint32_t tx) { asm volatile("mbarrier.arrive.expect_tx.shared::cta.b64 _, [%0], %1;" ::"r"(b), "r"(tx) : "memory"); }
__device__ __forceinline__ void mbar_wait(uint32_t b, uint32_t ph) {
    asm volatile("{\n.reg .pred p, q;\n.reg .u32 c;\nmov.u32 c, 0;\n"
                 "MW_LOOP:\n.pragma \"nounroll\";\n"
                 "mbarrier.try_wait.parity.shared::cta.b64 p, [%0], %1;\n"
                 "add.u32 c, c, 1;\nsetp.lt.u32 q, c, 65536;\nnot.pred p, p;\nand.pred p, p, q;\n@p bra MW_LOOP;\n}"
                 ::"r"(b), "r"(ph) : "memory");
}
__device__ __forceinline__ bool mbar_test(uint32_t b, uint32_t ph) {
    uint32_t ok;
    asm volatile("{\n.reg .pred p;\nmbarrier.test_wait.parity.shared::cta.b64 p, [%1], %2;\nselp.u32 %0, 1, 0, p;\n}" : "=r"(ok) : "r"(b), "r"(ph) : "memory");
    return ok;
}
__device__ __forceinline__ uint32_t mapa(uint32_t a, uint32_t r) { uint32_t o; asm("mapa.shared::cluster.u32 %0, %1, %2;" : "=r"(o) : "r"(a), "r"(r)); return o; }
__device__ __forceinline__ void fence_async_smem() { asm volatile("fence.proxy.async.shared::cta;" ::: "memory"); }
__device__ __forceinline__ void fence_async_global() { asm volatile("fence.proxy.async.global;" ::: "memory"); }
__device__ __forceinline__ void bar_sync(int id, int n) { asm volatile("bar.sync %0, %1;" ::"r"(id), "r"(n) : "memory"); }
__device__ __forceinline__ void bar_arrive(int id, int n) { asm volatile("bar.arrive %0, %1;" ::"r"(id), "r"(n) : "memory"); }
__device__ __forceinline__ void cluster_arrive() { asm volatile("barrier.cluster.arrive.relaxed.aligned;" ::: "memory"); }
__device__ __forceinline__ void cluster_wait() { asm volatile("barrier.cluster.wait.aligned;" ::: "memory"); }

__device__ __forceinline__ void ring_load(uint32_t dst, const CUtensorMap* tm, int col, int row16, uint32_t bar) {
    asm volatile("{\n.reg .pred p;\nelect.sync _|p, 0xffffffff;\n"
                 "@p mbarrier.arrive.expect_tx.shared::cta.b64 _, [%2], 16384;\n"
                 "@p cp.async.bulk.tensor.5d.shared::cluster.global.mbarrier::complete_tx::bytes [%0], [%1, {%3, 0, 0, 0, %4}], [%2];\n}"
                 ::"r"(dst), "l"(tm), "r"(bar), "r"(col), "r"(row16) : "memory");
}
__device__ __forceinline__ void ring_load_both(uint32_t dst, const CUtensorMap* tm, int c1, uint32_t bar) {
    asm volatile("{\n.reg .pred p;\nelect.sync _|p, 0xffffffff;\n"
                 "@p cp.async.bulk.tensor.2d.shared::cluster.global.mbarrier::complete_tx::bytes.multicast::cluster [%0], [%1, {0, %3}], [%2], %4;\n}"
                 ::"r"(dst), "l"(tm), "r"(bar), "r"(c1), "h"((uint16_t)3) : "memory");
}
__device__ __forceinline__ void mbar_arrive_peer(uint32_t b) { asm volatile("mbarrier.arrive.relaxed.cluster.shared::cluster.b64 _, [%0];" ::"r"(b) : "memory"); }
__device__ __forceinline__ void prefetch_l2(const void* src, uint32_t bytes) {
    asm volatile("cp.async.bulk.prefetch.L2.global [%0], %1;" ::"l"(src), "r"(bytes) : "memory");
}
__device__ __forceinline__ void peer_copy(uint32_t dst, uint32_t src, uint32_t bytes, uint32_t rbar) {
    asm volatile("{\n.reg .pred p;\nelect.sync _|p, 0xffffffff;\n"
                 "@p cp.async.bulk.shared::cluster.shared::cta.mbarrier::complete_tx::bytes [%0], [%1], %2, [%3];\n}"
                 ::"r"(dst), "r"(src), "r"(bytes), "r"(rbar) : "memory");
}
__device__ __forceinline__ void st_async4(uint32_t dst, uint32_t a, uint32_t b, uint32_t c, uint32_t d, uint32_t bar) {
    asm volatile("st.async.shared::cluster.mbarrier::complete_tx::bytes.v4.b32 [%0], {%1,%2,%3,%4}, [%5];" ::"r"(dst), "r"(a), "r"(b), "r"(c), "r"(d), "r"(bar) : "memory");
}
__device__ __forceinline__ void put_sums(uint32_t dst, uint32_t rdst, float a, float b, uint32_t rbar, bool on) {
    asm volatile("{\n.reg .pred p;\nsetp.ne.u32 p, %5, 0;\n"
                 "@p st.async.shared::cluster.mbarrier::complete_tx::bytes.v2.f32 [%1], {%2,%3}, [%4];\n"
                 "@p st.shared.v2.f32 [%0], {%2,%3};\n}" ::"r"(dst), "r"(rdst), "f"(a), "f"(b), "r"(rbar), "r"((uint32_t)on) : "memory");
}
__device__ __forceinline__ void stsm4(uint32_t a, uint32_t r0, uint32_t r1, uint32_t r2, uint32_t r3) {
    asm volatile("stmatrix.sync.aligned.m8n8.x4.shared.b16 [%0], {%1,%2,%3,%4};" ::"r"(a), "r"(r0), "r"(r1), "r"(r2), "r"(r3) : "memory");
}
__device__ __forceinline__ void ldsm4(uint32_t a, uint32_t& r0, uint32_t& r1, uint32_t& r2, uint32_t& r3) {
    asm volatile("ldmatrix.sync.aligned.m8n8.x4.shared.b16 {%0,%1,%2,%3}, [%4];" : "=r"(r0), "=r"(r1), "=r"(r2), "=r"(r3) : "r"(a) : "memory");
}
__device__ __forceinline__ uint4 lds128(uint32_t a) { uint4 v; asm volatile("ld.shared.v4.b32 {%0,%1,%2,%3}, [%4];" : "=r"(v.x), "=r"(v.y), "=r"(v.z), "=r"(v.w) : "r"(a) : "memory"); return v; }
__device__ __forceinline__ float4 lds128f(uint32_t a) { float4 v; asm volatile("ld.shared.v4.f32 {%0,%1,%2,%3}, [%4];" : "=f"(v.x), "=f"(v.y), "=f"(v.z), "=f"(v.w) : "r"(a) : "memory"); return v; }
__device__ __forceinline__ float2 lds64f(uint32_t a) { float2 v; asm volatile("ld.shared.v2.f32 {%0,%1}, [%2];" : "=f"(v.x), "=f"(v.y) : "r"(a) : "memory"); return v; }
__device__ __forceinline__ uint32_t lds32(uint32_t a) { uint32_t v; asm volatile("ld.shared.b32 %0, [%1];" : "=r"(v) : "r"(a) : "memory"); return v; }
__device__ __forceinline__ void sts128(uint32_t a, uint32_t x, uint32_t y, uint32_t z, uint32_t w) { asm volatile("st.shared.v4.b32 [%0], {%1,%2,%3,%4};" ::"r"(a), "r"(x), "r"(y), "r"(z), "r"(w) : "memory"); }
__device__ __forceinline__ void sts128f(uint32_t a, float x, float y, float z, float w) { asm volatile("st.shared.v4.f32 [%0], {%1,%2,%3,%4};" ::"r"(a), "f"(x), "f"(y), "f"(z), "f"(w) : "memory"); }
__device__ __forceinline__ void sts64f(uint32_t a, float x, float y) { asm volatile("st.shared.v2.f32 [%0], {%1,%2};" ::"r"(a), "f"(x), "f"(y) : "memory"); }
__device__ __forceinline__ void sts32(uint32_t a, uint32_t x) { asm volatile("st.shared.b32 [%0], %1;" ::"r"(a), "r"(x) : "memory"); }
__device__ __forceinline__ void stg128(void* p, uint4 v) { asm volatile("st.global.v4.b32 [%0], {%1,%2,%3,%4};" ::"l"(p), "r"(v.x), "r"(v.y), "r"(v.z), "r"(v.w) : "memory"); }

__device__ __forceinline__ uint32_t pack2(float lo, float hi) { uint32_t r; asm("cvt.rn.bf16x2.f32 %0, %1, %2;" : "=r"(r) : "f"(hi), "f"(lo)); return r; }
__device__ __forceinline__ float blo(uint32_t v) { return __uint_as_float(v << 16); }
__device__ __forceinline__ float bhi(uint32_t v) { return __uint_as_float(v & 0xffff0000u); }
__device__ __forceinline__ uint32_t hmul2(uint32_t a, uint32_t b) { uint32_t r; asm("mul.rn.bf16x2 %0, %1, %2;" : "=r"(r) : "r"(a), "r"(b)); return r; }
__device__ __forceinline__ uint32_t hadd2(uint32_t a, uint32_t b) { uint32_t r; asm("add.rn.bf16x2 %0, %1, %2;" : "=r"(r) : "r"(a), "r"(b)); return r; }
__device__ __forceinline__ uint32_t hsub2(uint32_t a, uint32_t b) { uint32_t r; asm("sub.rn.bf16x2 %0, %1, %2;" : "=r"(r) : "r"(a), "r"(b)); return r; }
__device__ __forceinline__ uint32_t hfma2(uint32_t a, uint32_t b, uint32_t c) { uint32_t r; asm("fma.rn.bf16x2 %0, %1, %2, %3;" : "=r"(r) : "r"(a), "r"(b), "r"(c)); return r; }
__device__ __forceinline__ float tanh_fast(float x) { float r; asm("tanh.approx.f32 %0, %1;" : "=f"(r) : "f"(x)); return r; }
__device__ __forceinline__ float rsq(float x) { float r; asm("rsqrt.approx.ftz.f32 %0, %1;" : "=f"(r) : "f"(x)); return r; }
__device__ __forceinline__ float ex2(float x) { float r; asm("ex2.approx.ftz.f32 %0, %1;" : "=f"(r) : "f"(x)); return r; }

__device__ __forceinline__ uint32_t ld_relaxed(const uint32_t* p) {
    uint32_t v;
    asm volatile("ld.relaxed.gpu.global.u32 %0, [%1];" : "=r"(v) : "l"(p) : "memory");
    return v;
}
__device__ __forceinline__ uint32_t clock32() { uint32_t c; asm volatile("mov.u32 %0, %%clock;" : "=r"(c)::"memory"); return c; }
__device__ __forceinline__ void spin(uint32_t clks) {
    const uint32_t t0 = clock32();
    while (clock32() - t0 < clks) {}
}
__device__ __forceinline__ void flag_wait(const uint32_t* p, uint32_t e, bool mine) {
#pragma unroll 1
    for (int i = 0; i < (1 << 19); i++) {
        if (mine) mine = ld_relaxed(p) != e;
        if (!__any_sync(~0u, mine)) break;
        if (BACKOFF) spin(BACKOFF);
    }
    asm volatile("fence.acquire.gpu;" ::: "memory");
    fence_async_global();
}
__device__ __forceinline__ void st_data(void* p, uint32_t x, uint32_t y, uint32_t z, uint32_t w) {
    asm volatile("st.relaxed.gpu.global.v4.b32 [%0], {%1,%2,%3,%4};" ::"l"(p), "r"(x), "r"(y), "r"(z), "r"(w) : "memory");
}
template <int STRIDE, int N>
__device__ __forceinline__ void ld_data(uint4 (&v)[N], const unsigned char* p) {
    int it = 0;
    bool again;
#pragma unroll 1
    do {
        uint32_t m = 0;
#pragma unroll
        for (int i = 0; i < N; i++)
            asm volatile("ld.relaxed.gpu.global.v4.b32 {%0,%1,%2,%3}, [%4];" : "=r"(v[i].x), "=r"(v[i].y), "=r"(v[i].z), "=r"(v[i].w) : "l"(p + i * STRIDE) : "memory");
#pragma unroll
        for (int i = 0; i < N; i++) m = __vimax3_u32(__vimax3_u32(v[i].x, v[i].y, v[i].z), v[i].w, m);
        again = __any_sync(~0u, m == ~0u) && ++it < (1 << 16);
    } while (again);
}
__device__ __forceinline__ uint32_t ld_epoch() { return ld_relaxed(&g_epoch[blockIdx.x * FS]) + 1; }
__device__ __forceinline__ void flag_set(uint32_t* p, uint32_t e) { asm volatile("st.release.gpu.global.u32 [%0], %1;" ::"l"(p), "r"(e) : "memory"); }

__device__ __forceinline__ uint32_t desc_lo(uint32_t addr) { return ((addr & 0x3FFFF) >> 4) | 0x10000u; }
__device__ __forceinline__ uint64_t mkdesc(uint32_t lo) { return (uint64_t)lo | (0x40000040ull << 32); }
__device__ __forceinline__ void wg_fence() { asm volatile("wgmma.fence.sync.aligned;" ::: "memory"); }
__device__ __forceinline__ void wg_commit() { asm volatile("wgmma.commit_group.sync.aligned;" ::: "memory"); }
template <int N> __device__ __forceinline__ void wg_wait() { asm volatile("wgmma.wait_group.sync.aligned %0;" ::"n"(N) : "memory"); }
template <int N> __device__ __forceinline__ void pin(float (&d)[N]) {
#pragma unroll
    for (int i = 0; i < N; i++) asm volatile("" : "+f"(d[i])::"memory");
}
template <int N> __device__ __forceinline__ void pin(uint32_t (&d)[N]) {
#pragma unroll
    for (int i = 0; i < N; i++) asm volatile("" : "+r"(d[i])::"memory");
}

template <typename Tp, int N> __device__ __forceinline__ void zero(Tp (&d)[N]) {
#pragma unroll
    for (int i = 0; i < N; i++) d[i] = 0;
    pin(d);
}

#define F4(d, i) "+f"(d[i]), "+f"(d[i + 1]), "+f"(d[i + 2]), "+f"(d[i + 3])
#define F16(d, i) F4(d, i), F4(d, i + 4), F4(d, i + 8), F4(d, i + 12)

__device__ __forceinline__ void mma16(float (&d)[4], const uint32_t* a, uint32_t b0, uint32_t b1) {
    asm("mma.sync.aligned.m16n8k16.row.col.f32.bf16.bf16.f32 {%0,%1,%2,%3}, {%4,%5,%6,%7}, {%8,%9}, {%0,%1,%2,%3};"
        : F4(d, 0) : "r"(a[0]), "r"(a[1]), "r"(a[2]), "r"(a[3]), "r"(b0), "r"(b1));
}
template <int N>
__device__ __forceinline__ float row_sum(const uint32_t* x, uint32_t ones = 0x3F803F80u) {
    float c[4] = {};
#pragma unroll
    for (int i = 0; i < N; i += 4) mma16(c, x + i, ones, ones);
    return c[0] + c[2];
}
template <int N>
__device__ __forceinline__ float row_sumsq(const uint32_t* x, int lane) {
    float c0[4] = {}, c1[4] = {};
#pragma unroll
    for (int i = 0; i < N; i += 4) {
        mma16(c0, x + i, x[i], x[i + 2]);
        mma16(c1, x + i, x[i + 1], x[i + 3]);
    }
    return (lane & 4) ? c0[1] + c1[3] : c0[0] + c1[2];
}
__device__ __forceinline__ void mma_sp(float (&d)[32], const uint32_t* a, uint64_t b, uint32_t meta, int acc) {
    asm volatile("{.reg .pred p; setp.ne.b32 p, %38, 0;\n"
                 "wgmma.mma_async.sp.sync.aligned.m64n64k32.f32.bf16.bf16 {%0,%1,%2,%3,%4,%5,%6,%7,%8,%9,%10,%11,%12,%13,%14,%15,%16,%17,%18,%19,%20,%21,%22,%23,%24,%25,%26,%27,%28,%29,%30,%31}, "
                 "{%32,%33,%34,%35}, %36, %37, 0, p, 1, 1, 1;}\n"
                 : F16(d, 0), F16(d, 16) : "r"(a[0]), "r"(a[1]), "r"(a[2]), "r"(a[3]), "l"(b), "r"(meta), "r"(acc));
}
__device__ __forceinline__ void mma_qk(float (&d)[32], uint32_t a0, uint32_t a1, uint32_t a2, uint32_t a3, uint64_t b, int acc) {
    asm volatile("{.reg .pred p; setp.ne.b32 p, %37, 0;\n"
                 "wgmma.mma_async.sync.aligned.m64n64k16.f32.bf16.bf16 {%0,%1,%2,%3,%4,%5,%6,%7,%8,%9,%10,%11,%12,%13,%14,%15,%16,%17,%18,%19,%20,%21,%22,%23,%24,%25,%26,%27,%28,%29,%30,%31}, "
                 "{%32,%33,%34,%35}, %36, p, 1, 1, 0;}\n"
                 : F16(d, 0), F16(d, 16) : "r"(a0), "r"(a1), "r"(a2), "r"(a3), "l"(b), "r"(acc));
}
__device__ __forceinline__ void mma_pv(float (&d)[36], uint32_t a0, uint32_t a1, uint32_t a2, uint32_t a3, uint64_t b) {
    asm volatile("wgmma.mma_async.sync.aligned.m64n72k16.f32.bf16.bf16 {%0,%1,%2,%3,%4,%5,%6,%7,%8,%9,%10,%11,%12,%13,%14,%15,%16,%17,%18,%19,%20,%21,%22,%23,%24,%25,%26,%27,%28,%29,%30,%31,%32,%33,%34,%35}, "
                 "{%36,%37,%38,%39}, %40, 1, 1, 1, 1;\n"
                 : F16(d, 0), F16(d, 16), F4(d, 32) : "r"(a0), "r"(a1), "r"(a2), "r"(a3), "l"(b));
}

__device__ __forceinline__ uint32_t load_code(int n, int r, int w) {
    const int tile = 2 * r + w;
    int m, col, row;
    if (n < 16 || n >= 40) {
        const int k = n < 16 ? n : n - 40;
        m = n < 16 ? 0 : 6;
        if (TWO && n >= 40 && k < 4) { col = 4 * tile + (k & 1); row = (k >> 1) ^ r; }
        else if (k < 8) { col = 4 * tile + (k >> 1); row = n < 16 ? (k & 1) : (k & 1) ^ r; }
        else { m++; col = k < 12 ? tile ^ 2 : tile; row = 2 * (tile ^ (k & 1)) + ((k >> 1) & 1); }
    } else if (n < 32) {
        const int k = n - 16;
        m = 2;
        if (k < 4) { col = tile + ((k & 1) ? 8 : 4); row = (k >> 1) ^ r; }
        else { col = tile; row = (k & 1) ^ r; }
    } else if (n < 34) { m = 3; col = tile; row = n - 32; }
    else if (n < 38) { const int k = n - 34; m = 4; col = tile + 4 * (k & 1); row = (k >> 1) ^ r; }
    else { m = 5; col = tile; row = (n & 1) ^ r; }
    return m | (col << 4) | (row << (m ? 11 : 10));
}

__global__ void __cluster_dims__(2, 1, 1) __launch_bounds__(NTHREADS, 1)
conformer_kernel(const Scalars p, const __grid_constant__ Maps m) {
    extern __shared__ __align__(1024) unsigned char smem_raw[];
    const uint32_t sb = smem_u32(smem_raw);
    const uint32_t bars = sb + OFF_BARS;
    const int tid = threadIdx.x;
    const int lane = tid & 31;
    const int warp = __shfl_sync(~0u, tid >> 5, 0);
    const int r = blockIdx.x & 1;
    const int pair = blockIdx.x >> 1;
    const int b = pair >> 5, pt = pair & 31;
    const int ah = pt >> 3, qt = (pt & 7) * 2 + r;
    const int abh = b * 4 + ah;

    TG(30);
    TSINIT();
    TS(0);
    const uint32_t P = sb + OFF_P, H = sb + OFF_H;
    if (warp == 11) {
        if (lane == 0) {
#pragma unroll
            for (int i = 0; i < 2 * NSLOT; i++) mbar_init(bars + (B_FULL + i) * 8, 1);
            asm volatile("fence.mbarrier_init.release.cluster;" ::: "memory");
            fence_async_smem();
        }
        __syncwarp();
#pragma unroll
        for (int i = 0; i < 2 * NFIRST; i++)
            ring_load(sb + OFF_RING + ((i & 1) * NSLOT + (i >> 1)) * SLOT, &m.tm[0], 64 * (8 * r + 4 * (i & 1) + (i >> 2)), 4 * ((i >> 1) & 1),
                      bars + (B_FULL + (i & 1) * NSLOT + (i >> 1)) * 8);
        bar_arrive(13, 96);
        cluster_arrive();
    }

    if (warp >= 8) {
        asm volatile("setmaxnreg.dec.sync.aligned.u32 48;");
        if (warp >= 12) {
            cluster_arrive();
            cluster_wait();
            const int ut = tid & 127;
            const uint32_t target = ld_epoch() * 64;
            auto reset_done = [&](int k) {
                bar_sync(11, 128);
                if (ut == 0) {
                    asm volatile("red.release.gpu.global.add.u32 [%0], 1;" ::"l"(&g_reset[(2 * b + k) * 32]) : "memory");
#pragma unroll 1
                    for (int i = 0; i < (1 << 20) && ld_relaxed(&g_reset[(2 * b + k) * 32]) != target; i++) __nanosleep(100);
                    asm volatile("fence.acquire.gpu;" ::: "memory");
                    mbar_arrive(bars + (B_RST + k) * 8);
                }
                __syncwarp();
                TS(13 + k);
            };
#pragma unroll
            for (int i = 0; i < 4; i++)
                st_data(g_kvq + 2097152 + (size_t)((b * 4 + 2 * r + (i >> 1)) * 1024 + pt * 32) * 128 + (i & 1) * 2048 + ut * 16, ~0u, ~0u, ~0u, ~0u);
            reset_done(0);
            bar_sync(6, 384);
#pragma unroll
            for (int i = 0; i < 4; i++) {
                st_data(g_o + (size_t)(b * 128 + qt * 8 + 2 * i + (ut >> 6)) * 4096 + ah * 1024 + (ut & 63) * 16, ~0u, ~0u, ~0u, ~0u);
                if (i < 2) st_data(&g_halo[(pair * 4 + 2 * r + i) * 128 + ut], ~0u, ~0u, ~0u, ~0u);
            }
            reset_done(1);
            const int side = warp & 1, wg = (warp >> 1) & 1, np = side ? pt + 1 : pt - 1;
            const unsigned char* src = reinterpret_cast<const unsigned char*>(&g_halo[(((b * 32 + np) * 4 + 2 * r + wg) * 2 + (side ^ 1)) * 64 + lane]);
            const uint32_t dst = H + 16384 + wg * GCH + side * 5120 + (lane & 7) * 128 + (((lane >> 3) ^ (lane & 7)) << 4);
            uint4 hv[2] = {make_uint4(0, 0, 0, 0), make_uint4(0, 0, 0, 0)};
            bar_sync(8 + wg, 192);
            if (np >= 0 && np < 32) {
                spin(HDELAY);
                ld_data<512>(hv, src);
            }
            stsm4(dst, hv[0].x, hv[0].y, hv[0].z, hv[0].w);
            stsm4(dst ^ 64, hv[1].x, hv[1].y, hv[1].z, hv[1].w);
            __syncwarp();
            if (lane == 0) mbar_arrive(bars + (B_HALO + (warp & 3)) * 8);
            TS(4);
        } else if (warp < 10) {
            const int w = warp - 8;
            const uint32_t ring = sb + OFF_RING + w * NSLOT * SLOT;
            const uint32_t full = bars + (B_FULL + w * NSLOT) * 8;
            cluster_arrive();
            bar_sync(13, 96);
            TS(1);
#pragma unroll
            for (int n = NFIRST; n < NSLOT; n++) {
                if (n == NFIRST + 1) bar_sync(12, 64);
                ring_load(ring + n * SLOT, &m.tm[0], 64 * (8 * r + 4 * w + (n >> 1)), 4 * (n & 1), full + n * 8);
            }
            TS(2);
            const uint32_t code = load_code(lane, r, w) | (load_code(lane + 32, r, w) << 16);
            cluster_wait();
            uint32_t s = 0, ph = 0;
            int n = NSLOT;
#pragma unroll 1
            for (int seg = 0; seg < 2; seg++) {
#pragma unroll 1
                for (; n < (seg == 0 ? 22 : NLOADS); n++) {
                    const uint32_t c = __shfl_sync(~0u, code, n) >> (n & 32 ? 16 : 0);
                    const CUtensorMap* tm = &m.tm[c & 15];
                    const uint32_t col = (c & 0xf0) * 4, row = (c & 0xff00) >> 8, dst = ring + s * SLOT;
                    mbar_wait(full + (B_EMPTY - B_FULL) * 8 + s * 8, ph + (((uint32_t)(size_t)tm | col | row | dst) & p.zero));
                    ring_load(dst, tm, col, row, full + s * 8);
                    if (++s == NSLOT) { s = 0; ph ^= 1; }
                }
                if (seg == 1) break;
                const uint32_t epoch = ld_epoch();
                const uint32_t rdy = bars + (B_RDY + 3 * w) * 8, prdy = mapa(rdy, r ^ 1);
                const int odd = r ^ w;
                const uint32_t* flags = g_flag_kv + (abh * 32 + lane) * KFS;
                auto kv_load = [&](uint32_t sl, int isv, int i) {
                    ring_load_both(ring + sl * SLOT, &m.tm[8], (isv * 64 + abh * 8 + 2 * i + w) * 128, full + sl * 8);
                };
#pragma unroll 1
                for (int i = 0; i < 2; i++) {
                    if (lane < 3 + i) {
                        const uint32_t sl = i ? lane : lane + 2;
                        mbar_wait(full + (B_EMPTY - B_FULL + sl) * 8, i ^ 1);
                        mbar_arrive_tx(full + sl * 8, (i || lane == 2) ? SLOT : 0);
                    }
                    __syncwarp();
                }
                if (lane == 0) mbar_arrive_peer(prdy);
                bar_sync(14, 96);
                spin(KDELAY);
                mbar_wait(rdy, 0);
                flag_wait(flags, epoch, (lane >> 2) == 2 * odd + w);
                TSW(5 + 2 * odd);
                if (!odd) { kv_load(4, 0, 0); bar_arrive(12, 64); }
                else bar_sync(12, 64);
                spin(w ? KD3 : KD2);
                kv_load(odd ^ 1, odd ^ 1, odd);
                flag_wait(flags, epoch, (lane >> 2) == 2 * odd + w + 4);
                mbar_wait(full + (odd ^ 1) * 8, 1);
                kv_load(2 + odd, odd, 2 - odd);
#pragma unroll 1
                for (int i = 0; i < 3; i++) {
                    const uint32_t sl = i ? i - 1 : 4, bo = i == 2 ? 16 : 8;
                    mbar_wait(full + (B_EMPTY - B_FULL + sl) * 8, i != 0);
                    if (lane == 0) mbar_arrive_tx(full + sl * 8, SLOT);
                    if ((i & 1) != odd) {
                        mbar_wait(rdy + bo, 0);
                        kv_load(sl, i != 0, 2 + odd);
                    } else if (lane == 0) mbar_arrive_peer(prdy + bo);
                    __syncwarp();
                }
                n = 32; s = 2; ph = 1;
            }
        } else if (warp == 10) {
            if (lane == 0) {
#pragma unroll
                for (int i = B_EMPTY; i < NBARS; i++) mbar_init(bars + i * 8, i < B_XA ? 4 : 1);
#pragma unroll
                for (int i = B_XA; i <= B_SR; i++) mbar_arrive_tx(bars + i * 8, i < B_XB ? 512 : ((i >= B_INB && i < B_SR) ? 4096 : 8192));
                asm volatile("fence.mbarrier_init.release.cluster;" ::: "memory");
                fence_async_smem();
            }
            __syncwarp();
            cluster_arrive();
            cluster_wait();
        } else {
            const uint32_t kb = (lane < 2 || lane > 5) ? 4096 : (lane == 2 ? 3072 : (lane == 4 ? 2048 : 1024));
            const char* pf = m.w[lane & 7] + blockIdx.x * kb;
            cluster_wait();
            if (lane < PF0) prefetch_l2(pf, kb);
            mbar_wait(bars + B_FULL * 8, 0);
            if (lane >= PF0 && lane < 3) prefetch_l2(pf, kb);
            if (lane >= 1 && lane < 9) asm volatile("prefetch.tensormap [%0];" ::"l"(&m.tm[lane]) : "memory");
            mbar_wait(bars + (B_FULL + 1) * 8, 1);
            if (lane > 2 && lane < 8) prefetch_l2(pf, kb);
            if (lane == 8 && blockIdx.x < 15) prefetch_l2(p.dw + blockIdx.x * 256, 512);
            const uint32_t epoch = ld_epoch();
            bar_sync(4, 288);
            if (lane < 16) flag_set(&g_flag_kv[((b * 4 + 2 * r + (lane >> 3)) * 32 + pt) * KFS + (lane & 7)], epoch);
            __syncwarp();
            bar_arrive(14, 96);
            TSW(8);
        }
        TSDUMP();
        return;
    }

    const int w = warp >> 2, wq = warp & 3;
    const int tile = 2 * r + w;
    const int wt = tid & 127;
    const int c4 = lane & 3;
    const int trow = pt * 32 + 8 * wq;
    uint32_t xr[8];
    uint32_t a[32];
    const char* xrow = reinterpret_cast<const char*>(p.x) + (b * T_ + trow + (lane >> 2)) * 512;
    zero(a);
    if (trow < T_) {
        const char* src = xrow + c4 * 16 + p.zero;
#pragma unroll
        for (int i = 0; i < 8; i++)
            asm volatile("ld.global.nc.v4.b32 {%0,%1,%2,%3}, [%4];" : "=r"(a[4 * i]), "=r"(a[4 * i + 1]), "=r"(a[4 * i + 2]), "=r"(a[4 * i + 3]) : "l"(src + 64 * i));
    }
    cluster_arrive();
    asm volatile("setmaxnreg.inc.sync.aligned.u32 208;");
    const uint32_t rbase = sb + OFF_RING + w * NSLOT * SLOT, fbar = bars + (B_FULL + w * NSLOT) * 8;
    const uint32_t rdesc = desc_lo(rbase);
    auto acq = [&](int n) { mbar_wait(fbar + (n % NSLOT) * 8, (n / NSLOT) & 1); };
    auto rel = [&](int n) { if (lane == 0) mbar_arrive(fbar + (B_EMPTY - B_FULL + n % NSLOT) * 8); };
    const uint32_t foff = (lane & 7) * 128 + (((lane >> 3) ^ (lane & 7)) << 4);
    float v[16];
    const uint32_t xown = __shfl_sync(~0u, P + wt * 16 + tile * 4096, lane), xrem = __shfl_sync(~0u, P + wt * 16 + (r ^ 1) * 8192, lane);
    const uint32_t sbuf = __shfl_sync(~0u, sb + OFF_MISC + 1024 + (8 * wq + (lane >> 2)) * 32, lane);
    const uint32_t sown = __shfl_sync(~0u, sbuf + tile * 8, lane);
    const uint32_t peer = __shfl_sync(~0u, mapa(sb, r ^ 1) - sb, lane);
    const uint32_t hbuf = __shfl_sync(~0u, H + w * 4096 + wt * 16, lane);
    const uint32_t meta = __shfl_sync(~0u, 0xEEEE4444u + p.zero, lane);
    cluster_wait();
    TS(56);
    float mean, msq;
    const int mir = wq < 2 ? 7 : 0;
    uint32_t dwr[15] = {};

#pragma unroll
    for (int ph = 0; ph < 5; ph++) {
        uint4 o0, o1;
        if (ph == 0) {
            const uint32_t one = 0x3F803F80u + ((xown | xrem | sbuf | sown | hbuf | foff | rdesc | fbar) & p.zero);
            mean = ((row_sum<8>(a, one) + row_sum<8>(a + 8, one)) + (row_sum<8>(a + 16, one) + row_sum<8>(a + 24, one))) * (1.f / 256.f);
            TS(57);
        } else {
            const uint32_t xa = bars + (B_XA + ph) * 8;
#pragma unroll
            for (int j = 0; j < 8; j++) xr[j] = pack2(v[2 * j], v[2 * j + 1]);
            const float s = row_sum<8>(xr), q = row_sumsq<8>(xr, lane);
            if (ph < 4) {
                sts128(xown, xr[0], xr[1], xr[2], xr[3]);
                sts128(xown + 2048, xr[4], xr[5], xr[6], xr[7]);
            }
            put_sums(sown, sown + peer, s, q, xa + peer, c4 == (lane >> 3));
            bar_sync(10, 256);
            if (ph < 4) {
                o0 = lds128(xown ^ 4096); o1 = lds128((xown ^ 4096) + 2048);
                st_async4(xown + peer, xr[0], xr[1], xr[2], xr[3], xa + (B_XB - B_XA) * 8 + peer);
                st_async4(xown + peer + 2048, xr[4], xr[5], xr[6], xr[7], xa + (B_XB - B_XA) * 8 + peer);
            }
            TS(57 + ph);
            if (ph == 3) acq(0);
            if (ph == 1) acq(16);
            mbar_wait(xa, 0);
            const float4 u0 = lds128f(sbuf), u1 = lds128f(sbuf + 16);
            mean = ((u0.x + u0.z) + (u1.x + u1.z)) * (1.f / 256.f);
            msq = ((u0.y + u0.w) + (u1.y + u1.w)) * (1.f / 256.f);
        }
        if (ph == 4) break;
        const uint32_t mean2 = pack2(mean, mean);
        auto centre = [&](int i, const uint4& u) {
            a[i] = hsub2(u.x, mean2); a[i + 1] = hsub2(u.y, mean2); a[i + 2] = hsub2(u.z, mean2); a[i + 3] = hsub2(u.w, mean2);
        };
        if (ph == 0) {
#pragma unroll
            for (int j = 0; j < 32; j++) a[j] = hsub2(a[j], mean2);
            zero(xr);
            if (trow < T_) {
                const char* src = xrow + tile * 128 + c4 * 4 + (mean2 & p.zero);
#pragma unroll
                for (int j = 0; j < 8; j++) asm volatile("ld.global.nc.b32 %0, [%1];" : "=r"(xr[j]) : "l"(src + 16 * j));
            }
            mean -= blo(mean2);
            msq = __shfl_sync(~0u, row_sumsq<16>(a, lane) + row_sumsq<16>(a + 16, lane), (lane & 28) + (lane >> 3)) * (1.f / 256.f);
            acq(0);
        } else {
#pragma unroll
            for (int j = 0; j < 8; j++) a[j] = hsub2(xr[j], mean2);
            centre(8, o0); centre(12, o1);
        }
        const float rstd = rsq(fmaxf(fmaf(-mean, mean, msq), 0.f) + 1e-5f);
        auto gather_peer = [&]() {
            mbar_wait(bars + (B_XB + ph) * 8, 0);
#pragma unroll
            for (int i = 0; i < 4; i++) centre(16 + 4 * i, lds128(xrem + i * 2048));
        };
        auto sp = [&](float (&d)[32], int n, const uint32_t* af, int flip, int acc) {
            const uint32_t lo = rdesc + p.zero * (ph * 64 + n + 1) + (n % NSLOT) * (SLOT >> 4);
            const uint64_t b0 = mkdesc(lo + flip * 512), b1 = mkdesc(lo + (flip ^ 1) * 512);
            wg_fence();
            mma_sp(d, af, b0, meta, acc);
            mma_sp(d, af + 4, b0 + 256, meta, 1);
            mma_sp(d, af + 8, b1, meta, 1);
            mma_sp(d, af + 12, b1 + 256, meta, 1);
            wg_commit();
        };
        float d0[32], d1[32];

        if (ph == 0 || ph == 3) {
            uint32_t h[32], ho[32];
            const float rs = 0.5f * rstd;
            const uint32_t inb = bars + (B_INB + (ph & 2) + w) * 8;
            bool ready = true;
            const int eager = ph ? (TWO ? EAGER + 5 : EAGER) : EAGER - 1;
            auto step = [&](float (&d)[32], int n, const uint32_t* af, int flip, int acc, auto work) {
                if (!ready) acq(n);
                if (((TURN >> n) & 1) && w == 1) bar_sync(7, 256);
                sp(d, n, af, flip, acc);
                if (n > 0 && ((TURN >> (n - 1)) & 1) && w == 0) bar_arrive(7, 256);
                if (n < 15) ready = mbar_test(fbar + ((n + 1) % NSLOT) * 8, ((n + 1) / NSLOT) & 1);
                wg_wait<1>();
                if (n > 0 && !((eager >> (n - 1)) & 1)) rel(n - 1);
                const uint32_t tie = work() & p.zero;
                if ((eager >> n) & 1) {
                    if (p.zero < n + ph + 1) wg_wait<0>();
                    if (lane == 0) mbar_arrive(fbar + (B_EMPTY - B_FULL + n % NSLOT) * 8 + tie);
                }
            };
            auto none = []() { return 0u; };
            const int fl = ph ? w : 0;
            auto fetch = [&](int i) {
                bar_sync(10, 256);
                const uint4 u0 = lds128((hbuf ^ 4096) + (i & 1) * 8192), u1 = lds128((hbuf ^ 4096) + (i & 1) * 8192 + 2048);
                ho[8 * i] = u0.x; ho[8 * i + 1] = u0.y; ho[8 * i + 2] = u0.z; ho[8 * i + 3] = u0.w;
                ho[8 * i + 4] = u1.x; ho[8 * i + 5] = u1.y; ho[8 * i + 6] = u1.z; ho[8 * i + 7] = u1.w;
                return u0.x | u1.x;
            };
            auto act = [&](float (&d)[32], int i) {
                if (i > 0) fetch(i - 1);
                pin(d);
#pragma unroll
                for (int j = 0; j < 8; j++) {
                    const float u0 = (d[4 * j] + d[4 * j + 2]) * rs, u1 = (d[4 * j + 1] + d[4 * j + 3]) * rs;
                    h[8 * i + j] = pack2(fmaf(u0, tanh_fast(u0), u0), fmaf(u1, tanh_fast(u1), u1));
                }
                sts128(hbuf + (i & 1) * 8192, h[8 * i], h[8 * i + 1], h[8 * i + 2], h[8 * i + 3]);
                sts128(hbuf + (i & 1) * 8192 + 2048, h[8 * i + 4], h[8 * i + 5], h[8 * i + 6], h[8 * i + 7]);
                return 0u;
            };
            TS(1 + (ph & 2) * 10);
            if (TWO && ph) {
                step(d0, 0, a, fl, 0, none);
                step(d1, 1, a, fl, 0, [&]() { gather_peer(); return 0u; });
                TS(32);
                step(d0, 2, a + 16, 0, 1, none);
                step(d1, 3, a + 16, 0, 1, [&]() { return act(d0, 0); });
            } else {
                step(d0, 0, a, fl, 0, [&]() { if (ph) gather_peer(); return 0u; });
                TS(32);
                step(d0, 1, a + 16, 0, 1, none);
                step(d1, 2, a, fl, 0, [&]() { return act(d0, 0); });
                step(d1, 3, a + 16, 0, 1, none);
            }
            step(d0, 4, a, fl, 0, [&]() { return act(d1, 1); });
            TS(33);
            step(d0, 5, a + 16, 0, 1, none);
            step(d1, 6, a, fl, 0, [&]() { return act(d0, 2); });
            step(d1, 7, a + 16, 0, 1, none);
            step(d0, 8, h, 0, 0, [&]() { act(d1, 3); return fetch(3); });
            TS(2 + (ph & 2) * 10);
            step(d0, 9, ho, 0, 1, none);
            step(d0, 10, h + 16, 0, 1, none);
            step(d0, 11, ho + 16, 0, 1, none);
            uint32_t pk[8];
            auto pack_out = [&]() {
                pin(d0);
#pragma unroll
                for (int j = 0; j < 8; j++) pk[j] = pack2(d0[4 * j] + d0[4 * j + 2], d0[4 * j + 1] + d0[4 * j + 3]);
            };
            auto send = [&](int i) { st_async4(hbuf + 16384 + i * 2048 + peer, pk[4 * i], pk[4 * i + 1], pk[4 * i + 2], pk[4 * i + 3], inb + peer); };
            step(d1, 12, h, 0, 0, [&]() { pack_out(); if (SND != 1) send(0); if (SND == 0) send(1); return 0u; });
            TS(34);
            step(d1, 13, ho, 0, 1, [&]() { if (SND == 1) send(0); if (SND) send(1); return 0u; });
            step(d1, 14, h + 16, 0, 1, none);
            step(d1, 15, ho + 16, 0, 1, none);
            mbar_wait(inb, 0);
#pragma unroll
            for (int i = 0; i < 2; i++) {
                const uint4 u = lds128(hbuf + 16384 + i * 2048);
                const uint32_t p0[4] = {u.x, u.y, u.z, u.w};
#pragma unroll
                for (int j = 0; j < 4; j++) {
                    v[8 * i + 2 * j] = fmaf(0.5f, blo(p0[j]), blo(xr[4 * i + j]));
                    v[8 * i + 2 * j + 1] = fmaf(0.5f, bhi(p0[j]), bhi(xr[4 * i + j]));
                }
            }
            wg_wait<0>();
            pin(d1);
            rel(15);
            TS(3 + (ph & 2) * 10);
#pragma unroll
            for (int j = 0; j < 8; j++) {
                v[2 * j] = fmaf(0.5f, d1[4 * j] + d1[4 * j + 2], v[2 * j]);
                v[2 * j + 1] = fmaf(0.5f, d1[4 * j + 1] + d1[4 * j + 3], v[2 * j + 1]);
            }
#pragma unroll
            for (int i = 0; i < 15; i++) dwr[i] = 0;
            continue;
        }

        auto residual = [&](int n) {
            wg_wait<1>();
            rel(n);
            wg_wait<0>();
            pin(d0);
            rel(n + 1);
#pragma unroll
            for (int j = 0; j < 8; j++) {
                v[2 * j] = d0[4 * j] + d0[4 * j + 2] + blo(xr[j]);
                v[2 * j + 1] = d0[4 * j + 1] + d0[4 * j + 3] + bhi(xr[j]);
            }
        };

        if (ph == 2) {
            TS(39);
            sp(d0, 34, a, w, 0);
            acq(35);
            sp(d1, 35, a, w, 0);
            acq(36); acq(37);
            gather_peer();
            sp(d0, 36, a + 16, 0, 1);
            sp(d1, 37, a + 16, 0, 1);
            wg_wait<2>();
            rel(34);
            if (!(LATE & 1)) rel(35);
            acq(38);
            const float rs = trow < T_ ? 0.5f * rstd : 0.f;
            wg_wait<0>();
            pin(d0); pin(d1);
            if (!(LATE & 2)) { rel(36); rel(37); }
            TS(18);
            uint32_t pk[8];
#pragma unroll
            for (int j = 0; j < 8; j++) {
                const float u0 = (d0[4 * j] + d0[4 * j + 2]) * rs, u1 = (d0[4 * j + 1] + d0[4 * j + 3]) * rs;
                const float t0 = tanh_fast((d1[4 * j] + d1[4 * j + 2]) * rs), t1 = tanh_fast((d1[4 * j + 1] + d1[4 * j + 3]) * rs);
                pk[j] = pack2(fmaf(u0, t0, u0), fmaf(u1, t1, u1));
            }
            if (wq == 0 || wq == 3) {
                uint4* hp = &g_halo[((pair * 4 + tile) * 2 + (wq & 1)) * 64 + lane];
                st_data(hp, pk[0], pk[1], pk[2], pk[3]);
                st_data(hp + 32, pk[4], pk[5], pk[6], pk[7]);
            }
            const uint32_t gs = H + 16384 + w * GCH + wq * 1024;
            stsm4(gs + 1024 + foff, pk[0], pk[1], pk[2], pk[3]);
            stsm4(gs + 1024 + (foff ^ 64), pk[4], pk[5], pk[6], pk[7]);
            bar_sync(8 + w, 192);
            TS(26);
            uint32_t ca[8], cb[8];
            const int e = (wq & 1) * 4;
            const uint32_t lo = ((mir ^ e) * 144) ^ (lane * 4);
            const int dir = mir ? -1024 : 1024;
            const uint32_t gb = H + 16384 + w * GCH + (mir ? 3072 : 2048) + lo, sown_ = H + tile * HCH, so = sown_ + (mir ? 1024 : 2048) + lo;
            auto finish = [&](int i) {
                const uint32_t c = hadd2(ca[i], cb[i]);
                const float h0 = blo(c), h1 = bhi(c);
                sts32((so + (i >> 2) * dir) ^ ((i & 3) * 144), pack2(fmaf(h0, tanh_fast(h0), h0), fmaf(h1, tanh_fast(h1), h1)));
            };
#pragma unroll
            for (int k = 0; k < 26; k++) {
                if (k == 19) {
#pragma unroll
                    for (int i = 0; i < 4; i++) finish(i);
                    fence_async_smem();
                    bar_sync(2 + w, 128);
                    if (wq == 0) peer_copy(mapa(sown_ + 1024, r ^ 1), sown_ + 1024, 2048, mapa(bars + B_SR * 8, r ^ 1));
                    mbar_wait(bars + (B_HALO + 2 * w + (wq >> 1)) * 8, 0);
                    if (LATE & 1) rel(35);
                    if (LATE & 2) { rel(36); rel(37); }
                    TS(27);
                }
                const uint32_t g = lds32((gb + (((k + 1) & 4) ? ((k + 1) >> 3) + (wq & 1) : ((k + 1) >> 3)) * dir) ^ (((k + 1) & 7) * 144));
#pragma unroll
                for (int i = 0; i < 8; i++) {
                    const int tap = k - (i & 3) - 2 * (i & 4);
                    if (tap == 0) ca[i] = hmul2(g, dwr[0]);
                    else if (tap > 0 && tap < 8) ca[i] = hfma2(g, dwr[tap], ca[i]);
                    else if (tap == 8) cb[i] = hmul2(g, dwr[8]);
                    else if (tap > 8 && tap < 15) cb[i] = hfma2(g, dwr[tap], cb[i]);
                }
            }
#pragma unroll
            for (int i = 4; i < 8; i++) finish(i);
            fence_async_smem();
            bar_sync(12 + (warp >> 1), 64);
            if (wq == 0 || wq == 3) peer_copy(mapa(sown_ + wq * 1024, r ^ 1), sown_ + wq * 1024, 1024, mapa(bars + B_SR * 8, r ^ 1));
            bar_sync(10, 256);
            TS(19);
            auto frags = [&](int i, int half) {
                const uint32_t src = H + 2 * half * HCH + wq * 1024;
#pragma unroll
                for (int k = 0; k < 4; k++) ldsm4(src + (k >> 1) * HCH + (foff ^ ((k & 1) * 64)), a[i + 4 * k], a[i + 4 * k + 1], a[i + 4 * k + 2], a[i + 4 * k + 3]);
            };
            frags(0, r);
            sp(d0, 38, a, 0, 0);
            acq(39);
            mbar_wait(bars + B_SR * 8, 0);
            frags(16, r ^ 1);
            sp(d0, 39, a + 16, 0, 1);
            residual(38);
            TS(20);
            continue;
        }

        {
            TS(11);
            const uint32_t stg = H + warp * 2048;
            unsigned char* g = g_kvq + (size_t)((b * 4 + tile) * 1024 + trow) * 128 + lane * 16;
            auto put = [&](float (&d)[32], int i) {
                pin(d);
                uint32_t pk[8];
#pragma unroll
                for (int j = 0; j < 8; j++) pk[j] = pack2((d[4 * j] + d[4 * j + 2]) * rstd, (d[4 * j + 1] + d[4 * j + 3]) * rstd);
                if (i == 2) {
                    st_data(g + 2097152, pk[0], pk[1], pk[2], pk[3]);
                    st_data(g + 2097152 + 512, pk[4], pk[5], pk[6], pk[7]);
                    return;
                }
                stsm4(stg + i * 1024 + foff, pk[0], pk[1], pk[2], pk[3]);
                stsm4(stg + i * 1024 + (foff ^ 64), pk[4], pk[5], pk[6], pk[7]);
                __syncwarp();
                const uint4 u0 = lds128(stg + i * 1024 + lane * 16), u1 = lds128(stg + i * 1024 + 512 + lane * 16);
                stg128(g + i * 1048576, u0); stg128(g + i * 1048576 + 512, u1);
            };
            sp(d0, 16, a, w, 0);
            acq(17);
            sp(d1, 17, a, w, 0);
            gather_peer();
            acq(18);
            sp(d0, 18, a + 16, 0, 1);
            wg_wait<1>();
            rel(16); rel(17);
            acq(19);
            sp(d1, 19, a + 16, 0, 1);
            wg_wait<1>();
            rel(18);
            put(d0, 0);
            wg_wait<0>();
            rel(19);
            TS(37);
            put(d1, 1);
            bar_arrive(4, 288);
            TS(38);
            acq(20);
            sp(d0, 20, a, w, 0);
            acq(21);
            sp(d0, 21, a + 16, 0, 1);
            acq(22); acq(23);
            rel(22); rel(23);
            mbar_wait(bars + B_RST * 8, 0);
            wg_wait<0>();
            rel(20); rel(21);
            put(d0, 2);
            TS(12);
        }

        {
            constexpr float CS = 0.125f * 1.4426950408889634f;
            float sa[32], sb2[32], o[36];
            uint32_t pa[16], pb[16], q[16];
            float n0 = INFINITY, n1 = INFINITY;
            zero(o); zero(pa); zero(pb); zero(sb2);
            const uint32_t ones = sb + OFF_MISC + 2048;
            { const uint32_t c = w ? 0u : 0x3F803F80u; sts128(ones + tid * 16, c, c, c, c); }
            fence_async_smem();
            bar_sync(10, 256);
            const uint32_t vdesc = rdesc + ((((ones - rbase) >> 4) - 1) << 16);
            auto qk_issue = [&](float (&s)[32], uint32_t lo) {
                const uint64_t kd = mkdesc(lo);
                wg_fence();
#pragma unroll
                for (int k = 0; k < 4; k++) mma_qk(s, q[4 * k], q[4 * k + 1], q[4 * k + 2], q[4 * k + 3], kd + 2 * k, k != 0);
                wg_commit();
            };
            auto both_issue = [&](float (&s)[32], uint32_t klo, uint32_t (&pp)[16], uint32_t vlo) {
                const uint64_t kd = mkdesc(klo), vd = mkdesc(vlo);
                wg_fence();
#pragma unroll
                for (int k = 0; k < 4; k++) {
                    mma_pv(o, pp[4 * k], pp[4 * k + 1], pp[4 * k + 2], pp[4 * k + 3], vd - k * (128 * 65535));
                    mma_qk(s, q[4 * k], q[4 * k + 1], q[4 * k + 2], q[4 * k + 3], kd + 2 * k, k != 0);
                }
                wg_commit();
            };
            auto new_max = [&](float (&s)[32], int nj, float& x0, float& x1) {
                x0 = s[0]; x1 = s[2];
#pragma unroll
                for (int j = 0; j < nj; j++) {
                    x0 = fmaxf(x0, fmaxf(s[4 * j], s[4 * j + 1]));
                    x1 = fmaxf(x1, fmaxf(s[4 * j + 2], s[4 * j + 3]));
                }
                x0 = fmaxf(x0, __shfl_xor_sync(~0u, x0, 1)); x1 = fmaxf(x1, __shfl_xor_sync(~0u, x1, 1));
                x0 = fmaxf(x0, __shfl_xor_sync(~0u, x0, 2)); x1 = fmaxf(x1, __shfl_xor_sync(~0u, x1, 2));
                x0 = fminf(n0, fmaf(x0, -CS, -20.f)); x1 = fminf(n1, fmaf(x1, -CS, -20.f));
            };
            auto probs = [&](float (&s)[32], uint32_t (&pp)[16], bool ready, bool tail, auto wait) {
                uint32_t any = 0;
#pragma unroll
                for (int i = 0; i < 16; i++) {
                    pp[i] = pack2(ex2(fmaf(s[2 * i], CS, (i & 1) ? n1 : n0)), ex2(fmaf(s[2 * i + 1], CS, (i & 1) ? n1 : n0)));
                    any |= pp[i];
                }
                wg_wait<0>();
                pin(sa); pin(sb2); pin(o); pin(pa); pin(pb);
                if (__builtin_expect(__any_sync(~0u, (any & 0x40004000u) || !ready), 0)) {
                    wait();
                    if (__any_sync(~0u, any & 0x40004000u)) {
                        if (tail) {
#pragma unroll
                            for (int i = 20; i < 32; i++) s[i] = -INFINITY;
                        }
                        float x0, x1;
                        new_max(s, 8, x0, x1);
                        const float sc0 = ex2(x0 - n0), sc1 = ex2(x1 - n1);
                        n0 = x0; n1 = x1;
#pragma unroll
                        for (int j = 0; j < 9; j++) { o[4 * j] *= sc0; o[4 * j + 1] *= sc0; o[4 * j + 2] *= sc1; o[4 * j + 3] *= sc1; }
#pragma unroll
                        for (int i = 0; i < 16; i++)
                            pp[i] = pack2(ex2(fmaf(s[2 * i], CS, (i & 1) ? n1 : n0)), ex2(fmaf(s[2 * i + 1], CS, (i & 1) ? n1 : n0)));
                    }
                }
            };
            {
                uint4 u[4];
                const unsigned char* src = g_kvq + 2097152 + (size_t)(abh * 1024 + qt * 64 + wq * 16) * 128 + lane * 16;
                spin(QGATE);
                ld_data<512>(u, src);
#pragma unroll
                for (int k = 0; k < 2; k++) {
                    q[8 * k] = u[k].x; q[8 * k + 1] = u[k + 2].x; q[8 * k + 2] = u[k].y; q[8 * k + 3] = u[k + 2].y;
                    q[8 * k + 4] = u[k].z; q[8 * k + 5] = u[k + 2].z; q[8 * k + 6] = u[k].w; q[8 * k + 7] = u[k + 2].w;
                }
                pin(q);
            }
            TS(40);
            acq(24);
            TS(13);
            qk_issue(sa, rdesc + (24 % NSLOT) * (SLOT >> 4));
            wg_wait<0>();
            pin(sa);
            {
                float x0, x1;
                new_max(sa, NJ0, x0, x1);
                n0 = x0; n1 = x1;
            }
            bar_arrive(6, 384);
            uint32_t vd = vdesc - (SLOT >> 4) * 65535u, kd = rdesc, vb = fbar + 8, kb = fbar;
            uint32_t vlast = vdesc - 4 * (SLOT >> 4) * 65535u, klast = rdesc + 4 * (SLOT >> 4) + 512;
            uint32_t kprev = fbar + 32, vprev = bars + (B_SINK - (B_EMPTY - B_FULL)) * 8;
#pragma unroll 1
            for (int it = 0; it < 4; it++) {
                both_issue(sb2, klast, pb, vlast);
                probs(sa, pa, mbar_test(vb, it < 2) & mbar_test(kb, it < 3), false, [&]() { mbar_wait(vb, it < 2); mbar_wait(kb, it < 3); });
                TS(41 + it * 4);
                if (lane == 0) mbar_arrive(kprev + (B_EMPTY - B_FULL) * 8);
                if (lane == 0) mbar_arrive(vprev + (B_EMPTY - B_FULL) * 8);
                both_issue(sa, kd, pa, vd);
                const int dv = it == 0 ? 2 : (it == 1 ? -3 : 1);
                kprev = kb; vprev = vb; vlast = vd - 512 * 65535u; klast = kd + 512;
                vd -= dv * (SLOT >> 4) * 65535u; vb += dv * 8;
                kd += (it == 2 ? -3 : 2) * (SLOT >> 4); kb = it == 2 ? vb : kb + 16;
                probs(sb2, pb, true, it == 3 && w == 1, []() {});
                TS(43 + it * 4);
            }
            wg_fence();
#pragma unroll
            for (int k = 0; k < 4; k++)
                mma_pv(o, pb[4 * k], pb[4 * k + 1], pb[4 * k + 2], pb[4 * k + 3], mkdesc(vlast - k * (128 * 65535) + (k > 1 ? w * ((k - 1) << 22) : 0)));
            wg_commit();
            const int row = wq * 16 + (lane >> 2);
            const uint32_t ml = sb + OFF_MISC;
            mbar_wait(bars + (B_RST + 1) * 8, 0);
            wg_wait<0>();
            pin(o); pin(pb); pin(sa); pin(sb2);
            if (!(LATE & 4)) rel(31);
            const float l0 = o[32], l1 = o[34];
            if (c4 == 0) { sts64f(ml + w * 512 + row * 8, n0, l0); sts64f(ml + w * 512 + row * 8 + 64, n1, l1); }
            TS(14);
            float mine[16];
#pragma unroll
            for (int j = 0; j < 4; j++) {
                if (w == 0) sts128f(H + j * 2048 + wt * 16, o[16 + 4 * j], o[17 + 4 * j], o[18 + 4 * j], o[19 + 4 * j]);
                else sts128f(H + 8192 + j * 2048 + wt * 16, o[4 * j], o[4 * j + 1], o[4 * j + 2], o[4 * j + 3]);
            }
#pragma unroll
            for (int i = 0; i < 16; i++) mine[i] = w == 0 ? o[i] : o[16 + i];
            bar_sync(10, 256);
            const float2 u0 = lds64f(ml + (w ^ 1) * 512 + row * 8), u1 = lds64f(ml + (w ^ 1) * 512 + row * 8 + 64);
            const float x0 = fminf(n0, u0.x), x1 = fminf(n1, u1.x);
            float a0 = ex2(x0 - n0), b0 = ex2(x0 - u0.x), a1 = ex2(x1 - n1), b1 = ex2(x1 - u1.x);
            const float i0 = __fdividef(1.f, fmaf(a0, l0, b0 * u0.y)), i1 = __fdividef(1.f, fmaf(a1, l1, b1 * u1.y));
            a0 *= i0; b0 *= i0; a1 *= i1; b1 *= i1;
            uint32_t pk[8];
#pragma unroll
            for (int j = 0; j < 4; j++) {
                const float4 v = lds128f(H + (w ^ 1) * 8192 + j * 2048 + wt * 16);
                pk[2 * j] = pack2(fmaf(a0, mine[4 * j], b0 * v.x), fmaf(a0, mine[4 * j + 1], b0 * v.y));
                pk[2 * j + 1] = pack2(fmaf(a1, mine[4 * j + 2], b1 * v.z), fmaf(a1, mine[4 * j + 3], b1 * v.w));
            }
            unsigned char* dst = g_o + (size_t)(b * 128 + qt * 8 + 2 * wq) * 4096 + ah * 1024 + w * 512 + lane * 16;
            st_data(dst, pk[0], pk[2], pk[4], pk[6]);
            st_data(dst + 4096, pk[1], pk[3], pk[5], pk[7]);
            if (tid == 0) asm volatile("red.relaxed.gpu.global.add.u32 [%0], 1;" ::"l"(&g_epoch[blockIdx.x * FS]) : "memory");
            TS(15);
        }

        {
            const uint32_t* dp = reinterpret_cast<const uint32_t*>(p.dw + (mir ? 14 * 256 : 0) + tile * 64) + lane;
#pragma unroll
            for (int i = 0; i < 15; i++) asm volatile("ld.global.nc.b32 %0, [%1];" : "=r"(dwr[i]) : "l"(dp + i * (mir ? -128 : 128)));
            acq(32); acq(33); acq(34);
            uint4 u[8];
            ld_data<512>(u, g_o + (size_t)(b * 128 + pt * 4 + wq) * 4096 + lane * 16);
#pragma unroll
            for (int i = 0; i < 8; i++) { a[4 * i] = u[i].x; a[4 * i + 1] = u[i].y; a[4 * i + 2] = u[i].z; a[4 * i + 3] = u[i].w; }
            if (LATE & 4) rel(31);
            TS(16);
            sp(d0, 32, a, 0, 0);
            sp(d0, 33, a + 16, 0, 1);
#pragma unroll
            for (int i = 0; i < 15; i++) dwr[i] = hmul2(dwr[i], 0x3F003F00u);
            residual(32);
            TS(17);
        }
    }

    cluster_arrive();
    TS(24);
    {
        const float rstd = rsq(fmaxf(fmaf(-mean, mean, msq), 0.f) + 1e-5f), nb = -mean * rstd;
#pragma unroll
        for (int j = 0; j < 8; j++) xr[j] = pack2(fmaf(v[2 * j], rstd, nb), fmaf(v[2 * j + 1], rstd, nb));
        const uint32_t stg = P + 16384 + warp * 1024;
        stsm4(stg + foff, xr[0], xr[1], xr[2], xr[3]);
        stsm4(stg + (foff ^ 64), xr[4], xr[5], xr[6], xr[7]);
        __syncwarp();
        const uint32_t src = stg + (lane >> 3) * 128 + (((lane & 7) ^ (lane >> 3)) << 4);
        const uint4 u0 = lds128(src), u1 = lds128((src + 512) ^ 64);
        __nv_bfloat16* dst = p.out + (size_t)(b * T_ + trow + (lane >> 3)) * 256 + tile * 64 + (lane & 7) * 8;
        if (trow < T_) { stg128(dst, u0); stg128(dst + 4 * 256, u1); }
    }
    TS(25);
    TG(31);
    TSDUMP();
    cluster_wait();
}

typedef CUresult (*EncodeFn)(CUtensorMap*, CUtensorMapDataType, cuuint32_t, void*, const cuuint64_t*, const cuuint64_t*,
                             const cuuint32_t*, const cuuint32_t*, CUtensorMapInterleave, CUtensorMapSwizzle,
                             CUtensorMapL2promotion, CUtensorMapFloatOOBfill);

}

extern "C" void kernel_launch(void* const* d_in, const int* in_sizes, int n_in, void* d_out, int out_size) {
    static EncodeFn encode = nullptr;
    if (!encode) {
        void* fn = nullptr;
        cudaDriverEntryPointQueryResult qr;
        cudaGetDriverEntryPoint("cuTensorMapEncodeTiled", &fn, cudaEnableDefault, &qr);
        encode = (EncodeFn)fn;
        cudaFuncSetAttribute(conformer_kernel, cudaFuncAttributeMaxDynamicSharedMemorySize, SMEM_LAUNCH);
    }
    Scalars p;
    Maps m;
    const cuuint32_t ones[5] = {1, 1, 1, 1, 1};
    const int idx[8] = {1, 2, 3, 4, 5, 7, 8, 9};
    const int rows[8] = {256, 1024, 256, 256, 256, 256, 256, 1024};
    const int cols[8] = {1024, 256, 768, 256, 512, 256, 1024, 256};
    for (int i = 0; i < 8; i++) {
        const cuuint64_t pitch = (cuuint64_t)cols[i] * 2;
        const cuuint64_t dims[5] = {(cuuint64_t)cols[i], i ? 2u : 4u, i ? 2u : 4u, i ? 4u : 2u, (cuuint64_t)rows[i] / (i ? 16 : 32)};
        const cuuint64_t strides[4] = {pitch, pitch * 8, pitch * (i ? 2 : 4), pitch * (i ? 16 : 32)};
        const cuuint32_t box[5] = {64, i ? 2u : 4u, i ? 2u : 4u, i ? 4u : 2u, i ? 8u : 4u};
        encode(&m.tm[i], CU_TENSOR_MAP_DATA_TYPE_BFLOAT16, 5, d_in[idx[i]], dims, strides, box, ones, CU_TENSOR_MAP_INTERLEAVE_NONE,
               CU_TENSOR_MAP_SWIZZLE_128B, CU_TENSOR_MAP_L2_PROMOTION_L2_128B, CU_TENSOR_MAP_FLOAT_OOB_FILL_NONE);
        m.w[i] = (const char*)d_in[idx[i]];
    }
    {
        void* kv = nullptr;
        cudaGetSymbolAddress(&kv, g_kvq);
        const cuuint64_t dims[2] = {64, 16384};
        const cuuint64_t strides[1] = {128};
        const cuuint32_t box[2] = {64, 128};
        encode(&m.tm[8], CU_TENSOR_MAP_DATA_TYPE_BFLOAT16, 2, kv, dims, strides, box, ones, CU_TENSOR_MAP_INTERLEAVE_NONE,
               CU_TENSOR_MAP_SWIZZLE_NONE, CU_TENSOR_MAP_L2_PROMOTION_L2_128B, CU_TENSOR_MAP_FLOAT_OOB_FILL_NONE);
    }
    p.x = (const __nv_bfloat16*)d_in[0];
    p.dw = (const __nv_bfloat16*)d_in[6];
    p.out = (__nv_bfloat16*)d_out;
    p.zero = 0;
    conformer_kernel<<<NCTA, NTHREADS, SMEM_LAUNCH>>>(p, m);
}
```

```cpp
#include <cuda_runtime.h>
#include <cuda_bf16.h>
#include <cuda.h>
#include <stdint.h>

namespace {

constexpr int T_ = 1000;
constexpr int NCTA = 128;
constexpr int NTHREADS = 512;
constexpr int NSLOT = 5;
constexpr int SLOT = 16384;
constexpr int NLOADS = 56;

constexpr uint32_t OFF_RING = 0;
constexpr uint32_t OFF_P = 163840;
constexpr uint32_t OFF_H = 188416;
constexpr uint32_t OFF_MISC = 221184;
constexpr uint32_t OFF_BARS = 229888;
constexpr uint32_t SMEM_BYTES = 230400;
constexpr uint32_t GCH = 6144;
constexpr uint32_t HCH = 4096;

constexpr int B_FULL = 0, B_EMPTY = 10, B_XA = 20  , B_XB = 25  , B_INB = 29  , B_SR = 33,
              B_RST = 34  , B_RDY = 36  , B_SINK = 42, B_HALO = 43  , NBARS = 47;

#define KD2 300u
#define KD3 500u
#define QGATE 500u
#define BACKOFF 0u
#define KFS 32
#define KDELAY 450u
#define NJ0 2
#define HDELAY 200u
#define LATE 3
#define SND 0
#define PF0 0
#define TWO 1
#define TURN 0x200
#define EAGER 0x0155
constexpr int FS = 8;

struct Scalars {
    const __nv_bfloat16* x;
    const __nv_bfloat16* dw;
    __nv_bfloat16* out;
    uint32_t zero;
};
struct Maps {
    CUtensorMap tm[9];
    const char* w[8];
};

__device__ __align__(1024) unsigned char g_kvq[3 * 8 * 1024 * 128];
__device__ __align__(1024) unsigned char g_o[2 * 128 * 4096];
__device__ uint4 g_halo[64 * 4 * 2 * 64];
__device__ __align__(128) uint32_t g_flag_kv[8 * 32 * KFS];
__device__ uint32_t g_reset[4 * 32];
__device__ uint32_t g_epoch[NCTA * FS];

#define TS(i) do { } while (0)
#define TSW(i) do { } while (0)
#define TG(i) do { } while (0)
#define TSINIT() do { } while (0)
#define TSDUMP() do { } while (0)
constexpr uint32_t SMEM_LAUNCH = SMEM_BYTES;

__device__ __forceinline__ uint32_t smem_u32(const void* p) { return (uint32_t)__cvta_generic_to_shared(p); }
__device__ __forceinline__ void mbar_init(uint32_t b, uint32_t c) { asm volatile("mbarrier.init.shared::cta.b64 [%0], %1;" ::"r"(b), "r"(c) : "memory"); }
__device__ __forceinline__ void mbar_arrive(uint32_t b) { asm volatile("mbarrier.arrive.shared::cta.b64 _, [%0];" ::"r"(b) : "memory"); }
__device__ __forceinline__ void mbar_arrive_tx(uint32_t b, uint32_t tx) { asm volatile("mbarrier.arrive.expect_tx.shared::cta.b64 _, [%0], %1;" ::"r"(b), "r"(tx) : "memory"); }
__device__ __forceinline__ void mbar_wait(uint32_t b, uint32_t ph) {
    asm volatile("{\n.reg .pred p, q;\n.reg .u32 c;\nmov.u32 c, 0;\n"
                 "MW_LOOP:\n.pragma \"nounroll\";\n"
                 "mbarrier.try_wait.parity.shared::cta.b64 p, [%0], %1;\n"
                 "add.u32 c, c, 1;\nsetp.lt.u32 q, c, 65536;\nnot.pred p, p;\nand.pred p, p, q;\n@p bra MW_LOOP;\n}"
                 ::"r"(b), "r"(ph) : "memory");
}
__device__ __forceinline__ bool mbar_test(uint32_t b, uint32_t ph) {
    uint32_t ok;
    asm volatile("{\n.reg .pred p;\nmbarrier.test_wait.parity.shared::cta.b64 p, [%1], %2;\nselp.u32 %0, 1, 0, p;\n}" : "=r"(ok) : "r"(b), "r"(ph) : "memory");
    return ok;
}
__device__ __forceinline__ uint32_t mapa(uint32_t a, uint32_t r) { uint32_t o; asm("mapa.shared::cluster.u32 %0, %1, %2;" : "=r"(o) : "r"(a), "r"(r)); return o; }
__device__ __forceinline__ void fence_async_smem() { asm volatile("fence.proxy.async.shared::cta;" ::: "memory"); }
__device__ __forceinline__ void fence_async_global() { asm volatile("fence.proxy.async.global;" ::: "memory"); }
__device__ __forceinline__ void bar_sync(int id, int n) { asm volatile("bar.sync %0, %1;" ::"r"(id), "r"(n) : "memory"); }
__device__ __forceinline__ void bar_arrive(int id, int n) { asm volatile("bar.arrive %0, %1;" ::"r"(id), "r"(n) : "memory"); }
__device__ __forceinline__ void cluster_arrive() { asm volatile("barrier.cluster.arrive.relaxed.aligned;" ::: "memory"); }
__device__ __forceinline__ void cluster_wait() { asm volatile("barrier.cluster.wait.aligned;" ::: "memory"); }

__device__ __forceinline__ void ring_load(uint32_t dst, const CUtensorMap* tm, int col, int row16, uint32_t bar) {
    asm volatile("{\n.reg .pred p;\nelect.sync _|p, 0xffffffff;\n"
                 "@p mbarrier.arrive.expect_tx.shared::cta.b64 _, [%2], 16384;\n"
                 "@p cp.async.bulk.tensor.5d.shared::cluster.global.mbarrier::complete_tx::bytes [%0], [%1, {%3, 0, 0, 0, %4}], [%2];\n}"
                 ::"r"(dst), "l"(tm), "r"(bar), "r"(col), "r"(row16) : "memory");
}
__device__ __forceinline__ void ring_load_both(uint32_t dst, const CUtensorMap* tm, int c1, uint32_t bar) {
    asm volatile("{\n.reg .pred p;\nelect.sync _|p, 0xffffffff;\n"
                 "@p cp.async.bulk.tensor.2d.shared::cluster.global.mbarrier::complete_tx::bytes.multicast::cluster [%0], [%1, {0, %3}], [%2], %4;\n}"
                 ::"r"(dst), "l"(tm), "r"(bar), "r"(c1), "h"((uint16_t)3) : "memory");
}
__device__ __forceinline__ void mbar_arrive_peer(uint32_t b) { asm volatile("mbarrier.arrive.relaxed.cluster.shared::cluster.b64 _, [%0];" ::"r"(b) : "memory"); }
__device__ __forceinline__ void prefetch_l2(const void* src, uint32_t bytes) {
    asm volatile("cp.async.bulk.prefetch.L2.global [%0], %1;" ::"l"(src), "r"(bytes) : "memory");
}
__device__ __forceinline__ void peer_copy(uint32_t dst, uint32_t src, uint32_t bytes, uint32_t rbar) {
    asm volatile("{\n.reg .pred p;\nelect.sync _|p, 0xffffffff;\n"
                 "@p cp.async.bulk.shared::cluster.shared::cta.mbarrier::complete_tx::bytes [%0], [%1], %2, [%3];\n}"
                 ::"r"(dst), "r"(src), "r"(bytes), "r"(rbar) : "memory");
}
__device__ __forceinline__ void st_async4(uint32_t dst, uint32_t a, uint32_t b, uint32_t c, uint32_t d, uint32_t bar) {
    asm volatile("st.async.shared::cluster.mbarrier::complete_tx::bytes.v4.b32 [%0], {%1,%2,%3,%4}, [%5];" ::"r"(dst), "r"(a), "r"(b), "r"(c), "r"(d), "r"(bar) : "memory");
}
__device__ __forceinline__ void put_sums(uint32_t dst, uint32_t rdst, float a, float b, uint32_t rbar, bool on) {
    asm volatile("{\n.reg .pred p;\nsetp.ne.u32 p, %5, 0;\n"
                 "@p st.async.shared::cluster.mbarrier::complete_tx::bytes.v2.f32 [%1], {%2,%3}, [%4];\n"
                 "@p st.shared.v2.f32 [%0], {%2,%3};\n}" ::"r"(dst), "r"(rdst), "f"(a), "f"(b), "r"(rbar), "r"((uint32_t)on) : "memory");
}
__device__ __forceinline__ void stsm4(uint32_t a, uint32_t r0, uint32_t r1, uint32_t r2, uint32_t r3) {
    asm volatile("stmatrix.sync.aligned.m8n8.x4.shared.b16 [%0], {%1,%2,%3,%4};" ::"r"(a), "r"(r0), "r"(r1), "r"(r2), "r"(r3) : "memory");
}
__device__ __forceinline__ void ldsm4(uint32_t a, uint32_t& r0, uint32_t& r1, uint32_t& r2, uint32_t& r3) {
    asm volatile("ldmatrix.sync.aligned.m8n8.x4.shared.b16 {%0,%1,%2,%3}, [%4];" : "=r"(r0), "=r"(r1), "=r"(r2), "=r"(r3) : "r"(a) : "memory");
}
__device__ __forceinline__ uint4 lds128(uint32_t a) { uint4 v; asm volatile("ld.shared.v4.b32 {%0,%1,%2,%3}, [%4];" : "=r"(v.x), "=r"(v.y), "=r"(v.z), "=r"(v.w) : "r"(a) : "memory"); return v; }
__device__ __forceinline__ float4 lds128f(uint32_t a) { float4 v; asm volatile("ld.shared.v4.f32 {%0,%1,%2,%3}, [%4];" : "=f"(v.x), "=f"(v.y), "=f"(v.z), "=f"(v.w) : "r"(a) : "memory"); return v; }
__device__ __forceinline__ float2 lds64f(uint32_t a) { float2 v; asm volatile("ld.shared.v2.f32 {%0,%1}, [%2];" : "=f"(v.x), "=f"(v.y) : "r"(a) : "memory"); return v; }
__device__ __forceinline__ uint32_t lds32(uint32_t a) { uint32_t v; asm volatile("ld.shared.b32 %0, [%1];" : "=r"(v) : "r"(a) : "memory"); return v; }
__device__ __forceinline__ void sts128(uint32_t a, uint32_t x, uint32_t y, uint32_t z, uint32_t w) { asm volatile("st.shared.v4.b32 [%0], {%1,%2,%3,%4};" ::"r"(a), "r"(x), "r"(y), "r"(z), "r"(w) : "memory"); }
__device__ __forceinline__ void sts128f(uint32_t a, float x, float y, float z, float w) { asm volatile("st.shared.v4.f32 [%0], {%1,%2,%3,%4};" ::"r"(a), "f"(x), "f"(y), "f"(z), "f"(w) : "memory"); }
__device__ __forceinline__ void sts64f(uint32_t a, float x, float y) { asm volatile("st.shared.v2.f32 [%0], {%1,%2};" ::"r"(a), "f"(x), "f"(y) : "memory"); }
__device__ __forceinline__ void sts32(uint32_t a, uint32_t x) { asm volatile("st.shared.b32 [%0], %1;" ::"r"(a), "r"(x) : "memory"); }
__device__ __forceinline__ void stg128(void* p, uint4 v) { asm volatile("st.global.v4.b32 [%0], {%1,%2,%3,%4};" ::"l"(p), "r"(v.x), "r"(v.y), "r"(v.z), "r"(v.w) : "memory"); }

__device__ __forceinline__ uint32_t pack2(float lo, float hi) { uint32_t r; asm("cvt.rn.bf16x2.f32 %0, %1, %2;" : "=r"(r) : "f"(hi), "f"(lo)); return r; }
__device__ __forceinline__ float blo(uint32_t v) { return __uint_as_float(v << 16); }
__device__ __forceinline__ float bhi(uint32_t v) { return __uint_as_float(v & 0xffff0000u); }
__device__ __forceinline__ uint32_t hmul2(uint32_t a, uint32_t b) { uint32_t r; asm("mul.rn.bf16x2 %0, %1, %2;" : "=r"(r) : "r"(a), "r"(b)); return r; }
__device__ __forceinline__ uint32_t hadd2(uint32_t a, uint32_t b) { uint32_t r; asm("add.rn.bf16x2 %0, %1, %2;" : "=r"(r) : "r"(a), "r"(b)); return r; }
__device__ __forceinline__ uint32_t hsub2(uint32_t a, uint32_t b) { uint32_t r; asm("sub.rn.bf16x2 %0, %1, %2;" : "=r"(r) : "r"(a), "r"(b)); return r; }
__device__ __forceinline__ uint32_t hfma2(uint32_t a, uint32_t b, uint32_t c) { uint32_t r; asm("fma.rn.bf16x2 %0, %1, %2, %3;" : "=r"(r) : "r"(a), "r"(b), "r"(c)); return r; }
__device__ __forceinline__ float tanh_fast(float x) { float r; asm("tanh.approx.f32 %0, %1;" : "=f"(r) : "f"(x)); return r; }
__device__ __forceinline__ float rsq(float x) { float r; asm("rsqrt.approx.ftz.f32 %0, %1;" : "=f"(r) : "f"(x)); return r; }
__device__ __forceinline__ float ex2(float x) { float r; asm("ex2.approx.ftz.f32 %0, %1;" : "=f"(r) : "f"(x)); return r; }

__device__ __forceinline__ uint32_t ld_relaxed(const uint32_t* p) {
    uint32_t v;
    asm volatile("ld.relaxed.gpu.global.u32 %0, [%1];" : "=r"(v) : "l"(p) : "memory");
    return v;
}
__device__ __forceinline__ uint32_t clock32() { uint32_t c; asm volatile("mov.u32 %0, %%clock;" : "=r"(c)::"memory"); return c; }
__device__ __forceinline__ void spin(uint32_t clks) {
    const uint32_t t0 = clock32();
    while (clock32() - t0 < clks) {}
}
__device__ __forceinline__ void flag_wait(const uint32_t* p, uint32_t e, bool mine) {
#pragma unroll 1
    for (int i = 0; i < (1 << 19); i++) {
        if (mine) mine = ld_relaxed(p) != e;
        if (!__any_sync(~0u, mine)) break;
        if (BACKOFF) spin(BACKOFF);
    }
    asm volatile("fence.acquire.gpu;" ::: "memory");
    fence_async_global();
}
__device__ __forceinline__ void st_data(void* p, uint32_t x, uint32_t y, uint32_t z, uint32_t w) {
    asm volatile("st.relaxed.gpu.global.v4.b32 [%0], {%1,%2,%3,%4};" ::"l"(p), "r"(x), "r"(y), "r"(z), "r"(w) : "memory");
}
template <int STRIDE, int N>
__device__ __forceinline__ void ld_data(uint4 (&v)[N], const unsigned char* p) {
    int it = 0;
    bool again;
#pragma unroll 1
    do {
        uint32_t m = 0;
#pragma unroll
        for (int i = 0; i < N; i++)
            asm volatile("ld.relaxed.gpu.global.v4.b32 {%0,%1,%2,%3}, [%4];" : "=r"(v[i].x), "=r"(v[i].y), "=r"(v[i].z), "=r"(v[i].w) : "l"(p + i * STRIDE) : "memory");
#pragma unroll
        for (int i = 0; i < N; i++) m = __vimax3_u32(__vimax3_u32(v[i].x, v[i].y, v[i].z), v[i].w, m);
        again = __any_sync(~0u, m == ~0u) && ++it < (1 << 16);
    } while (again);
}
__device__ __forceinline__ uint32_t ld_epoch() { return ld_relaxed(&g_epoch[blockIdx.x * FS]) + 1; }
__device__ __forceinline__ void flag_set(uint32_t* p, uint32_t e) { asm volatile("st.release.gpu.global.u32 [%0], %1;" ::"l"(p), "r"(e) : "memory"); }

__device__ __forceinline__ uint32_t desc_lo(uint32_t addr) { return ((addr & 0x3FFFF) >> 4) | 0x10000u; }
__device__ __forceinline__ uint64_t mkdesc(uint32_t lo) { return (uint64_t)lo | (0x40000040ull << 32); }
__device__ __forceinline__ void wg_fence() { asm volatile("wgmma.fence.sync.aligned;" ::: "memory"); }
__device__ __forceinline__ void wg_commit() { asm volatile("wgmma.commit_group.sync.aligned;" ::: "memory"); }
template <int N> __device__ __forceinline__ void wg_wait() { asm volatile("wgmma.wait_group.sync.aligned %0;" ::"n"(N) : "memory"); }
template <int N> __device__ __forceinline__ void pin(float (&d)[N]) {
#pragma unroll
    for (int i = 0; i < N; i++) asm volatile("" : "+f"(d[i])::"memory");
}
template <int N> __device__ __forceinline__ void pin(uint32_t (&d)[N]) {
#pragma unroll
    for (int i = 0; i < N; i++) asm volatile("" : "+r"(d[i])::"memory");
}

template <typename Tp, int N> __device__ __forceinline__ void zero(Tp (&d)[N]) {
#pragma unroll
    for (int i = 0; i < N; i++) d[i] = 0;
    pin(d);
}

#define F4(d, i) "+f"(d[i]), "+f"(d[i + 1]), "+f"(d[i + 2]), "+f"(d[i + 3])
#define F16(d, i) F4(d, i), F4(d, i + 4), F4(d, i + 8), F4(d, i + 12)

__device__ __forceinline__ void mma16(float (&d)[4], const uint32_t* a, uint32_t b0, uint32_t b1) {
    asm("mma.sync.aligned.m16n8k16.row.col.f32.bf16.bf16.f32 {%0,%1,%2,%3}, {%4,%5,%6,%7}, {%8,%9}, {%0,%1,%2,%3};"
        : F4(d, 0) : "r"(a[0]), "r"(a[1]), "r"(a[2]), "r"(a[3]), "r"(b0), "r"(b1));
}
template <int N>
__device__ __forceinline__ float row_sum(const uint32_t* x, uint32_t ones = 0x3F803F80u) {
    float c[4] = {};
#pragma unroll
    for (int i = 0; i < N; i += 4) mma16(c, x + i, ones, ones);
    return c[0] + c[2];
}
template <int N>
__device__ __forceinline__ float row_sumsq(const uint32_t* x, int lane) {
    float c0[4] = {}, c1[4] = {};
#pragma unroll
    for (int i = 0; i < N; i += 4) {
        mma16(c0, x + i, x[i], x[i + 2]);
        mma16(c1, x + i, x[i + 1], x[i + 3]);
    }
    return (lane & 4) ? c0[1] + c1[3] : c0[0] + c1[2];
}
__device__ __forceinline__ void mma_sp(float (&d)[32], const uint32_t* a, uint64_t b, uint32_t meta, int acc) {
    asm volatile("{.reg .pred p; setp.ne.b32 p, %38, 0;\n"
                 "wgmma.mma_async.sp.sync.aligned.m64n64k32.f32.bf16.bf16 {%0,%1,%2,%3,%4,%5,%6,%7,%8,%9,%10,%11,%12,%13,%14,%15,%16,%17,%18,%19,%20,%21,%22,%23,%24,%25,%26,%27,%28,%29,%30,%31}, "
                 "{%32,%33,%34,%35}, %36, %37, 0, p, 1, 1, 1;}\n"
                 : F16(d, 0), F16(d, 16) : "r"(a[0]), "r"(a[1]), "r"(a[2]), "r"(a[3]), "l"(b), "r"(meta), "r"(acc));
}
__device__ __forceinline__ void mma_qk(float (&d)[32], uint32_t a0, uint32_t a1, uint32_t a2, uint32_t a3, uint64_t b, int acc) {
    asm volatile("{.reg .pred p; setp.ne.b32 p, %37, 0;\n"
                 "wgmma.mma_async.sync.aligned.m64n64k16.f32.bf16.bf16 {%0,%1,%2,%3,%4,%5,%6,%7,%8,%9,%10,%11,%12,%13,%14,%15,%16,%17,%18,%19,%20,%21,%22,%23,%24,%25,%26,%27,%28,%29,%30,%31}, "
                 "{%32,%33,%34,%35}, %36, p, 1, 1, 0;}\n"
                 : F16(d, 0), F16(d, 16) : "r"(a0), "r"(a1), "r"(a2), "r"(a3), "l"(b), "r"(acc));
}
__device__ __forceinline__ void mma_pv(float (&d)[36], uint32_t a0, uint32_t a1, uint32_t a2, uint32_t a3, uint64_t b) {
    asm volatile("wgmma.mma_async.sync.aligned.m64n72k16.f32.bf16.bf16 {%0,%1,%2,%3,%4,%5,%6,%7,%8,%9,%10,%11,%12,%13,%14,%15,%16,%17,%18,%19,%20,%21,%22,%23,%24,%25,%26,%27,%28,%29,%30,%31,%32,%33,%34,%35}, "
                 "{%36,%37,%38,%39}, %40, 1, 1, 1, 1;\n"
                 : F16(d, 0), F16(d, 16), F4(d, 32) : "r"(a0), "r"(a1), "r"(a2), "r"(a3), "l"(b));
}

__device__ __forceinline__ uint32_t load_code(int n, int r, int w) {
    const int tile = 2 * r + w;
    int m, col, row;
    if (n < 16 || n >= 40) {
        const int k = n < 16 ? n : n - 40;
        m = n < 16 ? 0 : 6;
        if (TWO && n >= 40 && k < 4) { col = 4 * tile + (k & 1); row = (k >> 1) ^ r; }
        else if (k < 8) { col = 4 * tile + (k >> 1); row = n < 16 ? (k & 1) : (k & 1) ^ r; }
        else { m++; col = k < 12 ? tile ^ 2 : tile; row = 2 * (tile ^ (k & 1)) + ((k >> 1) & 1); }
    } else if (n < 32) {
        const int k = n - 16;
        m = 2;
        if (k < 4) { col = tile + ((k & 1) ? 8 : 4); row = (k >> 1) ^ r; }
        else { col = tile; row = (k & 1) ^ r; }
    } else if (n < 34) { m = 3; col = tile; row = n - 32; }
    else if (n < 38) { const int k = n - 34; m = 4; col = tile + 4 * (k & 1); row = (k >> 1) ^ r; }
    else { m = 5; col = tile; row = (n & 1) ^ r; }
    return m | (col << 4) | (row << ((m == 0 || m == 3) ? 10 : 11));
}

__global__ void __cluster_dims__(2, 1, 1) __launch_bounds__(NTHREADS, 1)
conformer_kernel(const Scalars p, const __grid_constant__ Maps m) {
    extern __shared__ __align__(1024) unsigned char smem_raw[];
    const uint32_t sb = smem_u32(smem_raw);
    const uint32_t bars = sb + OFF_BARS;
    const int tid = threadIdx.x;
    const int lane = tid & 31;
    const int warp = __shfl_sync(~0u, tid >> 5, 0);
    const int r = blockIdx.x & 1;
    const int pair = blockIdx.x >> 1;
    const int b = pair >> 5, pt = pair & 31;
    const int ah = pt >> 3, qt = (pt & 7) * 2 + r;
    const int abh = b * 4 + ah;

    TG(30);
    TSINIT();
    TS(0);
    const uint32_t P = sb + OFF_P, H = sb + OFF_H;
    if (warp == 11) {
        if (lane == 0) {
#pragma unroll
            for (int i = 0; i < 2 * NSLOT; i++) mbar_init(bars + (B_FULL + i) * 8, 1);
            asm volatile("fence.mbarrier_init.release.cluster;" ::: "memory");
            fence_async_smem();
        }
        __syncwarp();
        bar_arrive(13, 96);
        cluster_arrive();
    }

    if (warp >= 8) {
        asm volatile("setmaxnreg.dec.sync.aligned.u32 48;");
        if (warp >= 12) {
            cluster_arrive();
            cluster_wait();
            const int ut = tid & 127;
            const uint32_t target = ld_epoch() * 64;
            auto reset_done = [&](int k) {
                bar_sync(11, 128);
                if (ut == 0) {
                    asm volatile("red.release.gpu.global.add.u32 [%0], 1;" ::"l"(&g_reset[(2 * b + k) * 32]) : "memory");
#pragma unroll 1
                    for (int i = 0; i < (1 << 20) && ld_relaxed(&g_reset[(2 * b + k) * 32]) != target; i++) __nanosleep(100);
                    asm volatile("fence.acquire.gpu;" ::: "memory");
                    mbar_arrive(bars + (B_RST + k) * 8);
                }
                __syncwarp();
                TS(13 + k);
            };
#pragma unroll
            for (int i = 0; i < 4; i++)
                st_data(g_kvq + 2097152 + (size_t)((b * 4 + 2 * r + (i >> 1)) * 1024 + pt * 32) * 128 + (i & 1) * 2048 + ut * 16, ~0u, ~0u, ~0u, ~0u);
            reset_done(0);
            bar_sync(6, 384);
#pragma unroll
            for (int i = 0; i < 4; i++) {
                st_data(g_o + (size_t)(b * 128 + qt * 8 + 2 * i + (ut >> 6)) * 4096 + ah * 1024 + (ut & 63) * 16, ~0u, ~0u, ~0u, ~0u);
                if (i < 2) st_data(&g_halo[(pair * 4 + 2 * r + i) * 128 + ut], ~0u, ~0u, ~0u, ~0u);
            }
            reset_done(1);
            const int side = warp & 1, wg = (warp >> 1) & 1, np = side ? pt + 1 : pt - 1;
            const unsigned char* src = reinterpret_cast<const unsigned char*>(&g_halo[(((b * 32 + np) * 4 + 2 * r + wg) * 2 + (side ^ 1)) * 64 + lane]);
            const uint32_t dst = H + 16384 + wg * GCH + side * 5120 + (lane & 7) * 128 + (((lane >> 3) ^ (lane & 7)) << 4);
            uint4 hv[2] = {make_uint4(0, 0, 0, 0), make_uint4(0, 0, 0, 0)};
            bar_sync(8 + wg, 192);
            if (np >= 0 && np < 32) {
                spin(HDELAY);
                ld_data<512>(hv, src);
            }
            stsm4(dst, hv[0].x, hv[0].y, hv[0].z, hv[0].w);
            stsm4(dst ^ 64, hv[1].x, hv[1].y, hv[1].z, hv[1].w);
            __syncwarp();
            if (lane == 0) mbar_arrive(bars + (B_HALO + (warp & 3)) * 8);
            TS(4);
        } else if (warp < 10) {
            const int w = warp - 8;
            const uint32_t ring = sb + OFF_RING + w * NSLOT * SLOT;
            const uint32_t full = bars + (B_FULL + w * NSLOT) * 8;
            cluster_arrive();
            bar_sync(13, 96);
            TS(1);
#pragma unroll
            for (int n = 0; n < NSLOT; n++) {
                if (n == 1) bar_sync(12, 64);
                ring_load(ring + n * SLOT, &m.tm[0], 64 * (8 * r + 4 * w + (n >> 1)), 4 * (n & 1), full + n * 8);
            }
            TS(2);
            const uint32_t code = load_code(lane, r, w) | (load_code(lane + 32, r, w) << 16);
            cluster_wait();
            uint32_t s = 0, ph = 0;
            int n = NSLOT;
#pragma unroll 1
            for (int seg = 0; seg < 2; seg++) {
#pragma unroll 1
                for (; n < (seg == 0 ? 22 : NLOADS); n++) {
                    const uint32_t c = __shfl_sync(~0u, code, n) >> (n & 32 ? 16 : 0);
                    const CUtensorMap* tm = &m.tm[c & 15];
                    const uint32_t col = (c & 0xf0) * 4, row = (c & 0xff00) >> 8, dst = ring + s * SLOT;
                    mbar_wait(full + (B_EMPTY - B_FULL) * 8 + s * 8, ph + (((uint32_t)(size_t)tm | col | row | dst) & p.zero));
                    ring_load(dst, tm, col, row, full + s * 8);
                    if (++s == NSLOT) { s = 0; ph ^= 1; }
                }
                if (seg == 1) break;
                const uint32_t epoch = ld_epoch();
                const uint32_t rdy = bars + (B_RDY + 3 * w) * 8, prdy = mapa(rdy, r ^ 1);
                const int odd = r ^ w;
                const uint32_t* flags = g_flag_kv + (abh * 32 + lane) * KFS;
                auto kv_load = [&](uint32_t sl, int isv, int i) {
                    ring_load_both(ring + sl * SLOT, &m.tm[8], (isv * 64 + abh * 8 + 2 * i + w) * 128, full + sl * 8);
                };
#pragma unroll 1
                for (int i = 0; i < 2; i++) {
                    if (lane < 3 + i) {
                        const uint32_t sl = i ? lane : lane + 2;
                        mbar_wait(full + (B_EMPTY - B_FULL + sl) * 8, i ^ 1);
                        mbar_arrive_tx(full + sl * 8, (i || lane == 2) ? SLOT : 0);
                    }
                    __syncwarp();
                }
                if (lane == 0) mbar_arrive_peer(prdy);
                bar_sync(14, 96);
                spin(KDELAY);
                mbar_wait(rdy, 0);
                flag_wait(flags, epoch, (lane >> 2) == 2 * odd + w);
                TSW(5 + 2 * odd);
                if (!odd) { kv_load(4, 0, 0); bar_arrive(12, 64); }
                else bar_sync(12, 64);
                spin(w ? KD3 : KD2);
                kv_load(odd ^ 1, odd ^ 1, odd);
                flag_wait(flags, epoch, (lane >> 2) == 2 * odd + w + 4);
                mbar_wait(full + (odd ^ 1) * 8, 1);
                kv_load(2 + odd, odd, 2 - odd);
#pragma unroll 1
                for (int i = 0; i < 3; i++) {
                    const uint32_t sl = i ? i - 1 : 4, bo = i == 2 ? 16 : 8;
                    mbar_wait(full + (B_EMPTY - B_FULL + sl) * 8, i != 0);
                    if (lane == 0) mbar_arrive_tx(full + sl * 8, SLOT);
                    if ((i & 1) != odd) {
                        mbar_wait(rdy + bo, 0);
                        kv_load(sl, i != 0, 2 + odd);
                    } else if (lane == 0) mbar_arrive_peer(prdy + bo);
                    __syncwarp();
                }
                n = 32; s = 2; ph = 1;
            }
        } else if (warp == 10) {
            if (lane == 0) {
#pragma unroll
                for (int i = B_EMPTY; i < NBARS; i++) mbar_init(bars + i * 8, i < B_XA ? 4 : 1);
#pragma unroll
                for (int i = B_XA; i <= B_SR; i++) mbar_arrive_tx(bars + i * 8, i < B_XB ? 512 : ((i >= B_INB && i < B_SR) ? 4096 : 8192));
                asm volatile("fence.mbarrier_init.release.cluster;" ::: "memory");
                fence_async_smem();
            }
            __syncwarp();
            cluster_arrive();
            cluster_wait();
        } else {
            const uint32_t kb = (lane < 2 || lane > 5) ? 4096 : (lane == 2 ? 3072 : (lane == 4 ? 2048 : 1024));
            const char* pf = m.w[lane & 7] + blockIdx.x * kb;
            cluster_wait();
            if (lane < PF0) prefetch_l2(pf, kb);
            mbar_wait(bars + B_FULL * 8, 0);
            if (lane >= PF0 && lane < 3) prefetch_l2(pf, kb);
            if (lane >= 1 && lane < 9) asm volatile("prefetch.tensormap [%0];" ::"l"(&m.tm[lane]) : "memory");
            mbar_wait(bars + (B_FULL + 1) * 8, 1);
            if (lane > 2 && lane < 8) prefetch_l2(pf, kb);
            if (lane == 8 && blockIdx.x < 15) prefetch_l2(p.dw + blockIdx.x * 256, 512);
            const uint32_t epoch = ld_epoch();
            bar_sync(4, 288);
            if (lane < 16) flag_set(&g_flag_kv[((b * 4 + 2 * r + (lane >> 3)) * 32 + pt) * KFS + (lane & 7)], epoch);
            __syncwarp();
            bar_arrive(14, 96);
            TSW(8);
        }
        TSDUMP();
        return;
    }

    const int w = warp >> 2, wq = warp & 3;
    const int tile = 2 * r + w;
    const int wt = tid & 127;
    const int c4 = lane & 3;
    const int trow = pt * 32 + 8 * wq;
    uint32_t xr[8];
    uint32_t a[32];
    const char* xrow = reinterpret_cast<const char*>(p.x) + (b * T_ + trow + (lane >> 2)) * 512;
    zero(a);
    if (trow < T_) {
        const char* src = xrow + c4 * 16 + p.zero;
#pragma unroll
        for (int i = 0; i < 8; i++)
            asm volatile("ld.global.nc.v4.b32 {%0,%1,%2,%3}, [%4];" : "=r"(a[4 * i]), "=r"(a[4 * i + 1]), "=r"(a[4 * i + 2]), "=r"(a[4 * i + 3]) : "l"(src + 64 * i));
    }
    cluster_arrive();
    asm volatile("setmaxnreg.inc.sync.aligned.u32 208;");
    const uint32_t rbase = sb + OFF_RING + w * NSLOT * SLOT, fbar = bars + (B_FULL + w * NSLOT) * 8;
    const uint32_t rdesc = desc_lo(rbase);
    auto acq = [&](int n) { mbar_wait(fbar + (n % NSLOT) * 8, (n / NSLOT) & 1); };
    auto rel = [&](int n) { if (lane == 0) mbar_arrive(fbar + (B_EMPTY - B_FULL + n % NSLOT) * 8); };
    const uint32_t foff = (lane & 7) * 128 + (((lane >> 3) ^ (lane & 7)) << 4);
    float v[16];
    const uint32_t xown = __shfl_sync(~0u, P + wt * 16 + tile * 4096, lane), xrem = __shfl_sync(~0u, P + wt * 16 + (r ^ 1) * 8192, lane);
    const uint32_t sbuf = __shfl_sync(~0u, sb + OFF_MISC + 1024 + (8 * wq + (lane >> 2)) * 32, lane);
    const uint32_t sown = __shfl_sync(~0u, sbuf + tile * 8, lane);
    const uint32_t peer = __shfl_sync(~0u, mapa(sb, r ^ 1) - sb, lane);
    const uint32_t hbuf = __shfl_sync(~0u, H + w * 4096 + wt * 16, lane);
    const uint32_t meta = __shfl_sync(~0u, 0xEEEE4444u + p.zero, lane);
    cluster_wait();
    TS(56);
    float mean, msq;
    const int mir = wq < 2 ? 7 : 0;
    uint32_t dwr[15] = {};

#pragma unroll
    for (int ph = 0; ph < 5; ph++) {
        uint4 o0, o1;
        if (ph == 0) {
            const uint32_t one = 0x3F803F80u + ((xown | xrem | sbuf | sown | hbuf | foff | rdesc | fbar) & p.zero);
            mean = ((row_sum<8>(a, one) + row_sum<8>(a + 8, one)) + (row_sum<8>(a + 16, one) + row_sum<8>(a + 24, one))) * (1.f / 256.f);
            TS(57);
        } else {
            const uint32_t xa = bars + (B_XA + ph) * 8;
#pragma unroll
            for (int j = 0; j < 8; j++) xr[j] = pack2(v[2 * j], v[2 * j + 1]);
            const float s = row_sum<8>(xr), q = row_sumsq<8>(xr, lane);
            if (ph < 4) {
                sts128(xown, xr[0], xr[1], xr[2], xr[3]);
                sts128(xown + 2048, xr[4], xr[5], xr[6], xr[7]);
            }
            put_sums(sown, sown + peer, s, q, xa + peer, c4 == (lane >> 3));
            bar_sync(10, 256);
            if (ph < 4) {
                o0 = lds128(xown ^ 4096); o1 = lds128((xown ^ 4096) + 2048);
                st_async4(xown + peer, xr[0], xr[1], xr[2], xr[3], xa + (B_XB - B_XA) * 8 + peer);
                st_async4(xown + peer + 2048, xr[4], xr[5], xr[6], xr[7], xa + (B_XB - B_XA) * 8 + peer);
            }
            TS(57 + ph);
            if (ph == 3) acq(0);
            if (ph == 1) acq(16);
            mbar_wait(xa, 0);
            const float4 u0 = lds128f(sbuf), u1 = lds128f(sbuf + 16);
            mean = ((u0.x + u0.z) + (u1.x + u1.z)) * (1.f / 256.f);
            msq = ((u0.y + u0.w) + (u1.y + u1.w)) * (1.f / 256.f);
        }
        if (ph == 4) break;
        const uint32_t mean2 = pack2(mean, mean);
        auto centre = [&](int i, const uint4& u) {
            a[i] = hsub2(u.x, mean2); a[i + 1] = hsub2(u.y, mean2); a[i + 2] = hsub2(u.z, mean2); a[i + 3] = hsub2(u.w, mean2);
        };
        if (ph == 0) {
#pragma unroll
            for (int j = 0; j < 32; j++) a[j] = hsub2(a[j], mean2);
            zero(xr);
            if (trow < T_) {
                const char* src = xrow + tile * 128 + c4 * 4 + (mean2 & p.zero);
#pragma unroll
                for (int j = 0; j < 8; j++) asm volatile("ld.global.nc.b32 %0, [%1];" : "=r"(xr[j]) : "l"(src + 16 * j));
            }
            mean -= blo(mean2);
            msq = __shfl_sync(~0u, row_sumsq<16>(a, lane) + row_sumsq<16>(a + 16, lane), (lane & 28) + (lane >> 3)) * (1.f / 256.f);
            acq(0);
        } else {
#pragma unroll
            for (int j = 0; j < 8; j++) a[j] = hsub2(xr[j], mean2);
            centre(8, o0); centre(12, o1);
        }
        const float rstd = rsq(fmaxf(fmaf(-mean, mean, msq), 0.f) + 1e-5f);
        auto gather_peer = [&]() {
            mbar_wait(bars + (B_XB + ph) * 8, 0);
#pragma unroll
            for (int i = 0; i < 4; i++) centre(16 + 4 * i, lds128(xrem + i * 2048));
        };
        auto sp = [&](float (&d)[32], int n, const uint32_t* af, int flip, int acc) {
            const uint32_t lo = rdesc + p.zero * (ph * 64 + n + 1) + (n % NSLOT) * (SLOT >> 4);
            const uint64_t b0 = mkdesc(lo + flip * 512), b1 = mkdesc(lo + (flip ^ 1) * 512);
            wg_fence();
            mma_sp(d, af, b0, meta, acc);
            mma_sp(d, af + 4, b0 + 256, meta, 1);
            mma_sp(d, af + 8, b1, meta, 1);
            mma_sp(d, af + 12, b1 + 256, meta, 1);
            wg_commit();
        };
        float d0[32], d1[32];

        if (ph == 0 || ph == 3) {
            uint32_t h[32], ho[32];
            const float rs = 0.5f * rstd;
            const uint32_t inb = bars + (B_INB + (ph & 2) + w) * 8;
            bool ready = true;
            const int eager = ph ? (TWO ? EAGER + 5 : EAGER) : EAGER - 1;
            auto step = [&](float (&d)[32], int n, const uint32_t* af, int flip, int acc, auto work) {
                if (!ready) acq(n);
                if (((TURN >> n) & 1) && w == 1) bar_sync(7, 256);
                sp(d, n, af, flip, acc);
                if (n > 0 && ((TURN >> (n - 1)) & 1) && w == 0) bar_arrive(7, 256);
                if (n < 15) ready = mbar_test(fbar + ((n + 1) % NSLOT) * 8, ((n + 1) / NSLOT) & 1);
                wg_wait<1>();
                if (n > 0 && !((eager >> (n - 1)) & 1)) rel(n - 1);
                const uint32_t tie = work() & p.zero;
                if ((eager >> n) & 1) {
                    if (p.zero < n + ph + 1) wg_wait<0>();
                    if (lane == 0) mbar_arrive(fbar + (B_EMPTY - B_FULL + n % NSLOT) * 8 + tie);
                }
            };
            auto none = []() { return 0u; };
            const int fl = ph ? w : 0;
            auto fetch = [&](int i) {
                bar_sync(10, 256);
                const uint4 u0 = lds128((hbuf ^ 4096) + (i & 1) * 8192), u1 = lds128((hbuf ^ 4096) + (i & 1) * 8192 + 2048);
                ho[8 * i] = u0.x; ho[8 * i + 1] = u0.y; ho[8 * i + 2] = u0.z; ho[8 * i + 3] = u0.w;
                ho[8 * i + 4] = u1.x; ho[8 * i + 5] = u1.y; ho[8 * i + 6] = u1.z; ho[8 * i + 7] = u1.w;
                return u0.x | u1.x;
            };
            auto act = [&](float (&d)[32], int i) {
                if (i > 0) fetch(i - 1);
                pin(d);
#pragma unroll
                for (int j = 0; j < 8; j++) {
                    const float u0 = (d[4 * j] + d[4 * j + 2]) * rs, u1 = (d[4 * j + 1] + d[4 * j + 3]) * rs;
                    h[8 * i + j] = pack2(fmaf(u0, tanh_fast(u0), u0), fmaf(u1, tanh_fast(u1), u1));
                }
                sts128(hbuf + (i & 1) * 8192, h[8 * i], h[8 * i + 1], h[8 * i + 2], h[8 * i + 3]);
                sts128(hbuf + (i & 1) * 8192 + 2048, h[8 * i + 4], h[8 * i + 5], h[8 * i + 6], h[8 * i + 7]);
                return 0u;
            };
            TS(1 + (ph & 2) * 10);
            if (TWO && ph) {
                step(d0, 0, a, fl, 0, none);
                step(d1, 1, a, fl, 0, [&]() { gather_peer(); return 0u; });
                TS(32);
                step(d0, 2, a + 16, 0, 1, none);
                step(d1, 3, a + 16, 0, 1, [&]() { return act(d0, 0); });
            } else {
                step(d0, 0, a, fl, 0, [&]() { if (ph) gather_peer(); return 0u; });
                TS(32);
                step(d0, 1, a + 16, 0, 1, none);
                step(d1, 2, a, fl, 0, [&]() { return act(d0, 0); });
                step(d1, 3, a + 16, 0, 1, none);
            }
            step(d0, 4, a, fl, 0, [&]() { return act(d1, 1); });
            TS(33);
            step(d0, 5, a + 16, 0, 1, none);
            step(d1, 6, a, fl, 0, [&]() { return act(d0, 2); });
            step(d1, 7, a + 16, 0, 1, none);
            step(d0, 8, h, 0, 0, [&]() { act(d1, 3); return fetch(3); });
            TS(2 + (ph & 2) * 10);
            step(d0, 9, ho, 0, 1, none);
            step(d0, 10, h + 16, 0, 1, none);
            step(d0, 11, ho + 16, 0, 1, none);
            uint32_t pk[8];
            auto pack_out = [&]() {
                pin(d0);
#pragma unroll
                for (int j = 0; j < 8; j++) pk[j] = pack2(d0[4 * j] + d0[4 * j + 2], d0[4 * j + 1] + d0[4 * j + 3]);
            };
            auto send = [&](int i) { st_async4(hbuf + 16384 + i * 2048 + peer, pk[4 * i], pk[4 * i + 1], pk[4 * i + 2], pk[4 * i + 3], inb + peer); };
            step(d1, 12, h, 0, 0, [&]() { pack_out(); if (SND != 1) send(0); if (SND == 0) send(1); return 0u; });
            TS(34);
            step(d1, 13, ho, 0, 1, [&]() { if (SND == 1) send(0); if (SND) send(1); return 0u; });
            step(d1, 14, h + 16, 0, 1, none);
            step(d1, 15, ho + 16, 0, 1, none);
            mbar_wait(inb, 0);
#pragma unroll
            for (int i = 0; i < 2; i++) {
                const uint4 u = lds128(hbuf + 16384 + i * 2048);
                const uint32_t p0[4] = {u.x, u.y, u.z, u.w};
#pragma unroll
                for (int j = 0; j < 4; j++) {
                    v[8 * i + 2 * j] = fmaf(0.5f, blo(p0[j]), blo(xr[4 * i + j]));
                    v[8 * i + 2 * j + 1] = fmaf(0.5f, bhi(p0[j]), bhi(xr[4 * i + j]));
                }
            }
            wg_wait<0>();
            pin(d1);
            rel(15);
            TS(3 + (ph & 2) * 10);
#pragma unroll
            for (int j = 0; j < 8; j++) {
                v[2 * j] = fmaf(0.5f, d1[4 * j] + d1[4 * j + 2], v[2 * j]);
                v[2 * j + 1] = fmaf(0.5f, d1[4 * j + 1] + d1[4 * j + 3], v[2 * j + 1]);
            }
#pragma unroll
            for (int i = 0; i < 15; i++) dwr[i] = 0;
            continue;
        }

        auto residual = [&](int n) {
            wg_wait<1>();
            rel(n);
            wg_wait<0>();
            pin(d0);
            rel(n + 1);
#pragma unroll
            for (int j = 0; j < 8; j++) {
                v[2 * j] = d0[4 * j] + d0[4 * j + 2] + blo(xr[j]);
                v[2 * j + 1] = d0[4 * j + 1] + d0[4 * j + 3] + bhi(xr[j]);
            }
        };

        if (ph == 2) {
            TS(39);
            sp(d0, 34, a, w, 0);
            acq(35);
            sp(d1, 35, a, w, 0);
            acq(36); acq(37);
            gather_peer();
            sp(d0, 36, a + 16, 0, 1);
            sp(d1, 37, a + 16, 0, 1);
            wg_wait<2>();
            rel(34);
            if (!(LATE & 1)) rel(35);
            acq(38);
            const float rs = trow < T_ ? 0.5f * rstd : 0.f;
            wg_wait<0>();
            pin(d0); pin(d1);
            if (!(LATE & 2)) { rel(36); rel(37); }
            TS(18);
            uint32_t pk[8];
#pragma unroll
            for (int j = 0; j < 8; j++) {
                const float u0 = (d0[4 * j] + d0[4 * j + 2]) * rs, u1 = (d0[4 * j + 1] + d0[4 * j + 3]) * rs;
                const float t0 = tanh_fast((d1[4 * j] + d1[4 * j + 2]) * rs), t1 = tanh_fast((d1[4 * j + 1] + d1[4 * j + 3]) * rs);
                pk[j] = pack2(fmaf(u0, t0, u0), fmaf(u1, t1, u1));
            }
            if (wq == 0 || wq == 3) {
                uint4* hp = &g_halo[((pair * 4 + tile) * 2 + (wq & 1)) * 64 + lane];
                st_data(hp, pk[0], pk[1], pk[2], pk[3]);
                st_data(hp + 32, pk[4], pk[5], pk[6], pk[7]);
            }
            const uint32_t gs = H + 16384 + w * GCH + wq * 1024;
            stsm4(gs + 1024 + foff, pk[0], pk[1], pk[2], pk[3]);
            stsm4(gs + 1024 + (foff ^ 64), pk[4], pk[5], pk[6], pk[7]);
            bar_sync(8 + w, 192);
            TS(26);
            uint32_t ca[8], cb[8];
            const int e = (wq & 1) * 4;
            const uint32_t lo = ((mir ^ e) * 144) ^ (lane * 4);
            const int dir = mir ? -1024 : 1024;
            const uint32_t gb = H + 16384 + w * GCH + (mir ? 3072 : 2048) + lo, sown_ = H + tile * HCH, so = sown_ + (mir ? 1024 : 2048) + lo;
            auto finish = [&](int i) {
                const uint32_t c = hadd2(ca[i], cb[i]);
                const float h0 = blo(c), h1 = bhi(c);
                sts32((so + (i >> 2) * dir) ^ ((i & 3) * 144), pack2(fmaf(h0, tanh_fast(h0), h0), fmaf(h1, tanh_fast(h1), h1)));
            };
#pragma unroll
            for (int k = 0; k < 26; k++) {
                if (k == 19) {
#pragma unroll
                    for (int i = 0; i < 4; i++) finish(i);
                    fence_async_smem();
                    bar_sync(2 + w, 128);
                    if (wq == 0) peer_copy(mapa(sown_ + 1024, r ^ 1), sown_ + 1024, 2048, mapa(bars + B_SR * 8, r ^ 1));
                    mbar_wait(bars + (B_HALO + 2 * w + (wq >> 1)) * 8, 0);
                    if (LATE & 1) rel(35);
                    if (LATE & 2) { rel(36); rel(37); }
                    TS(27);
                }
                const uint32_t g = lds32((gb + (((k + 1) & 4) ? ((k + 1) >> 3) + (wq & 1) : ((k + 1) >> 3)) * dir) ^ (((k + 1) & 7) * 144));
#pragma unroll
                for (int i = 0; i < 8; i++) {
                    const int tap = k - (i & 3) - 2 * (i & 4);
                    if (tap == 0) ca[i] = hmul2(g, dwr[0]);
                    else if (tap > 0 && tap < 8) ca[i] = hfma2(g, dwr[tap], ca[i]);
                    else if (tap == 8) cb[i] = hmul2(g, dwr[8]);
                    else if (tap > 8 && tap < 15) cb[i] = hfma2(g, dwr[tap], cb[i]);
                }
            }
#pragma unroll
            for (int i = 4; i < 8; i++) finish(i);
            fence_async_smem();
            bar_sync(12 + (warp >> 1), 64);
            if (wq == 0 || wq == 3) peer_copy(mapa(sown_ + wq * 1024, r ^ 1), sown_ + wq * 1024, 1024, mapa(bars + B_SR * 8, r ^ 1));
            bar_sync(10, 256);
            TS(19);
            auto frags = [&](int i, int half) {
                const uint32_t src = H + 2 * half * HCH + wq * 1024;
#pragma unroll
                for (int k = 0; k < 4; k++) ldsm4(src + (k >> 1) * HCH + (foff ^ ((k & 1) * 64)), a[i + 4 * k], a[i + 4 * k + 1], a[i + 4 * k + 2], a[i + 4 * k + 3]);
            };
            frags(0, r);
            sp(d0, 38, a, 0, 0);
            acq(39);
            mbar_wait(bars + B_SR * 8, 0);
            frags(16, r ^ 1);
            sp(d0, 39, a + 16, 0, 1);
            residual(38);
            TS(20);
            continue;
        }

        {
            TS(11);
            unsigned char* g = g_kvq + (size_t)((b * 4 + tile) * 1024 + trow) * 128;
            const uint32_t uo = (lane >> 2) * 128 + ((c4 ^ (lane >> 2)) << 4);
            auto put = [&](float (&d)[32], int i) {
                pin(d);
                uint32_t pk[8];
#pragma unroll
                for (int j = 0; j < 8; j++) pk[j] = pack2((d[4 * j] + d[4 * j + 2]) * rstd, (d[4 * j + 1] + d[4 * j + 3]) * rstd);
                if (i < 2) {
                    stg128(g + i * 1048576 + uo, make_uint4(pk[0], pk[1], pk[2], pk[3]));
                    stg128(g + i * 1048576 + (uo ^ 64), make_uint4(pk[4], pk[5], pk[6], pk[7]));
                } else {
                    const uint32_t stg = H + warp * 1024;
                    sts128(stg + uo, pk[0], pk[1], pk[2], pk[3]);
                    sts128(stg + (uo ^ 64), pk[4], pk[5], pk[6], pk[7]);
                    __syncwarp();
                    ldsm4(stg + foff, pk[0], pk[1], pk[2], pk[3]);
                    ldsm4(stg + (foff ^ 64), pk[4], pk[5], pk[6], pk[7]);
                    st_data(g + 2097152 + lane * 16, pk[0], pk[1], pk[2], pk[3]);
                    st_data(g + 2097152 + 512 + lane * 16, pk[4], pk[5], pk[6], pk[7]);
                }
            };
            sp(d0, 16, a, w, 0);
            acq(17);
            sp(d1, 17, a, w, 0);
            gather_peer();
            acq(18);
            sp(d0, 18, a + 16, 0, 1);
            wg_wait<1>();
            rel(16); rel(17);
            acq(19);
            sp(d1, 19, a + 16, 0, 1);
            wg_wait<1>();
            rel(18);
            put(d0, 0);
            wg_wait<0>();
            rel(19);
            TS(37);
            put(d1, 1);
            bar_arrive(4, 288);
            TS(38);
            acq(20);
            sp(d0, 20, a, w, 0);
            acq(21);
            sp(d0, 21, a + 16, 0, 1);
            acq(22); acq(23);
            rel(22); rel(23);
            mbar_wait(bars + B_RST * 8, 0);
            wg_wait<0>();
            rel(20); rel(21);
            put(d0, 2);
            TS(12);
        }

        {
            constexpr float CS = 0.125f * 1.4426950408889634f;
            float sa[32], sb2[32], o[36];
            uint32_t pa[16], pb[16], q[16];
            float n0 = INFINITY, n1 = INFINITY;
            zero(o); zero(pa); zero(pb); zero(sb2);
            const uint32_t ones = sb + OFF_MISC + 2048;
            { const uint32_t c = w ? 0u : 0x3F803F80u; sts128(ones + tid * 16, c, c, c, c); }
            fence_async_smem();
            bar_sync(10, 256);
            const uint32_t vdesc = rdesc + ((((ones - rbase) >> 4) - 1) << 16);
            auto qk_issue = [&](float (&s)[32], uint32_t lo) {
                const uint64_t kd = mkdesc(lo);
                wg_fence();
#pragma unroll
                for (int k = 0; k < 4; k++) mma_qk(s, q[4 * k], q[4 * k + 1], q[4 * k + 2], q[4 * k + 3], kd + 2 * k, k != 0);
                wg_commit();
            };
            auto both_issue = [&](float (&s)[32], uint32_t klo, uint32_t (&pp)[16], uint32_t vlo) {
                const uint64_t kd = mkdesc(klo), vd = mkdesc(vlo);
                wg_fence();
#pragma unroll
                for (int k = 0; k < 4; k++) {
                    mma_pv(o, pp[4 * k], pp[4 * k + 1], pp[4 * k + 2], pp[4 * k + 3], vd - k * (128 * 65535));
                    mma_qk(s, q[4 * k], q[4 * k + 1], q[4 * k + 2], q[4 * k + 3], kd + 2 * k, k != 0);
                }
                wg_commit();
            };
            auto new_max = [&](float (&s)[32], int nj, float& x0, float& x1) {
                x0 = s[0]; x1 = s[2];
#pragma unroll
                for (int j = 0; j < nj; j++) {
                    x0 = fmaxf(x0, fmaxf(s[4 * j], s[4 * j + 1]));
                    x1 = fmaxf(x1, fmaxf(s[4 * j + 2], s[4 * j + 3]));
                }
                x0 = fmaxf(x0, __shfl_xor_sync(~0u, x0, 1)); x1 = fmaxf(x1, __shfl_xor_sync(~0u, x1, 1));
                x0 = fmaxf(x0, __shfl_xor_sync(~0u, x0, 2)); x1 = fmaxf(x1, __shfl_xor_sync(~0u, x1, 2));
                x0 = fminf(n0, fmaf(x0, -CS, -20.f)); x1 = fminf(n1, fmaf(x1, -CS, -20.f));
            };
            auto probs = [&](float (&s)[32], uint32_t (&pp)[16], bool ready, bool tail, auto wait) {
                uint32_t any = 0;
#pragma unroll
                for (int i = 0; i < 16; i++) {
                    pp[i] = pack2(ex2(fmaf(s[2 * i], CS, (i & 1) ? n1 : n0)), ex2(fmaf(s[2 * i + 1], CS, (i & 1) ? n1 : n0)));
                    any |= pp[i];
                }
                wg_wait<0>();
                pin(sa); pin(sb2); pin(o); pin(pa); pin(pb);
                if (__builtin_expect(__any_sync(~0u, (any & 0x40004000u) || !ready), 0)) {
                    wait();
                    if (__any_sync(~0u, any & 0x40004000u)) {
                        if (tail) {
#pragma unroll
                            for (int i = 20; i < 32; i++) s[i] = -INFINITY;
                        }
                        float x0, x1;
                        new_max(s, 8, x0, x1);
                        const float sc0 = ex2(x0 - n0), sc1 = ex2(x1 - n1);
                        n0 = x0; n1 = x1;
#pragma unroll
                        for (int j = 0; j < 9; j++) { o[4 * j] *= sc0; o[4 * j + 1] *= sc0; o[4 * j + 2] *= sc1; o[4 * j + 3] *= sc1; }
#pragma unroll
                        for (int i = 0; i < 16; i++)
                            pp[i] = pack2(ex2(fmaf(s[2 * i], CS, (i & 1) ? n1 : n0)), ex2(fmaf(s[2 * i + 1], CS, (i & 1) ? n1 : n0)));
                    }
                }
            };
            {
                uint4 u[4];
                const unsigned char* src = g_kvq + 2097152 + (size_t)(abh * 1024 + qt * 64 + wq * 16) * 128 + lane * 16;
                spin(QGATE);
                ld_data<512>(u, src);
#pragma unroll
                for (int k = 0; k < 2; k++) {
                    q[8 * k] = u[k].x; q[8 * k + 1] = u[k + 2].x; q[8 * k + 2] = u[k].y; q[8 * k + 3] = u[k + 2].y;
                    q[8 * k + 4] = u[k].z; q[8 * k + 5] = u[k + 2].z; q[8 * k + 6] = u[k].w; q[8 * k + 7] = u[k + 2].w;
                }
                pin(q);
            }
            TS(40);
            acq(24);
            TS(13);
            qk_issue(sa, rdesc + (24 % NSLOT) * (SLOT >> 4));
            wg_wait<0>();
            pin(sa);
            {
                float x0, x1;
                new_max(sa, NJ0, x0, x1);
                n0 = x0; n1 = x1;
            }
            bar_arrive(6, 384);
            uint32_t vd = vdesc - (SLOT >> 4) * 65535u, kd = rdesc, vb = fbar + 8, kb = fbar;
            uint32_t vlast = vdesc - 4 * (SLOT >> 4) * 65535u, klast = rdesc + 4 * (SLOT >> 4) + 512;
            uint32_t kprev = fbar + 32, vprev = bars + (B_SINK - (B_EMPTY - B_FULL)) * 8;
#pragma unroll 1
            for (int it = 0; it < 4; it++) {
                both_issue(sb2, klast, pb, vlast);
                probs(sa, pa, mbar_test(vb, it < 2) & mbar_test(kb, it < 3), false, [&]() { mbar_wait(vb, it < 2); mbar_wait(kb, it < 3); });
                TS(41 + it * 4);
                if (lane == 0) mbar_arrive(kprev + (B_EMPTY - B_FULL) * 8);
                if (lane == 0) mbar_arrive(vprev + (B_EMPTY - B_FULL) * 8);
                both_issue(sa, kd, pa, vd);
                const int dv = it == 0 ? 2 : (it == 1 ? -3 : 1);
                kprev = kb; vprev = vb; vlast = vd - 512 * 65535u; klast = kd + 512;
                vd -= dv * (SLOT >> 4) * 65535u; vb += dv * 8;
                kd += (it == 2 ? -3 : 2) * (SLOT >> 4); kb = it == 2 ? vb : kb + 16;
                probs(sb2, pb, true, it == 3 && w == 1, []() {});
                TS(43 + it * 4);
            }
            wg_fence();
#pragma unroll
            for (int k = 0; k < 4; k++)
                mma_pv(o, pb[4 * k], pb[4 * k + 1], pb[4 * k + 2], pb[4 * k + 3], mkdesc(vlast - k * (128 * 65535) + (k > 1 ? w * ((k - 1) << 22) : 0)));
            wg_commit();
            const int row = wq * 16 + (lane >> 2);
            const uint32_t ml = sb + OFF_MISC;
            mbar_wait(bars + (B_RST + 1) * 8, 0);
            wg_wait<0>();
            pin(o); pin(pb); pin(sa); pin(sb2);
            if (!(LATE & 4)) rel(31);
            const float l0 = o[32], l1 = o[34];
            if (c4 == 0) { sts64f(ml + w * 512 + row * 8, n0, l0); sts64f(ml + w * 512 + row * 8 + 64, n1, l1); }
            TS(14);
            float mine[16];
#pragma unroll
            for (int j = 0; j < 4; j++) {
                if (w == 0) sts128f(H + j * 2048 + wt * 16, o[16 + 4 * j], o[17 + 4 * j], o[18 + 4 * j], o[19 + 4 * j]);
                else sts128f(H + 8192 + j * 2048 + wt * 16, o[4 * j], o[4 * j + 1], o[4 * j + 2], o[4 * j + 3]);
            }
#pragma unroll
            for (int i = 0; i < 16; i++) mine[i] = w == 0 ? o[i] : o[16 + i];
            bar_sync(10, 256);
            const float2 u0 = lds64f(ml + (w ^ 1) * 512 + row * 8), u1 = lds64f(ml + (w ^ 1) * 512 + row * 8 + 64);
            const float x0 = fminf(n0, u0.x), x1 = fminf(n1, u1.x);
            float a0 = ex2(x0 - n0), b0 = ex2(x0 - u0.x), a1 = ex2(x1 - n1), b1 = ex2(x1 - u1.x);
            const float i0 = __fdividef(1.f, fmaf(a0, l0, b0 * u0.y)), i1 = __fdividef(1.f, fmaf(a1, l1, b1 * u1.y));
            a0 *= i0; b0 *= i0; a1 *= i1; b1 *= i1;
            uint32_t pk[8];
#pragma unroll
            for (int j = 0; j < 4; j++) {
                const float4 v = lds128f(H + (w ^ 1) * 8192 + j * 2048 + wt * 16);
                pk[2 * j] = pack2(fmaf(a0, mine[4 * j], b0 * v.x), fmaf(a0, mine[4 * j + 1], b0 * v.y));
                pk[2 * j + 1] = pack2(fmaf(a1, mine[4 * j + 2], b1 * v.z), fmaf(a1, mine[4 * j + 3], b1 * v.w));
            }
            unsigned char* dst = g_o + (size_t)(b * 128 + qt * 8 + 2 * wq) * 4096 + ah * 1024 + w * 512 + lane * 16;
            st_data(dst, pk[0], pk[2], pk[4], pk[6]);
            st_data(dst + 4096, pk[1], pk[3], pk[5], pk[7]);
            if (tid == 0) asm volatile("red.relaxed.gpu.global.add.u32 [%0], 1;" ::"l"(&g_epoch[blockIdx.x * FS]) : "memory");
            TS(15);
        }

        {
            const uint32_t* dp = reinterpret_cast<const uint32_t*>(p.dw + (mir ? 14 * 256 : 0) + tile * 64) + lane;
#pragma unroll
            for (int i = 0; i < 15; i++) asm volatile("ld.global.nc.b32 %0, [%1];" : "=r"(dwr[i]) : "l"(dp + i * (mir ? -128 : 128)));
            acq(32); acq(33); acq(34);
            uint4 u[8];
            ld_data<512>(u, g_o + (size_t)(b * 128 + pt * 4 + wq) * 4096 + lane * 16);
#pragma unroll
            for (int i = 0; i < 8; i++) { a[4 * i] = u[i].x; a[4 * i + 1] = u[i].y; a[4 * i + 2] = u[i].z; a[4 * i + 3] = u[i].w; }
            if (LATE & 4) rel(31);
            TS(16);
            sp(d0, 32, a, 0, 0);
            sp(d0, 33, a + 16, 0, 1);
#pragma unroll
            for (int i = 0; i < 15; i++) dwr[i] = hmul2(dwr[i], 0x3F003F00u);
            residual(32);
            TS(17);
        }
    }

    cluster_arrive();
    TS(24);
    {
        const float rstd = rsq(fmaxf(fmaf(-mean, mean, msq), 0.f) + 1e-5f), nb = -mean * rstd;
#pragma unroll
        for (int j = 0; j < 8; j++) xr[j] = pack2(fmaf(v[2 * j], rstd, nb), fmaf(v[2 * j + 1], rstd, nb));
        const uint32_t stg = P + 16384 + warp * 1024;
        stsm4(stg + foff, xr[0], xr[1], xr[2], xr[3]);
        stsm4(stg + (foff ^ 64), xr[4], xr[5], xr[6], xr[7]);
        __syncwarp();
        const uint32_t src = stg + (lane >> 3) * 128 + (((lane & 7) ^ (lane >> 3)) << 4);
        const uint4 u0 = lds128(src), u1 = lds128((src + 512) ^ 64);
        __nv_bfloat16* dst = p.out + (size_t)(b * T_ + trow + (lane >> 3)) * 256 + tile * 64 + (lane & 7) * 8;
        if (trow < T_) { stg128(dst, u0); stg128(dst + 4 * 256, u1); }
    }
    TS(25);
    TG(31);
    TSDUMP();
    cluster_wait();
}

typedef CUresult (*EncodeFn)(CUtensorMap*, CUtensorMapDataType, cuuint32_t, void*, const cuuint64_t*, const cuuint64_t*,
                             const cuuint32_t*, const cuuint32_t*, CUtensorMapInterleave, CUtensorMapSwizzle,
                             CUtensorMapL2promotion, CUtensorMapFloatOOBfill);

}

extern "C" void kernel_launch(void* const* d_in, const int* in_sizes, int n_in, void* d_out, int out_size) {
    static EncodeFn encode = nullptr;
    if (!encode) {
        void* fn = nullptr;
        cudaDriverEntryPointQueryResult qr;
        cudaGetDriverEntryPoint("cuTensorMapEncodeTiled", &fn, cudaEnableDefault, &qr);
        encode = (EncodeFn)fn;
        cudaFuncSetAttribute(conformer_kernel, cudaFuncAttributeMaxDynamicSharedMemorySize, SMEM_LAUNCH);
    }
    Scalars p;
    Maps m;
    const cuuint32_t ones[5] = {1, 1, 1, 1, 1};
    const int idx[8] = {1, 2, 3, 4, 5, 7, 8, 9};
    const int rows[8] = {256, 1024, 256, 256, 256, 256, 256, 1024};
    const int cols[8] = {1024, 256, 768, 256, 512, 256, 1024, 256};
    for (int i = 0; i < 8; i++) {
        const cuuint64_t pitch = (cuuint64_t)cols[i] * 2;
        const bool f = i != 0 && i != 3;
        const cuuint64_t dims[5] = {(cuuint64_t)cols[i], f ? 2u : 4u, f ? 2u : 4u, f ? 4u : 2u, (cuuint64_t)rows[i] / (f ? 16 : 32)};
        const cuuint64_t strides[4] = {pitch, pitch * 8, pitch * (f ? 2 : 4), pitch * (f ? 16 : 32)};
        const cuuint32_t box[5] = {64, f ? 2u : 4u, f ? 2u : 4u, f ? 4u : 2u, f ? 8u : 4u};
        encode(&m.tm[i], CU_TENSOR_MAP_DATA_TYPE_BFLOAT16, 5, d_in[idx[i]], dims, strides, box, ones, CU_TENSOR_MAP_INTERLEAVE_NONE,
               CU_TENSOR_MAP_SWIZZLE_128B, CU_TENSOR_MAP_L2_PROMOTION_L2_128B, CU_TENSOR_MAP_FLOAT_OOB_FILL_NONE);
        m.w[i] = (const char*)d_in[idx[i]];
    }
    {
        void* kv = nullptr;
        cudaGetSymbolAddress(&kv, g_kvq);
        const cuuint64_t dims[2] = {64, 16384};
        const cuuint64_t strides[1] = {128};
        const cuuint32_t box[2] = {64, 128};
        encode(&m.tm[8], CU_TENSOR_MAP_DATA_TYPE_BFLOAT16, 2, kv, dims, strides, box, ones, CU_TENSOR_MAP_INTERLEAVE_NONE,
               CU_TENSOR_MAP_SWIZZLE_NONE, CU_TENSOR_MAP_L2_PROMOTION_L2_128B, CU_TENSOR_MAP_FLOAT_OOB_FILL_NONE);
    }
    p.x = (const __nv_bfloat16*)d_in[0];
    p.dw = (const __nv_bfloat16*)d_in[6];
    p.out = (__nv_bfloat16*)d_out;
    p.zero = 0;
    conformer_kernel<<<NCTA, NTHREADS, SMEM_LAUNCH>>>(p, m);
}
```

```cpp
#include <cuda_runtime.h>
#include <cuda_bf16.h>
#include <cuda.h>
#include <stdint.h>

namespace {

constexpr int T_ = 1000;
constexpr int NCTA = 128;
constexpr int NTHREADS = 512;
constexpr int NSLOT = 5;
constexpr int SLOT = 16384;
constexpr int NLOADS = 56;

constexpr uint32_t OFF_RING = 0;
constexpr uint32_t OFF_P = 163840;
constexpr uint32_t OFF_H = 188416;
constexpr uint32_t OFF_MISC = 221184;
constexpr uint32_t OFF_BARS = 229888;
constexpr uint32_t SMEM_BYTES = 230400;
constexpr uint32_t GCH = 6144;
constexpr uint32_t HCH = 4096;

constexpr int B_FULL = 0, B_EMPTY = 10, B_XA = 20  , B_XB = 25  , B_INB = 29  , B_SR = 33,
              B_RST = 34  , B_RDY = 36  , B_SINK = 42, B_HALO = 43  , NBARS = 47;

#define KD2 300u
#define KD3 500u
#define QGATE 500u
#define BACKOFF 0u
#define KFS 32
#define KDELAY 450u
#define NJ0 2
#define HDELAY 200u
#define LATE 3
#define SND 0
#define PF0 0
#define TWO 1
#define SHX 3
#define TURN 0x200
#define EAGER 0x0155
constexpr int FS = 8;

struct Scalars {
    const __nv_bfloat16* x;
    const __nv_bfloat16* dw;
    __nv_bfloat16* out;
    uint32_t zero;
};
struct Maps {
    CUtensorMap tm[9];
    const char* w[8];
};

__device__ __align__(1024) unsigned char g_kvq[3 * 8 * 1024 * 128];
__device__ __align__(1024) unsigned char g_o[2 * 128 * 4096];
__device__ uint4 g_halo[64 * 4 * 2 * 64];
__device__ __align__(128) uint32_t g_flag_kv[8 * 32 * KFS];
__device__ uint32_t g_reset[4 * 32];
__device__ uint32_t g_epoch[NCTA * FS];

#define TS(i) do { } while (0)
#define TSW(i) do { } while (0)
#define TG(i) do { } while (0)
#define TSINIT() do { } while (0)
#define TSDUMP() do { } while (0)
constexpr uint32_t SMEM_LAUNCH = SMEM_BYTES;

__device__ __forceinline__ uint32_t smem_u32(const void* p) { return (uint32_t)__cvta_generic_to_shared(p); }
__device__ __forceinline__ void mbar_init(uint32_t b, uint32_t c) { asm volatile("mbarrier.init.shared::cta.b64 [%0], %1;" ::"r"(b), "r"(c) : "memory"); }
__device__ __forceinline__ void mbar_arrive(uint32_t b) { asm volatile("mbarrier.arrive.shared::cta.b64 _, [%0];" ::"r"(b) : "memory"); }
__device__ __forceinline__ void mbar_arrive_tx(uint32_t b, uint32_t tx) { asm volatile("mbarrier.arrive.expect_tx.shared::cta.b64 _, [%0], %1;" ::"r"(b), "r"(tx) : "memory"); }
__device__ __forceinline__ void mbar_wait(uint32_t b, uint32_t ph) {
    asm volatile("{\n.reg .pred p, q;\n.reg .u32 c;\nmov.u32 c, 0;\n"
                 "MW_LOOP:\n.pragma \"nounroll\";\n"
                 "mbarrier.try_wait.parity.shared::cta.b64 p, [%0], %1;\n"
                 "add.u32 c, c, 1;\nsetp.lt.u32 q, c, 65536;\nnot.pred p, p;\nand.pred p, p, q;\n@p bra MW_LOOP;\n}"
                 ::"r"(b), "r"(ph) : "memory");
}
__device__ __forceinline__ bool mbar_test(uint32_t b, uint32_t ph) {
    uint32_t ok;
    asm volatile("{\n.reg .pred p;\nmbarrier.test_wait.parity.shared::cta.b64 p, [%1], %2;\nselp.u32 %0, 1, 0, p;\n}" : "=r"(ok) : "r"(b), "r"(ph) : "memory");
    return ok;
}
__device__ __forceinline__ uint32_t mapa(uint32_t a, uint32_t r) { uint32_t o; asm("mapa.shared::cluster.u32 %0, %1, %2;" : "=r"(o) : "r"(a), "r"(r)); return o; }
__device__ __forceinline__ void fence_async_smem() { asm volatile("fence.proxy.async.shared::cta;" ::: "memory"); }
__device__ __forceinline__ void fence_async_global() { asm volatile("fence.proxy.async.global;" ::: "memory"); }
__device__ __forceinline__ void bar_sync(int id, int n) { asm volatile("bar.sync %0, %1;" ::"r"(id), "r"(n) : "memory"); }
__device__ __forceinline__ void bar_arrive(int id, int n) { asm volatile("bar.arrive %0, %1;" ::"r"(id), "r"(n) : "memory"); }
__device__ __forceinline__ void cluster_arrive() { asm volatile("barrier.cluster.arrive.relaxed.aligned;" ::: "memory"); }
__device__ __forceinline__ void cluster_wait() { asm volatile("barrier.cluster.wait.aligned;" ::: "memory"); }

__device__ __forceinline__ void ring_load(uint32_t dst, const CUtensorMap* tm, int col, int row16, uint32_t bar) {
    asm volatile("{\n.reg .pred p;\nelect.sync _|p, 0xffffffff;\n"
                 "@p mbarrier.arrive.expect_tx.shared::cta.b64 _, [%2], 16384;\n"
                 "@p cp.async.bulk.tensor.5d.shared::cluster.global.mbarrier::complete_tx::bytes [%0], [%1, {%3, 0, 0, 0, %4}], [%2];\n}"
                 ::"r"(dst), "l"(tm), "r"(bar), "r"(col), "r"(row16) : "memory");
}
__device__ __forceinline__ void ring_load_both(uint32_t dst, const CUtensorMap* tm, int c1, uint32_t bar) {
    asm volatile("{\n.reg .pred p;\nelect.sync _|p, 0xffffffff;\n"
                 "@p cp.async.bulk.tensor.2d.shared::cluster.global.mbarrier::complete_tx::bytes.multicast::cluster [%0], [%1, {0, %3}], [%2], %4;\n}"
                 ::"r"(dst), "l"(tm), "r"(bar), "r"(c1), "h"((uint16_t)3) : "memory");
}
__device__ __forceinline__ void mbar_arrive_peer(uint32_t b) { asm volatile("mbarrier.arrive.relaxed.cluster.shared::cluster.b64 _, [%0];" ::"r"(b) : "memory"); }
__device__ __forceinline__ void prefetch_l2(const void* src, uint32_t bytes) {
    asm volatile("cp.async.bulk.prefetch.L2.global [%0], %1;" ::"l"(src), "r"(bytes) : "memory");
}
__device__ __forceinline__ void peer_copy(uint32_t dst, uint32_t src, uint32_t bytes, uint32_t rbar) {
    asm volatile("{\n.reg .pred p;\nelect.sync _|p, 0xffffffff;\n"
                 "@p cp.async.bulk.shared::cluster.shared::cta.mbarrier::complete_tx::bytes [%0], [%1], %2, [%3];\n}"
                 ::"r"(dst), "r"(src), "r"(bytes), "r"(rbar) : "memory");
}
__device__ __forceinline__ void st_async4(uint32_t dst, uint32_t a, uint32_t b, uint32_t c, uint32_t d, uint32_t bar) {
    asm volatile("st.async.shared::cluster.mbarrier::complete_tx::bytes.v4.b32 [%0], {%1,%2,%3,%4}, [%5];" ::"r"(dst), "r"(a), "r"(b), "r"(c), "r"(d), "r"(bar) : "memory");
}
__device__ __forceinline__ void put_sums(uint32_t dst, uint32_t rdst, float a, float b, uint32_t rbar, bool on) {
    asm volatile("{\n.reg .pred p;\nsetp.ne.u32 p, %5, 0;\n"
                 "@p st.async.shared::cluster.mbarrier::complete_tx::bytes.v2.f32 [%1], {%2,%3}, [%4];\n"
                 "@p st.shared.v2.f32 [%0], {%2,%3};\n}" ::"r"(dst), "r"(rdst), "f"(a), "f"(b), "r"(rbar), "r"((uint32_t)on) : "memory");
}
__device__ __forceinline__ void stsm4(uint32_t a, uint32_t r0, uint32_t r1, uint32_t r2, uint32_t r3) {
    asm volatile("stmatrix.sync.aligned.m8n8.x4.shared.b16 [%0], {%1,%2,%3,%4};" ::"r"(a), "r"(r0), "r"(r1), "r"(r2), "r"(r3) : "memory");
}
__device__ __forceinline__ void ldsm4(uint32_t a, uint32_t& r0, uint32_t& r1, uint32_t& r2, uint32_t& r3) {
    asm volatile("ldmatrix.sync.aligned.m8n8.x4.shared.b16 {%0,%1,%2,%3}, [%4];" : "=r"(r0), "=r"(r1), "=r"(r2), "=r"(r3) : "r"(a) : "memory");
}
__device__ __forceinline__ uint4 lds128(uint32_t a) { uint4 v; asm volatile("ld.shared.v4.b32 {%0,%1,%2,%3}, [%4];" : "=r"(v.x), "=r"(v.y), "=r"(v.z), "=r"(v.w) : "r"(a) : "memory"); return v; }
__device__ __forceinline__ float4 lds128f(uint32_t a) { float4 v; asm volatile("ld.shared.v4.f32 {%0,%1,%2,%3}, [%4];" : "=f"(v.x), "=f"(v.y), "=f"(v.z), "=f"(v.w) : "r"(a) : "memory"); return v; }
__device__ __forceinline__ float2 lds64f(uint32_t a) { float2 v; asm volatile("ld.shared.v2.f32 {%0,%1}, [%2];" : "=f"(v.x), "=f"(v.y) : "r"(a) : "memory"); return v; }
__device__ __forceinline__ uint32_t lds32(uint32_t a) { uint32_t v; asm volatile("ld.shared.b32 %0, [%1];" : "=r"(v) : "r"(a) : "memory"); return v; }
__device__ __forceinline__ void sts128(uint32_t a, uint32_t x, uint32_t y, uint32_t z, uint32_t w) { asm volatile("st.shared.v4.b32 [%0], {%1,%2,%3,%4};" ::"r"(a), "r"(x), "r"(y), "r"(z), "r"(w) : "memory"); }
__device__ __forceinline__ void sts128f(uint32_t a, float x, float y, float z, float w) { asm volatile("st.shared.v4.f32 [%0], {%1,%2,%3,%4};" ::"r"(a), "f"(x), "f"(y), "f"(z), "f"(w) : "memory"); }
__device__ __forceinline__ void sts64f(uint32_t a, float x, float y) { asm volatile("st.shared.v2.f32 [%0], {%1,%2};" ::"r"(a), "f"(x), "f"(y) : "memory"); }
__device__ __forceinline__ void sts32(uint32_t a, uint32_t x) { asm volatile("st.shared.b32 [%0], %1;" ::"r"(a), "r"(x) : "memory"); }
__device__ __forceinline__ void stg128(void* p, uint4 v) { asm volatile("st.global.v4.b32 [%0], {%1,%2,%3,%4};" ::"l"(p), "r"(v.x), "r"(v.y), "r"(v.z), "r"(v.w) : "memory"); }

__device__ __forceinline__ uint32_t pack2(float lo, float hi) { uint32_t r; asm("cvt.rn.bf16x2.f32 %0, %1, %2;" : "=r"(r) : "f"(hi), "f"(lo)); return r; }
__device__ __forceinline__ float blo(uint32_t v) { return __uint_as_float(v << 16); }
__device__ __forceinline__ float bhi(uint32_t v) { return __uint_as_float(v & 0xffff0000u); }
__device__ __forceinline__ uint32_t hmul2(uint32_t a, uint32_t b) { uint32_t r; asm("mul.rn.bf16x2 %0, %1, %2;" : "=r"(r) : "r"(a), "r"(b)); return r; }
__device__ __forceinline__ uint32_t hadd2(uint32_t a, uint32_t b) { uint32_t r; asm("add.rn.bf16x2 %0, %1, %2;" : "=r"(r) : "r"(a), "r"(b)); return r; }
__device__ __forceinline__ uint32_t hsub2(uint32_t a, uint32_t b) { uint32_t r; asm("sub.rn.bf16x2 %0, %1, %2;" : "=r"(r) : "r"(a), "r"(b)); return r; }
__device__ __forceinline__ uint32_t hfma2(uint32_t a, uint32_t b, uint32_t c) { uint32_t r; asm("fma.rn.bf16x2 %0, %1, %2, %3;" : "=r"(r) : "r"(a), "r"(b), "r"(c)); return r; }
__device__ __forceinline__ float tanh_fast(float x) { float r; asm("tanh.approx.f32 %0, %1;" : "=f"(r) : "f"(x)); return r; }
__device__ __forceinline__ float rsq(float x) { float r; asm("rsqrt.approx.ftz.f32 %0, %1;" : "=f"(r) : "f"(x)); return r; }
__device__ __forceinline__ float ex2(float x) { float r; asm("ex2.approx.ftz.f32 %0, %1;" : "=f"(r) : "f"(x)); return r; }

__device__ __forceinline__ uint32_t ld_relaxed(const uint32_t* p) {
    uint32_t v;
    asm volatile("ld.relaxed.gpu.global.u32 %0, [%1];" : "=r"(v) : "l"(p) : "memory");
    return v;
}
__device__ __forceinline__ uint32_t clock32() { uint32_t c; asm volatile("mov.u32 %0, %%clock;" : "=r"(c)::"memory"); return c; }
__device__ __forceinline__ void spin(uint32_t clks) {
    const uint32_t t0 = clock32();
    while (clock32() - t0 < clks) {}
}
__device__ __forceinline__ void flag_wait(const uint32_t* p, uint32_t e, bool mine) {
#pragma unroll 1
    for (int i = 0; i < (1 << 19); i++) {
        if (mine) mine = ld_relaxed(p) != e;
        if (!__any_sync(~0u, mine)) break;
        if (BACKOFF) spin(BACKOFF);
    }
    asm volatile("fence.acquire.gpu;" ::: "memory");
    fence_async_global();
}
__device__ __forceinline__ void st_data(void* p, uint32_t x, uint32_t y, uint32_t z, uint32_t w) {
    asm volatile("st.relaxed.gpu.global.v4.b32 [%0], {%1,%2,%3,%4};" ::"l"(p), "r"(x), "r"(y), "r"(z), "r"(w) : "memory");
}
template <int STRIDE, int N>
__device__ __forceinline__ void ld_data(uint4 (&v)[N], const unsigned char* p) {
    int it = 0;
    bool again;
#pragma unroll 1
    do {
        uint32_t m = 0;
#pragma unroll
        for (int i = 0; i < N; i++)
            asm volatile("ld.relaxed.gpu.global.v4.b32 {%0,%1,%2,%3}, [%4];" : "=r"(v[i].x), "=r"(v[i].y), "=r"(v[i].z), "=r"(v[i].w) : "l"(p + i * STRIDE) : "memory");
#pragma unroll
        for (int i = 0; i < N; i++) m = __vimax3_u32(__vimax3_u32(v[i].x, v[i].y, v[i].z), v[i].w, m);
        again = __any_sync(~0u, m == ~0u) && ++it < (1 << 16);
    } while (again);
}
__device__ __forceinline__ uint32_t ld_epoch() { return ld_relaxed(&g_epoch[blockIdx.x * FS]) + 1; }
__device__ __forceinline__ void flag_set(uint32_t* p, uint32_t e) { asm volatile("st.release.gpu.global.u32 [%0], %1;" ::"l"(p), "r"(e) : "memory"); }

__device__ __forceinline__ uint32_t desc_lo(uint32_t addr) { return ((addr & 0x3FFFF) >> 4) | 0x10000u; }
__device__ __forceinline__ uint64_t mkdesc(uint32_t lo) { return (uint64_t)lo | (0x40000040ull << 32); }
__device__ __forceinline__ void wg_fence() { asm volatile("wgmma.fence.sync.aligned;" ::: "memory"); }
__device__ __forceinline__ void wg_commit() { asm volatile("wgmma.commit_group.sync.aligned;" ::: "memory"); }
template <int N> __device__ __forceinline__ void wg_wait() { asm volatile("wgmma.wait_group.sync.aligned %0;" ::"n"(N) : "memory"); }
template <int N> __device__ __forceinline__ void pin(float (&d)[N]) {
#pragma unroll
    for (int i = 0; i < N; i++) asm volatile("" : "+f"(d[i])::"memory");
}
template <int N> __device__ __forceinline__ void pin(uint32_t (&d)[N]) {
#pragma unroll
    for (int i = 0; i < N; i++) asm volatile("" : "+r"(d[i])::"memory");
}

template <typename Tp, int N> __device__ __forceinline__ void zero(Tp (&d)[N]) {
#pragma unroll
    for (int i = 0; i < N; i++) d[i] = 0;
    pin(d);
}

#define F4(d, i) "+f"(d[i]), "+f"(d[i + 1]), "+f"(d[i + 2]), "+f"(d[i + 3])
#define F16(d, i) F4(d, i), F4(d, i + 4), F4(d, i + 8), F4(d, i + 12)

__device__ __forceinline__ void mma16(float (&d)[4], const uint32_t* a, uint32_t b0, uint32_t b1) {
    asm("mma.sync.aligned.m16n8k16.row.col.f32.bf16.bf16.f32 {%0,%1,%2,%3}, {%4,%5,%6,%7}, {%8,%9}, {%0,%1,%2,%3};"
        : F4(d, 0) : "r"(a[0]), "r"(a[1]), "r"(a[2]), "r"(a[3]), "r"(b0), "r"(b1));
}
template <int N>
__device__ __forceinline__ float row_sum(const uint32_t* x, uint32_t ones = 0x3F803F80u) {
    float c[4] = {};
#pragma unroll
    for (int i = 0; i < N; i += 4) mma16(c, x + i, ones, ones);
    return c[0] + c[2];
}
template <int N>
__device__ __forceinline__ float row_sumsq(const uint32_t* x, int lane) {
    float c0[4] = {}, c1[4] = {};
#pragma unroll
    for (int i = 0; i < N; i += 4) {
        mma16(c0, x + i, x[i], x[i + 2]);
        mma16(c1, x + i, x[i + 1], x[i + 3]);
    }
    return (lane & 4) ? c0[1] + c1[3] : c0[0] + c1[2];
}
__device__ __forceinline__ void mma_sp(float (&d)[32], const uint32_t* a, uint64_t b, uint32_t meta, int acc) {
    asm volatile("{.reg .pred p; setp.ne.b32 p, %38, 0;\n"
                 "wgmma.mma_async.sp.sync.aligned.m64n64k32.f32.bf16.bf16 {%0,%1,%2,%3,%4,%5,%6,%7,%8,%9,%10,%11,%12,%13,%14,%15,%16,%17,%18,%19,%20,%21,%22,%23,%24,%25,%26,%27,%28,%29,%30,%31}, "
                 "{%32,%33,%34,%35}, %36, %37, 0, p, 1, 1, 1;}\n"
                 : F16(d, 0), F16(d, 16) : "r"(a[0]), "r"(a[1]), "r"(a[2]), "r"(a[3]), "l"(b), "r"(meta), "r"(acc));
}
__device__ __forceinline__ void mma_qk(float (&d)[32], uint32_t a0, uint32_t a1, uint32_t a2, uint32_t a3, uint64_t b, int acc) {
    asm volatile("{.reg .pred p; setp.ne.b32 p, %37, 0;\n"
                 "wgmma.mma_async.sync.aligned.m64n64k16.f32.bf16.bf16 {%0,%1,%2,%3,%4,%5,%6,%7,%8,%9,%10,%11,%12,%13,%14,%15,%16,%17,%18,%19,%20,%21,%22,%23,%24,%25,%26,%27,%28,%29,%30,%31}, "
                 "{%32,%33,%34,%35}, %36, p, 1, 1, 0;}\n"
                 : F16(d, 0), F16(d, 16) : "r"(a0), "r"(a1), "r"(a2), "r"(a3), "l"(b), "r"(acc));
}
__device__ __forceinline__ void mma_pv(float (&d)[36], uint32_t a0, uint32_t a1, uint32_t a2, uint32_t a3, uint64_t b) {
    asm volatile("wgmma.mma_async.sync.aligned.m64n72k16.f32.bf16.bf16 {%0,%1,%2,%3,%4,%5,%6,%7,%8,%9,%10,%11,%12,%13,%14,%15,%16,%17,%18,%19,%20,%21,%22,%23,%24,%25,%26,%27,%28,%29,%30,%31,%32,%33,%34,%35}, "
                 "{%36,%37,%38,%39}, %40, 1, 1, 1, 1;\n"
                 : F16(d, 0), F16(d, 16), F4(d, 32) : "r"(a0), "r"(a1), "r"(a2), "r"(a3), "l"(b));
}

__device__ __forceinline__ uint32_t load_code(int n, int r, int w) {
    const int tile = 2 * r + w;
    int m, col, row;
    if (n < 16 || n >= 40) {
        const int k = n < 16 ? n : n - 40;
        m = n < 16 ? 0 : 6;
        if (TWO && n >= 40 && k < 4) { col = 4 * tile + (k & 1); row = (k >> 1) ^ r; }
        else if (k < 8) { col = 4 * tile + (k >> 1); row = n < 16 ? (k & 1) : (k & 1) ^ r; }
        else { m++; col = k < 12 ? tile ^ 2 : tile; row = 2 * (tile ^ (k & 1)) + ((k >> 1) & 1); }
    } else if (n < 32) {
        const int k = n - 16;
        m = 2;
        if (k < 4) { col = tile + ((k & 1) ? 8 : 4); row = (k >> 1) ^ r; }
        else { col = tile; row = (k & 1) ^ r; }
    } else if (n < 34) { m = 3; col = tile; row = n - 32; }
    else if (n < 38) { const int k = n - 34; m = 4; col = tile + 4 * (k & 1); row = (k >> 1) ^ r; }
    else { m = 5; col = tile; row = (n & 1) ^ r; }
    return m | (col << 4) | (row << ((m == 0 || m == 3) ? 10 : 11));
}

__global__ void __cluster_dims__(2, 1, 1) __launch_bounds__(NTHREADS, 1)
conformer_kernel(const Scalars p, const __grid_constant__ Maps m) {
    extern __shared__ __align__(1024) unsigned char smem_raw[];
    const uint32_t sb = smem_u32(smem_raw);
    const uint32_t bars = sb + OFF_BARS;
    const int tid = threadIdx.x;
    const int lane = tid & 31;
    const int warp = __shfl_sync(~0u, tid >> 5, 0);
    const int r = blockIdx.x & 1;
    const int pair = blockIdx.x >> 1;
    const int b = pair >> 5, pt = pair & 31;
    const int ah = pt >> 3, qt = (pt & 7) * 2 + r;
    const int abh = b * 4 + ah;

    TG(30);
    TSINIT();
    TS(0);
    const uint32_t P = sb + OFF_P, H = sb + OFF_H;
    if (warp == 11) {
        if (lane == 0) {
#pragma unroll
            for (int i = 0; i < 2 * NSLOT; i++) mbar_init(bars + (B_FULL + i) * 8, 1);
            asm volatile("fence.mbarrier_init.release.cluster;" ::: "memory");
            fence_async_smem();
        }
        __syncwarp();
        bar_arrive(13, 96);
        cluster_arrive();
    }

    if (warp >= 8) {
        asm volatile("setmaxnreg.dec.sync.aligned.u32 48;");
        if (warp >= 12) {
            cluster_arrive();
            cluster_wait();
            const int ut = tid & 127;
            const uint32_t target = ld_epoch() * 64;
            auto reset_done = [&](int k) {
                bar_sync(11, 128);
                if (ut == 0) {
                    asm volatile("red.release.gpu.global.add.u32 [%0], 1;" ::"l"(&g_reset[(2 * b + k) * 32]) : "memory");
#pragma unroll 1
                    for (int i = 0; i < (1 << 20) && ld_relaxed(&g_reset[(2 * b + k) * 32]) != target; i++) __nanosleep(100);
                    asm volatile("fence.acquire.gpu;" ::: "memory");
                    mbar_arrive(bars + (B_RST + k) * 8);
                }
                __syncwarp();
                TS(13 + k);
            };
#pragma unroll
            for (int i = 0; i < 4; i++)
                st_data(g_kvq + 2097152 + (size_t)((b * 4 + 2 * r + (i >> 1)) * 1024 + pt * 32) * 128 + (i & 1) * 2048 + ut * 16, ~0u, ~0u, ~0u, ~0u);
            reset_done(0);
            bar_sync(6, 384);
#pragma unroll
            for (int i = 0; i < 4; i++) {
                st_data(g_o + (size_t)(b * 128 + qt * 8 + 2 * i + (ut >> 6)) * 4096 + ah * 1024 + (ut & 63) * 16, ~0u, ~0u, ~0u, ~0u);
                if (i < 2) st_data(&g_halo[(pair * 4 + 2 * r + i) * 128 + ut], ~0u, ~0u, ~0u, ~0u);
            }
            reset_done(1);
            const int side = warp & 1, wg = (warp >> 1) & 1, np = side ? pt + 1 : pt - 1;
            const unsigned char* src = reinterpret_cast<const unsigned char*>(&g_halo[(((b * 32 + np) * 4 + 2 * r + wg) * 2 + (side ^ 1)) * 64 + lane]);
            const uint32_t dst = H + 16384 + wg * GCH + side * 5120 + (lane & 7) * 128 + (((lane >> 3) ^ (lane & 7)) << 4);
            uint4 hv[2] = {make_uint4(0, 0, 0, 0), make_uint4(0, 0, 0, 0)};
            bar_sync(8 + wg, 192);
            if (np >= 0 && np < 32) {
                spin(HDELAY);
                ld_data<512>(hv, src);
            }
            stsm4(dst, hv[0].x, hv[0].y, hv[0].z, hv[0].w);
            stsm4(dst ^ 64, hv[1].x, hv[1].y, hv[1].z, hv[1].w);
            __syncwarp();
            if (lane == 0) mbar_arrive(bars + (B_HALO + (warp & 3)) * 8);
            TS(4);
        } else if (warp < 10) {
            const int w = warp - 8;
            const uint32_t ring = sb + OFF_RING + w * NSLOT * SLOT;
            const uint32_t full = bars + (B_FULL + w * NSLOT) * 8;
            cluster_arrive();
            bar_sync(13, 96);
            TS(1);
#pragma unroll
            for (int n = 0; n < NSLOT; n++) {
                if (n == 1) bar_sync(12, 64);
                ring_load(ring + n * SLOT, &m.tm[0], 64 * (8 * r + 4 * w + (n >> 1)), 4 * (n & 1), full + n * 8);
            }
            TS(2);
            const uint32_t code = load_code(lane, r, w) | (load_code(lane + 32, r, w) << 16);
            cluster_wait();
            uint32_t s = 0, ph = 0;
            int n = NSLOT;
#pragma unroll 1
            for (int seg = 0; seg < 2; seg++) {
#pragma unroll 1
                for (; n < (seg == 0 ? 22 : NLOADS); n++) {
                    const uint32_t c = __shfl_sync(~0u, code, n) >> (n & 32 ? 16 : 0);
                    const CUtensorMap* tm = &m.tm[c & 15];
                    const uint32_t col = (c & 0xf0) * 4, row = (c & 0xff00) >> 8, dst = ring + s * SLOT;
                    mbar_wait(full + (B_EMPTY - B_FULL) * 8 + s * 8, ph + (((uint32_t)(size_t)tm | col | row | dst) & p.zero));
                    ring_load(dst, tm, col, row, full + s * 8);
                    if (++s == NSLOT) { s = 0; ph ^= 1; }
                }
                if (seg == 1) break;
                const uint32_t epoch = ld_epoch();
                const uint32_t rdy = bars + (B_RDY + 3 * w) * 8, prdy = mapa(rdy, r ^ 1);
                const int odd = r ^ w;
                const uint32_t* flags = g_flag_kv + (abh * 32 + lane) * KFS;
                auto kv_load = [&](uint32_t sl, int isv, int i) {
                    ring_load_both(ring + sl * SLOT, &m.tm[8], (isv * 64 + abh * 8 + 2 * i + w) * 128, full + sl * 8);
                };
#pragma unroll 1
                for (int i = 0; i < 2; i++) {
                    if (lane < 3 + i) {
                        const uint32_t sl = i ? lane : lane + 2;
                        mbar_wait(full + (B_EMPTY - B_FULL + sl) * 8, i ^ 1);
                        mbar_arrive_tx(full + sl * 8, (i || lane == 2) ? SLOT : 0);
                    }
                    __syncwarp();
                }
                if (lane == 0) mbar_arrive_peer(prdy);
                bar_sync(14, 96);
                spin(KDELAY);
                mbar_wait(rdy, 0);
                flag_wait(flags, epoch, (lane >> 2) == 2 * odd + w);
                TSW(5 + 2 * odd);
                if (!odd) { kv_load(4, 0, 0); bar_arrive(12, 64); }
                else bar_sync(12, 64);
                spin(w ? KD3 : KD2);
                kv_load(odd ^ 1, odd ^ 1, odd);
                flag_wait(flags, epoch, (lane >> 2) == 2 * odd + w + 4);
                mbar_wait(full + (odd ^ 1) * 8, 1);
                kv_load(2 + odd, odd, 2 - odd);
#pragma unroll 1
                for (int i = 0; i < 3; i++) {
                    const uint32_t sl = i ? i - 1 : 4, bo = i == 2 ? 16 : 8;
                    mbar_wait(full + (B_EMPTY - B_FULL + sl) * 8, i != 0);
                    if (lane == 0) mbar_arrive_tx(full + sl * 8, SLOT);
                    if ((i & 1) != odd) {
                        mbar_wait(rdy + bo, 0);
                        kv_load(sl, i != 0, 2 + odd);
                    } else if (lane == 0) mbar_arrive_peer(prdy + bo);
                    __syncwarp();
                }
                n = 32; s = 2; ph = 1;
            }
        } else if (warp == 10) {
            if (lane == 0) {
#pragma unroll
                for (int i = B_EMPTY; i < NBARS; i++) mbar_init(bars + i * 8, i < B_XA ? 4 : 1);
#pragma unroll
                for (int i = B_XA; i <= B_SR; i++) mbar_arrive_tx(bars + i * 8, i < B_XB ? 512 : ((i >= B_INB && i < B_SR) ? 4096 : 8192));
                asm volatile("fence.mbarrier_init.release.cluster;" ::: "memory");
                fence_async_smem();
            }
            __syncwarp();
            cluster_arrive();
            cluster_wait();
        } else {
            const uint32_t kb = (lane < 2 || lane > 5) ? 4096 : (lane == 2 ? 3072 : (lane == 4 ? 2048 : 1024));
            const char* pf = m.w[lane & 7] + blockIdx.x * kb;
            cluster_wait();
            if (lane < PF0) prefetch_l2(pf, kb);
            mbar_wait(bars + B_FULL * 8, 0);
            if (lane >= PF0 && lane < 3) prefetch_l2(pf, kb);
            if (lane >= 1 && lane < 9) asm volatile("prefetch.tensormap [%0];" ::"l"(&m.tm[lane]) : "memory");
            mbar_wait(bars + (B_FULL + 1) * 8, 1);
            if (lane > 2 && lane < 8) prefetch_l2(pf, kb);
            if (lane == 8 && blockIdx.x < 15) prefetch_l2(p.dw + blockIdx.x * 256, 512);
            const uint32_t epoch = ld_epoch();
            bar_sync(4, 288);
            if (lane < 16) flag_set(&g_flag_kv[((b * 4 + 2 * r + (lane >> 3)) * 32 + pt) * KFS + (lane & 7)], epoch);
            __syncwarp();
            bar_arrive(14, 96);
            TSW(8);
        }
        TSDUMP();
        return;
    }

    const int w = warp >> 2, wq = warp & 3;
    const int tile = 2 * r + w;
    const int wt = tid & 127;
    const int c4 = lane & 3;
    const int trow = pt * 32 + 8 * wq;
    uint32_t xr[8];
    uint32_t a[32];
    const char* xrow = reinterpret_cast<const char*>(p.x) + (b * T_ + trow + (lane >> 2)) * 512;
    zero(a);
    if (trow < T_) {
        const char* src = xrow + c4 * 16 + p.zero;
#pragma unroll
        for (int i = 0; i < 8; i++)
            asm volatile("ld.global.nc.v4.b32 {%0,%1,%2,%3}, [%4];" : "=r"(a[4 * i]), "=r"(a[4 * i + 1]), "=r"(a[4 * i + 2]), "=r"(a[4 * i + 3]) : "l"(src + 64 * i));
    }
    cluster_arrive();
    asm volatile("setmaxnreg.inc.sync.aligned.u32 208;");
    const uint32_t rbase = sb + OFF_RING + w * NSLOT * SLOT, fbar = bars + (B_FULL + w * NSLOT) * 8;
    const uint32_t rdesc = desc_lo(rbase);
    auto acq = [&](int n) { mbar_wait(fbar + (n % NSLOT) * 8, (n / NSLOT) & 1); };
    auto rel = [&](int n) { if (lane == 0) mbar_arrive(fbar + (B_EMPTY - B_FULL + n % NSLOT) * 8); };
    const uint32_t foff = (lane & 7) * 128 + (((lane >> 3) ^ (lane & 7)) << 4);
    float v[16];
    const uint32_t xown = __shfl_sync(~0u, P + wt * 16 + tile * 4096, lane), xrem = __shfl_sync(~0u, P + wt * 16 + (r ^ 1) * 8192, lane);
    const uint32_t sbuf = __shfl_sync(~0u, sb + OFF_MISC + 1024 + (8 * wq + (lane >> 2)) * 32, lane);
    const uint32_t sown = __shfl_sync(~0u, sbuf + tile * 8, lane);
    const uint32_t peer = __shfl_sync(~0u, mapa(sb, r ^ 1) - sb, lane);
    const uint32_t hbuf = __shfl_sync(~0u, H + w * 4096 + wt * 16, lane);
    const uint32_t meta = __shfl_sync(~0u, 0xEEEE4444u + p.zero, lane);
    cluster_wait();
    TS(56);
    float mean, msq;
    const int mir = wq < 2 ? 7 : 0;
    uint32_t dwr[15] = {};

#pragma unroll
    for (int ph = 0; ph < 5; ph++) {
        uint4 o0, o1;
        if (ph == 0) {
            const uint32_t one = 0x3F803F80u + ((xown | xrem | sbuf | sown | hbuf | foff | rdesc | fbar) & p.zero);
            mean = ((row_sum<8>(a, one) + row_sum<8>(a + 8, one)) + (row_sum<8>(a + 16, one) + row_sum<8>(a + 24, one))) * (1.f / 256.f);
            TS(57);
        } else {
            const uint32_t xa = bars + (B_XA + ph) * 8;
#pragma unroll
            for (int j = 0; j < 8; j++) xr[j] = pack2(v[2 * j], v[2 * j + 1]);
            const float s = row_sum<8>(xr), q = row_sumsq<8>(xr, lane);
            if (ph < 4) {
                sts128(xown, xr[0], xr[1], xr[2], xr[3]);
                sts128(xown + 2048, xr[4], xr[5], xr[6], xr[7]);
            }
            put_sums(sown, sown + peer, s, q, xa + peer, c4 == (lane >> 3));
            bar_sync(10, 256);
            if (ph < 4) {
                o0 = lds128(xown ^ 4096); o1 = lds128((xown ^ 4096) + 2048);
                st_async4(xown + peer, xr[0], xr[1], xr[2], xr[3], xa + (B_XB - B_XA) * 8 + peer);
                st_async4(xown + peer + 2048, xr[4], xr[5], xr[6], xr[7], xa + (B_XB - B_XA) * 8 + peer);
            }
            TS(57 + ph);
            if (ph == 3) acq(0);
            if (ph == 1) acq(16);
            mbar_wait(xa, 0);
            const float4 u0 = lds128f(sbuf), u1 = lds128f(sbuf + 16);
            mean = ((u0.x + u0.z) + (u1.x + u1.z)) * (1.f / 256.f);
            msq = ((u0.y + u0.w) + (u1.y + u1.w)) * (1.f / 256.f);
        }
        if (ph == 4) break;
        const uint32_t mean2 = pack2(mean, mean);
        auto centre = [&](int i, const uint4& u) {
            a[i] = hsub2(u.x, mean2); a[i + 1] = hsub2(u.y, mean2); a[i + 2] = hsub2(u.z, mean2); a[i + 3] = hsub2(u.w, mean2);
        };
        if (ph == 0) {
#pragma unroll
            for (int j = 0; j < 32; j++) a[j] = hsub2(a[j], mean2);
            zero(xr);
            if (trow < T_) {
                const char* src = xrow + tile * 128 + c4 * 4 + (mean2 & p.zero);
#pragma unroll
                for (int j = 0; j < 8; j++) asm volatile("ld.global.nc.b32 %0, [%1];" : "=r"(xr[j]) : "l"(src + 16 * j));
            }
            mean -= blo(mean2);
            msq = __shfl_sync(~0u, row_sumsq<16>(a, lane) + row_sumsq<16>(a + 16, lane), (lane & 28) + (lane >> 3)) * (1.f / 256.f);
            acq(0);
        } else {
#pragma unroll
            for (int j = 0; j < 8; j++) a[j] = hsub2(xr[j], mean2);
            centre(8, o0); centre(12, o1);
        }
        const float rstd = rsq(fmaxf(fmaf(-mean, mean, msq), 0.f) + 1e-5f);
        auto gather_peer = [&]() {
            mbar_wait(bars + (B_XB + ph) * 8, 0);
#pragma unroll
            for (int i = 0; i < 4; i++) centre(16 + 4 * i, lds128(xrem + i * 2048));
        };
        auto sp = [&](float (&d)[32], int n, const uint32_t* af, int flip, int acc) {
            const uint32_t lo = rdesc + p.zero * (ph * 64 + n + 1) + (n % NSLOT) * (SLOT >> 4);
            const uint64_t b0 = mkdesc(lo + flip * 512), b1 = mkdesc(lo + (flip ^ 1) * 512);
            wg_fence();
            mma_sp(d, af, b0, meta, acc);
            mma_sp(d, af + 4, b0 + 256, meta, 1);
            mma_sp(d, af + 8, b1, meta, 1);
            mma_sp(d, af + 12, b1 + 256, meta, 1);
            wg_commit();
        };
        float d0[32], d1[32];

        if (ph == 0 || ph == 3) {
            uint32_t h[32], ho[32];
            const float rs = 0.5f * rstd;
            const uint32_t inb = bars + (B_INB + (ph & 2) + w) * 8;
            bool ready = true;
            const int eager = ph ? (TWO ? EAGER + 5 : EAGER) : EAGER - 1;
            auto step = [&](float (&d)[32], int n, const uint32_t* af, int flip, int acc, auto work) {
                if (!ready) acq(n);
                if (((TURN >> n) & 1) && w == 1) bar_sync(7, 256);
                sp(d, n, af, flip, acc);
                if (n > 0 && ((TURN >> (n - 1)) & 1) && w == 0) bar_arrive(7, 256);
                if (n < 15) ready = mbar_test(fbar + ((n + 1) % NSLOT) * 8, ((n + 1) / NSLOT) & 1);
                wg_wait<1>();
                if (n > 0 && !((eager >> (n - 1)) & 1)) rel(n - 1);
                const uint32_t tie = work() & p.zero;
                if ((eager >> n) & 1) {
                    if (p.zero < n + ph + 1) wg_wait<0>();
                    if (lane == 0) mbar_arrive(fbar + (B_EMPTY - B_FULL + n % NSLOT) * 8 + tie);
                }
            };
            auto none = []() { return 0u; };
            const int fl = ph ? w : 0;
            auto fetch = [&](int i) {
                bar_sync(10, 256);
                const uint4 u0 = lds128((hbuf ^ 4096) + (i & 1) * 8192), u1 = lds128((hbuf ^ 4096) + (i & 1) * 8192 + 2048);
                ho[8 * i] = u0.x; ho[8 * i + 1] = u0.y; ho[8 * i + 2] = u0.z; ho[8 * i + 3] = u0.w;
                ho[8 * i + 4] = u1.x; ho[8 * i + 5] = u1.y; ho[8 * i + 6] = u1.z; ho[8 * i + 7] = u1.w;
                return u0.x | u1.x;
            };
            auto act = [&](float (&d)[32], int i) {
                if (i > 0) fetch(i - 1);
                pin(d);
#pragma unroll
                for (int j = 0; j < 8; j++) {
                    const float u0 = (d[4 * j] + d[4 * j + 2]) * rs, u1 = (d[4 * j + 1] + d[4 * j + 3]) * rs;
                    h[8 * i + j] = pack2(fmaf(u0, tanh_fast(u0), u0), fmaf(u1, tanh_fast(u1), u1));
                }
                sts128(hbuf + (i & 1) * 8192, h[8 * i], h[8 * i + 1], h[8 * i + 2], h[8 * i + 3]);
                sts128(hbuf + (i & 1) * 8192 + 2048, h[8 * i + 4], h[8 * i + 5], h[8 * i + 6], h[8 * i + 7]);
                return 0u;
            };
            TS(1 + (ph & 2) * 10);
            if (TWO && ph) {
                step(d0, 0, a, fl, 0, none);
                step(d1, 1, a, fl, 0, [&]() { gather_peer(); return 0u; });
                TS(32);
                step(d0, 2, a + 16, 0, 1, none);
                step(d1, 3, a + 16, 0, 1, [&]() { return act(d0, 0); });
            } else {
                step(d0, 0, a, fl, 0, [&]() { if (ph) gather_peer(); return 0u; });
                TS(32);
                step(d0, 1, a + 16, 0, 1, none);
                step(d1, 2, a, fl, 0, [&]() { return act(d0, 0); });
                step(d1, 3, a + 16, 0, 1, none);
            }
            step(d0, 4, a, fl, 0, [&]() { return act(d1, 1); });
            TS(33);
            step(d0, 5, a + 16, 0, 1, none);
            step(d1, 6, a, fl, 0, [&]() { return act(d0, 2); });
            step(d1, 7, a + 16, 0, 1, none);
            step(d0, 8, h, 0, 0, [&]() { act(d1, 3); return fetch(3); });
            TS(2 + (ph & 2) * 10);
            step(d0, 9, ho, 0, 1, none);
            step(d0, 10, h + 16, 0, 1, none);
            step(d0, 11, ho + 16, 0, 1, none);
            uint32_t pk[8];
            auto pack_out = [&]() {
                pin(d0);
#pragma unroll
                for (int j = 0; j < 8; j++) pk[j] = pack2(d0[4 * j] + d0[4 * j + 2], d0[4 * j + 1] + d0[4 * j + 3]);
            };
            auto send = [&](int i) { st_async4(hbuf + 16384 + i * 2048 + peer, pk[4 * i], pk[4 * i + 1], pk[4 * i + 2], pk[4 * i + 3], inb + peer); };
            step(d1, 12, h, 0, 0, [&]() { pack_out(); if (SND != 1) send(0); if (SND == 0) send(1); return 0u; });
            TS(34);
            step(d1, 13, ho, 0, 1, [&]() { if (SND == 1) send(0); if (SND) send(1); return 0u; });
            step(d1, 14, h + 16, 0, 1, none);
            step(d1, 15, ho + 16, 0, 1, none);
            mbar_wait(inb, 0);
#pragma unroll
            for (int i = 0; i < 2; i++) {
                const uint4 u = lds128(hbuf + 16384 + i * 2048);
                const uint32_t p0[4] = {u.x, u.y, u.z, u.w};
#pragma unroll
                for (int j = 0; j < 4; j++) {
                    v[8 * i + 2 * j] = fmaf(0.5f, blo(p0[j]), blo(xr[4 * i + j]));
                    v[8 * i + 2 * j + 1] = fmaf(0.5f, bhi(p0[j]), bhi(xr[4 * i + j]));
                }
            }
            wg_wait<0>();
            pin(d1);
            rel(15);
            TS(3 + (ph & 2) * 10);
#pragma unroll
            for (int j = 0; j < 8; j++) {
                v[2 * j] = fmaf(0.5f, d1[4 * j] + d1[4 * j + 2], v[2 * j]);
                v[2 * j + 1] = fmaf(0.5f, d1[4 * j + 1] + d1[4 * j + 3], v[2 * j + 1]);
            }
#pragma unroll
            for (int i = 0; i < 15; i++) dwr[i] = 0;
            continue;
        }

        auto residual = [&](int n) {
            wg_wait<1>();
            rel(n);
            wg_wait<0>();
            pin(d0);
            rel(n + 1);
#pragma unroll
            for (int j = 0; j < 8; j++) {
                v[2 * j] = d0[4 * j] + d0[4 * j + 2] + blo(xr[j]);
                v[2 * j + 1] = d0[4 * j + 1] + d0[4 * j + 3] + bhi(xr[j]);
            }
        };

        if (ph == 2) {
            TS(39);
            sp(d0, 34, a, w, 0);
            acq(35);
            sp(d1, 35, a, w, 0);
            acq(36); acq(37);
            gather_peer();
            sp(d0, 36, a + 16, 0, 1);
            sp(d1, 37, a + 16, 0, 1);
            wg_wait<2>();
            rel(34);
            if (!(LATE & 1)) rel(35);
            acq(38);
            const float rs = trow < T_ ? 0.5f * rstd : 0.f;
            wg_wait<0>();
            pin(d0); pin(d1);
            if (!(LATE & 2)) { rel(36); rel(37); }
            TS(18);
            uint32_t pk[8];
#pragma unroll
            for (int j = 0; j < 8; j++) {
                const float u0 = (d0[4 * j] + d0[4 * j + 2]) * rs, u1 = (d0[4 * j + 1] + d0[4 * j + 3]) * rs;
                const float t0 = tanh_fast((d1[4 * j] + d1[4 * j + 2]) * rs), t1 = tanh_fast((d1[4 * j + 1] + d1[4 * j + 3]) * rs);
                pk[j] = pack2(fmaf(u0, t0, u0), fmaf(u1, t1, u1));
            }
            if (wq == 0 || wq == 3) {
                uint4* hp = &g_halo[((pair * 4 + tile) * 2 + (wq & 1)) * 64 + lane];
                st_data(hp, pk[0], pk[1], pk[2], pk[3]);
                st_data(hp + 32, pk[4], pk[5], pk[6], pk[7]);
            }
            const uint32_t gs = H + 16384 + w * GCH + wq * 1024;
            stsm4(gs + 1024 + foff, pk[0], pk[1], pk[2], pk[3]);
            stsm4(gs + 1024 + (foff ^ 64), pk[4], pk[5], pk[6], pk[7]);
            bar_sync(8 + w, 192);
            TS(26);
            uint32_t ca[8], cb[8];
            const int e = (wq & 1) * 4;
            const uint32_t lo = ((mir ^ e) * 144) ^ (lane * 4);
            const int dir = mir ? -1024 : 1024;
            const uint32_t gb = H + 16384 + w * GCH + (mir ? 3072 : 2048) + lo, sown_ = H + tile * HCH, so = sown_ + (mir ? 1024 : 2048) + lo;
            auto finish = [&](int i) {
                const uint32_t c = hadd2(ca[i], cb[i]);
                const float h0 = blo(c), h1 = bhi(c);
                sts32((so + (i >> 2) * dir) ^ ((i & 3) * 144), pack2(fmaf(h0, tanh_fast(h0), h0), fmaf(h1, tanh_fast(h1), h1)));
            };
#pragma unroll
            for (int k = 0; k < 26; k++) {
                if (k == 19) {
#pragma unroll
                    for (int i = 0; i < 4; i++) finish(i);
                    fence_async_smem();
                    bar_sync(2 + w, 128);
                    if (wq == 0) peer_copy(mapa(sown_ + 1024, r ^ 1), sown_ + 1024, 2048, mapa(bars + B_SR * 8, r ^ 1));
                    mbar_wait(bars + (B_HALO + 2 * w + (wq >> 1)) * 8, 0);
                    if (LATE & 1) rel(35);
                    if (LATE & 2) { rel(36); rel(37); }
                    TS(27);
                }
                const uint32_t g = lds32((gb + (((k + 1) & 4) ? ((k + 1) >> 3) + (wq & 1) : ((k + 1) >> 3)) * dir) ^ (((k + 1) & 7) * 144));
#pragma unroll
                for (int i = 0; i < 8; i++) {
                    const int tap = k - (i & 3) - 2 * (i & 4);
                    if (tap == 0) ca[i] = hmul2(g, dwr[0]);
                    else if (tap > 0 && tap < 8) ca[i] = hfma2(g, dwr[tap], ca[i]);
                    else if (tap == 8) cb[i] = hmul2(g, dwr[8]);
                    else if (tap > 8 && tap < 15) cb[i] = hfma2(g, dwr[tap], cb[i]);
                }
            }
#pragma unroll
            for (int i = 4; i < 8; i++) finish(i);
            fence_async_smem();
            bar_sync(12 + (warp >> 1), 64);
            if (wq == 0 || wq == 3) peer_copy(mapa(sown_ + wq * 1024, r ^ 1), sown_ + wq * 1024, 1024, mapa(bars + B_SR * 8, r ^ 1));
            bar_sync(10, 256);
            TS(19);
            auto frags = [&](int i, int half) {
                const uint32_t src = H + 2 * half * HCH + wq * 1024;
#pragma unroll
                for (int k = 0; k < 4; k++) ldsm4(src + (k >> 1) * HCH + (foff ^ ((k & 1) * 64)), a[i + 4 * k], a[i + 4 * k + 1], a[i + 4 * k + 2], a[i + 4 * k + 3]);
            };
            frags(0, r);
            sp(d0, 38, a, 0, 0);
            acq(39);
            mbar_wait(bars + B_SR * 8, 0);
            frags(16, r ^ 1);
            sp(d0, 39, a + 16, 0, 1);
            residual(38);
            TS(20);
            continue;
        }

        {
            TS(11);
            unsigned char* g = g_kvq + (size_t)((b * 4 + tile) * 1024 + trow) * 128;
            const uint32_t uo = (lane >> 2) * 128 + ((c4 ^ (lane >> 2)) << 4);
            auto put = [&](float (&d)[32], int i) {
                pin(d);
                uint32_t pk[8];
#pragma unroll
                for (int j = 0; j < 8; j++) pk[j] = pack2((d[4 * j] + d[4 * j + 2]) * rstd, (d[4 * j + 1] + d[4 * j + 3]) * rstd);
                if (i < 2 && ((SHX >> i) & 1)) {
                    const bool up = lane & 16;
                    uint32_t t[4];
#pragma unroll
                    for (int j = 0; j < 4; j++) t[j] = __shfl_xor_sync(~0u, up ? pk[j] : pk[4 + j], 16);
                    const uint32_t o0 = ((lane >> 2) & 3) * 128 + (((c4 + (up ? 4 : 0)) ^ ((lane >> 2) & 3)) << 4);
                    stg128(g + i * 1048576 + o0, up ? make_uint4(t[0], t[1], t[2], t[3]) : make_uint4(pk[0], pk[1], pk[2], pk[3]));
                    stg128(g + i * 1048576 + ((o0 + 512) ^ 64), up ? make_uint4(pk[4], pk[5], pk[6], pk[7]) : make_uint4(t[0], t[1], t[2], t[3]));
                } else if (i < 2) {
                    stg128(g + i * 1048576 + uo, make_uint4(pk[0], pk[1], pk[2], pk[3]));
                    stg128(g + i * 1048576 + (uo ^ 64), make_uint4(pk[4], pk[5], pk[6], pk[7]));
                } else {
                    const uint32_t stg = H + warp * 1024;
                    sts128(stg + uo, pk[0], pk[1], pk[2], pk[3]);
                    sts128(stg + (uo ^ 64), pk[4], pk[5], pk[6], pk[7]);
                    __syncwarp();
                    ldsm4(stg + foff, pk[0], pk[1], pk[2], pk[3]);
                    ldsm4(stg + (foff ^ 64), pk[4], pk[5], pk[6], pk[7]);
                    st_data(g + 2097152 + lane * 16, pk[0], pk[1], pk[2], pk[3]);
                    st_data(g + 2097152 + 512 + lane * 16, pk[4], pk[5], pk[6], pk[7]);
                }
            };
            sp(d0, 16, a, w, 0);
            acq(17);
            sp(d1, 17, a, w, 0);
            gather_peer();
            acq(18);
            sp(d0, 18, a + 16, 0, 1);
            wg_wait<1>();
            rel(16); rel(17);
            acq(19);
            sp(d1, 19, a + 16, 0, 1);
            wg_wait<1>();
            rel(18);
            put(d0, 0);
            wg_wait<0>();
            rel(19);
            TS(37);
            put(d1, 1);
            bar_arrive(4, 288);
            TS(38);
            acq(20);
            sp(d0, 20, a, w, 0);
            acq(21);
            sp(d0, 21, a + 16, 0, 1);
            acq(22); acq(23);
            rel(22); rel(23);
            mbar_wait(bars + B_RST * 8, 0);
            wg_wait<0>();
            rel(20); rel(21);
            put(d0, 2);
            TS(12);
        }

        {
            constexpr float CS = 0.125f * 1.4426950408889634f;
            float sa[32], sb2[32], o[36];
            uint32_t pa[16], pb[16], q[16];
            float n0 = INFINITY, n1 = INFINITY;
            zero(o); zero(pa); zero(pb); zero(sb2);
            const uint32_t ones = sb + OFF_MISC + 2048;
            { const uint32_t c = w ? 0u : 0x3F803F80u; sts128(ones + tid * 16, c, c, c, c); }
            fence_async_smem();
            bar_sync(10, 256);
            const uint32_t vdesc = rdesc + ((((ones - rbase) >> 4) - 1) << 16);
            auto qk_issue = [&](float (&s)[32], uint32_t lo) {
                const uint64_t kd = mkdesc(lo);
                wg_fence();
#pragma unroll
                for (int k = 0; k < 4; k++) mma_qk(s, q[4 * k], q[4 * k + 1], q[4 * k + 2], q[4 * k + 3], kd + 2 * k, k != 0);
                wg_commit();
            };
            auto both_issue = [&](float (&s)[32], uint32_t klo, uint32_t (&pp)[16], uint32_t vlo) {
                const uint64_t kd = mkdesc(klo), vd = mkdesc(vlo);
                wg_fence();
#pragma unroll
                for (int k = 0; k < 4; k++) {
                    mma_pv(o, pp[4 * k], pp[4 * k + 1], pp[4 * k + 2], pp[4 * k + 3], vd - k * (128 * 65535));
                    mma_qk(s, q[4 * k], q[4 * k + 1], q[4 * k + 2], q[4 * k + 3], kd + 2 * k, k != 0);
                }
                wg_commit();
            };
            auto new_max = [&](float (&s)[32], int nj, float& x0, float& x1) {
                x0 = s[0]; x1 = s[2];
#pragma unroll
                for (int j = 0; j < nj; j++) {
                    x0 = fmaxf(x0, fmaxf(s[4 * j], s[4 * j + 1]));
                    x1 = fmaxf(x1, fmaxf(s[4 * j + 2], s[4 * j + 3]));
                }
                x0 = fmaxf(x0, __shfl_xor_sync(~0u, x0, 1)); x1 = fmaxf(x1, __shfl_xor_sync(~0u, x1, 1));
                x0 = fmaxf(x0, __shfl_xor_sync(~0u, x0, 2)); x1 = fmaxf(x1, __shfl_xor_sync(~0u, x1, 2));
                x0 = fminf(n0, fmaf(x0, -CS, -20.f)); x1 = fminf(n1, fmaf(x1, -CS, -20.f));
            };
            auto probs = [&](float (&s)[32], uint32_t (&pp)[16], bool ready, bool tail, auto wait) {
                uint32_t any = 0;
#pragma unroll
                for (int i = 0; i < 16; i++) {
                    pp[i] = pack2(ex2(fmaf(s[2 * i], CS, (i & 1) ? n1 : n0)), ex2(fmaf(s[2 * i + 1], CS, (i & 1) ? n1 : n0)));
                    any |= pp[i];
                }
                wg_wait<0>();
                pin(sa); pin(sb2); pin(o); pin(pa); pin(pb);
                if (__builtin_expect(__any_sync(~0u, (any & 0x40004000u) || !ready), 0)) {
                    wait();
                    if (__any_sync(~0u, any & 0x40004000u)) {
                        if (tail) {
#pragma unroll
                            for (int i = 20; i < 32; i++) s[i] = -INFINITY;
                        }
                        float x0, x1;
                        new_max(s, 8, x0, x1);
                        const float sc0 = ex2(x0 - n0), sc1 = ex2(x1 - n1);
                        n0 = x0; n1 = x1;
#pragma unroll
                        for (int j = 0; j < 9; j++) { o[4 * j] *= sc0; o[4 * j + 1] *= sc0; o[4 * j + 2] *= sc1; o[4 * j + 3] *= sc1; }
#pragma unroll
                        for (int i = 0; i < 16; i++)
                            pp[i] = pack2(ex2(fmaf(s[2 * i], CS, (i & 1) ? n1 : n0)), ex2(fmaf(s[2 * i + 1], CS, (i & 1) ? n1 : n0)));
                    }
                }
            };
            {
                uint4 u[4];
                const unsigned char* src = g_kvq + 2097152 + (size_t)(abh * 1024 + qt * 64 + wq * 16) * 128 + lane * 16;
                spin(QGATE);
                ld_data<512>(u, src);
#pragma unroll
                for (int k = 0; k < 2; k++) {
                    q[8 * k] = u[k].x; q[8 * k + 1] = u[k + 2].x; q[8 * k + 2] = u[k].y; q[8 * k + 3] = u[k + 2].y;
                    q[8 * k + 4] = u[k].z; q[8 * k + 5] = u[k + 2].z; q[8 * k + 6] = u[k].w; q[8 * k + 7] = u[k + 2].w;
                }
                pin(q);
            }
            TS(40);
            acq(24);
            TS(13);
            qk_issue(sa, rdesc + (24 % NSLOT) * (SLOT >> 4));
            wg_wait<0>();
            pin(sa);
            {
                float x0, x1;
                new_max(sa, NJ0, x0, x1);
                n0 = x0; n1 = x1;
            }
            bar_arrive(6, 384);
            uint32_t vd = vdesc - (SLOT >> 4) * 65535u, kd = rdesc, vb = fbar + 8, kb = fbar;
            uint32_t vlast = vdesc - 4 * (SLOT >> 4) * 65535u, klast = rdesc + 4 * (SLOT >> 4) + 512;
            uint32_t kprev = fbar + 32, vprev = bars + (B_SINK - (B_EMPTY - B_FULL)) * 8;
#pragma unroll 1
            for (int it = 0; it < 4; it++) {
                both_issue(sb2, klast, pb, vlast);
                probs(sa, pa, mbar_test(vb, it < 2) & mbar_test(kb, it < 3), false, [&]() { mbar_wait(vb, it < 2); mbar_wait(kb, it < 3); });
                TS(41 + it * 4);
                if (lane == 0) mbar_arrive(kprev + (B_EMPTY - B_FULL) * 8);
                if (lane == 0) mbar_arrive(vprev + (B_EMPTY - B_FULL) * 8);
                both_issue(sa, kd, pa, vd);
                const int dv = it == 0 ? 2 : (it == 1 ? -3 : 1);
                kprev = kb; vprev = vb; vlast = vd - 512 * 65535u; klast = kd + 512;
                vd -= dv * (SLOT >> 4) * 65535u; vb += dv * 8;
                kd += (it == 2 ? -3 : 2) * (SLOT >> 4); kb = it == 2 ? vb : kb + 16;
                probs(sb2, pb, true, it == 3 && w == 1, []() {});
                TS(43 + it * 4);
            }
            wg_fence();
#pragma unroll
            for (int k = 0; k < 4; k++)
                mma_pv(o, pb[4 * k], pb[4 * k + 1], pb[4 * k + 2], pb[4 * k + 3], mkdesc(vlast - k * (128 * 65535) + (k > 1 ? w * ((k - 1) << 22) : 0)));
            wg_commit();
            const int row = wq * 16 + (lane >> 2);
            const uint32_t ml = sb + OFF_MISC;
            mbar_wait(bars + (B_RST + 1) * 8, 0);
            wg_wait<0>();
            pin(o); pin(pb); pin(sa); pin(sb2);
            if (!(LATE & 4)) rel(31);
            const float l0 = o[32], l1 = o[34];
            if (c4 == 0) { sts64f(ml + w * 512 + row * 8, n0, l0); sts64f(ml + w * 512 + row * 8 + 64, n1, l1); }
            TS(14);
            float mine[16];
#pragma unroll
            for (int j = 0; j < 4; j++) {
                if (w == 0) sts128f(H + j * 2048 + wt * 16, o[16 + 4 * j], o[17 + 4 * j], o[18 + 4 * j], o[19 + 4 * j]);
                else sts128f(H + 8192 + j * 2048 + wt * 16, o[4 * j], o[4 * j + 1], o[4 * j + 2], o[4 * j + 3]);
            }
#pragma unroll
            for (int i = 0; i < 16; i++) mine[i] = w == 0 ? o[i] : o[16 + i];
            bar_sync(10, 256);
            const float2 u0 = lds64f(ml + (w ^ 1) * 512 + row * 8), u1 = lds64f(ml + (w ^ 1) * 512 + row * 8 + 64);
            const float x0 = fminf(n0, u0.x), x1 = fminf(n1, u1.x);
            float a0 = ex2(x0 - n0), b0 = ex2(x0 - u0.x), a1 = ex2(x1 - n1), b1 = ex2(x1 - u1.x);
            const float i0 = __fdividef(1.f, fmaf(a0, l0, b0 * u0.y)), i1 = __fdividef(1.f, fmaf(a1, l1, b1 * u1.y));
            a0 *= i0; b0 *= i0; a1 *= i1; b1 *= i1;
            uint32_t pk[8];
#pragma unroll
            for (int j = 0; j < 4; j++) {
                const float4 v = lds128f(H + (w ^ 1) * 8192 + j * 2048 + wt * 16);
                pk[2 * j] = pack2(fmaf(a0, mine[4 * j], b0 * v.x), fmaf(a0, mine[4 * j + 1], b0 * v.y));
                pk[2 * j + 1] = pack2(fmaf(a1, mine[4 * j + 2], b1 * v.z), fmaf(a1, mine[4 * j + 3], b1 * v.w));
            }
            unsigned char* dst = g_o + (size_t)(b * 128 + qt * 8 + 2 * wq) * 4096 + ah * 1024 + w * 512 + lane * 16;
            st_data(dst, pk[0], pk[2], pk[4], pk[6]);
            st_data(dst + 4096, pk[1], pk[3], pk[5], pk[7]);
            if (tid == 0) asm volatile("red.relaxed.gpu.global.add.u32 [%0], 1;" ::"l"(&g_epoch[blockIdx.x * FS]) : "memory");
            TS(15);
        }

        {
            const uint32_t* dp = reinterpret_cast<const uint32_t*>(p.dw + (mir ? 14 * 256 : 0) + tile * 64) + lane;
#pragma unroll
            for (int i = 0; i < 15; i++) asm volatile("ld.global.nc.b32 %0, [%1];" : "=r"(dwr[i]) : "l"(dp + i * (mir ? -128 : 128)));
            acq(32); acq(33); acq(34);
            uint4 u[8];
            ld_data<512>(u, g_o + (size_t)(b * 128 + pt * 4 + wq) * 4096 + lane * 16);
#pragma unroll
            for (int i = 0; i < 8; i++) { a[4 * i] = u[i].x; a[4 * i + 1] = u[i].y; a[4 * i + 2] = u[i].z; a[4 * i + 3] = u[i].w; }
            if (LATE & 4) rel(31);
            TS(16);
            sp(d0, 32, a, 0, 0);
            sp(d0, 33, a + 16, 0, 1);
#pragma unroll
            for (int i = 0; i < 15; i++) dwr[i] = hmul2(dwr[i], 0x3F003F00u);
            residual(32);
            TS(17);
        }
    }

    cluster_arrive();
    TS(24);
    {
        const float rstd = rsq(fmaxf(fmaf(-mean, mean, msq), 0.f) + 1e-5f), nb = -mean * rstd;
#pragma unroll
        for (int j = 0; j < 8; j++) xr[j] = pack2(fmaf(v[2 * j], rstd, nb), fmaf(v[2 * j + 1], rstd, nb));
        const uint32_t stg = P + 16384 + warp * 1024;
        stsm4(stg + foff, xr[0], xr[1], xr[2], xr[3]);
        stsm4(stg + (foff ^ 64), xr[4], xr[5], xr[6], xr[7]);
        __syncwarp();
        const uint32_t src = stg + (lane >> 3) * 128 + (((lane & 7) ^ (lane >> 3)) << 4);
        const uint4 u0 = lds128(src), u1 = lds128((src + 512) ^ 64);
        __nv_bfloat16* dst = p.out + (size_t)(b * T_ + trow + (lane >> 3)) * 256 + tile * 64 + (lane & 7) * 8;
        if (trow < T_) { stg128(dst, u0); stg128(dst + 4 * 256, u1); }
    }
    TS(25);
    TG(31);
    TSDUMP();
    cluster_wait();
}

typedef CUresult (*EncodeFn)(CUtensorMap*, CUtensorMapDataType, cuuint32_t, void*, const cuuint64_t*, const cuuint64_t*,
                             const cuuint32_t*, const cuuint32_t*, CUtensorMapInterleave, CUtensorMapSwizzle,
                             CUtensorMapL2promotion, CUtensorMapFloatOOBfill);

}

extern "C" void kernel_launch(void* const* d_in, const int* in_sizes, int n_in, void* d_out, int out_size) {
    static EncodeFn encode = nullptr;
    if (!encode) {
        void* fn = nullptr;
        cudaDriverEntryPointQueryResult qr;
        cudaGetDriverEntryPoint("cuTensorMapEncodeTiled", &fn, cudaEnableDefault, &qr);
        encode = (EncodeFn)fn;
        cudaFuncSetAttribute(conformer_kernel, cudaFuncAttributeMaxDynamicSharedMemorySize, SMEM_LAUNCH);
    }
    Scalars p;
    Maps m;
    const cuuint32_t ones[5] = {1, 1, 1, 1, 1};
    const int idx[8] = {1, 2, 3, 4, 5, 7, 8, 9};
    const int rows[8] = {256, 1024, 256, 256, 256, 256, 256, 1024};
    const int cols[8] = {1024, 256, 768, 256, 512, 256, 1024, 256};
    for (int i = 0; i < 8; i++) {
        const cuuint64_t pitch = (cuuint64_t)cols[i] * 2;
        const bool f = i != 0 && i != 3;
        const cuuint64_t dims[5] = {(cuuint64_t)cols[i], f ? 2u : 4u, f ? 2u : 4u, f ? 4u : 2u, (cuuint64_t)rows[i] / (f ? 16 : 32)};
        const cuuint64_t strides[4] = {pitch, pitch * 8, pitch * (f ? 2 : 4), pitch * (f ? 16 : 32)};
        const cuuint32_t box[5] = {64, f ? 2u : 4u, f ? 2u : 4u, f ? 4u : 2u, f ? 8u : 4u};
        encode(&m.tm[i], CU_TENSOR_MAP_DATA_TYPE_BFLOAT16, 5, d_in[idx[i]], dims, strides, box, ones, CU_TENSOR_MAP_INTERLEAVE_NONE,
               CU_TENSOR_MAP_SWIZZLE_128B, CU_TENSOR_MAP_L2_PROMOTION_L2_128B, CU_TENSOR_MAP_FLOAT_OOB_FILL_NONE);
        m.w[i] = (const char*)d_in[idx[i]];
    }
    {
        void* kv = nullptr;
        cudaGetSymbolAddress(&kv, g_kvq);
        const cuuint64_t dims[2] = {64, 16384};
        const cuuint64_t strides[1] = {128};
        const cuuint32_t box[2] = {64, 128};
        encode(&m.tm[8], CU_TENSOR_MAP_DATA_TYPE_BFLOAT16, 2, kv, dims, strides, box, ones, CU_TENSOR_MAP_INTERLEAVE_NONE,
               CU_TENSOR_MAP_SWIZZLE_NONE, CU_TENSOR_MAP_L2_PROMOTION_L2_128B, CU_TENSOR_MAP_FLOAT_OOB_FILL_NONE);
    }
    p.x = (const __nv_bfloat16*)d_in[0];
    p.dw = (const __nv_bfloat16*)d_in[6];
    p.out = (__nv_bfloat16*)d_out;
    p.zero = 0;
    conformer_kernel<<<NCTA, NTHREADS, SMEM_LAUNCH>>>(p, m);
}
```

```cpp
#include <cuda_runtime.h>
#include <cuda_bf16.h>
#include <cuda.h>
#include <stdint.h>

namespace {

constexpr int T_ = 1000;
constexpr int NCTA = 128;
constexpr int NTHREADS = 512;
constexpr int NSLOT = 5;
constexpr int SLOT = 16384;
constexpr int NLOADS = 56;

constexpr uint32_t OFF_RING = 0;
constexpr uint32_t OFF_P = 163840;
constexpr uint32_t OFF_H = 188416;
constexpr uint32_t OFF_MISC = 221184;
constexpr uint32_t OFF_BARS = 229888;
constexpr uint32_t SMEM_BYTES = 230400;
constexpr uint32_t GCH = 6144;
constexpr uint32_t HCH = 4096;

constexpr int B_FULL = 0, B_EMPTY = 10, B_XA = 20  , B_XB = 25  , B_INB = 29  , B_SR = 33,
              B_RST = 34, B_RDY = 35  , B_SINK = 41, B_HALO = 42  , NBARS = 46;

#define KD2 300u
#define KD3 500u
#define QGATE 500u
#define BACKOFF 0u
#define KFS 32
#define KDELAY 450u
#define NJ0 2
#define HDELAY 200u
#define LATE 3
#define SND 0
#define PF0 0
#define TWO 1
#define TURN 0x200
#define EAGER 0x0155
constexpr int FS = 8;

struct Scalars {
    const __nv_bfloat16* x;
    const __nv_bfloat16* dw;
    __nv_bfloat16* out;
    uint32_t zero;
};
struct Maps {
    CUtensorMap tm[9];
    const char* w[8];
};

__device__ __align__(1024) unsigned char g_kvq[3 * 8 * 1024 * 128];
__device__ __align__(1024) unsigned char g_o[2 * 128 * 4096];
__device__ uint4 g_halo[64 * 4 * 2 * 64];
__device__ __align__(128) uint32_t g_flag_kv[8 * 32 * KFS];
__device__ uint32_t g_reset[2 * 32];
__device__ uint32_t g_epoch[NCTA * FS];

#define TS(i) do { } while (0)
#define TSW(i) do { } while (0)
#define TG(i) do { } while (0)
#define TSINIT() do { } while (0)
#define TSDUMP() do { } while (0)
constexpr uint32_t SMEM_LAUNCH = SMEM_BYTES;

__device__ __forceinline__ uint32_t smem_u32(const void* p) { return (uint32_t)__cvta_generic_to_shared(p); }
__device__ __forceinline__ void mbar_init(uint32_t b, uint32_t c) { asm volatile("mbarrier.init.shared::cta.b64 [%0], %1;" ::"r"(b), "r"(c) : "memory"); }
__device__ __forceinline__ void mbar_arrive(uint32_t b) { asm volatile("mbarrier.arrive.shared::cta.b64 _, [%0];" ::"r"(b) : "memory"); }
__device__ __forceinline__ void mbar_arrive_tx(uint32_t b, uint32_t tx) { asm volatile("mbarrier.arrive.expect_tx.shared::cta.b64 _, [%0], %1;" ::"r"(b), "r"(tx) : "memory"); }
__device__ __forceinline__ void mbar_wait(uint32_t b, uint32_t ph) {
    asm volatile("{\n.reg .pred p, q;\n.reg .u32 c;\nmov.u32 c, 0;\n"
                 "MW_LOOP:\n.pragma \"nounroll\";\n"
                 "mbarrier.try_wait.parity.shared::cta.b64 p, [%0], %1;\n"
                 "add.u32 c, c, 1;\nsetp.lt.u32 q, c, 65536;\nnot.pred p, p;\nand.pred p, p, q;\n@p bra MW_LOOP;\n}"
                 ::"r"(b), "r"(ph) : "memory");
}
__device__ __forceinline__ bool mbar_test(uint32_t b, uint32_t ph) {
    uint32_t ok;
    asm volatile("{\n.reg .pred p;\nmbarrier.test_wait.parity.shared::cta.b64 p, [%1], %2;\nselp.u32 %0, 1, 0, p;\n}" : "=r"(ok) : "r"(b), "r"(ph) : "memory");
    return ok;
}
__device__ __forceinline__ uint32_t mapa(uint32_t a, uint32_t r) { uint32_t o; asm("mapa.shared::cluster.u32 %0, %1, %2;" : "=r"(o) : "r"(a), "r"(r)); return o; }
__device__ __forceinline__ void fence_async_smem() { asm volatile("fence.proxy.async.shared::cta;" ::: "memory"); }
__device__ __forceinline__ void fence_async_global() { asm volatile("fence.proxy.async.global;" ::: "memory"); }
__device__ __forceinline__ void bar_sync(int id, int n) { asm volatile("bar.sync %0, %1;" ::"r"(id), "r"(n) : "memory"); }
__device__ __forceinline__ void bar_arrive(int id, int n) { asm volatile("bar.arrive %0, %1;" ::"r"(id), "r"(n) : "memory"); }
__device__ __forceinline__ void cluster_arrive() { asm volatile("barrier.cluster.arrive.relaxed.aligned;" ::: "memory"); }
__device__ __forceinline__ void cluster_wait() { asm volatile("barrier.cluster.wait.aligned;" ::: "memory"); }

__device__ __forceinline__ void ring_load(uint32_t dst, const CUtensorMap* tm, int col, int row16, uint32_t bar) {
    asm volatile("{\n.reg .pred p;\nelect.sync _|p, 0xffffffff;\n"
                 "@p mbarrier.arrive.expect_tx.shared::cta.b64 _, [%2], 16384;\n"
                 "@p cp.async.bulk.tensor.5d.shared::cluster.global.mbarrier::complete_tx::bytes [%0], [%1, {%3, 0, 0, 0, %4}], [%2];\n}"
                 ::"r"(dst), "l"(tm), "r"(bar), "r"(col), "r"(row16) : "memory");
}
__device__ __forceinline__ void ring_load_both(uint32_t dst, const CUtensorMap* tm, int c1, uint32_t bar) {
    asm volatile("{\n.reg .pred p;\nelect.sync _|p, 0xffffffff;\n"
                 "@p cp.async.bulk.tensor.2d.shared::cluster.global.mbarrier::complete_tx::bytes.multicast::cluster [%0], [%1, {0, %3}], [%2], %4;\n}"
                 ::"r"(dst), "l"(tm), "r"(bar), "r"(c1), "h"((uint16_t)3) : "memory");
}
__device__ __forceinline__ void mbar_arrive_peer(uint32_t b) { asm volatile("mbarrier.arrive.relaxed.cluster.shared::cluster.b64 _, [%0];" ::"r"(b) : "memory"); }
__device__ __forceinline__ void prefetch_l2(const void* src, uint32_t bytes) {
    asm volatile("cp.async.bulk.prefetch.L2.global [%0], %1;" ::"l"(src), "r"(bytes) : "memory");
}
__device__ __forceinline__ void peer_copy(uint32_t dst, uint32_t src, uint32_t bytes, uint32_t rbar) {
    asm volatile("{\n.reg .pred p;\nelect.sync _|p, 0xffffffff;\n"
                 "@p cp.async.bulk.shared::cluster.shared::cta.mbarrier::complete_tx::bytes [%0], [%1], %2, [%3];\n}"
                 ::"r"(dst), "r"(src), "r"(bytes), "r"(rbar) : "memory");
}
__device__ __forceinline__ void st_async4(uint32_t dst, uint32_t a, uint32_t b, uint32_t c, uint32_t d, uint32_t bar) {
    asm volatile("st.async.shared::cluster.mbarrier::complete_tx::bytes.v4.b32 [%0], {%1,%2,%3,%4}, [%5];" ::"r"(dst), "r"(a), "r"(b), "r"(c), "r"(d), "r"(bar) : "memory");
}
__device__ __forceinline__ void put_sums(uint32_t dst, uint32_t rdst, float a, float b, uint32_t rbar, bool on) {
    asm volatile("{\n.reg .pred p;\nsetp.ne.u32 p, %5, 0;\n"
                 "@p st.async.shared::cluster.mbarrier::complete_tx::bytes.v2.f32 [%1], {%2,%3}, [%4];\n"
                 "@p st.shared.v2.f32 [%0], {%2,%3};\n}" ::"r"(dst), "r"(rdst), "f"(a), "f"(b), "r"(rbar), "r"((uint32_t)on) : "memory");
}
__device__ __forceinline__ void stsm4(uint32_t a, uint32_t r0, uint32_t r1, uint32_t r2, uint32_t r3) {
    asm volatile("stmatrix.sync.aligned.m8n8.x4.shared.b16 [%0], {%1,%2,%3,%4};" ::"r"(a), "r"(r0), "r"(r1), "r"(r2), "r"(r3) : "memory");
}
__device__ __forceinline__ void ldsm4(uint32_t a, uint32_t& r0, uint32_t& r1, uint32_t& r2, uint32_t& r3) {
    asm volatile("ldmatrix.sync.aligned.m8n8.x4.shared.b16 {%0,%1,%2,%3}, [%4];" : "=r"(r0), "=r"(r1), "=r"(r2), "=r"(r3) : "r"(a) : "memory");
}
__device__ __forceinline__ uint4 lds128(uint32_t a) { uint4 v; asm volatile("ld.shared.v4.b32 {%0,%1,%2,%3}, [%4];" : "=r"(v.x), "=r"(v.y), "=r"(v.z), "=r"(v.w) : "r"(a) : "memory"); return v; }
__device__ __forceinline__ float4 lds128f(uint32_t a) { float4 v; asm volatile("ld.shared.v4.f32 {%0,%1,%2,%3}, [%4];" : "=f"(v.x), "=f"(v.y), "=f"(v.z), "=f"(v.w) : "r"(a) : "memory"); return v; }
__device__ __forceinline__ float2 lds64f(uint32_t a) { float2 v; asm volatile("ld.shared.v2.f32 {%0,%1}, [%2];" : "=f"(v.x), "=f"(v.y) : "r"(a) : "memory"); return v; }
__device__ __forceinline__ uint32_t lds32(uint32_t a) { uint32_t v; asm volatile("ld.shared.b32 %0, [%1];" : "=r"(v) : "r"(a) : "memory"); return v; }
__device__ __forceinline__ void sts128(uint32_t a, uint32_t x, uint32_t y, uint32_t z, uint32_t w) { asm volatile("st.shared.v4.b32 [%0], {%1,%2,%3,%4};" ::"r"(a), "r"(x), "r"(y), "r"(z), "r"(w) : "memory"); }
__device__ __forceinline__ void sts128f(uint32_t a, float x, float y, float z, float w) { asm volatile("st.shared.v4.f32 [%0], {%1,%2,%3,%4};" ::"r"(a), "f"(x), "f"(y), "f"(z), "f"(w) : "memory"); }
__device__ __forceinline__ void sts64f(uint32_t a, float x, float y) { asm volatile("st.shared.v2.f32 [%0], {%1,%2};" ::"r"(a), "f"(x), "f"(y) : "memory"); }
__device__ __forceinline__ void sts32(uint32_t a, uint32_t x) { asm volatile("st.shared.b32 [%0], %1;" ::"r"(a), "r"(x) : "memory"); }
__device__ __forceinline__ void stg128(void* p, uint4 v) { asm volatile("st.global.v4.b32 [%0], {%1,%2,%3,%4};" ::"l"(p), "r"(v.x), "r"(v.y), "r"(v.z), "r"(v.w) : "memory"); }

__device__ __forceinline__ uint32_t pack2(float lo, float hi) { uint32_t r; asm("cvt.rn.bf16x2.f32 %0, %1, %2;" : "=r"(r) : "f"(hi), "f"(lo)); return r; }
__device__ __forceinline__ float blo(uint32_t v) { return __uint_as_float(v << 16); }
__device__ __forceinline__ float bhi(uint32_t v) { return __uint_as_float(v & 0xffff0000u); }
__device__ __forceinline__ uint32_t hmul2(uint32_t a, uint32_t b) { uint32_t r; asm("mul.rn.bf16x2 %0, %1, %2;" : "=r"(r) : "r"(a), "r"(b)); return r; }
__device__ __forceinline__ uint32_t hadd2(uint32_t a, uint32_t b) { uint32_t r; asm("add.rn.bf16x2 %0, %1, %2;" : "=r"(r) : "r"(a), "r"(b)); return r; }
__device__ __forceinline__ uint32_t hsub2(uint32_t a, uint32_t b) { uint32_t r; asm("sub.rn.bf16x2 %0, %1, %2;" : "=r"(r) : "r"(a), "r"(b)); return r; }
__device__ __forceinline__ uint32_t hfma2(uint32_t a, uint32_t b, uint32_t c) { uint32_t r; asm("fma.rn.bf16x2 %0, %1, %2, %3;" : "=r"(r) : "r"(a), "r"(b), "r"(c)); return r; }
__device__ __forceinline__ float tanh_fast(float x) { float r; asm("tanh.approx.f32 %0, %1;" : "=f"(r) : "f"(x)); return r; }
__device__ __forceinline__ float rsq(float x) { float r; asm("rsqrt.approx.ftz.f32 %0, %1;" : "=f"(r) : "f"(x)); return r; }
__device__ __forceinline__ float ex2(float x) { float r; asm("ex2.approx.ftz.f32 %0, %1;" : "=f"(r) : "f"(x)); return r; }

__device__ __forceinline__ uint32_t ld_relaxed(const uint32_t* p) {
    uint32_t v;
    asm volatile("ld.relaxed.gpu.global.u32 %0, [%1];" : "=r"(v) : "l"(p) : "memory");
    return v;
}
__device__ __forceinline__ uint32_t clock32() { uint32_t c; asm volatile("mov.u32 %0, %%clock;" : "=r"(c)::"memory"); return c; }
__device__ __forceinline__ void spin(uint32_t clks) {
    const uint32_t t0 = clock32();
    while (clock32() - t0 < clks) {}
}
__device__ __forceinline__ void flag_wait(const uint32_t* p, uint32_t e, bool mine) {
#pragma unroll 1
    for (int i = 0; i < (1 << 19); i++) {
        if (mine) mine = ld_relaxed(p) != e;
        if (!__any_sync(~0u, mine)) break;
        if (BACKOFF) spin(BACKOFF);
    }
    asm volatile("fence.acquire.gpu;" ::: "memory");
    fence_async_global();
}
__device__ __forceinline__ void st_data(void* p, uint32_t x, uint32_t y, uint32_t z, uint32_t w) {
    asm volatile("st.relaxed.gpu.global.v4.b32 [%0], {%1,%2,%3,%4};" ::"l"(p), "r"(x), "r"(y), "r"(z), "r"(w) : "memory");
}
template <int STRIDE, bool INV = false, int N>
__device__ __forceinline__ void ld_data(uint4 (&v)[N], const unsigned char* p) {
    int it = 0;
    bool again;
#pragma unroll 1
    do {
        uint32_t m = INV ? ~0u : 0u;
#pragma unroll
        for (int i = 0; i < N; i++)
            asm volatile("ld.relaxed.gpu.global.v4.b32 {%0,%1,%2,%3}, [%4];" : "=r"(v[i].x), "=r"(v[i].y), "=r"(v[i].z), "=r"(v[i].w) : "l"(p + i * STRIDE) : "memory");
#pragma unroll
        for (int i = 0; i < N; i++)
            m = INV ? __vimin3_u32(__vimin3_u32(v[i].x, v[i].y, v[i].z), v[i].w, m) : __vimax3_u32(__vimax3_u32(v[i].x, v[i].y, v[i].z), v[i].w, m);
        again = __any_sync(~0u, m == (INV ? 0u : ~0u)) && ++it < (1 << 16);
    } while (again);
}
__device__ __forceinline__ uint32_t ld_epoch() { return ld_relaxed(&g_epoch[blockIdx.x * FS]) + 1; }
__device__ __forceinline__ void flag_set(uint32_t* p, uint32_t e) { asm volatile("st.release.gpu.global.u32 [%0], %1;" ::"l"(p), "r"(e) : "memory"); }

__device__ __forceinline__ uint32_t desc_lo(uint32_t addr) { return ((addr & 0x3FFFF) >> 4) | 0x10000u; }
__device__ __forceinline__ uint64_t mkdesc(uint32_t lo) { return (uint64_t)lo | (0x40000040ull << 32); }
__device__ __forceinline__ void wg_fence() { asm volatile("wgmma.fence.sync.aligned;" ::: "memory"); }
__device__ __forceinline__ void wg_commit() { asm volatile("wgmma.commit_group.sync.aligned;" ::: "memory"); }
template <int N> __device__ __forceinline__ void wg_wait() { asm volatile("wgmma.wait_group.sync.aligned %0;" ::"n"(N) : "memory"); }
template <int N> __device__ __forceinline__ void pin(float (&d)[N]) {
#pragma unroll
    for (int i = 0; i < N; i++) asm volatile("" : "+f"(d[i])::"memory");
}
template <int N> __device__ __forceinline__ void pin(uint32_t (&d)[N]) {
#pragma unroll
    for (int i = 0; i < N; i++) asm volatile("" : "+r"(d[i])::"memory");
}

template <typename Tp, int N> __device__ __forceinline__ void zero(Tp (&d)[N]) {
#pragma unroll
    for (int i = 0; i < N; i++) d[i] = 0;
    pin(d);
}

#define F4(d, i) "+f"(d[i]), "+f"(d[i + 1]), "+f"(d[i + 2]), "+f"(d[i + 3])
#define F16(d, i) F4(d, i), F4(d, i + 4), F4(d, i + 8), F4(d, i + 12)

__device__ __forceinline__ void mma16(float (&d)[4], const uint32_t* a, uint32_t b0, uint32_t b1) {
    asm("mma.sync.aligned.m16n8k16.row.col.f32.bf16.bf16.f32 {%0,%1,%2,%3}, {%4,%5,%6,%7}, {%8,%9}, {%0,%1,%2,%3};"
        : F4(d, 0) : "r"(a[0]), "r"(a[1]), "r"(a[2]), "r"(a[3]), "r"(b0), "r"(b1));
}
template <int N>
__device__ __forceinline__ float row_sum(const uint32_t* x, uint32_t ones = 0x3F803F80u) {
    float c[4] = {};
#pragma unroll
    for (int i = 0; i < N; i += 4) mma16(c, x + i, ones, ones);
    return c[0] + c[2];
}
template <int N>
__device__ __forceinline__ float row_sumsq(const uint32_t* x, int lane) {
    float c0[4] = {}, c1[4] = {};
#pragma unroll
    for (int i = 0; i < N; i += 4) {
        mma16(c0, x + i, x[i], x[i + 2]);
        mma16(c1, x + i, x[i + 1], x[i + 3]);
    }
    return (lane & 4) ? c0[1] + c1[3] : c0[0] + c1[2];
}
__device__ __forceinline__ void mma_sp(float (&d)[32], const uint32_t* a, uint64_t b, uint32_t meta, int acc) {
    asm volatile("{.reg .pred p; setp.ne.b32 p, %38, 0;\n"
                 "wgmma.mma_async.sp.sync.aligned.m64n64k32.f32.bf16.bf16 {%0,%1,%2,%3,%4,%5,%6,%7,%8,%9,%10,%11,%12,%13,%14,%15,%16,%17,%18,%19,%20,%21,%22,%23,%24,%25,%26,%27,%28,%29,%30,%31}, "
                 "{%32,%33,%34,%35}, %36, %37, 0, p, 1, 1, 1;}\n"
                 : F16(d, 0), F16(d, 16) : "r"(a[0]), "r"(a[1]), "r"(a[2]), "r"(a[3]), "l"(b), "r"(meta), "r"(acc));
}
__device__ __forceinline__ void mma_qk(float (&d)[32], uint32_t a0, uint32_t a1, uint32_t a2, uint32_t a3, uint64_t b, int acc) {
    asm volatile("{.reg .pred p; setp.ne.b32 p, %37, 0;\n"
                 "wgmma.mma_async.sync.aligned.m64n64k16.f32.bf16.bf16 {%0,%1,%2,%3,%4,%5,%6,%7,%8,%9,%10,%11,%12,%13,%14,%15,%16,%17,%18,%19,%20,%21,%22,%23,%24,%25,%26,%27,%28,%29,%30,%31}, "
                 "{%32,%33,%34,%35}, %36, p, 1, 1, 0;}\n"
                 : F16(d, 0), F16(d, 16) : "r"(a0), "r"(a1), "r"(a2), "r"(a3), "l"(b), "r"(acc));
}
__device__ __forceinline__ void mma_pv(float (&d)[36], uint32_t a0, uint32_t a1, uint32_t a2, uint32_t a3, uint64_t b) {
    asm volatile("wgmma.mma_async.sync.aligned.m64n72k16.f32.bf16.bf16 {%0,%1,%2,%3,%4,%5,%6,%7,%8,%9,%10,%11,%12,%13,%14,%15,%16,%17,%18,%19,%20,%21,%22,%23,%24,%25,%26,%27,%28,%29,%30,%31,%32,%33,%34,%35}, "
                 "{%36,%37,%38,%39}, %40, 1, 1, 1, 1;\n"
                 : F16(d, 0), F16(d, 16), F4(d, 32) : "r"(a0), "r"(a1), "r"(a2), "r"(a3), "l"(b));
}

__device__ __forceinline__ uint32_t load_code(int n, int r, int w) {
    const int tile = 2 * r + w;
    int m, col, row;
    if (n < 16 || n >= 40) {
        const int k = n < 16 ? n : n - 40;
        m = n < 16 ? 0 : 6;
        if (TWO && n >= 40 && k < 4) { col = 4 * tile + (k & 1); row = (k >> 1) ^ r; }
        else if (k < 8) { col = 4 * tile + (k >> 1); row = n < 16 ? (k & 1) : (k & 1) ^ r; }
        else { m++; col = k < 12 ? tile ^ 2 : tile; row = 2 * (tile ^ (k & 1)) + ((k >> 1) & 1); }
    } else if (n < 32) {
        const int k = n - 16;
        m = 2;
        if (k < 4) { col = tile + ((k & 1) ? 8 : 4); row = (k >> 1) ^ r; }
        else { col = tile; row = (k & 1) ^ r; }
    } else if (n < 34) { m = 3; col = tile; row = n - 32; }
    else if (n < 38) { const int k = n - 34; m = 4; col = tile + 4 * (k & 1); row = (k >> 1) ^ r; }
    else { m = 5; col = tile; row = (n & 1) ^ r; }
    return m | (col << 4) | (row << ((m == 0 || m == 3) ? 10 : 11));
}

__global__ void __cluster_dims__(2, 1, 1) __launch_bounds__(NTHREADS, 1)
conformer_kernel(const Scalars p, const __grid_constant__ Maps m) {
    extern __shared__ __align__(1024) unsigned char smem_raw[];
    const uint32_t sb = smem_u32(smem_raw);
    const uint32_t bars = sb + OFF_BARS;
    const int tid = threadIdx.x;
    const int lane = tid & 31;
    const int warp = __shfl_sync(~0u, tid >> 5, 0);
    const int r = blockIdx.x & 1;
    const int pair = blockIdx.x >> 1;
    const int b = pair >> 5, pt = pair & 31;
    const int ah = pt >> 3, qt = (pt & 7) * 2 + r;
    const int abh = b * 4 + ah;

    TG(30);
    TSINIT();
    TS(0);
    const uint32_t P = sb + OFF_P, H = sb + OFF_H;
    if (warp == 11) {
        if (lane == 0) {
#pragma unroll
            for (int i = 0; i < 2 * NSLOT; i++) mbar_init(bars + (B_FULL + i) * 8, 1);
            asm volatile("fence.mbarrier_init.release.cluster;" ::: "memory");
            fence_async_smem();
        }
        __syncwarp();
        bar_arrive(13, 96);
        cluster_arrive();
    }

    if (warp >= 8) {
        asm volatile("setmaxnreg.dec.sync.aligned.u32 48;");
        if (warp >= 12) {
            cluster_arrive();
            cluster_wait();
            const int ut = tid & 127;
            const uint32_t target = ld_epoch() * 64;
            bar_sync(6, 384);
#pragma unroll
            for (int i = 0; i < 4; i++) {
                st_data(g_o + (size_t)(b * 128 + qt * 8 + 2 * i + (ut >> 6)) * 4096 + ah * 1024 + (ut & 63) * 16, ~0u, ~0u, ~0u, ~0u);
                if (i < 2) st_data(&g_halo[(pair * 4 + 2 * r + i) * 128 + ut], ~0u, ~0u, ~0u, ~0u);
            }
            bar_sync(11, 128);
            if (ut == 0) {
                asm volatile("red.release.gpu.global.add.u32 [%0], 1;" ::"l"(&g_reset[b * 32]) : "memory");
#pragma unroll 1
                for (int i = 0; i < (1 << 20) && ld_relaxed(&g_reset[b * 32]) != target; i++) __nanosleep(100);
                asm volatile("fence.acquire.gpu;" ::: "memory");
                mbar_arrive(bars + B_RST * 8);
            }
            bar_sync(11, 128);
            TS(14);
#pragma unroll
            for (int i = 0; i < 4; i++) st_data(g_kvq + 2097152 + (size_t)(abh * 1024 + qt * 64) * 128 + i * 2048 + ut * 16, 0, 0, 0, 0);
            const int side = warp & 1, wg = (warp >> 1) & 1, np = side ? pt + 1 : pt - 1;
            const unsigned char* src = reinterpret_cast<const unsigned char*>(&g_halo[(((b * 32 + np) * 4 + 2 * r + wg) * 2 + (side ^ 1)) * 64 + lane]);
            const uint32_t dst = H + 16384 + wg * GCH + side * 5120 + (lane & 7) * 128 + (((lane >> 3) ^ (lane & 7)) << 4);
            uint4 hv[2] = {make_uint4(0, 0, 0, 0), make_uint4(0, 0, 0, 0)};
            bar_sync(8 + wg, 192);
            if (np >= 0 && np < 32) {
                spin(HDELAY);
                ld_data<512>(hv, src);
            }
            stsm4(dst, hv[0].x, hv[0].y, hv[0].z, hv[0].w);
            stsm4(dst ^ 64, hv[1].x, hv[1].y, hv[1].z, hv[1].w);
            __syncwarp();
            if (lane == 0) mbar_arrive(bars + (B_HALO + (warp & 3)) * 8);
            TS(4);
        } else if (warp < 10) {
            const int w = warp - 8;
            const uint32_t ring = sb + OFF_RING + w * NSLOT * SLOT;
            const uint32_t full = bars + (B_FULL + w * NSLOT) * 8;
            cluster_arrive();
            bar_sync(13, 96);
            TS(1);
#pragma unroll
            for (int n = 0; n < NSLOT; n++) {
                if (n == 1) bar_sync(12, 64);
                ring_load(ring + n * SLOT, &m.tm[0], 64 * (8 * r + 4 * w + (n >> 1)), 4 * (n & 1), full + n * 8);
            }
            TS(2);
            const uint32_t code = load_code(lane, r, w) | (load_code(lane + 32, r, w) << 16);
            cluster_wait();
            uint32_t s = 0, ph = 0;
            int n = NSLOT;
#pragma unroll 1
            for (int seg = 0; seg < 2; seg++) {
#pragma unroll 1
                for (; n < (seg == 0 ? 22 : NLOADS); n++) {
                    const uint32_t c = __shfl_sync(~0u, code, n) >> (n & 32 ? 16 : 0);
                    const CUtensorMap* tm = &m.tm[c & 15];
                    const uint32_t col = (c & 0xf0) * 4, row = (c & 0xff00) >> 8, dst = ring + s * SLOT;
                    mbar_wait(full + (B_EMPTY - B_FULL) * 8 + s * 8, ph + (((uint32_t)(size_t)tm | col | row | dst) & p.zero));
                    ring_load(dst, tm, col, row, full + s * 8);
                    if (++s == NSLOT) { s = 0; ph ^= 1; }
                }
                if (seg == 1) break;
                const uint32_t epoch = ld_epoch();
                const uint32_t rdy = bars + (B_RDY + 3 * w) * 8, prdy = mapa(rdy, r ^ 1);
                const int odd = r ^ w;
                const uint32_t* flags = g_flag_kv + (abh * 32 + lane) * KFS;
                auto kv_load = [&](uint32_t sl, int isv, int i) {
                    ring_load_both(ring + sl * SLOT, &m.tm[8], (isv * 64 + abh * 8 + 2 * i + w) * 128, full + sl * 8);
                };
#pragma unroll 1
                for (int i = 0; i < 2; i++) {
                    if (lane < 3 + i) {
                        const uint32_t sl = i ? lane : lane + 2;
                        mbar_wait(full + (B_EMPTY - B_FULL + sl) * 8, i ^ 1);
                        mbar_arrive_tx(full + sl * 8, (i || lane == 2) ? SLOT : 0);
                    }
                    __syncwarp();
                }
                if (lane == 0) mbar_arrive_peer(prdy);
                bar_sync(14, 96);
                spin(KDELAY);
                mbar_wait(rdy, 0);
                flag_wait(flags, epoch, (lane >> 2) == 2 * odd + w);
                TSW(5 + 2 * odd);
                if (!odd) { kv_load(4, 0, 0); bar_arrive(12, 64); }
                else bar_sync(12, 64);
                spin(w ? KD3 : KD2);
                kv_load(odd ^ 1, odd ^ 1, odd);
                flag_wait(flags, epoch, (lane >> 2) == 2 * odd + w + 4);
                mbar_wait(full + (odd ^ 1) * 8, 1);
                kv_load(2 + odd, odd, 2 - odd);
#pragma unroll 1
                for (int i = 0; i < 3; i++) {
                    const uint32_t sl = i ? i - 1 : 4, bo = i == 2 ? 16 : 8;
                    mbar_wait(full + (B_EMPTY - B_FULL + sl) * 8, i != 0);
                    if (lane == 0) mbar_arrive_tx(full + sl * 8, SLOT);
                    if ((i & 1) != odd) {
                        mbar_wait(rdy + bo, 0);
                        kv_load(sl, i != 0, 2 + odd);
                    } else if (lane == 0) mbar_arrive_peer(prdy + bo);
                    __syncwarp();
                }
                n = 32; s = 2; ph = 1;
            }
        } else if (warp == 10) {
            if (lane == 0) {
#pragma unroll
                for (int i = B_EMPTY; i < NBARS; i++) mbar_init(bars + i * 8, i < B_XA ? 4 : 1);
#pragma unroll
                for (int i = B_XA; i <= B_SR; i++) mbar_arrive_tx(bars + i * 8, i < B_XB ? 512 : ((i >= B_INB && i < B_SR) ? 4096 : 8192));
                asm volatile("fence.mbarrier_init.release.cluster;" ::: "memory");
                fence_async_smem();
            }
            __syncwarp();
            cluster_arrive();
            cluster_wait();
        } else {
            const uint32_t kb = (lane < 2 || lane > 5) ? 4096 : (lane == 2 ? 3072 : (lane == 4 ? 2048 : 1024));
            const char* pf = m.w[lane & 7] + blockIdx.x * kb;
            cluster_wait();
            if (lane < PF0) prefetch_l2(pf, kb);
            mbar_wait(bars + B_FULL * 8, 0);
            if (lane >= PF0 && lane < 3) prefetch_l2(pf, kb);
            if (lane >= 1 && lane < 9) asm volatile("prefetch.tensormap [%0];" ::"l"(&m.tm[lane]) : "memory");
            mbar_wait(bars + (B_FULL + 1) * 8, 1);
            if (lane > 2 && lane < 8) prefetch_l2(pf, kb);
            if (lane == 8 && blockIdx.x < 15) prefetch_l2(p.dw + blockIdx.x * 256, 512);
            const uint32_t epoch = ld_epoch();
            bar_sync(4, 288);
            if (lane < 16) flag_set(&g_flag_kv[((b * 4 + 2 * r + (lane >> 3)) * 32 + pt) * KFS + (lane & 7)], epoch);
            __syncwarp();
            bar_arrive(14, 96);
            TSW(8);
        }
        TSDUMP();
        return;
    }

    const int w = warp >> 2, wq = warp & 3;
    const int tile = 2 * r + w;
    const int wt = tid & 127;
    const int c4 = lane & 3;
    const int trow = pt * 32 + 8 * wq;
    uint32_t xr[8];
    uint32_t a[32];
    const char* xrow = reinterpret_cast<const char*>(p.x) + (b * T_ + trow + (lane >> 2)) * 512;
    zero(a);
    if (trow < T_) {
        const char* src = xrow + c4 * 16 + p.zero;
#pragma unroll
        for (int i = 0; i < 8; i++)
            asm volatile("ld.global.nc.v4.b32 {%0,%1,%2,%3}, [%4];" : "=r"(a[4 * i]), "=r"(a[4 * i + 1]), "=r"(a[4 * i + 2]), "=r"(a[4 * i + 3]) : "l"(src + 64 * i));
    }
    cluster_arrive();
    asm volatile("setmaxnreg.inc.sync.aligned.u32 208;");
    const uint32_t rbase = sb + OFF_RING + w * NSLOT * SLOT, fbar = bars + (B_FULL + w * NSLOT) * 8;
    const uint32_t rdesc = desc_lo(rbase);
    auto acq = [&](int n) { mbar_wait(fbar + (n % NSLOT) * 8, (n / NSLOT) & 1); };
    auto rel = [&](int n) { if (lane == 0) mbar_arrive(fbar + (B_EMPTY - B_FULL + n % NSLOT) * 8); };
    const uint32_t foff = (lane & 7) * 128 + (((lane >> 3) ^ (lane & 7)) << 4);
    float v[16];
    const uint32_t xown = __shfl_sync(~0u, P + wt * 16 + tile * 4096, lane), xrem = __shfl_sync(~0u, P + wt * 16 + (r ^ 1) * 8192, lane);
    const uint32_t sbuf = __shfl_sync(~0u, sb + OFF_MISC + 1024 + (8 * wq + (lane >> 2)) * 32, lane);
    const uint32_t sown = __shfl_sync(~0u, sbuf + tile * 8, lane);
    const uint32_t peer = __shfl_sync(~0u, mapa(sb, r ^ 1) - sb, lane);
    const uint32_t hbuf = __shfl_sync(~0u, H + w * 4096 + wt * 16, lane);
    const uint32_t meta = __shfl_sync(~0u, 0xEEEE4444u + p.zero, lane);
    cluster_wait();
    TS(56);
    float mean, msq;
    const int mir = wq < 2 ? 7 : 0;
    uint32_t dwr[15] = {};

#pragma unroll
    for (int ph = 0; ph < 5; ph++) {
        uint4 o0, o1;
        if (ph == 0) {
            const uint32_t one = 0x3F803F80u + ((xown | xrem | sbuf | sown | hbuf | foff | rdesc | fbar) & p.zero);
            mean = ((row_sum<8>(a, one) + row_sum<8>(a + 8, one)) + (row_sum<8>(a + 16, one) + row_sum<8>(a + 24, one))) * (1.f / 256.f);
            TS(57);
        } else {
            const uint32_t xa = bars + (B_XA + ph) * 8;
#pragma unroll
            for (int j = 0; j < 8; j++) xr[j] = pack2(v[2 * j], v[2 * j + 1]);
            const float s = row_sum<8>(xr), q = row_sumsq<8>(xr, lane);
            if (ph < 4) {
                sts128(xown, xr[0], xr[1], xr[2], xr[3]);
                sts128(xown + 2048, xr[4], xr[5], xr[6], xr[7]);
            }
            put_sums(sown, sown + peer, s, q, xa + peer, c4 == (lane >> 3));
            bar_sync(10, 256);
            if (ph < 4) {
                o0 = lds128(xown ^ 4096); o1 = lds128((xown ^ 4096) + 2048);
                st_async4(xown + peer, xr[0], xr[1], xr[2], xr[3], xa + (B_XB - B_XA) * 8 + peer);
                st_async4(xown + peer + 2048, xr[4], xr[5], xr[6], xr[7], xa + (B_XB - B_XA) * 8 + peer);
            }
            TS(57 + ph);
            if (ph == 3) acq(0);
            if (ph == 1) acq(16);
            mbar_wait(xa, 0);
            const float4 u0 = lds128f(sbuf), u1 = lds128f(sbuf + 16);
            mean = ((u0.x + u0.z) + (u1.x + u1.z)) * (1.f / 256.f);
            msq = ((u0.y + u0.w) + (u1.y + u1.w)) * (1.f / 256.f);
        }
        if (ph == 4) break;
        const uint32_t mean2 = pack2(mean, mean);
        auto centre = [&](int i, const uint4& u) {
            a[i] = hsub2(u.x, mean2); a[i + 1] = hsub2(u.y, mean2); a[i + 2] = hsub2(u.z, mean2); a[i + 3] = hsub2(u.w, mean2);
        };
        if (ph == 0) {
#pragma unroll
            for (int j = 0; j < 32; j++) a[j] = hsub2(a[j], mean2);
            zero(xr);
            if (trow < T_) {
                const char* src = xrow + tile * 128 + c4 * 4 + (mean2 & p.zero);
#pragma unroll
                for (int j = 0; j < 8; j++) asm volatile("ld.global.nc.b32 %0, [%1];" : "=r"(xr[j]) : "l"(src + 16 * j));
            }
            mean -= blo(mean2);
            msq = __shfl_sync(~0u, row_sumsq<16>(a, lane) + row_sumsq<16>(a + 16, lane), (lane & 28) + (lane >> 3)) * (1.f / 256.f);
            acq(0);
        } else {
#pragma unroll
            for (int j = 0; j < 8; j++) a[j] = hsub2(xr[j], mean2);
            centre(8, o0); centre(12, o1);
        }
        const float rstd = rsq(fmaxf(fmaf(-mean, mean, msq), 0.f) + 1e-5f);
        auto gather_peer = [&]() {
            mbar_wait(bars + (B_XB + ph) * 8, 0);
#pragma unroll
            for (int i = 0; i < 4; i++) centre(16 + 4 * i, lds128(xrem + i * 2048));
        };
        auto sp = [&](float (&d)[32], int n, const uint32_t* af, int flip, int acc) {
            const uint32_t lo = rdesc + p.zero * (ph * 64 + n + 1) + (n % NSLOT) * (SLOT >> 4);
            const uint64_t b0 = mkdesc(lo + flip * 512), b1 = mkdesc(lo + (flip ^ 1) * 512);
            wg_fence();
            mma_sp(d, af, b0, meta, acc);
            mma_sp(d, af + 4, b0 + 256, meta, 1);
            mma_sp(d, af + 8, b1, meta, 1);
            mma_sp(d, af + 12, b1 + 256, meta, 1);
            wg_commit();
        };
        float d0[32], d1[32];

        if (ph == 0 || ph == 3) {
            uint32_t h[32], ho[32];
            const float rs = 0.5f * rstd;
            const uint32_t inb = bars + (B_INB + (ph & 2) + w) * 8;
            bool ready = true;
            const int eager = ph ? (TWO ? EAGER + 5 : EAGER) : EAGER - 1;
            auto step = [&](float (&d)[32], int n, const uint32_t* af, int flip, int acc, auto work) {
                if (!ready) acq(n);
                if (((TURN >> n) & 1) && w == 1) bar_sync(7, 256);
                sp(d, n, af, flip, acc);
                if (n > 0 && ((TURN >> (n - 1)) & 1) && w == 0) bar_arrive(7, 256);
                if (n < 15) ready = mbar_test(fbar + ((n + 1) % NSLOT) * 8, ((n + 1) / NSLOT) & 1);
                wg_wait<1>();
                if (n > 0 && !((eager >> (n - 1)) & 1)) rel(n - 1);
                const uint32_t tie = work() & p.zero;
                if ((eager >> n) & 1) {
                    if (p.zero < n + ph + 1) wg_wait<0>();
                    if (lane == 0) mbar_arrive(fbar + (B_EMPTY - B_FULL + n % NSLOT) * 8 + tie);
                }
            };
            auto none = []() { return 0u; };
            const int fl = ph ? w : 0;
            auto fetch = [&](int i) {
                bar_sync(10, 256);
                const uint4 u0 = lds128((hbuf ^ 4096) + (i & 1) * 8192), u1 = lds128((hbuf ^ 4096) + (i & 1) * 8192 + 2048);
                ho[8 * i] = u0.x; ho[8 * i + 1] = u0.y; ho[8 * i + 2] = u0.z; ho[8 * i + 3] = u0.w;
                ho[8 * i + 4] = u1.x; ho[8 * i + 5] = u1.y; ho[8 * i + 6] = u1.z; ho[8 * i + 7] = u1.w;
                return u0.x | u1.x;
            };
            auto act = [&](float (&d)[32], int i) {
                if (i > 0) fetch(i - 1);
                pin(d);
#pragma unroll
                for (int j = 0; j < 8; j++) {
                    const float u0 = (d[4 * j] + d[4 * j + 2]) * rs, u1 = (d[4 * j + 1] + d[4 * j + 3]) * rs;
                    h[8 * i + j] = pack2(fmaf(u0, tanh_fast(u0), u0), fmaf(u1, tanh_fast(u1), u1));
                }
                sts128(hbuf + (i & 1) * 8192, h[8 * i], h[8 * i + 1], h[8 * i + 2], h[8 * i + 3]);
                sts128(hbuf + (i & 1) * 8192 + 2048, h[8 * i + 4], h[8 * i + 5], h[8 * i + 6], h[8 * i + 7]);
                return 0u;
            };
            TS(1 + (ph & 2) * 10);
            if (TWO && ph) {
                step(d0, 0, a, fl, 0, none);
                step(d1, 1, a, fl, 0, [&]() { gather_peer(); return 0u; });
                TS(32);
                step(d0, 2, a + 16, 0, 1, none);
                step(d1, 3, a + 16, 0, 1, [&]() { return act(d0, 0); });
            } else {
                step(d0, 0, a, fl, 0, [&]() { if (ph) gather_peer(); return 0u; });
                TS(32);
                step(d0, 1, a + 16, 0, 1, none);
                step(d1, 2, a, fl, 0, [&]() { return act(d0, 0); });
                step(d1, 3, a + 16, 0, 1, none);
            }
            step(d0, 4, a, fl, 0, [&]() { return act(d1, 1); });
            TS(33);
            step(d0, 5, a + 16, 0, 1, none);
            step(d1, 6, a, fl, 0, [&]() { return act(d0, 2); });
            step(d1, 7, a + 16, 0, 1, none);
            step(d0, 8, h, 0, 0, [&]() { act(d1, 3); return fetch(3); });
            TS(2 + (ph & 2) * 10);
            step(d0, 9, ho, 0, 1, none);
            step(d0, 10, h + 16, 0, 1, none);
            step(d0, 11, ho + 16, 0, 1, none);
            uint32_t pk[8];
            auto pack_out = [&]() {
                pin(d0);
#pragma unroll
                for (int j = 0; j < 8; j++) pk[j] = pack2(d0[4 * j] + d0[4 * j + 2], d0[4 * j + 1] + d0[4 * j + 3]);
            };
            auto send = [&](int i) { st_async4(hbuf + 16384 + i * 2048 + peer, pk[4 * i], pk[4 * i + 1], pk[4 * i + 2], pk[4 * i + 3], inb + peer); };
            step(d1, 12, h, 0, 0, [&]() { pack_out(); if (SND != 1) send(0); if (SND == 0) send(1); return 0u; });
            TS(34);
            step(d1, 13, ho, 0, 1, [&]() { if (SND == 1) send(0); if (SND) send(1); return 0u; });
            step(d1, 14, h + 16, 0, 1, none);
            step(d1, 15, ho + 16, 0, 1, none);
            mbar_wait(inb, 0);
#pragma unroll
            for (int i = 0; i < 2; i++) {
                const uint4 u = lds128(hbuf + 16384 + i * 2048);
                const uint32_t p0[4] = {u.x, u.y, u.z, u.w};
#pragma unroll
                for (int j = 0; j < 4; j++) {
                    v[8 * i + 2 * j] = fmaf(0.5f, blo(p0[j]), blo(xr[4 * i + j]));
                    v[8 * i + 2 * j + 1] = fmaf(0.5f, bhi(p0[j]), bhi(xr[4 * i + j]));
                }
            }
            wg_wait<0>();
            pin(d1);
            rel(15);
            TS(3 + (ph & 2) * 10);
#pragma unroll
            for (int j = 0; j < 8; j++) {
                v[2 * j] = fmaf(0.5f, d1[4 * j] + d1[4 * j + 2], v[2 * j]);
                v[2 * j + 1] = fmaf(0.5f, d1[4 * j + 1] + d1[4 * j + 3], v[2 * j + 1]);
            }
#pragma unroll
            for (int i = 0; i < 15; i++) dwr[i] = 0;
            continue;
        }

        auto residual = [&](int n) {
            wg_wait<1>();
            rel(n);
            wg_wait<0>();
            pin(d0);
            rel(n + 1);
#pragma unroll
            for (int j = 0; j < 8; j++) {
                v[2 * j] = d0[4 * j] + d0[4 * j + 2] + blo(xr[j]);
                v[2 * j + 1] = d0[4 * j + 1] + d0[4 * j + 3] + bhi(xr[j]);
            }
        };

        if (ph == 2) {
            TS(39);
            sp(d0, 34, a, w, 0);
            acq(35);
            sp(d1, 35, a, w, 0);
            acq(36); acq(37);
            gather_peer();
            sp(d0, 36, a + 16, 0, 1);
            sp(d1, 37, a + 16, 0, 1);
            wg_wait<2>();
            rel(34);
            if (!(LATE & 1)) rel(35);
            acq(38);
            const float rs = trow < T_ ? 0.5f * rstd : 0.f;
            wg_wait<0>();
            pin(d0); pin(d1);
            if (!(LATE & 2)) { rel(36); rel(37); }
            TS(18);
            uint32_t pk[8];
#pragma unroll
            for (int j = 0; j < 8; j++) {
                const float u0 = (d0[4 * j] + d0[4 * j + 2]) * rs, u1 = (d0[4 * j + 1] + d0[4 * j + 3]) * rs;
                const float t0 = tanh_fast((d1[4 * j] + d1[4 * j + 2]) * rs), t1 = tanh_fast((d1[4 * j + 1] + d1[4 * j + 3]) * rs);
                pk[j] = pack2(fmaf(u0, t0, u0), fmaf(u1, t1, u1));
            }
            if (wq == 0 || wq == 3) {
                uint4* hp = &g_halo[((pair * 4 + tile) * 2 + (wq & 1)) * 64 + lane];
                st_data(hp, pk[0], pk[1], pk[2], pk[3]);
                st_data(hp + 32, pk[4], pk[5], pk[6], pk[7]);
            }
            const uint32_t gs = H + 16384 + w * GCH + wq * 1024;
            stsm4(gs + 1024 + foff, pk[0], pk[1], pk[2], pk[3]);
            stsm4(gs + 1024 + (foff ^ 64), pk[4], pk[5], pk[6], pk[7]);
            bar_sync(8 + w, 192);
            TS(26);
            uint32_t ca[8], cb[8];
            const int e = (wq & 1) * 4;
            const uint32_t lo = ((mir ^ e) * 144) ^ (lane * 4);
            const int dir = mir ? -1024 : 1024;
            const uint32_t gb = H + 16384 + w * GCH + (mir ? 3072 : 2048) + lo, sown_ = H + tile * HCH, so = sown_ + (mir ? 1024 : 2048) + lo;
            auto finish = [&](int i) {
                const uint32_t c = hadd2(ca[i], cb[i]);
                const float h0 = blo(c), h1 = bhi(c);
                sts32((so + (i >> 2) * dir) ^ ((i & 3) * 144), pack2(fmaf(h0, tanh_fast(h0), h0), fmaf(h1, tanh_fast(h1), h1)));
            };
#pragma unroll
            for (int k = 0; k < 26; k++) {
                if (k == 19) {
#pragma unroll
                    for (int i = 0; i < 4; i++) finish(i);
                    fence_async_smem();
                    bar_sync(2 + w, 128);
                    if (wq == 0) peer_copy(mapa(sown_ + 1024, r ^ 1), sown_ + 1024, 2048, mapa(bars + B_SR * 8, r ^ 1));
                    mbar_wait(bars + (B_HALO + 2 * w + (wq >> 1)) * 8, 0);
                    if (LATE & 1) rel(35);
                    if (LATE & 2) { rel(36); rel(37); }
                    TS(27);
                }
                const uint32_t g = lds32((gb + (((k + 1) & 4) ? ((k + 1) >> 3) + (wq & 1) : ((k + 1) >> 3)) * dir) ^ (((k + 1) & 7) * 144));
#pragma unroll
                for (int i = 0; i < 8; i++) {
                    const int tap = k - (i & 3) - 2 * (i & 4);
                    if (tap == 0) ca[i] = hmul2(g, dwr[0]);
                    else if (tap > 0 && tap < 8) ca[i] = hfma2(g, dwr[tap], ca[i]);
                    else if (tap == 8) cb[i] = hmul2(g, dwr[8]);
                    else if (tap > 8 && tap < 15) cb[i] = hfma2(g, dwr[tap], cb[i]);
                }
            }
#pragma unroll
            for (int i = 4; i < 8; i++) finish(i);
            fence_async_smem();
            bar_sync(12 + (warp >> 1), 64);
            if (wq == 0 || wq == 3) peer_copy(mapa(sown_ + wq * 1024, r ^ 1), sown_ + wq * 1024, 1024, mapa(bars + B_SR * 8, r ^ 1));
            bar_sync(10, 256);
            TS(19);
            auto frags = [&](int i, int half) {
                const uint32_t src = H + 2 * half * HCH + wq * 1024;
#pragma unroll
                for (int k = 0; k < 4; k++) ldsm4(src + (k >> 1) * HCH + (foff ^ ((k & 1) * 64)), a[i + 4 * k], a[i + 4 * k + 1], a[i + 4 * k + 2], a[i + 4 * k + 3]);
            };
            frags(0, r);
            sp(d0, 38, a, 0, 0);
            acq(39);
            mbar_wait(bars + B_SR * 8, 0);
            frags(16, r ^ 1);
            sp(d0, 39, a + 16, 0, 1);
            residual(38);
            TS(20);
            continue;
        }

        {
            TS(11);
            unsigned char* g = g_kvq + (size_t)((b * 4 + tile) * 1024 + trow) * 128;
            const uint32_t uo = (lane >> 2) * 128 + ((c4 ^ (lane >> 2)) << 4);
            auto put = [&](float (&d)[32], int i) {
                pin(d);
                uint32_t pk[8];
#pragma unroll
                for (int j = 0; j < 8; j++) pk[j] = pack2((d[4 * j] + d[4 * j + 2]) * rstd, (d[4 * j + 1] + d[4 * j + 3]) * rstd);
                if (i < 2) {
                    stg128(g + i * 1048576 + uo, make_uint4(pk[0], pk[1], pk[2], pk[3]));
                    stg128(g + i * 1048576 + (uo ^ 64), make_uint4(pk[4], pk[5], pk[6], pk[7]));
                } else {
                    const uint32_t stg = H + warp * 1024;
                    sts128(stg + uo, pk[0], pk[1], pk[2], pk[3]);
                    sts128(stg + (uo ^ 64), pk[4], pk[5], pk[6], pk[7]);
                    __syncwarp();
                    ldsm4(stg + foff, pk[0], pk[1], pk[2], pk[3]);
                    ldsm4(stg + (foff ^ 64), pk[4], pk[5], pk[6], pk[7]);
                    st_data(g + 2097152 + lane * 16, ~pk[0], ~pk[1], ~pk[2], ~pk[3]);
                    st_data(g + 2097152 + 512 + lane * 16, ~pk[4], ~pk[5], ~pk[6], ~pk[7]);
                }
            };
            sp(d0, 16, a, w, 0);
            acq(17);
            sp(d1, 17, a, w, 0);
            gather_peer();
            acq(18);
            sp(d0, 18, a + 16, 0, 1);
            wg_wait<1>();
            rel(16); rel(17);
            acq(19);
            sp(d1, 19, a + 16, 0, 1);
            wg_wait<1>();
            rel(18);
            put(d0, 0);
            wg_wait<0>();
            rel(19);
            TS(37);
            put(d1, 1);
            bar_arrive(4, 288);
            TS(38);
            acq(20);
            sp(d0, 20, a, w, 0);
            acq(21);
            sp(d0, 21, a + 16, 0, 1);
            acq(22); acq(23);
            rel(22); rel(23);
            wg_wait<0>();
            rel(20); rel(21);
            put(d0, 2);
            TS(12);
        }

        {
            constexpr float CS = 0.125f * 1.4426950408889634f;
            float sa[32], sb2[32], o[36];
            uint32_t pa[16], pb[16], q[16];
            float n0 = INFINITY, n1 = INFINITY;
            zero(o); zero(pa); zero(pb); zero(sb2);
            const uint32_t ones = sb + OFF_MISC + 2048;
            { const uint32_t c = w ? 0u : 0x3F803F80u; sts128(ones + tid * 16, c, c, c, c); }
            fence_async_smem();
            bar_sync(10, 256);
            const uint32_t vdesc = rdesc + ((((ones - rbase) >> 4) - 1) << 16);
            auto qk_issue = [&](float (&s)[32], uint32_t lo) {
                const uint64_t kd = mkdesc(lo);
                wg_fence();
#pragma unroll
                for (int k = 0; k < 4; k++) mma_qk(s, q[4 * k], q[4 * k + 1], q[4 * k + 2], q[4 * k + 3], kd + 2 * k, k != 0);
                wg_commit();
            };
            auto both_issue = [&](float (&s)[32], uint32_t klo, uint32_t (&pp)[16], uint32_t vlo) {
                const uint64_t kd = mkdesc(klo), vd = mkdesc(vlo);
                wg_fence();
#pragma unroll
                for (int k = 0; k < 4; k++) {
                    mma_pv(o, pp[4 * k], pp[4 * k + 1], pp[4 * k + 2], pp[4 * k + 3], vd - k * (128 * 65535));
                    mma_qk(s, q[4 * k], q[4 * k + 1], q[4 * k + 2], q[4 * k + 3], kd + 2 * k, k != 0);
                }
                wg_commit();
            };
            auto new_max = [&](float (&s)[32], int nj, float& x0, float& x1) {
                x0 = s[0]; x1 = s[2];
#pragma unroll
                for (int j = 0; j < nj; j++) {
                    x0 = fmaxf(x0, fmaxf(s[4 * j], s[4 * j + 1]));
                    x1 = fmaxf(x1, fmaxf(s[4 * j + 2], s[4 * j + 3]));
                }
                x0 = fmaxf(x0, __shfl_xor_sync(~0u, x0, 1)); x1 = fmaxf(x1, __shfl_xor_sync(~0u, x1, 1));
                x0 = fmaxf(x0, __shfl_xor_sync(~0u, x0, 2)); x1 = fmaxf(x1, __shfl_xor_sync(~0u, x1, 2));
                x0 = fminf(n0, fmaf(x0, -CS, -20.f)); x1 = fminf(n1, fmaf(x1, -CS, -20.f));
            };
            auto probs = [&](float (&s)[32], uint32_t (&pp)[16], bool ready, bool tail, auto wait) {
                uint32_t any = 0;
#pragma unroll
                for (int i = 0; i < 16; i++) {
                    pp[i] = pack2(ex2(fmaf(s[2 * i], CS, (i & 1) ? n1 : n0)), ex2(fmaf(s[2 * i + 1], CS, (i & 1) ? n1 : n0)));
                    any |= pp[i];
                }
                wg_wait<0>();
                pin(sa); pin(sb2); pin(o); pin(pa); pin(pb);
                if (__builtin_expect(__any_sync(~0u, (any & 0x40004000u) || !ready), 0)) {
                    wait();
                    if (__any_sync(~0u, any & 0x40004000u)) {
                        if (tail) {
#pragma unroll
                            for (int i = 20; i < 32; i++) s[i] = -INFINITY;
                        }
                        float x0, x1;
                        new_max(s, 8, x0, x1);
                        const float sc0 = ex2(x0 - n0), sc1 = ex2(x1 - n1);
                        n0 = x0; n1 = x1;
#pragma unroll
                        for (int j = 0; j < 9; j++) { o[4 * j] *= sc0; o[4 * j + 1] *= sc0; o[4 * j + 2] *= sc1; o[4 * j + 3] *= sc1; }
#pragma unroll
                        for (int i = 0; i < 16; i++)
                            pp[i] = pack2(ex2(fmaf(s[2 * i], CS, (i & 1) ? n1 : n0)), ex2(fmaf(s[2 * i + 1], CS, (i & 1) ? n1 : n0)));
                    }
                }
            };
            {
                uint4 u[4];
                const unsigned char* src = g_kvq + 2097152 + (size_t)(abh * 1024 + qt * 64 + wq * 16) * 128 + lane * 16;
                spin(QGATE);
                ld_data<512, true>(u, src);
#pragma unroll
                for (int k = 0; k < 2; k++) {
                    q[8 * k] = ~u[k].x; q[8 * k + 1] = ~u[k + 2].x; q[8 * k + 2] = ~u[k].y; q[8 * k + 3] = ~u[k + 2].y;
                    q[8 * k + 4] = ~u[k].z; q[8 * k + 5] = ~u[k + 2].z; q[8 * k + 6] = ~u[k].w; q[8 * k + 7] = ~u[k + 2].w;
                }
                pin(q);
            }
            TS(40);
            acq(24);
            TS(13);
            qk_issue(sa, rdesc + (24 % NSLOT) * (SLOT >> 4));
            wg_wait<0>();
            pin(sa);
            {
                float x0, x1;
                new_max(sa, NJ0, x0, x1);
                n0 = x0; n1 = x1;
            }
            bar_arrive(6, 384);
            uint32_t vd = vdesc - (SLOT >> 4) * 65535u, kd = rdesc, vb = fbar + 8, kb = fbar;
            uint32_t vlast = vdesc - 4 * (SLOT >> 4) * 65535u, klast = rdesc + 4 * (SLOT >> 4) + 512;
            uint32_t kprev = fbar + 32, vprev = bars + (B_SINK - (B_EMPTY - B_FULL)) * 8;
#pragma unroll 1
            for (int it = 0; it < 4; it++) {
                both_issue(sb2, klast, pb, vlast);
                probs(sa, pa, mbar_test(vb, it < 2) & mbar_test(kb, it < 3), false, [&]() { mbar_wait(vb, it < 2); mbar_wait(kb, it < 3); });
                TS(41 + it * 4);
                if (lane == 0) mbar_arrive(kprev + (B_EMPTY - B_FULL) * 8);
                if (lane == 0) mbar_arrive(vprev + (B_EMPTY - B_FULL) * 8);
                both_issue(sa, kd, pa, vd);
                const int dv = it == 0 ? 2 : (it == 1 ? -3 : 1);
                kprev = kb; vprev = vb; vlast = vd - 512 * 65535u; klast = kd + 512;
                vd -= dv * (SLOT >> 4) * 65535u; vb += dv * 8;
                kd += (it == 2 ? -3 : 2) * (SLOT >> 4); kb = it == 2 ? vb : kb + 16;
                probs(sb2, pb, true, it == 3 && w == 1, []() {});
                TS(43 + it * 4);
            }
            wg_fence();
#pragma unroll
            for (int k = 0; k < 4; k++)
                mma_pv(o, pb[4 * k], pb[4 * k + 1], pb[4 * k + 2], pb[4 * k + 3], mkdesc(vlast - k * (128 * 65535) + (k > 1 ? w * ((k - 1) << 22) : 0)));
            wg_commit();
            const int row = wq * 16 + (lane >> 2);
            const uint32_t ml = sb + OFF_MISC;
            mbar_wait(bars + B_RST * 8, 0);
            wg_wait<0>();
            pin(o); pin(pb); pin(sa); pin(sb2);
            if (!(LATE & 4)) rel(31);
            const float l0 = o[32], l1 = o[34];
            if (c4 == 0) { sts64f(ml + w * 512 + row * 8, n0, l0); sts64f(ml + w * 512 + row * 8 + 64, n1, l1); }
            TS(14);
            float mine[16];
#pragma unroll
            for (int j = 0; j < 4; j++) {
                if (w == 0) sts128f(H + j * 2048 + wt * 16, o[16 + 4 * j], o[17 + 4 * j], o[18 + 4 * j], o[19 + 4 * j]);
                else sts128f(H + 8192 + j * 2048 + wt * 16, o[4 * j], o[4 * j + 1], o[4 * j + 2], o[4 * j + 3]);
            }
#pragma unroll
            for (int i = 0; i < 16; i++) mine[i] = w == 0 ? o[i] : o[16 + i];
            bar_sync(10, 256);
            const float2 u0 = lds64f(ml + (w ^ 1) * 512 + row * 8), u1 = lds64f(ml + (w ^ 1) * 512 + row * 8 + 64);
            const float x0 = fminf(n0, u0.x), x1 = fminf(n1, u1.x);
            float a0 = ex2(x0 - n0), b0 = ex2(x0 - u0.x), a1 = ex2(x1 - n1), b1 = ex2(x1 - u1.x);
            const float i0 = __fdividef(1.f, fmaf(a0, l0, b0 * u0.y)), i1 = __fdividef(1.f, fmaf(a1, l1, b1 * u1.y));
            a0 *= i0; b0 *= i0; a1 *= i1; b1 *= i1;
            uint32_t pk[8];
#pragma unroll
            for (int j = 0; j < 4; j++) {
                const float4 v = lds128f(H + (w ^ 1) * 8192 + j * 2048 + wt * 16);
                pk[2 * j] = pack2(fmaf(a0, mine[4 * j], b0 * v.x), fmaf(a0, mine[4 * j + 1], b0 * v.y));
                pk[2 * j + 1] = pack2(fmaf(a1, mine[4 * j + 2], b1 * v.z), fmaf(a1, mine[4 * j + 3], b1 * v.w));
            }
            unsigned char* dst = g_o + (size_t)(b * 128 + qt * 8 + 2 * wq) * 4096 + ah * 1024 + w * 512 + lane * 16;
            st_data(dst, pk[0], pk[2], pk[4], pk[6]);
            st_data(dst + 4096, pk[1], pk[3], pk[5], pk[7]);
            if (tid == 0) asm volatile("red.relaxed.gpu.global.add.u32 [%0], 1;" ::"l"(&g_epoch[blockIdx.x * FS]) : "memory");
            TS(15);
        }

        {
            const uint32_t* dp = reinterpret_cast<const uint32_t*>(p.dw + (mir ? 14 * 256 : 0) + tile * 64) + lane;
#pragma unroll
            for (int i = 0; i < 15; i++) asm volatile("ld.global.nc.b32 %0, [%1];" : "=r"(dwr[i]) : "l"(dp + i * (mir ? -128 : 128)));
            acq(32); acq(33); acq(34);
            uint4 u[8];
            ld_data<512>(u, g_o + (size_t)(b * 128 + pt * 4 + wq) * 4096 + lane * 16);
#pragma unroll
            for (int i = 0; i < 8; i++) { a[4 * i] = u[i].x; a[4 * i + 1] = u[i].y; a[4 * i + 2] = u[i].z; a[4 * i + 3] = u[i].w; }
            if (LATE & 4) rel(31);
            TS(16);
            sp(d0, 32, a, 0, 0);
            sp(d0, 33, a + 16, 0, 1);
#pragma unroll
            for (int i = 0; i < 15; i++) dwr[i] = hmul2(dwr[i], 0x3F003F00u);
            residual(32);
            TS(17);
        }
    }

    cluster_arrive();
    TS(24);
    {
        const float rstd = rsq(fmaxf(fmaf(-mean, mean, msq), 0.f) + 1e-5f), nb = -mean * rstd;
#pragma unroll
        for (int j = 0; j < 8; j++) xr[j] = pack2(fmaf(v[2 * j], rstd, nb), fmaf(v[2 * j + 1], rstd, nb));
        const uint32_t stg = P + 16384 + warp * 1024;
        stsm4(stg + foff, xr[0], xr[1], xr[2], xr[3]);
        stsm4(stg + (foff ^ 64), xr[4], xr[5], xr[6], xr[7]);
        __syncwarp();
        const uint32_t src = stg + (lane >> 3) * 128 + (((lane & 7) ^ (lane >> 3)) << 4);
        const uint4 u0 = lds128(src), u1 = lds128((src + 512) ^ 64);
        __nv_bfloat16* dst = p.out + (size_t)(b * T_ + trow + (lane >> 3)) * 256 + tile * 64 + (lane & 7) * 8;
        if (trow < T_) { stg128(dst, u0); stg128(dst + 4 * 256, u1); }
    }
    TS(25);
    TG(31);
    TSDUMP();
    cluster_wait();
}

typedef CUresult (*EncodeFn)(CUtensorMap*, CUtensorMapDataType, cuuint32_t, void*, const cuuint64_t*, const cuuint64_t*,
                             const cuuint32_t*, const cuuint32_t*, CUtensorMapInterleave, CUtensorMapSwizzle,
                             CUtensorMapL2promotion, CUtensorMapFloatOOBfill);

}

extern "C" void kernel_launch(void* const* d_in, const int* in_sizes, int n_in, void* d_out, int out_size) {
    static EncodeFn encode = nullptr;
    if (!encode) {
        void* fn = nullptr;
        cudaDriverEntryPointQueryResult qr;
        cudaGetDriverEntryPoint("cuTensorMapEncodeTiled", &fn, cudaEnableDefault, &qr);
        encode = (EncodeFn)fn;
        cudaFuncSetAttribute(conformer_kernel, cudaFuncAttributeMaxDynamicSharedMemorySize, SMEM_LAUNCH);
    }
    Scalars p;
    Maps m;
    const cuuint32_t ones[5] = {1, 1, 1, 1, 1};
    const int idx[8] = {1, 2, 3, 4, 5, 7, 8, 9};
    const int rows[8] = {256, 1024, 256, 256, 256, 256, 256, 1024};
    const int cols[8] = {1024, 256, 768, 256, 512, 256, 1024, 256};
    for (int i = 0; i < 8; i++) {
        const cuuint64_t pitch = (cuuint64_t)cols[i] * 2;
        const bool f = i != 0 && i != 3;
        const cuuint64_t dims[5] = {(cuuint64_t)cols[i], f ? 2u : 4u, f ? 2u : 4u, f ? 4u : 2u, (cuuint64_t)rows[i] / (f ? 16 : 32)};
        const cuuint64_t strides[4] = {pitch, pitch * 8, pitch * (f ? 2 : 4), pitch * (f ? 16 : 32)};
        const cuuint32_t box[5] = {64, f ? 2u : 4u, f ? 2u : 4u, f ? 4u : 2u, f ? 8u : 4u};
        encode(&m.tm[i], CU_TENSOR_MAP_DATA_TYPE_BFLOAT16, 5, d_in[idx[i]], dims, strides, box, ones, CU_TENSOR_MAP_INTERLEAVE_NONE,
               CU_TENSOR_MAP_SWIZZLE_128B, CU_TENSOR_MAP_L2_PROMOTION_L2_128B, CU_TENSOR_MAP_FLOAT_OOB_FILL_NONE);
        m.w[i] = (const char*)d_in[idx[i]];
    }
    {
        void* kv = nullptr;
        cudaGetSymbolAddress(&kv, g_kvq);
        const cuuint64_t dims[2] = {64, 16384};
        const cuuint64_t strides[1] = {128};
        const cuuint32_t box[2] = {64, 128};
        encode(&m.tm[8], CU_TENSOR_MAP_DATA_TYPE_BFLOAT16, 2, kv, dims, strides, box, ones, CU_TENSOR_MAP_INTERLEAVE_NONE,
               CU_TENSOR_MAP_SWIZZLE_NONE, CU_TENSOR_MAP_L2_PROMOTION_L2_128B, CU_TENSOR_MAP_FLOAT_OOB_FILL_NONE);
    }
    p.x = (const __nv_bfloat16*)d_in[0];
    p.dw = (const __nv_bfloat16*)d_in[6];
    p.out = (__nv_bfloat16*)d_out;
    p.zero = 0;
    conformer_kernel<<<NCTA, NTHREADS, SMEM_LAUNCH>>>(p, m);
}
```

```cpp
#include <cuda_runtime.h>
#include <cuda_bf16.h>
#include <cuda.h>
#include <stdint.h>

namespace {

constexpr int T_ = 1000;
constexpr int NCTA = 128;
constexpr int NTHREADS = 512;
constexpr int NSLOT = 5;
constexpr int SLOT = 16384;
constexpr int NLOADS = 56;

constexpr uint32_t OFF_RING = 0;
constexpr uint32_t OFF_P = 163840;
constexpr uint32_t OFF_H = 188416;
constexpr uint32_t OFF_MISC = 221184;
constexpr uint32_t OFF_BARS = 229888;
constexpr uint32_t SMEM_BYTES = 230400;
constexpr uint32_t GCH = 6144;
constexpr uint32_t HCH = 4096;

constexpr int B_FULL = 0, B_EMPTY = 10, B_XA = 20  , B_XB = 25  , B_INB = 29  , B_SR = 33,
              B_RST = 34, B_RDY = 35  , B_SINK = 41, B_HALO = 42  , NBARS = 46;

#define KD2 300u
#define KD3 500u
#define QGATE 700u
#define BACKOFF 0u
#define KFS 8
#define KDELAY 250u
#define NJ0 2
#define HDELAY 200u
#define LATE 3
#define SND 0
#define PF0 0
#define TWO 1
#define WARMF 1
#define SPLIT 0
#define TURN 0x200
#define EAGER 0x0155
constexpr int FS = 8;

struct Scalars {
    const __nv_bfloat16* x;
    const __nv_bfloat16* dw;
    __nv_bfloat16* out;
    uint32_t zero;
};
struct Maps {
    CUtensorMap tm[9];
    const char* w[8];
};

__device__ __align__(1024) unsigned char g_kvq[3 * 8 * 1024 * 128];
__device__ __align__(1024) unsigned char g_o[2 * 128 * 4096];
__device__ uint4 g_halo[64 * 4 * 2 * 64];
__device__ __align__(128) uint32_t g_flag_kv[8 * 32 * KFS];
__device__ uint32_t g_reset[2 * 32];
__device__ uint32_t g_epoch[NCTA * FS];

#define TS(i) do { } while (0)
#define TSW(i) do { } while (0)
#define TG(i) do { } while (0)
#define TSINIT() do { } while (0)
#define TSDUMP() do { } while (0)
constexpr uint32_t SMEM_LAUNCH = SMEM_BYTES;

__device__ __forceinline__ uint32_t smem_u32(const void* p) { return (uint32_t)__cvta_generic_to_shared(p); }
__device__ __forceinline__ void mbar_init(uint32_t b, uint32_t c) { asm volatile("mbarrier.init.shared::cta.b64 [%0], %1;" ::"r"(b), "r"(c) : "memory"); }
__device__ __forceinline__ void mbar_arrive(uint32_t b) { asm volatile("mbarrier.arrive.shared::cta.b64 _, [%0];" ::"r"(b) : "memory"); }
__device__ __forceinline__ void mbar_arrive_tx(uint32_t b, uint32_t tx) { asm volatile("mbarrier.arrive.expect_tx.shared::cta.b64 _, [%0], %1;" ::"r"(b), "r"(tx) : "memory"); }
__device__ __forceinline__ void mbar_wait(uint32_t b, uint32_t ph) {
    asm volatile("{\n.reg .pred p, q;\n.reg .u32 c;\nmov.u32 c, 0;\n"
                 "MW_LOOP:\n.pragma \"nounroll\";\n"
                 "mbarrier.try_wait.parity.shared::cta.b64 p, [%0], %1;\n"
                 "add.u32 c, c, 1;\nsetp.lt.u32 q, c, 65536;\nnot.pred p, p;\nand.pred p, p, q;\n@p bra MW_LOOP;\n}"
                 ::"r"(b), "r"(ph) : "memory");
}
__device__ __forceinline__ bool mbar_test(uint32_t b, uint32_t ph) {
    uint32_t ok;
    asm volatile("{\n.reg .pred p;\nmbarrier.test_wait.parity.shared::cta.b64 p, [%1], %2;\nselp.u32 %0, 1, 0, p;\n}" : "=r"(ok) : "r"(b), "r"(ph) : "memory");
    return ok;
}
__device__ __forceinline__ uint32_t mapa(uint32_t a, uint32_t r) { uint32_t o; asm("mapa.shared::cluster.u32 %0, %1, %2;" : "=r"(o) : "r"(a), "r"(r)); return o; }
__device__ __forceinline__ void fence_async_smem() { asm volatile("fence.proxy.async.shared::cta;" ::: "memory"); }
__device__ __forceinline__ void fence_async_global() { asm volatile("fence.proxy.async.global;" ::: "memory"); }
__device__ __forceinline__ void bar_sync(int id, int n) { asm volatile("bar.sync %0, %1;" ::"r"(id), "r"(n) : "memory"); }
__device__ __forceinline__ void bar_arrive(int id, int n) { asm volatile("bar.arrive %0, %1;" ::"r"(id), "r"(n) : "memory"); }
__device__ __forceinline__ void cluster_arrive() { asm volatile("barrier.cluster.arrive.relaxed.aligned;" ::: "memory"); }
__device__ __forceinline__ void cluster_wait() { asm volatile("barrier.cluster.wait.aligned;" ::: "memory"); }

__device__ __forceinline__ void ring_load(uint32_t dst, const CUtensorMap* tm, int col, int row16, uint32_t bar) {
    asm volatile("{\n.reg .pred p;\nelect.sync _|p, 0xffffffff;\n"
                 "@p mbarrier.arrive.expect_tx.shared::cta.b64 _, [%2], 16384;\n"
                 "@p cp.async.bulk.tensor.5d.shared::cluster.global.mbarrier::complete_tx::bytes [%0], [%1, {%3, 0, 0, 0, %4}], [%2];\n}"
                 ::"r"(dst), "l"(tm), "r"(bar), "r"(col), "r"(row16) : "memory");
}
__device__ __forceinline__ void ring_load_both(uint32_t dst, const CUtensorMap* tm, int c1, uint32_t bar) {
    asm volatile("{\n.reg .pred p;\nelect.sync _|p, 0xffffffff;\n"
                 "@p cp.async.bulk.tensor.2d.shared::cluster.global.mbarrier::complete_tx::bytes.multicast::cluster [%0], [%1, {0, %3}], [%2], %4;\n}"
                 ::"r"(dst), "l"(tm), "r"(bar), "r"(c1), "h"((uint16_t)3) : "memory");
}
__device__ __forceinline__ void mbar_arrive_peer(uint32_t b) { asm volatile("mbarrier.arrive.relaxed.cluster.shared::cluster.b64 _, [%0];" ::"r"(b) : "memory"); }
__device__ __forceinline__ void prefetch_l2(const void* src, uint32_t bytes) {
    asm volatile("cp.async.bulk.prefetch.L2.global [%0], %1;" ::"l"(src), "r"(bytes) : "memory");
}
__device__ __forceinline__ void peer_copy(uint32_t dst, uint32_t src, uint32_t bytes, uint32_t rbar) {
    asm volatile("{\n.reg .pred p;\nelect.sync _|p, 0xffffffff;\n"
                 "@p cp.async.bulk.shared::cluster.shared::cta.mbarrier::complete_tx::bytes [%0], [%1], %2, [%3];\n}"
                 ::"r"(dst), "r"(src), "r"(bytes), "r"(rbar) : "memory");
}
__device__ __forceinline__ void st_async4(uint32_t dst, uint32_t a, uint32_t b, uint32_t c, uint32_t d, uint32_t bar) {
    asm volatile("st.async.shared::cluster.mbarrier::complete_tx::bytes.v4.b32 [%0], {%1,%2,%3,%4}, [%5];" ::"r"(dst), "r"(a), "r"(b), "r"(c), "r"(d), "r"(bar) : "memory");
}
__device__ __forceinline__ void put_sums(uint32_t dst, uint32_t rdst, float a, float b, uint32_t rbar, bool on) {
    asm volatile("{\n.reg .pred p;\nsetp.ne.u32 p, %5, 0;\n"
                 "@p st.async.shared::cluster.mbarrier::complete_tx::bytes.v2.f32 [%1], {%2,%3}, [%4];\n"
                 "@p st.shared.v2.f32 [%0], {%2,%3};\n}" ::"r"(dst), "r"(rdst), "f"(a), "f"(b), "r"(rbar), "r"((uint32_t)on) : "memory");
}
__device__ __forceinline__ void stsm4(uint32_t a, uint32_t r0, uint32_t r1, uint32_t r2, uint32_t r3) {
    asm volatile("stmatrix.sync.aligned.m8n8.x4.shared.b16 [%0], {%1,%2,%3,%4};" ::"r"(a), "r"(r0), "r"(r1), "r"(r2), "r"(r3) : "memory");
}
__device__ __forceinline__ void ldsm4(uint32_t a, uint32_t& r0, uint32_t& r1, uint32_t& r2, uint32_t& r3) {
    asm volatile("ldmatrix.sync.aligned.m8n8.x4.shared.b16 {%0,%1,%2,%3}, [%4];" : "=r"(r0), "=r"(r1), "=r"(r2), "=r"(r3) : "r"(a) : "memory");
}
__device__ __forceinline__ uint4 lds128(uint32_t a) { uint4 v; asm volatile("ld.shared.v4.b32 {%0,%1,%2,%3}, [%4];" : "=r"(v.x), "=r"(v.y), "=r"(v.z), "=r"(v.w) : "r"(a) : "memory"); return v; }
__device__ __forceinline__ float4 lds128f(uint32_t a) { float4 v; asm volatile("ld.shared.v4.f32 {%0,%1,%2,%3}, [%4];" : "=f"(v.x), "=f"(v.y), "=f"(v.z), "=f"(v.w) : "r"(a) : "memory"); return v; }
__device__ __forceinline__ float2 lds64f(uint32_t a) { float2 v; asm volatile("ld.shared.v2.f32 {%0,%1}, [%2];" : "=f"(v.x), "=f"(v.y) : "r"(a) : "memory"); return v; }
__device__ __forceinline__ uint32_t lds32(uint32_t a) { uint32_t v; asm volatile("ld.shared.b32 %0, [%1];" : "=r"(v) : "r"(a) : "memory"); return v; }
__device__ __forceinline__ void sts128(uint32_t a, uint32_t x, uint32_t y, uint32_t z, uint32_t w) { asm volatile("st.shared.v4.b32 [%0], {%1,%2,%3,%4};" ::"r"(a), "r"(x), "r"(y), "r"(z), "r"(w) : "memory"); }
__device__ __forceinline__ void sts128f(uint32_t a, float x, float y, float z, float w) { asm volatile("st.shared.v4.f32 [%0], {%1,%2,%3,%4};" ::"r"(a), "f"(x), "f"(y), "f"(z), "f"(w) : "memory"); }
__device__ __forceinline__ void sts64f(uint32_t a, float x, float y) { asm volatile("st.shared.v2.f32 [%0], {%1,%2};" ::"r"(a), "f"(x), "f"(y) : "memory"); }
__device__ __forceinline__ void sts32(uint32_t a, uint32_t x) { asm volatile("st.shared.b32 [%0], %1;" ::"r"(a), "r"(x) : "memory"); }
__device__ __forceinline__ void stg128(void* p, uint4 v) { asm volatile("st.global.v4.b32 [%0], {%1,%2,%3,%4};" ::"l"(p), "r"(v.x), "r"(v.y), "r"(v.z), "r"(v.w) : "memory"); }

__device__ __forceinline__ uint32_t pack2(float lo, float hi) { uint32_t r; asm("cvt.rn.bf16x2.f32 %0, %1, %2;" : "=r"(r) : "f"(hi), "f"(lo)); return r; }
__device__ __forceinline__ float blo(uint32_t v) { return __uint_as_float(v << 16); }
__device__ __forceinline__ float bhi(uint32_t v) { return __uint_as_float(v & 0xffff0000u); }
__device__ __forceinline__ uint32_t hmul2(uint32_t a, uint32_t b) { uint32_t r; asm("mul.rn.bf16x2 %0, %1, %2;" : "=r"(r) : "r"(a), "r"(b)); return r; }
__device__ __forceinline__ uint32_t hadd2(uint32_t a, uint32_t b) { uint32_t r; asm("add.rn.bf16x2 %0, %1, %2;" : "=r"(r) : "r"(a), "r"(b)); return r; }
__device__ __forceinline__ uint32_t hsub2(uint32_t a, uint32_t b) { uint32_t r; asm("sub.rn.bf16x2 %0, %1, %2;" : "=r"(r) : "r"(a), "r"(b)); return r; }
__device__ __forceinline__ uint32_t hfma2(uint32_t a, uint32_t b, uint32_t c) { uint32_t r; asm("fma.rn.bf16x2 %0, %1, %2, %3;" : "=r"(r) : "r"(a), "r"(b), "r"(c)); return r; }
__device__ __forceinline__ float tanh_fast(float x) { float r; asm("tanh.approx.f32 %0, %1;" : "=f"(r) : "f"(x)); return r; }
__device__ __forceinline__ float rsq(float x) { float r; asm("rsqrt.approx.ftz.f32 %0, %1;" : "=f"(r) : "f"(x)); return r; }
__device__ __forceinline__ float ex2(float x) { float r; asm("ex2.approx.ftz.f32 %0, %1;" : "=f"(r) : "f"(x)); return r; }

__device__ __forceinline__ uint32_t ld_relaxed(const uint32_t* p) {
    uint32_t v;
    asm volatile("ld.relaxed.gpu.global.u32 %0, [%1];" : "=r"(v) : "l"(p) : "memory");
    return v;
}
__device__ __forceinline__ uint32_t clock32() { uint32_t c; asm volatile("mov.u32 %0, %%clock;" : "=r"(c)::"memory"); return c; }
__device__ __forceinline__ void spin(uint32_t clks) {
    const uint32_t t0 = clock32();
    while (clock32() - t0 < clks) {}
}
__device__ __forceinline__ void flag_wait(const uint32_t* p, uint32_t e, bool mine) {
#pragma unroll 1
    for (int i = 0; i < (1 << 19); i++) {
        if (mine) mine = ld_relaxed(p) != e;
        if (!__any_sync(~0u, mine)) break;
        if (BACKOFF) spin(BACKOFF);
    }
    asm volatile("fence.acquire.gpu;" ::: "memory");
    fence_async_global();
}
__device__ __forceinline__ void st_data(void* p, uint32_t x, uint32_t y, uint32_t z, uint32_t w) {
    asm volatile("st.relaxed.gpu.global.v4.b32 [%0], {%1,%2,%3,%4};" ::"l"(p), "r"(x), "r"(y), "r"(z), "r"(w) : "memory");
}
template <int STRIDE, bool INV = false, int N>
__device__ __forceinline__ void ld_data(uint4 (&v)[N], const unsigned char* p) {
    int it = 0;
    bool again;
#pragma unroll 1
    do {
        uint32_t m = INV ? ~0u : 0u;
#pragma unroll
        for (int i = 0; i < N; i++)
            asm volatile("ld.relaxed.gpu.global.v4.b32 {%0,%1,%2,%3}, [%4];" : "=r"(v[i].x), "=r"(v[i].y), "=r"(v[i].z), "=r"(v[i].w) : "l"(p + i * STRIDE) : "memory");
#pragma unroll
        for (int i = 0; i < N; i++)
            m = INV ? __vimin3_u32(__vimin3_u32(v[i].x, v[i].y, v[i].z), v[i].w, m) : __vimax3_u32(__vimax3_u32(v[i].x, v[i].y, v[i].z), v[i].w, m);
        again = __any_sync(~0u, m == (INV ? 0u : ~0u)) && ++it < (1 << 16);
    } while (again);
}
__device__ __forceinline__ uint32_t ld_epoch() { return ld_relaxed(&g_epoch[blockIdx.x * FS]) + 1; }
__device__ __forceinline__ void flag_set(uint32_t* p, uint32_t e) { asm volatile("st.release.gpu.global.u32 [%0], %1;" ::"l"(p), "r"(e) : "memory"); }

__device__ __forceinline__ uint32_t desc_lo(uint32_t addr) { return ((addr & 0x3FFFF) >> 4) | 0x10000u; }
__device__ __forceinline__ uint64_t mkdesc(uint32_t lo) { return (uint64_t)lo | (0x40000040ull << 32); }
__device__ __forceinline__ void wg_fence() { asm volatile("wgmma.fence.sync.aligned;" ::: "memory"); }
__device__ __forceinline__ void wg_commit() { asm volatile("wgmma.commit_group.sync.aligned;" ::: "memory"); }
template <int N> __device__ __forceinline__ void wg_wait() { asm volatile("wgmma.wait_group.sync.aligned %0;" ::"n"(N) : "memory"); }
template <int N> __device__ __forceinline__ void pin(float (&d)[N]) {
#pragma unroll
    for (int i = 0; i < N; i++) asm volatile("" : "+f"(d[i])::"memory");
}
template <int N> __device__ __forceinline__ void pin(uint32_t (&d)[N]) {
#pragma unroll
    for (int i = 0; i < N; i++) asm volatile("" : "+r"(d[i])::"memory");
}

template <typename Tp, int N> __device__ __forceinline__ void zero(Tp (&d)[N]) {
#pragma unroll
    for (int i = 0; i < N; i++) d[i] = 0;
    pin(d);
}

#define F4(d, i) "+f"(d[i]), "+f"(d[i + 1]), "+f"(d[i + 2]), "+f"(d[i + 3])
#define F16(d, i) F4(d, i), F4(d, i + 4), F4(d, i + 8), F4(d, i + 12)

__device__ __forceinline__ void mma16(float (&d)[4], const uint32_t* a, uint32_t b0, uint32_t b1) {
    asm("mma.sync.aligned.m16n8k16.row.col.f32.bf16.bf16.f32 {%0,%1,%2,%3}, {%4,%5,%6,%7}, {%8,%9}, {%0,%1,%2,%3};"
        : F4(d, 0) : "r"(a[0]), "r"(a[1]), "r"(a[2]), "r"(a[3]), "r"(b0), "r"(b1));
}
template <int N>
__device__ __forceinline__ float row_sum(const uint32_t* x, uint32_t ones = 0x3F803F80u) {
    float c[4] = {};
#pragma unroll
    for (int i = 0; i < N; i += 4) mma16(c, x + i, ones, ones);
    return c[0] + c[2];
}
template <int N>
__device__ __forceinline__ float row_sumsq(const uint32_t* x, int lane) {
    float c0[4] = {}, c1[4] = {};
#pragma unroll
    for (int i = 0; i < N; i += 4) {
        mma16(c0, x + i, x[i], x[i + 2]);
        mma16(c1, x + i, x[i + 1], x[i + 3]);
    }
    return (lane & 4) ? c0[1] + c1[3] : c0[0] + c1[2];
}
__device__ __forceinline__ void mma_sp(float (&d)[32], const uint32_t* a, uint64_t b, uint32_t meta, int acc) {
    asm volatile("{.reg .pred p; setp.ne.b32 p, %38, 0;\n"
                 "wgmma.mma_async.sp.sync.aligned.m64n64k32.f32.bf16.bf16 {%0,%1,%2,%3,%4,%5,%6,%7,%8,%9,%10,%11,%12,%13,%14,%15,%16,%17,%18,%19,%20,%21,%22,%23,%24,%25,%26,%27,%28,%29,%30,%31}, "
                 "{%32,%33,%34,%35}, %36, %37, 0, p, 1, 1, 1;}\n"
                 : F16(d, 0), F16(d, 16) : "r"(a[0]), "r"(a[1]), "r"(a[2]), "r"(a[3]), "l"(b), "r"(meta), "r"(acc));
}
__device__ __forceinline__ void mma_qk(float (&d)[32], uint32_t a0, uint32_t a1, uint32_t a2, uint32_t a3, uint64_t b, int acc) {
    asm volatile("{.reg .pred p; setp.ne.b32 p, %37, 0;\n"
                 "wgmma.mma_async.sync.aligned.m64n64k16.f32.bf16.bf16 {%0,%1,%2,%3,%4,%5,%6,%7,%8,%9,%10,%11,%12,%13,%14,%15,%16,%17,%18,%19,%20,%21,%22,%23,%24,%25,%26,%27,%28,%29,%30,%31}, "
                 "{%32,%33,%34,%35}, %36, p, 1, 1, 0;}\n"
                 : F16(d, 0), F16(d, 16) : "r"(a0), "r"(a1), "r"(a2), "r"(a3), "l"(b), "r"(acc));
}
__device__ __forceinline__ void mma_pv(float (&d)[36], uint32_t a0, uint32_t a1, uint32_t a2, uint32_t a3, uint64_t b) {
    asm volatile("wgmma.mma_async.sync.aligned.m64n72k16.f32.bf16.bf16 {%0,%1,%2,%3,%4,%5,%6,%7,%8,%9,%10,%11,%12,%13,%14,%15,%16,%17,%18,%19,%20,%21,%22,%23,%24,%25,%26,%27,%28,%29,%30,%31,%32,%33,%34,%35}, "
                 "{%36,%37,%38,%39}, %40, 1, 1, 1, 1;\n"
                 : F16(d, 0), F16(d, 16), F4(d, 32) : "r"(a0), "r"(a1), "r"(a2), "r"(a3), "l"(b));
}

__device__ __forceinline__ uint32_t load_code(int n, int r, int w) {
    const int tile = 2 * r + w;
    int m, col, row;
    if (n < 16 || n >= 40) {
        const int k = n < 16 ? n : n - 40;
        m = n < 16 ? 0 : 6;
        if (TWO && n >= 40 && k < 4) { col = 4 * tile + (k & 1); row = (k >> 1) ^ r; }
        else if (k < 8) { col = 4 * tile + (k >> 1); row = n < 16 ? (k & 1) : (k & 1) ^ r; }
        else { m++; col = k < 12 ? tile ^ 2 : tile; row = 2 * (tile ^ (k & 1)) + ((k >> 1) & 1); }
    } else if (n < 32) {
        const int k = n - 16;
        m = 2;
        if (k < 4) { col = tile + ((k & 1) ? 8 : 4); row = (k >> 1) ^ r; }
        else { col = tile; row = (k & 1) ^ r; }
    } else if (n < 34) { m = 3; col = tile; row = n - 32; }
    else if (n < 38) { const int k = n - 34; m = 4; col = tile + 4 * (k & 1); row = (k >> 1) ^ r; }
    else { m = 5; col = tile; row = (n & 1) ^ r; }
    return m | (col << 4) | (row << ((m == 0 || m == 3) ? 10 : 11));
}

__global__ void __cluster_dims__(2, 1, 1) __launch_bounds__(NTHREADS, 1)
conformer_kernel(const Scalars p, const __grid_constant__ Maps m) {
    extern __shared__ __align__(1024) unsigned char smem_raw[];
    const uint32_t sb = smem_u32(smem_raw);
    const uint32_t bars = sb + OFF_BARS;
    const int tid = threadIdx.x;
    const int lane = tid & 31;
    const int warp = __shfl_sync(~0u, tid >> 5, 0);
    const int r = blockIdx.x & 1;
    const int pair = blockIdx.x >> 1;
    const int b = pair >> 5, pt = pair & 31;
    const int ah = pt >> 3, qt = (pt & 7) * 2 + r;
    const int abh = b * 4 + ah;

    TG(30);
    TSINIT();
    TS(0);
    const uint32_t P = sb + OFF_P, H = sb + OFF_H;
    if (warp == 11) {
        if (lane == 0) {
#pragma unroll
            for (int i = 0; i < 2 * NSLOT; i++) mbar_init(bars + (B_FULL + i) * 8, 1);
            asm volatile("fence.mbarrier_init.release.cluster;" ::: "memory");
            fence_async_smem();
        }
        __syncwarp();
        bar_arrive(13, 96);
        cluster_arrive();
    }

    if (warp >= 8) {
        asm volatile("setmaxnreg.dec.sync.aligned.u32 48;");
        if (warp >= 12) {
            cluster_arrive();
            cluster_wait();
            const int ut = tid & 127;
            const uint32_t target = ld_epoch() * 64;
            bar_sync(6, 384);
#pragma unroll
            for (int i = 0; i < 4; i++) {
                st_data(g_o + (size_t)(b * 128 + qt * 8 + 2 * i + (ut >> 6)) * 4096 + ah * 1024 + (ut & 63) * 16, ~0u, ~0u, ~0u, ~0u);
                if (i < 2) st_data(&g_halo[(pair * 4 + 2 * r + i) * 128 + ut], ~0u, ~0u, ~0u, ~0u);
            }
            bar_sync(11, 128);
            if (ut == 0) {
                asm volatile("red.release.gpu.global.add.u32 [%0], 1;" ::"l"(&g_reset[b * 32]) : "memory");
#pragma unroll 1
                for (int i = 0; i < (1 << 20) && ld_relaxed(&g_reset[b * 32]) != target; i++) __nanosleep(100);
                asm volatile("fence.acquire.gpu;" ::: "memory");
                mbar_arrive(bars + B_RST * 8);
            }
            bar_sync(11, 128);
            TS(14);
#pragma unroll
            for (int i = 0; i < 4; i++) st_data(g_kvq + 2097152 + (size_t)(abh * 1024 + qt * 64) * 128 + i * 2048 + ut * 16, 0, 0, 0, 0);
            const int side = warp & 1, wg = (warp >> 1) & 1, np = side ? pt + 1 : pt - 1;
            const unsigned char* src = reinterpret_cast<const unsigned char*>(&g_halo[(((b * 32 + np) * 4 + 2 * r + wg) * 2 + (side ^ 1)) * 64 + lane]);
            const uint32_t dst = H + 16384 + wg * GCH + side * 5120 + (lane & 7) * 128 + (((lane >> 3) ^ (lane & 7)) << 4);
            uint4 hv[2] = {make_uint4(0, 0, 0, 0), make_uint4(0, 0, 0, 0)};
            bar_sync(8 + wg, 192);
            if (np >= 0 && np < 32) {
                spin(HDELAY);
                ld_data<512>(hv, src);
            }
            stsm4(dst, hv[0].x, hv[0].y, hv[0].z, hv[0].w);
            stsm4(dst ^ 64, hv[1].x, hv[1].y, hv[1].z, hv[1].w);
            __syncwarp();
            if (lane == 0) mbar_arrive(bars + (B_HALO + (warp & 3)) * 8);
            TS(4);
        } else if (warp < 10) {
            const int w = warp - 8;
            const uint32_t ring = sb + OFF_RING + w * NSLOT * SLOT;
            const uint32_t full = bars + (B_FULL + w * NSLOT) * 8;
            cluster_arrive();
            bar_sync(13, 96);
            TS(1);
#pragma unroll
            for (int n = 0; n < NSLOT; n++) {
                if (n == 1) bar_sync(12, 64);
                ring_load(ring + n * SLOT, &m.tm[0], 64 * (8 * r + 4 * w + (n >> 1)), 4 * (n & 1), full + n * 8);
            }
            TS(2);
            const uint32_t code = load_code(lane, r, w) | (load_code(lane + 32, r, w) << 16);
            cluster_wait();
            uint32_t s = 0, ph = 0;
            int n = NSLOT;
#pragma unroll 1
            for (int seg = 0; seg < 2; seg++) {
#pragma unroll 1
                for (; n < (seg == 0 ? 22 : NLOADS); n++) {
                    const uint32_t c = __shfl_sync(~0u, code, n) >> (n & 32 ? 16 : 0);
                    const CUtensorMap* tm = &m.tm[c & 15];
                    const uint32_t col = (c & 0xf0) * 4, row = (c & 0xff00) >> 8, dst = ring + s * SLOT;
                    mbar_wait(full + (B_EMPTY - B_FULL) * 8 + s * 8, ph + (((uint32_t)(size_t)tm | col | row | dst) & p.zero));
                    ring_load(dst, tm, col, row, full + s * 8);
                    if (++s == NSLOT) { s = 0; ph ^= 1; }
                }
                if (seg == 1) break;
                const uint32_t epoch = ld_epoch();
                const uint32_t rdy = bars + (B_RDY + 3 * w) * 8, prdy = mapa(rdy, r ^ 1);
                const int odd = r ^ w;
                const uint32_t* flags = g_flag_kv + (abh * 32 + lane) * KFS;
                bool first = (lane >> 2) == 2 * odd + w;
                if (WARMF && first) first = ld_relaxed(flags) != epoch;
                auto kv_load = [&](uint32_t sl, int isv, int i) {
                    ring_load_both(ring + sl * SLOT, &m.tm[8], (isv * 64 + abh * 8 + 2 * i + w) * 128, full + sl * 8);
                };
#pragma unroll 1
                for (int i = 0; i < 2; i++) {
                    if (lane < 3 + i) {
                        const uint32_t sl = i ? lane : lane + 2;
                        mbar_wait(full + (B_EMPTY - B_FULL + sl) * 8, i ^ 1);
                        mbar_arrive_tx(full + sl * 8, (i || lane == 2) ? SLOT : 0);
                    }
                    __syncwarp();
                }
                if (lane == 0) mbar_arrive_peer(prdy);
                bar_sync(14, 96);
                spin(KDELAY);
                mbar_wait(rdy, 0);
                flag_wait(flags, epoch, first);
                TSW(5 + 2 * odd);
                if (!odd) { kv_load(4, 0, 0); bar_arrive(12, 64); }
                else bar_sync(12, 64);
                spin(w ? KD3 : KD2);
                kv_load(odd ^ 1, odd ^ 1, odd);
                flag_wait(flags, epoch, (lane >> 2) == 2 * odd + w + 4);
                mbar_wait(full + (odd ^ 1) * 8, 1);
                kv_load(2 + odd, odd, 2 - odd);
#pragma unroll 1
                for (int i = 0; i < 3; i++) {
                    const uint32_t sl = i ? i - 1 : 4, bo = i == 2 ? 16 : 8;
                    mbar_wait(full + (B_EMPTY - B_FULL + sl) * 8, i != 0);
                    if (lane == 0) mbar_arrive_tx(full + sl * 8, SLOT);
                    if ((i & 1) != odd) {
                        mbar_wait(rdy + bo, 0);
                        kv_load(sl, i != 0, 2 + odd);
                    } else if (lane == 0) mbar_arrive_peer(prdy + bo);
                    __syncwarp();
                }
                n = 32; s = 2; ph = 1;
            }
        } else if (warp == 10) {
            if (lane == 0) {
#pragma unroll
                for (int i = B_EMPTY; i < NBARS; i++) mbar_init(bars + i * 8, i < B_XA ? 4 : 1);
#pragma unroll
                for (int i = B_XA; i <= B_SR; i++) mbar_arrive_tx(bars + i * 8, i < B_XB ? 512 : ((i >= B_INB && i < B_SR) ? 4096 : 8192));
                asm volatile("fence.mbarrier_init.release.cluster;" ::: "memory");
                fence_async_smem();
            }
            __syncwarp();
            cluster_arrive();
            cluster_wait();
        } else {
            const uint32_t kb = (lane < 2 || lane > 5) ? 4096 : (lane == 2 ? 3072 : (lane == 4 ? 2048 : 1024));
            const char* pf = m.w[lane & 7] + blockIdx.x * kb;
            cluster_wait();
            if (lane < PF0) prefetch_l2(pf, kb);
            mbar_wait(bars + B_FULL * 8, 0);
            if (lane >= PF0 && lane < 3) prefetch_l2(pf, kb);
            if (lane >= 1 && lane < 9) asm volatile("prefetch.tensormap [%0];" ::"l"(&m.tm[lane]) : "memory");
            mbar_wait(bars + (B_FULL + 1) * 8, 1);
            if (lane > 2 && lane < 8) prefetch_l2(pf, kb);
            if (lane == 8 && blockIdx.x < 15) prefetch_l2(p.dw + blockIdx.x * 256, 512);
            const uint32_t epoch = ld_epoch();
            bar_sync(4, 288);
            if (lane < 16) flag_set(&g_flag_kv[((b * 4 + 2 * r + (lane >> 3)) * 32 + pt) * KFS + (lane & 7)], epoch);
            __syncwarp();
            bar_arrive(14, 96);
            TSW(8);
        }
        TSDUMP();
        return;
    }

    const int w = warp >> 2, wq = warp & 3;
    const int tile = 2 * r + w;
    const int wt = tid & 127;
    const int c4 = lane & 3;
    const int trow = pt * 32 + 8 * wq;
    uint32_t xr[8];
    uint32_t a[32];
    const char* xrow = reinterpret_cast<const char*>(p.x) + (b * T_ + trow + (lane >> 2)) * 512;
    zero(a);
    if (trow < T_) {
        const char* src = xrow + c4 * 16 + p.zero;
#pragma unroll
        for (int i = 0; i < 8; i++)
            asm volatile("ld.global.nc.v4.b32 {%0,%1,%2,%3}, [%4];" : "=r"(a[4 * i]), "=r"(a[4 * i + 1]), "=r"(a[4 * i + 2]), "=r"(a[4 * i + 3]) : "l"(src + 64 * i));
    }
    cluster_arrive();
    asm volatile("setmaxnreg.inc.sync.aligned.u32 208;");
    const uint32_t rbase = sb + OFF_RING + w * NSLOT * SLOT, fbar = bars + (B_FULL + w * NSLOT) * 8;
    const uint32_t rdesc = desc_lo(rbase);
    auto acq = [&](int n) { mbar_wait(fbar + (n % NSLOT) * 8, (n / NSLOT) & 1); };
    auto rel = [&](int n) { if (lane == 0) mbar_arrive(fbar + (B_EMPTY - B_FULL + n % NSLOT) * 8); };
    const uint32_t foff = (lane & 7) * 128 + (((lane >> 3) ^ (lane & 7)) << 4);
    float v[16];
    const uint32_t xown = __shfl_sync(~0u, P + wt * 16 + tile * 4096, lane), xrem = __shfl_sync(~0u, P + wt * 16 + (r ^ 1) * 8192, lane);
    const uint32_t sbuf = __shfl_sync(~0u, sb + OFF_MISC + 1024 + (8 * wq + (lane >> 2)) * 32, lane);
    const uint32_t sown = __shfl_sync(~0u, sbuf + tile * 8, lane);
    const uint32_t peer = __shfl_sync(~0u, mapa(sb, r ^ 1) - sb, lane);
    const uint32_t hbuf = __shfl_sync(~0u, H + w * 4096 + wt * 16, lane);
    const uint32_t meta = __shfl_sync(~0u, 0xEEEE4444u + p.zero, lane);
    cluster_wait();
    TS(56);
    float mean, msq;
    const int mir = wq < 2 ? 7 : 0;
    uint32_t dwr[15] = {};

#pragma unroll
    for (int ph = 0; ph < 5; ph++) {
        uint4 o0, o1;
        if (ph == 0) {
            const uint32_t one = 0x3F803F80u + ((xown | xrem | sbuf | sown | hbuf | foff | rdesc | fbar) & p.zero);
            mean = ((row_sum<8>(a, one) + row_sum<8>(a + 8, one)) + (row_sum<8>(a + 16, one) + row_sum<8>(a + 24, one))) * (1.f / 256.f);
            TS(57);
        } else {
            const uint32_t xa = bars + (B_XA + ph) * 8;
#pragma unroll
            for (int j = 0; j < 8; j++) xr[j] = pack2(v[2 * j], v[2 * j + 1]);
            const float s = row_sum<8>(xr), q = row_sumsq<8>(xr, lane);
            if (ph < 4) {
                sts128(xown, xr[0], xr[1], xr[2], xr[3]);
                sts128(xown + 2048, xr[4], xr[5], xr[6], xr[7]);
            }
            put_sums(sown, sown + peer, s, q, xa + peer, c4 == (lane >> 3));
            bar_sync(10, 256);
            if (ph < 4) {
                o0 = lds128(xown ^ 4096); o1 = lds128((xown ^ 4096) + 2048);
                st_async4(xown + peer, xr[0], xr[1], xr[2], xr[3], xa + (B_XB - B_XA) * 8 + peer);
                st_async4(xown + peer + 2048, xr[4], xr[5], xr[6], xr[7], xa + (B_XB - B_XA) * 8 + peer);
            }
            TS(57 + ph);
            if (ph == 3) acq(0);
            if (ph == 1) acq(16);
            mbar_wait(xa, 0);
            const float4 u0 = lds128f(sbuf), u1 = lds128f(sbuf + 16);
            mean = ((u0.x + u0.z) + (u1.x + u1.z)) * (1.f / 256.f);
            msq = ((u0.y + u0.w) + (u1.y + u1.w)) * (1.f / 256.f);
        }
        if (ph == 4) break;
        const uint32_t mean2 = pack2(mean, mean);
        auto centre = [&](int i, const uint4& u) {
            a[i] = hsub2(u.x, mean2); a[i + 1] = hsub2(u.y, mean2); a[i + 2] = hsub2(u.z, mean2); a[i + 3] = hsub2(u.w, mean2);
        };
        if (ph == 0) {
#pragma unroll
            for (int j = 0; j < 32; j++) a[j] = hsub2(a[j], mean2);
            zero(xr);
            if (trow < T_) {
                const char* src = xrow + tile * 128 + c4 * 4 + (mean2 & p.zero);
#pragma unroll
                for (int j = 0; j < 8; j++) asm volatile("ld.global.nc.b32 %0, [%1];" : "=r"(xr[j]) : "l"(src + 16 * j));
            }
            mean -= blo(mean2);
            msq = __shfl_sync(~0u, row_sumsq<16>(a, lane) + row_sumsq<16>(a + 16, lane), (lane & 28) + (lane >> 3)) * (1.f / 256.f);
            acq(0);
        } else {
#pragma unroll
            for (int j = 0; j < 8; j++) a[j] = hsub2(xr[j], mean2);
            centre(8, o0); centre(12, o1);
        }
        const float rstd = rsq(fmaxf(fmaf(-mean, mean, msq), 0.f) + 1e-5f);
        auto gather_peer = [&]() {
            mbar_wait(bars + (B_XB + ph) * 8, 0);
#pragma unroll
            for (int i = 0; i < 4; i++) centre(16 + 4 * i, lds128(xrem + i * 2048));
        };
        auto sp = [&](float (&d)[32], int n, const uint32_t* af, int flip, int acc) {
            const uint32_t lo = rdesc + p.zero * (ph * 64 + n + 1) + (n % NSLOT) * (SLOT >> 4);
            const uint64_t b0 = mkdesc(lo + flip * 512), b1 = mkdesc(lo + (flip ^ 1) * 512);
            wg_fence();
            mma_sp(d, af, b0, meta, acc);
            mma_sp(d, af + 4, b0 + 256, meta, 1);
            mma_sp(d, af + 8, b1, meta, 1);
            mma_sp(d, af + 12, b1 + 256, meta, 1);
            wg_commit();
        };
        float d0[32], d1[32];

        if (ph == 0 || ph == 3) {
            uint32_t h[32], ho[32];
            const float rs = 0.5f * rstd;
            const uint32_t inb = bars + (B_INB + (ph & 2) + w) * 8;
            bool ready = true;
            const int eager = ph ? (TWO ? EAGER + 5 : EAGER) : EAGER - 1;
            auto step = [&](float (&d)[32], int n, const uint32_t* af, int flip, int acc, auto work) {
                if (!ready) acq(n);
                if (((TURN >> n) & 1) && w == 1) bar_sync(7, 256);
                sp(d, n, af, flip, acc);
                if (n > 0 && ((TURN >> (n - 1)) & 1) && w == 0) bar_arrive(7, 256);
                if (n < 15) ready = mbar_test(fbar + ((n + 1) % NSLOT) * 8, ((n + 1) / NSLOT) & 1);
                wg_wait<1>();
                if (n > 0 && !((eager >> (n - 1)) & 1)) rel(n - 1);
                const uint32_t tie = work() & p.zero;
                if ((eager >> n) & 1) {
                    if (p.zero < n + ph + 1) wg_wait<0>();
                    if (lane == 0) mbar_arrive(fbar + (B_EMPTY - B_FULL + n % NSLOT) * 8 + tie);
                }
            };
            auto none = []() { return 0u; };
            const int fl = ph ? w : 0;
            auto fetch = [&](int i) {
                if (SPLIT) bar_sync(2 * (i & 1) + (w ^ 1), 256);
                else bar_sync(10, 256);
                const uint4 u0 = lds128((hbuf ^ 4096) + (i & 1) * 8192), u1 = lds128((hbuf ^ 4096) + (i & 1) * 8192 + 2048);
                ho[8 * i] = u0.x; ho[8 * i + 1] = u0.y; ho[8 * i + 2] = u0.z; ho[8 * i + 3] = u0.w;
                ho[8 * i + 4] = u1.x; ho[8 * i + 5] = u1.y; ho[8 * i + 6] = u1.z; ho[8 * i + 7] = u1.w;
                return u0.x | u1.x;
            };
            auto act = [&](float (&d)[32], int i) {
                if (i > 0) fetch(i - 1);
                pin(d);
#pragma unroll
                for (int j = 0; j < 8; j++) {
                    const float u0 = (d[4 * j] + d[4 * j + 2]) * rs, u1 = (d[4 * j + 1] + d[4 * j + 3]) * rs;
                    h[8 * i + j] = pack2(fmaf(u0, tanh_fast(u0), u0), fmaf(u1, tanh_fast(u1), u1));
                }
                sts128(hbuf + (i & 1) * 8192, h[8 * i], h[8 * i + 1], h[8 * i + 2], h[8 * i + 3]);
                sts128(hbuf + (i & 1) * 8192 + 2048, h[8 * i + 4], h[8 * i + 5], h[8 * i + 6], h[8 * i + 7]);
                if (SPLIT) bar_arrive(2 * (i & 1) + w, 256);
                return 0u;
            };
            TS(1 + (ph & 2) * 10);
            if (TWO && ph) {
                step(d0, 0, a, fl, 0, none);
                step(d1, 1, a, fl, 0, [&]() { gather_peer(); return 0u; });
                TS(32);
                step(d0, 2, a + 16, 0, 1, none);
                step(d1, 3, a + 16, 0, 1, [&]() { return act(d0, 0); });
            } else {
                step(d0, 0, a, fl, 0, [&]() { if (ph) gather_peer(); return 0u; });
                TS(32);
                step(d0, 1, a + 16, 0, 1, none);
                step(d1, 2, a, fl, 0, [&]() { return act(d0, 0); });
                step(d1, 3, a + 16, 0, 1, none);
            }
            step(d0, 4, a, fl, 0, [&]() { return act(d1, 1); });
            TS(33);
            step(d0, 5, a + 16, 0, 1, none);
            step(d1, 6, a, fl, 0, [&]() { return act(d0, 2); });
            step(d1, 7, a + 16, 0, 1, none);
            step(d0, 8, h, 0, 0, [&]() { act(d1, 3); return fetch(3); });
            TS(2 + (ph & 2) * 10);
            step(d0, 9, ho, 0, 1, none);
            step(d0, 10, h + 16, 0, 1, none);
            step(d0, 11, ho + 16, 0, 1, none);
            uint32_t pk[8];
            auto pack_out = [&]() {
                pin(d0);
#pragma unroll
                for (int j = 0; j < 8; j++) pk[j] = pack2(d0[4 * j] + d0[4 * j + 2], d0[4 * j + 1] + d0[4 * j + 3]);
            };
            auto send = [&](int i) { st_async4(hbuf + 16384 + i * 2048 + peer, pk[4 * i], pk[4 * i + 1], pk[4 * i + 2], pk[4 * i + 3], inb + peer); };
            step(d1, 12, h, 0, 0, [&]() { pack_out(); if (SND != 1) send(0); if (SND == 0) send(1); return 0u; });
            TS(34);
            step(d1, 13, ho, 0, 1, [&]() { if (SND == 1) send(0); if (SND) send(1); return 0u; });
            step(d1, 14, h + 16, 0, 1, none);
            step(d1, 15, ho + 16, 0, 1, none);
            mbar_wait(inb, 0);
#pragma unroll
            for (int i = 0; i < 2; i++) {
                const uint4 u = lds128(hbuf + 16384 + i * 2048);
                const uint32_t p0[4] = {u.x, u.y, u.z, u.w};
#pragma unroll
                for (int j = 0; j < 4; j++) {
                    v[8 * i + 2 * j] = fmaf(0.5f, blo(p0[j]), blo(xr[4 * i + j]));
                    v[8 * i + 2 * j + 1] = fmaf(0.5f, bhi(p0[j]), bhi(xr[4 * i + j]));
                }
            }
            wg_wait<0>();
            pin(d1);
            rel(15);
            TS(3 + (ph & 2) * 10);
#pragma unroll
            for (int j = 0; j < 8; j++) {
                v[2 * j] = fmaf(0.5f, d1[4 * j] + d1[4 * j + 2], v[2 * j]);
                v[2 * j + 1] = fmaf(0.5f, d1[4 * j + 1] + d1[4 * j + 3], v[2 * j + 1]);
            }
#pragma unroll
            for (int i = 0; i < 15; i++) dwr[i] = 0;
            continue;
        }

        auto residual = [&](int n) {
            wg_wait<1>();
            rel(n);
            wg_wait<0>();
            pin(d0);
            rel(n + 1);
#pragma unroll
            for (int j = 0; j < 8; j++) {
                v[2 * j] = d0[4 * j] + d0[4 * j + 2] + blo(xr[j]);
                v[2 * j + 1] = d0[4 * j + 1] + d0[4 * j + 3] + bhi(xr[j]);
            }
        };

        if (ph == 2) {
            TS(39);
            sp(d0, 34, a, w, 0);
            acq(35);
            sp(d1, 35, a, w, 0);
            acq(36); acq(37);
            gather_peer();
            sp(d0, 36, a + 16, 0, 1);
            sp(d1, 37, a + 16, 0, 1);
            wg_wait<2>();
            rel(34);
            if (!(LATE & 1)) rel(35);
            acq(38);
            const float rs = trow < T_ ? 0.5f * rstd : 0.f;
            wg_wait<0>();
            pin(d0); pin(d1);
            if (!(LATE & 2)) { rel(36); rel(37); }
            TS(18);
            uint32_t pk[8];
#pragma unroll
            for (int j = 0; j < 8; j++) {
                const float u0 = (d0[4 * j] + d0[4 * j + 2]) * rs, u1 = (d0[4 * j + 1] + d0[4 * j + 3]) * rs;
                const float t0 = tanh_fast((d1[4 * j] + d1[4 * j + 2]) * rs), t1 = tanh_fast((d1[4 * j + 1] + d1[4 * j + 3]) * rs);
                pk[j] = pack2(fmaf(u0, t0, u0), fmaf(u1, t1, u1));
            }
            if (wq == 0 || wq == 3) {
                uint4* hp = &g_halo[((pair * 4 + tile) * 2 + (wq & 1)) * 64 + lane];
                st_data(hp, pk[0], pk[1], pk[2], pk[3]);
                st_data(hp + 32, pk[4], pk[5], pk[6], pk[7]);
            }
            const uint32_t gs = H + 16384 + w * GCH + wq * 1024;
            stsm4(gs + 1024 + foff, pk[0], pk[1], pk[2], pk[3]);
            stsm4(gs + 1024 + (foff ^ 64), pk[4], pk[5], pk[6], pk[7]);
            bar_sync(8 + w, 192);
            TS(26);
            uint32_t ca[8], cb[8];
            const int e = (wq & 1) * 4;
            const uint32_t lo = ((mir ^ e) * 144) ^ (lane * 4);
            const int dir = mir ? -1024 : 1024;
            const uint32_t gb = H + 16384 + w * GCH + (mir ? 3072 : 2048) + lo, sown_ = H + tile * HCH, so = sown_ + (mir ? 1024 : 2048) + lo;
            auto finish = [&](int i) {
                const uint32_t c = hadd2(ca[i], cb[i]);
                const float h0 = blo(c), h1 = bhi(c);
                sts32((so + (i >> 2) * dir) ^ ((i & 3) * 144), pack2(fmaf(h0, tanh_fast(h0), h0), fmaf(h1, tanh_fast(h1), h1)));
            };
#pragma unroll
            for (int k = 0; k < 26; k++) {
                if (k == 19) {
#pragma unroll
                    for (int i = 0; i < 4; i++) finish(i);
                    fence_async_smem();
                    bar_sync(2 + w, 128);
                    if (wq == 0) peer_copy(mapa(sown_ + 1024, r ^ 1), sown_ + 1024, 2048, mapa(bars + B_SR * 8, r ^ 1));
                    mbar_wait(bars + (B_HALO + 2 * w + (wq >> 1)) * 8, 0);
                    if (LATE & 1) rel(35);
                    if (LATE & 2) { rel(36); rel(37); }
                    TS(27);
                }
                const uint32_t g = lds32((gb + (((k + 1) & 4) ? ((k + 1) >> 3) + (wq & 1) : ((k + 1) >> 3)) * dir) ^ (((k + 1) & 7) * 144));
#pragma unroll
                for (int i = 0; i < 8; i++) {
                    const int tap = k - (i & 3) - 2 * (i & 4);
                    if (tap == 0) ca[i] = hmul2(g, dwr[0]);
                    else if (tap > 0 && tap < 8) ca[i] = hfma2(g, dwr[tap], ca[i]);
                    else if (tap == 8) cb[i] = hmul2(g, dwr[8]);
                    else if (tap > 8 && tap < 15) cb[i] = hfma2(g, dwr[tap], cb[i]);
                }
            }
#pragma unroll
            for (int i = 4; i < 8; i++) finish(i);
            fence_async_smem();
            bar_sync(12 + (warp >> 1), 64);
            if (wq == 0 || wq == 3) peer_copy(mapa(sown_ + wq * 1024, r ^ 1), sown_ + wq * 1024, 1024, mapa(bars + B_SR * 8, r ^ 1));
            bar_sync(10, 256);
            TS(19);
            auto frags = [&](int i, int half) {
                const uint32_t src = H + 2 * half * HCH + wq * 1024;
#pragma unroll
                for (int k = 0; k < 4; k++) ldsm4(src + (k >> 1) * HCH + (foff ^ ((k & 1) * 64)), a[i + 4 * k], a[i + 4 * k + 1], a[i + 4 * k + 2], a[i + 4 * k + 3]);
            };
            frags(0, r);
            sp(d0, 38, a, 0, 0);
            acq(39);
            mbar_wait(bars + B_SR * 8, 0);
            frags(16, r ^ 1);
            sp(d0, 39, a + 16, 0, 1);
            residual(38);
            TS(20);
            continue;
        }

        {
            TS(11);
            unsigned char* g = g_kvq + (size_t)((b * 4 + tile) * 1024 + trow) * 128;
            const uint32_t uo = (lane >> 2) * 128 + ((c4 ^ (lane >> 2)) << 4);
            auto put = [&](float (&d)[32], int i) {
                pin(d);
                uint32_t pk[8];
#pragma unroll
                for (int j = 0; j < 8; j++) pk[j] = pack2((d[4 * j] + d[4 * j + 2]) * rstd, (d[4 * j + 1] + d[4 * j + 3]) * rstd);
                if (i < 2) {
                    stg128(g + i * 1048576 + uo, make_uint4(pk[0], pk[1], pk[2], pk[3]));
                    stg128(g + i * 1048576 + (uo ^ 64), make_uint4(pk[4], pk[5], pk[6], pk[7]));
                } else {
                    const uint32_t stg = H + warp * 1024;
                    sts128(stg + uo, pk[0], pk[1], pk[2], pk[3]);
                    sts128(stg + (uo ^ 64), pk[4], pk[5], pk[6], pk[7]);
                    __syncwarp();
                    ldsm4(stg + foff, pk[0], pk[1], pk[2], pk[3]);
                    ldsm4(stg + (foff ^ 64), pk[4], pk[5], pk[6], pk[7]);
                    st_data(g + 2097152 + lane * 16, ~pk[0], ~pk[1], ~pk[2], ~pk[3]);
                    st_data(g + 2097152 + 512 + lane * 16, ~pk[4], ~pk[5], ~pk[6], ~pk[7]);
                }
            };
            sp(d0, 16, a, w, 0);
            acq(17);
            sp(d1, 17, a, w, 0);
            gather_peer();
            acq(18);
            sp(d0, 18, a + 16, 0, 1);
            wg_wait<1>();
            rel(16); rel(17);
            acq(19);
            sp(d1, 19, a + 16, 0, 1);
            wg_wait<1>();
            rel(18);
            put(d0, 0);
            wg_wait<0>();
            rel(19);
            TS(37);
            put(d1, 1);
            bar_arrive(4, 288);
            TS(38);
            acq(20);
            sp(d0, 20, a, w, 0);
            acq(21);
            sp(d0, 21, a + 16, 0, 1);
            acq(22); acq(23);
            rel(22); rel(23);
            wg_wait<0>();
            rel(20); rel(21);
            put(d0, 2);
            TS(12);
        }

        {
            constexpr float CS = 0.125f * 1.4426950408889634f;
            float sa[32], sb2[32], o[36];
            uint32_t pa[16], pb[16], q[16];
            float n0 = INFINITY, n1 = INFINITY;
            zero(o); zero(pa); zero(pb); zero(sb2);
            const uint32_t ones = sb + OFF_MISC + 2048;
            { const uint32_t c = w ? 0u : 0x3F803F80u; sts128(ones + tid * 16, c, c, c, c); }
            fence_async_smem();
            bar_sync(10, 256);
            const uint32_t vdesc = rdesc + ((((ones - rbase) >> 4) - 1) << 16);
            auto qk_issue = [&](float (&s)[32], uint32_t lo) {
                const uint64_t kd = mkdesc(lo);
                wg_fence();
#pragma unroll
                for (int k = 0; k < 4; k++) mma_qk(s, q[4 * k], q[4 * k + 1], q[4 * k + 2], q[4 * k + 3], kd + 2 * k, k != 0);
                wg_commit();
            };
            auto both_issue = [&](float (&s)[32], uint32_t klo, uint32_t (&pp)[16], uint32_t vlo) {
                const uint64_t kd = mkdesc(klo), vd = mkdesc(vlo);
                wg_fence();
#pragma unroll
                for (int k = 0; k < 4; k++) {
                    mma_pv(o, pp[4 * k], pp[4 * k + 1], pp[4 * k + 2], pp[4 * k + 3], vd - k * (128 * 65535));
                    mma_qk(s, q[4 * k], q[4 * k + 1], q[4 * k + 2], q[4 * k + 3], kd + 2 * k, k != 0);
                }
                wg_commit();
            };
            auto new_max = [&](float (&s)[32], int nj, float& x0, float& x1) {
                x0 = s[0]; x1 = s[2];
#pragma unroll
                for (int j = 0; j < nj; j++) {
                    x0 = fmaxf(x0, fmaxf(s[4 * j], s[4 * j + 1]));
                    x1 = fmaxf(x1, fmaxf(s[4 * j + 2], s[4 * j + 3]));
                }
                x0 = fmaxf(x0, __shfl_xor_sync(~0u, x0, 1)); x1 = fmaxf(x1, __shfl_xor_sync(~0u, x1, 1));
                x0 = fmaxf(x0, __shfl_xor_sync(~0u, x0, 2)); x1 = fmaxf(x1, __shfl_xor_sync(~0u, x1, 2));
                x0 = fminf(n0, fmaf(x0, -CS, -20.f)); x1 = fminf(n1, fmaf(x1, -CS, -20.f));
            };
            auto probs = [&](float (&s)[32], uint32_t (&pp)[16], bool ready, bool tail, auto wait) {
                uint32_t any = 0;
#pragma unroll
                for (int i = 0; i < 16; i++) {
                    pp[i] = pack2(ex2(fmaf(s[2 * i], CS, (i & 1) ? n1 : n0)), ex2(fmaf(s[2 * i + 1], CS, (i & 1) ? n1 : n0)));
                    any |= pp[i];
                }
                wg_wait<0>();
                pin(sa); pin(sb2); pin(o); pin(pa); pin(pb);
                if (__builtin_expect(__any_sync(~0u, (any & 0x40004000u) || !ready), 0)) {
                    wait();
                    if (__any_sync(~0u, any & 0x40004000u)) {
                        if (tail) {
#pragma unroll
                            for (int i = 20; i < 32; i++) s[i] = -INFINITY;
                        }
                        float x0, x1;
                        new_max(s, 8, x0, x1);
                        const float sc0 = ex2(x0 - n0), sc1 = ex2(x1 - n1);
                        n0 = x0; n1 = x1;
#pragma unroll
                        for (int j = 0; j < 9; j++) { o[4 * j] *= sc0; o[4 * j + 1] *= sc0; o[4 * j + 2] *= sc1; o[4 * j + 3] *= sc1; }
#pragma unroll
                        for (int i = 0; i < 16; i++)
                            pp[i] = pack2(ex2(fmaf(s[2 * i], CS, (i & 1) ? n1 : n0)), ex2(fmaf(s[2 * i + 1], CS, (i & 1) ? n1 : n0)));
                    }
                }
            };
            {
                uint4 u[4];
                const unsigned char* src = g_kvq + 2097152 + (size_t)(abh * 1024 + qt * 64 + wq * 16) * 128 + lane * 16;
                spin(QGATE);
                ld_data<512, true>(u, src);
#pragma unroll
                for (int k = 0; k < 2; k++) {
                    q[8 * k] = ~u[k].x; q[8 * k + 1] = ~u[k + 2].x; q[8 * k + 2] = ~u[k].y; q[8 * k + 3] = ~u[k + 2].y;
                    q[8 * k + 4] = ~u[k].z; q[8 * k + 5] = ~u[k + 2].z; q[8 * k + 6] = ~u[k].w; q[8 * k + 7] = ~u[k + 2].w;
                }
                pin(q);
            }
            TS(40);
            acq(24);
            TS(13);
            qk_issue(sa, rdesc + (24 % NSLOT) * (SLOT >> 4));
            wg_wait<0>();
            pin(sa);
            {
                float x0, x1;
                new_max(sa, NJ0, x0, x1);
                n0 = x0; n1 = x1;
            }
            bar_arrive(6, 384);
            uint32_t vd = vdesc - (SLOT >> 4) * 65535u, kd = rdesc, vb = fbar + 8, kb = fbar;
            uint32_t vlast = vdesc - 4 * (SLOT >> 4) * 65535u, klast = rdesc + 4 * (SLOT >> 4) + 512;
            uint32_t kprev = fbar + 32, vprev = bars + (B_SINK - (B_EMPTY - B_FULL)) * 8;
#pragma unroll 1
            for (int it = 0; it < 4; it++) {
                both_issue(sb2, klast, pb, vlast);
                probs(sa, pa, mbar_test(vb, it < 2) & mbar_test(kb, it < 3), false, [&]() { mbar_wait(vb, it < 2); mbar_wait(kb, it < 3); });
                TS(41 + it * 4);
                if (lane == 0) mbar_arrive(kprev + (B_EMPTY - B_FULL) * 8);
                if (lane == 0) mbar_arrive(vprev + (B_EMPTY - B_FULL) * 8);
                both_issue(sa, kd, pa, vd);
                const int dv = it == 0 ? 2 : (it == 1 ? -3 : 1);
                kprev = kb; vprev = vb; vlast = vd - 512 * 65535u; klast = kd + 512;
                vd -= dv * (SLOT >> 4) * 65535u; vb += dv * 8;
                kd += (it == 2 ? -3 : 2) * (SLOT >> 4); kb = it == 2 ? vb : kb + 16;
                probs(sb2, pb, true, it == 3 && w == 1, []() {});
                TS(43 + it * 4);
            }
            wg_fence();
#pragma unroll
            for (int k = 0; k < 4; k++)
                mma_pv(o, pb[4 * k], pb[4 * k + 1], pb[4 * k + 2], pb[4 * k + 3], mkdesc(vlast - k * (128 * 65535) + (k > 1 ? w * ((k - 1) << 22) : 0)));
            wg_commit();
            const int row = wq * 16 + (lane >> 2);
            const uint32_t ml = sb + OFF_MISC;
            mbar_wait(bars + B_RST * 8, 0);
            wg_wait<0>();
            pin(o); pin(pb); pin(sa); pin(sb2);
            if (!(LATE & 4)) rel(31);
            const float l0 = o[32], l1 = o[34];
            if (c4 == 0) { sts64f(ml + w * 512 + row * 8, n0, l0); sts64f(ml + w * 512 + row * 8 + 64, n1, l1); }
            TS(14);
            uint32_t pk[8];
            auto merge = [&](int keep) {
#pragma unroll
                for (int j = 0; j < 4; j++) sts128f(hbuf + (j & 1) * 2048 + (j >> 1) * 8192, o[16 - keep + 4 * j], o[17 - keep + 4 * j], o[18 - keep + 4 * j], o[19 - keep + 4 * j]);
                bar_sync(10, 256);
                const float2 u0 = lds64f(ml + (w ^ 1) * 512 + row * 8), u1 = lds64f(ml + (w ^ 1) * 512 + row * 8 + 64);
                const float x0 = fminf(n0, u0.x), x1 = fminf(n1, u1.x);
                float a0 = ex2(x0 - n0), b0 = ex2(x0 - u0.x), a1 = ex2(x1 - n1), b1 = ex2(x1 - u1.x);
                const float i0 = __fdividef(1.f, fmaf(a0, l0, b0 * u0.y)), i1 = __fdividef(1.f, fmaf(a1, l1, b1 * u1.y));
                a0 *= i0; b0 *= i0; a1 *= i1; b1 *= i1;
#pragma unroll
                for (int j = 0; j < 4; j++) {
                    const float4 v = lds128f((hbuf ^ 4096) + (j & 1) * 2048 + (j >> 1) * 8192);
                    pk[2 * j] = pack2(fmaf(a0, o[keep + 4 * j], b0 * v.x), fmaf(a0, o[keep + 4 * j + 1], b0 * v.y));
                    pk[2 * j + 1] = pack2(fmaf(a1, o[keep + 4 * j + 2], b1 * v.z), fmaf(a1, o[keep + 4 * j + 3], b1 * v.w));
                }
            };
            if (w == 0) merge(0); else merge(16);
            unsigned char* dst = g_o + (size_t)(b * 128 + qt * 8 + 2 * wq) * 4096 + ah * 1024 + w * 512 + lane * 16;
            st_data(dst, pk[0], pk[2], pk[4], pk[6]);
            st_data(dst + 4096, pk[1], pk[3], pk[5], pk[7]);
            if (tid == 0) asm volatile("red.relaxed.gpu.global.add.u32 [%0], 1;" ::"l"(&g_epoch[blockIdx.x * FS]) : "memory");
            TS(15);
        }

        {
            const uint32_t* dp = reinterpret_cast<const uint32_t*>(p.dw + (mir ? 14 * 256 : 0) + tile * 64) + lane;
#pragma unroll
            for (int i = 0; i < 15; i++) asm volatile("ld.global.nc.b32 %0, [%1];" : "=r"(dwr[i]) : "l"(dp + i * (mir ? -128 : 128)));
            acq(32); acq(33); acq(34);
            uint4 u[8];
            ld_data<512>(u, g_o + (size_t)(b * 128 + pt * 4 + wq) * 4096 + lane * 16);
#pragma unroll
            for (int i = 0; i < 8; i++) { a[4 * i] = u[i].x; a[4 * i + 1] = u[i].y; a[4 * i + 2] = u[i].z; a[4 * i + 3] = u[i].w; }
            if (LATE & 4) rel(31);
            TS(16);
            sp(d0, 32, a, 0, 0);
            sp(d0, 33, a + 16, 0, 1);
#pragma unroll
            for (int i = 0; i < 15; i++) dwr[i] = hmul2(dwr[i], 0x3F003F00u);
            residual(32);
            TS(17);
        }
    }

    cluster_arrive();
    TS(24);
    {
        const float rstd = rsq(fmaxf(fmaf(-mean, mean, msq), 0.f) + 1e-5f), nb = -mean * rstd;
#pragma unroll
        for (int j = 0; j < 8; j++) xr[j] = pack2(fmaf(v[2 * j], rstd, nb), fmaf(v[2 * j + 1], rstd, nb));
        const uint32_t stg = P + 16384 + warp * 1024;
        stsm4(stg + foff, xr[0], xr[1], xr[2], xr[3]);
        stsm4(stg + (foff ^ 64), xr[4], xr[5], xr[6], xr[7]);
        __syncwarp();
        const uint32_t src = stg + (lane >> 3) * 128 + (((lane & 7) ^ (lane >> 3)) << 4);
        const uint4 u0 = lds128(src), u1 = lds128((src + 512) ^ 64);
        __nv_bfloat16* dst = p.out + (size_t)(b * T_ + trow + (lane >> 3)) * 256 + tile * 64 + (lane & 7) * 8;
        if (trow < T_) { stg128(dst, u0); stg128(dst + 4 * 256, u1); }
    }
    TS(25);
    TG(31);
    TSDUMP();
    cluster_wait();
}

typedef CUresult (*EncodeFn)(CUtensorMap*, CUtensorMapDataType, cuuint32_t, void*, const cuuint64_t*, const cuuint64_t*,
                             const cuuint32_t*, const cuuint32_t*, CUtensorMapInterleave, CUtensorMapSwizzle,
                             CUtensorMapL2promotion, CUtensorMapFloatOOBfill);

}

extern "C" void kernel_launch(void* const* d_in, const int* in_sizes, int n_in, void* d_out, int out_size) {
    static EncodeFn encode = nullptr;
    if (!encode) {
        void* fn = nullptr;
        cudaDriverEntryPointQueryResult qr;
        cudaGetDriverEntryPoint("cuTensorMapEncodeTiled", &fn, cudaEnableDefault, &qr);
        encode = (EncodeFn)fn;
        cudaFuncSetAttribute(conformer_kernel, cudaFuncAttributeMaxDynamicSharedMemorySize, SMEM_LAUNCH);
    }
    Scalars p;
    Maps m;
    const cuuint32_t ones[5] = {1, 1, 1, 1, 1};
    const int idx[8] = {1, 2, 3, 4, 5, 7, 8, 9};
    const int rows[8] = {256, 1024, 256, 256, 256, 256, 256, 1024};
    const int cols[8] = {1024, 256, 768, 256, 512, 256, 1024, 256};
    for (int i = 0; i < 8; i++) {
        const cuuint64_t pitch = (cuuint64_t)cols[i] * 2;
        const bool f = i != 0 && i != 3;
        const cuuint64_t dims[5] = {(cuuint64_t)cols[i], f ? 2u : 4u, f ? 2u : 4u, f ? 4u : 2u, (cuuint64_t)rows[i] / (f ? 16 : 32)};
        const cuuint64_t strides[4] = {pitch, pitch * 8, pitch * (f ? 2 : 4), pitch * (f ? 16 : 32)};
        const cuuint32_t box[5] = {64, f ? 2u : 4u, f ? 2u : 4u, f ? 4u : 2u, f ? 8u : 4u};
        encode(&m.tm[i], CU_TENSOR_MAP_DATA_TYPE_BFLOAT16, 5, d_in[idx[i]], dims, strides, box, ones, CU_TENSOR_MAP_INTERLEAVE_NONE,
               CU_TENSOR_MAP_SWIZZLE_128B, CU_TENSOR_MAP_L2_PROMOTION_L2_128B, CU_TENSOR_MAP_FLOAT_OOB_FILL_NONE);
        m.w[i] = (const char*)d_in[idx[i]];
    }
    {
        void* kv = nullptr;
        cudaGetSymbolAddress(&kv, g_kvq);
        const cuuint64_t dims[2] = {64, 16384};
        const cuuint64_t strides[1] = {128};
        const cuuint32_t box[2] = {64, 128};
        encode(&m.tm[8], CU_TENSOR_MAP_DATA_TYPE_BFLOAT16, 2, kv, dims, strides, box, ones, CU_TENSOR_MAP_INTERLEAVE_NONE,
               CU_TENSOR_MAP_SWIZZLE_NONE, CU_TENSOR_MAP_L2_PROMOTION_L2_128B, CU_TENSOR_MAP_FLOAT_OOB_FILL_NONE);
    }
    p.x = (const __nv_bfloat16*)d_in[0];
    p.dw = (const __nv_bfloat16*)d_in[6];
    p.out = (__nv_bfloat16*)d_out;
    p.zero = 0;
    conformer_kernel<<<NCTA, NTHREADS, SMEM_LAUNCH>>>(p, m);
}
```

```cpp
#include <cuda_runtime.h>
#include <cuda_bf16.h>
#include <cuda.h>
#include <stdint.h>

namespace {

constexpr int T_ = 1000;
constexpr int NCTA = 128;
constexpr int NTHREADS = 512;
constexpr int NSLOT = 5;
constexpr int SLOT = 16384;
constexpr int NLOADS = 56;

constexpr uint32_t OFF_RING = 0;
constexpr uint32_t OFF_P = 163840;
constexpr uint32_t OFF_H = 188416;
constexpr uint32_t OFF_MISC = 221184;
constexpr uint32_t OFF_BARS = 229888;
constexpr uint32_t SMEM_BYTES = 230400;
constexpr uint32_t GCH = 6144;
constexpr uint32_t HCH = 4096;

constexpr int B_FULL = 0, B_EMPTY = 10, B_XA = 20  , B_XB = 25  , B_INB = 29  , B_SR = 33,
              B_RST = 34, B_RDY = 35  , B_SINK = 41, B_HALO = 42  , NBARS = 46;

#define KD2 300u
#define KD3 500u
#define QGATE 700u
#define BACKOFF 0u
#define KFS 8
#define KDELAY 250u
#define NJ0 2
#define HDELAY 200u
#define LATE 3
#define SND 0
#define PF0 0
#define TWO 1
#define WARMF 1
#define SPLIT 0
#define MRG 0
#define TURN 0x200
#define EAGER 0x0155
constexpr int FS = 8;

struct Scalars {
    const __nv_bfloat16* x;
    const __nv_bfloat16* dw;
    __nv_bfloat16* out;
    uint32_t zero;
};
struct Maps {
    CUtensorMap tm[9];
    const char* w[8];
};

__device__ __align__(1024) unsigned char g_kvq[3 * 8 * 1024 * 128];
__device__ __align__(1024) unsigned char g_o[2 * 128 * 4096];
__device__ uint4 g_halo[64 * 4 * 2 * 64];
__device__ __align__(128) uint32_t g_flag_kv[8 * 32 * KFS];
__device__ uint32_t g_reset[2 * 32];
__device__ uint32_t g_epoch[NCTA * FS];

#define TS(i) do { } while (0)
#define TSW(i) do { } while (0)
#define TG(i) do { } while (0)
#define TSINIT() do { } while (0)
#define TSDUMP() do { } while (0)
constexpr uint32_t SMEM_LAUNCH = SMEM_BYTES;

__device__ __forceinline__ uint32_t smem_u32(const void* p) { return (uint32_t)__cvta_generic_to_shared(p); }
__device__ __forceinline__ void mbar_init(uint32_t b, uint32_t c) { asm volatile("mbarrier.init.shared::cta.b64 [%0], %1;" ::"r"(b), "r"(c) : "memory"); }
__device__ __forceinline__ void mbar_arrive(uint32_t b) { asm volatile("mbarrier.arrive.shared::cta.b64 _, [%0];" ::"r"(b) : "memory"); }
__device__ __forceinline__ void mbar_arrive_tx(uint32_t b, uint32_t tx) { asm volatile("mbarrier.arrive.expect_tx.shared::cta.b64 _, [%0], %1;" ::"r"(b), "r"(tx) : "memory"); }
__device__ __forceinline__ void mbar_wait(uint32_t b, uint32_t ph) {
    asm volatile("{\n.reg .pred p, q;\n.reg .u32 c;\nmov.u32 c, 0;\n"
                 "MW_LOOP:\n.pragma \"nounroll\";\n"
                 "mbarrier.try_wait.parity.shared::cta.b64 p, [%0], %1;\n"
                 "add.u32 c, c, 1;\nsetp.lt.u32 q, c, 65536;\nnot.pred p, p;\nand.pred p, p, q;\n@p bra MW_LOOP;\n}"
                 ::"r"(b), "r"(ph) : "memory");
}
__device__ __forceinline__ bool mbar_test(uint32_t b, uint32_t ph) {
    uint32_t ok;
    asm volatile("{\n.reg .pred p;\nmbarrier.test_wait.parity.shared::cta.b64 p, [%1], %2;\nselp.u32 %0, 1, 0, p;\n}" : "=r"(ok) : "r"(b), "r"(ph) : "memory");
    return ok;
}
__device__ __forceinline__ uint32_t mapa(uint32_t a, uint32_t r) { uint32_t o; asm("mapa.shared::cluster.u32 %0, %1, %2;" : "=r"(o) : "r"(a), "r"(r)); return o; }
__device__ __forceinline__ void fence_async_smem() { asm volatile("fence.proxy.async.shared::cta;" ::: "memory"); }
__device__ __forceinline__ void fence_async_global() { asm volatile("fence.proxy.async.global;" ::: "memory"); }
__device__ __forceinline__ void bar_sync(int id, int n) { asm volatile("bar.sync %0, %1;" ::"r"(id), "r"(n) : "memory"); }
__device__ __forceinline__ void bar_arrive(int id, int n) { asm volatile("bar.arrive %0, %1;" ::"r"(id), "r"(n) : "memory"); }
__device__ __forceinline__ void cluster_arrive() { asm volatile("barrier.cluster.arrive.relaxed.aligned;" ::: "memory"); }
__device__ __forceinline__ void cluster_wait() { asm volatile("barrier.cluster.wait.aligned;" ::: "memory"); }

__device__ __forceinline__ void ring_load(uint32_t dst, const CUtensorMap* tm, int col, int row16, uint32_t bar) {
    asm volatile("{\n.reg .pred p;\nelect.sync _|p, 0xffffffff;\n"
                 "@p mbarrier.arrive.expect_tx.shared::cta.b64 _, [%2], 16384;\n"
                 "@p cp.async.bulk.tensor.5d.shared::cluster.global.mbarrier::complete_tx::bytes [%0], [%1, {%3, 0, 0, 0, %4}], [%2];\n}"
                 ::"r"(dst), "l"(tm), "r"(bar), "r"(col), "r"(row16) : "memory");
}
__device__ __forceinline__ void ring_load_both(uint32_t dst, const CUtensorMap* tm, int c1, uint32_t bar) {
    asm volatile("{\n.reg .pred p;\nelect.sync _|p, 0xffffffff;\n"
                 "@p cp.async.bulk.tensor.2d.shared::cluster.global.mbarrier::complete_tx::bytes.multicast::cluster [%0], [%1, {0, %3}], [%2], %4;\n}"
                 ::"r"(dst), "l"(tm), "r"(bar), "r"(c1), "h"((uint16_t)3) : "memory");
}
__device__ __forceinline__ void mbar_arrive_peer(uint32_t b) { asm volatile("mbarrier.arrive.relaxed.cluster.shared::cluster.b64 _, [%0];" ::"r"(b) : "memory"); }
__device__ __forceinline__ void prefetch_l2(const void* src, uint32_t bytes) {
    asm volatile("cp.async.bulk.prefetch.L2.global [%0], %1;" ::"l"(src), "r"(bytes) : "memory");
}
__device__ __forceinline__ void peer_copy(uint32_t dst, uint32_t src, uint32_t bytes, uint32_t rbar) {
    asm volatile("{\n.reg .pred p;\nelect.sync _|p, 0xffffffff;\n"
                 "@p cp.async.bulk.shared::cluster.shared::cta.mbarrier::complete_tx::bytes [%0], [%1], %2, [%3];\n}"
                 ::"r"(dst), "r"(src), "r"(bytes), "r"(rbar) : "memory");
}
__device__ __forceinline__ void st_async4(uint32_t dst, uint32_t a, uint32_t b, uint32_t c, uint32_t d, uint32_t bar) {
    asm volatile("st.async.shared::cluster.mbarrier::complete_tx::bytes.v4.b32 [%0], {%1,%2,%3,%4}, [%5];" ::"r"(dst), "r"(a), "r"(b), "r"(c), "r"(d), "r"(bar) : "memory");
}
__device__ __forceinline__ void put_sums(uint32_t dst, uint32_t rdst, float a, float b, uint32_t rbar, bool on) {
    asm volatile("{\n.reg .pred p;\nsetp.ne.u32 p, %5, 0;\n"
                 "@p st.async.shared::cluster.mbarrier::complete_tx::bytes.v2.f32 [%1], {%2,%3}, [%4];\n"
                 "@p st.shared.v2.f32 [%0], {%2,%3};\n}" ::"r"(dst), "r"(rdst), "f"(a), "f"(b), "r"(rbar), "r"((uint32_t)on) : "memory");
}
__device__ __forceinline__ void stsm4(uint32_t a, uint32_t r0, uint32_t r1, uint32_t r2, uint32_t r3) {
    asm volatile("stmatrix.sync.aligned.m8n8.x4.shared.b16 [%0], {%1,%2,%3,%4};" ::"r"(a), "r"(r0), "r"(r1), "r"(r2), "r"(r3) : "memory");
}
__device__ __forceinline__ void ldsm4(uint32_t a, uint32_t& r0, uint32_t& r1, uint32_t& r2, uint32_t& r3) {
    asm volatile("ldmatrix.sync.aligned.m8n8.x4.shared.b16 {%0,%1,%2,%3}, [%4];" : "=r"(r0), "=r"(r1), "=r"(r2), "=r"(r3) : "r"(a) : "memory");
}
__device__ __forceinline__ uint4 lds128(uint32_t a) { uint4 v; asm volatile("ld.shared.v4.b32 {%0,%1,%2,%3}, [%4];" : "=r"(v.x), "=r"(v.y), "=r"(v.z), "=r"(v.w) : "r"(a) : "memory"); return v; }
__device__ __forceinline__ float4 lds128f(uint32_t a) { float4 v; asm volatile("ld.shared.v4.f32 {%0,%1,%2,%3}, [%4];" : "=f"(v.x), "=f"(v.y), "=f"(v.z), "=f"(v.w) : "r"(a) : "memory"); return v; }
__device__ __forceinline__ float2 lds64f(uint32_t a) { float2 v; asm volatile("ld.shared.v2.f32 {%0,%1}, [%2];" : "=f"(v.x), "=f"(v.y) : "r"(a) : "memory"); return v; }
__device__ __forceinline__ uint32_t lds32(uint32_t a) { uint32_t v; asm volatile("ld.shared.b32 %0, [%1];" : "=r"(v) : "r"(a) : "memory"); return v; }
__device__ __forceinline__ void sts128(uint32_t a, uint32_t x, uint32_t y, uint32_t z, uint32_t w) { asm volatile("st.shared.v4.b32 [%0], {%1,%2,%3,%4};" ::"r"(a), "r"(x), "r"(y), "r"(z), "r"(w) : "memory"); }
__device__ __forceinline__ void sts128f(uint32_t a, float x, float y, float z, float w) { asm volatile("st.shared.v4.f32 [%0], {%1,%2,%3,%4};" ::"r"(a), "f"(x), "f"(y), "f"(z), "f"(w) : "memory"); }
__device__ __forceinline__ void sts64f(uint32_t a, float x, float y) { asm volatile("st.shared.v2.f32 [%0], {%1,%2};" ::"r"(a), "f"(x), "f"(y) : "memory"); }
__device__ __forceinline__ void sts32(uint32_t a, uint32_t x) { asm volatile("st.shared.b32 [%0], %1;" ::"r"(a), "r"(x) : "memory"); }
__device__ __forceinline__ void stg128(void* p, uint4 v) { asm volatile("st.global.v4.b32 [%0], {%1,%2,%3,%4};" ::"l"(p), "r"(v.x), "r"(v.y), "r"(v.z), "r"(v.w) : "memory"); }

__device__ __forceinline__ uint32_t pack2(float lo, float hi) { uint32_t r; asm("cvt.rn.bf16x2.f32 %0, %1, %2;" : "=r"(r) : "f"(hi), "f"(lo)); return r; }
__device__ __forceinline__ float blo(uint32_t v) { return __uint_as_float(v << 16); }
__device__ __forceinline__ float bhi(uint32_t v) { return __uint_as_float(v & 0xffff0000u); }
__device__ __forceinline__ uint32_t hmul2(uint32_t a, uint32_t b) { uint32_t r; asm("mul.rn.bf16x2 %0, %1, %2;" : "=r"(r) : "r"(a), "r"(b)); return r; }
__device__ __forceinline__ uint32_t hadd2(uint32_t a, uint32_t b) { uint32_t r; asm("add.rn.bf16x2 %0, %1, %2;" : "=r"(r) : "r"(a), "r"(b)); return r; }
__device__ __forceinline__ uint32_t hsub2(uint32_t a, uint32_t b) { uint32_t r; asm("sub.rn.bf16x2 %0, %1, %2;" : "=r"(r) : "r"(a), "r"(b)); return r; }
__device__ __forceinline__ uint32_t hfma2(uint32_t a, uint32_t b, uint32_t c) { uint32_t r; asm("fma.rn.bf16x2 %0, %1, %2, %3;" : "=r"(r) : "r"(a), "r"(b), "r"(c)); return r; }
__device__ __forceinline__ float tanh_fast(float x) { float r; asm("tanh.approx.f32 %0, %1;" : "=f"(r) : "f"(x)); return r; }
__device__ __forceinline__ float rsq(float x) { float r; asm("rsqrt.approx.ftz.f32 %0, %1;" : "=f"(r) : "f"(x)); return r; }
__device__ __forceinline__ float rcp(float x) { float r; asm("rcp.approx.ftz.f32 %0, %1;" : "=f"(r) : "f"(x)); return r; }
__device__ __forceinline__ float ex2(float x) { float r; asm("ex2.approx.ftz.f32 %0, %1;" : "=f"(r) : "f"(x)); return r; }

__device__ __forceinline__ uint32_t ld_relaxed(const uint32_t* p) {
    uint32_t v;
    asm volatile("ld.relaxed.gpu.global.u32 %0, [%1];" : "=r"(v) : "l"(p) : "memory");
    return v;
}
__device__ __forceinline__ uint32_t clock32() { uint32_t c; asm volatile("mov.u32 %0, %%clock;" : "=r"(c)::"memory"); return c; }
__device__ __forceinline__ void spin(uint32_t clks) {
    const uint32_t t0 = clock32();
    while (clock32() - t0 < clks) {}
}
__device__ __forceinline__ void flag_wait(const uint32_t* p, uint32_t e, bool mine) {
#pragma unroll 1
    for (int i = 0; i < (1 << 19); i++) {
        if (mine) mine = ld_relaxed(p) != e;
        if (!__any_sync(~0u, mine)) break;
        if (BACKOFF) spin(BACKOFF);
    }
    asm volatile("fence.acquire.gpu;" ::: "memory");
    fence_async_global();
}
__device__ __forceinline__ void st_data(void* p, uint32_t x, uint32_t y, uint32_t z, uint32_t w) {
    asm volatile("st.relaxed.gpu.global.v4.b32 [%0], {%1,%2,%3,%4};" ::"l"(p), "r"(x), "r"(y), "r"(z), "r"(w) : "memory");
}
template <int STRIDE, bool INV = false, int N>
__device__ __forceinline__ void ld_data(uint4 (&v)[N], const unsigned char* p) {
    int it = 0;
    bool again;
#pragma unroll 1
    do {
        uint32_t m = INV ? ~0u : 0u;
#pragma unroll
        for (int i = 0; i < N; i++)
            asm volatile("ld.relaxed.gpu.global.v4.b32 {%0,%1,%2,%3}, [%4];" : "=r"(v[i].x), "=r"(v[i].y), "=r"(v[i].z), "=r"(v[i].w) : "l"(p + i * STRIDE) : "memory");
#pragma unroll
        for (int i = 0; i < N; i++)
            m = INV ? __vimin3_u32(__vimin3_u32(v[i].x, v[i].y, v[i].z), v[i].w, m) : __vimax3_u32(__vimax3_u32(v[i].x, v[i].y, v[i].z), v[i].w, m);
        again = __any_sync(~0u, m == (INV ? 0u : ~0u)) && ++it < (1 << 16);
    } while (again);
}
__device__ __forceinline__ uint32_t ld_epoch() { return ld_relaxed(&g_epoch[blockIdx.x * FS]) + 1; }
__device__ __forceinline__ void flag_set(uint32_t* p, uint32_t e) { asm volatile("st.release.gpu.global.u32 [%0], %1;" ::"l"(p), "r"(e) : "memory"); }

__device__ __forceinline__ uint32_t desc_lo(uint32_t addr) { return ((addr & 0x3FFFF) >> 4) | 0x10000u; }
__device__ __forceinline__ uint64_t mkdesc(uint32_t lo) { return (uint64_t)lo | (0x40000040ull << 32); }
__device__ __forceinline__ void wg_fence() { asm volatile("wgmma.fence.sync.aligned;" ::: "memory"); }
__device__ __forceinline__ void wg_commit() { asm volatile("wgmma.commit_group.sync.aligned;" ::: "memory"); }
template <int N> __device__ __forceinline__ void wg_wait() { asm volatile("wgmma.wait_group.sync.aligned %0;" ::"n"(N) : "memory"); }
template <int N> __device__ __forceinline__ void pin(float (&d)[N]) {
#pragma unroll
    for (int i = 0; i < N; i++) asm volatile("" : "+f"(d[i])::"memory");
}
template <int N> __device__ __forceinline__ void pin(uint32_t (&d)[N]) {
#pragma unroll
    for (int i = 0; i < N; i++) asm volatile("" : "+r"(d[i])::"memory");
}

template <typename Tp, int N> __device__ __forceinline__ void zero(Tp (&d)[N]) {
#pragma unroll
    for (int i = 0; i < N; i++) d[i] = 0;
    pin(d);
}

#define F4(d, i) "+f"(d[i]), "+f"(d[i + 1]), "+f"(d[i + 2]), "+f"(d[i + 3])
#define F16(d, i) F4(d, i), F4(d, i + 4), F4(d, i + 8), F4(d, i + 12)

__device__ __forceinline__ void mma16(float (&d)[4], const uint32_t* a, uint32_t b0, uint32_t b1) {
    asm("mma.sync.aligned.m16n8k16.row.col.f32.bf16.bf16.f32 {%0,%1,%2,%3}, {%4,%5,%6,%7}, {%8,%9}, {%0,%1,%2,%3};"
        : F4(d, 0) : "r"(a[0]), "r"(a[1]), "r"(a[2]), "r"(a[3]), "r"(b0), "r"(b1));
}
template <int N>
__device__ __forceinline__ float row_sum(const uint32_t* x, uint32_t ones = 0x3F803F80u) {
    float c[4] = {};
#pragma unroll
    for (int i = 0; i < N; i += 4) mma16(c, x + i, ones, ones);
    return c[0] + c[2];
}
template <int N>
__device__ __forceinline__ float row_sumsq(const uint32_t* x, int lane) {
    float c0[4] = {}, c1[4] = {};
#pragma unroll
    for (int i = 0; i < N; i += 4) {
        mma16(c0, x + i, x[i], x[i + 2]);
        mma16(c1, x + i, x[i + 1], x[i + 3]);
    }
    return (lane & 4) ? c0[1] + c1[3] : c0[0] + c1[2];
}
__device__ __forceinline__ void mma_sp(float (&d)[32], const uint32_t* a, uint64_t b, uint32_t meta, int acc) {
    asm volatile("{.reg .pred p; setp.ne.b32 p, %38, 0;\n"
                 "wgmma.mma_async.sp.sync.aligned.m64n64k32.f32.bf16.bf16 {%0,%1,%2,%3,%4,%5,%6,%7,%8,%9,%10,%11,%12,%13,%14,%15,%16,%17,%18,%19,%20,%21,%22,%23,%24,%25,%26,%27,%28,%29,%30,%31}, "
                 "{%32,%33,%34,%35}, %36, %37, 0, p, 1, 1, 1;}\n"
                 : F16(d, 0), F16(d, 16) : "r"(a[0]), "r"(a[1]), "r"(a[2]), "r"(a[3]), "l"(b), "r"(meta), "r"(acc));
}
__device__ __forceinline__ void mma_qk(float (&d)[32], uint32_t a0, uint32_t a1, uint32_t a2, uint32_t a3, uint64_t b, int acc) {
    asm volatile("{.reg .pred p; setp.ne.b32 p, %37, 0;\n"
                 "wgmma.mma_async.sync.aligned.m64n64k16.f32.bf16.bf16 {%0,%1,%2,%3,%4,%5,%6,%7,%8,%9,%10,%11,%12,%13,%14,%15,%16,%17,%18,%19,%20,%21,%22,%23,%24,%25,%26,%27,%28,%29,%30,%31}, "
                 "{%32,%33,%34,%35}, %36, p, 1, 1, 0;}\n"
                 : F16(d, 0), F16(d, 16) : "r"(a0), "r"(a1), "r"(a2), "r"(a3), "l"(b), "r"(acc));
}
__device__ __forceinline__ void mma_pv(float (&d)[36], uint32_t a0, uint32_t a1, uint32_t a2, uint32_t a3, uint64_t b) {
    asm volatile("wgmma.mma_async.sync.aligned.m64n72k16.f32.bf16.bf16 {%0,%1,%2,%3,%4,%5,%6,%7,%8,%9,%10,%11,%12,%13,%14,%15,%16,%17,%18,%19,%20,%21,%22,%23,%24,%25,%26,%27,%28,%29,%30,%31,%32,%33,%34,%35}, "
                 "{%36,%37,%38,%39}, %40, 1, 1, 1, 1;\n"
                 : F16(d, 0), F16(d, 16), F4(d, 32) : "r"(a0), "r"(a1), "r"(a2), "r"(a3), "l"(b));
}

__device__ __forceinline__ uint32_t load_code(int n, int r, int w) {
    const int tile = 2 * r + w;
    int m, col, row;
    if (n < 16 || n >= 40) {
        const int k = n < 16 ? n : n - 40;
        m = n < 16 ? 0 : 6;
        if (TWO && n >= 40 && k < 4) { col = 4 * tile + (k & 1); row = (k >> 1) ^ r; }
        else if (k < 8) { col = 4 * tile + (k >> 1); row = n < 16 ? (k & 1) : (k & 1) ^ r; }
        else { m++; col = k < 12 ? tile ^ 2 : tile; row = 2 * (tile ^ (k & 1)) + ((k >> 1) & 1); }
    } else if (n < 32) {
        const int k = n - 16;
        m = 2;
        if (k < 4) { col = tile + ((k & 1) ? 8 : 4); row = (k >> 1) ^ r; }
        else { col = tile; row = (k & 1) ^ r; }
    } else if (n < 34) { m = 3; col = tile; row = n - 32; }
    else if (n < 38) { const int k = n - 34; m = 4; col = tile + 4 * (k & 1); row = (k >> 1) ^ r; }
    else { m = 5; col = tile; row = (n & 1) ^ r; }
    return m | (col << 4) | (row << ((m == 0 || m == 3) ? 10 : 11));
}

__global__ void __cluster_dims__(2, 1, 1) __launch_bounds__(NTHREADS, 1)
conformer_kernel(const Scalars p, const __grid_constant__ Maps m) {
    extern __shared__ __align__(1024) unsigned char smem_raw[];
    const uint32_t sb = smem_u32(smem_raw);
    const uint32_t bars = sb + OFF_BARS;
    const int tid = threadIdx.x;
    const int lane = tid & 31;
    const int warp = __shfl_sync(~0u, tid >> 5, 0);
    const int r = blockIdx.x & 1;
    const int pair = blockIdx.x >> 1;
    const int b = pair >> 5, pt = pair & 31;
    const int ah = pt >> 3, qt = (pt & 7) * 2 + r;
    const int abh = b * 4 + ah;

    TG(30);
    TSINIT();
    TS(0);
    const uint32_t P = sb + OFF_P, H = sb + OFF_H;
    if (warp == 11) {
        if (lane == 0) {
#pragma unroll
            for (int i = 0; i < 2 * NSLOT; i++) mbar_init(bars + (B_FULL + i) * 8, 1);
            asm volatile("fence.mbarrier_init.release.cluster;" ::: "memory");
            fence_async_smem();
        }
        __syncwarp();
        bar_arrive(13, 96);
        cluster_arrive();
    }

    if (warp >= 8) {
        asm volatile("setmaxnreg.dec.sync.aligned.u32 48;");
        if (warp >= 12) {
            cluster_arrive();
            cluster_wait();
            const int ut = tid & 127;
            const uint32_t target = ld_epoch() * 64;
            bar_sync(6, 384);
#pragma unroll
            for (int i = 0; i < 4; i++) {
                st_data(g_o + (size_t)(b * 128 + qt * 8 + 2 * i + (ut >> 6)) * 4096 + ah * 1024 + (ut & 63) * 16, ~0u, ~0u, ~0u, ~0u);
                if (i < 2) st_data(&g_halo[(pair * 4 + 2 * r + i) * 128 + ut], ~0u, ~0u, ~0u, ~0u);
            }
            bar_sync(11, 128);
            if (ut == 0) {
                asm volatile("red.release.gpu.global.add.u32 [%0], 1;" ::"l"(&g_reset[b * 32]) : "memory");
#pragma unroll 1
                for (int i = 0; i < (1 << 20) && ld_relaxed(&g_reset[b * 32]) != target; i++) __nanosleep(100);
                asm volatile("fence.acquire.gpu;" ::: "memory");
                mbar_arrive(bars + B_RST * 8);
            }
            bar_sync(11, 128);
            TS(14);
#pragma unroll
            for (int i = 0; i < 4; i++) st_data(g_kvq + 2097152 + (size_t)(abh * 1024 + qt * 64) * 128 + i * 2048 + ut * 16, 0, 0, 0, 0);
            const int side = warp & 1, wg = (warp >> 1) & 1, np = side ? pt + 1 : pt - 1;
            const unsigned char* src = reinterpret_cast<const unsigned char*>(&g_halo[(((b * 32 + np) * 4 + 2 * r + wg) * 2 + (side ^ 1)) * 64 + lane]);
            const uint32_t dst = H + 16384 + wg * GCH + side * 5120 + (lane & 7) * 128 + (((lane >> 3) ^ (lane & 7)) << 4);
            uint4 hv[2] = {make_uint4(0, 0, 0, 0), make_uint4(0, 0, 0, 0)};
            bar_sync(8 + wg, 192);
            if (np >= 0 && np < 32) {
                spin(HDELAY);
                ld_data<512>(hv, src);
            }
            stsm4(dst, hv[0].x, hv[0].y, hv[0].z, hv[0].w);
            stsm4(dst ^ 64, hv[1].x, hv[1].y, hv[1].z, hv[1].w);
            __syncwarp();
            if (lane == 0) mbar_arrive(bars + (B_HALO + (warp & 3)) * 8);
            TS(4);
        } else if (warp < 10) {
            const int w = warp - 8;
            const uint32_t ring = sb + OFF_RING + w * NSLOT * SLOT;
            const uint32_t full = bars + (B_FULL + w * NSLOT) * 8;
            cluster_arrive();
            bar_sync(13, 96);
            TS(1);
#pragma unroll
            for (int n = 0; n < NSLOT; n++) {
                if (n == 1) bar_sync(12, 64);
                ring_load(ring + n * SLOT, &m.tm[0], 64 * (8 * r + 4 * w + (n >> 1)), 4 * (n & 1), full + n * 8);
            }
            TS(2);
            const uint32_t code = load_code(lane, r, w) | (load_code(lane + 32, r, w) << 16);
            cluster_wait();
            uint32_t s = 0, ph = 0;
            int n = NSLOT;
#pragma unroll 1
            for (int seg = 0; seg < 2; seg++) {
#pragma unroll 1
                for (; n < (seg == 0 ? 22 : NLOADS); n++) {
                    const uint32_t c = __shfl_sync(~0u, code, n) >> (n & 32 ? 16 : 0);
                    const CUtensorMap* tm = &m.tm[c & 15];
                    const uint32_t col = (c & 0xf0) * 4, row = (c & 0xff00) >> 8, dst = ring + s * SLOT;
                    mbar_wait(full + (B_EMPTY - B_FULL) * 8 + s * 8, ph + (((uint32_t)(size_t)tm | col | row | dst) & p.zero));
                    ring_load(dst, tm, col, row, full + s * 8);
                    if (++s == NSLOT) { s = 0; ph ^= 1; }
                }
                if (seg == 1) break;
                const uint32_t epoch = ld_epoch();
                const uint32_t rdy = bars + (B_RDY + 3 * w) * 8, prdy = mapa(rdy, r ^ 1);
                const int odd = r ^ w;
                const uint32_t* flags = g_flag_kv + (abh * 32 + lane) * KFS;
                bool first = (lane >> 2) == 2 * odd + w;
                if (WARMF && first) first = ld_relaxed(flags) != epoch;
                auto kv_load = [&](uint32_t sl, int isv, int i) {
                    ring_load_both(ring + sl * SLOT, &m.tm[8], (isv * 64 + abh * 8 + 2 * i + w) * 128, full + sl * 8);
                };
#pragma unroll 1
                for (int i = 0; i < 2; i++) {
                    if (lane < 3 + i) {
                        const uint32_t sl = i ? lane : lane + 2;
                        mbar_wait(full + (B_EMPTY - B_FULL + sl) * 8, i ^ 1);
                        mbar_arrive_tx(full + sl * 8, (i || lane == 2) ? SLOT : 0);
                    }
                    __syncwarp();
                }
                if (lane == 0) mbar_arrive_peer(prdy);
                bar_sync(14, 96);
                spin(KDELAY);
                mbar_wait(rdy, 0);
                flag_wait(flags, epoch, first);
                TSW(5 + 2 * odd);
                if (!odd) { kv_load(4, 0, 0); bar_arrive(12, 64); }
                else bar_sync(12, 64);
                spin(w ? KD3 : KD2);
                kv_load(odd ^ 1, odd ^ 1, odd);
                flag_wait(flags, epoch, (lane >> 2) == 2 * odd + w + 4);
                mbar_wait(full + (odd ^ 1) * 8, 1);
                kv_load(2 + odd, odd, 2 - odd);
#pragma unroll 1
                for (int i = 0; i < 3; i++) {
                    const uint32_t sl = i ? i - 1 : 4, bo = i == 2 ? 16 : 8;
                    mbar_wait(full + (B_EMPTY - B_FULL + sl) * 8, i != 0);
                    if (lane == 0) mbar_arrive_tx(full + sl * 8, SLOT);
                    if ((i & 1) != odd) {
                        mbar_wait(rdy + bo, 0);
                        kv_load(sl, i != 0, 2 + odd);
                    } else if (lane == 0) mbar_arrive_peer(prdy + bo);
                    __syncwarp();
                }
                n = 32; s = 2; ph = 1;
            }
        } else if (warp == 10) {
            if (lane == 0) {
#pragma unroll
                for (int i = B_EMPTY; i < NBARS; i++) mbar_init(bars + i * 8, i < B_XA ? 4 : 1);
#pragma unroll
                for (int i = B_XA; i <= B_SR; i++) mbar_arrive_tx(bars + i * 8, i < B_XB ? 512 : ((i >= B_INB && i < B_SR) ? 4096 : 8192));
                asm volatile("fence.mbarrier_init.release.cluster;" ::: "memory");
                fence_async_smem();
            }
            __syncwarp();
            cluster_arrive();
            cluster_wait();
        } else {
            const uint32_t kb = (lane < 2 || lane > 5) ? 4096 : (lane == 2 ? 3072 : (lane == 4 ? 2048 : 1024));
            const char* pf = m.w[lane & 7] + blockIdx.x * kb;
            cluster_wait();
            if (lane < PF0) prefetch_l2(pf, kb);
            mbar_wait(bars + B_FULL * 8, 0);
            if (lane >= PF0 && lane < 3) prefetch_l2(pf, kb);
            if (lane >= 1 && lane < 9) asm volatile("prefetch.tensormap [%0];" ::"l"(&m.tm[lane]) : "memory");
            mbar_wait(bars + (B_FULL + 1) * 8, 1);
            if (lane > 2 && lane < 8) prefetch_l2(pf, kb);
            if (lane == 8 && blockIdx.x < 15) prefetch_l2(p.dw + blockIdx.x * 256, 512);
            const uint32_t epoch = ld_epoch();
            bar_sync(4, 288);
            if (lane < 16) flag_set(&g_flag_kv[((b * 4 + 2 * r + (lane >> 3)) * 32 + pt) * KFS + (lane & 7)], epoch);
            __syncwarp();
            bar_arrive(14, 96);
            TSW(8);
        }
        TSDUMP();
        return;
    }

    const int w = warp >> 2, wq = warp & 3;
    const int tile = 2 * r + w;
    const int wt = tid & 127;
    const int c4 = lane & 3;
    const int trow = pt * 32 + 8 * wq;
    uint32_t xr[8];
    uint32_t a[32];
    const char* xrow = reinterpret_cast<const char*>(p.x) + (b * T_ + trow + (lane >> 2)) * 512;
    zero(a);
    if (trow < T_) {
        const char* src = xrow + c4 * 16 + p.zero;
#pragma unroll
        for (int i = 0; i < 8; i++)
            asm volatile("ld.global.nc.v4.b32 {%0,%1,%2,%3}, [%4];" : "=r"(a[4 * i]), "=r"(a[4 * i + 1]), "=r"(a[4 * i + 2]), "=r"(a[4 * i + 3]) : "l"(src + 64 * i));
    }
    cluster_arrive();
    asm volatile("setmaxnreg.inc.sync.aligned.u32 208;");
    const uint32_t rbase = sb + OFF_RING + w * NSLOT * SLOT, fbar = bars + (B_FULL + w * NSLOT) * 8;
    const uint32_t rdesc = desc_lo(rbase);
    auto acq = [&](int n) { mbar_wait(fbar + (n % NSLOT) * 8, (n / NSLOT) & 1); };
    auto rel = [&](int n) { if (lane == 0) mbar_arrive(fbar + (B_EMPTY - B_FULL + n % NSLOT) * 8); };
    const uint32_t foff = (lane & 7) * 128 + (((lane >> 3) ^ (lane & 7)) << 4);
    float v[16];
    const uint32_t xown = __shfl_sync(~0u, P + wt * 16 + tile * 4096, lane), xrem = __shfl_sync(~0u, P + wt * 16 + (r ^ 1) * 8192, lane);
    const uint32_t sbuf = __shfl_sync(~0u, sb + OFF_MISC + 1024 + (8 * wq + (lane >> 2)) * 32, lane);
    const uint32_t sown = __shfl_sync(~0u, sbuf + tile * 8, lane);
    const uint32_t peer = __shfl_sync(~0u, mapa(sb, r ^ 1) - sb, lane);
    const uint32_t hbuf = __shfl_sync(~0u, H + w * 4096 + wt * 16, lane);
    const uint32_t meta = __shfl_sync(~0u, 0xEEEE4444u + p.zero, lane);
    cluster_wait();
    TS(56);
    float mean, msq;
    const int mir = wq < 2 ? 7 : 0;
    uint32_t dwr[15] = {};

#pragma unroll
    for (int ph = 0; ph < 5; ph++) {
        uint4 o0, o1;
        if (ph == 0) {
            const uint32_t one = 0x3F803F80u + ((xown | xrem | sbuf | sown | hbuf | foff | rdesc | fbar) & p.zero);
            mean = ((row_sum<8>(a, one) + row_sum<8>(a + 8, one)) + (row_sum<8>(a + 16, one) + row_sum<8>(a + 24, one))) * (1.f / 256.f);
            TS(57);
        } else {
            const uint32_t xa = bars + (B_XA + ph) * 8;
#pragma unroll
            for (int j = 0; j < 8; j++) xr[j] = pack2(v[2 * j], v[2 * j + 1]);
            const float s = row_sum<8>(xr), q = row_sumsq<8>(xr, lane);
            if (ph < 4) {
                sts128(xown, xr[0], xr[1], xr[2], xr[3]);
                sts128(xown + 2048, xr[4], xr[5], xr[6], xr[7]);
            }
            put_sums(sown, sown + peer, s, q, xa + peer, c4 == (lane >> 3));
            bar_sync(10, 256);
            if (ph < 4) {
                o0 = lds128(xown ^ 4096); o1 = lds128((xown ^ 4096) + 2048);
                st_async4(xown + peer, xr[0], xr[1], xr[2], xr[3], xa + (B_XB - B_XA) * 8 + peer);
                st_async4(xown + peer + 2048, xr[4], xr[5], xr[6], xr[7], xa + (B_XB - B_XA) * 8 + peer);
            }
            TS(57 + ph);
            if (ph == 3) acq(0);
            if (ph == 1) acq(16);
            mbar_wait(xa, 0);
            const float4 u0 = lds128f(sbuf), u1 = lds128f(sbuf + 16);
            mean = ((u0.x + u0.z) + (u1.x + u1.z)) * (1.f / 256.f);
            msq = ((u0.y + u0.w) + (u1.y + u1.w)) * (1.f / 256.f);
        }
        if (ph == 4) break;
        const uint32_t mean2 = pack2(mean, mean);
        auto centre = [&](int i, const uint4& u) {
            a[i] = hsub2(u.x, mean2); a[i + 1] = hsub2(u.y, mean2); a[i + 2] = hsub2(u.z, mean2); a[i + 3] = hsub2(u.w, mean2);
        };
        if (ph == 0) {
#pragma unroll
            for (int j = 0; j < 32; j++) a[j] = hsub2(a[j], mean2);
            zero(xr);
            if (trow < T_) {
                const char* src = xrow + tile * 128 + c4 * 4 + (mean2 & p.zero);
#pragma unroll
                for (int j = 0; j < 8; j++) asm volatile("ld.global.nc.b32 %0, [%1];" : "=r"(xr[j]) : "l"(src + 16 * j));
            }
            mean -= blo(mean2);
            msq = __shfl_sync(~0u, row_sumsq<16>(a, lane) + row_sumsq<16>(a + 16, lane), (lane & 28) + (lane >> 3)) * (1.f / 256.f);
            acq(0);
        } else {
#pragma unroll
            for (int j = 0; j < 8; j++) a[j] = hsub2(xr[j], mean2);
            centre(8, o0); centre(12, o1);
        }
        const float rstd = rsq(fmaxf(fmaf(-mean, mean, msq), 0.f) + 1e-5f);
        auto gather_peer = [&]() {
            mbar_wait(bars + (B_XB + ph) * 8, 0);
#pragma unroll
            for (int i = 0; i < 4; i++) centre(16 + 4 * i, lds128(xrem + i * 2048));
        };
        auto sp = [&](float (&d)[32], int n, const uint32_t* af, int flip, int acc) {
            const uint32_t lo = rdesc + p.zero * (ph * 64 + n + 1) + (n % NSLOT) * (SLOT >> 4);
            const uint64_t b0 = mkdesc(lo + flip * 512), b1 = mkdesc(lo + (flip ^ 1) * 512);
            wg_fence();
            mma_sp(d, af, b0, meta, acc);
            mma_sp(d, af + 4, b0 + 256, meta, 1);
            mma_sp(d, af + 8, b1, meta, 1);
            mma_sp(d, af + 12, b1 + 256, meta, 1);
            wg_commit();
        };
        float d0[32], d1[32];

        if (ph == 0 || ph == 3) {
            uint32_t h[32], ho[32];
            const float rs = 0.5f * rstd;
            const uint32_t inb = bars + (B_INB + (ph & 2) + w) * 8;
            bool ready = true;
            const int eager = ph ? (TWO ? EAGER + 5 : EAGER) : EAGER - 1;
            auto step = [&](float (&d)[32], int n, const uint32_t* af, int flip, int acc, auto work) {
                if (!ready) acq(n);
                if (((TURN >> n) & 1) && w == 1) bar_sync(7, 256);
                sp(d, n, af, flip, acc);
                if (n > 0 && ((TURN >> (n - 1)) & 1) && w == 0) bar_arrive(7, 256);
                if (n < 15) ready = mbar_test(fbar + ((n + 1) % NSLOT) * 8, ((n + 1) / NSLOT) & 1);
                wg_wait<1>();
                if (n > 0 && !((eager >> (n - 1)) & 1)) rel(n - 1);
                const uint32_t tie = work() & p.zero;
                if ((eager >> n) & 1) {
                    if (p.zero < n + ph + 1) wg_wait<0>();
                    if (lane == 0) mbar_arrive(fbar + (B_EMPTY - B_FULL + n % NSLOT) * 8 + tie);
                }
            };
            auto none = []() { return 0u; };
            const int fl = ph ? w : 0;
            auto fetch = [&](int i) {
                if (SPLIT) bar_sync(2 * (i & 1) + (w ^ 1), 256);
                else bar_sync(10, 256);
                const uint4 u0 = lds128((hbuf ^ 4096) + (i & 1) * 8192), u1 = lds128((hbuf ^ 4096) + (i & 1) * 8192 + 2048);
                ho[8 * i] = u0.x; ho[8 * i + 1] = u0.y; ho[8 * i + 2] = u0.z; ho[8 * i + 3] = u0.w;
                ho[8 * i + 4] = u1.x; ho[8 * i + 5] = u1.y; ho[8 * i + 6] = u1.z; ho[8 * i + 7] = u1.w;
                return u0.x | u1.x;
            };
            auto act = [&](float (&d)[32], int i) {
                if (i > 0) fetch(i - 1);
                pin(d);
#pragma unroll
                for (int j = 0; j < 8; j++) {
                    const float u0 = (d[4 * j] + d[4 * j + 2]) * rs, u1 = (d[4 * j + 1] + d[4 * j + 3]) * rs;
                    h[8 * i + j] = pack2(fmaf(u0, tanh_fast(u0), u0), fmaf(u1, tanh_fast(u1), u1));
                }
                sts128(hbuf + (i & 1) * 8192, h[8 * i], h[8 * i + 1], h[8 * i + 2], h[8 * i + 3]);
                sts128(hbuf + (i & 1) * 8192 + 2048, h[8 * i + 4], h[8 * i + 5], h[8 * i + 6], h[8 * i + 7]);
                if (SPLIT) bar_arrive(2 * (i & 1) + w, 256);
                return 0u;
            };
            TS(1 + (ph & 2) * 10);
            if (TWO && ph) {
                step(d0, 0, a, fl, 0, none);
                step(d1, 1, a, fl, 0, [&]() { gather_peer(); return 0u; });
                TS(32);
                step(d0, 2, a + 16, 0, 1, none);
                step(d1, 3, a + 16, 0, 1, [&]() { return act(d0, 0); });
            } else {
                step(d0, 0, a, fl, 0, [&]() { if (ph) gather_peer(); return 0u; });
                TS(32);
                step(d0, 1, a + 16, 0, 1, none);
                step(d1, 2, a, fl, 0, [&]() { return act(d0, 0); });
                step(d1, 3, a + 16, 0, 1, none);
            }
            step(d0, 4, a, fl, 0, [&]() { return act(d1, 1); });
            TS(33);
            step(d0, 5, a + 16, 0, 1, none);
            step(d1, 6, a, fl, 0, [&]() { return act(d0, 2); });
            step(d1, 7, a + 16, 0, 1, none);
            step(d0, 8, h, 0, 0, [&]() { act(d1, 3); return fetch(3); });
            TS(2 + (ph & 2) * 10);
            step(d0, 9, ho, 0, 1, none);
            step(d0, 10, h + 16, 0, 1, none);
            step(d0, 11, ho + 16, 0, 1, none);
            uint32_t pk[8];
            auto pack_out = [&]() {
                pin(d0);
#pragma unroll
                for (int j = 0; j < 8; j++) pk[j] = pack2(d0[4 * j] + d0[4 * j + 2], d0[4 * j + 1] + d0[4 * j + 3]);
            };
            auto send = [&](int i) { st_async4(hbuf + 16384 + i * 2048 + peer, pk[4 * i], pk[4 * i + 1], pk[4 * i + 2], pk[4 * i + 3], inb + peer); };
            step(d1, 12, h, 0, 0, [&]() { pack_out(); if (SND != 1) send(0); if (SND == 0) send(1); return 0u; });
            TS(34);
            step(d1, 13, ho, 0, 1, [&]() { if (SND == 1) send(0); if (SND) send(1); return 0u; });
            step(d1, 14, h + 16, 0, 1, none);
            step(d1, 15, ho + 16, 0, 1, none);
            mbar_wait(inb, 0);
#pragma unroll
            for (int i = 0; i < 2; i++) {
                const uint4 u = lds128(hbuf + 16384 + i * 2048);
                const uint32_t p0[4] = {u.x, u.y, u.z, u.w};
#pragma unroll
                for (int j = 0; j < 4; j++) {
                    v[8 * i + 2 * j] = fmaf(0.5f, blo(p0[j]), blo(xr[4 * i + j]));
                    v[8 * i + 2 * j + 1] = fmaf(0.5f, bhi(p0[j]), bhi(xr[4 * i + j]));
                }
            }
            wg_wait<0>();
            pin(d1);
            rel(15);
            TS(3 + (ph & 2) * 10);
#pragma unroll
            for (int j = 0; j < 8; j++) {
                v[2 * j] = fmaf(0.5f, d1[4 * j] + d1[4 * j + 2], v[2 * j]);
                v[2 * j + 1] = fmaf(0.5f, d1[4 * j + 1] + d1[4 * j + 3], v[2 * j + 1]);
            }
#pragma unroll
            for (int i = 0; i < 15; i++) dwr[i] = 0;
            continue;
        }

        auto residual = [&](int n) {
            wg_wait<1>();
            rel(n);
            wg_wait<0>();
            pin(d0);
            rel(n + 1);
#pragma unroll
            for (int j = 0; j < 8; j++) {
                v[2 * j] = d0[4 * j] + d0[4 * j + 2] + blo(xr[j]);
                v[2 * j + 1] = d0[4 * j + 1] + d0[4 * j + 3] + bhi(xr[j]);
            }
        };

        if (ph == 2) {
            TS(39);
            sp(d0, 34, a, w, 0);
            acq(35);
            sp(d1, 35, a, w, 0);
            acq(36); acq(37);
            gather_peer();
            sp(d0, 36, a + 16, 0, 1);
            sp(d1, 37, a + 16, 0, 1);
            wg_wait<2>();
            rel(34);
            if (!(LATE & 1)) rel(35);
            acq(38);
            const float rs = trow < T_ ? 0.5f * rstd : 0.f;
            wg_wait<0>();
            pin(d0); pin(d1);
            if (!(LATE & 2)) { rel(36); rel(37); }
            TS(18);
            uint32_t pk[8];
#pragma unroll
            for (int j = 0; j < 8; j++) {
                const float u0 = (d0[4 * j] + d0[4 * j + 2]) * rs, u1 = (d0[4 * j + 1] + d0[4 * j + 3]) * rs;
                const float t0 = tanh_fast((d1[4 * j] + d1[4 * j + 2]) * rs), t1 = tanh_fast((d1[4 * j + 1] + d1[4 * j + 3]) * rs);
                pk[j] = pack2(fmaf(u0, t0, u0), fmaf(u1, t1, u1));
            }
            if (wq == 0 || wq == 3) {
                uint4* hp = &g_halo[((pair * 4 + tile) * 2 + (wq & 1)) * 64 + lane];
                st_data(hp, pk[0], pk[1], pk[2], pk[3]);
                st_data(hp + 32, pk[4], pk[5], pk[6], pk[7]);
            }
            const uint32_t gs = H + 16384 + w * GCH + wq * 1024;
            stsm4(gs + 1024 + foff, pk[0], pk[1], pk[2], pk[3]);
            stsm4(gs + 1024 + (foff ^ 64), pk[4], pk[5], pk[6], pk[7]);
            bar_sync(8 + w, 192);
            TS(26);
            uint32_t ca[8], cb[8];
            const int e = (wq & 1) * 4;
            const uint32_t lo = ((mir ^ e) * 144) ^ (lane * 4);
            const int dir = mir ? -1024 : 1024;
            const uint32_t gb = H + 16384 + w * GCH + (mir ? 3072 : 2048) + lo, sown_ = H + tile * HCH, so = sown_ + (mir ? 1024 : 2048) + lo;
            auto finish = [&](int i) {
                const uint32_t c = hadd2(ca[i], cb[i]);
                const float h0 = blo(c), h1 = bhi(c);
                sts32((so + (i >> 2) * dir) ^ ((i & 3) * 144), pack2(fmaf(h0, tanh_fast(h0), h0), fmaf(h1, tanh_fast(h1), h1)));
            };
#pragma unroll
            for (int k = 0; k < 26; k++) {
                if (k == 19) {
#pragma unroll
                    for (int i = 0; i < 4; i++) finish(i);
                    fence_async_smem();
                    bar_sync(2 + w, 128);
                    if (wq == 0) peer_copy(mapa(sown_ + 1024, r ^ 1), sown_ + 1024, 2048, mapa(bars + B_SR * 8, r ^ 1));
                    mbar_wait(bars + (B_HALO + 2 * w + (wq >> 1)) * 8, 0);
                    if (LATE & 1) rel(35);
                    if (LATE & 2) { rel(36); rel(37); }
                    TS(27);
                }
                const uint32_t g = lds32((gb + (((k + 1) & 4) ? ((k + 1) >> 3) + (wq & 1) : ((k + 1) >> 3)) * dir) ^ (((k + 1) & 7) * 144));
#pragma unroll
                for (int i = 0; i < 8; i++) {
                    const int tap = k - (i & 3) - 2 * (i & 4);
                    if (tap == 0) ca[i] = hmul2(g, dwr[0]);
                    else if (tap > 0 && tap < 8) ca[i] = hfma2(g, dwr[tap], ca[i]);
                    else if (tap == 8) cb[i] = hmul2(g, dwr[8]);
                    else if (tap > 8 && tap < 15) cb[i] = hfma2(g, dwr[tap], cb[i]);
                }
            }
#pragma unroll
            for (int i = 4; i < 8; i++) finish(i);
            fence_async_smem();
            bar_sync(12 + (warp >> 1), 64);
            if (wq == 0 || wq == 3) peer_copy(mapa(sown_ + wq * 1024, r ^ 1), sown_ + wq * 1024, 1024, mapa(bars + B_SR * 8, r ^ 1));
            bar_sync(10, 256);
            TS(19);
            auto frags = [&](int i, int half) {
                const uint32_t src = H + 2 * half * HCH + wq * 1024;
#pragma unroll
                for (int k = 0; k < 4; k++) ldsm4(src + (k >> 1) * HCH + (foff ^ ((k & 1) * 64)), a[i + 4 * k], a[i + 4 * k + 1], a[i + 4 * k + 2], a[i + 4 * k + 3]);
            };
            frags(0, r);
            sp(d0, 38, a, 0, 0);
            acq(39);
            mbar_wait(bars + B_SR * 8, 0);
            frags(16, r ^ 1);
            sp(d0, 39, a + 16, 0, 1);
            residual(38);
            TS(20);
            continue;
        }

        {
            TS(11);
            unsigned char* g = g_kvq + (size_t)((b * 4 + tile) * 1024 + trow) * 128;
            const uint32_t uo = (lane >> 2) * 128 + ((c4 ^ (lane >> 2)) << 4);
            auto put = [&](float (&d)[32], int i) {
                pin(d);
                uint32_t pk[8];
#pragma unroll
                for (int j = 0; j < 8; j++) pk[j] = pack2((d[4 * j] + d[4 * j + 2]) * rstd, (d[4 * j + 1] + d[4 * j + 3]) * rstd);
                if (i < 2) {
                    stg128(g + i * 1048576 + uo, make_uint4(pk[0], pk[1], pk[2], pk[3]));
                    stg128(g + i * 1048576 + (uo ^ 64), make_uint4(pk[4], pk[5], pk[6], pk[7]));
                } else {
                    const uint32_t stg = H + warp * 1024;
                    sts128(stg + uo, pk[0], pk[1], pk[2], pk[3]);
                    sts128(stg + (uo ^ 64), pk[4], pk[5], pk[6], pk[7]);
                    __syncwarp();
                    ldsm4(stg + foff, pk[0], pk[1], pk[2], pk[3]);
                    ldsm4(stg + (foff ^ 64), pk[4], pk[5], pk[6], pk[7]);
                    st_data(g + 2097152 + lane * 16, ~pk[0], ~pk[1], ~pk[2], ~pk[3]);
                    st_data(g + 2097152 + 512 + lane * 16, ~pk[4], ~pk[5], ~pk[6], ~pk[7]);
                }
            };
            sp(d0, 16, a, w, 0);
            acq(17);
            sp(d1, 17, a, w, 0);
            gather_peer();
            acq(18);
            sp(d0, 18, a + 16, 0, 1);
            wg_wait<1>();
            rel(16); rel(17);
            acq(19);
            sp(d1, 19, a + 16, 0, 1);
            wg_wait<1>();
            rel(18);
            put(d0, 0);
            wg_wait<0>();
            rel(19);
            TS(37);
            put(d1, 1);
            bar_arrive(4, 288);
            TS(38);
            acq(20);
            sp(d0, 20, a, w, 0);
            acq(21);
            sp(d0, 21, a + 16, 0, 1);
            acq(22); acq(23);
            rel(22); rel(23);
            wg_wait<0>();
            rel(20); rel(21);
            put(d0, 2);
            TS(12);
        }

        {
            constexpr float CS = 0.125f * 1.4426950408889634f;
            float sa[32], sb2[32], o[36];
            uint32_t pa[16], pb[16], q[16];
            float n0 = INFINITY, n1 = INFINITY;
            zero(o); zero(pa); zero(pb); zero(sb2);
            const uint32_t ones = sb + OFF_MISC + 2048;
            { const uint32_t c = w ? 0u : 0x3F803F80u; sts128(ones + tid * 16, c, c, c, c); }
            fence_async_smem();
            bar_sync(10, 256);
            const uint32_t vdesc = rdesc + ((((ones - rbase) >> 4) - 1) << 16);
            auto qk_issue = [&](float (&s)[32], uint32_t lo) {
                const uint64_t kd = mkdesc(lo);
                wg_fence();
#pragma unroll
                for (int k = 0; k < 4; k++) mma_qk(s, q[4 * k], q[4 * k + 1], q[4 * k + 2], q[4 * k + 3], kd + 2 * k, k != 0);
                wg_commit();
            };
            auto both_issue = [&](float (&s)[32], uint32_t klo, uint32_t (&pp)[16], uint32_t vlo) {
                const uint64_t kd = mkdesc(klo), vd = mkdesc(vlo);
                wg_fence();
#pragma unroll
                for (int k = 0; k < 4; k++) {
                    mma_pv(o, pp[4 * k], pp[4 * k + 1], pp[4 * k + 2], pp[4 * k + 3], vd - k * (128 * 65535));
                    mma_qk(s, q[4 * k], q[4 * k + 1], q[4 * k + 2], q[4 * k + 3], kd + 2 * k, k != 0);
                }
                wg_commit();
            };
            auto new_max = [&](float (&s)[32], int nj, float& x0, float& x1) {
                x0 = s[0]; x1 = s[2];
#pragma unroll
                for (int j = 0; j < nj; j++) {
                    x0 = fmaxf(x0, fmaxf(s[4 * j], s[4 * j + 1]));
                    x1 = fmaxf(x1, fmaxf(s[4 * j + 2], s[4 * j + 3]));
                }
                x0 = fmaxf(x0, __shfl_xor_sync(~0u, x0, 1)); x1 = fmaxf(x1, __shfl_xor_sync(~0u, x1, 1));
                x0 = fmaxf(x0, __shfl_xor_sync(~0u, x0, 2)); x1 = fmaxf(x1, __shfl_xor_sync(~0u, x1, 2));
                x0 = fminf(n0, fmaf(x0, -CS, -20.f)); x1 = fminf(n1, fmaf(x1, -CS, -20.f));
            };
            auto probs = [&](float (&s)[32], uint32_t (&pp)[16], bool ready, bool tail, auto wait) {
                uint32_t any = 0;
#pragma unroll
                for (int i = 0; i < 16; i++) {
                    pp[i] = pack2(ex2(fmaf(s[2 * i], CS, (i & 1) ? n1 : n0)), ex2(fmaf(s[2 * i + 1], CS, (i & 1) ? n1 : n0)));
                    any |= pp[i];
                }
                wg_wait<0>();
                pin(sa); pin(sb2); pin(o); pin(pa); pin(pb);
                if (__builtin_expect(__any_sync(~0u, (any & 0x40004000u) || !ready), 0)) {
                    wait();
                    if (__any_sync(~0u, any & 0x40004000u)) {
                        if (tail) {
#pragma unroll
                            for (int i = 20; i < 32; i++) s[i] = -INFINITY;
                        }
                        float x0, x1;
                        new_max(s, 8, x0, x1);
                        const float sc0 = ex2(x0 - n0), sc1 = ex2(x1 - n1);
                        n0 = x0; n1 = x1;
#pragma unroll
                        for (int j = 0; j < 9; j++) { o[4 * j] *= sc0; o[4 * j + 1] *= sc0; o[4 * j + 2] *= sc1; o[4 * j + 3] *= sc1; }
#pragma unroll
                        for (int i = 0; i < 16; i++)
                            pp[i] = pack2(ex2(fmaf(s[2 * i], CS, (i & 1) ? n1 : n0)), ex2(fmaf(s[2 * i + 1], CS, (i & 1) ? n1 : n0)));
                    }
                }
            };
            {
                uint4 u[4];
                const unsigned char* src = g_kvq + 2097152 + (size_t)(abh * 1024 + qt * 64 + wq * 16) * 128 + lane * 16;
                spin(QGATE);
                ld_data<512, true>(u, src);
#pragma unroll
                for (int k = 0; k < 2; k++) {
                    q[8 * k] = ~u[k].x; q[8 * k + 1] = ~u[k + 2].x; q[8 * k + 2] = ~u[k].y; q[8 * k + 3] = ~u[k + 2].y;
                    q[8 * k + 4] = ~u[k].z; q[8 * k + 5] = ~u[k + 2].z; q[8 * k + 6] = ~u[k].w; q[8 * k + 7] = ~u[k + 2].w;
                }
                pin(q);
            }
            TS(40);
            acq(24);
            TS(13);
            qk_issue(sa, rdesc + (24 % NSLOT) * (SLOT >> 4));
            wg_wait<0>();
            pin(sa);
            {
                float x0, x1;
                new_max(sa, NJ0, x0, x1);
                n0 = x0; n1 = x1;
            }
            bar_arrive(6, 384);
            uint32_t vd = vdesc - (SLOT >> 4) * 65535u, kd = rdesc, vb = fbar + 8, kb = fbar;
            uint32_t vlast = vdesc - 4 * (SLOT >> 4) * 65535u, klast = rdesc + 4 * (SLOT >> 4) + 512;
            uint32_t kprev = fbar + 32, vprev = bars + (B_SINK - (B_EMPTY - B_FULL)) * 8;
#pragma unroll 1
            for (int it = 0; it < 4; it++) {
                both_issue(sb2, klast, pb, vlast);
                probs(sa, pa, mbar_test(vb, it < 2) & mbar_test(kb, it < 3), false, [&]() { mbar_wait(vb, it < 2); mbar_wait(kb, it < 3); });
                TS(41 + it * 4);
                if (lane == 0) mbar_arrive(kprev + (B_EMPTY - B_FULL) * 8);
                if (lane == 0) mbar_arrive(vprev + (B_EMPTY - B_FULL) * 8);
                both_issue(sa, kd, pa, vd);
                const int dv = it == 0 ? 2 : (it == 1 ? -3 : 1);
                kprev = kb; vprev = vb; vlast = vd - 512 * 65535u; klast = kd + 512;
                vd -= dv * (SLOT >> 4) * 65535u; vb += dv * 8;
                kd += (it == 2 ? -3 : 2) * (SLOT >> 4); kb = it == 2 ? vb : kb + 16;
                probs(sb2, pb, true, it == 3 && w == 1, []() {});
                TS(43 + it * 4);
            }
            wg_fence();
#pragma unroll
            for (int k = 0; k < 4; k++)
                mma_pv(o, pb[4 * k], pb[4 * k + 1], pb[4 * k + 2], pb[4 * k + 3], mkdesc(vlast - k * (128 * 65535) + (k > 1 ? w * ((k - 1) << 22) : 0)));
            wg_commit();
            const uint32_t mlw = sb + OFF_MISC + (tid >> 2) * 8;
            unsigned char* odst = g_o + (size_t)(b * 128 + qt * 8 + 2 * wq + w) * 4096 + ah * 1024 + lane * 16;
            mbar_wait(bars + B_RST * 8, (mlw | (uint32_t)(size_t)odst) & p.zero);
            wg_wait<0>();
            pin(o); pin(pb); pin(sa); pin(sb2);
            if (!(LATE & 4)) rel(31);
            TS(14);
            auto merge = [&](int keep, float nk, float ns) {
                const int snd = 2 - keep;
                if (c4 == 0) sts64f(mlw, ns, o[32 + snd]);
                if (MRG == 0) {
#pragma unroll
                    for (int j = 0; j < 4; j++)
                        sts128f(hbuf + (j & 1) * 2048 + (j >> 1) * 8192, o[8 * j + snd], o[8 * j + snd + 1], o[8 * j + 4 + snd], o[8 * j + 5 + snd]);
                } else {
#pragma unroll
                    for (int j = 0; j < 2; j++)
                        sts128(hbuf + j * 2048, pack2(o[16 * j + snd], o[16 * j + snd + 1]), pack2(o[16 * j + 4 + snd], o[16 * j + 5 + snd]),
                               pack2(o[16 * j + 8 + snd], o[16 * j + 9 + snd]), pack2(o[16 * j + 12 + snd], o[16 * j + 13 + snd]));
                }
                bar_sync(10, 256);
                const float2 u = lds64f(mlw ^ 256);
                const float x = fminf(nk, u.x);
                float a = ex2(x - nk), c = ex2(x - u.x);
                const float inv = rcp(fmaf(a, o[32 + keep], c * u.y));
                a *= inv; c *= inv;
                uint32_t pk[8];
                if (MRG == 0) {
#pragma unroll
                    for (int j = 0; j < 4; j++) {
                        const float4 t = lds128f((hbuf ^ 4096) + (j & 1) * 2048 + (j >> 1) * 8192);
                        pk[2 * j] = pack2(fmaf(a, o[8 * j + keep], c * t.x), fmaf(a, o[8 * j + keep + 1], c * t.y));
                        pk[2 * j + 1] = pack2(fmaf(a, o[8 * j + 4 + keep], c * t.z), fmaf(a, o[8 * j + 5 + keep], c * t.w));
                    }
                } else {
#pragma unroll
                    for (int j = 0; j < 2; j++) {
                        const uint4 t4 = lds128((hbuf ^ 4096) + j * 2048);
                        const uint32_t t[4] = {t4.x, t4.y, t4.z, t4.w};
#pragma unroll
                        for (int i = 0; i < 4; i++)
                            pk[4 * j + i] = pack2(fmaf(a, o[16 * j + 4 * i + keep], c * blo(t[i])), fmaf(a, o[16 * j + 4 * i + keep + 1], c * bhi(t[i])));
                    }
                }
                st_data(odst, pk[0], pk[1], pk[2], pk[3]);
                st_data(odst + 512, pk[4], pk[5], pk[6], pk[7]);
            };
            if (tid < 128) merge(0, n0, n1); else merge(2, n1, n0);
            if (tid == 0) asm volatile("red.relaxed.gpu.global.add.u32 [%0], 1;" ::"l"(&g_epoch[blockIdx.x * FS]) : "memory");
            TS(15);
        }

        {
            const uint32_t* dp = reinterpret_cast<const uint32_t*>(p.dw + (mir ? 14 * 256 : 0) + tile * 64) + lane;
#pragma unroll
            for (int i = 0; i < 15; i++) asm volatile("ld.global.nc.b32 %0, [%1];" : "=r"(dwr[i]) : "l"(dp + i * (mir ? -128 : 128)));
            acq(32); acq(33); acq(34);
            uint4 u[8];
            ld_data<512>(u, g_o + (size_t)(b * 128 + pt * 4 + wq) * 4096 + lane * 16);
#pragma unroll
            for (int i = 0; i < 8; i++) { a[4 * i] = u[i].x; a[4 * i + 1] = u[i].y; a[4 * i + 2] = u[i].z; a[4 * i + 3] = u[i].w; }
            if (LATE & 4) rel(31);
            TS(16);
            sp(d0, 32, a, 0, 0);
            sp(d0, 33, a + 16, 0, 1);
#pragma unroll
            for (int i = 0; i < 15; i++) dwr[i] = hmul2(dwr[i], 0x3F003F00u);
            residual(32);
            TS(17);
        }
    }

    cluster_arrive();
    TS(24);
    {
        const float rstd = rsq(fmaxf(fmaf(-mean, mean, msq), 0.f) + 1e-5f), nb = -mean * rstd;
#pragma unroll
        for (int j = 0; j < 8; j++) xr[j] = pack2(fmaf(v[2 * j], rstd, nb), fmaf(v[2 * j + 1], rstd, nb));
        const uint32_t stg = P + 16384 + warp * 1024;
        stsm4(stg + foff, xr[0], xr[1], xr[2], xr[3]);
        stsm4(stg + (foff ^ 64), xr[4], xr[5], xr[6], xr[7]);
        __syncwarp();
        const uint32_t src = stg + (lane >> 3) * 128 + (((lane & 7) ^ (lane >> 3)) << 4);
        const uint4 u0 = lds128(src), u1 = lds128((src + 512) ^ 64);
        __nv_bfloat16* dst = p.out + (size_t)(b * T_ + trow + (lane >> 3)) * 256 + tile * 64 + (lane & 7) * 8;
        if (trow < T_) { stg128(dst, u0); stg128(dst + 4 * 256, u1); }
    }
    TS(25);
    TG(31);
    TSDUMP();
    cluster_wait();
}

typedef CUresult (*EncodeFn)(CUtensorMap*, CUtensorMapDataType, cuuint32_t, void*, const cuuint64_t*, const cuuint64_t*,
                             const cuuint32_t*, const cuuint32_t*, CUtensorMapInterleave, CUtensorMapSwizzle,
                             CUtensorMapL2promotion, CUtensorMapFloatOOBfill);

}

extern "C" void kernel_launch(void* const* d_in, const int* in_sizes, int n_in, void* d_out, int out_size) {
    static EncodeFn encode = nullptr;
    if (!encode) {
        void* fn = nullptr;
        cudaDriverEntryPointQueryResult qr;
        cudaGetDriverEntryPoint("cuTensorMapEncodeTiled", &fn, cudaEnableDefault, &qr);
        encode = (EncodeFn)fn;
        cudaFuncSetAttribute(conformer_kernel, cudaFuncAttributeMaxDynamicSharedMemorySize, SMEM_LAUNCH);
    }
    Scalars p;
    Maps m;
    const cuuint32_t ones[5] = {1, 1, 1, 1, 1};
    const int idx[8] = {1, 2, 3, 4, 5, 7, 8, 9};
    const int rows[8] = {256, 1024, 256, 256, 256, 256, 256, 1024};
    const int cols[8] = {1024, 256, 768, 256, 512, 256, 1024, 256};
    for (int i = 0; i < 8; i++) {
        const cuuint64_t pitch = (cuuint64_t)cols[i] * 2;
        const bool f = i != 0 && i != 3;
        const cuuint64_t dims[5] = {(cuuint64_t)cols[i], f ? 2u : 4u, f ? 2u : 4u, f ? 4u : 2u, (cuuint64_t)rows[i] / (f ? 16 : 32)};
        const cuuint64_t strides[4] = {pitch, pitch * 8, pitch * (f ? 2 : 4), pitch * (f ? 16 : 32)};
        const cuuint32_t box[5] = {64, f ? 2u : 4u, f ? 2u : 4u, f ? 4u : 2u, f ? 8u : 4u};
        encode(&m.tm[i], CU_TENSOR_MAP_DATA_TYPE_BFLOAT16, 5, d_in[idx[i]], dims, strides, box, ones, CU_TENSOR_MAP_INTERLEAVE_NONE,
               CU_TENSOR_MAP_SWIZZLE_128B, CU_TENSOR_MAP_L2_PROMOTION_L2_128B, CU_TENSOR_MAP_FLOAT_OOB_FILL_NONE);
        m.w[i] = (const char*)d_in[idx[i]];
    }
    {
        void* kv = nullptr;
        cudaGetSymbolAddress(&kv, g_kvq);
        const cuuint64_t dims[2] = {64, 16384};
        const cuuint64_t strides[1] = {128};
        const cuuint32_t box[2] = {64, 128};
        encode(&m.tm[8], CU_TENSOR_MAP_DATA_TYPE_BFLOAT16, 2, kv, dims, strides, box, ones, CU_TENSOR_MAP_INTERLEAVE_NONE,
               CU_TENSOR_MAP_SWIZZLE_NONE, CU_TENSOR_MAP_L2_PROMOTION_L2_128B, CU_TENSOR_MAP_FLOAT_OOB_FILL_NONE);
    }
    p.x = (const __nv_bfloat16*)d_in[0];
    p.dw = (const __nv_bfloat16*)d_in[6];
    p.out = (__nv_bfloat16*)d_out;
    p.zero = 0;
    conformer_kernel<<<NCTA, NTHREADS, SMEM_LAUNCH>>>(p, m);
}
```

```cpp
#include <cuda_runtime.h>
#include <cuda_bf16.h>
#include <cuda.h>
#include <stdint.h>

namespace {

constexpr int T_ = 1000;
constexpr int NCTA = 128;
constexpr int NTHREADS = 512;
constexpr int NSLOT = 5;
constexpr int SLOT = 16384;
constexpr int NLOADS = 56;

constexpr uint32_t OFF_RING = 0;
constexpr uint32_t OFF_P = 163840;
constexpr uint32_t OFF_H = 188416;
constexpr uint32_t OFF_MISC = 221184;
constexpr uint32_t OFF_BARS = 229888;
constexpr uint32_t SMEM_BYTES = 230400;
constexpr uint32_t GCH = 6144;
constexpr uint32_t HCH = 4096;

constexpr int B_FULL = 0, B_EMPTY = 10, B_XA = 20  , B_XB = 25  , B_INB = 29  , B_SR = 33,
              B_RST = 34, B_RDY = 35  , B_SINK = 41, B_HALO = 42  , NBARS = 46;

#define KD2 300u
#define KD3 500u
#define QGATE 700u
#define BACKOFF 0u
#define KFS 8
#define KDELAY 250u
#define NJ0 2
#define HDELAY 200u
#define LATE 3
#define SND 0
#define PF0 0
#define TWO 1
#define WARMF 1
#define SPLIT 0
#define MRG 1
#define MW 0
#define SAS 3
#define TURN 0
#define EAGER 0x0155
constexpr int FS = 8;

struct Scalars {
    const __nv_bfloat16* x;
    const __nv_bfloat16* dw;
    __nv_bfloat16* out;
    uint32_t zero;
};
struct Maps {
    CUtensorMap tm[9];
    const char* w[8];
};

__device__ __align__(1024) unsigned char g_kvq[3 * 8 * 1024 * 128];
__device__ __align__(1024) unsigned char g_o[2 * 128 * 4096];
__device__ uint4 g_halo[64 * 4 * 2 * 64];
__device__ __align__(128) uint32_t g_flag_kv[8 * 32 * KFS];
__device__ uint32_t g_reset[2 * 32];
__device__ uint32_t g_epoch[NCTA * FS];

#define TS(i) do { } while (0)
#define TSW(i) do { } while (0)
#define TG(i) do { } while (0)
#define TSINIT() do { } while (0)
#define TSDUMP() do { } while (0)
constexpr uint32_t SMEM_LAUNCH = SMEM_BYTES;

__device__ __forceinline__ uint32_t smem_u32(const void* p) { return (uint32_t)__cvta_generic_to_shared(p); }
__device__ __forceinline__ void mbar_init(uint32_t b, uint32_t c) { asm volatile("mbarrier.init.shared::cta.b64 [%0], %1;" ::"r"(b), "r"(c) : "memory"); }
__device__ __forceinline__ void mbar_arrive(uint32_t b) { asm volatile("mbarrier.arrive.shared::cta.b64 _, [%0];" ::"r"(b) : "memory"); }
__device__ __forceinline__ void mbar_arrive_tx(uint32_t b, uint32_t tx) { asm volatile("mbarrier.arrive.expect_tx.shared::cta.b64 _, [%0], %1;" ::"r"(b), "r"(tx) : "memory"); }
__device__ __forceinline__ void mbar_wait(uint32_t b, uint32_t ph) {
    asm volatile("{\n.reg .pred p, q;\n.reg .u32 c;\nmov.u32 c, 0;\n"
                 "MW_LOOP:\n.pragma \"nounroll\";\n"
                 "mbarrier.try_wait.parity.shared::cta.b64 p, [%0], %1;\n"
                 "add.u32 c, c, 1;\nsetp.lt.u32 q, c, 65536;\nnot.pred p, p;\nand.pred p, p, q;\n@p bra MW_LOOP;\n}"
                 ::"r"(b), "r"(ph) : "memory");
}
__device__ __forceinline__ bool mbar_test(uint32_t b, uint32_t ph) {
    uint32_t ok;
    asm volatile("{\n.reg .pred p;\nmbarrier.test_wait.parity.shared::cta.b64 p, [%1], %2;\nselp.u32 %0, 1, 0, p;\n}" : "=r"(ok) : "r"(b), "r"(ph) : "memory");
    return ok;
}
__device__ __forceinline__ uint32_t mapa(uint32_t a, uint32_t r) { uint32_t o; asm("mapa.shared::cluster.u32 %0, %1, %2;" : "=r"(o) : "r"(a), "r"(r)); return o; }
__device__ __forceinline__ void fence_async_smem() { asm volatile("fence.proxy.async.shared::cta;" ::: "memory"); }
__device__ __forceinline__ void fence_async_global() { asm volatile("fence.proxy.async.global;" ::: "memory"); }
__device__ __forceinline__ void bar_sync(int id, int n) { asm volatile("bar.sync %0, %1;" ::"r"(id), "r"(n) : "memory"); }
__device__ __forceinline__ void bar_arrive(int id, int n) { asm volatile("bar.arrive %0, %1;" ::"r"(id), "r"(n) : "memory"); }
__device__ __forceinline__ void cluster_arrive() { asm volatile("barrier.cluster.arrive.relaxed.aligned;" ::: "memory"); }
__device__ __forceinline__ void cluster_wait() { asm volatile("barrier.cluster.wait.aligned;" ::: "memory"); }

__device__ __forceinline__ void ring_load(uint32_t dst, const CUtensorMap* tm, int col, int row16, uint32_t bar) {
    asm volatile("{\n.reg .pred p;\nelect.sync _|p, 0xffffffff;\n"
                 "@p mbarrier.arrive.expect_tx.shared::cta.b64 _, [%2], 16384;\n"
                 "@p cp.async.bulk.tensor.5d.shared::cluster.global.mbarrier::complete_tx::bytes [%0], [%1, {%3, 0, 0, 0, %4}], [%2];\n}"
                 ::"r"(dst), "l"(tm), "r"(bar), "r"(col), "r"(row16) : "memory");
}
__device__ __forceinline__ void ring_load_both(uint32_t dst, const CUtensorMap* tm, int c1, uint32_t bar) {
    asm volatile("{\n.reg .pred p;\nelect.sync _|p, 0xffffffff;\n"
                 "@p cp.async.bulk.tensor.2d.shared::cluster.global.mbarrier::complete_tx::bytes.multicast::cluster [%0], [%1, {0, %3}], [%2], %4;\n}"
                 ::"r"(dst), "l"(tm), "r"(bar), "r"(c1), "h"((uint16_t)3) : "memory");
}
__device__ __forceinline__ void mbar_arrive_peer(uint32_t b) { asm volatile("mbarrier.arrive.relaxed.cluster.shared::cluster.b64 _, [%0];" ::"r"(b) : "memory"); }
__device__ __forceinline__ void prefetch_l2(const void* src, uint32_t bytes) {
    asm volatile("cp.async.bulk.prefetch.L2.global [%0], %1;" ::"l"(src), "r"(bytes) : "memory");
}
__device__ __forceinline__ void peer_copy(uint32_t dst, uint32_t src, uint32_t bytes, uint32_t rbar) {
    asm volatile("{\n.reg .pred p;\nelect.sync _|p, 0xffffffff;\n"
                 "@p cp.async.bulk.shared::cluster.shared::cta.mbarrier::complete_tx::bytes [%0], [%1], %2, [%3];\n}"
                 ::"r"(dst), "r"(src), "r"(bytes), "r"(rbar) : "memory");
}
__device__ __forceinline__ void st_async4(uint32_t dst, uint32_t a, uint32_t b, uint32_t c, uint32_t d, uint32_t bar) {
    asm volatile("st.async.shared::cluster.mbarrier::complete_tx::bytes.v4.b32 [%0], {%1,%2,%3,%4}, [%5];" ::"r"(dst), "r"(a), "r"(b), "r"(c), "r"(d), "r"(bar) : "memory");
}
__device__ __forceinline__ void put_sums(uint32_t dst, uint32_t rdst, float a, float b, uint32_t rbar, bool on) {
    asm volatile("{\n.reg .pred p;\nsetp.ne.u32 p, %5, 0;\n"
                 "@p st.async.shared::cluster.mbarrier::complete_tx::bytes.v2.f32 [%1], {%2,%3}, [%4];\n"
                 "@p st.shared.v2.f32 [%0], {%2,%3};\n}" ::"r"(dst), "r"(rdst), "f"(a), "f"(b), "r"(rbar), "r"((uint32_t)on) : "memory");
}
__device__ __forceinline__ void stsm4(uint32_t a, uint32_t r0, uint32_t r1, uint32_t r2, uint32_t r3) {
    asm volatile("stmatrix.sync.aligned.m8n8.x4.shared.b16 [%0], {%1,%2,%3,%4};" ::"r"(a), "r"(r0), "r"(r1), "r"(r2), "r"(r3) : "memory");
}
__device__ __forceinline__ void ldsm4(uint32_t a, uint32_t& r0, uint32_t& r1, uint32_t& r2, uint32_t& r3) {
    asm volatile("ldmatrix.sync.aligned.m8n8.x4.shared.b16 {%0,%1,%2,%3}, [%4];" : "=r"(r0), "=r"(r1), "=r"(r2), "=r"(r3) : "r"(a) : "memory");
}
__device__ __forceinline__ uint4 lds128(uint32_t a) { uint4 v; asm volatile("ld.shared.v4.b32 {%0,%1,%2,%3}, [%4];" : "=r"(v.x), "=r"(v.y), "=r"(v.z), "=r"(v.w) : "r"(a) : "memory"); return v; }
__device__ __forceinline__ float4 lds128f(uint32_t a) { float4 v; asm volatile("ld.shared.v4.f32 {%0,%1,%2,%3}, [%4];" : "=f"(v.x), "=f"(v.y), "=f"(v.z), "=f"(v.w) : "r"(a) : "memory"); return v; }
__device__ __forceinline__ float2 lds64f(uint32_t a) { float2 v; asm volatile("ld.shared.v2.f32 {%0,%1}, [%2];" : "=f"(v.x), "=f"(v.y) : "r"(a) : "memory"); return v; }
__device__ __forceinline__ uint32_t lds32(uint32_t a) { uint32_t v; asm volatile("ld.shared.b32 %0, [%1];" : "=r"(v) : "r"(a) : "memory"); return v; }
__device__ __forceinline__ void sts128(uint32_t a, uint32_t x, uint32_t y, uint32_t z, uint32_t w) { asm volatile("st.shared.v4.b32 [%0], {%1,%2,%3,%4};" ::"r"(a), "r"(x), "r"(y), "r"(z), "r"(w) : "memory"); }
__device__ __forceinline__ void sts128f(uint32_t a, float x, float y, float z, float w) { asm volatile("st.shared.v4.f32 [%0], {%1,%2,%3,%4};" ::"r"(a), "f"(x), "f"(y), "f"(z), "f"(w) : "memory"); }
__device__ __forceinline__ void sts64f(uint32_t a, float x, float y) { asm volatile("st.shared.v2.f32 [%0], {%1,%2};" ::"r"(a), "f"(x), "f"(y) : "memory"); }
__device__ __forceinline__ void sts32(uint32_t a, uint32_t x) { asm volatile("st.shared.b32 [%0], %1;" ::"r"(a), "r"(x) : "memory"); }
__device__ __forceinline__ void stg128(void* p, uint4 v) { asm volatile("st.global.v4.b32 [%0], {%1,%2,%3,%4};" ::"l"(p), "r"(v.x), "r"(v.y), "r"(v.z), "r"(v.w) : "memory"); }

__device__ __forceinline__ uint32_t pack2(float lo, float hi) { uint32_t r; asm("cvt.rn.bf16x2.f32 %0, %1, %2;" : "=r"(r) : "f"(hi), "f"(lo)); return r; }
__device__ __forceinline__ float blo(uint32_t v) { return __uint_as_float(v << 16); }
__device__ __forceinline__ float bhi(uint32_t v) { return __uint_as_float(v & 0xffff0000u); }
__device__ __forceinline__ uint32_t hmul2(uint32_t a, uint32_t b) { uint32_t r; asm("mul.rn.bf16x2 %0, %1, %2;" : "=r"(r) : "r"(a), "r"(b)); return r; }
__device__ __forceinline__ uint32_t hadd2(uint32_t a, uint32_t b) { uint32_t r; asm("add.rn.bf16x2 %0, %1, %2;" : "=r"(r) : "r"(a), "r"(b)); return r; }
__device__ __forceinline__ uint32_t hsub2(uint32_t a, uint32_t b) { uint32_t r; asm("sub.rn.bf16x2 %0, %1, %2;" : "=r"(r) : "r"(a), "r"(b)); return r; }
__device__ __forceinline__ uint32_t hfma2(uint32_t a, uint32_t b, uint32_t c) { uint32_t r; asm("fma.rn.bf16x2 %0, %1, %2, %3;" : "=r"(r) : "r"(a), "r"(b), "r"(c)); return r; }
__device__ __forceinline__ float tanh_fast(float x) { float r; asm("tanh.approx.f32 %0, %1;" : "=f"(r) : "f"(x)); return r; }
__device__ __forceinline__ float rsq(float x) { float r; asm("rsqrt.approx.ftz.f32 %0, %1;" : "=f"(r) : "f"(x)); return r; }
__device__ __forceinline__ float rcp(float x) { float r; asm("rcp.approx.ftz.f32 %0, %1;" : "=f"(r) : "f"(x)); return r; }
__device__ __forceinline__ float ex2(float x) { float r; asm("ex2.approx.ftz.f32 %0, %1;" : "=f"(r) : "f"(x)); return r; }

__device__ __forceinline__ uint32_t ld_relaxed(const uint32_t* p) {
    uint32_t v;
    asm volatile("ld.relaxed.gpu.global.u32 %0, [%1];" : "=r"(v) : "l"(p) : "memory");
    return v;
}
__device__ __forceinline__ uint32_t clock32() { uint32_t c; asm volatile("mov.u32 %0, %%clock;" : "=r"(c)::"memory"); return c; }
__device__ __forceinline__ void spin(uint32_t clks) {
    const uint32_t t0 = clock32();
    while (clock32() - t0 < clks) {}
}
__device__ __forceinline__ void flag_wait(const uint32_t* p, uint32_t e, bool mine) {
#pragma unroll 1
    for (int i = 0; i < (1 << 19); i++) {
        if (mine) mine = ld_relaxed(p) != e;
        if (!__any_sync(~0u, mine)) break;
        if (BACKOFF) spin(BACKOFF);
    }
    asm volatile("fence.acquire.gpu;" ::: "memory");
    fence_async_global();
}
__device__ __forceinline__ void st_data(void* p, uint32_t x, uint32_t y, uint32_t z, uint32_t w) {
    asm volatile("st.relaxed.gpu.global.v4.b32 [%0], {%1,%2,%3,%4};" ::"l"(p), "r"(x), "r"(y), "r"(z), "r"(w) : "memory");
}
template <int STRIDE, bool INV = false, int N>
__device__ __forceinline__ void ld_data(uint4 (&v)[N], const unsigned char* p) {
    int it = 0;
    bool again;
#pragma unroll 1
    do {
        uint32_t m = INV ? ~0u : 0u;
#pragma unroll
        for (int i = 0; i < N; i++)
            asm volatile("ld.relaxed.gpu.global.v4.b32 {%0,%1,%2,%3}, [%4];" : "=r"(v[i].x), "=r"(v[i].y), "=r"(v[i].z), "=r"(v[i].w) : "l"(p + i * STRIDE) : "memory");
#pragma unroll
        for (int i = 0; i < N; i++)
            m = INV ? __vimin3_u32(__vimin3_u32(v[i].x, v[i].y, v[i].z), v[i].w, m) : __vimax3_u32(__vimax3_u32(v[i].x, v[i].y, v[i].z), v[i].w, m);
        again = __any_sync(~0u, m == (INV ? 0u : ~0u)) && ++it < (1 << 16);
    } while (again);
}
__device__ __forceinline__ uint32_t ld_epoch() { return ld_relaxed(&g_epoch[blockIdx.x * FS]) + 1; }
__device__ __forceinline__ void flag_set(uint32_t* p, uint32_t e) { asm volatile("st.release.gpu.global.u32 [%0], %1;" ::"l"(p), "r"(e) : "memory"); }

__device__ __forceinline__ uint32_t desc_lo(uint32_t addr) { return ((addr & 0x3FFFF) >> 4) | 0x10000u; }
__device__ __forceinline__ uint64_t mkdesc(uint32_t lo) { return (uint64_t)lo | (0x40000040ull << 32); }
__device__ __forceinline__ void wg_fence() { asm volatile("wgmma.fence.sync.aligned;" ::: "memory"); }
__device__ __forceinline__ void wg_commit() { asm volatile("wgmma.commit_group.sync.aligned;" ::: "memory"); }
template <int N> __device__ __forceinline__ void wg_wait() { asm volatile("wgmma.wait_group.sync.aligned %0;" ::"n"(N) : "memory"); }
template <int N> __device__ __forceinline__ void pin(float (&d)[N]) {
#pragma unroll
    for (int i = 0; i < N; i++) asm volatile("" : "+f"(d[i])::"memory");
}
template <int N> __device__ __forceinline__ void pin(uint32_t (&d)[N]) {
#pragma unroll
    for (int i = 0; i < N; i++) asm volatile("" : "+r"(d[i])::"memory");
}

template <typename Tp, int N> __device__ __forceinline__ void zero(Tp (&d)[N]) {
#pragma unroll
    for (int i = 0; i < N; i++) d[i] = 0;
    pin(d);
}

#define F4(d, i) "+f"(d[i]), "+f"(d[i + 1]), "+f"(d[i + 2]), "+f"(d[i + 3])
#define F16(d, i) F4(d, i), F4(d, i + 4), F4(d, i + 8), F4(d, i + 12)

__device__ __forceinline__ void mma16(float (&d)[4], const uint32_t* a, uint32_t b0, uint32_t b1) {
    asm("mma.sync.aligned.m16n8k16.row.col.f32.bf16.bf16.f32 {%0,%1,%2,%3}, {%4,%5,%6,%7}, {%8,%9}, {%0,%1,%2,%3};"
        : F4(d, 0) : "r"(a[0]), "r"(a[1]), "r"(a[2]), "r"(a[3]), "r"(b0), "r"(b1));
}
template <int N>
__device__ __forceinline__ float row_sum(const uint32_t* x, uint32_t ones = 0x3F803F80u) {
    float c[4] = {};
#pragma unroll
    for (int i = 0; i < N; i += 4) mma16(c, x + i, ones, ones);
    return c[0] + c[2];
}
template <int N>
__device__ __forceinline__ float row_sumsq(const uint32_t* x, int lane) {
    float c0[4] = {}, c1[4] = {};
#pragma unroll
    for (int i = 0; i < N; i += 4) {
        mma16(c0, x + i, x[i], x[i + 2]);
        mma16(c1, x + i, x[i + 1], x[i + 3]);
    }
    return (lane & 4) ? c0[1] + c1[3] : c0[0] + c1[2];
}
__device__ __forceinline__ void mma_sp(float (&d)[32], const uint32_t* a, uint64_t b, uint32_t meta, int acc) {
    asm volatile("{.reg .pred p; setp.ne.b32 p, %38, 0;\n"
                 "wgmma.mma_async.sp.sync.aligned.m64n64k32.f32.bf16.bf16 {%0,%1,%2,%3,%4,%5,%6,%7,%8,%9,%10,%11,%12,%13,%14,%15,%16,%17,%18,%19,%20,%21,%22,%23,%24,%25,%26,%27,%28,%29,%30,%31}, "
                 "{%32,%33,%34,%35}, %36, %37, 0, p, 1, 1, 1;}\n"
                 : F16(d, 0), F16(d, 16) : "r"(a[0]), "r"(a[1]), "r"(a[2]), "r"(a[3]), "l"(b), "r"(meta), "r"(acc));
}
__device__ __forceinline__ void mma_qk(float (&d)[32], uint32_t a0, uint32_t a1, uint32_t a2, uint32_t a3, uint64_t b, int acc) {
    asm volatile("{.reg .pred p; setp.ne.b32 p, %37, 0;\n"
                 "wgmma.mma_async.sync.aligned.m64n64k16.f32.bf16.bf16 {%0,%1,%2,%3,%4,%5,%6,%7,%8,%9,%10,%11,%12,%13,%14,%15,%16,%17,%18,%19,%20,%21,%22,%23,%24,%25,%26,%27,%28,%29,%30,%31}, "
                 "{%32,%33,%34,%35}, %36, p, 1, 1, 0;}\n"
                 : F16(d, 0), F16(d, 16) : "r"(a0), "r"(a1), "r"(a2), "r"(a3), "l"(b), "r"(acc));
}
__device__ __forceinline__ void mma_pv(float (&d)[36], uint32_t a0, uint32_t a1, uint32_t a2, uint32_t a3, uint64_t b) {
    asm volatile("wgmma.mma_async.sync.aligned.m64n72k16.f32.bf16.bf16 {%0,%1,%2,%3,%4,%5,%6,%7,%8,%9,%10,%11,%12,%13,%14,%15,%16,%17,%18,%19,%20,%21,%22,%23,%24,%25,%26,%27,%28,%29,%30,%31,%32,%33,%34,%35}, "
                 "{%36,%37,%38,%39}, %40, 1, 1, 1, 1;\n"
                 : F16(d, 0), F16(d, 16), F4(d, 32) : "r"(a0), "r"(a1), "r"(a2), "r"(a3), "l"(b));
}

__device__ __forceinline__ uint32_t load_code(int n, int r, int w) {
    const int tile = 2 * r + w;
    int m, col, row;
    if (n < 16 || n >= 40) {
        const int k = n < 16 ? n : n - 40;
        m = n < 16 ? 0 : 6;
        if (TWO && n >= 40 && k < 4) { col = 4 * tile + (k & 1); row = (k >> 1) ^ r; }
        else if (k < 8) { col = 4 * tile + (k >> 1); row = n < 16 ? (k & 1) : (k & 1) ^ r; }
        else { m++; col = k < 12 ? tile ^ 2 : tile; row = 2 * (tile ^ (k & 1)) + ((k >> 1) & 1); }
    } else if (n < 32) {
        const int k = n - 16;
        m = 2;
        if (k < 4) { col = tile + ((k & 1) ? 8 : 4); row = (k >> 1) ^ r; }
        else { col = tile; row = (k & 1) ^ r; }
    } else if (n < 34) { m = 3; col = tile; row = n - 32; }
    else if (n < 38) { const int k = n - 34; m = 4; col = tile + 4 * (k & 1); row = (k >> 1) ^ r; }
    else { m = 5; col = tile; row = (n & 1) ^ r; }
    return m | (col << 4) | (row << ((m == 0 || m == 3) ? 10 : 11));
}

__global__ void __cluster_dims__(2, 1, 1) __launch_bounds__(NTHREADS, 1)
conformer_kernel(const Scalars p, const __grid_constant__ Maps m) {
    extern __shared__ __align__(1024) unsigned char smem_raw[];
    const uint32_t sb = smem_u32(smem_raw);
    const uint32_t bars = sb + OFF_BARS;
    const int tid = threadIdx.x;
    const int lane = tid & 31;
    const int warp = __shfl_sync(~0u, tid >> 5, 0);
    const int r = blockIdx.x & 1;
    const int pair = blockIdx.x >> 1;
    const int b = pair >> 5, pt = pair & 31;
    const int ah = pt >> 3, qt = (pt & 7) * 2 + r;
    const int abh = b * 4 + ah;

    TG(30);
    TSINIT();
    TS(0);
    const uint32_t P = sb + OFF_P, H = sb + OFF_H;
    if (warp == 11) {
        if (lane == 0) {
#pragma unroll
            for (int i = 0; i < 2 * NSLOT; i++) mbar_init(bars + (B_FULL + i) * 8, 1);
            asm volatile("fence.mbarrier_init.release.cluster;" ::: "memory");
            fence_async_smem();
        }
        __syncwarp();
        bar_arrive(13, 96);
        cluster_arrive();
    }

    if (warp >= 8) {
        asm volatile("setmaxnreg.dec.sync.aligned.u32 48;");
        if (warp >= 12) {
            cluster_arrive();
            cluster_wait();
            const int ut = tid & 127;
            const uint32_t target = ld_epoch() * 64;
            bar_sync(6, 384);
#pragma unroll
            for (int i = 0; i < 4; i++) {
                st_data(g_o + (size_t)(b * 128 + qt * 8 + 2 * i + (ut >> 6)) * 4096 + ah * 1024 + (ut & 63) * 16, ~0u, ~0u, ~0u, ~0u);
                if (i < 2) st_data(&g_halo[(pair * 4 + 2 * r + i) * 128 + ut], ~0u, ~0u, ~0u, ~0u);
            }
            bar_sync(11, 128);
            if (ut == 0) {
                asm volatile("red.release.gpu.global.add.u32 [%0], 1;" ::"l"(&g_reset[b * 32]) : "memory");
#pragma unroll 1
                for (int i = 0; i < (1 << 20) && ld_relaxed(&g_reset[b * 32]) != target; i++) __nanosleep(100);
                asm volatile("fence.acquire.gpu;" ::: "memory");
                mbar_arrive(bars + B_RST * 8);
            }
            bar_sync(11, 128);
            TS(14);
#pragma unroll
            for (int i = 0; i < 4; i++) st_data(g_kvq + 2097152 + (size_t)(abh * 1024 + qt * 64) * 128 + i * 2048 + ut * 16, 0, 0, 0, 0);
            const int side = warp & 1, wg = (warp >> 1) & 1, np = side ? pt + 1 : pt - 1;
            const unsigned char* src = reinterpret_cast<const unsigned char*>(&g_halo[(((b * 32 + np) * 4 + 2 * r + wg) * 2 + (side ^ 1)) * 64 + lane]);
            const uint32_t dst = H + 16384 + wg * GCH + side * 5120 + (lane & 7) * 128 + (((lane >> 3) ^ (lane & 7)) << 4);
            uint4 hv[2] = {make_uint4(0, 0, 0, 0), make_uint4(0, 0, 0, 0)};
            bar_sync(8 + wg, 192);
            if (np >= 0 && np < 32) {
                spin(HDELAY);
                ld_data<512>(hv, src);
            }
            stsm4(dst, hv[0].x, hv[0].y, hv[0].z, hv[0].w);
            stsm4(dst ^ 64, hv[1].x, hv[1].y, hv[1].z, hv[1].w);
            __syncwarp();
            if (lane == 0) mbar_arrive(bars + (B_HALO + (warp & 3)) * 8);
            TS(4);
        } else if (warp < 10) {
            const int w = warp - 8;
            const uint32_t ring = sb + OFF_RING + w * NSLOT * SLOT;
            const uint32_t full = bars + (B_FULL + w * NSLOT) * 8;
            cluster_arrive();
            bar_sync(13, 96);
            TS(1);
#pragma unroll
            for (int n = 0; n < NSLOT; n++) {
                if (n == 1) bar_sync(12, 64);
                ring_load(ring + n * SLOT, &m.tm[0], 64 * (8 * r + 4 * w + (n >> 1)), 4 * (n & 1), full + n * 8);
            }
            TS(2);
            const uint32_t code = load_code(lane, r, w) | (load_code(lane + 32, r, w) << 16);
            cluster_wait();
            uint32_t s = 0, ph = 0;
            int n = NSLOT;
#pragma unroll 1
            for (int seg = 0; seg < 2; seg++) {
#pragma unroll 1
                for (; n < (seg == 0 ? 22 : NLOADS); n++) {
                    const uint32_t c = __shfl_sync(~0u, code, n) >> (n & 32 ? 16 : 0);
                    const CUtensorMap* tm = &m.tm[c & 15];
                    const uint32_t col = (c & 0xf0) * 4, row = (c & 0xff00) >> 8, dst = ring + s * SLOT;
                    mbar_wait(full + (B_EMPTY - B_FULL) * 8 + s * 8, ph + (((uint32_t)(size_t)tm | col | row | dst) & p.zero));
                    ring_load(dst, tm, col, row, full + s * 8);
                    if (++s == NSLOT) { s = 0; ph ^= 1; }
                }
                if (seg == 1) break;
                const uint32_t epoch = ld_epoch();
                const uint32_t rdy = bars + (B_RDY + 3 * w) * 8, prdy = mapa(rdy, r ^ 1);
                const int odd = r ^ w;
                const uint32_t* flags = g_flag_kv + (abh * 32 + lane) * KFS;
                bool first = (lane >> 2) == 2 * odd + w;
                if (WARMF && first) first = ld_relaxed(flags) != epoch;
                auto kv_load = [&](uint32_t sl, int isv, int i) {
                    ring_load_both(ring + sl * SLOT, &m.tm[8], (isv * 64 + abh * 8 + 2 * i + w) * 128, full + sl * 8);
                };
#pragma unroll 1
                for (int i = 0; i < 2; i++) {
                    if (lane < 3 + i) {
                        const uint32_t sl = i ? lane : lane + 2;
                        mbar_wait(full + (B_EMPTY - B_FULL + sl) * 8, i ^ 1);
                        mbar_arrive_tx(full + sl * 8, (i || lane == 2) ? SLOT : 0);
                    }
                    __syncwarp();
                }
                if (lane == 0) mbar_arrive_peer(prdy);
                bar_sync(14, 96);
                spin(KDELAY);
                mbar_wait(rdy, 0);
                flag_wait(flags, epoch, first);
                TSW(5 + 2 * odd);
                if (!odd) { kv_load(4, 0, 0); bar_arrive(12, 64); }
                else bar_sync(12, 64);
                spin(w ? KD3 : KD2);
                kv_load(odd ^ 1, odd ^ 1, odd);
                flag_wait(flags, epoch, (lane >> 2) == 2 * odd + w + 4);
                mbar_wait(full + (odd ^ 1) * 8, 1);
                kv_load(2 + odd, odd, 2 - odd);
#pragma unroll 1
                for (int i = 0; i < 3; i++) {
                    const uint32_t sl = i ? i - 1 : 4, bo = i == 2 ? 16 : 8;
                    mbar_wait(full + (B_EMPTY - B_FULL + sl) * 8, i != 0);
                    if (lane == 0) mbar_arrive_tx(full + sl * 8, SLOT);
                    if ((i & 1) != odd) {
                        mbar_wait(rdy + bo, 0);
                        kv_load(sl, i != 0, 2 + odd);
                    } else if (lane == 0) mbar_arrive_peer(prdy + bo);
                    __syncwarp();
                }
                n = 32; s = 2; ph = 1;
            }
        } else if (warp == 10) {
            if (lane == 0) {
#pragma unroll
                for (int i = B_EMPTY; i < NBARS; i++) mbar_init(bars + i * 8, i < B_XA ? 4 : 1);
#pragma unroll
                for (int i = B_XA; i <= B_SR; i++) mbar_arrive_tx(bars + i * 8, i < B_XB ? 512 : ((i >= B_INB && i < B_SR) ? 4096 : 8192));
                asm volatile("fence.mbarrier_init.release.cluster;" ::: "memory");
                fence_async_smem();
            }
            __syncwarp();
            cluster_arrive();
            cluster_wait();
        } else {
            const uint32_t kb = (lane < 2 || lane > 5) ? 4096 : (lane == 2 ? 3072 : (lane == 4 ? 2048 : 1024));
            const char* pf = m.w[lane & 7] + blockIdx.x * kb;
            cluster_wait();
            if (lane < PF0) prefetch_l2(pf, kb);
            mbar_wait(bars + B_FULL * 8, 0);
            if (lane >= PF0 && lane < 3) prefetch_l2(pf, kb);
            if (lane >= 1 && lane < 9) asm volatile("prefetch.tensormap [%0];" ::"l"(&m.tm[lane]) : "memory");
            mbar_wait(bars + (B_FULL + 1) * 8, 1);
            if (lane > 2 && lane < 8) prefetch_l2(pf, kb);
            if (lane == 8 && blockIdx.x < 15) prefetch_l2(p.dw + blockIdx.x * 256, 512);
            const uint32_t epoch = ld_epoch();
            bar_sync(4, 288);
            if (lane < 16) flag_set(&g_flag_kv[((b * 4 + 2 * r + (lane >> 3)) * 32 + pt) * KFS + (lane & 7)], epoch);
            __syncwarp();
            bar_arrive(14, 96);
            TSW(8);
        }
        TSDUMP();
        return;
    }

    const int w = warp >> 2, wq = warp & 3;
    const int tile = 2 * r + w;
    const int wt = tid & 127;
    const int c4 = lane & 3;
    const int trow = pt * 32 + 8 * wq;
    uint32_t xr[8];
    uint32_t a[32];
    const char* xrow = reinterpret_cast<const char*>(p.x) + (b * T_ + trow + (lane >> 2)) * 512;
    zero(a);
    if (trow < T_) {
        const char* src = xrow + c4 * 16 + p.zero;
#pragma unroll
        for (int i = 0; i < 8; i++)
            asm volatile("ld.global.nc.v4.b32 {%0,%1,%2,%3}, [%4];" : "=r"(a[4 * i]), "=r"(a[4 * i + 1]), "=r"(a[4 * i + 2]), "=r"(a[4 * i + 3]) : "l"(src + 64 * i));
    }
    cluster_arrive();
    asm volatile("setmaxnreg.inc.sync.aligned.u32 208;");
    const uint32_t rbase = sb + OFF_RING + w * NSLOT * SLOT, fbar = bars + (B_FULL + w * NSLOT) * 8;
    const uint32_t rdesc = desc_lo(rbase);
    auto acq = [&](int n) { mbar_wait(fbar + (n % NSLOT) * 8, (n / NSLOT) & 1); };
    auto rel = [&](int n) { if (lane == 0) mbar_arrive(fbar + (B_EMPTY - B_FULL + n % NSLOT) * 8); };
    const uint32_t foff = (lane & 7) * 128 + (((lane >> 3) ^ (lane & 7)) << 4);
    float v[16];
    const uint32_t xown = __shfl_sync(~0u, P + wt * 16 + tile * 4096, lane), xrem = __shfl_sync(~0u, P + wt * 16 + (r ^ 1) * 8192, lane);
    const uint32_t sbuf = __shfl_sync(~0u, sb + OFF_MISC + 1024 + (8 * wq + (lane >> 2)) * 32, lane);
    const uint32_t sown = __shfl_sync(~0u, sbuf + tile * 8, lane);
    const uint32_t peer = __shfl_sync(~0u, mapa(sb, r ^ 1) - sb, lane);
    const uint32_t hbuf = __shfl_sync(~0u, H + w * 4096 + wt * 16, lane);
    const uint32_t meta = __shfl_sync(~0u, 0xEEEE4444u + p.zero, lane);
    cluster_wait();
    TS(56);
    float mean, msq;
    const int mir = wq < 2 ? 7 : 0;
    uint32_t dwr[15] = {};

#pragma unroll
    for (int ph = 0; ph < 5; ph++) {
        uint4 o0, o1;
        if (ph == 0) {
            const uint32_t one = 0x3F803F80u + ((xown | xrem | sbuf | sown | hbuf | foff | rdesc | fbar) & p.zero);
            mean = ((row_sum<8>(a, one) + row_sum<8>(a + 8, one)) + (row_sum<8>(a + 16, one) + row_sum<8>(a + 24, one))) * (1.f / 256.f);
            TS(57);
        } else {
            const uint32_t xa = bars + (B_XA + ph) * 8;
#pragma unroll
            for (int j = 0; j < 8; j++) xr[j] = pack2(v[2 * j], v[2 * j + 1]);
            const float s = row_sum<8>(xr), q = row_sumsq<8>(xr, lane);
            if (ph < 4) {
                sts128(xown, xr[0], xr[1], xr[2], xr[3]);
                sts128(xown + 2048, xr[4], xr[5], xr[6], xr[7]);
            }
            put_sums(sown, sown + peer, s, q, xa + peer, c4 == (lane >> 3));
            bar_sync(10, 256);
            if (ph < 4) {
                o0 = lds128(xown ^ 4096); o1 = lds128((xown ^ 4096) + 2048);
                st_async4(xown + peer, xr[0], xr[1], xr[2], xr[3], xa + (B_XB - B_XA) * 8 + peer);
                st_async4(xown + peer + 2048, xr[4], xr[5], xr[6], xr[7], xa + (B_XB - B_XA) * 8 + peer);
            }
            TS(57 + ph);
            if (ph == 3) acq(0);
            if (ph == 1) acq(16);
            mbar_wait(xa, 0);
            const float4 u0 = lds128f(sbuf), u1 = lds128f(sbuf + 16);
            mean = ((u0.x + u0.z) + (u1.x + u1.z)) * (1.f / 256.f);
            msq = ((u0.y + u0.w) + (u1.y + u1.w)) * (1.f / 256.f);
        }
        if (ph == 4) break;
        const uint32_t mean2 = pack2(mean, mean);
        auto centre = [&](int i, const uint4& u) {
            a[i] = hsub2(u.x, mean2); a[i + 1] = hsub2(u.y, mean2); a[i + 2] = hsub2(u.z, mean2); a[i + 3] = hsub2(u.w, mean2);
        };
        if (ph == 0) {
#pragma unroll
            for (int j = 0; j < 32; j++) a[j] = hsub2(a[j], mean2);
            zero(xr);
            if (trow < T_) {
                const char* src = xrow + tile * 128 + c4 * 4 + (mean2 & p.zero);
#pragma unroll
                for (int j = 0; j < 8; j++) asm volatile("ld.global.nc.b32 %0, [%1];" : "=r"(xr[j]) : "l"(src + 16 * j));
            }
            mean -= blo(mean2);
            msq = __shfl_sync(~0u, row_sumsq<16>(a, lane) + row_sumsq<16>(a + 16, lane), (lane & 28) + (lane >> 3)) * (1.f / 256.f);
            acq(0);
        } else {
#pragma unroll
            for (int j = 0; j < 8; j++) a[j] = hsub2(xr[j], mean2);
            centre(8, o0); centre(12, o1);
        }
        const float rstd = rsq(fmaxf(fmaf(-mean, mean, msq), 0.f) + 1e-5f);
        auto gather_peer = [&]() {
            mbar_wait(bars + (B_XB + ph) * 8, 0);
#pragma unroll
            for (int i = 0; i < 4; i++) centre(16 + 4 * i, lds128(xrem + i * 2048));
        };
        auto sp = [&](float (&d)[32], int n, const uint32_t* af, int flip, int acc) {
            const uint32_t lo = rdesc + p.zero * (ph * 64 + n + 1) + (n % NSLOT) * (SLOT >> 4);
            const uint64_t b0 = mkdesc(lo + flip * 512), b1 = mkdesc(lo + (flip ^ 1) * 512);
            wg_fence();
            mma_sp(d, af, b0, meta, acc);
            mma_sp(d, af + 4, b0 + 256, meta, 1);
            mma_sp(d, af + 8, b1, meta, 1);
            mma_sp(d, af + 12, b1 + 256, meta, 1);
            wg_commit();
        };
        float d0[32], d1[32];

        if (ph == 0 || ph == 3) {
            uint32_t h[32], ho[32];
            const float rs = 0.5f * rstd;
            const uint32_t inb = bars + (B_INB + (ph & 2) + w) * 8;
            bool ready = true;
            const int eager = ph ? (TWO ? EAGER + 5 : EAGER) : EAGER - 1;
            auto step = [&](float (&d)[32], int n, const uint32_t* af, int flip, int acc, auto work) {
                if (!ready) acq(n);
                if (((TURN >> n) & 1) && w == 1) bar_sync(7, 256);
                sp(d, n, af, flip, acc);
                if (n > 0 && ((TURN >> (n - 1)) & 1) && w == 0) bar_arrive(7, 256);
                if (n < 15) ready = mbar_test(fbar + ((n + 1) % NSLOT) * 8, ((n + 1) / NSLOT) & 1);
                wg_wait<1>();
                if (n > 0 && !((eager >> (n - 1)) & 1)) rel(n - 1);
                const uint32_t tie = work() & p.zero;
                if ((eager >> n) & 1) {
                    if (p.zero < n + ph + 1) wg_wait<0>();
                    if (lane == 0) mbar_arrive(fbar + (B_EMPTY - B_FULL + n % NSLOT) * 8 + tie);
                }
            };
            auto none = []() { return 0u; };
            const int fl = ph ? w : 0;
            auto fetch = [&](int i) {
                if (SPLIT) bar_sync(2 * (i & 1) + (w ^ 1), 256);
                else bar_sync(10, 256);
                const uint4 u0 = lds128((hbuf ^ 4096) + (i & 1) * 8192), u1 = lds128((hbuf ^ 4096) + (i & 1) * 8192 + 2048);
                ho[8 * i] = u0.x; ho[8 * i + 1] = u0.y; ho[8 * i + 2] = u0.z; ho[8 * i + 3] = u0.w;
                ho[8 * i + 4] = u1.x; ho[8 * i + 5] = u1.y; ho[8 * i + 6] = u1.z; ho[8 * i + 7] = u1.w;
                return u0.x | u1.x;
            };
            auto act = [&](float (&d)[32], int i) {
                if (i > 0) fetch(i - 1);
                pin(d);
#pragma unroll
                for (int j = 0; j < 8; j++) {
                    const float u0 = (d[4 * j] + d[4 * j + 2]) * rs, u1 = (d[4 * j + 1] + d[4 * j + 3]) * rs;
                    h[8 * i + j] = pack2(fmaf(u0, tanh_fast(u0), u0), fmaf(u1, tanh_fast(u1), u1));
                }
                sts128(hbuf + (i & 1) * 8192, h[8 * i], h[8 * i + 1], h[8 * i + 2], h[8 * i + 3]);
                sts128(hbuf + (i & 1) * 8192 + 2048, h[8 * i + 4], h[8 * i + 5], h[8 * i + 6], h[8 * i + 7]);
                if (SPLIT) bar_arrive(2 * (i & 1) + w, 256);
                return 0u;
            };
            TS(1 + (ph & 2) * 10);
            if (TWO && ph) {
                step(d0, 0, a, fl, 0, none);
                step(d1, 1, a, fl, 0, [&]() { gather_peer(); return 0u; });
                TS(32);
                step(d0, 2, a + 16, 0, 1, none);
                step(d1, 3, a + 16, 0, 1, [&]() { return act(d0, 0); });
            } else {
                step(d0, 0, a, fl, 0, [&]() { if (ph) gather_peer(); return 0u; });
                TS(32);
                step(d0, 1, a + 16, 0, 1, none);
                step(d1, 2, a, fl, 0, [&]() { return act(d0, 0); });
                step(d1, 3, a + 16, 0, 1, none);
            }
            step(d0, 4, a, fl, 0, [&]() { return act(d1, 1); });
            TS(33);
            step(d0, 5, a + 16, 0, 1, none);
            step(d1, 6, a, fl, 0, [&]() { return act(d0, 2); });
            step(d1, 7, a + 16, 0, 1, none);
            step(d0, 8, h, 0, 0, [&]() { act(d1, 3); return fetch(3); });
            TS(2 + (ph & 2) * 10);
            step(d0, 9, ho, 0, 1, none);
            step(d0, 10, h + 16, 0, 1, none);
            step(d0, 11, ho + 16, 0, 1, none);
            uint32_t pk[8];
            auto pack_out = [&]() {
                pin(d0);
#pragma unroll
                for (int j = 0; j < 8; j++) pk[j] = pack2(d0[4 * j] + d0[4 * j + 2], d0[4 * j + 1] + d0[4 * j + 3]);
            };
            auto send = [&](int i) { st_async4(hbuf + 16384 + i * 2048 + peer, pk[4 * i], pk[4 * i + 1], pk[4 * i + 2], pk[4 * i + 3], inb + peer); };
            step(d1, 12, h, 0, 0, [&]() { pack_out(); if (SND != 1) send(0); if (SND == 0) send(1); return 0u; });
            TS(34);
            step(d1, 13, ho, 0, 1, [&]() { if (SND == 1) send(0); if (SND) send(1); return 0u; });
            step(d1, 14, h + 16, 0, 1, none);
            step(d1, 15, ho + 16, 0, 1, none);
            mbar_wait(inb, 0);
#pragma unroll
            for (int i = 0; i < 2; i++) {
                const uint4 u = lds128(hbuf + 16384 + i * 2048);
                const uint32_t p0[4] = {u.x, u.y, u.z, u.w};
#pragma unroll
                for (int j = 0; j < 4; j++) {
                    v[8 * i + 2 * j] = fmaf(0.5f, blo(p0[j]), blo(xr[4 * i + j]));
                    v[8 * i + 2 * j + 1] = fmaf(0.5f, bhi(p0[j]), bhi(xr[4 * i + j]));
                }
            }
            wg_wait<0>();
            pin(d1);
            rel(15);
            TS(3 + (ph & 2) * 10);
#pragma unroll
            for (int j = 0; j < 8; j++) {
                v[2 * j] = fmaf(0.5f, d1[4 * j] + d1[4 * j + 2], v[2 * j]);
                v[2 * j + 1] = fmaf(0.5f, d1[4 * j + 1] + d1[4 * j + 3], v[2 * j + 1]);
            }
#pragma unroll
            for (int i = 0; i < 15; i++) dwr[i] = 0;
            continue;
        }

        auto residual = [&](int n) {
            wg_wait<1>();
            rel(n);
            wg_wait<0>();
            pin(d0);
            rel(n + 1);
#pragma unroll
            for (int j = 0; j < 8; j++) {
                v[2 * j] = d0[4 * j] + d0[4 * j + 2] + blo(xr[j]);
                v[2 * j + 1] = d0[4 * j + 1] + d0[4 * j + 3] + bhi(xr[j]);
            }
        };

        if (ph == 2) {
            TS(39);
            sp(d0, 34, a, w, 0);
            acq(35);
            sp(d1, 35, a, w, 0);
            acq(36); acq(37);
            gather_peer();
            sp(d0, 36, a + 16, 0, 1);
            sp(d1, 37, a + 16, 0, 1);
            wg_wait<2>();
            rel(34);
            if (!(LATE & 1)) rel(35);
            acq(38);
            const float rs = trow < T_ ? 0.5f * rstd : 0.f;
            wg_wait<0>();
            pin(d0); pin(d1);
            if (!(LATE & 2)) { rel(36); rel(37); }
            TS(18);
            uint32_t pk[8];
#pragma unroll
            for (int j = 0; j < 8; j++) {
                const float u0 = (d0[4 * j] + d0[4 * j + 2]) * rs, u1 = (d0[4 * j + 1] + d0[4 * j + 3]) * rs;
                const float t0 = tanh_fast((d1[4 * j] + d1[4 * j + 2]) * rs), t1 = tanh_fast((d1[4 * j + 1] + d1[4 * j + 3]) * rs);
                pk[j] = pack2(fmaf(u0, t0, u0), fmaf(u1, t1, u1));
            }
            if (wq == 0 || wq == 3) {
                uint4* hp = &g_halo[((pair * 4 + tile) * 2 + (wq & 1)) * 64 + lane];
                st_data(hp, pk[0], pk[1], pk[2], pk[3]);
                st_data(hp + 32, pk[4], pk[5], pk[6], pk[7]);
            }
            const uint32_t gs = H + 16384 + w * GCH + wq * 1024;
            stsm4(gs + 1024 + foff, pk[0], pk[1], pk[2], pk[3]);
            stsm4(gs + 1024 + (foff ^ 64), pk[4], pk[5], pk[6], pk[7]);
            bar_sync(8 + w, 192);
            TS(26);
            uint32_t ca[8], cb[8];
            const int e = (wq & 1) * 4;
            const uint32_t lo = ((mir ^ e) * 144) ^ (lane * 4);
            const int dir = mir ? -1024 : 1024;
            const uint32_t gb = H + 16384 + w * GCH + (mir ? 3072 : 2048) + lo, sown_ = H + tile * HCH, so = sown_ + (mir ? 1024 : 2048) + lo;
            auto finish = [&](int i) {
                const uint32_t c = hadd2(ca[i], cb[i]);
                const float h0 = blo(c), h1 = bhi(c);
                const uint32_t dst = (so + (i >> 2) * dir) ^ ((i & 3) * 144), val = pack2(fmaf(h0, tanh_fast(h0), h0), fmaf(h1, tanh_fast(h1), h1));
                if ((SAS >> (i >> 2)) & 1)
                    asm volatile("st.async.shared::cluster.mbarrier::complete_tx::bytes.b32 [%0], %1, [%2];" ::"r"(dst + peer), "r"(val), "r"(bars + B_SR * 8 + peer) : "memory");
                sts32(dst, val);
            };
#pragma unroll
            for (int k = 0; k < 26; k++) {
                if (k == 19) {
#pragma unroll
                    for (int i = 0; i < 4; i++) finish(i);
                    if (!(SAS & 1)) {
                        fence_async_smem();
                        bar_sync(2 + w, 128);
                        if (wq == 0) peer_copy(mapa(sown_ + 1024, r ^ 1), sown_ + 1024, 2048, mapa(bars + B_SR * 8, r ^ 1));
                    }
                    mbar_wait(bars + (B_HALO + 2 * w + (wq >> 1)) * 8, 0);
                    if (LATE & 1) rel(35);
                    if (LATE & 2) { rel(36); rel(37); }
                    TS(27);
                }
                const uint32_t g = lds32((gb + (((k + 1) & 4) ? ((k + 1) >> 3) + (wq & 1) : ((k + 1) >> 3)) * dir) ^ (((k + 1) & 7) * 144));
#pragma unroll
                for (int i = 0; i < 8; i++) {
                    const int tap = k - (i & 3) - 2 * (i & 4);
                    if (tap == 0) ca[i] = hmul2(g, dwr[0]);
                    else if (tap > 0 && tap < 8) ca[i] = hfma2(g, dwr[tap], ca[i]);
                    else if (tap == 8) cb[i] = hmul2(g, dwr[8]);
                    else if (tap > 8 && tap < 15) cb[i] = hfma2(g, dwr[tap], cb[i]);
                }
            }
#pragma unroll
            for (int i = 4; i < 8; i++) finish(i);
            if (!(SAS & 2)) {
                fence_async_smem();
                bar_sync(12 + (warp >> 1), 64);
                if (wq == 0 || wq == 3) peer_copy(mapa(sown_ + wq * 1024, r ^ 1), sown_ + wq * 1024, 1024, mapa(bars + B_SR * 8, r ^ 1));
            }
            bar_sync(10, 256);
            TS(19);
            auto frags = [&](int i, int half) {
                const uint32_t src = H + 2 * half * HCH + wq * 1024;
#pragma unroll
                for (int k = 0; k < 4; k++) ldsm4(src + (k >> 1) * HCH + (foff ^ ((k & 1) * 64)), a[i + 4 * k], a[i + 4 * k + 1], a[i + 4 * k + 2], a[i + 4 * k + 3]);
            };
            frags(0, r);
            sp(d0, 38, a, 0, 0);
            acq(39);
            mbar_wait(bars + B_SR * 8, 0);
            frags(16, r ^ 1);
            sp(d0, 39, a + 16, 0, 1);
            residual(38);
            TS(20);
            continue;
        }

        {
            TS(11);
            unsigned char* g = g_kvq + (size_t)((b * 4 + tile) * 1024 + trow) * 128;
            const uint32_t uo = (lane >> 2) * 128 + ((c4 ^ (lane >> 2)) << 4);
            auto put = [&](float (&d)[32], int i) {
                pin(d);
                uint32_t pk[8];
#pragma unroll
                for (int j = 0; j < 8; j++) pk[j] = pack2((d[4 * j] + d[4 * j + 2]) * rstd, (d[4 * j + 1] + d[4 * j + 3]) * rstd);
                if (i < 2) {
                    stg128(g + i * 1048576 + uo, make_uint4(pk[0], pk[1], pk[2], pk[3]));
                    stg128(g + i * 1048576 + (uo ^ 64), make_uint4(pk[4], pk[5], pk[6], pk[7]));
                } else {
                    const uint32_t stg = H + warp * 1024;
                    sts128(stg + uo, pk[0], pk[1], pk[2], pk[3]);
                    sts128(stg + (uo ^ 64), pk[4], pk[5], pk[6], pk[7]);
                    __syncwarp();
                    ldsm4(stg + foff, pk[0], pk[1], pk[2], pk[3]);
                    ldsm4(stg + (foff ^ 64), pk[4], pk[5], pk[6], pk[7]);
                    st_data(g + 2097152 + lane * 16, ~pk[0], ~pk[1], ~pk[2], ~pk[3]);
                    st_data(g + 2097152 + 512 + lane * 16, ~pk[4], ~pk[5], ~pk[6], ~pk[7]);
                }
            };
            sp(d0, 16, a, w, 0);
            acq(17);
            sp(d1, 17, a, w, 0);
            gather_peer();
            acq(18);
            sp(d0, 18, a + 16, 0, 1);
            wg_wait<1>();
            rel(16); rel(17);
            acq(19);
            sp(d1, 19, a + 16, 0, 1);
            wg_wait<1>();
            rel(18);
            put(d0, 0);
            wg_wait<0>();
            rel(19);
            TS(37);
            put(d1, 1);
            bar_arrive(4, 288);
            TS(38);
            acq(20);
            sp(d0, 20, a, w, 0);
            acq(21);
            sp(d0, 21, a + 16, 0, 1);
            acq(22); acq(23);
            rel(22); rel(23);
            wg_wait<0>();
            rel(20); rel(21);
            put(d0, 2);
            TS(12);
        }

        {
            constexpr float CS = 0.125f * 1.4426950408889634f;
            float sa[32], sb2[32], o[36];
            uint32_t pa[16], pb[16], q[16];
            float n0 = INFINITY, n1 = INFINITY;
            zero(o); zero(pa); zero(pb); zero(sb2);
            const uint32_t ones = sb + OFF_MISC + 2048;
            { const uint32_t c = w ? 0u : 0x3F803F80u; sts128(ones + tid * 16, c, c, c, c); }
            fence_async_smem();
            bar_sync(10, 256);
            const uint32_t vdesc = rdesc + ((((ones - rbase) >> 4) - 1) << 16);
            auto qk_issue = [&](float (&s)[32], uint32_t lo) {
                const uint64_t kd = mkdesc(lo);
                wg_fence();
#pragma unroll
                for (int k = 0; k < 4; k++) mma_qk(s, q[4 * k], q[4 * k + 1], q[4 * k + 2], q[4 * k + 3], kd + 2 * k, k != 0);
                wg_commit();
            };
            auto both_issue = [&](float (&s)[32], uint32_t klo, uint32_t (&pp)[16], uint32_t vlo) {
                const uint64_t kd = mkdesc(klo), vd = mkdesc(vlo);
                wg_fence();
#pragma unroll
                for (int k = 0; k < 4; k++) {
                    mma_pv(o, pp[4 * k], pp[4 * k + 1], pp[4 * k + 2], pp[4 * k + 3], vd - k * (128 * 65535));
                    mma_qk(s, q[4 * k], q[4 * k + 1], q[4 * k + 2], q[4 * k + 3], kd + 2 * k, k != 0);
                }
                wg_commit();
            };
            auto new_max = [&](float (&s)[32], int nj, float& x0, float& x1) {
                x0 = s[0]; x1 = s[2];
#pragma unroll
                for (int j = 0; j < nj; j++) {
                    x0 = fmaxf(x0, fmaxf(s[4 * j], s[4 * j + 1]));
                    x1 = fmaxf(x1, fmaxf(s[4 * j + 2], s[4 * j + 3]));
                }
                x0 = fmaxf(x0, __shfl_xor_sync(~0u, x0, 1)); x1 = fmaxf(x1, __shfl_xor_sync(~0u, x1, 1));
                x0 = fmaxf(x0, __shfl_xor_sync(~0u, x0, 2)); x1 = fmaxf(x1, __shfl_xor_sync(~0u, x1, 2));
                x0 = fminf(n0, fmaf(x0, -CS, -20.f)); x1 = fminf(n1, fmaf(x1, -CS, -20.f));
            };
            auto probs = [&](float (&s)[32], uint32_t (&pp)[16], bool ready, bool tail, auto wait) {
                uint32_t any = 0;
#pragma unroll
                for (int i = 0; i < 16; i++) {
                    pp[i] = pack2(ex2(fmaf(s[2 * i], CS, (i & 1) ? n1 : n0)), ex2(fmaf(s[2 * i + 1], CS, (i & 1) ? n1 : n0)));
                    any |= pp[i];
                }
                wg_wait<0>();
                pin(sa); pin(sb2); pin(o); pin(pa); pin(pb);
                if (__builtin_expect(__any_sync(~0u, (any & 0x40004000u) || !ready), 0)) {
                    wait();
                    if (__any_sync(~0u, any & 0x40004000u)) {
                        if (tail) {
#pragma unroll
                            for (int i = 20; i < 32; i++) s[i] = -INFINITY;
                        }
                        float x0, x1;
                        new_max(s, 8, x0, x1);
                        const float sc0 = ex2(x0 - n0), sc1 = ex2(x1 - n1);
                        n0 = x0; n1 = x1;
#pragma unroll
                        for (int j = 0; j < 9; j++) { o[4 * j] *= sc0; o[4 * j + 1] *= sc0; o[4 * j + 2] *= sc1; o[4 * j + 3] *= sc1; }
#pragma unroll
                        for (int i = 0; i < 16; i++)
                            pp[i] = pack2(ex2(fmaf(s[2 * i], CS, (i & 1) ? n1 : n0)), ex2(fmaf(s[2 * i + 1], CS, (i & 1) ? n1 : n0)));
                    }
                }
            };
            {
                uint4 u[4];
                const unsigned char* src = g_kvq + 2097152 + (size_t)(abh * 1024 + qt * 64 + wq * 16) * 128 + lane * 16;
                spin(QGATE);
                ld_data<512, true>(u, src);
#pragma unroll
                for (int k = 0; k < 2; k++) {
                    q[8 * k] = ~u[k].x; q[8 * k + 1] = ~u[k + 2].x; q[8 * k + 2] = ~u[k].y; q[8 * k + 3] = ~u[k + 2].y;
                    q[8 * k + 4] = ~u[k].z; q[8 * k + 5] = ~u[k + 2].z; q[8 * k + 6] = ~u[k].w; q[8 * k + 7] = ~u[k + 2].w;
                }
                pin(q);
            }
            TS(40);
            acq(24);
            TS(13);
            qk_issue(sa, rdesc + (24 % NSLOT) * (SLOT >> 4));
            wg_wait<0>();
            pin(sa);
            {
                float x0, x1;
                new_max(sa, NJ0, x0, x1);
                n0 = x0; n1 = x1;
            }
            bar_arrive(6, 384);
            uint32_t vd = vdesc - (SLOT >> 4) * 65535u, kd = rdesc, vb = fbar + 8, kb = fbar;
            uint32_t vlast = vdesc - 4 * (SLOT >> 4) * 65535u, klast = rdesc + 4 * (SLOT >> 4) + 512;
            uint32_t kprev = fbar + 32, vprev = bars + (B_SINK - (B_EMPTY - B_FULL)) * 8;
#pragma unroll 1
            for (int it = 0; it < 4; it++) {
                both_issue(sb2, klast, pb, vlast);
                probs(sa, pa, mbar_test(vb, it < 2) & mbar_test(kb, it < 3), false, [&]() { mbar_wait(vb, it < 2); mbar_wait(kb, it < 3); });
                TS(41 + it * 4);
                if (lane == 0) mbar_arrive(kprev + (B_EMPTY - B_FULL) * 8);
                if (lane == 0) mbar_arrive(vprev + (B_EMPTY - B_FULL) * 8);
                both_issue(sa, kd, pa, vd);
                const int dv = it == 0 ? 2 : (it == 1 ? -3 : 1);
                kprev = kb; vprev = vb; vlast = vd - 512 * 65535u; klast = kd + 512;
                vd -= dv * (SLOT >> 4) * 65535u; vb += dv * 8;
                kd += (it == 2 ? -3 : 2) * (SLOT >> 4); kb = it == 2 ? vb : kb + 16;
                probs(sb2, pb, true, it == 3 && w == 1, []() {});
                TS(43 + it * 4);
            }
            wg_fence();
#pragma unroll
            for (int k = 0; k < 4; k++)
                mma_pv(o, pb[4 * k], pb[4 * k + 1], pb[4 * k + 2], pb[4 * k + 3], mkdesc(vlast - k * (128 * 65535) + (k > 1 ? w * ((k - 1) << 22) : 0)));
            wg_commit();
            const uint32_t mlw = sb + OFF_MISC + (tid >> 2) * 8;
            unsigned char* odst = g_o + (size_t)(b * 128 + qt * 8 + 2 * wq + w) * 4096 + ah * 1024 + lane * 16;
            mbar_wait(bars + B_RST * 8, (mlw | (uint32_t)(size_t)odst) & p.zero);
            wg_wait<0>();
            pin(o); pin(pb); pin(sa); pin(sb2);
            if (!(LATE & 4)) rel(31);
            TS(14);
            auto merge = [&](int keep, float nk, float ns) {
                const int snd = 2 - keep;
                if (c4 == 0) sts64f(mlw, ns, o[32 + snd]);
                if (MRG == 0) {
#pragma unroll
                    for (int j = 0; j < 4; j++)
                        sts128f(hbuf + (j & 1) * 2048 + (j >> 1) * 8192, o[8 * j + snd], o[8 * j + snd + 1], o[8 * j + 4 + snd], o[8 * j + 5 + snd]);
                } else {
#pragma unroll
                    for (int j = 0; j < 2; j++)
                        sts128(hbuf + j * 2048, pack2(o[16 * j + snd], o[16 * j + snd + 1]), pack2(o[16 * j + 4 + snd], o[16 * j + 5 + snd]),
                               pack2(o[16 * j + 8 + snd], o[16 * j + 9 + snd]), pack2(o[16 * j + 12 + snd], o[16 * j + 13 + snd]));
                }
                bar_sync(10, 256);
                const float2 u = lds64f(mlw ^ 256);
                const float x = fminf(nk, u.x);
                float a = ex2(x - nk), c = ex2(x - u.x);
                const float inv = rcp(fmaf(a, o[32 + keep], c * u.y));
                a *= inv; c *= inv;
                uint32_t pk[8];
                if (MRG == 0) {
#pragma unroll
                    for (int j = 0; j < 4; j++) {
                        const float4 t = lds128f((hbuf ^ 4096) + (j & 1) * 2048 + (j >> 1) * 8192);
                        pk[2 * j] = pack2(fmaf(a, o[8 * j + keep], c * t.x), fmaf(a, o[8 * j + keep + 1], c * t.y));
                        pk[2 * j + 1] = pack2(fmaf(a, o[8 * j + 4 + keep], c * t.z), fmaf(a, o[8 * j + 5 + keep], c * t.w));
                    }
                } else {
#pragma unroll
                    for (int j = 0; j < 2; j++) {
                        const uint4 t4 = lds128((hbuf ^ 4096) + j * 2048);
                        const uint32_t t[4] = {t4.x, t4.y, t4.z, t4.w};
#pragma unroll
                        for (int i = 0; i < 4; i++)
                            pk[4 * j + i] = pack2(fmaf(a, o[16 * j + 4 * i + keep], c * blo(t[i])), fmaf(a, o[16 * j + 4 * i + keep + 1], c * bhi(t[i])));
                    }
                }
                st_data(odst, pk[0], pk[1], pk[2], pk[3]);
                st_data(odst + 512, pk[4], pk[5], pk[6], pk[7]);
            };
            if (MW ? w == 0 : tid < 128) merge(0, n0, n1); else merge(2, n1, n0);
            if (tid == 0) asm volatile("red.relaxed.gpu.global.add.u32 [%0], 1;" ::"l"(&g_epoch[blockIdx.x * FS]) : "memory");
            TS(15);
        }

        {
            const uint32_t* dp = reinterpret_cast<const uint32_t*>(p.dw + (mir ? 14 * 256 : 0) + tile * 64) + lane;
#pragma unroll
            for (int i = 0; i < 15; i++) asm volatile("ld.global.nc.b32 %0, [%1];" : "=r"(dwr[i]) : "l"(dp + i * (mir ? -128 : 128)));
            acq(32); acq(33); acq(34);
            uint4 u[8];
            ld_data<512>(u, g_o + (size_t)(b * 128 + pt * 4 + wq) * 4096 + lane * 16);
#pragma unroll
            for (int i = 0; i < 8; i++) { a[4 * i] = u[i].x; a[4 * i + 1] = u[i].y; a[4 * i + 2] = u[i].z; a[4 * i + 3] = u[i].w; }
            if (LATE & 4) rel(31);
            TS(16);
            sp(d0, 32, a, 0, 0);
            sp(d0, 33, a + 16, 0, 1);
#pragma unroll
            for (int i = 0; i < 15; i++) dwr[i] = hmul2(dwr[i], 0x3F003F00u);
            residual(32);
            TS(17);
        }
    }

    cluster_arrive();
    TS(24);
    {
        const float rstd = rsq(fmaxf(fmaf(-mean, mean, msq), 0.f) + 1e-5f), nb = -mean * rstd;
#pragma unroll
        for (int j = 0; j < 8; j++) xr[j] = pack2(fmaf(v[2 * j], rstd, nb), fmaf(v[2 * j + 1], rstd, nb));
        const uint32_t stg = P + 16384 + warp * 1024;
        stsm4(stg + foff, xr[0], xr[1], xr[2], xr[3]);
        stsm4(stg + (foff ^ 64), xr[4], xr[5], xr[6], xr[7]);
        __syncwarp();
        const uint32_t src = stg + (lane >> 3) * 128 + (((lane & 7) ^ (lane >> 3)) << 4);
        const uint4 u0 = lds128(src), u1 = lds128((src + 512) ^ 64);
        __nv_bfloat16* dst = p.out + (size_t)(b * T_ + trow + (lane >> 3)) * 256 + tile * 64 + (lane & 7) * 8;
        if (trow < T_) { stg128(dst, u0); stg128(dst + 4 * 256, u1); }
    }
    TS(25);
    TG(31);
    TSDUMP();
    cluster_wait();
}

typedef CUresult (*EncodeFn)(CUtensorMap*, CUtensorMapDataType, cuuint32_t, void*, const cuuint64_t*, const cuuint64_t*,
                             const cuuint32_t*, const cuuint32_t*, CUtensorMapInterleave, CUtensorMapSwizzle,
                             CUtensorMapL2promotion, CUtensorMapFloatOOBfill);

}

extern "C" void kernel_launch(void* const* d_in, const int* in_sizes, int n_in, void* d_out, int out_size) {
    static EncodeFn encode = nullptr;
    if (!encode) {
        void* fn = nullptr;
        cudaDriverEntryPointQueryResult qr;
        cudaGetDriverEntryPoint("cuTensorMapEncodeTiled", &fn, cudaEnableDefault, &qr);
        encode = (EncodeFn)fn;
        cudaFuncSetAttribute(conformer_kernel, cudaFuncAttributeMaxDynamicSharedMemorySize, SMEM_LAUNCH);
    }
    Scalars p;
    Maps m;
    const cuuint32_t ones[5] = {1, 1, 1, 1, 1};
    const int idx[8] = {1, 2, 3, 4, 5, 7, 8, 9};
    const int rows[8] = {256, 1024, 256, 256, 256, 256, 256, 1024};
    const int cols[8] = {1024, 256, 768, 256, 512, 256, 1024, 256};
    for (int i = 0; i < 8; i++) {
        const cuuint64_t pitch = (cuuint64_t)cols[i] * 2;
        const bool f = i != 0 && i != 3;
        const cuuint64_t dims[5] = {(cuuint64_t)cols[i], f ? 2u : 4u, f ? 2u : 4u, f ? 4u : 2u, (cuuint64_t)rows[i] / (f ? 16 : 32)};
        const cuuint64_t strides[4] = {pitch, pitch * 8, pitch * (f ? 2 : 4), pitch * (f ? 16 : 32)};
        const cuuint32_t box[5] = {64, f ? 2u : 4u, f ? 2u : 4u, f ? 4u : 2u, f ? 8u : 4u};
        encode(&m.tm[i], CU_TENSOR_MAP_DATA_TYPE_BFLOAT16, 5, d_in[idx[i]], dims, strides, box, ones, CU_TENSOR_MAP_INTERLEAVE_NONE,
               CU_TENSOR_MAP_SWIZZLE_128B, CU_TENSOR_MAP_L2_PROMOTION_L2_128B, CU_TENSOR_MAP_FLOAT_OOB_FILL_NONE);
        m.w[i] = (const char*)d_in[idx[i]];
    }
    {
        void* kv = nullptr;
        cudaGetSymbolAddress(&kv, g_kvq);
        const cuuint64_t dims[2] = {64, 16384};
        const cuuint64_t strides[1] = {128};
        const cuuint32_t box[2] = {64, 128};
        encode(&m.tm[8], CU_TENSOR_MAP_DATA_TYPE_BFLOAT16, 2, kv, dims, strides, box, ones, CU_TENSOR_MAP_INTERLEAVE_NONE,
               CU_TENSOR_MAP_SWIZZLE_NONE, CU_TENSOR_MAP_L2_PROMOTION_L2_128B, CU_TENSOR_MAP_FLOAT_OOB_FILL_NONE);
    }
    p.x = (const __nv_bfloat16*)d_in[0];
    p.dw = (const __nv_bfloat16*)d_in[6];
    p.out = (__nv_bfloat16*)d_out;
    p.zero = 0;
    conformer_kernel<<<NCTA, NTHREADS, SMEM_LAUNCH>>>(p, m);
}
```

```cpp
#include <cuda_runtime.h>
#include <cuda_bf16.h>
#include <cuda.h>
#include <stdint.h>

namespace {

constexpr int T_ = 1000;
constexpr int NCTA = 128;
constexpr int NTHREADS = 512;
constexpr int NSLOT = 5;
constexpr int SLOT = 16384;
constexpr int NLOADS = 56;

constexpr uint32_t OFF_RING = 0;
constexpr uint32_t OFF_P = 163840;
constexpr uint32_t OFF_H = 188416;
constexpr uint32_t OFF_MISC = 221184;
constexpr uint32_t OFF_BARS = 229888;
constexpr uint32_t SMEM_BYTES = 230400;
constexpr uint32_t GCH = 6144;
constexpr uint32_t HCH = 4096;

constexpr int B_FULL = 0, B_EMPTY = 10, B_XA = 20  , B_XB = 25  , B_INB = 29  , B_SR = 33,
              B_RST = 34, B_RDY = 35  , B_SINK = 41, B_HALO = 42  , NBARS = 46;

#define KD2 300u
#define KD3 500u
#define QGATE 700u
#define BACKOFF 0u
#define KFS 8
#define KDELAY 250u
#define NJ0 2
#define HDELAY 200u
#define LATE 3
#define SND 0
#define PF0 0
#define TWO 1
#define WARMF 1
#define USQ 1
#define ONE 0
#define TURN 0
#define EAGER 0x0155
constexpr int FS = 8;

struct Scalars {
    const __nv_bfloat16* x;
    const __nv_bfloat16* dw;
    __nv_bfloat16* out;
    uint32_t zero;
};
struct Maps {
    CUtensorMap tm[9];
    const char* w[8];
};

__device__ __align__(1024) unsigned char g_kvq[3 * 8 * 1024 * 128];
__device__ __align__(1024) unsigned char g_o[2 * 128 * 4096];
__device__ uint4 g_halo[64 * 4 * 2 * 64];
__device__ __align__(128) uint32_t g_flag_kv[8 * 32 * KFS];
__device__ uint32_t g_reset[2 * 32];
__device__ uint32_t g_epoch[NCTA * FS];

#define TS(i) do { } while (0)
#define TSW(i) do { } while (0)
#define TG(i) do { } while (0)
#define TSINIT() do { } while (0)
#define TSDUMP() do { } while (0)
constexpr uint32_t SMEM_LAUNCH = SMEM_BYTES;

__device__ __forceinline__ uint32_t smem_u32(const void* p) { return (uint32_t)__cvta_generic_to_shared(p); }
__device__ __forceinline__ void mbar_init(uint32_t b, uint32_t c) { asm volatile("mbarrier.init.shared::cta.b64 [%0], %1;" ::"r"(b), "r"(c) : "memory"); }
__device__ __forceinline__ void mbar_arrive(uint32_t b) { asm volatile("mbarrier.arrive.shared::cta.b64 _, [%0];" ::"r"(b) : "memory"); }
__device__ __forceinline__ void mbar_arrive_tx(uint32_t b, uint32_t tx) { asm volatile("mbarrier.arrive.expect_tx.shared::cta.b64 _, [%0], %1;" ::"r"(b), "r"(tx) : "memory"); }
__device__ __forceinline__ void mbar_wait(uint32_t b, uint32_t ph) {
    asm volatile("{\n.reg .pred p, q;\n.reg .u32 c;\nmov.u32 c, 0;\n"
                 "MW_LOOP:\n.pragma \"nounroll\";\n"
                 "mbarrier.try_wait.parity.shared::cta.b64 p, [%0], %1;\n"
                 "add.u32 c, c, 1;\nsetp.lt.u32 q, c, 65536;\nnot.pred p, p;\nand.pred p, p, q;\n@p bra MW_LOOP;\n}"
                 ::"r"(b), "r"(ph) : "memory");
}
__device__ __forceinline__ bool mbar_test(uint32_t b, uint32_t ph) {
    uint32_t ok;
    asm volatile("{\n.reg .pred p;\nmbarrier.test_wait.parity.shared::cta.b64 p, [%1], %2;\nselp.u32 %0, 1, 0, p;\n}" : "=r"(ok) : "r"(b), "r"(ph) : "memory");
    return ok;
}
__device__ __forceinline__ uint32_t mapa(uint32_t a, uint32_t r) { uint32_t o; asm("mapa.shared::cluster.u32 %0, %1, %2;" : "=r"(o) : "r"(a), "r"(r)); return o; }
__device__ __forceinline__ void fence_async_smem() { asm volatile("fence.proxy.async.shared::cta;" ::: "memory"); }
__device__ __forceinline__ void fence_async_global() { asm volatile("fence.proxy.async.global;" ::: "memory"); }
__device__ __forceinline__ void bar_sync(int id, int n) { asm volatile("bar.sync %0, %1;" ::"r"(id), "r"(n) : "memory"); }
__device__ __forceinline__ void bar_arrive(int id, int n) { asm volatile("bar.arrive %0, %1;" ::"r"(id), "r"(n) : "memory"); }
__device__ __forceinline__ void cluster_arrive() { asm volatile("barrier.cluster.arrive.relaxed.aligned;" ::: "memory"); }
__device__ __forceinline__ void cluster_wait() { asm volatile("barrier.cluster.wait.aligned;" ::: "memory"); }

__device__ __forceinline__ void ring_load(uint32_t dst, const CUtensorMap* tm, int col, int row16, uint32_t bar) {
    asm volatile("{\n.reg .pred p;\nelect.sync _|p, 0xffffffff;\n"
                 "@p mbarrier.arrive.expect_tx.shared::cta.b64 _, [%2], 16384;\n"
                 "@p cp.async.bulk.tensor.5d.shared::cluster.global.mbarrier::complete_tx::bytes [%0], [%1, {%3, 0, 0, 0, %4}], [%2];\n}"
                 ::"r"(dst), "l"(tm), "r"(bar), "r"(col), "r"(row16) : "memory");
}
__device__ __forceinline__ void ring_load_both(uint32_t dst, const CUtensorMap* tm, int c1, uint32_t bar) {
    asm volatile("{\n.reg .pred p;\nelect.sync _|p, 0xffffffff;\n"
                 "@p cp.async.bulk.tensor.2d.shared::cluster.global.mbarrier::complete_tx::bytes.multicast::cluster [%0], [%1, {0, %3}], [%2], %4;\n}"
                 ::"r"(dst), "l"(tm), "r"(bar), "r"(c1), "h"((uint16_t)3) : "memory");
}
__device__ __forceinline__ void mbar_arrive_peer(uint32_t b) { asm volatile("mbarrier.arrive.relaxed.cluster.shared::cluster.b64 _, [%0];" ::"r"(b) : "memory"); }
__device__ __forceinline__ void prefetch_l2(const void* src, uint32_t bytes) {
    asm volatile("cp.async.bulk.prefetch.L2.global [%0], %1;" ::"l"(src), "r"(bytes) : "memory");
}
__device__ __forceinline__ void st_async4(uint32_t dst, uint32_t a, uint32_t b, uint32_t c, uint32_t d, uint32_t bar) {
    asm volatile("st.async.shared::cluster.mbarrier::complete_tx::bytes.v4.b32 [%0], {%1,%2,%3,%4}, [%5];" ::"r"(dst), "r"(a), "r"(b), "r"(c), "r"(d), "r"(bar) : "memory");
}
__device__ __forceinline__ void put_sums(uint32_t dst, uint32_t rdst, float a, float b, uint32_t rbar, bool on) {
    asm volatile("{\n.reg .pred p;\nsetp.ne.u32 p, %5, 0;\n"
                 "@p st.async.shared::cluster.mbarrier::complete_tx::bytes.v2.f32 [%1], {%2,%3}, [%4];\n"
                 "@p st.shared.v2.f32 [%0], {%2,%3};\n}" ::"r"(dst), "r"(rdst), "f"(a), "f"(b), "r"(rbar), "r"((uint32_t)on) : "memory");
}
__device__ __forceinline__ void stsm4(uint32_t a, uint32_t r0, uint32_t r1, uint32_t r2, uint32_t r3) {
    asm volatile("stmatrix.sync.aligned.m8n8.x4.shared.b16 [%0], {%1,%2,%3,%4};" ::"r"(a), "r"(r0), "r"(r1), "r"(r2), "r"(r3) : "memory");
}
__device__ __forceinline__ void ldsm4(uint32_t a, uint32_t& r0, uint32_t& r1, uint32_t& r2, uint32_t& r3) {
    asm volatile("ldmatrix.sync.aligned.m8n8.x4.shared.b16 {%0,%1,%2,%3}, [%4];" : "=r"(r0), "=r"(r1), "=r"(r2), "=r"(r3) : "r"(a) : "memory");
}
__device__ __forceinline__ uint4 lds128(uint32_t a) { uint4 v; asm volatile("ld.shared.v4.b32 {%0,%1,%2,%3}, [%4];" : "=r"(v.x), "=r"(v.y), "=r"(v.z), "=r"(v.w) : "r"(a) : "memory"); return v; }
__device__ __forceinline__ float4 lds128f(uint32_t a) { float4 v; asm volatile("ld.shared.v4.f32 {%0,%1,%2,%3}, [%4];" : "=f"(v.x), "=f"(v.y), "=f"(v.z), "=f"(v.w) : "r"(a) : "memory"); return v; }
__device__ __forceinline__ float2 lds64f(uint32_t a) { float2 v; asm volatile("ld.shared.v2.f32 {%0,%1}, [%2];" : "=f"(v.x), "=f"(v.y) : "r"(a) : "memory"); return v; }
__device__ __forceinline__ uint32_t lds32(uint32_t a) { uint32_t v; asm volatile("ld.shared.b32 %0, [%1];" : "=r"(v) : "r"(a) : "memory"); return v; }
__device__ __forceinline__ void sts128(uint32_t a, uint32_t x, uint32_t y, uint32_t z, uint32_t w) { asm volatile("st.shared.v4.b32 [%0], {%1,%2,%3,%4};" ::"r"(a), "r"(x), "r"(y), "r"(z), "r"(w) : "memory"); }
__device__ __forceinline__ void sts128f(uint32_t a, float x, float y, float z, float w) { asm volatile("st.shared.v4.f32 [%0], {%1,%2,%3,%4};" ::"r"(a), "f"(x), "f"(y), "f"(z), "f"(w) : "memory"); }
__device__ __forceinline__ void sts64f(uint32_t a, float x, float y) { asm volatile("st.shared.v2.f32 [%0], {%1,%2};" ::"r"(a), "f"(x), "f"(y) : "memory"); }
__device__ __forceinline__ void sts32(uint32_t a, uint32_t x) { asm volatile("st.shared.b32 [%0], %1;" ::"r"(a), "r"(x) : "memory"); }
__device__ __forceinline__ void stg128(void* p, uint4 v) { asm volatile("st.global.v4.b32 [%0], {%1,%2,%3,%4};" ::"l"(p), "r"(v.x), "r"(v.y), "r"(v.z), "r"(v.w) : "memory"); }

__device__ __forceinline__ uint32_t pack2(float lo, float hi) { uint32_t r; asm("cvt.rn.bf16x2.f32 %0, %1, %2;" : "=r"(r) : "f"(hi), "f"(lo)); return r; }
__device__ __forceinline__ float blo(uint32_t v) { return __uint_as_float(v << 16); }
__device__ __forceinline__ float bhi(uint32_t v) { return __uint_as_float(v & 0xffff0000u); }
__device__ __forceinline__ uint32_t hmul2(uint32_t a, uint32_t b) { uint32_t r; asm("mul.rn.bf16x2 %0, %1, %2;" : "=r"(r) : "r"(a), "r"(b)); return r; }
__device__ __forceinline__ uint32_t hadd2(uint32_t a, uint32_t b) { uint32_t r; asm("add.rn.bf16x2 %0, %1, %2;" : "=r"(r) : "r"(a), "r"(b)); return r; }
__device__ __forceinline__ uint32_t hsub2(uint32_t a, uint32_t b) { uint32_t r; asm("sub.rn.bf16x2 %0, %1, %2;" : "=r"(r) : "r"(a), "r"(b)); return r; }
__device__ __forceinline__ uint32_t hfma2(uint32_t a, uint32_t b, uint32_t c) { uint32_t r; asm("fma.rn.bf16x2 %0, %1, %2, %3;" : "=r"(r) : "r"(a), "r"(b), "r"(c)); return r; }
__device__ __forceinline__ float tanh_fast(float x) { float r; asm("tanh.approx.f32 %0, %1;" : "=f"(r) : "f"(x)); return r; }
__device__ __forceinline__ float rsq(float x) { float r; asm("rsqrt.approx.ftz.f32 %0, %1;" : "=f"(r) : "f"(x)); return r; }
__device__ __forceinline__ float rcp(float x) { float r; asm("rcp.approx.ftz.f32 %0, %1;" : "=f"(r) : "f"(x)); return r; }
__device__ __forceinline__ float ex2(float x) { float r; asm("ex2.approx.ftz.f32 %0, %1;" : "=f"(r) : "f"(x)); return r; }

__device__ __forceinline__ uint32_t ld_relaxed(const uint32_t* p) {
    uint32_t v;
    asm volatile("ld.relaxed.gpu.global.u32 %0, [%1];" : "=r"(v) : "l"(p) : "memory");
    return v;
}
__device__ __forceinline__ uint32_t clock32() { uint32_t c; asm volatile("mov.u32 %0, %%clock;" : "=r"(c)::"memory"); return c; }
__device__ __forceinline__ void spin(uint32_t clks) {
    const uint32_t t0 = clock32();
    while (clock32() - t0 < clks) {}
}
__device__ __forceinline__ void flag_wait(const uint32_t* p, uint32_t e, bool mine) {
#pragma unroll 1
    for (int i = 0; i < (1 << 19); i++) {
        if (mine) mine = ld_relaxed(p) != e;
        if (!__any_sync(~0u, mine)) break;
        if (BACKOFF) spin(BACKOFF);
    }
    asm volatile("fence.acquire.gpu;" ::: "memory");
    fence_async_global();
}
__device__ __forceinline__ void st_data(void* p, uint32_t x, uint32_t y, uint32_t z, uint32_t w) {
    asm volatile("st.relaxed.gpu.global.v4.b32 [%0], {%1,%2,%3,%4};" ::"l"(p), "r"(x), "r"(y), "r"(z), "r"(w) : "memory");
}
template <int STRIDE, bool INV = false, int N>
__device__ __forceinline__ void ld_data(uint4 (&v)[N], const unsigned char* p) {
    int it = 0;
    bool again;
#pragma unroll 1
    do {
        uint32_t m = INV ? ~0u : 0u;
#pragma unroll
        for (int i = 0; i < N; i++)
            asm volatile("ld.relaxed.gpu.global.v4.b32 {%0,%1,%2,%3}, [%4];" : "=r"(v[i].x), "=r"(v[i].y), "=r"(v[i].z), "=r"(v[i].w) : "l"(p + i * STRIDE) : "memory");
#pragma unroll
        for (int i = 0; i < N; i++)
            m = INV ? __vimin3_u32(__vimin3_u32(v[i].x, v[i].y, v[i].z), v[i].w, m) : __vimax3_u32(__vimax3_u32(v[i].x, v[i].y, v[i].z), v[i].w, m);
        again = __any_sync(~0u, m == (INV ? 0u : ~0u)) && ++it < (1 << 16);
    } while (again);
}
__device__ __forceinline__ uint32_t ld_epoch() { return ld_relaxed(&g_epoch[blockIdx.x * FS]) + 1; }
__device__ __forceinline__ void flag_set(uint32_t* p, uint32_t e) { asm volatile("st.release.gpu.global.u32 [%0], %1;" ::"l"(p), "r"(e) : "memory"); }

__device__ __forceinline__ uint32_t desc_lo(uint32_t addr) { return ((addr & 0x3FFFF) >> 4) | 0x10000u; }
__device__ __forceinline__ uint64_t mkdesc(uint32_t lo) { return (uint64_t)lo | (0x40000040ull << 32); }
__device__ __forceinline__ void wg_fence() { asm volatile("wgmma.fence.sync.aligned;" ::: "memory"); }
__device__ __forceinline__ void wg_commit() { asm volatile("wgmma.commit_group.sync.aligned;" ::: "memory"); }
template <int N> __device__ __forceinline__ void wg_wait() { asm volatile("wgmma.wait_group.sync.aligned %0;" ::"n"(N) : "memory"); }
template <int N> __device__ __forceinline__ void pin(float (&d)[N]) {
#pragma unroll
    for (int i = 0; i < N; i++) asm volatile("" : "+f"(d[i])::"memory");
}
template <int N> __device__ __forceinline__ void pin(uint32_t (&d)[N]) {
#pragma unroll
    for (int i = 0; i < N; i++) asm volatile("" : "+r"(d[i])::"memory");
}

template <typename Tp, int N> __device__ __forceinline__ void zero(Tp (&d)[N]) {
#pragma unroll
    for (int i = 0; i < N; i++) d[i] = 0;
    pin(d);
}

#define F4(d, i) "+f"(d[i]), "+f"(d[i + 1]), "+f"(d[i + 2]), "+f"(d[i + 3])
#define F16(d, i) F4(d, i), F4(d, i + 4), F4(d, i + 8), F4(d, i + 12)

__device__ __forceinline__ void mma16(float (&d)[4], const uint32_t* a, uint32_t b0, uint32_t b1) {
    asm("mma.sync.aligned.m16n8k16.row.col.f32.bf16.bf16.f32 {%0,%1,%2,%3}, {%4,%5,%6,%7}, {%8,%9}, {%0,%1,%2,%3};"
        : F4(d, 0) : "r"(a[0]), "r"(a[1]), "r"(a[2]), "r"(a[3]), "r"(b0), "r"(b1));
}
template <int N>
__device__ __forceinline__ float row_sum(const uint32_t* x, uint32_t ones = 0x3F803F80u) {
    float c[4] = {};
#pragma unroll
    for (int i = 0; i < N; i += 4) mma16(c, x + i, ones, ones);
    return c[0] + c[2];
}
template <int N>
__device__ __forceinline__ float row_sumsq(const uint32_t* x, int lane) {
    float c0[4] = {}, c1[4] = {};
#pragma unroll
    for (int i = 0; i < N; i += 4) {
        mma16(c0, x + i, x[i], x[i + 2]);
        mma16(c1, x + i, x[i + 1], x[i + 3]);
    }
    return (lane & 4) ? c0[1] + c1[3] : c0[0] + c1[2];
}
__device__ __forceinline__ void mma_sp(float (&d)[32], const uint32_t* a, uint64_t b, uint32_t meta, int acc) {
    asm volatile("{.reg .pred p; setp.ne.b32 p, %38, 0;\n"
                 "wgmma.mma_async.sp.sync.aligned.m64n64k32.f32.bf16.bf16 {%0,%1,%2,%3,%4,%5,%6,%7,%8,%9,%10,%11,%12,%13,%14,%15,%16,%17,%18,%19,%20,%21,%22,%23,%24,%25,%26,%27,%28,%29,%30,%31}, "
                 "{%32,%33,%34,%35}, %36, %37, 0, p, 1, 1, 1;}\n"
                 : F16(d, 0), F16(d, 16) : "r"(a[0]), "r"(a[1]), "r"(a[2]), "r"(a[3]), "l"(b), "r"(meta), "r"(acc));
}
__device__ __forceinline__ void mma_qk(float (&d)[32], uint32_t a0, uint32_t a1, uint32_t a2, uint32_t a3, uint64_t b, int acc) {
    asm volatile("{.reg .pred p; setp.ne.b32 p, %37, 0;\n"
                 "wgmma.mma_async.sync.aligned.m64n64k16.f32.bf16.bf16 {%0,%1,%2,%3,%4,%5,%6,%7,%8,%9,%10,%11,%12,%13,%14,%15,%16,%17,%18,%19,%20,%21,%22,%23,%24,%25,%26,%27,%28,%29,%30,%31}, "
                 "{%32,%33,%34,%35}, %36, p, 1, 1, 0;}\n"
                 : F16(d, 0), F16(d, 16) : "r"(a0), "r"(a1), "r"(a2), "r"(a3), "l"(b), "r"(acc));
}
__device__ __forceinline__ void mma_pv(float (&d)[36], uint32_t a0, uint32_t a1, uint32_t a2, uint32_t a3, uint64_t b) {
    asm volatile("wgmma.mma_async.sync.aligned.m64n72k16.f32.bf16.bf16 {%0,%1,%2,%3,%4,%5,%6,%7,%8,%9,%10,%11,%12,%13,%14,%15,%16,%17,%18,%19,%20,%21,%22,%23,%24,%25,%26,%27,%28,%29,%30,%31,%32,%33,%34,%35}, "
                 "{%36,%37,%38,%39}, %40, 1, 1, 1, 1;\n"
                 : F16(d, 0), F16(d, 16), F4(d, 32) : "r"(a0), "r"(a1), "r"(a2), "r"(a3), "l"(b));
}

__device__ __forceinline__ uint32_t load_code(int n, int r, int w) {
    const int tile = 2 * r + w;
    int m, col, row;
    if (n < 16 || n >= 40) {
        const int k = n < 16 ? n : n - 40;
        m = n < 16 ? 0 : 6;
        if (TWO && n >= 40 && k < 4) { col = 4 * tile + (k & 1); row = (k >> 1) ^ r; }
        else if (k < 8) { col = 4 * tile + (k >> 1); row = n < 16 ? (k & 1) : (k & 1) ^ r; }
        else { m++; col = k < 12 ? tile ^ 2 : tile; row = 2 * (tile ^ (k & 1)) + ((k >> 1) & 1); }
    } else if (n < 32) {
        const int k = n - 16;
        m = 2;
        if (k < 4) { col = tile + ((k & 1) ? 8 : 4); row = (k >> 1) ^ r; }
        else { col = tile; row = (k & 1) ^ r; }
    } else if (n < 34) { m = 3; col = tile; row = n - 32; }
    else if (n < 38) { const int k = n - 34; m = 4; col = tile + 4 * (k & 1); row = (k >> 1) ^ r; }
    else { m = 5; col = tile; row = (n & 1) ^ r; }
    return m | (col << 4) | (row << ((m == 0 || m == 3) ? 10 : 11));
}

__global__ void __cluster_dims__(2, 1, 1) __launch_bounds__(NTHREADS, 1)
conformer_kernel(const Scalars p, const __grid_constant__ Maps m) {
    extern __shared__ __align__(1024) unsigned char smem_raw[];
    const uint32_t sb = smem_u32(smem_raw);
    const uint32_t bars = sb + OFF_BARS;
    const int tid = threadIdx.x;
    const int lane = tid & 31;
    const int warp = __shfl_sync(~0u, tid >> 5, 0);
    const int r = blockIdx.x & 1;
    const int pair = blockIdx.x >> 1;
    const int b = pair >> 5, pt = pair & 31;
    const int ah = pt >> 3, qt = (pt & 7) * 2 + r;
    const int abh = b * 4 + ah;

    TG(30);
    TSINIT();
    TS(0);
    const uint32_t P = sb + OFF_P, H = sb + OFF_H;
    if (warp == 11) {
        if (lane == 0) {
#pragma unroll
            for (int i = 0; i < 2 * NSLOT; i++) mbar_init(bars + (B_FULL + i) * 8, 1);
            asm volatile("fence.mbarrier_init.release.cluster;" ::: "memory");
            fence_async_smem();
        }
        __syncwarp();
        bar_arrive(13, 96);
        cluster_arrive();
    }

    if (warp >= 8) {
        asm volatile("setmaxnreg.dec.sync.aligned.u32 48;");
        if (warp >= 12) {
            cluster_arrive();
            const int ut = tid & 127;
            if (USQ) {
                const int row = pt * 32 + (ut >> 2);
                const char* src = reinterpret_cast<const char*>(p.x) + (b * T_ + min(row, T_ - 1)) * 512 + (ut & 3) * 16;
                float s = 0.f, q = 0.f;
                uint4 u[8];
#pragma unroll
                for (int i = 0; i < 8; i++) u[i] = __ldg(reinterpret_cast<const uint4*>(src + 64 * i));
#pragma unroll
                for (int i = 0; i < 8; i++) {
                    const float a0 = blo(u[i].x), a1 = bhi(u[i].x), a2 = blo(u[i].y), a3 = bhi(u[i].y), a4 = blo(u[i].z), a5 = bhi(u[i].z), a6 = blo(u[i].w), a7 = bhi(u[i].w);
                    s += ((a0 + a1) + (a2 + a3)) + ((a4 + a5) + (a6 + a7));
                    q += fmaf(a0, a0, fmaf(a1, a1, fmaf(a2, a2, a3 * a3))) + fmaf(a4, a4, fmaf(a5, a5, fmaf(a6, a6, a7 * a7)));
                }
                s += __shfl_xor_sync(~0u, s, 1); q += __shfl_xor_sync(~0u, q, 1);
                s += __shfl_xor_sync(~0u, s, 2); q += __shfl_xor_sync(~0u, q, 2);
                s *= 1.f / 256.f;
                sts32(sb + OFF_MISC + 1024 + (ut >> 2) * 32, __float_as_uint(0.5f * rsq(fmaxf(fmaf(-s, s, q * (1.f / 256.f)), 0.f) + 1e-5f)));
                bar_arrive(1, 384);
            }
            cluster_wait();
            const uint32_t target = ld_epoch() * 64;
            bar_sync(6, 384);
#pragma unroll
            for (int i = 0; i < 4; i++) {
                st_data(g_o + (size_t)(b * 128 + qt * 8 + 2 * i + (ut >> 6)) * 4096 + ah * 1024 + (ut & 63) * 16, ~0u, ~0u, ~0u, ~0u);
                if (i < 2) st_data(&g_halo[(pair * 4 + 2 * r + i) * 128 + ut], ~0u, ~0u, ~0u, ~0u);
            }
            bar_sync(11, 128);
            if (ut == 0) {
                asm volatile("red.release.gpu.global.add.u32 [%0], 1;" ::"l"(&g_reset[b * 32]) : "memory");
#pragma unroll 1
                for (int i = 0; i < (1 << 20) && ld_relaxed(&g_reset[b * 32]) != target; i++) __nanosleep(100);
                asm volatile("fence.acquire.gpu;" ::: "memory");
                mbar_arrive(bars + B_RST * 8);
            }
            bar_sync(11, 128);
            TS(14);
#pragma unroll
            for (int i = 0; i < 4; i++) st_data(g_kvq + 2097152 + (size_t)(abh * 1024 + qt * 64) * 128 + i * 2048 + ut * 16, 0, 0, 0, 0);
            const int side = warp & 1, wg = (warp >> 1) & 1, np = side ? pt + 1 : pt - 1;
            const unsigned char* src = reinterpret_cast<const unsigned char*>(&g_halo[(((b * 32 + np) * 4 + 2 * r + wg) * 2 + (side ^ 1)) * 64 + lane]);
            const uint32_t dst = H + 16384 + wg * GCH + side * 5120 + (lane & 7) * 128 + (((lane >> 3) ^ (lane & 7)) << 4);
            uint4 hv[2] = {make_uint4(0, 0, 0, 0), make_uint4(0, 0, 0, 0)};
            bar_sync(8 + wg, 192);
            if (np >= 0 && np < 32) {
                spin(HDELAY);
                ld_data<512>(hv, src);
            }
            stsm4(dst, hv[0].x, hv[0].y, hv[0].z, hv[0].w);
            stsm4(dst ^ 64, hv[1].x, hv[1].y, hv[1].z, hv[1].w);
            __syncwarp();
            if (lane == 0) mbar_arrive(bars + (B_HALO + (warp & 3)) * 8);
            TS(4);
        } else if (warp < 10) {
            const int w = warp - 8;
            const uint32_t ring = sb + OFF_RING + w * NSLOT * SLOT;
            const uint32_t full = bars + (B_FULL + w * NSLOT) * 8;
            cluster_arrive();
            bar_sync(13, 96);
            TS(1);
#pragma unroll
            for (int n = 0; n < NSLOT; n++) {
                if (n == 1) bar_sync(12, 64);
                ring_load(ring + n * SLOT, &m.tm[0], 64 * (8 * r + 4 * w + (n >> 1)), 4 * (n & 1), full + n * 8);
            }
            TS(2);
            const uint32_t code = load_code(lane, r, w) | (load_code(lane + 32, r, w) << 16);
            cluster_wait();
            uint32_t s = 0, ph = 0;
            int n = NSLOT;
#pragma unroll 1
            for (int seg = 0; seg < 2; seg++) {
#pragma unroll 1
                for (; n < (seg == 0 ? 22 : NLOADS); n++) {
                    const uint32_t c = __shfl_sync(~0u, code, n) >> (n & 32 ? 16 : 0);
                    const CUtensorMap* tm = &m.tm[c & 15];
                    const uint32_t col = (c & 0xf0) * 4, row = (c & 0xff00) >> 8, dst = ring + s * SLOT;
                    mbar_wait(full + (B_EMPTY - B_FULL) * 8 + s * 8, ph + (((uint32_t)(size_t)tm | col | row | dst) & p.zero));
                    ring_load(dst, tm, col, row, full + s * 8);
                    if (++s == NSLOT) { s = 0; ph ^= 1; }
                }
                if (seg == 1) break;
                const uint32_t epoch = ld_epoch();
                const uint32_t rdy = bars + (B_RDY + 3 * w) * 8, prdy = mapa(rdy, r ^ 1);
                const int odd = r ^ w;
                const uint32_t* flags = g_flag_kv + (abh * 32 + lane) * KFS;
                bool first = (lane >> 2) == 2 * odd + w;
                if (WARMF && first) first = ld_relaxed(flags) != epoch;
                auto kv_load = [&](uint32_t sl, int isv, int i) {
                    ring_load_both(ring + sl * SLOT, &m.tm[8], (isv * 64 + abh * 8 + 2 * i + w) * 128, full + sl * 8);
                };
#pragma unroll 1
                for (int i = 0; i < 2; i++) {
                    if (lane < 3 + i) {
                        const uint32_t sl = i ? lane : lane + 2;
                        mbar_wait(full + (B_EMPTY - B_FULL + sl) * 8, i ^ 1);
                        mbar_arrive_tx(full + sl * 8, (i || lane == 2) ? SLOT : 0);
                    }
                    __syncwarp();
                }
                if (lane == 0) mbar_arrive_peer(prdy);
                bar_sync(14, 96);
                spin(KDELAY);
                mbar_wait(rdy, 0);
                flag_wait(flags, epoch, first);
                TSW(5 + 2 * odd);
                if (!odd) { kv_load(4, 0, 0); bar_arrive(12, 64); }
                else bar_sync(12, 64);
                spin(w ? KD3 : KD2);
                kv_load(odd ^ 1, odd ^ 1, odd);
                flag_wait(flags, epoch, (lane >> 2) == 2 * odd + w + 4);
                mbar_wait(full + (odd ^ 1) * 8, 1);
                kv_load(2 + odd, odd, 2 - odd);
#pragma unroll 1
                for (int i = 0; i < 3; i++) {
                    const uint32_t sl = i ? i - 1 : 4, bo = i == 2 ? 16 : 8;
                    mbar_wait(full + (B_EMPTY - B_FULL + sl) * 8, i != 0);
                    if (lane == 0) mbar_arrive_tx(full + sl * 8, SLOT);
                    if ((i & 1) != odd) {
                        mbar_wait(rdy + bo, 0);
                        kv_load(sl, i != 0, 2 + odd);
                    } else if (lane == 0) mbar_arrive_peer(prdy + bo);
                    __syncwarp();
                }
                n = 32; s = 2; ph = 1;
            }
        } else if (warp == 10) {
            if (lane == 0) {
#pragma unroll
                for (int i = B_EMPTY; i < NBARS; i++) mbar_init(bars + i * 8, i < B_XA ? 4 : 1);
#pragma unroll
                for (int i = B_XA; i <= B_SR; i++) mbar_arrive_tx(bars + i * 8, i < B_XB ? 512 : ((i >= B_INB && i < B_SR) ? 4096 : 8192));
                asm volatile("fence.mbarrier_init.release.cluster;" ::: "memory");
                fence_async_smem();
            }
            __syncwarp();
            cluster_arrive();
            cluster_wait();
        } else {
            const uint32_t kb = (lane < 2 || lane > 5) ? 4096 : (lane == 2 ? 3072 : (lane == 4 ? 2048 : 1024));
            const char* pf = m.w[lane & 7] + blockIdx.x * kb;
            cluster_wait();
            if (lane < PF0) prefetch_l2(pf, kb);
            mbar_wait(bars + B_FULL * 8, 0);
            if (lane >= PF0 && lane < 3) prefetch_l2(pf, kb);
            if (lane >= 1 && lane < 9) asm volatile("prefetch.tensormap [%0];" ::"l"(&m.tm[lane]) : "memory");
            mbar_wait(bars + (B_FULL + 1) * 8, 1);
            if (lane > 2 && lane < 8) prefetch_l2(pf, kb);
            if (lane == 8 && blockIdx.x < 15) prefetch_l2(p.dw + blockIdx.x * 256, 512);
            const uint32_t epoch = ld_epoch();
            bar_sync(4, 288);
            if (lane < 16) flag_set(&g_flag_kv[((b * 4 + 2 * r + (lane >> 3)) * 32 + pt) * KFS + (lane & 7)], epoch);
            __syncwarp();
            bar_arrive(14, 96);
            TSW(8);
        }
        TSDUMP();
        return;
    }

    const int w = warp >> 2, wq = warp & 3;
    const int tile = 2 * r + w;
    const int wt = tid & 127;
    const int c4 = lane & 3;
    const int trow = pt * 32 + 8 * wq;
    uint32_t xr[8];
    uint32_t a[32];
    const char* xrow = reinterpret_cast<const char*>(p.x) + (b * T_ + trow + (lane >> 2)) * 512;
    zero(a);
    if (trow < T_) {
        const char* src = xrow + c4 * 16 + p.zero;
#pragma unroll
        for (int i = 0; i < 8; i++)
            asm volatile("ld.global.nc.v4.b32 {%0,%1,%2,%3}, [%4];" : "=r"(a[4 * i]), "=r"(a[4 * i + 1]), "=r"(a[4 * i + 2]), "=r"(a[4 * i + 3]) : "l"(src + 64 * i));
    }
    cluster_arrive();
    asm volatile("setmaxnreg.inc.sync.aligned.u32 208;");
    const uint32_t rbase = sb + OFF_RING + w * NSLOT * SLOT, fbar = bars + (B_FULL + w * NSLOT) * 8;
    const uint32_t rdesc = desc_lo(rbase);
    auto acq = [&](int n) { mbar_wait(fbar + (n % NSLOT) * 8, (n / NSLOT) & 1); };
    auto rel = [&](int n) { if (lane == 0) mbar_arrive(fbar + (B_EMPTY - B_FULL + n % NSLOT) * 8); };
    const uint32_t foff = (lane & 7) * 128 + (((lane >> 3) ^ (lane & 7)) << 4);
    float v[16];
    const uint32_t xown = __shfl_sync(~0u, P + wt * 16 + tile * 4096, lane), xrem = __shfl_sync(~0u, P + wt * 16 + (r ^ 1) * 8192, lane);
    const uint32_t sbuf = __shfl_sync(~0u, sb + OFF_MISC + 1024 + (8 * wq + (lane >> 2)) * 32, lane);
    const uint32_t sown = __shfl_sync(~0u, sbuf + tile * 8, lane);
    const uint32_t peer = __shfl_sync(~0u, mapa(sb, r ^ 1) - sb, lane);
    const uint32_t hbuf = __shfl_sync(~0u, H + w * 4096 + wt * 16, lane);
    const uint32_t meta = __shfl_sync(~0u, 0xEEEE4444u + p.zero, lane);
    cluster_wait();
    TS(56);
    float mean, msq;
    const int mir = wq < 2 ? 7 : 0;
    uint32_t dwr[15] = {};

#pragma unroll
    for (int ph = 0; ph < 5; ph++) {
        uint4 o0, o1;
        if (ph == 0) {
            const uint32_t one = 0x3F803F80u + ((xown | xrem | sbuf | sown | hbuf | foff | rdesc | fbar) & p.zero);
            mean = ((row_sum<8>(a, one) + row_sum<8>(a + 8, one)) + (row_sum<8>(a + 16, one) + row_sum<8>(a + 24, one))) * (1.f / 256.f);
            TS(57);
        } else {
            const uint32_t xa = bars + (B_XA + ph) * 8;
#pragma unroll
            for (int j = 0; j < 8; j++) xr[j] = pack2(v[2 * j], v[2 * j + 1]);
            const float s = row_sum<8>(xr), q = row_sumsq<8>(xr, lane);
            if (ph < 4) {
                sts128(xown, xr[0], xr[1], xr[2], xr[3]);
                sts128(xown + 2048, xr[4], xr[5], xr[6], xr[7]);
            }
            put_sums(sown, sown + peer, s, q, xa + peer, c4 == (lane >> 3));
            bar_sync(10, 256);
            if (ph < 4) {
                o0 = lds128(xown ^ 4096); o1 = lds128((xown ^ 4096) + 2048);
                st_async4(xown + peer, xr[0], xr[1], xr[2], xr[3], xa + (B_XB - B_XA) * 8 + peer);
                st_async4(xown + peer + 2048, xr[4], xr[5], xr[6], xr[7], xa + (B_XB - B_XA) * 8 + peer);
            }
            TS(57 + ph);
            if (ph == 3) acq(0);
            if (ph == 1) acq(16);
            mbar_wait(xa, 0);
            const float4 u0 = lds128f(sbuf), u1 = lds128f(sbuf + 16);
            mean = ((u0.x + u0.z) + (u1.x + u1.z)) * (1.f / 256.f);
            msq = ((u0.y + u0.w) + (u1.y + u1.w)) * (1.f / 256.f);
        }
        if (ph == 4) break;
        const uint32_t mean2 = pack2(mean, mean);
        auto centre = [&](int i, const uint4& u) {
            a[i] = hsub2(u.x, mean2); a[i + 1] = hsub2(u.y, mean2); a[i + 2] = hsub2(u.z, mean2); a[i + 3] = hsub2(u.w, mean2);
        };
        if (ph == 0) {
#pragma unroll
            for (int j = 0; j < 32; j++) a[j] = hsub2(a[j], mean2);
            zero(xr);
            if (trow < T_) {
                const char* src = xrow + tile * 128 + c4 * 4 + (mean2 & p.zero);
#pragma unroll
                for (int j = 0; j < 8; j++) asm volatile("ld.global.nc.b32 %0, [%1];" : "=r"(xr[j]) : "l"(src + 16 * j));
            }
            mean -= blo(mean2);
            msq = USQ ? 0.f : __shfl_sync(~0u, row_sumsq<16>(a, lane) + row_sumsq<16>(a + 16, lane), (lane & 28) + (lane >> 3)) * (1.f / 256.f);
            acq(0);
        } else {
#pragma unroll
            for (int j = 0; j < 8; j++) a[j] = hsub2(xr[j], mean2);
            centre(8, o0); centre(12, o1);
        }
        const float rstd = rsq(fmaxf(fmaf(-mean, mean, msq), 0.f) + 1e-5f);
        auto gather_peer = [&]() {
            mbar_wait(bars + (B_XB + ph) * 8, 0);
#pragma unroll
            for (int i = 0; i < 4; i++) centre(16 + 4 * i, lds128(xrem + i * 2048));
        };
        auto sp = [&](float (&d)[32], int n, const uint32_t* af, int flip, int acc) {
            const uint32_t lo = rdesc + p.zero * (ph * 64 + n + 1) + (n % NSLOT) * (SLOT >> 4);
            const uint64_t b0 = mkdesc(lo + flip * 512), b1 = mkdesc(lo + (flip ^ 1) * 512);
            wg_fence();
            mma_sp(d, af, b0, meta, acc);
            mma_sp(d, af + 4, b0 + 256, meta, 1);
            mma_sp(d, af + 8, b1, meta, 1);
            mma_sp(d, af + 12, b1 + 256, meta, 1);
            wg_commit();
        };
        float d0[32], d1[32];

        if (ph == 0 || ph == 3) {
            uint32_t h[32], ho[32];
            float rs = 0.5f * rstd;
            const uint32_t inb = bars + (B_INB + (ph & 2) + w) * 8;
            bool ready = true;
            const int eager = ph ? (TWO ? EAGER + 5 : EAGER) : EAGER - 1;
            auto step = [&](float (&d)[32], int n, const uint32_t* af, int flip, int acc, auto work) {
                if (!ready) acq(n);
                if (((TURN >> n) & 1) && w == 1) bar_sync(7, 256);
                sp(d, n, af, flip, acc);
                if (n > 0 && ((TURN >> (n - 1)) & 1) && w == 0) bar_arrive(7, 256);
                if (n < 15) ready = mbar_test(fbar + ((n + 1) % NSLOT) * 8, ((n + 1) / NSLOT) & 1);
                wg_wait<1>();
                if (n > 0 && !((eager >> (n - 1)) & 1)) rel(n - 1);
                const uint32_t tie = work() & p.zero;
                if ((eager >> n) & 1) {
                    if (p.zero < n + ph + 1) wg_wait<0>();
                    if (lane == 0) mbar_arrive(fbar + (B_EMPTY - B_FULL + n % NSLOT) * 8 + tie);
                }
            };
            auto none = []() { return 0u; };
            const int fl = ph ? w : 0;
            auto fetch = [&](int i) {
                bar_sync(10, 256);
                const uint4 u0 = lds128((hbuf ^ 4096) + (i & 1) * 8192), u1 = lds128((hbuf ^ 4096) + (i & 1) * 8192 + 2048);
                ho[8 * i] = u0.x; ho[8 * i + 1] = u0.y; ho[8 * i + 2] = u0.z; ho[8 * i + 3] = u0.w;
                ho[8 * i + 4] = u1.x; ho[8 * i + 5] = u1.y; ho[8 * i + 6] = u1.z; ho[8 * i + 7] = u1.w;
                return u0.x | u1.x;
            };
            auto act = [&](float (&d)[32], int i) {
                if (i > 0) fetch(i - 1);
                else if (USQ && ph == 0) { bar_sync(1, 384); rs = __uint_as_float(lds32(sbuf)); }
                pin(d);
#pragma unroll
                for (int j = 0; j < 8; j++) {
                    const float u0 = (d[4 * j] + d[4 * j + 2]) * rs, u1 = (d[4 * j + 1] + d[4 * j + 3]) * rs;
                    h[8 * i + j] = pack2(fmaf(u0, tanh_fast(u0), u0), fmaf(u1, tanh_fast(u1), u1));
                }
                sts128(hbuf + (i & 1) * 8192, h[8 * i], h[8 * i + 1], h[8 * i + 2], h[8 * i + 3]);
                sts128(hbuf + (i & 1) * 8192 + 2048, h[8 * i + 4], h[8 * i + 5], h[8 * i + 6], h[8 * i + 7]);
                return 0u;
            };
            TS(1 + (ph & 2) * 10);
            if (TWO && ph) {
                step(d0, 0, a, fl, 0, none);
                step(d1, 1, a, fl, 0, [&]() { gather_peer(); return 0u; });
                TS(32);
                step(d0, 2, a + 16, 0, 1, none);
                step(d1, 3, a + 16, 0, 1, [&]() { return act(d0, 0); });
            } else {
                step(d0, 0, a, fl, 0, [&]() { if (ph) gather_peer(); return 0u; });
                TS(32);
                step(d0, 1, a + 16, 0, 1, none);
                step(d1, 2, a, fl, 0, [&]() { return act(d0, 0); });
                step(d1, 3, a + 16, 0, 1, none);
            }
            step(d0, 4, a, fl, 0, [&]() { return act(d1, 1); });
            TS(33);
            step(d0, 5, a + 16, 0, 1, none);
            step(d1, 6, a, fl, 0, [&]() { return act(d0, 2); });
            step(d1, 7, a + 16, 0, 1, none);
            step(d0, 8, h, 0, 0, [&]() { act(d1, 3); return fetch(3); });
            TS(2 + (ph & 2) * 10);
            step(d0, 9, ho, 0, 1, none);
            step(d0, 10, h + 16, 0, 1, none);
            step(d0, 11, ho + 16, 0, 1, none);
            uint32_t pk[8];
            auto pack_out = [&]() {
                pin(d0);
#pragma unroll
                for (int j = 0; j < 8; j++) pk[j] = pack2(d0[4 * j] + d0[4 * j + 2], d0[4 * j + 1] + d0[4 * j + 3]);
            };
            auto send = [&](int i) { st_async4(hbuf + 16384 + i * 2048 + peer, pk[4 * i], pk[4 * i + 1], pk[4 * i + 2], pk[4 * i + 3], inb + peer); };
            step(d1, 12, h, 0, 0, [&]() { pack_out(); if (SND != 1) send(0); if (SND == 0) send(1); return 0u; });
            TS(34);
            step(d1, 13, ho, 0, 1, [&]() { if (SND == 1) send(0); if (SND) send(1); return 0u; });
            step(d1, 14, h + 16, 0, 1, none);
            step(d1, 15, ho + 16, 0, 1, none);
            mbar_wait(inb, 0);
#pragma unroll
            for (int i = 0; i < 2; i++) {
                const uint4 u = lds128(hbuf + 16384 + i * 2048);
                const uint32_t p0[4] = {u.x, u.y, u.z, u.w};
#pragma unroll
                for (int j = 0; j < 4; j++) {
                    v[8 * i + 2 * j] = fmaf(0.5f, blo(p0[j]), blo(xr[4 * i + j]));
                    v[8 * i + 2 * j + 1] = fmaf(0.5f, bhi(p0[j]), bhi(xr[4 * i + j]));
                }
            }
            wg_wait<0>();
            pin(d1);
            rel(15);
            TS(3 + (ph & 2) * 10);
#pragma unroll
            for (int j = 0; j < 8; j++) {
                v[2 * j] = fmaf(0.5f, d1[4 * j] + d1[4 * j + 2], v[2 * j]);
                v[2 * j + 1] = fmaf(0.5f, d1[4 * j + 1] + d1[4 * j + 3], v[2 * j + 1]);
            }
#pragma unroll
            for (int i = 0; i < 15; i++) dwr[i] = 0;
            continue;
        }

        auto residual = [&](int n) {
            wg_wait<1>();
            rel(n);
            wg_wait<0>();
            pin(d0);
            rel(n + 1);
#pragma unroll
            for (int j = 0; j < 8; j++) {
                v[2 * j] = d0[4 * j] + d0[4 * j + 2] + blo(xr[j]);
                v[2 * j + 1] = d0[4 * j + 1] + d0[4 * j + 3] + bhi(xr[j]);
            }
        };

        if (ph == 2) {
            TS(39);
            sp(d0, 34, a, w, 0);
            acq(35);
            sp(d1, 35, a, w, 0);
            acq(36); acq(37);
            gather_peer();
            sp(d0, 36, a + 16, 0, 1);
            sp(d1, 37, a + 16, 0, 1);
            wg_wait<2>();
            rel(34);
            if (!(LATE & 1)) rel(35);
            acq(38);
            const float rs = trow < T_ ? 0.5f * rstd : 0.f;
            wg_wait<0>();
            pin(d0); pin(d1);
            if (!(LATE & 2)) { rel(36); rel(37); }
            TS(18);
            uint32_t pk[8];
#pragma unroll
            for (int j = 0; j < 8; j++) {
                const float u0 = (d0[4 * j] + d0[4 * j + 2]) * rs, u1 = (d0[4 * j + 1] + d0[4 * j + 3]) * rs;
                const float t0 = tanh_fast((d1[4 * j] + d1[4 * j + 2]) * rs), t1 = tanh_fast((d1[4 * j + 1] + d1[4 * j + 3]) * rs);
                pk[j] = pack2(fmaf(u0, t0, u0), fmaf(u1, t1, u1));
            }
            if (wq == 0 || wq == 3) {
                uint4* hp = &g_halo[((pair * 4 + tile) * 2 + (wq & 1)) * 64 + lane];
                st_data(hp, pk[0], pk[1], pk[2], pk[3]);
                st_data(hp + 32, pk[4], pk[5], pk[6], pk[7]);
            }
            const uint32_t gs = H + 16384 + w * GCH + wq * 1024;
            stsm4(gs + 1024 + foff, pk[0], pk[1], pk[2], pk[3]);
            stsm4(gs + 1024 + (foff ^ 64), pk[4], pk[5], pk[6], pk[7]);
            bar_sync(8 + w, 192);
            TS(26);
            uint32_t ca[8], cb[8];
            const int e = (wq & 1) * 4;
            const uint32_t lo = ((mir ^ e) * 144) ^ (lane * 4);
            const int dir = mir ? -1024 : 1024;
            const uint32_t gb = H + 16384 + w * GCH + (mir ? 3072 : 2048) + lo, sown_ = H + tile * HCH, so = sown_ + (mir ? 1024 : 2048) + lo;
            auto finish = [&](int i) {
                const uint32_t c = hadd2(ca[i], cb[i]);
                const float h0 = blo(c), h1 = bhi(c);
                const uint32_t dst = (so + (i >> 2) * dir) ^ ((i & 3) * 144), val = pack2(fmaf(h0, tanh_fast(h0), h0), fmaf(h1, tanh_fast(h1), h1));
                asm volatile("st.async.shared::cluster.mbarrier::complete_tx::bytes.b32 [%0], %1, [%2];" ::"r"(dst + peer), "r"(val), "r"(bars + B_SR * 8 + peer) : "memory");
                sts32(dst, val);
            };
#pragma unroll
            for (int k = 0; k < 26; k++) {
                if (k == 19) {
#pragma unroll
                    for (int i = 0; i < 4; i++) finish(i);
                    mbar_wait(bars + (B_HALO + 2 * w + (wq >> 1)) * 8, 0);
                    if (LATE & 1) rel(35);
                    if (LATE & 2) { rel(36); rel(37); }
                    TS(27);
                }
                const uint32_t g = lds32((gb + (((k + 1) & 4) ? ((k + 1) >> 3) + (wq & 1) : ((k + 1) >> 3)) * dir) ^ (((k + 1) & 7) * 144));
#pragma unroll
                for (int i = 0; i < 8; i++) {
                    const int tap = k - (i & 3) - 2 * (i & 4);
                    if (tap == 0) ca[i] = hmul2(g, dwr[0]);
                    else if (tap > 0 && tap < 8) ca[i] = hfma2(g, dwr[tap], ca[i]);
                    else if (tap == 8) cb[i] = hmul2(g, dwr[8]);
                    else if (tap > 8 && tap < 15) cb[i] = hfma2(g, dwr[tap], cb[i]);
                }
            }
#pragma unroll
            for (int i = 4; i < 8; i++) finish(i);
            bar_sync(10, 256);
            TS(19);
            auto frags = [&](int i, int half) {
                const uint32_t src = H + 2 * half * HCH + wq * 1024;
#pragma unroll
                for (int k = 0; k < 4; k++) ldsm4(src + (k >> 1) * HCH + (foff ^ ((k & 1) * 64)), a[i + 4 * k], a[i + 4 * k + 1], a[i + 4 * k + 2], a[i + 4 * k + 3]);
            };
            frags(0, r);
            if (!ONE) sp(d0, 38, a, 0, 0);
            acq(39);
            mbar_wait(bars + B_SR * 8, 0);
            frags(16, r ^ 1);
            if (ONE) {
                if (ONE == 2 && __any_sync(~0u, (a[16] | a[20] | a[24] | a[28]) & p.zero)) spin(1);
                sp(d0, 38, a, 0, 0);
            }
            sp(d0, 39, a + 16, 0, 1);
            residual(38);
            TS(20);
            continue;
        }

        {
            TS(11);
            unsigned char* g = g_kvq + (size_t)((b * 4 + tile) * 1024 + trow) * 128;
            const uint32_t uo = (lane >> 2) * 128 + ((c4 ^ (lane >> 2)) << 4);
            auto put = [&](float (&d)[32], int i) {
                pin(d);
                uint32_t pk[8];
#pragma unroll
                for (int j = 0; j < 8; j++) pk[j] = pack2((d[4 * j] + d[4 * j + 2]) * rstd, (d[4 * j + 1] + d[4 * j + 3]) * rstd);
                if (i < 2) {
                    stg128(g + i * 1048576 + uo, make_uint4(pk[0], pk[1], pk[2], pk[3]));
                    stg128(g + i * 1048576 + (uo ^ 64), make_uint4(pk[4], pk[5], pk[6], pk[7]));
                } else {
                    const uint32_t stg = H + warp * 1024;
                    sts128(stg + uo, pk[0], pk[1], pk[2], pk[3]);
                    sts128(stg + (uo ^ 64), pk[4], pk[5], pk[6], pk[7]);
                    __syncwarp();
                    ldsm4(stg + foff, pk[0], pk[1], pk[2], pk[3]);
                    ldsm4(stg + (foff ^ 64), pk[4], pk[5], pk[6], pk[7]);
                    st_data(g + 2097152 + lane * 16, ~pk[0], ~pk[1], ~pk[2], ~pk[3]);
                    st_data(g + 2097152 + 512 + lane * 16, ~pk[4], ~pk[5], ~pk[6], ~pk[7]);
                }
            };
            sp(d0, 16, a, w, 0);
            acq(17);
            sp(d1, 17, a, w, 0);
            gather_peer();
            acq(18);
            sp(d0, 18, a + 16, 0, 1);
            wg_wait<1>();
            rel(16); rel(17);
            acq(19);
            sp(d1, 19, a + 16, 0, 1);
            wg_wait<1>();
            rel(18);
            put(d0, 0);
            wg_wait<0>();
            rel(19);
            TS(37);
            put(d1, 1);
            bar_arrive(4, 288);
            TS(38);
            acq(20);
            sp(d0, 20, a, w, 0);
            acq(21);
            sp(d0, 21, a + 16, 0, 1);
            acq(22); acq(23);
            rel(22); rel(23);
            wg_wait<0>();
            rel(20); rel(21);
            put(d0, 2);
            TS(12);
        }

        {
            constexpr float CS = 0.125f * 1.4426950408889634f;
            float sa[32], sb2[32], o[36];
            uint32_t pa[16], pb[16], q[16];
            float n0 = INFINITY, n1 = INFINITY;
            zero(o); zero(pa); zero(pb); zero(sb2);
            const uint32_t ones = sb + OFF_MISC + 2048;
            { const uint32_t c = w ? 0u : 0x3F803F80u; sts128(ones + tid * 16, c, c, c, c); }
            fence_async_smem();
            bar_sync(10, 256);
            const uint32_t vdesc = rdesc + ((((ones - rbase) >> 4) - 1) << 16);
            auto qk_issue = [&](float (&s)[32], uint32_t lo) {
                const uint64_t kd = mkdesc(lo);
                wg_fence();
#pragma unroll
                for (int k = 0; k < 4; k++) mma_qk(s, q[4 * k], q[4 * k + 1], q[4 * k + 2], q[4 * k + 3], kd + 2 * k, k != 0);
                wg_commit();
            };
            auto both_issue = [&](float (&s)[32], uint32_t klo, uint32_t (&pp)[16], uint32_t vlo) {
                const uint64_t kd = mkdesc(klo), vd = mkdesc(vlo);
                wg_fence();
#pragma unroll
                for (int k = 0; k < 4; k++) {
                    mma_pv(o, pp[4 * k], pp[4 * k + 1], pp[4 * k + 2], pp[4 * k + 3], vd - k * (128 * 65535));
                    mma_qk(s, q[4 * k], q[4 * k + 1], q[4 * k + 2], q[4 * k + 3], kd + 2 * k, k != 0);
                }
                wg_commit();
            };
            auto new_max = [&](float (&s)[32], int nj, float& x0, float& x1) {
                x0 = s[0]; x1 = s[2];
#pragma unroll
                for (int j = 0; j < nj; j++) {
                    x0 = fmaxf(x0, fmaxf(s[4 * j], s[4 * j + 1]));
                    x1 = fmaxf(x1, fmaxf(s[4 * j + 2], s[4 * j + 3]));
                }
                x0 = fmaxf(x0, __shfl_xor_sync(~0u, x0, 1)); x1 = fmaxf(x1, __shfl_xor_sync(~0u, x1, 1));
                x0 = fmaxf(x0, __shfl_xor_sync(~0u, x0, 2)); x1 = fmaxf(x1, __shfl_xor_sync(~0u, x1, 2));
                x0 = fminf(n0, fmaf(x0, -CS, -20.f)); x1 = fminf(n1, fmaf(x1, -CS, -20.f));
            };
            auto probs = [&](float (&s)[32], uint32_t (&pp)[16], bool ready, bool tail, auto wait) {
                uint32_t any = 0;
#pragma unroll
                for (int i = 0; i < 16; i++) {
                    pp[i] = pack2(ex2(fmaf(s[2 * i], CS, (i & 1) ? n1 : n0)), ex2(fmaf(s[2 * i + 1], CS, (i & 1) ? n1 : n0)));
                    any |= pp[i];
                }
                wg_wait<0>();
                pin(sa); pin(sb2); pin(o); pin(pa); pin(pb);
                if (__builtin_expect(__any_sync(~0u, (any & 0x40004000u) || !ready), 0)) {
                    wait();
                    if (__any_sync(~0u, any & 0x40004000u)) {
                        if (tail) {
#pragma unroll
                            for (int i = 20; i < 32; i++) s[i] = -INFINITY;
                        }
                        float x0, x1;
                        new_max(s, 8, x0, x1);
                        const float sc0 = ex2(x0 - n0), sc1 = ex2(x1 - n1);
                        n0 = x0; n1 = x1;
#pragma unroll
                        for (int j = 0; j < 9; j++) { o[4 * j] *= sc0; o[4 * j + 1] *= sc0; o[4 * j + 2] *= sc1; o[4 * j + 3] *= sc1; }
#pragma unroll
                        for (int i = 0; i < 16; i++)
                            pp[i] = pack2(ex2(fmaf(s[2 * i], CS, (i & 1) ? n1 : n0)), ex2(fmaf(s[2 * i + 1], CS, (i & 1) ? n1 : n0)));
                    }
                }
            };
            {
                uint4 u[4];
                const unsigned char* src = g_kvq + 2097152 + (size_t)(abh * 1024 + qt * 64 + wq * 16) * 128 + lane * 16;
                spin(QGATE);
                ld_data<512, true>(u, src);
#pragma unroll
                for (int k = 0; k < 2; k++) {
                    q[8 * k] = ~u[k].x; q[8 * k + 1] = ~u[k + 2].x; q[8 * k + 2] = ~u[k].y; q[8 * k + 3] = ~u[k + 2].y;
                    q[8 * k + 4] = ~u[k].z; q[8 * k + 5] = ~u[k + 2].z; q[8 * k + 6] = ~u[k].w; q[8 * k + 7] = ~u[k + 2].w;
                }
                pin(q);
            }
            TS(40);
            acq(24);
            TS(13);
            qk_issue(sa, rdesc + (24 % NSLOT) * (SLOT >> 4));
            wg_wait<0>();
            pin(sa);
            {
                float x0, x1;
                new_max(sa, NJ0, x0, x1);
                n0 = x0; n1 = x1;
            }
            bar_arrive(6, 384);
            uint32_t vd = vdesc - (SLOT >> 4) * 65535u, kd = rdesc, vb = fbar + 8, kb = fbar;
            uint32_t vlast = vdesc - 4 * (SLOT >> 4) * 65535u, klast = rdesc + 4 * (SLOT >> 4) + 512;
            uint32_t kprev = fbar + 32, vprev = bars + (B_SINK - (B_EMPTY - B_FULL)) * 8;
#pragma unroll 1
            for (int it = 0; it < 4; it++) {
                both_issue(sb2, klast, pb, vlast);
                probs(sa, pa, mbar_test(vb, it < 2) & mbar_test(kb, it < 3), false, [&]() { mbar_wait(vb, it < 2); mbar_wait(kb, it < 3); });
                TS(41 + it * 4);
                if (lane == 0) mbar_arrive(kprev + (B_EMPTY - B_FULL) * 8);
                if (lane == 0) mbar_arrive(vprev + (B_EMPTY - B_FULL) * 8);
                both_issue(sa, kd, pa, vd);
                const int dv = it == 0 ? 2 : (it == 1 ? -3 : 1);
                kprev = kb; vprev = vb; vlast = vd - 512 * 65535u; klast = kd + 512;
                vd -= dv * (SLOT >> 4) * 65535u; vb += dv * 8;
                kd += (it == 2 ? -3 : 2) * (SLOT >> 4); kb = it == 2 ? vb : kb + 16;
                probs(sb2, pb, true, it == 3 && w == 1, []() {});
                TS(43 + it * 4);
            }
            wg_fence();
#pragma unroll
            for (int k = 0; k < 4; k++)
                mma_pv(o, pb[4 * k], pb[4 * k + 1], pb[4 * k + 2], pb[4 * k + 3], mkdesc(vlast - k * (128 * 65535) + (k > 1 ? w * ((k - 1) << 22) : 0)));
            wg_commit();
            const uint32_t mlw = sb + OFF_MISC + (tid >> 2) * 8;
            unsigned char* odst = g_o + (size_t)(b * 128 + qt * 8 + 2 * wq + w) * 4096 + ah * 1024 + lane * 16;
            mbar_wait(bars + B_RST * 8, (mlw | (uint32_t)(size_t)odst) & p.zero);
            wg_wait<0>();
            pin(o); pin(pb); pin(sa); pin(sb2);
            if (!(LATE & 4)) rel(31);
            TS(14);
            auto merge = [&](int keep, float nk, float ns) {
                const int snd = 2 - keep;
                if (c4 == 0) sts64f(mlw, ns, o[32 + snd]);
#pragma unroll
                for (int j = 0; j < 2; j++)
                    sts128(hbuf + j * 2048, pack2(o[16 * j + snd], o[16 * j + snd + 1]), pack2(o[16 * j + 4 + snd], o[16 * j + 5 + snd]),
                           pack2(o[16 * j + 8 + snd], o[16 * j + 9 + snd]), pack2(o[16 * j + 12 + snd], o[16 * j + 13 + snd]));
                bar_sync(10, 256);
                const float2 u = lds64f(mlw ^ 256);
                const float x = fminf(nk, u.x);
                float a = ex2(x - nk), c = ex2(x - u.x);
                const float inv = rcp(fmaf(a, o[32 + keep], c * u.y));
                a *= inv; c *= inv;
                uint32_t pk[8];
#pragma unroll
                for (int j = 0; j < 2; j++) {
                    const uint4 t4 = lds128((hbuf ^ 4096) + j * 2048);
                    const uint32_t t[4] = {t4.x, t4.y, t4.z, t4.w};
#pragma unroll
                    for (int i = 0; i < 4; i++)
                        pk[4 * j + i] = pack2(fmaf(a, o[16 * j + 4 * i + keep], c * blo(t[i])), fmaf(a, o[16 * j + 4 * i + keep + 1], c * bhi(t[i])));
                }
                st_data(odst, pk[0], pk[1], pk[2], pk[3]);
                st_data(odst + 512, pk[4], pk[5], pk[6], pk[7]);
            };
            if (tid < 128) merge(0, n0, n1); else merge(2, n1, n0);
            if (tid == 0) asm volatile("red.relaxed.gpu.global.add.u32 [%0], 1;" ::"l"(&g_epoch[blockIdx.x * FS]) : "memory");
            TS(15);
        }

        {
            const uint32_t* dp = reinterpret_cast<const uint32_t*>(p.dw + (mir ? 14 * 256 : 0) + tile * 64) + lane;
#pragma unroll
            for (int i = 0; i < 15; i++) asm volatile("ld.global.nc.b32 %0, [%1];" : "=r"(dwr[i]) : "l"(dp + i * (mir ? -128 : 128)));
            acq(32); acq(33); acq(34);
            uint4 u[8];
            ld_data<512>(u, g_o + (size_t)(b * 128 + pt * 4 + wq) * 4096 + lane * 16);
#pragma unroll
            for (int i = 0; i < 8; i++) { a[4 * i] = u[i].x; a[4 * i + 1] = u[i].y; a[4 * i + 2] = u[i].z; a[4 * i + 3] = u[i].w; }
            if (LATE & 4) rel(31);
            TS(16);
            sp(d0, 32, a, 0, 0);
            sp(d0, 33, a + 16, 0, 1);
#pragma unroll
            for (int i = 0; i < 15; i++) dwr[i] = hmul2(dwr[i], 0x3F003F00u);
            residual(32);
            TS(17);
        }
    }

    cluster_arrive();
    TS(24);
    {
        const float rstd = rsq(fmaxf(fmaf(-mean, mean, msq), 0.f) + 1e-5f), nb = -mean * rstd;
#pragma unroll
        for (int j = 0; j < 8; j++) xr[j] = pack2(fmaf(v[2 * j], rstd, nb), fmaf(v[2 * j + 1], rstd, nb));
        const uint32_t stg = P + 16384 + warp * 1024;
        stsm4(stg + foff, xr[0], xr[1], xr[2], xr[3]);
        stsm4(stg + (foff ^ 64), xr[4], xr[5], xr[6], xr[7]);
        __syncwarp();
        const uint32_t src = stg + (lane >> 3) * 128 + (((lane & 7) ^ (lane >> 3)) << 4);
        const uint4 u0 = lds128(src), u1 = lds128((src + 512) ^ 64);
        __nv_bfloat16* dst = p.out + (size_t)(b * T_ + trow + (lane >> 3)) * 256 + tile * 64 + (lane & 7) * 8;
        if (trow < T_) { stg128(dst, u0); stg128(dst + 4 * 256, u1); }
    }
    TS(25);
    TG(31);
    TSDUMP();
    cluster_wait();
}

typedef CUresult (*EncodeFn)(CUtensorMap*, CUtensorMapDataType, cuuint32_t, void*, const cuuint64_t*, const cuuint64_t*,
                             const cuuint32_t*, const cuuint32_t*, CUtensorMapInterleave, CUtensorMapSwizzle,
                             CUtensorMapL2promotion, CUtensorMapFloatOOBfill);

}

extern "C" void kernel_launch(void* const* d_in, const int* in_sizes, int n_in, void* d_out, int out_size) {
    static EncodeFn encode = nullptr;
    if (!encode) {
        void* fn = nullptr;
        cudaDriverEntryPointQueryResult qr;
        cudaGetDriverEntryPoint("cuTensorMapEncodeTiled", &fn, cudaEnableDefault, &qr);
        encode = (EncodeFn)fn;
        cudaFuncSetAttribute(conformer_kernel, cudaFuncAttributeMaxDynamicSharedMemorySize, SMEM_LAUNCH);
    }
    Scalars p;
    Maps m;
    const cuuint32_t ones[5] = {1, 1, 1, 1, 1};
    const int idx[8] = {1, 2, 3, 4, 5, 7, 8, 9};
    const int rows[8] = {256, 1024, 256, 256, 256, 256, 256, 1024};
    const int cols[8] = {1024, 256, 768, 256, 512, 256, 1024, 256};
    for (int i = 0; i < 8; i++) {
        const cuuint64_t pitch = (cuuint64_t)cols[i] * 2;
        const bool f = i != 0 && i != 3;
        const cuuint64_t dims[5] = {(cuuint64_t)cols[i], f ? 2u : 4u, f ? 2u : 4u, f ? 4u : 2u, (cuuint64_t)rows[i] / (f ? 16 : 32)};
        const cuuint64_t strides[4] = {pitch, pitch * 8, pitch * (f ? 2 : 4), pitch * (f ? 16 : 32)};
        const cuuint32_t box[5] = {64, f ? 2u : 4u, f ? 2u : 4u, f ? 4u : 2u, f ? 8u : 4u};
        encode(&m.tm[i], CU_TENSOR_MAP_DATA_TYPE_BFLOAT16, 5, d_in[idx[i]], dims, strides, box, ones, CU_TENSOR_MAP_INTERLEAVE_NONE,
               CU_TENSOR_MAP_SWIZZLE_128B, CU_TENSOR_MAP_L2_PROMOTION_L2_128B, CU_TENSOR_MAP_FLOAT_OOB_FILL_NONE);
        m.w[i] = (const char*)d_in[idx[i]];
    }
    {
        void* kv = nullptr;
        cudaGetSymbolAddress(&kv, g_kvq);
        const cuuint64_t dims[2] = {64, 16384};
        const cuuint64_t strides[1] = {128};
        const cuuint32_t box[2] = {64, 128};
        encode(&m.tm[8], CU_TENSOR_MAP_DATA_TYPE_BFLOAT16, 2, kv, dims, strides, box, ones, CU_TENSOR_MAP_INTERLEAVE_NONE,
               CU_TENSOR_MAP_SWIZZLE_NONE, CU_TENSOR_MAP_L2_PROMOTION_L2_128B, CU_TENSOR_MAP_FLOAT_OOB_FILL_NONE);
    }
    p.x = (const __nv_bfloat16*)d_in[0];
    p.dw = (const __nv_bfloat16*)d_in[6];
    p.out = (__nv_bfloat16*)d_out;
    p.zero = 0;
    conformer_kernel<<<NCTA, NTHREADS, SMEM_LAUNCH>>>(p, m);
}
```

```cpp
#include <cuda_runtime.h>
#include <cuda_bf16.h>
#include <cuda.h>
#include <stdint.h>
#include <type_traits>

namespace {

constexpr int T_ = 1000;
constexpr int NCTA = 128;
constexpr int NTHREADS = 512;
constexpr int NSLOT = 6;
constexpr int SLOT = 16384;
constexpr int NLOADS = 54;

constexpr uint32_t OFF_RING = 0;
constexpr uint32_t OFF_P = 196608;
constexpr uint32_t OFF_H = 212992;
constexpr uint32_t OFF_MISC = 229376;
constexpr uint32_t OFF_BARS = 230912;
constexpr uint32_t SMEM_BYTES = 231424;
constexpr uint32_t GCH = 6144;
constexpr uint32_t HCH = 4096;

constexpr int B_FULL = 0, B_EMPTY = 12, B_XA = 24  , B_XB = 29  , B_INB = 33  , B_SR = 37,
              B_RST = 38, B_RDY = 39  , B_SINK = 43, B_HALO = 44  , NBARS = 48;

#define KD2 300u
#define KD3 500u
#define QGATE 700u
#define BACKOFF 0u
#define KFS 8
#define KDELAY 250u
#define NJ0 2
#define HDELAY 200u
#define LATE 3
#define SND 0
#define PF0 0
#define WARMF 1
#define EARLY 0
#define EAGER 0x0155
constexpr int FS = 8;

struct Scalars {
    const __nv_bfloat16* x;
    const __nv_bfloat16* dw;
    __nv_bfloat16* out;
    uint32_t zero;
};
struct Maps {
    CUtensorMap tm[9];
    const char* w[8];
};

__device__ __align__(1024) unsigned char g_kvq[3 * 8 * 1024 * 128];
__device__ __align__(1024) unsigned char g_o[2 * 128 * 4096];
__device__ uint4 g_halo[64 * 4 * 2 * 64];
__device__ __align__(128) uint32_t g_flag_kv[8 * 32 * KFS];
__device__ uint32_t g_reset[2 * 32];
__device__ uint32_t g_epoch[NCTA * FS];

#define TS(i) do { } while (0)
#define TSW(i) do { } while (0)
#define TG(i) do { } while (0)
#define TSINIT() do { } while (0)
#define TSDUMP() do { } while (0)
constexpr uint32_t SMEM_LAUNCH = SMEM_BYTES;

__device__ __forceinline__ uint32_t smem_u32(const void* p) { return (uint32_t)__cvta_generic_to_shared(p); }
__device__ __forceinline__ void mbar_init(uint32_t b, uint32_t c) { asm volatile("mbarrier.init.shared::cta.b64 [%0], %1;" ::"r"(b), "r"(c) : "memory"); }
__device__ __forceinline__ void mbar_arrive(uint32_t b) { asm volatile("mbarrier.arrive.shared::cta.b64 _, [%0];" ::"r"(b) : "memory"); }
__device__ __forceinline__ void mbar_arrive_tx(uint32_t b, uint32_t tx) { asm volatile("mbarrier.arrive.expect_tx.shared::cta.b64 _, [%0], %1;" ::"r"(b), "r"(tx) : "memory"); }
__device__ __forceinline__ void mbar_wait(uint32_t b, uint32_t ph) {
    asm volatile("{\n.reg .pred p, q;\n.reg .u32 c;\nmov.u32 c, 0;\n"
                 "MW_LOOP:\n.pragma \"nounroll\";\n"
                 "mbarrier.try_wait.parity.shared::cta.b64 p, [%0], %1;\n"
                 "add.u32 c, c, 1;\nsetp.lt.u32 q, c, 65536;\nnot.pred p, p;\nand.pred p, p, q;\n@p bra MW_LOOP;\n}"
                 ::"r"(b), "r"(ph) : "memory");
}
__device__ __forceinline__ bool mbar_test(uint32_t b, uint32_t ph) {
    uint32_t ok;
    asm volatile("{\n.reg .pred p;\nmbarrier.test_wait.parity.shared::cta.b64 p, [%1], %2;\nselp.u32 %0, 1, 0, p;\n}" : "=r"(ok) : "r"(b), "r"(ph) : "memory");
    return ok;
}
__device__ __forceinline__ uint32_t mapa(uint32_t a, uint32_t r) { uint32_t o; asm("mapa.shared::cluster.u32 %0, %1, %2;" : "=r"(o) : "r"(a), "r"(r)); return o; }
__device__ __forceinline__ void fence_async_smem() { asm volatile("fence.proxy.async.shared::cta;" ::: "memory"); }
__device__ __forceinline__ void fence_async_global() { asm volatile("fence.proxy.async.global;" ::: "memory"); }
__device__ __forceinline__ void bar_sync(int id, int n) { asm volatile("bar.sync %0, %1;" ::"r"(id), "r"(n) : "memory"); }
__device__ __forceinline__ void bar_arrive(int id, int n) { asm volatile("bar.arrive %0, %1;" ::"r"(id), "r"(n) : "memory"); }
__device__ __forceinline__ void cluster_arrive() { asm volatile("barrier.cluster.arrive.relaxed.aligned;" ::: "memory"); }
__device__ __forceinline__ void cluster_wait() { asm volatile("barrier.cluster.wait.aligned;" ::: "memory"); }

__device__ __forceinline__ void ring_load(uint32_t dst, const CUtensorMap* tm, int col, int row16, uint32_t bar) {
    asm volatile("{\n.reg .pred p;\nelect.sync _|p, 0xffffffff;\n"
                 "@p mbarrier.arrive.expect_tx.shared::cta.b64 _, [%2], 16384;\n"
                 "@p cp.async.bulk.tensor.5d.shared::cluster.global.mbarrier::complete_tx::bytes [%0], [%1, {%3, 0, 0, 0, %4}], [%2];\n}"
                 ::"r"(dst), "l"(tm), "r"(bar), "r"(col), "r"(row16) : "memory");
}
__device__ __forceinline__ void ring_load_both(uint32_t dst, const CUtensorMap* tm, int c1, uint32_t bar) {
    asm volatile("{\n.reg .pred p;\nelect.sync _|p, 0xffffffff;\n"
                 "@p cp.async.bulk.tensor.2d.shared::cluster.global.mbarrier::complete_tx::bytes.multicast::cluster [%0], [%1, {0, %3}], [%2], %4;\n}"
                 ::"r"(dst), "l"(tm), "r"(bar), "r"(c1), "h"((uint16_t)3) : "memory");
}
__device__ __forceinline__ void mbar_arrive_peer(uint32_t b) { asm volatile("mbarrier.arrive.relaxed.cluster.shared::cluster.b64 _, [%0];" ::"r"(b) : "memory"); }
__device__ __forceinline__ void prefetch_l2(const void* src, uint32_t bytes) {
    asm volatile("cp.async.bulk.prefetch.L2.global [%0], %1;" ::"l"(src), "r"(bytes) : "memory");
}
__device__ __forceinline__ void st_async4(uint32_t dst, uint32_t a, uint32_t b, uint32_t c, uint32_t d, uint32_t bar) {
    asm volatile("st.async.shared::cluster.mbarrier::complete_tx::bytes.v4.b32 [%0], {%1,%2,%3,%4}, [%5];" ::"r"(dst), "r"(a), "r"(b), "r"(c), "r"(d), "r"(bar) : "memory");
}
__device__ __forceinline__ void put_sums(uint32_t dst, uint32_t rdst, float a, float b, uint32_t rbar, bool on) {
    asm volatile("{\n.reg .pred p;\nsetp.ne.u32 p, %5, 0;\n"
                 "@p st.async.shared::cluster.mbarrier::complete_tx::bytes.v2.f32 [%1], {%2,%3}, [%4];\n"
                 "@p st.shared.v2.f32 [%0], {%2,%3};\n}" ::"r"(dst), "r"(rdst), "f"(a), "f"(b), "r"(rbar), "r"((uint32_t)on) : "memory");
}
__device__ __forceinline__ void stsm4(uint32_t a, uint32_t r0, uint32_t r1, uint32_t r2, uint32_t r3) {
    asm volatile("stmatrix.sync.aligned.m8n8.x4.shared.b16 [%0], {%1,%2,%3,%4};" ::"r"(a), "r"(r0), "r"(r1), "r"(r2), "r"(r3) : "memory");
}
__device__ __forceinline__ void ldsm4(uint32_t a, uint32_t& r0, uint32_t& r1, uint32_t& r2, uint32_t& r3) {
    asm volatile("ldmatrix.sync.aligned.m8n8.x4.shared.b16 {%0,%1,%2,%3}, [%4];" : "=r"(r0), "=r"(r1), "=r"(r2), "=r"(r3) : "r"(a) : "memory");
}
__device__ __forceinline__ uint4 lds128(uint32_t a) { uint4 v; asm volatile("ld.shared.v4.b32 {%0,%1,%2,%3}, [%4];" : "=r"(v.x), "=r"(v.y), "=r"(v.z), "=r"(v.w) : "r"(a) : "memory"); return v; }
__device__ __forceinline__ float4 lds128f(uint32_t a) { float4 v; asm volatile("ld.shared.v4.f32 {%0,%1,%2,%3}, [%4];" : "=f"(v.x), "=f"(v.y), "=f"(v.z), "=f"(v.w) : "r"(a) : "memory"); return v; }
__device__ __forceinline__ float2 lds64f(uint32_t a) { float2 v; asm volatile("ld.shared.v2.f32 {%0,%1}, [%2];" : "=f"(v.x), "=f"(v.y) : "r"(a) : "memory"); return v; }
__device__ __forceinline__ uint32_t lds32(uint32_t a) { uint32_t v; asm volatile("ld.shared.b32 %0, [%1];" : "=r"(v) : "r"(a) : "memory"); return v; }
__device__ __forceinline__ void sts128(uint32_t a, uint32_t x, uint32_t y, uint32_t z, uint32_t w) { asm volatile("st.shared.v4.b32 [%0], {%1,%2,%3,%4};" ::"r"(a), "r"(x), "r"(y), "r"(z), "r"(w) : "memory"); }
__device__ __forceinline__ void sts128f(uint32_t a, float x, float y, float z, float w) { asm volatile("st.shared.v4.f32 [%0], {%1,%2,%3,%4};" ::"r"(a), "f"(x), "f"(y), "f"(z), "f"(w) : "memory"); }
__device__ __forceinline__ void sts64f(uint32_t a, float x, float y) { asm volatile("st.shared.v2.f32 [%0], {%1,%2};" ::"r"(a), "f"(x), "f"(y) : "memory"); }
__device__ __forceinline__ void sts32(uint32_t a, uint32_t x) { asm volatile("st.shared.b32 [%0], %1;" ::"r"(a), "r"(x) : "memory"); }
__device__ __forceinline__ void stg128(void* p, uint4 v) { asm volatile("st.global.v4.b32 [%0], {%1,%2,%3,%4};" ::"l"(p), "r"(v.x), "r"(v.y), "r"(v.z), "r"(v.w) : "memory"); }

__device__ __forceinline__ uint32_t pack2(float lo, float hi) { uint32_t r; asm("cvt.rn.bf16x2.f32 %0, %1, %2;" : "=r"(r) : "f"(hi), "f"(lo)); return r; }
__device__ __forceinline__ float blo(uint32_t v) { return __uint_as_float(v << 16); }
__device__ __forceinline__ float bhi(uint32_t v) { return __uint_as_float(v & 0xffff0000u); }
__device__ __forceinline__ uint32_t hmul2(uint32_t a, uint32_t b) { uint32_t r; asm("mul.rn.bf16x2 %0, %1, %2;" : "=r"(r) : "r"(a), "r"(b)); return r; }
__device__ __forceinline__ uint32_t hadd2(uint32_t a, uint32_t b) { uint32_t r; asm("add.rn.bf16x2 %0, %1, %2;" : "=r"(r) : "r"(a), "r"(b)); return r; }
__device__ __forceinline__ uint32_t hsub2(uint32_t a, uint32_t b) { uint32_t r; asm("sub.rn.bf16x2 %0, %1, %2;" : "=r"(r) : "r"(a), "r"(b)); return r; }
__device__ __forceinline__ uint32_t hfma2(uint32_t a, uint32_t b, uint32_t c) { uint32_t r; asm("fma.rn.bf16x2 %0, %1, %2, %3;" : "=r"(r) : "r"(a), "r"(b), "r"(c)); return r; }
__device__ __forceinline__ float tanh_fast(float x) { float r; asm("tanh.approx.f32 %0, %1;" : "=f"(r) : "f"(x)); return r; }
__device__ __forceinline__ float rsq(float x) { float r; asm("rsqrt.approx.ftz.f32 %0, %1;" : "=f"(r) : "f"(x)); return r; }
__device__ __forceinline__ float rcp(float x) { float r; asm("rcp.approx.ftz.f32 %0, %1;" : "=f"(r) : "f"(x)); return r; }
__device__ __forceinline__ float ex2(float x) { float r; asm("ex2.approx.ftz.f32 %0, %1;" : "=f"(r) : "f"(x)); return r; }

__device__ __forceinline__ uint32_t ld_relaxed(const uint32_t* p) {
    uint32_t v;
    asm volatile("ld.relaxed.gpu.global.u32 %0, [%1];" : "=r"(v) : "l"(p) : "memory");
    return v;
}
__device__ __forceinline__ uint32_t clock32() { uint32_t c; asm volatile("mov.u32 %0, %%clock;" : "=r"(c)::"memory"); return c; }
__device__ __forceinline__ void spin(uint32_t clks) {
    const uint32_t t0 = clock32();
    while (clock32() - t0 < clks) {}
}
__device__ __forceinline__ void flag_wait(const uint32_t* p, uint32_t e, bool mine) {
#pragma unroll 1
    for (int i = 0; i < (1 << 19); i++) {
        if (mine) mine = ld_relaxed(p) != e;
        if (!__any_sync(~0u, mine)) break;
        if (BACKOFF) spin(BACKOFF);
    }
    asm volatile("fence.acquire.gpu;" ::: "memory");
    fence_async_global();
}
__device__ __forceinline__ void st_data(void* p, uint32_t x, uint32_t y, uint32_t z, uint32_t w) {
    asm volatile("st.relaxed.gpu.global.v4.b32 [%0], {%1,%2,%3,%4};" ::"l"(p), "r"(x), "r"(y), "r"(z), "r"(w) : "memory");
}
template <int STRIDE, bool INV = false, int N>
__device__ __forceinline__ void ld_data(uint4 (&v)[N], const unsigned char* p) {
    int it = 0;
    bool again;
#pragma unroll 1
    do {
        uint32_t m = INV ? ~0u : 0u;
#pragma unroll
        for (int i = 0; i < N; i++)
            asm volatile("ld.relaxed.gpu.global.v4.b32 {%0,%1,%2,%3}, [%4];" : "=r"(v[i].x), "=r"(v[i].y), "=r"(v[i].z), "=r"(v[i].w) : "l"(p + i * STRIDE) : "memory");
#pragma unroll
        for (int i = 0; i < N; i++)
            m = INV ? __vimin3_u32(__vimin3_u32(v[i].x, v[i].y, v[i].z), v[i].w, m) : __vimax3_u32(__vimax3_u32(v[i].x, v[i].y, v[i].z), v[i].w, m);
        again = __any_sync(~0u, m == (INV ? 0u : ~0u)) && ++it < (1 << 16);
    } while (again);
}
__device__ __forceinline__ uint32_t ld_epoch() { return ld_relaxed(&g_epoch[blockIdx.x * FS]) + 1; }
__device__ __forceinline__ void flag_set(uint32_t* p, uint32_t e) { asm volatile("st.release.gpu.global.u32 [%0], %1;" ::"l"(p), "r"(e) : "memory"); }

__device__ __forceinline__ uint32_t desc_lo(uint32_t addr) { return ((addr & 0x3FFFF) >> 4) | 0x10000u; }
__device__ __forceinline__ uint64_t mkdesc(uint32_t lo) { return (uint64_t)lo | (0x40000040ull << 32); }
__device__ __forceinline__ void wg_fence() { asm volatile("wgmma.fence.sync.aligned;" ::: "memory"); }
__device__ __forceinline__ void wg_commit() { asm volatile("wgmma.commit_group.sync.aligned;" ::: "memory"); }
template <int N> __device__ __forceinline__ void wg_wait() { asm volatile("wgmma.wait_group.sync.aligned %0;" ::"n"(N) : "memory"); }
template <int N> __device__ __forceinline__ void pin(float (&d)[N]) {
#pragma unroll
    for (int i = 0; i < N; i++) asm volatile("" : "+f"(d[i])::"memory");
}
template <int N> __device__ __forceinline__ void pin(uint32_t (&d)[N]) {
#pragma unroll
    for (int i = 0; i < N; i++) asm volatile("" : "+r"(d[i])::"memory");
}

template <typename Tp, int N> __device__ __forceinline__ void zero(Tp (&d)[N]) {
#pragma unroll
    for (int i = 0; i < N; i++) d[i] = 0;
    pin(d);
}

#define F4(d, i) "+f"(d[i]), "+f"(d[i + 1]), "+f"(d[i + 2]), "+f"(d[i + 3])
#define F16(d, i) F4(d, i), F4(d, i + 4), F4(d, i + 8), F4(d, i + 12)

__device__ __forceinline__ void mma16(float (&d)[4], const uint32_t* a, uint32_t b0, uint32_t b1) {
    asm("mma.sync.aligned.m16n8k16.row.col.f32.bf16.bf16.f32 {%0,%1,%2,%3}, {%4,%5,%6,%7}, {%8,%9}, {%0,%1,%2,%3};"
        : F4(d, 0) : "r"(a[0]), "r"(a[1]), "r"(a[2]), "r"(a[3]), "r"(b0), "r"(b1));
}
template <int N>
__device__ __forceinline__ float row_sum(const uint32_t* x, uint32_t ones = 0x3F803F80u) {
    float c[4] = {};
#pragma unroll
    for (int i = 0; i < N; i += 4) mma16(c, x + i, ones, ones);
    return c[0] + c[2];
}
template <int N>
__device__ __forceinline__ float row_sumsq(const uint32_t* x, int lane) {
    float c0[4] = {}, c1[4] = {};
#pragma unroll
    for (int i = 0; i < N; i += 4) {
        mma16(c0, x + i, x[i], x[i + 2]);
        mma16(c1, x + i, x[i + 1], x[i + 3]);
    }
    return (lane & 4) ? c0[1] + c1[3] : c0[0] + c1[2];
}
__device__ __forceinline__ void mma_sp(float (&d)[32], const uint32_t* a, uint64_t b, uint32_t meta, int acc) {
    asm volatile("{.reg .pred p; setp.ne.b32 p, %38, 0;\n"
                 "wgmma.mma_async.sp.sync.aligned.m64n64k32.f32.bf16.bf16 {%0,%1,%2,%3,%4,%5,%6,%7,%8,%9,%10,%11,%12,%13,%14,%15,%16,%17,%18,%19,%20,%21,%22,%23,%24,%25,%26,%27,%28,%29,%30,%31}, "
                 "{%32,%33,%34,%35}, %36, %37, 0, p, 1, 1, 1;}\n"
                 : F16(d, 0), F16(d, 16) : "r"(a[0]), "r"(a[1]), "r"(a[2]), "r"(a[3]), "l"(b), "r"(meta), "r"(acc));
}
__device__ __forceinline__ void mma_qk(float (&d)[32], uint32_t a0, uint32_t a1, uint32_t a2, uint32_t a3, uint64_t b, int acc) {
    asm volatile("{.reg .pred p; setp.ne.b32 p, %37, 0;\n"
                 "wgmma.mma_async.sync.aligned.m64n64k16.f32.bf16.bf16 {%0,%1,%2,%3,%4,%5,%6,%7,%8,%9,%10,%11,%12,%13,%14,%15,%16,%17,%18,%19,%20,%21,%22,%23,%24,%25,%26,%27,%28,%29,%30,%31}, "
                 "{%32,%33,%34,%35}, %36, p, 1, 1, 0;}\n"
                 : F16(d, 0), F16(d, 16) : "r"(a0), "r"(a1), "r"(a2), "r"(a3), "l"(b), "r"(acc));
}
__device__ __forceinline__ void mma_pv(float (&d)[36], uint32_t a0, uint32_t a1, uint32_t a2, uint32_t a3, uint64_t b) {
    asm volatile("wgmma.mma_async.sync.aligned.m64n72k16.f32.bf16.bf16 {%0,%1,%2,%3,%4,%5,%6,%7,%8,%9,%10,%11,%12,%13,%14,%15,%16,%17,%18,%19,%20,%21,%22,%23,%24,%25,%26,%27,%28,%29,%30,%31,%32,%33,%34,%35}, "
                 "{%36,%37,%38,%39}, %40, 1, 1, 1, 1;\n"
                 : F16(d, 0), F16(d, 16), F4(d, 32) : "r"(a0), "r"(a1), "r"(a2), "r"(a3), "l"(b));
}

__device__ __forceinline__ uint32_t load_code(int n, int r, int w) {
    const int tile = 2 * r + w;
    int m, col, row;
    if (n < 16 || n >= 38) {
        const int k = n < 16 ? n : n - 38;
        m = n < 16 ? 0 : 6;
        if (n >= 38 && k < 4) { col = 4 * tile + (k & 1); row = (k >> 1) ^ r; }
        else if (k < 8) { col = 4 * tile + (k >> 1); row = n < 16 ? (k & 1) : (k & 1) ^ r; }
        else { m++; col = k < 12 ? tile ^ 2 : tile; row = 2 * (tile ^ (k & 1)) + ((k >> 1) & 1); }
    } else if (n < 30) {
        const int k = n - 16;
        m = 2;
        if (k < 4) { col = tile + ((k & 1) ? 8 : 4); row = (k >> 1) ^ r; }
        else { col = tile; row = (k & 1) ^ r; }
    } else if (n < 32) { m = 3; col = tile; row = n - 30; }
    else if (n < 36) { const int k = n - 32; m = 4; col = tile + 4 * (k & 1); row = (k >> 1) ^ r; }
    else { m = 5; col = tile; row = (n & 1) ^ r; }
    return m | (col << 4) | (row << ((m == 0 || m == 3) ? 10 : 11));
}

__global__ void __cluster_dims__(2, 1, 1) __launch_bounds__(NTHREADS, 1)
conformer_kernel(const Scalars p, const __grid_constant__ Maps m) {
    extern __shared__ __align__(1024) unsigned char smem_raw[];
    const uint32_t sb = smem_u32(smem_raw);
    const uint32_t bars = sb + OFF_BARS;
    const int tid = threadIdx.x;
    const int lane = tid & 31;
    const int warp = __shfl_sync(~0u, tid >> 5, 0);
    const int r = blockIdx.x & 1;
    const int pair = blockIdx.x >> 1;
    const int b = pair >> 5, pt = pair & 31;
    const int ah = pt >> 3, qt = (pt & 7) * 2 + r;
    const int abh = b * 4 + ah;

    TG(30);
    TSINIT();
    TS(0);
    const uint32_t P = sb + OFF_P, H = sb + OFF_H;
    if (warp == 11) {
        if (lane == 0) {
#pragma unroll
            for (int i = 0; i < 2 * NSLOT; i++) mbar_init(bars + (B_FULL + i) * 8, 1);
            asm volatile("fence.mbarrier_init.release.cluster;" ::: "memory");
            fence_async_smem();
        }
        __syncwarp();
        bar_arrive(13, 96);
        cluster_arrive();
    }

    if (warp >= 8) {
        asm volatile("setmaxnreg.dec.sync.aligned.u32 48;");
        auto first_loads = [&]() {
            const int w = warp - 8;
            const uint32_t ring = sb + OFF_RING + w * NSLOT * SLOT;
            const uint32_t full = bars + (B_FULL + w * NSLOT) * 8;
            cluster_arrive();
            bar_sync(13, 96);
            TS(1);
#pragma unroll
            for (int n = 0; n < NSLOT; n++) {
                if (n == 1) bar_sync(12, 64);
                ring_load(ring + n * SLOT, &m.tm[0], 64 * (8 * r + 4 * w + (n >> 1)), 4 * (n & 1), full + n * 8);
            }
        };
        if (EARLY && warp < 10 + (int)p.zero) first_loads();
        if (warp >= 12) {
            cluster_arrive();
            const int ut = tid & 127;
            cluster_wait();
            const uint32_t target = ld_epoch() * 64;
            bar_sync(6, 384);
#pragma unroll
            for (int i = 0; i < 4; i++) {
                st_data(g_o + (size_t)(b * 128 + qt * 8 + 2 * i + (ut >> 6)) * 4096 + ah * 1024 + (ut & 63) * 16, ~0u, ~0u, ~0u, ~0u);
                if (i < 2) st_data(&g_halo[(pair * 4 + 2 * r + i) * 128 + ut], ~0u, ~0u, ~0u, ~0u);
            }
            bar_sync(11, 128);
            if (ut == 0) {
                asm volatile("red.release.gpu.global.add.u32 [%0], 1;" ::"l"(&g_reset[b * 32]) : "memory");
#pragma unroll 1
                for (int i = 0; i < (1 << 20) && ld_relaxed(&g_reset[b * 32]) != target; i++) __nanosleep(100);
                asm volatile("fence.acquire.gpu;" ::: "memory");
                mbar_arrive(bars + B_RST * 8);
            }
            bar_sync(11, 128);
            TS(14);
#pragma unroll
            for (int i = 0; i < 4; i++) st_data(g_kvq + 2097152 + (size_t)(abh * 1024 + qt * 64) * 128 + i * 2048 + ut * 16, 0, 0, 0, 0);
            const int side = warp & 1, wg = (warp >> 1) & 1, np = side ? pt + 1 : pt - 1;
            const unsigned char* src = reinterpret_cast<const unsigned char*>(&g_halo[(((b * 32 + np) * 4 + 2 * r + wg) * 2 + (side ^ 1)) * 64 + lane]);
            const uint32_t dst = P + wg * GCH + side * 5120 + (lane & 7) * 128 + (((lane >> 3) ^ (lane & 7)) << 4);
            uint4 hv[2] = {make_uint4(0, 0, 0, 0), make_uint4(0, 0, 0, 0)};
            bar_sync(8 + wg, 192);
            if (np >= 0 && np < 32) {
                spin(HDELAY);
                ld_data<512>(hv, src);
            }
            stsm4(dst, hv[0].x, hv[0].y, hv[0].z, hv[0].w);
            stsm4(dst ^ 64, hv[1].x, hv[1].y, hv[1].z, hv[1].w);
            __syncwarp();
            if (lane == 0) mbar_arrive(bars + (B_HALO + (warp & 3)) * 8);
            TS(4);
        } else if (warp < 10) {
            const int w = warp - 8;
            const uint32_t ring = sb + OFF_RING + w * NSLOT * SLOT;
            const uint32_t full = bars + (B_FULL + w * NSLOT) * 8;
            if (!EARLY) first_loads();
            TS(2);
            const uint32_t code = load_code(lane, r, w) | (load_code(lane + 32, r, w) << 16);
            cluster_wait();
            uint32_t s = 0, ph = 0;
            int n = NSLOT;
#pragma unroll 1
            for (int seg = 0; seg < 2; seg++) {
#pragma unroll 1
                for (; n < (seg == 0 ? 22 : NLOADS); n++) {
                    const uint32_t c = __shfl_sync(~0u, code, n) >> (n & 32 ? 16 : 0);
                    const CUtensorMap* tm = &m.tm[c & 15];
                    const uint32_t col = (c & 0xf0) * 4, row = (c & 0xff00) >> 8, dst = ring + s * SLOT;
                    mbar_wait(full + (B_EMPTY - B_FULL) * 8 + s * 8, ph + (((uint32_t)(size_t)tm | col | row | dst) & p.zero));
                    ring_load(dst, tm, col, row, full + s * 8);
                    if (++s == NSLOT) { s = 0; ph ^= 1; }
                }
                if (seg == 1) break;
                const uint32_t epoch = ld_epoch();
                const uint32_t rdy = bars + (B_RDY + 2 * w) * 8, prdy = mapa(rdy, r ^ 1);
                const int odd = r ^ w;
                const uint32_t* flags = g_flag_kv + (abh * 32 + lane) * KFS;
                bool first = (lane >> 2) == 2 * odd + w;
                if (WARMF && first) first = ld_relaxed(flags) != epoch;
                auto kv_load = [&](uint32_t sl, int isv, int i) {
                    ring_load_both(ring + sl * SLOT, &m.tm[8], (isv * 64 + abh * 8 + 2 * i + w) * 128, full + sl * 8);
                };
                if (lane < NSLOT) {
                    mbar_wait(full + (B_EMPTY - B_FULL + lane) * 8, lane < 4);
                    mbar_arrive_tx(full + lane * 8, SLOT);
                }
                __syncwarp();
                if (lane == 0) mbar_arrive_peer(prdy);
                bar_sync(14, 96);
                spin(KDELAY);
                mbar_wait(rdy, 0);
                flag_wait(flags, epoch, first);
                TSW(5 + 2 * odd);
                if (!odd) { kv_load(4, 0, 0); bar_arrive(12, 64); }
                else bar_sync(12, 64);
                spin(w ? KD3 : KD2);
                kv_load(odd ? 5 : 0, odd ^ 1, odd);
                flag_wait(flags, epoch, (lane >> 2) == 2 * odd + w + 4);
                mbar_wait(full + (odd ? 5 : 0) * 8, odd);
                kv_load(1 + odd, odd, 2 - odd);
                if (odd) { mbar_wait(full + 16, 0); kv_load(3, 0, 3); }
#pragma unroll 1
                for (int i = 0; i < 2; i++) {
                    mbar_wait(full + (B_EMPTY - B_FULL + 4 + i) * 8, 1);
                    if (lane == 0) mbar_arrive_tx(full + (4 + i) * 8, SLOT);
                    if (i == odd) {
                        mbar_wait(rdy + 8, 0);
                        kv_load(4 + i, 1, 2 + i);
                    } else if (lane == 0) mbar_arrive_peer(prdy + 8);
                    __syncwarp();
                }
                n = 30; s = 0; ph = 0;
            }
        } else if (warp == 10) {
            if (lane == 0) {
#pragma unroll
                for (int i = B_EMPTY; i < NBARS; i++) mbar_init(bars + i * 8, i < B_XA ? 4 : 1);
#pragma unroll
                for (int i = B_XA; i <= B_SR; i++) mbar_arrive_tx(bars + i * 8, i < B_XB ? 512 : ((i >= B_INB && i < B_SR) ? 4096 : 8192));
                asm volatile("fence.mbarrier_init.release.cluster;" ::: "memory");
                fence_async_smem();
            }
            __syncwarp();
            cluster_arrive();
            cluster_wait();
        } else {
            const uint32_t kb = (lane < 2 || lane > 5) ? 4096 : (lane == 2 ? 3072 : (lane == 4 ? 2048 : 1024));
            const char* pf = m.w[lane & 7] + blockIdx.x * kb;
            cluster_wait();
            if (lane < PF0) prefetch_l2(pf, kb);
            mbar_wait(bars + B_FULL * 8, 0);
            if (lane >= PF0 && lane < 3) prefetch_l2(pf, kb);
            if (lane >= 1 && lane < 9) asm volatile("prefetch.tensormap [%0];" ::"l"(&m.tm[lane]) : "memory");
            mbar_wait(bars + (B_FULL + 1) * 8, 1);
            if (lane > 2 && lane < 8) prefetch_l2(pf, kb);
            if (lane == 8 && blockIdx.x < 15) prefetch_l2(p.dw + blockIdx.x * 256, 512);
            const uint32_t epoch = ld_epoch();
            bar_sync(4, 288);
            if (lane < 16) flag_set(&g_flag_kv[((b * 4 + 2 * r + (lane >> 3)) * 32 + pt) * KFS + (lane & 7)], epoch);
            __syncwarp();
            bar_arrive(14, 96);
            TSW(8);
        }
        TSDUMP();
        return;
    }

    const int w = warp >> 2, wq = warp & 3;
    const int tile = 2 * r + w;
    const int wt = tid & 127;
    const int c4 = lane & 3;
    const int trow = pt * 32 + 8 * wq;
    uint32_t xr[8];
    uint32_t a[32];
    const char* xrow = reinterpret_cast<const char*>(p.x) + (b * T_ + trow + (lane >> 2)) * 512;
    zero(a);
    if (trow < T_) {
        const char* src = xrow + c4 * 16 + p.zero;
#pragma unroll
        for (int i = 0; i < 8; i++)
            asm volatile("ld.global.nc.v4.b32 {%0,%1,%2,%3}, [%4];" : "=r"(a[4 * i]), "=r"(a[4 * i + 1]), "=r"(a[4 * i + 2]), "=r"(a[4 * i + 3]) : "l"(src + 64 * i));
    }
    cluster_arrive();
    asm volatile("setmaxnreg.inc.sync.aligned.u32 208;");
    const uint32_t rbase = sb + OFF_RING + w * NSLOT * SLOT, fbar = bars + (B_FULL + w * NSLOT) * 8;
    const uint32_t rdesc = desc_lo(rbase);
    auto acq = [&](int n) { mbar_wait(fbar + (n % NSLOT) * 8, (n / NSLOT) & 1); };
    auto rel = [&](int n) { if (lane == 0) mbar_arrive(fbar + (B_EMPTY - B_FULL + n % NSLOT) * 8); };
    const uint32_t foff = (lane & 7) * 128 + (((lane >> 3) ^ (lane & 7)) << 4);
    float v[16];
    const uint32_t xown = __shfl_sync(~0u, P + wt * 16 + tile * 4096, lane), xrem = __shfl_sync(~0u, P + wt * 16 + (r ^ 1) * 8192, lane);
    const uint32_t sbuf = __shfl_sync(~0u, sb + OFF_MISC + (8 * wq + (lane >> 2)) * 32, lane);
    const uint32_t sown = __shfl_sync(~0u, sbuf + tile * 8, lane);
    const uint32_t peer = __shfl_sync(~0u, mapa(sb, r ^ 1) - sb, lane);
    const uint32_t hbuf = __shfl_sync(~0u, H + w * 4096 + wt * 16, lane);
    const uint32_t meta = __shfl_sync(~0u, 0xEEEE4444u + p.zero, lane);
    cluster_wait();
    TS(56);
    float mean, msq;
    const int mir = wq < 2 ? 7 : 0;
    uint32_t dwr[15];

    auto phase = [&](auto phc) __attribute__((always_inline)) {
        constexpr int ph = decltype(phc)::value;
        uint4 o0, o1;
        if (ph == 0) {
            const uint32_t one = 0x3F803F80u + ((xown | xrem | sbuf | sown | hbuf | foff | rdesc | fbar) & p.zero);
            mean = ((row_sum<8>(a, one) + row_sum<8>(a + 8, one)) + (row_sum<8>(a + 16, one) + row_sum<8>(a + 24, one))) * (1.f / 256.f);
            TS(57);
        } else {
            const uint32_t xa = bars + (B_XA + ph) * 8;
#pragma unroll
            for (int j = 0; j < 8; j++) xr[j] = pack2(v[2 * j], v[2 * j + 1]);
            const float s = row_sum<8>(xr), q = row_sumsq<8>(xr, lane);
            if (ph < 4) {
                sts128(xown, xr[0], xr[1], xr[2], xr[3]);
                sts128(xown + 2048, xr[4], xr[5], xr[6], xr[7]);
            }
            put_sums(sown, sown + peer, s, q, xa + peer, c4 == (lane >> 3));
            bar_sync(10, 256);
            if (ph < 4) {
                o0 = lds128(xown ^ 4096); o1 = lds128((xown ^ 4096) + 2048);
                st_async4(xown + peer, xr[0], xr[1], xr[2], xr[3], xa + (B_XB - B_XA) * 8 + peer);
                st_async4(xown + peer + 2048, xr[4], xr[5], xr[6], xr[7], xa + (B_XB - B_XA) * 8 + peer);
            }
            TS(57 + ph);
            if (ph == 3) acq(38);
            if (ph == 1) acq(16);
            mbar_wait(xa, 0);
            const float4 u0 = lds128f(sbuf), u1 = lds128f(sbuf + 16);
            mean = ((u0.x + u0.z) + (u1.x + u1.z)) * (1.f / 256.f);
            msq = ((u0.y + u0.w) + (u1.y + u1.w)) * (1.f / 256.f);
        }
        if (ph == 4) return;
        const uint32_t mean2 = pack2(mean, mean);
        auto centre = [&](int i, const uint4& u) {
            a[i] = hsub2(u.x, mean2); a[i + 1] = hsub2(u.y, mean2); a[i + 2] = hsub2(u.z, mean2); a[i + 3] = hsub2(u.w, mean2);
        };
        if (ph == 0) {
#pragma unroll
            for (int j = 0; j < 32; j++) a[j] = hsub2(a[j], mean2);
            zero(xr);
            if (trow < T_) {
                const char* src = xrow + tile * 128 + c4 * 4 + (mean2 & p.zero);
#pragma unroll
                for (int j = 0; j < 8; j++) asm volatile("ld.global.nc.b32 %0, [%1];" : "=r"(xr[j]) : "l"(src + 16 * j));
            }
            mean -= blo(mean2);
            msq = __shfl_sync(~0u, row_sumsq<16>(a, lane) + row_sumsq<16>(a + 16, lane), (lane & 28) + (lane >> 3)) * (1.f / 256.f);
            acq(0);
        } else {
#pragma unroll
            for (int j = 0; j < 8; j++) a[j] = hsub2(xr[j], mean2);
            centre(8, o0); centre(12, o1);
        }
        const float rstd = rsq(fmaxf(fmaf(-mean, mean, msq), 0.f) + 1e-5f);
        auto gather_peer = [&]() {
            mbar_wait(bars + (B_XB + ph) * 8, 0);
#pragma unroll
            for (int i = 0; i < 4; i++) centre(16 + 4 * i, lds128(xrem + i * 2048));
        };
        auto sp = [&](float (&d)[32], int n, const uint32_t* af, int flip, int acc) {
            const uint32_t lo = rdesc + p.zero * (ph * 64 + n + 1) + (n % NSLOT) * (SLOT >> 4);
            const uint64_t b0 = mkdesc(lo + flip * 512), b1 = mkdesc(lo + (flip ^ 1) * 512);
            wg_fence();
            mma_sp(d, af, b0, meta, acc);
            mma_sp(d, af + 4, b0 + 256, meta, 1);
            mma_sp(d, af + 8, b1, meta, 1);
            mma_sp(d, af + 12, b1 + 256, meta, 1);
            wg_commit();
        };
        float d0[32], d1[32];

        if (ph == 0 || ph == 3) {
            uint32_t h[32], ho[32];
            const float rs = 0.5f * rstd;
            const uint32_t inb = bars + (B_INB + (ph & 2) + w) * 8;
            bool ready = true;
            const int eager = ph ? EAGER + 5 : EAGER - 1;
            auto step = [&](float (&d)[32], int n, const uint32_t* af, int flip, int acc, auto work) {
                const int l = n + (ph ? 38 : 0);
                if (!ready) acq(l);
                sp(d, l, af, flip, acc);
                if (n < 15) ready = mbar_test(fbar + ((l + 1) % NSLOT) * 8, ((l + 1) / NSLOT) & 1);
                wg_wait<1>();
                if (n > 0 && !((eager >> (n - 1)) & 1)) rel(l - 1);
                const uint32_t tie = work() & p.zero;
                if ((eager >> n) & 1) {
                    if (p.zero < l + 1) wg_wait<0>();
                    if (lane == 0) mbar_arrive(fbar + (B_EMPTY - B_FULL + l % NSLOT) * 8 + tie);
                }
            };
            auto none = []() { return 0u; };
            const int fl = ph ? w : 0;
            auto fetch = [&](int i) {
                bar_sync(10, 256);
                const uint32_t src = ((i & 1) ? hbuf : xown) ^ 4096;
                const uint4 u0 = lds128(src), u1 = lds128(src + 2048);
                ho[8 * i] = u0.x; ho[8 * i + 1] = u0.y; ho[8 * i + 2] = u0.z; ho[8 * i + 3] = u0.w;
                ho[8 * i + 4] = u1.x; ho[8 * i + 5] = u1.y; ho[8 * i + 6] = u1.z; ho[8 * i + 7] = u1.w;
                return u0.x | u1.x;
            };
            auto act = [&](float (&d)[32], int i) {
                if (i > 0) fetch(i - 1);
                else if (ph) bar_sync(10, 256);
                pin(d);
#pragma unroll
                for (int j = 0; j < 8; j++) {
                    const float u0 = (d[4 * j] + d[4 * j + 2]) * rs, u1 = (d[4 * j + 1] + d[4 * j + 3]) * rs;
                    h[8 * i + j] = pack2(fmaf(u0, tanh_fast(u0), u0), fmaf(u1, tanh_fast(u1), u1));
                }
                sts128((i & 1) ? hbuf : xown, h[8 * i], h[8 * i + 1], h[8 * i + 2], h[8 * i + 3]);
                sts128(((i & 1) ? hbuf : xown) + 2048, h[8 * i + 4], h[8 * i + 5], h[8 * i + 6], h[8 * i + 7]);
                return 0u;
            };
            TS(1 + (ph & 2) * 10);
            if (ph) {
                step(d0, 0, a, fl, 0, none);
                step(d1, 1, a, fl, 0, [&]() { gather_peer(); return 0u; });
                TS(32);
                step(d0, 2, a + 16, 0, 1, none);
                step(d1, 3, a + 16, 0, 1, [&]() { return act(d0, 0); });
            } else {
                step(d0, 0, a, fl, 0, none);
                TS(32);
                step(d0, 1, a + 16, 0, 1, none);
                step(d1, 2, a, fl, 0, [&]() { return act(d0, 0); });
                step(d1, 3, a + 16, 0, 1, none);
            }
            step(d0, 4, a, fl, 0, [&]() { return act(d1, 1); });
            TS(33);
            step(d0, 5, a + 16, 0, 1, none);
            step(d1, 6, a, fl, 0, [&]() { return act(d0, 2); });
            step(d1, 7, a + 16, 0, 1, none);
            step(d0, 8, h, 0, 0, [&]() { act(d1, 3); return fetch(3); });
            TS(2 + (ph & 2) * 10);
            step(d0, 9, ho, 0, 1, none);
            step(d0, 10, h + 16, 0, 1, none);
            step(d0, 11, ho + 16, 0, 1, none);
            uint32_t pk[8];
            auto pack_out = [&]() {
                pin(d0);
#pragma unroll
                for (int j = 0; j < 8; j++) pk[j] = pack2(d0[4 * j] + d0[4 * j + 2], d0[4 * j + 1] + d0[4 * j + 3]);
            };
            auto send = [&](int i) { st_async4(hbuf + 8192 + i * 2048 + peer, pk[4 * i], pk[4 * i + 1], pk[4 * i + 2], pk[4 * i + 3], inb + peer); };
            step(d1, 12, h, 0, 0, [&]() { pack_out(); if (SND != 1) send(0); if (SND == 0) send(1); return 0u; });
            TS(34);
            step(d1, 13, ho, 0, 1, [&]() { if (SND == 1) send(0); if (SND) send(1); return 0u; });
            step(d1, 14, h + 16, 0, 1, none);
            step(d1, 15, ho + 16, 0, 1, none);
            mbar_wait(inb, 0);
#pragma unroll
            for (int i = 0; i < 2; i++) {
                const uint4 u = lds128(hbuf + 8192 + i * 2048);
                const uint32_t p0[4] = {u.x, u.y, u.z, u.w};
#pragma unroll
                for (int j = 0; j < 4; j++) {
                    v[8 * i + 2 * j] = fmaf(0.5f, blo(p0[j]), blo(xr[4 * i + j]));
                    v[8 * i + 2 * j + 1] = fmaf(0.5f, bhi(p0[j]), bhi(xr[4 * i + j]));
                }
            }
            wg_wait<0>();
            pin(d1);
            if (ph == 0) rel(15);
            TS(3 + (ph & 2) * 10);
#pragma unroll
            for (int j = 0; j < 8; j++) {
                v[2 * j] = fmaf(0.5f, d1[4 * j] + d1[4 * j + 2], v[2 * j]);
                v[2 * j + 1] = fmaf(0.5f, d1[4 * j + 1] + d1[4 * j + 3], v[2 * j + 1]);
            }
            return;
        }

        auto residual = [&](int n) {
            wg_wait<1>();
            rel(n);
            wg_wait<0>();
            pin(d0);
            rel(n + 1);
#pragma unroll
            for (int j = 0; j < 8; j++) {
                v[2 * j] = d0[4 * j] + d0[4 * j + 2] + blo(xr[j]);
                v[2 * j + 1] = d0[4 * j + 1] + d0[4 * j + 3] + bhi(xr[j]);
            }
        };

        if (ph == 2) {
            TS(39);
            sp(d0, 32, a, w, 0);
            acq(33);
            sp(d1, 33, a, w, 0);
            acq(34); acq(35);
            gather_peer();
            sp(d0, 34, a + 16, 0, 1);
            sp(d1, 35, a + 16, 0, 1);
            wg_wait<2>();
            if (!(LATE & 8)) rel(32);
            if (!(LATE & 1)) rel(33);
            acq(36);
            bar_sync(10, 256);
            const float rs = trow < T_ ? 0.5f * rstd : 0.f;
            wg_wait<0>();
            pin(d0); pin(d1);
            if (!(LATE & 2)) { rel(34); rel(35); }
            TS(18);
            uint32_t pk[8];
#pragma unroll
            for (int j = 0; j < 8; j++) {
                const float u0 = (d0[4 * j] + d0[4 * j + 2]) * rs, u1 = (d0[4 * j + 1] + d0[4 * j + 3]) * rs;
                const float t0 = tanh_fast((d1[4 * j] + d1[4 * j + 2]) * rs), t1 = tanh_fast((d1[4 * j + 1] + d1[4 * j + 3]) * rs);
                pk[j] = pack2(fmaf(u0, t0, u0), fmaf(u1, t1, u1));
            }
            if (wq == 0 || wq == 3) {
                uint4* hp = &g_halo[((pair * 4 + tile) * 2 + (wq & 1)) * 64 + lane];
                st_data(hp, pk[0], pk[1], pk[2], pk[3]);
                st_data(hp + 32, pk[4], pk[5], pk[6], pk[7]);
            }
            const uint32_t gs = P + w * GCH + wq * 1024;
            stsm4(gs + 1024 + foff, pk[0], pk[1], pk[2], pk[3]);
            stsm4(gs + 1024 + (foff ^ 64), pk[4], pk[5], pk[6], pk[7]);
            bar_sync(8 + w, 192);
            TS(26);
            uint32_t ca[8], cb[8];
            const int e = (wq & 1) * 4;
            const uint32_t lo = ((mir ^ e) * 144) ^ (lane * 4);
            const int dir = mir ? -1024 : 1024;
            const uint32_t gb = P + w * GCH + (mir ? 3072 : 2048) + lo, sown_ = H + tile * HCH, so = sown_ + (mir ? 1024 : 2048) + lo;
            auto finish = [&](int i) {
                const uint32_t c = hadd2(ca[i], cb[i]);
                const float h0 = blo(c), h1 = bhi(c);
                const uint32_t dst = (so + (i >> 2) * dir) ^ ((i & 3) * 144), val = pack2(fmaf(h0, tanh_fast(h0), h0), fmaf(h1, tanh_fast(h1), h1));
                asm volatile("st.async.shared::cluster.mbarrier::complete_tx::bytes.b32 [%0], %1, [%2];" ::"r"(dst + peer), "r"(val), "r"(bars + B_SR * 8 + peer) : "memory");
                sts32(dst, val);
            };
#pragma unroll
            for (int k = 0; k < 26; k++) {
                if (k == 19) {
#pragma unroll
                    for (int i = 0; i < 4; i++) finish(i);
                    mbar_wait(bars + (B_HALO + 2 * w + (wq >> 1)) * 8, 0);
                    if (LATE & 8) rel(32);
                    if (LATE & 1) rel(33);
                    if (LATE & 2) { rel(34); rel(35); }
                    TS(27);
                }
                const uint32_t g = lds32((gb + (((k + 1) & 4) ? ((k + 1) >> 3) + (wq & 1) : ((k + 1) >> 3)) * dir) ^ (((k + 1) & 7) * 144));
#pragma unroll
                for (int i = 0; i < 8; i++) {
                    const int tap = k - (i & 3) - 2 * (i & 4);
                    if (tap == 0) ca[i] = hmul2(g, dwr[0]);
                    else if (tap > 0 && tap < 8) ca[i] = hfma2(g, dwr[tap], ca[i]);
                    else if (tap == 8) cb[i] = hmul2(g, dwr[8]);
                    else if (tap > 8 && tap < 15) cb[i] = hfma2(g, dwr[tap], cb[i]);
                }
            }
#pragma unroll
            for (int i = 4; i < 8; i++) finish(i);
            bar_sync(10, 256);
            TS(19);
            auto frags = [&](int i, int half) {
                const uint32_t src = H + 2 * half * HCH + wq * 1024;
#pragma unroll
                for (int k = 0; k < 4; k++) ldsm4(src + (k >> 1) * HCH + (foff ^ ((k & 1) * 64)), a[i + 4 * k], a[i + 4 * k + 1], a[i + 4 * k + 2], a[i + 4 * k + 3]);
            };
            frags(0, r);
            sp(d0, 36, a, 0, 0);
            acq(37);
            mbar_wait(bars + B_SR * 8, 0);
            frags(16, r ^ 1);
            sp(d0, 37, a + 16, 0, 1);
            residual(36);
            TS(20);
            return;
        }

        {
            TS(11);
            unsigned char* g = g_kvq + (size_t)((b * 4 + tile) * 1024 + trow) * 128;
            const uint32_t uo = (lane >> 2) * 128 + ((c4 ^ (lane >> 2)) << 4);
            auto put = [&](float (&d)[32], int i) {
                pin(d);
                uint32_t pk[8];
#pragma unroll
                for (int j = 0; j < 8; j++) pk[j] = pack2((d[4 * j] + d[4 * j + 2]) * rstd, (d[4 * j + 1] + d[4 * j + 3]) * rstd);
                if (i < 2) {
                    stg128(g + i * 1048576 + uo, make_uint4(pk[0], pk[1], pk[2], pk[3]));
                    stg128(g + i * 1048576 + (uo ^ 64), make_uint4(pk[4], pk[5], pk[6], pk[7]));
                } else {
                    const uint32_t stg = H + warp * 1024;
                    sts128(stg + uo, pk[0], pk[1], pk[2], pk[3]);
                    sts128(stg + (uo ^ 64), pk[4], pk[5], pk[6], pk[7]);
                    __syncwarp();
                    ldsm4(stg + foff, pk[0], pk[1], pk[2], pk[3]);
                    ldsm4(stg + (foff ^ 64), pk[4], pk[5], pk[6], pk[7]);
                    st_data(g + 2097152 + lane * 16, ~pk[0], ~pk[1], ~pk[2], ~pk[3]);
                    st_data(g + 2097152 + 512 + lane * 16, ~pk[4], ~pk[5], ~pk[6], ~pk[7]);
                }
            };
            sp(d0, 16, a, w, 0);
            acq(17);
            sp(d1, 17, a, w, 0);
            gather_peer();
            acq(18);
            sp(d0, 18, a + 16, 0, 1);
            wg_wait<1>();
            rel(16); rel(17);
            acq(19);
            sp(d1, 19, a + 16, 0, 1);
            wg_wait<1>();
            rel(18);
            put(d0, 0);
            wg_wait<0>();
            rel(19);
            TS(37);
            put(d1, 1);
            bar_arrive(4, 288);
            TS(38);
            acq(20);
            sp(d0, 20, a, w, 0);
            acq(21);
            sp(d0, 21, a + 16, 0, 1);
            wg_wait<0>();
            rel(20); rel(21);
            put(d0, 2);
            TS(12);
        }

        {
            constexpr float CS = 0.125f * 1.4426950408889634f;
            float sa[32], sb2[32], o[36];
            uint32_t pa[16], pb[16], q[16];
            float n0 = INFINITY, n1 = INFINITY;
            zero(o); zero(pa); zero(pb); zero(sb2);
            const uint32_t ones = H + 8192;
            { const uint32_t c = w ? 0u : 0x3F803F80u; sts128(ones + tid * 16, c, c, c, c); }
            fence_async_smem();
            bar_sync(10, 256);
            const uint32_t vdesc = rdesc + ((((ones - rbase) >> 4) - 1) << 16);
            auto qk_issue = [&](float (&s)[32], uint32_t lo) {
                const uint64_t kd = mkdesc(lo);
                wg_fence();
#pragma unroll
                for (int k = 0; k < 4; k++) mma_qk(s, q[4 * k], q[4 * k + 1], q[4 * k + 2], q[4 * k + 3], kd + 2 * k, k != 0);
                wg_commit();
            };
            auto both_issue = [&](float (&s)[32], uint32_t klo, uint32_t (&pp)[16], uint32_t vlo) {
                const uint64_t kd = mkdesc(klo), vd = mkdesc(vlo);
                wg_fence();
#pragma unroll
                for (int k = 0; k < 4; k++) {
                    mma_pv(o, pp[4 * k], pp[4 * k + 1], pp[4 * k + 2], pp[4 * k + 3], vd - k * (128 * 65535));
                    mma_qk(s, q[4 * k], q[4 * k + 1], q[4 * k + 2], q[4 * k + 3], kd + 2 * k, k != 0);
                }
                wg_commit();
            };
            auto new_max = [&](float (&s)[32], int nj, float& x0, float& x1) {
                x0 = s[0]; x1 = s[2];
#pragma unroll
                for (int j = 0; j < nj; j++) {
                    x0 = fmaxf(x0, fmaxf(s[4 * j], s[4 * j + 1]));
                    x1 = fmaxf(x1, fmaxf(s[4 * j + 2], s[4 * j + 3]));
                }
                x0 = fmaxf(x0, __shfl_xor_sync(~0u, x0, 1)); x1 = fmaxf(x1, __shfl_xor_sync(~0u, x1, 1));
                x0 = fmaxf(x0, __shfl_xor_sync(~0u, x0, 2)); x1 = fmaxf(x1, __shfl_xor_sync(~0u, x1, 2));
                x0 = fminf(n0, fmaf(x0, -CS, -20.f)); x1 = fminf(n1, fmaf(x1, -CS, -20.f));
            };
            auto probs = [&](float (&s)[32], uint32_t (&pp)[16], bool ready, bool tail, auto wait) {
                uint32_t any = 0;
#pragma unroll
                for (int i = 0; i < 16; i++) {
                    pp[i] = pack2(ex2(fmaf(s[2 * i], CS, (i & 1) ? n1 : n0)), ex2(fmaf(s[2 * i + 1], CS, (i & 1) ? n1 : n0)));
                    any |= pp[i];
                }
                wg_wait<0>();
                pin(sa); pin(sb2); pin(o); pin(pa); pin(pb);
                if (__builtin_expect(__any_sync(~0u, (any & 0x40004000u) || !ready), 0)) {
                    wait();
                    if (__any_sync(~0u, any & 0x40004000u)) {
                        if (tail) {
#pragma unroll
                            for (int i = 20; i < 32; i++) s[i] = -INFINITY;
                        }
                        float x0, x1;
                        new_max(s, 8, x0, x1);
                        const float sc0 = ex2(x0 - n0), sc1 = ex2(x1 - n1);
                        n0 = x0; n1 = x1;
#pragma unroll
                        for (int j = 0; j < 9; j++) { o[4 * j] *= sc0; o[4 * j + 1] *= sc0; o[4 * j + 2] *= sc1; o[4 * j + 3] *= sc1; }
#pragma unroll
                        for (int i = 0; i < 16; i++)
                            pp[i] = pack2(ex2(fmaf(s[2 * i], CS, (i & 1) ? n1 : n0)), ex2(fmaf(s[2 * i + 1], CS, (i & 1) ? n1 : n0)));
                    }
                }
            };
            {
                uint4 u[4];
                const unsigned char* src = g_kvq + 2097152 + (size_t)(abh * 1024 + qt * 64 + wq * 16) * 128 + lane * 16;
                spin(QGATE);
                ld_data<512, true>(u, src);
#pragma unroll
                for (int k = 0; k < 2; k++) {
                    q[8 * k] = ~u[k].x; q[8 * k + 1] = ~u[k + 2].x; q[8 * k + 2] = ~u[k].y; q[8 * k + 3] = ~u[k + 2].y;
                    q[8 * k + 4] = ~u[k].z; q[8 * k + 5] = ~u[k + 2].z; q[8 * k + 6] = ~u[k].w; q[8 * k + 7] = ~u[k + 2].w;
                }
                pin(q);
            }
            TS(40);
            acq(22);
            TS(13);
            qk_issue(sa, rdesc + (22 % NSLOT) * (SLOT >> 4));
            wg_wait<0>();
            pin(sa);
            {
                float x0, x1;
                new_max(sa, NJ0, x0, x1);
                n0 = x0; n1 = x1;
            }
            bar_arrive(6, 384);
            uint32_t vd = vdesc, kd = rdesc + 5 * (SLOT >> 4), vb = fbar, kb = fbar + 40;
            uint32_t vlast = vdesc - 4 * (SLOT >> 4) * 65535u, klast = rdesc + 4 * (SLOT >> 4) + 512;
            uint32_t kprev = fbar + 32, vprev = bars + (B_SINK - (B_EMPTY - B_FULL)) * 8;
#pragma unroll 1
            for (int it = 0; it < 4; it++) {
                both_issue(sb2, klast, pb, vlast);
                probs(sa, pa, mbar_test(vb, 0) & mbar_test(kb, it == 0), false, [&]() { mbar_wait(vb, 0); mbar_wait(kb, it == 0); });
                TS(41 + it * 4);
                if (lane == 0) mbar_arrive(kprev + (B_EMPTY - B_FULL) * 8);
                if (lane == 0) mbar_arrive(vprev + (B_EMPTY - B_FULL) * 8);
                both_issue(sa, kd, pa, vd);
                const int dv = it == 2 ? 1 : 2, dk = it == 0 ? -4 : 2;
                kprev = kb; vprev = vb; vlast = vd - 512 * 65535u; klast = kd + 512;
                vd -= dv * (SLOT >> 4) * 65535u; vb += dv * 8;
                kd += dk * (SLOT >> 4); kb += dk * 8;
                probs(sb2, pb, true, it == 3 && w == 1, []() {});
                TS(43 + it * 4);
            }
            wg_fence();
#pragma unroll
            for (int k = 0; k < 4; k++)
                mma_pv(o, pb[4 * k], pb[4 * k + 1], pb[4 * k + 2], pb[4 * k + 3], mkdesc(vlast - k * (128 * 65535) + (k > 1 ? w * ((k - 1) << 22) : 0)));
            wg_commit();
            const uint32_t mlw = sb + OFF_MISC + 1024 + (tid >> 2) * 8;
            unsigned char* odst = g_o + (size_t)(b * 128 + qt * 8 + 2 * wq + w) * 4096 + ah * 1024 + lane * 16;
            mbar_wait(bars + B_RST * 8, (mlw | (uint32_t)(size_t)odst) & p.zero);
            wg_wait<0>();
            pin(o); pin(pb); pin(sa); pin(sb2);
            rel(29);
            TS(14);
            auto merge = [&](int keep, float nk, float ns) {
                const int snd = 2 - keep;
                if (c4 == 0) sts64f(mlw, ns, o[32 + snd]);
#pragma unroll
                for (int j = 0; j < 2; j++)
                    sts128(hbuf + j * 2048, pack2(o[16 * j + snd], o[16 * j + snd + 1]), pack2(o[16 * j + 4 + snd], o[16 * j + 5 + snd]),
                           pack2(o[16 * j + 8 + snd], o[16 * j + 9 + snd]), pack2(o[16 * j + 12 + snd], o[16 * j + 13 + snd]));
                bar_sync(10, 256);
                const float2 u = lds64f(mlw ^ 256);
                const float x = fminf(nk, u.x);
                float a = ex2(x - nk), c = ex2(x - u.x);
                const float inv = rcp(fmaf(a, o[32 + keep], c * u.y));
                a *= inv; c *= inv;
                uint32_t pk[8];
#pragma unroll
                for (int j = 0; j < 2; j++) {
                    const uint4 t4 = lds128((hbuf ^ 4096) + j * 2048);
                    const uint32_t t[4] = {t4.x, t4.y, t4.z, t4.w};
#pragma unroll
                    for (int i = 0; i < 4; i++)
                        pk[4 * j + i] = pack2(fmaf(a, o[16 * j + 4 * i + keep], c * blo(t[i])), fmaf(a, o[16 * j + 4 * i + keep + 1], c * bhi(t[i])));
                }
                st_data(odst, pk[0], pk[1], pk[2], pk[3]);
                st_data(odst + 512, pk[4], pk[5], pk[6], pk[7]);
            };
            if (tid < 128) merge(0, n0, n1); else merge(2, n1, n0);
            if (tid == 0) asm volatile("red.relaxed.gpu.global.add.u32 [%0], 1;" ::"l"(&g_epoch[blockIdx.x * FS]) : "memory");
            TS(15);
        }

        {
            const uint32_t* dp = reinterpret_cast<const uint32_t*>(p.dw + (mir ? 14 * 256 : 0) + tile * 64) + lane;
#pragma unroll
            for (int i = 0; i < 15; i++) asm volatile("ld.global.nc.b32 %0, [%1];" : "=r"(dwr[i]) : "l"(dp + i * (mir ? -128 : 128)));
            acq(30); acq(31); acq(32);
            uint4 u[8];
            ld_data<512>(u, g_o + (size_t)(b * 128 + pt * 4 + wq) * 4096 + lane * 16);
#pragma unroll
            for (int i = 0; i < 8; i++) { a[4 * i] = u[i].x; a[4 * i + 1] = u[i].y; a[4 * i + 2] = u[i].z; a[4 * i + 3] = u[i].w; }
            TS(16);
            sp(d0, 30, a, 0, 0);
            sp(d0, 31, a + 16, 0, 1);
#pragma unroll
            for (int i = 0; i < 15; i++) dwr[i] = hmul2(dwr[i], 0x3F003F00u);
            residual(30);
            TS(17);
        }
    };
    phase(std::integral_constant<int, 0>{});
    phase(std::integral_constant<int, 1>{});
    phase(std::integral_constant<int, 2>{});
    phase(std::integral_constant<int, 3>{});
    phase(std::integral_constant<int, 4>{});

    cluster_arrive();
    TS(24);
    {
        const float rstd = rsq(fmaxf(fmaf(-mean, mean, msq), 0.f) + 1e-5f), nb = -mean * rstd;
#pragma unroll
        for (int j = 0; j < 8; j++) xr[j] = pack2(fmaf(v[2 * j], rstd, nb), fmaf(v[2 * j + 1], rstd, nb));
        const uint32_t stg = H + warp * 1024;
        stsm4(stg + foff, xr[0], xr[1], xr[2], xr[3]);
        stsm4(stg + (foff ^ 64), xr[4], xr[5], xr[6], xr[7]);
        __syncwarp();
        const uint32_t src = stg + (lane >> 3) * 128 + (((lane & 7) ^ (lane >> 3)) << 4);
        const uint4 u0 = lds128(src), u1 = lds128((src + 512) ^ 64);
        __nv_bfloat16* dst = p.out + (size_t)(b * T_ + trow + (lane >> 3)) * 256 + tile * 64 + (lane & 7) * 8;
        if (trow < T_) { stg128(dst, u0); stg128(dst + 4 * 256, u1); }
    }
    TS(25);
    TG(31);
    TSDUMP();
    cluster_wait();
}

typedef CUresult (*EncodeFn)(CUtensorMap*, CUtensorMapDataType, cuuint32_t, void*, const cuuint64_t*, const cuuint64_t*,
                             const cuuint32_t*, const cuuint32_t*, CUtensorMapInterleave, CUtensorMapSwizzle,
                             CUtensorMapL2promotion, CUtensorMapFloatOOBfill);

}

extern "C" void kernel_launch(void* const* d_in, const int* in_sizes, int n_in, void* d_out, int out_size) {
    static EncodeFn encode = nullptr;
    if (!encode) {
        void* fn = nullptr;
        cudaDriverEntryPointQueryResult qr;
        cudaGetDriverEntryPoint("cuTensorMapEncodeTiled", &fn, cudaEnableDefault, &qr);
        encode = (EncodeFn)fn;
        cudaFuncSetAttribute(conformer_kernel, cudaFuncAttributeMaxDynamicSharedMemorySize, SMEM_LAUNCH);
    }
    Scalars p;
    Maps m;
    const cuuint32_t ones[5] = {1, 1, 1, 1, 1};
    const int idx[8] = {1, 2, 3, 4, 5, 7, 8, 9};
    const int rows[8] = {256, 1024, 256, 256, 256, 256, 256, 1024};
    const int cols[8] = {1024, 256, 768, 256, 512, 256, 1024, 256};
    for (int i = 0; i < 8; i++) {
        const cuuint64_t pitch = (cuuint64_t)cols[i] * 2;
        const bool f = i != 0 && i != 3;
        const cuuint64_t dims[5] = {(cuuint64_t)cols[i], f ? 2u : 4u, f ? 2u : 4u, f ? 4u : 2u, (cuuint64_t)rows[i] / (f ? 16 : 32)};
        const cuuint64_t strides[4] = {pitch, pitch * 8, pitch * (f ? 2 : 4), pitch * (f ? 16 : 32)};
        const cuuint32_t box[5] = {64, f ? 2u : 4u, f ? 2u : 4u, f ? 4u : 2u, f ? 8u : 4u};
        encode(&m.tm[i], CU_TENSOR_MAP_DATA_TYPE_BFLOAT16, 5, d_in[idx[i]], dims, strides, box, ones, CU_TENSOR_MAP_INTERLEAVE_NONE,
               CU_TENSOR_MAP_SWIZZLE_128B, CU_TENSOR_MAP_L2_PROMOTION_L2_128B, CU_TENSOR_MAP_FLOAT_OOB_FILL_NONE);
        m.w[i] = (const char*)d_in[idx[i]];
    }
    {
        void* kv = nullptr;
        cudaGetSymbolAddress(&kv, g_kvq);
        const cuuint64_t dims[2] = {64, 16384};
        const cuuint64_t strides[1] = {128};
        const cuuint32_t box[2] = {64, 128};
        encode(&m.tm[8], CU_TENSOR_MAP_DATA_TYPE_BFLOAT16, 2, kv, dims, strides, box, ones, CU_TENSOR_MAP_INTERLEAVE_NONE,
               CU_TENSOR_MAP_SWIZZLE_NONE, CU_TENSOR_MAP_L2_PROMOTION_L2_128B, CU_TENSOR_MAP_FLOAT_OOB_FILL_NONE);
    }
    p.x = (const __nv_bfloat16*)d_in[0];
    p.dw = (const __nv_bfloat16*)d_in[6];
    p.out = (__nv_bfloat16*)d_out;
    p.zero = 0;
    conformer_kernel<<<NCTA, NTHREADS, SMEM_LAUNCH>>>(p, m);
}
```

```cpp
#include <cuda_runtime.h>
#include <cuda_bf16.h>
#include <cuda.h>
#include <stdint.h>
#include <type_traits>

namespace {

constexpr int T_ = 1000;
constexpr int NCTA = 128;
constexpr int NTHREADS = 512;
constexpr int NSLOT = 6;
constexpr int SLOT = 16384;
constexpr int NLOADS = 54;

constexpr uint32_t OFF_RING = 0;
constexpr uint32_t OFF_P = 196608;
constexpr uint32_t OFF_H = 212992;
constexpr uint32_t OFF_MISC = 229376;
constexpr uint32_t OFF_BARS = 230912;
constexpr uint32_t SMEM_BYTES = 231424;
constexpr uint32_t GCH = 6144;
constexpr uint32_t HCH = 4096;

constexpr int B_FULL = 0, B_EMPTY = 12, B_XA = 24  , B_XB = 29  , B_INB = 33  , B_SR = 37,
              B_RST = 38, B_RDY = 39  , B_SINK = 43, B_HALO = 44  , NBARS = 48;

constexpr uint32_t KDELAY = 250, KD2 = 300, KD3 = 500, QGATE = 700, HDELAY = 200;
constexpr int FS = 8;

struct Scalars {
    const __nv_bfloat16* x;
    const __nv_bfloat16* dw;
    __nv_bfloat16* out;
    uint32_t zero;
};
struct Maps {
    CUtensorMap tm[9];
    const char* w[8];
};

__device__ __align__(1024) unsigned char g_kvq[3 * 8 * 1024 * 128];
__device__ __align__(1024) unsigned char g_o[2 * 128 * 4096];
__device__ uint4 g_halo[64 * 4 * 2 * 64];
__device__ __align__(128) uint32_t g_flag_kv[8 * 32 * FS];
__device__ uint32_t g_reset[2 * 32];
__device__ uint32_t g_epoch[NCTA * FS];

#define TS(i) do { } while (0)
#define TSW(i) do { } while (0)
#define TG(i) do { } while (0)
#define TSINIT() do { } while (0)
#define TSDUMP() do { } while (0)
constexpr uint32_t SMEM_LAUNCH = SMEM_BYTES;

__device__ __forceinline__ uint32_t smem_u32(const void* p) { return (uint32_t)__cvta_generic_to_shared(p); }
__device__ __forceinline__ void mbar_init(uint32_t b, uint32_t c) { asm volatile("mbarrier.init.shared::cta.b64 [%0], %1;" ::"r"(b), "r"(c) : "memory"); }
__device__ __forceinline__ void mbar_arrive(uint32_t b) { asm volatile("mbarrier.arrive.shared::cta.b64 _, [%0];" ::"r"(b) : "memory"); }
__device__ __forceinline__ void mbar_arrive_tx(uint32_t b, uint32_t tx) { asm volatile("mbarrier.arrive.expect_tx.shared::cta.b64 _, [%0], %1;" ::"r"(b), "r"(tx) : "memory"); }
__device__ __forceinline__ void mbar_wait(uint32_t b, uint32_t ph) {
    asm volatile("{\n.reg .pred p, q;\n.reg .u32 c;\nmov.u32 c, 0;\n"
                 "MW_LOOP:\n.pragma \"nounroll\";\n"
                 "mbarrier.try_wait.parity.shared::cta.b64 p, [%0], %1;\n"
                 "add.u32 c, c, 1;\nsetp.lt.u32 q, c, 65536;\nnot.pred p, p;\nand.pred p, p, q;\n@p bra MW_LOOP;\n}"
                 ::"r"(b), "r"(ph) : "memory");
}
__device__ __forceinline__ bool mbar_test(uint32_t b, uint32_t ph) {
    uint32_t ok;
    asm volatile("{\n.reg .pred p;\nmbarrier.test_wait.parity.shared::cta.b64 p, [%1], %2;\nselp.u32 %0, 1, 0, p;\n}" : "=r"(ok) : "r"(b), "r"(ph) : "memory");
    return ok;
}
__device__ __forceinline__ uint32_t mapa(uint32_t a, uint32_t r) { uint32_t o; asm("mapa.shared::cluster.u32 %0, %1, %2;" : "=r"(o) : "r"(a), "r"(r)); return o; }
__device__ __forceinline__ void fence_async_smem() { asm volatile("fence.proxy.async.shared::cta;" ::: "memory"); }
__device__ __forceinline__ void fence_async_global() { asm volatile("fence.proxy.async.global;" ::: "memory"); }
__device__ __forceinline__ void bar_sync(int id, int n) { asm volatile("bar.sync %0, %1;" ::"r"(id), "r"(n) : "memory"); }
__device__ __forceinline__ void bar_arrive(int id, int n) { asm volatile("bar.arrive %0, %1;" ::"r"(id), "r"(n) : "memory"); }
__device__ __forceinline__ void cluster_arrive() { asm volatile("barrier.cluster.arrive.relaxed.aligned;" ::: "memory"); }
__device__ __forceinline__ void cluster_wait() { asm volatile("barrier.cluster.wait.aligned;" ::: "memory"); }

__device__ __forceinline__ void ring_load(uint32_t dst, const CUtensorMap* tm, int col, int row16, uint32_t bar) {
    asm volatile("{\n.reg .pred p;\nelect.sync _|p, 0xffffffff;\n"
                 "@p mbarrier.arrive.expect_tx.shared::cta.b64 _, [%2], 16384;\n"
                 "@p cp.async.bulk.tensor.5d.shared::cluster.global.mbarrier::complete_tx::bytes [%0], [%1, {%3, 0, 0, 0, %4}], [%2];\n}"
                 ::"r"(dst), "l"(tm), "r"(bar), "r"(col), "r"(row16) : "memory");
}
__device__ __forceinline__ void ring_load_both(uint32_t dst, const CUtensorMap* tm, int c1, uint32_t bar) {
    asm volatile("{\n.reg .pred p;\nelect.sync _|p, 0xffffffff;\n"
                 "@p cp.async.bulk.tensor.2d.shared::cluster.global.mbarrier::complete_tx::bytes.multicast::cluster [%0], [%1, {0, %3}], [%2], %4;\n}"
                 ::"r"(dst), "l"(tm), "r"(bar), "r"(c1), "h"((uint16_t)3) : "memory");
}
__device__ __forceinline__ void mbar_arrive_peer(uint32_t b) { asm volatile("mbarrier.arrive.relaxed.cluster.shared::cluster.b64 _, [%0];" ::"r"(b) : "memory"); }
__device__ __forceinline__ void prefetch_l2(const void* src, uint32_t bytes) {
    asm volatile("cp.async.bulk.prefetch.L2.global [%0], %1;" ::"l"(src), "r"(bytes) : "memory");
}
__device__ __forceinline__ void st_async4(uint32_t dst, uint32_t a, uint32_t b, uint32_t c, uint32_t d, uint32_t bar) {
    asm volatile("st.async.shared::cluster.mbarrier::complete_tx::bytes.v4.b32 [%0], {%1,%2,%3,%4}, [%5];" ::"r"(dst), "r"(a), "r"(b), "r"(c), "r"(d), "r"(bar) : "memory");
}
__device__ __forceinline__ void put_sums(uint32_t dst, uint32_t rdst, float a, float b, uint32_t rbar, bool on) {
    asm volatile("{\n.reg .pred p;\nsetp.ne.u32 p, %5, 0;\n"
                 "@p st.async.shared::cluster.mbarrier::complete_tx::bytes.v2.f32 [%1], {%2,%3}, [%4];\n"
                 "@p st.shared.v2.f32 [%0], {%2,%3};\n}" ::"r"(dst), "r"(rdst), "f"(a), "f"(b), "r"(rbar), "r"((uint32_t)on) : "memory");
}
__device__ __forceinline__ void stsm4(uint32_t a, uint32_t r0, uint32_t r1, uint32_t r2, uint32_t r3) {
    asm volatile("stmatrix.sync.aligned.m8n8.x4.shared.b16 [%0], {%1,%2,%3,%4};" ::"r"(a), "r"(r0), "r"(r1), "r"(r2), "r"(r3) : "memory");
}
__device__ __forceinline__ void ldsm4(uint32_t a, uint32_t& r0, uint32_t& r1, uint32_t& r2, uint32_t& r3) {
    asm volatile("ldmatrix.sync.aligned.m8n8.x4.shared.b16 {%0,%1,%2,%3}, [%4];" : "=r"(r0), "=r"(r1), "=r"(r2), "=r"(r3) : "r"(a) : "memory");
}
__device__ __forceinline__ uint4 lds128(uint32_t a) { uint4 v; asm volatile("ld.shared.v4.b32 {%0,%1,%2,%3}, [%4];" : "=r"(v.x), "=r"(v.y), "=r"(v.z), "=r"(v.w) : "r"(a) : "memory"); return v; }
__device__ __forceinline__ float4 lds128f(uint32_t a) { float4 v; asm volatile("ld.shared.v4.f32 {%0,%1,%2,%3}, [%4];" : "=f"(v.x), "=f"(v.y), "=f"(v.z), "=f"(v.w) : "r"(a) : "memory"); return v; }
__device__ __forceinline__ float2 lds64f(uint32_t a) { float2 v; asm volatile("ld.shared.v2.f32 {%0,%1}, [%2];" : "=f"(v.x), "=f"(v.y) : "r"(a) : "memory"); return v; }
__device__ __forceinline__ uint32_t lds32(uint32_t a) { uint32_t v; asm volatile("ld.shared.b32 %0, [%1];" : "=r"(v) : "r"(a) : "memory"); return v; }
__device__ __forceinline__ void sts128(uint32_t a, uint32_t x, uint32_t y, uint32_t z, uint32_t w) { asm volatile("st.shared.v4.b32 [%0], {%1,%2,%3,%4};" ::"r"(a), "r"(x), "r"(y), "r"(z), "r"(w) : "memory"); }
__device__ __forceinline__ void sts128f(uint32_t a, float x, float y, float z, float w) { asm volatile("st.shared.v4.f32 [%0], {%1,%2,%3,%4};" ::"r"(a), "f"(x), "f"(y), "f"(z), "f"(w) : "memory"); }
__device__ __forceinline__ void sts64f(uint32_t a, float x, float y) { asm volatile("st.shared.v2.f32 [%0], {%1,%2};" ::"r"(a), "f"(x), "f"(y) : "memory"); }
__device__ __forceinline__ void sts32(uint32_t a, uint32_t x) { asm volatile("st.shared.b32 [%0], %1;" ::"r"(a), "r"(x) : "memory"); }
__device__ __forceinline__ void stg128(void* p, uint4 v) { asm volatile("st.global.v4.b32 [%0], {%1,%2,%3,%4};" ::"l"(p), "r"(v.x), "r"(v.y), "r"(v.z), "r"(v.w) : "memory"); }

__device__ __forceinline__ uint32_t pack2(float lo, float hi) { uint32_t r; asm("cvt.rn.bf16x2.f32 %0, %1, %2;" : "=r"(r) : "f"(hi), "f"(lo)); return r; }
__device__ __forceinline__ float blo(uint32_t v) { return __uint_as_float(v << 16); }
__device__ __forceinline__ float bhi(uint32_t v) { return __uint_as_float(v & 0xffff0000u); }
__device__ __forceinline__ uint32_t hmul2(uint32_t a, uint32_t b) { uint32_t r; asm("mul.rn.bf16x2 %0, %1, %2;" : "=r"(r) : "r"(a), "r"(b)); return r; }
__device__ __forceinline__ uint32_t hadd2(uint32_t a, uint32_t b) { uint32_t r; asm("add.rn.bf16x2 %0, %1, %2;" : "=r"(r) : "r"(a), "r"(b)); return r; }
__device__ __forceinline__ uint32_t hsub2(uint32_t a, uint32_t b) { uint32_t r; asm("sub.rn.bf16x2 %0, %1, %2;" : "=r"(r) : "r"(a), "r"(b)); return r; }
__device__ __forceinline__ uint32_t hfma2(uint32_t a, uint32_t b, uint32_t c) { uint32_t r; asm("fma.rn.bf16x2 %0, %1, %2, %3;" : "=r"(r) : "r"(a), "r"(b), "r"(c)); return r; }
__device__ __forceinline__ float tanh_fast(float x) { float r; asm("tanh.approx.f32 %0, %1;" : "=f"(r) : "f"(x)); return r; }
__device__ __forceinline__ float rsq(float x) { float r; asm("rsqrt.approx.ftz.f32 %0, %1;" : "=f"(r) : "f"(x)); return r; }
__device__ __forceinline__ float rcp(float x) { float r; asm("rcp.approx.ftz.f32 %0, %1;" : "=f"(r) : "f"(x)); return r; }
__device__ __forceinline__ float ex2(float x) { float r; asm("ex2.approx.ftz.f32 %0, %1;" : "=f"(r) : "f"(x)); return r; }

__device__ __forceinline__ uint32_t ld_relaxed(const uint32_t* p) {
    uint32_t v;
    asm volatile("ld.relaxed.gpu.global.u32 %0, [%1];" : "=r"(v) : "l"(p) : "memory");
    return v;
}
__device__ __forceinline__ uint32_t clock32() { uint32_t c; asm volatile("mov.u32 %0, %%clock;" : "=r"(c)::"memory"); return c; }
__device__ __forceinline__ void spin(uint32_t clks) {
    const uint32_t t0 = clock32();
    while (clock32() - t0 < clks) {}
}
__device__ __forceinline__ void flag_wait(const uint32_t* p, uint32_t e, bool mine) {
#pragma unroll 1
    for (int i = 0; i < (1 << 19); i++) {
        if (mine) mine = ld_relaxed(p) != e;
        if (!__any_sync(~0u, mine)) break;
    }
    asm volatile("fence.acquire.gpu;" ::: "memory");
    fence_async_global();
}
__device__ __forceinline__ void st_data(void* p, uint32_t x, uint32_t y, uint32_t z, uint32_t w) {
    asm volatile("st.relaxed.gpu.global.v4.b32 [%0], {%1,%2,%3,%4};" ::"l"(p), "r"(x), "r"(y), "r"(z), "r"(w) : "memory");
}
template <int STRIDE, bool INV = false, int N>
__device__ __forceinline__ void ld_data(uint4 (&v)[N], const unsigned char* p) {
    int it = 0;
    bool again;
#pragma unroll 1
    do {
        uint32_t m = INV ? ~0u : 0u;
#pragma unroll
        for (int i = 0; i < N; i++)
            asm volatile("ld.relaxed.gpu.global.v4.b32 {%0,%1,%2,%3}, [%4];" : "=r"(v[i].x), "=r"(v[i].y), "=r"(v[i].z), "=r"(v[i].w) : "l"(p + i * STRIDE) : "memory");
#pragma unroll
        for (int i = 0; i < N; i++)
            m = INV ? __vimin3_u32(__vimin3_u32(v[i].x, v[i].y, v[i].z), v[i].w, m) : __vimax3_u32(__vimax3_u32(v[i].x, v[i].y, v[i].z), v[i].w, m);
        again = __any_sync(~0u, m == (INV ? 0u : ~0u)) && ++it < (1 << 16);
    } while (again);
}
__device__ __forceinline__ uint32_t ld_epoch() { return ld_relaxed(&g_epoch[blockIdx.x * FS]) + 1; }
__device__ __forceinline__ void flag_set(uint32_t* p, uint32_t e) { asm volatile("st.release.gpu.global.u32 [%0], %1;" ::"l"(p), "r"(e) : "memory"); }

__device__ __forceinline__ uint32_t desc_lo(uint32_t addr) { return ((addr & 0x3FFFF) >> 4) | 0x10000u; }
__device__ __forceinline__ uint64_t mkdesc(uint32_t lo) { return (uint64_t)lo | (0x40000040ull << 32); }
__device__ __forceinline__ void wg_fence() { asm volatile("wgmma.fence.sync.aligned;" ::: "memory"); }
__device__ __forceinline__ void wg_commit() { asm volatile("wgmma.commit_group.sync.aligned;" ::: "memory"); }
template <int N> __device__ __forceinline__ void wg_wait() { asm volatile("wgmma.wait_group.sync.aligned %0;" ::"n"(N) : "memory"); }
template <int N> __device__ __forceinline__ void pin(float (&d)[N]) {
#pragma unroll
    for (int i = 0; i < N; i++) asm volatile("" : "+f"(d[i])::"memory");
}
template <int N> __device__ __forceinline__ void pin(uint32_t (&d)[N]) {
#pragma unroll
    for (int i = 0; i < N; i++) asm volatile("" : "+r"(d[i])::"memory");
}

template <typename Tp, int N> __device__ __forceinline__ void zero(Tp (&d)[N]) {
#pragma unroll
    for (int i = 0; i < N; i++) d[i] = 0;
    pin(d);
}

#define F4(d, i) "+f"(d[i]), "+f"(d[i + 1]), "+f"(d[i + 2]), "+f"(d[i + 3])
#define F16(d, i) F4(d, i), F4(d, i + 4), F4(d, i + 8), F4(d, i + 12)

__device__ __forceinline__ void mma16(float (&d)[4], const uint32_t* a, uint32_t b0, uint32_t b1) {
    asm("mma.sync.aligned.m16n8k16.row.col.f32.bf16.bf16.f32 {%0,%1,%2,%3}, {%4,%5,%6,%7}, {%8,%9}, {%0,%1,%2,%3};"
        : F4(d, 0) : "r"(a[0]), "r"(a[1]), "r"(a[2]), "r"(a[3]), "r"(b0), "r"(b1));
}
template <int N>
__device__ __forceinline__ float row_sum(const uint32_t* x, uint32_t ones = 0x3F803F80u) {
    float c[4] = {};
#pragma unroll
    for (int i = 0; i < N; i += 4) mma16(c, x + i, ones, ones);
    return c[0] + c[2];
}
template <int N>
__device__ __forceinline__ float row_sumsq(const uint32_t* x, int lane) {
    float c0[4] = {}, c1[4] = {};
#pragma unroll
    for (int i = 0; i < N; i += 4) {
        mma16(c0, x + i, x[i], x[i + 2]);
        mma16(c1, x + i, x[i + 1], x[i + 3]);
    }
    return (lane & 4) ? c0[1] + c1[3] : c0[0] + c1[2];
}
__device__ __forceinline__ void mma_sp(float (&d)[32], const uint32_t* a, uint64_t b, uint32_t meta, int acc) {
    asm volatile("{.reg .pred p; setp.ne.b32 p, %38, 0;\n"
                 "wgmma.mma_async.sp.sync.aligned.m64n64k32.f32.bf16.bf16 {%0,%1,%2,%3,%4,%5,%6,%7,%8,%9,%10,%11,%12,%13,%14,%15,%16,%17,%18,%19,%20,%21,%22,%23,%24,%25,%26,%27,%28,%29,%30,%31}, "
                 "{%32,%33,%34,%35}, %36, %37, 0, p, 1, 1, 1;}\n"
                 : F16(d, 0), F16(d, 16) : "r"(a[0]), "r"(a[1]), "r"(a[2]), "r"(a[3]), "l"(b), "r"(meta), "r"(acc));
}
__device__ __forceinline__ void mma_qk(float (&d)[32], uint32_t a0, uint32_t a1, uint32_t a2, uint32_t a3, uint64_t b, int acc) {
    asm volatile("{.reg .pred p; setp.ne.b32 p, %37, 0;\n"
                 "wgmma.mma_async.sync.aligned.m64n64k16.f32.bf16.bf16 {%0,%1,%2,%3,%4,%5,%6,%7,%8,%9,%10,%11,%12,%13,%14,%15,%16,%17,%18,%19,%20,%21,%22,%23,%24,%25,%26,%27,%28,%29,%30,%31}, "
                 "{%32,%33,%34,%35}, %36, p, 1, 1, 0;}\n"
                 : F16(d, 0), F16(d, 16) : "r"(a0), "r"(a1), "r"(a2), "r"(a3), "l"(b), "r"(acc));
}
__device__ __forceinline__ void mma_pv(float (&d)[36], uint32_t a0, uint32_t a1, uint32_t a2, uint32_t a3, uint64_t b) {
    asm volatile("wgmma.mma_async.sync.aligned.m64n72k16.f32.bf16.bf16 {%0,%1,%2,%3,%4,%5,%6,%7,%8,%9,%10,%11,%12,%13,%14,%15,%16,%17,%18,%19,%20,%21,%22,%23,%24,%25,%26,%27,%28,%29,%30,%31,%32,%33,%34,%35}, "
                 "{%36,%37,%38,%39}, %40, 1, 1, 1, 1;\n"
                 : F16(d, 0), F16(d, 16), F4(d, 32) : "r"(a0), "r"(a1), "r"(a2), "r"(a3), "l"(b));
}

__device__ __forceinline__ uint32_t load_code(int n, int r, int w) {
    const int tile = 2 * r + w;
    int m, col, row;
    if (n < 16 || n >= 38) {
        const int k = n < 16 ? n : n - 38;
        m = n < 16 ? 0 : 6;
        if (n >= 38 && k < 4) { col = 4 * tile + (k & 1); row = (k >> 1) ^ r; }
        else if (k < 8) { col = 4 * tile + (k >> 1); row = n < 16 ? (k & 1) : (k & 1) ^ r; }
        else { m++; col = k < 12 ? tile ^ 2 : tile; row = 2 * (tile ^ (k & 1)) + ((k >> 1) & 1); }
    } else if (n < 30) {
        const int k = n - 16;
        m = 2;
        if (k < 4) { col = tile + ((k & 1) ? 8 : 4); row = (k >> 1) ^ r; }
        else { col = tile; row = (k & 1) ^ r; }
    } else if (n < 32) { m = 3; col = tile; row = n - 30; }
    else if (n < 36) { const int k = n - 32; m = 4; col = tile + 4 * (k & 1); row = (k >> 1) ^ r; }
    else { m = 5; col = tile; row = (n & 1) ^ r; }
    return m | (col << 4) | (row << ((m == 0 || m == 3) ? 10 : 11));
}

__global__ void __cluster_dims__(2, 1, 1) __launch_bounds__(NTHREADS, 1)
conformer_kernel(const Scalars p, const __grid_constant__ Maps m) {
    extern __shared__ __align__(1024) unsigned char smem_raw[];
    const uint32_t sb = smem_u32(smem_raw);
    const uint32_t bars = sb + OFF_BARS;
    const int tid = threadIdx.x;
    const int lane = tid & 31;
    const int warp = __shfl_sync(~0u, tid >> 5, 0);
    const int r = blockIdx.x & 1;
    const int pair = blockIdx.x >> 1;
    const int b = pair >> 5, pt = pair & 31;
    const int ah = pt >> 3, qt = (pt & 7) * 2 + r;
    const int abh = b * 4 + ah;

    TG(30);
    TSINIT();
    TS(0);
    const uint32_t P = sb + OFF_P, H = sb + OFF_H;
    if (warp == 11) {
        if (lane == 0) {
#pragma unroll
            for (int i = 0; i < 2 * NSLOT; i++) mbar_init(bars + (B_FULL + i) * 8, 1);
            asm volatile("fence.mbarrier_init.release.cluster;" ::: "memory");
            fence_async_smem();
        }
        __syncwarp();
        bar_arrive(13, 96);
        cluster_arrive();
    }

    if (warp >= 8) {
        asm volatile("setmaxnreg.dec.sync.aligned.u32 48;");
        if (warp >= 12) {
            cluster_arrive();
            const int ut = tid & 127;
            cluster_wait();
            const uint32_t target = ld_epoch() * 64;
            bar_sync(6, 384);
#pragma unroll
            for (int i = 0; i < 4; i++) {
                st_data(g_o + (size_t)(b * 128 + qt * 8 + 2 * i + (ut >> 6)) * 4096 + ah * 1024 + (ut & 63) * 16, ~0u, ~0u, ~0u, ~0u);
                if (i < 2) st_data(&g_halo[(pair * 4 + 2 * r + i) * 128 + ut], ~0u, ~0u, ~0u, ~0u);
            }
            bar_sync(11, 128);
            if (ut == 0) {
                asm volatile("red.release.gpu.global.add.u32 [%0], 1;" ::"l"(&g_reset[b * 32]) : "memory");
#pragma unroll 1
                for (int i = 0; i < (1 << 20) && ld_relaxed(&g_reset[b * 32]) != target; i++) __nanosleep(100);
                asm volatile("fence.acquire.gpu;" ::: "memory");
                mbar_arrive(bars + B_RST * 8);
            }
            bar_sync(11, 128);
            TS(14);
#pragma unroll
            for (int i = 0; i < 4; i++) st_data(g_kvq + 2097152 + (size_t)(abh * 1024 + qt * 64) * 128 + i * 2048 + ut * 16, 0, 0, 0, 0);
            const int side = warp & 1, wg = (warp >> 1) & 1, np = side ? pt + 1 : pt - 1;
            const unsigned char* src = reinterpret_cast<const unsigned char*>(&g_halo[(((b * 32 + np) * 4 + 2 * r + wg) * 2 + (side ^ 1)) * 64 + lane]);
            const uint32_t dst = P + wg * GCH + side * 5120 + (lane & 7) * 128 + (((lane >> 3) ^ (lane & 7)) << 4);
            uint4 hv[2] = {make_uint4(0, 0, 0, 0), make_uint4(0, 0, 0, 0)};
            bar_sync(8 + wg, 192);
            if (np >= 0 && np < 32) {
                spin(HDELAY);
                ld_data<512>(hv, src);
            }
            stsm4(dst, hv[0].x, hv[0].y, hv[0].z, hv[0].w);
            stsm4(dst ^ 64, hv[1].x, hv[1].y, hv[1].z, hv[1].w);
            __syncwarp();
            if (lane == 0) mbar_arrive(bars + (B_HALO + (warp & 3)) * 8);
            TS(4);
        } else if (warp < 10) {
            const int w = warp - 8;
            const uint32_t ring = sb + OFF_RING + w * NSLOT * SLOT;
            const uint32_t full = bars + (B_FULL + w * NSLOT) * 8;
            cluster_arrive();
            bar_sync(13, 96);
            TS(1);
#pragma unroll
            for (int n = 0; n < NSLOT; n++) {
                if (n == 1) bar_sync(12, 64);
                ring_load(ring + n * SLOT, &m.tm[0], 64 * (8 * r + 4 * w + (n >> 1)), 4 * (n & 1), full + n * 8);
            }
            TS(2);
            const uint32_t code = load_code(lane, r, w) | (load_code(lane + 32, r, w) << 16);
            cluster_wait();
            uint32_t s = 0, ph = 0;
            int n = NSLOT;
#pragma unroll 1
            for (int seg = 0; seg < 2; seg++) {
#pragma unroll 1
                for (; n < (seg == 0 ? 22 : NLOADS); n++) {
                    const uint32_t c = __shfl_sync(~0u, code, n) >> (n & 32 ? 16 : 0);
                    const CUtensorMap* tm = &m.tm[c & 15];
                    const uint32_t col = (c & 0xf0) * 4, row = (c & 0xff00) >> 8, dst = ring + s * SLOT;
                    mbar_wait(full + (B_EMPTY - B_FULL) * 8 + s * 8, ph + (((uint32_t)(size_t)tm | col | row | dst) & p.zero));
                    ring_load(dst, tm, col, row, full + s * 8);
                    if (++s == NSLOT) { s = 0; ph ^= 1; }
                }
                if (seg == 1) break;
                const uint32_t epoch = ld_epoch();
                const uint32_t rdy = bars + (B_RDY + 2 * w) * 8, prdy = mapa(rdy, r ^ 1);
                const int odd = r ^ w;
                const uint32_t* flags = g_flag_kv + (abh * 32 + lane) * FS;
                bool first = (lane >> 2) == 2 * odd + w;
                if (first) first = ld_relaxed(flags) != epoch;
                auto kv_load = [&](uint32_t sl, int isv, int i) {
                    ring_load_both(ring + sl * SLOT, &m.tm[8], (isv * 64 + abh * 8 + 2 * i + w) * 128, full + sl * 8);
                };
                if (lane < NSLOT) {
                    mbar_wait(full + (B_EMPTY - B_FULL + lane) * 8, lane < 4);
                    mbar_arrive_tx(full + lane * 8, SLOT);
                }
                __syncwarp();
                if (lane == 0) mbar_arrive_peer(prdy);
                bar_sync(14, 96);
                spin(KDELAY);
                mbar_wait(rdy, 0);
                flag_wait(flags, epoch, first);
                TSW(5 + 2 * odd);
                if (!odd) { kv_load(4, 0, 0); bar_arrive(12, 64); }
                else bar_sync(12, 64);
                spin(w ? KD3 : KD2);
                kv_load(odd ? 5 : 0, odd ^ 1, odd);
                flag_wait(flags, epoch, (lane >> 2) == 2 * odd + w + 4);
                mbar_wait(full + (odd ? 5 : 0) * 8, odd);
                kv_load(1 + odd, odd, 2 - odd);
                if (odd) { mbar_wait(full + 16, 0); kv_load(3, 0, 3); }
#pragma unroll 1
                for (int i = 0; i < 2; i++) {
                    mbar_wait(full + (B_EMPTY - B_FULL + 4 + i) * 8, 1);
                    if (lane == 0) mbar_arrive_tx(full + (4 + i) * 8, SLOT);
                    if (i == odd) {
                        mbar_wait(rdy + 8, 0);
                        kv_load(4 + i, 1, 2 + i);
                    } else if (lane == 0) mbar_arrive_peer(prdy + 8);
                    __syncwarp();
                }
                n = 30; s = 0; ph = 0;
            }
        } else if (warp == 10) {
            if (lane == 0) {
#pragma unroll
                for (int i = B_EMPTY; i < NBARS; i++) mbar_init(bars + i * 8, i < B_XA ? 4 : 1);
#pragma unroll
                for (int i = B_XA; i <= B_SR; i++) mbar_arrive_tx(bars + i * 8, i < B_XB ? 512 : ((i >= B_INB && i < B_SR) ? 4096 : 8192));
                asm volatile("fence.mbarrier_init.release.cluster;" ::: "memory");
                fence_async_smem();
            }
            __syncwarp();
            cluster_arrive();
            cluster_wait();
        } else {
            const uint32_t kb = (lane < 2 || lane > 5) ? 4096 : (lane == 2 ? 3072 : (lane == 4 ? 2048 : 1024));
            const char* pf = m.w[lane & 7] + blockIdx.x * kb;
            cluster_wait();
            mbar_wait(bars + B_FULL * 8, 0);
            if (lane < 3) prefetch_l2(pf, kb);
            if (lane >= 1 && lane < 9) asm volatile("prefetch.tensormap [%0];" ::"l"(&m.tm[lane]) : "memory");
            mbar_wait(bars + (B_FULL + 1) * 8, 1);
            if (lane > 2 && lane < 8) prefetch_l2(pf, kb);
            if (lane == 8 && blockIdx.x < 15) prefetch_l2(p.dw + blockIdx.x * 256, 512);
            const uint32_t epoch = ld_epoch();
            bar_sync(4, 288);
            if (lane < 16) flag_set(&g_flag_kv[((b * 4 + 2 * r + (lane >> 3)) * 32 + pt) * FS + (lane & 7)], epoch);
            __syncwarp();
            bar_arrive(14, 96);
            TSW(8);
        }
        TSDUMP();
        return;
    }

    const int w = warp >> 2, wq = warp & 3;
    const int tile = 2 * r + w;
    const int wt = tid & 127;
    const int c4 = lane & 3;
    const int trow = pt * 32 + 8 * wq;
    uint32_t xr[8];
    uint32_t a[32];
    const char* xrow = reinterpret_cast<const char*>(p.x) + (b * T_ + trow + (lane >> 2)) * 512;
    zero(a);
    if (trow < T_) {
        const char* src = xrow + c4 * 16 + p.zero;
#pragma unroll
        for (int i = 0; i < 8; i++)
            asm volatile("ld.global.nc.v4.b32 {%0,%1,%2,%3}, [%4];" : "=r"(a[4 * i]), "=r"(a[4 * i + 1]), "=r"(a[4 * i + 2]), "=r"(a[4 * i + 3]) : "l"(src + 64 * i));
    }
    cluster_arrive();
    asm volatile("setmaxnreg.inc.sync.aligned.u32 208;");
    const uint32_t rbase = sb + OFF_RING + w * NSLOT * SLOT, fbar = bars + (B_FULL + w * NSLOT) * 8;
    const uint32_t rdesc = desc_lo(rbase);
    auto acq = [&](int n) { mbar_wait(fbar + (n % NSLOT) * 8, (n / NSLOT) & 1); };
    auto rel = [&](int n) { if (lane == 0) mbar_arrive(fbar + (B_EMPTY - B_FULL + n % NSLOT) * 8); };
    const uint32_t foff = (lane & 7) * 128 + (((lane >> 3) ^ (lane & 7)) << 4);
    float v[16];
    const uint32_t xown = __shfl_sync(~0u, P + wt * 16 + tile * 4096, lane), xrem = __shfl_sync(~0u, P + wt * 16 + (r ^ 1) * 8192, lane);
    const uint32_t sbuf = __shfl_sync(~0u, sb + OFF_MISC + (8 * wq + (lane >> 2)) * 32, lane);
    const uint32_t sown = __shfl_sync(~0u, sbuf + tile * 8, lane);
    const uint32_t peer = __shfl_sync(~0u, mapa(sb, r ^ 1) - sb, lane);
    const uint32_t hbuf = __shfl_sync(~0u, H + w * 4096 + wt * 16, lane);
    const uint32_t meta = __shfl_sync(~0u, 0xEEEE4444u + p.zero, lane);
    cluster_wait();
    TS(56);
    float mean, msq;
    const int mir = wq < 2 ? 7 : 0;
    uint32_t dwr[15];

    auto phase = [&](auto phc) __attribute__((always_inline)) {
        constexpr int ph = decltype(phc)::value;
        uint4 o0, o1;
        if (ph == 0) {
            const uint32_t one = 0x3F803F80u + ((xown | xrem | sbuf | sown | hbuf | foff | rdesc | fbar) & p.zero);
            mean = ((row_sum<8>(a, one) + row_sum<8>(a + 8, one)) + (row_sum<8>(a + 16, one) + row_sum<8>(a + 24, one))) * (1.f / 256.f);
            TS(57);
        } else {
            const uint32_t xa = bars + (B_XA + ph) * 8;
#pragma unroll
            for (int j = 0; j < 8; j++) xr[j] = pack2(v[2 * j], v[2 * j + 1]);
            const float s = row_sum<8>(xr), q = row_sumsq<8>(xr, lane);
            if (ph < 4) {
                sts128(xown, xr[0], xr[1], xr[2], xr[3]);
                sts128(xown + 2048, xr[4], xr[5], xr[6], xr[7]);
            }
            put_sums(sown, sown + peer, s, q, xa + peer, c4 == (lane >> 3));
            bar_sync(10, 256);
            if (ph < 4) {
                o0 = lds128(xown ^ 4096); o1 = lds128((xown ^ 4096) + 2048);
                st_async4(xown + peer, xr[0], xr[1], xr[2], xr[3], xa + (B_XB - B_XA) * 8 + peer);
                st_async4(xown + peer + 2048, xr[4], xr[5], xr[6], xr[7], xa + (B_XB - B_XA) * 8 + peer);
            }
            TS(57 + ph);
            if (ph == 3) acq(38);
            if (ph == 1) acq(16);
            mbar_wait(xa, 0);
            const float4 u0 = lds128f(sbuf), u1 = lds128f(sbuf + 16);
            mean = ((u0.x + u0.z) + (u1.x + u1.z)) * (1.f / 256.f);
            msq = ((u0.y + u0.w) + (u1.y + u1.w)) * (1.f / 256.f);
        }
        if (ph == 4) return;
        const uint32_t mean2 = pack2(mean, mean);
        auto centre = [&](int i, const uint4& u) {
            a[i] = hsub2(u.x, mean2); a[i + 1] = hsub2(u.y, mean2); a[i + 2] = hsub2(u.z, mean2); a[i + 3] = hsub2(u.w, mean2);
        };
        if (ph == 0) {
#pragma unroll
            for (int j = 0; j < 32; j++) a[j] = hsub2(a[j], mean2);
            zero(xr);
            if (trow < T_) {
                const char* src = xrow + tile * 128 + c4 * 4 + (mean2 & p.zero);
#pragma unroll
                for (int j = 0; j < 8; j++) asm volatile("ld.global.nc.b32 %0, [%1];" : "=r"(xr[j]) : "l"(src + 16 * j));
            }
            mean -= blo(mean2);
            msq = __shfl_sync(~0u, row_sumsq<16>(a, lane) + row_sumsq<16>(a + 16, lane), (lane & 28) + (lane >> 3)) * (1.f / 256.f);
            acq(0);
        } else {
#pragma unroll
            for (int j = 0; j < 8; j++) a[j] = hsub2(xr[j], mean2);
            centre(8, o0); centre(12, o1);
        }
        const float rstd = rsq(fmaxf(fmaf(-mean, mean, msq), 0.f) + 1e-5f);
        auto gather_peer = [&]() {
            mbar_wait(bars + (B_XB + ph) * 8, 0);
#pragma unroll
            for (int i = 0; i < 4; i++) centre(16 + 4 * i, lds128(xrem + i * 2048));
        };
        auto sp = [&](float (&d)[32], int n, const uint32_t* af, int flip, int acc) {
            const uint32_t lo = rdesc + p.zero * (ph * 64 + n + 1) + (n % NSLOT) * (SLOT >> 4);
            const uint64_t b0 = mkdesc(lo + flip * 512), b1 = mkdesc(lo + (flip ^ 1) * 512);
            wg_fence();
            mma_sp(d, af, b0, meta, acc);
            mma_sp(d, af + 4, b0 + 256, meta, 1);
            mma_sp(d, af + 8, b1, meta, 1);
            mma_sp(d, af + 12, b1 + 256, meta, 1);
            wg_commit();
        };
        float d0[32], d1[32];

        if (ph == 0 || ph == 3) {
            uint32_t h[32], ho[32];
            const float rs = 0.5f * rstd;
            const uint32_t inb = bars + (B_INB + (ph & 2) + w) * 8;
            bool ready = true;
            const int eager = ph ? 0x5a : 0x54;
            auto step = [&](float (&d)[32], int n, const uint32_t* af, int flip, int acc, auto work) {
                const int l = n + (ph ? 38 : 0);
                if (!ready) acq(l);
                sp(d, l, af, flip, acc);
                if (n < 15) ready = mbar_test(fbar + ((l + 1) % NSLOT) * 8, ((l + 1) / NSLOT) & 1);
                wg_wait<1>();
                if (n > 0 && !((eager >> (n - 1)) & 1)) rel(l - 1);
                const uint32_t tie = work() & p.zero;
                if ((eager >> n) & 1) {
                    if (p.zero < l + 1) wg_wait<0>();
                    if (lane == 0) mbar_arrive(fbar + (B_EMPTY - B_FULL + l % NSLOT) * 8 + tie);
                }
            };
            auto none = []() { return 0u; };
            const int fl = ph ? w : 0;
            auto fetch = [&](int i) {
                bar_sync(10, 256);
                const uint32_t src = ((i & 1) ? hbuf : xown) ^ 4096;
                const uint4 u0 = lds128(src), u1 = lds128(src + 2048);
                ho[8 * i] = u0.x; ho[8 * i + 1] = u0.y; ho[8 * i + 2] = u0.z; ho[8 * i + 3] = u0.w;
                ho[8 * i + 4] = u1.x; ho[8 * i + 5] = u1.y; ho[8 * i + 6] = u1.z; ho[8 * i + 7] = u1.w;
                return u0.x | u1.x;
            };
            auto act = [&](float (&d)[32], int i) {
                if (i > 0) fetch(i - 1);
                else if (ph) bar_sync(10, 256);
                pin(d);
#pragma unroll
                for (int j = 0; j < 8; j++) {
                    const float u0 = (d[4 * j] + d[4 * j + 2]) * rs, u1 = (d[4 * j + 1] + d[4 * j + 3]) * rs;
                    h[8 * i + j] = pack2(fmaf(u0, tanh_fast(u0), u0), fmaf(u1, tanh_fast(u1), u1));
                }
                sts128((i & 1) ? hbuf : xown, h[8 * i], h[8 * i + 1], h[8 * i + 2], h[8 * i + 3]);
                sts128(((i & 1) ? hbuf : xown) + 2048, h[8 * i + 4], h[8 * i + 5], h[8 * i + 6], h[8 * i + 7]);
                return 0u;
            };
            TS(1 + (ph & 2) * 10);
            if (ph) {
                step(d0, 0, a, fl, 0, none);
                step(d1, 1, a, fl, 0, [&]() { gather_peer(); return 0u; });
                TS(32);
                step(d0, 2, a + 16, 0, 1, none);
                step(d1, 3, a + 16, 0, 1, [&]() { return act(d0, 0); });
            } else {
                step(d0, 0, a, fl, 0, none);
                TS(32);
                step(d0, 1, a + 16, 0, 1, none);
                step(d1, 2, a, fl, 0, [&]() { return act(d0, 0); });
                step(d1, 3, a + 16, 0, 1, none);
            }
            step(d0, 4, a, fl, 0, [&]() { return act(d1, 1); });
            TS(33);
            step(d0, 5, a + 16, 0, 1, none);
            step(d1, 6, a, fl, 0, [&]() { return act(d0, 2); });
            step(d1, 7, a + 16, 0, 1, none);
            step(d0, 8, h, 0, 0, [&]() { act(d1, 3); return fetch(3); });
            TS(2 + (ph & 2) * 10);
            step(d0, 9, ho, 0, 1, none);
            step(d0, 10, h + 16, 0, 1, none);
            step(d0, 11, ho + 16, 0, 1, none);
            uint32_t pk[8];
            auto pack_out = [&]() {
                pin(d0);
#pragma unroll
                for (int j = 0; j < 8; j++) pk[j] = pack2(d0[4 * j] + d0[4 * j + 2], d0[4 * j + 1] + d0[4 * j + 3]);
            };
            auto send = [&](int i) { st_async4(hbuf + 8192 + i * 2048 + peer, pk[4 * i], pk[4 * i + 1], pk[4 * i + 2], pk[4 * i + 3], inb + peer); };
            step(d1, 12, h, 0, 0, [&]() { pack_out(); send(0); return 0u; });
            TS(34);
            step(d1, 13, ho, 0, 1, [&]() { send(1); return 0u; });
            step(d1, 14, h + 16, 0, 1, none);
            step(d1, 15, ho + 16, 0, 1, none);
            mbar_wait(inb, 0);
#pragma unroll
            for (int i = 0; i < 2; i++) {
                const uint4 u = lds128(hbuf + 8192 + i * 2048);
                const uint32_t p0[4] = {u.x, u.y, u.z, u.w};
#pragma unroll
                for (int j = 0; j < 4; j++) {
                    v[8 * i + 2 * j] = fmaf(0.5f, blo(p0[j]), blo(xr[4 * i + j]));
                    v[8 * i + 2 * j + 1] = fmaf(0.5f, bhi(p0[j]), bhi(xr[4 * i + j]));
                }
            }
            wg_wait<0>();
            pin(d1);
            if (ph == 0) rel(15);
            TS(3 + (ph & 2) * 10);
#pragma unroll
            for (int j = 0; j < 8; j++) {
                v[2 * j] = fmaf(0.5f, d1[4 * j] + d1[4 * j + 2], v[2 * j]);
                v[2 * j + 1] = fmaf(0.5f, d1[4 * j + 1] + d1[4 * j + 3], v[2 * j + 1]);
            }
            return;
        }

        auto residual = [&](int n) {
            wg_wait<1>();
            rel(n);
            wg_wait<0>();
            pin(d0);
            rel(n + 1);
#pragma unroll
            for (int j = 0; j < 8; j++) {
                v[2 * j] = d0[4 * j] + d0[4 * j + 2] + blo(xr[j]);
                v[2 * j + 1] = d0[4 * j + 1] + d0[4 * j + 3] + bhi(xr[j]);
            }
        };

        if (ph == 2) {
            TS(39);
            sp(d0, 32, a, w, 0);
            acq(33);
            sp(d1, 33, a, w, 0);
            acq(34); acq(35);
            gather_peer();
            sp(d0, 34, a + 16, 0, 1);
            sp(d1, 35, a + 16, 0, 1);
            wg_wait<2>();
            rel(32);
            acq(36);
            bar_sync(10, 256);
            const float rs = trow < T_ ? 0.5f * rstd : 0.f;
            wg_wait<0>();
            pin(d0); pin(d1);
            TS(18);
            uint32_t pk[8];
#pragma unroll
            for (int j = 0; j < 8; j++) {
                const float u0 = (d0[4 * j] + d0[4 * j + 2]) * rs, u1 = (d0[4 * j + 1] + d0[4 * j + 3]) * rs;
                const float t0 = tanh_fast((d1[4 * j] + d1[4 * j + 2]) * rs), t1 = tanh_fast((d1[4 * j + 1] + d1[4 * j + 3]) * rs);
                pk[j] = pack2(fmaf(u0, t0, u0), fmaf(u1, t1, u1));
            }
            if (wq == 0 || wq == 3) {
                uint4* hp = &g_halo[((pair * 4 + tile) * 2 + (wq & 1)) * 64 + lane];
                st_data(hp, pk[0], pk[1], pk[2], pk[3]);
                st_data(hp + 32, pk[4], pk[5], pk[6], pk[7]);
            }
            const uint32_t gs = P + w * GCH + wq * 1024;
            stsm4(gs + 1024 + foff, pk[0], pk[1], pk[2], pk[3]);
            stsm4(gs + 1024 + (foff ^ 64), pk[4], pk[5], pk[6], pk[7]);
            bar_sync(8 + w, 192);
            TS(26);
            uint32_t ca[8], cb[8];
            const int e = (wq & 1) * 4;
            const uint32_t lo = ((mir ^ e) * 144) ^ (lane * 4);
            const int dir = mir ? -1024 : 1024;
            const uint32_t gb = P + w * GCH + (mir ? 3072 : 2048) + lo, sown_ = H + tile * HCH, so = sown_ + (mir ? 1024 : 2048) + lo;
            auto finish = [&](int i) {
                const uint32_t c = hadd2(ca[i], cb[i]);
                const float h0 = blo(c), h1 = bhi(c);
                const uint32_t dst = (so + (i >> 2) * dir) ^ ((i & 3) * 144), val = pack2(fmaf(h0, tanh_fast(h0), h0), fmaf(h1, tanh_fast(h1), h1));
                asm volatile("st.async.shared::cluster.mbarrier::complete_tx::bytes.b32 [%0], %1, [%2];" ::"r"(dst + peer), "r"(val), "r"(bars + B_SR * 8 + peer) : "memory");
                sts32(dst, val);
            };
#pragma unroll
            for (int k = 0; k < 26; k++) {
                if (k == 19) {
#pragma unroll
                    for (int i = 0; i < 4; i++) finish(i);
                    mbar_wait(bars + (B_HALO + 2 * w + (wq >> 1)) * 8, 0);
                    rel(33); rel(34); rel(35);
                    TS(27);
                }
                const uint32_t g = lds32((gb + (((k + 1) & 4) ? ((k + 1) >> 3) + (wq & 1) : ((k + 1) >> 3)) * dir) ^ (((k + 1) & 7) * 144));
#pragma unroll
                for (int i = 0; i < 8; i++) {
                    const int tap = k - (i & 3) - 2 * (i & 4);
                    if (tap == 0) ca[i] = hmul2(g, dwr[0]);
                    else if (tap > 0 && tap < 8) ca[i] = hfma2(g, dwr[tap], ca[i]);
                    else if (tap == 8) cb[i] = hmul2(g, dwr[8]);
                    else if (tap > 8 && tap < 15) cb[i] = hfma2(g, dwr[tap], cb[i]);
                }
            }
#pragma unroll
            for (int i = 4; i < 8; i++) finish(i);
            bar_sync(10, 256);
            TS(19);
            auto frags = [&](int i, int half) {
                const uint32_t src = H + 2 * half * HCH + wq * 1024;
#pragma unroll
                for (int k = 0; k < 4; k++) ldsm4(src + (k >> 1) * HCH + (foff ^ ((k & 1) * 64)), a[i + 4 * k], a[i + 4 * k + 1], a[i + 4 * k + 2], a[i + 4 * k + 3]);
            };
            frags(0, r);
            sp(d0, 36, a, 0, 0);
            acq(37);
            mbar_wait(bars + B_SR * 8, 0);
            frags(16, r ^ 1);
            sp(d0, 37, a + 16, 0, 1);
            residual(36);
            TS(20);
            return;
        }

        {
            TS(11);
            unsigned char* g = g_kvq + (size_t)((b * 4 + tile) * 1024 + trow) * 128;
            const uint32_t uo = (lane >> 2) * 128 + ((c4 ^ (lane >> 2)) << 4);
            auto put = [&](float (&d)[32], int i) {
                pin(d);
                uint32_t pk[8];
#pragma unroll
                for (int j = 0; j < 8; j++) pk[j] = pack2((d[4 * j] + d[4 * j + 2]) * rstd, (d[4 * j + 1] + d[4 * j + 3]) * rstd);
                if (i < 2) {
                    stg128(g + i * 1048576 + uo, make_uint4(pk[0], pk[1], pk[2], pk[3]));
                    stg128(g + i * 1048576 + (uo ^ 64), make_uint4(pk[4], pk[5], pk[6], pk[7]));
                } else {
                    const uint32_t stg = H + warp * 1024;
                    sts128(stg + uo, pk[0], pk[1], pk[2], pk[3]);
                    sts128(stg + (uo ^ 64), pk[4], pk[5], pk[6], pk[7]);
                    __syncwarp();
                    ldsm4(stg + foff, pk[0], pk[1], pk[2], pk[3]);
                    ldsm4(stg + (foff ^ 64), pk[4], pk[5], pk[6], pk[7]);
                    st_data(g + 2097152 + lane * 16, ~pk[0], ~pk[1], ~pk[2], ~pk[3]);
                    st_data(g + 2097152 + 512 + lane * 16, ~pk[4], ~pk[5], ~pk[6], ~pk[7]);
                }
            };
            sp(d0, 16, a, w, 0);
            acq(17);
            sp(d1, 17, a, w, 0);
            gather_peer();
            acq(18);
            sp(d0, 18, a + 16, 0, 1);
            wg_wait<1>();
            rel(16); rel(17);
            acq(19);
            sp(d1, 19, a + 16, 0, 1);
            wg_wait<1>();
            rel(18);
            put(d0, 0);
            wg_wait<0>();
            rel(19);
            TS(37);
            put(d1, 1);
            bar_arrive(4, 288);
            TS(38);
            acq(20);
            sp(d0, 20, a, w, 0);
            acq(21);
            sp(d0, 21, a + 16, 0, 1);
            wg_wait<0>();
            rel(20); rel(21);
            put(d0, 2);
            TS(12);
        }

        {
            constexpr float CS = 0.125f * 1.4426950408889634f;
            float sa[32], sb2[32], o[36];
            uint32_t pa[16], pb[16], q[16];
            float n0 = INFINITY, n1 = INFINITY;
            zero(o); zero(pa); zero(pb); zero(sb2);
            const uint32_t ones = H + 8192;
            { const uint32_t c = w ? 0u : 0x3F803F80u; sts128(ones + tid * 16, c, c, c, c); }
            fence_async_smem();
            bar_sync(10, 256);
            const uint32_t vdesc = rdesc + ((((ones - rbase) >> 4) - 1) << 16);
            auto qk_issue = [&](float (&s)[32], uint32_t lo) {
                const uint64_t kd = mkdesc(lo);
                wg_fence();
#pragma unroll
                for (int k = 0; k < 4; k++) mma_qk(s, q[4 * k], q[4 * k + 1], q[4 * k + 2], q[4 * k + 3], kd + 2 * k, k != 0);
                wg_commit();
            };
            auto both_issue = [&](float (&s)[32], uint32_t klo, uint32_t (&pp)[16], uint32_t vlo) {
                const uint64_t kd = mkdesc(klo), vd = mkdesc(vlo);
                wg_fence();
#pragma unroll
                for (int k = 0; k < 4; k++) {
                    mma_pv(o, pp[4 * k], pp[4 * k + 1], pp[4 * k + 2], pp[4 * k + 3], vd - k * (128 * 65535));
                    mma_qk(s, q[4 * k], q[4 * k + 1], q[4 * k + 2], q[4 * k + 3], kd + 2 * k, k != 0);
                }
                wg_commit();
            };
            auto new_max = [&](float (&s)[32], int nj, float& x0, float& x1) {
                x0 = s[0]; x1 = s[2];
#pragma unroll
                for (int j = 0; j < nj; j++) {
                    x0 = fmaxf(x0, fmaxf(s[4 * j], s[4 * j + 1]));
                    x1 = fmaxf(x1, fmaxf(s[4 * j + 2], s[4 * j + 3]));
                }
                x0 = fmaxf(x0, __shfl_xor_sync(~0u, x0, 1)); x1 = fmaxf(x1, __shfl_xor_sync(~0u, x1, 1));
                x0 = fmaxf(x0, __shfl_xor_sync(~0u, x0, 2)); x1 = fmaxf(x1, __shfl_xor_sync(~0u, x1, 2));
                x0 = fminf(n0, fmaf(x0, -CS, -20.f)); x1 = fminf(n1, fmaf(x1, -CS, -20.f));
            };
            auto probs = [&](float (&s)[32], uint32_t (&pp)[16], bool ready, bool tail, auto wait) {
                uint32_t any = 0;
#pragma unroll
                for (int i = 0; i < 16; i++) {
                    pp[i] = pack2(ex2(fmaf(s[2 * i], CS, (i & 1) ? n1 : n0)), ex2(fmaf(s[2 * i + 1], CS, (i & 1) ? n1 : n0)));
                    any |= pp[i];
                }
                wg_wait<0>();
                pin(sa); pin(sb2); pin(o); pin(pa); pin(pb);
                if (__builtin_expect(__any_sync(~0u, (any & 0x40004000u) || !ready), 0)) {
                    wait();
                    if (__any_sync(~0u, any & 0x40004000u)) {
                        if (tail) {
#pragma unroll
                            for (int i = 20; i < 32; i++) s[i] = -INFINITY;
                        }
                        float x0, x1;
                        new_max(s, 8, x0, x1);
                        const float sc0 = ex2(x0 - n0), sc1 = ex2(x1 - n1);
                        n0 = x0; n1 = x1;
#pragma unroll
                        for (int j = 0; j < 9; j++) { o[4 * j] *= sc0; o[4 * j + 1] *= sc0; o[4 * j + 2] *= sc1; o[4 * j + 3] *= sc1; }
#pragma unroll
                        for (int i = 0; i < 16; i++)
                            pp[i] = pack2(ex2(fmaf(s[2 * i], CS, (i & 1) ? n1 : n0)), ex2(fmaf(s[2 * i + 1], CS, (i & 1) ? n1 : n0)));
                    }
                }
            };
            {
                uint4 u[4];
                const unsigned char* src = g_kvq + 2097152 + (size_t)(abh * 1024 + qt * 64 + wq * 16) * 128 + lane * 16;
                spin(QGATE);
                ld_data<512, true>(u, src);
#pragma unroll
                for (int k = 0; k < 2; k++) {
                    q[8 * k] = ~u[k].x; q[8 * k + 1] = ~u[k + 2].x; q[8 * k + 2] = ~u[k].y; q[8 * k + 3] = ~u[k + 2].y;
                    q[8 * k + 4] = ~u[k].z; q[8 * k + 5] = ~u[k + 2].z; q[8 * k + 6] = ~u[k].w; q[8 * k + 7] = ~u[k + 2].w;
                }
                pin(q);
            }
            TS(40);
            acq(22);
            TS(13);
            qk_issue(sa, rdesc + (22 % NSLOT) * (SLOT >> 4));
            wg_wait<0>();
            pin(sa);
            {
                float x0, x1;
                new_max(sa, 2, x0, x1);
                n0 = x0; n1 = x1;
            }
            bar_arrive(6, 384);
            uint32_t vd = vdesc, kd = rdesc + 5 * (SLOT >> 4), vb = fbar, kb = fbar + 40;
            uint32_t vlast = vdesc - 4 * (SLOT >> 4) * 65535u, klast = rdesc + 4 * (SLOT >> 4) + 512;
            uint32_t kprev = fbar + 32, vprev = bars + (B_SINK - (B_EMPTY - B_FULL)) * 8;
#pragma unroll 1
            for (int it = 0; it < 4; it++) {
                both_issue(sb2, klast, pb, vlast);
                probs(sa, pa, mbar_test(vb, 0) & mbar_test(kb, it == 0), false, [&]() { mbar_wait(vb, 0); mbar_wait(kb, it == 0); });
                TS(41 + it * 4);
                if (lane == 0) mbar_arrive(kprev + (B_EMPTY - B_FULL) * 8);
                if (lane == 0) mbar_arrive(vprev + (B_EMPTY - B_FULL) * 8);
                both_issue(sa, kd, pa, vd);
                const int dv = it == 2 ? 1 : 2, dk = it == 0 ? -4 : 2;
                kprev = kb; vprev = vb; vlast = vd - 512 * 65535u; klast = kd + 512;
                vd -= dv * (SLOT >> 4) * 65535u; vb += dv * 8;
                kd += dk * (SLOT >> 4); kb += dk * 8;
                probs(sb2, pb, true, it == 3 && w == 1, []() {});
                TS(43 + it * 4);
            }
            wg_fence();
#pragma unroll
            for (int k = 0; k < 4; k++)
                mma_pv(o, pb[4 * k], pb[4 * k + 1], pb[4 * k + 2], pb[4 * k + 3], mkdesc(vlast - k * (128 * 65535) + (k > 1 ? w * ((k - 1) << 22) : 0)));
            wg_commit();
            const uint32_t mlw = sb + OFF_MISC + 1024 + (tid >> 2) * 8;
            unsigned char* odst = g_o + (size_t)(b * 128 + qt * 8 + 2 * wq + w) * 4096 + ah * 1024 + lane * 16;
            mbar_wait(bars + B_RST * 8, __any_sync(~0u, (mlw | (uint32_t)(size_t)odst) & p.zero));
            wg_wait<0>();
            pin(o); pin(pb); pin(sa); pin(sb2);
            rel(29);
            TS(14);
            auto merge = [&](int keep, float nk, float ns) {
                const int snd = 2 - keep;
                if (c4 == 0) sts64f(mlw, ns, o[32 + snd]);
#pragma unroll
                for (int j = 0; j < 2; j++)
                    sts128(hbuf + j * 2048, pack2(o[16 * j + snd], o[16 * j + snd + 1]), pack2(o[16 * j + 4 + snd], o[16 * j + 5 + snd]),
                           pack2(o[16 * j + 8 + snd], o[16 * j + 9 + snd]), pack2(o[16 * j + 12 + snd], o[16 * j + 13 + snd]));
                bar_sync(10, 256);
                const float2 u = lds64f(mlw ^ 256);
                const float x = fminf(nk, u.x);
                float a = ex2(x - nk), c = ex2(x - u.x);
                const float inv = rcp(fmaf(a, o[32 + keep], c * u.y));
                a *= inv; c *= inv;
                uint32_t pk[8];
#pragma unroll
                for (int j = 0; j < 2; j++) {
                    const uint4 t4 = lds128((hbuf ^ 4096) + j * 2048);
                    const uint32_t t[4] = {t4.x, t4.y, t4.z, t4.w};
#pragma unroll
                    for (int i = 0; i < 4; i++)
                        pk[4 * j + i] = pack2(fmaf(a, o[16 * j + 4 * i + keep], c * blo(t[i])), fmaf(a, o[16 * j + 4 * i + keep + 1], c * bhi(t[i])));
                }
                st_data(odst, pk[0], pk[1], pk[2], pk[3]);
                st_data(odst + 512, pk[4], pk[5], pk[6], pk[7]);
            };
            if (tid < 128) merge(0, n0, n1); else merge(2, n1, n0);
            if (tid == 0) asm volatile("red.relaxed.gpu.global.add.u32 [%0], 1;" ::"l"(&g_epoch[blockIdx.x * FS]) : "memory");
            TS(15);
        }

        {
            const uint32_t* dp = reinterpret_cast<const uint32_t*>(p.dw + (mir ? 14 * 256 : 0) + tile * 64) + lane;
#pragma unroll
            for (int i = 0; i < 15; i++) asm volatile("ld.global.nc.b32 %0, [%1];" : "=r"(dwr[i]) : "l"(dp + i * (mir ? -128 : 128)));
            acq(30); acq(31); acq(32);
            uint4 u[8];
            ld_data<512>(u, g_o + (size_t)(b * 128 + pt * 4 + wq) * 4096 + lane * 16);
#pragma unroll
            for (int i = 0; i < 8; i++) { a[4 * i] = u[i].x; a[4 * i + 1] = u[i].y; a[4 * i + 2] = u[i].z; a[4 * i + 3] = u[i].w; }
            TS(16);
            sp(d0, 30, a, 0, 0);
            sp(d0, 31, a + 16, 0, 1);
#pragma unroll
            for (int i = 0; i < 15; i++) dwr[i] = hmul2(dwr[i], 0x3F003F00u);
            residual(30);
            TS(17);
        }
    };
    phase(std::integral_constant<int, 0>{});
    phase(std::integral_constant<int, 1>{});
    phase(std::integral_constant<int, 2>{});
    phase(std::integral_constant<int, 3>{});
    phase(std::integral_constant<int, 4>{});

    cluster_arrive();
    TS(24);
    {
        const float rstd = rsq(fmaxf(fmaf(-mean, mean, msq), 0.f) + 1e-5f), nb = -mean * rstd;
#pragma unroll
        for (int j = 0; j < 8; j++) xr[j] = pack2(fmaf(v[2 * j], rstd, nb), fmaf(v[2 * j + 1], rstd, nb));
        const uint32_t stg = H + warp * 1024;
        stsm4(stg + foff, xr[0], xr[1], xr[2], xr[3]);
        stsm4(stg + (foff ^ 64), xr[4], xr[5], xr[6], xr[7]);
        __syncwarp();
        const uint32_t src = stg + (lane >> 3) * 128 + (((lane & 7) ^ (lane >> 3)) << 4);
        const uint4 u0 = lds128(src), u1 = lds128((src + 512) ^ 64);
        __nv_bfloat16* dst = p.out + (size_t)(b * T_ + trow + (lane >> 3)) * 256 + tile * 64 + (lane & 7) * 8;
        if (trow < T_) { stg128(dst, u0); stg128(dst + 4 * 256, u1); }
    }
    TS(25);
    TG(31);
    TSDUMP();
    cluster_wait();
}

typedef CUresult (*EncodeFn)(CUtensorMap*, CUtensorMapDataType, cuuint32_t, void*, const cuuint64_t*, const cuuint64_t*,
                             const cuuint32_t*, const cuuint32_t*, CUtensorMapInterleave, CUtensorMapSwizzle,
                             CUtensorMapL2promotion, CUtensorMapFloatOOBfill);

}

extern "C" void kernel_launch(void* const* d_in, const int* in_sizes, int n_in, void* d_out, int out_size) {
    static EncodeFn encode = nullptr;
    if (!encode) {
        void* fn = nullptr;
        cudaDriverEntryPointQueryResult qr;
        cudaGetDriverEntryPoint("cuTensorMapEncodeTiled", &fn, cudaEnableDefault, &qr);
        encode = (EncodeFn)fn;
        cudaFuncSetAttribute(conformer_kernel, cudaFuncAttributeMaxDynamicSharedMemorySize, SMEM_LAUNCH);
    }
    Scalars p;
    Maps m;
    const cuuint32_t ones[5] = {1, 1, 1, 1, 1};
    const int idx[8] = {1, 2, 3, 4, 5, 7, 8, 9};
    const int rows[8] = {256, 1024, 256, 256, 256, 256, 256, 1024};
    const int cols[8] = {1024, 256, 768, 256, 512, 256, 1024, 256};
    for (int i = 0; i < 8; i++) {
        const cuuint64_t pitch = (cuuint64_t)cols[i] * 2;
        const bool f = i != 0 && i != 3;
        const cuuint64_t dims[5] = {(cuuint64_t)cols[i], f ? 2u : 4u, f ? 2u : 4u, f ? 4u : 2u, (cuuint64_t)rows[i] / (f ? 16 : 32)};
        const cuuint64_t strides[4] = {pitch, pitch * 8, pitch * (f ? 2 : 4), pitch * (f ? 16 : 32)};
        const cuuint32_t box[5] = {64, f ? 2u : 4u, f ? 2u : 4u, f ? 4u : 2u, f ? 8u : 4u};
        encode(&m.tm[i], CU_TENSOR_MAP_DATA_TYPE_BFLOAT16, 5, d_in[idx[i]], dims, strides, box, ones, CU_TENSOR_MAP_INTERLEAVE_NONE,
               CU_TENSOR_MAP_SWIZZLE_128B, CU_TENSOR_MAP_L2_PROMOTION_L2_128B, CU_TENSOR_MAP_FLOAT_OOB_FILL_NONE);
        m.w[i] = (const char*)d_in[idx[i]];
    }
    {
        void* kv = nullptr;
        cudaGetSymbolAddress(&kv, g_kvq);
        const cuuint64_t dims[2] = {64, 16384};
        const cuuint64_t strides[1] = {128};
        const cuuint32_t box[2] = {64, 128};
        encode(&m.tm[8], CU_TENSOR_MAP_DATA_TYPE_BFLOAT16, 2, kv, dims, strides, box, ones, CU_TENSOR_MAP_INTERLEAVE_NONE,
               CU_TENSOR_MAP_SWIZZLE_NONE, CU_TENSOR_MAP_L2_PROMOTION_L2_128B, CU_TENSOR_MAP_FLOAT_OOB_FILL_NONE);
    }
    p.x = (const __nv_bfloat16*)d_in[0];
    p.dw = (const __nv_bfloat16*)d_in[6];
    p.out = (__nv_bfloat16*)d_out;
    p.zero = 0;
    conformer_kernel<<<NCTA, NTHREADS, SMEM_LAUNCH>>>(p, m);
}
```

```cpp
#include <cuda_runtime.h>
#include <cuda_bf16.h>
#include <cuda.h>
#include <stdint.h>
#include <type_traits>

namespace {

constexpr int T_ = 1000;
constexpr int NCTA = 128;
constexpr int NTHREADS = 512;
constexpr int NSLOT = 6;
constexpr int SLOT = 16384;
constexpr int NLOADS = 54;

constexpr uint32_t OFF_RING = 0;
constexpr uint32_t OFF_P = 196608;
constexpr uint32_t OFF_H = 212992;
constexpr uint32_t OFF_MISC = 229376;
constexpr uint32_t OFF_BARS = 230912;
constexpr uint32_t SMEM_BYTES = 231424;
constexpr uint32_t GCH = 6144;
constexpr uint32_t HCH = 4096;

constexpr int B_FULL = 0, B_EMPTY = 12, B_XA = 24  , B_XB = 29  , B_INB = 33  , B_SR = 37,
              B_RST = 38, B_RDY = 39  , B_SINK = 43, B_HALO = 44  , NBARS = 48;

#define PACE KDELAY = 250, KD2 = 300, KD3 = 500, QGATE = 700, HDELAY = 200
constexpr uint32_t PACE;
constexpr int FS = 8;

struct Scalars {
    const __nv_bfloat16* x;
    const __nv_bfloat16* dw;
    __nv_bfloat16* out;
    uint32_t zero;
};
struct Maps {
    CUtensorMap tm[9];
    const char* w[8];
};

__device__ __align__(1024) unsigned char g_kvq[3 * 8 * 1024 * 128];
__device__ __align__(1024) unsigned char g_o[2 * 128 * 4096];
__device__ uint4 g_halo[64 * 4 * 2 * 64];
__device__ __align__(128) uint32_t g_flag_kv[8 * 32 * FS];
__device__ uint32_t g_reset[2 * 32];
__device__ uint32_t g_epoch[NCTA * FS];

#define TS(i) do { } while (0)
#define TSW(i) do { } while (0)
#define TG(i) do { } while (0)
#define TSINIT() do { } while (0)
#define TSDUMP() do { } while (0)
constexpr uint32_t SMEM_LAUNCH = SMEM_BYTES;

__device__ __forceinline__ uint32_t smem_u32(const void* p) { return (uint32_t)__cvta_generic_to_shared(p); }
__device__ __forceinline__ void mbar_init(uint32_t b, uint32_t c) { asm volatile("mbarrier.init.shared::cta.b64 [%0], %1;" ::"r"(b), "r"(c) : "memory"); }
__device__ __forceinline__ void mbar_arrive(uint32_t b) { asm volatile("mbarrier.arrive.shared::cta.b64 _, [%0];" ::"r"(b) : "memory"); }
__device__ __forceinline__ void mbar_arrive_tx(uint32_t b, uint32_t tx) { asm volatile("mbarrier.arrive.expect_tx.shared::cta.b64 _, [%0], %1;" ::"r"(b), "r"(tx) : "memory"); }
__device__ __forceinline__ void mbar_wait(uint32_t b, uint32_t ph) {
    asm volatile("{\n.reg .pred p, q;\n.reg .u32 c;\nmov.u32 c, 0;\n"
                 "MW_LOOP:\n.pragma \"nounroll\";\n"
                 "mbarrier.try_wait.parity.shared::cta.b64 p, [%0], %1;\n"
                 "add.u32 c, c, 1;\nsetp.lt.u32 q, c, 65536;\nnot.pred p, p;\nand.pred p, p, q;\n@p bra MW_LOOP;\n}"
                 ::"r"(b), "r"(ph) : "memory");
}
__device__ __forceinline__ bool mbar_test(uint32_t b, uint32_t ph) {
    uint32_t ok;
    asm volatile("{\n.reg .pred p;\nmbarrier.test_wait.parity.shared::cta.b64 p, [%1], %2;\nselp.u32 %0, 1, 0, p;\n}" : "=r"(ok) : "r"(b), "r"(ph) : "memory");
    return ok;
}
__device__ __forceinline__ uint32_t mapa(uint32_t a, uint32_t r) { uint32_t o; asm("mapa.shared::cluster.u32 %0, %1, %2;" : "=r"(o) : "r"(a), "r"(r)); return o; }
__device__ __forceinline__ void fence_async_smem() { asm volatile("fence.proxy.async.shared::cta;" ::: "memory"); }
__device__ __forceinline__ void fence_async_global() { asm volatile("fence.proxy.async.global;" ::: "memory"); }
__device__ __forceinline__ void bar_sync(int id, int n) { asm volatile("bar.sync %0, %1;" ::"r"(id), "r"(n) : "memory"); }
__device__ __forceinline__ void bar_arrive(int id, int n) { asm volatile("bar.arrive %0, %1;" ::"r"(id), "r"(n) : "memory"); }
__device__ __forceinline__ void cluster_arrive() { asm volatile("barrier.cluster.arrive.relaxed.aligned;" ::: "memory"); }
__device__ __forceinline__ void cluster_wait() { asm volatile("barrier.cluster.wait.aligned;" ::: "memory"); }

__device__ __forceinline__ void ring_load(uint32_t dst, const CUtensorMap* tm, int col, int row16, uint32_t bar) {
    asm volatile("{\n.reg .pred p;\nelect.sync _|p, 0xffffffff;\n"
                 "@p mbarrier.arrive.expect_tx.shared::cta.b64 _, [%2], 16384;\n"
                 "@p cp.async.bulk.tensor.5d.shared::cluster.global.mbarrier::complete_tx::bytes [%0], [%1, {%3, 0, 0, 0, %4}], [%2];\n}"
                 ::"r"(dst), "l"(tm), "r"(bar), "r"(col), "r"(row16) : "memory");
}
__device__ __forceinline__ void ring_load_both(uint32_t dst, const CUtensorMap* tm, int c1, uint32_t bar) {
    asm volatile("{\n.reg .pred p;\nelect.sync _|p, 0xffffffff;\n"
                 "@p cp.async.bulk.tensor.2d.shared::cluster.global.mbarrier::complete_tx::bytes.multicast::cluster [%0], [%1, {0, %3}], [%2], %4;\n}"
                 ::"r"(dst), "l"(tm), "r"(bar), "r"(c1), "h"((uint16_t)3) : "memory");
}
__device__ __forceinline__ void mbar_arrive_peer(uint32_t b) { asm volatile("mbarrier.arrive.relaxed.cluster.shared::cluster.b64 _, [%0];" ::"r"(b) : "memory"); }
__device__ __forceinline__ void prefetch_l2(const void* src, uint32_t bytes) {
    asm volatile("cp.async.bulk.prefetch.L2.global [%0], %1;" ::"l"(src), "r"(bytes) : "memory");
}
__device__ __forceinline__ void st_async4(uint32_t dst, uint32_t a, uint32_t b, uint32_t c, uint32_t d, uint32_t bar) {
    asm volatile("st.async.shared::cluster.mbarrier::complete_tx::bytes.v4.b32 [%0], {%1,%2,%3,%4}, [%5];" ::"r"(dst), "r"(a), "r"(b), "r"(c), "r"(d), "r"(bar) : "memory");
}
__device__ __forceinline__ void put_sums(uint32_t dst, uint32_t rdst, float a, float b, uint32_t rbar, bool on) {
    asm volatile("{\n.reg .pred p;\nsetp.ne.u32 p, %5, 0;\n"
                 "@p st.async.shared::cluster.mbarrier::complete_tx::bytes.v2.f32 [%1], {%2,%3}, [%4];\n"
                 "@p st.shared.v2.f32 [%0], {%2,%3};\n}" ::"r"(dst), "r"(rdst), "f"(a), "f"(b), "r"(rbar), "r"((uint32_t)on) : "memory");
}
__device__ __forceinline__ void stsm4(uint32_t a, uint32_t r0, uint32_t r1, uint32_t r2, uint32_t r3) {
    asm volatile("stmatrix.sync.aligned.m8n8.x4.shared.b16 [%0], {%1,%2,%3,%4};" ::"r"(a), "r"(r0), "r"(r1), "r"(r2), "r"(r3) : "memory");
}
__device__ __forceinline__ void ldsm4(uint32_t a, uint32_t& r0, uint32_t& r1, uint32_t& r2, uint32_t& r3) {
    asm volatile("ldmatrix.sync.aligned.m8n8.x4.shared.b16 {%0,%1,%2,%3}, [%4];" : "=r"(r0), "=r"(r1), "=r"(r2), "=r"(r3) : "r"(a) : "memory");
}
__device__ __forceinline__ uint4 lds128(uint32_t a) { uint4 v; asm volatile("ld.shared.v4.b32 {%0,%1,%2,%3}, [%4];" : "=r"(v.x), "=r"(v.y), "=r"(v.z), "=r"(v.w) : "r"(a) : "memory"); return v; }
__device__ __forceinline__ float4 lds128f(uint32_t a) { float4 v; asm volatile("ld.shared.v4.f32 {%0,%1,%2,%3}, [%4];" : "=f"(v.x), "=f"(v.y), "=f"(v.z), "=f"(v.w) : "r"(a) : "memory"); return v; }
__device__ __forceinline__ float2 lds64f(uint32_t a) { float2 v; asm volatile("ld.shared.v2.f32 {%0,%1}, [%2];" : "=f"(v.x), "=f"(v.y) : "r"(a) : "memory"); return v; }
__device__ __forceinline__ uint32_t lds32(uint32_t a) { uint32_t v; asm volatile("ld.shared.b32 %0, [%1];" : "=r"(v) : "r"(a) : "memory"); return v; }
__device__ __forceinline__ void sts128(uint32_t a, uint32_t x, uint32_t y, uint32_t z, uint32_t w) { asm volatile("st.shared.v4.b32 [%0], {%1,%2,%3,%4};" ::"r"(a), "r"(x), "r"(y), "r"(z), "r"(w) : "memory"); }
__device__ __forceinline__ void sts128f(uint32_t a, float x, float y, float z, float w) { asm volatile("st.shared.v4.f32 [%0], {%1,%2,%3,%4};" ::"r"(a), "f"(x), "f"(y), "f"(z), "f"(w) : "memory"); }
__device__ __forceinline__ void sts64f(uint32_t a, float x, float y) { asm volatile("st.shared.v2.f32 [%0], {%1,%2};" ::"r"(a), "f"(x), "f"(y) : "memory"); }
__device__ __forceinline__ void sts32(uint32_t a, uint32_t x) { asm volatile("st.shared.b32 [%0], %1;" ::"r"(a), "r"(x) : "memory"); }
__device__ __forceinline__ void stg128(void* p, uint4 v) { asm volatile("st.global.v4.b32 [%0], {%1,%2,%3,%4};" ::"l"(p), "r"(v.x), "r"(v.y), "r"(v.z), "r"(v.w) : "memory"); }

__device__ __forceinline__ uint32_t pack2(float lo, float hi) { uint32_t r; asm("cvt.rn.bf16x2.f32 %0, %1, %2;" : "=r"(r) : "f"(hi), "f"(lo)); return r; }
__device__ __forceinline__ float blo(uint32_t v) { return __uint_as_float(v << 16); }
__device__ __forceinline__ float bhi(uint32_t v) { return __uint_as_float(v & 0xffff0000u); }
__device__ __forceinline__ uint32_t hmul2(uint32_t a, uint32_t b) { uint32_t r; asm("mul.rn.bf16x2 %0, %1, %2;" : "=r"(r) : "r"(a), "r"(b)); return r; }
__device__ __forceinline__ uint32_t hadd2(uint32_t a, uint32_t b) { uint32_t r; asm("add.rn.bf16x2 %0, %1, %2;" : "=r"(r) : "r"(a), "r"(b)); return r; }
__device__ __forceinline__ uint32_t hsub2(uint32_t a, uint32_t b) { uint32_t r; asm("sub.rn.bf16x2 %0, %1, %2;" : "=r"(r) : "r"(a), "r"(b)); return r; }
__device__ __forceinline__ uint32_t hfma2(uint32_t a, uint32_t b, uint32_t c) { uint32_t r; asm("fma.rn.bf16x2 %0, %1, %2, %3;" : "=r"(r) : "r"(a), "r"(b), "r"(c)); return r; }
__device__ __forceinline__ float tanh_fast(float x) { float r; asm("tanh.approx.f32 %0, %1;" : "=f"(r) : "f"(x)); return r; }
__device__ __forceinline__ float rsq(float x) { float r; asm("rsqrt.approx.ftz.f32 %0, %1;" : "=f"(r) : "f"(x)); return r; }
__device__ __forceinline__ float rcp(float x) { float r; asm("rcp.approx.ftz.f32 %0, %1;" : "=f"(r) : "f"(x)); return r; }
__device__ __forceinline__ float ex2(float x) { float r; asm("ex2.approx.ftz.f32 %0, %1;" : "=f"(r) : "f"(x)); return r; }

__device__ __forceinline__ uint32_t ld_relaxed(const uint32_t* p) {
    uint32_t v;
    asm volatile("ld.relaxed.gpu.global.u32 %0, [%1];" : "=r"(v) : "l"(p) : "memory");
    return v;
}
__device__ __forceinline__ uint32_t clock32() { uint32_t c; asm volatile("mov.u32 %0, %%clock;" : "=r"(c)::"memory"); return c; }
__device__ __forceinline__ void spin(uint32_t clks) {
    const uint32_t t0 = clock32();
    while (clock32() - t0 < clks) {}
}
__device__ __forceinline__ void flag_wait(const uint32_t* p, uint32_t e, bool mine) {
#pragma unroll 1
    for (int i = 0; i < (1 << 19); i++) {
        if (mine) mine = ld_relaxed(p) != e;
        if (!__any_sync(~0u, mine)) break;
    }
    asm volatile("fence.acquire.gpu;" ::: "memory");
    fence_async_global();
}
__device__ __forceinline__ void st_data(void* p, uint32_t x, uint32_t y, uint32_t z, uint32_t w) {
    asm volatile("st.relaxed.gpu.global.v4.b32 [%0], {%1,%2,%3,%4};" ::"l"(p), "r"(x), "r"(y), "r"(z), "r"(w) : "memory");
}
template <int STRIDE, bool INV = false, int N>
__device__ __forceinline__ void ld_data(uint4 (&v)[N], const unsigned char* p) {
    int it = 0;
    bool again;
#pragma unroll 1
    do {
        uint32_t m = INV ? ~0u : 0u;
#pragma unroll
        for (int i = 0; i < N; i++)
            asm volatile("ld.relaxed.gpu.global.v4.b32 {%0,%1,%2,%3}, [%4];" : "=r"(v[i].x), "=r"(v[i].y), "=r"(v[i].z), "=r"(v[i].w) : "l"(p + i * STRIDE) : "memory");
#pragma unroll
        for (int i = 0; i < N; i++)
            m = INV ? __vimin3_u32(__vimin3_u32(v[i].x, v[i].y, v[i].z), v[i].w, m) : __vimax3_u32(__vimax3_u32(v[i].x, v[i].y, v[i].z), v[i].w, m);
        again = __any_sync(~0u, m == (INV ? 0u : ~0u)) && ++it < (1 << 16);
    } while (again);
}
__device__ __forceinline__ uint32_t ld_epoch() { return ld_relaxed(&g_epoch[blockIdx.x * FS]) + 1; }
__device__ __forceinline__ void flag_set(uint32_t* p, uint32_t e) { asm volatile("st.release.gpu.global.u32 [%0], %1;" ::"l"(p), "r"(e) : "memory"); }

__device__ __forceinline__ uint32_t desc_lo(uint32_t addr) { return ((addr & 0x3FFFF) >> 4) | 0x10000u; }
__device__ __forceinline__ uint64_t mkdesc(uint32_t lo) { return (uint64_t)lo | (0x40000040ull << 32); }
__device__ __forceinline__ void wg_fence() { asm volatile("wgmma.fence.sync.aligned;" ::: "memory"); }
__device__ __forceinline__ void wg_commit() { asm volatile("wgmma.commit_group.sync.aligned;" ::: "memory"); }
template <int N> __device__ __forceinline__ void wg_wait() { asm volatile("wgmma.wait_group.sync.aligned %0;" ::"n"(N) : "memory"); }
template <int N> __device__ __forceinline__ void pin(float (&d)[N]) {
#pragma unroll
    for (int i = 0; i < N; i++) asm volatile("" : "+f"(d[i])::"memory");
}
template <int N> __device__ __forceinline__ void pin(uint32_t (&d)[N]) {
#pragma unroll
    for (int i = 0; i < N; i++) asm volatile("" : "+r"(d[i])::"memory");
}

template <typename Tp, int N> __device__ __forceinline__ void zero(Tp (&d)[N]) {
#pragma unroll
    for (int i = 0; i < N; i++) d[i] = 0;
    pin(d);
}

#define F4(d, i) "+f"(d[i]), "+f"(d[i + 1]), "+f"(d[i + 2]), "+f"(d[i + 3])
#define F16(d, i) F4(d, i), F4(d, i + 4), F4(d, i + 8), F4(d, i + 12)

__device__ __forceinline__ void mma16(float (&d)[4], const uint32_t* a, uint32_t b0, uint32_t b1) {
    asm("mma.sync.aligned.m16n8k16.row.col.f32.bf16.bf16.f32 {%0,%1,%2,%3}, {%4,%5,%6,%7}, {%8,%9}, {%0,%1,%2,%3};"
        : F4(d, 0) : "r"(a[0]), "r"(a[1]), "r"(a[2]), "r"(a[3]), "r"(b0), "r"(b1));
}
template <int N>
__device__ __forceinline__ float row_sum(const uint32_t* x, uint32_t ones = 0x3F803F80u) {
    float c[4] = {};
#pragma unroll
    for (int i = 0; i < N; i += 4) mma16(c, x + i, ones, ones);
    return c[0] + c[2];
}
template <int N>
__device__ __forceinline__ float row_sumsq(const uint32_t* x, int lane) {
    float c0[4] = {}, c1[4] = {};
#pragma unroll
    for (int i = 0; i < N; i += 4) {
        mma16(c0, x + i, x[i], x[i + 2]);
        mma16(c1, x + i, x[i + 1], x[i + 3]);
    }
    return (lane & 4) ? c0[1] + c1[3] : c0[0] + c1[2];
}
__device__ __forceinline__ void mma_sp(float (&d)[32], const uint32_t* a, uint64_t b, uint32_t meta, int acc) {
    asm volatile("{.reg .pred p; setp.ne.b32 p, %38, 0;\n"
                 "wgmma.mma_async.sp.sync.aligned.m64n64k32.f32.bf16.bf16 {%0,%1,%2,%3,%4,%5,%6,%7,%8,%9,%10,%11,%12,%13,%14,%15,%16,%17,%18,%19,%20,%21,%22,%23,%24,%25,%26,%27,%28,%29,%30,%31}, "
                 "{%32,%33,%34,%35}, %36, %37, 0, p, 1, 1, 1;}\n"
                 : F16(d, 0), F16(d, 16) : "r"(a[0]), "r"(a[1]), "r"(a[2]), "r"(a[3]), "l"(b), "r"(meta), "r"(acc));
}
__device__ __forceinline__ void mma_qk(float (&d)[32], uint32_t a0, uint32_t a1, uint32_t a2, uint32_t a3, uint64_t b, int acc) {
    asm volatile("{.reg .pred p; setp.ne.b32 p, %37, 0;\n"
                 "wgmma.mma_async.sync.aligned.m64n64k16.f32.bf16.bf16 {%0,%1,%2,%3,%4,%5,%6,%7,%8,%9,%10,%11,%12,%13,%14,%15,%16,%17,%18,%19,%20,%21,%22,%23,%24,%25,%26,%27,%28,%29,%30,%31}, "
                 "{%32,%33,%34,%35}, %36, p, 1, 1, 0;}\n"
                 : F16(d, 0), F16(d, 16) : "r"(a0), "r"(a1), "r"(a2), "r"(a3), "l"(b), "r"(acc));
}
__device__ __forceinline__ void mma_pv(float (&d)[36], uint32_t a0, uint32_t a1, uint32_t a2, uint32_t a3, uint64_t b) {
    asm volatile("wgmma.mma_async.sync.aligned.m64n72k16.f32.bf16.bf16 {%0,%1,%2,%3,%4,%5,%6,%7,%8,%9,%10,%11,%12,%13,%14,%15,%16,%17,%18,%19,%20,%21,%22,%23,%24,%25,%26,%27,%28,%29,%30,%31,%32,%33,%34,%35}, "
                 "{%36,%37,%38,%39}, %40, 1, 1, 1, 1;\n"
                 : F16(d, 0), F16(d, 16), F4(d, 32) : "r"(a0), "r"(a1), "r"(a2), "r"(a3), "l"(b));
}

__device__ __forceinline__ uint32_t load_code(int n, int r, int w) {
    const int tile = 2 * r + w;
    int m, col, row;
    if (n < 16 || n >= 38) {
        const int k = n < 16 ? n : n - 38;
        m = n < 16 ? 0 : 6;
        if (n >= 38 && k < 4) { col = 4 * tile + (k & 1); row = (k >> 1) ^ r; }
        else if (k < 8) { col = 4 * tile + (k >> 1); row = n < 16 ? (k & 1) : (k & 1) ^ r; }
        else { m++; col = k < 12 ? tile ^ 2 : tile; row = 2 * (tile ^ (k & 1)) + ((k >> 1) & 1); }
    } else if (n < 30) {
        const int k = n - 16;
        m = 2;
        if (k < 4) { col = tile + ((k & 1) ? 8 : 4); row = (k >> 1) ^ r; }
        else { col = tile; row = (k & 1) ^ r; }
    } else if (n < 32) { m = 3; col = tile; row = n - 30; }
    else if (n < 36) { const int k = n - 32; m = 4; col = tile + 4 * (k & 1); row = (k >> 1) ^ r; }
    else { m = 5; col = tile; row = (n & 1) ^ r; }
    return m | (col << 4) | (row << ((m == 0 || m == 3) ? 10 : 11));
}

__global__ void __cluster_dims__(2, 1, 1) __launch_bounds__(NTHREADS, 1)
conformer_kernel(const Scalars p, const __grid_constant__ Maps m) {
    extern __shared__ __align__(1024) unsigned char smem_raw[];
    const uint32_t sb = smem_u32(smem_raw);
    const uint32_t bars = sb + OFF_BARS;
    const int tid = threadIdx.x;
    const int lane = tid & 31;
    const int warp = __shfl_sync(~0u, tid >> 5, 0);
    const int r = blockIdx.x & 1;
    const int pair = blockIdx.x >> 1;
    const int b = pair >> 5, pt = pair & 31;
    const int ah = pt >> 3, qt = (pt & 7) * 2 + r;
    const int abh = b * 4 + ah;

    TG(30);
    TSINIT();
    TS(0);
    const uint32_t P = sb + OFF_P, H = sb + OFF_H;
    if (warp == 11) {
        if (lane == 0) {
#pragma unroll
            for (int i = 0; i < 2 * NSLOT; i++) mbar_init(bars + (B_FULL + i) * 8, 1);
            asm volatile("fence.mbarrier_init.release.cluster;" ::: "memory");
            fence_async_smem();
        }
        __syncwarp();
        bar_arrive(13, 96);
        cluster_arrive();
    }

    if (warp >= 8) {
        asm volatile("setmaxnreg.dec.sync.aligned.u32 48;");
        if (warp >= 12) {
            cluster_arrive();
            const int ut = tid & 127;
            cluster_wait();
            const uint32_t target = ld_epoch() * 64;
            bar_sync(6, 384);
#pragma unroll
            for (int i = 0; i < 4; i++) {
                st_data(g_o + (size_t)(b * 128 + qt * 8 + 2 * i + (ut >> 6)) * 4096 + ah * 1024 + (ut & 63) * 16, ~0u, ~0u, ~0u, ~0u);
                if (i < 2) st_data(&g_halo[(pair * 4 + 2 * r + i) * 128 + ut], ~0u, ~0u, ~0u, ~0u);
            }
            bar_sync(11, 128);
            if (ut == 0) {
                asm volatile("red.release.gpu.global.add.u32 [%0], 1;" ::"l"(&g_reset[b * 32]) : "memory");
#pragma unroll 1
                for (int i = 0; i < (1 << 20) && ld_relaxed(&g_reset[b * 32]) != target; i++) __nanosleep(100);
                asm volatile("fence.acquire.gpu;" ::: "memory");
                mbar_arrive(bars + B_RST * 8);
            }
            bar_sync(11, 128);
            TS(14);
#pragma unroll
            for (int i = 0; i < 4; i++) st_data(g_kvq + 2097152 + (size_t)(abh * 1024 + qt * 64) * 128 + i * 2048 + ut * 16, 0, 0, 0, 0);
            const int side = warp & 1, wg = (warp >> 1) & 1, np = side ? pt + 1 : pt - 1;
            const unsigned char* src = reinterpret_cast<const unsigned char*>(&g_halo[(((b * 32 + np) * 4 + 2 * r + wg) * 2 + (side ^ 1)) * 64 + lane]);
            const uint32_t dst = P + wg * GCH + side * 5120 + (lane & 7) * 128 + (((lane >> 3) ^ (lane & 7)) << 4);
            uint4 hv[2] = {make_uint4(0, 0, 0, 0), make_uint4(0, 0, 0, 0)};
            bar_sync(8 + wg, 192);
            if (np >= 0 && np < 32) {
                spin(HDELAY);
                ld_data<512>(hv, src);
            }
            stsm4(dst, hv[0].x, hv[0].y, hv[0].z, hv[0].w);
            stsm4(dst ^ 64, hv[1].x, hv[1].y, hv[1].z, hv[1].w);
            __syncwarp();
            if (lane == 0) mbar_arrive(bars + (B_HALO + (warp & 3)) * 8);
            TS(4);
        } else if (warp < 10) {
            const int w = warp - 8;
            const uint32_t ring = sb + OFF_RING + w * NSLOT * SLOT;
            const uint32_t full = bars + (B_FULL + w * NSLOT) * 8;
            cluster_arrive();
            bar_sync(13, 96);
            TS(1);
#pragma unroll
            for (int n = 0; n < NSLOT; n++) {
                if (n == 1) bar_sync(12, 64);
                ring_load(ring + n * SLOT, &m.tm[0], 64 * (8 * r + 4 * w + (n >> 1)), 4 * (n & 1), full + n * 8);
            }
            TS(2);
            const uint32_t code = load_code(lane, r, w) | (load_code(lane + 32, r, w) << 16);
            cluster_wait();
            uint32_t s = 0, ph = 0;
            int n = NSLOT;
#pragma unroll 1
            for (int seg = 0; seg < 2; seg++) {
#pragma unroll 1
                for (; n < (seg == 0 ? 22 : NLOADS); n++) {
                    const uint32_t c = __shfl_sync(~0u, code, n) >> (n & 32 ? 16 : 0);
                    const CUtensorMap* tm = &m.tm[c & 15];
                    const uint32_t col = (c & 0xf0) * 4, row = (c & 0xff00) >> 8, dst = ring + s * SLOT;
                    mbar_wait(full + (B_EMPTY - B_FULL) * 8 + s * 8, ph + (((uint32_t)(size_t)tm | col | row | dst) & p.zero));
                    ring_load(dst, tm, col, row, full + s * 8);
                    if (++s == NSLOT) { s = 0; ph ^= 1; }
                }
                if (seg == 1) break;
                const uint32_t epoch = ld_epoch();
                const uint32_t rdy = bars + (B_RDY + 2 * w) * 8, prdy = mapa(rdy, r ^ 1);
                const int odd = r ^ w;
                const uint32_t* flags = g_flag_kv + (abh * 32 + lane) * FS;
                bool first = (lane >> 2) == 2 * odd + w;
                if (first) first = ld_relaxed(flags) != epoch;
                auto kv_load = [&](uint32_t sl, int isv, int i) {
                    ring_load_both(ring + sl * SLOT, &m.tm[8], (isv * 64 + abh * 8 + 2 * i + w) * 128, full + sl * 8);
                };
                if (lane < NSLOT) {
                    mbar_wait(full + (B_EMPTY - B_FULL + lane) * 8, lane < 4);
                    mbar_arrive_tx(full + lane * 8, SLOT);
                }
                __syncwarp();
                if (lane == 0) mbar_arrive_peer(prdy);
                bar_sync(14, 96);
                spin(KDELAY);
                mbar_wait(rdy, 0);
                flag_wait(flags, epoch, first);
                TSW(5 + 2 * odd);
                if (!odd) { kv_load(4, 0, 0); bar_arrive(12, 64); }
                else bar_sync(12, 64);
                spin(w ? KD3 : KD2);
                kv_load(odd ? 5 : 0, odd ^ 1, odd);
                flag_wait(flags, epoch, (lane >> 2) == 2 * odd + w + 4);
                mbar_wait(full + (odd ? 5 : 0) * 8, odd);
                kv_load(1 + odd, odd, 2 - odd);
                if (odd) { mbar_wait(full + 16, 0); kv_load(3, 0, 3); }
#pragma unroll 1
                for (int i = 0; i < 2; i++) {
                    mbar_wait(full + (B_EMPTY - B_FULL + 4 + i) * 8, 1);
                    if (lane == 0) mbar_arrive_tx(full + (4 + i) * 8, SLOT);
                    if (i == odd) {
                        mbar_wait(rdy + 8, 0);
                        kv_load(4 + i, 1, 2 + i);
                    } else if (lane == 0) mbar_arrive_peer(prdy + 8);
                    __syncwarp();
                }
                n = 30; s = 0; ph = 0;
            }
        } else if (warp == 10) {
            if (lane == 0) {
#pragma unroll
                for (int i = B_EMPTY; i < NBARS; i++) mbar_init(bars + i * 8, i < B_XA ? 4 : 1);
#pragma unroll
                for (int i = B_XA; i <= B_SR; i++) mbar_arrive_tx(bars + i * 8, i < B_XB ? 512 : ((i >= B_INB && i < B_SR) ? 4096 : 8192));
                asm volatile("fence.mbarrier_init.release.cluster;" ::: "memory");
                fence_async_smem();
            }
            __syncwarp();
            cluster_arrive();
            cluster_wait();
            float ka[4] = {};
            const uint32_t kz[4] = {p.zero, p.zero, p.zero, p.zero};
#pragma unroll 1
            for (int i = 0; i < 4096 && !mbar_test(bars + (B_XA + 3) * 8, __float_as_uint(ka[0])); i++) {
                mma16(ka, kz, p.zero, p.zero);
                __nanosleep(250);
            }
        } else {
            const uint32_t kb = (lane < 2 || lane > 5) ? 4096 : (lane == 2 ? 3072 : (lane == 4 ? 2048 : 1024));
            const char* pf = m.w[lane & 7] + blockIdx.x * kb;
            cluster_wait();
            mbar_wait(bars + B_FULL * 8, 0);
            if (lane < 3) prefetch_l2(pf, kb);
            if (lane >= 1 && lane < 9) asm volatile("prefetch.tensormap [%0];" ::"l"(&m.tm[lane]) : "memory");
            mbar_wait(bars + (B_FULL + 1) * 8, 1);
            if (lane > 2 && lane < 8) prefetch_l2(pf, kb);
            if (lane == 8 && blockIdx.x < 15) prefetch_l2(p.dw + blockIdx.x * 256, 512);
            const uint32_t epoch = ld_epoch();
            bar_sync(4, 288);
            if (lane < 16) flag_set(&g_flag_kv[((b * 4 + 2 * r + (lane >> 3)) * 32 + pt) * FS + (lane & 7)], epoch);
            __syncwarp();
            bar_arrive(14, 96);
            TSW(8);
        }
        TSDUMP();
        return;
    }

    const int w = warp >> 2, wq = warp & 3;
    const int tile = 2 * r + w;
    const int wt = tid & 127;
    const int c4 = lane & 3;
    const int trow = pt * 32 + 8 * wq;
    uint32_t xr[8];
    uint32_t a[32];
    const char* xrow = reinterpret_cast<const char*>(p.x) + (b * T_ + trow + (lane >> 2)) * 512;
    zero(a);
    if (trow < T_) {
        const char* src = xrow + c4 * 16 + p.zero;
#pragma unroll
        for (int i = 0; i < 8; i++)
            asm volatile("ld.global.nc.v4.b32 {%0,%1,%2,%3}, [%4];" : "=r"(a[4 * i]), "=r"(a[4 * i + 1]), "=r"(a[4 * i + 2]), "=r"(a[4 * i + 3]) : "l"(src + 64 * i));
    }
    cluster_arrive();
    asm volatile("setmaxnreg.inc.sync.aligned.u32 208;");
    const uint32_t rbase = sb + OFF_RING + w * NSLOT * SLOT, fbar = bars + (B_FULL + w * NSLOT) * 8;
    const uint32_t rdesc = desc_lo(rbase);
    auto acq = [&](int n) { mbar_wait(fbar + (n % NSLOT) * 8, (n / NSLOT) & 1); };
    auto rel = [&](int n) { if (lane == 0) mbar_arrive(fbar + (B_EMPTY - B_FULL + n % NSLOT) * 8); };
    const uint32_t foff = (lane & 7) * 128 + (((lane >> 3) ^ (lane & 7)) << 4);
    float v[16];
    const uint32_t xown = __shfl_sync(~0u, P + wt * 16 + tile * 4096, lane), xrem = __shfl_sync(~0u, P + wt * 16 + (r ^ 1) * 8192, lane);
    const uint32_t sbuf = __shfl_sync(~0u, sb + OFF_MISC + (8 * wq + (lane >> 2)) * 32, lane);
    const uint32_t sown = __shfl_sync(~0u, sbuf + tile * 8, lane);
    const uint32_t peer = __shfl_sync(~0u, mapa(sb, r ^ 1) - sb, lane);
    const uint32_t hbuf = __shfl_sync(~0u, H + w * 4096 + wt * 16, lane);
    const uint32_t meta = __shfl_sync(~0u, 0xEEEE4444u + p.zero, lane);
    cluster_wait();
    TS(56);
    float mean, msq;
    const int mir = wq < 2 ? 7 : 0;
    uint32_t dwr[15];

    auto phase = [&](auto phc) __attribute__((always_inline)) {
        constexpr int ph = decltype(phc)::value;
        uint4 o0, o1;
        if (ph == 0) {
            const uint32_t one = 0x3F803F80u + ((xown | xrem | sbuf | sown | hbuf | foff | rdesc | fbar) & p.zero);
            mean = ((row_sum<8>(a, one) + row_sum<8>(a + 8, one)) + (row_sum<8>(a + 16, one) + row_sum<8>(a + 24, one))) * (1.f / 256.f);
            TS(57);
        } else {
            const uint32_t xa = bars + (B_XA + ph) * 8;
#pragma unroll
            for (int j = 0; j < 8; j++) xr[j] = pack2(v[2 * j], v[2 * j + 1]);
            const float s = row_sum<8>(xr), q = row_sumsq<8>(xr, lane);
            if (ph < 4) {
                sts128(xown, xr[0], xr[1], xr[2], xr[3]);
                sts128(xown + 2048, xr[4], xr[5], xr[6], xr[7]);
            }
            put_sums(sown, sown + peer, s, q, xa + peer, c4 == (lane >> 3));
            bar_sync(10, 256);
            if (ph < 4) {
                o0 = lds128(xown ^ 4096); o1 = lds128((xown ^ 4096) + 2048);
                st_async4(xown + peer, xr[0], xr[1], xr[2], xr[3], xa + (B_XB - B_XA) * 8 + peer);
                st_async4(xown + peer + 2048, xr[4], xr[5], xr[6], xr[7], xa + (B_XB - B_XA) * 8 + peer);
            }
            TS(57 + ph);
            if (ph == 3) acq(38);
            if (ph == 1) acq(16);
            mbar_wait(xa, 0);
            const float4 u0 = lds128f(sbuf), u1 = lds128f(sbuf + 16);
            mean = ((u0.x + u0.z) + (u1.x + u1.z)) * (1.f / 256.f);
            msq = ((u0.y + u0.w) + (u1.y + u1.w)) * (1.f / 256.f);
        }
        if (ph == 4) return;
        const uint32_t mean2 = pack2(mean, mean);
        auto centre = [&](int i, const uint4& u) {
            a[i] = hsub2(u.x, mean2); a[i + 1] = hsub2(u.y, mean2); a[i + 2] = hsub2(u.z, mean2); a[i + 3] = hsub2(u.w, mean2);
        };
        if (ph == 0) {
#pragma unroll
            for (int j = 0; j < 32; j++) a[j] = hsub2(a[j], mean2);
            zero(xr);
            if (trow < T_) {
                const char* src = xrow + tile * 128 + c4 * 4 + (mean2 & p.zero);
#pragma unroll
                for (int j = 0; j < 8; j++) asm volatile("ld.global.nc.b32 %0, [%1];" : "=r"(xr[j]) : "l"(src + 16 * j));
            }
            mean -= blo(mean2);
            msq = __shfl_sync(~0u, row_sumsq<16>(a, lane) + row_sumsq<16>(a + 16, lane), (lane & 28) + (lane >> 3)) * (1.f / 256.f);
            acq(0);
        } else {
#pragma unroll
            for (int j = 0; j < 8; j++) a[j] = hsub2(xr[j], mean2);
            centre(8, o0); centre(12, o1);
        }
        const float rstd = rsq(fmaxf(fmaf(-mean, mean, msq), 0.f) + 1e-5f);
        auto gather_peer = [&]() {
            mbar_wait(bars + (B_XB + ph) * 8, 0);
#pragma unroll
            for (int i = 0; i < 4; i++) centre(16 + 4 * i, lds128(xrem + i * 2048));
        };
        auto sp = [&](float (&d)[32], int n, const uint32_t* af, int flip, int acc) {
            const uint32_t lo = rdesc + p.zero * (ph * 64 + n + 1) + (n % NSLOT) * (SLOT >> 4);
            const uint64_t b0 = mkdesc(lo + flip * 512), b1 = mkdesc(lo + (flip ^ 1) * 512);
            wg_fence();
            mma_sp(d, af, b0, meta, acc);
            mma_sp(d, af + 4, b0 + 256, meta, 1);
            mma_sp(d, af + 8, b1, meta, 1);
            mma_sp(d, af + 12, b1 + 256, meta, 1);
            wg_commit();
        };
        float d0[32], d1[32];

        if (ph == 0 || ph == 3) {
            uint32_t h[32], ho[32];
            const float rs = 0.5f * rstd;
            const uint32_t inb = bars + (B_INB + (ph & 2) + w) * 8;
            bool ready = true;
            const int eager = ph ? 0x5a : 0x54;
            auto step = [&](float (&d)[32], int n, const uint32_t* af, int flip, int acc, auto work) {
                const int l = n + (ph ? 38 : 0);
                if (!ready) acq(l);
                sp(d, l, af, flip, acc);
                if (n < 15) ready = mbar_test(fbar + ((l + 1) % NSLOT) * 8, ((l + 1) / NSLOT) & 1);
                wg_wait<1>();
                if (n > 0 && !((eager >> (n - 1)) & 1)) rel(l - 1);
                const uint32_t tie = work() & p.zero;
                if ((eager >> n) & 1) {
                    if (p.zero < l + 1) wg_wait<0>();
                    if (lane == 0) mbar_arrive(fbar + (B_EMPTY - B_FULL + l % NSLOT) * 8 + tie);
                }
            };
            auto none = []() { return 0u; };
            const int fl = ph ? w : 0;
            auto fetch = [&](int i) {
                bar_sync(10, 256);
                const uint32_t src = ((i & 1) ? hbuf : xown) ^ 4096;
                const uint4 u0 = lds128(src), u1 = lds128(src + 2048);
                ho[8 * i] = u0.x; ho[8 * i + 1] = u0.y; ho[8 * i + 2] = u0.z; ho[8 * i + 3] = u0.w;
                ho[8 * i + 4] = u1.x; ho[8 * i + 5] = u1.y; ho[8 * i + 6] = u1.z; ho[8 * i + 7] = u1.w;
                return u0.x | u1.x;
            };
            auto act = [&](float (&d)[32], int i) {
                if (i > 0) fetch(i - 1);
                else if (ph) bar_sync(10, 256);
                pin(d);
#pragma unroll
                for (int j = 0; j < 8; j++) {
                    const float u0 = (d[4 * j] + d[4 * j + 2]) * rs, u1 = (d[4 * j + 1] + d[4 * j + 3]) * rs;
                    h[8 * i + j] = pack2(fmaf(u0, tanh_fast(u0), u0), fmaf(u1, tanh_fast(u1), u1));
                }
                sts128((i & 1) ? hbuf : xown, h[8 * i], h[8 * i + 1], h[8 * i + 2], h[8 * i + 3]);
                sts128(((i & 1) ? hbuf : xown) + 2048, h[8 * i + 4], h[8 * i + 5], h[8 * i + 6], h[8 * i + 7]);
                return 0u;
            };
            TS(1 + (ph & 2) * 10);
            if (ph) {
                step(d0, 0, a, fl, 0, none);
                step(d1, 1, a, fl, 0, [&]() { gather_peer(); return 0u; });
                TS(32);
                step(d0, 2, a + 16, 0, 1, none);
                step(d1, 3, a + 16, 0, 1, [&]() { return act(d0, 0); });
            } else {
                step(d0, 0, a, fl, 0, none);
                TS(32);
                step(d0, 1, a + 16, 0, 1, none);
                step(d1, 2, a, fl, 0, [&]() { return act(d0, 0); });
                step(d1, 3, a + 16, 0, 1, none);
            }
            step(d0, 4, a, fl, 0, [&]() { return act(d1, 1); });
            TS(33);
            step(d0, 5, a + 16, 0, 1, none);
            step(d1, 6, a, fl, 0, [&]() { return act(d0, 2); });
            step(d1, 7, a + 16, 0, 1, none);
            step(d0, 8, h, 0, 0, [&]() { act(d1, 3); return fetch(3); });
            TS(2 + (ph & 2) * 10);
            step(d0, 9, ho, 0, 1, none);
            step(d0, 10, h + 16, 0, 1, none);
            step(d0, 11, ho + 16, 0, 1, none);
            uint32_t pk[8];
            auto pack_out = [&]() {
                pin(d0);
#pragma unroll
                for (int j = 0; j < 8; j++) pk[j] = pack2(d0[4 * j] + d0[4 * j + 2], d0[4 * j + 1] + d0[4 * j + 3]);
            };
            auto send = [&](int i) { st_async4(hbuf + 8192 + i * 2048 + peer, pk[4 * i], pk[4 * i + 1], pk[4 * i + 2], pk[4 * i + 3], inb + peer); };
            step(d1, 12, h, 0, 0, [&]() { pack_out(); send(0); return 0u; });
            TS(34);
            step(d1, 13, ho, 0, 1, [&]() { send(1); return 0u; });
            step(d1, 14, h + 16, 0, 1, none);
            step(d1, 15, ho + 16, 0, 1, none);
            mbar_wait(inb, 0);
#pragma unroll
            for (int i = 0; i < 2; i++) {
                const uint4 u = lds128(hbuf + 8192 + i * 2048);
                const uint32_t p0[4] = {u.x, u.y, u.z, u.w};
#pragma unroll
                for (int j = 0; j < 4; j++) {
                    v[8 * i + 2 * j] = fmaf(0.5f, blo(p0[j]), blo(xr[4 * i + j]));
                    v[8 * i + 2 * j + 1] = fmaf(0.5f, bhi(p0[j]), bhi(xr[4 * i + j]));
                }
            }
            wg_wait<0>();
            pin(d1);
            if (ph == 0) rel(15);
            TS(3 + (ph & 2) * 10);
#pragma unroll
            for (int j = 0; j < 8; j++) {
                v[2 * j] = fmaf(0.5f, d1[4 * j] + d1[4 * j + 2], v[2 * j]);
                v[2 * j + 1] = fmaf(0.5f, d1[4 * j + 1] + d1[4 * j + 3], v[2 * j + 1]);
            }
            return;
        }

        auto residual = [&](int n) {
            wg_wait<1>();
            rel(n);
            wg_wait<0>();
            pin(d0);
            rel(n + 1);
#pragma unroll
            for (int j = 0; j < 8; j++) {
                v[2 * j] = d0[4 * j] + d0[4 * j + 2] + blo(xr[j]);
                v[2 * j + 1] = d0[4 * j + 1] + d0[4 * j + 3] + bhi(xr[j]);
            }
        };

        if (ph == 2) {
            TS(39);
            sp(d0, 32, a, w, 0);
            acq(33);
            sp(d1, 33, a, w, 0);
            acq(34); acq(35);
            gather_peer();
            sp(d0, 34, a + 16, 0, 1);
            sp(d1, 35, a + 16, 0, 1);
            wg_wait<2>();
            rel(32);
            acq(36);
            bar_sync(10, 256);
            const float rs = trow < T_ ? 0.5f * rstd : 0.f;
            wg_wait<0>();
            pin(d0); pin(d1);
            TS(18);
            uint32_t pk[8];
#pragma unroll
            for (int j = 0; j < 8; j++) {
                const float u0 = (d0[4 * j] + d0[4 * j + 2]) * rs, u1 = (d0[4 * j + 1] + d0[4 * j + 3]) * rs;
                const float t0 = tanh_fast((d1[4 * j] + d1[4 * j + 2]) * rs), t1 = tanh_fast((d1[4 * j + 1] + d1[4 * j + 3]) * rs);
                pk[j] = pack2(fmaf(u0, t0, u0), fmaf(u1, t1, u1));
            }
            if (wq == 0 || wq == 3) {
                uint4* hp = &g_halo[((pair * 4 + tile) * 2 + (wq & 1)) * 64 + lane];
                st_data(hp, pk[0], pk[1], pk[2], pk[3]);
                st_data(hp + 32, pk[4], pk[5], pk[6], pk[7]);
            }
            const uint32_t gs = P + w * GCH + wq * 1024;
            stsm4(gs + 1024 + foff, pk[0], pk[1], pk[2], pk[3]);
            stsm4(gs + 1024 + (foff ^ 64), pk[4], pk[5], pk[6], pk[7]);
            bar_sync(8 + w, 192);
            TS(26);
            uint32_t ca[8], cb[8];
            const int e = (wq & 1) * 4;
            const uint32_t lo = ((mir ^ e) * 144) ^ (lane * 4);
            const int dir = mir ? -1024 : 1024;
            const uint32_t gb = P + w * GCH + (mir ? 3072 : 2048) + lo, sown_ = H + tile * HCH, so = sown_ + (mir ? 1024 : 2048) + lo;
            auto finish = [&](int i) {
                const uint32_t c = hadd2(ca[i], cb[i]);
                const float h0 = blo(c), h1 = bhi(c);
                const uint32_t dst = (so + (i >> 2) * dir) ^ ((i & 3) * 144), val = pack2(fmaf(h0, tanh_fast(h0), h0), fmaf(h1, tanh_fast(h1), h1));
                asm volatile("st.async.shared::cluster.mbarrier::complete_tx::bytes.b32 [%0], %1, [%2];" ::"r"(dst + peer), "r"(val), "r"(bars + B_SR * 8 + peer) : "memory");
                sts32(dst, val);
            };
#pragma unroll
            for (int k = 0; k < 26; k++) {
                if (k == 19) {
#pragma unroll
                    for (int i = 0; i < 4; i++) finish(i);
                    mbar_wait(bars + (B_HALO + 2 * w + (wq >> 1)) * 8, 0);
                    rel(33); rel(34); rel(35);
                    TS(27);
                }
                const uint32_t g = lds32((gb + (((k + 1) & 4) ? ((k + 1) >> 3) + (wq & 1) : ((k + 1) >> 3)) * dir) ^ (((k + 1) & 7) * 144));
#pragma unroll
                for (int i = 0; i < 8; i++) {
                    const int tap = k - (i & 3) - 2 * (i & 4);
                    if (tap == 0) ca[i] = hmul2(g, dwr[0]);
                    else if (tap > 0 && tap < 8) ca[i] = hfma2(g, dwr[tap], ca[i]);
                    else if (tap == 8) cb[i] = hmul2(g, dwr[8]);
                    else if (tap > 8 && tap < 15) cb[i] = hfma2(g, dwr[tap], cb[i]);
                }
            }
#pragma unroll
            for (int i = 4; i < 8; i++) finish(i);
            bar_sync(10, 256);
            TS(19);
            auto frags = [&](int i, int half) {
                const uint32_t src = H + 2 * half * HCH + wq * 1024;
#pragma unroll
                for (int k = 0; k < 4; k++) ldsm4(src + (k >> 1) * HCH + (foff ^ ((k & 1) * 64)), a[i + 4 * k], a[i + 4 * k + 1], a[i + 4 * k + 2], a[i + 4 * k + 3]);
            };
            frags(0, r);
            sp(d0, 36, a, 0, 0);
            acq(37);
            mbar_wait(bars + B_SR * 8, 0);
            frags(16, r ^ 1);
            sp(d0, 37, a + 16, 0, 1);
            residual(36);
            TS(20);
            return;
        }

        {
            TS(11);
            unsigned char* g = g_kvq + (size_t)((b * 4 + tile) * 1024 + trow) * 128;
            const uint32_t uo = (lane >> 2) * 128 + ((c4 ^ (lane >> 2)) << 4);
            auto put = [&](float (&d)[32], int i) {
                pin(d);
                uint32_t pk[8];
#pragma unroll
                for (int j = 0; j < 8; j++) pk[j] = pack2((d[4 * j] + d[4 * j + 2]) * rstd, (d[4 * j + 1] + d[4 * j + 3]) * rstd);
                if (i < 2) {
                    stg128(g + i * 1048576 + uo, make_uint4(pk[0], pk[1], pk[2], pk[3]));
                    stg128(g + i * 1048576 + (uo ^ 64), make_uint4(pk[4], pk[5], pk[6], pk[7]));
                } else {
                    const uint32_t stg = H + warp * 1024;
                    sts128(stg + uo, pk[0], pk[1], pk[2], pk[3]);
                    sts128(stg + (uo ^ 64), pk[4], pk[5], pk[6], pk[7]);
                    __syncwarp();
                    ldsm4(stg + foff, pk[0], pk[1], pk[2], pk[3]);
                    ldsm4(stg + (foff ^ 64), pk[4], pk[5], pk[6], pk[7]);
                    st_data(g + 2097152 + lane * 16, ~pk[0], ~pk[1], ~pk[2], ~pk[3]);
                    st_data(g + 2097152 + 512 + lane * 16, ~pk[4], ~pk[5], ~pk[6], ~pk[7]);
                }
            };
            sp(d0, 16, a, w, 0);
            acq(17);
            sp(d1, 17, a, w, 0);
            gather_peer();
            acq(18);
            sp(d0, 18, a + 16, 0, 1);
            wg_wait<1>();
            rel(16); rel(17);
            acq(19);
            sp(d1, 19, a + 16, 0, 1);
            wg_wait<1>();
            rel(18);
            put(d0, 0);
            wg_wait<0>();
            rel(19);
            TS(37);
            put(d1, 1);
            bar_arrive(4, 288);
            TS(38);
            acq(20);
            sp(d0, 20, a, w, 0);
            acq(21);
            sp(d0, 21, a + 16, 0, 1);
            wg_wait<0>();
            rel(20); rel(21);
            put(d0, 2);
            TS(12);
        }

        {
            constexpr float CS = 0.125f * 1.4426950408889634f;
            float sa[32], sb2[32], o[36];
            uint32_t pa[16], pb[16], q[16];
            float n0 = INFINITY, n1 = INFINITY;
            zero(o); zero(pa); zero(pb); zero(sb2);
            const uint32_t ones = H + 8192;
            { const uint32_t c = w ? 0u : 0x3F803F80u; sts128(ones + tid * 16, c, c, c, c); }
            fence_async_smem();
            bar_sync(10, 256);
            const uint32_t vdesc = rdesc + ((((ones - rbase) >> 4) - 1) << 16);
            auto qk_issue = [&](float (&s)[32], uint32_t lo) {
                const uint64_t kd = mkdesc(lo);
                wg_fence();
#pragma unroll
                for (int k = 0; k < 4; k++) mma_qk(s, q[4 * k], q[4 * k + 1], q[4 * k + 2], q[4 * k + 3], kd + 2 * k, k != 0);
                wg_commit();
            };
            auto both_issue = [&](float (&s)[32], uint32_t klo, uint32_t (&pp)[16], uint32_t vlo) {
                const uint64_t kd = mkdesc(klo), vd = mkdesc(vlo);
                wg_fence();
#pragma unroll
                for (int k = 0; k < 4; k++) {
                    mma_pv(o, pp[4 * k], pp[4 * k + 1], pp[4 * k + 2], pp[4 * k + 3], vd - k * (128 * 65535));
                    mma_qk(s, q[4 * k], q[4 * k + 1], q[4 * k + 2], q[4 * k + 3], kd + 2 * k, k != 0);
                }
                wg_commit();
            };
            auto new_max = [&](float (&s)[32], int nj, float& x0, float& x1) {
                x0 = s[0]; x1 = s[2];
#pragma unroll
                for (int j = 0; j < nj; j++) {
                    x0 = fmaxf(x0, fmaxf(s[4 * j], s[4 * j + 1]));
                    x1 = fmaxf(x1, fmaxf(s[4 * j + 2], s[4 * j + 3]));
                }
                x0 = fmaxf(x0, __shfl_xor_sync(~0u, x0, 1)); x1 = fmaxf(x1, __shfl_xor_sync(~0u, x1, 1));
                x0 = fmaxf(x0, __shfl_xor_sync(~0u, x0, 2)); x1 = fmaxf(x1, __shfl_xor_sync(~0u, x1, 2));
                x0 = fminf(n0, fmaf(x0, -CS, -20.f)); x1 = fminf(n1, fmaf(x1, -CS, -20.f));
            };
            auto probs = [&](float (&s)[32], uint32_t (&pp)[16], bool ready, bool tail, auto wait) {
                uint32_t any = 0;
#pragma unroll
                for (int i = 0; i < 16; i++) {
                    pp[i] = pack2(ex2(fmaf(s[2 * i], CS, (i & 1) ? n1 : n0)), ex2(fmaf(s[2 * i + 1], CS, (i & 1) ? n1 : n0)));
                    any |= pp[i];
                }
                wg_wait<0>();
                pin(sa); pin(sb2); pin(o); pin(pa); pin(pb);
                if (__builtin_expect(__any_sync(~0u, (any & 0x40004000u) || !ready), 0)) {
                    wait();
                    if (__any_sync(~0u, any & 0x40004000u)) {
                        if (tail) {
#pragma unroll
                            for (int i = 20; i < 32; i++) s[i] = -INFINITY;
                        }
                        float x0, x1;
                        new_max(s, 8, x0, x1);
                        const float sc0 = ex2(x0 - n0), sc1 = ex2(x1 - n1);
                        n0 = x0; n1 = x1;
#pragma unroll
                        for (int j = 0; j < 9; j++) { o[4 * j] *= sc0; o[4 * j + 1] *= sc0; o[4 * j + 2] *= sc1; o[4 * j + 3] *= sc1; }
#pragma unroll
                        for (int i = 0; i < 16; i++)
                            pp[i] = pack2(ex2(fmaf(s[2 * i], CS, (i & 1) ? n1 : n0)), ex2(fmaf(s[2 * i + 1], CS, (i & 1) ? n1 : n0)));
                    }
                }
            };
            {
                uint4 u[4];
                const unsigned char* src = g_kvq + 2097152 + (size_t)(abh * 1024 + qt * 64 + wq * 16) * 128 + lane * 16;
                spin(QGATE);
                ld_data<512, true>(u, src);
#pragma unroll
                for (int k = 0; k < 2; k++) {
                    q[8 * k] = ~u[k].x; q[8 * k + 1] = ~u[k + 2].x; q[8 * k + 2] = ~u[k].y; q[8 * k + 3] = ~u[k + 2].y;
                    q[8 * k + 4] = ~u[k].z; q[8 * k + 5] = ~u[k + 2].z; q[8 * k + 6] = ~u[k].w; q[8 * k + 7] = ~u[k + 2].w;
                }
                pin(q);
            }
            TS(40);
            acq(22);
            TS(13);
            qk_issue(sa, rdesc + (22 % NSLOT) * (SLOT >> 4));
            wg_wait<0>();
            pin(sa);
            {
                float x0, x1;
                new_max(sa, 2, x0, x1);
                n0 = x0; n1 = x1;
            }
            bar_arrive(6, 384);
            uint32_t vd = vdesc, kd = rdesc + 5 * (SLOT >> 4), vb = fbar, kb = fbar + 40;
            uint32_t vlast = vdesc - 4 * (SLOT >> 4) * 65535u, klast = rdesc + 4 * (SLOT >> 4) + 512;
            uint32_t kprev = fbar + 32, vprev = bars + (B_SINK - (B_EMPTY - B_FULL)) * 8;
#pragma unroll 1
            for (int it = 0; it < 4; it++) {
                both_issue(sb2, klast, pb, vlast);
                probs(sa, pa, mbar_test(vb, 0) & mbar_test(kb, it == 0), false, [&]() { mbar_wait(vb, 0); mbar_wait(kb, it == 0); });
                TS(41 + it * 4);
                if (lane == 0) mbar_arrive(kprev + (B_EMPTY - B_FULL) * 8);
                if (lane == 0) mbar_arrive(vprev + (B_EMPTY - B_FULL) * 8);
                both_issue(sa, kd, pa, vd);
                const int dv = it == 2 ? 1 : 2, dk = it == 0 ? -4 : 2;
                kprev = kb; vprev = vb; vlast = vd - 512 * 65535u; klast = kd + 512;
                vd -= dv * (SLOT >> 4) * 65535u; vb += dv * 8;
                kd += dk * (SLOT >> 4); kb += dk * 8;
                probs(sb2, pb, true, it == 3 && w == 1, []() {});
                TS(43 + it * 4);
            }
            wg_fence();
#pragma unroll
            for (int k = 0; k < 4; k++)
                mma_pv(o, pb[4 * k], pb[4 * k + 1], pb[4 * k + 2], pb[4 * k + 3], mkdesc(vlast - k * (128 * 65535) + (k > 1 ? w * ((k - 1) << 22) : 0)));
            wg_commit();
            const uint32_t mlw = sb + OFF_MISC + 1024 + (tid >> 2) * 8;
            unsigned char* odst = g_o + (size_t)(b * 128 + qt * 8 + 2 * wq + w) * 4096 + ah * 1024 + lane * 16;
            mbar_wait(bars + B_RST * 8, __any_sync(~0u, (mlw | (uint32_t)(size_t)odst) & p.zero));
            wg_wait<0>();
            pin(o); pin(pb); pin(sa); pin(sb2);
            rel(29);
            TS(14);
            auto merge = [&](int keep, float nk, float ns) {
                const int snd = 2 - keep;
                if (c4 == 0) sts64f(mlw, ns, o[32 + snd]);
#pragma unroll
                for (int j = 0; j < 2; j++)
                    sts128(hbuf + j * 2048, pack2(o[16 * j + snd], o[16 * j + snd + 1]), pack2(o[16 * j + 4 + snd], o[16 * j + 5 + snd]),
                           pack2(o[16 * j + 8 + snd], o[16 * j + 9 + snd]), pack2(o[16 * j + 12 + snd], o[16 * j + 13 + snd]));
                bar_sync(10, 256);
                const float2 u = lds64f(mlw ^ 256);
                const float x = fminf(nk, u.x);
                float a = ex2(x - nk), c = ex2(x - u.x);
                const float inv = rcp(fmaf(a, o[32 + keep], c * u.y));
                a *= inv; c *= inv;
                uint32_t pk[8];
#pragma unroll
                for (int j = 0; j < 2; j++) {
                    const uint4 t4 = lds128((hbuf ^ 4096) + j * 2048);
                    const uint32_t t[4] = {t4.x, t4.y, t4.z, t4.w};
#pragma unroll
                    for (int i = 0; i < 4; i++)
                        pk[4 * j + i] = pack2(fmaf(a, o[16 * j + 4 * i + keep], c * blo(t[i])), fmaf(a, o[16 * j + 4 * i + keep + 1], c * bhi(t[i])));
                }
                st_data(odst, pk[0], pk[1], pk[2], pk[3]);
                st_data(odst + 512, pk[4], pk[5], pk[6], pk[7]);
            };
            if (tid < 128) merge(0, n0, n1); else merge(2, n1, n0);
            if (tid == 0) asm volatile("red.relaxed.gpu.global.add.u32 [%0], 1;" ::"l"(&g_epoch[blockIdx.x * FS]) : "memory");
            TS(15);
        }

        {
            const uint32_t* dp = reinterpret_cast<const uint32_t*>(p.dw + (mir ? 14 * 256 : 0) + tile * 64) + lane;
#pragma unroll
            for (int i = 0; i < 15; i++) asm volatile("ld.global.nc.b32 %0, [%1];" : "=r"(dwr[i]) : "l"(dp + i * (mir ? -128 : 128)));
            acq(30); acq(31); acq(32);
            uint4 u[8];
            ld_data<512>(u, g_o + (size_t)(b * 128 + pt * 4 + wq) * 4096 + lane * 16);
#pragma unroll
            for (int i = 0; i < 8; i++) { a[4 * i] = u[i].x; a[4 * i + 1] = u[i].y; a[4 * i + 2] = u[i].z; a[4 * i + 3] = u[i].w; }
            TS(16);
            sp(d0, 30, a, 0, 0);
            sp(d0, 31, a + 16, 0, 1);
#pragma unroll
            for (int i = 0; i < 15; i++) dwr[i] = hmul2(dwr[i], 0x3F003F00u);
            residual(30);
            TS(17);
        }
    };
    phase(std::integral_constant<int, 0>{});
    phase(std::integral_constant<int, 1>{});
    phase(std::integral_constant<int, 2>{});
    phase(std::integral_constant<int, 3>{});
    phase(std::integral_constant<int, 4>{});

    cluster_arrive();
    TS(24);
    {
        const float rstd = rsq(fmaxf(fmaf(-mean, mean, msq), 0.f) + 1e-5f), nb = -mean * rstd;
#pragma unroll
        for (int j = 0; j < 8; j++) xr[j] = pack2(fmaf(v[2 * j], rstd, nb), fmaf(v[2 * j + 1], rstd, nb));
        const uint32_t stg = H + warp * 1024;
        stsm4(stg + foff, xr[0], xr[1], xr[2], xr[3]);
        stsm4(stg + (foff ^ 64), xr[4], xr[5], xr[6], xr[7]);
        __syncwarp();
        const uint32_t src = stg + (lane >> 3) * 128 + (((lane & 7) ^ (lane >> 3)) << 4);
        const uint4 u0 = lds128(src), u1 = lds128((src + 512) ^ 64);
        __nv_bfloat16* dst = p.out + (size_t)(b * T_ + trow + (lane >> 3)) * 256 + tile * 64 + (lane & 7) * 8;
        if (trow < T_) { stg128(dst, u0); stg128(dst + 4 * 256, u1); }
    }
    TS(25);
    TG(31);
    TSDUMP();
    cluster_wait();
}

typedef CUresult (*EncodeFn)(CUtensorMap*, CUtensorMapDataType, cuuint32_t, void*, const cuuint64_t*, const cuuint64_t*,
                             const cuuint32_t*, const cuuint32_t*, CUtensorMapInterleave, CUtensorMapSwizzle,
                             CUtensorMapL2promotion, CUtensorMapFloatOOBfill);

}

extern "C" void kernel_launch(void* const* d_in, const int* in_sizes, int n_in, void* d_out, int out_size) {
    static EncodeFn encode = nullptr;
    if (!encode) {
        void* fn = nullptr;
        cudaDriverEntryPointQueryResult qr;
        cudaGetDriverEntryPoint("cuTensorMapEncodeTiled", &fn, cudaEnableDefault, &qr);
        encode = (EncodeFn)fn;
        cudaFuncSetAttribute(conformer_kernel, cudaFuncAttributeMaxDynamicSharedMemorySize, SMEM_LAUNCH);
    }
    Scalars p;
    Maps m;
    const cuuint32_t ones[5] = {1, 1, 1, 1, 1};
    const int idx[8] = {1, 2, 3, 4, 5, 7, 8, 9};
    const int rows[8] = {256, 1024, 256, 256, 256, 256, 256, 1024};
    const int cols[8] = {1024, 256, 768, 256, 512, 256, 1024, 256};
    for (int i = 0; i < 8; i++) {
        const cuuint64_t pitch = (cuuint64_t)cols[i] * 2;
        const bool f = i != 0 && i != 3;
        const cuuint64_t dims[5] = {(cuuint64_t)cols[i], f ? 2u : 4u, f ? 2u : 4u, f ? 4u : 2u, (cuuint64_t)rows[i] / (f ? 16 : 32)};
        const cuuint64_t strides[4] = {pitch, pitch * 8, pitch * (f ? 2 : 4), pitch * (f ? 16 : 32)};
        const cuuint32_t box[5] = {64, f ? 2u : 4u, f ? 2u : 4u, f ? 4u : 2u, f ? 8u : 4u};
        encode(&m.tm[i], CU_TENSOR_MAP_DATA_TYPE_BFLOAT16, 5, d_in[idx[i]], dims, strides, box, ones, CU_TENSOR_MAP_INTERLEAVE_NONE,
               CU_TENSOR_MAP_SWIZZLE_128B, CU_TENSOR_MAP_L2_PROMOTION_L2_128B, CU_TENSOR_MAP_FLOAT_OOB_FILL_NONE);
        m.w[i] = (const char*)d_in[idx[i]];
    }
    {
        void* kv = nullptr;
        cudaGetSymbolAddress(&kv, g_kvq);
        const cuuint64_t dims[2] = {64, 16384};
        const cuuint64_t strides[1] = {128};
        const cuuint32_t box[2] = {64, 128};
        encode(&m.tm[8], CU_TENSOR_MAP_DATA_TYPE_BFLOAT16, 2, kv, dims, strides, box, ones, CU_TENSOR_MAP_INTERLEAVE_NONE,
               CU_TENSOR_MAP_SWIZZLE_NONE, CU_TENSOR_MAP_L2_PROMOTION_L2_128B, CU_TENSOR_MAP_FLOAT_OOB_FILL_NONE);
    }
    p.x = (const __nv_bfloat16*)d_in[0];
    p.dw = (const __nv_bfloat16*)d_in[6];
    p.out = (__nv_bfloat16*)d_out;
    p.zero = 0;
    conformer_kernel<<<NCTA, NTHREADS, SMEM_LAUNCH>>>(p, m);
}
```

```cpp
#include <cuda_runtime.h>
#include <cuda_bf16.h>
#include <cuda.h>
#include <stdint.h>
#include <type_traits>

namespace {

constexpr int T_ = 1000;
constexpr int NCTA = 128;
constexpr int NTHREADS = 512;
constexpr int NSLOT = 6;
constexpr int SLOT = 16384;
constexpr int NLOADS = 54;

constexpr uint32_t OFF_RING = 0;
constexpr uint32_t OFF_P = 196608;
constexpr uint32_t OFF_H = 212992;
constexpr uint32_t OFF_MISC = 229376;
constexpr uint32_t OFF_BARS = 230912;
constexpr uint32_t SMEM_BYTES = 231424;
constexpr uint32_t GCH = 6144;
constexpr uint32_t HCH = 4096;

constexpr int B_FULL = 0, B_EMPTY = 12, B_XA = 24  , B_XB = 29  , B_INB = 33  , B_SR = 37,
              B_RST = 38, B_RDY = 39  , B_SINK = 43, B_HALO = 44  , NBARS = 48;

#define PACE KDELAY = 250, KD2 = 300, KD3 = 500, QGATE = 700, HDELAY = 200
constexpr uint32_t PACE;
constexpr int FS = 8;

struct Scratch {
    unsigned char kvq[3 * 8 * 1024 * 128];
    unsigned char o[2 * 128 * 4096];
    uint4 halo[64 * 4 * 2 * 64];
    uint32_t flag_kv[8 * 32 * FS];
    uint32_t reset[2 * 32];
    uint32_t epoch[NCTA * FS];
};
__device__ __align__(1024) Scratch g_scratch;

struct Scalars {
    const __nv_bfloat16* x;
    const __nv_bfloat16* dw;
    __nv_bfloat16* out;
    Scratch* g;
    uint32_t zero;
};
struct Maps {
    CUtensorMap tm[9];
    const char* w[8];
};

#define TS(i) do { } while (0)
#define TSW(i) do { } while (0)
#define TG(i) do { } while (0)
#define TSINIT() do { } while (0)
#define TSDUMP() do { } while (0)
constexpr uint32_t SMEM_LAUNCH = SMEM_BYTES;

__device__ __forceinline__ uint32_t smem_u32(const void* p) { return (uint32_t)__cvta_generic_to_shared(p); }
__device__ __forceinline__ void mbar_init(uint32_t b, uint32_t c) { asm volatile("mbarrier.init.shared::cta.b64 [%0], %1;" ::"r"(b), "r"(c) : "memory"); }
__device__ __forceinline__ void mbar_arrive(uint32_t b) { asm volatile("mbarrier.arrive.shared::cta.b64 _, [%0];" ::"r"(b) : "memory"); }
__device__ __forceinline__ void mbar_arrive_tx(uint32_t b, uint32_t tx) { asm volatile("mbarrier.arrive.expect_tx.shared::cta.b64 _, [%0], %1;" ::"r"(b), "r"(tx) : "memory"); }
__device__ __forceinline__ void mbar_wait(uint32_t b, uint32_t ph) {
    asm volatile("{\n.reg .pred p, q;\n.reg .u32 c;\nmov.u32 c, 0;\n"
                 "MW_LOOP:\n.pragma \"nounroll\";\n"
                 "mbarrier.try_wait.parity.shared::cta.b64 p, [%0], %1;\n"
                 "add.u32 c, c, 1;\nsetp.lt.u32 q, c, 65536;\nnot.pred p, p;\nand.pred p, p, q;\n@p bra MW_LOOP;\n}"
                 ::"r"(b), "r"(ph) : "memory");
}
__device__ __forceinline__ bool mbar_test(uint32_t b, uint32_t ph) {
    uint32_t ok;
    asm volatile("{\n.reg .pred p;\nmbarrier.test_wait.parity.shared::cta.b64 p, [%1], %2;\nselp.u32 %0, 1, 0, p;\n}" : "=r"(ok) : "r"(b), "r"(ph) : "memory");
    return ok;
}
__device__ __forceinline__ uint32_t mapa(uint32_t a, uint32_t r) { uint32_t o; asm("mapa.shared::cluster.u32 %0, %1, %2;" : "=r"(o) : "r"(a), "r"(r)); return o; }
__device__ __forceinline__ void fence_async_smem() { asm volatile("fence.proxy.async.shared::cta;" ::: "memory"); }
__device__ __forceinline__ void fence_async_global() { asm volatile("fence.proxy.async.global;" ::: "memory"); }
__device__ __forceinline__ void bar_sync(int id, int n) { asm volatile("bar.sync %0, %1;" ::"r"(id), "r"(n) : "memory"); }
__device__ __forceinline__ void bar_arrive(int id, int n) { asm volatile("bar.arrive %0, %1;" ::"r"(id), "r"(n) : "memory"); }
__device__ __forceinline__ void cluster_arrive() { asm volatile("barrier.cluster.arrive.relaxed.aligned;" ::: "memory"); }
__device__ __forceinline__ void cluster_wait() { asm volatile("barrier.cluster.wait.aligned;" ::: "memory"); }

__device__ __forceinline__ void ring_load(uint32_t dst, const CUtensorMap* tm, int col, int row16, uint32_t bar) {
    asm volatile("{\n.reg .pred p;\nelect.sync _|p, 0xffffffff;\n"
                 "@p mbarrier.arrive.expect_tx.shared::cta.b64 _, [%2], 16384;\n"
                 "@p cp.async.bulk.tensor.5d.shared::cluster.global.mbarrier::complete_tx::bytes [%0], [%1, {%3, 0, 0, 0, %4}], [%2];\n}"
                 ::"r"(dst), "l"(tm), "r"(bar), "r"(col), "r"(row16) : "memory");
}
__device__ __forceinline__ void ring_load_both(uint32_t dst, const CUtensorMap* tm, int c1, uint32_t bar) {
    asm volatile("{\n.reg .pred p;\nelect.sync _|p, 0xffffffff;\n"
                 "@p cp.async.bulk.tensor.2d.shared::cluster.global.mbarrier::complete_tx::bytes.multicast::cluster [%0], [%1, {0, %3}], [%2], %4;\n}"
                 ::"r"(dst), "l"(tm), "r"(bar), "r"(c1), "h"((uint16_t)3) : "memory");
}
__device__ __forceinline__ void mbar_arrive_peer(uint32_t b) { asm volatile("mbarrier.arrive.relaxed.cluster.shared::cluster.b64 _, [%0];" ::"r"(b) : "memory"); }
__device__ __forceinline__ void prefetch_l2(const void* src, uint32_t bytes) {
    asm volatile("cp.async.bulk.prefetch.L2.global [%0], %1;" ::"l"(src), "r"(bytes) : "memory");
}
__device__ __forceinline__ void st_async4(uint32_t dst, uint32_t a, uint32_t b, uint32_t c, uint32_t d, uint32_t bar) {
    asm volatile("st.async.shared::cluster.mbarrier::complete_tx::bytes.v4.b32 [%0], {%1,%2,%3,%4}, [%5];" ::"r"(dst), "r"(a), "r"(b), "r"(c), "r"(d), "r"(bar) : "memory");
}
__device__ __forceinline__ void put_sums(uint32_t dst, uint32_t rdst, float a, float b, uint32_t rbar, bool on) {
    asm volatile("{\n.reg .pred p;\nsetp.ne.u32 p, %5, 0;\n"
                 "@p st.async.shared::cluster.mbarrier::complete_tx::bytes.v2.f32 [%1], {%2,%3}, [%4];\n"
                 "@p st.shared.v2.f32 [%0], {%2,%3};\n}" ::"r"(dst), "r"(rdst), "f"(a), "f"(b), "r"(rbar), "r"((uint32_t)on) : "memory");
}
__device__ __forceinline__ void stsm4(uint32_t a, uint32_t r0, uint32_t r1, uint32_t r2, uint32_t r3) {
    asm volatile("stmatrix.sync.aligned.m8n8.x4.shared.b16 [%0], {%1,%2,%3,%4};" ::"r"(a), "r"(r0), "r"(r1), "r"(r2), "r"(r3) : "memory");
}
__device__ __forceinline__ void ldsm4(uint32_t a, uint32_t& r0, uint32_t& r1, uint32_t& r2, uint32_t& r3) {
    asm volatile("ldmatrix.sync.aligned.m8n8.x4.shared.b16 {%0,%1,%2,%3}, [%4];" : "=r"(r0), "=r"(r1), "=r"(r2), "=r"(r3) : "r"(a) : "memory");
}
__device__ __forceinline__ uint4 lds128(uint32_t a) { uint4 v; asm volatile("ld.shared.v4.b32 {%0,%1,%2,%3}, [%4];" : "=r"(v.x), "=r"(v.y), "=r"(v.z), "=r"(v.w) : "r"(a) : "memory"); return v; }
__device__ __forceinline__ float4 lds128f(uint32_t a) { float4 v; asm volatile("ld.shared.v4.f32 {%0,%1,%2,%3}, [%4];" : "=f"(v.x), "=f"(v.y), "=f"(v.z), "=f"(v.w) : "r"(a) : "memory"); return v; }
__device__ __forceinline__ float2 lds64f(uint32_t a) { float2 v; asm volatile("ld.shared.v2.f32 {%0,%1}, [%2];" : "=f"(v.x), "=f"(v.y) : "r"(a) : "memory"); return v; }
__device__ __forceinline__ uint32_t lds32(uint32_t a) { uint32_t v; asm volatile("ld.shared.b32 %0, [%1];" : "=r"(v) : "r"(a) : "memory"); return v; }
__device__ __forceinline__ void sts128(uint32_t a, uint32_t x, uint32_t y, uint32_t z, uint32_t w) { asm volatile("st.shared.v4.b32 [%0], {%1,%2,%3,%4};" ::"r"(a), "r"(x), "r"(y), "r"(z), "r"(w) : "memory"); }
__device__ __forceinline__ void sts128f(uint32_t a, float x, float y, float z, float w) { asm volatile("st.shared.v4.f32 [%0], {%1,%2,%3,%4};" ::"r"(a), "f"(x), "f"(y), "f"(z), "f"(w) : "memory"); }
__device__ __forceinline__ void sts64f(uint32_t a, float x, float y) { asm volatile("st.shared.v2.f32 [%0], {%1,%2};" ::"r"(a), "f"(x), "f"(y) : "memory"); }
__device__ __forceinline__ void sts32(uint32_t a, uint32_t x) { asm volatile("st.shared.b32 [%0], %1;" ::"r"(a), "r"(x) : "memory"); }
__device__ __forceinline__ void stg128(void* p, uint4 v) { asm volatile("st.global.v4.b32 [%0], {%1,%2,%3,%4};" ::"l"(p), "r"(v.x), "r"(v.y), "r"(v.z), "r"(v.w) : "memory"); }

__device__ __forceinline__ uint32_t pack2(float lo, float hi) { uint32_t r; asm("cvt.rn.bf16x2.f32 %0, %1, %2;" : "=r"(r) : "f"(hi), "f"(lo)); return r; }
__device__ __forceinline__ float blo(uint32_t v) { return __uint_as_float(v << 16); }
__device__ __forceinline__ float bhi(uint32_t v) { return __uint_as_float(v & 0xffff0000u); }
__device__ __forceinline__ uint32_t hmul2(uint32_t a, uint32_t b) { uint32_t r; asm("mul.rn.bf16x2 %0, %1, %2;" : "=r"(r) : "r"(a), "r"(b)); return r; }
__device__ __forceinline__ uint32_t hadd2(uint32_t a, uint32_t b) { uint32_t r; asm("add.rn.bf16x2 %0, %1, %2;" : "=r"(r) : "r"(a), "r"(b)); return r; }
__device__ __forceinline__ uint32_t hsub2(uint32_t a, uint32_t b) { uint32_t r; asm("sub.rn.bf16x2 %0, %1, %2;" : "=r"(r) : "r"(a), "r"(b)); return r; }
__device__ __forceinline__ uint32_t hfma2(uint32_t a, uint32_t b, uint32_t c) { uint32_t r; asm("fma.rn.bf16x2 %0, %1, %2, %3;" : "=r"(r) : "r"(a), "r"(b), "r"(c)); return r; }
__device__ __forceinline__ float tanh_fast(float x) { float r; asm("tanh.approx.f32 %0, %1;" : "=f"(r) : "f"(x)); return r; }
__device__ __forceinline__ float rsq(float x) { float r; asm("rsqrt.approx.ftz.f32 %0, %1;" : "=f"(r) : "f"(x)); return r; }
__device__ __forceinline__ float rcp(float x) { float r; asm("rcp.approx.ftz.f32 %0, %1;" : "=f"(r) : "f"(x)); return r; }
__device__ __forceinline__ float ex2(float x) { float r; asm("ex2.approx.ftz.f32 %0, %1;" : "=f"(r) : "f"(x)); return r; }

__device__ __forceinline__ uint32_t ld_relaxed(const uint32_t* p) {
    uint32_t v;
    asm volatile("ld.relaxed.gpu.global.u32 %0, [%1];" : "=r"(v) : "l"(p) : "memory");
    return v;
}
__device__ __forceinline__ uint32_t clock32() { uint32_t c; asm volatile("mov.u32 %0, %%clock;" : "=r"(c)::"memory"); return c; }
__device__ __forceinline__ void spin(uint32_t clks) {
    const uint32_t t0 = clock32();
    while (clock32() - t0 < clks) {}
}
__device__ __forceinline__ void flag_wait(const uint32_t* p, uint32_t e, bool mine) {
#pragma unroll 1
    for (int i = 0; i < (1 << 19); i++) {
        if (mine) mine = ld_relaxed(p) != e;
        if (!__any_sync(~0u, mine)) break;
    }
    asm volatile("fence.acquire.gpu;" ::: "memory");
    fence_async_global();
}
__device__ __forceinline__ void st_data(void* p, uint32_t x, uint32_t y, uint32_t z, uint32_t w) {
    asm volatile("st.relaxed.gpu.global.v4.b32 [%0], {%1,%2,%3,%4};" ::"l"(p), "r"(x), "r"(y), "r"(z), "r"(w) : "memory");
}
template <int STRIDE, bool INV = false, int N>
__device__ __forceinline__ void ld_data(uint4 (&v)[N], const unsigned char* p) {
    int it = 0;
    bool again;
#pragma unroll 1
    do {
        uint32_t m = INV ? ~0u : 0u;
#pragma unroll
        for (int i = 0; i < N; i++)
            asm volatile("ld.relaxed.gpu.global.v4.b32 {%0,%1,%2,%3}, [%4];" : "=r"(v[i].x), "=r"(v[i].y), "=r"(v[i].z), "=r"(v[i].w) : "l"(p + i * STRIDE) : "memory");
#pragma unroll
        for (int i = 0; i < N; i++)
            m = INV ? __vimin3_u32(__vimin3_u32(v[i].x, v[i].y, v[i].z), v[i].w, m) : __vimax3_u32(__vimax3_u32(v[i].x, v[i].y, v[i].z), v[i].w, m);
        again = __any_sync(~0u, m == (INV ? 0u : ~0u)) && ++it < (1 << 16);
    } while (again);
}
__device__ __forceinline__ uint32_t ld_epoch(const Scratch* g) { return ld_relaxed(&g->epoch[blockIdx.x * FS]) + 1; }
__device__ __forceinline__ void flag_set(uint32_t* p, uint32_t e) { asm volatile("st.release.gpu.global.u32 [%0], %1;" ::"l"(p), "r"(e) : "memory"); }

__device__ __forceinline__ uint32_t desc_lo(uint32_t addr) { return ((addr & 0x3FFFF) >> 4) | 0x10000u; }
__device__ __forceinline__ uint64_t mkdesc(uint32_t lo) { return (uint64_t)lo | (0x40000040ull << 32); }
__device__ __forceinline__ void wg_fence() { asm volatile("wgmma.fence.sync.aligned;" ::: "memory"); }
__device__ __forceinline__ void wg_commit() { asm volatile("wgmma.commit_group.sync.aligned;" ::: "memory"); }
template <int N> __device__ __forceinline__ void wg_wait() { asm volatile("wgmma.wait_group.sync.aligned %0;" ::"n"(N) : "memory"); }
template <int N> __device__ __forceinline__ void pin(float (&d)[N]) {
#pragma unroll
    for (int i = 0; i < N; i++) asm volatile("" : "+f"(d[i])::"memory");
}
template <int N> __device__ __forceinline__ void pin(uint32_t (&d)[N]) {
#pragma unroll
    for (int i = 0; i < N; i++) asm volatile("" : "+r"(d[i])::"memory");
}

template <typename Tp, int N> __device__ __forceinline__ void zero(Tp (&d)[N]) {
#pragma unroll
    for (int i = 0; i < N; i++) d[i] = 0;
    pin(d);
}

#define F4(d, i) "+f"(d[i]), "+f"(d[i + 1]), "+f"(d[i + 2]), "+f"(d[i + 3])
#define F16(d, i) F4(d, i), F4(d, i + 4), F4(d, i + 8), F4(d, i + 12)

__device__ __forceinline__ void mma16(float (&d)[4], const uint32_t* a, uint32_t b0, uint32_t b1) {
    asm("mma.sync.aligned.m16n8k16.row.col.f32.bf16.bf16.f32 {%0,%1,%2,%3}, {%4,%5,%6,%7}, {%8,%9}, {%0,%1,%2,%3};"
        : F4(d, 0) : "r"(a[0]), "r"(a[1]), "r"(a[2]), "r"(a[3]), "r"(b0), "r"(b1));
}
template <int N>
__device__ __forceinline__ float row_sum(const uint32_t* x, uint32_t ones = 0x3F803F80u) {
    float c[4] = {};
#pragma unroll
    for (int i = 0; i < N; i += 4) mma16(c, x + i, ones, ones);
    return c[0] + c[2];
}
template <int N>
__device__ __forceinline__ float row_sumsq(const uint32_t* x, int lane) {
    float c0[4] = {}, c1[4] = {};
#pragma unroll
    for (int i = 0; i < N; i += 4) {
        mma16(c0, x + i, x[i], x[i + 2]);
        mma16(c1, x + i, x[i + 1], x[i + 3]);
    }
    return (lane & 4) ? c0[1] + c1[3] : c0[0] + c1[2];
}
__device__ __forceinline__ void mma_sp(float (&d)[32], const uint32_t* a, uint64_t b, uint32_t meta, int acc) {
    asm volatile("{.reg .pred p; setp.ne.b32 p, %38, 0;\n"
                 "wgmma.mma_async.sp.sync.aligned.m64n64k32.f32.bf16.bf16 {%0,%1,%2,%3,%4,%5,%6,%7,%8,%9,%10,%11,%12,%13,%14,%15,%16,%17,%18,%19,%20,%21,%22,%23,%24,%25,%26,%27,%28,%29,%30,%31}, "
                 "{%32,%33,%34,%35}, %36, %37, 0, p, 1, 1, 1;}\n"
                 : F16(d, 0), F16(d, 16) : "r"(a[0]), "r"(a[1]), "r"(a[2]), "r"(a[3]), "l"(b), "r"(meta), "r"(acc));
}
__device__ __forceinline__ void mma_qk(float (&d)[32], uint32_t a0, uint32_t a1, uint32_t a2, uint32_t a3, uint64_t b, int acc) {
    asm volatile("{.reg .pred p; setp.ne.b32 p, %37, 0;\n"
                 "wgmma.mma_async.sync.aligned.m64n64k16.f32.bf16.bf16 {%0,%1,%2,%3,%4,%5,%6,%7,%8,%9,%10,%11,%12,%13,%14,%15,%16,%17,%18,%19,%20,%21,%22,%23,%24,%25,%26,%27,%28,%29,%30,%31}, "
                 "{%32,%33,%34,%35}, %36, p, 1, 1, 0;}\n"
                 : F16(d, 0), F16(d, 16) : "r"(a0), "r"(a1), "r"(a2), "r"(a3), "l"(b), "r"(acc));
}
__device__ __forceinline__ void mma_pv(float (&d)[36], uint32_t a0, uint32_t a1, uint32_t a2, uint32_t a3, uint64_t b) {
    asm volatile("wgmma.mma_async.sync.aligned.m64n72k16.f32.bf16.bf16 {%0,%1,%2,%3,%4,%5,%6,%7,%8,%9,%10,%11,%12,%13,%14,%15,%16,%17,%18,%19,%20,%21,%22,%23,%24,%25,%26,%27,%28,%29,%30,%31,%32,%33,%34,%35}, "
                 "{%36,%37,%38,%39}, %40, 1, 1, 1, 1;\n"
                 : F16(d, 0), F16(d, 16), F4(d, 32) : "r"(a0), "r"(a1), "r"(a2), "r"(a3), "l"(b));
}

__device__ __forceinline__ uint32_t load_code(int n, int r, int w) {
    const int tile = 2 * r + w;
    int m, col, row;
    if (n < 16 || n >= 38) {
        const int k = n < 16 ? n : n - 38;
        m = n < 16 ? 0 : 6;
        if (n >= 38 && k < 4) { col = 4 * tile + (k & 1); row = (k >> 1) ^ r; }
        else if (k < 8) { col = 4 * tile + (k >> 1); row = n < 16 ? (k & 1) : (k & 1) ^ r; }
        else { m++; col = k < 12 ? tile ^ 2 : tile; row = 2 * (tile ^ (k & 1)) + ((k >> 1) & 1); }
    } else if (n < 30) {
        const int k = n - 16;
        m = 2;
        if (k < 4) { col = tile + ((k & 1) ? 8 : 4); row = (k >> 1) ^ r; }
        else { col = tile; row = (k & 1) ^ r; }
    } else if (n < 32) { m = 3; col = tile; row = n - 30; }
    else if (n < 36) { const int k = n - 32; m = 4; col = tile + 4 * (k & 1); row = (k >> 1) ^ r; }
    else { m = 5; col = tile; row = (n & 1) ^ r; }
    return m | (col << 4) | (row << ((m == 0 || m == 3) ? 10 : 11));
}

__global__ void __cluster_dims__(2, 1, 1) __launch_bounds__(NTHREADS, 1)
conformer_kernel(const Scalars p, const __grid_constant__ Maps m) {
    extern __shared__ __align__(1024) unsigned char smem_raw[];
    const uint32_t sb = smem_u32(smem_raw);
    const uint32_t bars = sb + OFF_BARS;
    const int tid = threadIdx.x;
    const int lane = tid & 31;
    const int warp = __shfl_sync(~0u, tid >> 5, 0);
    const int r = blockIdx.x & 1;
    const int pair = blockIdx.x >> 1;
    const int b = pair >> 5, pt = pair & 31;
    const int ah = pt >> 3, qt = (pt & 7) * 2 + r;
    const int abh = b * 4 + ah;

    TG(30);
    TSINIT();
    TS(0);
    const uint32_t P = sb + OFF_P, H = sb + OFF_H;
    if (warp == 11) {
        if (lane == 0) {
#pragma unroll
            for (int i = 0; i < 2 * NSLOT; i++) mbar_init(bars + (B_FULL + i) * 8, 1);
            asm volatile("fence.mbarrier_init.release.cluster;" ::: "memory");
            fence_async_smem();
        }
        __syncwarp();
        bar_arrive(13, 96);
        cluster_arrive();
    }

    if (warp >= 8) {
        asm volatile("setmaxnreg.dec.sync.aligned.u32 48;");
        if (warp >= 12) {
            cluster_arrive();
            const int ut = tid & 127;
            cluster_wait();
            const uint32_t target = ld_epoch(p.g) * 64;
            bar_sync(6, 384);
#pragma unroll
            for (int i = 0; i < 4; i++) {
                st_data(p.g->o + (size_t)(b * 128 + qt * 8 + 2 * i + (ut >> 6)) * 4096 + ah * 1024 + (ut & 63) * 16, ~0u, ~0u, ~0u, ~0u);
                if (i < 2) st_data(&p.g->halo[(pair * 4 + 2 * r + i) * 128 + ut], ~0u, ~0u, ~0u, ~0u);
            }
            bar_sync(11, 128);
            if (ut == 0) {
                asm volatile("red.release.gpu.global.add.u32 [%0], 1;" ::"l"(&p.g->reset[b * 32]) : "memory");
#pragma unroll 1
                for (int i = 0; i < (1 << 20) && ld_relaxed(&p.g->reset[b * 32]) != target; i++) __nanosleep(100);
                asm volatile("fence.acquire.gpu;" ::: "memory");
                mbar_arrive(bars + B_RST * 8);
            }
            bar_sync(11, 128);
            TS(14);
#pragma unroll
            for (int i = 0; i < 4; i++) st_data(p.g->kvq + 2097152 + (size_t)(abh * 1024 + qt * 64) * 128 + i * 2048 + ut * 16, 0, 0, 0, 0);
            const int side = warp & 1, wg = (warp >> 1) & 1, np = side ? pt + 1 : pt - 1;
            const unsigned char* src = reinterpret_cast<const unsigned char*>(&p.g->halo[(((b * 32 + np) * 4 + 2 * r + wg) * 2 + (side ^ 1)) * 64 + lane]);
            const uint32_t dst = P + wg * GCH + side * 5120 + (lane & 7) * 128 + (((lane >> 3) ^ (lane & 7)) << 4);
            uint4 hv[2] = {make_uint4(0, 0, 0, 0), make_uint4(0, 0, 0, 0)};
            bar_sync(8 + wg, 192);
            if (np >= 0 && np < 32) {
                spin(HDELAY);
                ld_data<512>(hv, src);
            }
            stsm4(dst, hv[0].x, hv[0].y, hv[0].z, hv[0].w);
            stsm4(dst ^ 64, hv[1].x, hv[1].y, hv[1].z, hv[1].w);
            __syncwarp();
            if (lane == 0) mbar_arrive(bars + (B_HALO + (warp & 3)) * 8);
            TS(4);
        } else if (warp < 10) {
            const int w = warp - 8;
            const uint32_t ring = sb + OFF_RING + w * NSLOT * SLOT;
            const uint32_t full = bars + (B_FULL + w * NSLOT) * 8;
            cluster_arrive();
            bar_sync(13, 96);
            TS(1);
#pragma unroll
            for (int n = 0; n < NSLOT; n++) {
                if (n == 1) bar_sync(12, 64);
                ring_load(ring + n * SLOT, &m.tm[0], 64 * (8 * r + 4 * w + (n >> 1)), 4 * (n & 1), full + n * 8);
            }
            TS(2);
            const uint32_t code = load_code(lane, r, w) | (load_code(lane + 32, r, w) << 16);
            cluster_wait();
            uint32_t s = 0, ph = 0;
            int n = NSLOT;
#pragma unroll 1
            for (int seg = 0; seg < 2; seg++) {
#pragma unroll 1
                for (; n < (seg == 0 ? 22 : NLOADS); n++) {
                    const uint32_t c = __shfl_sync(~0u, code, n) >> (n & 32 ? 16 : 0);
                    const CUtensorMap* tm = &m.tm[c & 15];
                    const uint32_t col = (c & 0xf0) * 4, row = (c & 0xff00) >> 8, dst = ring + s * SLOT;
                    mbar_wait(full + (B_EMPTY - B_FULL) * 8 + s * 8, ph + (((uint32_t)(size_t)tm | col | row | dst) & p.zero));
                    ring_load(dst, tm, col, row, full + s * 8);
                    if (++s == NSLOT) { s = 0; ph ^= 1; }
                }
                if (seg == 1) break;
                const uint32_t epoch = ld_epoch(p.g);
                const uint32_t rdy = bars + (B_RDY + 2 * w) * 8, prdy = mapa(rdy, r ^ 1);
                const int odd = r ^ w;
                const uint32_t* flags = p.g->flag_kv + (abh * 32 + lane) * FS;
                bool first = (lane >> 2) == 2 * odd + w;
                if (first) first = ld_relaxed(flags) != epoch;
                auto kv_load = [&](uint32_t sl, int isv, int i) {
                    ring_load_both(ring + sl * SLOT, &m.tm[8], (isv * 64 + abh * 8 + 2 * i + w) * 128, full + sl * 8);
                };
                if (lane < NSLOT) {
                    mbar_wait(full + (B_EMPTY - B_FULL + lane) * 8, lane < 4);
                    mbar_arrive_tx(full + lane * 8, SLOT);
                }
                __syncwarp();
                if (lane == 0) mbar_arrive_peer(prdy);
                bar_sync(14, 96);
                spin(KDELAY);
                mbar_wait(rdy, 0);
                flag_wait(flags, epoch, first);
                TSW(5 + 2 * odd);
                if (!odd) { kv_load(4, 0, 0); bar_arrive(12, 64); }
                else bar_sync(12, 64);
                spin(w ? KD3 : KD2);
                kv_load(odd ? 5 : 0, odd ^ 1, odd);
                flag_wait(flags, epoch, (lane >> 2) == 2 * odd + w + 4);
                mbar_wait(full + (odd ? 5 : 0) * 8, odd);
                kv_load(1 + odd, odd, 2 - odd);
                if (odd) { mbar_wait(full + 16, 0); kv_load(3, 0, 3); }
#pragma unroll 1
                for (int i = 0; i < 2; i++) {
                    mbar_wait(full + (B_EMPTY - B_FULL + 4 + i) * 8, 1);
                    if (lane == 0) mbar_arrive_tx(full + (4 + i) * 8, SLOT);
                    if (i == odd) {
                        mbar_wait(rdy + 8, 0);
                        kv_load(4 + i, 1, 2 + i);
                    } else if (lane == 0) mbar_arrive_peer(prdy + 8);
                    __syncwarp();
                }
                n = 30; s = 0; ph = 0;
            }
        } else if (warp == 10) {
            if (lane == 0) {
#pragma unroll
                for (int i = B_EMPTY; i < NBARS; i++) mbar_init(bars + i * 8, i < B_XA ? 4 : 1);
#pragma unroll
                for (int i = B_XA; i <= B_SR; i++) mbar_arrive_tx(bars + i * 8, i < B_XB ? 512 : ((i >= B_INB && i < B_SR) ? 4096 : 8192));
                asm volatile("fence.mbarrier_init.release.cluster;" ::: "memory");
                fence_async_smem();
            }
            __syncwarp();
            cluster_arrive();
            cluster_wait();
            float ka[4] = {};
            const uint32_t kz[4] = {p.zero, p.zero, p.zero, p.zero};
#pragma unroll 1
            for (int i = 0; i < 4096 && !mbar_test(bars + (B_XA + 3) * 8, __float_as_uint(ka[0])); i++) {
                mma16(ka, kz, p.zero, p.zero);
                __nanosleep(250);
            }
        } else {
            const uint32_t kb = (lane < 2 || lane > 5) ? 4096 : (lane == 2 ? 3072 : (lane == 4 ? 2048 : 1024));
            const char* pf = m.w[lane & 7] + blockIdx.x * kb;
            cluster_wait();
            mbar_wait(bars + B_FULL * 8, 0);
            if (lane < 3) prefetch_l2(pf, kb);
            if (lane >= 1 && lane < 9) asm volatile("prefetch.tensormap [%0];" ::"l"(&m.tm[lane]) : "memory");
            mbar_wait(bars + (B_FULL + 1) * 8, 1);
            if (lane > 2 && lane < 8) prefetch_l2(pf, kb);
            if (lane == 8 && blockIdx.x < 15) prefetch_l2(p.dw + blockIdx.x * 256, 512);
            const uint32_t epoch = ld_epoch(p.g);
            bar_sync(4, 288);
            if (lane < 16) flag_set(&p.g->flag_kv[((b * 4 + 2 * r + (lane >> 3)) * 32 + pt) * FS + (lane & 7)], epoch);
            __syncwarp();
            bar_arrive(14, 96);
            TSW(8);
        }
        TSDUMP();
        return;
    }

    const int w = warp >> 2, wq = warp & 3;
    const int tile = 2 * r + w;
    const int wt = tid & 127;
    const int c4 = lane & 3;
    const int trow = pt * 32 + 8 * wq;
    uint32_t xr[8];
    uint32_t a[32];
    const char* xrow = reinterpret_cast<const char*>(p.x) + (b * T_ + trow + (lane >> 2)) * 512;
    zero(a);
    if (trow < T_) {
        const char* src = xrow + c4 * 16 + p.zero;
#pragma unroll
        for (int i = 0; i < 8; i++)
            asm volatile("ld.global.nc.v4.b32 {%0,%1,%2,%3}, [%4];" : "=r"(a[4 * i]), "=r"(a[4 * i + 1]), "=r"(a[4 * i + 2]), "=r"(a[4 * i + 3]) : "l"(src + 64 * i));
    }
    cluster_arrive();
    asm volatile("setmaxnreg.inc.sync.aligned.u32 208;");
    const uint32_t rbase = sb + OFF_RING + w * NSLOT * SLOT, fbar = bars + (B_FULL + w * NSLOT) * 8;
    const uint32_t rdesc = desc_lo(rbase);
    auto acq = [&](int n) { mbar_wait(fbar + (n % NSLOT) * 8, (n / NSLOT) & 1); };
    auto rel = [&](int n) { if (lane == 0) mbar_arrive(fbar + (B_EMPTY - B_FULL + n % NSLOT) * 8); };
    const uint32_t foff = (lane & 7) * 128 + (((lane >> 3) ^ (lane & 7)) << 4);
    float v[16];
    const uint32_t xown = __shfl_sync(~0u, P + wt * 16 + tile * 4096, lane), xrem = __shfl_sync(~0u, P + wt * 16 + (r ^ 1) * 8192, lane);
    const uint32_t sbuf = __shfl_sync(~0u, sb + OFF_MISC + (8 * wq + (lane >> 2)) * 32, lane);
    const uint32_t sown = __shfl_sync(~0u, sbuf + tile * 8, lane);
    const uint32_t peer = __shfl_sync(~0u, mapa(sb, r ^ 1) - sb, lane);
    const uint32_t hbuf = __shfl_sync(~0u, H + w * 4096 + wt * 16, lane);
    const uint32_t meta = __shfl_sync(~0u, 0xEEEE4444u + p.zero, lane);
    cluster_wait();
    TS(56);
    float mean, msq;
    const int mir = wq < 2 ? 7 : 0;
    uint32_t dwr[15];

    auto phase = [&](auto phc) __attribute__((always_inline)) {
        constexpr int ph = decltype(phc)::value;
        uint4 o0, o1;
        if (ph == 0) {
            const uint32_t one = 0x3F803F80u + ((xown | xrem | sbuf | sown | hbuf | foff | rdesc | fbar) & p.zero);
            mean = ((row_sum<8>(a, one) + row_sum<8>(a + 8, one)) + (row_sum<8>(a + 16, one) + row_sum<8>(a + 24, one))) * (1.f / 256.f);
            TS(57);
        } else {
            const uint32_t xa = bars + (B_XA + ph) * 8;
#pragma unroll
            for (int j = 0; j < 8; j++) xr[j] = pack2(v[2 * j], v[2 * j + 1]);
            const float s = row_sum<8>(xr), q = row_sumsq<8>(xr, lane);
            if (ph < 4) {
                sts128(xown, xr[0], xr[1], xr[2], xr[3]);
                sts128(xown + 2048, xr[4], xr[5], xr[6], xr[7]);
            }
            put_sums(sown, sown + peer, s, q, xa + peer, c4 == (lane >> 3));
            bar_sync(10, 256);
            if (ph < 4) {
                o0 = lds128(xown ^ 4096); o1 = lds128((xown ^ 4096) + 2048);
                st_async4(xown + peer, xr[0], xr[1], xr[2], xr[3], xa + (B_XB - B_XA) * 8 + peer);
                st_async4(xown + peer + 2048, xr[4], xr[5], xr[6], xr[7], xa + (B_XB - B_XA) * 8 + peer);
            }
            TS(57 + ph);
            if (ph == 3) acq(38);
            if (ph == 1) acq(16);
            mbar_wait(xa, 0);
            const float4 u0 = lds128f(sbuf), u1 = lds128f(sbuf + 16);
            mean = ((u0.x + u0.z) + (u1.x + u1.z)) * (1.f / 256.f);
            msq = ((u0.y + u0.w) + (u1.y + u1.w)) * (1.f / 256.f);
        }
        if (ph == 4) return;
        const uint32_t mean2 = pack2(mean, mean);
        auto centre = [&](int i, const uint4& u) {
            a[i] = hsub2(u.x, mean2); a[i + 1] = hsub2(u.y, mean2); a[i + 2] = hsub2(u.z, mean2); a[i + 3] = hsub2(u.w, mean2);
        };
        if (ph == 0) {
#pragma unroll
            for (int j = 0; j < 32; j++) a[j] = hsub2(a[j], mean2);
            zero(xr);
            if (trow < T_) {
                const char* src = xrow + tile * 128 + c4 * 4 + (mean2 & p.zero);
#pragma unroll
                for (int j = 0; j < 8; j++) asm volatile("ld.global.nc.b32 %0, [%1];" : "=r"(xr[j]) : "l"(src + 16 * j));
            }
            mean -= blo(mean2);
            msq = __shfl_sync(~0u, row_sumsq<16>(a, lane) + row_sumsq<16>(a + 16, lane), (lane & 28) + (lane >> 3)) * (1.f / 256.f);
            acq(0);
        } else {
#pragma unroll
            for (int j = 0; j < 8; j++) a[j] = hsub2(xr[j], mean2);
            centre(8, o0); centre(12, o1);
        }
        const float rstd = rsq(fmaxf(fmaf(-mean, mean, msq), 0.f) + 1e-5f);
        auto gather_peer = [&]() {
            mbar_wait(bars + (B_XB + ph) * 8, 0);
#pragma unroll
            for (int i = 0; i < 4; i++) centre(16 + 4 * i, lds128(xrem + i * 2048));
        };
        auto sp = [&](float (&d)[32], int n, const uint32_t* af, int flip, int acc) {
            const uint32_t lo = rdesc + p.zero * (ph * 64 + n + 1) + (n % NSLOT) * (SLOT >> 4);
            const uint64_t b0 = mkdesc(lo + flip * 512), b1 = mkdesc(lo + (flip ^ 1) * 512);
            wg_fence();
            mma_sp(d, af, b0, meta, acc);
            mma_sp(d, af + 4, b0 + 256, meta, 1);
            mma_sp(d, af + 8, b1, meta, 1);
            mma_sp(d, af + 12, b1 + 256, meta, 1);
            wg_commit();
        };
        float d0[32], d1[32];

        if (ph == 0 || ph == 3) {
            uint32_t h[32], ho[32];
            const float rs = 0.5f * rstd;
            const uint32_t inb = bars + (B_INB + (ph & 2) + w) * 8;
            bool ready = true;
            const int eager = ph ? 0x5a : 0x54;
            auto step = [&](float (&d)[32], int n, const uint32_t* af, int flip, int acc, auto work) {
                const int l = n + (ph ? 38 : 0);
                if (!ready) acq(l);
                sp(d, l, af, flip, acc);
                if (n < 15) ready = mbar_test(fbar + ((l + 1) % NSLOT) * 8, ((l + 1) / NSLOT) & 1);
                wg_wait<1>();
                if (n > 0 && !((eager >> (n - 1)) & 1)) rel(l - 1);
                const uint32_t tie = work() & p.zero;
                if ((eager >> n) & 1) {
                    if (p.zero < l + 1) wg_wait<0>();
                    if (lane == 0) mbar_arrive(fbar + (B_EMPTY - B_FULL + l % NSLOT) * 8 + tie);
                }
            };
            auto none = []() { return 0u; };
            const int fl = ph ? w : 0;
            auto fetch = [&](int i) {
                bar_sync(10, 256);
                const uint32_t src = ((i & 1) ? hbuf : xown) ^ 4096;
                const uint4 u0 = lds128(src), u1 = lds128(src + 2048);
                ho[8 * i] = u0.x; ho[8 * i + 1] = u0.y; ho[8 * i + 2] = u0.z; ho[8 * i + 3] = u0.w;
                ho[8 * i + 4] = u1.x; ho[8 * i + 5] = u1.y; ho[8 * i + 6] = u1.z; ho[8 * i + 7] = u1.w;
                return u0.x | u1.x;
            };
            auto act = [&](float (&d)[32], int i) {
                if (i > 0) fetch(i - 1);
                else if (ph) bar_sync(10, 256);
                pin(d);
#pragma unroll
                for (int j = 0; j < 8; j++) {
                    const float u0 = (d[4 * j] + d[4 * j + 2]) * rs, u1 = (d[4 * j + 1] + d[4 * j + 3]) * rs;
                    h[8 * i + j] = pack2(fmaf(u0, tanh_fast(u0), u0), fmaf(u1, tanh_fast(u1), u1));
                }
                sts128((i & 1) ? hbuf : xown, h[8 * i], h[8 * i + 1], h[8 * i + 2], h[8 * i + 3]);
                sts128(((i & 1) ? hbuf : xown) + 2048, h[8 * i + 4], h[8 * i + 5], h[8 * i + 6], h[8 * i + 7]);
                return 0u;
            };
            TS(1 + (ph & 2) * 10);
            if (ph) {
                step(d0, 0, a, fl, 0, none);
                step(d1, 1, a, fl, 0, [&]() { gather_peer(); return 0u; });
                TS(32);
                step(d0, 2, a + 16, 0, 1, none);
                step(d1, 3, a + 16, 0, 1, [&]() { return act(d0, 0); });
            } else {
                step(d0, 0, a, fl, 0, none);
                TS(32);
                step(d0, 1, a + 16, 0, 1, none);
                step(d1, 2, a, fl, 0, [&]() { return act(d0, 0); });
                step(d1, 3, a + 16, 0, 1, none);
            }
            step(d0, 4, a, fl, 0, [&]() { return act(d1, 1); });
            TS(33);
            step(d0, 5, a + 16, 0, 1, none);
            step(d1, 6, a, fl, 0, [&]() { return act(d0, 2); });
            step(d1, 7, a + 16, 0, 1, none);
            step(d0, 8, h, 0, 0, [&]() { act(d1, 3); return fetch(3); });
            TS(2 + (ph & 2) * 10);
            step(d0, 9, ho, 0, 1, none);
            step(d0, 10, h + 16, 0, 1, none);
            step(d0, 11, ho + 16, 0, 1, none);
            uint32_t pk[8];
            auto pack_out = [&]() {
                pin(d0);
#pragma unroll
                for (int j = 0; j < 8; j++) pk[j] = pack2(d0[4 * j] + d0[4 * j + 2], d0[4 * j + 1] + d0[4 * j + 3]);
            };
            auto send = [&](int i) { st_async4(hbuf + 8192 + i * 2048 + peer, pk[4 * i], pk[4 * i + 1], pk[4 * i + 2], pk[4 * i + 3], inb + peer); };
            step(d1, 12, h, 0, 0, [&]() { pack_out(); send(0); return 0u; });
            TS(34);
            step(d1, 13, ho, 0, 1, [&]() { send(1); return 0u; });
            step(d1, 14, h + 16, 0, 1, none);
            step(d1, 15, ho + 16, 0, 1, none);
            mbar_wait(inb, 0);
#pragma unroll
            for (int i = 0; i < 2; i++) {
                const uint4 u = lds128(hbuf + 8192 + i * 2048);
                const uint32_t p0[4] = {u.x, u.y, u.z, u.w};
#pragma unroll
                for (int j = 0; j < 4; j++) {
                    v[8 * i + 2 * j] = fmaf(0.5f, blo(p0[j]), blo(xr[4 * i + j]));
                    v[8 * i + 2 * j + 1] = fmaf(0.5f, bhi(p0[j]), bhi(xr[4 * i + j]));
                }
            }
            wg_wait<0>();
            pin(d1);
            if (ph == 0) rel(15);
            TS(3 + (ph & 2) * 10);
#pragma unroll
            for (int j = 0; j < 8; j++) {
                v[2 * j] = fmaf(0.5f, d1[4 * j] + d1[4 * j + 2], v[2 * j]);
                v[2 * j + 1] = fmaf(0.5f, d1[4 * j + 1] + d1[4 * j + 3], v[2 * j + 1]);
            }
            return;
        }

        auto residual = [&](int n) {
            wg_wait<1>();
            rel(n);
            wg_wait<0>();
            pin(d0);
            rel(n + 1);
#pragma unroll
            for (int j = 0; j < 8; j++) {
                v[2 * j] = d0[4 * j] + d0[4 * j + 2] + blo(xr[j]);
                v[2 * j + 1] = d0[4 * j + 1] + d0[4 * j + 3] + bhi(xr[j]);
            }
        };

        if (ph == 2) {
            TS(39);
            sp(d0, 32, a, w, 0);
            acq(33);
            sp(d1, 33, a, w, 0);
            acq(34); acq(35);
            gather_peer();
            sp(d0, 34, a + 16, 0, 1);
            sp(d1, 35, a + 16, 0, 1);
            wg_wait<2>();
            rel(32);
            acq(36);
            bar_sync(10, 256);
            const float rs = trow < T_ ? 0.5f * rstd : 0.f;
            wg_wait<0>();
            pin(d0); pin(d1);
            TS(18);
            uint32_t pk[8];
#pragma unroll
            for (int j = 0; j < 8; j++) {
                const float u0 = (d0[4 * j] + d0[4 * j + 2]) * rs, u1 = (d0[4 * j + 1] + d0[4 * j + 3]) * rs;
                const float t0 = tanh_fast((d1[4 * j] + d1[4 * j + 2]) * rs), t1 = tanh_fast((d1[4 * j + 1] + d1[4 * j + 3]) * rs);
                pk[j] = pack2(fmaf(u0, t0, u0), fmaf(u1, t1, u1));
            }
            if (wq == 0 || wq == 3) {
                uint4* hp = &p.g->halo[((pair * 4 + tile) * 2 + (wq & 1)) * 64 + lane];
                st_data(hp, pk[0], pk[1], pk[2], pk[3]);
                st_data(hp + 32, pk[4], pk[5], pk[6], pk[7]);
            }
            const uint32_t gs = P + w * GCH + wq * 1024;
            stsm4(gs + 1024 + foff, pk[0], pk[1], pk[2], pk[3]);
            stsm4(gs + 1024 + (foff ^ 64), pk[4], pk[5], pk[6], pk[7]);
            bar_sync(8 + w, 192);
            TS(26);
            uint32_t ca[8], cb[8];
            const int e = (wq & 1) * 4;
            const uint32_t lo = ((mir ^ e) * 144) ^ (lane * 4);
            const int dir = mir ? -1024 : 1024;
            const uint32_t gb = P + w * GCH + (mir ? 3072 : 2048) + lo, sown_ = H + tile * HCH, so = sown_ + (mir ? 1024 : 2048) + lo;
            auto finish = [&](int i) {
                const uint32_t c = hadd2(ca[i], cb[i]);
                const float h0 = blo(c), h1 = bhi(c);
                const uint32_t dst = (so + (i >> 2) * dir) ^ ((i & 3) * 144), val = pack2(fmaf(h0, tanh_fast(h0), h0), fmaf(h1, tanh_fast(h1), h1));
                asm volatile("st.async.shared::cluster.mbarrier::complete_tx::bytes.b32 [%0], %1, [%2];" ::"r"(dst + peer), "r"(val), "r"(bars + B_SR * 8 + peer) : "memory");
                sts32(dst, val);
            };
#pragma unroll
            for (int k = 0; k < 26; k++) {
                if (k == 19) {
#pragma unroll
                    for (int i = 0; i < 4; i++) finish(i);
                    mbar_wait(bars + (B_HALO + 2 * w + (wq >> 1)) * 8, 0);
                    rel(33); rel(34); rel(35);
                    TS(27);
                }
                const uint32_t g = lds32((gb + (((k + 1) & 4) ? ((k + 1) >> 3) + (wq & 1) : ((k + 1) >> 3)) * dir) ^ (((k + 1) & 7) * 144));
#pragma unroll
                for (int i = 0; i < 8; i++) {
                    const int tap = k - (i & 3) - 2 * (i & 4);
                    if (tap == 0) ca[i] = hmul2(g, dwr[0]);
                    else if (tap > 0 && tap < 8) ca[i] = hfma2(g, dwr[tap], ca[i]);
                    else if (tap == 8) cb[i] = hmul2(g, dwr[8]);
                    else if (tap > 8 && tap < 15) cb[i] = hfma2(g, dwr[tap], cb[i]);
                }
            }
#pragma unroll
            for (int i = 4; i < 8; i++) finish(i);
            bar_sync(10, 256);
            TS(19);
            auto frags = [&](int i, int half) {
                const uint32_t src = H + 2 * half * HCH + wq * 1024;
#pragma unroll
                for (int k = 0; k < 4; k++) ldsm4(src + (k >> 1) * HCH + (foff ^ ((k & 1) * 64)), a[i + 4 * k], a[i + 4 * k + 1], a[i + 4 * k + 2], a[i + 4 * k + 3]);
            };
            frags(0, r);
            sp(d0, 36, a, 0, 0);
            acq(37);
            mbar_wait(bars + B_SR * 8, 0);
            frags(16, r ^ 1);
            sp(d0, 37, a + 16, 0, 1);
            residual(36);
            TS(20);
            return;
        }

        {
            TS(11);
            unsigned char* g = p.g->kvq + (size_t)((b * 4 + tile) * 1024 + trow) * 128;
            const uint32_t uo = (lane >> 2) * 128 + ((c4 ^ (lane >> 2)) << 4);
            auto put = [&](float (&d)[32], int i) {
                pin(d);
                uint32_t pk[8];
#pragma unroll
                for (int j = 0; j < 8; j++) pk[j] = pack2((d[4 * j] + d[4 * j + 2]) * rstd, (d[4 * j + 1] + d[4 * j + 3]) * rstd);
                if (i < 2) {
                    stg128(g + i * 1048576 + uo, make_uint4(pk[0], pk[1], pk[2], pk[3]));
                    stg128(g + i * 1048576 + (uo ^ 64), make_uint4(pk[4], pk[5], pk[6], pk[7]));
                } else {
                    const uint32_t stg = H + warp * 1024;
                    sts128(stg + uo, pk[0], pk[1], pk[2], pk[3]);
                    sts128(stg + (uo ^ 64), pk[4], pk[5], pk[6], pk[7]);
                    __syncwarp();
                    ldsm4(stg + foff, pk[0], pk[1], pk[2], pk[3]);
                    ldsm4(stg + (foff ^ 64), pk[4], pk[5], pk[6], pk[7]);
                    st_data(g + 2097152 + lane * 16, ~pk[0], ~pk[1], ~pk[2], ~pk[3]);
                    st_data(g + 2097152 + 512 + lane * 16, ~pk[4], ~pk[5], ~pk[6], ~pk[7]);
                }
            };
            sp(d0, 16, a, w, 0);
            acq(17);
            sp(d1, 17, a, w, 0);
            gather_peer();
            acq(18);
            sp(d0, 18, a + 16, 0, 1);
            wg_wait<1>();
            rel(16); rel(17);
            acq(19);
            sp(d1, 19, a + 16, 0, 1);
            wg_wait<1>();
            rel(18);
            put(d0, 0);
            wg_wait<0>();
            rel(19);
            TS(37);
            put(d1, 1);
            bar_arrive(4, 288);
            TS(38);
            acq(20);
            sp(d0, 20, a, w, 0);
            acq(21);
            sp(d0, 21, a + 16, 0, 1);
            wg_wait<0>();
            rel(20); rel(21);
            put(d0, 2);
            TS(12);
        }

        {
            constexpr float CS = 0.125f * 1.4426950408889634f;
            float sa[32], sb2[32], o[36];
            uint32_t pa[16], pb[16], q[16];
            float n0 = INFINITY, n1 = INFINITY;
            zero(o); zero(pa); zero(pb); zero(sb2);
            const uint32_t ones = H + 8192;
            { const uint32_t c = w ? 0u : 0x3F803F80u; sts128(ones + tid * 16, c, c, c, c); }
            fence_async_smem();
            bar_sync(10, 256);
            const uint32_t vdesc = rdesc + ((((ones - rbase) >> 4) - 1) << 16);
            auto qk_issue = [&](float (&s)[32], uint32_t lo) {
                const uint64_t kd = mkdesc(lo);
                wg_fence();
#pragma unroll
                for (int k = 0; k < 4; k++) mma_qk(s, q[4 * k], q[4 * k + 1], q[4 * k + 2], q[4 * k + 3], kd + 2 * k, k != 0);
                wg_commit();
            };
            auto both_issue = [&](float (&s)[32], uint32_t klo, uint32_t (&pp)[16], uint32_t vlo) {
                const uint64_t kd = mkdesc(klo), vd = mkdesc(vlo);
                wg_fence();
#pragma unroll
                for (int k = 0; k < 4; k++) {
                    mma_pv(o, pp[4 * k], pp[4 * k + 1], pp[4 * k + 2], pp[4 * k + 3], vd - k * (128 * 65535));
                    mma_qk(s, q[4 * k], q[4 * k + 1], q[4 * k + 2], q[4 * k + 3], kd + 2 * k, k != 0);
                }
                wg_commit();
            };
            auto new_max = [&](float (&s)[32], int nj, float& x0, float& x1) {
                x0 = s[0]; x1 = s[2];
#pragma unroll
                for (int j = 0; j < nj; j++) {
                    x0 = fmaxf(x0, fmaxf(s[4 * j], s[4 * j + 1]));
                    x1 = fmaxf(x1, fmaxf(s[4 * j + 2], s[4 * j + 3]));
                }
                x0 = fmaxf(x0, __shfl_xor_sync(~0u, x0, 1)); x1 = fmaxf(x1, __shfl_xor_sync(~0u, x1, 1));
                x0 = fmaxf(x0, __shfl_xor_sync(~0u, x0, 2)); x1 = fmaxf(x1, __shfl_xor_sync(~0u, x1, 2));
                x0 = fminf(n0, fmaf(x0, -CS, -20.f)); x1 = fminf(n1, fmaf(x1, -CS, -20.f));
            };
            auto probs = [&](float (&s)[32], uint32_t (&pp)[16], bool ready, bool tail, auto wait) {
                uint32_t any = 0;
#pragma unroll
                for (int i = 0; i < 16; i++) {
                    pp[i] = pack2(ex2(fmaf(s[2 * i], CS, (i & 1) ? n1 : n0)), ex2(fmaf(s[2 * i + 1], CS, (i & 1) ? n1 : n0)));
                    any |= pp[i];
                }
                wg_wait<0>();
                pin(sa); pin(sb2); pin(o); pin(pa); pin(pb);
                if (__builtin_expect(__any_sync(~0u, (any & 0x40004000u) || !ready), 0)) {
                    wait();
                    if (__any_sync(~0u, any & 0x40004000u)) {
                        if (tail) {
#pragma unroll
                            for (int i = 20; i < 32; i++) s[i] = -INFINITY;
                        }
                        float x0, x1;
                        new_max(s, 8, x0, x1);
                        const float sc0 = ex2(x0 - n0), sc1 = ex2(x1 - n1);
                        n0 = x0; n1 = x1;
#pragma unroll
                        for (int j = 0; j < 9; j++) { o[4 * j] *= sc0; o[4 * j + 1] *= sc0; o[4 * j + 2] *= sc1; o[4 * j + 3] *= sc1; }
#pragma unroll
                        for (int i = 0; i < 16; i++)
                            pp[i] = pack2(ex2(fmaf(s[2 * i], CS, (i & 1) ? n1 : n0)), ex2(fmaf(s[2 * i + 1], CS, (i & 1) ? n1 : n0)));
                    }
                }
            };
            {
                uint4 u[4];
                const unsigned char* src = p.g->kvq + 2097152 + (size_t)(abh * 1024 + qt * 64 + wq * 16) * 128 + lane * 16;
                spin(QGATE);
                ld_data<512, true>(u, src);
#pragma unroll
                for (int k = 0; k < 2; k++) {
                    q[8 * k] = ~u[k].x; q[8 * k + 1] = ~u[k + 2].x; q[8 * k + 2] = ~u[k].y; q[8 * k + 3] = ~u[k + 2].y;
                    q[8 * k + 4] = ~u[k].z; q[8 * k + 5] = ~u[k + 2].z; q[8 * k + 6] = ~u[k].w; q[8 * k + 7] = ~u[k + 2].w;
                }
                pin(q);
            }
            TS(40);
            acq(22);
            TS(13);
            qk_issue(sa, rdesc + (22 % NSLOT) * (SLOT >> 4));
            wg_wait<0>();
            pin(sa);
            {
                float x0, x1;
                new_max(sa, 2, x0, x1);
                n0 = x0; n1 = x1;
            }
            bar_arrive(6, 384);
            uint32_t vd = vdesc, kd = rdesc + 5 * (SLOT >> 4), vb = fbar, kb = fbar + 40;
            uint32_t vlast = vdesc - 4 * (SLOT >> 4) * 65535u, klast = rdesc + 4 * (SLOT >> 4) + 512;
            uint32_t kprev = fbar + 32, vprev = bars + (B_SINK - (B_EMPTY - B_FULL)) * 8;
#pragma unroll 1
            for (int it = 0; it < 4; it++) {
                both_issue(sb2, klast, pb, vlast);
                probs(sa, pa, mbar_test(vb, 0) & mbar_test(kb, it == 0), false, [&]() { mbar_wait(vb, 0); mbar_wait(kb, it == 0); });
                TS(41 + it * 4);
                if (lane == 0) mbar_arrive(kprev + (B_EMPTY - B_FULL) * 8);
                if (lane == 0) mbar_arrive(vprev + (B_EMPTY - B_FULL) * 8);
                both_issue(sa, kd, pa, vd);
                const int dv = it == 2 ? 1 : 2, dk = it == 0 ? -4 : 2;
                kprev = kb; vprev = vb; vlast = vd - 512 * 65535u; klast = kd + 512;
                vd -= dv * (SLOT >> 4) * 65535u; vb += dv * 8;
                kd += dk * (SLOT >> 4); kb += dk * 8;
                probs(sb2, pb, true, it == 3 && w == 1, []() {});
                TS(43 + it * 4);
            }
            wg_fence();
#pragma unroll
            for (int k = 0; k < 4; k++)
                mma_pv(o, pb[4 * k], pb[4 * k + 1], pb[4 * k + 2], pb[4 * k + 3], mkdesc(vlast - k * (128 * 65535) + (k > 1 ? w * ((k - 1) << 22) : 0)));
            wg_commit();
            const uint32_t mlw = sb + OFF_MISC + 1024 + (tid >> 2) * 8;
            unsigned char* odst = p.g->o + (size_t)(b * 128 + qt * 8 + 2 * wq + w) * 4096 + ah * 1024 + lane * 16;
            mbar_wait(bars + B_RST * 8, __any_sync(~0u, (mlw | (uint32_t)(size_t)odst) & p.zero));
            wg_wait<0>();
            pin(o); pin(pb); pin(sa); pin(sb2);
            rel(29);
            TS(14);
            auto merge = [&](int keep, float nk, float ns) {
                const int snd = 2 - keep;
                if (c4 == 0) sts64f(mlw, ns, o[32 + snd]);
#pragma unroll
                for (int j = 0; j < 2; j++)
                    sts128(hbuf + j * 2048, pack2(o[16 * j + snd], o[16 * j + snd + 1]), pack2(o[16 * j + 4 + snd], o[16 * j + 5 + snd]),
                           pack2(o[16 * j + 8 + snd], o[16 * j + 9 + snd]), pack2(o[16 * j + 12 + snd], o[16 * j + 13 + snd]));
                bar_sync(10, 256);
                const float2 u = lds64f(mlw ^ 256);
                const float x = fminf(nk, u.x);
                float a = ex2(x - nk), c = ex2(x - u.x);
                const float inv = rcp(fmaf(a, o[32 + keep], c * u.y));
                a *= inv; c *= inv;
                uint32_t pk[8];
#pragma unroll
                for (int j = 0; j < 2; j++) {
                    const uint4 t4 = lds128((hbuf ^ 4096) + j * 2048);
                    const uint32_t t[4] = {t4.x, t4.y, t4.z, t4.w};
#pragma unroll
                    for (int i = 0; i < 4; i++)
                        pk[4 * j + i] = pack2(fmaf(a, o[16 * j + 4 * i + keep], c * blo(t[i])), fmaf(a, o[16 * j + 4 * i + keep + 1], c * bhi(t[i])));
                }
                st_data(odst, pk[0], pk[1], pk[2], pk[3]);
                st_data(odst + 512, pk[4], pk[5], pk[6], pk[7]);
            };
            if (tid < 128) merge(0, n0, n1); else merge(2, n1, n0);
            if (tid == 0) asm volatile("red.relaxed.gpu.global.add.u32 [%0], 1;" ::"l"(&p.g->epoch[blockIdx.x * FS]) : "memory");
            TS(15);
        }

        {
            const uint32_t* dp = reinterpret_cast<const uint32_t*>(p.dw + (mir ? 14 * 256 : 0) + tile * 64) + lane;
#pragma unroll
            for (int i = 0; i < 15; i++) asm volatile("ld.global.nc.b32 %0, [%1];" : "=r"(dwr[i]) : "l"(dp + i * (mir ? -128 : 128)));
            acq(30); acq(31); acq(32);
            uint4 u[8];
            ld_data<512>(u, p.g->o + (size_t)(b * 128 + pt * 4 + wq) * 4096 + lane * 16);
#pragma unroll
            for (int i = 0; i < 8; i++) { a[4 * i] = u[i].x; a[4 * i + 1] = u[i].y; a[4 * i + 2] = u[i].z; a[4 * i + 3] = u[i].w; }
            TS(16);
            sp(d0, 30, a, 0, 0);
            sp(d0, 31, a + 16, 0, 1);
#pragma unroll
            for (int i = 0; i < 15; i++) dwr[i] = hmul2(dwr[i], 0x3F003F00u);
            residual(30);
            TS(17);
        }
    };
    phase(std::integral_constant<int, 0>{});
    phase(std::integral_constant<int, 1>{});
    phase(std::integral_constant<int, 2>{});
    phase(std::integral_constant<int, 3>{});
    phase(std::integral_constant<int, 4>{});

    cluster_arrive();
    TS(24);
    {
        const float rstd = rsq(fmaxf(fmaf(-mean, mean, msq), 0.f) + 1e-5f), nb = -mean * rstd;
#pragma unroll
        for (int j = 0; j < 8; j++) xr[j] = pack2(fmaf(v[2 * j], rstd, nb), fmaf(v[2 * j + 1], rstd, nb));
        const uint32_t stg = H + warp * 1024;
        stsm4(stg + foff, xr[0], xr[1], xr[2], xr[3]);
        stsm4(stg + (foff ^ 64), xr[4], xr[5], xr[6], xr[7]);
        __syncwarp();
        const uint32_t src = stg + (lane >> 3) * 128 + (((lane & 7) ^ (lane >> 3)) << 4);
        const uint4 u0 = lds128(src), u1 = lds128((src + 512) ^ 64);
        __nv_bfloat16* dst = p.out + (size_t)(b * T_ + trow + (lane >> 3)) * 256 + tile * 64 + (lane & 7) * 8;
        if (trow < T_) { stg128(dst, u0); stg128(dst + 4 * 256, u1); }
    }
    TS(25);
    TG(31);
    TSDUMP();
    cluster_wait();
}

typedef CUresult (*EncodeFn)(CUtensorMap*, CUtensorMapDataType, cuuint32_t, void*, const cuuint64_t*, const cuuint64_t*,
                             const cuuint32_t*, const cuuint32_t*, CUtensorMapInterleave, CUtensorMapSwizzle,
                             CUtensorMapL2promotion, CUtensorMapFloatOOBfill);

}

extern "C" void kernel_launch(void* const* d_in, const int* in_sizes, int n_in, void* d_out, int out_size) {
    static EncodeFn encode = nullptr;
    if (!encode) {
        void* fn = nullptr;
        cudaDriverEntryPointQueryResult qr;
        cudaGetDriverEntryPoint("cuTensorMapEncodeTiled", &fn, cudaEnableDefault, &qr);
        encode = (EncodeFn)fn;
        cudaFuncSetAttribute(conformer_kernel, cudaFuncAttributeMaxDynamicSharedMemorySize, SMEM_LAUNCH);
    }
    Scalars p;
    Maps m;
    const cuuint32_t ones[5] = {1, 1, 1, 1, 1};
    const int idx[8] = {1, 2, 3, 4, 5, 7, 8, 9};
    const int rows[8] = {256, 1024, 256, 256, 256, 256, 256, 1024};
    const int cols[8] = {1024, 256, 768, 256, 512, 256, 1024, 256};
    for (int i = 0; i < 8; i++) {
        const cuuint64_t pitch = (cuuint64_t)cols[i] * 2;
        const bool f = i != 0 && i != 3;
        const cuuint64_t dims[5] = {(cuuint64_t)cols[i], f ? 2u : 4u, f ? 2u : 4u, f ? 4u : 2u, (cuuint64_t)rows[i] / (f ? 16 : 32)};
        const cuuint64_t strides[4] = {pitch, pitch * 8, pitch * (f ? 2 : 4), pitch * (f ? 16 : 32)};
        const cuuint32_t box[5] = {64, f ? 2u : 4u, f ? 2u : 4u, f ? 4u : 2u, f ? 8u : 4u};
        encode(&m.tm[i], CU_TENSOR_MAP_DATA_TYPE_BFLOAT16, 5, d_in[idx[i]], dims, strides, box, ones, CU_TENSOR_MAP_INTERLEAVE_NONE,
               CU_TENSOR_MAP_SWIZZLE_128B, CU_TENSOR_MAP_L2_PROMOTION_L2_128B, CU_TENSOR_MAP_FLOAT_OOB_FILL_NONE);
        m.w[i] = (const char*)d_in[idx[i]];
    }
    {
        void* kv = nullptr;
        cudaGetSymbolAddress(&kv, g_scratch);
        p.g = (Scratch*)kv;
        const cuuint64_t dims[2] = {64, 16384};
        const cuuint64_t strides[1] = {128};
        const cuuint32_t box[2] = {64, 128};
        encode(&m.tm[8], CU_TENSOR_MAP_DATA_TYPE_BFLOAT16, 2, kv, dims, strides, box, ones, CU_TENSOR_MAP_INTERLEAVE_NONE,
               CU_TENSOR_MAP_SWIZZLE_NONE, CU_TENSOR_MAP_L2_PROMOTION_L2_128B, CU_TENSOR_MAP_FLOAT_OOB_FILL_NONE);
    }
    p.x = (const __nv_bfloat16*)d_in[0];
    p.dw = (const __nv_bfloat16*)d_in[6];
    p.out = (__nv_bfloat16*)d_out;
    p.zero = 0;
    conformer_kernel<<<NCTA, NTHREADS, SMEM_LAUNCH>>>(p, m);
}
```

```cpp
#include <cuda_runtime.h>
#include <cuda_bf16.h>
#include <cuda.h>
#include <stdint.h>
#include <type_traits>

namespace {

constexpr int T_ = 1000;
constexpr int NCTA = 128;
constexpr int NTHREADS = 512;
constexpr int NSLOT = 6;
constexpr int SLOT = 16384;
constexpr int NLOADS = 54;

constexpr uint32_t OFF_RING = 0;
constexpr uint32_t OFF_P = 196608;
constexpr uint32_t OFF_H = 212992;
constexpr uint32_t OFF_MISC = 229376;
constexpr uint32_t OFF_BARS = 230912;
constexpr uint32_t SMEM_BYTES = 231424;
constexpr uint32_t GCH = 6144;
constexpr uint32_t HCH = 4096;

constexpr int B_FULL = 0, B_EMPTY = 12, B_XA = 24  , B_XB = 29  , B_INB = 33  , B_SR = 37,
              B_RST = 38, B_RDY = 39  , B_SINK = 43, B_HALO = 44  , NBARS = 48;

#define PACE KDELAY = 250, KD2 = 300, KD3 = 500, QGATE = 700, HDELAY = 200
constexpr uint32_t PACE;
#define GB 1
#define GT 2
constexpr int FS = 8;

struct Scratch {
    unsigned char kvq[3 * 8 * 1024 * 128];
    unsigned char o[2 * 128 * 4096];
    uint4 halo[64 * 4 * 2 * 64];
    uint32_t flag_kv[8 * 32 * FS];
    uint32_t reset[2 * 32];
    uint32_t epoch[NCTA * FS];
};
__device__ __align__(1024) Scratch g_scratch;

struct Scalars {
    const __nv_bfloat16* x;
    const __nv_bfloat16* dw;
    __nv_bfloat16* out;
    Scratch* g;
    uint32_t zero;
};
struct Maps {
    CUtensorMap tm[9];
    const char* w[8];
};

#define TS(i) do { } while (0)
#define TSW(i) do { } while (0)
#define TG(i) do { } while (0)
#define TSINIT() do { } while (0)
#define TSDUMP() do { } while (0)
constexpr uint32_t SMEM_LAUNCH = SMEM_BYTES;

__device__ __forceinline__ uint32_t smem_u32(const void* p) { return (uint32_t)__cvta_generic_to_shared(p); }
__device__ __forceinline__ void mbar_init(uint32_t b, uint32_t c) { asm volatile("mbarrier.init.shared::cta.b64 [%0], %1;" ::"r"(b), "r"(c) : "memory"); }
__device__ __forceinline__ void mbar_arrive(uint32_t b) { asm volatile("mbarrier.arrive.shared::cta.b64 _, [%0];" ::"r"(b) : "memory"); }
__device__ __forceinline__ void mbar_arrive_tx(uint32_t b, uint32_t tx) { asm volatile("mbarrier.arrive.expect_tx.shared::cta.b64 _, [%0], %1;" ::"r"(b), "r"(tx) : "memory"); }
__device__ __forceinline__ void mbar_wait(uint32_t b, uint32_t ph) {
    asm volatile("{\n.reg .pred p, q;\n.reg .u32 c;\nmov.u32 c, 0;\n"
                 "MW_LOOP:\n.pragma \"nounroll\";\n"
                 "mbarrier.try_wait.parity.shared::cta.b64 p, [%0], %1;\n"
                 "add.u32 c, c, 1;\nsetp.lt.u32 q, c, 65536;\nnot.pred p, p;\nand.pred p, p, q;\n@p bra MW_LOOP;\n}"
                 ::"r"(b), "r"(ph) : "memory");
}
__device__ __forceinline__ bool mbar_test(uint32_t b, uint32_t ph) {
    uint32_t ok;
    asm volatile("{\n.reg .pred p;\nmbarrier.test_wait.parity.shared::cta.b64 p, [%1], %2;\nselp.u32 %0, 1, 0, p;\n}" : "=r"(ok) : "r"(b), "r"(ph) : "memory");
    return ok;
}
__device__ __forceinline__ uint32_t mapa(uint32_t a, uint32_t r) { uint32_t o; asm("mapa.shared::cluster.u32 %0, %1, %2;" : "=r"(o) : "r"(a), "r"(r)); return o; }
__device__ __forceinline__ void fence_async_smem() { asm volatile("fence.proxy.async.shared::cta;" ::: "memory"); }
__device__ __forceinline__ void fence_async_global() { asm volatile("fence.proxy.async.global;" ::: "memory"); }
__device__ __forceinline__ void bar_sync(int id, int n) { asm volatile("bar.sync %0, %1;" ::"r"(id), "r"(n) : "memory"); }
__device__ __forceinline__ void bar_arrive(int id, int n) { asm volatile("bar.arrive %0, %1;" ::"r"(id), "r"(n) : "memory"); }
__device__ __forceinline__ void cluster_arrive() { asm volatile("barrier.cluster.arrive.relaxed.aligned;" ::: "memory"); }
__device__ __forceinline__ void cluster_wait() { asm volatile("barrier.cluster.wait.aligned;" ::: "memory"); }

__device__ __forceinline__ void ring_load(uint32_t dst, const CUtensorMap* tm, int col, int row16, uint32_t bar) {
    asm volatile("{\n.reg .pred p;\nelect.sync _|p, 0xffffffff;\n"
                 "@p mbarrier.arrive.expect_tx.shared::cta.b64 _, [%2], 16384;\n"
                 "@p cp.async.bulk.tensor.5d.shared::cluster.global.mbarrier::complete_tx::bytes [%0], [%1, {%3, 0, 0, 0, %4}], [%2];\n}"
                 ::"r"(dst), "l"(tm), "r"(bar), "r"(col), "r"(row16) : "memory");
}
__device__ __forceinline__ void ring_load_both(uint32_t dst, const CUtensorMap* tm, int c1, uint32_t bar) {
    asm volatile("{\n.reg .pred p;\nelect.sync _|p, 0xffffffff;\n"
                 "@p cp.async.bulk.tensor.2d.shared::cluster.global.mbarrier::complete_tx::bytes.multicast::cluster [%0], [%1, {0, %3}], [%2], %4;\n}"
                 ::"r"(dst), "l"(tm), "r"(bar), "r"(c1), "h"((uint16_t)3) : "memory");
}
__device__ __forceinline__ void mbar_arrive_peer(uint32_t b) { asm volatile("mbarrier.arrive.relaxed.cluster.shared::cluster.b64 _, [%0];" ::"r"(b) : "memory"); }
__device__ __forceinline__ void prefetch_l2(const void* src, uint32_t bytes) {
    asm volatile("cp.async.bulk.prefetch.L2.global [%0], %1;" ::"l"(src), "r"(bytes) : "memory");
}
__device__ __forceinline__ void st_async4(uint32_t dst, uint32_t a, uint32_t b, uint32_t c, uint32_t d, uint32_t bar) {
    asm volatile("st.async.shared::cluster.mbarrier::complete_tx::bytes.v4.b32 [%0], {%1,%2,%3,%4}, [%5];" ::"r"(dst), "r"(a), "r"(b), "r"(c), "r"(d), "r"(bar) : "memory");
}
__device__ __forceinline__ void put_sums(uint32_t dst, uint32_t rdst, float a, float b, uint32_t rbar, bool on) {
    asm volatile("{\n.reg .pred p;\nsetp.ne.u32 p, %5, 0;\n"
                 "@p st.async.shared::cluster.mbarrier::complete_tx::bytes.v2.f32 [%1], {%2,%3}, [%4];\n"
                 "@p st.shared.v2.f32 [%0], {%2,%3};\n}" ::"r"(dst), "r"(rdst), "f"(a), "f"(b), "r"(rbar), "r"((uint32_t)on) : "memory");
}
__device__ __forceinline__ void stsm4(uint32_t a, uint32_t r0, uint32_t r1, uint32_t r2, uint32_t r3) {
    asm volatile("stmatrix.sync.aligned.m8n8.x4.shared.b16 [%0], {%1,%2,%3,%4};" ::"r"(a), "r"(r0), "r"(r1), "r"(r2), "r"(r3) : "memory");
}
__device__ __forceinline__ void ldsm4(uint32_t a, uint32_t& r0, uint32_t& r1, uint32_t& r2, uint32_t& r3) {
    asm volatile("ldmatrix.sync.aligned.m8n8.x4.shared.b16 {%0,%1,%2,%3}, [%4];" : "=r"(r0), "=r"(r1), "=r"(r2), "=r"(r3) : "r"(a) : "memory");
}
__device__ __forceinline__ uint4 lds128(uint32_t a) { uint4 v; asm volatile("ld.shared.v4.b32 {%0,%1,%2,%3}, [%4];" : "=r"(v.x), "=r"(v.y), "=r"(v.z), "=r"(v.w) : "r"(a) : "memory"); return v; }
__device__ __forceinline__ float4 lds128f(uint32_t a) { float4 v; asm volatile("ld.shared.v4.f32 {%0,%1,%2,%3}, [%4];" : "=f"(v.x), "=f"(v.y), "=f"(v.z), "=f"(v.w) : "r"(a) : "memory"); return v; }
__device__ __forceinline__ float2 lds64f(uint32_t a) { float2 v; asm volatile("ld.shared.v2.f32 {%0,%1}, [%2];" : "=f"(v.x), "=f"(v.y) : "r"(a) : "memory"); return v; }
__device__ __forceinline__ uint32_t lds32(uint32_t a) { uint32_t v; asm volatile("ld.shared.b32 %0, [%1];" : "=r"(v) : "r"(a) : "memory"); return v; }
__device__ __forceinline__ void sts128(uint32_t a, uint32_t x, uint32_t y, uint32_t z, uint32_t w) { asm volatile("st.shared.v4.b32 [%0], {%1,%2,%3,%4};" ::"r"(a), "r"(x), "r"(y), "r"(z), "r"(w) : "memory"); }
__device__ __forceinline__ void sts128f(uint32_t a, float x, float y, float z, float w) { asm volatile("st.shared.v4.f32 [%0], {%1,%2,%3,%4};" ::"r"(a), "f"(x), "f"(y), "f"(z), "f"(w) : "memory"); }
__device__ __forceinline__ void sts64f(uint32_t a, float x, float y) { asm volatile("st.shared.v2.f32 [%0], {%1,%2};" ::"r"(a), "f"(x), "f"(y) : "memory"); }
__device__ __forceinline__ void sts32(uint32_t a, uint32_t x) { asm volatile("st.shared.b32 [%0], %1;" ::"r"(a), "r"(x) : "memory"); }
__device__ __forceinline__ void stg128(void* p, uint4 v) { asm volatile("st.global.v4.b32 [%0], {%1,%2,%3,%4};" ::"l"(p), "r"(v.x), "r"(v.y), "r"(v.z), "r"(v.w) : "memory"); }

__device__ __forceinline__ uint32_t pack2(float lo, float hi) { uint32_t r; asm("cvt.rn.bf16x2.f32 %0, %1, %2;" : "=r"(r) : "f"(hi), "f"(lo)); return r; }
__device__ __forceinline__ float blo(uint32_t v) { return __uint_as_float(v << 16); }
__device__ __forceinline__ float bhi(uint32_t v) { return __uint_as_float(v & 0xffff0000u); }
__device__ __forceinline__ uint32_t hmul2(uint32_t a, uint32_t b) { uint32_t r; asm("mul.rn.bf16x2 %0, %1, %2;" : "=r"(r) : "r"(a), "r"(b)); return r; }
__device__ __forceinline__ uint32_t hadd2(uint32_t a, uint32_t b) { uint32_t r; asm("add.rn.bf16x2 %0, %1, %2;" : "=r"(r) : "r"(a), "r"(b)); return r; }
__device__ __forceinline__ uint32_t hsub2(uint32_t a, uint32_t b) { uint32_t r; asm("sub.rn.bf16x2 %0, %1, %2;" : "=r"(r) : "r"(a), "r"(b)); return r; }
__device__ __forceinline__ uint32_t hfma2(uint32_t a, uint32_t b, uint32_t c) { uint32_t r; asm("fma.rn.bf16x2 %0, %1, %2, %3;" : "=r"(r) : "r"(a), "r"(b), "r"(c)); return r; }
__device__ __forceinline__ float tanh_fast(float x) { float r; asm("tanh.approx.f32 %0, %1;" : "=f"(r) : "f"(x)); return r; }
__device__ __forceinline__ float rsq(float x) { float r; asm("rsqrt.approx.ftz.f32 %0, %1;" : "=f"(r) : "f"(x)); return r; }
__device__ __forceinline__ float rcp(float x) { float r; asm("rcp.approx.ftz.f32 %0, %1;" : "=f"(r) : "f"(x)); return r; }
__device__ __forceinline__ float ex2(float x) { float r; asm("ex2.approx.ftz.f32 %0, %1;" : "=f"(r) : "f"(x)); return r; }

__device__ __forceinline__ uint32_t ld_relaxed(const uint32_t* p) {
    uint32_t v;
    asm volatile("ld.relaxed.gpu.global.u32 %0, [%1];" : "=r"(v) : "l"(p) : "memory");
    return v;
}
__device__ __forceinline__ uint32_t clock32() { uint32_t c; asm volatile("mov.u32 %0, %%clock;" : "=r"(c)::"memory"); return c; }
__device__ __forceinline__ void spin(uint32_t clks) {
    const uint32_t t0 = clock32();
    while (clock32() - t0 < clks) {}
}
__device__ __forceinline__ void flag_wait(const uint32_t* p, uint32_t e, bool mine) {
#pragma unroll 1
    for (int i = 0; i < (1 << 19); i++) {
        if (mine) mine = ld_relaxed(p) != e;
        if (!__any_sync(~0u, mine)) break;
    }
    asm volatile("fence.acquire.gpu;" ::: "memory");
    fence_async_global();
}
__device__ __forceinline__ void st_data(void* p, uint32_t x, uint32_t y, uint32_t z, uint32_t w) {
    asm volatile("st.relaxed.gpu.global.v4.b32 [%0], {%1,%2,%3,%4};" ::"l"(p), "r"(x), "r"(y), "r"(z), "r"(w) : "memory");
}
template <int STRIDE, bool INV = false, int N>
__device__ __forceinline__ void ld_data(uint4 (&v)[N], const unsigned char* p) {
    int it = 0;
    bool again;
#pragma unroll 1
    do {
        uint32_t m = INV ? ~0u : 0u;
#pragma unroll
        for (int i = 0; i < N; i++)
            asm volatile("ld.relaxed.gpu.global.v4.b32 {%0,%1,%2,%3}, [%4];" : "=r"(v[i].x), "=r"(v[i].y), "=r"(v[i].z), "=r"(v[i].w) : "l"(p + i * STRIDE) : "memory");
#pragma unroll
        for (int i = 0; i < N; i++)
            m = INV ? __vimin3_u32(__vimin3_u32(v[i].x, v[i].y, v[i].z), v[i].w, m) : __vimax3_u32(__vimax3_u32(v[i].x, v[i].y, v[i].z), v[i].w, m);
        again = __any_sync(~0u, m == (INV ? 0u : ~0u)) && ++it < (1 << 16);
    } while (again);
}
__device__ __forceinline__ uint32_t ld_epoch(const Scratch* g) { return ld_relaxed(&g->epoch[blockIdx.x * FS]) + 1; }
__device__ __forceinline__ void flag_set(uint32_t* p, uint32_t e) { asm volatile("st.release.gpu.global.u32 [%0], %1;" ::"l"(p), "r"(e) : "memory"); }

__device__ __forceinline__ uint32_t desc_lo(uint32_t addr) { return ((addr & 0x3FFFF) >> 4) | 0x10000u; }
__device__ __forceinline__ uint64_t mkdesc(uint32_t lo) { return (uint64_t)lo | (0x40000040ull << 32); }
__device__ __forceinline__ void wg_fence() { asm volatile("wgmma.fence.sync.aligned;" ::: "memory"); }
__device__ __forceinline__ void wg_commit() { asm volatile("wgmma.commit_group.sync.aligned;" ::: "memory"); }
template <int N> __device__ __forceinline__ void wg_wait() { asm volatile("wgmma.wait_group.sync.aligned %0;" ::"n"(N) : "memory"); }
template <int N> __device__ __forceinline__ void pin(float (&d)[N]) {
#pragma unroll
    for (int i = 0; i < N; i++) asm volatile("" : "+f"(d[i])::"memory");
}
template <int N> __device__ __forceinline__ void pin(uint32_t (&d)[N]) {
#pragma unroll
    for (int i = 0; i < N; i++) asm volatile("" : "+r"(d[i])::"memory");
}

template <typename Tp, int N> __device__ __forceinline__ void zero(Tp (&d)[N]) {
#pragma unroll
    for (int i = 0; i < N; i++) d[i] = 0;
    pin(d);
}

#define F4(d, i) "+f"(d[i]), "+f"(d[i + 1]), "+f"(d[i + 2]), "+f"(d[i + 3])
#define F16(d, i) F4(d, i), F4(d, i + 4), F4(d, i + 8), F4(d, i + 12)

__device__ __forceinline__ void mma16(float (&d)[4], const uint32_t* a, uint32_t b0, uint32_t b1) {
    asm("mma.sync.aligned.m16n8k16.row.col.f32.bf16.bf16.f32 {%0,%1,%2,%3}, {%4,%5,%6,%7}, {%8,%9}, {%0,%1,%2,%3};"
        : F4(d, 0) : "r"(a[0]), "r"(a[1]), "r"(a[2]), "r"(a[3]), "r"(b0), "r"(b1));
}
template <int N>
__device__ __forceinline__ float row_sum(const uint32_t* x, uint32_t ones = 0x3F803F80u) {
    float c[4] = {};
#pragma unroll
    for (int i = 0; i < N; i += 4) mma16(c, x + i, ones, ones);
    return c[0] + c[2];
}
template <int N>
__device__ __forceinline__ float row_sumsq(const uint32_t* x, int lane) {
    float c0[4] = {}, c1[4] = {};
#pragma unroll
    for (int i = 0; i < N; i += 4) {
        mma16(c0, x + i, x[i], x[i + 2]);
        mma16(c1, x + i, x[i + 1], x[i + 3]);
    }
    return (lane & 4) ? c0[1] + c1[3] : c0[0] + c1[2];
}
__device__ __forceinline__ void mma_sp(float (&d)[32], const uint32_t* a, uint64_t b, uint32_t meta, int acc) {
    asm volatile("{.reg .pred p; setp.ne.b32 p, %38, 0;\n"
                 "wgmma.mma_async.sp.sync.aligned.m64n64k32.f32.bf16.bf16 {%0,%1,%2,%3,%4,%5,%6,%7,%8,%9,%10,%11,%12,%13,%14,%15,%16,%17,%18,%19,%20,%21,%22,%23,%24,%25,%26,%27,%28,%29,%30,%31}, "
                 "{%32,%33,%34,%35}, %36, %37, 0, p, 1, 1, 1;}\n"
                 : F16(d, 0), F16(d, 16) : "r"(a[0]), "r"(a[1]), "r"(a[2]), "r"(a[3]), "l"(b), "r"(meta), "r"(acc));
}
__device__ __forceinline__ void mma_qk(float (&d)[32], uint32_t a0, uint32_t a1, uint32_t a2, uint32_t a3, uint64_t b, int acc) {
    asm volatile("{.reg .pred p; setp.ne.b32 p, %37, 0;\n"
                 "wgmma.mma_async.sync.aligned.m64n64k16.f32.bf16.bf16 {%0,%1,%2,%3,%4,%5,%6,%7,%8,%9,%10,%11,%12,%13,%14,%15,%16,%17,%18,%19,%20,%21,%22,%23,%24,%25,%26,%27,%28,%29,%30,%31}, "
                 "{%32,%33,%34,%35}, %36, p, 1, 1, 0;}\n"
                 : F16(d, 0), F16(d, 16) : "r"(a0), "r"(a1), "r"(a2), "r"(a3), "l"(b), "r"(acc));
}
__device__ __forceinline__ void mma_pv(float (&d)[36], uint32_t a0, uint32_t a1, uint32_t a2, uint32_t a3, uint64_t b) {
    asm volatile("wgmma.mma_async.sync.aligned.m64n72k16.f32.bf16.bf16 {%0,%1,%2,%3,%4,%5,%6,%7,%8,%9,%10,%11,%12,%13,%14,%15,%16,%17,%18,%19,%20,%21,%22,%23,%24,%25,%26,%27,%28,%29,%30,%31,%32,%33,%34,%35}, "
                 "{%36,%37,%38,%39}, %40, 1, 1, 1, 1;\n"
                 : F16(d, 0), F16(d, 16), F4(d, 32) : "r"(a0), "r"(a1), "r"(a2), "r"(a3), "l"(b));
}

__device__ __forceinline__ uint32_t load_code(int n, int r, int w) {
    const int tile = 2 * r + w;
    int m, col, row;
    if (n < 16 || n >= 38) {
        const int k = n < 16 ? n : n - 38;
        m = n < 16 ? 0 : 6;
        if (n >= 38 && k < 4) { col = 4 * tile + (k & 1); row = (k >> 1) ^ r; }
        else if (k < 8) { col = 4 * tile + (k >> 1); row = n < 16 ? (k & 1) : (k & 1) ^ r; }
        else { m++; col = k < 12 ? tile ^ 2 : tile; row = 2 * (tile ^ (k & 1)) + ((k >> 1) & 1); }
    } else if (n < 30) {
        const int k = n - 16;
        m = 2;
        if (k < 4) { col = tile + ((k & 1) ? 8 : 4); row = (k >> 1) ^ r; }
        else { col = tile; row = (k & 1) ^ r; }
    } else if (n < 32) { m = 3; col = tile; row = n - 30; }
    else if (n < 36) { const int k = n - 32; m = 4; col = tile + 4 * ((k & 1) ^ GB); row = (k >> 1) ^ r; }
    else { m = 5; col = tile; row = (n & 1) ^ r; }
    return m | (col << 4) | (row << ((m == 0 || m == 3) ? 10 : 11));
}

__global__ void __cluster_dims__(2, 1, 1) __launch_bounds__(NTHREADS, 1)
conformer_kernel(const Scalars p, const __grid_constant__ Maps m) {
    extern __shared__ __align__(1024) unsigned char smem_raw[];
    const uint32_t sb = smem_u32(smem_raw);
    const uint32_t bars = sb + OFF_BARS;
    const int tid = threadIdx.x;
    const int lane = tid & 31;
    const int warp = __shfl_sync(~0u, tid >> 5, 0);
    const int r = blockIdx.x & 1;
    const int pair = blockIdx.x >> 1;
    const int b = pair >> 5, pt = pair & 31;
    const int ah = pt >> 3, qt = (pt & 7) * 2 + r;
    const int abh = b * 4 + ah;

    TSINIT();
    TS(0);
    TG(30);
    const uint32_t P = sb + OFF_P, H = sb + OFF_H;
    if (warp == 11) {
        if (lane == 0) {
#pragma unroll
            for (int i = 0; i < 2 * NSLOT; i++) mbar_init(bars + (B_FULL + i) * 8, 1);
            asm volatile("fence.mbarrier_init.release.cluster;" ::: "memory");
            fence_async_smem();
        }
        __syncwarp();
        bar_arrive(13, 96);
        cluster_arrive();
    }

    if (warp >= 8) {
        asm volatile("setmaxnreg.dec.sync.aligned.u32 48;");
        if (warp >= 12) {
            cluster_arrive();
            const int ut = tid & 127;
            cluster_wait();
            const uint32_t target = ld_epoch(p.g) * 64;
            bar_sync(6, 384);
#pragma unroll
            for (int i = 0; i < 4; i++) {
                st_data(p.g->o + (size_t)(b * 128 + qt * 8 + 2 * i + (ut >> 6)) * 4096 + ah * 1024 + (ut & 63) * 16, ~0u, ~0u, ~0u, ~0u);
                if (i < 2) st_data(&p.g->halo[(pair * 4 + 2 * r + i) * 128 + ut], ~0u, ~0u, ~0u, ~0u);
            }
            bar_sync(11, 128);
            if (ut == 0) {
                asm volatile("red.release.gpu.global.add.u32 [%0], 1;" ::"l"(&p.g->reset[b * 32]) : "memory");
#pragma unroll 1
                for (int i = 0; i < (1 << 20) && ld_relaxed(&p.g->reset[b * 32]) != target; i++) __nanosleep(100);
                asm volatile("fence.acquire.gpu;" ::: "memory");
                mbar_arrive(bars + B_RST * 8);
            }
            bar_sync(11, 128);
            TS(14);
#pragma unroll
            for (int i = 0; i < 4; i++) st_data(p.g->kvq + 2097152 + (size_t)(abh * 1024 + qt * 64) * 128 + i * 2048 + ut * 16, 0, 0, 0, 0);
            const int side = warp & 1, wg = (warp >> 1) & 1, np = side ? pt + 1 : pt - 1;
            const unsigned char* src = reinterpret_cast<const unsigned char*>(&p.g->halo[(((b * 32 + np) * 4 + 2 * r + wg) * 2 + (side ^ 1)) * 64 + lane]);
            const uint32_t dst = P + wg * GCH + side * 5120 + (lane & 7) * 128 + (((lane >> 3) ^ (lane & 7)) << 4);
            uint4 hv[2] = {make_uint4(0, 0, 0, 0), make_uint4(0, 0, 0, 0)};
            bar_sync(8 + wg, 192);
            if (np >= 0 && np < 32) {
                spin(HDELAY);
                ld_data<512>(hv, src);
            }
            stsm4(dst, hv[0].x, hv[0].y, hv[0].z, hv[0].w);
            stsm4(dst ^ 64, hv[1].x, hv[1].y, hv[1].z, hv[1].w);
            __syncwarp();
            if (lane == 0) mbar_arrive(bars + (B_HALO + (warp & 3)) * 8);
            TS(4);
        } else if (warp < 10) {
            const int w = warp - 8;
            const uint32_t ring = sb + OFF_RING + w * NSLOT * SLOT;
            const uint32_t full = bars + (B_FULL + w * NSLOT) * 8;
            cluster_arrive();
            bar_sync(13, 96);
            TS(1);
#pragma unroll
            for (int n = 0; n < NSLOT; n++) {
                if (n == 1) bar_sync(12, 64);
                ring_load(ring + n * SLOT, &m.tm[0], 64 * (8 * r + 4 * w + (n >> 1)), 4 * (n & 1), full + n * 8);
            }
            TS(2);
            const uint32_t code = load_code(lane, r, w) | (load_code(lane + 32, r, w) << 16);
            cluster_wait();
            uint32_t s = 0, ph = 0;
            int n = NSLOT;
#pragma unroll 1
            for (int seg = 0; seg < 2; seg++) {
#pragma unroll 1
                for (; n < (seg == 0 ? 22 : NLOADS); n++) {
                    const uint32_t c = __shfl_sync(~0u, code, n) >> (n & 32 ? 16 : 0);
                    const CUtensorMap* tm = &m.tm[c & 15];
                    const uint32_t col = (c & 0xf0) * 4, row = (c & 0xff00) >> 8, dst = ring + s * SLOT;
                    mbar_wait(full + (B_EMPTY - B_FULL) * 8 + s * 8, ph + (((uint32_t)(size_t)tm | col | row | dst) & p.zero));
                    ring_load(dst, tm, col, row, full + s * 8);
                    if (++s == NSLOT) { s = 0; ph ^= 1; }
                }
                if (seg == 1) break;
                const uint32_t epoch = ld_epoch(p.g);
                const uint32_t rdy = bars + (B_RDY + 2 * w) * 8, prdy = mapa(rdy, r ^ 1);
                const int odd = r ^ w;
                const uint32_t* flags = p.g->flag_kv + (abh * 32 + lane) * FS;
                bool first = (lane >> 2) == 2 * odd + w;
                if (first) first = ld_relaxed(flags) != epoch;
                auto kv_load = [&](uint32_t sl, int isv, int i) {
                    ring_load_both(ring + sl * SLOT, &m.tm[8], (isv * 64 + abh * 8 + 2 * i + w) * 128, full + sl * 8);
                };
                if (lane < NSLOT) {
                    mbar_wait(full + (B_EMPTY - B_FULL + lane) * 8, lane < 4);
                    mbar_arrive_tx(full + lane * 8, SLOT);
                }
                __syncwarp();
                if (lane == 0) mbar_arrive_peer(prdy);
                bar_sync(14, 96);
                spin(KDELAY);
                mbar_wait(rdy, 0);
                flag_wait(flags, epoch, first);
                TSW(5 + 2 * odd);
                if (!odd) { kv_load(4, 0, 0); bar_arrive(12, 64); }
                else bar_sync(12, 64);
                spin(w ? KD3 : KD2);
                kv_load(odd ? 5 : 0, odd ^ 1, odd);
                flag_wait(flags, epoch, (lane >> 2) == 2 * odd + w + 4);
                mbar_wait(full + (odd ? 5 : 0) * 8, odd);
                kv_load(1 + odd, odd, 2 - odd);
                if (odd) { mbar_wait(full + 16, 0); kv_load(3, 0, 3); }
#pragma unroll 1
                for (int i = 0; i < 2; i++) {
                    mbar_wait(full + (B_EMPTY - B_FULL + 4 + i) * 8, 1);
                    if (lane == 0) mbar_arrive_tx(full + (4 + i) * 8, SLOT);
                    if (i == odd) {
                        mbar_wait(rdy + 8, 0);
                        kv_load(4 + i, 1, 2 + i);
                    } else if (lane == 0) mbar_arrive_peer(prdy + 8);
                    __syncwarp();
                }
                n = 30; s = 0; ph = 0;
            }
        } else if (warp == 10) {
            if (lane == 0) {
#pragma unroll
                for (int i = B_EMPTY; i < NBARS; i++) mbar_init(bars + i * 8, i < B_XA ? 4 : 1);
#pragma unroll
                for (int i = B_XA; i <= B_SR; i++) mbar_arrive_tx(bars + i * 8, i < B_XB ? 512 : ((i >= B_INB && i < B_SR) ? 4096 : 8192));
                asm volatile("fence.mbarrier_init.release.cluster;" ::: "memory");
                fence_async_smem();
            }
            __syncwarp();
            cluster_arrive();
            cluster_wait();
            float ka[4] = {};
            const uint32_t kz[4] = {p.zero, p.zero, p.zero, p.zero};
#pragma unroll 1
            for (int i = 0; i < 4096 && !mbar_test(bars + (B_XA + 3) * 8, __float_as_uint(ka[0])); i++) {
                mma16(ka, kz, p.zero, p.zero);
                __nanosleep(250);
            }
        } else {
            const uint32_t kb = (lane < 2 || lane > 5) ? 4096 : (lane == 2 ? 3072 : (lane == 4 ? 2048 : 1024));
            const char* pf = m.w[lane & 7] + blockIdx.x * kb;
            cluster_wait();
            mbar_wait(bars + B_FULL * 8, 0);
            if (lane < 3) prefetch_l2(pf, kb);
            if (lane >= 1 && lane < 9) asm volatile("prefetch.tensormap [%0];" ::"l"(&m.tm[lane]) : "memory");
            mbar_wait(bars + (B_FULL + 1) * 8, 1);
            if (lane > 2 && lane < 8) prefetch_l2(pf, kb);
            if (lane == 8 && blockIdx.x < 15) prefetch_l2(p.dw + blockIdx.x * 256, 512);
            const uint32_t epoch = ld_epoch(p.g);
            bar_sync(4, 288);
            if (lane < 16) flag_set(&p.g->flag_kv[((b * 4 + 2 * r + (lane >> 3)) * 32 + pt) * FS + (lane & 7)], epoch);
            __syncwarp();
            bar_arrive(14, 96);
            TSW(8);
        }
        TSDUMP();
        return;
    }

    const int w = warp >> 2, wq = warp & 3;
    const int tile = 2 * r + w;
    const int wt = tid & 127;
    const int c4 = lane & 3;
    const int trow = pt * 32 + 8 * wq;
    uint32_t xr[8];
    uint32_t a[32];
    const char* xrow = reinterpret_cast<const char*>(p.x) + (b * T_ + trow + (lane >> 2)) * 512;
    zero(a);
    if (trow < T_) {
        const char* src = xrow + c4 * 16 + p.zero;
#pragma unroll
        for (int i = 0; i < 8; i++)
            asm volatile("ld.global.nc.v4.b32 {%0,%1,%2,%3}, [%4];" : "=r"(a[4 * i]), "=r"(a[4 * i + 1]), "=r"(a[4 * i + 2]), "=r"(a[4 * i + 3]) : "l"(src + 64 * i));
    }
    cluster_arrive();
    asm volatile("setmaxnreg.inc.sync.aligned.u32 208;");
    const uint32_t rbase = sb + OFF_RING + w * NSLOT * SLOT, fbar = bars + (B_FULL + w * NSLOT) * 8;
    const uint32_t rdesc = desc_lo(rbase);
    auto acq = [&](int n) { mbar_wait(fbar + (n % NSLOT) * 8, (n / NSLOT) & 1); };
    auto rel = [&](int n) { if (lane == 0) mbar_arrive(fbar + (B_EMPTY - B_FULL + n % NSLOT) * 8); };
    const uint32_t foff = (lane & 7) * 128 + (((lane >> 3) ^ (lane & 7)) << 4);
    float v[16];
    const uint32_t xown = __shfl_sync(~0u, P + wt * 16 + tile * 4096, lane), xrem = __shfl_sync(~0u, P + wt * 16 + (r ^ 1) * 8192, lane);
    const uint32_t sbuf = __shfl_sync(~0u, sb + OFF_MISC + (8 * wq + (lane >> 2)) * 32, lane);
    const uint32_t sown = __shfl_sync(~0u, sbuf + tile * 8, lane);
    const uint32_t peer = __shfl_sync(~0u, mapa(sb, r ^ 1) - sb, lane);
    const uint32_t hbuf = __shfl_sync(~0u, H + w * 4096 + wt * 16, lane);
    const uint32_t meta = __shfl_sync(~0u, 0xEEEE4444u + p.zero, lane);
    cluster_wait();
    TS(56);
    float mean, msq;
    const int mir = wq < 2 ? 7 : 0;
    uint32_t dwr[15];

    auto phase = [&](auto phc) __attribute__((always_inline)) {
        constexpr int ph = decltype(phc)::value;
        uint4 o0, o1;
        if (ph == 0) {
            const uint32_t one = 0x3F803F80u + ((xown | xrem | sbuf | sown | hbuf | foff | rdesc | fbar) & p.zero);
            mean = ((row_sum<8>(a, one) + row_sum<8>(a + 8, one)) + (row_sum<8>(a + 16, one) + row_sum<8>(a + 24, one))) * (1.f / 256.f);
            TS(57);
        } else {
            const uint32_t xa = bars + (B_XA + ph) * 8;
#pragma unroll
            for (int j = 0; j < 8; j++) xr[j] = pack2(v[2 * j], v[2 * j + 1]);
            const float s = row_sum<8>(xr), q = row_sumsq<8>(xr, lane);
            if (ph < 4) {
                sts128(xown, xr[0], xr[1], xr[2], xr[3]);
                sts128(xown + 2048, xr[4], xr[5], xr[6], xr[7]);
            }
            put_sums(sown, sown + peer, s, q, xa + peer, c4 == (lane >> 3));
            bar_sync(10, 256);
            if (ph < 4) {
                o0 = lds128(xown ^ 4096); o1 = lds128((xown ^ 4096) + 2048);
                st_async4(xown + peer, xr[0], xr[1], xr[2], xr[3], xa + (B_XB - B_XA) * 8 + peer);
                st_async4(xown + peer + 2048, xr[4], xr[5], xr[6], xr[7], xa + (B_XB - B_XA) * 8 + peer);
            }
            TS(57 + ph);
            if (ph == 3) acq(38);
            if (ph == 1) acq(16);
            mbar_wait(xa, 0);
            const float4 u0 = lds128f(sbuf), u1 = lds128f(sbuf + 16);
            mean = ((u0.x + u0.z) + (u1.x + u1.z)) * (1.f / 256.f);
            msq = ((u0.y + u0.w) + (u1.y + u1.w)) * (1.f / 256.f);
        }
        if (ph == 4) return;
        const uint32_t mean2 = pack2(mean, mean);
        auto centre = [&](int i, const uint4& u) {
            a[i] = hsub2(u.x, mean2); a[i + 1] = hsub2(u.y, mean2); a[i + 2] = hsub2(u.z, mean2); a[i + 3] = hsub2(u.w, mean2);
        };
        if (ph == 0) {
#pragma unroll
            for (int j = 0; j < 32; j++) a[j] = hsub2(a[j], mean2);
            zero(xr);
            if (trow < T_) {
                const char* src = xrow + tile * 128 + c4 * 4 + (mean2 & p.zero);
#pragma unroll
                for (int j = 0; j < 8; j++) asm volatile("ld.global.nc.b32 %0, [%1];" : "=r"(xr[j]) : "l"(src + 16 * j));
            }
            mean -= blo(mean2);
            msq = __shfl_sync(~0u, row_sumsq<16>(a, lane) + row_sumsq<16>(a + 16, lane), (lane & 28) + (lane >> 3)) * (1.f / 256.f);
            acq(0);
        } else {
#pragma unroll
            for (int j = 0; j < 8; j++) a[j] = hsub2(xr[j], mean2);
            centre(8, o0); centre(12, o1);
        }
        const float rstd = rsq(fmaxf(fmaf(-mean, mean, msq), 0.f) + 1e-5f);
        auto gather_peer = [&]() {
            mbar_wait(bars + (B_XB + ph) * 8, 0);
#pragma unroll
            for (int i = 0; i < 4; i++) centre(16 + 4 * i, lds128(xrem + i * 2048));
        };
        auto sp = [&](float (&d)[32], int n, const uint32_t* af, int flip, int acc) {
            const uint32_t lo = rdesc + p.zero * (ph * 64 + n + 1) + (n % NSLOT) * (SLOT >> 4);
            const uint64_t b0 = mkdesc(lo + flip * 512), b1 = mkdesc(lo + (flip ^ 1) * 512);
            wg_fence();
            mma_sp(d, af, b0, meta, acc);
            mma_sp(d, af + 4, b0 + 256, meta, 1);
            mma_sp(d, af + 8, b1, meta, 1);
            mma_sp(d, af + 12, b1 + 256, meta, 1);
            wg_commit();
        };
        float d0[32], d1[32];

        if (ph == 0 || ph == 3) {
            uint32_t h[32], ho[32];
            const float rs = 0.5f * rstd;
            const uint32_t inb = bars + (B_INB + (ph & 2) + w) * 8;
            bool ready = true;
            const int eager = ph ? 0x5a : 0x54;
            auto step = [&](float (&d)[32], int n, const uint32_t* af, int flip, int acc, auto work) {
                const int l = n + (ph ? 38 : 0);
                if (!ready) acq(l);
                sp(d, l, af, flip, acc);
                if (n < 15) ready = mbar_test(fbar + ((l + 1) % NSLOT) * 8, ((l + 1) / NSLOT) & 1);
                wg_wait<1>();
                if (n > 0 && !((eager >> (n - 1)) & 1)) rel(l - 1);
                const uint32_t tie = work() & p.zero;
                if ((eager >> n) & 1) {
                    if (p.zero < l + 1) wg_wait<0>();
                    if (lane == 0) mbar_arrive(fbar + (B_EMPTY - B_FULL + l % NSLOT) * 8 + tie);
                }
            };
            auto none = []() { return 0u; };
            const int fl = ph ? w : 0;
            auto fetch = [&](int i) {
                bar_sync(10, 256);
                const uint32_t src = ((i & 1) ? hbuf : xown) ^ 4096;
                const uint4 u0 = lds128(src), u1 = lds128(src + 2048);
                ho[8 * i] = u0.x; ho[8 * i + 1] = u0.y; ho[8 * i + 2] = u0.z; ho[8 * i + 3] = u0.w;
                ho[8 * i + 4] = u1.x; ho[8 * i + 5] = u1.y; ho[8 * i + 6] = u1.z; ho[8 * i + 7] = u1.w;
                return u0.x | u1.x;
            };
            auto act = [&](float (&d)[32], int i) {
                if (i > 0) fetch(i - 1);
                else if (ph) bar_sync(10, 256);
                pin(d);
#pragma unroll
                for (int j = 0; j < 8; j++) {
                    const float u0 = (d[4 * j] + d[4 * j + 2]) * rs, u1 = (d[4 * j + 1] + d[4 * j + 3]) * rs;
                    h[8 * i + j] = pack2(fmaf(u0, tanh_fast(u0), u0), fmaf(u1, tanh_fast(u1), u1));
                }
                sts128((i & 1) ? hbuf : xown, h[8 * i], h[8 * i + 1], h[8 * i + 2], h[8 * i + 3]);
                sts128(((i & 1) ? hbuf : xown) + 2048, h[8 * i + 4], h[8 * i + 5], h[8 * i + 6], h[8 * i + 7]);
                return 0u;
            };
            TS(1 + (ph & 2) * 10);
            if (ph) {
                step(d0, 0, a, fl, 0, none);
                step(d1, 1, a, fl, 0, [&]() { gather_peer(); return 0u; });
                TS(32);
                step(d0, 2, a + 16, 0, 1, none);
                step(d1, 3, a + 16, 0, 1, [&]() { return act(d0, 0); });
            } else {
                step(d0, 0, a, fl, 0, none);
                TS(32);
                step(d0, 1, a + 16, 0, 1, none);
                step(d1, 2, a, fl, 0, [&]() { return act(d0, 0); });
                step(d1, 3, a + 16, 0, 1, none);
            }
            step(d0, 4, a, fl, 0, [&]() { return act(d1, 1); });
            TS(33);
            step(d0, 5, a + 16, 0, 1, none);
            step(d1, 6, a, fl, 0, [&]() { return act(d0, 2); });
            step(d1, 7, a + 16, 0, 1, none);
            step(d0, 8, h, 0, 0, [&]() { act(d1, 3); return fetch(3); });
            TS(2 + (ph & 2) * 10);
            step(d0, 9, ho, 0, 1, none);
            step(d0, 10, h + 16, 0, 1, none);
            step(d0, 11, ho + 16, 0, 1, none);
            uint32_t pk[8];
            auto pack_out = [&]() {
                pin(d0);
#pragma unroll
                for (int j = 0; j < 8; j++) pk[j] = pack2(d0[4 * j] + d0[4 * j + 2], d0[4 * j + 1] + d0[4 * j + 3]);
            };
            auto send = [&](int i) { st_async4(hbuf + 8192 + i * 2048 + peer, pk[4 * i], pk[4 * i + 1], pk[4 * i + 2], pk[4 * i + 3], inb + peer); };
            step(d1, 12, h, 0, 0, [&]() { pack_out(); send(0); return 0u; });
            TS(34);
            step(d1, 13, ho, 0, 1, [&]() { send(1); return 0u; });
            step(d1, 14, h + 16, 0, 1, none);
            step(d1, 15, ho + 16, 0, 1, none);
            mbar_wait(inb, 0);
#pragma unroll
            for (int i = 0; i < 2; i++) {
                const uint4 u = lds128(hbuf + 8192 + i * 2048);
                const uint32_t p0[4] = {u.x, u.y, u.z, u.w};
#pragma unroll
                for (int j = 0; j < 4; j++) {
                    v[8 * i + 2 * j] = fmaf(0.5f, blo(p0[j]), blo(xr[4 * i + j]));
                    v[8 * i + 2 * j + 1] = fmaf(0.5f, bhi(p0[j]), bhi(xr[4 * i + j]));
                }
            }
            wg_wait<0>();
            pin(d1);
            if (ph == 0) rel(15);
            TS(3 + (ph & 2) * 10);
#pragma unroll
            for (int j = 0; j < 8; j++) {
                v[2 * j] = fmaf(0.5f, d1[4 * j] + d1[4 * j + 2], v[2 * j]);
                v[2 * j + 1] = fmaf(0.5f, d1[4 * j + 1] + d1[4 * j + 3], v[2 * j + 1]);
            }
            return;
        }

        auto residual = [&](int n) {
            wg_wait<1>();
            rel(n);
            wg_wait<0>();
            pin(d0);
            rel(n + 1);
#pragma unroll
            for (int j = 0; j < 8; j++) {
                v[2 * j] = d0[4 * j] + d0[4 * j + 2] + blo(xr[j]);
                v[2 * j + 1] = d0[4 * j + 1] + d0[4 * j + 3] + bhi(xr[j]);
            }
        };

        if (ph == 2) {
            TS(39);
            sp(d0, 32, a, w, 0);
            acq(33);
            sp(d1, 33, a, w, 0);
            acq(34); acq(35);
            gather_peer();
            sp(d0, 34, a + 16, 0, 1);
            sp(d1, 35, a + 16, 0, 1);
            wg_wait<2>();
            rel(32);
            acq(36);
            bar_sync(10, 256);
            const float rs = trow < T_ ? 0.5f * rstd : 0.f;
            uint32_t pk[8];
            if (GB) {
                wg_wait<1>();
                pin(d0);
                float t[16];
                uint32_t tie = 0;
#pragma unroll
                for (int j = 0; j < 16; j++) {
                    t[j] = (d0[4 * (j >> 1) + (j & 1)] + d0[4 * (j >> 1) + (j & 1) + 2]) * rs;
                    if (j < GT) t[j] = tanh_fast(t[j]);
                    tie |= __float_as_uint(t[j]);
                }
                if (__any_sync(~0u, tie & p.zero)) spin(1);
                wg_wait<0>();
                pin(d1);
                TS(18);
#pragma unroll
                for (int j = 0; j < 8; j++) {
                    const float u0 = (d1[4 * j] + d1[4 * j + 2]) * rs, u1 = (d1[4 * j + 1] + d1[4 * j + 3]) * rs;
                    pk[j] = pack2(fmaf(u0, 2 * j < GT ? t[2 * j] : tanh_fast(t[2 * j]), u0), fmaf(u1, 2 * j + 1 < GT ? t[2 * j + 1] : tanh_fast(t[2 * j + 1]), u1));
                }
            } else {
                wg_wait<0>();
                pin(d0); pin(d1);
                TS(18);
#pragma unroll
                for (int j = 0; j < 8; j++) {
                    const float u0 = (d0[4 * j] + d0[4 * j + 2]) * rs, u1 = (d0[4 * j + 1] + d0[4 * j + 3]) * rs;
                    const float t0 = tanh_fast((d1[4 * j] + d1[4 * j + 2]) * rs), t1 = tanh_fast((d1[4 * j + 1] + d1[4 * j + 3]) * rs);
                    pk[j] = pack2(fmaf(u0, t0, u0), fmaf(u1, t1, u1));
                }
            }
            if (wq == 0 || wq == 3) {
                uint4* hp = &p.g->halo[((pair * 4 + tile) * 2 + (wq & 1)) * 64 + lane];
                st_data(hp, pk[0], pk[1], pk[2], pk[3]);
                st_data(hp + 32, pk[4], pk[5], pk[6], pk[7]);
            }
            const uint32_t gs = P + w * GCH + wq * 1024;
            stsm4(gs + 1024 + foff, pk[0], pk[1], pk[2], pk[3]);
            stsm4(gs + 1024 + (foff ^ 64), pk[4], pk[5], pk[6], pk[7]);
            bar_sync(8 + w, 192);
            TS(26);
            uint32_t ca[8], cb[8];
            const int e = (wq & 1) * 4;
            const uint32_t lo = ((mir ^ e) * 144) ^ (lane * 4);
            const int dir = mir ? -1024 : 1024;
            const uint32_t gb = P + w * GCH + (mir ? 3072 : 2048) + lo, sown_ = H + tile * HCH, so = sown_ + (mir ? 1024 : 2048) + lo;
            auto finish = [&](int i) {
                const uint32_t c = hadd2(ca[i], cb[i]);
                const float h0 = blo(c), h1 = bhi(c);
                const uint32_t dst = (so + (i >> 2) * dir) ^ ((i & 3) * 144), val = pack2(fmaf(h0, tanh_fast(h0), h0), fmaf(h1, tanh_fast(h1), h1));
                asm volatile("st.async.shared::cluster.mbarrier::complete_tx::bytes.b32 [%0], %1, [%2];" ::"r"(dst + peer), "r"(val), "r"(bars + B_SR * 8 + peer) : "memory");
                sts32(dst, val);
            };
#pragma unroll
            for (int k = 0; k < 26; k++) {
                if (k == 19) {
#pragma unroll
                    for (int i = 0; i < 4; i++) finish(i);
                    mbar_wait(bars + (B_HALO + 2 * w + (wq >> 1)) * 8, 0);
                    rel(33); rel(34); rel(35);
                    TS(27);
                }
                const uint32_t g = lds32((gb + (((k + 1) & 4) ? ((k + 1) >> 3) + (wq & 1) : ((k + 1) >> 3)) * dir) ^ (((k + 1) & 7) * 144));
#pragma unroll
                for (int i = 0; i < 8; i++) {
                    const int tap = k - (i & 3) - 2 * (i & 4);
                    if (tap == 0) ca[i] = hmul2(g, dwr[0]);
                    else if (tap > 0 && tap < 8) ca[i] = hfma2(g, dwr[tap], ca[i]);
                    else if (tap == 8) cb[i] = hmul2(g, dwr[8]);
                    else if (tap > 8 && tap < 15) cb[i] = hfma2(g, dwr[tap], cb[i]);
                }
            }
#pragma unroll
            for (int i = 4; i < 8; i++) finish(i);
            bar_sync(10, 256);
            TS(19);
            auto frags = [&](int i, int half) {
                const uint32_t src = H + 2 * half * HCH + wq * 1024;
#pragma unroll
                for (int k = 0; k < 4; k++) ldsm4(src + (k >> 1) * HCH + (foff ^ ((k & 1) * 64)), a[i + 4 * k], a[i + 4 * k + 1], a[i + 4 * k + 2], a[i + 4 * k + 3]);
            };
            frags(0, r);
            sp(d0, 36, a, 0, 0);
            acq(37);
            mbar_wait(bars + B_SR * 8, 0);
            frags(16, r ^ 1);
            sp(d0, 37, a + 16, 0, 1);
            residual(36);
            TS(20);
            return;
        }

        {
            TS(11);
            unsigned char* g = p.g->kvq + (size_t)((b * 4 + tile) * 1024 + trow) * 128;
            const uint32_t uo = (lane >> 2) * 128 + ((c4 ^ (lane >> 2)) << 4);
            auto put = [&](float (&d)[32], int i) {
                pin(d);
                uint32_t pk[8];
#pragma unroll
                for (int j = 0; j < 8; j++) pk[j] = pack2((d[4 * j] + d[4 * j + 2]) * rstd, (d[4 * j + 1] + d[4 * j + 3]) * rstd);
                if (i < 2) {
                    stg128(g + i * 1048576 + uo, make_uint4(pk[0], pk[1], pk[2], pk[3]));
                    stg128(g + i * 1048576 + (uo ^ 64), make_uint4(pk[4], pk[5], pk[6], pk[7]));
                } else {
                    const uint32_t stg = H + warp * 1024;
                    sts128(stg + uo, pk[0], pk[1], pk[2], pk[3]);
                    sts128(stg + (uo ^ 64), pk[4], pk[5], pk[6], pk[7]);
                    __syncwarp();
                    ldsm4(stg + foff, pk[0], pk[1], pk[2], pk[3]);
                    ldsm4(stg + (foff ^ 64), pk[4], pk[5], pk[6], pk[7]);
                    st_data(g + 2097152 + lane * 16, ~pk[0], ~pk[1], ~pk[2], ~pk[3]);
                    st_data(g + 2097152 + 512 + lane * 16, ~pk[4], ~pk[5], ~pk[6], ~pk[7]);
                }
            };
            sp(d0, 16, a, w, 0);
            acq(17);
            sp(d1, 17, a, w, 0);
            gather_peer();
            acq(18);
            sp(d0, 18, a + 16, 0, 1);
            wg_wait<1>();
            rel(16); rel(17);
            acq(19);
            sp(d1, 19, a + 16, 0, 1);
            wg_wait<1>();
            rel(18);
            put(d0, 0);
            wg_wait<0>();
            rel(19);
            TS(37);
            put(d1, 1);
            bar_arrive(4, 288);
            TS(38);
            acq(20);
            sp(d0, 20, a, w, 0);
            acq(21);
            sp(d0, 21, a + 16, 0, 1);
            wg_wait<0>();
            rel(20); rel(21);
            put(d0, 2);
            TS(12);
        }

        {
            constexpr float CS = 0.125f * 1.4426950408889634f;
            float sa[32], sb2[32], o[36];
            uint32_t pa[16], pb[16], q[16];
            float n0 = INFINITY, n1 = INFINITY;
            zero(o); zero(pa); zero(pb); zero(sb2);
            const uint32_t ones = H + 8192;
            { const uint32_t c = w ? 0u : 0x3F803F80u; sts128(ones + tid * 16, c, c, c, c); }
            fence_async_smem();
            bar_sync(10, 256);
            const uint32_t vdesc = rdesc + ((((ones - rbase) >> 4) - 1) << 16);
            auto qk_issue = [&](float (&s)[32], uint32_t lo) {
                const uint64_t kd = mkdesc(lo);
                wg_fence();
#pragma unroll
                for (int k = 0; k < 4; k++) mma_qk(s, q[4 * k], q[4 * k + 1], q[4 * k + 2], q[4 * k + 3], kd + 2 * k, k != 0);
                wg_commit();
            };
            auto both_issue = [&](float (&s)[32], uint32_t klo, uint32_t (&pp)[16], uint32_t vlo) {
                const uint64_t kd = mkdesc(klo), vd = mkdesc(vlo);
                wg_fence();
#pragma unroll
                for (int k = 0; k < 4; k++) {
                    mma_pv(o, pp[4 * k], pp[4 * k + 1], pp[4 * k + 2], pp[4 * k + 3], vd - k * (128 * 65535));
                    mma_qk(s, q[4 * k], q[4 * k + 1], q[4 * k + 2], q[4 * k + 3], kd + 2 * k, k != 0);
                }
                wg_commit();
            };
            auto new_max = [&](float (&s)[32], int nj, float& x0, float& x1) {
                x0 = s[0]; x1 = s[2];
#pragma unroll
                for (int j = 0; j < nj; j++) {
                    x0 = fmaxf(x0, fmaxf(s[4 * j], s[4 * j + 1]));
                    x1 = fmaxf(x1, fmaxf(s[4 * j + 2], s[4 * j + 3]));
                }
                x0 = fmaxf(x0, __shfl_xor_sync(~0u, x0, 1)); x1 = fmaxf(x1, __shfl_xor_sync(~0u, x1, 1));
                x0 = fmaxf(x0, __shfl_xor_sync(~0u, x0, 2)); x1 = fmaxf(x1, __shfl_xor_sync(~0u, x1, 2));
                x0 = fminf(n0, fmaf(x0, -CS, -20.f)); x1 = fminf(n1, fmaf(x1, -CS, -20.f));
            };
            auto probs = [&](float (&s)[32], uint32_t (&pp)[16], bool ready, bool tail, auto wait) {
                uint32_t any = 0;
#pragma unroll
                for (int i = 0; i < 16; i++) {
                    pp[i] = pack2(ex2(fmaf(s[2 * i], CS, (i & 1) ? n1 : n0)), ex2(fmaf(s[2 * i + 1], CS, (i & 1) ? n1 : n0)));
                    any |= pp[i];
                }
                wg_wait<0>();
                pin(sa); pin(sb2); pin(o); pin(pa); pin(pb);
                if (__builtin_expect(__any_sync(~0u, (any & 0x40004000u) || !ready), 0)) {
                    wait();
                    if (__any_sync(~0u, any & 0x40004000u)) {
                        if (tail) {
#pragma unroll
                            for (int i = 20; i < 32; i++) s[i] = -INFINITY;
                        }
                        float x0, x1;
                        new_max(s, 8, x0, x1);
                        const float sc0 = ex2(x0 - n0), sc1 = ex2(x1 - n1);
                        n0 = x0; n1 = x1;
#pragma unroll
                        for (int j = 0; j < 9; j++) { o[4 * j] *= sc0; o[4 * j + 1] *= sc0; o[4 * j + 2] *= sc1; o[4 * j + 3] *= sc1; }
#pragma unroll
                        for (int i = 0; i < 16; i++)
                            pp[i] = pack2(ex2(fmaf(s[2 * i], CS, (i & 1) ? n1 : n0)), ex2(fmaf(s[2 * i + 1], CS, (i & 1) ? n1 : n0)));
                    }
                }
            };
            {
                uint4 u[4];
                const unsigned char* src = p.g->kvq + 2097152 + (size_t)(abh * 1024 + qt * 64 + wq * 16) * 128 + lane * 16;
                spin(QGATE);
                ld_data<512, true>(u, src);
#pragma unroll
                for (int k = 0; k < 2; k++) {
                    q[8 * k] = ~u[k].x; q[8 * k + 1] = ~u[k + 2].x; q[8 * k + 2] = ~u[k].y; q[8 * k + 3] = ~u[k + 2].y;
                    q[8 * k + 4] = ~u[k].z; q[8 * k + 5] = ~u[k + 2].z; q[8 * k + 6] = ~u[k].w; q[8 * k + 7] = ~u[k + 2].w;
                }
                pin(q);
            }
            TS(40);
            acq(22);
            TS(13);
            qk_issue(sa, rdesc + (22 % NSLOT) * (SLOT >> 4));
            wg_wait<0>();
            pin(sa);
            {
                float x0, x1;
                new_max(sa, 2, x0, x1);
                n0 = x0; n1 = x1;
            }
            bar_arrive(6, 384);
            uint32_t vd = vdesc, kd = rdesc + 5 * (SLOT >> 4), vb = fbar, kb = fbar + 40;
            uint32_t vlast = vdesc - 4 * (SLOT >> 4) * 65535u, klast = rdesc + 4 * (SLOT >> 4) + 512;
            uint32_t kprev = fbar + 32, vprev = bars + (B_SINK - (B_EMPTY - B_FULL)) * 8;
#pragma unroll 1
            for (int it = 0; it < 4; it++) {
                both_issue(sb2, klast, pb, vlast);
                probs(sa, pa, mbar_test(vb, 0) & mbar_test(kb, it == 0), false, [&]() { mbar_wait(vb, 0); mbar_wait(kb, it == 0); });
                TS(41 + it * 4);
                if (lane == 0) mbar_arrive(kprev + (B_EMPTY - B_FULL) * 8);
                if (lane == 0) mbar_arrive(vprev + (B_EMPTY - B_FULL) * 8);
                both_issue(sa, kd, pa, vd);
                const int dv = it == 2 ? 1 : 2, dk = it == 0 ? -4 : 2;
                kprev = kb; vprev = vb; vlast = vd - 512 * 65535u; klast = kd + 512;
                vd -= dv * (SLOT >> 4) * 65535u; vb += dv * 8;
                kd += dk * (SLOT >> 4); kb += dk * 8;
                probs(sb2, pb, true, it == 3 && w == 1, []() {});
                TS(43 + it * 4);
            }
            wg_fence();
#pragma unroll
            for (int k = 0; k < 4; k++)
                mma_pv(o, pb[4 * k], pb[4 * k + 1], pb[4 * k + 2], pb[4 * k + 3], mkdesc(vlast - k * (128 * 65535) + (k > 1 ? w * ((k - 1) << 22) : 0)));
            wg_commit();
            const uint32_t mlw = sb + OFF_MISC + 1024 + (tid >> 2) * 8;
            unsigned char* odst = p.g->o + (size_t)(b * 128 + qt * 8 + 2 * wq + w) * 4096 + ah * 1024 + lane * 16;
            mbar_wait(bars + B_RST * 8, __any_sync(~0u, (mlw | (uint32_t)(size_t)odst) & p.zero));
            wg_wait<0>();
            pin(o); pin(pb); pin(sa); pin(sb2);
            rel(29);
            TS(14);
            auto merge = [&](int keep, float nk, float ns) {
                const int snd = 2 - keep;
                if (c4 == 0) sts64f(mlw, ns, o[32 + snd]);
#pragma unroll
                for (int j = 0; j < 2; j++)
                    sts128(hbuf + j * 2048, pack2(o[16 * j + snd], o[16 * j + snd + 1]), pack2(o[16 * j + 4 + snd], o[16 * j + 5 + snd]),
                           pack2(o[16 * j + 8 + snd], o[16 * j + 9 + snd]), pack2(o[16 * j + 12 + snd], o[16 * j + 13 + snd]));
                bar_sync(10, 256);
                const float2 u = lds64f(mlw ^ 256);
                const float x = fminf(nk, u.x);
                float a = ex2(x - nk), c = ex2(x - u.x);
                const float inv = rcp(fmaf(a, o[32 + keep], c * u.y));
                a *= inv; c *= inv;
                uint32_t pk[8];
#pragma unroll
                for (int j = 0; j < 2; j++) {
                    const uint4 t4 = lds128((hbuf ^ 4096) + j * 2048);
                    const uint32_t t[4] = {t4.x, t4.y, t4.z, t4.w};
#pragma unroll
                    for (int i = 0; i < 4; i++)
                        pk[4 * j + i] = pack2(fmaf(a, o[16 * j + 4 * i + keep], c * blo(t[i])), fmaf(a, o[16 * j + 4 * i + keep + 1], c * bhi(t[i])));
                }
                st_data(odst, pk[0], pk[1], pk[2], pk[3]);
                st_data(odst + 512, pk[4], pk[5], pk[6], pk[7]);
            };
            if (tid < 128) merge(0, n0, n1); else merge(2, n1, n0);
            if (tid == 0) asm volatile("red.relaxed.gpu.global.add.u32 [%0], 1;" ::"l"(&p.g->epoch[blockIdx.x * FS]) : "memory");
            TS(15);
        }

        {
            const uint32_t* dp = reinterpret_cast<const uint32_t*>(p.dw + (mir ? 14 * 256 : 0) + tile * 64) + lane;
#pragma unroll
            for (int i = 0; i < 15; i++) asm volatile("ld.global.nc.b32 %0, [%1];" : "=r"(dwr[i]) : "l"(dp + i * (mir ? -128 : 128)));
            acq(30); acq(31); acq(32);
            uint4 u[8];
            ld_data<512>(u, p.g->o + (size_t)(b * 128 + pt * 4 + wq) * 4096 + lane * 16);
#pragma unroll
            for (int i = 0; i < 8; i++) { a[4 * i] = u[i].x; a[4 * i + 1] = u[i].y; a[4 * i + 2] = u[i].z; a[4 * i + 3] = u[i].w; }
            TS(16);
            sp(d0, 30, a, 0, 0);
            sp(d0, 31, a + 16, 0, 1);
#pragma unroll
            for (int i = 0; i < 15; i++) dwr[i] = hmul2(dwr[i], 0x3F003F00u);
            residual(30);
            TS(17);
        }
    };
    phase(std::integral_constant<int, 0>{});
    phase(std::integral_constant<int, 1>{});
    phase(std::integral_constant<int, 2>{});
    phase(std::integral_constant<int, 3>{});
    phase(std::integral_constant<int, 4>{});

    cluster_arrive();
    TS(24);
    {
        const float rstd = rsq(fmaxf(fmaf(-mean, mean, msq), 0.f) + 1e-5f), nb = -mean * rstd;
#pragma unroll
        for (int j = 0; j < 8; j++) xr[j] = pack2(fmaf(v[2 * j], rstd, nb), fmaf(v[2 * j + 1], rstd, nb));
        const uint32_t stg = H + warp * 1024;
        stsm4(stg + foff, xr[0], xr[1], xr[2], xr[3]);
        stsm4(stg + (foff ^ 64), xr[4], xr[5], xr[6], xr[7]);
        __syncwarp();
        const uint32_t src = stg + (lane >> 3) * 128 + (((lane & 7) ^ (lane >> 3)) << 4);
        const uint4 u0 = lds128(src), u1 = lds128((src + 512) ^ 64);
        __nv_bfloat16* dst = p.out + (size_t)(b * T_ + trow + (lane >> 3)) * 256 + tile * 64 + (lane & 7) * 8;
        if (trow < T_) { stg128(dst, u0); stg128(dst + 4 * 256, u1); }
    }
    TS(25);
    TG(31);
    TSDUMP();
    cluster_wait();
}

typedef CUresult (*EncodeFn)(CUtensorMap*, CUtensorMapDataType, cuuint32_t, void*, const cuuint64_t*, const cuuint64_t*,
                             const cuuint32_t*, const cuuint32_t*, CUtensorMapInterleave, CUtensorMapSwizzle,
                             CUtensorMapL2promotion, CUtensorMapFloatOOBfill);

}

extern "C" void kernel_launch(void* const* d_in, const int* in_sizes, int n_in, void* d_out, int out_size) {
    static EncodeFn encode = nullptr;
    if (!encode) {
        void* fn = nullptr;
        cudaDriverEntryPointQueryResult qr;
        cudaGetDriverEntryPoint("cuTensorMapEncodeTiled", &fn, cudaEnableDefault, &qr);
        encode = (EncodeFn)fn;
        cudaFuncSetAttribute(conformer_kernel, cudaFuncAttributeMaxDynamicSharedMemorySize, SMEM_LAUNCH);
    }
    Scalars p;
    Maps m;
    const cuuint32_t ones[5] = {1, 1, 1, 1, 1};
    const int idx[8] = {1, 2, 3, 4, 5, 7, 8, 9};
    const int rows[8] = {256, 1024, 256, 256, 256, 256, 256, 1024};
    const int cols[8] = {1024, 256, 768, 256, 512, 256, 1024, 256};
    for (int i = 0; i < 8; i++) {
        const cuuint64_t pitch = (cuuint64_t)cols[i] * 2;
        const bool f = i != 0 && i != 3;
        const cuuint64_t dims[5] = {(cuuint64_t)cols[i], f ? 2u : 4u, f ? 2u : 4u, f ? 4u : 2u, (cuuint64_t)rows[i] / (f ? 16 : 32)};
        const cuuint64_t strides[4] = {pitch, pitch * 8, pitch * (f ? 2 : 4), pitch * (f ? 16 : 32)};
        const cuuint32_t box[5] = {64, f ? 2u : 4u, f ? 2u : 4u, f ? 4u : 2u, f ? 8u : 4u};
        encode(&m.tm[i], CU_TENSOR_MAP_DATA_TYPE_BFLOAT16, 5, d_in[idx[i]], dims, strides, box, ones, CU_TENSOR_MAP_INTERLEAVE_NONE,
               CU_TENSOR_MAP_SWIZZLE_128B, CU_TENSOR_MAP_L2_PROMOTION_L2_128B, CU_TENSOR_MAP_FLOAT_OOB_FILL_NONE);
        m.w[i] = (const char*)d_in[idx[i]];
    }
    {
        void* kv = nullptr;
        cudaGetSymbolAddress(&kv, g_scratch);
        p.g = (Scratch*)kv;
        const cuuint64_t dims[2] = {64, 16384};
        const cuuint64_t strides[1] = {128};
        const cuuint32_t box[2] = {64, 128};
        encode(&m.tm[8], CU_TENSOR_MAP_DATA_TYPE_BFLOAT16, 2, kv, dims, strides, box, ones, CU_TENSOR_MAP_INTERLEAVE_NONE,
               CU_TENSOR_MAP_SWIZZLE_NONE, CU_TENSOR_MAP_L2_PROMOTION_L2_128B, CU_TENSOR_MAP_FLOAT_OOB_FILL_NONE);
    }
    p.x = (const __nv_bfloat16*)d_in[0];
    p.dw = (const __nv_bfloat16*)d_in[6];
    p.out = (__nv_bfloat16*)d_out;
    p.zero = 0;
    conformer_kernel<<<NCTA, NTHREADS, SMEM_LAUNCH>>>(p, m);
}
```
